```python
import torch

def _softmax(x, axis=-1):
    return torch.softmax(x, dim=axis)
def _gelu(x):
    return torch.nn.functional.gelu(x, approximate="tanh")
def _silu(x):
    return torch.nn.functional.silu(x)
def _sigmoid(x):
    return torch.sigmoid(x)
def _layernorm(x, axis=-1, eps=1e-5):
    m = x.mean(dim=axis, keepdim=True)
    v = x.var(dim=axis, keepdim=True, unbiased=False)
    return (x - m) / torch.sqrt(v + eps)
def _scatter_add(tgt, idx, src, axis=0):
    return tgt.clone().index_add_(axis, idx, src)
def _segment_sum(src, seg, n):
    out = torch.zeros((n,) + src.shape[1:], dtype=src.dtype)
    return out.index_add_(0, seg, src)
def _pad(x, pw):
    flat = tuple(v for pair in reversed(pw) for v in pair)
    return torch.nn.functional.pad(x, flat)

kernel_name = 'gated_mix__sliding_local_dilated__compressed_kv_cla__prompt'

def setup_inputs():

    _w = (lambda a: (lambda t: t.to(torch.bfloat16) if t.is_floating_point() else t)(torch.as_tensor(a)))
    def _A_setup():
        B, S, D = 1, 2048, 576
        return {
            "x": _w((lambda *s: torch.randn(*s, dtype=torch.bfloat16) * 0.05)(B, S, D)),
            "wqkv": _w((lambda *s: torch.randn(*s, dtype=torch.bfloat16) * 1.6)(D, 3 * D)),
            "wo": _w((lambda *s: torch.randn(*s, dtype=torch.bfloat16) * 0.05)(D, D)),
        }
    _A_in = _A_setup()

    def _B_setup():
        B, H, Sq, Sk, D, M = 1, 32, 2048, 2048, 128, 576
        Dc = 4 * D
        return {
            "x": _w((lambda *s: torch.randn(*s, dtype=torch.bfloat16) * 0.05)(B, Sq, M)),
            "c_kv": _w((lambda *s: torch.randn(*s, dtype=torch.bfloat16) * 1.6)(B, Sk, Dc)),
            "w_q": _w((lambda *s: torch.randn(*s, dtype=torch.bfloat16) * 6.4)(M, H, D) * (M ** -0.5)),
            "w_uk": _w((lambda *s: torch.randn(*s, dtype=torch.bfloat16) * 6.4)(Dc, H, D) * (Dc ** -0.5)),
            "w_uv": _w((lambda *s: torch.randn(*s, dtype=torch.bfloat16) * 1.6)(Dc, H, D) * (Dc ** -0.5)),
            "w_o": _w((lambda *s: torch.randn(*s, dtype=torch.bfloat16) * 1.6)(H, D, M) * ((H * D) ** -0.5)),
        }
    _B_in = _B_setup()

    return {
        "A_x": _A_in["x"],
        "A_wqkv": _A_in["wqkv"],
        "A_wo": _A_in["wo"],
        "B_x": _B_in["x"],
        "B_c_kv": _B_in["c_kv"],
        "B_w_q": _B_in["w_q"],
        "B_w_uk": _B_in["w_uk"],
        "B_w_uv": _B_in["w_uv"],
        "B_w_o": _B_in["w_o"],
        "gate_w": _w((lambda *s: torch.randn(*s, dtype=torch.bfloat16) * 0.05)(576) * 16.0),
    }

def reference(A_x, A_wqkv, A_wo, B_x, B_c_kv, B_w_q, B_w_uk, B_w_uv, B_w_o, gate_w):
    def _A_ref(x, wqkv, wo):
        B, S, D = x.shape
        H = 32; Dh = D // H
        W, dil = 8, 2
        qkv = (lambda x, *d: x.permute(*d))((x @ wqkv).reshape(B, S, 3, H, Dh), 2, 0, 3, 1, 4)
        q, k, v = qkv[0], qkv[1], qkv[2]
        scale = Dh ** -0.5
        pos = torch.arange(S)
        off = torch.arange(W) * dil
        idx = pos[:, None] - off[None, :]
        mask = idx >= 0
        idx_c = torch.where(mask, idx, 0).reshape(-1)
        kg = k[:, :, idx_c, :].reshape(B, H, S, W, Dh)
        vg = v[:, :, idx_c, :].reshape(B, H, S, W, Dh)
        logits = torch.einsum("bhsd,bhswd->bhsw", q, kg) * scale
        logits = torch.where(mask[None, None, :, :], logits, -1e9)
        attn = _softmax(logits, axis=-1)
        o = torch.einsum("bhsw,bhswd->bhsd", attn, vg)
        return (lambda x, *d: x.permute(*d))(o, 0, 2, 1, 3).reshape(B, S, D) @ wo

    def _B_ref(x, c_kv, w_q, w_uk, w_uv, w_o):
        B, Sq, M = x.shape[0], x.shape[1], x.shape[2]
        Sk = c_kv.shape[1]
        H, D = w_q.shape[1], w_q.shape[2]
        q = torch.einsum("bqm,mhd->bhqd", x, w_q)
        k = torch.einsum("bkc,chd->bhkd", c_kv, w_uk)
        v = torch.einsum("bkc,chd->bhkd", c_kv, w_uv)
        scores = torch.einsum("bhqd,bhkd->bhqk", q, k) * (D ** -0.5)
        off = Sk - Sq
        qi = torch.arange(Sq)[:, None]
        kj = torch.arange(Sk)[None, :]
        cmask = kj <= (qi + off)
        scores = torch.where(cmask[None, None], scores, -1e9)
        p = _softmax(scores, axis=-1)
        ctx = torch.einsum("bhqk,bhkd->bhqd", p, v)
        return torch.einsum("bhqd,hdm->bqm", ctx, w_o)

    x = A_x
    g = _sigmoid((x * gate_w).sum(-1, keepdims=True))
    a = _A_ref(x, A_wqkv, A_wo)
    b = _B_ref(x, B_c_kv, B_w_q, B_w_uk, B_w_uv, B_w_o)
    return g * a + (1 - g) * b
```

```cpp
#include <cuda_runtime.h>
#include <cuda_bf16.h>
#include <cuda.h>
#include <stdint.h>

namespace {

constexpr int SEQ = 2048, DM = 576, DC = 512, NH = 32;
constexpr int NCL = 66;
constexpr int NKB3 = 73;
constexpr uint32_t DESC_HI = 0x40000040u;

constexpr int SM_RING = 0;
constexpr int SM_BUF = 163840;
constexpr int SM_BAR = 229376;
constexpr int B_P1F = 0, B_P1E = 10, B_P2F = 20, B_P2E = 25, B_P3F = 30, B_P3E = 35, B_SF = 40, B_SE = 44, B_QF = 48, B_DONE = 52, B_FIN = 53, B_NUM = 54;
constexpr int SMEM_BYTES = SM_BAR + B_NUM * 8 + 1024;

constexpr int F_HEAD = 0;
constexpr int F_QKVA = 32;
constexpr int F_GATE = 40;
constexpr int F_DONE = 41;
constexpr int F_CTX = 64;
constexpr int F_NUM = 64 + 8 * 64;

struct Sched {
  uint8_t p1_slab[NCL];
  uint8_t p1_n[NCL];
  uint8_t p1_tile[NCL][18];
  uint8_t p2_n[NCL];
  uint8_t p2_item[NCL][10];
  uint8_t p3_tile[NCL];
  uint8_t p3_order[8][33];
};

struct Params {
  CUtensorMap map_a[2];
  CUtensorMap map_w[4];
  CUtensorMap map_o[2];
  const __nv_bfloat16* x;
  const __nv_bfloat16* gate_w;
  __nv_bfloat16* out;
  int phases;
  Sched s;
};

__device__ __align__(1024) uint8_t g_Q[NH * 32 * 16384];
__device__ __align__(1024) uint8_t g_KV[2 * NH * 16 * 32768];
__device__ __align__(1024) uint8_t g_ctx[32 * NKB3 * 8192];
constexpr int TP = SEQ + 16;
__device__ __align__(1024) uint32_t g_T[864 * TP];
__device__ float g_gate[SEQ];
__device__ int g_flags[F_NUM];

__device__ __forceinline__ void mbar_init(uint32_t b, int c) { asm volatile("mbarrier.init.shared::cta.b64 [%0], %1;" ::"r"(b), "r"(c)); }
__device__ __forceinline__ void mbar_expect(uint32_t b, int bytes) {
  asm volatile("mbarrier.arrive.expect_tx.shared::cta.b64 _, [%0], %1;" ::"r"(b), "r"(bytes) : "memory");
}
__device__ __forceinline__ void mbar_arrive(uint32_t b) { asm volatile("mbarrier.arrive.shared::cta.b64 _, [%0];" ::"r"(b) : "memory"); }
__device__ __forceinline__ void mbar_arrive_cl(uint32_t b, int cnt) {
  asm volatile("mbarrier.arrive.shared::cluster.b64 _, [%0], %1;" ::"r"(b), "r"(cnt) : "memory");
}
__device__ __forceinline__ void mbar_wait(uint32_t b, int par) {
  asm volatile(
      "{\n.reg .pred p;\n.reg .u32 c;\n"
      "mbarrier.try_wait.parity.shared::cta.b64 p, [%0], %1;\n@p bra DN;\nmov.u32 c, 0;\n"
      "LP:\nmbarrier.try_wait.parity.shared::cta.b64 p, [%0], %1;\n@p bra DN;\n"
      "add.u32 c, c, 1;\nsetp.lt.u32 p, c, 4000000;\n@p bra LP;\ntrap;\nDN:\n}" ::"r"(b), "r"(par) : "memory");
}
__device__ __forceinline__ uint32_t mapa(uint32_t a, uint32_t cta) {
  uint32_t r; asm("mapa.shared::cluster.u32 %0, %1, %2;" : "=r"(r) : "r"(a), "r"(cta)); return r;
}
__device__ __forceinline__ void bulk_load(uint32_t dst, const void* src, int bytes, uint32_t bar) {
  asm volatile("cp.async.bulk.shared::cluster.global.mbarrier::complete_tx::bytes [%0], [%1], %2, [%3];" ::"r"(dst), "l"(src), "r"(bytes), "r"(bar) : "memory");
}
__device__ __forceinline__ void bulk_load_mc(uint32_t dst, const void* src, int bytes, uint32_t bar) {
  asm volatile("cp.async.bulk.shared::cluster.global.mbarrier::complete_tx::bytes.multicast::cluster [%0], [%1], %2, [%3], %4;" ::"r"(dst), "l"(src), "r"(bytes), "r"(bar), "h"((uint16_t)3) : "memory");
}
__device__ __forceinline__ void bulk_store(void* dst, uint32_t src, int bytes) {
  asm volatile("cp.async.bulk.global.shared::cta.bulk_group [%0], [%1], %2;" ::"l"(dst), "r"(src), "r"(bytes) : "memory");
}
__device__ __forceinline__ void tma2d(uint32_t dst, const CUtensorMap* m, int c0, int c1, uint32_t bar) {
  asm volatile("cp.async.bulk.tensor.2d.shared::cluster.global.mbarrier::complete_tx::bytes [%0], [%1, {%3, %4}], [%2];" ::"r"(dst), "l"(m), "r"(bar), "r"(c0), "r"(c1) : "memory");
}
__device__ __forceinline__ void tma2d_mc(uint32_t dst, const CUtensorMap* m, int c0, int c1, uint32_t bar) {
  asm volatile("cp.async.bulk.tensor.2d.shared::cluster.global.mbarrier::complete_tx::bytes.multicast::cluster [%0], [%1, {%3, %4}], [%2], %5;" ::"r"(dst), "l"(m), "r"(bar), "r"(c0), "r"(c1), "h"((uint16_t)3) : "memory");
}
__device__ __forceinline__ void tma3d_mc(uint32_t dst, const CUtensorMap* m, int c0, int c1, int c2, uint32_t bar) {
  asm volatile("cp.async.bulk.tensor.3d.shared::cluster.global.mbarrier::complete_tx::bytes.multicast::cluster [%0], [%1, {%3, %4, %5}], [%2], %6;" ::"r"(dst), "l"(m), "r"(bar), "r"(c0), "r"(c1), "r"(c2), "h"((uint16_t)3) : "memory");
}
#define BULK_COMMIT() asm volatile("cp.async.bulk.commit_group;" ::: "memory")
#define BULK_WAIT(n) asm volatile("cp.async.bulk.wait_group %0;" ::"n"(n) : "memory")
#define BULK_WAIT_READ(n) asm volatile("cp.async.bulk.wait_group.read %0;" ::"n"(n) : "memory")
#define FENCE_ASYNC_SMEM() asm volatile("fence.proxy.async.shared::cta;" ::: "memory")
#define FENCE_ASYNC_ALL() asm volatile("fence.proxy.async;" ::: "memory")
#define WG_FENCE() asm volatile("wgmma.fence.sync.aligned;" ::: "memory")
#define WG_COMMIT() asm volatile("wgmma.commit_group.sync.aligned;" ::: "memory")
#define WG_WAIT(n) asm volatile("wgmma.wait_group.sync.aligned %0;" ::"n"(n) : "memory")
__device__ __forceinline__ void bar_sync(int id, int n) { asm volatile("bar.sync %0, %1;" ::"r"(id), "r"(n) : "memory"); }
__device__ __forceinline__ void bar_arrive(int id, int n) { asm volatile("bar.arrive %0, %1;" ::"r"(id), "r"(n) : "memory"); }
__device__ __forceinline__ void cluster_sync() {
  asm volatile("barrier.cluster.arrive.release;\nbarrier.cluster.wait.acquire;" ::: "memory");
}
template <int N> __device__ __forceinline__ void pin(float (&r)[N]) {
#pragma unroll
  for (int i = 0; i < N; i++) asm volatile("" : "+f"(r[i])::"memory");
}
template <int N> __device__ __forceinline__ void pin(uint32_t (&r)[N]) {
#pragma unroll
  for (int i = 0; i < N; i++) asm volatile("" : "+r"(r[i])::"memory");
}
__device__ __forceinline__ uint32_t pack_bf16(float lo, float hi) {
  uint32_t r; asm("cvt.rn.bf16x2.f32 %0, %1, %2;" : "=r"(r) : "f"(hi), "f"(lo)); return r;
}
__device__ __forceinline__ float ex2(float x) { float r; asm("ex2.approx.ftz.f32 %0, %1;" : "=f"(r) : "f"(x)); return r; }
__device__ __forceinline__ void ldsm4(uint32_t a, uint32_t& r0, uint32_t& r1, uint32_t& r2, uint32_t& r3) {
  asm volatile("ldmatrix.sync.aligned.m8n8.x4.shared.b16 {%0,%1,%2,%3}, [%4];" : "=r"(r0), "=r"(r1), "=r"(r2), "=r"(r3) : "r"(a) : "memory");
}
__device__ __forceinline__ void stsm4(uint32_t a, uint32_t r0, uint32_t r1, uint32_t r2, uint32_t r3) {
  asm volatile("stmatrix.sync.aligned.m8n8.x4.shared.b16 [%0], {%1,%2,%3,%4};" ::"r"(a), "r"(r0), "r"(r1), "r"(r2), "r"(r3) : "memory");
}
__device__ __forceinline__ void flag_add(int idx, int v) {
  asm volatile("red.release.gpu.global.add.s32 [%0], %1;" ::"l"(g_flags + idx), "r"(v) : "memory");
}
__device__ __forceinline__ void flag_wait(int idx, int target) {
  int n = 0;
  while (true) {
    int v; asm volatile("ld.acquire.gpu.global.s32 %0, [%1];" : "=r"(v) : "l"(g_flags + idx) : "memory");
    if (v >= target) break;
    if (++n > 20000000) __trap();
    __nanosleep(64);
  }
}
__device__ __forceinline__ uint32_t desc_lo(uint32_t addr, uint32_t lbo) { return ((addr & 0x3FFFFu) >> 4) | ((lbo >> 4) << 16); }
#define PROF(role, i)

template <int TB> __device__ __forceinline__ void wgmma_ss64(float (&d)[32], uint32_t alo, uint32_t blo, int sd) {
  asm volatile("{\n.reg .pred p;\n.reg .b64 da, db;\n"
    "setp.ne.b32 p, %34, 0;\nmov.b64 da, {%32, %36};\nmov.b64 db, {%33, %36};\n"
    "wgmma.mma_async.sync.aligned.m64n64k16.f32.bf16.bf16 "
    "{%0,%1,%2,%3,%4,%5,%6,%7,%8,%9,%10,%11,%12,%13,%14,%15,%16,%17,%18,%19,%20,%21,%22,%23,"
    "%24,%25,%26,%27,%28,%29,%30,%31}, "
    "da, db, p, 1, 1, 0, %35;\n}\n"
    : "+f"(d[0]),"+f"(d[1]),"+f"(d[2]),"+f"(d[3]),"+f"(d[4]),"+f"(d[5]),"+f"(d[6]),"+f"(d[7]),"+f"(d[8]),"+f"(d[9]),"+f"(d[10]),"+f"(d[11]),
      "+f"(d[12]),"+f"(d[13]),"+f"(d[14]),"+f"(d[15]),"+f"(d[16]),"+f"(d[17]),"+f"(d[18]),"+f"(d[19]),"+f"(d[20]),"+f"(d[21]),"+f"(d[22]),"+f"(d[23]),
      "+f"(d[24]),"+f"(d[25]),"+f"(d[26]),"+f"(d[27]),"+f"(d[28]),"+f"(d[29]),"+f"(d[30]),"+f"(d[31])
    : "r"(alo), "r"(blo), "r"(sd), "n"(TB), "r"(DESC_HI));
}
template <int TB> __device__ __forceinline__ void wgmma_ss128(float (&d)[64], uint32_t alo, uint32_t blo, int sd) {
  asm volatile("{\n.reg .pred p;\n.reg .b64 da, db;\n"
    "setp.ne.b32 p, %66, 0;\nmov.b64 da, {%64, %68};\nmov.b64 db, {%65, %68};\n"
    "wgmma.mma_async.sync.aligned.m64n128k16.f32.bf16.bf16 "
    "{%0,%1,%2,%3,%4,%5,%6,%7,%8,%9,%10,%11,%12,%13,%14,%15,%16,%17,%18,%19,%20,%21,%22,%23,"
    "%24,%25,%26,%27,%28,%29,%30,%31,%32,%33,%34,%35,%36,%37,%38,%39,%40,%41,%42,%43,%44,%45,%46,%47,"
    "%48,%49,%50,%51,%52,%53,%54,%55,%56,%57,%58,%59,%60,%61,%62,%63}, "
    "da, db, p, 1, 1, 0, %67;\n}\n"
    : "+f"(d[0]),"+f"(d[1]),"+f"(d[2]),"+f"(d[3]),"+f"(d[4]),"+f"(d[5]),"+f"(d[6]),"+f"(d[7]),"+f"(d[8]),"+f"(d[9]),"+f"(d[10]),"+f"(d[11]),
      "+f"(d[12]),"+f"(d[13]),"+f"(d[14]),"+f"(d[15]),"+f"(d[16]),"+f"(d[17]),"+f"(d[18]),"+f"(d[19]),"+f"(d[20]),"+f"(d[21]),"+f"(d[22]),"+f"(d[23]),
      "+f"(d[24]),"+f"(d[25]),"+f"(d[26]),"+f"(d[27]),"+f"(d[28]),"+f"(d[29]),"+f"(d[30]),"+f"(d[31]),"+f"(d[32]),"+f"(d[33]),"+f"(d[34]),"+f"(d[35]),
      "+f"(d[36]),"+f"(d[37]),"+f"(d[38]),"+f"(d[39]),"+f"(d[40]),"+f"(d[41]),"+f"(d[42]),"+f"(d[43]),"+f"(d[44]),"+f"(d[45]),"+f"(d[46]),"+f"(d[47]),
      "+f"(d[48]),"+f"(d[49]),"+f"(d[50]),"+f"(d[51]),"+f"(d[52]),"+f"(d[53]),"+f"(d[54]),"+f"(d[55]),"+f"(d[56]),"+f"(d[57]),"+f"(d[58]),"+f"(d[59]),
      "+f"(d[60]),"+f"(d[61]),"+f"(d[62]),"+f"(d[63])
    : "r"(alo), "r"(blo), "r"(sd), "n"(TB), "r"(DESC_HI));
}
template <int TB> __device__ __forceinline__ void wgmma_rs128(float (&d)[64], uint32_t a0, uint32_t a1, uint32_t a2, uint32_t a3, uint32_t blo, int sd) {
  asm volatile("{\n.reg .pred p;\n.reg .b64 db;\n"
    "setp.ne.b32 p, %69, 0;\nmov.b64 db, {%68, %71};\n"
    "wgmma.mma_async.sync.aligned.m64n128k16.f32.bf16.bf16 "
    "{%0,%1,%2,%3,%4,%5,%6,%7,%8,%9,%10,%11,%12,%13,%14,%15,%16,%17,%18,%19,%20,%21,%22,%23,"
    "%24,%25,%26,%27,%28,%29,%30,%31,%32,%33,%34,%35,%36,%37,%38,%39,%40,%41,%42,%43,%44,%45,%46,%47,"
    "%48,%49,%50,%51,%52,%53,%54,%55,%56,%57,%58,%59,%60,%61,%62,%63}, "
    "{%64,%65,%66,%67}, db, p, 1, 1, %70;\n}\n"
    : "+f"(d[0]),"+f"(d[1]),"+f"(d[2]),"+f"(d[3]),"+f"(d[4]),"+f"(d[5]),"+f"(d[6]),"+f"(d[7]),"+f"(d[8]),"+f"(d[9]),"+f"(d[10]),"+f"(d[11]),
      "+f"(d[12]),"+f"(d[13]),"+f"(d[14]),"+f"(d[15]),"+f"(d[16]),"+f"(d[17]),"+f"(d[18]),"+f"(d[19]),"+f"(d[20]),"+f"(d[21]),"+f"(d[22]),"+f"(d[23]),
      "+f"(d[24]),"+f"(d[25]),"+f"(d[26]),"+f"(d[27]),"+f"(d[28]),"+f"(d[29]),"+f"(d[30]),"+f"(d[31]),"+f"(d[32]),"+f"(d[33]),"+f"(d[34]),"+f"(d[35]),
      "+f"(d[36]),"+f"(d[37]),"+f"(d[38]),"+f"(d[39]),"+f"(d[40]),"+f"(d[41]),"+f"(d[42]),"+f"(d[43]),"+f"(d[44]),"+f"(d[45]),"+f"(d[46]),"+f"(d[47]),
      "+f"(d[48]),"+f"(d[49]),"+f"(d[50]),"+f"(d[51]),"+f"(d[52]),"+f"(d[53]),"+f"(d[54]),"+f"(d[55]),"+f"(d[56]),"+f"(d[57]),"+f"(d[58]),"+f"(d[59]),
      "+f"(d[60]),"+f"(d[61]),"+f"(d[62]),"+f"(d[63])
    : "r"(a0), "r"(a1), "r"(a2), "r"(a3), "r"(blo), "r"(sd), "n"(TB), "r"(DESC_HI));
}
template <int TB> __device__ __forceinline__ void wgmma_ss192(float (&d)[96], uint32_t alo, uint32_t blo, int sd) {
  asm volatile("{\n.reg .pred p;\n.reg .b64 da, db;\n"
    "setp.ne.b32 p, %98, 0;\nmov.b64 da, {%96, %100};\nmov.b64 db, {%97, %100};\n"
    "wgmma.mma_async.sync.aligned.m64n192k16.f32.bf16.bf16 "
    "{%0,%1,%2,%3,%4,%5,%6,%7,%8,%9,%10,%11,%12,%13,%14,%15,%16,%17,%18,%19,%20,%21,%22,%23,"
    "%24,%25,%26,%27,%28,%29,%30,%31,%32,%33,%34,%35,%36,%37,%38,%39,%40,%41,%42,%43,%44,%45,%46,%47,"
    "%48,%49,%50,%51,%52,%53,%54,%55,%56,%57,%58,%59,%60,%61,%62,%63,%64,%65,%66,%67,%68,%69,%70,%71,"
    "%72,%73,%74,%75,%76,%77,%78,%79,%80,%81,%82,%83,%84,%85,%86,%87,%88,%89,%90,%91,%92,%93,%94,%95}, "
    "da, db, p, 1, 1, 0, %99;\n}\n"
    : "+f"(d[0]),"+f"(d[1]),"+f"(d[2]),"+f"(d[3]),"+f"(d[4]),"+f"(d[5]),"+f"(d[6]),"+f"(d[7]),"+f"(d[8]),"+f"(d[9]),"+f"(d[10]),"+f"(d[11]),
      "+f"(d[12]),"+f"(d[13]),"+f"(d[14]),"+f"(d[15]),"+f"(d[16]),"+f"(d[17]),"+f"(d[18]),"+f"(d[19]),"+f"(d[20]),"+f"(d[21]),"+f"(d[22]),"+f"(d[23]),
      "+f"(d[24]),"+f"(d[25]),"+f"(d[26]),"+f"(d[27]),"+f"(d[28]),"+f"(d[29]),"+f"(d[30]),"+f"(d[31]),"+f"(d[32]),"+f"(d[33]),"+f"(d[34]),"+f"(d[35]),
      "+f"(d[36]),"+f"(d[37]),"+f"(d[38]),"+f"(d[39]),"+f"(d[40]),"+f"(d[41]),"+f"(d[42]),"+f"(d[43]),"+f"(d[44]),"+f"(d[45]),"+f"(d[46]),"+f"(d[47]),
      "+f"(d[48]),"+f"(d[49]),"+f"(d[50]),"+f"(d[51]),"+f"(d[52]),"+f"(d[53]),"+f"(d[54]),"+f"(d[55]),"+f"(d[56]),"+f"(d[57]),"+f"(d[58]),"+f"(d[59]),
      "+f"(d[60]),"+f"(d[61]),"+f"(d[62]),"+f"(d[63]),"+f"(d[64]),"+f"(d[65]),"+f"(d[66]),"+f"(d[67]),"+f"(d[68]),"+f"(d[69]),"+f"(d[70]),"+f"(d[71]),
      "+f"(d[72]),"+f"(d[73]),"+f"(d[74]),"+f"(d[75]),"+f"(d[76]),"+f"(d[77]),"+f"(d[78]),"+f"(d[79]),"+f"(d[80]),"+f"(d[81]),"+f"(d[82]),"+f"(d[83]),
      "+f"(d[84]),"+f"(d[85]),"+f"(d[86]),"+f"(d[87]),"+f"(d[88]),"+f"(d[89]),"+f"(d[90]),"+f"(d[91]),"+f"(d[92]),"+f"(d[93]),"+f"(d[94]),"+f"(d[95])
    : "r"(alo), "r"(blo), "r"(sd), "n"(TB), "r"(DESC_HI));
}

struct Ctx {
  uint32_t sm;
  uint32_t bar;
  uint32_t rbar;
  int cl, rank, wg, warp, lane;
};
__device__ __forceinline__ void release(const Ctx& c, int b, int cnt = 1) {
  if (c.lane < 2) mbar_arrive_cl(c.rbar + b * 8, cnt);
}
constexpr int ORDER = 1;

__device__ __forceinline__ void stage_tile(const float (&a)[64], uint32_t buf, const Ctx& c, float s0, float s1) {
  const int row = (c.lane & 7) + ((c.lane >> 3) & 1) * 8;
  const uint32_t base = buf + (c.warp * 16 + row) * 128 + (((c.lane >> 4) ^ (row & 7)) << 4);
#pragma unroll
  for (int i = 0; i < 8; i++)
    stsm4((base ^ ((i & 3) << 5)) + (i >> 2) * 8192, pack_bf16(a[8 * i] * s0, a[8 * i + 1] * s0), pack_bf16(a[8 * i + 2] * s1, a[8 * i + 3] * s1),
          pack_bf16(a[8 * i + 4] * s0, a[8 * i + 5] * s0), pack_bf16(a[8 * i + 6] * s1, a[8 * i + 7] * s1));
}

__device__ __forceinline__ void p1_consumer(const Params& p, const Ctx& c, bool signal_last) {
  const int n = p.s.p1_n[c.cl];
  const int type = p.s.p1_slab[c.cl] >> 3, grp = p.s.p1_slab[c.cl] & 7;
  uint32_t A[128];
  {
    const int row = (c.lane & 7) + ((c.lane >> 3) & 1) * 8;
    const uint32_t base = c.sm + SM_RING + (c.wg * 64 + c.warp * 16 + row) * 128 + (((c.lane >> 4) ^ (row & 7)) << 4);
#pragma unroll
    for (int kb = 0; kb < 8; kb++) {
      mbar_wait(c.bar + (B_P1F + kb) * 8, 0);
#pragma unroll
      for (int kk = 0; kk < 4; kk++) ldsm4((base ^ (kk << 5)) + kb * 16384, A[kb * 16 + kk * 4], A[kb * 16 + kk * 4 + 1], A[kb * 16 + kk * 4 + 2], A[kb * 16 + kk * 4 + 3]);
      __syncwarp();
      release(c, B_P1E + kb);
    }
  }
  PROF(c.wg, 1);
  int slot = 8, par = 0;
  const uint32_t bdesc = desc_lo(c.sm + SM_RING, 8192), adesc = desc_lo(c.sm + SM_BUF + 32768 + c.wg * 8192, 16);
  float acc[64];
  for (int t = 0; t < n; t++) {
    const int tile = p.s.p1_tile[c.cl][t];
    bar_sync(ORDER + c.wg, 256);
    int prev = -1;
    if (type) {
      mbar_wait(c.bar + (B_P1F + slot) * 8, par);
      WG_FENCE();
#pragma unroll
      for (int kk = 0; kk < 4; kk++) wgmma_ss128<1>(acc, adesc + kk * 2, bdesc + slot * 1024 + kk * 128, kk != 0);
      WG_COMMIT();
      prev = slot;
      if (++slot == 10) { slot = 0; par ^= 1; }
    }
#pragma unroll
    for (int kb = 0; kb < 8; kb++) {
      mbar_wait(c.bar + (B_P1F + slot) * 8, par);
      WG_FENCE();
      const uint32_t d = bdesc + slot * 1024;
#pragma unroll
      for (int kk = 0; kk < 4; kk++)
        wgmma_rs128<1>(acc, A[kb * 16 + kk * 4], A[kb * 16 + kk * 4 + 1], A[kb * 16 + kk * 4 + 2], A[kb * 16 + kk * 4 + 3], d + kk * 128, (kb | kk) != 0 ? 1 : type);
      WG_COMMIT();
      if (kb == 7) { if (t + 1 < n || c.wg == 0 || signal_last) bar_arrive(ORDER + (c.wg ^ 1), 256); }
      WG_WAIT(1);
      if (kb > 0 || prev >= 0) release(c, B_P1E + prev);
      prev = slot;
      if (++slot == 10) { slot = 0; par ^= 1; }
    }
    WG_WAIT(0);
    pin(acc);
    release(c, B_P1E + prev);
    const int b = c.wg * 2 + 1;
    mbar_wait(c.bar + (B_SE + b) * 8, (t & 1) ^ 1);
    if (type && tile >= 32) {
      const int row = grp * 256 + c.rank * 128 + c.wg * 64 + c.warp * 16 + (c.lane >> 2);
      uint32_t* dst = g_T + ((tile - 32) * 64 + (c.lane & 3)) * TP + 16 + row;
#pragma unroll
      for (int i = 0; i < 16; i++) {
        if (i < 8 || tile < 45) {
          dst[i * 4 * TP] = pack_bf16(acc[4 * i], acc[4 * i + 1]);
          dst[i * 4 * TP + 8] = pack_bf16(acc[4 * i + 2], acc[4 * i + 3]);
        }
      }
    } else {
      stage_tile(acc, c.sm + SM_BUF + b * 16384, c, 1.f, 1.f);
      FENCE_ASYNC_SMEM();
    }
    __syncwarp();
    if (c.lane == 0) mbar_arrive(c.bar + (B_SF + b) * 8);
    PROF(c.wg, 2 + t);
  }
}

__device__ __forceinline__ void p1_producer(const Params& p, const Ctx& c) {
  const int n = p.s.p1_n[c.cl];
  const int type = p.s.p1_slab[c.cl] >> 3, grp = p.s.p1_slab[c.cl] & 7;
  for (int kb = 0; kb < 8; kb++) {
    mbar_expect(c.bar + (B_P1F + kb) * 8, kb == 7 && type ? 32768 : 16384);
    tma2d(c.sm + SM_RING + kb * 16384, &p.map_a[type], kb * 64, grp * 256 + c.rank * 128, c.bar + (B_P1F + kb) * 8);
  }
  if (type) tma2d(c.sm + SM_BUF + 32768, &p.map_a[1], 512, grp * 256 + c.rank * 128, c.bar + (B_P1F + 7) * 8);
  int slot = 8, par = 1;
  for (int t = 0; t < n; t++) {
    const int tile = p.s.p1_tile[c.cl][t];
    const CUtensorMap* m = &p.map_w[type * 2 + (tile >> 5)];
    const int n0 = (tile & 31) * 128 + c.rank * 64;
    for (int kb = -type; kb < 8; kb++) {
      mbar_wait(c.bar + (B_P1E + slot) * 8, par);
      mbar_expect(c.bar + (B_P1F + slot) * 8, 16384);
      tma2d_mc(c.sm + SM_RING + slot * 16384 + c.rank * 8192, m, n0, kb < 0 ? 512 : kb * 64, c.bar + (B_P1F + slot) * 8);
      if (++slot == 10) { slot = 0; par ^= 1; }
    }
  }
}

__device__ __forceinline__ void p1_storer(const Params& p, const Ctx& c) {
  const int n = p.s.p1_n[c.cl];
  const int type = p.s.p1_slab[c.cl] >> 3, grp = p.s.p1_slab[c.cl] & 7;
  int pf = -1;
  for (int i = 0; i < 2 * n; i++) {
    const int t = i >> 1, w = i & 1, b = w * 2 + 1;
    const int tile = p.s.p1_tile[c.cl][t];
    mbar_wait(c.bar + (B_SF + b) * 8, t & 1);
    const uint32_t src = c.sm + SM_BUF + b * 16384;
    int f = F_HEAD + (tile & 31);
    if (type == 0) {
      uint8_t* dst = g_KV + (size_t)(tile * 16 + grp * 2 + c.rank) * 32768 + w * 8192;
      bulk_store(dst, src, 8192);
      bulk_store(dst + 16384, src + 8192, 8192);
    } else if (tile < 32) {
      bulk_store(g_Q + (size_t)(tile * 32 + grp * 4 + c.rank * 2 + w) * 16384, src, 16384);
    } else {
      f = F_QKVA + grp;
    }
    BULK_COMMIT();
    BULK_WAIT_READ(0);
    mbar_arrive(c.bar + (B_SE + b) * 8);
    if (pf >= 0) {
      BULK_WAIT(1);
      FENCE_ASYNC_ALL();
      flag_add(pf, 1);
    }
    pf = f;
  }
  BULK_WAIT(0);
  FENCE_ASYNC_ALL();
  flag_add(pf, 1);
}

__device__ __forceinline__ void ring5(int pos, int& slot, int& par) {
  const int q = (pos * 52429) >> 18;
  slot = pos - q * 5; par = q & 1;
}
__device__ __forceinline__ int p2_ntiles(const Params& p, int cl) {
  int N = 0;
  for (int i = 0; i < p.s.p2_n[cl]; i++) N += 2 * (p.s.p2_item[cl][i] & 7) + 2;
  return N;
}
__device__ __forceinline__ int p2_blk(int rank, int w, int i) { return ((i ^ w) & 1) == 0 ? 3 - rank : rank; }

constexpr int SPLIT = 8;
constexpr float SM_SCALE = 0.08838834764831845f * 1.4426950408889634f;

__device__ __forceinline__ void row_max(const float (&s)[64], float& m0, float& m1) {
#pragma unroll
  for (int i = 0; i < 16; i++) {
    m0 = fmaxf(m0, fmaxf(s[4 * i], s[4 * i + 1]));
    m1 = fmaxf(m1, fmaxf(s[4 * i + 2], s[4 * i + 3]));
  }
  m0 = fmaxf(m0, __shfl_xor_sync(0xffffffffu, m0, 1));
  m1 = fmaxf(m1, __shfl_xor_sync(0xffffffffu, m1, 1));
  m0 = fmaxf(m0, __shfl_xor_sync(0xffffffffu, m0, 2));
  m1 = fmaxf(m1, __shfl_xor_sync(0xffffffffu, m1, 2));
}
template <int I0, int I1>
__device__ __forceinline__ void row_exp(float (&s)[64], float m0, float m1, float& l0, float& l1) {
  const float b0 = -m0 * SM_SCALE, b1 = -m1 * SM_SCALE;
  float t0 = 0.f, t1 = 0.f;
#pragma unroll
  for (int i = I0; i < I1; i++) {
    s[4 * i] = ex2(fmaf(s[4 * i], SM_SCALE, b0));
    s[4 * i + 1] = ex2(fmaf(s[4 * i + 1], SM_SCALE, b0));
    s[4 * i + 2] = ex2(fmaf(s[4 * i + 2], SM_SCALE, b1));
    s[4 * i + 3] = ex2(fmaf(s[4 * i + 3], SM_SCALE, b1));
    l0 += s[4 * i]; t0 += s[4 * i + 1];
    l1 += s[4 * i + 2]; t1 += s[4 * i + 3];
  }
  l0 += t0; l1 += t1;
}
__device__ __forceinline__ void order_after(float v, uint32_t bar) {
  asm volatile("{\n.reg .pred p;\nsetp.lt.f32 p, %0, 0f00000000;\n@p mbarrier.arrive.shared::cta.b64 _, [%1];\n}" ::"f"(v), "r"(bar) : "memory");
}
__device__ __forceinline__ void causal_mask(float (&s)[64], int thr) {
#pragma unroll
  for (int i = 0; i < 16; i++) {
    if (8 * i > thr) s[4 * i] = -INFINITY;
    if (8 * i + 1 > thr) s[4 * i + 1] = -INFINITY;
    if (8 * i - 8 > thr) s[4 * i + 2] = -INFINITY;
    if (8 * i - 7 > thr) s[4 * i + 3] = -INFINITY;
  }
}
__device__ __forceinline__ void issue_qk(float (&s)[64], uint32_t qd, uint32_t kd) {
#pragma unroll
  for (int kk = 0; kk < 8; kk++) wgmma_ss128<0>(s, qd + (kk >> 2) * 512 + (kk & 3) * 2, kd + (kk >> 2) * 1024 + (kk & 3) * 2, kk != 0);
  WG_COMMIT();
}
__device__ __forceinline__ void issue_pv(float (&o)[64], const uint32_t (&P)[32], uint32_t vd, int acc) {
#pragma unroll
  for (int kk = 0; kk < 8; kk++) wgmma_rs128<1>(o, P[4 * kk], P[4 * kk + 1], P[4 * kk + 2], P[4 * kk + 3], vd + kk * 128, kk != 0 ? 1 : acc);
  WG_COMMIT();
}
__device__ __forceinline__ void p2_epilogue(const float (&o)[64], float l0, float l1, float g0, float g1, const Ctx& c, int b) {
  l0 += __shfl_xor_sync(0xffffffffu, l0, 1);
  l1 += __shfl_xor_sync(0xffffffffu, l1, 1);
  l0 += __shfl_xor_sync(0xffffffffu, l0, 2);
  l1 += __shfl_xor_sync(0xffffffffu, l1, 2);
  stage_tile(o, c.sm + SM_BUF + b * 16384, c, __fdividef(1.f - g0, l0), __fdividef(1.f - g1, l1));
  FENCE_ASYNC_SMEM();
  __syncwarp();
  if (c.lane == 0) mbar_arrive(c.bar + (B_SF + b) * 8);
}

__device__ __forceinline__ void p2_consumer(const Params& p, const Ctx& c) {
  const int nit = p.s.p2_n[c.cl];
  const int N = p2_ntiles(p, c.cl);
  const uint32_t kdesc = desc_lo(c.sm + SM_RING, 16), vdesc = desc_lo(c.sm + SM_RING, 16384);
  const uint32_t qdesc = desc_lo(c.sm + SM_BUF + c.wg * 32768, 16);
  const int rloc = c.warp * 16 + (c.lane >> 2);
  float o[64], s[64];
  uint32_t P[32];
  float m0, m1, l0, l1, g0, g1;
  int it = 0, n, nend, pn, pcnt, acc;
  {
    const int j = p.s.p2_item[c.cl][0] & 7, blk = p2_blk(c.rank, c.wg, 0);
    n = c.wg; nend = 2 * j + 2;
    const int pos = n;
    bar_sync(ORDER + c.wg, 256);
    mbar_wait(c.bar + (B_QF + c.wg * 2) * 8, 0);
    mbar_wait(c.bar + (B_P2F + pos) * 8, 0);
    WG_FENCE();
    issue_qk(s, qdesc, kdesc + pos * 2048);
    bar_arrive(ORDER + (c.wg ^ 1), 256);
    g0 = __ldcg(g_gate + (j * 4 + blk) * 64 + rloc);
    g1 = __ldcg(g_gate + (j * 4 + blk) * 64 + rloc + 8);
    pcnt = c.wg == 0 ? 2 : 1;
    WG_WAIT(0);
    pin(s);
    release(c, B_P2E + pos, pcnt);
    causal_mask(s, rloc + (blk & 1) * 64 - 2 * (c.lane & 3));
    m0 = m1 = -INFINITY; l0 = l1 = 0.f;
    row_max(s, m0, m1);
    row_exp<0, 16>(s, m0, m1, l0, l1);
#pragma unroll
    for (int i = 0; i < 32; i++) P[i] = pack_bf16(s[2 * i], s[2 * i + 1]);
    pn = n; n++; acc = 0;
  }
  PROF(c.wg, 24);
  while (true) {
    bool first = false;
    int j = 0, blk = 0, cnt = 1;
    if (n == nend) {
      if (++it == nit) break;
      first = true;
      j = p.s.p2_item[c.cl][it] & 7;
      blk = p2_blk(c.rank, c.wg, it);
      nend = n + 2 * j + 2;
      if ((it ^ c.wg) & 1) n++; else cnt = 2;
    }
    int ks, kp, vs, vp;
    ring5(2 * n - 1, ks, kp);
    ring5(2 * pn + 2, vs, vp);
    if (first) mbar_wait(c.bar + (B_QF + c.wg * 2 + (it & 1)) * 8, (it >> 1) & 1);
    mbar_wait(c.bar + (B_P2F + ks) * 8, kp);
    mbar_wait(c.bar + (B_P2F + vs) * 8, vp);
    bar_sync(ORDER + c.wg, 256);
    pin(o); pin(P);
    WG_FENCE();
    issue_qk(s, qdesc + (it & 1) * 1024, kdesc + ks * 2048);
    issue_pv(o, P, vdesc + vs * 2048, acc);
    bar_arrive(ORDER + (c.wg ^ 1), 256);
    WG_WAIT(1);
    pin(s);
    release(c, B_P2E + ks, cnt);
    if (first) {
      const float h0 = __ldcg(g_gate + (j * 4 + blk) * 64 + rloc), h1 = __ldcg(g_gate + (j * 4 + blk) * 64 + rloc + 8);
      causal_mask(s, rloc + (blk & 1) * 64 - 2 * (c.lane & 3));
      float n0 = 0.f, n1 = 0.f;
      m0 = m1 = -INFINITY;
      row_max(s, m0, m1);
      row_exp<0, SPLIT>(s, m0, m1, n0, n1);
      order_after(n0 + n1, c.bar + B_FIN * 8);
      WG_WAIT(0);
      pin(o);
      release(c, B_P2E + vs, pcnt);
      row_exp<SPLIT, 16>(s, m0, m1, n0, n1);
      p2_epilogue(o, l0, l1, g0, g1, c, c.wg * 2 + ((it - 1) & 1));
      l0 = n0; l1 = n1; g0 = h0; g1 = h1; acc = 0;
      PROF(c.wg, 24 + it);
    } else {
      float n0 = m0, n1 = m1;
      row_max(s, n0, n1);
      const float a0 = ex2((m0 - n0) * SM_SCALE), a1 = ex2((m1 - n1) * SM_SCALE);
      m0 = n0; m1 = n1;
      l0 *= a0; l1 *= a1;
      row_exp<0, SPLIT>(s, m0, m1, l0, l1);
      order_after(l0 + l1, c.bar + B_FIN * 8);
      WG_WAIT(0);
      pin(o);
      release(c, B_P2E + vs, pcnt);
      row_exp<SPLIT, 16>(s, m0, m1, l0, l1);
#pragma unroll
      for (int i = 0; i < 16; i++) { o[4 * i] *= a0; o[4 * i + 1] *= a0; o[4 * i + 2] *= a1; o[4 * i + 3] *= a1; }
      acc = 1;
    }
#pragma unroll
    for (int i = 0; i < 32; i++) P[i] = pack_bf16(s[2 * i], s[2 * i + 1]);
    pn = n; pcnt = cnt; n++;
  }
  {
    int vs, vp;
    ring5(2 * N - 1, vs, vp);
    bar_sync(ORDER + c.wg, 256);
    mbar_wait(c.bar + (B_P2F + vs) * 8, vp);
    pin(o); pin(P);
    WG_FENCE();
    issue_pv(o, P, vdesc + vs * 2048, acc);
    if (((nit - 1) ^ c.wg) & 1) bar_arrive(ORDER + (c.wg ^ 1), 256);
    WG_WAIT(0);
    pin(o);
    p2_epilogue(o, l0, l1, g0, g1, c, c.wg * 2 + ((nit - 1) & 1));
    PROF(c.wg, 24 + nit);
  }
}

__device__ __forceinline__ void p2_producer(const Params& p, const Ctx& c) {
  const int nit = p.s.p2_n[c.cl];
  int slot = 0, par = 0;
  const uint8_t* pv = nullptr;
  auto load = [&](const uint8_t* src) {
    mbar_wait(c.bar + (B_P2E + slot) * 8, par);
    mbar_expect(c.bar + (B_P2F + slot) * 8, 32768);
    bulk_load_mc(c.sm + SM_RING + slot * 32768 + c.rank * 16384, src, 16384, c.bar + (B_P2F + slot) * 8);
    if (++slot == 5) { slot = 0; par ^= 1; }
  };
  for (int it = 0; it < nit; it++) {
    const int item = p.s.p2_item[c.cl][it], h = item >> 3, j = item & 7;
    if (p.phases & 16) { flag_wait(F_HEAD + h, 96); FENCE_ASYNC_ALL(); }
    for (int t = 2 * j + 1; t >= 0; t--) {
      const uint8_t* k = g_KV + (size_t)(h * 16 + t) * 32768 + c.rank * 16384;
      load(k);
      if (pv) load(pv);
      pv = k + (size_t)NH * 16 * 32768;
    }
  }
  load(pv);
}

__device__ __forceinline__ void p2_storer(const Params& p, const Ctx& c, int sfpar) {
  const int nit = p.s.p2_n[c.cl];
  auto load_q = [&](int it, int w) {
    const int item = p.s.p2_item[c.cl][it], h = item >> 3, j = item & 7, b = w * 2 + (it & 1);
    if (p.phases & 16) { flag_wait(F_HEAD + h, 96); FENCE_ASYNC_ALL(); }
    mbar_expect(c.bar + (B_QF + b) * 8, 16384);
    bulk_load(c.sm + SM_BUF + b * 16384, g_Q + (size_t)(h * 32 + j * 4 + p2_blk(c.rank, w, it)) * 16384, 16384, c.bar + (B_QF + b) * 8);
  };
  if (p.phases & 16) flag_wait(F_GATE, 256);
  load_q(0, 0); load_q(0, 1);
  if (nit > 1) { load_q(1, 1); load_q(1, 0); }
  for (int i = 0; i < 2 * nit; i++) {
    const int it = i >> 1, w = (it ^ i ^ 1) & 1, b = w * 2 + (it & 1);
    const int item = p.s.p2_item[c.cl][it], h = item >> 3, j = item & 7;
    mbar_wait(c.bar + (B_SF + b) * 8, (sfpar >> b) & 1);
    sfpar ^= 1 << b;
    bulk_store(g_ctx + (size_t)((j * 4 + p2_blk(c.rank, w, it)) * NKB3 + 9 + 2 * h) * 8192, c.sm + SM_BUF + b * 16384, 16384);
    BULK_COMMIT();
    BULK_WAIT(0);
    FENCE_ASYNC_ALL();
    flag_add(F_CTX + j * 64 + h, 1);
    if (it + 2 < nit) load_q(it + 2, w);
  }
}

__device__ __forceinline__ void p3_consumer(const Params& p, const Ctx& c) {
  const int tile = p.s.p3_tile[c.cl], j = tile / 3, nt = tile - 3 * j;
  const uint32_t ad = desc_lo(c.sm + SM_RING + c.wg * 8192, 16), bd = desc_lo(c.sm + SM_RING + 16384, 4096);
  float acc[96];
  int slot = 0, par = 0, prev = 0;
  for (int kb = 0; kb < NKB3; kb++) {
    mbar_wait(c.bar + (B_P3F + slot) * 8, par);
    WG_FENCE();
#pragma unroll
    for (int kk = 0; kk < 4; kk++) wgmma_ss192<1>(acc, ad + slot * 2560 + kk * 2, bd + slot * 2560 + (kk >> 1) * 768 + (kk & 1) * 128, kk != 0 ? 1 : kb != 0);
    WG_COMMIT();
    WG_WAIT(1);
    if (kb > 0) release(c, B_P3E + prev);
    prev = slot;
    if (++slot == 5) { slot = 0; par ^= 1; }
  }
  WG_WAIT(0);
  pin(acc);
  PROF(c.wg, 40);
  const int row = j * 256 + c.rank * 128 + c.wg * 64 + c.warp * 16 + (c.lane >> 2);
  uint32_t* dst = reinterpret_cast<uint32_t*>(p.out + (size_t)row * DM + nt * 192) + (c.lane & 3);
#pragma unroll
  for (int i = 0; i < 24; i++) {
    dst[i * 4] = pack_bf16(acc[4 * i], acc[4 * i + 1]);
    dst[i * 4 + 4 * DM] = pack_bf16(acc[4 * i + 2], acc[4 * i + 3]);
  }
}

__device__ __forceinline__ void p3_producer(const Params& p, const Ctx& c) {
  const int tile = p.s.p3_tile[c.cl], j = tile / 3, nt = tile - 3 * j;
  int slot = 0, par = 0;
  const uint8_t* a = g_ctx + (size_t)(j * 4 + c.rank * 2) * NKB3 * 8192;
  for (int q = 0; q < 33; q++) {
    const int g = p.s.p3_order[j][q];
    if (p.phases & 16) { flag_wait(F_CTX + j * 64 + g, g == 32 ? 128 : 4); FENCE_ASYNC_ALL(); }
    const int kb0 = g == 32 ? 0 : 9 + 2 * g, nk = g == 32 ? 9 : 2, k0 = (g == 32 ? 0 : g * 128) + c.rank * 32;
    const CUtensorMap* m = &p.map_o[g == 32];
    for (int i = 0; i < nk; i++) {
      const uint32_t st = c.sm + SM_RING + slot * 40960, fb = c.bar + (B_P3F + slot) * 8;
      mbar_wait(c.bar + (B_P3E + slot) * 8, par);
      mbar_expect(fb, 40960);
      bulk_load(st, a + (size_t)(kb0 + i) * 8192, 8192, fb);
      bulk_load(st + 8192, a + (size_t)(NKB3 + kb0 + i) * 8192, 8192, fb);
      tma3d_mc(st + 16384 + c.rank * 12288, m, 0, k0 + i * 64, nt * 3, fb);
      if (++slot == 5) { slot = 0; par ^= 1; }
    }
  }
}

__device__ __forceinline__ float bf_lo(uint32_t w) { return __uint_as_float(w << 16); }
__device__ __forceinline__ float bf_hi(uint32_t w) { return __uint_as_float(w & 0xffff0000u); }

__device__ __forceinline__ void gate_row(const Params& p, int row, int lane) {
  const uint32_t* x = reinterpret_cast<const uint32_t*>(p.x + (size_t)row * DM);
  const uint32_t* w = reinterpret_cast<const uint32_t*>(p.gate_w);
  float a = 0.f;
#pragma unroll
  for (int i = 0; i < 9; i++) {
    const uint32_t u = __ldg(x + i * 32 + lane), v = __ldg(w + i * 32 + lane);
    a = fmaf(bf_lo(u), bf_lo(v), a);
    a = fmaf(bf_hi(u), bf_hi(v), a);
  }
#pragma unroll
  for (int o = 16; o > 0; o >>= 1) a += __shfl_xor_sync(0xffffffffu, a, o);
  if (lane == 0) g_gate[row] = 1.f / (1.f + __expf(-a));
}

__device__ __forceinline__ void local_attn(int rb, int h, int lane) {
  const int s0 = rb * 64 + 2 * lane;
  const uint32_t* T = g_T + (9 * h) * TP + 16 + s0;
  float a[8], b[8];
#pragma unroll
  for (int w = 0; w < 8; w++) a[w] = b[w] = 0.f;
#pragma unroll 1
  for (int j = 0; j < 9; j++) {
    const uint2 q = *reinterpret_cast<const uint2*>(T + j * TP);
    const uint32_t* K = T + (288 + j) * TP;
#pragma unroll
    for (int w = 0; w < 8; w++) {
      const uint2 k = *reinterpret_cast<const uint2*>(K - 2 * w);
      a[w] = fmaf(bf_lo(q.x), bf_lo(k.x), fmaf(bf_hi(q.x), bf_hi(k.x), a[w]));
      b[w] = fmaf(bf_lo(q.y), bf_lo(k.y), fmaf(bf_hi(q.y), bf_hi(k.y), b[w]));
    }
  }
  constexpr float SC = 0.23570226039551584f * 1.4426950408889634f;
  float ma = a[0], mb = b[0];
#pragma unroll
  for (int w = 1; w < 8; w++) {
    if (s0 < 2 * w) a[w] = b[w] = -INFINITY;
    ma = fmaxf(ma, a[w]); mb = fmaxf(mb, b[w]);
  }
  float la = 0.f, lb = 0.f;
#pragma unroll
  for (int w = 0; w < 8; w++) {
    a[w] = ex2((a[w] - ma) * SC); b[w] = ex2((b[w] - mb) * SC);
    la += a[w]; lb += b[w];
  }
  const float2 g = __ldcg(reinterpret_cast<const float2*>(g_gate + s0));
  la = __fdividef(g.x, la); lb = __fdividef(g.y, lb);
#pragma unroll
  for (int w = 0; w < 8; w++) { a[w] *= la; b[w] *= lb; }
  uint8_t* dst = g_ctx + (size_t)rb * NKB3 * 8192 + 2 * lane * 128;
#pragma unroll 1
  for (int j = 0; j < 9; j++) {
    const uint32_t* V = T + (576 + j) * TP;
    float a0 = 0.f, a1 = 0.f, b0 = 0.f, b1 = 0.f;
#pragma unroll
    for (int w = 0; w < 8; w++) {
      const uint2 v = *reinterpret_cast<const uint2*>(V - 2 * w);
      a0 = fmaf(a[w], bf_lo(v.x), a0); a1 = fmaf(a[w], bf_hi(v.x), a1);
      b0 = fmaf(b[w], bf_lo(v.y), b0); b1 = fmaf(b[w], bf_hi(v.y), b1);
    }
    const int col = 18 * h + 2 * j, ch = (col >> 3) & 7;
    uint8_t* d = dst + (col >> 6) * 8192 + (col & 7) * 2;
    *reinterpret_cast<uint32_t*>(d + ((ch ^ ((2 * lane) & 7)) << 4)) = pack_bf16(a0, a1);
    *reinterpret_cast<uint32_t*>(d + 128 + ((ch ^ ((2 * lane + 1) & 7)) << 4)) = pack_bf16(b0, b1);
  }
}

__global__ void __cluster_dims__(2, 1, 1) __launch_bounds__(384, 1) fused_kernel(const __grid_constant__ Params p) {
  extern __shared__ uint8_t smem_raw[];
  Ctx c;
  c.sm = ((uint32_t)__cvta_generic_to_shared(smem_raw) + 1023u) & ~1023u;
  c.bar = c.sm + SM_BAR;
  c.lane = threadIdx.x & 31;
  c.wg = __shfl_sync(0xffffffffu, threadIdx.x >> 7, 0);
  c.warp = __shfl_sync(0xffffffffu, (threadIdx.x >> 5) & 3, 0);
  c.cl = blockIdx.x >> 1;
  c.rank = blockIdx.x & 1;
  c.rbar = mapa(c.bar, c.lane & 1);
  const bool do1 = (p.phases & 1) && p.s.p1_n[c.cl] > 0;
  const bool do2 = (p.phases & 2) && p.s.p2_n[c.cl] > 0;
  const bool do3 = (p.phases & 4) && p.s.p3_tile[c.cl] != 255;
  PROF(c.wg, 0);
  if (threadIdx.x == 0) {
    for (int i = 0; i < 10; i++) { mbar_init(c.bar + (B_P1F + i) * 8, 1); mbar_init(c.bar + (B_P1E + i) * 8, 16); }
    for (int i = 0; i < 5; i++) {
      mbar_init(c.bar + (B_P2F + i) * 8, 1); mbar_init(c.bar + (B_P2E + i) * 8, 16);
      mbar_init(c.bar + (B_P3F + i) * 8, 1); mbar_init(c.bar + (B_P3E + i) * 8, 16);
    }
    for (int i = 0; i < 4; i++) { mbar_init(c.bar + (B_SF + i) * 8, 4); mbar_init(c.bar + (B_SE + i) * 8, 1); mbar_init(c.bar + (B_QF + i) * 8, 1); }
    mbar_init(c.bar + B_DONE * 8, 1);
    mbar_init(c.bar + B_FIN * 8, 8);
    asm volatile("fence.mbarrier_init.release.cluster;" ::: "memory");
  }
  cluster_sync();

  if (c.wg < 2) {
    asm volatile("setmaxnreg.inc.sync.aligned.u32 224;");
    if (c.wg == 1 && (do1 || do2)) bar_arrive(ORDER, 256);
    if (do1) p1_consumer(p, c, do2);
    if (do2) {
#pragma unroll
      for (int i = 0; i < 5; i++) release(c, B_P2E + i);
      p2_consumer(p, c);
    }
    if (do3) {
      mbar_wait(c.bar + B_DONE * 8, 0);
#pragma unroll
      for (int i = 0; i < 5; i++) release(c, B_P3E + i);
      p3_consumer(p, c);
    }
    PROF(c.wg, 63);
    if (c.lane == 0) mbar_arrive(c.bar + B_FIN * 8);
    __syncwarp();
    cluster_sync();
  } else {
    asm volatile("setmaxnreg.dec.sync.aligned.u32 56;");
    if (c.warp == 0) {
      if (c.lane == 0) {
        if (do1) p1_producer(p, c);
        if (do2) p2_producer(p, c);
        if (do3) p3_producer(p, c);
      }
    } else if (c.warp == 1) {
      if (c.lane == 0) {
        int sfpar = 0;
        if (do1) {
          p1_storer(p, c);
          sfpar = (p.s.p1_n[c.cl] & 1) * 10;
        }
        if (do2) p2_storer(p, c, sfpar);
        mbar_arrive(c.bar + B_DONE * 8);
      }
    } else {
      const int bw = blockIdx.x * 2 + (c.warp - 2);
      if ((p.phases & 1) && bw < 256) {
        for (int i = 0; i < 8; i++) gate_row(p, bw * 8 + i, c.lane);
        if (c.lane == 0) flag_add(F_GATE, 1);
      }
      if (p.phases & 8) {
        if (p.phases & 16) { if (c.lane == 0) flag_wait(F_GATE, 256); __syncwarp(); }
        for (int job = bw; job < 1024; job += 264) {
          const int rb = job >> 5, h = job & 31;
          if (p.phases & 16) {
            if (c.lane == 0) { flag_wait(F_QKVA + (rb >> 2), 56); if (rb >= 4 && (rb & 3) == 0) flag_wait(F_QKVA + (rb >> 2) - 1, 56); }
            __syncwarp();
          }
          local_attn(rb, h, c.lane);
          __syncwarp();
          if (c.lane == 0) { __threadfence(); flag_add(F_CTX + (rb >> 2) * 64 + 32, 1); }
        }
      }
    }
    __syncwarp();
    bar_sync(3, 128);
    if (c.warp == 0 && (p.phases & 4)) {
      int last = 0;
      if (c.lane == 0) { __threadfence(); last = atomicAdd(g_flags + F_DONE, 1) == 2 * NCL - 1; }
      if (__shfl_sync(0xffffffffu, last, 0)) for (int i = c.lane; i < F_NUM; i += 32) g_flags[i] = 0;
    }
    if (c.warp == 1) mbar_wait(c.bar + B_FIN * 8, 0);
    __syncwarp();
    cluster_sync();
  }
}

static const Sched k_sched = {
  {0,0,0,0,0,8,8,8,1,1,1,1,9,9,9,9,2,2,2,2,2,10,10,10,10,3,3,3,3,3,11,11,11,4,4,4,4,12,12,12,12,5,5,5,5,5,13,13,13,6,6,6,6,6,14,14,14,14,7,7,7,7,15,15,15,15},
  {13,13,13,13,12,16,15,15,16,16,16,16,12,12,11,11,13,13,13,13,12,12,12,11,11,13,13,13,13,12,16,15,15,16,16,16,16,12,12,11,11,13,13,13,13,12,16,15,15,13,13,13,13,12,12,12,11,11,16,16,16,16,12,12,11,11},
  {{0,34,5,39,10,44,15,49,20,54,25,59,30,0,0,0,0,0},
   {32,3,37,8,42,13,47,18,52,23,57,28,62,0,0,0,0,0},
   {1,35,6,40,11,45,16,50,21,55,26,60,31,0,0,0,0,0},
   {33,4,38,9,43,14,48,19,53,24,58,29,63,0,0,0,0,0},
   {2,36,7,41,12,46,17,51,22,56,27,61,0,0,0,0,0,0},
   {0,3,6,33,36,39,42,45,10,13,16,19,22,25,28,31,0,0},
   {1,4,7,34,37,40,43,8,11,14,17,20,23,26,29,0,0,0},
   {2,5,32,35,38,41,44,9,12,15,18,21,24,27,30,0,0,0},
   {0,2,4,6,8,10,12,14,16,18,20,22,24,26,28,30,0,0},
   {32,34,36,38,40,42,44,46,48,50,52,54,56,58,60,62,0,0},
   {1,3,5,7,9,11,13,15,17,19,21,23,25,27,29,31,0,0},
   {33,35,37,39,41,43,45,47,49,51,53,55,57,59,61,63,0,0},
   {0,4,32,36,40,44,10,14,18,22,26,30,0,0,0,0,0,0},
   {1,5,33,37,41,45,11,15,19,23,27,31,0,0,0,0,0,0},
   {2,6,34,38,42,8,12,16,20,24,28,0,0,0,0,0,0,0},
   {3,7,35,39,43,9,13,17,21,25,29,0,0,0,0,0,0,0},
   {0,34,5,39,10,44,15,49,20,54,25,59,30,0,0,0,0,0},
   {32,3,37,8,42,13,47,18,52,23,57,28,62,0,0,0,0,0},
   {1,35,6,40,11,45,16,50,21,55,26,60,31,0,0,0,0,0},
   {33,4,38,9,43,14,48,19,53,24,58,29,63,0,0,0,0,0},
   {2,36,7,41,12,46,17,51,22,56,27,61,0,0,0,0,0,0},
   {0,4,32,36,40,44,10,14,18,22,26,30,0,0,0,0,0,0},
   {1,5,33,37,41,45,11,15,19,23,27,31,0,0,0,0,0,0},
   {2,6,34,38,42,8,12,16,20,24,28,0,0,0,0,0,0,0},
   {3,7,35,39,43,9,13,17,21,25,29,0,0,0,0,0,0,0},
   {0,34,5,39,10,44,15,49,20,54,25,59,30,0,0,0,0,0},
   {32,3,37,8,42,13,47,18,52,23,57,28,62,0,0,0,0,0},
   {1,35,6,40,11,45,16,50,21,55,26,60,31,0,0,0,0,0},
   {33,4,38,9,43,14,48,19,53,24,58,29,63,0,0,0,0,0},
   {2,36,7,41,12,46,17,51,22,56,27,61,0,0,0,0,0,0},
   {0,3,6,33,36,39,42,45,10,13,16,19,22,25,28,31,0,0},
   {1,4,7,34,37,40,43,8,11,14,17,20,23,26,29,0,0,0},
   {2,5,32,35,38,41,44,9,12,15,18,21,24,27,30,0,0,0},
   {0,2,4,6,8,10,12,14,16,18,20,22,24,26,28,30,0,0},
   {32,34,36,38,40,42,44,46,48,50,52,54,56,58,60,62,0,0},
   {1,3,5,7,9,11,13,15,17,19,21,23,25,27,29,31,0,0},
   {33,35,37,39,41,43,45,47,49,51,53,55,57,59,61,63,0,0},
   {0,4,32,36,40,44,10,14,18,22,26,30,0,0,0,0,0,0},
   {1,5,33,37,41,45,11,15,19,23,27,31,0,0,0,0,0,0},
   {2,6,34,38,42,8,12,16,20,24,28,0,0,0,0,0,0,0},
   {3,7,35,39,43,9,13,17,21,25,29,0,0,0,0,0,0,0},
   {0,34,5,39,10,44,15,49,20,54,25,59,30,0,0,0,0,0},
   {32,3,37,8,42,13,47,18,52,23,57,28,62,0,0,0,0,0},
   {1,35,6,40,11,45,16,50,21,55,26,60,31,0,0,0,0,0},
   {33,4,38,9,43,14,48,19,53,24,58,29,63,0,0,0,0,0},
   {2,36,7,41,12,46,17,51,22,56,27,61,0,0,0,0,0,0},
   {0,3,6,33,36,39,42,45,10,13,16,19,22,25,28,31,0,0},
   {1,4,7,34,37,40,43,8,11,14,17,20,23,26,29,0,0,0},
   {2,5,32,35,38,41,44,9,12,15,18,21,24,27,30,0,0,0},
   {0,34,5,39,10,44,15,49,20,54,25,59,30,0,0,0,0,0},
   {32,3,37,8,42,13,47,18,52,23,57,28,62,0,0,0,0,0},
   {1,35,6,40,11,45,16,50,21,55,26,60,31,0,0,0,0,0},
   {33,4,38,9,43,14,48,19,53,24,58,29,63,0,0,0,0,0},
   {2,36,7,41,12,46,17,51,22,56,27,61,0,0,0,0,0,0},
   {0,4,32,36,40,44,10,14,18,22,26,30,0,0,0,0,0,0},
   {1,5,33,37,41,45,11,15,19,23,27,31,0,0,0,0,0,0},
   {2,6,34,38,42,8,12,16,20,24,28,0,0,0,0,0,0,0},
   {3,7,35,39,43,9,13,17,21,25,29,0,0,0,0,0,0,0},
   {0,2,4,6,8,10,12,14,16,18,20,22,24,26,28,30,0,0},
   {32,34,36,38,40,42,44,46,48,50,52,54,56,58,60,62,0,0},
   {1,3,5,7,9,11,13,15,17,19,21,23,25,27,29,31,0,0},
   {33,35,37,39,41,43,45,47,49,51,53,55,57,59,61,63,0,0},
   {0,4,32,36,40,44,10,14,18,22,26,30,0,0,0,0,0,0},
   {1,5,33,37,41,45,11,15,19,23,27,31,0,0,0,0,0,0},
   {2,6,34,38,42,8,12,16,20,24,28,0,0,0,0,0,0,0},
   {3,7,35,39,43,9,13,17,21,25,29,0,0,0,0,0,0,0}},
  {6,6,5,4,5,5,3,3,3,1,2,2,3,3,4,4,4,5,3,3,6,2,4,6,4,5,3,4,5,6,1,1,3,3,1,4,4,6,5,4,3,3,4,5,5,6,3,2,1,5,4,3,5,4,6,5,4,5,5,1,2,3,7,5,5,4},
  {{12,49,142,205,200,241,0,0,0,0},
   {55,123,138,187,201,224,0,0,0,0},
   {29,126,154,212,240,0,0,0,0,0},
   {3,111,207,251,0,0,0,0,0,0},
   {7,150,170,211,248,0,0,0,0,0},
   {32,74,96,128,152,0,0,0,0,0},
   {42,73,122,0,0,0,0,0,0,0},
   {16,84,145,0,0,0,0,0,0,0},
   {0,76,113,0,0,0,0,0,0,0},
   {95,0,0,0,0,0,0,0,0,0},
   {69,129,0,0,0,0,0,0,0,0},
   {43,107,0,0,0,0,0,0,0,0},
   {27,67,105,0,0,0,0,0,0,0},
   {1,52,115,0,0,0,0,0,0,0},
   {31,141,214,233,0,0,0,0,0,0},
   {5,135,188,236,0,0,0,0,0,0},
   {46,116,181,219,0,0,0,0,0,0},
   {20,118,155,186,244,0,0,0,0,0},
   {63,166,221,0,0,0,0,0,0,0},
   {37,143,222,0,0,0,0,0,0,0},
   {15,124,146,204,208,249,0,0,0,0},
   {70,106,0,0,0,0,0,0,0,0},
   {44,57,167,238,0,0,0,0,0,0},
   {22,56,72,157,196,235,0,0,0,0},
   {39,158,213,250,0,0,0,0,0,0},
   {11,24,110,164,246,0,0,0,0,0},
   {54,159,247,0,0,0,0,0,0,0},
   {28,92,156,230,0,0,0,0,0,0},
   {2,25,127,206,243,0,0,0,0,0},
   {6,65,149,179,202,232,0,0,0,0},
   {101,0,0,0,0,0,0,0,0,0},
   {85,0,0,0,0,0,0,0,0,0},
   {59,97,136,0,0,0,0,0,0,0},
   {17,58,114,0,0,0,0,0,0,0},
   {86,0,0,0,0,0,0,0,0,0},
   {60,88,104,144,0,0,0,0,0,0},
   {34,48,90,153,0,0,0,0,0,0},
   {18,68,174,169,185,209,0,0,0,0},
   {87,148,162,203,242,0,0,0,0,0},
   {13,109,190,210,0,0,0,0,0,0},
   {30,151,239,0,0,0,0,0,0,0},
   {71,140,223,0,0,0,0,0,0,0},
   {45,117,198,218,0,0,0,0,0,0},
   {19,119,172,194,217,0,0,0,0,0},
   {62,133,197,192,234,0,0,0,0,0},
   {23,98,130,180,176,227,0,0,0,0},
   {75,112,161,0,0,0,0,0,0,0},
   {33,100,0,0,0,0,0,0,0,0},
   {102,0,0,0,0,0,0,0,0,0},
   {36,66,175,160,220,0,0,0,0,0},
   {10,94,139,231,0,0,0,0,0,0},
   {79,183,255,0,0,0,0,0,0,0},
   {53,91,182,168,228,0,0,0,0,0},
   {14,134,171,237,0,0,0,0,0,0},
   {61,99,173,177,193,225,0,0,0,0},
   {35,41,82,191,254,0,0,0,0,0},
   {4,93,199,253,0,0,0,0,0,0},
   {47,132,189,184,252,0,0,0,0,0},
   {8,50,64,89,137,0,0,0,0,0},
   {103,0,0,0,0,0,0,0,0,0},
   {77,120,0,0,0,0,0,0,0,0},
   {51,81,121,0,0,0,0,0,0,0},
   {9,26,40,108,147,178,245,0,0,0},
   {78,80,131,215,216,0,0,0,0,0},
   {21,83,165,195,226,0,0,0,0,0},
   {38,125,163,229,0,0,0,0,0,0}},
  {255,255,255,255,255,0,3,4,9,10,11,12,21,22,255,255,255,255,255,255,255,23,255,255,255,255,255,255,255,255,1,5,6,13,14,15,16,255,255,255,255,255,255,255,255,255,2,7,8,255,255,255,255,255,255,255,255,255,17,18,19,20,255,255,255,255},
  {{0,1,2,3,4,5,32,6,7,8,9,10,11,12,13,14,15,16,17,18,19,20,21,22,23,24,25,26,27,28,29,30,31},
   {0,1,2,3,4,5,32,6,7,8,9,10,11,12,13,14,15,16,17,18,19,20,21,22,23,24,25,26,27,28,29,30,31},
   {0,1,2,3,4,5,32,6,7,8,9,10,11,12,13,14,15,16,17,18,19,20,21,22,23,24,25,26,27,28,29,30,31},
   {0,1,2,3,4,5,32,6,7,8,9,10,11,12,13,14,15,16,17,18,19,20,21,22,23,24,25,26,27,28,29,30,31},
   {0,1,2,3,4,5,32,6,7,8,9,10,11,12,13,14,15,16,17,18,19,20,21,22,23,24,25,26,27,28,29,30,31},
   {0,1,2,3,4,5,32,6,7,8,9,10,11,12,13,14,15,16,17,18,19,20,21,22,23,24,25,26,27,28,29,30,31},
   {0,1,2,3,4,5,32,6,7,8,9,10,11,12,13,14,15,16,17,18,19,20,21,22,23,24,25,26,27,28,29,30,31},
   {0,1,2,3,4,5,32,6,7,8,9,10,11,12,13,14,15,16,17,18,19,20,21,22,23,24,25,26,27,28,29,30,31}}};

typedef CUresult (*EncodeFn)(CUtensorMap*, CUtensorMapDataType, cuuint32_t, void*, const cuuint64_t*, const cuuint64_t*, const cuuint32_t*,
                             const cuuint32_t*, CUtensorMapInterleave, CUtensorMapSwizzle, CUtensorMapL2promotion, CUtensorMapFloatOOBfill);

void make_map2(EncodeFn enc, CUtensorMap* m, const void* ptr, int rows, int cols, int box_rows) {
  cuuint64_t dim[2] = {(cuuint64_t)cols, (cuuint64_t)rows}, str[1] = {(cuuint64_t)cols * 2};
  cuuint32_t box[2] = {64, (cuuint32_t)box_rows}, es[2] = {1, 1};
  enc(m, CU_TENSOR_MAP_DATA_TYPE_BFLOAT16, 2, const_cast<void*>(ptr), dim, str, box, es, CU_TENSOR_MAP_INTERLEAVE_NONE, CU_TENSOR_MAP_SWIZZLE_128B,
      CU_TENSOR_MAP_L2_PROMOTION_L2_128B, CU_TENSOR_MAP_FLOAT_OOB_FILL_NONE);
}
void make_map3(EncodeFn enc, CUtensorMap* m, const void* ptr, int rows) {
  cuuint64_t dim[3] = {64, (cuuint64_t)rows, 9}, str[2] = {DM * 2, 128};
  cuuint32_t box[3] = {64, 32, 3}, es[3] = {1, 1, 1};
  enc(m, CU_TENSOR_MAP_DATA_TYPE_BFLOAT16, 3, const_cast<void*>(ptr), dim, str, box, es, CU_TENSOR_MAP_INTERLEAVE_NONE, CU_TENSOR_MAP_SWIZZLE_128B,
      CU_TENSOR_MAP_L2_PROMOTION_L2_128B, CU_TENSOR_MAP_FLOAT_OOB_FILL_NONE);
}

int g_mode = -1;

}

extern "C" void kernel_launch(void* const* d_in, const int* in_sizes, int n_in, void* d_out, int out_size) {
  static EncodeFn enc = nullptr;
  if (!enc) {
    void* fn = nullptr;
    cudaDriverEntryPointQueryResult st;
    cudaGetDriverEntryPoint("cuTensorMapEncodeTiled", &fn, cudaEnableDefault, &st);
    enc = (EncodeFn)fn;
    cudaFuncSetAttribute(fused_kernel, cudaFuncAttributeMaxDynamicSharedMemorySize, SMEM_BYTES);
    if (g_mode < 0) {
      cudaLaunchConfig_t cfg = {};
      cfg.gridDim = dim3(2 * NCL); cfg.blockDim = dim3(384); cfg.dynamicSmemBytes = SMEM_BYTES;
      cudaLaunchAttribute at; at.id = cudaLaunchAttributeClusterDimension;
      at.val.clusterDim.x = 2; at.val.clusterDim.y = 1; at.val.clusterDim.z = 1;
      cfg.attrs = &at; cfg.numAttrs = 1;
      int nc = 0;
      g_mode = (cudaOccupancyMaxActiveClusters(&nc, fused_kernel, &cfg) == cudaSuccess && nc >= NCL) ? 1 : 0;
      (void)cudaGetLastError();
    }
  }
  Params p;
  make_map2(enc, &p.map_a[0], d_in[4], SEQ, DC, 128);
  make_map2(enc, &p.map_a[1], d_in[0], SEQ, DM, 128);
  make_map2(enc, &p.map_w[0], d_in[6], DC, 4096, 64);
  make_map2(enc, &p.map_w[1], d_in[7], DC, 4096, 64);
  make_map2(enc, &p.map_w[2], d_in[5], DM, 4096, 64);
  make_map2(enc, &p.map_w[3], d_in[1], DM, 1728, 64);
  make_map3(enc, &p.map_o[0], d_in[8], 4096);
  make_map3(enc, &p.map_o[1], d_in[2], DM);
  p.x = (const __nv_bfloat16*)d_in[0];
  p.gate_w = (const __nv_bfloat16*)d_in[9];
  p.out = (__nv_bfloat16*)d_out;
  p.s = k_sched;
  if (g_mode == 1) {
    p.phases = 31;
    fused_kernel<<<2 * NCL, 384, SMEM_BYTES>>>(p);
  } else {
    p.phases = 1;  fused_kernel<<<2 * NCL, 384, SMEM_BYTES>>>(p);
    p.phases = 10; fused_kernel<<<2 * NCL, 384, SMEM_BYTES>>>(p);
    p.phases = 4;  fused_kernel<<<2 * NCL, 384, SMEM_BYTES>>>(p);
  }
}
```

```cpp
#include <cuda_runtime.h>
#include <cuda_bf16.h>
#include <cuda.h>
#include <stdint.h>

namespace {

constexpr int SEQ = 2048, DM = 576, DC = 512, NH = 32;
constexpr int NCL = 66;
constexpr int NKB3 = 73;
constexpr uint32_t DESC_HI = 0x40000040u;

constexpr int SM_RING = 0;
constexpr int SM_BUF = 163840;
constexpr int SM_BAR = 229376;
constexpr int B_P1F = 0, B_P1E = 10, B_P2F = 20, B_P2E = 25, B_P3F = 30, B_P3E = 35, B_SF = 40, B_SE = 44, B_QF = 48, B_DONE = 52, B_FIN = 53, B_ORD = 54, B_LA = 58, B_LAD = 62, B_NUM = 63;
constexpr int SMEM_BYTES = SM_BAR + B_NUM * 8 + 1024;

constexpr int F_HEAD = 0;
constexpr int F_QKVA = 32;
constexpr int F_GATE = 64;
constexpr int F_DONE = 65;
constexpr int F_CTX = 96;
constexpr int F_NUM = 96 + 8 * 64;

struct Sched {
  uint8_t p1_slab[NCL];
  uint8_t p1_n[NCL];
  uint8_t p1_tile[NCL][18];
  uint8_t p2_n[NCL];
  uint8_t p2_item[NCL][10];
  uint8_t p3_tile[NCL];
  uint8_t p3_order[8][33];
};

struct Params {
  CUtensorMap map_a[2];
  CUtensorMap map_w[4];
  CUtensorMap map_o[2];
  CUtensorMap map_t[2];
  CUtensorMap map_out;
  const __nv_bfloat16* x;
  const __nv_bfloat16* gate_w;
  int zero;
  int phases;
  Sched s;
};

__device__ __align__(1024) uint8_t g_Q[NH * 32 * 16384];
__device__ __align__(1024) uint8_t g_KV[2 * NH * 16 * 32768];
__device__ __align__(1024) uint8_t g_ctx[32 * NKB3 * 8192];
constexpr int TP = SEQ + 16;
__device__ __align__(1024) uint32_t g_T[864 * TP];
__device__ float g_gate[SEQ];
__device__ int g_flags[F_NUM];

__device__ __forceinline__ void mbar_init(uint32_t b, int c) { asm volatile("mbarrier.init.shared::cta.b64 [%0], %1;" ::"r"(b), "r"(c)); }
__device__ __forceinline__ void mbar_expect(uint32_t b, int bytes) {
  asm volatile("mbarrier.arrive.expect_tx.shared::cta.b64 _, [%0], %1;" ::"r"(b), "r"(bytes) : "memory");
}
__device__ __forceinline__ void mbar_arrive(uint32_t b) { asm volatile("mbarrier.arrive.shared::cta.b64 _, [%0];" ::"r"(b) : "memory"); }
__device__ __forceinline__ void mbar_arrive_cl(uint32_t b, int cnt) {
  asm volatile("mbarrier.arrive.shared::cluster.b64 _, [%0], %1;" ::"r"(b), "r"(cnt) : "memory");
}
__device__ __forceinline__ void mbar_wait(uint32_t b, int par) {
  asm volatile(
      "{\n.reg .pred p;\n.reg .u32 c;\n"
      "mbarrier.try_wait.parity.shared::cta.b64 p, [%0], %1;\n@p bra DN;\nmov.u32 c, 0;\n"
      "LP:\nmbarrier.try_wait.parity.shared::cta.b64 p, [%0], %1;\n@p bra DN;\n"
      "add.u32 c, c, 1;\nsetp.lt.u32 p, c, 4000000;\n@p bra LP;\ntrap;\nDN:\n}" ::"r"(b), "r"(par) : "memory");
}
__device__ __forceinline__ uint32_t mapa(uint32_t a, uint32_t cta) {
  uint32_t r; asm("mapa.shared::cluster.u32 %0, %1, %2;" : "=r"(r) : "r"(a), "r"(cta)); return r;
}
__device__ __forceinline__ void bulk_load(uint32_t dst, const void* src, int bytes, uint32_t bar) {
  asm volatile("cp.async.bulk.shared::cluster.global.mbarrier::complete_tx::bytes [%0], [%1], %2, [%3];" ::"r"(dst), "l"(src), "r"(bytes), "r"(bar) : "memory");
}
__device__ __forceinline__ void bulk_load_mc(uint32_t dst, const void* src, int bytes, uint32_t bar) {
  asm volatile("cp.async.bulk.shared::cluster.global.mbarrier::complete_tx::bytes.multicast::cluster [%0], [%1], %2, [%3], %4;" ::"r"(dst), "l"(src), "r"(bytes), "r"(bar), "h"((uint16_t)3) : "memory");
}
__device__ __forceinline__ void bulk_store(void* dst, uint32_t src, int bytes) {
  asm volatile("cp.async.bulk.global.shared::cta.bulk_group [%0], [%1], %2;" ::"l"(dst), "r"(src), "r"(bytes) : "memory");
}
__device__ __forceinline__ void tma2d(uint32_t dst, const CUtensorMap* m, int c0, int c1, uint32_t bar) {
  asm volatile("cp.async.bulk.tensor.2d.shared::cluster.global.mbarrier::complete_tx::bytes [%0], [%1, {%3, %4}], [%2];" ::"r"(dst), "l"(m), "r"(bar), "r"(c0), "r"(c1) : "memory");
}
__device__ __forceinline__ void tma2d_mc(uint32_t dst, const CUtensorMap* m, int c0, int c1, uint32_t bar) {
  asm volatile("cp.async.bulk.tensor.2d.shared::cluster.global.mbarrier::complete_tx::bytes.multicast::cluster [%0], [%1, {%3, %4}], [%2], %5;" ::"r"(dst), "l"(m), "r"(bar), "r"(c0), "r"(c1), "h"((uint16_t)3) : "memory");
}
__device__ __forceinline__ void tma3d_mc(uint32_t dst, const CUtensorMap* m, int c0, int c1, int c2, uint32_t bar) {
  asm volatile("cp.async.bulk.tensor.3d.shared::cluster.global.mbarrier::complete_tx::bytes.multicast::cluster [%0], [%1, {%3, %4, %5}], [%2], %6;" ::"r"(dst), "l"(m), "r"(bar), "r"(c0), "r"(c1), "r"(c2), "h"((uint16_t)3) : "memory");
}
__device__ __forceinline__ void tma2d_store(const CUtensorMap* m, uint32_t src, int c0, int c1) {
  asm volatile("cp.async.bulk.tensor.2d.global.shared::cta.bulk_group [%0, {%2, %3}], [%1];" ::"l"(m), "r"(src), "r"(c0), "r"(c1) : "memory");
}
__device__ __forceinline__ void tma2d_prefetch(const CUtensorMap* m, int c0, int c1) {
  asm volatile("cp.async.bulk.prefetch.tensor.2d.L2.global [%0, {%1, %2}];" ::"l"(m), "r"(c0), "r"(c1) : "memory");
}
__device__ __forceinline__ void tma3d_elect(uint32_t dst, const CUtensorMap* m, int c0, int c2, uint32_t bar, int expect) {
  asm volatile("{\n.reg .pred p, q;\nelect.sync _|p, 0xffffffff;\nsetp.ne.and.s32 q, %5, 0, p;\n"
               "@q mbarrier.arrive.expect_tx.shared::cta.b64 _, [%2], %5;\n"
               "@p cp.async.bulk.tensor.3d.shared::cluster.global.mbarrier::complete_tx::bytes [%0], [%1, {%3, 0, %4}], [%2];\n}"
               ::"r"(dst), "l"(m), "r"(bar), "r"(c0), "r"(c2), "r"(expect) : "memory");
}
#define BULK_COMMIT() asm volatile("cp.async.bulk.commit_group;" ::: "memory")
#define BULK_WAIT(n) asm volatile("cp.async.bulk.wait_group %0;" ::"n"(n) : "memory")
#define BULK_WAIT_READ(n) asm volatile("cp.async.bulk.wait_group.read %0;" ::"n"(n) : "memory")
#define FENCE_ASYNC_SMEM() asm volatile("fence.proxy.async.shared::cta;" ::: "memory")
#define FENCE_ASYNC_ALL() asm volatile("fence.proxy.async;" ::: "memory")
#define WG_FENCE() asm volatile("wgmma.fence.sync.aligned;" ::: "memory")
#define WG_COMMIT() asm volatile("wgmma.commit_group.sync.aligned;" ::: "memory")
#define WG_WAIT(n) asm volatile("wgmma.wait_group.sync.aligned %0;" ::"n"(n) : "memory")
__device__ __forceinline__ void bar_sync(int id, int n) { asm volatile("bar.sync %0, %1;" ::"r"(id), "r"(n) : "memory"); }
__device__ __forceinline__ void bar_arrive(int id, int n) { asm volatile("bar.arrive %0, %1;" ::"r"(id), "r"(n) : "memory"); }
__device__ __forceinline__ void cluster_sync() {
  asm volatile("barrier.cluster.arrive.release;\nbarrier.cluster.wait.acquire;" ::: "memory");
}
template <int N> __device__ __forceinline__ void pin(float (&r)[N]) {
#pragma unroll
  for (int i = 0; i < N; i++) asm volatile("" : "+f"(r[i])::"memory");
}
template <int N> __device__ __forceinline__ void pin(uint32_t (&r)[N]) {
#pragma unroll
  for (int i = 0; i < N; i++) asm volatile("" : "+r"(r[i])::"memory");
}
__device__ __forceinline__ uint32_t pack_bf16(float lo, float hi) {
  uint32_t r; asm("cvt.rn.bf16x2.f32 %0, %1, %2;" : "=r"(r) : "f"(hi), "f"(lo)); return r;
}
__device__ __forceinline__ float ex2(float x) { float r; asm("ex2.approx.ftz.f32 %0, %1;" : "=f"(r) : "f"(x)); return r; }
__device__ __forceinline__ void ldsm4(uint32_t a, uint32_t& r0, uint32_t& r1, uint32_t& r2, uint32_t& r3) {
  asm volatile("ldmatrix.sync.aligned.m8n8.x4.shared.b16 {%0,%1,%2,%3}, [%4];" : "=r"(r0), "=r"(r1), "=r"(r2), "=r"(r3) : "r"(a) : "memory");
}
__device__ __forceinline__ void stsm4(uint32_t a, uint32_t r0, uint32_t r1, uint32_t r2, uint32_t r3) {
  asm volatile("stmatrix.sync.aligned.m8n8.x4.shared.b16 [%0], {%1,%2,%3,%4};" ::"r"(a), "r"(r0), "r"(r1), "r"(r2), "r"(r3) : "memory");
}
__device__ __forceinline__ void flag_add(int idx, int v) {
  asm volatile("red.release.gpu.global.add.s32 [%0], %1;" ::"l"(g_flags + idx), "r"(v) : "memory");
}
__device__ __forceinline__ void flag_add_rx(int idx, int v) {
  asm volatile("red.relaxed.gpu.global.add.s32 [%0], %1;" ::"l"(g_flags + idx), "r"(v) : "memory");
}
template <bool ACQ> __device__ __forceinline__ void flag_wait(int idx, int target) {
  int n = 0;
  while (true) {
    int v;
    if (ACQ) asm volatile("ld.acquire.gpu.global.s32 %0, [%1];" : "=r"(v) : "l"(g_flags + idx) : "memory");
    else asm volatile("ld.relaxed.gpu.global.s32 %0, [%1];" : "=r"(v) : "l"(g_flags + idx) : "memory");
    if (v >= target) break;
    if (++n > 20000000) __trap();
    __nanosleep(64);
  }
}
__device__ __forceinline__ void flag_wait_warp(int idx, int target) {
  int n = 0;
  while (true) {
    int v;
    asm volatile("ld.acquire.gpu.global.s32 %0, [%1];" : "=r"(v) : "l"(g_flags + idx) : "memory");
    if (__all_sync(0xffffffffu, v >= target)) break;
    if (++n > 20000000) __trap();
    __nanosleep(100);
  }
}
__device__ __forceinline__ uint32_t desc_lo(uint32_t addr, uint32_t lbo) { return ((addr & 0x3FFFFu) >> 4) | ((lbo >> 4) << 16); }
#define PROF(role, i)
#define PROFX(cond, i)
#define PROFB(i)

template <int TB, int TA = 0> __device__ __forceinline__ void wgmma_ss64(float (&d)[32], uint32_t alo, uint32_t blo, int sd) {
  asm volatile("{\n.reg .pred p;\n.reg .b64 da, db;\n"
    "setp.ne.b32 p, %34, 0;\nmov.b64 da, {%32, %36};\nmov.b64 db, {%33, %36};\n"
    "wgmma.mma_async.sync.aligned.m64n64k16.f32.bf16.bf16 "
    "{%0,%1,%2,%3,%4,%5,%6,%7,%8,%9,%10,%11,%12,%13,%14,%15,%16,%17,%18,%19,%20,%21,%22,%23,"
    "%24,%25,%26,%27,%28,%29,%30,%31}, "
    "da, db, p, 1, 1, %37, %35;\n}\n"
    : "+f"(d[0]),"+f"(d[1]),"+f"(d[2]),"+f"(d[3]),"+f"(d[4]),"+f"(d[5]),"+f"(d[6]),"+f"(d[7]),"+f"(d[8]),"+f"(d[9]),"+f"(d[10]),"+f"(d[11]),
      "+f"(d[12]),"+f"(d[13]),"+f"(d[14]),"+f"(d[15]),"+f"(d[16]),"+f"(d[17]),"+f"(d[18]),"+f"(d[19]),"+f"(d[20]),"+f"(d[21]),"+f"(d[22]),"+f"(d[23]),
      "+f"(d[24]),"+f"(d[25]),"+f"(d[26]),"+f"(d[27]),"+f"(d[28]),"+f"(d[29]),"+f"(d[30]),"+f"(d[31])
    : "r"(alo), "r"(blo), "r"(sd), "n"(TB), "r"(DESC_HI), "n"(TA));
}
template <int TB, int TA = 0> __device__ __forceinline__ void wgmma_ss128(float (&d)[64], uint32_t alo, uint32_t blo, int sd) {
  asm volatile("{\n.reg .pred p;\n.reg .b64 da, db;\n"
    "setp.ne.b32 p, %66, 0;\nmov.b64 da, {%64, %68};\nmov.b64 db, {%65, %68};\n"
    "wgmma.mma_async.sync.aligned.m64n128k16.f32.bf16.bf16 "
    "{%0,%1,%2,%3,%4,%5,%6,%7,%8,%9,%10,%11,%12,%13,%14,%15,%16,%17,%18,%19,%20,%21,%22,%23,"
    "%24,%25,%26,%27,%28,%29,%30,%31,%32,%33,%34,%35,%36,%37,%38,%39,%40,%41,%42,%43,%44,%45,%46,%47,"
    "%48,%49,%50,%51,%52,%53,%54,%55,%56,%57,%58,%59,%60,%61,%62,%63}, "
    "da, db, p, 1, 1, %69, %67;\n}\n"
    : "+f"(d[0]),"+f"(d[1]),"+f"(d[2]),"+f"(d[3]),"+f"(d[4]),"+f"(d[5]),"+f"(d[6]),"+f"(d[7]),"+f"(d[8]),"+f"(d[9]),"+f"(d[10]),"+f"(d[11]),
      "+f"(d[12]),"+f"(d[13]),"+f"(d[14]),"+f"(d[15]),"+f"(d[16]),"+f"(d[17]),"+f"(d[18]),"+f"(d[19]),"+f"(d[20]),"+f"(d[21]),"+f"(d[22]),"+f"(d[23]),
      "+f"(d[24]),"+f"(d[25]),"+f"(d[26]),"+f"(d[27]),"+f"(d[28]),"+f"(d[29]),"+f"(d[30]),"+f"(d[31]),"+f"(d[32]),"+f"(d[33]),"+f"(d[34]),"+f"(d[35]),
      "+f"(d[36]),"+f"(d[37]),"+f"(d[38]),"+f"(d[39]),"+f"(d[40]),"+f"(d[41]),"+f"(d[42]),"+f"(d[43]),"+f"(d[44]),"+f"(d[45]),"+f"(d[46]),"+f"(d[47]),
      "+f"(d[48]),"+f"(d[49]),"+f"(d[50]),"+f"(d[51]),"+f"(d[52]),"+f"(d[53]),"+f"(d[54]),"+f"(d[55]),"+f"(d[56]),"+f"(d[57]),"+f"(d[58]),"+f"(d[59]),
      "+f"(d[60]),"+f"(d[61]),"+f"(d[62]),"+f"(d[63])
    : "r"(alo), "r"(blo), "r"(sd), "n"(TB), "r"(DESC_HI), "n"(TA));
}
template <int TB> __device__ __forceinline__ void wgmma_rs128(float (&d)[64], uint32_t a0, uint32_t a1, uint32_t a2, uint32_t a3, uint32_t blo, int sd) {
  asm volatile("{\n.reg .pred p;\n.reg .b64 db;\n"
    "setp.ne.b32 p, %69, 0;\nmov.b64 db, {%68, %71};\n"
    "wgmma.mma_async.sync.aligned.m64n128k16.f32.bf16.bf16 "
    "{%0,%1,%2,%3,%4,%5,%6,%7,%8,%9,%10,%11,%12,%13,%14,%15,%16,%17,%18,%19,%20,%21,%22,%23,"
    "%24,%25,%26,%27,%28,%29,%30,%31,%32,%33,%34,%35,%36,%37,%38,%39,%40,%41,%42,%43,%44,%45,%46,%47,"
    "%48,%49,%50,%51,%52,%53,%54,%55,%56,%57,%58,%59,%60,%61,%62,%63}, "
    "{%64,%65,%66,%67}, db, p, 1, 1, %70;\n}\n"
    : "+f"(d[0]),"+f"(d[1]),"+f"(d[2]),"+f"(d[3]),"+f"(d[4]),"+f"(d[5]),"+f"(d[6]),"+f"(d[7]),"+f"(d[8]),"+f"(d[9]),"+f"(d[10]),"+f"(d[11]),
      "+f"(d[12]),"+f"(d[13]),"+f"(d[14]),"+f"(d[15]),"+f"(d[16]),"+f"(d[17]),"+f"(d[18]),"+f"(d[19]),"+f"(d[20]),"+f"(d[21]),"+f"(d[22]),"+f"(d[23]),
      "+f"(d[24]),"+f"(d[25]),"+f"(d[26]),"+f"(d[27]),"+f"(d[28]),"+f"(d[29]),"+f"(d[30]),"+f"(d[31]),"+f"(d[32]),"+f"(d[33]),"+f"(d[34]),"+f"(d[35]),
      "+f"(d[36]),"+f"(d[37]),"+f"(d[38]),"+f"(d[39]),"+f"(d[40]),"+f"(d[41]),"+f"(d[42]),"+f"(d[43]),"+f"(d[44]),"+f"(d[45]),"+f"(d[46]),"+f"(d[47]),
      "+f"(d[48]),"+f"(d[49]),"+f"(d[50]),"+f"(d[51]),"+f"(d[52]),"+f"(d[53]),"+f"(d[54]),"+f"(d[55]),"+f"(d[56]),"+f"(d[57]),"+f"(d[58]),"+f"(d[59]),
      "+f"(d[60]),"+f"(d[61]),"+f"(d[62]),"+f"(d[63])
    : "r"(a0), "r"(a1), "r"(a2), "r"(a3), "r"(blo), "r"(sd), "n"(TB), "r"(DESC_HI));
}
template <int TB, int TA = 0> __device__ __forceinline__ void wgmma_ss192(float (&d)[96], uint32_t alo, uint32_t blo, int sd) {
  asm volatile("{\n.reg .pred p;\n.reg .b64 da, db;\n"
    "setp.ne.b32 p, %98, 0;\nmov.b64 da, {%96, %100};\nmov.b64 db, {%97, %100};\n"
    "wgmma.mma_async.sync.aligned.m64n192k16.f32.bf16.bf16 "
    "{%0,%1,%2,%3,%4,%5,%6,%7,%8,%9,%10,%11,%12,%13,%14,%15,%16,%17,%18,%19,%20,%21,%22,%23,"
    "%24,%25,%26,%27,%28,%29,%30,%31,%32,%33,%34,%35,%36,%37,%38,%39,%40,%41,%42,%43,%44,%45,%46,%47,"
    "%48,%49,%50,%51,%52,%53,%54,%55,%56,%57,%58,%59,%60,%61,%62,%63,%64,%65,%66,%67,%68,%69,%70,%71,"
    "%72,%73,%74,%75,%76,%77,%78,%79,%80,%81,%82,%83,%84,%85,%86,%87,%88,%89,%90,%91,%92,%93,%94,%95}, "
    "da, db, p, 1, 1, %101, %99;\n}\n"
    : "+f"(d[0]),"+f"(d[1]),"+f"(d[2]),"+f"(d[3]),"+f"(d[4]),"+f"(d[5]),"+f"(d[6]),"+f"(d[7]),"+f"(d[8]),"+f"(d[9]),"+f"(d[10]),"+f"(d[11]),
      "+f"(d[12]),"+f"(d[13]),"+f"(d[14]),"+f"(d[15]),"+f"(d[16]),"+f"(d[17]),"+f"(d[18]),"+f"(d[19]),"+f"(d[20]),"+f"(d[21]),"+f"(d[22]),"+f"(d[23]),
      "+f"(d[24]),"+f"(d[25]),"+f"(d[26]),"+f"(d[27]),"+f"(d[28]),"+f"(d[29]),"+f"(d[30]),"+f"(d[31]),"+f"(d[32]),"+f"(d[33]),"+f"(d[34]),"+f"(d[35]),
      "+f"(d[36]),"+f"(d[37]),"+f"(d[38]),"+f"(d[39]),"+f"(d[40]),"+f"(d[41]),"+f"(d[42]),"+f"(d[43]),"+f"(d[44]),"+f"(d[45]),"+f"(d[46]),"+f"(d[47]),
      "+f"(d[48]),"+f"(d[49]),"+f"(d[50]),"+f"(d[51]),"+f"(d[52]),"+f"(d[53]),"+f"(d[54]),"+f"(d[55]),"+f"(d[56]),"+f"(d[57]),"+f"(d[58]),"+f"(d[59]),
      "+f"(d[60]),"+f"(d[61]),"+f"(d[62]),"+f"(d[63]),"+f"(d[64]),"+f"(d[65]),"+f"(d[66]),"+f"(d[67]),"+f"(d[68]),"+f"(d[69]),"+f"(d[70]),"+f"(d[71]),
      "+f"(d[72]),"+f"(d[73]),"+f"(d[74]),"+f"(d[75]),"+f"(d[76]),"+f"(d[77]),"+f"(d[78]),"+f"(d[79]),"+f"(d[80]),"+f"(d[81]),"+f"(d[82]),"+f"(d[83]),
      "+f"(d[84]),"+f"(d[85]),"+f"(d[86]),"+f"(d[87]),"+f"(d[88]),"+f"(d[89]),"+f"(d[90]),"+f"(d[91]),"+f"(d[92]),"+f"(d[93]),"+f"(d[94]),"+f"(d[95])
    : "r"(alo), "r"(blo), "r"(sd), "n"(TB), "r"(DESC_HI), "n"(TA));
}

struct Ctx {
  uint32_t sm;
  uint32_t bar;
  uint32_t rbar;
  int cl, rank, wg, warp, lane;
};
__device__ __forceinline__ void release(const Ctx& c, int b, int cnt = 1) {
  if (c.lane < 2) mbar_arrive_cl(c.rbar + b * 8, cnt);
}
constexpr int PF1 = 1;
constexpr int ORDER = 1;

__device__ __forceinline__ void stage_tile(const float (&a)[64], uint32_t buf, const Ctx& c, float s0, float s1) {
  const int row = (c.lane & 7) + ((c.lane >> 3) & 1) * 8;
  const uint32_t base = buf + (c.warp * 16 + row) * 128 + (((c.lane >> 4) ^ (row & 7)) << 4);
#pragma unroll
  for (int i = 0; i < 8; i++)
    stsm4((base ^ ((i & 3) << 5)) + (i >> 2) * 8192, pack_bf16(a[8 * i] * s0, a[8 * i + 1] * s0), pack_bf16(a[8 * i + 2] * s1, a[8 * i + 3] * s1),
          pack_bf16(a[8 * i + 4] * s0, a[8 * i + 5] * s0), pack_bf16(a[8 * i + 6] * s1, a[8 * i + 7] * s1));
}

__device__ __forceinline__ void p1_consumer(const Params& p, const Ctx& c) {
  const int n = p.s.p1_n[c.cl];
  const int type = p.s.p1_slab[c.cl] >> 3, grp = p.s.p1_slab[c.cl] & 7;
  uint32_t A[128];
  {
    const int row = (c.lane & 7) + ((c.lane >> 3) & 1) * 8;
    const uint32_t base = c.sm + SM_RING + (c.wg * 64 + c.warp * 16 + row) * 128 + (((c.lane >> 4) ^ (row & 7)) << 4);
#pragma unroll
    for (int kb = 0; kb < 8; kb++) {
      mbar_wait(c.bar + (B_P1F + kb) * 8, 0);
#pragma unroll
      for (int kk = 0; kk < 4; kk++) ldsm4((base ^ (kk << 5)) + kb * 16384, A[kb * 16 + kk * 4], A[kb * 16 + kk * 4 + 1], A[kb * 16 + kk * 4 + 2], A[kb * 16 + kk * 4 + 3]);
      __syncwarp();
      release(c, B_P1E + kb);
    }
  }
  PROF(c.wg, 1);
  int slot = 8, par = 0;
  const uint32_t bdesc = desc_lo(c.sm + SM_RING, 8192), adesc = desc_lo(c.sm + SM_BUF + 32768 + c.wg * 8192, 16);
  float acc[64];
  for (int t = 0; t < n; t++) {
    const int tile = p.s.p1_tile[c.cl][t];
    bar_sync(ORDER + c.wg, 256);
    int prev1 = -1, prev2 = -1;
    if (type) {
      mbar_wait(c.bar + (B_P1F + slot) * 8, par);
      WG_FENCE();
#pragma unroll
      for (int kk = 0; kk < 4; kk++) wgmma_ss128<1>(acc, adesc + kk * 2, bdesc + slot * 1024 + kk * 128, kk != 0);
      WG_COMMIT();
      prev1 = slot;
      if (++slot == 10) { slot = 0; par ^= 1; }
    }
#pragma unroll
    for (int kb = 0; kb < 8; kb++) {
      mbar_wait(c.bar + (B_P1F + slot) * 8, par);
      WG_FENCE();
      const uint32_t d = bdesc + slot * 1024;
#pragma unroll
      for (int kk = 0; kk < 4; kk++)
        wgmma_rs128<1>(acc, A[kb * 16 + kk * 4], A[kb * 16 + kk * 4 + 1], A[kb * 16 + kk * 4 + 2], A[kb * 16 + kk * 4 + 3], d + kk * 128, (kb | kk) != 0 ? 1 : type);
      WG_COMMIT();
      if (kb == 7) {
        if (t + 1 < n || c.wg == 0) bar_arrive(ORDER + (c.wg ^ 1), 256);
        else if (c.lane == 0) mbar_arrive(c.bar + B_P2F * 8);
      }
      if (kb > 0) { WG_WAIT(2); if (kb > 1 || prev2 >= 0) release(c, B_P1E + prev2); }
      prev2 = prev1; prev1 = slot;
      if (++slot == 10) { slot = 0; par ^= 1; }
    }
    WG_WAIT(1);
    release(c, B_P1E + prev2);
    WG_WAIT(0);
    pin(acc);
    release(c, B_P1E + prev1);
    const int b = c.wg * 2 + 1;
    mbar_wait(c.bar + (B_SE + b) * 8, (t & 1) ^ 1);
    if (type && tile >= 32) {
      const int row = grp * 256 + c.rank * 128 + c.wg * 64 + c.warp * 16 + (c.lane >> 2);
      uint32_t* dst = g_T + ((tile - 32) * 64 + (c.lane & 3)) * TP + (row & 1) * (TP / 2) + 8 + (row >> 1);
#pragma unroll
      for (int i = 0; i < 16; i++) {
        if (i < 8 || tile < 45) {
          dst[i * 4 * TP] = pack_bf16(acc[4 * i], acc[4 * i + 1]);
          dst[i * 4 * TP + 4] = pack_bf16(acc[4 * i + 2], acc[4 * i + 3]);
        }
      }
    } else {
      stage_tile(acc, c.sm + SM_BUF + b * 16384, c, 1.f, 1.f);
      FENCE_ASYNC_SMEM();
    }
    __syncwarp();
    if (c.lane == 0) mbar_arrive(c.bar + (B_SF + b) * 8);
    PROF(c.wg, 2 + t);
  }
}

__device__ __forceinline__ void p1_producer(const Params& p, const Ctx& c) {
  const int n = p.s.p1_n[c.cl];
  const int type = p.s.p1_slab[c.cl] >> 3, grp = p.s.p1_slab[c.cl] & 7;
  for (int kb = 0; kb < 8; kb++) {
    mbar_expect(c.bar + (B_P1F + kb) * 8, kb == 7 && type ? 32768 : 16384);
    tma2d(c.sm + SM_RING + kb * 16384, &p.map_a[type], kb * 64, grp * 256 + c.rank * 128, c.bar + (B_P1F + kb) * 8);
  }
  if (type) tma2d(c.sm + SM_BUF + 32768, &p.map_a[1], 512, grp * 256 + c.rank * 128, c.bar + (B_P1F + 7) * 8);
  int slot = 8, par = 1;
  for (int t = 0; t < n; t++) {
    const int tile = p.s.p1_tile[c.cl][t];
    const CUtensorMap* m = &p.map_w[type * 2 + (tile >> 5)];
    const int n0 = (tile & 31) * 128 + c.rank * 64;
    const int ptile = p.s.p1_tile[c.cl][t + PF1 < n ? t + PF1 : t];
    const CUtensorMap* pm = &p.map_w[type * 2 + (ptile >> 5)];
    for (int kb = -type; kb < 8; kb++) {
      if (t + PF1 < n) tma2d_prefetch(pm, (ptile & 31) * 128 + c.rank * 64, kb < 0 ? 512 : kb * 64);
      mbar_wait(c.bar + (B_P1E + slot) * 8, par);
      mbar_expect(c.bar + (B_P1F + slot) * 8, 16384);
      tma2d_mc(c.sm + SM_RING + slot * 16384 + c.rank * 8192, m, n0, kb < 0 ? 512 : kb * 64, c.bar + (B_P1F + slot) * 8);
      if (++slot == 10) { slot = 0; par ^= 1; }
    }
  }
}

__device__ __forceinline__ void p1_storer(const Params& p, const Ctx& c) {
  const int n = p.s.p1_n[c.cl];
  const int type = p.s.p1_slab[c.cl] >> 3, grp = p.s.p1_slab[c.cl] & 7;
  int pf = -1;
  for (int i = 0; i < 2 * n; i++) {
    const int t = i >> 1, w = i & 1, b = w * 2 + 1;
    const int tile = p.s.p1_tile[c.cl][t];
    mbar_wait(c.bar + (B_SF + b) * 8, t & 1);
    const uint32_t src = c.sm + SM_BUF + b * 16384;
    int f = F_HEAD + (tile & 31);
    if (type == 0) {
      uint8_t* dst = g_KV + (size_t)(tile * 16 + grp * 2 + c.rank) * 32768 + w * 8192;
      bulk_store(dst, src, 8192);
      bulk_store(dst + 16384, src + 8192, 8192);
    } else if (tile < 32) {
      bulk_store(g_Q + (size_t)(tile * 32 + grp * 4 + c.rank * 2 + w) * 16384, src, 16384);
    } else {
      f = F_QKVA + grp * 4 + ((0xE4390900u >> (2 * (tile - 30))) & 3);
    }
    BULK_COMMIT();
    BULK_WAIT_READ(0);
    mbar_arrive(c.bar + (B_SE + b) * 8);
    if (pf >= 0) {
      BULK_WAIT(1);
      flag_add_rx(pf, 1);
    }
    pf = f;
    if (f >= F_QKVA) { flag_add(f, 1); pf = -1; }
  }
  BULK_WAIT(0);
  if (pf >= 0) flag_add_rx(pf, 1);
}

__device__ __forceinline__ int p2_buf(int w, int i) { return w * 2 + ((i ^ w ^ 1) & 1); }
__device__ __forceinline__ int p2_blk(int rank, int w, int i) { return ((i ^ w) & 1) == 0 ? 3 - rank : rank; }

constexpr float SM_SCALE = 0.08838834764831845f * 1.4426950408889634f;
constexpr float SM_LIMIT = 1.0995116e12f;

template <int N>
__device__ __forceinline__ void row_max(const float (&s)[N], float& m0, float& m1) {
  float a0 = fmaxf(s[0], s[1]), a1 = fmaxf(s[2], s[3]);
#pragma unroll
  for (int i = 1; i < N / 4; i++) {
    m0 = fmaxf(m0, s[4 * i]); a0 = fmaxf(a0, s[4 * i + 1]);
    m1 = fmaxf(m1, s[4 * i + 2]); a1 = fmaxf(a1, s[4 * i + 3]);
  }
  m0 = fmaxf(m0, a0); m1 = fmaxf(m1, a1);
  m0 = fmaxf(m0, __shfl_xor_sync(0xffffffffu, m0, 1));
  m1 = fmaxf(m1, __shfl_xor_sync(0xffffffffu, m1, 1));
  m0 = fmaxf(m0, __shfl_xor_sync(0xffffffffu, m0, 2));
  m1 = fmaxf(m1, __shfl_xor_sync(0xffffffffu, m1, 2));
}
template <int N>
__device__ __forceinline__ void row_exp(const float (&s)[N], uint32_t (&P)[32], float m0, float m1, float& t0, float& t1) {
  const float b0 = -m0 * SM_SCALE, b1 = -m1 * SM_SCALE;
  float u0 = 0.f, u1 = 0.f;
  t0 = t1 = 0.f;
#pragma unroll
  for (int i = 0; i < N / 4; i++) {
    const float e0 = ex2(fmaf(s[4 * i], SM_SCALE, b0)), e1 = ex2(fmaf(s[4 * i + 1], SM_SCALE, b0));
    const float e2 = ex2(fmaf(s[4 * i + 2], SM_SCALE, b1)), e3 = ex2(fmaf(s[4 * i + 3], SM_SCALE, b1));
    t0 += e0; u0 += e1; t1 += e2; u1 += e3;
    P[2 * i] = pack_bf16(e0, e1);
    P[2 * i + 1] = pack_bf16(e2, e3);
  }
#pragma unroll
  for (int i = N / 2; i < 32; i++) P[i] = 0;
  pin(P);
  t0 += u0; t1 += u1;
}
template <int N>
__device__ __forceinline__ void order_after(const uint32_t (&P)[32], int zero, uint32_t addr) {
  if (zero) {
#pragma unroll
    for (int i = 0; i < N / 8; i++)
      asm volatile("st.shared.v4.b32 [%0], {%1, %2, %3, %4};" ::"r"(addr + 16 * i), "r"(P[4 * i]), "r"(P[4 * i + 1]), "r"(P[4 * i + 2]), "r"(P[4 * i + 3]) : "memory");
  }
}
template <int N>
__device__ __forceinline__ void causal_mask(float (&s)[N], int thr) {
#pragma unroll
  for (int i = 0; i < 8; i++) {
    if (8 * i > thr) s[N - 32 + 4 * i] = -INFINITY;
    if (8 * i + 1 > thr) s[N - 32 + 4 * i + 1] = -INFINITY;
    if (8 * i - 8 > thr) s[N - 32 + 4 * i + 2] = -INFINITY;
    if (8 * i - 7 > thr) s[N - 32 + 4 * i + 3] = -INFINITY;
  }
}
__device__ __forceinline__ void issue_qk(float (&s)[32], uint32_t qd, uint32_t kd) {
  WG_FENCE();
#pragma unroll
  for (int kk = 0; kk < 8; kk++) wgmma_ss64<0>(s, qd + (kk >> 2) * 512 + (kk & 3) * 2, kd + (kk >> 2) * 1024 + (kk & 3) * 2, kk != 0);
  WG_COMMIT();
}
__device__ __forceinline__ void issue_qk(float (&s)[64], uint32_t qd, uint32_t kd) {
  WG_FENCE();
#pragma unroll
  for (int kk = 0; kk < 8; kk++) wgmma_ss128<0>(s, qd + (kk >> 2) * 512 + (kk & 3) * 2, kd + (kk >> 2) * 1024 + (kk & 3) * 2, kk != 0);
  WG_COMMIT();
}
template <int NK>
__device__ __forceinline__ void issue_pv(float (&o)[64], const uint32_t (&P)[32], uint32_t vd, int acc) {
  WG_FENCE();
#pragma unroll
  for (int kk = 0; kk < NK; kk++) wgmma_rs128<1>(o, P[4 * kk], P[4 * kk + 1], P[4 * kk + 2], P[4 * kk + 3], vd + kk * 128, kk != 0 ? 1 : acc);
  WG_COMMIT();
}
__device__ __forceinline__ void p2_epilogue(const float (&o)[64], float s0, float s1, const Ctx& c, int b) {
  stage_tile(o, c.sm + SM_BUF + b * 16384, c, s0, s1);
  FENCE_ASYNC_SMEM();
  __syncwarp();
  if (c.lane == 0) mbar_arrive(c.bar + (B_SF + b) * 8);
}

struct P2State {
  float m0, m1, l0, l1;
  float e0, e1;
  int row0;
  int ks;
  int wi, ai;
  uint32_t wb, ab;
  uint32_t qd;
};
__device__ __forceinline__ int wrap5(int q) { return q >= 5 ? q - 5 : q; }
__device__ __forceinline__ void turn_wait(uint32_t ring, int i) { mbar_wait(ring + (i & 3) * 8, (i >> 2) & 1); }
__device__ __forceinline__ void turn_pass(const Ctx& c, uint32_t ring, int i) { if (c.lane == 0) mbar_arrive(ring + (i & 3) * 8); }
__device__ __forceinline__ void p2_scales(P2State& z, const Ctx& c) {
  const float* g = g_gate + z.row0 + c.warp * 16 + (c.lane >> 2);
  const float g0 = __ldcg(g), g1 = __ldcg(g + 8);
  float l0 = z.l0, l1 = z.l1;
  l0 += __shfl_xor_sync(0xffffffffu, l0, 1);
  l1 += __shfl_xor_sync(0xffffffffu, l1, 1);
  l0 += __shfl_xor_sync(0xffffffffu, l0, 2);
  l1 += __shfl_xor_sync(0xffffffffu, l1, 2);
  z.e0 = __fdividef(1.f - g0, l0); z.e1 = __fdividef(1.f - g1, l1);
}
template <int N, bool PV>
__device__ __forceinline__ void p2_first(const Params& p, const Ctx& c, P2State& z, float (&o)[64], uint32_t (&Pc)[32], uint32_t (&Pn)[32],
                                         int ks, int vs, int cnt, int acc, int row0) {
  float s[N] = {};
  issue_qk(s, z.qd, desc_lo(c.sm + SM_RING, 16) + ks * 2048);
  if (PV) issue_pv<8>(o, Pc, desc_lo(c.sm + SM_RING, 16384) + vs * 2048, acc);
  turn_pass(c, z.ab, z.ai++);
  if (PV) WG_WAIT(1); else WG_WAIT(0);
  pin(s);
  release(c, B_P2E + ks, cnt);
  if (PV) p2_scales(z, c);
  z.row0 = row0;
  causal_mask(s, c.warp * 16 + (c.lane >> 2) - 2 * (c.lane & 3));
  z.m0 = z.m1 = -INFINITY;
  row_max(s, z.m0, z.m1);
  row_exp(s, Pn, z.m0, z.m1, z.l0, z.l1);
  if (PV) {
    order_after<N>(Pn, p.zero, c.sm);
    WG_WAIT(0);
    pin(o);
    release(c, B_P2E + vs, 1);
  }
}

template <bool SECOND>
__device__ __forceinline__ void p2_turn(const Ctx& c, P2State& z, float (&o)[64], uint32_t (&Pc)[32], uint32_t (&Pn)[32],
                                        int eb = -1, bool half = false, int vcnt = 1) {
  float s[64] = {};
  const int ks = z.ks, vs = wrap5(ks + 1);
  turn_wait(z.wb, z.wi++);
  issue_qk(s, z.qd, desc_lo(c.sm + SM_RING, 16) + ks * 2048);
  const uint32_t vd = desc_lo(c.sm + SM_RING, 16384) + vs * 2048;
  if (SECOND) {
    if (eb >= 0) p2_epilogue(o, z.e0, z.e1, c, eb);
    if (half) issue_pv<4>(o, Pc, vd, 0); else issue_pv<8>(o, Pc, vd, 0);
  } else {
    issue_pv<8>(o, Pc, vd, 1);
  }
  turn_pass(c, z.ab, z.ai++);
  z.ks = wrap5(ks + 2);
  WG_WAIT(1);
  pin(s);
  release(c, B_P2E + ks, 1);
  float t0, t1, a0 = 1.f, a1 = 1.f;
  row_exp(s, Pn, z.m0, z.m1, t0, t1);
  const bool redo = __any_sync(0xffffffffu, !(t0 + t1 <= SM_LIMIT));
  if (__builtin_expect(redo, 0)) {
    float n0 = z.m0, n1 = z.m1;
    row_max(s, n0, n1);
    a0 = ex2((z.m0 - n0) * SM_SCALE); a1 = ex2((z.m1 - n1) * SM_SCALE);
    z.m0 = n0; z.m1 = n1;
    z.l0 *= a0; z.l1 *= a1;
    row_exp(s, Pn, z.m0, z.m1, t0, t1);
  }
  WG_WAIT(0);
  pin(o);
  release(c, B_P2E + vs, vcnt);
  if (__builtin_expect(redo, 0)) {
#pragma unroll
    for (int i = 0; i < 16; i++) { o[4 * i] *= a0; o[4 * i + 1] *= a0; o[4 * i + 2] *= a1; o[4 * i + 3] *= a1; }
  }
  z.l0 += t0; z.l1 += t1;
}
__device__ __forceinline__ void copy_p(uint32_t (&d)[32], const uint32_t (&s)[32], int zero) {
#pragma unroll
  for (int i = 0; i < 32; i++) asm volatile("add.s32 %0, %1, %2;" : "=r"(d[i]) : "r"(s[i]), "r"(zero));
}

__device__ __forceinline__ void p2_consumer(const Params& p, const Ctx& c, int rot) {
  const int nit = p.s.p2_n[c.cl];
  const uint32_t fring = c.bar + B_P2F * 8, oring = c.bar + B_ORD * 8;
  float o[64] = {};
  uint32_t Pa[32] = {}, Pb[32] = {};
  P2State z;
  z.e0 = z.e1 = z.l0 = z.l1 = 0.f; z.row0 = 0; z.ks = rot;
  int acc = 0, n = 0;
  for (int it = 0; it < nit; it++) {
    const int j = p.s.p2_item[c.cl][it] & 7, blk = p2_blk(c.rank, c.wg, it), row0 = (j * 4 + blk) * 64;
    const int lng = ((it ^ c.wg) & 1) ^ 1;
    z.qd = desc_lo(c.sm + SM_BUF, 16) + p2_buf(c.wg, it) * 1024;
    if (lng) { z.wb = oring; z.wi = n - it; z.ab = fring; z.ai = n + 1; }
    else { z.wb = fring; z.wi = n + 2; z.ab = oring; z.ai = n - it; }
    mbar_wait(c.bar + (B_QF + p2_buf(c.wg, it)) * 8, (it >> 1) & 1);
    turn_wait(fring, n + 1 - lng);
    if (it == 0) {
      const int ks = wrap5(rot + c.wg);
      if (blk & 1) p2_first<64, false>(p, c, z, o, Pa, Pb, ks, 0, 1 + lng, 0, row0);
      else p2_first<32, false>(p, c, z, o, Pa, Pb, ks, 0, 1 + lng, 0, row0);
      z.ks = wrap5(rot + 1 + 2 * c.wg);
    } else {
      const int vs = wrap5(z.ks + 1), ks = lng ? z.ks : wrap5(z.ks + 2);
      if (blk & 1) p2_first<64, true>(p, c, z, o, Pa, Pb, ks, vs, 1 + lng, acc, row0);
      else p2_first<32, true>(p, c, z, o, Pa, Pb, ks, vs, 1 + lng, acc, row0);
      z.ks = wrap5(ks + 2);
    }
    PROF(c.wg, 24 + it);
    n += 2 * j + 2;
    int left = 2 * j + lng;
    acc = left != 0;
    if (left == 0) { copy_p(Pa, Pb, p.zero); continue; }
    p2_turn<true>(c, z, o, Pb, Pa, it > 0 ? p2_buf(c.wg, it - 1) : -1, !(blk & 1), 1 + lng);
    while (--left > 0) {
      p2_turn<false>(c, z, o, Pa, Pb);
      if (--left == 0) { copy_p(Pa, Pb, p.zero); break; }
      p2_turn<false>(c, z, o, Pb, Pa);
    }
  }
  {
    if (!acc && nit > 1) p2_epilogue(o, z.e0, z.e1, c, p2_buf(c.wg, nit));
    turn_wait(z.wb, z.wi);
    issue_pv<8>(o, Pa, desc_lo(c.sm + SM_RING, 16384) + z.ks * 2048, acc);
    if (((nit - 1) ^ c.wg) & 1) turn_pass(c, z.ab, z.ai);
    p2_scales(z, c);
    WG_WAIT(0);
    pin(o);
    p2_epilogue(o, z.e0, z.e1, c, p2_buf(c.wg, nit - 1));
    PROF(c.wg, 24 + nit);
  }
}

__device__ __forceinline__ void p2_load_q(const Params& p, const Ctx& c, int it, int w) {
  const int item = p.s.p2_item[c.cl][it], h = item >> 3, j = item & 7, b = p2_buf(w, it);
  mbar_expect(c.bar + (B_QF + b) * 8, 16384);
  bulk_load(c.sm + SM_BUF + b * 16384, g_Q + (size_t)(h * 32 + j * 4 + p2_blk(c.rank, w, it)) * 16384, 16384, c.bar + (B_QF + b) * 8);
}
__device__ __forceinline__ void p2_producer(const Params& p, const Ctx& c, int u1, int rot) {
  const int nit = p.s.p2_n[c.cl];
  int slot = rot, cnt = 0, par = 1, n = 0;
  const uint8_t* pv = nullptr;
  auto load = [&](const uint8_t* src, int expect) {
    if (cnt < 5) {
      if (u1) {
        mbar_wait(c.bar + (B_P1E + 2 * slot) * 8, ((u1 - 1 - 2 * slot) / 10) & 1);
        mbar_wait(c.bar + (B_P1E + 2 * slot + 1) * 8, ((u1 - 2 - 2 * slot) / 10) & 1);
        if (cnt == 0) p2_load_q(p, c, 0, 1);
      }
      cnt++;
    } else {
      if (slot == rot) par ^= 1;
      mbar_wait(c.bar + (B_P2E + slot) * 8, par);
    }
    const uint32_t fb = c.bar + (B_P2F + (n & 3)) * 8;
    if (expect) mbar_expect(fb, expect);
    bulk_load_mc(c.sm + SM_RING + slot * 32768 + c.rank * 16384, src, 16384, fb);
    if (cnt == 1 && u1) {
      mbar_wait(c.bar + (B_SE + 1) * 8, (p.s.p1_n[c.cl] - 1) & 1);
      p2_load_q(p, c, 0, 0);
    }
    slot = wrap5(slot + 1);
  };
  if (p.phases & 16) flag_wait<true>(F_GATE, 256);
  for (int it = 0; it < nit; it++) {
    const int item = p.s.p2_item[c.cl][it], h = item >> 3, j = item & 7;
    if (p.phases & 16) flag_wait<false>(F_HEAD + h, 96);
    if (it == 0 && !u1) { p2_load_q(p, c, 0, 0); p2_load_q(p, c, 0, 1); }
    for (int t = 2 * j + 1; t >= 0; t--) {
      const uint8_t* k = g_KV + (size_t)(h * 16 + t) * 32768 + c.rank * 16384;
      load(k, pv ? 65536 : 32768);
      if (pv) load(pv, 0);
      pv = k + (size_t)NH * 16 * 32768;
      n++;
    }
  }
  load(pv, 32768);
}

__device__ __forceinline__ void p2_storer(const Params& p, const Ctx& c, int sfpar) {
  const int nit = p.s.p2_n[c.cl];
  auto load_q = [&](int it, int w) {
    if (p.phases & 16) flag_wait<false>(F_HEAD + (p.s.p2_item[c.cl][it] >> 3), 96);
    p2_load_q(p, c, it, w);
  };
  if (nit > 1) { load_q(1, 1); mbar_wait(c.bar + B_LAD * 8, 0); p2_load_q(p, c, 1, 0); }
  for (int i = 0; i < 2 * nit; i++) {
    const int it = i >> 1, w = (it ^ i ^ 1) & 1, b = p2_buf(w, it);
    const int item = p.s.p2_item[c.cl][it], h = item >> 3, j = item & 7;
    mbar_wait(c.bar + (B_SF + b) * 8, (sfpar >> b) & 1);
    sfpar ^= 1 << b;
    bulk_store(g_ctx + (size_t)((j * 4 + p2_blk(c.rank, w, it)) * NKB3 + 9 + 2 * h) * 8192, c.sm + SM_BUF + b * 16384, 16384);
    BULK_COMMIT();
    if (it + 2 < nit) { BULK_WAIT_READ(0); load_q(it + 2, w); }
    BULK_WAIT(0);
    flag_add_rx(F_CTX + j * 64 + h, 1);
  }
}

__device__ __forceinline__ void p3_consumer(const Params& p, const Ctx& c) {
  const int tile = p.s.p3_tile[c.cl], j = tile / 3, nt = tile - 3 * j;
  const uint32_t ad = desc_lo(c.sm + SM_RING + c.wg * 8192, 16), bd = desc_lo(c.sm + SM_RING + 16384, 4096);
  float acc[96] = {};
  int slot = 0, par = 0, prev = 0;
#pragma unroll 1
  for (int kb = 0; kb < 9; kb++) {
    mbar_wait(c.bar + (B_P3F + slot) * 8, par);
    WG_FENCE();
#pragma unroll
    for (int kk = 0; kk < 4; kk++) wgmma_ss192<1, 1>(acc, ad + slot * 2560 + kk * 128, bd + slot * 2560 + (kk >> 1) * 768 + (kk & 1) * 128, kk != 0 ? 1 : kb != 0);
    WG_COMMIT();
    WG_WAIT(1);
    if (kb > 0) release(c, B_P3E + prev);
    prev = slot;
    if (++slot == 5) { slot = 0; par ^= 1; }
  }
#pragma unroll 1
  for (int kb = 9; kb < NKB3; kb++) {
    mbar_wait(c.bar + (B_P3F + slot) * 8, par);
    WG_FENCE();
#pragma unroll
    for (int kk = 0; kk < 4; kk++) wgmma_ss192<1>(acc, ad + slot * 2560 + kk * 2, bd + slot * 2560 + (kk >> 1) * 768 + (kk & 1) * 128, 1);
    WG_COMMIT();
    WG_WAIT(1);
    release(c, B_P3E + prev);
    prev = slot;
    if (++slot == 5) { slot = 0; par ^= 1; }
  }
  WG_WAIT(0);
  pin(acc);
  PROF(c.wg, 40);
  const int row = (c.lane & 7) + ((c.lane >> 3) & 1) * 8;
  const uint32_t wbase = c.sm + SM_RING + c.wg * 8192 + c.warp * 2048;
  const uint32_t base = wbase + row * 128 + (((c.lane >> 4) ^ (row & 7)) << 4);
#pragma unroll
  for (int i = 0; i < 12; i++)
    stsm4((base ^ ((i & 3) << 5)) + (i >> 2) * 40960, pack_bf16(acc[8 * i], acc[8 * i + 1]), pack_bf16(acc[8 * i + 2], acc[8 * i + 3]),
          pack_bf16(acc[8 * i + 4], acc[8 * i + 5]), pack_bf16(acc[8 * i + 6], acc[8 * i + 7]));
  FENCE_ASYNC_SMEM();
  __syncwarp();
  if (c.lane == 0) {
#pragma unroll
    for (int i = 0; i < 3; i++) tma2d_store(&p.map_out, wbase + i * 40960, nt * 192 + i * 64, j * 256 + c.rank * 128 + c.wg * 64 + c.warp * 16);
    BULK_COMMIT();
    BULK_WAIT_READ(0);
  }
}

__device__ __forceinline__ void p3_producer(const Params& p, const Ctx& c) {
  const int tile = p.s.p3_tile[c.cl], j = tile / 3, nt = tile - 3 * j;
  int slot = 0, par = 0;
  const uint8_t* a = g_ctx + (size_t)(j * 4 + c.rank * 2) * NKB3 * 8192;
  for (int q = 0; q < 33; q++) {
    const int g = p.s.p3_order[j][q];
    if (p.phases & 16) flag_wait<false>(F_CTX + j * 64 + g, g == 32 ? 32 : 4);
    const int kb0 = g == 32 ? 0 : 9 + 2 * g, nk = g == 32 ? 9 : 2, k0 = (g == 32 ? 0 : g * 128) + c.rank * 32;
    const CUtensorMap* m = &p.map_o[g == 32];
    for (int i = 0; i < nk; i++) {
      const uint32_t st = c.sm + SM_RING + slot * 40960, fb = c.bar + (B_P3F + slot) * 8;
      mbar_wait(c.bar + (B_P3E + slot) * 8, par);
      mbar_expect(fb, 40960);
      bulk_load(st, a + (size_t)(kb0 + i) * 8192, 8192, fb);
      bulk_load(st + 8192, a + (size_t)(NKB3 + kb0 + i) * 8192, 8192, fb);
      tma3d_mc(st + 16384 + c.rank * 12288, m, 0, k0 + i * 64, nt * 3, fb);
      if (++slot == 5) { slot = 0; par ^= 1; }
    }
  }
}

__device__ __forceinline__ float bf_lo(uint32_t w) { return __uint_as_float(w << 16); }
__device__ __forceinline__ float bf_hi(uint32_t w) { return __uint_as_float(w & 0xffff0000u); }

__device__ __forceinline__ void gate_row(const Params& p, int row, int lane) {
  const uint32_t* x = reinterpret_cast<const uint32_t*>(p.x + (size_t)row * DM);
  const uint32_t* w = reinterpret_cast<const uint32_t*>(p.gate_w);
  float a = 0.f;
#pragma unroll
  for (int i = 0; i < 9; i++) {
    const uint32_t u = __ldg(x + i * 32 + lane), v = __ldg(w + i * 32 + lane);
    a = fmaf(bf_lo(u), bf_lo(v), a);
    a = fmaf(bf_hi(u), bf_hi(v), a);
  }
#pragma unroll
  for (int o = 16; o > 0; o >>= 1) a += __shfl_xor_sync(0xffffffffu, a, o);
  if (lane == 0) g_gate[row] = 1.f / (1.f + __expf(-a));
}

__device__ __forceinline__ void lds10(uint32_t (&k)[10], uint32_t a) {
  asm volatile("ld.shared.v2.u32 {%0, %1}, [%10];\nld.shared.v2.u32 {%2, %3}, [%10+8];\nld.shared.v2.u32 {%4, %5}, [%10+16];\n"
               "ld.shared.v2.u32 {%6, %7}, [%10+24];\nld.shared.v2.u32 {%8, %9}, [%10+32];"
               : "=r"(k[0]), "=r"(k[1]), "=r"(k[2]), "=r"(k[3]), "=r"(k[4]), "=r"(k[5]), "=r"(k[6]), "=r"(k[7]), "=r"(k[8]), "=r"(k[9]) : "r"(a));
}
__device__ __forceinline__ void local_attn(const Params& p, const Ctx& c, int rb, int hs) {
  const int lane = c.lane, grp = rb >> 2, par = lane >> 4, i0 = 2 * (lane & 15);
  const uint32_t buf = c.sm + SM_BUF + (c.warp - 2) * 8192, bqk = c.bar + (B_LA + (c.warp - 2) * 2) * 8, bv = bqk + 8;
  const uint32_t mine = buf + 2304 + par * 160 + i0 * 4;
  const bool flags = p.phases & 16;
  auto fetch_qk = [&](int q) {
    if (flags) {
      const int tgt = q == 0 ? 24 : q == 3 ? 8 : 12;
      flag_wait_warp(F_QKVA + (grp - (grp > 0 && (rb & 3) == 0 ? par : 0)) * 4 + q, tgt);
    }
    tma3d_elect(buf, &p.map_t[0], rb * 32 + 8, 9 * (8 * q + hs), bqk, 5184);
    tma3d_elect(buf + 2304, &p.map_t[1], rb * 32, 288 + 9 * (8 * q + hs), bqk, 0);
  };
  auto fetch_v = [&](int q) { tma3d_elect(buf + 5248, &p.map_t[1], rb * 32, 576 + 9 * (8 * q + hs), bv, 2880); };
  fetch_qk(0);
  if (flags) flag_wait_warp(F_GATE, 256);
#pragma unroll 1
  for (int q = 0; q < 4; q++) {
    fetch_v(q);
    float a[8], b[8];
#pragma unroll
    for (int w = 0; w < 8; w++) a[w] = b[w] = 0.f;
    mbar_wait(bqk, q & 1);
    PROFB(1 + 2 * q);
#pragma unroll 1
    for (int j = 0; j < 9; j++) {
      uint32_t x, y, k[10];
      asm volatile("ld.shared.v2.u32 {%0, %1}, [%2];" : "=r"(x), "=r"(y) : "r"(buf + lane * 8 + j * 256));
      lds10(k, mine + j * 320);
      const float xl = bf_lo(x), xh = bf_hi(x), yl = bf_lo(y), yh = bf_hi(y);
#pragma unroll
      for (int m = 1; m < 10; m++) {
        const float kl = bf_lo(k[m]), kh = bf_hi(k[m]);
        if (m < 9) a[8 - m] = fmaf(xl, kl, fmaf(xh, kh, a[8 - m]));
        if (m > 1) b[9 - m] = fmaf(yl, kl, fmaf(yh, kh, b[9 - m]));
      }
    }
    __syncwarp();
    if (q < 3) fetch_qk(q + 1);
    constexpr float SC = 0.23570226039551584f * 1.4426950408889634f;
    const float* gp = g_gate + rb * 64 + 2 * i0 + par;
    const float ga = __ldcg(gp), gb = __ldcg(gp + 2);
    float ma = a[0], mb = b[0];
#pragma unroll
    for (int w = 1; w < 8; w++) {
      if (rb == 0) {
        if (i0 < w) a[w] = -INFINITY;
        if (i0 + 1 < w) b[w] = -INFINITY;
      }
      ma = fmaxf(ma, a[w]); mb = fmaxf(mb, b[w]);
    }
    float la = 0.f, lb = 0.f;
#pragma unroll
    for (int w = 0; w < 8; w++) {
      a[w] = ex2((a[w] - ma) * SC); b[w] = ex2((b[w] - mb) * SC);
      la += a[w]; lb += b[w];
    }
    la = __fdividef(ga, la); lb = __fdividef(gb, lb);
#pragma unroll
    for (int w = 0; w < 8; w++) { a[w] *= la; b[w] *= lb; }
    uint8_t* dst = g_ctx + (size_t)rb * NKB3 * 8192 + ((i0 & 2) + par) * 4;
    mbar_wait(bv, q & 1);
#pragma unroll 1
    for (int j = 0; j < 9; j++) {
      uint32_t v[10];
      lds10(v, mine + 2944 + j * 320);
      float a0 = 0.f, a1 = 0.f, b0 = 0.f, b1 = 0.f;
#pragma unroll
      for (int m = 1; m < 10; m++) {
        const float vl = bf_lo(v[m]), vh = bf_hi(v[m]);
        if (m < 9) { a0 = fmaf(a[8 - m], vl, a0); a1 = fmaf(a[8 - m], vh, a1); }
        if (m > 1) { b0 = fmaf(b[9 - m], vl, b0); b1 = fmaf(b[9 - m], vh, b1); }
      }
      const uint32_t wa = pack_bf16(a0, a1), wb = pack_bf16(b0, b1);
      const uint32_t got = __shfl_xor_sync(0xffffffffu, par ? wa : wb, 16);
      const uint32_t r0 = par ? got : wa, r1 = par ? wb : got;
      const int col = 18 * (8 * q + hs) + 2 * j, o = col * 128 + ((((i0 >> 2) ^ col) & 7) << 4);
      *reinterpret_cast<uint32_t*>(dst + o) = __byte_perm(r0, r1, 0x5410);
      *reinterpret_cast<uint32_t*>(dst + ((o + 128) ^ 16)) = __byte_perm(r0, r1, 0x7632);
    }
    __syncwarp();
    PROFB(2 + 2 * q);
  }
  if (lane == 0) { mbar_arrive(c.bar + B_LAD * 8); flag_add(F_CTX + grp * 64 + 32, 1); }
}

__global__ void __cluster_dims__(2, 1, 1) __launch_bounds__(384, 1) fused_kernel(const __grid_constant__ Params p) {
  extern __shared__ uint8_t smem_raw[];
  Ctx c;
  c.sm = ((uint32_t)__cvta_generic_to_shared(smem_raw) + 1023u) & ~1023u;
  c.bar = c.sm + SM_BAR;
  c.lane = threadIdx.x & 31;
  c.wg = __shfl_sync(0xffffffffu, threadIdx.x >> 7, 0);
  c.warp = __shfl_sync(0xffffffffu, (threadIdx.x >> 5) & 3, 0);
  c.cl = blockIdx.x >> 1;
  c.rank = blockIdx.x & 1;
  c.rbar = mapa(c.bar, c.lane & 1);
  const bool do1 = (p.phases & 1) && p.s.p1_n[c.cl] > 0;
  const bool do2 = (p.phases & 2) && p.s.p2_n[c.cl] > 0;
  const bool do3 = (p.phases & 4) && p.s.p3_tile[c.cl] != 255;
  const int u1 = do1 ? 8 + p.s.p1_n[c.cl] * (8 + (p.s.p1_slab[c.cl] >> 3)) : 0;
  const int rot = ((u1 % 10 + 1) >> 1) % 5;
  PROF(c.wg, 0);
  if (threadIdx.x == 0) {
    for (int i = 0; i < 10; i++) { mbar_init(c.bar + (B_P1F + i) * 8, 1); mbar_init(c.bar + (B_P1E + i) * 8, 16); }
    for (int i = 0; i < 5; i++) {
      mbar_init(c.bar + (B_P2E + i) * 8, 16);
      mbar_init(c.bar + (B_P3F + i) * 8, 1); mbar_init(c.bar + (B_P3E + i) * 8, 16);
    }
    for (int i = 0; i < 4; i++) { mbar_init(c.bar + (B_SF + i) * 8, 4); mbar_init(c.bar + (B_SE + i) * 8, 1); mbar_init(c.bar + (B_QF + i) * 8, 1);
      mbar_init(c.bar + (B_P2F + i) * 8, 5); mbar_init(c.bar + (B_ORD + i) * 8, 4); }
    for (int i = 0; i < 4; i++) mbar_init(c.bar + (B_LA + i) * 8, 1);
    mbar_init(c.bar + B_LAD * 8, 2);
    mbar_init(c.bar + B_DONE * 8, 1);
    mbar_init(c.bar + B_FIN * 8, 8);
    asm volatile("fence.mbarrier_init.release.cluster;" ::: "memory");
  }
  cluster_sync();

  if (c.wg < 2) {
    asm volatile("setmaxnreg.inc.sync.aligned.u32 224;");
    if (c.wg == 1) { if (do1) bar_arrive(ORDER, 256); else if (c.lane == 0) mbar_arrive(c.bar + B_P2F * 8); }
    if (do1) p1_consumer(p, c);
    if (do2) p2_consumer(p, c, rot);
    if (do3) {
      mbar_wait(c.bar + B_DONE * 8, 0);
#pragma unroll
      for (int i = 0; i < 5; i++) release(c, B_P3E + i);
      p3_consumer(p, c);
    }
    PROF(c.wg, 63);
    if (c.lane == 0) mbar_arrive(c.bar + B_FIN * 8);
    __syncwarp();
    cluster_sync();
  } else {
    asm volatile("setmaxnreg.dec.sync.aligned.u32 56;");
    if (c.warp == 0) {
      if (c.lane == 0) {
        if (do1) p1_producer(p, c);
        if (do2) p2_producer(p, c, u1, rot);
        if (do3) p3_producer(p, c);
      }
    } else if (c.warp == 1) {
      if (c.lane == 0) {
        int sfpar = 0;
        if (do1) {
          p1_storer(p, c);
          sfpar = (p.s.p1_n[c.cl] & 1) * 10;
        }
        if (do2) p2_storer(p, c, sfpar);
        mbar_wait(c.bar + B_LAD * 8, 0);
        mbar_arrive(c.bar + B_DONE * 8);
      }
    } else {
      const int bw = blockIdx.x * 2 + (c.warp - 2);
      if ((p.phases & 1) && bw < 256) {
        for (int i = 0; i < 8; i++) gate_row(p, bw * 8 + i, c.lane);
        if (c.lane == 0) flag_add(F_GATE, 1);
      }
      if ((p.phases & 8) && bw < 256) local_attn(p, c, bw >> 3, bw & 7);
      else if (c.lane == 0) mbar_arrive(c.bar + B_LAD * 8);
    }
    __syncwarp();
    bar_sync(3, 128);
    if (c.warp == 0 && (p.phases & 4)) {
      int last = 0;
      if (c.lane == 0) { __threadfence(); last = atomicAdd(g_flags + F_DONE, 1) == 2 * NCL - 1; }
      if (__shfl_sync(0xffffffffu, last, 0)) for (int i = c.lane; i < F_NUM; i += 32) g_flags[i] = 0;
    }
    if (c.warp == 1) mbar_wait(c.bar + B_FIN * 8, 0);
    __syncwarp();
    cluster_sync();
  }
}

static const Sched k_sched = {
  {0,0,0,0,0,8,8,8,1,1,1,1,9,9,9,9,2,2,2,2,2,10,10,10,10,3,3,3,3,3,11,11,11,4,4,4,4,12,12,12,12,5,5,5,5,5,13,13,13,6,6,6,6,6,14,14,14,14,7,7,7,7,15,15,15,15},
  {13,13,13,13,12,16,15,15,16,16,16,16,12,12,11,11,13,13,13,13,12,12,12,11,11,13,13,13,13,12,16,15,15,16,16,16,16,12,12,11,11,13,13,13,13,12,16,15,15,13,13,13,13,12,12,12,11,11,16,16,16,16,12,12,11,11},
  {{0,34,5,39,10,44,15,49,20,54,25,59,30,0,0,0,0,0},
   {32,3,37,8,42,13,47,18,52,23,57,28,62,0,0,0,0,0},
   {1,35,6,40,11,45,16,50,21,55,26,60,31,0,0,0,0,0},
   {33,4,38,9,43,14,48,19,53,24,58,29,63,0,0,0,0,0},
   {2,36,7,41,12,46,17,51,22,56,27,61,0,0,0,0,0,0},
   {32,33,34,35,40,1,4,7,10,13,16,19,22,25,28,31,0,0},
   {36,37,38,39,45,2,5,8,11,14,17,20,23,26,29,0,0,0},
   {41,42,43,44,0,3,6,9,12,15,18,21,24,27,30,0,0,0},
   {0,2,4,6,8,10,12,14,16,18,20,22,24,26,28,30,0,0},
   {32,34,36,38,40,42,44,46,48,50,52,54,56,58,60,62,0,0},
   {1,3,5,7,9,11,13,15,17,19,21,23,25,27,29,31,0,0},
   {33,35,37,39,41,43,45,47,49,51,53,55,57,59,61,63,0,0},
   {32,37,43,40,2,6,10,14,18,22,26,30,0,0,0,0,0,0},
   {36,42,35,45,3,7,11,15,19,23,27,31,0,0,0,0,0,0},
   {41,34,39,0,4,8,12,16,20,24,28,0,0,0,0,0,0,0},
   {33,38,44,1,5,9,13,17,21,25,29,0,0,0,0,0,0,0},
   {0,34,5,39,10,44,15,49,20,54,25,59,30,0,0,0,0,0},
   {32,3,37,8,42,13,47,18,52,23,57,28,62,0,0,0,0,0},
   {1,35,6,40,11,45,16,50,21,55,26,60,31,0,0,0,0,0},
   {33,4,38,9,43,14,48,19,53,24,58,29,63,0,0,0,0,0},
   {2,36,7,41,12,46,17,51,22,56,27,61,0,0,0,0,0,0},
   {32,37,43,40,2,6,10,14,18,22,26,30,0,0,0,0,0,0},
   {36,42,35,45,3,7,11,15,19,23,27,31,0,0,0,0,0,0},
   {41,34,39,0,4,8,12,16,20,24,28,0,0,0,0,0,0,0},
   {33,38,44,1,5,9,13,17,21,25,29,0,0,0,0,0,0,0},
   {0,34,5,39,10,44,15,49,20,54,25,59,30,0,0,0,0,0},
   {32,3,37,8,42,13,47,18,52,23,57,28,62,0,0,0,0,0},
   {1,35,6,40,11,45,16,50,21,55,26,60,31,0,0,0,0,0},
   {33,4,38,9,43,14,48,19,53,24,58,29,63,0,0,0,0,0},
   {2,36,7,41,12,46,17,51,22,56,27,61,0,0,0,0,0,0},
   {32,33,34,35,40,1,4,7,10,13,16,19,22,25,28,31,0,0},
   {36,37,38,39,45,2,5,8,11,14,17,20,23,26,29,0,0,0},
   {41,42,43,44,0,3,6,9,12,15,18,21,24,27,30,0,0,0},
   {0,2,4,6,8,10,12,14,16,18,20,22,24,26,28,30,0,0},
   {32,34,36,38,40,42,44,46,48,50,52,54,56,58,60,62,0,0},
   {1,3,5,7,9,11,13,15,17,19,21,23,25,27,29,31,0,0},
   {33,35,37,39,41,43,45,47,49,51,53,55,57,59,61,63,0,0},
   {32,37,43,40,2,6,10,14,18,22,26,30,0,0,0,0,0,0},
   {36,42,35,45,3,7,11,15,19,23,27,31,0,0,0,0,0,0},
   {41,34,39,0,4,8,12,16,20,24,28,0,0,0,0,0,0,0},
   {33,38,44,1,5,9,13,17,21,25,29,0,0,0,0,0,0,0},
   {0,34,5,39,10,44,15,49,20,54,25,59,30,0,0,0,0,0},
   {32,3,37,8,42,13,47,18,52,23,57,28,62,0,0,0,0,0},
   {1,35,6,40,11,45,16,50,21,55,26,60,31,0,0,0,0,0},
   {33,4,38,9,43,14,48,19,53,24,58,29,63,0,0,0,0,0},
   {2,36,7,41,12,46,17,51,22,56,27,61,0,0,0,0,0,0},
   {32,33,34,35,40,1,4,7,10,13,16,19,22,25,28,31,0,0},
   {36,37,38,39,45,2,5,8,11,14,17,20,23,26,29,0,0,0},
   {41,42,43,44,0,3,6,9,12,15,18,21,24,27,30,0,0,0},
   {0,34,5,39,10,44,15,49,20,54,25,59,30,0,0,0,0,0},
   {32,3,37,8,42,13,47,18,52,23,57,28,62,0,0,0,0,0},
   {1,35,6,40,11,45,16,50,21,55,26,60,31,0,0,0,0,0},
   {33,4,38,9,43,14,48,19,53,24,58,29,63,0,0,0,0,0},
   {2,36,7,41,12,46,17,51,22,56,27,61,0,0,0,0,0,0},
   {32,37,43,40,2,6,10,14,18,22,26,30,0,0,0,0,0,0},
   {36,42,35,45,3,7,11,15,19,23,27,31,0,0,0,0,0,0},
   {41,34,39,0,4,8,12,16,20,24,28,0,0,0,0,0,0,0},
   {33,38,44,1,5,9,13,17,21,25,29,0,0,0,0,0,0,0},
   {0,2,4,6,8,10,12,14,16,18,20,22,24,26,28,30,0,0},
   {32,34,36,38,40,42,44,46,48,50,52,54,56,58,60,62,0,0},
   {1,3,5,7,9,11,13,15,17,19,21,23,25,27,29,31,0,0},
   {33,35,37,39,41,43,45,47,49,51,53,55,57,59,61,63,0,0},
   {32,37,43,40,2,6,10,14,18,22,26,30,0,0,0,0,0,0},
   {36,42,35,45,3,7,11,15,19,23,27,31,0,0,0,0,0,0},
   {41,34,39,0,4,8,12,16,20,24,28,0,0,0,0,0,0,0},
   {33,38,44,1,5,9,13,17,21,25,29,0,0,0,0,0,0,0}},
  {4,4,5,4,5,4,3,2,4,4,4,2,4,3,4,4,4,6,3,4,4,3,6,4,5,4,5,5,5,4,3,2,1,3,4,3,1,5,5,4,4,4,5,5,5,5,2,2,2,5,5,3,4,5,5,4,6,4,2,3,2,2,5,4,5,5},
  {{12,127,171,237,0,0,0,0,0,0},
   {55,123,207,242,0,0,0,0,0,0},
   {29,126,180,202,184,0,0,0,0,0},
   {3,111,181,245,0,0,0,0,0,0},
   {7,124,146,161,220,0,0,0,0,0},
   {24,74,121,152,0,0,0,0,0,0},
   {16,84,88,0,0,0,0,0,0,0},
   {59,122,0,0,0,0,0,0,0,0},
   {0,42,90,80,0,0,0,0,0,0},
   {43,81,129,160,0,0,0,0,0,0},
   {17,58,114,168,0,0,0,0,0,0},
   {86,128,0,0,0,0,0,0,0,0},
   {27,41,99,144,0,0,0,0,0,0},
   {1,52,115,0,0,0,0,0,0,0},
   {31,158,222,248,0,0,0,0,0,0},
   {5,135,214,176,0,0,0,0,0,0},
   {46,159,178,219,0,0,0,0,0,0},
   {20,49,116,138,170,228,0,0,0,0},
   {63,166,247,0,0,0,0,0,0,0},
   {37,143,205,233,0,0,0,0,0,0},
   {15,167,221,232,0,0,0,0,0,0},
   {70,97,64,0,0,0,0,0,0,0},
   {44,57,89,139,206,225,0,0,0,0},
   {22,151,196,243,0,0,0,0,0,0},
   {39,132,189,210,240,0,0,0,0,0},
   {11,119,155,238,0,0,0,0,0,0},
   {54,133,154,212,192,0,0,0,0,0},
   {28,118,172,211,200,0,0,0,0,0},
   {2,95,173,194,217,0,0,0,0,0},
   {6,108,147,230,0,0,0,0,0,0},
   {32,91,96,0,0,0,0,0,0,0},
   {33,100,0,0,0,0,0,0,0,0},
   {102,0,0,0,0,0,0,0,0,0},
   {60,113,104,0,0,0,0,0,0,0},
   {34,65,105,72,0,0,0,0,0,0},
   {8,85,112,0,0,0,0,0,0,0},
   {103,0,0,0,0,0,0,0,0,0},
   {18,68,174,195,226,0,0,0,0,0},
   {87,148,188,201,249,0,0,0,0,0},
   {13,109,190,253,0,0,0,0,0,0},
   {30,125,163,229,0,0,0,0,0,0},
   {71,140,223,224,0,0,0,0,0,0},
   {45,117,198,209,208,0,0,0,0,0},
   {19,93,156,213,216,0,0,0,0,0},
   {62,150,179,193,234,0,0,0,0,0},
   {23,141,145,187,218,0,0,0,0,0},
   {75,48,0,0,0,0,0,0,0,0},
   {76,40,0,0,0,0,0,0,0,0},
   {50,107,0,0,0,0,0,0,0,0},
   {36,92,130,137,239,0,0,0,0,0},
   {10,69,191,185,244,0,0,0,0,0},
   {79,183,255,0,0,0,0,0,0,0},
   {53,134,197,252,0,0,0,0,0,0},
   {14,82,165,204,251,0,0,0,0,0},
   {61,142,162,177,236,0,0,0,0,0},
   {35,110,164,246,0,0,0,0,0,0},
   {4,67,157,153,186,235,0,0,0,0},
   {47,106,199,227,0,0,0,0,0,0},
   {77,56,0,0,0,0,0,0,0,0},
   {51,98,120,0,0,0,0,0,0,0},
   {25,101,0,0,0,0,0,0,0,0},
   {94,136,0,0,0,0,0,0,0,0},
   {9,26,66,149,231,0,0,0,0,0},
   {78,175,169,254,0,0,0,0,0,0},
   {21,83,182,203,250,0,0,0,0,0},
   {38,73,131,215,241,0,0,0,0,0}},
  {255,255,255,255,255,0,3,4,9,10,11,12,21,22,255,255,255,255,255,255,255,23,255,255,255,255,255,255,255,255,1,5,6,13,14,15,16,255,255,255,255,255,255,255,255,255,2,7,8,255,255,255,255,255,255,255,255,255,17,18,19,20,255,255,255,255},
  {{32,0,1,2,3,4,5,6,7,8,9,10,11,12,13,14,15,16,17,18,19,20,21,22,23,24,25,26,27,28,29,30,31},
   {32,0,1,2,3,4,5,6,7,8,9,10,11,12,13,14,15,16,17,18,19,20,21,22,23,24,25,26,27,28,29,30,31},
   {32,0,1,2,3,4,5,6,7,8,9,10,11,12,13,14,15,16,17,18,19,20,21,22,23,24,25,26,27,28,29,30,31},
   {32,0,1,2,3,4,5,6,7,8,9,10,11,12,13,14,15,16,17,18,19,20,21,22,23,24,25,26,27,28,29,30,31},
   {32,0,1,2,3,4,5,6,7,8,9,10,11,12,13,14,15,16,17,18,19,20,21,22,23,24,25,26,27,28,29,30,31},
   {32,0,1,2,3,4,5,6,7,8,9,10,11,12,13,14,15,16,17,18,19,20,21,22,23,24,25,26,27,28,29,30,31},
   {32,0,1,2,3,4,5,6,7,8,9,10,11,12,13,14,15,16,17,18,19,20,21,22,23,24,25,26,27,28,29,30,31},
   {32,0,1,2,3,4,5,6,7,8,9,10,11,12,13,14,15,16,17,18,19,20,21,22,23,24,25,26,27,28,29,30,31}}};

typedef CUresult (*EncodeFn)(CUtensorMap*, CUtensorMapDataType, cuuint32_t, void*, const cuuint64_t*, const cuuint64_t*, const cuuint32_t*,
                             const cuuint32_t*, CUtensorMapInterleave, CUtensorMapSwizzle, CUtensorMapL2promotion, CUtensorMapFloatOOBfill);

void make_map2(EncodeFn enc, CUtensorMap* m, const void* ptr, int rows, int cols, int box_rows) {
  cuuint64_t dim[2] = {(cuuint64_t)cols, (cuuint64_t)rows}, str[1] = {(cuuint64_t)cols * 2};
  cuuint32_t box[2] = {64, (cuuint32_t)box_rows}, es[2] = {1, 1};
  enc(m, CU_TENSOR_MAP_DATA_TYPE_BFLOAT16, 2, const_cast<void*>(ptr), dim, str, box, es, CU_TENSOR_MAP_INTERLEAVE_NONE, CU_TENSOR_MAP_SWIZZLE_128B,
      CU_TENSOR_MAP_L2_PROMOTION_L2_128B, CU_TENSOR_MAP_FLOAT_OOB_FILL_NONE);
}
void make_map3(EncodeFn enc, CUtensorMap* m, const void* ptr, int rows) {
  cuuint64_t dim[3] = {64, (cuuint64_t)rows, 9}, str[2] = {DM * 2, 128};
  cuuint32_t box[3] = {64, 32, 3}, es[3] = {1, 1, 1};
  enc(m, CU_TENSOR_MAP_DATA_TYPE_BFLOAT16, 3, const_cast<void*>(ptr), dim, str, box, es, CU_TENSOR_MAP_INTERLEAVE_NONE, CU_TENSOR_MAP_SWIZZLE_128B,
      CU_TENSOR_MAP_L2_PROMOTION_L2_128B, CU_TENSOR_MAP_FLOAT_OOB_FILL_NONE);
}

void make_map_t(EncodeFn enc, CUtensorMap* m, void* ptr, int width) {
  cuuint64_t dim[3] = {TP / 2, 2, 864}, str[2] = {TP * 2, TP * 4};
  cuuint32_t box[3] = {(cuuint32_t)width, 2, 9}, es[3] = {1, 1, 1};
  enc(m, CU_TENSOR_MAP_DATA_TYPE_UINT32, 3, ptr, dim, str, box, es, CU_TENSOR_MAP_INTERLEAVE_NONE, CU_TENSOR_MAP_SWIZZLE_NONE,
      CU_TENSOR_MAP_L2_PROMOTION_NONE, CU_TENSOR_MAP_FLOAT_OOB_FILL_NONE);
}

int g_mode = -1;

}

extern "C" void kernel_launch(void* const* d_in, const int* in_sizes, int n_in, void* d_out, int out_size) {
  static EncodeFn enc = nullptr;
  static void* t_ptr = nullptr;
  if (!enc) {
    void* fn = nullptr;
    cudaDriverEntryPointQueryResult st;
    cudaGetDriverEntryPoint("cuTensorMapEncodeTiled", &fn, cudaEnableDefault, &st);
    enc = (EncodeFn)fn;
    cudaGetSymbolAddress(&t_ptr, g_T);
    cudaFuncSetAttribute(fused_kernel, cudaFuncAttributeMaxDynamicSharedMemorySize, SMEM_BYTES);
    if (g_mode < 0) {
      cudaLaunchConfig_t cfg = {};
      cfg.gridDim = dim3(2 * NCL); cfg.blockDim = dim3(384); cfg.dynamicSmemBytes = SMEM_BYTES;
      cudaLaunchAttribute at; at.id = cudaLaunchAttributeClusterDimension;
      at.val.clusterDim.x = 2; at.val.clusterDim.y = 1; at.val.clusterDim.z = 1;
      cfg.attrs = &at; cfg.numAttrs = 1;
      int nc = 0;
      g_mode = (cudaOccupancyMaxActiveClusters(&nc, fused_kernel, &cfg) == cudaSuccess && nc >= NCL) ? 1 : 0;
      (void)cudaGetLastError();
    }
  }
  Params p;
  make_map2(enc, &p.map_a[0], d_in[4], SEQ, DC, 128);
  make_map2(enc, &p.map_a[1], d_in[0], SEQ, DM, 128);
  make_map2(enc, &p.map_w[0], d_in[6], DC, 4096, 64);
  make_map2(enc, &p.map_w[1], d_in[7], DC, 4096, 64);
  make_map2(enc, &p.map_w[2], d_in[5], DM, 4096, 64);
  make_map2(enc, &p.map_w[3], d_in[1], DM, 1728, 64);
  make_map3(enc, &p.map_o[0], d_in[8], 4096);
  make_map3(enc, &p.map_o[1], d_in[2], DM);
  make_map_t(enc, &p.map_t[0], t_ptr, 32);
  make_map_t(enc, &p.map_t[1], t_ptr, 40);
  p.x = (const __nv_bfloat16*)d_in[0];
  p.gate_w = (const __nv_bfloat16*)d_in[9];
  make_map2(enc, &p.map_out, d_out, SEQ, DM, 16);
  p.zero = 0;
  p.s = k_sched;
  if (g_mode == 1) {
    p.phases = 31;
    fused_kernel<<<2 * NCL, 384, SMEM_BYTES>>>(p);
  } else {
    p.phases = 1;  fused_kernel<<<2 * NCL, 384, SMEM_BYTES>>>(p);
    p.phases = 10; fused_kernel<<<2 * NCL, 384, SMEM_BYTES>>>(p);
    p.phases = 4;  fused_kernel<<<2 * NCL, 384, SMEM_BYTES>>>(p);
  }
}
```

```cpp
#include <cuda_runtime.h>
#include <cuda_bf16.h>
#include <cuda.h>
#include <stdint.h>

namespace {

constexpr int SEQ = 2048, DM = 576, DC = 512, NH = 32;
constexpr int NCL = 66;
constexpr int NKB3 = 73;
constexpr uint32_t DESC_HI = 0x40000040u;

constexpr int SM_RING = 0;
constexpr int SM_BUF = 163840;
constexpr int SM_BAR = 229376;
constexpr int B_P1F = 0, B_P1E = 10, B_P2F = 20, B_P2E = 25, B_P3F = 30, B_P3E = 35, B_SF = 40, B_SE = 44, B_QF = 48, B_DONE = 52, B_FIN = 53, B_ORD = 54, B_LA = 58, B_LAD = 62, B_NUM = 63;
constexpr int SMEM_BYTES = SM_BAR + B_NUM * 8 + 1024;

constexpr int F_HEAD = 0;
constexpr int F_QKVA = 32;
constexpr int F_GATE = 64;
constexpr int F_DONE = 65;
constexpr int F_CTX = 96;
constexpr int F_NUM = 96 + 8 * 64;

struct Rec {
  uint8_t slab;
  uint8_t n1, n2;
  uint8_t p3;
  uint8_t item[12];
  uint8_t tile[48];
};
struct Sched {
  Rec r[NCL];
  uint8_t p3_order[8][32];
};

struct Params {
  CUtensorMap map_a[2];
  CUtensorMap map_w[4];
  CUtensorMap map_o[2];
  CUtensorMap map_t[3];
  CUtensorMap map_out;
  const __nv_bfloat16* x;
  const __nv_bfloat16* gate_w;
  int zero;
  int phases;
  alignas(64) Sched s;
};

__device__ __align__(1024) uint8_t g_Q[NH * 32 * 16384];
__device__ __align__(1024) uint8_t g_KV[2 * NH * 16 * 32768];
__device__ __align__(1024) uint8_t g_oA[32 * 576 * 128];
constexpr int TP = SEQ + 16;
__device__ __align__(1024) uint32_t g_T[864 * TP];
__device__ float g_gate[SEQ];
__device__ int g_flags[F_NUM];

__device__ __forceinline__ void mbar_init(uint32_t b, int c) { asm volatile("mbarrier.init.shared::cta.b64 [%0], %1;" ::"r"(b), "r"(c)); }
__device__ __forceinline__ void mbar_arrive(uint32_t b) { asm volatile("mbarrier.arrive.shared::cta.b64 _, [%0];" ::"r"(b) : "memory"); }
__device__ __forceinline__ void mbar_arrive_cl(uint32_t b, int cnt) {
  asm volatile("mbarrier.arrive.shared::cluster.b64 _, [%0], %1;" ::"r"(b), "r"(cnt) : "memory");
}
__device__ __forceinline__ void mbar_wait(uint32_t b, int par) {
  asm volatile(
      "{\n.reg .pred p;\n.reg .u32 c;\n"
      "mbarrier.try_wait.parity.shared::cta.b64 p, [%0], %1;\n@p bra DN;\nmov.u32 c, 0;\n"
      "LP:\nmbarrier.try_wait.parity.shared::cta.b64 p, [%0], %1;\n@p bra DN;\n"
      "add.u32 c, c, 1;\nsetp.lt.u32 p, c, 4000000;\n@p bra LP;\ntrap;\nDN:\n}" ::"r"(b), "r"(par) : "memory");
}
__device__ __forceinline__ uint32_t mapa(uint32_t a, uint32_t cta) {
  uint32_t r; asm("mapa.shared::cluster.u32 %0, %1, %2;" : "=r"(r) : "r"(a), "r"(cta)); return r;
}
#define ELECT(ins) "{\n.reg .pred e;\nelect.sync _|e, 0xffffffff;\n@e " ins "\n}"
__device__ __forceinline__ void mbar_expect(uint32_t b, int bytes) {
  asm volatile(ELECT("mbarrier.arrive.expect_tx.shared::cta.b64 _, [%0], %1;") ::"r"(b), "r"(bytes) : "memory");
}
__device__ __forceinline__ void mbar_arrive_one(uint32_t b) { asm volatile(ELECT("mbarrier.arrive.shared::cta.b64 _, [%0];") ::"r"(b) : "memory"); }
__device__ __forceinline__ void bulk_load(uint32_t dst, const void* src, int bytes, uint32_t bar) {
  asm volatile(ELECT("cp.async.bulk.shared::cluster.global.mbarrier::complete_tx::bytes [%0], [%1], %2, [%3];") ::"r"(dst), "l"(src), "r"(bytes), "r"(bar) : "memory");
}
__device__ __forceinline__ void bulk_load_mc(uint32_t dst, const void* src, int bytes, uint32_t bar) {
  asm volatile(ELECT("cp.async.bulk.shared::cluster.global.mbarrier::complete_tx::bytes.multicast::cluster [%0], [%1], %2, [%3], %4;") ::"r"(dst), "l"(src), "r"(bytes), "r"(bar), "h"((uint16_t)3) : "memory");
}
__device__ __forceinline__ void bulk_store(void* dst, uint32_t src, int bytes) {
  asm volatile(ELECT("cp.async.bulk.global.shared::cta.bulk_group [%0], [%1], %2;") ::"l"(dst), "r"(src), "r"(bytes) : "memory");
}
__device__ __forceinline__ void tma2d(uint32_t dst, const CUtensorMap* m, int c0, int c1, uint32_t bar) {
  asm volatile(ELECT("cp.async.bulk.tensor.2d.shared::cluster.global.mbarrier::complete_tx::bytes [%0], [%1, {%3, %4}], [%2];") ::"r"(dst), "l"(m), "r"(bar), "r"(c0), "r"(c1) : "memory");
}
__device__ __forceinline__ void tma2d_mc(uint32_t dst, const CUtensorMap* m, int c0, int c1, uint32_t bar) {
  asm volatile(ELECT("cp.async.bulk.tensor.2d.shared::cluster.global.mbarrier::complete_tx::bytes.multicast::cluster [%0], [%1, {%3, %4}], [%2], %5;") ::"r"(dst), "l"(m), "r"(bar), "r"(c0), "r"(c1), "h"((uint16_t)3) : "memory");
}
__device__ __forceinline__ void tma3d(uint32_t dst, const CUtensorMap* m, int c0, int c1, int c2, uint32_t bar) {
  asm volatile(ELECT("cp.async.bulk.tensor.3d.shared::cluster.global.mbarrier::complete_tx::bytes [%0], [%1, {%3, %4, %5}], [%2];") ::"r"(dst), "l"(m), "r"(bar), "r"(c0), "r"(c1), "r"(c2) : "memory");
}
__device__ __forceinline__ void tma3d_mc(uint32_t dst, const CUtensorMap* m, int c0, int c1, int c2, uint32_t bar) {
  asm volatile(ELECT("cp.async.bulk.tensor.3d.shared::cluster.global.mbarrier::complete_tx::bytes.multicast::cluster [%0], [%1, {%3, %4, %5}], [%2], %6;") ::"r"(dst), "l"(m), "r"(bar), "r"(c0), "r"(c1), "r"(c2), "h"((uint16_t)3) : "memory");
}
__device__ __forceinline__ void tma2d_store(const CUtensorMap* m, uint32_t src, int c0, int c1) {
  asm volatile(ELECT("cp.async.bulk.tensor.2d.global.shared::cta.bulk_group [%0, {%2, %3}], [%1];") ::"l"(m), "r"(src), "r"(c0), "r"(c1) : "memory");
}
__device__ __forceinline__ void tma3d_store(const CUtensorMap* m, uint32_t src, int c0, int c1, int c2) {
  asm volatile(ELECT("cp.async.bulk.tensor.3d.global.shared::cta.bulk_group [%0, {%2, %3, %4}], [%1];") ::"l"(m), "r"(src), "r"(c0), "r"(c1), "r"(c2) : "memory");
}
__device__ __forceinline__ void tma2d_prefetch(const CUtensorMap* m, int c0, int c1) {
  asm volatile(ELECT("cp.async.bulk.prefetch.tensor.2d.L2.global [%0, {%1, %2}];") ::"l"(m), "r"(c0), "r"(c1) : "memory");
}
#define BULK_COMMIT() asm volatile("cp.async.bulk.commit_group;" ::: "memory")
#define BULK_WAIT(n) asm volatile("cp.async.bulk.wait_group %0;" ::"n"(n) : "memory")
#define BULK_WAIT_READ(n) asm volatile("cp.async.bulk.wait_group.read %0;" ::"n"(n) : "memory")
#define FENCE_ASYNC_SMEM() asm volatile("fence.proxy.async.shared::cta;" ::: "memory")
#define FENCE_ASYNC_ALL() asm volatile("fence.proxy.async;" ::: "memory")
#define WG_FENCE() asm volatile("wgmma.fence.sync.aligned;" ::: "memory")
#define WG_COMMIT() asm volatile("wgmma.commit_group.sync.aligned;" ::: "memory")
#define WG_WAIT(n) asm volatile("wgmma.wait_group.sync.aligned %0;" ::"n"(n) : "memory")
__device__ __forceinline__ void bar_sync(int id, int n) { asm volatile("bar.sync %0, %1;" ::"r"(id), "r"(n) : "memory"); }
__device__ __forceinline__ void bar_arrive(int id, int n) { asm volatile("bar.arrive %0, %1;" ::"r"(id), "r"(n) : "memory"); }
__device__ __forceinline__ void cluster_sync() {
  asm volatile("barrier.cluster.arrive.relaxed;\nbarrier.cluster.wait.acquire;" ::: "memory");
}
template <int N> __device__ __forceinline__ void pin(float (&r)[N]) {
#pragma unroll
  for (int i = 0; i < N; i++) asm volatile("" : "+f"(r[i])::"memory");
}
template <int N> __device__ __forceinline__ void pin(uint32_t (&r)[N]) {
#pragma unroll
  for (int i = 0; i < N; i++) asm volatile("" : "+r"(r[i])::"memory");
}
__device__ __forceinline__ uint32_t pack_bf16(float lo, float hi) {
  uint32_t r; asm("cvt.rn.bf16x2.f32 %0, %1, %2;" : "=r"(r) : "f"(hi), "f"(lo)); return r;
}
__device__ __forceinline__ float ex2(float x) { float r; asm("ex2.approx.ftz.f32 %0, %1;" : "=f"(r) : "f"(x)); return r; }
__device__ __forceinline__ void ldsm4(uint32_t a, uint32_t& r0, uint32_t& r1, uint32_t& r2, uint32_t& r3) {
  asm volatile("ldmatrix.sync.aligned.m8n8.x4.shared.b16 {%0,%1,%2,%3}, [%4];" : "=r"(r0), "=r"(r1), "=r"(r2), "=r"(r3) : "r"(a) : "memory");
}
__device__ __forceinline__ void stsm4(uint32_t a, uint32_t r0, uint32_t r1, uint32_t r2, uint32_t r3) {
  asm volatile("stmatrix.sync.aligned.m8n8.x4.shared.b16 [%0], {%1,%2,%3,%4};" ::"r"(a), "r"(r0), "r"(r1), "r"(r2), "r"(r3) : "memory");
}
__device__ __forceinline__ void flag_add(int idx) {
  asm volatile(ELECT("red.release.gpu.global.add.s32 [%0], 1;") ::"l"(g_flags + idx) : "memory");
}
__device__ __forceinline__ void flag_add_rx(int idx) {
  asm volatile(ELECT("red.relaxed.gpu.global.add.s32 [%0], 1;") ::"l"(g_flags + idx) : "memory");
}
template <bool ACQ> __device__ __forceinline__ void flag_wait(int idx, int target) {
  int n = 0;
  while (true) {
    int v;
    if (ACQ) asm volatile("ld.acquire.gpu.global.s32 %0, [%1];" : "=r"(v) : "l"(g_flags + idx) : "memory");
    else asm volatile("ld.relaxed.gpu.global.s32 %0, [%1];" : "=r"(v) : "l"(g_flags + idx) : "memory");
    if (__all_sync(0xffffffffu, v >= target)) break;
    if (++n > 20000000) __trap();
    __nanosleep(64);
  }
}
__device__ __forceinline__ uint32_t desc_lo(uint32_t addr, uint32_t lbo) { return ((addr & 0x3FFFFu) >> 4) | ((lbo >> 4) << 16); }
#define PROF(role, i)
#define PROFX(cond, i)
#define PROFB(i)
#define PROFG(i)

template <int TB, int TA = 0> __device__ __forceinline__ void wgmma_ss64(float (&d)[32], uint32_t alo, uint32_t blo, int sd) {
  asm volatile("{\n.reg .pred p;\n.reg .b64 da, db;\n"
    "setp.ne.b32 p, %34, 0;\nmov.b64 da, {%32, %36};\nmov.b64 db, {%33, %36};\n"
    "wgmma.mma_async.sync.aligned.m64n64k16.f32.bf16.bf16 "
    "{%0,%1,%2,%3,%4,%5,%6,%7,%8,%9,%10,%11,%12,%13,%14,%15,%16,%17,%18,%19,%20,%21,%22,%23,"
    "%24,%25,%26,%27,%28,%29,%30,%31}, "
    "da, db, p, 1, 1, %37, %35;\n}\n"
    : "+f"(d[0]),"+f"(d[1]),"+f"(d[2]),"+f"(d[3]),"+f"(d[4]),"+f"(d[5]),"+f"(d[6]),"+f"(d[7]),"+f"(d[8]),"+f"(d[9]),"+f"(d[10]),"+f"(d[11]),
      "+f"(d[12]),"+f"(d[13]),"+f"(d[14]),"+f"(d[15]),"+f"(d[16]),"+f"(d[17]),"+f"(d[18]),"+f"(d[19]),"+f"(d[20]),"+f"(d[21]),"+f"(d[22]),"+f"(d[23]),
      "+f"(d[24]),"+f"(d[25]),"+f"(d[26]),"+f"(d[27]),"+f"(d[28]),"+f"(d[29]),"+f"(d[30]),"+f"(d[31])
    : "r"(alo), "r"(blo), "r"(sd), "n"(TB), "r"(DESC_HI), "n"(TA));
}
template <int TB, int TA = 0> __device__ __forceinline__ void wgmma_ss128(float (&d)[64], uint32_t alo, uint32_t blo, int sd) {
  asm volatile("{\n.reg .pred p;\n.reg .b64 da, db;\n"
    "setp.ne.b32 p, %66, 0;\nmov.b64 da, {%64, %68};\nmov.b64 db, {%65, %68};\n"
    "wgmma.mma_async.sync.aligned.m64n128k16.f32.bf16.bf16 "
    "{%0,%1,%2,%3,%4,%5,%6,%7,%8,%9,%10,%11,%12,%13,%14,%15,%16,%17,%18,%19,%20,%21,%22,%23,"
    "%24,%25,%26,%27,%28,%29,%30,%31,%32,%33,%34,%35,%36,%37,%38,%39,%40,%41,%42,%43,%44,%45,%46,%47,"
    "%48,%49,%50,%51,%52,%53,%54,%55,%56,%57,%58,%59,%60,%61,%62,%63}, "
    "da, db, p, 1, 1, %69, %67;\n}\n"
    : "+f"(d[0]),"+f"(d[1]),"+f"(d[2]),"+f"(d[3]),"+f"(d[4]),"+f"(d[5]),"+f"(d[6]),"+f"(d[7]),"+f"(d[8]),"+f"(d[9]),"+f"(d[10]),"+f"(d[11]),
      "+f"(d[12]),"+f"(d[13]),"+f"(d[14]),"+f"(d[15]),"+f"(d[16]),"+f"(d[17]),"+f"(d[18]),"+f"(d[19]),"+f"(d[20]),"+f"(d[21]),"+f"(d[22]),"+f"(d[23]),
      "+f"(d[24]),"+f"(d[25]),"+f"(d[26]),"+f"(d[27]),"+f"(d[28]),"+f"(d[29]),"+f"(d[30]),"+f"(d[31]),"+f"(d[32]),"+f"(d[33]),"+f"(d[34]),"+f"(d[35]),
      "+f"(d[36]),"+f"(d[37]),"+f"(d[38]),"+f"(d[39]),"+f"(d[40]),"+f"(d[41]),"+f"(d[42]),"+f"(d[43]),"+f"(d[44]),"+f"(d[45]),"+f"(d[46]),"+f"(d[47]),
      "+f"(d[48]),"+f"(d[49]),"+f"(d[50]),"+f"(d[51]),"+f"(d[52]),"+f"(d[53]),"+f"(d[54]),"+f"(d[55]),"+f"(d[56]),"+f"(d[57]),"+f"(d[58]),"+f"(d[59]),
      "+f"(d[60]),"+f"(d[61]),"+f"(d[62]),"+f"(d[63])
    : "r"(alo), "r"(blo), "r"(sd), "n"(TB), "r"(DESC_HI), "n"(TA));
}
template <int TB> __device__ __forceinline__ void wgmma_rs128(float (&d)[64], uint32_t a0, uint32_t a1, uint32_t a2, uint32_t a3, uint32_t blo, int sd) {
  asm volatile("{\n.reg .pred p;\n.reg .b64 db;\n"
    "setp.ne.b32 p, %69, 0;\nmov.b64 db, {%68, %71};\n"
    "wgmma.mma_async.sync.aligned.m64n128k16.f32.bf16.bf16 "
    "{%0,%1,%2,%3,%4,%5,%6,%7,%8,%9,%10,%11,%12,%13,%14,%15,%16,%17,%18,%19,%20,%21,%22,%23,"
    "%24,%25,%26,%27,%28,%29,%30,%31,%32,%33,%34,%35,%36,%37,%38,%39,%40,%41,%42,%43,%44,%45,%46,%47,"
    "%48,%49,%50,%51,%52,%53,%54,%55,%56,%57,%58,%59,%60,%61,%62,%63}, "
    "{%64,%65,%66,%67}, db, p, 1, 1, %70;\n}\n"
    : "+f"(d[0]),"+f"(d[1]),"+f"(d[2]),"+f"(d[3]),"+f"(d[4]),"+f"(d[5]),"+f"(d[6]),"+f"(d[7]),"+f"(d[8]),"+f"(d[9]),"+f"(d[10]),"+f"(d[11]),
      "+f"(d[12]),"+f"(d[13]),"+f"(d[14]),"+f"(d[15]),"+f"(d[16]),"+f"(d[17]),"+f"(d[18]),"+f"(d[19]),"+f"(d[20]),"+f"(d[21]),"+f"(d[22]),"+f"(d[23]),
      "+f"(d[24]),"+f"(d[25]),"+f"(d[26]),"+f"(d[27]),"+f"(d[28]),"+f"(d[29]),"+f"(d[30]),"+f"(d[31]),"+f"(d[32]),"+f"(d[33]),"+f"(d[34]),"+f"(d[35]),
      "+f"(d[36]),"+f"(d[37]),"+f"(d[38]),"+f"(d[39]),"+f"(d[40]),"+f"(d[41]),"+f"(d[42]),"+f"(d[43]),"+f"(d[44]),"+f"(d[45]),"+f"(d[46]),"+f"(d[47]),
      "+f"(d[48]),"+f"(d[49]),"+f"(d[50]),"+f"(d[51]),"+f"(d[52]),"+f"(d[53]),"+f"(d[54]),"+f"(d[55]),"+f"(d[56]),"+f"(d[57]),"+f"(d[58]),"+f"(d[59]),
      "+f"(d[60]),"+f"(d[61]),"+f"(d[62]),"+f"(d[63])
    : "r"(a0), "r"(a1), "r"(a2), "r"(a3), "r"(blo), "r"(sd), "n"(TB), "r"(DESC_HI));
}
template <int TB, int TA = 0> __device__ __forceinline__ void wgmma_ss192(float (&d)[96], uint32_t alo, uint32_t blo, int sd) {
  asm volatile("{\n.reg .pred p;\n.reg .b64 da, db;\n"
    "setp.ne.b32 p, %98, 0;\nmov.b64 da, {%96, %100};\nmov.b64 db, {%97, %100};\n"
    "wgmma.mma_async.sync.aligned.m64n192k16.f32.bf16.bf16 "
    "{%0,%1,%2,%3,%4,%5,%6,%7,%8,%9,%10,%11,%12,%13,%14,%15,%16,%17,%18,%19,%20,%21,%22,%23,"
    "%24,%25,%26,%27,%28,%29,%30,%31,%32,%33,%34,%35,%36,%37,%38,%39,%40,%41,%42,%43,%44,%45,%46,%47,"
    "%48,%49,%50,%51,%52,%53,%54,%55,%56,%57,%58,%59,%60,%61,%62,%63,%64,%65,%66,%67,%68,%69,%70,%71,"
    "%72,%73,%74,%75,%76,%77,%78,%79,%80,%81,%82,%83,%84,%85,%86,%87,%88,%89,%90,%91,%92,%93,%94,%95}, "
    "da, db, p, 1, 1, %101, %99;\n}\n"
    : "+f"(d[0]),"+f"(d[1]),"+f"(d[2]),"+f"(d[3]),"+f"(d[4]),"+f"(d[5]),"+f"(d[6]),"+f"(d[7]),"+f"(d[8]),"+f"(d[9]),"+f"(d[10]),"+f"(d[11]),
      "+f"(d[12]),"+f"(d[13]),"+f"(d[14]),"+f"(d[15]),"+f"(d[16]),"+f"(d[17]),"+f"(d[18]),"+f"(d[19]),"+f"(d[20]),"+f"(d[21]),"+f"(d[22]),"+f"(d[23]),
      "+f"(d[24]),"+f"(d[25]),"+f"(d[26]),"+f"(d[27]),"+f"(d[28]),"+f"(d[29]),"+f"(d[30]),"+f"(d[31]),"+f"(d[32]),"+f"(d[33]),"+f"(d[34]),"+f"(d[35]),
      "+f"(d[36]),"+f"(d[37]),"+f"(d[38]),"+f"(d[39]),"+f"(d[40]),"+f"(d[41]),"+f"(d[42]),"+f"(d[43]),"+f"(d[44]),"+f"(d[45]),"+f"(d[46]),"+f"(d[47]),
      "+f"(d[48]),"+f"(d[49]),"+f"(d[50]),"+f"(d[51]),"+f"(d[52]),"+f"(d[53]),"+f"(d[54]),"+f"(d[55]),"+f"(d[56]),"+f"(d[57]),"+f"(d[58]),"+f"(d[59]),
      "+f"(d[60]),"+f"(d[61]),"+f"(d[62]),"+f"(d[63]),"+f"(d[64]),"+f"(d[65]),"+f"(d[66]),"+f"(d[67]),"+f"(d[68]),"+f"(d[69]),"+f"(d[70]),"+f"(d[71]),
      "+f"(d[72]),"+f"(d[73]),"+f"(d[74]),"+f"(d[75]),"+f"(d[76]),"+f"(d[77]),"+f"(d[78]),"+f"(d[79]),"+f"(d[80]),"+f"(d[81]),"+f"(d[82]),"+f"(d[83]),
      "+f"(d[84]),"+f"(d[85]),"+f"(d[86]),"+f"(d[87]),"+f"(d[88]),"+f"(d[89]),"+f"(d[90]),"+f"(d[91]),"+f"(d[92]),"+f"(d[93]),"+f"(d[94]),"+f"(d[95])
    : "r"(alo), "r"(blo), "r"(sd), "n"(TB), "r"(DESC_HI), "n"(TA));
}

struct Ctx {
  uint32_t sm;
  uint32_t bar;
  uint32_t rbar;
  int cl, rank, wg, warp, lane;
};
__device__ __forceinline__ void release(const Ctx& c, int b, int cnt = 1) {
  if (c.lane < 2) mbar_arrive_cl(c.rbar + b * 8, cnt);
}
constexpr int PF1 = 1;
constexpr float SM_SCALE = 0.08838834764831845f * 1.4426950408889634f;
constexpr float SM_HI = 1.8446744e19f, SM_LO = 5.4210109e-20f;
constexpr int ORDER = 1;

__device__ __forceinline__ void stage_tile(const float (&a)[64], uint32_t buf, const Ctx& c, float s0, float s1) {
  const int row = (c.lane & 7) + ((c.lane >> 3) & 1) * 8;
  const uint32_t base = buf + (c.warp * 16 + row) * 128 + (((c.lane >> 4) ^ (row & 7)) << 4);
#pragma unroll
  for (int i = 0; i < 8; i++)
    stsm4((base ^ ((i & 3) << 5)) + (i >> 2) * 8192, pack_bf16(a[8 * i] * s0, a[8 * i + 1] * s0), pack_bf16(a[8 * i + 2] * s1, a[8 * i + 3] * s1),
          pack_bf16(a[8 * i + 4] * s0, a[8 * i + 5] * s0), pack_bf16(a[8 * i + 6] * s1, a[8 * i + 7] * s1));
}

__device__ __forceinline__ void p1_epilogue(const Params& p, const Ctx& c, const float (&acc)[64], int t, int type) {
  const int tile = p.s.r[c.cl].tile[t], b = c.wg * 2 + 1;
  mbar_wait(c.bar + (B_SE + b) * 8, (t & 1) ^ 1);
  if (type && tile >= 32) {
    const int r = 2 * (c.lane & 3) + ((c.lane >> 2) & 1);
    const uint32_t dst = c.sm + SM_BUF + b * 16384 + r * 128 + (((c.warp * 2) ^ r) << 4) + (c.lane >> 3) * 4;
#pragma unroll
    for (int i = 0; i < 16; i++) {
      asm volatile("st.shared.u32 [%0], %1;" ::"r"(dst + i * 1024), "r"(pack_bf16(acc[4 * i], acc[4 * i + 1])) : "memory");
      asm volatile("st.shared.u32 [%0], %1;" ::"r"((dst ^ 16) + i * 1024), "r"(pack_bf16(acc[4 * i + 2], acc[4 * i + 3])) : "memory");
    }
  } else {
    const float sc = type ? SM_SCALE : 1.f;
    stage_tile(acc, c.sm + SM_BUF + b * 16384, c, sc, sc);
  }
  FENCE_ASYNC_SMEM();
  __syncwarp();
  if (c.lane == 0) mbar_arrive(c.bar + (B_SF + b) * 8);
}

__device__ __forceinline__ void p1_consumer(const Params& p, const Ctx& c) {
  const int n = p.s.r[c.cl].n1;
  const int type = p.s.r[c.cl].slab >> 3;
  const uint32_t bdesc = desc_lo(c.sm + SM_RING, 8192), adesc = desc_lo(c.sm + SM_BUF + 32768 + c.wg * 8192, 16);
  uint32_t A[128];
  float acc[64] = {};
  int slot = 0, par = 0;
  auto next = [&]() { if (++slot == 10) { slot = 0; par ^= 1; } };
  {
    const int row = (c.lane & 7) + ((c.lane >> 3) & 1) * 8;
    const uint32_t base = c.sm + SM_RING + (c.wg * 64 + c.warp * 16 + row) * 128 + (((c.lane >> 4) ^ (row & 7)) << 4);
    if (type) {
      mbar_wait(c.bar + B_P1F * 8, 0);
      WG_FENCE();
#pragma unroll
      for (int kk = 0; kk < 4; kk++) wgmma_ss128<1>(acc, adesc + kk * 2, bdesc + kk * 128, kk != 0);
      WG_COMMIT();
      WG_WAIT(0);
      release(c, B_P1E);
      slot = 1;
    }
#pragma unroll
    for (int kb = 0; kb < 8; kb++) {
      mbar_wait(c.bar + (B_P1F + slot) * 8, par);
#pragma unroll
      for (int kk = 0; kk < 4; kk++) ldsm4((base ^ (kk << 5)) + slot * 16384, A[kb * 16 + kk * 4], A[kb * 16 + kk * 4 + 1], A[kb * 16 + kk * 4 + 2], A[kb * 16 + kk * 4 + 3]);
      __syncwarp();
      PROF(c.wg, 5 + 2 * kb);
      release(c, B_P1E + slot);
      next();
      mbar_wait(c.bar + (B_P1F + slot) * 8, par);
      PROF(c.wg, 6 + 2 * kb);
      WG_FENCE();
#pragma unroll
      for (int kk = 0; kk < 4; kk++)
        wgmma_rs128<1>(acc, A[kb * 16 + kk * 4], A[kb * 16 + kk * 4 + 1], A[kb * 16 + kk * 4 + 2], A[kb * 16 + kk * 4 + 3], bdesc + slot * 1024 + kk * 128, (kb | kk) != 0 ? 1 : type);
      WG_COMMIT();
      WG_WAIT(0);
      release(c, B_P1E + slot);
      next();
    }
    pin(acc);
    PROF(c.wg, 1);
    p1_epilogue(p, c, acc, 0, type);
    PROF(c.wg, 2);
  }
  for (int t = 1; t < n; t++) {
    bar_sync(ORDER + c.wg, 256);
    int prev1 = -1, prev2 = -1;
    if (type) {
      mbar_wait(c.bar + (B_P1F + slot) * 8, par);
      WG_FENCE();
#pragma unroll
      for (int kk = 0; kk < 4; kk++) wgmma_ss128<1>(acc, adesc + kk * 2, bdesc + slot * 1024 + kk * 128, kk != 0);
      WG_COMMIT();
      prev1 = slot;
      next();
    }
#pragma unroll
    for (int kb = 0; kb < 8; kb++) {
      mbar_wait(c.bar + (B_P1F + slot) * 8, par);
      WG_FENCE();
      const uint32_t d = bdesc + slot * 1024;
#pragma unroll
      for (int kk = 0; kk < 4; kk++)
        wgmma_rs128<1>(acc, A[kb * 16 + kk * 4], A[kb * 16 + kk * 4 + 1], A[kb * 16 + kk * 4 + 2], A[kb * 16 + kk * 4 + 3], d + kk * 128, (kb | kk) != 0 ? 1 : type);
      WG_COMMIT();
      if (kb == 7) {
        if (t + 1 < n || c.wg == 0) bar_arrive(ORDER + (c.wg ^ 1), 256);
        else if (c.lane == 0) mbar_arrive(c.bar + B_P2F * 8);
      }
      if (kb > 0) { WG_WAIT(2); if (kb > 1 || prev2 >= 0) release(c, B_P1E + prev2); }
      prev2 = prev1; prev1 = slot;
      next();
    }
    WG_WAIT(1);
    release(c, B_P1E + prev2);
    WG_WAIT(0);
    pin(acc);
    release(c, B_P1E + prev1);
    p1_epilogue(p, c, acc, t, type);
    PROF(c.wg, 3);
  }
}

__device__ __forceinline__ void p1_producer(const Params& p, const Ctx& c) {
  const int n = p.s.r[c.cl].n1;
  const int type = p.s.r[c.cl].slab >> 3, grp = p.s.r[c.cl].slab & 7;
  int slot = 0, par = 1;
#pragma unroll 1
  for (int t = 0; t < n; t++) {
    const int tile = p.s.r[c.cl].tile[t];
    const CUtensorMap* m = &p.map_w[type * 2 + (tile >> 5)];
    const int n0 = (tile & 31) * 128 + c.rank * 64;
    const int ptile = p.s.r[c.cl].tile[t + PF1 < n ? t + PF1 : t];
    const CUtensorMap* pm = &p.map_w[type * 2 + (ptile >> 5)];
#pragma unroll 1
    for (int kb = -type; kb < 8; kb++) {
      if (t == 0) {
        mbar_wait(c.bar + (B_P1E + slot) * 8, par);
        mbar_expect(c.bar + (B_P1F + slot) * 8, kb < 0 ? 32768 : 16384);
        tma2d(kb < 0 ? c.sm + SM_BUF + 32768 : c.sm + SM_RING + slot * 16384, &p.map_a[type], kb < 0 ? 512 : kb * 64, grp * 256 + c.rank * 128, c.bar + (B_P1F + slot) * 8);
        if (kb >= 0 && ++slot == 10) { slot = 0; par ^= 1; }
      }
      mbar_wait(c.bar + (B_P1E + slot) * 8, par);
      if (t > 0 || kb >= 0) mbar_expect(c.bar + (B_P1F + slot) * 8, 16384);
      tma2d_mc(c.sm + SM_RING + slot * 16384 + c.rank * 8192, m, n0, kb < 0 ? 512 : kb * 64, c.bar + (B_P1F + slot) * 8);
      if (t == 0 && kb == 0) PROF(2, 61);
      if (t == 0 && kb == 3) PROF(2, 62);
      if (t + PF1 < n && (t > 0 || kb >= 3)) tma2d_prefetch(pm, (ptile & 31) * 128 + c.rank * 64, kb < 0 ? 512 : kb * 64);
      if (++slot == 10) { slot = 0; par ^= 1; }
    }
  }
}

__device__ __forceinline__ void p1_storer(const Params& p, const Ctx& c) {
  const int n = p.s.r[c.cl].n1;
  const int type = p.s.r[c.cl].slab >> 3, grp = p.s.r[c.cl].slab & 7;
  int pf = -1;
  for (int i = 0; i < 2 * n; i++) {
    const int t = i >> 1, w = i & 1, b = w * 2 + 1;
    const int tile = p.s.r[c.cl].tile[t];
    mbar_wait(c.bar + (B_SF + b) * 8, t & 1);
    const uint32_t src = c.sm + SM_BUF + b * 16384;
    int f = F_HEAD + (tile & 31);
    if (type == 0) {
      uint8_t* dst = g_KV + (size_t)(tile * 16 + grp * 2 + c.rank) * 32768 + w * 8192;
      bulk_store(dst, src, 8192);
      bulk_store(dst + 16384, src + 8192, 8192);
    } else if (tile < 32) {
      bulk_store(g_Q + (size_t)(tile * 32 + grp * 4 + c.rank * 2 + w) * 16384, src, 16384);
    } else {
      tma3d_store(&p.map_t[2], src, 8 + (grp * 4 + c.rank * 2 + w) * 32, 0, (tile - 32) * 64);
      f = F_QKVA + grp * 4 + ((0xE4390900u >> (2 * (tile - 30))) & 3);
    }
    BULK_COMMIT();
    BULK_WAIT_READ(0);
    mbar_arrive_one(c.bar + (B_SE + b) * 8);
    if (pf >= 0) {
      BULK_WAIT(1);
      flag_add_rx(pf);
    }
    pf = f;
  }
  BULK_WAIT(0);
  flag_add_rx(pf);
}

__device__ __forceinline__ int p2_buf(int w, int i) { return w * 2 + ((i ^ w ^ 1) & 1); }
__device__ __forceinline__ int p2_blk(int rank, int w, int i) { return ((i ^ w) & 1) == 0 ? 3 - rank : rank; }

template <int N>
__device__ __forceinline__ void row_max(const float (&s)[N], float& m0, float& m1) {
  float a0 = fmaxf(s[0], s[1]), a1 = fmaxf(s[2], s[3]);
#pragma unroll
  for (int i = 1; i < N / 4; i++) {
    m0 = fmaxf(m0, s[4 * i]); a0 = fmaxf(a0, s[4 * i + 1]);
    m1 = fmaxf(m1, s[4 * i + 2]); a1 = fmaxf(a1, s[4 * i + 3]);
  }
  m0 = fmaxf(m0, a0); m1 = fmaxf(m1, a1);
  m0 = fmaxf(m0, __shfl_xor_sync(0xffffffffu, m0, 1));
  m1 = fmaxf(m1, __shfl_xor_sync(0xffffffffu, m1, 1));
  m0 = fmaxf(m0, __shfl_xor_sync(0xffffffffu, m0, 2));
  m1 = fmaxf(m1, __shfl_xor_sync(0xffffffffu, m1, 2));
}
template <bool SUB, int N>
__device__ __forceinline__ void row_exp(const float (&s)[N], uint32_t (&P)[32], float m0, float m1, float& t0, float& t1) {
  float u0 = 0.f, u1 = 0.f;
  t0 = t1 = 0.f;
#pragma unroll
  for (int i = 0; i < N / 4; i++) {
    const float e0 = ex2(SUB ? s[4 * i] - m0 : s[4 * i]), e1 = ex2(SUB ? s[4 * i + 1] - m0 : s[4 * i + 1]);
    const float e2 = ex2(SUB ? s[4 * i + 2] - m1 : s[4 * i + 2]), e3 = ex2(SUB ? s[4 * i + 3] - m1 : s[4 * i + 3]);
    if (i == 0) { t0 = e0; u0 = e1; t1 = e2; u1 = e3; }
    else { t0 += e0; u0 += e1; t1 += e2; u1 += e3; }
    P[2 * i] = pack_bf16(e0, e1);
    P[2 * i + 1] = pack_bf16(e2, e3);
  }
#pragma unroll
  for (int i = N / 2; i < 32; i++) P[i] = 0;
  pin(P);
  t0 += u0; t1 += u1;
}
template <int N>
__device__ __forceinline__ void causal_mask(float (&s)[N], int thr) {
#pragma unroll
  for (int i = 0; i < 8; i++) {
    if (8 * i > thr) s[N - 32 + 4 * i] = -INFINITY;
    if (8 * i + 1 > thr) s[N - 32 + 4 * i + 1] = -INFINITY;
    if (8 * i - 8 > thr) s[N - 32 + 4 * i + 2] = -INFINITY;
    if (8 * i - 7 > thr) s[N - 32 + 4 * i + 3] = -INFINITY;
  }
}
__device__ __forceinline__ void issue_qk(float (&s)[32], uint32_t qd, uint32_t kd) {
  WG_FENCE();
#pragma unroll
  for (int kk = 0; kk < 8; kk++) wgmma_ss64<0>(s, qd + (kk >> 2) * 512 + (kk & 3) * 2, kd + (kk >> 2) * 1024 + (kk & 3) * 2, kk != 0);
  WG_COMMIT();
}
__device__ __forceinline__ void issue_qk(float (&s)[64], uint32_t qd, uint32_t kd) {
  WG_FENCE();
#pragma unroll
  for (int kk = 0; kk < 8; kk++) wgmma_ss128<0>(s, qd + (kk >> 2) * 512 + (kk & 3) * 2, kd + (kk >> 2) * 1024 + (kk & 3) * 2, kk != 0);
  WG_COMMIT();
}
template <int NK>
__device__ __forceinline__ void issue_pv(float (&o)[64], const uint32_t (&P)[32], uint32_t vd, int acc) {
  WG_FENCE();
#pragma unroll
  for (int kk = 0; kk < NK; kk++) wgmma_rs128<1>(o, P[4 * kk], P[4 * kk + 1], P[4 * kk + 2], P[4 * kk + 3], vd + kk * 128, kk != 0 ? 1 : acc);
  WG_COMMIT();
}
__device__ __forceinline__ void p2_epilogue(const float (&o)[64], float s0, float s1, const Ctx& c, int b) {
  stage_tile(o, c.sm + SM_BUF + b * 16384, c, s0, s1);
  FENCE_ASYNC_SMEM();
  __syncwarp();
  if (c.lane == 0) mbar_arrive(c.bar + (B_SF + b) * 8);
}

struct P2State {
  float m0, m1, l0, l1;
  bool shift;
  float e0, e1;
  int row0;
  int ks;
  int wi, ai;
  uint32_t wb, ab;
  uint32_t qd;
};
__device__ __forceinline__ int wrap5(int q) { return q >= 5 ? q - 5 : q; }
__device__ __forceinline__ void turn_wait(uint32_t ring, int i) { mbar_wait(ring + (i & 3) * 8, (i >> 2) & 1); }
__device__ __forceinline__ void turn_pass(const Ctx& c, uint32_t ring, int i) { if (c.lane == 0) mbar_arrive(ring + (i & 3) * 8); }
__device__ __forceinline__ void p2_scales(P2State& z, const Ctx& c) {
  const float* g = g_gate + z.row0 + c.warp * 16 + (c.lane >> 2);
  const float g0 = __ldcg(g), g1 = __ldcg(g + 8);
  float l0 = z.l0, l1 = z.l1;
  l0 += __shfl_xor_sync(0xffffffffu, l0, 1);
  l1 += __shfl_xor_sync(0xffffffffu, l1, 1);
  l0 += __shfl_xor_sync(0xffffffffu, l0, 2);
  l1 += __shfl_xor_sync(0xffffffffu, l1, 2);
  z.e0 = __fdividef(1.f - g0, l0); z.e1 = __fdividef(1.f - g1, l1);
}
template <int N, bool PV>
__device__ __forceinline__ void p2_first(const Params& p, const Ctx& c, P2State& z, float (&o)[64], uint32_t (&Pc)[32], uint32_t (&Pn)[32],
                                         int ks, int vs, int cnt, int acc, int row0) {
  float s[N] = {};
  issue_qk(s, z.qd, desc_lo(c.sm + SM_RING, 16) + ks * 2048);
  if (PV) issue_pv<8>(o, Pc, desc_lo(c.sm + SM_RING, 16384) + vs * 2048, acc);
  turn_pass(c, z.ab, z.ai++);
  if (PV) WG_WAIT(1); else WG_WAIT(0);
  pin(s);
  release(c, B_P2E + ks, cnt);
  if (PV) p2_scales(z, c);
  z.row0 = row0;
  causal_mask(s, c.warp * 16 + (c.lane >> 2) - 2 * (c.lane & 3));
  z.m0 = z.m1 = 0.f;
  row_exp<false>(s, Pn, 0.f, 0.f, z.l0, z.l1);
  uint32_t b0 = __ballot_sync(0xffffffffu, z.l0 >= SM_LO), b1 = __ballot_sync(0xffffffffu, z.l1 >= SM_LO);
  b0 |= b0 >> 1; b1 |= b1 >> 1;
  z.shift = __any_sync(0xffffffffu, !(z.l0 + z.l1 <= SM_HI)) || (((b0 | b0 >> 2) & (b1 | b1 >> 2) & 0x11111111u) != 0x11111111u);
  if (__builtin_expect(z.shift, 0)) {
    z.m0 = z.m1 = -INFINITY;
    row_max(s, z.m0, z.m1);
    row_exp<true>(s, Pn, z.m0, z.m1, z.l0, z.l1);
  }
  if (PV) {
    WG_WAIT(0);
    pin(o);
    release(c, B_P2E + vs, 1);
  }
}

template <bool SECOND>
__device__ __forceinline__ void p2_turn(const Ctx& c, P2State& z, float (&o)[64], uint32_t (&Pc)[32], uint32_t (&Pn)[32],
                                        int eb = -1, bool half = false, int vcnt = 1) {
  float s[64] = {};
  const int ks = z.ks, vs = wrap5(ks + 1);
  turn_wait(z.wb, z.wi++);
  issue_qk(s, z.qd, desc_lo(c.sm + SM_RING, 16) + ks * 2048);
  const uint32_t vd = desc_lo(c.sm + SM_RING, 16384) + vs * 2048;
  if (SECOND) {
    if (eb >= 0) p2_epilogue(o, z.e0, z.e1, c, eb);
    if (half) issue_pv<4>(o, Pc, vd, 0); else issue_pv<8>(o, Pc, vd, 0);
  } else {
    issue_pv<8>(o, Pc, vd, 1);
  }
  turn_pass(c, z.ab, z.ai++);
  z.ks = wrap5(ks + 2);
  WG_WAIT(1);
  pin(s);
  release(c, B_P2E + ks, 1);
  float t0, t1, a0 = 1.f, a1 = 1.f;
  row_exp<false>(s, Pn, 0.f, 0.f, t0, t1);
  z.shift = __any_sync(0xffffffffu, z.shift || !(t0 + t1 <= SM_HI));
  const bool redo = z.shift;
  if (__builtin_expect(redo, 0)) {
    float n0 = z.m0, n1 = z.m1;
    row_max(s, n0, n1);
    a0 = ex2(z.m0 - n0); a1 = ex2(z.m1 - n1);
    z.m0 = n0; z.m1 = n1;
    z.l0 *= a0; z.l1 *= a1;
    row_exp<true>(s, Pn, z.m0, z.m1, t0, t1);
  }
  WG_WAIT(0);
  pin(o);
  release(c, B_P2E + vs, vcnt);
  if (__builtin_expect(redo, 0)) {
#pragma unroll
    for (int i = 0; i < 16; i++) { o[4 * i] *= a0; o[4 * i + 1] *= a0; o[4 * i + 2] *= a1; o[4 * i + 3] *= a1; }
  }
  z.l0 += t0; z.l1 += t1;
}
__device__ __forceinline__ void copy_p(uint32_t (&d)[32], const uint32_t (&s)[32], int zero) {
#pragma unroll
  for (int i = 0; i < 32; i++) asm volatile("add.s32 %0, %1, %2;" : "=r"(d[i]) : "r"(s[i]), "r"(zero));
}

__device__ __forceinline__ void p2_consumer(const Params& p, const Ctx& c, int rot) {
  const int nit = p.s.r[c.cl].n2;
  const uint32_t fring = c.bar + B_P2F * 8, oring = c.bar + B_ORD * 8;
  float o[64] = {};
  uint32_t Pa[32] = {}, Pb[32] = {};
  P2State z;
  z.e0 = z.e1 = z.l0 = z.l1 = 0.f; z.row0 = 0; z.ks = rot; z.shift = false;
  int acc = 0, n = 0;
  for (int it = 0; it < nit; it++) {
    const int j = p.s.r[c.cl].item[it] & 7, blk = p2_blk(c.rank, c.wg, it), row0 = (j * 4 + blk) * 64;
    const int lng = ((it ^ c.wg) & 1) ^ 1;
    z.qd = desc_lo(c.sm + SM_BUF, 16) + p2_buf(c.wg, it) * 1024;
    if (lng) { z.wb = oring; z.wi = n - it; z.ab = fring; z.ai = n + 1; }
    else { z.wb = fring; z.wi = n + 2; z.ab = oring; z.ai = n - it; }
    mbar_wait(c.bar + (B_QF + p2_buf(c.wg, it)) * 8, (it >> 1) & 1);
    turn_wait(fring, n + 1 - lng);
    if (it == 0) {
      const int ks = wrap5(rot + c.wg);
      if (blk & 1) p2_first<64, false>(p, c, z, o, Pa, Pb, ks, 0, 1 + lng, 0, row0);
      else p2_first<32, false>(p, c, z, o, Pa, Pb, ks, 0, 1 + lng, 0, row0);
      z.ks = wrap5(rot + 1 + 2 * c.wg);
    } else {
      const int vs = wrap5(z.ks + 1), ks = lng ? z.ks : wrap5(z.ks + 2);
      if (blk & 1) p2_first<64, true>(p, c, z, o, Pa, Pb, ks, vs, 1 + lng, acc, row0);
      else p2_first<32, true>(p, c, z, o, Pa, Pb, ks, vs, 1 + lng, acc, row0);
      z.ks = wrap5(ks + 2);
    }
    PROF(c.wg, 24 + it);
    n += 2 * j + 2;
    int left = 2 * j + lng;
    acc = left != 0;
    if (left == 0) { copy_p(Pa, Pb, p.zero); continue; }
    p2_turn<true>(c, z, o, Pb, Pa, it > 0 ? p2_buf(c.wg, it - 1) : -1, !(blk & 1), 1 + lng);
    while (--left > 0) {
      p2_turn<false>(c, z, o, Pa, Pb);
      if (--left == 0) { copy_p(Pa, Pb, p.zero); break; }
      p2_turn<false>(c, z, o, Pb, Pa);
    }
  }
  {
    if (!acc && nit > 1) p2_epilogue(o, z.e0, z.e1, c, p2_buf(c.wg, nit));
    turn_wait(z.wb, z.wi);
    issue_pv<8>(o, Pa, desc_lo(c.sm + SM_RING, 16384) + z.ks * 2048, acc);
    if (((nit - 1) ^ c.wg) & 1) turn_pass(c, z.ab, z.ai);
    p2_scales(z, c);
    WG_WAIT(0);
    pin(o);
    p2_epilogue(o, z.e0, z.e1, c, p2_buf(c.wg, nit - 1));
    PROF(c.wg, 24 + nit);
  }
}

__device__ __forceinline__ void p2_load_q(const Params& p, const Ctx& c, int it, int w) {
  const int item = p.s.r[c.cl].item[it], h = item >> 3, j = item & 7, b = p2_buf(w, it);
  mbar_expect(c.bar + (B_QF + b) * 8, 16384);
  bulk_load(c.sm + SM_BUF + b * 16384, g_Q + (size_t)(h * 32 + j * 4 + p2_blk(c.rank, w, it)) * 16384, 16384, c.bar + (B_QF + b) * 8);
}
__device__ __forceinline__ void p2_producer(const Params& p, const Ctx& c, int u1, int rot) {
  const int nit = p.s.r[c.cl].n2;
  int slot = rot, cnt = 0, par = 1, n = 0;
  const uint8_t* pv = nullptr;
  auto load = [&](const uint8_t* src, int expect) {
    if (cnt < 5) {
      if (u1) {
        mbar_wait(c.bar + (B_P1E + 2 * slot) * 8, ((u1 - 1 - 2 * slot) / 10) & 1);
        mbar_wait(c.bar + (B_P1E + 2 * slot + 1) * 8, ((u1 - 2 - 2 * slot) / 10) & 1);
        if (cnt == 0) p2_load_q(p, c, 0, 1);
      }
      cnt++;
    } else {
      if (slot == rot) par ^= 1;
      mbar_wait(c.bar + (B_P2E + slot) * 8, par);
    }
    const uint32_t fb = c.bar + (B_P2F + (n & 3)) * 8;
    if (expect) mbar_expect(fb, expect);
    bulk_load_mc(c.sm + SM_RING + slot * 32768 + c.rank * 16384, src, 16384, fb);
    if (cnt == 1 && u1) {
      mbar_wait(c.bar + (B_SE + 1) * 8, (p.s.r[c.cl].n1 - 1) & 1);
      p2_load_q(p, c, 0, 0);
    }
    slot = wrap5(slot + 1);
  };
  if (p.phases & 16) flag_wait<true>(F_GATE, 256);
  for (int it = 0; it < nit; it++) {
    const int item = p.s.r[c.cl].item[it], h = item >> 3, j = item & 7;
    if (p.phases & 16) flag_wait<false>(F_HEAD + h, 96);
    if (it == 0 && !u1) { p2_load_q(p, c, 0, 0); p2_load_q(p, c, 0, 1); }
    for (int t = 2 * j + 1; t >= 0; t--) {
      const uint8_t* k = g_KV + (size_t)(h * 16 + t) * 32768 + c.rank * 16384;
      load(k, pv ? 65536 : 32768);
      if (pv) load(pv, 0);
      pv = k + (size_t)NH * 16 * 32768;
      n++;
    }
  }
  load(pv, 32768);
}

__device__ __forceinline__ void p2_storer(const Params& p, const Ctx& c, int sfpar) {
  const int nit = p.s.r[c.cl].n2;
  auto load_q = [&](int it, int w) {
    if (p.phases & 16) flag_wait<false>(F_HEAD + (p.s.r[c.cl].item[it] >> 3), 96);
    p2_load_q(p, c, it, w);
  };
  if (nit > 1) { load_q(1, 1); mbar_wait(c.bar + B_LAD * 8, 0); p2_load_q(p, c, 1, 0); }
  for (int i = 0; i < 2 * nit; i++) {
    const int it = i >> 1, w = (it ^ i ^ 1) & 1, b = p2_buf(w, it);
    const int item = p.s.r[c.cl].item[it], h = item >> 3, j = item & 7;
    mbar_wait(c.bar + (B_SF + b) * 8, (sfpar >> b) & 1);
    sfpar ^= 1 << b;
    bulk_store(g_Q + (size_t)(h * 32 + j * 4 + p2_blk(c.rank, w, it)) * 16384, c.sm + SM_BUF + b * 16384, 16384);
    BULK_COMMIT();
    if (it + 2 < nit) { BULK_WAIT_READ(0); load_q(it + 2, w); }
    BULK_WAIT(0);
    flag_add_rx(F_CTX + j * 64 + h);
  }
}

__device__ __forceinline__ void p3_consumer(const Params& p, const Ctx& c) {
  const int tile = p.s.r[c.cl].p3, j = tile / 3, nt = tile - 3 * j;
  const uint32_t ad = desc_lo(c.sm + SM_RING + c.wg * 8192, 16), bd = desc_lo(c.sm + SM_RING + 16384, 4096);
  float acc[96] = {};
  int slot = 0, par = 0, prev = 0;
#pragma unroll 1
  for (int kb = 0; kb < 9; kb++) {
    mbar_wait(c.bar + (B_P3F + slot) * 8, par);
    if (kb == 0) PROF(c.wg, 39);
    WG_FENCE();
#pragma unroll
    for (int kk = 0; kk < 4; kk++) wgmma_ss192<1, 1>(acc, ad + slot * 2560 + kk * 128, bd + slot * 2560 + (kk >> 1) * 768 + (kk & 1) * 128, kk != 0 ? 1 : kb != 0);
    WG_COMMIT();
    WG_WAIT(1);
    if (kb > 0) release(c, B_P3E + prev);
    prev = slot;
    if (++slot == 5) { slot = 0; par ^= 1; }
  }
#pragma unroll 1
  for (int kb = 9; kb < NKB3; kb++) {
    mbar_wait(c.bar + (B_P3F + slot) * 8, par);
    WG_FENCE();
#pragma unroll
    for (int kk = 0; kk < 4; kk++) wgmma_ss192<1>(acc, ad + slot * 2560 + kk * 2, bd + slot * 2560 + (kk >> 1) * 768 + (kk & 1) * 128, 1);
    WG_COMMIT();
    WG_WAIT(1);
    release(c, B_P3E + prev);
    prev = slot;
    if (++slot == 5) { slot = 0; par ^= 1; }
  }
  WG_WAIT(0);
  pin(acc);
  PROF(c.wg, 40);
  const int row = (c.lane & 7) + ((c.lane >> 3) & 1) * 8;
  const uint32_t wbase = c.sm + SM_RING + c.wg * 8192 + c.warp * 2048;
  const uint32_t base = wbase + row * 128 + (((c.lane >> 4) ^ (row & 7)) << 4);
#pragma unroll
  for (int i = 0; i < 12; i++)
    stsm4((base ^ ((i & 3) << 5)) + (i >> 2) * 40960, pack_bf16(acc[8 * i], acc[8 * i + 1]), pack_bf16(acc[8 * i + 2], acc[8 * i + 3]),
          pack_bf16(acc[8 * i + 4], acc[8 * i + 5]), pack_bf16(acc[8 * i + 6], acc[8 * i + 7]));
  FENCE_ASYNC_SMEM();
  __syncwarp();
#pragma unroll
  for (int i = 0; i < 3; i++) tma2d_store(&p.map_out, wbase + i * 40960, nt * 192 + i * 64, j * 256 + c.rank * 128 + c.wg * 64 + c.warp * 16);
  BULK_COMMIT();
  BULK_WAIT_READ(0);
}

__device__ __forceinline__ void p3_producer(const Params& p, const Ctx& c) {
  const int tile = p.s.r[c.cl].p3, j = tile / 3, nt = tile - 3 * j;
  int slot = 0, par = 0;
  for (int q = -1; q < 32; q++) {
    const int g = q < 0 ? 32 : p.s.p3_order[j][q];
    if (p.phases & 16) flag_wait<false>(F_CTX + j * 64 + g, q < 0 ? 32 : 4);
    const int nk = q < 0 ? 9 : 2, k0 = (q < 0 ? 0 : g * 128) + c.rank * 32;
    const uint8_t* a = q < 0 ? g_oA + (j * 4 + c.rank * 2) * 73728 : g_Q + (size_t)(g * 32 + j * 4 + c.rank * 2) * 16384;
    const CUtensorMap* m = &p.map_o[q < 0];
    for (int i = 0; i < nk; i++) {
      const uint32_t st = c.sm + SM_RING + slot * 40960, fb = c.bar + (B_P3F + slot) * 8;
      mbar_wait(c.bar + (B_P3E + slot) * 8, par);
      mbar_expect(fb, 40960);
      bulk_load(st, a + i * 8192, 8192, fb);
      bulk_load(st + 8192, a + (nk + i) * 8192, 8192, fb);
      tma3d_mc(st + 16384 + c.rank * 12288, m, 0, k0 + i * 64, nt * 3, fb);
      if (++slot == 5) { slot = 0; par ^= 1; }
    }
  }
}

__device__ __forceinline__ float bf_lo(uint32_t w) { return __uint_as_float(w << 16); }
__device__ __forceinline__ float bf_hi(uint32_t w) { return __uint_as_float(w & 0xffff0000u); }

__device__ __forceinline__ void gate_row(const Params& p, int row, int lane) {
  const uint32_t* x = reinterpret_cast<const uint32_t*>(p.x + (size_t)row * DM);
  const uint32_t* w = reinterpret_cast<const uint32_t*>(p.gate_w);
  float a = 0.f;
#pragma unroll
  for (int i = 0; i < 9; i++) {
    const uint32_t u = __ldg(x + i * 32 + lane), v = __ldg(w + i * 32 + lane);
    a = fmaf(bf_lo(u), bf_lo(v), a);
    a = fmaf(bf_hi(u), bf_hi(v), a);
  }
#pragma unroll
  for (int o = 16; o > 0; o >>= 1) a += __shfl_xor_sync(0xffffffffu, a, o);
  if (lane == 0) g_gate[row] = 1.f / (1.f + __expf(-a));
}

__device__ __forceinline__ void lds10(uint32_t (&k)[10], uint32_t a) {
  asm volatile("ld.shared.v2.u32 {%0, %1}, [%10];\nld.shared.v2.u32 {%2, %3}, [%10+8];\nld.shared.v2.u32 {%4, %5}, [%10+16];\n"
               "ld.shared.v2.u32 {%6, %7}, [%10+24];\nld.shared.v2.u32 {%8, %9}, [%10+32];"
               : "=r"(k[0]), "=r"(k[1]), "=r"(k[2]), "=r"(k[3]), "=r"(k[4]), "=r"(k[5]), "=r"(k[6]), "=r"(k[7]), "=r"(k[8]), "=r"(k[9]) : "r"(a));
}
__device__ __forceinline__ void local_attn(const Params& p, const Ctx& c, int rb, int hs) {
  const int lane = c.lane, grp = rb >> 2, par = lane >> 4, i0 = 2 * (lane & 15);
  const uint32_t buf = c.sm + SM_BUF + (c.warp - 2) * 8192, bqk = c.bar + (B_LA + (c.warp - 2) * 2) * 8, bv = bqk + 8;
  const uint32_t mine = buf + 2304 + par * 160 + i0 * 4;
  const bool flags = p.phases & 16;
  auto fetch_qk = [&](int q) {
    if (flags) {
      const int tgt = q == 0 ? 24 : q == 3 ? 8 : 12;
      flag_wait<false>(F_QKVA + (grp - (grp > 0 && (rb & 3) == 0 ? par : 0)) * 4 + q, tgt);
    }
    mbar_expect(bqk, 5184);
    tma3d(buf, &p.map_t[0], rb * 32 + 8, 0, 9 * (8 * q + hs), bqk);
    tma3d(buf + 2304, &p.map_t[1], rb * 32, 0, 288 + 9 * (8 * q + hs), bqk);
  };
  auto fetch_v = [&](int q) { mbar_expect(bv, 2880); tma3d(buf + 5248, &p.map_t[1], rb * 32, 0, 576 + 9 * (8 * q + hs), bv); };
  fetch_qk(0);
  if (flags) flag_wait<true>(F_GATE, 256);
#pragma unroll 1
  for (int q = 0; q < 4; q++) {
    fetch_v(q);
    float a[8], b[8];
#pragma unroll
    for (int w = 0; w < 8; w++) a[w] = b[w] = 0.f;
    mbar_wait(bqk, q & 1);
    PROFB(1 + 2 * q);
#pragma unroll 1
    for (int j = 0; j < 9; j++) {
      uint32_t x, y, k[10];
      asm volatile("ld.shared.v2.u32 {%0, %1}, [%2];" : "=r"(x), "=r"(y) : "r"(buf + lane * 8 + j * 256));
      lds10(k, mine + j * 320);
      const float xl = bf_lo(x), xh = bf_hi(x), yl = bf_lo(y), yh = bf_hi(y);
#pragma unroll
      for (int m = 1; m < 10; m++) {
        const float kl = bf_lo(k[m]), kh = bf_hi(k[m]);
        if (m < 9) a[8 - m] = fmaf(xl, kl, fmaf(xh, kh, a[8 - m]));
        if (m > 1) b[9 - m] = fmaf(yl, kl, fmaf(yh, kh, b[9 - m]));
      }
    }
    __syncwarp();
    if (q < 3) fetch_qk(q + 1);
    constexpr float SC = 0.23570226039551584f * 1.4426950408889634f;
    const float* gp = g_gate + rb * 64 + 2 * i0 + par;
    const float ga = __ldcg(gp), gb = __ldcg(gp + 2);
    float ma = a[0], mb = b[0];
#pragma unroll
    for (int w = 1; w < 8; w++) {
      if (rb == 0) {
        if (i0 < w) a[w] = -INFINITY;
        if (i0 + 1 < w) b[w] = -INFINITY;
      }
      ma = fmaxf(ma, a[w]); mb = fmaxf(mb, b[w]);
    }
    float la = 0.f, lb = 0.f;
#pragma unroll
    for (int w = 0; w < 8; w++) {
      a[w] = ex2((a[w] - ma) * SC); b[w] = ex2((b[w] - mb) * SC);
      la += a[w]; lb += b[w];
    }
    la = __fdividef(ga, la); lb = __fdividef(gb, lb);
#pragma unroll
    for (int w = 0; w < 8; w++) { a[w] *= la; b[w] *= lb; }
    uint8_t* dst = g_oA + rb * 73728 + ((i0 & 2) + par) * 4;
    mbar_wait(bv, q & 1);
#pragma unroll 1
    for (int j = 0; j < 9; j++) {
      uint32_t v[10];
      lds10(v, mine + 2944 + j * 320);
      float a0 = 0.f, a1 = 0.f, b0 = 0.f, b1 = 0.f;
#pragma unroll
      for (int m = 1; m < 10; m++) {
        const float vl = bf_lo(v[m]), vh = bf_hi(v[m]);
        if (m < 9) { a0 = fmaf(a[8 - m], vl, a0); a1 = fmaf(a[8 - m], vh, a1); }
        if (m > 1) { b0 = fmaf(b[9 - m], vl, b0); b1 = fmaf(b[9 - m], vh, b1); }
      }
      const uint32_t wa = pack_bf16(a0, a1), wb = pack_bf16(b0, b1);
      const uint32_t got = __shfl_xor_sync(0xffffffffu, par ? wa : wb, 16);
      const uint32_t r0 = par ? got : wa, r1 = par ? wb : got;
      const int col = 18 * (8 * q + hs) + 2 * j, o = col * 128 + ((((i0 >> 2) ^ col) & 7) << 4);
      *reinterpret_cast<uint32_t*>(dst + o) = __byte_perm(r0, r1, 0x5410);
      *reinterpret_cast<uint32_t*>(dst + ((o + 128) ^ 16)) = __byte_perm(r0, r1, 0x7632);
    }
    __syncwarp();
    PROFB(2 + 2 * q);
  }
  mbar_arrive_one(c.bar + B_LAD * 8);
  flag_add(F_CTX + grp * 64 + 32);
}

__global__ void __cluster_dims__(2, 1, 1) __launch_bounds__(384, 1) fused_kernel(const __grid_constant__ Params p) {
  extern __shared__ uint8_t smem_raw[];
  Ctx c;
  c.sm = ((uint32_t)__cvta_generic_to_shared(smem_raw) + 1023u) & ~1023u;
  c.bar = c.sm + SM_BAR;
  c.lane = threadIdx.x & 31;
  c.wg = __shfl_sync(0xffffffffu, threadIdx.x >> 7, 0);
  c.warp = __shfl_sync(0xffffffffu, (threadIdx.x >> 5) & 3, 0);
  PROF(c.wg, 0);
  PROFG(61);
  c.cl = blockIdx.x >> 1;
  c.rank = blockIdx.x & 1;
  c.rbar = mapa(c.bar, c.lane & 1);
  if (c.wg == 1 && c.lane < 6 && c.warp == 0) asm volatile("prefetch.tensormap [%0];" ::"l"(&p.map_a[0] + c.lane) : "memory");
  const bool do1 = (p.phases & 1) && p.s.r[c.cl].n1 > 0;
  const bool do2 = (p.phases & 2) && p.s.r[c.cl].n2 > 0;
  const bool do3 = (p.phases & 4) && p.s.r[c.cl].p3 != 255;
  const int u1 = do1 ? 8 + p.s.r[c.cl].n1 * (8 + (p.s.r[c.cl].slab >> 3)) : 0;
  const int rot = ((u1 % 10 + 1) >> 1) % 5;
  if (threadIdx.x < B_NUM) {
    const int i = threadIdx.x;
    int cnt = 1;
    if ((i >= B_P1E && i < B_P1E + 10) || (i >= B_P2E && i < B_P2E + 5) || (i >= B_P3E && i < B_P3E + 5)) cnt = 16;
    if (i >= B_P2F && i < B_P2F + 4) cnt = 5;
    if ((i >= B_SF && i < B_SF + 4) || (i >= B_ORD && i < B_ORD + 4)) cnt = 4;
    if (i == B_LAD) cnt = 2;
    if (i == B_FIN) cnt = 8;
    mbar_init(c.bar + i * 8, cnt);
    asm volatile("fence.mbarrier_init.release.cluster;" ::: "memory");
  }
  __syncwarp();
  cluster_sync();

  if (c.wg < 2) {
    PROF(c.wg, 4);
    asm volatile("setmaxnreg.inc.sync.aligned.u32 224;");
    if (c.wg == 1) { if (do1) bar_arrive(ORDER, 256); else if (c.lane == 0) mbar_arrive(c.bar + B_P2F * 8); }
    if (do1) p1_consumer(p, c);
    if (do2) p2_consumer(p, c, rot);
    if (do3) {
      mbar_wait(c.bar + B_DONE * 8, 0);
#pragma unroll
      for (int i = 0; i < 5; i++) release(c, B_P3E + i);
      p3_consumer(p, c);
    }
    PROF(c.wg, 63);
    PROFG(62);
    if (c.lane == 0) mbar_arrive(c.bar + B_FIN * 8);
    __syncwarp();
    cluster_sync();
  } else {
    asm volatile("setmaxnreg.dec.sync.aligned.u32 56;");
    if (c.warp == 0) {
      PROF(2, 60);
      if (do1) p1_producer(p, c);
      if (do2) p2_producer(p, c, u1, rot);
      if (do3) p3_producer(p, c);
    } else if (c.warp == 1) {
      int sfpar = 0;
      if (do1) {
        p1_storer(p, c);
        sfpar = (p.s.r[c.cl].n1 & 1) * 10;
      }
      if (do2) p2_storer(p, c, sfpar);
      mbar_wait(c.bar + B_LAD * 8, 0);
      mbar_arrive_one(c.bar + B_DONE * 8);
    } else {
      const int bw = blockIdx.x * 2 + (c.warp - 2);
      if ((p.phases & 1) && bw < 256) {
        for (int i = 0; i < 8; i++) gate_row(p, bw * 8 + i, c.lane);
        __syncwarp();
        flag_add(F_GATE);
      }
      if ((p.phases & 8) && bw < 256) local_attn(p, c, bw >> 3, bw & 7);
      else if (c.lane == 0) mbar_arrive(c.bar + B_LAD * 8);
    }
    __syncwarp();
    bar_sync(3, 128);
    if (c.warp == 0 && (p.phases & 4)) {
      int last = 0;
      if (c.lane == 0) { __threadfence(); last = atomicAdd(g_flags + F_DONE, 1) == 2 * NCL - 1; }
      if (__shfl_sync(0xffffffffu, last, 0)) for (int i = c.lane; i < F_NUM; i += 32) g_flags[i] = 0;
    }
    if (c.warp == 1) mbar_wait(c.bar + B_FIN * 8, 0);
    __syncwarp();
    cluster_sync();
  }
}

static const Sched k_sched = {
  {{0,24,2,255,{167,228,0,0,0,0,0,0,0,0,0,0},{0,2,4,6,8,10,12,14,16,17,18,19,20,21,22,23,24,25,26,27,28,29,30,31,0,0,0,0,0,0,0,0}},
   {0,24,3,255,{150,234,248,0,0,0,0,0,0,0,0,0},{32,34,36,38,40,42,44,46,48,49,50,51,52,53,54,55,56,57,58,59,60,61,62,63,0,0,0,0,0,0,0,0}},
   {0,8,4,0,{28,92,60,120,0,0,0,0,0,0,0,0},{1,3,5,7,9,11,13,15,0,0,0,0,0,0,0,0,0,0,0,0,0,0,0,0,0,0,0,0,0,0,0,0}},
   {0,8,5,1,{30,49,99,65,104,0,0,0,0,0,0,0},{33,35,37,39,41,43,45,47,0,0,0,0,0,0,0,0,0,0,0,0,0,0,0,0,0,0,0,0,0,0,0,0}},
   {8,22,2,255,{201,183,0,0,0,0,0,0,0,0,0,0},{32,37,43,40,2,6,10,14,18,19,20,21,22,23,24,25,26,27,28,29,30,31,0,0,0,0,0,0,0,0,0,0}},
   {8,8,4,255,{55,158,139,199,0,0,0,0,0,0,0,0},{36,42,35,45,3,7,11,15,0,0,0,0,0,0,0,0,0,0,0,0,0,0,0,0,0,0,0,0,0,0,0,0}},
   {8,8,4,2,{85,83,26,0,0,0,0,0,0,0,0,0},{41,34,39,0,4,8,12,16,0,0,0,0,0,0,0,0,0,0,0,0,0,0,0,0,0,0,0,0,0,0,0,0}},
   {8,8,3,3,{101,114,84,0,0,0,0,0,0,0,0,0},{33,38,44,1,5,9,13,17,0,0,0,0,0,0,0,0,0,0,0,0,0,0,0,0,0,0,0,0,0,0,0,0}},
   {1,24,2,255,{182,205,0,0,0,0,0,0,0,0,0,0},{0,2,4,6,8,10,12,14,16,17,18,19,20,21,22,23,24,25,26,27,28,29,30,31,0,0,0,0,0,0,0,0}},
   {1,24,3,255,{136,215,226,0,0,0,0,0,0,0,0,0},{32,34,36,38,40,42,44,46,48,49,50,51,52,53,54,55,56,57,58,59,60,61,62,63,0,0,0,0,0,0,0,0}},
   {1,8,3,4,{23,41,149,0,0,0,0,0,0,0,0,0},{1,3,5,7,9,11,13,15,0,0,0,0,0,0,0,0,0,0,0,0,0,0,0,0,0,0,0,0,0,0,0,0}},
   {1,8,4,5,{4,100,68,24,0,0,0,0,0,0,0,0},{33,35,37,39,41,43,45,47,0,0,0,0,0,0,0,0,0,0,0,0,0,0,0,0,0,0,0,0,0,0,0,0}},
   {9,22,3,255,{168,186,238,0,0,0,0,0,0,0,0,0},{32,37,43,40,2,6,10,14,18,19,20,21,22,23,24,25,26,27,28,29,30,31,0,0,0,0,0,0,0,0,0,0}},
   {9,8,6,255,{62,119,221,243,249,224,0,0,0,0,0,0},{36,42,35,45,3,7,11,15,0,0,0,0,0,0,0,0,0,0,0,0,0,0,0,0,0,0,0,0,0,0,0,0}},
   {9,8,6,255,{67,34,98,191,173,211,0,0,0,0,0,0},{41,34,39,0,4,8,12,16,0,0,0,0,0,0,0,0,0,0,0,0,0,0,0,0,0,0,0,0,0,0,0,0}},
   {9,8,4,6,{59,141,122,128,0,0,0,0,0,0,0,0},{33,38,44,1,5,9,13,17,0,0,0,0,0,0,0,0,0,0,0,0,0,0,0,0,0,0,0,0,0,0,0,0}},
   {2,25,2,255,{156,236,0,0,0,0,0,0,0,0,0,0},{0,34,5,39,10,12,14,15,16,17,18,19,20,21,22,23,24,25,26,27,28,29,30,31,63,0,0,0,0,0,0,0}},
   {2,23,3,255,{108,198,232,0,0,0,0,0,0,0,0,0},{32,3,37,8,42,44,46,47,48,49,50,51,52,53,54,55,56,57,58,59,60,61,62,0,0,0,0,0,0,0,0,0}},
   {2,6,6,255,{13,109,154,91,171,255,0,0,0,0,0,0},{1,35,6,40,11,13,0,0,0,0,0,0,0,0,0,0,0,0,0,0,0,0,0,0,0,0,0,0,0,0,0,0}},
   {2,4,5,7,{6,73,157,145,80,0,0,0,0,0,0,0},{33,4,38,9,0,0,0,0,0,0,0,0,0,0,0,0,0,0,0,0,0,0,0,0,0,0,0,0,0,0,0,0}},
   {2,6,3,8,{15,111,8,0,0,0,0,0,0,0,0,0},{2,36,7,41,43,45,0,0,0,0,0,0,0,0,0,0,0,0,0,0,0,0,0,0,0,0,0,0,0,0,0,0}},
   {10,22,2,255,{223,210,0,0,0,0,0,0,0,0,0,0},{32,37,43,40,2,6,10,14,18,19,20,21,22,23,24,25,26,27,28,29,30,31,0,0,0,0,0,0,0,0,0,0}},
   {10,8,3,9,{69,134,40,0,0,0,0,0,0,0,0,0},{36,42,35,45,3,7,11,15,0,0,0,0,0,0,0,0,0,0,0,0,0,0,0,0,0,0,0,0,0,0,0,0}},
   {10,8,3,10,{53,102,48,0,0,0,0,0,0,0,0,0},{41,34,39,0,4,8,12,16,0,0,0,0,0,0,0,0,0,0,0,0,0,0,0,0,0,0,0,0,0,0,0,0}},
   {10,8,6,255,{29,130,110,175,209,216,0,0,0,0,0,0},{33,38,44,1,5,9,13,17,0,0,0,0,0,0,0,0,0,0,0,0,0,0,0,0,0,0,0,0,0,0,0,0}},
   {3,26,2,255,{214,251,0,0,0,0,0,0,0,0,0,0},{0,2,4,6,8,10,12,14,16,17,18,19,20,21,22,23,24,25,26,27,28,29,30,62,31,63,0,0,0,0,0,0}},
   {3,22,3,255,{133,252,225,0,0,0,0,0,0,0,0,0},{32,34,36,38,40,42,44,46,48,49,50,51,52,53,54,55,56,57,58,59,60,61,0,0,0,0,0,0,0,0,0,0}},
   {3,8,5,11,{20,25,2,148,88,0,0,0,0,0,0,0},{1,3,5,7,9,11,13,15,0,0,0,0,0,0,0,0,0,0,0,0,0,0,0,0,0,0,0,0,0,0,0,0}},
   {3,8,5,12,{45,115,90,129,16,0,0,0,0,0,0,0},{33,35,37,39,41,43,45,47,0,0,0,0,0,0,0,0,0,0,0,0,0,0,0,0,0,0,0,0,0,0,0,0}},
   {11,22,3,255,{237,202,208,0,0,0,0,0,0,0,0,0},{32,37,43,40,2,6,10,14,18,19,20,21,22,23,24,25,26,27,28,29,30,31,0,0,0,0,0,0,0,0,0,0}},
   {11,8,3,13,{78,170,11,0,0,0,0,0,0,0,0,0},{36,42,35,45,3,7,11,15,0,0,0,0,0,0,0,0,0,0,0,0,0,0,0,0,0,0,0,0,0,0,0,0}},
   {11,8,4,255,{71,131,63,231,0,0,0,0,0,0,0,0},{41,34,39,0,4,8,12,16,0,0,0,0,0,0,0,0,0,0,0,0,0,0,0,0,0,0,0,0,0,0,0,0}},
   {11,8,5,255,{19,3,142,118,188,0,0,0,0,0,0,0},{33,38,44,1,5,9,13,17,0,0,0,0,0,0,0,0,0,0,0,0,0,0,0,0,0,0,0,0,0,0,0,0}},
   {4,24,3,255,{152,165,244,0,0,0,0,0,0,0,0,0},{0,2,4,6,8,10,12,14,16,17,18,19,20,21,22,23,24,25,26,27,28,29,30,31,0,0,0,0,0,0,0,0}},
   {4,24,3,255,{192,212,213,0,0,0,0,0,0,0,0,0},{32,34,36,38,40,42,44,46,48,49,50,51,52,53,54,55,56,57,58,59,60,61,62,63,0,0,0,0,0,0,0,0}},
   {4,8,4,14,{37,113,155,51,0,0,0,0,0,0,0,0},{1,3,5,7,9,11,13,15,0,0,0,0,0,0,0,0,0,0,0,0,0,0,0,0,0,0,0,0,0,0,0,0}},
   {4,8,4,15,{38,50,124,32,0,0,0,0,0,0,0,0},{33,35,37,39,41,43,45,47,0,0,0,0,0,0,0,0,0,0,0,0,0,0,0,0,0,0,0,0,0,0,0,0}},
   {12,22,3,255,{176,166,242,0,0,0,0,0,0,0,0,0},{32,37,43,40,2,6,10,14,18,19,20,21,22,23,24,25,26,27,28,29,30,31,0,0,0,0,0,0,0,0,0,0}},
   {12,8,5,255,{31,74,117,179,190,0,0,0,0,0,0,0},{36,42,35,45,3,7,11,15,0,0,0,0,0,0,0,0,0,0,0,0,0,0,0,0,0,0,0,0,0,0,0,0}},
   {12,8,5,255,{52,9,151,159,220,0,0,0,0,0,0,0},{41,34,39,0,4,8,12,16,0,0,0,0,0,0,0,0,0,0,0,0,0,0,0,0,0,0,0,0,0,0,0,0}},
   {12,8,5,255,{77,36,66,135,229,0,0,0,0,0,0,0},{33,38,44,1,5,9,13,17,0,0,0,0,0,0,0,0,0,0,0,0,0,0,0,0,0,0,0,0,0,0,0,0}},
   {5,23,2,255,{116,246,0,0,0,0,0,0,0,0,0,0},{0,34,5,39,10,12,45,15,16,17,18,19,20,21,22,23,24,25,26,27,28,29,30,0,0,0,0,0,0,0,0,0}},
   {5,25,2,255,{178,247,0,0,0,0,0,0,0,0,0,0},{32,3,37,8,42,44,14,47,48,49,50,51,52,53,54,55,56,57,58,59,60,61,62,31,63,0,0,0,0,0,0,0}},
   {5,7,5,16,{5,18,17,172,96,0,0,0,0,0,0,0},{1,35,6,40,11,13,46,0,0,0,0,0,0,0,0,0,0,0,0,0,0,0,0,0,0,0,0,0,0,0,0,0}},
   {5,4,4,17,{7,123,76,56,0,0,0,0,0,0,0,0},{33,4,38,9,0,0,0,0,0,0,0,0,0,0,0,0,0,0,0,0,0,0,0,0,0,0,0,0,0,0,0,0}},
   {5,5,5,18,{14,140,177,162,72,0,0,0,0,0,0,0},{2,36,7,41,43,0,0,0,0,0,0,0,0,0,0,0,0,0,0,0,0,0,0,0,0,0,0,0,0,0,0,0}},
   {13,22,4,255,{169,253,217,240,0,0,0,0,0,0,0,0},{32,37,43,40,2,6,10,14,17,19,20,21,22,23,24,25,26,27,28,29,30,31,0,0,0,0,0,0,0,0,0,0}},
   {13,7,5,19,{21,147,138,105,112,0,0,0,0,0,0,0},{36,42,35,45,3,7,11,0,0,0,0,0,0,0,0,0,0,0,0,0,0,0,0,0,0,0,0,0,0,0,0,0}},
   {13,8,5,255,{61,125,143,180,250,0,0,0,0,0,0,0},{41,34,39,0,4,8,12,15,0,0,0,0,0,0,0,0,0,0,0,0,0,0,0,0,0,0,0,0,0,0,0,0}},
   {13,9,5,255,{94,106,57,103,197,0,0,0,0,0,0,0},{33,38,44,1,5,9,13,16,18,0,0,0,0,0,0,0,0,0,0,0,0,0,0,0,0,0,0,0,0,0,0,0}},
   {6,24,3,255,{184,230,195,0,0,0,0,0,0,0,0,0},{0,2,4,6,8,10,12,14,16,17,18,19,20,21,22,23,24,25,26,27,28,29,30,31,0,0,0,0,0,0,0,0}},
   {6,24,2,255,{207,227,0,0,0,0,0,0,0,0,0,0},{32,34,36,38,40,42,44,46,48,49,50,51,52,53,54,55,56,57,58,59,60,61,62,63,0,0,0,0,0,0,0,0}},
   {6,8,6,255,{39,42,121,54,185,181,0,0,0,0,0,0},{1,3,5,7,9,11,13,15,0,0,0,0,0,0,0,0,0,0,0,0,0,0,0,0,0,0,0,0,0,0,0,0}},
   {6,8,4,20,{46,10,132,160,0,0,0,0,0,0,0,0},{33,35,37,39,41,43,45,47,0,0,0,0,0,0,0,0,0,0,0,0,0,0,0,0,0,0,0,0,0,0,0,0}},
   {14,22,2,255,{206,218,0,0,0,0,0,0,0,0,0,0},{32,37,43,40,2,6,10,14,18,19,20,21,22,23,24,25,26,27,28,29,30,31,0,0,0,0,0,0,0,0,0,0}},
   {14,8,5,255,{22,146,127,193,254,0,0,0,0,0,0,0},{36,42,35,45,3,7,11,15,0,0,0,0,0,0,0,0,0,0,0,0,0,0,0,0,0,0,0,0,0,0,0,0}},
   {14,8,7,255,{47,89,81,97,219,239,241,0,0,0,0,0},{41,34,39,0,4,8,12,16,0,0,0,0,0,0,0,0,0,0,0,0,0,0,0,0,0,0,0,0,0,0,0,0}},
   {14,8,5,255,{27,70,87,189,233,0,0,0,0,0,0,0},{33,38,44,1,5,9,13,17,0,0,0,0,0,0,0,0,0,0,0,0,0,0,0,0,0,0,0,0,0,0,0,0}},
   {7,24,2,255,{174,235,0,0,0,0,0,0,0,0,0,0},{0,2,4,6,8,10,12,14,16,17,18,19,20,21,22,23,24,25,26,27,28,29,30,31,0,0,0,0,0,0,0,0}},
   {7,24,3,255,{200,164,222,0,0,0,0,0,0,0,0,0},{32,34,36,38,40,42,44,46,48,49,50,51,52,53,54,55,56,57,58,59,60,61,62,63,0,0,0,0,0,0,0,0}},
   {7,8,5,255,{12,93,79,196,204,0,0,0,0,0,0,0},{1,3,5,7,9,11,13,15,0,0,0,0,0,0,0,0,0,0,0,0,0,0,0,0,0,0,0,0,0,0,0,0}},
   {7,8,4,21,{44,33,1,126,0,0,0,0,0,0,0,0},{33,35,37,39,41,43,45,47,0,0,0,0,0,0,0,0,0,0,0,0,0,0,0,0,0,0,0,0,0,0,0,0}},
   {15,22,2,255,{163,245,0,0,0,0,0,0,0,0,0,0},{32,37,43,40,2,6,10,14,18,19,20,21,22,23,24,25,26,27,28,29,30,31,0,0,0,0,0,0,0,0,0,0}},
   {15,8,4,22,{86,153,107,64,0,0,0,0,0,0,0,0},{36,42,35,45,3,7,11,15,0,0,0,0,0,0,0,0,0,0,0,0,0,0,0,0,0,0,0,0,0,0,0,0}},
   {15,8,6,255,{35,75,95,194,187,203,0,0,0,0,0,0},{41,34,39,0,4,8,12,16,0,0,0,0,0,0,0,0,0,0,0,0,0,0,0,0,0,0,0,0,0,0,0,0}},
   {15,8,6,23,{43,137,161,58,82,144,0,0,0,0,0,0},{33,38,44,1,5,9,13,17,0,0,0,0,0,0,0,0,0,0,0,0,0,0,0,0,0,0,0,0,0,0,0,0}}},
  {{1,16,5,6,8,0,10,9,7,12,13,2,11,14,3,4,15,20,18,17,19,23,24,25,21,22,31,26,27,29,30,28},
   {9,3,4,17,14,1,0,6,20,2,5,19,11,22,15,10,7,18,8,16,13,12,21,25,24,23,28,26,29,27,31,30},
   {2,4,0,1,6,16,14,5,12,18,21,7,9,13,11,17,19,15,3,20,10,8,24,22,23,29,25,27,28,30,26,31},
   {2,3,4,5,7,8,0,9,15,14,18,10,19,12,16,13,1,6,11,27,17,21,20,22,23,30,29,25,24,28,26,31},
   {0,1,2,3,5,6,17,11,12,4,10,9,21,18,7,8,15,16,13,14,20,26,19,24,31,22,29,23,30,25,27,28},
   {1,0,4,5,2,3,6,7,8,9,10,12,13,11,17,19,15,18,14,16,27,20,29,21,31,23,22,30,24,26,28,25},
   {0,1,3,4,5,2,7,9,10,11,8,12,16,15,17,19,13,6,14,18,21,22,28,25,26,20,30,31,24,29,23,27},
   {0,1,2,4,3,5,6,8,13,18,14,11,9,23,15,10,7,17,12,16,19,20,25,21,26,27,29,22,24,30,28,31}}};

typedef CUresult (*EncodeFn)(CUtensorMap*, CUtensorMapDataType, cuuint32_t, void*, const cuuint64_t*, const cuuint64_t*, const cuuint32_t*,
                             const cuuint32_t*, CUtensorMapInterleave, CUtensorMapSwizzle, CUtensorMapL2promotion, CUtensorMapFloatOOBfill);

void make_map2(EncodeFn enc, CUtensorMap* m, const void* ptr, int rows, int cols, int box_rows) {
  cuuint64_t dim[2] = {(cuuint64_t)cols, (cuuint64_t)rows}, str[1] = {(cuuint64_t)cols * 2};
  cuuint32_t box[2] = {64, (cuuint32_t)box_rows}, es[2] = {1, 1};
  enc(m, CU_TENSOR_MAP_DATA_TYPE_BFLOAT16, 2, const_cast<void*>(ptr), dim, str, box, es, CU_TENSOR_MAP_INTERLEAVE_NONE, CU_TENSOR_MAP_SWIZZLE_128B,
      CU_TENSOR_MAP_L2_PROMOTION_L2_128B, CU_TENSOR_MAP_FLOAT_OOB_FILL_NONE);
}
void make_map3(EncodeFn enc, CUtensorMap* m, const void* ptr, int rows) {
  cuuint64_t dim[3] = {64, (cuuint64_t)rows, 9}, str[2] = {DM * 2, 128};
  cuuint32_t box[3] = {64, 32, 3}, es[3] = {1, 1, 1};
  enc(m, CU_TENSOR_MAP_DATA_TYPE_BFLOAT16, 3, const_cast<void*>(ptr), dim, str, box, es, CU_TENSOR_MAP_INTERLEAVE_NONE, CU_TENSOR_MAP_SWIZZLE_128B,
      CU_TENSOR_MAP_L2_PROMOTION_L2_128B, CU_TENSOR_MAP_FLOAT_OOB_FILL_NONE);
}

void make_map_t(EncodeFn enc, CUtensorMap* m, void* ptr, int width, int cols) {
  cuuint64_t dim[3] = {TP / 2, 2, 864}, str[2] = {TP * 2, TP * 4};
  cuuint32_t box[3] = {(cuuint32_t)width, 2, (cuuint32_t)cols}, es[3] = {1, 1, 1};
  enc(m, CU_TENSOR_MAP_DATA_TYPE_UINT32, 3, ptr, dim, str, box, es, CU_TENSOR_MAP_INTERLEAVE_NONE, cols == 64 ? CU_TENSOR_MAP_SWIZZLE_128B : CU_TENSOR_MAP_SWIZZLE_NONE,
      CU_TENSOR_MAP_L2_PROMOTION_NONE, CU_TENSOR_MAP_FLOAT_OOB_FILL_NONE);
}

int g_mode = -1;

}

extern "C" void kernel_launch(void* const* d_in, const int* in_sizes, int n_in, void* d_out, int out_size) {
  static EncodeFn enc = nullptr;
  static void* t_ptr = nullptr;
  if (!enc) {
    void* fn = nullptr;
    cudaDriverEntryPointQueryResult st;
    cudaGetDriverEntryPoint("cuTensorMapEncodeTiled", &fn, cudaEnableDefault, &st);
    enc = (EncodeFn)fn;
    cudaGetSymbolAddress(&t_ptr, g_T);
    cudaFuncSetAttribute(fused_kernel, cudaFuncAttributeMaxDynamicSharedMemorySize, SMEM_BYTES);
    if (g_mode < 0) {
      cudaLaunchConfig_t cfg = {};
      cfg.gridDim = dim3(2 * NCL); cfg.blockDim = dim3(384); cfg.dynamicSmemBytes = SMEM_BYTES;
      cudaLaunchAttribute at; at.id = cudaLaunchAttributeClusterDimension;
      at.val.clusterDim.x = 2; at.val.clusterDim.y = 1; at.val.clusterDim.z = 1;
      cfg.attrs = &at; cfg.numAttrs = 1;
      int nc = 0;
      g_mode = (cudaOccupancyMaxActiveClusters(&nc, fused_kernel, &cfg) == cudaSuccess && nc >= NCL) ? 1 : 0;
      (void)cudaGetLastError();
    }
  }
  Params p;
  make_map2(enc, &p.map_a[0], d_in[4], SEQ, DC, 128);
  make_map2(enc, &p.map_a[1], d_in[0], SEQ, DM, 128);
  make_map2(enc, &p.map_w[0], d_in[6], DC, 4096, 64);
  make_map2(enc, &p.map_w[1], d_in[7], DC, 4096, 64);
  make_map2(enc, &p.map_w[2], d_in[5], DM, 4096, 64);
  make_map2(enc, &p.map_w[3], d_in[1], DM, 1728, 64);
  make_map3(enc, &p.map_o[0], d_in[8], 4096);
  make_map3(enc, &p.map_o[1], d_in[2], DM);
  make_map_t(enc, &p.map_t[0], t_ptr, 32, 9);
  make_map_t(enc, &p.map_t[1], t_ptr, 40, 9);
  make_map_t(enc, &p.map_t[2], t_ptr, 32, 64);
  p.x = (const __nv_bfloat16*)d_in[0];
  p.gate_w = (const __nv_bfloat16*)d_in[9];
  make_map2(enc, &p.map_out, d_out, SEQ, DM, 16);
  p.zero = 0;
  p.s = k_sched;
  if (g_mode == 1) {
    p.phases = 31;
    fused_kernel<<<2 * NCL, 384, SMEM_BYTES>>>(p);
  } else {
    p.phases = 1;  fused_kernel<<<2 * NCL, 384, SMEM_BYTES>>>(p);
    p.phases = 10; fused_kernel<<<2 * NCL, 384, SMEM_BYTES>>>(p);
    p.phases = 4;  fused_kernel<<<2 * NCL, 384, SMEM_BYTES>>>(p);
  }
}
```

```cpp
#include <cuda_runtime.h>
#include <cuda_bf16.h>
#include <cuda.h>
#include <stdint.h>

namespace {

constexpr int SEQ = 2048, DM = 576, DC = 512, NH = 32;
constexpr int NCL = 66;
constexpr int NKB3 = 73;
constexpr uint32_t DESC_HI = 0x40000040u;

constexpr int SM_RING = 0;
constexpr int SM_BUF = 163840;
constexpr int SM_BAR = 229376;
constexpr int B_P1F = 0, B_P1E = 10, B_P2F = 20, B_P2E = 25, B_P3F = 30, B_P3E = 35, B_SF = 40, B_SE = 44, B_QF = 48, B_DONE = 52, B_FIN = 53, B_ORD = 54, B_LA = 58, B_LAD = 62, B_NUM = 63;
constexpr int SMEM_BYTES = SM_BAR + B_NUM * 8 + 1024;

constexpr int F_HEAD = 0;
constexpr int F_QKVA = 32;
constexpr int F_GATE = 64;
constexpr int F_DONE = 65;
constexpr int F_CTX = 96;
constexpr int F_NUM = 96 + 8 * 64;

struct Rec {
  uint8_t slab;
  uint8_t n1, n2;
  uint8_t p3;
  uint8_t bg;
  uint8_t item[11];
  uint8_t tile[47];
  uint8_t phases;
};
struct Sched {
  Rec r[NCL];
  uint8_t p3_order[8][32];
};

struct Params {
  CUtensorMap map_a[2];
  CUtensorMap map_w[4];
  CUtensorMap map_o[2];
  CUtensorMap map_t[3];
  CUtensorMap map_out;
  const __nv_bfloat16* x;
  const __nv_bfloat16* gate_w;
  int zero;
  alignas(64) Sched s;
};

__device__ __align__(1024) uint8_t g_Q[NH * 32 * 16384];
__device__ __align__(1024) uint8_t g_KV[2 * NH * 16 * 32768];
__device__ __align__(1024) uint8_t g_oA[32 * 576 * 128];
constexpr int TP = SEQ + 16;
__device__ __align__(1024) uint32_t g_T[864 * TP];
__device__ float g_gate[SEQ];
__device__ int g_flags[F_NUM];

__device__ __forceinline__ void mbar_arrive(uint32_t b) { asm volatile("mbarrier.arrive.shared::cta.b64 _, [%0];" ::"r"(b) : "memory"); }
__device__ __forceinline__ void mbar_arrive_cl(uint32_t b, int cnt) {
  asm volatile("mbarrier.arrive.shared::cluster.b64 _, [%0], %1;" ::"r"(b), "r"(cnt) : "memory");
}
__device__ __forceinline__ void mbar_wait(uint32_t b, int par) {
  asm volatile(
      "{\n.reg .pred p;\n.reg .u32 c;\n"
      "mbarrier.try_wait.parity.shared::cta.b64 p, [%0], %1;\n@p bra DN;\nmov.u32 c, 0;\n"
      "LP:\nmbarrier.try_wait.parity.shared::cta.b64 p, [%0], %1;\n@p bra DN;\n"
      "add.u32 c, c, 1;\nsetp.lt.u32 p, c, 4000000;\n@p bra LP;\ntrap;\nDN:\n}" ::"r"(b), "r"(par) : "memory");
}
__device__ __forceinline__ uint32_t mapa(uint32_t a, uint32_t cta) {
  uint32_t r; asm("mapa.shared::cluster.u32 %0, %1, %2;" : "=r"(r) : "r"(a), "r"(cta)); return r;
}
#define ELECT(ins) "{\n.reg .pred e;\nelect.sync _|e, 0xffffffff;\n@e " ins "\n}"
__device__ __forceinline__ void mbar_expect(uint32_t b, int bytes) {
  asm volatile(ELECT("mbarrier.arrive.expect_tx.shared::cta.b64 _, [%0], %1;") ::"r"(b), "r"(bytes) : "memory");
}
__device__ __forceinline__ void mbar_arrive_one(uint32_t b) { asm volatile(ELECT("mbarrier.arrive.shared::cta.b64 _, [%0];") ::"r"(b) : "memory"); }
constexpr uint64_t L2_NORMAL = 0x1000000000000000ull, L2_FIRST = 0x12F0000000000000ull;
__device__ __forceinline__ void bulk_load(uint32_t dst, const void* src, int bytes, uint32_t bar, uint64_t pol = L2_NORMAL) {
  asm volatile(ELECT("cp.async.bulk.shared::cluster.global.mbarrier::complete_tx::bytes.L2::cache_hint [%0], [%1], %2, [%3], %4;") ::"r"(dst), "l"(src), "r"(bytes), "r"(bar), "l"(pol) : "memory");
}
__device__ __forceinline__ void bulk_load_mc(uint32_t dst, const void* src, int bytes, uint32_t bar, uint64_t pol = L2_NORMAL) {
  asm volatile(ELECT("cp.async.bulk.shared::cluster.global.mbarrier::complete_tx::bytes.multicast::cluster.L2::cache_hint [%0], [%1], %2, [%3], %4, %5;") ::"r"(dst), "l"(src), "r"(bytes), "r"(bar), "h"((uint16_t)3), "l"(pol) : "memory");
}
__device__ __forceinline__ void bulk_store(void* dst, uint32_t src, int bytes, uint64_t pol = L2_NORMAL) {
  asm volatile(ELECT("cp.async.bulk.global.shared::cta.bulk_group.L2::cache_hint [%0], [%1], %2, %3;") ::"l"(dst), "r"(src), "r"(bytes), "l"(pol) : "memory");
}
__device__ __forceinline__ void tma2d(uint32_t dst, const CUtensorMap* m, int c0, int c1, uint32_t bar, uint64_t pol = L2_NORMAL) {
  asm volatile(ELECT("cp.async.bulk.tensor.2d.shared::cluster.global.mbarrier::complete_tx::bytes.L2::cache_hint [%0], [%1, {%3, %4}], [%2], %5;") ::"r"(dst), "l"(m), "r"(bar), "r"(c0), "r"(c1), "l"(pol) : "memory");
}
__device__ __forceinline__ void tma2d_mc(uint32_t dst, const CUtensorMap* m, int c0, int c1, uint32_t bar, uint64_t pol = L2_NORMAL) {
  asm volatile(ELECT("cp.async.bulk.tensor.2d.shared::cluster.global.mbarrier::complete_tx::bytes.multicast::cluster.L2::cache_hint [%0], [%1, {%3, %4}], [%2], %5, %6;") ::"r"(dst), "l"(m), "r"(bar), "r"(c0), "r"(c1), "h"((uint16_t)3), "l"(pol) : "memory");
}
__device__ __forceinline__ void tma3d(uint32_t dst, const CUtensorMap* m, int c0, int c1, int c2, uint32_t bar, uint64_t pol = L2_NORMAL) {
  asm volatile(ELECT("cp.async.bulk.tensor.3d.shared::cluster.global.mbarrier::complete_tx::bytes.L2::cache_hint [%0], [%1, {%3, %4, %5}], [%2], %6;") ::"r"(dst), "l"(m), "r"(bar), "r"(c0), "r"(c1), "r"(c2), "l"(pol) : "memory");
}
__device__ __forceinline__ void tma3d_mc(uint32_t dst, const CUtensorMap* m, int c0, int c1, int c2, uint32_t bar, uint64_t pol = L2_NORMAL) {
  asm volatile(ELECT("cp.async.bulk.tensor.3d.shared::cluster.global.mbarrier::complete_tx::bytes.multicast::cluster.L2::cache_hint [%0], [%1, {%3, %4, %5}], [%2], %6, %7;") ::"r"(dst), "l"(m), "r"(bar), "r"(c0), "r"(c1), "r"(c2), "h"((uint16_t)3), "l"(pol) : "memory");
}
__device__ __forceinline__ void tma2d_store(const CUtensorMap* m, uint32_t src, int c0, int c1, uint64_t pol = L2_NORMAL) {
  asm volatile(ELECT("cp.async.bulk.tensor.2d.global.shared::cta.bulk_group.L2::cache_hint [%0, {%2, %3}], [%1], %4;") ::"l"(m), "r"(src), "r"(c0), "r"(c1), "l"(pol) : "memory");
}
__device__ __forceinline__ void tma3d_store(const CUtensorMap* m, uint32_t src, int c0, int c1, int c2, uint64_t pol = L2_NORMAL) {
  asm volatile(ELECT("cp.async.bulk.tensor.3d.global.shared::cta.bulk_group.L2::cache_hint [%0, {%2, %3, %4}], [%1], %5;") ::"l"(m), "r"(src), "r"(c0), "r"(c1), "r"(c2), "l"(pol) : "memory");
}
__device__ __forceinline__ void tma2d_prefetch(const CUtensorMap* m, int c0, int c1, uint64_t pol = L2_NORMAL) {
  asm volatile(ELECT("cp.async.bulk.prefetch.tensor.2d.L2.global.L2::cache_hint [%0, {%1, %2}], %3;") ::"l"(m), "r"(c0), "r"(c1), "l"(pol) : "memory");
}
__device__ __forceinline__ void bulk_prefetch(const void* src, int bytes) {
  asm volatile(ELECT("cp.async.bulk.prefetch.L2.global [%0], %1;") ::"l"(src), "r"(bytes) : "memory");
}
#define HINT 6
#define POL(bit) ((HINT >> (bit)) & 1 ? L2_FIRST : L2_NORMAL)
#define BULK_COMMIT() asm volatile("cp.async.bulk.commit_group;" ::: "memory")
#define BULK_WAIT(n) asm volatile("cp.async.bulk.wait_group %0;" ::"n"(n) : "memory")
#define BULK_WAIT_READ(n) asm volatile("cp.async.bulk.wait_group.read %0;" ::"n"(n) : "memory")
#define FENCE_ASYNC_SMEM() asm volatile("fence.proxy.async.shared::cta;" ::: "memory")
#define FENCE_ASYNC_ALL() asm volatile("fence.proxy.async;" ::: "memory")
#define WG_FENCE() asm volatile("wgmma.fence.sync.aligned;" ::: "memory")
#define WG_COMMIT() asm volatile("wgmma.commit_group.sync.aligned;" ::: "memory")
#define WG_WAIT(n) asm volatile("wgmma.wait_group.sync.aligned %0;" ::"n"(n) : "memory")
__device__ __forceinline__ void bar_sync(int id, int n) { asm volatile("bar.sync %0, %1;" ::"r"(id), "r"(n) : "memory"); }
__device__ __forceinline__ void bar_arrive(int id, int n) { asm volatile("bar.arrive %0, %1;" ::"r"(id), "r"(n) : "memory"); }
__device__ __forceinline__ void cluster_sync() {
  asm volatile("barrier.cluster.arrive.relaxed;\nbarrier.cluster.wait.acquire;" ::: "memory");
}
template <int N> __device__ __forceinline__ void pin(float (&r)[N]) {
#pragma unroll
  for (int i = 0; i < N; i++) asm volatile("" : "+f"(r[i])::"memory");
}
template <int N> __device__ __forceinline__ void pin(uint32_t (&r)[N]) {
#pragma unroll
  for (int i = 0; i < N; i++) asm volatile("" : "+r"(r[i])::"memory");
}
__device__ __forceinline__ uint32_t pack_bf16(float lo, float hi) {
  uint32_t r; asm("cvt.rn.bf16x2.f32 %0, %1, %2;" : "=r"(r) : "f"(hi), "f"(lo)); return r;
}
__device__ __forceinline__ float ex2(float x) { float r; asm("ex2.approx.ftz.f32 %0, %1;" : "=f"(r) : "f"(x)); return r; }
__device__ __forceinline__ void ldsm4(uint32_t a, uint32_t& r0, uint32_t& r1, uint32_t& r2, uint32_t& r3) {
  asm volatile("ldmatrix.sync.aligned.m8n8.x4.shared.b16 {%0,%1,%2,%3}, [%4];" : "=r"(r0), "=r"(r1), "=r"(r2), "=r"(r3) : "r"(a) : "memory");
}
__device__ __forceinline__ void stsm4(uint32_t a, uint32_t r0, uint32_t r1, uint32_t r2, uint32_t r3) {
  asm volatile("stmatrix.sync.aligned.m8n8.x4.shared.b16 [%0], {%1,%2,%3,%4};" ::"r"(a), "r"(r0), "r"(r1), "r"(r2), "r"(r3) : "memory");
}
__device__ __forceinline__ void flag_add(int idx) {
  asm volatile(ELECT("red.release.gpu.global.add.s32 [%0], 1;") ::"l"(g_flags + idx) : "memory");
}
__device__ __forceinline__ void flag_add_rx(int idx) {
  asm volatile(ELECT("red.relaxed.gpu.global.add.s32 [%0], 1;") ::"l"(g_flags + idx) : "memory");
}
__device__ __forceinline__ bool flag_test(int idx, int target) {
  int v;
  asm volatile("ld.relaxed.gpu.global.s32 %0, [%1];" : "=r"(v) : "l"(g_flags + idx) : "memory");
  return __all_sync(0xffffffffu, v >= target);
}
template <bool ACQ> __device__ __forceinline__ void flag_wait(int idx, int target) {
  int n = 0;
  while (true) {
    int v;
    if (ACQ) asm volatile("ld.acquire.gpu.global.s32 %0, [%1];" : "=r"(v) : "l"(g_flags + idx) : "memory");
    else asm volatile("ld.relaxed.gpu.global.s32 %0, [%1];" : "=r"(v) : "l"(g_flags + idx) : "memory");
    if (__all_sync(0xffffffffu, v >= target)) break;
    if (++n > 20000000) __trap();
    __nanosleep(64);
  }
}
__device__ __forceinline__ uint32_t desc_lo(uint32_t addr, uint32_t lbo) { return ((addr & 0x3FFFFu) >> 4) | ((lbo >> 4) << 16); }
#define PROF(role, i)
#define PROFX(cond, i)
#define PROFB(i)
#define PROFG(i)

template <int TB, int TA = 0> __device__ __forceinline__ void wgmma_ss64(float (&d)[32], uint32_t alo, uint32_t blo, int sd) {
  asm volatile("{\n.reg .pred p;\n.reg .b64 da, db;\n"
    "setp.ne.b32 p, %34, 0;\nmov.b64 da, {%32, %36};\nmov.b64 db, {%33, %36};\n"
    "wgmma.mma_async.sync.aligned.m64n64k16.f32.bf16.bf16 "
    "{%0,%1,%2,%3,%4,%5,%6,%7,%8,%9,%10,%11,%12,%13,%14,%15,%16,%17,%18,%19,%20,%21,%22,%23,"
    "%24,%25,%26,%27,%28,%29,%30,%31}, "
    "da, db, p, 1, 1, %37, %35;\n}\n"
    : "+f"(d[0]),"+f"(d[1]),"+f"(d[2]),"+f"(d[3]),"+f"(d[4]),"+f"(d[5]),"+f"(d[6]),"+f"(d[7]),"+f"(d[8]),"+f"(d[9]),"+f"(d[10]),"+f"(d[11]),
      "+f"(d[12]),"+f"(d[13]),"+f"(d[14]),"+f"(d[15]),"+f"(d[16]),"+f"(d[17]),"+f"(d[18]),"+f"(d[19]),"+f"(d[20]),"+f"(d[21]),"+f"(d[22]),"+f"(d[23]),
      "+f"(d[24]),"+f"(d[25]),"+f"(d[26]),"+f"(d[27]),"+f"(d[28]),"+f"(d[29]),"+f"(d[30]),"+f"(d[31])
    : "r"(alo), "r"(blo), "r"(sd), "n"(TB), "r"(DESC_HI), "n"(TA));
}
template <int TB, int TA = 0> __device__ __forceinline__ void wgmma_ss128(float (&d)[64], uint32_t alo, uint32_t blo, int sd) {
  asm volatile("{\n.reg .pred p;\n.reg .b64 da, db;\n"
    "setp.ne.b32 p, %66, 0;\nmov.b64 da, {%64, %68};\nmov.b64 db, {%65, %68};\n"
    "wgmma.mma_async.sync.aligned.m64n128k16.f32.bf16.bf16 "
    "{%0,%1,%2,%3,%4,%5,%6,%7,%8,%9,%10,%11,%12,%13,%14,%15,%16,%17,%18,%19,%20,%21,%22,%23,"
    "%24,%25,%26,%27,%28,%29,%30,%31,%32,%33,%34,%35,%36,%37,%38,%39,%40,%41,%42,%43,%44,%45,%46,%47,"
    "%48,%49,%50,%51,%52,%53,%54,%55,%56,%57,%58,%59,%60,%61,%62,%63}, "
    "da, db, p, 1, 1, %69, %67;\n}\n"
    : "+f"(d[0]),"+f"(d[1]),"+f"(d[2]),"+f"(d[3]),"+f"(d[4]),"+f"(d[5]),"+f"(d[6]),"+f"(d[7]),"+f"(d[8]),"+f"(d[9]),"+f"(d[10]),"+f"(d[11]),
      "+f"(d[12]),"+f"(d[13]),"+f"(d[14]),"+f"(d[15]),"+f"(d[16]),"+f"(d[17]),"+f"(d[18]),"+f"(d[19]),"+f"(d[20]),"+f"(d[21]),"+f"(d[22]),"+f"(d[23]),
      "+f"(d[24]),"+f"(d[25]),"+f"(d[26]),"+f"(d[27]),"+f"(d[28]),"+f"(d[29]),"+f"(d[30]),"+f"(d[31]),"+f"(d[32]),"+f"(d[33]),"+f"(d[34]),"+f"(d[35]),
      "+f"(d[36]),"+f"(d[37]),"+f"(d[38]),"+f"(d[39]),"+f"(d[40]),"+f"(d[41]),"+f"(d[42]),"+f"(d[43]),"+f"(d[44]),"+f"(d[45]),"+f"(d[46]),"+f"(d[47]),
      "+f"(d[48]),"+f"(d[49]),"+f"(d[50]),"+f"(d[51]),"+f"(d[52]),"+f"(d[53]),"+f"(d[54]),"+f"(d[55]),"+f"(d[56]),"+f"(d[57]),"+f"(d[58]),"+f"(d[59]),
      "+f"(d[60]),"+f"(d[61]),"+f"(d[62]),"+f"(d[63])
    : "r"(alo), "r"(blo), "r"(sd), "n"(TB), "r"(DESC_HI), "n"(TA));
}
template <int TB> __device__ __forceinline__ void wgmma_rs128(float (&d)[64], uint32_t a0, uint32_t a1, uint32_t a2, uint32_t a3, uint32_t blo, int sd) {
  asm volatile("{\n.reg .pred p;\n.reg .b64 db;\n"
    "setp.ne.b32 p, %69, 0;\nmov.b64 db, {%68, %71};\n"
    "wgmma.mma_async.sync.aligned.m64n128k16.f32.bf16.bf16 "
    "{%0,%1,%2,%3,%4,%5,%6,%7,%8,%9,%10,%11,%12,%13,%14,%15,%16,%17,%18,%19,%20,%21,%22,%23,"
    "%24,%25,%26,%27,%28,%29,%30,%31,%32,%33,%34,%35,%36,%37,%38,%39,%40,%41,%42,%43,%44,%45,%46,%47,"
    "%48,%49,%50,%51,%52,%53,%54,%55,%56,%57,%58,%59,%60,%61,%62,%63}, "
    "{%64,%65,%66,%67}, db, p, 1, 1, %70;\n}\n"
    : "+f"(d[0]),"+f"(d[1]),"+f"(d[2]),"+f"(d[3]),"+f"(d[4]),"+f"(d[5]),"+f"(d[6]),"+f"(d[7]),"+f"(d[8]),"+f"(d[9]),"+f"(d[10]),"+f"(d[11]),
      "+f"(d[12]),"+f"(d[13]),"+f"(d[14]),"+f"(d[15]),"+f"(d[16]),"+f"(d[17]),"+f"(d[18]),"+f"(d[19]),"+f"(d[20]),"+f"(d[21]),"+f"(d[22]),"+f"(d[23]),
      "+f"(d[24]),"+f"(d[25]),"+f"(d[26]),"+f"(d[27]),"+f"(d[28]),"+f"(d[29]),"+f"(d[30]),"+f"(d[31]),"+f"(d[32]),"+f"(d[33]),"+f"(d[34]),"+f"(d[35]),
      "+f"(d[36]),"+f"(d[37]),"+f"(d[38]),"+f"(d[39]),"+f"(d[40]),"+f"(d[41]),"+f"(d[42]),"+f"(d[43]),"+f"(d[44]),"+f"(d[45]),"+f"(d[46]),"+f"(d[47]),
      "+f"(d[48]),"+f"(d[49]),"+f"(d[50]),"+f"(d[51]),"+f"(d[52]),"+f"(d[53]),"+f"(d[54]),"+f"(d[55]),"+f"(d[56]),"+f"(d[57]),"+f"(d[58]),"+f"(d[59]),
      "+f"(d[60]),"+f"(d[61]),"+f"(d[62]),"+f"(d[63])
    : "r"(a0), "r"(a1), "r"(a2), "r"(a3), "r"(blo), "r"(sd), "n"(TB), "r"(DESC_HI));
}
template <int TB, int TA = 0> __device__ __forceinline__ void wgmma_ss192(float (&d)[96], uint32_t alo, uint32_t blo, int sd) {
  asm volatile("{\n.reg .pred p;\n.reg .b64 da, db;\n"
    "setp.ne.b32 p, %98, 0;\nmov.b64 da, {%96, %100};\nmov.b64 db, {%97, %100};\n"
    "wgmma.mma_async.sync.aligned.m64n192k16.f32.bf16.bf16 "
    "{%0,%1,%2,%3,%4,%5,%6,%7,%8,%9,%10,%11,%12,%13,%14,%15,%16,%17,%18,%19,%20,%21,%22,%23,"
    "%24,%25,%26,%27,%28,%29,%30,%31,%32,%33,%34,%35,%36,%37,%38,%39,%40,%41,%42,%43,%44,%45,%46,%47,"
    "%48,%49,%50,%51,%52,%53,%54,%55,%56,%57,%58,%59,%60,%61,%62,%63,%64,%65,%66,%67,%68,%69,%70,%71,"
    "%72,%73,%74,%75,%76,%77,%78,%79,%80,%81,%82,%83,%84,%85,%86,%87,%88,%89,%90,%91,%92,%93,%94,%95}, "
    "da, db, p, 1, 1, %101, %99;\n}\n"
    : "+f"(d[0]),"+f"(d[1]),"+f"(d[2]),"+f"(d[3]),"+f"(d[4]),"+f"(d[5]),"+f"(d[6]),"+f"(d[7]),"+f"(d[8]),"+f"(d[9]),"+f"(d[10]),"+f"(d[11]),
      "+f"(d[12]),"+f"(d[13]),"+f"(d[14]),"+f"(d[15]),"+f"(d[16]),"+f"(d[17]),"+f"(d[18]),"+f"(d[19]),"+f"(d[20]),"+f"(d[21]),"+f"(d[22]),"+f"(d[23]),
      "+f"(d[24]),"+f"(d[25]),"+f"(d[26]),"+f"(d[27]),"+f"(d[28]),"+f"(d[29]),"+f"(d[30]),"+f"(d[31]),"+f"(d[32]),"+f"(d[33]),"+f"(d[34]),"+f"(d[35]),
      "+f"(d[36]),"+f"(d[37]),"+f"(d[38]),"+f"(d[39]),"+f"(d[40]),"+f"(d[41]),"+f"(d[42]),"+f"(d[43]),"+f"(d[44]),"+f"(d[45]),"+f"(d[46]),"+f"(d[47]),
      "+f"(d[48]),"+f"(d[49]),"+f"(d[50]),"+f"(d[51]),"+f"(d[52]),"+f"(d[53]),"+f"(d[54]),"+f"(d[55]),"+f"(d[56]),"+f"(d[57]),"+f"(d[58]),"+f"(d[59]),
      "+f"(d[60]),"+f"(d[61]),"+f"(d[62]),"+f"(d[63]),"+f"(d[64]),"+f"(d[65]),"+f"(d[66]),"+f"(d[67]),"+f"(d[68]),"+f"(d[69]),"+f"(d[70]),"+f"(d[71]),
      "+f"(d[72]),"+f"(d[73]),"+f"(d[74]),"+f"(d[75]),"+f"(d[76]),"+f"(d[77]),"+f"(d[78]),"+f"(d[79]),"+f"(d[80]),"+f"(d[81]),"+f"(d[82]),"+f"(d[83]),
      "+f"(d[84]),"+f"(d[85]),"+f"(d[86]),"+f"(d[87]),"+f"(d[88]),"+f"(d[89]),"+f"(d[90]),"+f"(d[91]),"+f"(d[92]),"+f"(d[93]),"+f"(d[94]),"+f"(d[95])
    : "r"(alo), "r"(blo), "r"(sd), "n"(TB), "r"(DESC_HI), "n"(TA));
}

struct Ctx {
  uint32_t sm;
  uint32_t bar;
  uint32_t rbar;
  int cl, rank, wg, warp, lane, phases;
};
__device__ __forceinline__ void release(const Ctx& c, int b, int cnt = 1) {
  if (c.lane < 2) mbar_arrive_cl(c.rbar + b * 8, cnt);
}
#define PF1 1
#define PF2 0
constexpr float SM_SCALE = 0.08838834764831845f * 1.4426950408889634f;
constexpr float SM_HI = 1.8446744e19f, SM_LO = 5.4210109e-20f;
constexpr int ORDER = 1;

__device__ __forceinline__ void stage_tile(const float (&a)[64], uint32_t buf, const Ctx& c, float s0, float s1) {
  const int row = (c.lane & 7) + ((c.lane >> 3) & 1) * 8;
  const uint32_t base = buf + (c.warp * 16 + row) * 128 + (((c.lane >> 4) ^ (row & 7)) << 4);
#pragma unroll
  for (int i = 0; i < 8; i++)
    stsm4((base ^ ((i & 3) << 5)) + (i >> 2) * 8192, pack_bf16(a[8 * i] * s0, a[8 * i + 1] * s0), pack_bf16(a[8 * i + 2] * s1, a[8 * i + 3] * s1),
          pack_bf16(a[8 * i + 4] * s0, a[8 * i + 5] * s0), pack_bf16(a[8 * i + 6] * s1, a[8 * i + 7] * s1));
}

__device__ __forceinline__ void p1_epilogue(const Params& p, const Ctx& c, const float (&acc)[64], int t, int type) {
  const int tile = p.s.r[c.cl].tile[t], b = c.wg * 2 + 1;
  mbar_wait(c.bar + (B_SE + b) * 8, (t & 1) ^ 1);
  if (type && tile >= 32) {
    const int r = 2 * (c.lane & 3) + ((c.lane >> 2) & 1);
    const uint32_t dst = c.sm + SM_BUF + b * 16384 + r * 128 + (((c.warp * 2) ^ r) << 4) + (c.lane >> 3) * 4;
#pragma unroll
    for (int i = 0; i < 16; i++) {
      asm volatile("st.shared.u32 [%0], %1;" ::"r"(dst + i * 1024), "r"(pack_bf16(acc[4 * i], acc[4 * i + 1])) : "memory");
      asm volatile("st.shared.u32 [%0], %1;" ::"r"((dst ^ 16) + i * 1024), "r"(pack_bf16(acc[4 * i + 2], acc[4 * i + 3])) : "memory");
    }
  } else {
    const float sc = type ? SM_SCALE : 1.f;
    stage_tile(acc, c.sm + SM_BUF + b * 16384, c, sc, sc);
  }
  FENCE_ASYNC_SMEM();
  __syncwarp();
  if (c.lane == 0) mbar_arrive(c.bar + (B_SF + b) * 8);
}

__device__ __forceinline__ void p1_consumer(const Params& p, const Ctx& c) {
  const int n = p.s.r[c.cl].n1;
  const int type = p.s.r[c.cl].slab >> 3;
  const uint32_t bdesc = desc_lo(c.sm + SM_RING, 8192), adesc = desc_lo(c.sm + SM_BUF + 32768 + c.wg * 8192, 16);
  uint32_t A[128];
  float acc[64] = {};
  int slot = 0, par = 0;
  auto next = [&]() { if (++slot == 10) { slot = 0; par ^= 1; } };
  {
    const int row = (c.lane & 7) + ((c.lane >> 3) & 1) * 8;
    const uint32_t base = c.sm + SM_RING + (c.wg * 64 + c.warp * 16 + row) * 128 + (((c.lane >> 4) ^ (row & 7)) << 4);
    if (type) {
      mbar_wait(c.bar + B_P1F * 8, 0);
      WG_FENCE();
#pragma unroll
      for (int kk = 0; kk < 4; kk++) wgmma_ss128<1>(acc, adesc + kk * 2, bdesc + kk * 128, kk != 0);
      WG_COMMIT();
      WG_WAIT(0);
      release(c, B_P1E);
      slot = 1;
    }
#pragma unroll
    for (int kb = 0; kb < 8; kb++) {
      mbar_wait(c.bar + (B_P1F + slot) * 8, par);
#pragma unroll
      for (int kk = 0; kk < 4; kk++) ldsm4((base ^ (kk << 5)) + slot * 16384, A[kb * 16 + kk * 4], A[kb * 16 + kk * 4 + 1], A[kb * 16 + kk * 4 + 2], A[kb * 16 + kk * 4 + 3]);
      __syncwarp();
      PROF(c.wg, 5 + 2 * kb);
      release(c, B_P1E + slot);
      next();
      mbar_wait(c.bar + (B_P1F + slot) * 8, par);
      PROF(c.wg, 6 + 2 * kb);
      WG_FENCE();
#pragma unroll
      for (int kk = 0; kk < 4; kk++)
        wgmma_rs128<1>(acc, A[kb * 16 + kk * 4], A[kb * 16 + kk * 4 + 1], A[kb * 16 + kk * 4 + 2], A[kb * 16 + kk * 4 + 3], bdesc + slot * 1024 + kk * 128, (kb | kk) != 0 ? 1 : type);
      WG_COMMIT();
      WG_WAIT(0);
      release(c, B_P1E + slot);
      next();
    }
    pin(acc);
    PROF(c.wg, 1);
    p1_epilogue(p, c, acc, 0, type);
    PROF(c.wg, 2);
  }
  for (int t = 1; t < n; t++) {
    bar_sync(ORDER + c.wg, 256);
    int prev1 = -1, prev2 = -1;
    if (type) {
      mbar_wait(c.bar + (B_P1F + slot) * 8, par);
      WG_FENCE();
#pragma unroll
      for (int kk = 0; kk < 4; kk++) wgmma_ss128<1>(acc, adesc + kk * 2, bdesc + slot * 1024 + kk * 128, kk != 0);
      WG_COMMIT();
      prev1 = slot;
      next();
    }
#pragma unroll
    for (int kb = 0; kb < 8; kb++) {
      mbar_wait(c.bar + (B_P1F + slot) * 8, par);
      WG_FENCE();
      const uint32_t d = bdesc + slot * 1024;
#pragma unroll
      for (int kk = 0; kk < 4; kk++)
        wgmma_rs128<1>(acc, A[kb * 16 + kk * 4], A[kb * 16 + kk * 4 + 1], A[kb * 16 + kk * 4 + 2], A[kb * 16 + kk * 4 + 3], d + kk * 128, (kb | kk) != 0 ? 1 : type);
      WG_COMMIT();
      if (kb == 7) {
        if (t + 1 < n || c.wg == 0) bar_arrive(ORDER + (c.wg ^ 1), 256);
        else if (c.lane == 0) mbar_arrive(c.bar + B_P2F * 8);
      }
      if (kb > 0) { WG_WAIT(2); if (kb > 1 || prev2 >= 0) release(c, B_P1E + prev2); }
      prev2 = prev1; prev1 = slot;
      next();
    }
    WG_WAIT(1);
    release(c, B_P1E + prev2);
    WG_WAIT(0);
    pin(acc);
    release(c, B_P1E + prev1);
    p1_epilogue(p, c, acc, t, type);
    PROF(c.wg, 3);
  }
}

__device__ __forceinline__ void p1_producer(const Params& p, const Ctx& c) {
  const int n = p.s.r[c.cl].n1;
  const int type = p.s.r[c.cl].slab >> 3, grp = p.s.r[c.cl].slab & 7;
  int slot = 0, par = 1;
#pragma unroll 1
  for (int t = 0; t < n; t++) {
    const int tile = p.s.r[c.cl].tile[t];
    const CUtensorMap* m = &p.map_w[type * 2 + (tile >> 5)];
    const int n0 = (tile & 31) * 128 + c.rank * 64;
    const int ptile = p.s.r[c.cl].tile[t + PF1 < n ? t + PF1 : t];
    const CUtensorMap* pm = &p.map_w[type * 2 + (ptile >> 5)];
#pragma unroll 1
    for (int kb = -type; kb < 8; kb++) {
      if (t == 0) {
        mbar_wait(c.bar + (B_P1E + slot) * 8, par);
        mbar_expect(c.bar + (B_P1F + slot) * 8, kb < 0 ? 32768 : 16384);
        tma2d(kb < 0 ? c.sm + SM_BUF + 32768 : c.sm + SM_RING + slot * 16384, &p.map_a[type], kb < 0 ? 512 : kb * 64, grp * 256 + c.rank * 128, c.bar + (B_P1F + slot) * 8, POL(0));
        if (kb >= 0 && ++slot == 10) { slot = 0; par ^= 1; }
      }
      mbar_wait(c.bar + (B_P1E + slot) * 8, par);
      if (t > 0 || kb >= 0) mbar_expect(c.bar + (B_P1F + slot) * 8, 16384);
      tma2d_mc(c.sm + SM_RING + slot * 16384 + c.rank * 8192, m, n0, kb < 0 ? 512 : kb * 64, c.bar + (B_P1F + slot) * 8, POL(0));
      if (t == 0 && kb == 0) PROF(2, 61);
      if (t == 0 && kb == 3) PROF(2, 62);
      if (t + PF1 < n && (t > 0 || kb >= 3)) tma2d_prefetch(pm, (ptile & 31) * 128 + c.rank * 64, kb < 0 ? 512 : kb * 64, POL(0));
      if (++slot == 10) { slot = 0; par ^= 1; }
    }
  }
}

__device__ __forceinline__ void p1_storer(const Params& p, const Ctx& c) {
  const int n = p.s.r[c.cl].n1;
  const int type = p.s.r[c.cl].slab >> 3, grp = p.s.r[c.cl].slab & 7;
  int pf = -1;
  for (int i = 0; i < 2 * n; i++) {
    const int t = i >> 1, w = i & 1, b = w * 2 + 1;
    const int tile = p.s.r[c.cl].tile[t];
    mbar_wait(c.bar + (B_SF + b) * 8, t & 1);
    const uint32_t src = c.sm + SM_BUF + b * 16384;
    int f = F_HEAD + (tile & 31);
    if (type == 0) {
      uint8_t* dst = g_KV + (size_t)(tile * 16 + grp * 2 + c.rank) * 32768 + w * 8192;
      bulk_store(dst, src, 8192);
      bulk_store(dst + 16384, src + 8192, 8192);
    } else if (tile < 32) {
      bulk_store(g_Q + (size_t)(tile * 32 + grp * 4 + c.rank * 2 + w) * 16384, src, 16384);
    } else {
      tma3d_store(&p.map_t[2], src, 8 + (grp * 4 + c.rank * 2 + w) * 32, 0, (tile - 32) * 64);
      f = F_QKVA + grp * 4 + ((0xE4390900u >> (2 * (tile - 30))) & 3);
    }
    BULK_COMMIT();
    BULK_WAIT_READ(0);
    mbar_arrive_one(c.bar + (B_SE + b) * 8);
    if (pf >= 0) {
      BULK_WAIT(1);
      flag_add_rx(pf);
    }
    pf = f;
  }
  BULK_WAIT(0);
  flag_add_rx(pf);
}

__device__ __forceinline__ int p2_buf(int w, int i) { return w * 2 + ((i ^ w ^ 1) & 1); }
__device__ __forceinline__ int p2_blk(int rank, int w, int i) { return ((i ^ w) & 1) == 0 ? 3 - rank : rank; }

template <int N>
__device__ __forceinline__ void row_max(const float (&s)[N], float& m0, float& m1) {
  float a0 = fmaxf(s[0], s[1]), a1 = fmaxf(s[2], s[3]);
#pragma unroll
  for (int i = 1; i < N / 4; i++) {
    m0 = fmaxf(m0, s[4 * i]); a0 = fmaxf(a0, s[4 * i + 1]);
    m1 = fmaxf(m1, s[4 * i + 2]); a1 = fmaxf(a1, s[4 * i + 3]);
  }
  m0 = fmaxf(m0, a0); m1 = fmaxf(m1, a1);
  m0 = fmaxf(m0, __shfl_xor_sync(0xffffffffu, m0, 1));
  m1 = fmaxf(m1, __shfl_xor_sync(0xffffffffu, m1, 1));
  m0 = fmaxf(m0, __shfl_xor_sync(0xffffffffu, m0, 2));
  m1 = fmaxf(m1, __shfl_xor_sync(0xffffffffu, m1, 2));
}
template <bool SUB, int N>
__device__ __forceinline__ void row_exp(const float (&s)[N], uint32_t (&P)[32], float m0, float m1, float& t0, float& t1) {
  float u0 = 0.f, u1 = 0.f;
  t0 = t1 = 0.f;
#pragma unroll
  for (int i = 0; i < N / 4; i++) {
    const float e0 = ex2(SUB ? s[4 * i] - m0 : s[4 * i]), e1 = ex2(SUB ? s[4 * i + 1] - m0 : s[4 * i + 1]);
    const float e2 = ex2(SUB ? s[4 * i + 2] - m1 : s[4 * i + 2]), e3 = ex2(SUB ? s[4 * i + 3] - m1 : s[4 * i + 3]);
    if (i == 0) { t0 = e0; u0 = e1; t1 = e2; u1 = e3; }
    else { t0 += e0; u0 += e1; t1 += e2; u1 += e3; }
    P[2 * i] = pack_bf16(e0, e1);
    P[2 * i + 1] = pack_bf16(e2, e3);
  }
#pragma unroll
  for (int i = N / 2; i < 32; i++) P[i] = 0;
  pin(P);
  t0 += u0; t1 += u1;
}
template <int N>
__device__ __forceinline__ void causal_mask(float (&s)[N], int thr) {
#pragma unroll
  for (int i = 0; i < 8; i++) {
    if (8 * i > thr) s[N - 32 + 4 * i] = -INFINITY;
    if (8 * i + 1 > thr) s[N - 32 + 4 * i + 1] = -INFINITY;
    if (8 * i - 8 > thr) s[N - 32 + 4 * i + 2] = -INFINITY;
    if (8 * i - 7 > thr) s[N - 32 + 4 * i + 3] = -INFINITY;
  }
}
__device__ __forceinline__ void issue_qk(float (&s)[32], uint32_t qd, uint32_t kd) {
  WG_FENCE();
#pragma unroll
  for (int kk = 0; kk < 8; kk++) wgmma_ss64<0>(s, qd + (kk >> 2) * 512 + (kk & 3) * 2, kd + (kk >> 2) * 1024 + (kk & 3) * 2, kk != 0);
  WG_COMMIT();
}
__device__ __forceinline__ void issue_qk(float (&s)[64], uint32_t qd, uint32_t kd) {
  WG_FENCE();
#pragma unroll
  for (int kk = 0; kk < 8; kk++) wgmma_ss128<0>(s, qd + (kk >> 2) * 512 + (kk & 3) * 2, kd + (kk >> 2) * 1024 + (kk & 3) * 2, kk != 0);
  WG_COMMIT();
}
template <int NK>
__device__ __forceinline__ void issue_pv(float (&o)[64], const uint32_t (&P)[32], uint32_t vd, int acc) {
  WG_FENCE();
#pragma unroll
  for (int kk = 0; kk < NK; kk++) wgmma_rs128<1>(o, P[4 * kk], P[4 * kk + 1], P[4 * kk + 2], P[4 * kk + 3], vd + kk * 128, kk != 0 ? 1 : acc);
  WG_COMMIT();
}
__device__ __forceinline__ void p2_epilogue(const float (&o)[64], float s0, float s1, const Ctx& c, int b) {
  stage_tile(o, c.sm + SM_BUF + b * 16384, c, s0, s1);
  FENCE_ASYNC_SMEM();
  __syncwarp();
  if (c.lane == 0) mbar_arrive(c.bar + (B_SF + b) * 8);
}

struct P2State {
  float m0, m1, l0, l1;
  bool shift;
  float e0, e1;
  int row0;
  int ks;
  int wi, ai;
  uint32_t wb, ab;
  uint32_t qd;
};
__device__ __forceinline__ int wrap5(int q) { return q >= 5 ? q - 5 : q; }
__device__ __forceinline__ void turn_wait(uint32_t ring, int i) { mbar_wait(ring + (i & 3) * 8, (i >> 2) & 1); }
__device__ __forceinline__ void turn_pass(const Ctx& c, uint32_t ring, int i) { if (c.lane == 0) mbar_arrive(ring + (i & 3) * 8); }
__device__ __forceinline__ void p2_scales(P2State& z, const Ctx& c) {
  const float* g = g_gate + z.row0 + c.warp * 16 + (c.lane >> 2);
  const float g0 = __ldcg(g), g1 = __ldcg(g + 8);
  float l0 = z.l0, l1 = z.l1;
  l0 += __shfl_xor_sync(0xffffffffu, l0, 1);
  l1 += __shfl_xor_sync(0xffffffffu, l1, 1);
  l0 += __shfl_xor_sync(0xffffffffu, l0, 2);
  l1 += __shfl_xor_sync(0xffffffffu, l1, 2);
  z.e0 = __fdividef(1.f - g0, l0); z.e1 = __fdividef(1.f - g1, l1);
}
template <int N, bool PV>
__device__ __forceinline__ void p2_first(const Params& p, const Ctx& c, P2State& z, float (&o)[64], uint32_t (&Pc)[32], uint32_t (&Pn)[32],
                                         int ks, int vs, int cnt, int acc, int row0) {
  float s[N] = {};
  issue_qk(s, z.qd, desc_lo(c.sm + SM_RING, 16) + ks * 2048);
  if (PV) issue_pv<8>(o, Pc, desc_lo(c.sm + SM_RING, 16384) + vs * 2048, acc);
  turn_pass(c, z.ab, z.ai++);
  if (PV) WG_WAIT(1); else WG_WAIT(0);
  pin(s);
  release(c, B_P2E + ks, cnt);
  if (PV) p2_scales(z, c);
  z.row0 = row0;
  causal_mask(s, c.warp * 16 + (c.lane >> 2) - 2 * (c.lane & 3));
  z.m0 = z.m1 = 0.f;
  row_exp<false>(s, Pn, 0.f, 0.f, z.l0, z.l1);
  uint32_t b0 = __ballot_sync(0xffffffffu, z.l0 >= SM_LO), b1 = __ballot_sync(0xffffffffu, z.l1 >= SM_LO);
  b0 |= b0 >> 1; b1 |= b1 >> 1;
  z.shift = __any_sync(0xffffffffu, !(z.l0 + z.l1 <= SM_HI)) || (((b0 | b0 >> 2) & (b1 | b1 >> 2) & 0x11111111u) != 0x11111111u);
  if (__builtin_expect(z.shift, 0)) {
    z.m0 = z.m1 = -INFINITY;
    row_max(s, z.m0, z.m1);
    row_exp<true>(s, Pn, z.m0, z.m1, z.l0, z.l1);
  }
  if (PV) {
    WG_WAIT(0);
    pin(o);
    release(c, B_P2E + vs, 1);
  }
}

template <bool SECOND>
__device__ __forceinline__ void p2_turn(const Ctx& c, P2State& z, float (&o)[64], uint32_t (&Pc)[32], uint32_t (&Pn)[32],
                                        int eb = -1, bool half = false, int vcnt = 1) {
  float s[64] = {};
  const int ks = z.ks, vs = wrap5(ks + 1);
  turn_wait(z.wb, z.wi++);
  issue_qk(s, z.qd, desc_lo(c.sm + SM_RING, 16) + ks * 2048);
  const uint32_t vd = desc_lo(c.sm + SM_RING, 16384) + vs * 2048;
  if (SECOND) {
    if (eb >= 0) p2_epilogue(o, z.e0, z.e1, c, eb);
    if (half) issue_pv<4>(o, Pc, vd, 0); else issue_pv<8>(o, Pc, vd, 0);
  } else {
    issue_pv<8>(o, Pc, vd, 1);
  }
  turn_pass(c, z.ab, z.ai++);
  z.ks = wrap5(ks + 2);
  WG_WAIT(1);
  pin(s);
  release(c, B_P2E + ks, 1);
  float t0, t1, a0 = 1.f, a1 = 1.f;
  row_exp<false>(s, Pn, 0.f, 0.f, t0, t1);
  z.shift = __any_sync(0xffffffffu, z.shift || !(t0 + t1 <= SM_HI));
  const bool redo = z.shift;
  if (__builtin_expect(redo, 0)) {
    float n0 = z.m0, n1 = z.m1;
    row_max(s, n0, n1);
    a0 = ex2(z.m0 - n0); a1 = ex2(z.m1 - n1);
    z.m0 = n0; z.m1 = n1;
    z.l0 *= a0; z.l1 *= a1;
    row_exp<true>(s, Pn, z.m0, z.m1, t0, t1);
  }
  WG_WAIT(0);
  pin(o);
  release(c, B_P2E + vs, vcnt);
  if (__builtin_expect(redo, 0)) {
#pragma unroll
    for (int i = 0; i < 16; i++) { o[4 * i] *= a0; o[4 * i + 1] *= a0; o[4 * i + 2] *= a1; o[4 * i + 3] *= a1; }
  }
  z.l0 += t0; z.l1 += t1;
}
__device__ __forceinline__ void copy_p(uint32_t (&d)[32], const uint32_t (&s)[32], int zero) {
#pragma unroll
  for (int i = 0; i < 32; i++) asm volatile("add.s32 %0, %1, %2;" : "=r"(d[i]) : "r"(s[i]), "r"(zero));
}

__device__ __forceinline__ void p2_consumer(const Params& p, const Ctx& c, int rot) {
  const int nit = p.s.r[c.cl].n2;
  const uint32_t fring = c.bar + B_P2F * 8, oring = c.bar + B_ORD * 8;
  float o[64] = {};
  uint32_t Pa[32] = {}, Pb[32] = {};
  P2State z;
  z.e0 = z.e1 = z.l0 = z.l1 = 0.f; z.row0 = 0; z.ks = rot; z.shift = false;
  int acc = 0, n = 0;
  for (int it = 0; it < nit; it++) {
    const int j = p.s.r[c.cl].item[it] & 7, blk = p2_blk(c.rank, c.wg, it), row0 = (j * 4 + blk) * 64;
    const int lng = ((it ^ c.wg) & 1) ^ 1;
    z.qd = desc_lo(c.sm + SM_BUF, 16) + p2_buf(c.wg, it) * 1024;
    if (lng) { z.wb = oring; z.wi = n - it; z.ab = fring; z.ai = n + 1; }
    else { z.wb = fring; z.wi = n + 2; z.ab = oring; z.ai = n - it; }
    mbar_wait(c.bar + (B_QF + p2_buf(c.wg, it)) * 8, (it >> 1) & 1);
    turn_wait(fring, n + 1 - lng);
    if (it == 0) {
      const int ks = wrap5(rot + c.wg);
      if (blk & 1) p2_first<64, false>(p, c, z, o, Pa, Pb, ks, 0, 1 + lng, 0, row0);
      else p2_first<32, false>(p, c, z, o, Pa, Pb, ks, 0, 1 + lng, 0, row0);
      z.ks = wrap5(rot + 1 + 2 * c.wg);
    } else {
      const int vs = wrap5(z.ks + 1), ks = lng ? z.ks : wrap5(z.ks + 2);
      if (blk & 1) p2_first<64, true>(p, c, z, o, Pa, Pb, ks, vs, 1 + lng, acc, row0);
      else p2_first<32, true>(p, c, z, o, Pa, Pb, ks, vs, 1 + lng, acc, row0);
      z.ks = wrap5(ks + 2);
    }
    PROF(c.wg, 24 + it);
    n += 2 * j + 2;
    int left = 2 * j + lng;
    acc = left != 0;
    if (left == 0) { copy_p(Pa, Pb, p.zero); continue; }
    p2_turn<true>(c, z, o, Pb, Pa, it > 0 ? p2_buf(c.wg, it - 1) : -1, !(blk & 1), 1 + lng);
    while (--left > 0) {
      p2_turn<false>(c, z, o, Pa, Pb);
      if (--left == 0) { copy_p(Pa, Pb, p.zero); break; }
      p2_turn<false>(c, z, o, Pb, Pa);
    }
  }
  {
    if (!acc && nit > 1) p2_epilogue(o, z.e0, z.e1, c, p2_buf(c.wg, nit));
    turn_wait(z.wb, z.wi);
    issue_pv<8>(o, Pa, desc_lo(c.sm + SM_RING, 16384) + z.ks * 2048, acc);
    if (((nit - 1) ^ c.wg) & 1) turn_pass(c, z.ab, z.ai);
    p2_scales(z, c);
    WG_WAIT(0);
    pin(o);
    p2_epilogue(o, z.e0, z.e1, c, p2_buf(c.wg, nit - 1));
    PROF(c.wg, 24 + nit);
  }
}

__device__ __forceinline__ void p2_load_q(const Params& p, const Ctx& c, int it, int w) {
  const int item = p.s.r[c.cl].item[it], h = item >> 3, j = item & 7, b = p2_buf(w, it);
  mbar_expect(c.bar + (B_QF + b) * 8, 16384);
  bulk_load(c.sm + SM_BUF + b * 16384, g_Q + (size_t)(h * 32 + j * 4 + p2_blk(c.rank, w, it)) * 16384, 16384, c.bar + (B_QF + b) * 8, POL(4));
}
__device__ __forceinline__ void p2_producer(const Params& p, const Ctx& c, int u1, int rot) {
  const int nit = p.s.r[c.cl].n2;
  int slot = rot, cnt = 0, par = 1, n = 0;
  bool nxok = false;
  const uint8_t* pv = nullptr;
  auto load = [&](const uint8_t* src, int expect) {
    if (cnt < 5) {
      if (u1) {
        mbar_wait(c.bar + (B_P1E + 2 * slot) * 8, ((u1 - 1 - 2 * slot) / 10) & 1);
        mbar_wait(c.bar + (B_P1E + 2 * slot + 1) * 8, ((u1 - 2 - 2 * slot) / 10) & 1);
        if (cnt == 0) p2_load_q(p, c, 0, 1);
      }
      cnt++;
    } else {
      if (slot == rot) par ^= 1;
      mbar_wait(c.bar + (B_P2E + slot) * 8, par);
    }
    const uint32_t fb = c.bar + (B_P2F + (n & 3)) * 8;
    if (expect) mbar_expect(fb, expect);
    bulk_load_mc(c.sm + SM_RING + slot * 32768 + c.rank * 16384, src, 16384, fb);
    if (cnt == 1 && u1) {
      mbar_wait(c.bar + (B_SE + 1) * 8, (p.s.r[c.cl].n1 - 1) & 1);
      p2_load_q(p, c, 0, 0);
    }
    slot = wrap5(slot + 1);
  };
  for (int it = 0; it < nit; it++) {
    const int item = p.s.r[c.cl].item[it], h = item >> 3, j = item & 7;
    if (c.phases & 16) {
      if (it == 1) flag_wait<true>(F_GATE, 256);
      if (!nxok) flag_wait<false>(F_HEAD + h, 96);
    }
    nxok = false;
    if (it == 0 && !u1) { p2_load_q(p, c, 0, 0); p2_load_q(p, c, 0, 1); }
    for (int t = 2 * j + 1; t >= 0; t--) {
      const uint8_t* k = g_KV + (size_t)(h * 16 + t) * 32768 + c.rank * 16384;
      if (PF2) {
        int ph = h, pt = t - PF2;
        if (pt < 0 && it + 1 < nit) {
          const int nx = p.s.r[c.cl].item[it + 1];
          if (!nxok) nxok = !(c.phases & 16) || flag_test(F_HEAD + (nx >> 3), 96);
          if (nxok) { ph = nx >> 3; pt += 2 * (nx & 7) + 2; }
        }
        if (pt >= 0) {
          const uint8_t* f = g_KV + (size_t)(ph * 16 + pt) * 32768 + c.rank * 16384;
          bulk_prefetch(f, 16384);
          bulk_prefetch(f + (size_t)NH * 16 * 32768, 16384);
        }
      }
      load(k, pv ? 65536 : 32768);
      if (pv) load(pv, 0);
      pv = k + (size_t)NH * 16 * 32768;
      n++;
    }
  }
  if ((c.phases & 16) && nit == 1) flag_wait<true>(F_GATE, 256);
  load(pv, 32768);
}

__device__ __forceinline__ void p2_storer(const Params& p, const Ctx& c, int sfpar) {
  const int nit = p.s.r[c.cl].n2;
  auto load_q = [&](int it, int w) {
    if (c.phases & 16) flag_wait<false>(F_HEAD + (p.s.r[c.cl].item[it] >> 3), 96);
    p2_load_q(p, c, it, w);
  };
  if (nit > 1) { load_q(1, 1); mbar_wait(c.bar + B_LAD * 8, 0); p2_load_q(p, c, 1, 0); }
  for (int i = 0; i < 2 * nit; i++) {
    const int it = i >> 1, w = (it ^ i ^ 1) & 1, b = p2_buf(w, it);
    const int item = p.s.r[c.cl].item[it], h = item >> 3, j = item & 7;
    mbar_wait(c.bar + (B_SF + b) * 8, (sfpar >> b) & 1);
    sfpar ^= 1 << b;
    bulk_store(g_Q + (size_t)(h * 32 + j * 4 + p2_blk(c.rank, w, it)) * 16384, c.sm + SM_BUF + b * 16384, 16384, POL(1));
    BULK_COMMIT();
    if (it + 2 < nit) { BULK_WAIT_READ(0); load_q(it + 2, w); }
    BULK_WAIT(0);
    flag_add_rx(F_CTX + j * 64 + h);
  }
}

__device__ __forceinline__ void p3_consumer(const Params& p, const Ctx& c) {
  const int tile = p.s.r[c.cl].p3, j = tile / 3, nt = tile - 3 * j;
  const uint32_t ad = desc_lo(c.sm + SM_RING + c.wg * 8192, 16), bd = desc_lo(c.sm + SM_RING + 16384, 4096);
  float acc[96] = {};
  int slot = 0, par = 0, prev = 0;
#pragma unroll 1
  for (int kb = 0; kb < 9; kb++) {
    mbar_wait(c.bar + (B_P3F + slot) * 8, par);
    if (kb == 0) PROF(c.wg, 39);
    WG_FENCE();
#pragma unroll
    for (int kk = 0; kk < 4; kk++) wgmma_ss192<1, 1>(acc, ad + slot * 2560 + kk * 128, bd + slot * 2560 + (kk >> 1) * 768 + (kk & 1) * 128, kk != 0 ? 1 : kb != 0);
    WG_COMMIT();
    WG_WAIT(1);
    if (kb > 0) release(c, B_P3E + prev);
    prev = slot;
    if (++slot == 5) { slot = 0; par ^= 1; }
  }
#pragma unroll 1
  for (int kb = 9; kb < NKB3; kb++) {
    mbar_wait(c.bar + (B_P3F + slot) * 8, par);
    WG_FENCE();
#pragma unroll
    for (int kk = 0; kk < 4; kk++) wgmma_ss192<1>(acc, ad + slot * 2560 + kk * 2, bd + slot * 2560 + (kk >> 1) * 768 + (kk & 1) * 128, 1);
    WG_COMMIT();
    WG_WAIT(1);
    release(c, B_P3E + prev);
    prev = slot;
    if (++slot == 5) { slot = 0; par ^= 1; }
  }
  WG_WAIT(0);
  pin(acc);
  PROF(c.wg, 40);
  const int row = (c.lane & 7) + ((c.lane >> 3) & 1) * 8;
  const uint32_t wbase = c.sm + SM_RING + c.wg * 8192 + c.warp * 2048;
  const uint32_t base = wbase + row * 128 + (((c.lane >> 4) ^ (row & 7)) << 4);
#pragma unroll
  for (int i = 0; i < 12; i++)
    stsm4((base ^ ((i & 3) << 5)) + (i >> 2) * 40960, pack_bf16(acc[8 * i], acc[8 * i + 1]), pack_bf16(acc[8 * i + 2], acc[8 * i + 3]),
          pack_bf16(acc[8 * i + 4], acc[8 * i + 5]), pack_bf16(acc[8 * i + 6], acc[8 * i + 7]));
  FENCE_ASYNC_SMEM();
  __syncwarp();
#pragma unroll
  for (int i = 0; i < 3; i++) tma2d_store(&p.map_out, wbase + i * 40960, nt * 192 + i * 64, j * 256 + c.rank * 128 + c.wg * 64 + c.warp * 16);
  BULK_COMMIT();
  BULK_WAIT_READ(0);
}

__device__ __forceinline__ void p3_producer(const Params& p, const Ctx& c) {
  const int tile = p.s.r[c.cl].p3, j = tile / 3, nt = tile - 3 * j;
  int slot = 0, par = 0;
  for (int q = -1; q < 32; q++) {
    const int g = q < 0 ? 32 : p.s.p3_order[j][q];
    if (c.phases & 16) flag_wait<false>(F_CTX + j * 64 + g, q < 0 ? 16 : 4);
    const int nk = q < 0 ? 9 : 2, k0 = (q < 0 ? 0 : g * 128) + c.rank * 32;
    const uint8_t* a = q < 0 ? g_oA + (j * 4 + c.rank * 2) * 73728 : g_Q + (size_t)(g * 32 + j * 4 + c.rank * 2) * 16384;
    const CUtensorMap* m = &p.map_o[q < 0];
    for (int i = 0; i < nk; i++) {
      const uint32_t st = c.sm + SM_RING + slot * 40960, fb = c.bar + (B_P3F + slot) * 8;
      mbar_wait(c.bar + (B_P3E + slot) * 8, par);
      mbar_expect(fb, 40960);
      bulk_load(st, a + i * 8192, 8192, fb, POL(3));
      bulk_load(st + 8192, a + (nk + i) * 8192, 8192, fb, POL(3));
      tma3d_mc(st + 16384 + c.rank * 12288, m, 0, k0 + i * 64, nt * 3, fb);
      if (++slot == 5) { slot = 0; par ^= 1; }
    }
  }
}

__device__ __forceinline__ float bf_lo(uint32_t w) { return __uint_as_float(w << 16); }
__device__ __forceinline__ float bf_hi(uint32_t w) { return __uint_as_float(w & 0xffff0000u); }

__device__ __forceinline__ void gate_rows(const Params& p, int row0, int lane) {
  const uint4* x = reinterpret_cast<const uint4*>(p.x + (size_t)(row0 + (lane >> 2)) * DM) + (lane & 3);
  const uint4* w = reinterpret_cast<const uint4*>(p.gate_w) + (lane & 3);
  float a = 0.f;
#pragma unroll 1
  for (int b = 0; b < 3; b++) {
    uint4 u[6];
#pragma unroll
    for (int i = 0; i < 6; i++) u[i] = __ldg(x + (b * 6 + i) * 4);
#pragma unroll
    for (int i = 0; i < 6; i++) {
      const uint4 v = __ldg(w + (b * 6 + i) * 4);
      a = fmaf(bf_lo(u[i].x), bf_lo(v.x), a); a = fmaf(bf_hi(u[i].x), bf_hi(v.x), a);
      a = fmaf(bf_lo(u[i].y), bf_lo(v.y), a); a = fmaf(bf_hi(u[i].y), bf_hi(v.y), a);
      a = fmaf(bf_lo(u[i].z), bf_lo(v.z), a); a = fmaf(bf_hi(u[i].z), bf_hi(v.z), a);
      a = fmaf(bf_lo(u[i].w), bf_lo(v.w), a); a = fmaf(bf_hi(u[i].w), bf_hi(v.w), a);
    }
  }
  a += __shfl_xor_sync(0xffffffffu, a, 1);
  a += __shfl_xor_sync(0xffffffffu, a, 2);
  if ((lane & 3) == 0) g_gate[row0 + (lane >> 2)] = 1.f / (1.f + __expf(-a));
}

__device__ __forceinline__ void lds10(uint32_t (&k)[10], uint32_t a) {
  asm volatile("ld.shared.v2.u32 {%0, %1}, [%10];\nld.shared.v2.u32 {%2, %3}, [%10+8];\nld.shared.v2.u32 {%4, %5}, [%10+16];\n"
               "ld.shared.v2.u32 {%6, %7}, [%10+24];\nld.shared.v2.u32 {%8, %9}, [%10+32];"
               : "=r"(k[0]), "=r"(k[1]), "=r"(k[2]), "=r"(k[3]), "=r"(k[4]), "=r"(k[5]), "=r"(k[6]), "=r"(k[7]), "=r"(k[8]), "=r"(k[9]) : "r"(a));
}
__device__ __forceinline__ void local_attn(const Params& p, const Ctx& c, int rb, int hs) {
  const int lane = c.lane, grp = rb >> 2, par = lane >> 4, i0 = 2 * (lane & 15);
  const uint32_t buf = c.sm + SM_BUF + (c.warp - 2) * 8192, bqk = c.bar + (B_LA + (c.warp - 2) * 2) * 8, bv = bqk + 8;
  const uint32_t mine = buf + 2304 + par * 160 + i0 * 4;
  const bool flags = c.phases & 16;
  auto fetch_qk = [&](int i) {
    if (flags && !(i & 1)) {
      const int q = i >> 1;
      const int tgt = q == 0 ? 24 : q == 3 ? 8 : 12;
      flag_wait<false>(F_QKVA + (grp - (grp > 0 && (rb & 3) == 0 ? par : 0)) * 4 + q, tgt);
    }
    mbar_expect(bqk, 5184);
    tma3d(buf, &p.map_t[0], rb * 32 + 8, 0, 9 * (4 * i + hs), bqk, POL(2));
    tma3d(buf + 2304, &p.map_t[1], rb * 32, 0, 288 + 9 * (4 * i + hs), bqk, POL(2));
  };
  auto fetch_v = [&](int i) { mbar_expect(bv, 2880); tma3d(buf + 5248, &p.map_t[1], rb * 32, 0, 576 + 9 * (4 * i + hs), bv, POL(2)); };
  fetch_qk(0);
  if (flags) flag_wait<true>(F_GATE, 256);
#pragma unroll 1
  for (int q = 0; q < 8; q++) {
    fetch_v(q);
    float a[8], b[8];
#pragma unroll
    for (int w = 0; w < 8; w++) a[w] = b[w] = 0.f;
    mbar_wait(bqk, q & 1);
    PROFB(1 + 2 * q);
#pragma unroll 1
    for (int j = 0; j < 9; j++) {
      uint32_t x, y, k[10];
      asm volatile("ld.shared.v2.u32 {%0, %1}, [%2];" : "=r"(x), "=r"(y) : "r"(buf + lane * 8 + j * 256));
      lds10(k, mine + j * 320);
      const float xl = bf_lo(x), xh = bf_hi(x), yl = bf_lo(y), yh = bf_hi(y);
#pragma unroll
      for (int m = 1; m < 10; m++) {
        const float kl = bf_lo(k[m]), kh = bf_hi(k[m]);
        if (m < 9) a[8 - m] = fmaf(xl, kl, fmaf(xh, kh, a[8 - m]));
        if (m > 1) b[9 - m] = fmaf(yl, kl, fmaf(yh, kh, b[9 - m]));
      }
    }
    __syncwarp();
    if (q < 7) fetch_qk(q + 1);
    constexpr float SC = 0.23570226039551584f * 1.4426950408889634f;
    const float* gp = g_gate + rb * 64 + 2 * i0 + par;
    const float ga = __ldcg(gp), gb = __ldcg(gp + 2);
    float ma = a[0], mb = b[0];
#pragma unroll
    for (int w = 1; w < 8; w++) {
      if (rb == 0) {
        if (i0 < w) a[w] = -INFINITY;
        if (i0 + 1 < w) b[w] = -INFINITY;
      }
      ma = fmaxf(ma, a[w]); mb = fmaxf(mb, b[w]);
    }
    float la = 0.f, lb = 0.f;
#pragma unroll
    for (int w = 0; w < 8; w++) {
      a[w] = ex2((a[w] - ma) * SC); b[w] = ex2((b[w] - mb) * SC);
      la += a[w]; lb += b[w];
    }
    la = __fdividef(ga, la); lb = __fdividef(gb, lb);
#pragma unroll
    for (int w = 0; w < 8; w++) { a[w] *= la; b[w] *= lb; }
    uint8_t* dst = g_oA + rb * 73728 + ((i0 & 2) + par) * 4;
    mbar_wait(bv, q & 1);
#pragma unroll 1
    for (int j = 0; j < 9; j++) {
      uint32_t v[10];
      lds10(v, mine + 2944 + j * 320);
      float a0 = 0.f, a1 = 0.f, b0 = 0.f, b1 = 0.f;
#pragma unroll
      for (int m = 1; m < 10; m++) {
        const float vl = bf_lo(v[m]), vh = bf_hi(v[m]);
        if (m < 9) { a0 = fmaf(a[8 - m], vl, a0); a1 = fmaf(a[8 - m], vh, a1); }
        if (m > 1) { b0 = fmaf(b[9 - m], vl, b0); b1 = fmaf(b[9 - m], vh, b1); }
      }
      const uint32_t wa = pack_bf16(a0, a1), wb = pack_bf16(b0, b1);
      const uint32_t got = __shfl_xor_sync(0xffffffffu, par ? wa : wb, 16);
      const uint32_t r0 = par ? got : wa, r1 = par ? wb : got;
      const int col = 18 * (4 * q + hs) + 2 * j, o = col * 128 + ((((i0 >> 2) ^ col) & 7) << 4);
      *reinterpret_cast<uint32_t*>(dst + o) = __byte_perm(r0, r1, 0x5410);
      *reinterpret_cast<uint32_t*>(dst + ((o + 128) ^ 16)) = __byte_perm(r0, r1, 0x7632);
    }
    __syncwarp();
    PROFB(2 + 2 * q);
  }
  mbar_arrive_one(c.bar + B_LAD * 8);
  flag_add(F_CTX + grp * 64 + 32);
}

__global__ void __cluster_dims__(2, 1, 1) __launch_bounds__(384, 1) fused_kernel(const __grid_constant__ Params p) {
  extern __shared__ uint8_t smem_raw[];
  Ctx c;
  c.sm = ((uint32_t)__cvta_generic_to_shared(smem_raw) + 1023u) & ~1023u;
  c.bar = c.sm + SM_BAR;
  c.lane = threadIdx.x & 31;
  c.wg = __shfl_sync(0xffffffffu, threadIdx.x >> 7, 0);
  c.warp = __shfl_sync(0xffffffffu, (threadIdx.x >> 5) & 3, 0);
  PROF(c.wg, 0);
  PROFG(61);
  c.cl = blockIdx.x >> 1;
  c.rank = blockIdx.x & 1;
  c.rbar = mapa(c.bar, c.lane & 1);
  if (threadIdx.x == 288) {
#pragma unroll
    for (int i = 0; i < B_NUM; i++) {
      int cnt = 1;
      if ((i >= B_P1E && i < B_P1E + 10) || (i >= B_P2E && i < B_P2E + 5) || (i >= B_P3E && i < B_P3E + 5)) cnt = 16;
      if (i >= B_P2F && i < B_P2F + 4) cnt = 5;
      if ((i >= B_SF && i < B_SF + 4) || (i >= B_ORD && i < B_ORD + 4)) cnt = 4;
      if (i == B_LAD) cnt = 2;
      if (i == B_FIN) cnt = 8;
      asm volatile("mbarrier.init.shared::cta.b64 [%0], %1;" ::"r"(c.bar + i * 8), "r"(cnt));
    }
    asm volatile("fence.mbarrier_init.release.cluster;" ::: "memory");
  }
  __syncwarp();
  asm volatile("barrier.cluster.arrive.relaxed;" ::: "memory");
  if (c.wg * 4 + c.warp < 6) asm volatile(ELECT("prefetch.tensormap [%0];") ::"l"(&p.map_a[0] + c.wg * 4 + c.warp) : "memory");
  c.phases = p.s.r[c.cl].phases;
  const bool do1 = (c.phases & 1) && p.s.r[c.cl].n1 > 0;
  const bool do2 = (c.phases & 2) && p.s.r[c.cl].n2 > 0;
  const bool do3 = (c.phases & 4) && p.s.r[c.cl].p3 != 255;
  const int u1 = do1 ? 8 + p.s.r[c.cl].n1 * (8 + (p.s.r[c.cl].slab >> 3)) : 0;
  const int rot = ((u1 % 10 + 1) >> 1) % 5;
  asm volatile("barrier.cluster.wait.acquire;" ::: "memory");

  if (c.wg < 2) {
    PROF(c.wg, 4);
    asm volatile("setmaxnreg.inc.sync.aligned.u32 224;");
    if (c.wg == 1) { if (do1) bar_arrive(ORDER, 256); else if (c.lane == 0) mbar_arrive(c.bar + B_P2F * 8); }
    if (do1) p1_consumer(p, c);
    if (do2) p2_consumer(p, c, rot);
    if (do3) {
      mbar_wait(c.bar + B_DONE * 8, 0);
#pragma unroll
      for (int i = 0; i < 5; i++) release(c, B_P3E + i);
      p3_consumer(p, c);
    }
    PROF(c.wg, 63);
    PROFG(62);
    if (c.lane == 0) mbar_arrive(c.bar + B_FIN * 8);
    __syncwarp();
    cluster_sync();
  } else {
    asm volatile("setmaxnreg.dec.sync.aligned.u32 56;");
    if (c.warp == 0) {
      PROF(2, 60);
      if (do1) p1_producer(p, c);
      if (do2) p2_producer(p, c, u1, rot);
      if (do3) p3_producer(p, c);
    } else if (c.warp == 1) {
      int sfpar = 0;
      if (do1) {
        p1_storer(p, c);
        sfpar = (p.s.r[c.cl].n1 & 1) * 10;
      }
      if (do2) p2_storer(p, c, sfpar);
      mbar_wait(c.bar + B_LAD * 8, 0);
      mbar_arrive_one(c.bar + B_DONE * 8);
    } else {
      const int bw = blockIdx.x * 2 + (c.warp - 2);
      if ((c.phases & 1) && bw < 256) {
        gate_rows(p, bw * 8, c.lane);
        __syncwarp();
        flag_add(F_GATE);
      }
      if ((c.phases & 8) && p.s.r[c.cl].bg != 255) local_attn(p, c, p.s.r[c.cl].bg, bw & 3);
      else if (c.lane == 0) mbar_arrive(c.bar + B_LAD * 8);
    }
    __syncwarp();
    bar_sync(3, 128);
    if (c.warp == 0 && (c.phases & 4)) {
      int last = 0;
      if (c.lane == 0) { __threadfence(); last = atomicAdd(g_flags + F_DONE, 1) == 2 * NCL - 1; }
      if (__shfl_sync(0xffffffffu, last, 0)) for (int i = c.lane; i < F_NUM; i += 32) g_flags[i] = 0;
    }
    if (c.warp == 1) mbar_wait(c.bar + B_FIN * 8, 0);
    __syncwarp();
    cluster_sync();
  }
}

static const Sched k_sched = {
  {{0,26,3,255,0,{224,193,230,0,0,0,0,0,0,0,0},{0,2,4,6,8,10,43,13,14,15,16,17,18,19,20,21,22,23,24,25,26,27,28,29,30,31,0,0,0,0,0,0}},
   {0,26,2,255,1,{206,233,0,0,0,0,0,0,0,0,0},{32,34,36,38,40,42,12,45,46,47,48,49,50,51,52,53,54,55,56,57,58,59,60,61,62,63,0,0,0,0,0,0}},
   {0,7,4,0,255,{74,65,85,125,0,0,0,0,0,0,0},{1,3,5,7,9,11,44,0,0,0,0,0,0,0,0,0,0,0,0,0,0,0,0,0,0,0,0,0,0,0,0,0}},
   {0,5,4,1,255,{61,76,94,184,0,0,0,0,0,0,0},{33,35,37,39,41,0,0,0,0,0,0,0,0,0,0,0,0,0,0,0,0,0,0,0,0,0,0,0,0,0,0,0}},
   {8,20,0,2,2,{0,0,0,0,0,0,0,0,0,0,0},{0,4,36,33,42,34,38,43,35,39,44,40,45,20,22,24,26,28,30,31,0,0,0,0,0,0,0,0,0,0,0,0}},
   {8,18,4,255,3,{112,149,188,218,0,0,0,0,0,0,0},{1,5,7,9,11,12,13,14,15,16,17,18,19,21,23,25,27,29,0,0,0,0,0,0,0,0,0,0,0,0,0,0}},
   {8,4,7,255,255,{9,44,55,130,155,179,213,0,0,0,0},{2,32,41,37,0,0,0,0,0,0,0,0,0,0,0,0,0,0,0,0,0,0,0,0,0,0,0,0,0,0,0,0}},
   {8,4,6,3,255,{16,34,18,58,109,147,0,0,0,0,0},{3,6,8,10,0,0,0,0,0,0,0,0,0,0,0,0,0,0,0,0,0,0,0,0,0,0,0,0,0,0,0,0}},
   {1,26,2,255,4,{180,210,0,0,0,0,0,0,0,0,0},{0,2,4,6,8,10,43,13,14,15,16,17,18,19,20,21,22,23,24,25,26,27,28,29,30,31,0,0,0,0,0,0}},
   {1,26,1,255,5,{191,0,0,0,0,0,0,0,0,0,0},{32,34,36,38,40,42,12,45,46,47,48,49,50,51,52,53,54,55,56,57,58,59,60,61,62,63,0,0,0,0,0,0}},
   {1,5,4,4,255,{2,63,110,144,0,0,0,0,0,0,0},{1,3,5,7,9,0,0,0,0,0,0,0,0,0,0,0,0,0,0,0,0,0,0,0,0,0,0,0,0,0,0,0}},
   {1,7,4,5,255,{17,14,114,124,0,0,0,0,0,0,0},{33,35,37,39,41,11,44,0,0,0,0,0,0,0,0,0,0,0,0,0,0,0,0,0,0,0,0,0,0,0,0,0}},
   {9,18,6,255,6,{104,178,165,211,241,248,0,0,0,0,0},{0,4,36,33,10,34,38,43,35,39,44,40,45,20,22,24,26,28,0,0,0,0,0,0,0,0,0,0,0,0,0,0}},
   {9,20,0,6,7,{0,0,0,0,0,0,0,0,0,0,0},{1,5,7,9,42,12,13,14,15,16,17,18,19,21,23,25,27,29,30,31,0,0,0,0,0,0,0,0,0,0,0,0}},
   {9,3,6,255,255,{4,28,78,163,172,255,0,0,0,0,0},{2,32,41,0,0,0,0,0,0,0,0,0,0,0,0,0,0,0,0,0,0,0,0,0,0,0,0,0,0,0,0,0}},
   {9,5,6,255,255,{48,21,67,126,158,254,0,0,0,0,0},{3,6,8,37,11,0,0,0,0,0,0,0,0,0,0,0,0,0,0,0,0,0,0,0,0,0,0,0,0,0,0,0}},
   {2,27,2,255,8,{202,220,0,0,0,0,0,0,0,0,0},{0,34,5,39,41,11,12,13,14,15,16,17,18,19,20,21,22,23,24,25,26,27,28,29,30,31,63,0,0,0,0,0}},
   {2,25,3,255,9,{187,203,242,0,0,0,0,0,0,0,0},{32,3,37,8,10,43,44,45,46,47,48,49,50,51,52,53,54,55,56,57,58,59,60,61,62,0,0,0,0,0,0,0}},
   {2,5,4,7,255,{23,68,116,168,0,0,0,0,0,0,0},{1,35,6,40,42,0,0,0,0,0,0,0,0,0,0,0,0,0,0,0,0,0,0,0,0,0,0,0,0,0,0,0}},
   {2,4,6,255,255,{39,57,82,119,175,227,0,0,0,0,0},{33,4,38,9,0,0,0,0,0,0,0,0,0,0,0,0,0,0,0,0,0,0,0,0,0,0,0,0,0,0,0,0}},
   {2,3,6,255,255,{15,47,121,135,201,229,0,0,0,0,0},{2,36,7,0,0,0,0,0,0,0,0,0,0,0,0,0,0,0,0,0,0,0,0,0,0,0,0,0,0,0,0,0}},
   {10,19,3,255,10,{136,173,222,0,0,0,0,0,0,0,0},{0,4,36,33,10,34,38,43,35,39,44,40,45,20,22,24,26,28,30,0,0,0,0,0,0,0,0,0,0,0,0,0}},
   {10,19,2,255,11,{150,253,0,0,0,0,0,0,0,0,0},{1,5,7,9,42,12,13,14,15,16,17,18,19,21,23,25,27,29,31,0,0,0,0,0,0,0,0,0,0,0,0,0}},
   {10,5,6,255,255,{56,31,86,177,183,237,0,0,0,0,0},{2,32,41,37,11,0,0,0,0,0,0,0,0,0,0,0,0,0,0,0,0,0,0,0,0,0,0,0,0,0,0,0}},
   {10,3,7,255,255,{3,27,89,90,111,159,219,0,0,0,0},{3,6,8,0,0,0,0,0,0,0,0,0,0,0,0,0,0,0,0,0,0,0,0,0,0,0,0,0,0,0,0,0}},
   {3,25,3,255,12,{176,231,232,0,0,0,0,0,0,0,0},{0,2,4,6,8,10,43,13,14,15,16,17,18,19,20,21,22,23,24,25,26,27,28,29,30,0,0,0,0,0,0,0}},
   {3,27,2,255,13,{197,250,0,0,0,0,0,0,0,0,0},{32,34,36,38,40,42,12,45,46,47,48,49,50,51,52,53,54,55,56,57,58,59,60,61,62,31,63,0,0,0,0,0}},
   {3,7,4,8,255,{72,52,84,141,0,0,0,0,0,0,0},{1,3,5,7,9,11,44,0,0,0,0,0,0,0,0,0,0,0,0,0,0,0,0,0,0,0,0,0,0,0,0,0}},
   {3,5,6,255,255,{8,30,102,137,143,246,0,0,0,0,0},{33,35,37,39,41,0,0,0,0,0,0,0,0,0,0,0,0,0,0,0,0,0,0,0,0,0,0,0,0,0,0,0}},
   {11,19,3,255,14,{128,156,247,0,0,0,0,0,0,0,0},{0,4,36,33,42,34,38,43,35,39,44,40,45,20,22,24,26,28,30,0,0,0,0,0,0,0,0,0,0,0,0,0}},
   {11,19,3,255,15,{157,195,243,0,0,0,0,0,0,0,0},{1,5,7,9,11,12,13,14,15,16,17,18,19,21,23,25,27,29,31,0,0,0,0,0,0,0,0,0,0,0,0,0}},
   {11,4,8,255,255,{12,99,83,122,134,185,196,234,0,0,0},{2,32,41,37,0,0,0,0,0,0,0,0,0,0,0,0,0,0,0,0,0,0,0,0,0,0,0,0,0,0,0,0}},
   {11,4,6,9,255,{0,35,38,106,123,160,0,0,0,0,0},{3,6,8,10,0,0,0,0,0,0,0,0,0,0,0,0,0,0,0,0,0,0,0,0,0,0,0,0,0,0,0,0}},
   {4,26,2,255,16,{205,226,0,0,0,0,0,0,0,0,0},{0,2,4,6,8,10,43,13,14,15,16,17,18,19,20,21,22,23,24,25,26,27,28,29,30,31,0,0,0,0,0,0}},
   {4,26,3,255,17,{216,238,249,0,0,0,0,0,0,0,0},{32,34,36,38,40,42,12,45,46,47,48,49,50,51,52,53,54,55,56,57,58,59,60,61,62,63,0,0,0,0,0,0}},
   {4,5,4,10,255,{62,77,129,131,0,0,0,0,0,0,0},{1,3,5,7,9,0,0,0,0,0,0,0,0,0,0,0,0,0,0,0,0,0,0,0,0,0,0,0,0,0,0,0}},
   {4,7,4,11,255,{80,20,71,138,0,0,0,0,0,0,0},{33,35,37,39,41,11,44,0,0,0,0,0,0,0,0,0,0,0,0,0,0,0,0,0,0,0,0,0,0,0,0,0}},
   {12,20,0,12,18,{0,0,0,0,0,0,0,0,0,0,0},{0,4,36,33,42,34,38,43,35,39,44,40,45,20,22,24,26,28,30,31,0,0,0,0,0,0,0,0,0,0,0,0}},
   {12,18,3,255,19,{161,166,204,0,0,0,0,0,0,0,0},{1,5,7,9,11,12,13,14,15,16,17,18,19,21,23,25,27,29,0,0,0,0,0,0,0,0,0,0,0,0,0,0}},
   {12,4,6,13,255,{40,19,13,105,113,140,0,0,0,0,0},{2,32,41,37,0,0,0,0,0,0,0,0,0,0,0,0,0,0,0,0,0,0,0,0,0,0,0,0,0,0,0,0}},
   {12,4,6,255,255,{22,66,92,127,189,251,0,0,0,0,0},{3,6,8,10,0,0,0,0,0,0,0,0,0,0,0,0,0,0,0,0,0,0,0,0,0,0,0,0,0,0,0,0}},
   {5,25,2,255,20,{208,207,0,0,0,0,0,0,0,0,0},{0,34,5,39,41,11,12,13,14,15,16,17,18,19,20,21,22,23,24,25,26,27,28,29,30,0,0,0,0,0,0,0}},
   {5,27,1,255,21,{239,0,0,0,0,0,0,0,0,0,0},{32,3,37,8,10,43,44,45,46,47,48,49,50,51,52,53,54,55,56,57,58,59,60,61,62,31,63,0,0,0,0,0}},
   {5,4,4,14,255,{43,11,108,142,0,0,0,0,0,0,0},{1,35,6,40,0,0,0,0,0,0,0,0,0,0,0,0,0,0,0,0,0,0,0,0,0,0,0,0,0,0,0,0}},
   {5,5,4,15,255,{51,100,97,95,0,0,0,0,0,0,0},{33,4,38,9,42,0,0,0,0,0,0,0,0,0,0,0,0,0,0,0,0,0,0,0,0,0,0,0,0,0,0,0}},
   {5,3,7,255,255,{10,45,107,87,170,182,235,0,0,0,0},{2,36,7,0,0,0,0,0,0,0,0,0,0,0,0,0,0,0,0,0,0,0,0,0,0,0,0,0,0,0,0,0}},
   {13,18,4,255,22,{96,154,174,244,0,0,0,0,0,0,0},{0,4,36,33,42,34,38,43,35,39,44,40,45,20,22,24,26,28,0,0,0,0,0,0,0,0,0,0,0,0,0,0}},
   {13,20,3,255,23,{152,167,252,0,0,0,0,0,0,0,0},{1,5,7,9,11,12,13,14,15,16,17,18,19,21,23,25,27,29,30,31,0,0,0,0,0,0,0,0,0,0,0,0}},
   {13,4,6,16,255,{32,49,36,70,162,153,0,0,0,0,0},{2,32,41,37,0,0,0,0,0,0,0,0,0,0,0,0,0,0,0,0,0,0,0,0,0,0,0,0,0,0,0,0}},
   {13,4,6,17,255,{1,59,50,101,139,192,0,0,0,0,0},{3,6,8,10,0,0,0,0,0,0,0,0,0,0,0,0,0,0,0,0,0,0,0,0,0,0,0,0,0,0,0,0}},
   {6,26,3,255,24,{200,194,245,0,0,0,0,0,0,0,0},{0,2,4,6,8,10,43,13,14,15,16,17,18,19,20,21,22,23,24,25,26,27,28,29,30,31,0,0,0,0,0,0}},
   {6,26,2,255,25,{186,221,0,0,0,0,0,0,0,0,0},{32,34,36,38,40,42,12,45,46,47,48,49,50,51,52,53,54,55,56,57,58,59,60,61,62,63,0,0,0,0,0,0}},
   {6,7,4,18,255,{64,6,93,146,0,0,0,0,0,0,0},{1,3,5,7,9,11,44,0,0,0,0,0,0,0,0,0,0,0,0,0,0,0,0,0,0,0,0,0,0,0,0,0}},
   {6,5,4,19,255,{42,69,81,103,0,0,0,0,0,0,0},{33,35,37,39,41,0,0,0,0,0,0,0,0,0,0,0,0,0,0,0,0,0,0,0,0,0,0,0,0,0,0,0}},
   {14,20,0,20,26,{0,0,0,0,0,0,0,0,0,0,0},{0,4,36,33,10,34,38,43,35,39,44,40,45,20,22,24,26,28,30,31,0,0,0,0,0,0,0,0,0,0,0,0}},
   {14,18,4,255,27,{88,148,190,225,0,0,0,0,0,0,0},{1,5,7,9,42,12,13,14,15,16,17,18,19,21,23,25,27,29,0,0,0,0,0,0,0,0,0,0,0,0,0,0}},
   {14,3,8,255,255,{29,5,91,132,169,215,217,240,0,0,0},{2,32,41,0,0,0,0,0,0,0,0,0,0,0,0,0,0,0,0,0,0,0,0,0,0,0,0,0,0,0,0,0}},
   {14,5,5,255,255,{41,54,79,151,212,0,0,0,0,0,0},{3,6,8,37,11,0,0,0,0,0,0,0,0,0,0,0,0,0,0,0,0,0,0,0,0,0,0,0,0,0,0,0}},
   {7,27,1,255,28,{214,0,0,0,0,0,0,0,0,0,0},{0,2,4,6,8,10,43,13,14,15,16,17,18,19,20,21,22,23,24,25,26,27,28,29,30,31,63,0,0,0,0,0}},
   {7,25,1,255,29,{199,0,0,0,0,0,0,0,0,0,0},{32,34,36,38,40,42,12,45,46,47,48,49,50,51,52,53,54,55,56,57,58,59,60,61,62,0,0,0,0,0,0,0}},
   {7,7,4,21,255,{25,73,46,117,0,0,0,0,0,0,0},{1,3,5,7,9,11,44,0,0,0,0,0,0,0,0,0,0,0,0,0,0,0,0,0,0,0,0,0,0,0,0,0}},
   {7,5,4,22,255,{53,60,115,171,0,0,0,0,0,0,0},{33,35,37,39,41,0,0,0,0,0,0,0,0,0,0,0,0,0,0,0,0,0,0,0,0,0,0,0,0,0,0,0}},
   {15,20,0,23,30,{0,0,0,0,0,0,0,0,0,0,0},{0,4,36,33,10,34,38,43,35,39,44,40,45,20,22,24,26,28,30,31,0,0,0,0,0,0,0,0,0,0,0,0}},
   {15,18,4,255,31,{120,145,198,236,0,0,0,0,0,0,0},{1,5,7,9,42,12,13,14,15,16,17,18,19,21,23,25,27,29,0,0,0,0,0,0,0,0,0,0,0,0,0,0}},
   {15,5,6,255,255,{33,37,75,118,164,223,0,0,0,0,0},{2,32,41,37,11,0,0,0,0,0,0,0,0,0,0,0,0,0,0,0,0,0,0,0,0,0,0,0,0,0,0,0}},
   {15,3,8,255,255,{24,26,7,98,133,209,181,228,0,0,0},{3,6,8,0,0,0,0,0,0,0,0,0,0,0,0,0,0,0,0,0,0,0,0,0,0,0,0,0,0,0,0,0}}},
  {{3,0,2,4,5,1,6,7,8,9,10,11,12,13,14,15,18,21,23,24,20,16,17,19,22,26,25,27,28,29,30,31},
   {0,1,6,4,5,2,3,9,8,11,7,10,12,13,14,16,15,17,19,20,22,18,26,21,23,24,25,28,29,27,31,30},
   {1,3,0,5,4,9,2,6,7,8,11,10,12,14,13,15,20,16,17,18,19,22,21,23,24,25,26,27,28,29,30,31},
   {0,5,6,2,4,7,3,1,12,13,8,10,9,11,14,17,15,16,21,18,20,19,22,23,24,25,26,27,30,28,31,29},
   {0,1,5,4,2,6,3,12,7,9,13,10,8,11,14,17,15,16,18,19,21,20,22,23,24,25,26,29,27,28,30,31},
   {3,6,7,5,2,4,8,1,0,10,9,12,13,11,14,15,17,16,18,19,21,20,22,23,25,24,31,26,27,28,30,29},
   {2,7,3,6,0,1,4,5,8,12,9,10,13,11,17,15,14,16,18,20,19,24,21,22,23,25,26,29,27,30,28,31},
   {1,4,2,3,0,7,5,6,8,9,11,12,10,13,14,15,16,17,18,22,19,20,21,24,26,25,23,28,30,29,31,27}}};

typedef CUresult (*EncodeFn)(CUtensorMap*, CUtensorMapDataType, cuuint32_t, void*, const cuuint64_t*, const cuuint64_t*, const cuuint32_t*,
                             const cuuint32_t*, CUtensorMapInterleave, CUtensorMapSwizzle, CUtensorMapL2promotion, CUtensorMapFloatOOBfill);

void make_map2(EncodeFn enc, CUtensorMap* m, const void* ptr, int rows, int cols, int box_rows) {
  cuuint64_t dim[2] = {(cuuint64_t)cols, (cuuint64_t)rows}, str[1] = {(cuuint64_t)cols * 2};
  cuuint32_t box[2] = {64, (cuuint32_t)box_rows}, es[2] = {1, 1};
  enc(m, CU_TENSOR_MAP_DATA_TYPE_BFLOAT16, 2, const_cast<void*>(ptr), dim, str, box, es, CU_TENSOR_MAP_INTERLEAVE_NONE, CU_TENSOR_MAP_SWIZZLE_128B,
      CU_TENSOR_MAP_L2_PROMOTION_L2_128B, CU_TENSOR_MAP_FLOAT_OOB_FILL_NONE);
}
void make_map3(EncodeFn enc, CUtensorMap* m, const void* ptr, int rows) {
  cuuint64_t dim[3] = {64, (cuuint64_t)rows, 9}, str[2] = {DM * 2, 128};
  cuuint32_t box[3] = {64, 32, 3}, es[3] = {1, 1, 1};
  enc(m, CU_TENSOR_MAP_DATA_TYPE_BFLOAT16, 3, const_cast<void*>(ptr), dim, str, box, es, CU_TENSOR_MAP_INTERLEAVE_NONE, CU_TENSOR_MAP_SWIZZLE_128B,
      CU_TENSOR_MAP_L2_PROMOTION_L2_128B, CU_TENSOR_MAP_FLOAT_OOB_FILL_NONE);
}

void make_map_t(EncodeFn enc, CUtensorMap* m, void* ptr, int width, int cols) {
  cuuint64_t dim[3] = {TP / 2, 2, 864}, str[2] = {TP * 2, TP * 4};
  cuuint32_t box[3] = {(cuuint32_t)width, 2, (cuuint32_t)cols}, es[3] = {1, 1, 1};
  enc(m, CU_TENSOR_MAP_DATA_TYPE_UINT32, 3, ptr, dim, str, box, es, CU_TENSOR_MAP_INTERLEAVE_NONE, cols == 64 ? CU_TENSOR_MAP_SWIZZLE_128B : CU_TENSOR_MAP_SWIZZLE_NONE,
      CU_TENSOR_MAP_L2_PROMOTION_NONE, CU_TENSOR_MAP_FLOAT_OOB_FILL_NONE);
}

int g_mode = -1;

}

extern "C" void kernel_launch(void* const* d_in, const int* in_sizes, int n_in, void* d_out, int out_size) {
  static EncodeFn enc = nullptr;
  static void* t_ptr = nullptr;
  if (!enc) {
    void* fn = nullptr;
    cudaDriverEntryPointQueryResult st;
    cudaGetDriverEntryPoint("cuTensorMapEncodeTiled", &fn, cudaEnableDefault, &st);
    enc = (EncodeFn)fn;
    cudaGetSymbolAddress(&t_ptr, g_T);
    cudaFuncSetAttribute(fused_kernel, cudaFuncAttributeMaxDynamicSharedMemorySize, SMEM_BYTES);
    if (g_mode < 0) {
      cudaLaunchConfig_t cfg = {};
      cfg.gridDim = dim3(2 * NCL); cfg.blockDim = dim3(384); cfg.dynamicSmemBytes = SMEM_BYTES;
      cudaLaunchAttribute at; at.id = cudaLaunchAttributeClusterDimension;
      at.val.clusterDim.x = 2; at.val.clusterDim.y = 1; at.val.clusterDim.z = 1;
      cfg.attrs = &at; cfg.numAttrs = 1;
      int nc = 0;
      g_mode = (cudaOccupancyMaxActiveClusters(&nc, fused_kernel, &cfg) == cudaSuccess && nc >= NCL) ? 1 : 0;
      (void)cudaGetLastError();
    }
  }
  Params p;
  make_map2(enc, &p.map_a[0], d_in[4], SEQ, DC, 128);
  make_map2(enc, &p.map_a[1], d_in[0], SEQ, DM, 128);
  make_map2(enc, &p.map_w[0], d_in[6], DC, 4096, 64);
  make_map2(enc, &p.map_w[1], d_in[7], DC, 4096, 64);
  make_map2(enc, &p.map_w[2], d_in[5], DM, 4096, 64);
  make_map2(enc, &p.map_w[3], d_in[1], DM, 1728, 64);
  make_map3(enc, &p.map_o[0], d_in[8], 4096);
  make_map3(enc, &p.map_o[1], d_in[2], DM);
  make_map_t(enc, &p.map_t[0], t_ptr, 32, 9);
  make_map_t(enc, &p.map_t[1], t_ptr, 40, 9);
  make_map_t(enc, &p.map_t[2], t_ptr, 32, 64);
  p.x = (const __nv_bfloat16*)d_in[0];
  p.gate_w = (const __nv_bfloat16*)d_in[9];
  make_map2(enc, &p.map_out, d_out, SEQ, DM, 16);
  p.zero = 0;
  p.s = k_sched;
  auto launch = [&](int phases) {
    for (int i = 0; i < NCL; i++) p.s.r[i].phases = (uint8_t)phases;
    fused_kernel<<<2 * NCL, 384, SMEM_BYTES>>>(p);
  };
  if (g_mode == 1) launch(31);
  else { launch(1); launch(10); launch(4); }
}
```

```cpp
#include <cuda_runtime.h>
#include <cuda_bf16.h>
#include <cuda.h>
#include <stdint.h>

namespace {

constexpr int SEQ = 2048, DM = 576, DC = 512, NH = 32;
constexpr int NCL = 66;
constexpr uint32_t DESC_HI = 0x40000040u;

constexpr int SM_RING = 0;
constexpr int SM_BUF = 163840;
constexpr int SM_BAR = 229376;
constexpr int B_P1F = 0, B_P1E = 10, B_P2F = 20, B_P2E = 25, B_P3F = 30, B_P3E = 35, B_SF = 40, B_SE = 44, B_QF = 48, B_DONE = 52, B_FIN = 53, B_ORD = 54, B_LA = 58, B_LAD = 62, B_OUT = 63, B_NUM = 64;
constexpr int SMEM_BYTES = SM_BAR + B_NUM * 8 + 1024;

constexpr int F_HEAD = 0;
constexpr int F_QKVA = 32;
constexpr int F_GATE = 64;
constexpr int F_DONE = 65;
constexpr int F_CTX = 96;
constexpr int F_OUT = 96 + 8 * 64;
constexpr int F_NUM = F_OUT + 48;

struct Rec {
  uint8_t slab;
  uint8_t n1, n2;
  uint8_t p3;
  uint8_t bg;
  uint8_t item[11];
  uint8_t tile[45];
  uint8_t ring;
  uint8_t u2;
  uint8_t phases;
};
struct Sched {
  Rec r[NCL];
  uint8_t ring, nh;
  uint8_t p3_order[8][32];
};

struct Params {
  CUtensorMap map_a[2];
  CUtensorMap map_w[4];
  CUtensorMap map_o[2];
  CUtensorMap map_t[3];
  CUtensorMap map_out;
  const __nv_bfloat16* x;
  const __nv_bfloat16* gate_w;
  int zero;
  alignas(64) Sched s;
};

__device__ __align__(1024) uint8_t g_Q[NH * 32 * 16384];
__device__ __align__(1024) uint8_t g_KV[2 * NH * 16 * 32768];
__device__ __align__(1024) uint8_t g_oA[32 * 576 * 128];
constexpr int TP = SEQ + 16;
__device__ __align__(1024) uint32_t g_T[864 * TP];
__device__ float g_gate[SEQ];
__device__ int g_flags[F_NUM];

__device__ __forceinline__ void mbar_arrive(uint32_t b) { asm volatile("mbarrier.arrive.shared::cta.b64 _, [%0];" ::"r"(b) : "memory"); }
__device__ __forceinline__ void mbar_arrive_cl(uint32_t b, int cnt) {
  asm volatile("mbarrier.arrive.shared::cluster.b64 _, [%0], %1;" ::"r"(b), "r"(cnt) : "memory");
}
__device__ __forceinline__ void mbar_wait(uint32_t b, int par) {
  asm volatile(
      "{\n.reg .pred p;\n.reg .u32 c;\n"
      "mbarrier.try_wait.parity.shared::cta.b64 p, [%0], %1;\n@p bra DN;\nmov.u32 c, 0;\n"
      "LP:\nmbarrier.try_wait.parity.shared::cta.b64 p, [%0], %1;\n@p bra DN;\n"
      "add.u32 c, c, 1;\nsetp.lt.u32 p, c, 4000000;\n@p bra LP;\ntrap;\nDN:\n}" ::"r"(b), "r"(par) : "memory");
}
__device__ __forceinline__ uint32_t mapa(uint32_t a, uint32_t cta) {
  uint32_t r; asm("mapa.shared::cluster.u32 %0, %1, %2;" : "=r"(r) : "r"(a), "r"(cta)); return r;
}
#define ELECT(ins) "{\n.reg .pred e;\nelect.sync _|e, 0xffffffff;\n@e " ins "\n}"
__device__ __forceinline__ void mbar_expect(uint32_t b, int bytes) {
  asm volatile(ELECT("mbarrier.arrive.expect_tx.shared::cta.b64 _, [%0], %1;") ::"r"(b), "r"(bytes) : "memory");
}
__device__ __forceinline__ void mbar_arrive_one(uint32_t b) { asm volatile(ELECT("mbarrier.arrive.shared::cta.b64 _, [%0];") ::"r"(b) : "memory"); }
constexpr uint64_t L2_NORMAL = 0x1000000000000000ull, L2_FIRST = 0x12F0000000000000ull;
__device__ __forceinline__ void bulk_load(uint32_t dst, const void* src, int bytes, uint32_t bar, uint64_t pol = L2_NORMAL) {
  asm volatile(ELECT("cp.async.bulk.shared::cluster.global.mbarrier::complete_tx::bytes.L2::cache_hint [%0], [%1], %2, [%3], %4;") ::"r"(dst), "l"(src), "r"(bytes), "r"(bar), "l"(pol) : "memory");
}
__device__ __forceinline__ void bulk_load_mc(uint32_t dst, const void* src, int bytes, uint32_t bar, uint64_t pol = L2_NORMAL) {
  asm volatile(ELECT("cp.async.bulk.shared::cluster.global.mbarrier::complete_tx::bytes.multicast::cluster.L2::cache_hint [%0], [%1], %2, [%3], %4, %5;") ::"r"(dst), "l"(src), "r"(bytes), "r"(bar), "h"((uint16_t)3), "l"(pol) : "memory");
}
__device__ __forceinline__ void bulk_store(void* dst, uint32_t src, int bytes, uint64_t pol = L2_NORMAL) {
  asm volatile(ELECT("cp.async.bulk.global.shared::cta.bulk_group.L2::cache_hint [%0], [%1], %2, %3;") ::"l"(dst), "r"(src), "r"(bytes), "l"(pol) : "memory");
}
__device__ __forceinline__ void tma2d(uint32_t dst, const CUtensorMap* m, int c0, int c1, uint32_t bar, uint64_t pol = L2_NORMAL) {
  asm volatile(ELECT("cp.async.bulk.tensor.2d.shared::cluster.global.mbarrier::complete_tx::bytes.L2::cache_hint [%0], [%1, {%3, %4}], [%2], %5;") ::"r"(dst), "l"(m), "r"(bar), "r"(c0), "r"(c1), "l"(pol) : "memory");
}
__device__ __forceinline__ void tma2d_mc(uint32_t dst, const CUtensorMap* m, int c0, int c1, uint32_t bar, uint64_t pol = L2_NORMAL) {
  asm volatile(ELECT("cp.async.bulk.tensor.2d.shared::cluster.global.mbarrier::complete_tx::bytes.multicast::cluster.L2::cache_hint [%0], [%1, {%3, %4}], [%2], %5, %6;") ::"r"(dst), "l"(m), "r"(bar), "r"(c0), "r"(c1), "h"((uint16_t)3), "l"(pol) : "memory");
}
__device__ __forceinline__ void tma3d(uint32_t dst, const CUtensorMap* m, int c0, int c1, int c2, uint32_t bar, uint64_t pol = L2_NORMAL) {
  asm volatile(ELECT("cp.async.bulk.tensor.3d.shared::cluster.global.mbarrier::complete_tx::bytes.L2::cache_hint [%0], [%1, {%3, %4, %5}], [%2], %6;") ::"r"(dst), "l"(m), "r"(bar), "r"(c0), "r"(c1), "r"(c2), "l"(pol) : "memory");
}
__device__ __forceinline__ void tma3d_mc(uint32_t dst, const CUtensorMap* m, int c0, int c1, int c2, uint32_t bar, uint64_t pol = L2_NORMAL) {
  asm volatile(ELECT("cp.async.bulk.tensor.3d.shared::cluster.global.mbarrier::complete_tx::bytes.multicast::cluster.L2::cache_hint [%0], [%1, {%3, %4, %5}], [%2], %6, %7;") ::"r"(dst), "l"(m), "r"(bar), "r"(c0), "r"(c1), "r"(c2), "h"((uint16_t)3), "l"(pol) : "memory");
}
__device__ __forceinline__ void tma2d_store(const CUtensorMap* m, uint32_t src, int c0, int c1, uint64_t pol = L2_NORMAL) {
  asm volatile(ELECT("cp.async.bulk.tensor.2d.global.shared::cta.bulk_group.L2::cache_hint [%0, {%2, %3}], [%1], %4;") ::"l"(m), "r"(src), "r"(c0), "r"(c1), "l"(pol) : "memory");
}
__device__ __forceinline__ void tma2d_add(const CUtensorMap* m, uint32_t src, int c0, int c1) {
  asm volatile(ELECT("cp.reduce.async.bulk.tensor.2d.global.shared::cta.add.bulk_group [%0, {%2, %3}], [%1];") ::"l"(m), "r"(src), "r"(c0), "r"(c1) : "memory");
}
__device__ __forceinline__ void tma3d_store(const CUtensorMap* m, uint32_t src, int c0, int c1, int c2, uint64_t pol = L2_NORMAL) {
  asm volatile(ELECT("cp.async.bulk.tensor.3d.global.shared::cta.bulk_group.L2::cache_hint [%0, {%2, %3, %4}], [%1], %5;") ::"l"(m), "r"(src), "r"(c0), "r"(c1), "r"(c2), "l"(pol) : "memory");
}
__device__ __forceinline__ void tma2d_prefetch(const CUtensorMap* m, int c0, int c1, uint64_t pol = L2_NORMAL) {
  asm volatile(ELECT("cp.async.bulk.prefetch.tensor.2d.L2.global.L2::cache_hint [%0, {%1, %2}], %3;") ::"l"(m), "r"(c0), "r"(c1), "l"(pol) : "memory");
}
#define HINT 22
#define POL(bit) ((HINT >> (bit)) & 1 ? L2_FIRST : L2_NORMAL)
#define BULK_COMMIT() asm volatile("cp.async.bulk.commit_group;" ::: "memory")
#define BULK_WAIT(n) asm volatile("cp.async.bulk.wait_group %0;" ::"n"(n) : "memory")
#define BULK_WAIT_READ(n) asm volatile("cp.async.bulk.wait_group.read %0;" ::"n"(n) : "memory")
#define FENCE_ASYNC_SMEM() asm volatile("fence.proxy.async.shared::cta;" ::: "memory")
#define FENCE_ASYNC_ALL() asm volatile("fence.proxy.async;" ::: "memory")
#define WG_FENCE() asm volatile("wgmma.fence.sync.aligned;" ::: "memory")
#define WG_COMMIT() asm volatile("wgmma.commit_group.sync.aligned;" ::: "memory")
#define WG_WAIT(n) asm volatile("wgmma.wait_group.sync.aligned %0;" ::"n"(n) : "memory")
__device__ __forceinline__ void bar_sync(int id, int n) { asm volatile("bar.sync %0, %1;" ::"r"(id), "r"(n) : "memory"); }
__device__ __forceinline__ void bar_arrive(int id, int n) { asm volatile("bar.arrive %0, %1;" ::"r"(id), "r"(n) : "memory"); }
__device__ __forceinline__ void cluster_sync() {
  asm volatile("barrier.cluster.arrive.relaxed;\nbarrier.cluster.wait.acquire;" ::: "memory");
}
template <int N> __device__ __forceinline__ void pin(float (&r)[N]) {
#pragma unroll
  for (int i = 0; i < N; i++) asm volatile("" : "+f"(r[i])::"memory");
}
template <int N> __device__ __forceinline__ void pin(uint32_t (&r)[N]) {
#pragma unroll
  for (int i = 0; i < N; i++) asm volatile("" : "+r"(r[i])::"memory");
}
__device__ __forceinline__ uint32_t pack_bf16(float lo, float hi) {
  uint32_t r; asm("cvt.rn.bf16x2.f32 %0, %1, %2;" : "=r"(r) : "f"(hi), "f"(lo)); return r;
}
__device__ __forceinline__ float ex2(float x) { float r; asm("ex2.approx.ftz.f32 %0, %1;" : "=f"(r) : "f"(x)); return r; }
__device__ __forceinline__ void ldsm4(uint32_t a, uint32_t& r0, uint32_t& r1, uint32_t& r2, uint32_t& r3) {
  asm volatile("ldmatrix.sync.aligned.m8n8.x4.shared.b16 {%0,%1,%2,%3}, [%4];" : "=r"(r0), "=r"(r1), "=r"(r2), "=r"(r3) : "r"(a) : "memory");
}
__device__ __forceinline__ void stsm4(uint32_t a, uint32_t r0, uint32_t r1, uint32_t r2, uint32_t r3) {
  asm volatile("stmatrix.sync.aligned.m8n8.x4.shared.b16 [%0], {%1,%2,%3,%4};" ::"r"(a), "r"(r0), "r"(r1), "r"(r2), "r"(r3) : "memory");
}
__device__ __forceinline__ void flag_add(int idx) {
  asm volatile(ELECT("red.release.gpu.global.add.s32 [%0], 1;") ::"l"(g_flags + idx) : "memory");
}
__device__ __forceinline__ void flag_add_rx(int idx) {
  asm volatile(ELECT("red.relaxed.gpu.global.add.s32 [%0], 1;") ::"l"(g_flags + idx) : "memory");
}
template <bool ACQ, int NS = 32> __device__ __forceinline__ void flag_wait(int idx, int target) {
  int n = 0;
  while (true) {
    int v;
    if (ACQ) asm volatile("ld.acquire.gpu.global.s32 %0, [%1];" : "=r"(v) : "l"(g_flags + idx) : "memory");
    else asm volatile("ld.relaxed.gpu.global.s32 %0, [%1];" : "=r"(v) : "l"(g_flags + idx) : "memory");
    if (__all_sync(0xffffffffu, v >= target)) break;
    if (++n > 20000000) __trap();
    __nanosleep(NS);
  }
}
__device__ __forceinline__ uint32_t desc_lo(uint32_t addr, uint32_t lbo) { return ((addr & 0x3FFFFu) >> 4) | ((lbo >> 4) << 16); }
#define PROF(role, i)
#define PROFX(cond, i)
#define PROFB(i)
#define PROFG(i)

template <int TB, int TA = 0> __device__ __forceinline__ void wgmma_ss64(float (&d)[32], uint32_t alo, uint32_t blo, int sd) {
  asm volatile("{\n.reg .pred p;\n.reg .b64 da, db;\n"
    "setp.ne.b32 p, %34, 0;\nmov.b64 da, {%32, %36};\nmov.b64 db, {%33, %36};\n"
    "wgmma.mma_async.sync.aligned.m64n64k16.f32.bf16.bf16 "
    "{%0,%1,%2,%3,%4,%5,%6,%7,%8,%9,%10,%11,%12,%13,%14,%15,%16,%17,%18,%19,%20,%21,%22,%23,"
    "%24,%25,%26,%27,%28,%29,%30,%31}, "
    "da, db, p, 1, 1, %37, %35;\n}\n"
    : "+f"(d[0]),"+f"(d[1]),"+f"(d[2]),"+f"(d[3]),"+f"(d[4]),"+f"(d[5]),"+f"(d[6]),"+f"(d[7]),"+f"(d[8]),"+f"(d[9]),"+f"(d[10]),"+f"(d[11]),
      "+f"(d[12]),"+f"(d[13]),"+f"(d[14]),"+f"(d[15]),"+f"(d[16]),"+f"(d[17]),"+f"(d[18]),"+f"(d[19]),"+f"(d[20]),"+f"(d[21]),"+f"(d[22]),"+f"(d[23]),
      "+f"(d[24]),"+f"(d[25]),"+f"(d[26]),"+f"(d[27]),"+f"(d[28]),"+f"(d[29]),"+f"(d[30]),"+f"(d[31])
    : "r"(alo), "r"(blo), "r"(sd), "n"(TB), "r"(DESC_HI), "n"(TA));
}
template <int TB, int TA = 0> __device__ __forceinline__ void wgmma_ss128(float (&d)[64], uint32_t alo, uint32_t blo, int sd) {
  asm volatile("{\n.reg .pred p;\n.reg .b64 da, db;\n"
    "setp.ne.b32 p, %66, 0;\nmov.b64 da, {%64, %68};\nmov.b64 db, {%65, %68};\n"
    "wgmma.mma_async.sync.aligned.m64n128k16.f32.bf16.bf16 "
    "{%0,%1,%2,%3,%4,%5,%6,%7,%8,%9,%10,%11,%12,%13,%14,%15,%16,%17,%18,%19,%20,%21,%22,%23,"
    "%24,%25,%26,%27,%28,%29,%30,%31,%32,%33,%34,%35,%36,%37,%38,%39,%40,%41,%42,%43,%44,%45,%46,%47,"
    "%48,%49,%50,%51,%52,%53,%54,%55,%56,%57,%58,%59,%60,%61,%62,%63}, "
    "da, db, p, 1, 1, %69, %67;\n}\n"
    : "+f"(d[0]),"+f"(d[1]),"+f"(d[2]),"+f"(d[3]),"+f"(d[4]),"+f"(d[5]),"+f"(d[6]),"+f"(d[7]),"+f"(d[8]),"+f"(d[9]),"+f"(d[10]),"+f"(d[11]),
      "+f"(d[12]),"+f"(d[13]),"+f"(d[14]),"+f"(d[15]),"+f"(d[16]),"+f"(d[17]),"+f"(d[18]),"+f"(d[19]),"+f"(d[20]),"+f"(d[21]),"+f"(d[22]),"+f"(d[23]),
      "+f"(d[24]),"+f"(d[25]),"+f"(d[26]),"+f"(d[27]),"+f"(d[28]),"+f"(d[29]),"+f"(d[30]),"+f"(d[31]),"+f"(d[32]),"+f"(d[33]),"+f"(d[34]),"+f"(d[35]),
      "+f"(d[36]),"+f"(d[37]),"+f"(d[38]),"+f"(d[39]),"+f"(d[40]),"+f"(d[41]),"+f"(d[42]),"+f"(d[43]),"+f"(d[44]),"+f"(d[45]),"+f"(d[46]),"+f"(d[47]),
      "+f"(d[48]),"+f"(d[49]),"+f"(d[50]),"+f"(d[51]),"+f"(d[52]),"+f"(d[53]),"+f"(d[54]),"+f"(d[55]),"+f"(d[56]),"+f"(d[57]),"+f"(d[58]),"+f"(d[59]),
      "+f"(d[60]),"+f"(d[61]),"+f"(d[62]),"+f"(d[63])
    : "r"(alo), "r"(blo), "r"(sd), "n"(TB), "r"(DESC_HI), "n"(TA));
}
template <int TB> __device__ __forceinline__ void wgmma_rs128(float (&d)[64], uint32_t a0, uint32_t a1, uint32_t a2, uint32_t a3, uint32_t blo, int sd) {
  asm volatile("{\n.reg .pred p;\n.reg .b64 db;\n"
    "setp.ne.b32 p, %69, 0;\nmov.b64 db, {%68, %71};\n"
    "wgmma.mma_async.sync.aligned.m64n128k16.f32.bf16.bf16 "
    "{%0,%1,%2,%3,%4,%5,%6,%7,%8,%9,%10,%11,%12,%13,%14,%15,%16,%17,%18,%19,%20,%21,%22,%23,"
    "%24,%25,%26,%27,%28,%29,%30,%31,%32,%33,%34,%35,%36,%37,%38,%39,%40,%41,%42,%43,%44,%45,%46,%47,"
    "%48,%49,%50,%51,%52,%53,%54,%55,%56,%57,%58,%59,%60,%61,%62,%63}, "
    "{%64,%65,%66,%67}, db, p, 1, 1, %70;\n}\n"
    : "+f"(d[0]),"+f"(d[1]),"+f"(d[2]),"+f"(d[3]),"+f"(d[4]),"+f"(d[5]),"+f"(d[6]),"+f"(d[7]),"+f"(d[8]),"+f"(d[9]),"+f"(d[10]),"+f"(d[11]),
      "+f"(d[12]),"+f"(d[13]),"+f"(d[14]),"+f"(d[15]),"+f"(d[16]),"+f"(d[17]),"+f"(d[18]),"+f"(d[19]),"+f"(d[20]),"+f"(d[21]),"+f"(d[22]),"+f"(d[23]),
      "+f"(d[24]),"+f"(d[25]),"+f"(d[26]),"+f"(d[27]),"+f"(d[28]),"+f"(d[29]),"+f"(d[30]),"+f"(d[31]),"+f"(d[32]),"+f"(d[33]),"+f"(d[34]),"+f"(d[35]),
      "+f"(d[36]),"+f"(d[37]),"+f"(d[38]),"+f"(d[39]),"+f"(d[40]),"+f"(d[41]),"+f"(d[42]),"+f"(d[43]),"+f"(d[44]),"+f"(d[45]),"+f"(d[46]),"+f"(d[47]),
      "+f"(d[48]),"+f"(d[49]),"+f"(d[50]),"+f"(d[51]),"+f"(d[52]),"+f"(d[53]),"+f"(d[54]),"+f"(d[55]),"+f"(d[56]),"+f"(d[57]),"+f"(d[58]),"+f"(d[59]),
      "+f"(d[60]),"+f"(d[61]),"+f"(d[62]),"+f"(d[63])
    : "r"(a0), "r"(a1), "r"(a2), "r"(a3), "r"(blo), "r"(sd), "n"(TB), "r"(DESC_HI));
}
template <int TB, int TA = 0> __device__ __forceinline__ void wgmma_ss192(float (&d)[96], uint32_t alo, uint32_t blo, int sd) {
  asm volatile("{\n.reg .pred p;\n.reg .b64 da, db;\n"
    "setp.ne.b32 p, %98, 0;\nmov.b64 da, {%96, %100};\nmov.b64 db, {%97, %100};\n"
    "wgmma.mma_async.sync.aligned.m64n192k16.f32.bf16.bf16 "
    "{%0,%1,%2,%3,%4,%5,%6,%7,%8,%9,%10,%11,%12,%13,%14,%15,%16,%17,%18,%19,%20,%21,%22,%23,"
    "%24,%25,%26,%27,%28,%29,%30,%31,%32,%33,%34,%35,%36,%37,%38,%39,%40,%41,%42,%43,%44,%45,%46,%47,"
    "%48,%49,%50,%51,%52,%53,%54,%55,%56,%57,%58,%59,%60,%61,%62,%63,%64,%65,%66,%67,%68,%69,%70,%71,"
    "%72,%73,%74,%75,%76,%77,%78,%79,%80,%81,%82,%83,%84,%85,%86,%87,%88,%89,%90,%91,%92,%93,%94,%95}, "
    "da, db, p, 1, 1, %101, %99;\n}\n"
    : "+f"(d[0]),"+f"(d[1]),"+f"(d[2]),"+f"(d[3]),"+f"(d[4]),"+f"(d[5]),"+f"(d[6]),"+f"(d[7]),"+f"(d[8]),"+f"(d[9]),"+f"(d[10]),"+f"(d[11]),
      "+f"(d[12]),"+f"(d[13]),"+f"(d[14]),"+f"(d[15]),"+f"(d[16]),"+f"(d[17]),"+f"(d[18]),"+f"(d[19]),"+f"(d[20]),"+f"(d[21]),"+f"(d[22]),"+f"(d[23]),
      "+f"(d[24]),"+f"(d[25]),"+f"(d[26]),"+f"(d[27]),"+f"(d[28]),"+f"(d[29]),"+f"(d[30]),"+f"(d[31]),"+f"(d[32]),"+f"(d[33]),"+f"(d[34]),"+f"(d[35]),
      "+f"(d[36]),"+f"(d[37]),"+f"(d[38]),"+f"(d[39]),"+f"(d[40]),"+f"(d[41]),"+f"(d[42]),"+f"(d[43]),"+f"(d[44]),"+f"(d[45]),"+f"(d[46]),"+f"(d[47]),
      "+f"(d[48]),"+f"(d[49]),"+f"(d[50]),"+f"(d[51]),"+f"(d[52]),"+f"(d[53]),"+f"(d[54]),"+f"(d[55]),"+f"(d[56]),"+f"(d[57]),"+f"(d[58]),"+f"(d[59]),
      "+f"(d[60]),"+f"(d[61]),"+f"(d[62]),"+f"(d[63]),"+f"(d[64]),"+f"(d[65]),"+f"(d[66]),"+f"(d[67]),"+f"(d[68]),"+f"(d[69]),"+f"(d[70]),"+f"(d[71]),
      "+f"(d[72]),"+f"(d[73]),"+f"(d[74]),"+f"(d[75]),"+f"(d[76]),"+f"(d[77]),"+f"(d[78]),"+f"(d[79]),"+f"(d[80]),"+f"(d[81]),"+f"(d[82]),"+f"(d[83]),
      "+f"(d[84]),"+f"(d[85]),"+f"(d[86]),"+f"(d[87]),"+f"(d[88]),"+f"(d[89]),"+f"(d[90]),"+f"(d[91]),"+f"(d[92]),"+f"(d[93]),"+f"(d[94]),"+f"(d[95])
    : "r"(alo), "r"(blo), "r"(sd), "n"(TB), "r"(DESC_HI), "n"(TA));
}

struct Ctx {
  uint32_t sm;
  uint32_t bar;
  uint32_t rbar;
  int cl, rank, wg, warp, lane, phases;
};
__device__ __forceinline__ void release(const Ctx& c, int b, int cnt = 1) {
  if (c.lane < 2) mbar_arrive_cl(c.rbar + b * 8, cnt);
}
#define PFM 7
#define PF1 1
constexpr float SM_SCALE = 0.08838834764831845f * 1.4426950408889634f;
constexpr float SM_HI = 1.8446744e19f, SM_LO = 5.4210109e-20f;
constexpr int ORDER = 1;

__device__ __forceinline__ void stage_tile(const float (&a)[64], uint32_t buf, const Ctx& c, float s0, float s1) {
  const int row = (c.lane & 7) + ((c.lane >> 3) & 1) * 8;
  const uint32_t base = buf + (c.warp * 16 + row) * 128 + (((c.lane >> 4) ^ (row & 7)) << 4);
#pragma unroll
  for (int i = 0; i < 8; i++)
    stsm4((base ^ ((i & 3) << 5)) + (i >> 2) * 8192, pack_bf16(a[8 * i] * s0, a[8 * i + 1] * s0), pack_bf16(a[8 * i + 2] * s1, a[8 * i + 3] * s1),
          pack_bf16(a[8 * i + 4] * s0, a[8 * i + 5] * s0), pack_bf16(a[8 * i + 6] * s1, a[8 * i + 7] * s1));
}

__device__ __forceinline__ void p1_epilogue(const Params& p, const Ctx& c, const float (&acc)[64], int t, int type) {
  const int tile = p.s.r[c.cl].tile[t], b = c.wg * 2 + 1;
  mbar_wait(c.bar + (B_SE + b) * 8, (t & 1) ^ 1);
  if (type && tile >= 32) {
    const int r = 2 * (c.lane & 3) + ((c.lane >> 2) & 1);
    const uint32_t dst = c.sm + SM_BUF + b * 16384 + r * 128 + (((c.warp * 2) ^ r) << 4) + (c.lane >> 3) * 4;
#pragma unroll
    for (int i = 0; i < 16; i++) {
      asm volatile("st.shared.u32 [%0], %1;" ::"r"(dst + i * 1024), "r"(pack_bf16(acc[4 * i], acc[4 * i + 1])) : "memory");
      asm volatile("st.shared.u32 [%0], %1;" ::"r"((dst ^ 16) + i * 1024), "r"(pack_bf16(acc[4 * i + 2], acc[4 * i + 3])) : "memory");
    }
  } else {
    if (type) stage_tile(acc, c.sm + SM_BUF + b * 16384, c, SM_SCALE, SM_SCALE);
    else stage_tile(acc, c.sm + SM_BUF + b * 16384, c, 1.f, 1.f);
  }
  FENCE_ASYNC_SMEM();
  __syncwarp();
  if (c.lane == 0) mbar_arrive(c.bar + (B_SF + b) * 8);
}

__device__ __forceinline__ void p1_consumer(const Params& p, const Ctx& c) {
  const int n = p.s.r[c.cl].n1;
  const int type = p.s.r[c.cl].slab >> 3;
  const uint32_t bdesc = desc_lo(c.sm + SM_RING, 8192), adesc = desc_lo(c.sm + SM_BUF + 32768 + c.wg * 8192, 16);
  uint32_t A[128];
  float acc[64] = {};
  int slot = 0, par = 0;
  auto next = [&]() { if (++slot == 10) { slot = 0; par ^= 1; } };
  {
    const int row = (c.lane & 7) + ((c.lane >> 3) & 1) * 8;
    const uint32_t base = c.sm + SM_RING + (c.wg * 64 + c.warp * 16 + row) * 128 + (((c.lane >> 4) ^ (row & 7)) << 4);
    if (c.wg == 1) bar_sync(ORDER + 1, 256);
    int pa = -1, pb = -1;
    if (type) {
      mbar_wait(c.bar + B_P1F * 8, 0);
      WG_FENCE();
#pragma unroll
      for (int kk = 0; kk < 4; kk++) wgmma_ss128<1>(acc, adesc + kk * 2, bdesc + kk * 128, kk != 0);
      WG_COMMIT();
      pb = 0; slot = 1;
    }
#pragma unroll
    for (int kb = 0; kb < 8; kb++) {
      const int sa = slot;
      mbar_wait(c.bar + (B_P1F + slot) * 8, par);
      next();
      mbar_wait(c.bar + (B_P1F + slot) * 8, par);
      PROF(c.wg, 6 + 2 * kb);
      WG_FENCE();
#pragma unroll
      for (int kk = 0; kk < 4; kk++)
        wgmma_ss128<1>(acc, desc_lo(c.sm + SM_RING + c.wg * 8192, 16) + sa * 1024 + kk * 2, bdesc + slot * 1024 + kk * 128, (kb | kk) != 0 ? 1 : type);
      WG_COMMIT();
      if (kb == 1 && c.wg == 0) bar_arrive(ORDER + 1, 256);
#pragma unroll
      for (int kk = 0; kk < 4; kk++) ldsm4((base ^ (kk << 5)) + sa * 16384, A[kb * 16 + kk * 4], A[kb * 16 + kk * 4 + 1], A[kb * 16 + kk * 4 + 2], A[kb * 16 + kk * 4 + 3]);
      WG_WAIT(1);
      if (kb > 0) release(c, B_P1E + pa);
      if (kb > 0 || pb >= 0) release(c, B_P1E + pb);
      pa = sa; pb = slot;
      next();
    }
    WG_WAIT(0);
    __syncwarp();
    release(c, B_P1E + pa);
    release(c, B_P1E + pb);
    pin(acc);
    PROF(c.wg, 1);
    p1_epilogue(p, c, acc, 0, type);
    PROF(c.wg, 2);
  }
  for (int t = 1; t < n; t++) {
    bar_sync(ORDER + c.wg, 256);
    int prev1 = -1, prev2 = -1;
    if (type) {
      mbar_wait(c.bar + (B_P1F + slot) * 8, par);
      WG_FENCE();
#pragma unroll
      for (int kk = 0; kk < 4; kk++) wgmma_ss128<1>(acc, adesc + kk * 2, bdesc + slot * 1024 + kk * 128, kk != 0);
      WG_COMMIT();
      prev1 = slot;
      next();
    }
#pragma unroll
    for (int kb = 0; kb < 8; kb++) {
      mbar_wait(c.bar + (B_P1F + slot) * 8, par);
      WG_FENCE();
      const uint32_t d = bdesc + slot * 1024;
#pragma unroll
      for (int kk = 0; kk < 4; kk++)
        wgmma_rs128<1>(acc, A[kb * 16 + kk * 4], A[kb * 16 + kk * 4 + 1], A[kb * 16 + kk * 4 + 2], A[kb * 16 + kk * 4 + 3], d + kk * 128, (kb | kk) != 0 ? 1 : type);
      WG_COMMIT();
      if (kb == 7) {
        if (t + 1 < n || c.wg == 0) bar_arrive(ORDER + (c.wg ^ 1), 256);
      }
      if (kb > 0) { WG_WAIT(2); if (kb > 1 || prev2 >= 0) release(c, B_P1E + prev2); }
      prev2 = prev1; prev1 = slot;
      next();
    }
    WG_WAIT(1);
    release(c, B_P1E + prev2);
    WG_WAIT(0);
    pin(acc);
    release(c, B_P1E + prev1);
    p1_epilogue(p, c, acc, t, type);
    PROF(c.wg, 3);
  }
}

__device__ __forceinline__ void p1_producer(const Params& p, const Ctx& c) {
  const int n = p.s.r[c.cl].n1;
  const int type = p.s.r[c.cl].slab >> 3, grp = p.s.r[c.cl].slab & 7;
  int slot = 0, par = 1;
#pragma unroll 1
  for (int t = 0; t < n; t++) {
    const int tile = p.s.r[c.cl].tile[t];
    const CUtensorMap* m = &p.map_w[type * 2 + (tile >> 5)];
    const int n0 = (tile & 31) * 128 + c.rank * 64;
    const int ptile = p.s.r[c.cl].tile[t + PF1 < n ? t + PF1 : t];
    const CUtensorMap* pm = &p.map_w[type * 2 + (ptile >> 5)];
#pragma unroll 1
    for (int kb = -type; kb < 8; kb++) {
      if (t == 0 && kb >= 0) {
        if (kb > -type) {
          mbar_wait(c.bar + (B_P1E + slot) * 8, par);
          mbar_expect(c.bar + (B_P1F + slot) * 8, 16384);
          tma2d(c.sm + SM_RING + slot * 16384, &p.map_a[type], kb * 64, grp * 256 + c.rank * 128, c.bar + (B_P1F + slot) * 8);
        }
        if (++slot == 10) { slot = 0; par ^= 1; }
      }
      mbar_wait(c.bar + (B_P1E + slot) * 8, par);
      if (t > 0 || kb >= 0) mbar_expect(c.bar + (B_P1F + slot) * 8, 16384);
      tma2d_mc(c.sm + SM_RING + slot * 16384 + c.rank * 8192, m, n0, kb < 0 ? 512 : kb * 64, c.bar + (B_P1F + slot) * 8, POL(0));
      if (t == 0 && kb == 0) PROF(2, 61);
      if (t == 0 && kb == 3) PROF(2, 62);
      if (t + PF1 < n && (t > 0 || kb >= 3) && ((kb ^ grp) & PFM) == 0) tma2d_prefetch(pm, (ptile & 31) * 128 + c.rank * 64, kb < 0 ? 512 : kb * 64, POL(0));
      if (++slot == 10) { slot = 0; par ^= 1; }
    }
  }
}

__device__ __forceinline__ void p1_storer(const Params& p, const Ctx& c) {
  const int n = p.s.r[c.cl].n1;
  const int type = p.s.r[c.cl].slab >> 3, grp = p.s.r[c.cl].slab & 7;
  int pf = -1;
  for (int i = 0; i < 2 * n; i++) {
    const int t = i >> 1, w = i & 1, b = w * 2 + 1;
    const int tile = p.s.r[c.cl].tile[t];
    mbar_wait(c.bar + (B_SF + b) * 8, t & 1);
    const uint32_t src = c.sm + SM_BUF + b * 16384;
    int f = F_HEAD + (tile & 31);
    if (type == 0) {
      const int h = tile & 31, ring = p.s.r[c.cl].ring;
      if (h >= ring && w == 0) flag_wait<false>(F_CTX + max(c.lane & 7, grp) * 64 + h - ring, 4);
      uint8_t* dst = g_KV + (size_t)((h >= ring ? tile - ring : tile) * 16 + grp * 2 + c.rank) * 32768 + w * 8192;
      bulk_store(dst, src, 8192);
      bulk_store(dst + 16384, src + 8192, 8192);
    } else if (tile < 32) {
      bulk_store(g_Q + (size_t)(tile * 32 + grp * 4 + c.rank * 2 + w) * 16384, src, 16384);
    } else {
      tma3d_store(&p.map_t[2], src, 8 + (grp * 4 + c.rank * 2 + w) * 32, 0, (tile - 32) * 64);
      f = F_QKVA + grp * 4 + ((0xE4390900u >> (2 * (tile - 30))) & 3);
    }
    BULK_COMMIT();
    BULK_WAIT_READ(0);
    mbar_arrive_one(c.bar + (B_SE + b) * 8);
    if (pf >= 0) {
      BULK_WAIT(1);
      flag_add_rx(pf);
    }
    pf = f;
  }
  BULK_WAIT(0);
  flag_add_rx(pf);
}

__device__ __forceinline__ int p2_buf(int w, int i) { return w * 2 + (i & 1); }
__device__ __forceinline__ int p2_blk(int rank, int w, int i) { return ((i ^ w) & 1) == 0 ? 3 - rank : rank; }

template <int N>
__device__ __forceinline__ void row_max(const float (&s)[N], float& m0, float& m1) {
  float a0 = fmaxf(s[0], s[1]), a1 = fmaxf(s[2], s[3]);
#pragma unroll
  for (int i = 1; i < N / 4; i++) {
    m0 = fmaxf(m0, s[4 * i]); a0 = fmaxf(a0, s[4 * i + 1]);
    m1 = fmaxf(m1, s[4 * i + 2]); a1 = fmaxf(a1, s[4 * i + 3]);
  }
  m0 = fmaxf(m0, a0); m1 = fmaxf(m1, a1);
  m0 = fmaxf(m0, __shfl_xor_sync(0xffffffffu, m0, 1));
  m1 = fmaxf(m1, __shfl_xor_sync(0xffffffffu, m1, 1));
  m0 = fmaxf(m0, __shfl_xor_sync(0xffffffffu, m0, 2));
  m1 = fmaxf(m1, __shfl_xor_sync(0xffffffffu, m1, 2));
}
template <bool SUB, int N>
__device__ __forceinline__ void row_exp(const float (&s)[N], uint32_t (&P)[32], float m0, float m1, float& t0, float& t1) {
  float u0 = 0.f, u1 = 0.f;
  t0 = t1 = 0.f;
#pragma unroll
  for (int i = 0; i < N / 4; i++) {
    const float e0 = ex2(SUB ? s[4 * i] - m0 : s[4 * i]), e1 = ex2(SUB ? s[4 * i + 1] - m0 : s[4 * i + 1]);
    const float e2 = ex2(SUB ? s[4 * i + 2] - m1 : s[4 * i + 2]), e3 = ex2(SUB ? s[4 * i + 3] - m1 : s[4 * i + 3]);
    if (i == 0) { t0 = e0; u0 = e1; t1 = e2; u1 = e3; }
    else { t0 += e0; u0 += e1; t1 += e2; u1 += e3; }
    P[2 * i] = pack_bf16(e0, e1);
    P[2 * i + 1] = pack_bf16(e2, e3);
  }
#pragma unroll
  for (int i = N / 2; i < 32; i++) P[i] = 0;
  pin(P);
  t0 += u0; t1 += u1;
}
template <int N>
__device__ __forceinline__ void causal_mask(float (&s)[N], int thr) {
#pragma unroll
  for (int i = 0; i < 8; i++) {
    if (8 * i > thr) s[N - 32 + 4 * i] = -INFINITY;
    if (8 * i + 1 > thr) s[N - 32 + 4 * i + 1] = -INFINITY;
    if (8 * i - 8 > thr) s[N - 32 + 4 * i + 2] = -INFINITY;
    if (8 * i - 7 > thr) s[N - 32 + 4 * i + 3] = -INFINITY;
  }
}
__device__ __forceinline__ void issue_qk(float (&s)[32], uint32_t qd, uint32_t kd) {
  WG_FENCE();
#pragma unroll
  for (int kk = 0; kk < 8; kk++) wgmma_ss64<0>(s, qd + (kk >> 2) * 512 + (kk & 3) * 2, kd + (kk >> 2) * 1024 + (kk & 3) * 2, kk != 0);
  WG_COMMIT();
}
__device__ __forceinline__ void issue_qk(float (&s)[64], uint32_t qd, uint32_t kd) {
  WG_FENCE();
#pragma unroll
  for (int kk = 0; kk < 8; kk++) wgmma_ss128<0>(s, qd + (kk >> 2) * 512 + (kk & 3) * 2, kd + (kk >> 2) * 1024 + (kk & 3) * 2, kk != 0);
  WG_COMMIT();
}
template <int NK>
__device__ __forceinline__ void issue_pv(float (&o)[64], const uint32_t (&P)[32], uint32_t vd, int acc) {
  WG_FENCE();
#pragma unroll
  for (int kk = 0; kk < NK; kk++) wgmma_rs128<1>(o, P[4 * kk], P[4 * kk + 1], P[4 * kk + 2], P[4 * kk + 3], vd + kk * 128, kk != 0 ? 1 : acc);
  WG_COMMIT();
}
__device__ __forceinline__ void stage_done(const Ctx& c, int b) {
  FENCE_ASYNC_SMEM();
  __syncwarp();
  if (c.lane == 0) mbar_arrive(c.bar + (B_SF + b) * 8);
}
__device__ __forceinline__ void p2_epilogue(const float (&o)[64], float s0, float s1, const Ctx& c, int b) {
  stage_tile(o, c.sm + SM_BUF + b * 16384, c, s0, s1);
  stage_done(c, b);
}

struct P2State {
  float m0, m1, l0, l1;
  bool shift;
  float e0, e1;
  float g0, g1;
  int ks;
  int wi, ai;
  uint32_t wb, ab;
  uint32_t qd;
};
#define PROFZ()
__device__ __forceinline__ int wrap5(int q) { return q >= 5 ? q - 5 : q; }
__device__ __forceinline__ void turn_wait(uint32_t ring, int i) { mbar_wait(ring + (i & 3) * 8, (i >> 2) & 1); }
__device__ __forceinline__ void turn_pass(const Ctx& c, uint32_t ring, int i) { if (c.lane == 0) mbar_arrive(ring + (i & 3) * 8); }
__device__ __forceinline__ void p2_gate(P2State& z, const Ctx& c, int row0) {
  const float* g = g_gate + row0 + c.warp * 16 + (c.lane >> 2);
  asm volatile("ld.global.cg.f32 %0, [%2];\nld.global.cg.f32 %1, [%2+32];" : "=f"(z.g0), "=f"(z.g1) : "l"(g) : "memory");
}
__device__ __forceinline__ void p2_scales(P2State& z) {
  float l0 = z.l0, l1 = z.l1;
  l0 += __shfl_xor_sync(0xffffffffu, l0, 1);
  l1 += __shfl_xor_sync(0xffffffffu, l1, 1);
  l0 += __shfl_xor_sync(0xffffffffu, l0, 2);
  l1 += __shfl_xor_sync(0xffffffffu, l1, 2);
  z.e0 = __fdividef(1.f - z.g0, l0); z.e1 = __fdividef(1.f - z.g1, l1);
}
template <int N, bool PV>
__device__ __forceinline__ void p2_first(const Params& p, const Ctx& c, P2State& z, float (&o)[64], uint32_t (&Pc)[32], uint32_t (&Pn)[32],
                                         int ks, int vs, int cnt, int acc, int row0) {
  float s[N] = {};
  issue_qk(s, z.qd, desc_lo(c.sm + SM_RING, 16) + ks * 2048);
  if (PV) {
    if (p.zero == 0) p2_scales(z);
    issue_pv<8>(o, Pc, desc_lo(c.sm + SM_RING, 16384) + vs * 2048, acc);
  }
  if (cnt == 1 && c.warp == 0) mbar_expect(z.ab + (z.ai & 3) * 8, 32768); else turn_pass(c, z.ab, z.ai);
  z.ai++;
  PROFZ();
  if (PV) WG_WAIT(1); else WG_WAIT(0);
  PROFZ();
  pin(s);
  release(c, B_P2E + ks, cnt);
  p2_gate(z, c, row0);
  causal_mask(s, c.warp * 16 + (c.lane >> 2) - 2 * (c.lane & 3));
  z.m0 = z.m1 = 0.f;
  row_exp<false>(s, Pn, 0.f, 0.f, z.l0, z.l1);
  z.shift = __any_sync(0xffffffffu, !(z.l0 + z.l1 <= SM_HI) || ((c.lane & 3) == 0 && !(fminf(z.l0, z.l1) >= SM_LO)));
  if (__builtin_expect(z.shift, 0)) {
    z.m0 = z.m1 = -INFINITY;
    row_max(s, z.m0, z.m1);
    row_exp<true>(s, Pn, z.m0, z.m1, z.l0, z.l1);
  }
  if (PV) {
    WG_WAIT(0);
    pin(o);
    release(c, B_P2E + vs, 1);
  }
}

template <bool SECOND>
__device__ __forceinline__ void p2_turn(const Ctx& c, P2State& z, float (&o)[64], uint32_t (&Pc)[32], uint32_t (&Pn)[32],
                                        int eb = -1, bool half = false, int vcnt = 1) {
  float s[64] = {};
  const int ks = z.ks, vs = wrap5(ks + 1);
  PROFZ();
  turn_wait(z.wb, z.wi++);
  PROFZ();
  issue_qk(s, z.qd, desc_lo(c.sm + SM_RING, 16) + ks * 2048);
  const uint32_t vd = desc_lo(c.sm + SM_RING, 16384) + vs * 2048;
  if (SECOND) {
    if (eb >= 0) stage_tile(o, c.sm + SM_BUF + eb * 16384, c, z.e0, z.e1);
    if (half) issue_pv<4>(o, Pc, vd, 0); else issue_pv<8>(o, Pc, vd, 0);
  } else {
    issue_pv<8>(o, Pc, vd, 1);
  }
  turn_pass(c, z.ab, z.ai++);
  if (SECOND) { if (eb >= 0) stage_done(c, eb); }
  PROFZ();
  z.ks = wrap5(ks + 2);
  WG_WAIT(1);
  PROFZ();
  pin(s);
  release(c, B_P2E + ks, 1);
  float t0, t1, a0 = 1.f, a1 = 1.f;
  row_exp<false>(s, Pn, 0.f, 0.f, t0, t1);
  z.shift = __any_sync(0xffffffffu, z.shift || !(t0 + t1 <= SM_HI));
  const bool redo = z.shift;
  if (__builtin_expect(redo, 0)) {
    float n0 = z.m0, n1 = z.m1;
    row_max(s, n0, n1);
    a0 = ex2(z.m0 - n0); a1 = ex2(z.m1 - n1);
    z.m0 = n0; z.m1 = n1;
    z.l0 *= a0; z.l1 *= a1;
    row_exp<true>(s, Pn, z.m0, z.m1, t0, t1);
  }
  WG_WAIT(0);
  pin(o);
  release(c, B_P2E + vs, vcnt);
  if (__builtin_expect(redo, 0)) {
#pragma unroll
    for (int i = 0; i < 16; i++) { o[4 * i] *= a0; o[4 * i + 1] *= a0; o[4 * i + 2] *= a1; o[4 * i + 3] *= a1; }
  }
  z.l0 += t0; z.l1 += t1;
}
__device__ __forceinline__ void copy_p(uint32_t (&d)[32], const uint32_t (&s)[32], int zero) {
#pragma unroll
  for (int i = 0; i < 32; i++) asm volatile("add.s32 %0, %1, %2;" : "=r"(d[i]) : "r"(s[i]), "r"(zero));
}

__device__ __forceinline__ void p2_consumer(const Params& p, const Ctx& c, int rot) {
  const int nit = p.s.r[c.cl].n2;
  const uint32_t fring = c.bar + B_P2F * 8, oring = c.bar + B_ORD * 8;
  float o[64] = {};
  uint32_t Pa[32] = {}, Pb[32] = {};
  P2State z;
  z.e0 = z.e1 = z.l0 = z.l1 = z.g0 = z.g1 = 0.f; z.ks = rot; z.shift = false;
  int acc = 0, n = 0;
  for (int it = 0; it < nit; it++) {
    const int j = p.s.r[c.cl].item[it] & 7, blk = p2_blk(c.rank, c.wg, it), row0 = (j * 4 + blk) * 64;
    const int lng = ((it ^ c.wg) & 1) ^ 1;
    z.qd = desc_lo(c.sm + SM_BUF, 16) + p2_buf(c.wg, it) * 1024;
    if (lng) { z.wb = oring; z.wi = n - it; z.ab = fring; z.ai = n + 1; }
    else { z.wb = fring; z.wi = n + 2; z.ab = oring; z.ai = n - it; }
    PROFZ();
    mbar_wait(c.bar + (B_QF + p2_buf(c.wg, it)) * 8, (it >> 1) & 1);
    turn_wait(fring, n + 1 - lng);
    PROFZ();
    if (it == 0) {
      const int ks = wrap5(rot + c.wg);
      if (blk & 1) p2_first<64, false>(p, c, z, o, Pa, Pb, ks, 0, 1 + lng, 0, row0);
      else p2_first<32, false>(p, c, z, o, Pa, Pb, ks, 0, 1 + lng, 0, row0);
      z.ks = wrap5(rot + 1 + 2 * c.wg);
    } else {
      const int vs = wrap5(z.ks + 1), ks = lng ? z.ks : wrap5(z.ks + 2);
      if (blk & 1) p2_first<64, true>(p, c, z, o, Pa, Pb, ks, vs, 1 + lng, acc, row0);
      else p2_first<32, true>(p, c, z, o, Pa, Pb, ks, vs, 1 + lng, acc, row0);
      z.ks = wrap5(ks + 2);
    }
    PROF(c.wg, 24 + it);
    n += 2 * j + 2;
    int left = 2 * j + lng;
    acc = left != 0;
    if (left == 0) { copy_p(Pa, Pb, p.zero); continue; }
    p2_turn<true>(c, z, o, Pb, Pa, it > 0 ? p2_buf(c.wg, it - 1) : -1, !(blk & 1), 1 + lng);
    while (--left > 0) {
      p2_turn<false>(c, z, o, Pa, Pb);
      if (--left == 0) { copy_p(Pa, Pb, p.zero); break; }
      p2_turn<false>(c, z, o, Pb, Pa);
    }
  }
  {
    if (!acc && nit > 1) p2_epilogue(o, z.e0, z.e1, c, p2_buf(c.wg, nit));
    turn_wait(z.wb, z.wi);
    issue_pv<8>(o, Pa, desc_lo(c.sm + SM_RING, 16384) + z.ks * 2048, acc);
    if (((nit - 1) ^ c.wg) & 1) turn_pass(c, z.ab, z.ai);
    p2_scales(z);
    WG_WAIT(0);
    pin(o);
    release(c, B_P2E + z.ks);
    p2_epilogue(o, z.e0, z.e1, c, p2_buf(c.wg, nit - 1));
    PROF(c.wg, 24 + nit);
  }
}

__device__ __forceinline__ void p2_load_q(const Params& p, const Ctx& c, int it, int w) {
  const int item = p.s.r[c.cl].item[it], h = item >> 3, j = item & 7, b = p2_buf(w, it);
  mbar_expect(c.bar + (B_QF + b) * 8, 16384);
  bulk_load(c.sm + SM_BUF + b * 16384, g_Q + (size_t)(h * 32 + j * 4 + p2_blk(c.rank, w, it)) * 16384, 16384, c.bar + (B_QF + b) * 8, POL(4));
}
__device__ __forceinline__ void wait_p1_free(const Ctx& c, int u1, int s) {
  mbar_wait(c.bar + (B_P1E + 2 * s) * 8, ((u1 - 1 - 2 * s) / 10) & 1);
  mbar_wait(c.bar + (B_P1E + 2 * s + 1) * 8, ((u1 - 2 - 2 * s) / 10) & 1);
}
__device__ __forceinline__ void p2_producer(const Params& p, const Ctx& c, int u1, int rot) {
  const int nit = p.s.r[c.cl].n2;
  int slot = rot, cnt = 0, par = 1, n = 0;
  const int ring = p.s.r[c.cl].ring;
  const uint8_t* pv = nullptr;
  auto load = [&](const uint8_t* src, int expect, uint32_t fb) {
    if (cnt < 5) {
      if (u1) {
        wait_p1_free(c, u1, slot);
        if (cnt == 0) p2_load_q(p, c, 0, 1);
      }
      cnt++;
    } else {
      if (slot == rot) par ^= 1;
      mbar_wait(c.bar + (B_P2E + slot) * 8, par);
    }
    if (expect) mbar_expect(fb, expect);
    bulk_load_mc(c.sm + SM_RING + slot * 32768 + c.rank * 16384, src, 16384, fb);
    slot = wrap5(slot + 1);
  };
  if (c.phases & 16) flag_wait<true>(F_GATE, 256);
  for (int it = 0; it < nit; it++) {
    const int item = p.s.r[c.cl].item[it], h = item >> 3, j = item & 7;
    if (c.phases & 16) flag_wait<false>(F_HEAD + h, 96);
    if (it == 0) { mbar_wait(c.bar + B_LAD * 8, 0); p2_load_q(p, c, 0, 0); if (!u1) p2_load_q(p, c, 0, 1); }
    for (int t = 2 * j + 1; t >= 0; t--) {
      const uint8_t* k = g_KV + (size_t)((h >= ring ? h - ring : h) * 16 + t) * 32768 + c.rank * 16384;
      const uint32_t fb = c.bar + (B_P2F + (n & 3)) * 8;
      load(k, pv && t != 2 * j ? 65536 : 32768, fb);
      if (pv) load(pv, 0, t != 2 * j ? fb : c.bar + (B_ORD + ((n - 1 - it) & 3)) * 8);
      pv = k + (size_t)NH * 16 * 32768;
      n++;
    }
  }
  load(pv, 32768, c.bar + (B_P2F + (n & 3)) * 8);
}

__device__ __forceinline__ void p2_storer(const Params& p, const Ctx& c, int sfpar) {
  const int nit = p.s.r[c.cl].n2;
  auto load_q = [&](int it, int w) {
    if (c.phases & 16) flag_wait<false>(F_HEAD + (p.s.r[c.cl].item[it] >> 3), 96);
    p2_load_q(p, c, it, w);
  };
  if (nit > 1) {
    load_q(1, 1); p2_load_q(p, c, 1, 0); }
  for (int i = 0; i < 2 * nit; i++) {
    const int it = i >> 1, w = (it ^ i ^ 1) & 1, b = p2_buf(w, it);
    const int item = p.s.r[c.cl].item[it], h = item >> 3, j = item & 7;
    mbar_wait(c.bar + (B_SF + b) * 8, (sfpar >> b) & 1);
    sfpar ^= 1 << b;
    bulk_store(g_Q + (size_t)(h * 32 + j * 4 + p2_blk(c.rank, w, it)) * 16384, c.sm + SM_BUF + b * 16384, 16384, POL(1));
    BULK_COMMIT();
    BULK_WAIT(0);
    flag_add_rx(F_CTX + j * 64 + h);
    if ((i & 1) && it + 2 < nit) { load_q(it + 2, w); p2_load_q(p, c, it + 2, w ^ 1); }
  }
  release(c, B_DONE);
}

__device__ __forceinline__ int p3_pos(int i, int x) { return i < 4 ? (i + x) & 3 : 4; }
__device__ __forceinline__ void p3_consumer(const Params& p, const Ctx& c, int x) {
  const bool first = p.s.r[c.cl].p3 >= 24;
  const int tile = p.s.r[c.cl].p3 - (first ? 24 : 0), j = tile / 3, nt = tile - 3 * j;
  const int na = first ? 9 : 0, nb = first ? 2 * p.s.nh : 64 - 2 * p.s.nh;
  const uint32_t ad = desc_lo(c.sm + SM_RING + c.wg * 8192, 16), bd = desc_lo(c.sm + SM_RING + 16384, 4096);
  float acc[96] = {};
  int slot = 0, par = 0, prev = 0;
#pragma unroll 1
  for (int kb = 0; kb < na; kb++) {
    mbar_wait(c.bar + (B_P3F + slot) * 8, par);
    if (kb == 0) PROF(c.wg, 39);
    WG_FENCE();
#pragma unroll
    for (int kk = 0; kk < 4; kk++) wgmma_ss192<1, 1>(acc, ad + p3_pos(slot, x) * 2560 + kk * 128, bd + p3_pos(slot, x) * 2560 + (kk >> 1) * 768 + (kk & 1) * 128, kk != 0 ? 1 : kb != 0);
    WG_COMMIT();
    WG_WAIT(1);
    if (kb > 0) release(c, B_P3E + prev);
    prev = slot;
    if (++slot == 5) { slot = 0; par ^= 1; }
  }
#pragma unroll 1
  for (int kb = na; kb < na + nb; kb++) {
    mbar_wait(c.bar + (B_P3F + slot) * 8, par);
    if (kb == 0) PROF(c.wg, 39);
    WG_FENCE();
#pragma unroll
    for (int kk = 0; kk < 4; kk++) wgmma_ss192<1>(acc, ad + p3_pos(slot, x) * 2560 + kk * 2, bd + p3_pos(slot, x) * 2560 + (kk >> 1) * 768 + (kk & 1) * 128, kk != 0 ? 1 : kb != 0);
    WG_COMMIT();
    WG_WAIT(1);
    if (kb > 0) release(c, B_P3E + prev);
    prev = slot;
    if (++slot == 5) { slot = 0; par ^= 1; }
  }
  WG_WAIT(0);
  pin(acc);
  PROF(c.wg, 40);
  if (first) bar_sync(4 + c.wg, 128);
  else mbar_wait(c.bar + B_OUT * 8, 0);
  const int row = (c.lane & 7) + ((c.lane >> 3) & 1) * 8;
  const uint32_t wbase = c.sm + SM_RING + c.wg * 8192 + c.warp * 2048;
  const uint32_t base = wbase + row * 128 + (((c.lane >> 4) ^ (row & 7)) << 4);
#pragma unroll
  for (int i = 0; i < 12; i++) {
    stsm4((base ^ ((i & 3) << 5)) + (i >> 2) * 40960, pack_bf16(acc[8 * i], acc[8 * i + 1]), pack_bf16(acc[8 * i + 2], acc[8 * i + 3]),
          pack_bf16(acc[8 * i + 4], acc[8 * i + 5]), pack_bf16(acc[8 * i + 6], acc[8 * i + 7]));
    if ((i & 3) == 3) {
      FENCE_ASYNC_SMEM();
      __syncwarp();
      const int c0 = nt * 192 + (i >> 2) * 64, c1 = j * 256 + c.rank * 128 + c.wg * 64 + c.warp * 16;
      if (first) tma2d_store(&p.map_out, wbase + (i >> 2) * 40960, c0, c1);
      else tma2d_add(&p.map_out, wbase + (i >> 2) * 40960, c0, c1);
    }
  }
  BULK_COMMIT();
  PROF(c.wg, 43);
  BULK_WAIT(0);
  if (first) flag_add_rx(F_OUT + tile * 2 + c.rank);
  PROF(c.wg, 44);
}

__device__ __forceinline__ void p3_producer(const Params& p, const Ctx& c, int u1, int u2, int rot, int x) {
  const bool first = p.s.r[c.cl].p3 >= 24;
  const int tile = p.s.r[c.cl].p3 - (first ? 24 : 0), j = tile / 3, nt = tile - 3 * j;
  int slot = 0, par = 1, cnt = 0;
  auto wait_free = [&](int s) {
    const int f = wrap5(s + 5 - rot);
    if (f < u2) mbar_wait(c.bar + (B_P2E + s) * 8, ((u2 - 1 - f) / 5) & 1);
    else if (u1) wait_p1_free(c, u1, s);
  };
  asm volatile(ELECT("prefetch.tensormap [%0];") ::"l"(&p.map_o[first]) : "memory");
  asm volatile(ELECT("prefetch.tensormap [%0];") ::"l"(&p.map_out) : "memory");
  const int q1 = first ? p.s.nh : 32;
  for (int q = first ? -1 : p.s.nh; q < q1; q++) {
    const int g = q < 0 ? 32 : p.s.p3_order[j][q];
    if (c.phases & 16) flag_wait<false>(F_CTX + j * 64 + g, q < 0 ? 16 : 4);
    const int nk = q < 0 ? 9 : 2, k0 = (q < 0 ? 0 : g * 128) + c.rank * 32;
    const uint8_t* a = q < 0 ? g_oA + (j * 4 + c.rank * 2) * 73728 : g_Q + (size_t)(g * 32 + j * 4 + c.rank * 2) * 16384;
    const CUtensorMap* m = &p.map_o[q < 0];
    for (int i = 0; i < nk; i++) {
      const uint32_t st = c.sm + SM_RING + p3_pos(slot, x) * 40960, fb = c.bar + (B_P3F + slot) * 8;
      if (cnt < 4) { wait_free(p3_pos(cnt, x)); wait_free(p3_pos(cnt, x) + 1); }
      else if (cnt == 4) mbar_wait(c.bar + B_DONE * 8, 0);
      else mbar_wait(c.bar + (B_P3E + slot) * 8, par);
      cnt++;
      mbar_expect(fb, 40960);
      bulk_load(st, a + i * 8192, 8192, fb, POL(3));
      bulk_load(st + 8192, a + (nk + i) * 8192, 8192, fb, POL(3));
      tma3d_mc(st + 16384 + c.rank * 12288, m, 0, k0 + i * 64, nt * 3, fb);
      if (++slot == 5) { slot = 0; par ^= 1; }
    }
  }
}

__device__ __forceinline__ float bf_lo(uint32_t w) { return __uint_as_float(w << 16); }
__device__ __forceinline__ float bf_hi(uint32_t w) { return __uint_as_float(w & 0xffff0000u); }

__device__ __forceinline__ void gate_rows(const Params& p, int row0, int lane) {
  const uint4* x = reinterpret_cast<const uint4*>(p.x + (size_t)(row0 + (lane >> 2)) * DM) + (lane & 3);
  const uint4* w = reinterpret_cast<const uint4*>(p.gate_w) + (lane & 3);
  float a = 0.f;
#pragma unroll 1
  for (int b = 0; b < 3; b++) {
    uint4 u[6];
#pragma unroll
    for (int i = 0; i < 6; i++) u[i] = __ldg(x + (b * 6 + i) * 4);
#pragma unroll
    for (int i = 0; i < 6; i++) {
      const uint4 v = __ldg(w + (b * 6 + i) * 4);
      a = fmaf(bf_lo(u[i].x), bf_lo(v.x), a); a = fmaf(bf_hi(u[i].x), bf_hi(v.x), a);
      a = fmaf(bf_lo(u[i].y), bf_lo(v.y), a); a = fmaf(bf_hi(u[i].y), bf_hi(v.y), a);
      a = fmaf(bf_lo(u[i].z), bf_lo(v.z), a); a = fmaf(bf_hi(u[i].z), bf_hi(v.z), a);
      a = fmaf(bf_lo(u[i].w), bf_lo(v.w), a); a = fmaf(bf_hi(u[i].w), bf_hi(v.w), a);
    }
  }
  a += __shfl_xor_sync(0xffffffffu, a, 1);
  a += __shfl_xor_sync(0xffffffffu, a, 2);
  if ((lane & 3) == 0) g_gate[row0 + (lane >> 2)] = 1.f / (1.f + __expf(-a));
}

__device__ __forceinline__ void lds10(uint32_t (&k)[10], uint32_t a) {
  asm volatile("ld.shared.v2.u32 {%0, %1}, [%10];\nld.shared.v2.u32 {%2, %3}, [%10+8];\nld.shared.v2.u32 {%4, %5}, [%10+16];\n"
               "ld.shared.v2.u32 {%6, %7}, [%10+24];\nld.shared.v2.u32 {%8, %9}, [%10+32];"
               : "=r"(k[0]), "=r"(k[1]), "=r"(k[2]), "=r"(k[3]), "=r"(k[4]), "=r"(k[5]), "=r"(k[6]), "=r"(k[7]), "=r"(k[8]), "=r"(k[9]) : "r"(a));
}
__device__ __forceinline__ void local_attn(const Params& p, const Ctx& c, int rb, int hs) {
  const int lane = c.lane, grp = rb >> 2, par = lane >> 4, i0 = 2 * (lane & 15);
  const uint32_t buf = c.sm + SM_BUF + (c.warp - 2) * 8192, bqk = c.bar + (B_LA + (c.warp - 2) * 2) * 8, bv = bqk + 8;
  const uint32_t mine = buf + 2304 + par * 160 + i0 * 4;
  const bool flags = c.phases & 16;
  auto fetch_qk = [&](int i) {
    if (flags && !(i & 1)) {
      const int q = i >> 1;
      const int tgt = q == 0 ? 24 : q == 3 ? 8 : 12;
      flag_wait<false>(F_QKVA + (grp - (grp > 0 && (rb & 3) == 0 ? par : 0)) * 4 + q, tgt);
    }
    mbar_expect(bqk, 5184);
    tma3d(buf, &p.map_t[0], rb * 32 + 8, 0, 9 * (4 * i + hs), bqk, POL(2));
    tma3d(buf + 2304, &p.map_t[1], rb * 32, 0, 288 + 9 * (4 * i + hs), bqk, POL(2));
  };
  auto fetch_v = [&](int i) { mbar_expect(bv, 2880); tma3d(buf + 5248, &p.map_t[1], rb * 32, 0, 576 + 9 * (4 * i + hs), bv, POL(2)); };
  fetch_qk(0);
  if (flags) flag_wait<true>(F_GATE, 256);
#pragma unroll 1
  for (int q = 0; q < 8; q++) {
    fetch_v(q);
    float a[8], b[8];
#pragma unroll
    for (int w = 0; w < 8; w++) a[w] = b[w] = 0.f;
    mbar_wait(bqk, q & 1);
    PROFB(1 + 2 * q);
#pragma unroll 1
    for (int j = 0; j < 9; j++) {
      uint32_t x, y, k[10];
      asm volatile("ld.shared.v2.u32 {%0, %1}, [%2];" : "=r"(x), "=r"(y) : "r"(buf + lane * 8 + j * 256));
      lds10(k, mine + j * 320);
      const float xl = bf_lo(x), xh = bf_hi(x), yl = bf_lo(y), yh = bf_hi(y);
#pragma unroll
      for (int m = 1; m < 10; m++) {
        const float kl = bf_lo(k[m]), kh = bf_hi(k[m]);
        if (m < 9) a[8 - m] = fmaf(xl, kl, fmaf(xh, kh, a[8 - m]));
        if (m > 1) b[9 - m] = fmaf(yl, kl, fmaf(yh, kh, b[9 - m]));
      }
    }
    __syncwarp();
    if (q < 7) fetch_qk(q + 1);
    constexpr float SC = 0.23570226039551584f * 1.4426950408889634f;
    const float* gp = g_gate + rb * 64 + 2 * i0 + par;
    const float ga = __ldcg(gp), gb = __ldcg(gp + 2);
    float ma = a[0], mb = b[0];
#pragma unroll
    for (int w = 1; w < 8; w++) {
      if (rb == 0) {
        if (i0 < w) a[w] = -INFINITY;
        if (i0 + 1 < w) b[w] = -INFINITY;
      }
      ma = fmaxf(ma, a[w]); mb = fmaxf(mb, b[w]);
    }
    float la = 0.f, lb = 0.f;
#pragma unroll
    for (int w = 0; w < 8; w++) {
      a[w] = ex2((a[w] - ma) * SC); b[w] = ex2((b[w] - mb) * SC);
      la += a[w]; lb += b[w];
    }
    la = __fdividef(ga, la); lb = __fdividef(gb, lb);
#pragma unroll
    for (int w = 0; w < 8; w++) { a[w] *= la; b[w] *= lb; }
    uint8_t* dst = g_oA + rb * 73728 + ((i0 & 2) + par) * 4;
    mbar_wait(bv, q & 1);
#pragma unroll 1
    for (int j = 0; j < 9; j++) {
      uint32_t v[10];
      lds10(v, mine + 2944 + j * 320);
      float a0 = 0.f, a1 = 0.f, b0 = 0.f, b1 = 0.f;
#pragma unroll
      for (int m = 1; m < 10; m++) {
        const float vl = bf_lo(v[m]), vh = bf_hi(v[m]);
        if (m < 9) { a0 = fmaf(a[8 - m], vl, a0); a1 = fmaf(a[8 - m], vh, a1); }
        if (m > 1) { b0 = fmaf(b[9 - m], vl, b0); b1 = fmaf(b[9 - m], vh, b1); }
      }
      const uint32_t wa = pack_bf16(a0, a1), wb = pack_bf16(b0, b1);
      const uint32_t got = __shfl_xor_sync(0xffffffffu, par ? wa : wb, 16);
      const uint32_t r0 = par ? got : wa, r1 = par ? wb : got;
      const int col = 18 * (4 * q + hs) + 2 * j, o = col * 128 + ((((i0 >> 2) ^ col) & 7) << 4);
      *reinterpret_cast<uint32_t*>(dst + o) = __byte_perm(r0, r1, 0x5410);
      *reinterpret_cast<uint32_t*>(dst + ((o + 128) ^ 16)) = __byte_perm(r0, r1, 0x7632);
    }
    __syncwarp();
    PROFB(2 + 2 * q);
  }
  mbar_arrive_one(c.bar + B_LAD * 8);
  flag_add(F_CTX + grp * 64 + 32);
}

__global__ void __cluster_dims__(2, 1, 1) __launch_bounds__(384, 1) fused_kernel(const __grid_constant__ Params p) {
  extern __shared__ uint8_t smem_raw[];
  Ctx c;
  c.sm = ((uint32_t)__cvta_generic_to_shared(smem_raw) + 1023u) & ~1023u;
  c.bar = c.sm + SM_BAR;
  c.lane = threadIdx.x & 31;
  c.wg = __shfl_sync(0xffffffffu, threadIdx.x >> 7, 0);
  c.warp = __shfl_sync(0xffffffffu, (threadIdx.x >> 5) & 3, 0);
  PROF(c.wg, 0);
  PROFG(61);
  c.cl = blockIdx.x >> 1;
  c.rank = blockIdx.x & 1;
  c.rbar = mapa(c.bar, c.lane & 1);
  if (threadIdx.x == 256) {
#pragma unroll
    for (int i = 0; i < B_NUM; i++) {
      int cnt = 1;
      if ((i >= B_P1E && i < B_P1E + 10) || (i >= B_P2E && i < B_P2E + 5) || (i >= B_P3E && i < B_P3E + 5)) cnt = 16;
      if (i >= B_P2F && i < B_P2F + 4) cnt = 5;
      if ((i >= B_SF && i < B_SF + 4) || (i >= B_ORD && i < B_ORD + 4)) cnt = 4;
      if (i == B_LAD || i == B_DONE) cnt = 2;
      if (i == B_FIN) cnt = 8;
      asm volatile("mbarrier.init.shared::cta.b64 [%0], %1;" ::"r"(c.bar + i * 8), "r"(cnt));
    }
    asm volatile("fence.mbarrier_init.release.cluster;" ::: "memory");
  }
  __syncwarp();
  asm volatile("barrier.cluster.arrive.relaxed;" ::: "memory");
  if (c.wg * 4 + c.warp < 6) asm volatile(ELECT("prefetch.tensormap [%0];") ::"l"(&p.map_a[0] + c.wg * 4 + c.warp) : "memory");
  c.phases = p.s.r[c.cl].phases;
  const bool do1 = (c.phases & 1) && p.s.r[c.cl].n1 > 0;
  const bool do2 = (c.phases & 2) && p.s.r[c.cl].n2 > 0;
  const bool do3 = (c.phases & (p.s.r[c.cl].p3 < 24 ? 4 : 32)) && p.s.r[c.cl].p3 != 255;
  const int u1 = do1 ? 8 + p.s.r[c.cl].n1 * (8 + (p.s.r[c.cl].slab >> 3)) : 0;
  const int rot = ((u1 % 10 + 1) >> 1) % 5;
  const int u2 = do2 ? p.s.r[c.cl].u2 : 0, x3 = (rot + u2) % 5 & 3;
  if (do1 && c.wg == 2 && c.warp == 0) {
    const int type = p.s.r[c.cl].slab >> 3;
    FENCE_ASYNC_SMEM();
    mbar_expect(c.bar + B_P1F * 8, type ? 32768 : 16384);
    tma2d(type ? c.sm + SM_BUF + 32768 : c.sm + SM_RING, &p.map_a[type], type ? 512 : 0, (p.s.r[c.cl].slab & 7) * 256 + c.rank * 128, c.bar + B_P1F * 8);
  }
  asm volatile("barrier.cluster.wait.acquire;" ::: "memory");

  if (c.wg < 2) {
    PROF(c.wg, 4);
    asm volatile("setmaxnreg.inc.sync.aligned.u32 224;");
    if (c.wg == 1) {
      if (do1) bar_arrive(ORDER, 256);
      if (c.lane == 0) mbar_arrive(c.bar + B_P2F * 8);
    }
    if (do1) p1_consumer(p, c);
    if (do2) p2_consumer(p, c, rot);
    if (do3) p3_consumer(p, c, x3);
    PROF(c.wg, 63);
    PROFG(62);
    if (c.lane == 0) mbar_arrive(c.bar + B_FIN * 8);
    __syncwarp();
    cluster_sync();
  } else {
    asm volatile("setmaxnreg.dec.sync.aligned.u32 56;");
    if (c.warp == 0) {
      PROF(2, 60);
      if (do1) p1_producer(p, c);
      if (do2) p2_producer(p, c, u1, rot);
      if (do3) p3_producer(p, c, u1, u2, rot, x3);
    } else if (c.warp == 1) {
      int sfpar = 0;
      if (do1) {
        p1_storer(p, c);
        sfpar = (p.s.r[c.cl].n1 & 1) * 10;
      }
      if (do2) p2_storer(p, c, sfpar);
      else { mbar_wait(c.bar + B_LAD * 8, 0); release(c, B_DONE); }
      if (do3 && p.s.r[c.cl].p3 < 24) {
        if (c.phases & 16) flag_wait<false, 256>(F_OUT + p.s.r[c.cl].p3 * 2 + c.rank, 8);
        mbar_arrive_one(c.bar + B_OUT * 8);
      }
    } else {
      const int bw = blockIdx.x * 2 + (c.warp - 2);
      if ((c.phases & 1) && bw < 256) {
        gate_rows(p, bw * 8, c.lane);
        __syncwarp();
        flag_add(F_GATE);
      }
      if ((c.phases & 8) && p.s.r[c.cl].bg != 255) local_attn(p, c, p.s.r[c.cl].bg, bw & 3);
      else if (c.lane == 0) mbar_arrive(c.bar + B_LAD * 8);
    }
    __syncwarp();
    bar_sync(3, 128);
    if (c.warp == 0 && (c.phases & 4)) {
      int last = 0;
      if (c.lane == 0) { __threadfence(); last = atomicAdd(g_flags + F_DONE, 1) == 2 * NCL - 1; }
      if (__shfl_sync(0xffffffffu, last, 0)) for (int i = c.lane; i < F_NUM; i += 32) g_flags[i] = 0;
    }
    if (c.warp == 1) mbar_wait(c.bar + B_FIN * 8, 0);
    __syncwarp();
    cluster_sync();
  }
}

static const Sched k_sched = {
  {{0,26,0,0,0,{0,0,0,0,0,0,0,0,0,0,0},{0,2,4,6,8,10,12,45,15,16,17,18,19,20,21,22,23,24,25,26,27,28,29,30,31,63,0,0,0,0,0,0}},
   {0,24,4,255,1,{144,187,218,251,0,0,0,0,0,0,0},{32,34,36,38,40,42,44,14,47,48,49,50,51,52,53,54,55,56,57,58,59,60,61,62,0,0,0,0,0,0,0,0}},
   {0,8,4,24,255,{3,38,118,191,0,0,0,0,0,0,0},{1,3,5,7,9,11,13,46,0,0,0,0,0,0,0,0,0,0,0,0,0,0,0,0,0,0,0,0,0,0,0,0}},
   {0,6,5,255,255,{14,55,130,207,236,0,0,0,0,0,0},{33,35,37,39,41,43,0,0,0,0,0,0,0,0,0,0,0,0,0,0,0,0,0,0,0,0,0,0,0,0,0,0}},
   {8,19,3,255,2,{146,175,250,0,0,0,0,0,0,0,0},{0,32,41,37,34,38,43,35,39,44,40,45,18,20,22,24,26,28,30,0,0,0,0,0,0,0,0,0,0,0,0,0}},
   {8,19,3,25,3,{112,188,204,0,0,0,0,0,0,0,0},{1,4,6,8,10,11,12,13,14,15,16,17,19,21,23,25,27,29,31,0,0,0,0,0,0,0,0,0,0,0,0,0}},
   {8,4,3,1,255,{45,63,127,0,0,0,0,0,0,0,0},{2,36,33,42,0,0,0,0,0,0,0,0,0,0,0,0,0,0,0,0,0,0,0,0,0,0,0,0,0,0,0,0}},
   {8,4,7,26,255,{32,12,49,90,91,117,223,0,0,0,0},{3,5,7,9,0,0,0,0,0,0,0,0,0,0,0,0,0,0,0,0,0,0,0,0,0,0,0,0,0,0,0,0}},
   {1,26,0,2,4,{0,0,0,0,0,0,0,0,0,0,0},{0,2,4,6,8,10,12,45,15,16,17,18,19,20,21,22,23,24,25,26,27,28,29,30,31,63,0,0,0,0,0,0}},
   {1,24,1,3,5,{161,0,0,0,0,0,0,0,0,0,0},{32,34,36,38,40,42,44,14,47,48,49,50,51,52,53,54,55,56,57,58,59,60,61,62,0,0,0,0,0,0,0,0}},
   {1,6,8,4,255,{16,25,74,59,106,113,149,192,0,0,0},{1,3,5,7,9,11,0,0,0,0,0,0,0,0,0,0,0,0,0,0,0,0,0,0,0,0,0,0,0,0,0,0}},
   {1,8,6,27,255,{72,81,37,143,171,228,0,0,0,0,0},{33,35,37,39,41,43,13,46,0,0,0,0,0,0,0,0,0,0,0,0,0,0,0,0,0,0,0,0,0,0,0,0}},
   {9,20,2,255,6,{215,252,0,0,0,0,0,0,0,0,0},{0,32,41,37,34,38,43,35,39,44,40,45,18,20,22,24,26,28,30,31,0,0,0,0,0,0,0,0,0,0,0,0}},
   {9,18,3,28,7,{88,158,227,0,0,0,0,0,0,0,0},{1,4,6,8,10,11,12,13,14,15,16,17,19,21,23,25,27,29,0,0,0,0,0,0,0,0,0,0,0,0,0,0}},
   {9,4,4,5,255,{44,7,135,208,0,0,0,0,0,0,0},{2,36,33,42,0,0,0,0,0,0,0,0,0,0,0,0,0,0,0,0,0,0,0,0,0,0,0,0,0,0,0,0}},
   {9,4,7,255,255,{13,97,54,186,155,179,253,0,0,0,0},{3,5,7,9,0,0,0,0,0,0,0,0,0,0,0,0,0,0,0,0,0,0,0,0,0,0,0,0,0,0,0,0}},
   {2,26,0,6,8,{0,0,0,0,0,0,0,0,0,0,0},{0,34,5,7,9,11,13,14,15,16,17,18,19,20,21,22,23,24,25,26,27,28,29,30,31,63,0,0,0,0,0,0}},
   {2,24,1,7,9,{169,0,0,0,0,0,0,0,0,0,0},{32,3,37,39,41,43,45,46,47,48,49,50,51,52,53,54,55,56,57,58,59,60,61,62,0,0,0,0,0,0,0,0}},
   {2,6,6,29,255,{48,15,107,114,132,230,0,0,0,0,0},{1,35,6,8,10,12,0,0,0,0,0,0,0,0,0,0,0,0,0,0,0,0,0,0,0,0,0,0,0,0,0,0}},
   {2,2,6,30,255,{1,9,23,100,196,182,0,0,0,0,0},{33,4,0,0,0,0,0,0,0,0,0,0,0,0,0,0,0,0,0,0,0,0,0,0,0,0,0,0,0,0,0,0}},
   {2,6,5,255,255,{29,76,110,165,254,0,0,0,0,0,0},{2,36,38,40,42,44,0,0,0,0,0,0,0,0,0,0,0,0,0,0,0,0,0,0,0,0,0,0,0,0,0,0}},
   {10,20,4,255,10,{145,183,241,248,0,0,0,0,0,0,0},{0,32,41,37,34,38,43,35,39,44,40,45,18,20,22,24,26,28,30,31,0,0,0,0,0,0,0,0,0,0,0,0}},
   {10,18,3,31,11,{104,147,222,0,0,0,0,0,0,0,0},{1,4,6,8,10,11,12,13,14,15,16,17,19,21,23,25,27,29,0,0,0,0,0,0,0,0,0,0,0,0,0,0}},
   {10,4,6,255,255,{36,82,69,131,150,238,0,0,0,0,0},{2,36,33,42,0,0,0,0,0,0,0,0,0,0,0,0,0,0,0,0,0,0,0,0,0,0,0,0,0,0,0,0}},
   {10,4,7,32,255,{8,33,5,85,123,170,214,0,0,0,0},{3,5,7,9,0,0,0,0,0,0,0,0,0,0,0,0,0,0,0,0,0,0,0,0,0,0,0,0,0,0,0,0}},
   {3,24,2,8,12,{152,200,0,0,0,0,0,0,0,0,0},{0,2,4,6,8,10,12,45,15,16,17,18,19,20,21,22,23,24,25,26,27,28,29,30,0,0,0,0,0,0,0,0}},
   {3,26,0,9,13,{0,0,0,0,0,0,0,0,0,0,0},{32,34,36,38,40,42,44,14,47,48,49,50,51,52,53,54,55,56,57,58,59,60,61,62,31,63,0,0,0,0,0,0}},
   {3,6,7,255,255,{17,60,58,94,157,202,244,0,0,0,0},{1,3,5,7,9,11,0,0,0,0,0,0,0,0,0,0,0,0,0,0,0,0,0,0,0,0,0,0,0,0,0,0}},
   {3,8,6,33,255,{56,57,53,101,194,231,0,0,0,0,0},{33,35,37,39,41,43,13,46,0,0,0,0,0,0,0,0,0,0,0,0,0,0,0,0,0,0,0,0,0,0,0,0}},
   {11,20,2,255,14,{164,247,0,0,0,0,0,0,0,0,0},{0,32,41,37,34,38,43,35,39,44,40,45,18,20,22,24,26,28,30,31,0,0,0,0,0,0,0,0,0,0,0,0}},
   {11,18,3,34,15,{96,181,212,0,0,0,0,0,0,0,0},{1,4,6,8,10,11,12,13,14,15,16,17,19,21,23,25,27,29,0,0,0,0,0,0,0,0,0,0,0,0,0,0}},
   {11,4,8,255,255,{19,66,75,92,125,177,203,243,0,0,0},{2,36,33,42,0,0,0,0,0,0,0,0,0,0,0,0,0,0,0,0,0,0,0,0,0,0,0,0,0,0,0,0}},
   {11,4,6,35,255,{35,67,78,121,151,235,0,0,0,0,0},{3,5,7,9,0,0,0,0,0,0,0,0,0,0,0,0,0,0,0,0,0,0,0,0,0,0,0,0,0,0,0,0}},
   {4,26,0,10,16,{0,0,0,0,0,0,0,0,0,0,0},{0,2,4,6,8,10,12,45,15,16,17,18,19,20,21,22,23,24,25,26,27,28,29,30,31,63,0,0,0,0,0,0}},
   {4,24,3,255,17,{173,219,249,0,0,0,0,0,0,0,0},{32,34,36,38,40,42,44,14,47,48,49,50,51,52,53,54,55,56,57,58,59,60,61,62,0,0,0,0,0,0,0,0}},
   {4,6,7,255,255,{26,21,93,153,199,226,234,0,0,0,0},{1,3,5,7,9,11,0,0,0,0,0,0,0,0,0,0,0,0,0,0,0,0,0,0,0,0,0,0,0,0,0,0}},
   {4,8,6,36,255,{64,31,102,190,233,232,0,0,0,0,0},{33,35,37,39,41,43,13,46,0,0,0,0,0,0,0,0,0,0,0,0,0,0,0,0,0,0,0,0,0,0,0,0}},
   {12,21,2,11,18,{136,184,0,0,0,0,0,0,0,0,0},{0,32,41,37,34,38,43,35,39,44,40,45,18,20,22,24,26,28,29,30,31,0,0,0,0,0,0,0,0,0,0,0}},
   {12,17,2,12,19,{80,180,0,0,0,0,0,0,0,0,0},{1,4,6,8,10,11,12,13,14,15,16,17,19,21,23,25,27,0,0,0,0,0,0,0,0,0,0,0,0,0,0,0}},
   {12,4,3,13,255,{39,86,134,0,0,0,0,0,0,0,0},{2,36,33,42,0,0,0,0,0,0,0,0,0,0,0,0,0,0,0,0,0,0,0,0,0,0,0,0,0,0,0,0}},
   {12,4,4,14,255,{6,61,111,176,0,0,0,0,0,0,0},{3,5,7,9,0,0,0,0,0,0,0,0,0,0,0,0,0,0,0,0,0,0,0,0,0,0,0,0,0,0,0,0}},
   {5,26,0,15,20,{0,0,0,0,0,0,0,0,0,0,0},{0,34,5,39,10,12,13,14,15,16,17,18,19,20,21,22,23,24,25,26,27,28,29,30,31,63,0,0,0,0,0,0}},
   {5,24,3,255,21,{178,245,242,0,0,0,0,0,0,0,0},{32,3,37,8,42,44,45,46,47,48,49,50,51,52,53,54,55,56,57,58,59,60,61,62,0,0,0,0,0,0,0,0}},
   {5,5,3,16,255,{47,70,174,0,0,0,0,0,0,0,0},{1,35,6,40,11,0,0,0,0,0,0,0,0,0,0,0,0,0,0,0,0,0,0,0,0,0,0,0,0,0,0,0}},
   {5,4,8,255,255,{0,11,50,65,98,116,189,255,0,0,0},{33,4,38,9,0,0,0,0,0,0,0,0,0,0,0,0,0,0,0,0,0,0,0,0,0,0,0,0,0,0,0,0}},
   {5,5,6,37,255,{43,27,77,115,142,211,0,0,0,0,0},{2,36,7,41,43,0,0,0,0,0,0,0,0,0,0,0,0,0,0,0,0,0,0,0,0,0,0,0,0,0,0,0}},
   {13,20,2,17,22,{128,193,0,0,0,0,0,0,0,0,0},{0,32,41,37,34,38,43,35,39,44,40,45,18,20,22,24,26,28,30,31,0,0,0,0,0,0,0,0,0,0,0,0}},
   {13,18,4,255,23,{137,201,172,213,0,0,0,0,0,0,0},{1,4,6,8,10,11,12,13,14,15,16,17,19,21,23,25,27,29,0,0,0,0,0,0,0,0,0,0,0,0,0,0}},
   {13,4,4,18,255,{22,79,141,160,0,0,0,0,0,0,0},{2,36,33,42,0,0,0,0,0,0,0,0,0,0,0,0,0,0,0,0,0,0,0,0,0,0,0,0,0,0,0,0}},
   {13,4,7,38,255,{24,42,89,71,124,148,220,0,0,0,0},{3,5,7,9,0,0,0,0,0,0,0,0,0,0,0,0,0,0,0,0,0,0,0,0,0,0,0,0,0,0,0,0}},
   {6,26,0,19,24,{0,0,0,0,0,0,0,0,0,0,0},{0,2,4,6,8,10,12,14,15,16,17,18,19,20,21,22,23,24,25,26,27,28,29,30,31,63,0,0,0,0,0,0}},
   {6,24,1,20,25,{185,0,0,0,0,0,0,0,0,0,0},{32,34,36,38,40,42,44,46,47,48,49,50,51,52,53,54,55,56,57,58,59,60,61,62,0,0,0,0,0,0,0,0}},
   {6,7,4,39,255,{46,68,126,167,0,0,0,0,0,0,0},{1,3,5,7,9,11,13,0,0,0,0,0,0,0,0,0,0,0,0,0,0,0,0,0,0,0,0,0,0,0,0,0}},
   {6,7,6,21,255,{18,73,99,129,109,139,0,0,0,0,0},{33,35,37,39,41,43,45,0,0,0,0,0,0,0,0,0,0,0,0,0,0,0,0,0,0,0,0,0,0,0,0,0}},
   {14,18,2,40,26,{133,197,0,0,0,0,0,0,0,0,0},{0,32,41,37,34,38,43,35,39,44,40,45,18,20,22,24,26,28,0,0,0,0,0,0,0,0,0,0,0,0,0,0}},
   {14,20,4,41,27,{120,162,195,225,0,0,0,0,0,0,0},{1,4,6,8,10,11,12,13,14,15,16,17,19,21,23,25,27,29,30,31,0,0,0,0,0,0,0,0,0,0,0,0}},
   {14,4,7,42,255,{2,84,52,108,154,206,224,0,0,0,0},{2,36,33,42,0,0,0,0,0,0,0,0,0,0,0,0,0,0,0,0,0,0,0,0,0,0,0,0,0,0,0,0}},
   {14,4,5,43,255,{30,105,95,140,246,0,0,0,0,0,0},{3,5,7,9,0,0,0,0,0,0,0,0,0,0,0,0,0,0,0,0,0,0,0,0,0,0,0,0,0,0,0,0}},
   {7,25,3,255,28,{217,210,237,0,0,0,0,0,0,0,0},{0,2,4,6,8,10,12,45,15,16,17,18,19,20,21,22,23,24,25,26,27,28,29,30,31,0,0,0,0,0,0,0}},
   {7,25,3,255,29,{216,239,240,0,0,0,0,0,0,0,0},{32,34,36,38,40,42,44,14,47,48,49,50,51,52,53,54,55,56,57,58,59,60,61,62,63,0,0,0,0,0,0,0}},
   {7,8,4,44,255,{28,62,159,229,0,0,0,0,0,0,0},{1,3,5,7,9,11,13,46,0,0,0,0,0,0,0,0,0,0,0,0,0,0,0,0,0,0,0,0,0,0,0,0}},
   {7,6,6,22,255,{41,34,51,103,138,209,0,0,0,0,0},{33,35,37,39,41,43,0,0,0,0,0,0,0,0,0,0,0,0,0,0,0,0,0,0,0,0,0,0,0,0,0,0}},
   {15,20,2,45,30,{163,221,0,0,0,0,0,0,0,0,0},{0,32,41,37,34,38,43,35,39,44,40,45,18,20,22,24,26,28,30,31,0,0,0,0,0,0,0,0,0,0,0,0}},
   {15,18,2,46,31,{156,198,0,0,0,0,0,0,0,0,0},{1,4,6,8,10,11,12,13,14,15,16,17,19,21,23,25,27,29,0,0,0,0,0,0,0,0,0,0,0,0,0,0}},
   {15,4,5,47,255,{10,4,87,166,205,0,0,0,0,0,0},{2,36,33,42,0,0,0,0,0,0,0,0,0,0,0,0,0,0,0,0,0,0,0,0,0,0,0,0,0,0,0,0}},
   {15,4,6,23,255,{40,20,83,122,119,168,0,0,0,0,0},{3,5,7,9,0,0,0,0,0,0,0,0,0,0,0,0,0,0,0,0,0,0,0,0,0,0,0,0,0,0,0,0}}},
  32, 4,
  {{0,1,3,4,5,2,6,7,8,9,10,11,12,13,14,15,16,21,20,22,26,17,18,19,24,23,25,27,28,29,30,31},
   {0,2,5,4,1,3,7,10,11,9,12,6,13,8,16,14,15,19,17,25,18,24,20,21,23,26,27,22,29,28,30,31},
   {0,1,3,5,2,4,9,8,10,6,7,11,12,15,13,14,23,16,17,19,24,18,21,20,22,26,25,27,28,29,31,30},
   {2,4,5,1,0,3,8,6,10,12,7,9,13,11,14,16,15,17,19,18,20,21,23,22,24,25,26,29,28,27,30,31},
   {4,5,1,2,7,3,0,10,9,6,8,11,12,14,13,15,22,19,24,16,17,18,23,20,21,28,26,27,25,30,29,31},
   {1,5,3,0,2,4,6,7,8,9,10,11,12,13,14,17,18,15,16,19,23,22,20,21,24,28,25,27,30,26,31,29},
   {0,2,3,1,5,4,7,6,9,8,10,11,13,12,15,14,16,21,20,17,18,19,23,25,24,22,28,27,26,30,31,29},
   {4,5,1,2,3,0,8,7,9,6,10,11,12,17,14,13,16,15,19,18,24,25,26,28,27,20,23,21,22,29,31,30}}};

typedef CUresult (*EncodeFn)(CUtensorMap*, CUtensorMapDataType, cuuint32_t, void*, const cuuint64_t*, const cuuint64_t*, const cuuint32_t*,
                             const cuuint32_t*, CUtensorMapInterleave, CUtensorMapSwizzle, CUtensorMapL2promotion, CUtensorMapFloatOOBfill);

void make_map2(EncodeFn enc, CUtensorMap* m, const void* ptr, int rows, int cols, int box_rows) {
  cuuint64_t dim[2] = {(cuuint64_t)cols, (cuuint64_t)rows}, str[1] = {(cuuint64_t)cols * 2};
  cuuint32_t box[2] = {64, (cuuint32_t)box_rows}, es[2] = {1, 1};
  enc(m, CU_TENSOR_MAP_DATA_TYPE_BFLOAT16, 2, const_cast<void*>(ptr), dim, str, box, es, CU_TENSOR_MAP_INTERLEAVE_NONE, CU_TENSOR_MAP_SWIZZLE_128B,
      CU_TENSOR_MAP_L2_PROMOTION_L2_128B, CU_TENSOR_MAP_FLOAT_OOB_FILL_NONE);
}
void make_map3(EncodeFn enc, CUtensorMap* m, const void* ptr, int rows) {
  cuuint64_t dim[3] = {64, (cuuint64_t)rows, 9}, str[2] = {DM * 2, 128};
  cuuint32_t box[3] = {64, 32, 3}, es[3] = {1, 1, 1};
  enc(m, CU_TENSOR_MAP_DATA_TYPE_BFLOAT16, 3, const_cast<void*>(ptr), dim, str, box, es, CU_TENSOR_MAP_INTERLEAVE_NONE, CU_TENSOR_MAP_SWIZZLE_128B,
      CU_TENSOR_MAP_L2_PROMOTION_L2_128B, CU_TENSOR_MAP_FLOAT_OOB_FILL_NONE);
}

void make_map_t(EncodeFn enc, CUtensorMap* m, void* ptr, int width, int cols) {
  cuuint64_t dim[3] = {TP / 2, 2, 864}, str[2] = {TP * 2, TP * 4};
  cuuint32_t box[3] = {(cuuint32_t)width, 2, (cuuint32_t)cols}, es[3] = {1, 1, 1};
  enc(m, CU_TENSOR_MAP_DATA_TYPE_UINT32, 3, ptr, dim, str, box, es, CU_TENSOR_MAP_INTERLEAVE_NONE, cols == 64 ? CU_TENSOR_MAP_SWIZZLE_128B : CU_TENSOR_MAP_SWIZZLE_NONE,
      CU_TENSOR_MAP_L2_PROMOTION_NONE, CU_TENSOR_MAP_FLOAT_OOB_FILL_NONE);
}

int g_mode = -1;

}

extern "C" void kernel_launch(void* const* d_in, const int* in_sizes, int n_in, void* d_out, int out_size) {
  static EncodeFn enc = nullptr;
  static void* t_ptr = nullptr;
  if (!enc) {
    void* fn = nullptr;
    cudaDriverEntryPointQueryResult st;
    cudaGetDriverEntryPoint("cuTensorMapEncodeTiled", &fn, cudaEnableDefault, &st);
    enc = (EncodeFn)fn;
    cudaGetSymbolAddress(&t_ptr, g_T);
    cudaFuncSetAttribute(fused_kernel, cudaFuncAttributeMaxDynamicSharedMemorySize, SMEM_BYTES);
    if (g_mode < 0) {
      cudaLaunchConfig_t cfg = {};
      cfg.gridDim = dim3(2 * NCL); cfg.blockDim = dim3(384); cfg.dynamicSmemBytes = SMEM_BYTES;
      cudaLaunchAttribute at; at.id = cudaLaunchAttributeClusterDimension;
      at.val.clusterDim.x = 2; at.val.clusterDim.y = 1; at.val.clusterDim.z = 1;
      cfg.attrs = &at; cfg.numAttrs = 1;
      int nc = 0;
      g_mode = (cudaOccupancyMaxActiveClusters(&nc, fused_kernel, &cfg) == cudaSuccess && nc >= NCL) ? 1 : 0;
      (void)cudaGetLastError();
    }
  }
  Params p;
  make_map2(enc, &p.map_a[0], d_in[4], SEQ, DC, 128);
  make_map2(enc, &p.map_a[1], d_in[0], SEQ, DM, 128);
  make_map2(enc, &p.map_w[0], d_in[6], DC, 4096, 64);
  make_map2(enc, &p.map_w[1], d_in[7], DC, 4096, 64);
  make_map2(enc, &p.map_w[2], d_in[5], DM, 4096, 64);
  make_map2(enc, &p.map_w[3], d_in[1], DM, 1728, 64);
  make_map3(enc, &p.map_o[0], d_in[8], 4096);
  make_map3(enc, &p.map_o[1], d_in[2], DM);
  make_map_t(enc, &p.map_t[0], t_ptr, 32, 9);
  make_map_t(enc, &p.map_t[1], t_ptr, 40, 9);
  make_map_t(enc, &p.map_t[2], t_ptr, 32, 64);
  p.x = (const __nv_bfloat16*)d_in[0];
  p.gate_w = (const __nv_bfloat16*)d_in[9];
  make_map2(enc, &p.map_out, d_out, SEQ, DM, 16);
  p.zero = 0;
  p.s = k_sched;
  for (int i = 0; i < NCL; i++) {
    int u = 0;
    for (int k = 0; k < p.s.r[i].n2; k++) u += 4 * (p.s.r[i].item[k] & 7) + 4;
    p.s.r[i].u2 = (uint8_t)u;
    p.s.r[i].ring = g_mode == 1 ? p.s.ring : 32;
  }
  auto launch = [&](int phases) {
    for (int i = 0; i < NCL; i++) p.s.r[i].phases = (uint8_t)phases;
    fused_kernel<<<2 * NCL, 384, SMEM_BYTES>>>(p);
  };
  if (g_mode == 1) launch(63);
  else { launch(1); launch(10); launch(32); launch(4); }
}
```

```cpp
#include <cuda_runtime.h>
#include <cuda_bf16.h>
#include <cuda.h>
#include <stdint.h>

namespace {

constexpr int SEQ = 2048, DM = 576, DC = 512, NH = 32;
constexpr int NCL = 66;
constexpr uint32_t DESC_HI = 0x40000040u;

constexpr int SM_RING = 0;
constexpr int SM_BUF = 163840;
constexpr int SM_BAR = 229376;
constexpr int B_P1E = 0, B_P2E = 10, B_P3E = 15, B_P2F = 24, B_SF = 32, B_ORD = 36, B_LAD = 40, B_DONE = 41, B_FIN = 48;
constexpr int B_P3F = 56, B_OUT = 61, B_P1F = 64, B_SE = 74, B_QF = 80, B_LA = 84, B_NUM = 88;
constexpr uint64_t B_CNT = 0x11118245000ull;
constexpr int SMEM_BYTES = SM_BAR + B_NUM * 8 + 1024;

constexpr int F_HEAD = 0;
constexpr int F_QKVA = 32;
constexpr int F_GATE = 64;
constexpr int F_DONE = 65;
constexpr int F_CTX = 96;
constexpr int F_OUT = 96 + 8 * 64;
constexpr int F_NUM = F_OUT + 48;

struct Rec {
  uint8_t slab;
  uint8_t n1, n2;
  uint8_t p3;
  uint8_t bg;
  uint8_t item[11];
  uint8_t last[11];
  uint8_t tile[31];
  uint8_t ring;
  uint8_t u1, u2;
  uint8_t rot, x3;
  uint8_t phases;
};
struct Sched {
  Rec r[NCL];
  uint8_t ring, nh;
  uint8_t p3_order[8][32];
};

struct Params {
  CUtensorMap map_a[2];
  CUtensorMap map_w[4];
  CUtensorMap map_o[2];
  CUtensorMap map_t[3];
  CUtensorMap map_out;
  const __nv_bfloat16* x;
  const __nv_bfloat16* gate_w;
  int zero;
  alignas(64) Sched s;
};

__device__ __align__(1024) uint8_t g_Q[NH * 32 * 16384];
__device__ __align__(1024) uint8_t g_KV[2 * NH * 16 * 32768];
__device__ __align__(1024) uint8_t g_oA[32 * 576 * 128];
constexpr int TP = SEQ + 16;
__device__ __align__(1024) uint32_t g_T[864 * TP];
__device__ float g_gate[SEQ];
__device__ int g_flags[F_NUM];

__device__ __forceinline__ void mbar_arrive(uint32_t b) { asm volatile("mbarrier.arrive.shared::cta.b64 _, [%0];" ::"r"(b) : "memory"); }
__device__ __forceinline__ void mbar_arrive_cl(uint32_t b, int cnt) {
  asm volatile("mbarrier.arrive.shared::cluster.b64 _, [%0], %1;" ::"r"(b), "r"(cnt) : "memory");
}
__device__ __forceinline__ void mbar_wait(uint32_t b, int par) {
  asm volatile(
      "{\n.reg .pred p;\n.reg .u32 c;\n"
      "mbarrier.try_wait.parity.shared::cta.b64 p, [%0], %1;\n@p bra DN;\nmov.u32 c, 0;\n"
      "LP:\nmbarrier.try_wait.parity.shared::cta.b64 p, [%0], %1;\n@p bra DN;\n"
      "add.u32 c, c, 1;\nsetp.lt.u32 p, c, 4000000;\n@p bra LP;\ntrap;\nDN:\n}" ::"r"(b), "r"(par) : "memory");
}
__device__ __forceinline__ uint32_t mapa(uint32_t a, uint32_t cta) {
  uint32_t r; asm("mapa.shared::cluster.u32 %0, %1, %2;" : "=r"(r) : "r"(a), "r"(cta)); return r;
}
#define ELECT(ins) "{\n.reg .pred e;\nelect.sync _|e, 0xffffffff;\n@e " ins "\n}"
__device__ __forceinline__ void mbar_expect(uint32_t b, int bytes) {
  asm volatile(ELECT("mbarrier.arrive.expect_tx.shared::cta.b64 _, [%0], %1;") ::"r"(b), "r"(bytes) : "memory");
}
__device__ __forceinline__ void mbar_arrive_one(uint32_t b) { asm volatile(ELECT("mbarrier.arrive.shared::cta.b64 _, [%0];") ::"r"(b) : "memory"); }
constexpr uint64_t L2_NORMAL = 0x1000000000000000ull, L2_FIRST = 0x12F0000000000000ull;
__device__ __forceinline__ void bulk_load(uint32_t dst, const void* src, int bytes, uint32_t bar, uint64_t pol = L2_NORMAL) {
  asm volatile(ELECT("cp.async.bulk.shared::cluster.global.mbarrier::complete_tx::bytes.L2::cache_hint [%0], [%1], %2, [%3], %4;") ::"r"(dst), "l"(src), "r"(bytes), "r"(bar), "l"(pol) : "memory");
}
__device__ __forceinline__ void bulk_load_mc(uint32_t dst, const void* src, int bytes, uint32_t bar, uint64_t pol = L2_NORMAL) {
  asm volatile(ELECT("cp.async.bulk.shared::cluster.global.mbarrier::complete_tx::bytes.multicast::cluster.L2::cache_hint [%0], [%1], %2, [%3], %4, %5;") ::"r"(dst), "l"(src), "r"(bytes), "r"(bar), "h"((uint16_t)3), "l"(pol) : "memory");
}
__device__ __forceinline__ void bulk_store(void* dst, uint32_t src, int bytes, uint64_t pol = L2_NORMAL) {
  asm volatile(ELECT("cp.async.bulk.global.shared::cta.bulk_group.L2::cache_hint [%0], [%1], %2, %3;") ::"l"(dst), "r"(src), "r"(bytes), "l"(pol) : "memory");
}
__device__ __forceinline__ void tma2d(uint32_t dst, const CUtensorMap* m, int c0, int c1, uint32_t bar, uint64_t pol = L2_NORMAL) {
  asm volatile(ELECT("cp.async.bulk.tensor.2d.shared::cluster.global.mbarrier::complete_tx::bytes.L2::cache_hint [%0], [%1, {%3, %4}], [%2], %5;") ::"r"(dst), "l"(m), "r"(bar), "r"(c0), "r"(c1), "l"(pol) : "memory");
}
__device__ __forceinline__ void tma2d_mc(uint32_t dst, const CUtensorMap* m, int c0, int c1, uint32_t bar, uint64_t pol = L2_NORMAL) {
  asm volatile(ELECT("cp.async.bulk.tensor.2d.shared::cluster.global.mbarrier::complete_tx::bytes.multicast::cluster.L2::cache_hint [%0], [%1, {%3, %4}], [%2], %5, %6;") ::"r"(dst), "l"(m), "r"(bar), "r"(c0), "r"(c1), "h"((uint16_t)3), "l"(pol) : "memory");
}
__device__ __forceinline__ void tma3d(uint32_t dst, const CUtensorMap* m, int c0, int c1, int c2, uint32_t bar, uint64_t pol = L2_NORMAL) {
  asm volatile(ELECT("cp.async.bulk.tensor.3d.shared::cluster.global.mbarrier::complete_tx::bytes.L2::cache_hint [%0], [%1, {%3, %4, %5}], [%2], %6;") ::"r"(dst), "l"(m), "r"(bar), "r"(c0), "r"(c1), "r"(c2), "l"(pol) : "memory");
}
__device__ __forceinline__ void tma3d_mc(uint32_t dst, const CUtensorMap* m, int c0, int c1, int c2, uint32_t bar, uint64_t pol = L2_NORMAL) {
  asm volatile(ELECT("cp.async.bulk.tensor.3d.shared::cluster.global.mbarrier::complete_tx::bytes.multicast::cluster.L2::cache_hint [%0], [%1, {%3, %4, %5}], [%2], %6, %7;") ::"r"(dst), "l"(m), "r"(bar), "r"(c0), "r"(c1), "r"(c2), "h"((uint16_t)3), "l"(pol) : "memory");
}
__device__ __forceinline__ void tma2d_store(const CUtensorMap* m, uint32_t src, int c0, int c1, uint64_t pol = L2_NORMAL) {
  asm volatile(ELECT("cp.async.bulk.tensor.2d.global.shared::cta.bulk_group.L2::cache_hint [%0, {%2, %3}], [%1], %4;") ::"l"(m), "r"(src), "r"(c0), "r"(c1), "l"(pol) : "memory");
}
__device__ __forceinline__ void tma2d_add(const CUtensorMap* m, uint32_t src, int c0, int c1) {
  asm volatile(ELECT("cp.reduce.async.bulk.tensor.2d.global.shared::cta.add.bulk_group [%0, {%2, %3}], [%1];") ::"l"(m), "r"(src), "r"(c0), "r"(c1) : "memory");
}
__device__ __forceinline__ void tma3d_store(const CUtensorMap* m, uint32_t src, int c0, int c1, int c2, uint64_t pol = L2_NORMAL) {
  asm volatile(ELECT("cp.async.bulk.tensor.3d.global.shared::cta.bulk_group.L2::cache_hint [%0, {%2, %3, %4}], [%1], %5;") ::"l"(m), "r"(src), "r"(c0), "r"(c1), "r"(c2), "l"(pol) : "memory");
}
__device__ __forceinline__ void tma2d_prefetch(const CUtensorMap* m, int c0, int c1, uint64_t pol = L2_NORMAL) {
  asm volatile(ELECT("cp.async.bulk.prefetch.tensor.2d.L2.global.L2::cache_hint [%0, {%1, %2}], %3;") ::"l"(m), "r"(c0), "r"(c1), "l"(pol) : "memory");
}
#define HINT 62
#define POL(bit) ((HINT >> (bit)) & 1 ? L2_FIRST : L2_NORMAL)
#define BULK_COMMIT() asm volatile("cp.async.bulk.commit_group;" ::: "memory")
#define BULK_WAIT(n) asm volatile("cp.async.bulk.wait_group %0;" ::"n"(n) : "memory")
#define BULK_WAIT_READ(n) asm volatile("cp.async.bulk.wait_group.read %0;" ::"n"(n) : "memory")
#define FENCE_ASYNC_SMEM() asm volatile("fence.proxy.async.shared::cta;" ::: "memory")
#define FENCE_ASYNC_ALL() asm volatile("fence.proxy.async;" ::: "memory")
#define WG_FENCE() asm volatile("wgmma.fence.sync.aligned;" ::: "memory")
#define WG_COMMIT() asm volatile("wgmma.commit_group.sync.aligned;" ::: "memory")
#define WG_WAIT(n) asm volatile("wgmma.wait_group.sync.aligned %0;" ::"n"(n) : "memory")
__device__ __forceinline__ void bar_sync(int id, int n) { asm volatile("bar.sync %0, %1;" ::"r"(id), "r"(n) : "memory"); }
__device__ __forceinline__ void bar_arrive(int id, int n) { asm volatile("bar.arrive %0, %1;" ::"r"(id), "r"(n) : "memory"); }
__device__ __forceinline__ void cluster_sync() {
  asm volatile("barrier.cluster.arrive.relaxed;\nbarrier.cluster.wait.acquire;" ::: "memory");
}
template <int N> __device__ __forceinline__ void pin(float (&r)[N]) {
#pragma unroll
  for (int i = 0; i < N; i++) asm volatile("" : "+f"(r[i])::"memory");
}
template <int N> __device__ __forceinline__ void pin(uint32_t (&r)[N]) {
#pragma unroll
  for (int i = 0; i < N; i++) asm volatile("" : "+r"(r[i])::"memory");
}
__device__ __forceinline__ uint32_t pack_bf16(float lo, float hi) {
  uint32_t r; asm("cvt.rn.bf16x2.f32 %0, %1, %2;" : "=r"(r) : "f"(hi), "f"(lo)); return r;
}
__device__ __forceinline__ float ex2(float x) { float r; asm("ex2.approx.ftz.f32 %0, %1;" : "=f"(r) : "f"(x)); return r; }
__device__ __forceinline__ void ldsm4(uint32_t a, uint32_t& r0, uint32_t& r1, uint32_t& r2, uint32_t& r3) {
  asm volatile("ldmatrix.sync.aligned.m8n8.x4.shared.b16 {%0,%1,%2,%3}, [%4];" : "=r"(r0), "=r"(r1), "=r"(r2), "=r"(r3) : "r"(a) : "memory");
}
__device__ __forceinline__ void stsm4(uint32_t a, uint32_t r0, uint32_t r1, uint32_t r2, uint32_t r3) {
  asm volatile("stmatrix.sync.aligned.m8n8.x4.shared.b16 [%0], {%1,%2,%3,%4};" ::"r"(a), "r"(r0), "r"(r1), "r"(r2), "r"(r3) : "memory");
}
__device__ __forceinline__ void flag_add(int idx) {
  asm volatile(ELECT("red.release.gpu.global.add.s32 [%0], 1;") ::"l"(g_flags + idx) : "memory");
}
__device__ __forceinline__ void flag_add_rx(int idx) {
  asm volatile(ELECT("red.relaxed.gpu.global.add.s32 [%0], 1;") ::"l"(g_flags + idx) : "memory");
}
template <bool ACQ, int NS = 32> __device__ __forceinline__ void flag_wait(int idx, int target) {
  int n = 0;
  while (true) {
    int v;
    if (ACQ) asm volatile("ld.acquire.gpu.global.s32 %0, [%1];" : "=r"(v) : "l"(g_flags + idx) : "memory");
    else asm volatile("ld.relaxed.gpu.global.s32 %0, [%1];" : "=r"(v) : "l"(g_flags + idx) : "memory");
    if (__all_sync(0xffffffffu, v >= target)) break;
    if (++n > 20000000) __trap();
    __nanosleep(NS);
  }
}
__device__ __forceinline__ uint32_t desc_lo(uint32_t addr, uint32_t lbo) { return ((addr & 0x3FFFFu) >> 4) | ((lbo >> 4) << 16); }
#define PROF(role, i)
#define PROFX(cond, i)
#define PROFB(i)
#define PROFG(i)

template <int TB, int TA = 0> __device__ __forceinline__ void wgmma_ss64(float (&d)[32], uint32_t alo, uint32_t blo, int sd) {
  asm volatile("{\n.reg .pred p;\n.reg .b64 da, db;\n"
    "setp.ne.b32 p, %34, 0;\nmov.b64 da, {%32, %36};\nmov.b64 db, {%33, %36};\n"
    "wgmma.mma_async.sync.aligned.m64n64k16.f32.bf16.bf16 "
    "{%0,%1,%2,%3,%4,%5,%6,%7,%8,%9,%10,%11,%12,%13,%14,%15,%16,%17,%18,%19,%20,%21,%22,%23,"
    "%24,%25,%26,%27,%28,%29,%30,%31}, "
    "da, db, p, 1, 1, %37, %35;\n}\n"
    : "+f"(d[0]),"+f"(d[1]),"+f"(d[2]),"+f"(d[3]),"+f"(d[4]),"+f"(d[5]),"+f"(d[6]),"+f"(d[7]),"+f"(d[8]),"+f"(d[9]),"+f"(d[10]),"+f"(d[11]),
      "+f"(d[12]),"+f"(d[13]),"+f"(d[14]),"+f"(d[15]),"+f"(d[16]),"+f"(d[17]),"+f"(d[18]),"+f"(d[19]),"+f"(d[20]),"+f"(d[21]),"+f"(d[22]),"+f"(d[23]),
      "+f"(d[24]),"+f"(d[25]),"+f"(d[26]),"+f"(d[27]),"+f"(d[28]),"+f"(d[29]),"+f"(d[30]),"+f"(d[31])
    : "r"(alo), "r"(blo), "r"(sd), "n"(TB), "r"(DESC_HI), "n"(TA));
}
template <int TB, int TA = 0> __device__ __forceinline__ void wgmma_ss128(float (&d)[64], uint32_t alo, uint32_t blo, int sd) {
  asm volatile("{\n.reg .pred p;\n.reg .b64 da, db;\n"
    "setp.ne.b32 p, %66, 0;\nmov.b64 da, {%64, %68};\nmov.b64 db, {%65, %68};\n"
    "wgmma.mma_async.sync.aligned.m64n128k16.f32.bf16.bf16 "
    "{%0,%1,%2,%3,%4,%5,%6,%7,%8,%9,%10,%11,%12,%13,%14,%15,%16,%17,%18,%19,%20,%21,%22,%23,"
    "%24,%25,%26,%27,%28,%29,%30,%31,%32,%33,%34,%35,%36,%37,%38,%39,%40,%41,%42,%43,%44,%45,%46,%47,"
    "%48,%49,%50,%51,%52,%53,%54,%55,%56,%57,%58,%59,%60,%61,%62,%63}, "
    "da, db, p, 1, 1, %69, %67;\n}\n"
    : "+f"(d[0]),"+f"(d[1]),"+f"(d[2]),"+f"(d[3]),"+f"(d[4]),"+f"(d[5]),"+f"(d[6]),"+f"(d[7]),"+f"(d[8]),"+f"(d[9]),"+f"(d[10]),"+f"(d[11]),
      "+f"(d[12]),"+f"(d[13]),"+f"(d[14]),"+f"(d[15]),"+f"(d[16]),"+f"(d[17]),"+f"(d[18]),"+f"(d[19]),"+f"(d[20]),"+f"(d[21]),"+f"(d[22]),"+f"(d[23]),
      "+f"(d[24]),"+f"(d[25]),"+f"(d[26]),"+f"(d[27]),"+f"(d[28]),"+f"(d[29]),"+f"(d[30]),"+f"(d[31]),"+f"(d[32]),"+f"(d[33]),"+f"(d[34]),"+f"(d[35]),
      "+f"(d[36]),"+f"(d[37]),"+f"(d[38]),"+f"(d[39]),"+f"(d[40]),"+f"(d[41]),"+f"(d[42]),"+f"(d[43]),"+f"(d[44]),"+f"(d[45]),"+f"(d[46]),"+f"(d[47]),
      "+f"(d[48]),"+f"(d[49]),"+f"(d[50]),"+f"(d[51]),"+f"(d[52]),"+f"(d[53]),"+f"(d[54]),"+f"(d[55]),"+f"(d[56]),"+f"(d[57]),"+f"(d[58]),"+f"(d[59]),
      "+f"(d[60]),"+f"(d[61]),"+f"(d[62]),"+f"(d[63])
    : "r"(alo), "r"(blo), "r"(sd), "n"(TB), "r"(DESC_HI), "n"(TA));
}
template <int TB> __device__ __forceinline__ void wgmma_rs128(float (&d)[64], uint32_t a0, uint32_t a1, uint32_t a2, uint32_t a3, uint32_t blo, int sd) {
  asm volatile("{\n.reg .pred p;\n.reg .b64 db;\n"
    "setp.ne.b32 p, %69, 0;\nmov.b64 db, {%68, %71};\n"
    "wgmma.mma_async.sync.aligned.m64n128k16.f32.bf16.bf16 "
    "{%0,%1,%2,%3,%4,%5,%6,%7,%8,%9,%10,%11,%12,%13,%14,%15,%16,%17,%18,%19,%20,%21,%22,%23,"
    "%24,%25,%26,%27,%28,%29,%30,%31,%32,%33,%34,%35,%36,%37,%38,%39,%40,%41,%42,%43,%44,%45,%46,%47,"
    "%48,%49,%50,%51,%52,%53,%54,%55,%56,%57,%58,%59,%60,%61,%62,%63}, "
    "{%64,%65,%66,%67}, db, p, 1, 1, %70;\n}\n"
    : "+f"(d[0]),"+f"(d[1]),"+f"(d[2]),"+f"(d[3]),"+f"(d[4]),"+f"(d[5]),"+f"(d[6]),"+f"(d[7]),"+f"(d[8]),"+f"(d[9]),"+f"(d[10]),"+f"(d[11]),
      "+f"(d[12]),"+f"(d[13]),"+f"(d[14]),"+f"(d[15]),"+f"(d[16]),"+f"(d[17]),"+f"(d[18]),"+f"(d[19]),"+f"(d[20]),"+f"(d[21]),"+f"(d[22]),"+f"(d[23]),
      "+f"(d[24]),"+f"(d[25]),"+f"(d[26]),"+f"(d[27]),"+f"(d[28]),"+f"(d[29]),"+f"(d[30]),"+f"(d[31]),"+f"(d[32]),"+f"(d[33]),"+f"(d[34]),"+f"(d[35]),
      "+f"(d[36]),"+f"(d[37]),"+f"(d[38]),"+f"(d[39]),"+f"(d[40]),"+f"(d[41]),"+f"(d[42]),"+f"(d[43]),"+f"(d[44]),"+f"(d[45]),"+f"(d[46]),"+f"(d[47]),
      "+f"(d[48]),"+f"(d[49]),"+f"(d[50]),"+f"(d[51]),"+f"(d[52]),"+f"(d[53]),"+f"(d[54]),"+f"(d[55]),"+f"(d[56]),"+f"(d[57]),"+f"(d[58]),"+f"(d[59]),
      "+f"(d[60]),"+f"(d[61]),"+f"(d[62]),"+f"(d[63])
    : "r"(a0), "r"(a1), "r"(a2), "r"(a3), "r"(blo), "r"(sd), "n"(TB), "r"(DESC_HI));
}
template <int TB, int TA = 0> __device__ __forceinline__ void wgmma_ss192(float (&d)[96], uint32_t alo, uint32_t blo, int sd) {
  asm volatile("{\n.reg .pred p;\n.reg .b64 da, db;\n"
    "setp.ne.b32 p, %98, 0;\nmov.b64 da, {%96, %100};\nmov.b64 db, {%97, %100};\n"
    "wgmma.mma_async.sync.aligned.m64n192k16.f32.bf16.bf16 "
    "{%0,%1,%2,%3,%4,%5,%6,%7,%8,%9,%10,%11,%12,%13,%14,%15,%16,%17,%18,%19,%20,%21,%22,%23,"
    "%24,%25,%26,%27,%28,%29,%30,%31,%32,%33,%34,%35,%36,%37,%38,%39,%40,%41,%42,%43,%44,%45,%46,%47,"
    "%48,%49,%50,%51,%52,%53,%54,%55,%56,%57,%58,%59,%60,%61,%62,%63,%64,%65,%66,%67,%68,%69,%70,%71,"
    "%72,%73,%74,%75,%76,%77,%78,%79,%80,%81,%82,%83,%84,%85,%86,%87,%88,%89,%90,%91,%92,%93,%94,%95}, "
    "da, db, p, 1, 1, %101, %99;\n}\n"
    : "+f"(d[0]),"+f"(d[1]),"+f"(d[2]),"+f"(d[3]),"+f"(d[4]),"+f"(d[5]),"+f"(d[6]),"+f"(d[7]),"+f"(d[8]),"+f"(d[9]),"+f"(d[10]),"+f"(d[11]),
      "+f"(d[12]),"+f"(d[13]),"+f"(d[14]),"+f"(d[15]),"+f"(d[16]),"+f"(d[17]),"+f"(d[18]),"+f"(d[19]),"+f"(d[20]),"+f"(d[21]),"+f"(d[22]),"+f"(d[23]),
      "+f"(d[24]),"+f"(d[25]),"+f"(d[26]),"+f"(d[27]),"+f"(d[28]),"+f"(d[29]),"+f"(d[30]),"+f"(d[31]),"+f"(d[32]),"+f"(d[33]),"+f"(d[34]),"+f"(d[35]),
      "+f"(d[36]),"+f"(d[37]),"+f"(d[38]),"+f"(d[39]),"+f"(d[40]),"+f"(d[41]),"+f"(d[42]),"+f"(d[43]),"+f"(d[44]),"+f"(d[45]),"+f"(d[46]),"+f"(d[47]),
      "+f"(d[48]),"+f"(d[49]),"+f"(d[50]),"+f"(d[51]),"+f"(d[52]),"+f"(d[53]),"+f"(d[54]),"+f"(d[55]),"+f"(d[56]),"+f"(d[57]),"+f"(d[58]),"+f"(d[59]),
      "+f"(d[60]),"+f"(d[61]),"+f"(d[62]),"+f"(d[63]),"+f"(d[64]),"+f"(d[65]),"+f"(d[66]),"+f"(d[67]),"+f"(d[68]),"+f"(d[69]),"+f"(d[70]),"+f"(d[71]),
      "+f"(d[72]),"+f"(d[73]),"+f"(d[74]),"+f"(d[75]),"+f"(d[76]),"+f"(d[77]),"+f"(d[78]),"+f"(d[79]),"+f"(d[80]),"+f"(d[81]),"+f"(d[82]),"+f"(d[83]),
      "+f"(d[84]),"+f"(d[85]),"+f"(d[86]),"+f"(d[87]),"+f"(d[88]),"+f"(d[89]),"+f"(d[90]),"+f"(d[91]),"+f"(d[92]),"+f"(d[93]),"+f"(d[94]),"+f"(d[95])
    : "r"(alo), "r"(blo), "r"(sd), "n"(TB), "r"(DESC_HI), "n"(TA));
}

struct Ctx {
  uint32_t sm;
  uint32_t bar;
  uint32_t rbar;
  int cl, rank, wg, warp, lane, phases;
};
__device__ __forceinline__ void release(const Ctx& c, int b, int cnt = 1) {
  if (c.lane < 2) mbar_arrive_cl(c.rbar + b * 8, cnt);
}
#define NPF 6
#define PFM 7
#define PF1 1
constexpr float SM_SCALE = 0.08838834764831845f * 1.4426950408889634f;
constexpr float SM_HI = 1.8446744e19f, SM_LO = 5.4210109e-20f;
constexpr int ORDER = 1;

__device__ __forceinline__ void stage_tile(const float (&a)[64], uint32_t buf, const Ctx& c, float s0, float s1) {
  const int row = (c.lane & 7) + ((c.lane >> 3) & 1) * 8;
  const uint32_t base = buf + (c.warp * 16 + row) * 128 + (((c.lane >> 4) ^ (row & 7)) << 4);
#pragma unroll
  for (int i = 0; i < 8; i++)
    stsm4((base ^ ((i & 3) << 5)) + (i >> 2) * 8192, pack_bf16(a[8 * i] * s0, a[8 * i + 1] * s0), pack_bf16(a[8 * i + 2] * s1, a[8 * i + 3] * s1),
          pack_bf16(a[8 * i + 4] * s0, a[8 * i + 5] * s0), pack_bf16(a[8 * i + 6] * s1, a[8 * i + 7] * s1));
}

__device__ __forceinline__ void p1_epilogue(const Params& p, const Ctx& c, const float (&acc)[64], int t, int type) {
  const int tile = p.s.r[c.cl].tile[t], b = c.wg * 2 + 1;
  mbar_wait(c.bar + (B_SE + b) * 8, (t & 1) ^ 1);
  if (type && tile >= 32) {
    const int r = 2 * (c.lane & 3) + ((c.lane >> 2) & 1);
    const uint32_t dst = c.sm + SM_BUF + b * 16384 + r * 128 + (((c.warp * 2) ^ r) << 4) + (c.lane >> 3) * 4;
#pragma unroll
    for (int i = 0; i < 16; i++) {
      asm volatile("st.shared.u32 [%0], %1;" ::"r"(dst + i * 1024), "r"(pack_bf16(acc[4 * i], acc[4 * i + 1])) : "memory");
      asm volatile("st.shared.u32 [%0], %1;" ::"r"((dst ^ 16) + i * 1024), "r"(pack_bf16(acc[4 * i + 2], acc[4 * i + 3])) : "memory");
    }
  } else {
    if (type) stage_tile(acc, c.sm + SM_BUF + b * 16384, c, SM_SCALE, SM_SCALE);
    else stage_tile(acc, c.sm + SM_BUF + b * 16384, c, 1.f, 1.f);
  }
  FENCE_ASYNC_SMEM();
  __syncwarp();
  if (c.lane == 0) mbar_arrive(c.bar + (B_SF + b) * 8);
}

__device__ __forceinline__ void p1_consumer(const Params& p, const Ctx& c) {
  const int n = p.s.r[c.cl].n1;
  const int type = p.s.r[c.cl].slab >> 3;
  const uint32_t bdesc = desc_lo(c.sm + SM_RING, 8192), adesc = desc_lo(c.sm + SM_BUF + 32768 + c.wg * 8192, 16);
  uint32_t A[128];
  float acc[64] = {};
  int slot = 0, par = 0;
  auto next = [&]() { if (++slot == 10) { slot = 0; par ^= 1; } };
  {
    const int row = (c.lane & 7) + ((c.lane >> 3) & 1) * 8;
    const uint32_t base = c.sm + SM_RING + (c.wg * 64 + c.warp * 16 + row) * 128 + (((c.lane >> 4) ^ (row & 7)) << 4);
    if (c.wg == 1) bar_sync(ORDER + 1, 256);
    int pa = -1, pb = -1;
    if (type) {
      mbar_wait(c.bar + B_P1F * 8, 0);
      WG_FENCE();
#pragma unroll
      for (int kk = 0; kk < 4; kk++) wgmma_ss128<1>(acc, adesc + kk * 2, bdesc + kk * 128, kk != 0);
      WG_COMMIT();
      pb = 0; slot = 1;
    }
#pragma unroll
    for (int kb = 0; kb < 8; kb++) {
      const int sa = slot;
      mbar_wait(c.bar + (B_P1F + slot) * 8, par);
      if (kb == 0) PROF(c.wg, 5);
      next();
      mbar_wait(c.bar + (B_P1F + slot) * 8, par);
      PROF(c.wg, 6 + 2 * kb);
      WG_FENCE();
#pragma unroll
      for (int kk = 0; kk < 4; kk++)
        wgmma_ss128<1>(acc, desc_lo(c.sm + SM_RING + c.wg * 8192, 16) + sa * 1024 + kk * 2, bdesc + slot * 1024 + kk * 128, (kb | kk) != 0 ? 1 : type);
      WG_COMMIT();
      if (kb == 1 && c.wg == 0) bar_arrive(ORDER + 1, 256);
#pragma unroll
      for (int kk = 0; kk < 4; kk++) ldsm4((base ^ (kk << 5)) + sa * 16384, A[kb * 16 + kk * 4], A[kb * 16 + kk * 4 + 1], A[kb * 16 + kk * 4 + 2], A[kb * 16 + kk * 4 + 3]);
      WG_WAIT(1);
      if (kb > 0) release(c, B_P1E + pa);
      if (kb > 0 || pb >= 0) release(c, B_P1E + pb);
      pa = sa; pb = slot;
      next();
    }
    WG_WAIT(0);
    __syncwarp();
    release(c, B_P1E + pa);
    release(c, B_P1E + pb);
    pin(acc);
    PROF(c.wg, 1);
    p1_epilogue(p, c, acc, 0, type);
    PROF(c.wg, 2);
  }
  for (int t = 1; t < n; t++) {
    bar_sync(ORDER + c.wg, 256);
    int prev1 = -1, prev2 = -1;
    if (type) {
      mbar_wait(c.bar + (B_P1F + slot) * 8, par);
      WG_FENCE();
#pragma unroll
      for (int kk = 0; kk < 4; kk++) wgmma_ss128<1>(acc, adesc + kk * 2, bdesc + slot * 1024 + kk * 128, kk != 0);
      WG_COMMIT();
      prev1 = slot;
      next();
    }
#pragma unroll
    for (int kb = 0; kb < 8; kb++) {
      mbar_wait(c.bar + (B_P1F + slot) * 8, par);
      WG_FENCE();
      const uint32_t d = bdesc + slot * 1024;
#pragma unroll
      for (int kk = 0; kk < 4; kk++)
        wgmma_rs128<1>(acc, A[kb * 16 + kk * 4], A[kb * 16 + kk * 4 + 1], A[kb * 16 + kk * 4 + 2], A[kb * 16 + kk * 4 + 3], d + kk * 128, (kb | kk) != 0 ? 1 : type);
      WG_COMMIT();
      if (kb == 7) {
        if (t + 1 < n || c.wg == 0) bar_arrive(ORDER + (c.wg ^ 1), 256);
      }
      if (kb > 0) { WG_WAIT(2); if (kb > 1 || prev2 >= 0) release(c, B_P1E + prev2); }
      prev2 = prev1; prev1 = slot;
      next();
    }
    WG_WAIT(1);
    release(c, B_P1E + prev2);
    WG_WAIT(0);
    pin(acc);
    release(c, B_P1E + prev1);
    p1_epilogue(p, c, acc, t, type);
    PROF(c.wg, 3);
  }
}

__device__ __forceinline__ void p1_producer(const Params& p, const Ctx& c) {
  const int n = p.s.r[c.cl].n1;
  const int type = p.s.r[c.cl].slab >> 3, grp = p.s.r[c.cl].slab & 7;
  int slot = 2 - type, par = 1;
#pragma unroll 1
  for (int t = 0; t < n; t++) {
    const int tile = p.s.r[c.cl].tile[t];
    const CUtensorMap* m = &p.map_w[type * 2 + (tile >> 5)];
    const int n0 = (tile & 31) * 128 + c.rank * 64;
    const int ptile = p.s.r[c.cl].tile[t + PF1 < n ? t + PF1 : t];
    const CUtensorMap* pm = &p.map_w[type * 2 + (ptile >> 5)];
#pragma unroll 1
    for (int kb = (t == 0) - type; kb < 8; kb++) {
      if (t == 0) {
        mbar_wait(c.bar + (B_P1E + slot) * 8, par);
        mbar_expect(c.bar + (B_P1F + slot) * 8, 16384);
        tma2d(c.sm + SM_RING + slot * 16384, &p.map_a[type], kb * 64, grp * 256 + c.rank * 128, c.bar + (B_P1F + slot) * 8);
        if (++slot == 10) { slot = 0; par ^= 1; }
      }
      mbar_wait(c.bar + (B_P1E + slot) * 8, par);
      mbar_expect(c.bar + (B_P1F + slot) * 8, 16384);
      tma2d_mc(c.sm + SM_RING + slot * 16384 + c.rank * 8192, m, n0, kb < 0 ? 512 : kb * 64, c.bar + (B_P1F + slot) * 8);
      if (t == 0 && kb == 1) PROF(2, 61);
      if (t == 0 && kb == 3) PROF(2, 62);
      if (t + PF1 < n && (t > 0 || kb >= 3) && ((kb ^ grp) & PFM) == 0) tma2d_prefetch(pm, (ptile & 31) * 128 + c.rank * 64, kb < 0 ? 512 : kb * 64);
      if (++slot == 10) { slot = 0; par ^= 1; }
    }
  }
}

__device__ __forceinline__ void p1_storer(const Params& p, const Ctx& c) {
  const int n = p.s.r[c.cl].n1;
  const int type = p.s.r[c.cl].slab >> 3, grp = p.s.r[c.cl].slab & 7;
  int pf = -1;
  for (int i = 0; i < 2 * n; i++) {
    const int t = i >> 1, w = i & 1, b = w * 2 + 1;
    const int tile = p.s.r[c.cl].tile[t];
    mbar_wait(c.bar + (B_SF + b) * 8, t & 1);
    const uint32_t src = c.sm + SM_BUF + b * 16384;
    int f = F_HEAD + (tile & 31);
    if (type == 0) {
      const int h = tile & 31, ring = p.s.r[c.cl].ring;
      if (h >= ring && w == 0) flag_wait<false>(F_CTX + max(c.lane & 7, grp) * 64 + h - ring, 4);
      uint8_t* dst = g_KV + (size_t)((h >= ring ? tile - ring : tile) * 16 + grp * 2 + c.rank) * 32768 + w * 8192;
      bulk_store(dst, src, 8192);
      bulk_store(dst + 16384, src + 8192, 8192);
    } else if (tile < 32) {
      bulk_store(g_Q + (size_t)(tile * 32 + grp * 4 + c.rank * 2 + w) * 16384, src, 16384);
    } else {
      tma3d_store(&p.map_t[2], src, 8 + (grp * 4 + c.rank * 2 + w) * 32, 0, (tile - 32) * 64);
      f = F_QKVA + grp * 4 + ((0xE4390900u >> (2 * (tile - 30))) & 3);
    }
    BULK_COMMIT();
    BULK_WAIT_READ(0);
    mbar_arrive_one(c.bar + (B_SE + b) * 8);
    if (pf >= 0) {
      BULK_WAIT(1);
      flag_add_rx(pf);
    }
    pf = f;
  }
  BULK_WAIT(0);
  flag_add_rx(pf);
}

__device__ __forceinline__ int p2_buf(int w, int i) { return w * 2 + (i & 1); }
__device__ __forceinline__ int p2_blk(int rank, int w, int i) { return ((i ^ w) & 1) == 0 ? 3 - rank : rank; }

template <int N>
__device__ __forceinline__ void row_max(const float (&s)[N], float& m0, float& m1) {
  float a0 = fmaxf(s[0], s[1]), a1 = fmaxf(s[2], s[3]);
#pragma unroll
  for (int i = 1; i < N / 4; i++) {
    m0 = fmaxf(m0, s[4 * i]); a0 = fmaxf(a0, s[4 * i + 1]);
    m1 = fmaxf(m1, s[4 * i + 2]); a1 = fmaxf(a1, s[4 * i + 3]);
  }
  m0 = fmaxf(m0, a0); m1 = fmaxf(m1, a1);
  m0 = fmaxf(m0, __shfl_xor_sync(0xffffffffu, m0, 1));
  m1 = fmaxf(m1, __shfl_xor_sync(0xffffffffu, m1, 1));
  m0 = fmaxf(m0, __shfl_xor_sync(0xffffffffu, m0, 2));
  m1 = fmaxf(m1, __shfl_xor_sync(0xffffffffu, m1, 2));
}
template <bool SUB, int N>
__device__ __forceinline__ void row_exp(const float (&s)[N], uint32_t (&P)[32], float m0, float m1, float& t0, float& t1) {
  float u0 = 0.f, u1 = 0.f;
  t0 = t1 = 0.f;
#pragma unroll
  for (int i = 0; i < N / 4; i++) {
    const float e0 = ex2(SUB ? s[4 * i] - m0 : s[4 * i]), e1 = ex2(SUB ? s[4 * i + 1] - m0 : s[4 * i + 1]);
    const float e2 = ex2(SUB ? s[4 * i + 2] - m1 : s[4 * i + 2]), e3 = ex2(SUB ? s[4 * i + 3] - m1 : s[4 * i + 3]);
    if (i == 0) { t0 = e0; u0 = e1; t1 = e2; u1 = e3; }
    else { t0 += e0; u0 += e1; t1 += e2; u1 += e3; }
    P[2 * i] = pack_bf16(e0, e1);
    P[2 * i + 1] = pack_bf16(e2, e3);
  }
#pragma unroll
  for (int i = N / 2; i < 32; i++) P[i] = 0;
  pin(P);
  t0 += u0; t1 += u1;
}
template <int N>
__device__ __forceinline__ void causal_mask(float (&s)[N], int thr) {
#pragma unroll
  for (int i = 0; i < 8; i++) {
    if (8 * i > thr) s[N - 32 + 4 * i] = -INFINITY;
    if (8 * i + 1 > thr) s[N - 32 + 4 * i + 1] = -INFINITY;
    if (8 * i - 8 > thr) s[N - 32 + 4 * i + 2] = -INFINITY;
    if (8 * i - 7 > thr) s[N - 32 + 4 * i + 3] = -INFINITY;
  }
}
__device__ __forceinline__ void issue_qk(float (&s)[32], uint32_t qd, uint32_t kd) {
  WG_FENCE();
#pragma unroll
  for (int kk = 0; kk < 8; kk++) wgmma_ss64<0>(s, qd + (kk >> 2) * 512 + (kk & 3) * 2, kd + (kk >> 2) * 1024 + (kk & 3) * 2, kk != 0);
  WG_COMMIT();
}
__device__ __forceinline__ void issue_qk(float (&s)[64], uint32_t qd, uint32_t kd) {
  WG_FENCE();
#pragma unroll
  for (int kk = 0; kk < 8; kk++) wgmma_ss128<0>(s, qd + (kk >> 2) * 512 + (kk & 3) * 2, kd + (kk >> 2) * 1024 + (kk & 3) * 2, kk != 0);
  WG_COMMIT();
}
template <int NK>
__device__ __forceinline__ void issue_pv(float (&o)[64], const uint32_t (&P)[32], uint32_t vd, int acc) {
  WG_FENCE();
#pragma unroll
  for (int kk = 0; kk < NK; kk++) wgmma_rs128<1>(o, P[4 * kk], P[4 * kk + 1], P[4 * kk + 2], P[4 * kk + 3], vd + kk * 128, kk != 0 ? 1 : acc);
  WG_COMMIT();
}
__device__ __forceinline__ void stage_done(const Ctx& c, int b) {
  FENCE_ASYNC_SMEM();
  __syncwarp();
  if (c.lane == 0) mbar_arrive(c.bar + (B_SF + b) * 8);
}
__device__ __forceinline__ void p2_epilogue(const float (&o)[64], float s0, float s1, const Ctx& c, int b) {
  stage_tile(o, c.sm + SM_BUF + b * 16384, c, s0, s1);
  stage_done(c, b);
}

struct P2State {
  float m0, m1, l0, l1;
  bool shift;
  float e0, e1;
  float g0, g1;
  int ks;
  int wi, ai;
  uint32_t wb, ab;
  uint32_t qd;
};
#define PROFZ()
__device__ __forceinline__ int wrap5(int q) { return q >= 5 ? q - 5 : q; }
__device__ __forceinline__ void turn_wait(uint32_t ring, int i) { mbar_wait(ring + (i & 3) * 8, (i >> 2) & 1); }
__device__ __forceinline__ void turn_pass(const Ctx& c, uint32_t ring, int i) { if (c.lane == 0) mbar_arrive(ring + (i & 3) * 8); }
__device__ __forceinline__ void p2_gate(P2State& z, const Ctx& c, int row0) {
  const float* g = g_gate + row0 + c.warp * 16 + (c.lane >> 2);
  asm volatile("ld.global.cg.f32 %0, [%2];\nld.global.cg.f32 %1, [%2+32];" : "=f"(z.g0), "=f"(z.g1) : "l"(g) : "memory");
}
__device__ __forceinline__ void p2_scales(P2State& z) {
  float l0 = z.l0, l1 = z.l1;
  l0 += __shfl_xor_sync(0xffffffffu, l0, 1);
  l1 += __shfl_xor_sync(0xffffffffu, l1, 1);
  l0 += __shfl_xor_sync(0xffffffffu, l0, 2);
  l1 += __shfl_xor_sync(0xffffffffu, l1, 2);
  z.e0 = __fdividef(1.f - z.g0, l0); z.e1 = __fdividef(1.f - z.g1, l1);
}
template <int N, bool PV>
__device__ __forceinline__ void p2_first(const Params& p, const Ctx& c, P2State& z, float (&o)[64], uint32_t (&Pc)[32], uint32_t (&Pn)[32],
                                         int ks, int vs, int cnt, int acc, int row0) {
  float s[N] = {};
  issue_qk(s, z.qd, desc_lo(c.sm + SM_RING, 16) + ks * 2048);
  if (PV) {
    if (p.zero == 0) p2_scales(z);
    issue_pv<8>(o, Pc, desc_lo(c.sm + SM_RING, 16384) + vs * 2048, acc);
  }
  if (cnt == 1 && c.warp == 0) mbar_expect(z.ab + (z.ai & 3) * 8, 32768); else turn_pass(c, z.ab, z.ai);
  z.ai++;
  PROFZ();
  if (PV) WG_WAIT(1); else WG_WAIT(0);
  PROFZ();
  pin(s);
  release(c, B_P2E + ks, cnt);
  p2_gate(z, c, row0);
  causal_mask(s, c.warp * 16 + (c.lane >> 2) - 2 * (c.lane & 3));
  z.m0 = z.m1 = 0.f;
  row_exp<false>(s, Pn, 0.f, 0.f, z.l0, z.l1);
  z.shift = __any_sync(0xffffffffu, !(z.l0 + z.l1 <= SM_HI) || ((c.lane & 3) == 0 && !(fminf(z.l0, z.l1) >= SM_LO)));
  if (__builtin_expect(z.shift, 0)) {
    z.m0 = z.m1 = -INFINITY;
    row_max(s, z.m0, z.m1);
    row_exp<true>(s, Pn, z.m0, z.m1, z.l0, z.l1);
  }
  if (PV) {
    WG_WAIT(0);
    pin(o);
    release(c, B_P2E + vs, 1);
  }
}

template <bool SECOND>
__device__ __forceinline__ void p2_turn(const Ctx& c, P2State& z, float (&o)[64], uint32_t (&Pc)[32], uint32_t (&Pn)[32],
                                        int eb = -1, bool half = false, int vcnt = 1) {
  float s[64] = {};
  const int ks = z.ks, vs = wrap5(ks + 1);
  PROFZ();
  turn_wait(z.wb, z.wi++);
  PROFZ();
  issue_qk(s, z.qd, desc_lo(c.sm + SM_RING, 16) + ks * 2048);
  const uint32_t vd = desc_lo(c.sm + SM_RING, 16384) + vs * 2048;
  if (SECOND) {
    if (eb >= 0) stage_tile(o, c.sm + SM_BUF + eb * 16384, c, z.e0, z.e1);
    if (half) issue_pv<4>(o, Pc, vd, 0); else issue_pv<8>(o, Pc, vd, 0);
  } else {
    issue_pv<8>(o, Pc, vd, 1);
  }
  turn_pass(c, z.ab, z.ai++);
  if (SECOND) { if (eb >= 0) stage_done(c, eb); }
  PROFZ();
  z.ks = wrap5(ks + 2);
  WG_WAIT(1);
  PROFZ();
  pin(s);
  release(c, B_P2E + ks, 1);
  float t0, t1, a0 = 1.f, a1 = 1.f;
  row_exp<false>(s, Pn, 0.f, 0.f, t0, t1);
  z.shift = __any_sync(0xffffffffu, z.shift || !(t0 + t1 <= SM_HI));
  const bool redo = z.shift;
  if (__builtin_expect(redo, 0)) {
    float n0 = z.m0, n1 = z.m1;
    row_max(s, n0, n1);
    a0 = ex2(z.m0 - n0); a1 = ex2(z.m1 - n1);
    z.m0 = n0; z.m1 = n1;
    z.l0 *= a0; z.l1 *= a1;
    row_exp<true>(s, Pn, z.m0, z.m1, t0, t1);
  }
  WG_WAIT(0);
  pin(o);
  release(c, B_P2E + vs, vcnt);
  if (__builtin_expect(redo, 0)) {
#pragma unroll
    for (int i = 0; i < 16; i++) { o[4 * i] *= a0; o[4 * i + 1] *= a0; o[4 * i + 2] *= a1; o[4 * i + 3] *= a1; }
  }
  z.l0 += t0; z.l1 += t1;
}
__device__ __forceinline__ void copy_p(uint32_t (&d)[32], const uint32_t (&s)[32], int zero) {
#pragma unroll
  for (int i = 0; i < 32; i++) asm volatile("add.s32 %0, %1, %2;" : "=r"(d[i]) : "r"(s[i]), "r"(zero));
}

__device__ __forceinline__ void p2_consumer(const Params& p, const Ctx& c, int rot) {
  const int nit = p.s.r[c.cl].n2;
  const uint32_t fring = c.bar + B_P2F * 8, oring = c.bar + B_ORD * 8;
  float o[64] = {};
  uint32_t Pa[32] = {}, Pb[32] = {};
  P2State z;
  z.e0 = z.e1 = z.l0 = z.l1 = z.g0 = z.g1 = 0.f; z.ks = rot; z.shift = false;
  int acc = 0, n = 0;
  for (int it = 0; it < nit; it++) {
    const int j = p.s.r[c.cl].item[it] & 7, blk = p2_blk(c.rank, c.wg, it), row0 = (j * 4 + blk) * 64;
    const int lng = ((it ^ c.wg) & 1) ^ 1;
    z.qd = desc_lo(c.sm + SM_BUF, 16) + p2_buf(c.wg, it) * 1024;
    if (lng) { z.wb = oring; z.wi = n - it; z.ab = fring; z.ai = n + 1; }
    else { z.wb = fring; z.wi = n + 2; z.ab = oring; z.ai = n - it; }
    PROFZ();
    mbar_wait(c.bar + (B_QF + p2_buf(c.wg, it)) * 8, (it >> 1) & 1);
    turn_wait(fring, n + 1 - lng);
    PROFZ();
    if (it == 0) {
      const int ks = wrap5(rot + c.wg);
      if (blk & 1) p2_first<64, false>(p, c, z, o, Pa, Pb, ks, 0, 1 + lng, 0, row0);
      else p2_first<32, false>(p, c, z, o, Pa, Pb, ks, 0, 1 + lng, 0, row0);
      z.ks = wrap5(rot + 1 + 2 * c.wg);
    } else {
      const int vs = wrap5(z.ks + 1), ks = lng ? z.ks : wrap5(z.ks + 2);
      if (blk & 1) p2_first<64, true>(p, c, z, o, Pa, Pb, ks, vs, 1 + lng, acc, row0);
      else p2_first<32, true>(p, c, z, o, Pa, Pb, ks, vs, 1 + lng, acc, row0);
      z.ks = wrap5(ks + 2);
    }
    PROF(c.wg, 24 + it);
    n += 2 * j + 2;
    int left = 2 * j + lng;
    acc = left != 0;
    if (left == 0) { copy_p(Pa, Pb, p.zero); continue; }
    p2_turn<true>(c, z, o, Pb, Pa, it > 0 ? p2_buf(c.wg, it - 1) : -1, !(blk & 1), 1 + lng);
    while (--left > 0) {
      p2_turn<false>(c, z, o, Pa, Pb);
      if (--left == 0) { copy_p(Pa, Pb, p.zero); break; }
      p2_turn<false>(c, z, o, Pb, Pa);
    }
  }
  {
    if (!acc && nit > 1) p2_epilogue(o, z.e0, z.e1, c, p2_buf(c.wg, nit));
    turn_wait(z.wb, z.wi);
    issue_pv<8>(o, Pa, desc_lo(c.sm + SM_RING, 16384) + z.ks * 2048, acc);
    if (((nit - 1) ^ c.wg) & 1) turn_pass(c, z.ab, z.ai);
    p2_scales(z);
    WG_WAIT(0);
    pin(o);
    release(c, B_P2E + z.ks);
    p2_epilogue(o, z.e0, z.e1, c, p2_buf(c.wg, nit - 1));
    PROF(c.wg, 24 + nit);
  }
}

__device__ __forceinline__ void p2_load_q(const Params& p, const Ctx& c, int it, int w) {
  const int item = p.s.r[c.cl].item[it], h = item >> 3, j = item & 7, b = p2_buf(w, it);
  mbar_expect(c.bar + (B_QF + b) * 8, 16384);
  bulk_load(c.sm + SM_BUF + b * 16384, g_Q + (size_t)(h * 32 + j * 4 + p2_blk(c.rank, w, it)) * 16384, 16384, c.bar + (B_QF + b) * 8, POL(4));
}
__device__ __forceinline__ void wait_p1_free(const Ctx& c, int u1, int s) {
  mbar_wait(c.bar + (B_P1E + 2 * s) * 8, ((u1 - 1 - 2 * s) / 10) & 1);
  mbar_wait(c.bar + (B_P1E + 2 * s + 1) * 8, ((u1 - 2 - 2 * s) / 10) & 1);
}
__device__ __forceinline__ void p2_producer(const Params& p, const Ctx& c, int u1, int rot) {
  const int nit = p.s.r[c.cl].n2;
  int slot = rot, cnt = 0, par = 1, n = 0;
  const int ring = p.s.r[c.cl].ring;
  const uint8_t* pv = nullptr;
  bool pl = false;
  auto load = [&](const uint8_t* src, int expect, uint32_t fb, bool last) {
    if (cnt < 5) {
      if (u1) {
        wait_p1_free(c, u1, slot);
        if (cnt == 0) p2_load_q(p, c, 0, 1);
      }
      cnt++;
    } else {
      if (slot == rot) par ^= 1;
      mbar_wait(c.bar + (B_P2E + slot) * 8, par);
    }
    if (expect) mbar_expect(fb, expect);
    bulk_load_mc(c.sm + SM_RING + slot * 32768 + c.rank * 16384, src, 16384, fb, last ? POL(5) : L2_NORMAL);
    slot = wrap5(slot + 1);
  };
  if (c.phases & 16) flag_wait<true>(F_GATE, 256);
  for (int it = 0; it < nit; it++) {
    const int item = p.s.r[c.cl].item[it], h = item >> 3, j = item & 7;
    if (c.phases & 16) flag_wait<false>(F_HEAD + h, 96);
    if (it == 0) { mbar_wait(c.bar + B_LAD * 8, 0); p2_load_q(p, c, 0, 0); if (!u1) p2_load_q(p, c, 0, 1); }
    for (int t = 2 * j + 1; t >= 0; t--) {
      const uint8_t* k = g_KV + (size_t)((h >= ring ? h - ring : h) * 16 + t) * 32768 + c.rank * 16384;
      const uint32_t fb = c.bar + (B_P2F + (n & 3)) * 8;
      const bool last = (p.s.r[c.cl].last[it] >> (t >> 1)) & 1;
      load(k, pv && t != 2 * j ? 65536 : 32768, fb, last);
      if (pv) load(pv, 0, t != 2 * j ? fb : c.bar + (B_ORD + ((n - 1 - it) & 3)) * 8, pl);
      pl = last;
      pv = k + (size_t)NH * 16 * 32768;
      n++;
    }
  }
  load(pv, 32768, c.bar + (B_P2F + (n & 3)) * 8, pl);
}

__device__ __forceinline__ void p2_storer(const Params& p, const Ctx& c, int sfpar) {
  const int nit = p.s.r[c.cl].n2;
  auto load_q = [&](int it, int w) {
    if (c.phases & 16) flag_wait<false>(F_HEAD + (p.s.r[c.cl].item[it] >> 3), 96);
    p2_load_q(p, c, it, w);
  };
  if (nit > 1) {
    load_q(1, 1); p2_load_q(p, c, 1, 0); }
  for (int i = 0; i < 2 * nit; i++) {
    const int it = i >> 1, w = (it ^ i ^ 1) & 1, b = p2_buf(w, it);
    const int item = p.s.r[c.cl].item[it], h = item >> 3, j = item & 7;
    mbar_wait(c.bar + (B_SF + b) * 8, (sfpar >> b) & 1);
    sfpar ^= 1 << b;
    bulk_store(g_Q + (size_t)(h * 32 + j * 4 + p2_blk(c.rank, w, it)) * 16384, c.sm + SM_BUF + b * 16384, 16384, POL(1));
    BULK_COMMIT();
    BULK_WAIT(0);
    flag_add_rx(F_CTX + j * 64 + h);
    if ((i & 1) && it + 2 < nit) { load_q(it + 2, w); p2_load_q(p, c, it + 2, w ^ 1); }
  }
  release(c, B_DONE);
}

__device__ __forceinline__ int p3_pos(int i, int x) { return i < 4 ? (i + x) & 3 : 4; }
__device__ __forceinline__ void p3_consumer(const Params& p, const Ctx& c, int x) {
  const bool first = p.s.r[c.cl].p3 >= 24;
  const int tile = p.s.r[c.cl].p3 - (first ? 24 : 0), j = tile / 3, nt = tile - 3 * j;
  const int na = first ? 9 : 0, nb = first ? 2 * p.s.nh : 64 - 2 * p.s.nh;
  const uint32_t ad = desc_lo(c.sm + SM_RING + c.wg * 8192, 16), bd = desc_lo(c.sm + SM_RING + 16384, 4096);
  float acc[96] = {};
  int slot = 0, par = 0, prev = 0;
#pragma unroll 1
  for (int kb = 0; kb < na; kb++) {
    mbar_wait(c.bar + (B_P3F + slot) * 8, par);
    if (kb == 0) PROF(c.wg, 39);
    WG_FENCE();
#pragma unroll
    for (int kk = 0; kk < 4; kk++) wgmma_ss192<1, 1>(acc, ad + p3_pos(slot, x) * 2560 + kk * 128, bd + p3_pos(slot, x) * 2560 + (kk >> 1) * 768 + (kk & 1) * 128, kk != 0 ? 1 : kb != 0);
    WG_COMMIT();
    WG_WAIT(1);
    if (kb > 0) release(c, B_P3E + prev);
    prev = slot;
    if (++slot == 5) { slot = 0; par ^= 1; }
  }
#pragma unroll 1
  for (int kb = na; kb < na + nb; kb++) {
    mbar_wait(c.bar + (B_P3F + slot) * 8, par);
    if (kb == 0) PROF(c.wg, 39);
    WG_FENCE();
#pragma unroll
    for (int kk = 0; kk < 4; kk++) wgmma_ss192<1>(acc, ad + p3_pos(slot, x) * 2560 + kk * 2, bd + p3_pos(slot, x) * 2560 + (kk >> 1) * 768 + (kk & 1) * 128, kk != 0 ? 1 : kb != 0);
    WG_COMMIT();
    WG_WAIT(1);
    if (kb > 0) release(c, B_P3E + prev);
    prev = slot;
    if (++slot == 5) { slot = 0; par ^= 1; }
  }
  WG_WAIT(0);
  pin(acc);
  PROF(c.wg, 40);
  if (first) bar_sync(4 + c.wg, 128);
  else mbar_wait(c.bar + B_OUT * 8, 0);
  const int row = (c.lane & 7) + ((c.lane >> 3) & 1) * 8;
  const uint32_t wbase = c.sm + SM_RING + c.wg * 8192 + c.warp * 2048;
  const uint32_t base = wbase + row * 128 + (((c.lane >> 4) ^ (row & 7)) << 4);
#pragma unroll
  for (int i = 0; i < 12; i++) {
    stsm4((base ^ ((i & 3) << 5)) + (i >> 2) * 40960, pack_bf16(acc[8 * i], acc[8 * i + 1]), pack_bf16(acc[8 * i + 2], acc[8 * i + 3]),
          pack_bf16(acc[8 * i + 4], acc[8 * i + 5]), pack_bf16(acc[8 * i + 6], acc[8 * i + 7]));
    if ((i & 3) == 3) {
      FENCE_ASYNC_SMEM();
      __syncwarp();
      const int c0 = nt * 192 + (i >> 2) * 64, c1 = j * 256 + c.rank * 128 + c.wg * 64 + c.warp * 16;
      if (first) tma2d_store(&p.map_out, wbase + (i >> 2) * 40960, c0, c1);
      else tma2d_add(&p.map_out, wbase + (i >> 2) * 40960, c0, c1);
    }
  }
  BULK_COMMIT();
  PROF(c.wg, 43);
  BULK_WAIT(0);
  if (first) flag_add_rx(F_OUT + tile * 2 + c.rank);
  PROF(c.wg, 44);
}

__device__ __forceinline__ void p3_producer(const Params& p, const Ctx& c, int u1, int u2, int rot, int x) {
  const bool first = p.s.r[c.cl].p3 >= 24;
  const int tile = p.s.r[c.cl].p3 - (first ? 24 : 0), j = tile / 3, nt = tile - 3 * j;
  int slot = 0, par = 1, cnt = 0;
  auto wait_free = [&](int s) {
    const int f = wrap5(s + 5 - rot);
    if (f < u2) mbar_wait(c.bar + (B_P2E + s) * 8, ((u2 - 1 - f) / 5) & 1);
    else if (u1) wait_p1_free(c, u1, s);
  };
  asm volatile(ELECT("prefetch.tensormap [%0];") ::"l"(&p.map_o[first]) : "memory");
  asm volatile(ELECT("prefetch.tensormap [%0];") ::"l"(&p.map_out) : "memory");
  const int q1 = first ? p.s.nh : 32;
  for (int q = first ? -1 : p.s.nh; q < q1; q++) {
    const int g = q < 0 ? 32 : p.s.p3_order[j][q];
    if (c.phases & 16) flag_wait<false>(F_CTX + j * 64 + g, q < 0 ? 16 : 4);
    const int nk = q < 0 ? 9 : 2, k0 = (q < 0 ? 0 : g * 128) + c.rank * 32;
    const uint8_t* a = q < 0 ? g_oA + (j * 4 + c.rank * 2) * 73728 : g_Q + (size_t)(g * 32 + j * 4 + c.rank * 2) * 16384;
    const CUtensorMap* m = &p.map_o[q < 0];
    for (int i = 0; i < nk; i++) {
      const uint32_t st = c.sm + SM_RING + p3_pos(slot, x) * 40960, fb = c.bar + (B_P3F + slot) * 8;
      if (cnt < 4) { wait_free(p3_pos(cnt, x)); wait_free(p3_pos(cnt, x) + 1); }
      else if (cnt == 4) mbar_wait(c.bar + B_DONE * 8, 0);
      else mbar_wait(c.bar + (B_P3E + slot) * 8, par);
      cnt++;
      mbar_expect(fb, 40960);
      bulk_load(st, a + i * 8192, 8192, fb, POL(3));
      bulk_load(st + 8192, a + (nk + i) * 8192, 8192, fb, POL(3));
      tma3d_mc(st + 16384 + c.rank * 12288, m, 0, k0 + i * 64, nt * 3, fb);
      if (++slot == 5) { slot = 0; par ^= 1; }
    }
  }
}

__device__ __forceinline__ float bf_lo(uint32_t w) { return __uint_as_float(w << 16); }
__device__ __forceinline__ float bf_hi(uint32_t w) { return __uint_as_float(w & 0xffff0000u); }

__device__ __forceinline__ void gate_rows(const Params& p, int row0, int lane) {
  const uint4* x = reinterpret_cast<const uint4*>(p.x + (size_t)(row0 + (lane >> 2)) * DM) + (lane & 3);
  const uint4* w = reinterpret_cast<const uint4*>(p.gate_w) + (lane & 3);
  float a = 0.f;
#pragma unroll 1
  for (int b = 0; b < 3; b++) {
    uint4 u[6];
#pragma unroll
    for (int i = 0; i < 6; i++) u[i] = __ldg(x + (b * 6 + i) * 4);
#pragma unroll
    for (int i = 0; i < 6; i++) {
      const uint4 v = __ldg(w + (b * 6 + i) * 4);
      a = fmaf(bf_lo(u[i].x), bf_lo(v.x), a); a = fmaf(bf_hi(u[i].x), bf_hi(v.x), a);
      a = fmaf(bf_lo(u[i].y), bf_lo(v.y), a); a = fmaf(bf_hi(u[i].y), bf_hi(v.y), a);
      a = fmaf(bf_lo(u[i].z), bf_lo(v.z), a); a = fmaf(bf_hi(u[i].z), bf_hi(v.z), a);
      a = fmaf(bf_lo(u[i].w), bf_lo(v.w), a); a = fmaf(bf_hi(u[i].w), bf_hi(v.w), a);
    }
  }
  a += __shfl_xor_sync(0xffffffffu, a, 1);
  a += __shfl_xor_sync(0xffffffffu, a, 2);
  if ((lane & 3) == 0) g_gate[row0 + (lane >> 2)] = 1.f / (1.f + __expf(-a));
}

__device__ __forceinline__ void lds10(uint32_t (&k)[10], uint32_t a) {
  asm volatile("ld.shared.v2.u32 {%0, %1}, [%10];\nld.shared.v2.u32 {%2, %3}, [%10+8];\nld.shared.v2.u32 {%4, %5}, [%10+16];\n"
               "ld.shared.v2.u32 {%6, %7}, [%10+24];\nld.shared.v2.u32 {%8, %9}, [%10+32];"
               : "=r"(k[0]), "=r"(k[1]), "=r"(k[2]), "=r"(k[3]), "=r"(k[4]), "=r"(k[5]), "=r"(k[6]), "=r"(k[7]), "=r"(k[8]), "=r"(k[9]) : "r"(a));
}
__device__ __forceinline__ void local_attn(const Params& p, const Ctx& c, int rb, int hs) {
  const int lane = c.lane, grp = rb >> 2, par = lane >> 4, i0 = 2 * (lane & 15);
  const uint32_t buf = c.sm + SM_BUF + (c.warp - 2) * 8192, bqk = c.bar + (B_LA + (c.warp - 2) * 2) * 8, bv = bqk + 8;
  const uint32_t mine = buf + 2304 + par * 160 + i0 * 4;
  const bool flags = c.phases & 16;
  auto fetch_qk = [&](int i) {
    if (flags && !(i & 1)) {
      const int q = i >> 1;
      const int tgt = q == 0 ? 24 : q == 3 ? 8 : 12;
      flag_wait<false>(F_QKVA + (grp - (grp > 0 && (rb & 3) == 0 ? par : 0)) * 4 + q, tgt);
    }
    mbar_expect(bqk, 5184);
    tma3d(buf, &p.map_t[0], rb * 32 + 8, 0, 9 * (4 * i + hs), bqk, POL(2));
    tma3d(buf + 2304, &p.map_t[1], rb * 32, 0, 288 + 9 * (4 * i + hs), bqk, POL(2));
  };
  auto fetch_v = [&](int i) { mbar_expect(bv, 2880); tma3d(buf + 5248, &p.map_t[1], rb * 32, 0, 576 + 9 * (4 * i + hs), bv, POL(2)); };
  fetch_qk(0);
  if (flags) flag_wait<true>(F_GATE, 256);
#pragma unroll 1
  for (int q = 0; q < 8; q++) {
    fetch_v(q);
    float a[8], b[8];
#pragma unroll
    for (int w = 0; w < 8; w++) a[w] = b[w] = 0.f;
    mbar_wait(bqk, q & 1);
    PROFB(1 + 2 * q);
#pragma unroll 1
    for (int j = 0; j < 9; j++) {
      uint32_t x, y, k[10];
      asm volatile("ld.shared.v2.u32 {%0, %1}, [%2];" : "=r"(x), "=r"(y) : "r"(buf + lane * 8 + j * 256));
      lds10(k, mine + j * 320);
      const float xl = bf_lo(x), xh = bf_hi(x), yl = bf_lo(y), yh = bf_hi(y);
#pragma unroll
      for (int m = 1; m < 10; m++) {
        const float kl = bf_lo(k[m]), kh = bf_hi(k[m]);
        if (m < 9) a[8 - m] = fmaf(xl, kl, fmaf(xh, kh, a[8 - m]));
        if (m > 1) b[9 - m] = fmaf(yl, kl, fmaf(yh, kh, b[9 - m]));
      }
    }
    __syncwarp();
    if (q < 7) fetch_qk(q + 1);
    constexpr float SC = 0.23570226039551584f * 1.4426950408889634f;
    const float* gp = g_gate + rb * 64 + 2 * i0 + par;
    const float ga = __ldcg(gp), gb = __ldcg(gp + 2);
    float ma = a[0], mb = b[0];
#pragma unroll
    for (int w = 1; w < 8; w++) {
      if (rb == 0) {
        if (i0 < w) a[w] = -INFINITY;
        if (i0 + 1 < w) b[w] = -INFINITY;
      }
      ma = fmaxf(ma, a[w]); mb = fmaxf(mb, b[w]);
    }
    float la = 0.f, lb = 0.f;
#pragma unroll
    for (int w = 0; w < 8; w++) {
      a[w] = ex2((a[w] - ma) * SC); b[w] = ex2((b[w] - mb) * SC);
      la += a[w]; lb += b[w];
    }
    la = __fdividef(ga, la); lb = __fdividef(gb, lb);
#pragma unroll
    for (int w = 0; w < 8; w++) { a[w] *= la; b[w] *= lb; }
    uint8_t* dst = g_oA + rb * 73728 + ((i0 & 2) + par) * 4;
    mbar_wait(bv, q & 1);
#pragma unroll 1
    for (int j = 0; j < 9; j++) {
      uint32_t v[10];
      lds10(v, mine + 2944 + j * 320);
      float a0 = 0.f, a1 = 0.f, b0 = 0.f, b1 = 0.f;
#pragma unroll
      for (int m = 1; m < 10; m++) {
        const float vl = bf_lo(v[m]), vh = bf_hi(v[m]);
        if (m < 9) { a0 = fmaf(a[8 - m], vl, a0); a1 = fmaf(a[8 - m], vh, a1); }
        if (m > 1) { b0 = fmaf(b[9 - m], vl, b0); b1 = fmaf(b[9 - m], vh, b1); }
      }
      const uint32_t wa = pack_bf16(a0, a1), wb = pack_bf16(b0, b1);
      const uint32_t got = __shfl_xor_sync(0xffffffffu, par ? wa : wb, 16);
      const uint32_t r0 = par ? got : wa, r1 = par ? wb : got;
      const int col = 18 * (4 * q + hs) + 2 * j, o = col * 128 + ((((i0 >> 2) ^ col) & 7) << 4);
      *reinterpret_cast<uint32_t*>(dst + o) = __byte_perm(r0, r1, 0x5410);
      *reinterpret_cast<uint32_t*>(dst + ((o + 128) ^ 16)) = __byte_perm(r0, r1, 0x7632);
    }
    __syncwarp();
    PROFB(2 + 2 * q);
  }
  mbar_arrive_one(c.bar + B_LAD * 8);
  flag_add(F_CTX + grp * 64 + 32);
}

__global__ void __cluster_dims__(2, 1, 1) __launch_bounds__(384, 1) fused_kernel(const __grid_constant__ Params p) {
  extern __shared__ uint8_t smem_raw[];
  Ctx c;
  c.sm = ((uint32_t)__cvta_generic_to_shared(smem_raw) + 1023u) & ~1023u;
  c.bar = c.sm + SM_BAR;
  c.lane = threadIdx.x & 31;
  const int wid = __shfl_sync(0xffffffffu, threadIdx.x >> 5, 0);
  if (wid < NPF) asm volatile("prefetch.tensormap [%0];" ::"l"(&p.map_a[0] + wid) : "memory");
  c.wg = wid >> 2;
  c.warp = wid & 3;
  PROF(c.wg, 0);
  PROFG(61);
  c.cl = (blockIdx.x + (wid >> 4)) >> 1;
  c.rank = blockIdx.x & 1;
  c.rbar = mapa(c.bar, c.lane & 1);
  {
    const int w = wid, cnt = (((int)(B_CNT >> (4 * w)) - 1) & 15) + 1;
    if (w < 11) {
#pragma unroll
      for (int i = 0; i < 8; i++) asm volatile("mbarrier.init.shared::cta.b64 [%0], %1;" ::"r"(c.bar + w * 64 + i * 8), "r"(cnt));
    }
    asm volatile("fence.mbarrier_init.release.cluster;" ::: "memory");
  }
  if (c.wg == 2) PROF(2, 56);
  asm volatile("barrier.cluster.arrive.relaxed;" ::: "memory");
  c.phases = p.s.r[c.cl].phases;
  const bool do1 = p.s.r[c.cl].n1 > 0, do2 = p.s.r[c.cl].n2 > 0, do3 = p.s.r[c.cl].p3 != 255;
  if (do1 && c.wg == 2 && c.warp == 0) {
    const int type = p.s.r[c.cl].slab >> 3;
    PROF(2, 57);
    FENCE_ASYNC_SMEM();
    mbar_expect(c.bar + B_P1F * 8, type ? 32768 : 16384);
    tma2d(type ? c.sm + SM_BUF + 32768 : c.sm + SM_RING, &p.map_a[type], type ? 512 : 0, (p.s.r[c.cl].slab & 7) * 256 + c.rank * 128, c.bar + B_P1F * 8);
    PROF(2, 58);
  }
  asm volatile("barrier.cluster.wait.acquire;" ::: "memory");
  if (c.wg == 2) PROF(2, 59);
  if (do1 && c.wg == 2 && c.warp == 0) {
    const int type = p.s.r[c.cl].slab >> 3, tile = p.s.r[c.cl].tile[0];
    if (!type) mbar_expect(c.bar + (B_P1F + 1) * 8, 16384);
    tma2d_mc(c.sm + SM_RING + (1 - type) * 16384 + c.rank * 8192, &p.map_w[type * 2 + (tile >> 5)], (tile & 31) * 128 + c.rank * 64, type ? 512 : 0, c.bar + (B_P1F + 1 - type) * 8);
  }

  if (c.wg < 2) {
    PROF(c.wg, 4);
    asm volatile("setmaxnreg.inc.sync.aligned.u32 224;");
    if (c.wg == 1) {
      if (do1) bar_arrive(ORDER, 256);
      if (c.lane == 0) mbar_arrive(c.bar + B_P2F * 8);
    }
    if (do1) p1_consumer(p, c);
    if (do2) p2_consumer(p, c, p.s.r[c.cl].rot);
    if (do3) p3_consumer(p, c, p.s.r[c.cl].x3);
    PROF(c.wg, 63);
    PROFG(62);
    if (c.lane == 0) mbar_arrive(c.bar + B_FIN * 8);
    __syncwarp();
    cluster_sync();
  } else {
    asm volatile("setmaxnreg.dec.sync.aligned.u32 56;");
    if (c.warp == 0) {
      PROF(2, 60);
      if (do1) p1_producer(p, c);
      if (do2) p2_producer(p, c, p.s.r[c.cl].u1, p.s.r[c.cl].rot);
      if (do3) p3_producer(p, c, p.s.r[c.cl].u1, p.s.r[c.cl].u2, p.s.r[c.cl].rot, p.s.r[c.cl].x3);
    } else if (c.warp == 1) {
      int sfpar = 0;
      if (do1) {
        p1_storer(p, c);
        sfpar = (p.s.r[c.cl].n1 & 1) * 10;
      }
      if (do2) p2_storer(p, c, sfpar);
      else { mbar_wait(c.bar + B_LAD * 8, 0); release(c, B_DONE); }
      if (do3 && p.s.r[c.cl].p3 < 24) {
        if (c.phases & 16) flag_wait<false, 256>(F_OUT + p.s.r[c.cl].p3 * 2 + c.rank, 8);
        mbar_arrive_one(c.bar + B_OUT * 8);
      }
    } else {
      const int bw = blockIdx.x * 2 + (c.warp - 2);
      if ((c.phases & 1) && bw < 256) {
        gate_rows(p, bw * 8, c.lane);
        __syncwarp();
        flag_add(F_GATE);
      }
      if (p.s.r[c.cl].bg != 255) local_attn(p, c, p.s.r[c.cl].bg, bw & 3);
      else if (c.lane == 0) mbar_arrive(c.bar + B_LAD * 8);
    }
    __syncwarp();
    bar_sync(3, 128);
    if (c.warp == 0 && (c.phases & 4)) {
      int last = 0;
      if (c.lane == 0) { __threadfence(); last = atomicAdd(g_flags + F_DONE, 1) == 2 * NCL - 1; }
      if (__shfl_sync(0xffffffffu, last, 0)) for (int i = c.lane; i < F_NUM; i += 32) g_flags[i] = 0;
    }
    if (c.warp == 1) mbar_wait(c.bar + B_FIN * 8, 0);
    __syncwarp();
    cluster_sync();
  }
}

static const Sched k_sched = {
  {{0,26,0,0,0,{0,0,0,0,0,0,0,0,0,0,0},{0,0,0,0,0,0,0,0,0,0,0},{0,2,4,6,8,10,12,45,15,16,17,18,19,20,21,22,23,24,25,26,27,28,29,30,31,63,0,0,0,0}},
   {0,24,4,255,1,{144,187,218,251,0,0,0,0,0,0,0},{0,0,0,15,0,0,0,0,0,0,0},{32,34,36,38,40,42,44,14,47,48,49,50,51,52,53,54,55,56,57,58,59,60,61,62,0,0,0,0,0,0}},
   {0,8,4,24,255,{3,38,118,191,0,0,0,0,0,0,0},{0,127,0,255,0,0,0,0,0,0,0},{1,3,5,7,9,11,13,46,0,0,0,0,0,0,0,0,0,0,0,0,0,0,0,0,0,0,0,0,0,0}},
   {0,6,5,255,255,{14,55,130,207,236,0,0,0,0,0,0},{0,255,0,128,0,0,0,0,0,0,0},{33,35,37,39,41,43,0,0,0,0,0,0,0,0,0,0,0,0,0,0,0,0,0,0,0,0,0,0,0,0}},
   {8,19,3,255,2,{146,175,250,0,0,0,0,0,0,0,0},{0,255,0,0,0,0,0,0,0,0,0},{0,32,41,37,34,38,43,35,39,44,40,45,18,20,22,24,26,28,30,0,0,0,0,0,0,0,0,0,0,0}},
   {8,19,3,25,3,{112,188,204,0,0,0,0,0,0,0,0},{0,0,0,0,0,0,0,0,0,0,0},{1,4,6,8,10,11,12,13,14,15,16,17,19,21,23,25,27,29,31,0,0,0,0,0,0,0,0,0,0,0}},
   {8,4,3,1,255,{45,63,127,0,0,0,0,0,0,0,0},{0,128,255,0,0,0,0,0,0,0,0},{2,36,33,42,0,0,0,0,0,0,0,0,0,0,0,0,0,0,0,0,0,0,0,0,0,0,0,0,0,0}},
   {8,4,7,26,255,{32,12,49,90,91,117,223,0,0,0,0},{0,0,0,0,0,0,192,0,0,0,0},{3,5,7,9,0,0,0,0,0,0,0,0,0,0,0,0,0,0,0,0,0,0,0,0,0,0,0,0,0,0}},
   {1,26,0,2,4,{0,0,0,0,0,0,0,0,0,0,0},{0,0,0,0,0,0,0,0,0,0,0},{0,2,4,6,8,10,12,45,15,16,17,18,19,20,21,22,23,24,25,26,27,28,29,30,31,63,0,0,0,0}},
   {1,24,1,3,5,{161,0,0,0,0,0,0,0,0,0,0},{0,0,0,0,0,0,0,0,0,0,0},{32,34,36,38,40,42,44,14,47,48,49,50,51,52,53,54,55,56,57,58,59,60,61,62,0,0,0,0,0,0}},
   {1,6,8,4,255,{16,25,74,59,106,113,149,192,0,0,0},{0,0,0,0,0,0,0,0,0,0,0},{1,3,5,7,9,11,0,0,0,0,0,0,0,0,0,0,0,0,0,0,0,0,0,0,0,0,0,0,0,0}},
   {1,8,6,27,255,{72,81,37,143,171,228,0,0,0,0,0},{0,0,0,128,0,0,0,0,0,0,0},{33,35,37,39,41,43,13,46,0,0,0,0,0,0,0,0,0,0,0,0,0,0,0,0,0,0,0,0,0,0}},
   {9,20,2,255,6,{215,252,0,0,0,0,0,0,0,0,0},{128,16,0,0,0,0,0,0,0,0,0},{0,32,41,37,34,38,43,35,39,44,40,45,18,20,22,24,26,28,30,31,0,0,0,0,0,0,0,0,0,0}},
   {9,18,3,28,7,{88,158,227,0,0,0,0,0,0,0,0},{1,127,0,0,0,0,0,0,0,0,0},{1,4,6,8,10,11,12,13,14,15,16,17,19,21,23,25,27,29,0,0,0,0,0,0,0,0,0,0,0,0}},
   {9,4,4,5,255,{44,7,135,208,0,0,0,0,0,0,0},{0,255,128,0,0,0,0,0,0,0,0},{2,36,33,42,0,0,0,0,0,0,0,0,0,0,0,0,0,0,0,0,0,0,0,0,0,0,0,0,0,0}},
   {9,4,7,255,255,{13,97,54,186,155,179,253,0,0,0,0},{0,0,0,0,0,0,0,0,0,0,0},{3,5,7,9,0,0,0,0,0,0,0,0,0,0,0,0,0,0,0,0,0,0,0,0,0,0,0,0,0,0}},
   {2,26,0,6,8,{0,0,0,0,0,0,0,0,0,0,0},{0,0,0,0,0,0,0,0,0,0,0},{0,34,5,7,9,11,13,14,15,16,17,18,19,20,21,22,23,24,25,26,27,28,29,30,31,63,0,0,0,0}},
   {2,24,1,7,9,{169,0,0,0,0,0,0,0,0,0,0},{0,0,0,0,0,0,0,0,0,0,0},{32,3,37,39,41,43,45,46,47,48,49,50,51,52,53,54,55,56,57,58,59,60,61,62,0,0,0,0,0,0}},
   {2,6,6,29,255,{48,15,107,114,132,230,0,0,0,0,0},{0,255,0,0,0,0,0,0,0,0,0},{1,35,6,8,10,12,0,0,0,0,0,0,0,0,0,0,0,0,0,0,0,0,0,0,0,0,0,0,0,0}},
   {2,2,6,30,255,{1,9,23,100,196,182,0,0,0,0,0},{0,0,255,0,0,0,0,0,0,0,0},{33,4,0,0,0,0,0,0,0,0,0,0,0,0,0,0,0,0,0,0,0,0,0,0,0,0,0,0,0,0}},
   {2,6,5,255,255,{29,76,110,165,254,0,0,0,0,0,0},{0,0,0,0,96,0,0,0,0,0,0},{2,36,38,40,42,44,0,0,0,0,0,0,0,0,0,0,0,0,0,0,0,0,0,0,0,0,0,0,0,0}},
   {10,20,4,255,10,{145,183,241,248,0,0,0,0,0,0,0},{0,255,0,0,0,0,0,0,0,0,0},{0,32,41,37,34,38,43,35,39,44,40,45,18,20,22,24,26,28,30,31,0,0,0,0,0,0,0,0,0,0}},
   {10,18,3,31,11,{104,147,222,0,0,0,0,0,0,0,0},{0,0,0,0,0,0,0,0,0,0,0},{1,4,6,8,10,11,12,13,14,15,16,17,19,21,23,25,27,29,0,0,0,0,0,0,0,0,0,0,0,0}},
   {10,4,6,255,255,{36,82,69,131,150,238,0,0,0,0,0},{0,0,0,0,127,64,0,0,0,0,0},{2,36,33,42,0,0,0,0,0,0,0,0,0,0,0,0,0,0,0,0,0,0,0,0,0,0,0,0,0,0}},
   {10,4,7,32,255,{8,33,5,85,123,170,214,0,0,0,0},{0,0,0,0,0,0,64,0,0,0,0},{3,5,7,9,0,0,0,0,0,0,0,0,0,0,0,0,0,0,0,0,0,0,0,0,0,0,0,0,0,0}},
   {3,24,2,8,12,{152,200,0,0,0,0,0,0,0,0,0},{0,0,0,0,0,0,0,0,0,0,0},{0,2,4,6,8,10,12,45,15,16,17,18,19,20,21,22,23,24,25,26,27,28,29,30,0,0,0,0,0,0}},
   {3,26,0,9,13,{0,0,0,0,0,0,0,0,0,0,0},{0,0,0,0,0,0,0,0,0,0,0},{32,34,36,38,40,42,44,14,47,48,49,50,51,52,53,54,55,56,57,58,59,60,61,62,31,63,0,0,0,0}},
   {3,6,7,255,255,{17,60,58,94,157,202,244,0,0,0,0},{0,0,0,126,0,0,0,0,0,0,0},{1,3,5,7,9,11,0,0,0,0,0,0,0,0,0,0,0,0,0,0,0,0,0,0,0,0,0,0,0,0}},
   {3,8,6,33,255,{56,57,53,101,194,231,0,0,0,0,0},{0,0,0,0,0,192,0,0,0,0,0},{33,35,37,39,41,43,13,46,0,0,0,0,0,0,0,0,0,0,0,0,0,0,0,0,0,0,0,0,0,0}},
   {11,20,2,255,14,{164,247,0,0,0,0,0,0,0,0,0},{0,255,0,0,0,0,0,0,0,0,0},{0,32,41,37,34,38,43,35,39,44,40,45,18,20,22,24,26,28,30,31,0,0,0,0,0,0,0,0,0,0}},
   {11,18,3,34,15,{96,181,212,0,0,0,0,0,0,0,0},{0,0,0,0,0,0,0,0,0,0,0},{1,4,6,8,10,11,12,13,14,15,16,17,19,21,23,25,27,29,0,0,0,0,0,0,0,0,0,0,0,0}},
   {11,4,8,255,255,{19,66,75,92,125,177,203,243,0,0,0},{0,0,0,0,0,0,0,0,0,0,0},{2,36,33,42,0,0,0,0,0,0,0,0,0,0,0,0,0,0,0,0,0,0,0,0,0,0,0,0,0,0}},
   {11,4,6,35,255,{35,67,78,121,151,235,0,0,0,0,0},{0,0,0,0,255,0,0,0,0,0,0},{3,5,7,9,0,0,0,0,0,0,0,0,0,0,0,0,0,0,0,0,0,0,0,0,0,0,0,0,0,0}},
   {4,26,0,10,16,{0,0,0,0,0,0,0,0,0,0,0},{0,0,0,0,0,0,0,0,0,0,0},{0,2,4,6,8,10,12,45,15,16,17,18,19,20,21,22,23,24,25,26,27,28,29,30,31,63,0,0,0,0}},
   {4,24,3,255,17,{173,219,249,0,0,0,0,0,0,0,0},{0,15,0,0,0,0,0,0,0,0,0},{32,34,36,38,40,42,44,14,47,48,49,50,51,52,53,54,55,56,57,58,59,60,61,62,0,0,0,0,0,0}},
   {4,6,7,255,255,{26,21,93,153,199,226,234,0,0,0,0},{0,0,0,0,128,0,0,0,0,0,0},{1,3,5,7,9,11,0,0,0,0,0,0,0,0,0,0,0,0,0,0,0,0,0,0,0,0,0,0,0,0}},
   {4,8,6,36,255,{64,31,102,190,233,232,0,0,0,0,0},{0,255,127,0,0,0,0,0,0,0,0},{33,35,37,39,41,43,13,46,0,0,0,0,0,0,0,0,0,0,0,0,0,0,0,0,0,0,0,0,0,0}},
   {12,21,2,11,18,{136,184,0,0,0,0,0,0,0,0,0},{0,0,0,0,0,0,0,0,0,0,0},{0,32,41,37,34,38,43,35,39,44,40,45,18,20,22,24,26,28,29,30,31,0,0,0,0,0,0,0,0,0}},
   {12,17,2,12,19,{80,180,0,0,0,0,0,0,0,0,0},{1,0,0,0,0,0,0,0,0,0,0},{1,4,6,8,10,11,12,13,14,15,16,17,19,21,23,25,27,0,0,0,0,0,0,0,0,0,0,0,0,0}},
   {12,4,3,13,255,{39,86,134,0,0,0,0,0,0,0,0},{128,0,64,0,0,0,0,0,0,0,0},{2,36,33,42,0,0,0,0,0,0,0,0,0,0,0,0,0,0,0,0,0,0,0,0,0,0,0,0,0,0}},
   {12,4,4,14,255,{6,61,111,176,0,0,0,0,0,0,0},{0,0,255,0,0,0,0,0,0,0,0},{3,5,7,9,0,0,0,0,0,0,0,0,0,0,0,0,0,0,0,0,0,0,0,0,0,0,0,0,0,0}},
   {5,26,0,15,20,{0,0,0,0,0,0,0,0,0,0,0},{0,0,0,0,0,0,0,0,0,0,0},{0,34,5,39,10,12,13,14,15,16,17,18,19,20,21,22,23,24,25,26,27,28,29,30,31,63,0,0,0,0}},
   {5,24,3,255,21,{178,245,242,0,0,0,0,0,0,0,0},{0,0,0,0,0,0,0,0,0,0,0},{32,3,37,8,42,44,45,46,47,48,49,50,51,52,53,54,55,56,57,58,59,60,61,62,0,0,0,0,0,0}},
   {5,5,3,16,255,{47,70,174,0,0,0,0,0,0,0,0},{128,127,0,0,0,0,0,0,0,0,0},{1,35,6,40,11,0,0,0,0,0,0,0,0,0,0,0,0,0,0,0,0,0,0,0,0,0,0,0,0,0}},
   {5,4,8,255,255,{0,11,50,65,98,116,189,255,0,0,0},{0,0,0,0,0,0,0,128,0,0,0},{33,4,38,9,0,0,0,0,0,0,0,0,0,0,0,0,0,0,0,0,0,0,0,0,0,0,0,0,0,0}},
   {5,5,6,37,255,{43,27,77,115,142,211,0,0,0,0,0},{0,0,0,0,127,0,0,0,0,0,0},{2,36,7,41,43,0,0,0,0,0,0,0,0,0,0,0,0,0,0,0,0,0,0,0,0,0,0,0,0,0}},
   {13,20,2,17,22,{128,193,0,0,0,0,0,0,0,0,0},{0,0,0,0,0,0,0,0,0,0,0},{0,32,41,37,34,38,43,35,39,44,40,45,18,20,22,24,26,28,30,31,0,0,0,0,0,0,0,0,0,0}},
   {13,18,4,255,23,{137,201,172,213,0,0,0,0,0,0,0},{0,0,0,63,0,0,0,0,0,0,0},{1,4,6,8,10,11,12,13,14,15,16,17,19,21,23,25,27,29,0,0,0,0,0,0,0,0,0,0,0,0}},
   {13,4,4,18,255,{22,79,141,160,0,0,0,0,0,0,0},{0,255,0,0,0,0,0,0,0,0,0},{2,36,33,42,0,0,0,0,0,0,0,0,0,0,0,0,0,0,0,0,0,0,0,0,0,0,0,0,0,0}},
   {13,4,7,38,255,{24,42,89,71,124,148,220,0,0,0,0},{0,0,0,128,0,0,0,0,0,0,0},{3,5,7,9,0,0,0,0,0,0,0,0,0,0,0,0,0,0,0,0,0,0,0,0,0,0,0,0,0,0}},
   {6,26,0,19,24,{0,0,0,0,0,0,0,0,0,0,0},{0,0,0,0,0,0,0,0,0,0,0},{0,2,4,6,8,10,12,14,15,16,17,18,19,20,21,22,23,24,25,26,27,28,29,30,31,63,0,0,0,0}},
   {6,24,1,20,25,{185,0,0,0,0,0,0,0,0,0,0},{0,0,0,0,0,0,0,0,0,0,0},{32,34,36,38,40,42,44,46,47,48,49,50,51,52,53,54,55,56,57,58,59,60,61,62,0,0,0,0,0,0}},
   {6,7,4,39,255,{46,68,126,167,0,0,0,0,0,0,0},{127,0,0,255,0,0,0,0,0,0,0},{1,3,5,7,9,11,13,0,0,0,0,0,0,0,0,0,0,0,0,0,0,0,0,0,0,0,0,0,0,0}},
   {6,7,6,21,255,{18,73,99,129,109,139,0,0,0,0,0},{0,0,0,0,0,0,0,0,0,0,0},{33,35,37,39,41,43,45,0,0,0,0,0,0,0,0,0,0,0,0,0,0,0,0,0,0,0,0,0,0,0}},
   {14,18,2,40,26,{133,197,0,0,0,0,0,0,0,0,0},{63,63,0,0,0,0,0,0,0,0,0},{0,32,41,37,34,38,43,35,39,44,40,45,18,20,22,24,26,28,0,0,0,0,0,0,0,0,0,0,0,0}},
   {14,20,4,41,27,{120,162,195,225,0,0,0,0,0,0,0},{0,0,0,0,0,0,0,0,0,0,0},{1,4,6,8,10,11,12,13,14,15,16,17,19,21,23,25,27,29,30,31,0,0,0,0,0,0,0,0,0,0}},
   {14,4,7,42,255,{2,84,52,108,154,206,224,0,0,0,0},{0,0,0,0,0,64,0,0,0,0,0},{2,36,33,42,0,0,0,0,0,0,0,0,0,0,0,0,0,0,0,0,0,0,0,0,0,0,0,0,0,0}},
   {14,4,5,43,255,{30,105,95,140,246,0,0,0,0,0,0},{0,0,128,0,0,0,0,0,0,0,0},{3,5,7,9,0,0,0,0,0,0,0,0,0,0,0,0,0,0,0,0,0,0,0,0,0,0,0,0,0,0}},
   {7,25,3,255,28,{217,210,237,0,0,0,0,0,0,0,0},{0,0,63,0,0,0,0,0,0,0,0},{0,2,4,6,8,10,12,45,15,16,17,18,19,20,21,22,23,24,25,26,27,28,29,30,31,0,0,0,0,0}},
   {7,25,3,255,29,{216,239,240,0,0,0,0,0,0,0,0},{0,128,0,0,0,0,0,0,0,0,0},{32,34,36,38,40,42,44,14,47,48,49,50,51,52,53,54,55,56,57,58,59,60,61,62,63,0,0,0,0,0}},
   {7,8,4,44,255,{28,62,159,229,0,0,0,0,0,0,0},{0,127,128,63,0,0,0,0,0,0,0},{1,3,5,7,9,11,13,46,0,0,0,0,0,0,0,0,0,0,0,0,0,0,0,0,0,0,0,0,0,0}},
   {7,6,6,22,255,{41,34,51,103,138,209,0,0,0,0,0},{0,0,0,128,0,0,0,0,0,0,0},{33,35,37,39,41,43,0,0,0,0,0,0,0,0,0,0,0,0,0,0,0,0,0,0,0,0,0,0,0,0}},
   {15,20,2,45,30,{163,221,0,0,0,0,0,0,0,0,0},{0,48,0,0,0,0,0,0,0,0,0},{0,32,41,37,34,38,43,35,39,44,40,45,18,20,22,24,26,28,30,31,0,0,0,0,0,0,0,0,0,0}},
   {15,18,2,46,31,{156,198,0,0,0,0,0,0,0,0,0},{0,64,0,0,0,0,0,0,0,0,0},{1,4,6,8,10,11,12,13,14,15,16,17,19,21,23,25,27,29,0,0,0,0,0,0,0,0,0,0,0,0}},
   {15,4,5,47,255,{10,4,87,166,205,0,0,0,0,0,0},{0,0,254,0,63,0,0,0,0,0,0},{2,36,33,42,0,0,0,0,0,0,0,0,0,0,0,0,0,0,0,0,0,0,0,0,0,0,0,0,0,0}},
   {15,4,6,23,255,{40,20,83,122,119,168,0,0,0,0,0},{0,0,0,0,255,0,0,0,0,0,0},{3,5,7,9,0,0,0,0,0,0,0,0,0,0,0,0,0,0,0,0,0,0,0,0,0,0,0,0,0,0}}},
  32, 4,
  {{0,1,3,4,5,2,6,7,8,9,10,11,12,13,14,15,16,21,20,22,26,17,18,19,24,23,25,27,28,29,30,31},
   {0,2,5,4,1,3,7,10,11,9,12,6,13,8,16,14,15,19,17,25,18,24,20,21,23,26,27,22,29,28,30,31},
   {0,1,3,5,2,4,9,8,10,6,7,11,12,15,13,14,23,16,17,19,24,18,21,20,22,26,25,27,28,29,31,30},
   {2,4,5,1,0,3,8,6,10,12,7,9,13,11,14,16,15,17,19,18,20,21,23,22,24,25,26,29,28,27,30,31},
   {4,5,1,2,7,3,0,10,9,6,8,11,12,14,13,15,22,19,24,16,17,18,23,20,21,28,26,27,25,30,29,31},
   {1,5,3,0,2,4,6,7,8,9,10,11,12,13,14,17,18,15,16,19,23,22,20,21,24,28,25,27,30,26,31,29},
   {0,2,3,1,5,4,7,6,9,8,10,11,13,12,15,14,16,21,20,17,18,19,23,25,24,22,28,27,26,30,31,29},
   {4,5,1,2,3,0,8,7,9,6,10,11,12,17,14,13,16,15,19,18,24,25,26,28,27,20,23,21,22,29,31,30}}};

typedef CUresult (*EncodeFn)(CUtensorMap*, CUtensorMapDataType, cuuint32_t, void*, const cuuint64_t*, const cuuint64_t*, const cuuint32_t*,
                             const cuuint32_t*, CUtensorMapInterleave, CUtensorMapSwizzle, CUtensorMapL2promotion, CUtensorMapFloatOOBfill);

void make_map2(EncodeFn enc, CUtensorMap* m, const void* ptr, int rows, int cols, int box_rows) {
  cuuint64_t dim[2] = {(cuuint64_t)cols, (cuuint64_t)rows}, str[1] = {(cuuint64_t)cols * 2};
  cuuint32_t box[2] = {64, (cuuint32_t)box_rows}, es[2] = {1, 1};
  enc(m, CU_TENSOR_MAP_DATA_TYPE_BFLOAT16, 2, const_cast<void*>(ptr), dim, str, box, es, CU_TENSOR_MAP_INTERLEAVE_NONE, CU_TENSOR_MAP_SWIZZLE_128B,
      CU_TENSOR_MAP_L2_PROMOTION_L2_128B, CU_TENSOR_MAP_FLOAT_OOB_FILL_NONE);
}
void make_map3(EncodeFn enc, CUtensorMap* m, const void* ptr, int rows) {
  cuuint64_t dim[3] = {64, (cuuint64_t)rows, 9}, str[2] = {DM * 2, 128};
  cuuint32_t box[3] = {64, 32, 3}, es[3] = {1, 1, 1};
  enc(m, CU_TENSOR_MAP_DATA_TYPE_BFLOAT16, 3, const_cast<void*>(ptr), dim, str, box, es, CU_TENSOR_MAP_INTERLEAVE_NONE, CU_TENSOR_MAP_SWIZZLE_128B,
      CU_TENSOR_MAP_L2_PROMOTION_L2_128B, CU_TENSOR_MAP_FLOAT_OOB_FILL_NONE);
}

void make_map_t(EncodeFn enc, CUtensorMap* m, void* ptr, int width, int cols) {
  cuuint64_t dim[3] = {TP / 2, 2, 864}, str[2] = {TP * 2, TP * 4};
  cuuint32_t box[3] = {(cuuint32_t)width, 2, (cuuint32_t)cols}, es[3] = {1, 1, 1};
  enc(m, CU_TENSOR_MAP_DATA_TYPE_UINT32, 3, ptr, dim, str, box, es, CU_TENSOR_MAP_INTERLEAVE_NONE, cols == 64 ? CU_TENSOR_MAP_SWIZZLE_128B : CU_TENSOR_MAP_SWIZZLE_NONE,
      CU_TENSOR_MAP_L2_PROMOTION_NONE, CU_TENSOR_MAP_FLOAT_OOB_FILL_NONE);
}

int g_mode = -1;

}

extern "C" void kernel_launch(void* const* d_in, const int* in_sizes, int n_in, void* d_out, int out_size) {
  static EncodeFn enc = nullptr;
  static void* t_ptr = nullptr;
  if (!enc) {
    void* fn = nullptr;
    cudaDriverEntryPointQueryResult st;
    cudaGetDriverEntryPoint("cuTensorMapEncodeTiled", &fn, cudaEnableDefault, &st);
    enc = (EncodeFn)fn;
    cudaGetSymbolAddress(&t_ptr, g_T);
    cudaFuncSetAttribute(fused_kernel, cudaFuncAttributeMaxDynamicSharedMemorySize, SMEM_BYTES);
    if (g_mode < 0) {
      cudaLaunchConfig_t cfg = {};
      cfg.gridDim = dim3(2 * NCL); cfg.blockDim = dim3(384); cfg.dynamicSmemBytes = SMEM_BYTES;
      cudaLaunchAttribute at; at.id = cudaLaunchAttributeClusterDimension;
      at.val.clusterDim.x = 2; at.val.clusterDim.y = 1; at.val.clusterDim.z = 1;
      cfg.attrs = &at; cfg.numAttrs = 1;
      int nc = 0;
      g_mode = (cudaOccupancyMaxActiveClusters(&nc, fused_kernel, &cfg) == cudaSuccess && nc >= NCL) ? 1 : 0;
      (void)cudaGetLastError();
    }
  }
  Params p;
  make_map2(enc, &p.map_a[0], d_in[4], SEQ, DC, 128);
  make_map2(enc, &p.map_a[1], d_in[0], SEQ, DM, 128);
  make_map2(enc, &p.map_w[0], d_in[6], DC, 4096, 64);
  make_map2(enc, &p.map_w[1], d_in[7], DC, 4096, 64);
  make_map2(enc, &p.map_w[2], d_in[5], DM, 4096, 64);
  make_map2(enc, &p.map_w[3], d_in[1], DM, 1728, 64);
  make_map3(enc, &p.map_o[0], d_in[8], 4096);
  make_map3(enc, &p.map_o[1], d_in[2], DM);
  make_map_t(enc, &p.map_t[0], t_ptr, 32, 9);
  make_map_t(enc, &p.map_t[1], t_ptr, 40, 9);
  make_map_t(enc, &p.map_t[2], t_ptr, 32, 64);
  p.x = (const __nv_bfloat16*)d_in[0];
  p.gate_w = (const __nv_bfloat16*)d_in[9];
  make_map2(enc, &p.map_out, d_out, SEQ, DM, 16);
  p.zero = 0;
  auto launch = [&](int phases) {
    p.s = k_sched;
    for (int i = 0; i < NCL; i++) {
      Rec& r = p.s.r[i];
      if (!(phases & 1)) r.n1 = 0;
      if (!(phases & 2)) r.n2 = 0;
      if (!(phases & (r.p3 < 24 ? 4 : 32))) r.p3 = 255;
      if (!(phases & 8)) r.bg = 255;
      const int u1 = r.n1 ? 8 + r.n1 * (8 + (r.slab >> 3)) : 0;
      int u2 = 0;
      for (int k = 0; k < r.n2; k++) u2 += 4 * (r.item[k] & 7) + 4;
      r.u1 = (uint8_t)u1; r.u2 = (uint8_t)u2;
      r.rot = (uint8_t)(((u1 % 10 + 1) >> 1) % 5);
      r.x3 = (uint8_t)((r.rot + u2) % 5 & 3);
      r.ring = (phases & 16) ? p.s.ring : 32;
      r.phases = (uint8_t)phases;
    }
    fused_kernel<<<2 * NCL, 384, SMEM_BYTES>>>(p);
  };
  if (g_mode == 1) launch(63);
  else { launch(1); launch(10); launch(32); launch(4); }
}
```

```cpp
#include <cuda_runtime.h>
#include <cuda_bf16.h>
#include <cuda.h>
#include <stdint.h>

namespace {

constexpr int SEQ = 2048, DM = 576, DC = 512, NH = 32;
constexpr int NCL = 66;
constexpr uint32_t DESC_HI = 0x40000040u;

constexpr int SM_RING = 0;
constexpr int SM_BUF = 163840;
constexpr int SM_BAR = 229376;
constexpr int B_P1E = 0, B_P2E = 10, B_P3E = 15, B_P2F = 24, B_SF = 32, B_ORD = 36, B_LAD = 40, B_DONE = 41, B_FIN = 48;
constexpr int B_P3F = 56, B_OUT = 61, B_P1F = 64, B_SE = 74, B_QF = 80, B_LA = 84, B_NUM = 88;
constexpr uint64_t B_CNT = 0x11118245000ull;
constexpr int SMEM_BYTES = SM_BAR + B_NUM * 8 + 1024;

constexpr int F_HEAD = 0;
constexpr int F_QKVA = 32;
constexpr int F_GATE = 64;
constexpr int F_DONE = 65;
constexpr int F_CTX = 96;
constexpr int F_OUT = 96 + 8 * 64;
constexpr int F_NUM = F_OUT + 48;

struct Rec {
  uint8_t slab;
  uint8_t n1, n2;
  uint8_t p3;
  uint8_t bg;
  uint8_t item[11];
  uint8_t last[11];
  uint8_t tile[31];
  uint8_t ring;
  uint8_t u1, u2;
  uint8_t rot, x3;
  uint8_t phases;
};
struct Sched {
  Rec r[NCL];
  uint8_t ring;
  uint8_t nh[24];
  uint8_t p3_order[8][32];
};

struct Params {
  CUtensorMap map_a[2];
  CUtensorMap map_w[4];
  CUtensorMap map_o[2];
  CUtensorMap map_t[3];
  CUtensorMap map_out;
  const __nv_bfloat16* x;
  const __nv_bfloat16* gate_w;
  __nv_bfloat16* out;
  int zero;
  alignas(64) Sched s;
};

__device__ __align__(1024) uint8_t g_Q[NH * 32 * 16384];
__device__ __align__(1024) uint8_t g_KV[2 * NH * 16 * 32768];
__device__ __align__(1024) uint8_t g_oA[32 * 576 * 128];
constexpr int TP = SEQ + 16;
__device__ __align__(1024) uint32_t g_T[864 * TP];
__device__ float g_gate[SEQ];
__device__ int g_flags[F_NUM];

__device__ __forceinline__ void mbar_arrive(uint32_t b) { asm volatile("mbarrier.arrive.shared::cta.b64 _, [%0];" ::"r"(b) : "memory"); }
__device__ __forceinline__ void mbar_arrive_cl(uint32_t b, int cnt) {
  asm volatile("mbarrier.arrive.shared::cluster.b64 _, [%0], %1;" ::"r"(b), "r"(cnt) : "memory");
}
__device__ __forceinline__ void mbar_wait(uint32_t b, int par) {
  asm volatile(
      "{\n.reg .pred p;\n.reg .u32 c;\n"
      "mbarrier.try_wait.parity.shared::cta.b64 p, [%0], %1;\n@p bra DN;\nmov.u32 c, 0;\n"
      "LP:\nmbarrier.try_wait.parity.shared::cta.b64 p, [%0], %1;\n@p bra DN;\n"
      "add.u32 c, c, 1;\nsetp.lt.u32 p, c, 4000000;\n@p bra LP;\ntrap;\nDN:\n}" ::"r"(b), "r"(par) : "memory");
}
__device__ __forceinline__ uint32_t mapa(uint32_t a, uint32_t cta) {
  uint32_t r; asm("mapa.shared::cluster.u32 %0, %1, %2;" : "=r"(r) : "r"(a), "r"(cta)); return r;
}
#define ELECT(ins) "{\n.reg .pred e;\nelect.sync _|e, 0xffffffff;\n@e " ins "\n}"
__device__ __forceinline__ void mbar_expect(uint32_t b, int bytes) {
  asm volatile(ELECT("mbarrier.arrive.expect_tx.shared::cta.b64 _, [%0], %1;") ::"r"(b), "r"(bytes) : "memory");
}
__device__ __forceinline__ void mbar_arrive_one(uint32_t b) { asm volatile(ELECT("mbarrier.arrive.shared::cta.b64 _, [%0];") ::"r"(b) : "memory"); }
constexpr uint64_t L2_NORMAL = 0x1000000000000000ull, L2_FIRST = 0x12F0000000000000ull;
__device__ __forceinline__ void bulk_load(uint32_t dst, const void* src, int bytes, uint32_t bar, uint64_t pol = L2_NORMAL) {
  asm volatile(ELECT("cp.async.bulk.shared::cluster.global.mbarrier::complete_tx::bytes.L2::cache_hint [%0], [%1], %2, [%3], %4;") ::"r"(dst), "l"(src), "r"(bytes), "r"(bar), "l"(pol) : "memory");
}
__device__ __forceinline__ void bulk_load_mc(uint32_t dst, const void* src, int bytes, uint32_t bar, uint64_t pol = L2_NORMAL) {
  asm volatile(ELECT("cp.async.bulk.shared::cluster.global.mbarrier::complete_tx::bytes.multicast::cluster.L2::cache_hint [%0], [%1], %2, [%3], %4, %5;") ::"r"(dst), "l"(src), "r"(bytes), "r"(bar), "h"((uint16_t)3), "l"(pol) : "memory");
}
__device__ __forceinline__ void bulk_store(void* dst, uint32_t src, int bytes, uint64_t pol = L2_NORMAL) {
  asm volatile(ELECT("cp.async.bulk.global.shared::cta.bulk_group.L2::cache_hint [%0], [%1], %2, %3;") ::"l"(dst), "r"(src), "r"(bytes), "l"(pol) : "memory");
}
__device__ __forceinline__ void tma2d(uint32_t dst, const CUtensorMap* m, int c0, int c1, uint32_t bar, uint64_t pol = L2_NORMAL) {
  asm volatile(ELECT("cp.async.bulk.tensor.2d.shared::cluster.global.mbarrier::complete_tx::bytes.L2::cache_hint [%0], [%1, {%3, %4}], [%2], %5;") ::"r"(dst), "l"(m), "r"(bar), "r"(c0), "r"(c1), "l"(pol) : "memory");
}
__device__ __forceinline__ void tma2d_mc(uint32_t dst, const CUtensorMap* m, int c0, int c1, uint32_t bar, uint64_t pol = L2_NORMAL) {
  asm volatile(ELECT("cp.async.bulk.tensor.2d.shared::cluster.global.mbarrier::complete_tx::bytes.multicast::cluster.L2::cache_hint [%0], [%1, {%3, %4}], [%2], %5, %6;") ::"r"(dst), "l"(m), "r"(bar), "r"(c0), "r"(c1), "h"((uint16_t)3), "l"(pol) : "memory");
}
__device__ __forceinline__ void tma3d(uint32_t dst, const CUtensorMap* m, int c0, int c1, int c2, uint32_t bar, uint64_t pol = L2_NORMAL) {
  asm volatile(ELECT("cp.async.bulk.tensor.3d.shared::cluster.global.mbarrier::complete_tx::bytes.L2::cache_hint [%0], [%1, {%3, %4, %5}], [%2], %6;") ::"r"(dst), "l"(m), "r"(bar), "r"(c0), "r"(c1), "r"(c2), "l"(pol) : "memory");
}
__device__ __forceinline__ void tma3d_mc(uint32_t dst, const CUtensorMap* m, int c0, int c1, int c2, uint32_t bar, uint64_t pol = L2_NORMAL) {
  asm volatile(ELECT("cp.async.bulk.tensor.3d.shared::cluster.global.mbarrier::complete_tx::bytes.multicast::cluster.L2::cache_hint [%0], [%1, {%3, %4, %5}], [%2], %6, %7;") ::"r"(dst), "l"(m), "r"(bar), "r"(c0), "r"(c1), "r"(c2), "h"((uint16_t)3), "l"(pol) : "memory");
}
__device__ __forceinline__ void tma2d_add(const CUtensorMap* m, uint32_t src, int c0, int c1) {
  asm volatile(ELECT("cp.reduce.async.bulk.tensor.2d.global.shared::cta.add.bulk_group [%0, {%2, %3}], [%1];") ::"l"(m), "r"(src), "r"(c0), "r"(c1) : "memory");
}
__device__ __forceinline__ void tma3d_store(const CUtensorMap* m, uint32_t src, int c0, int c1, int c2, uint64_t pol = L2_NORMAL) {
  asm volatile(ELECT("cp.async.bulk.tensor.3d.global.shared::cta.bulk_group.L2::cache_hint [%0, {%2, %3, %4}], [%1], %5;") ::"l"(m), "r"(src), "r"(c0), "r"(c1), "r"(c2), "l"(pol) : "memory");
}
__device__ __forceinline__ void tma2d_prefetch(const CUtensorMap* m, int c0, int c1, uint64_t pol = L2_NORMAL) {
  asm volatile(ELECT("cp.async.bulk.prefetch.tensor.2d.L2.global.L2::cache_hint [%0, {%1, %2}], %3;") ::"l"(m), "r"(c0), "r"(c1), "l"(pol) : "memory");
}
#define HINT 62
#define POL(bit) ((HINT >> (bit)) & 1 ? L2_FIRST : L2_NORMAL)
#define BULK_COMMIT() asm volatile("cp.async.bulk.commit_group;" ::: "memory")
#define BULK_WAIT(n) asm volatile("cp.async.bulk.wait_group %0;" ::"n"(n) : "memory")
#define BULK_WAIT_READ(n) asm volatile("cp.async.bulk.wait_group.read %0;" ::"n"(n) : "memory")
#define FENCE_ASYNC_SMEM() asm volatile("fence.proxy.async.shared::cta;" ::: "memory")
#define FENCE_ASYNC_ALL() asm volatile("fence.proxy.async;" ::: "memory")
#define WG_FENCE() asm volatile("wgmma.fence.sync.aligned;" ::: "memory")
#define WG_COMMIT() asm volatile("wgmma.commit_group.sync.aligned;" ::: "memory")
#define WG_WAIT(n) asm volatile("wgmma.wait_group.sync.aligned %0;" ::"n"(n) : "memory")
__device__ __forceinline__ void bar_sync(int id, int n) { asm volatile("bar.sync %0, %1;" ::"r"(id), "r"(n) : "memory"); }
__device__ __forceinline__ void bar_arrive(int id, int n) { asm volatile("bar.arrive %0, %1;" ::"r"(id), "r"(n) : "memory"); }
__device__ __forceinline__ void cluster_sync() {
  asm volatile("barrier.cluster.arrive.relaxed;\nbarrier.cluster.wait.acquire;" ::: "memory");
}
template <int N> __device__ __forceinline__ void pin(float (&r)[N]) {
#pragma unroll
  for (int i = 0; i < N; i++) asm volatile("" : "+f"(r[i])::"memory");
}
template <int N> __device__ __forceinline__ void pin(uint32_t (&r)[N]) {
#pragma unroll
  for (int i = 0; i < N; i++) asm volatile("" : "+r"(r[i])::"memory");
}
__device__ __forceinline__ uint32_t pack_bf16(float lo, float hi) {
  uint32_t r; asm("cvt.rn.bf16x2.f32 %0, %1, %2;" : "=r"(r) : "f"(hi), "f"(lo)); return r;
}
__device__ __forceinline__ float ex2(float x) { float r; asm("ex2.approx.ftz.f32 %0, %1;" : "=f"(r) : "f"(x)); return r; }
__device__ __forceinline__ void ldsm4(uint32_t a, uint32_t& r0, uint32_t& r1, uint32_t& r2, uint32_t& r3) {
  asm volatile("ldmatrix.sync.aligned.m8n8.x4.shared.b16 {%0,%1,%2,%3}, [%4];" : "=r"(r0), "=r"(r1), "=r"(r2), "=r"(r3) : "r"(a) : "memory");
}
__device__ __forceinline__ void stsm4(uint32_t a, uint32_t r0, uint32_t r1, uint32_t r2, uint32_t r3) {
  asm volatile("stmatrix.sync.aligned.m8n8.x4.shared.b16 [%0], {%1,%2,%3,%4};" ::"r"(a), "r"(r0), "r"(r1), "r"(r2), "r"(r3) : "memory");
}
__device__ __forceinline__ void flag_add(int idx) {
  asm volatile(ELECT("red.release.gpu.global.add.s32 [%0], 1;") ::"l"(g_flags + idx) : "memory");
}
__device__ __forceinline__ void flag_add_rx(int idx) {
  asm volatile(ELECT("red.relaxed.gpu.global.add.s32 [%0], 1;") ::"l"(g_flags + idx) : "memory");
}
template <bool ACQ, int NS = 32> __device__ __forceinline__ void flag_wait(int idx, int target) {
  int n = 0;
  while (true) {
    int v;
    if (ACQ) asm volatile("ld.acquire.gpu.global.s32 %0, [%1];" : "=r"(v) : "l"(g_flags + idx) : "memory");
    else asm volatile("ld.relaxed.gpu.global.s32 %0, [%1];" : "=r"(v) : "l"(g_flags + idx) : "memory");
    if (__all_sync(0xffffffffu, v >= target)) break;
    if (++n > 20000000) __trap();
    __nanosleep(NS);
  }
}
__device__ __forceinline__ uint32_t desc_lo(uint32_t addr, uint32_t lbo) { return ((addr & 0x3FFFFu) >> 4) | ((lbo >> 4) << 16); }
#define PROF(role, i)
#define PROFX(cond, i)
#define PROFB(i)
#define PROFG(i)

template <int TB, int TA = 0> __device__ __forceinline__ void wgmma_ss64(float (&d)[32], uint32_t alo, uint32_t blo, int sd) {
  asm volatile("{\n.reg .pred p;\n.reg .b64 da, db;\n"
    "setp.ne.b32 p, %34, 0;\nmov.b64 da, {%32, %36};\nmov.b64 db, {%33, %36};\n"
    "wgmma.mma_async.sync.aligned.m64n64k16.f32.bf16.bf16 "
    "{%0,%1,%2,%3,%4,%5,%6,%7,%8,%9,%10,%11,%12,%13,%14,%15,%16,%17,%18,%19,%20,%21,%22,%23,"
    "%24,%25,%26,%27,%28,%29,%30,%31}, "
    "da, db, p, 1, 1, %37, %35;\n}\n"
    : "+f"(d[0]),"+f"(d[1]),"+f"(d[2]),"+f"(d[3]),"+f"(d[4]),"+f"(d[5]),"+f"(d[6]),"+f"(d[7]),"+f"(d[8]),"+f"(d[9]),"+f"(d[10]),"+f"(d[11]),
      "+f"(d[12]),"+f"(d[13]),"+f"(d[14]),"+f"(d[15]),"+f"(d[16]),"+f"(d[17]),"+f"(d[18]),"+f"(d[19]),"+f"(d[20]),"+f"(d[21]),"+f"(d[22]),"+f"(d[23]),
      "+f"(d[24]),"+f"(d[25]),"+f"(d[26]),"+f"(d[27]),"+f"(d[28]),"+f"(d[29]),"+f"(d[30]),"+f"(d[31])
    : "r"(alo), "r"(blo), "r"(sd), "n"(TB), "r"(DESC_HI), "n"(TA));
}
template <int TB, int TA = 0> __device__ __forceinline__ void wgmma_ss128(float (&d)[64], uint32_t alo, uint32_t blo, int sd) {
  asm volatile("{\n.reg .pred p;\n.reg .b64 da, db;\n"
    "setp.ne.b32 p, %66, 0;\nmov.b64 da, {%64, %68};\nmov.b64 db, {%65, %68};\n"
    "wgmma.mma_async.sync.aligned.m64n128k16.f32.bf16.bf16 "
    "{%0,%1,%2,%3,%4,%5,%6,%7,%8,%9,%10,%11,%12,%13,%14,%15,%16,%17,%18,%19,%20,%21,%22,%23,"
    "%24,%25,%26,%27,%28,%29,%30,%31,%32,%33,%34,%35,%36,%37,%38,%39,%40,%41,%42,%43,%44,%45,%46,%47,"
    "%48,%49,%50,%51,%52,%53,%54,%55,%56,%57,%58,%59,%60,%61,%62,%63}, "
    "da, db, p, 1, 1, %69, %67;\n}\n"
    : "+f"(d[0]),"+f"(d[1]),"+f"(d[2]),"+f"(d[3]),"+f"(d[4]),"+f"(d[5]),"+f"(d[6]),"+f"(d[7]),"+f"(d[8]),"+f"(d[9]),"+f"(d[10]),"+f"(d[11]),
      "+f"(d[12]),"+f"(d[13]),"+f"(d[14]),"+f"(d[15]),"+f"(d[16]),"+f"(d[17]),"+f"(d[18]),"+f"(d[19]),"+f"(d[20]),"+f"(d[21]),"+f"(d[22]),"+f"(d[23]),
      "+f"(d[24]),"+f"(d[25]),"+f"(d[26]),"+f"(d[27]),"+f"(d[28]),"+f"(d[29]),"+f"(d[30]),"+f"(d[31]),"+f"(d[32]),"+f"(d[33]),"+f"(d[34]),"+f"(d[35]),
      "+f"(d[36]),"+f"(d[37]),"+f"(d[38]),"+f"(d[39]),"+f"(d[40]),"+f"(d[41]),"+f"(d[42]),"+f"(d[43]),"+f"(d[44]),"+f"(d[45]),"+f"(d[46]),"+f"(d[47]),
      "+f"(d[48]),"+f"(d[49]),"+f"(d[50]),"+f"(d[51]),"+f"(d[52]),"+f"(d[53]),"+f"(d[54]),"+f"(d[55]),"+f"(d[56]),"+f"(d[57]),"+f"(d[58]),"+f"(d[59]),
      "+f"(d[60]),"+f"(d[61]),"+f"(d[62]),"+f"(d[63])
    : "r"(alo), "r"(blo), "r"(sd), "n"(TB), "r"(DESC_HI), "n"(TA));
}
template <int TB> __device__ __forceinline__ void wgmma_rs128(float (&d)[64], uint32_t a0, uint32_t a1, uint32_t a2, uint32_t a3, uint32_t blo, int sd) {
  asm volatile("{\n.reg .pred p;\n.reg .b64 db;\n"
    "setp.ne.b32 p, %69, 0;\nmov.b64 db, {%68, %71};\n"
    "wgmma.mma_async.sync.aligned.m64n128k16.f32.bf16.bf16 "
    "{%0,%1,%2,%3,%4,%5,%6,%7,%8,%9,%10,%11,%12,%13,%14,%15,%16,%17,%18,%19,%20,%21,%22,%23,"
    "%24,%25,%26,%27,%28,%29,%30,%31,%32,%33,%34,%35,%36,%37,%38,%39,%40,%41,%42,%43,%44,%45,%46,%47,"
    "%48,%49,%50,%51,%52,%53,%54,%55,%56,%57,%58,%59,%60,%61,%62,%63}, "
    "{%64,%65,%66,%67}, db, p, 1, 1, %70;\n}\n"
    : "+f"(d[0]),"+f"(d[1]),"+f"(d[2]),"+f"(d[3]),"+f"(d[4]),"+f"(d[5]),"+f"(d[6]),"+f"(d[7]),"+f"(d[8]),"+f"(d[9]),"+f"(d[10]),"+f"(d[11]),
      "+f"(d[12]),"+f"(d[13]),"+f"(d[14]),"+f"(d[15]),"+f"(d[16]),"+f"(d[17]),"+f"(d[18]),"+f"(d[19]),"+f"(d[20]),"+f"(d[21]),"+f"(d[22]),"+f"(d[23]),
      "+f"(d[24]),"+f"(d[25]),"+f"(d[26]),"+f"(d[27]),"+f"(d[28]),"+f"(d[29]),"+f"(d[30]),"+f"(d[31]),"+f"(d[32]),"+f"(d[33]),"+f"(d[34]),"+f"(d[35]),
      "+f"(d[36]),"+f"(d[37]),"+f"(d[38]),"+f"(d[39]),"+f"(d[40]),"+f"(d[41]),"+f"(d[42]),"+f"(d[43]),"+f"(d[44]),"+f"(d[45]),"+f"(d[46]),"+f"(d[47]),
      "+f"(d[48]),"+f"(d[49]),"+f"(d[50]),"+f"(d[51]),"+f"(d[52]),"+f"(d[53]),"+f"(d[54]),"+f"(d[55]),"+f"(d[56]),"+f"(d[57]),"+f"(d[58]),"+f"(d[59]),
      "+f"(d[60]),"+f"(d[61]),"+f"(d[62]),"+f"(d[63])
    : "r"(a0), "r"(a1), "r"(a2), "r"(a3), "r"(blo), "r"(sd), "n"(TB), "r"(DESC_HI));
}
template <int TB, int TA = 0> __device__ __forceinline__ void wgmma_ss192(float (&d)[96], uint32_t alo, uint32_t blo, int sd) {
  asm volatile("{\n.reg .pred p;\n.reg .b64 da, db;\n"
    "setp.ne.b32 p, %98, 0;\nmov.b64 da, {%96, %100};\nmov.b64 db, {%97, %100};\n"
    "wgmma.mma_async.sync.aligned.m64n192k16.f32.bf16.bf16 "
    "{%0,%1,%2,%3,%4,%5,%6,%7,%8,%9,%10,%11,%12,%13,%14,%15,%16,%17,%18,%19,%20,%21,%22,%23,"
    "%24,%25,%26,%27,%28,%29,%30,%31,%32,%33,%34,%35,%36,%37,%38,%39,%40,%41,%42,%43,%44,%45,%46,%47,"
    "%48,%49,%50,%51,%52,%53,%54,%55,%56,%57,%58,%59,%60,%61,%62,%63,%64,%65,%66,%67,%68,%69,%70,%71,"
    "%72,%73,%74,%75,%76,%77,%78,%79,%80,%81,%82,%83,%84,%85,%86,%87,%88,%89,%90,%91,%92,%93,%94,%95}, "
    "da, db, p, 1, 1, %101, %99;\n}\n"
    : "+f"(d[0]),"+f"(d[1]),"+f"(d[2]),"+f"(d[3]),"+f"(d[4]),"+f"(d[5]),"+f"(d[6]),"+f"(d[7]),"+f"(d[8]),"+f"(d[9]),"+f"(d[10]),"+f"(d[11]),
      "+f"(d[12]),"+f"(d[13]),"+f"(d[14]),"+f"(d[15]),"+f"(d[16]),"+f"(d[17]),"+f"(d[18]),"+f"(d[19]),"+f"(d[20]),"+f"(d[21]),"+f"(d[22]),"+f"(d[23]),
      "+f"(d[24]),"+f"(d[25]),"+f"(d[26]),"+f"(d[27]),"+f"(d[28]),"+f"(d[29]),"+f"(d[30]),"+f"(d[31]),"+f"(d[32]),"+f"(d[33]),"+f"(d[34]),"+f"(d[35]),
      "+f"(d[36]),"+f"(d[37]),"+f"(d[38]),"+f"(d[39]),"+f"(d[40]),"+f"(d[41]),"+f"(d[42]),"+f"(d[43]),"+f"(d[44]),"+f"(d[45]),"+f"(d[46]),"+f"(d[47]),
      "+f"(d[48]),"+f"(d[49]),"+f"(d[50]),"+f"(d[51]),"+f"(d[52]),"+f"(d[53]),"+f"(d[54]),"+f"(d[55]),"+f"(d[56]),"+f"(d[57]),"+f"(d[58]),"+f"(d[59]),
      "+f"(d[60]),"+f"(d[61]),"+f"(d[62]),"+f"(d[63]),"+f"(d[64]),"+f"(d[65]),"+f"(d[66]),"+f"(d[67]),"+f"(d[68]),"+f"(d[69]),"+f"(d[70]),"+f"(d[71]),
      "+f"(d[72]),"+f"(d[73]),"+f"(d[74]),"+f"(d[75]),"+f"(d[76]),"+f"(d[77]),"+f"(d[78]),"+f"(d[79]),"+f"(d[80]),"+f"(d[81]),"+f"(d[82]),"+f"(d[83]),
      "+f"(d[84]),"+f"(d[85]),"+f"(d[86]),"+f"(d[87]),"+f"(d[88]),"+f"(d[89]),"+f"(d[90]),"+f"(d[91]),"+f"(d[92]),"+f"(d[93]),"+f"(d[94]),"+f"(d[95])
    : "r"(alo), "r"(blo), "r"(sd), "n"(TB), "r"(DESC_HI), "n"(TA));
}

struct Ctx {
  uint32_t sm;
  uint32_t bar;
  uint32_t rbar;
  int cl, rank, wg, warp, lane, phases;
};
__device__ __forceinline__ void release(const Ctx& c, int b, int cnt = 1) {
  if (c.lane < 2) mbar_arrive_cl(c.rbar + b * 8, cnt);
}
#define NPF 6
#define PFM 7
#define PF1 1
constexpr float SM_SCALE = 0.08838834764831845f * 1.4426950408889634f;
constexpr float SM_HI = 1.8446744e19f, SM_LO = 5.4210109e-20f;
constexpr int ORDER = 1;

__device__ __forceinline__ void stage_tile(const float (&a)[64], uint32_t buf, const Ctx& c, float s0, float s1) {
  const int row = (c.lane & 7) + ((c.lane >> 3) & 1) * 8;
  const uint32_t base = buf + (c.warp * 16 + row) * 128 + (((c.lane >> 4) ^ (row & 7)) << 4);
#pragma unroll
  for (int i = 0; i < 8; i++)
    stsm4((base ^ ((i & 3) << 5)) + (i >> 2) * 8192, pack_bf16(a[8 * i] * s0, a[8 * i + 1] * s0), pack_bf16(a[8 * i + 2] * s1, a[8 * i + 3] * s1),
          pack_bf16(a[8 * i + 4] * s0, a[8 * i + 5] * s0), pack_bf16(a[8 * i + 6] * s1, a[8 * i + 7] * s1));
}

__device__ __forceinline__ void p1_epilogue(const Params& p, const Ctx& c, const float (&acc)[64], int t, int type) {
  const int tile = p.s.r[c.cl].tile[t], b = c.wg * 2 + 1;
  mbar_wait(c.bar + (B_SE + b) * 8, (t & 1) ^ 1);
  if (type && tile >= 32) {
    const int r = 2 * (c.lane & 3) + ((c.lane >> 2) & 1);
    const uint32_t dst = c.sm + SM_BUF + b * 16384 + r * 128 + (((c.warp * 2) ^ r) << 4) + (c.lane >> 3) * 4;
#pragma unroll
    for (int i = 0; i < 16; i++) {
      asm volatile("st.shared.u32 [%0], %1;" ::"r"(dst + i * 1024), "r"(pack_bf16(acc[4 * i], acc[4 * i + 1])) : "memory");
      asm volatile("st.shared.u32 [%0], %1;" ::"r"((dst ^ 16) + i * 1024), "r"(pack_bf16(acc[4 * i + 2], acc[4 * i + 3])) : "memory");
    }
  } else {
    if (type) stage_tile(acc, c.sm + SM_BUF + b * 16384, c, SM_SCALE, SM_SCALE);
    else stage_tile(acc, c.sm + SM_BUF + b * 16384, c, 1.f, 1.f);
  }
  FENCE_ASYNC_SMEM();
  __syncwarp();
  if (c.lane == 0) mbar_arrive(c.bar + (B_SF + b) * 8);
}

__device__ __forceinline__ void p1_consumer(const Params& p, const Ctx& c) {
  const int n = p.s.r[c.cl].n1;
  const int type = p.s.r[c.cl].slab >> 3;
  const uint32_t bdesc = desc_lo(c.sm + SM_RING, 8192), adesc = desc_lo(c.sm + SM_BUF + 32768 + c.wg * 8192, 16);
  uint32_t A[128];
  float acc[64] = {};
  int slot = 0, par = 0;
  auto next = [&]() { if (++slot == 10) { slot = 0; par ^= 1; } };
  {
    const int row = (c.lane & 7) + ((c.lane >> 3) & 1) * 8;
    const uint32_t base = c.sm + SM_RING + (c.wg * 64 + c.warp * 16 + row) * 128 + (((c.lane >> 4) ^ (row & 7)) << 4);
    if (c.wg == 1) bar_sync(ORDER + 1, 256);
    int pa = -1, pb = -1;
    if (type) {
      mbar_wait(c.bar + B_P1F * 8, 0);
      WG_FENCE();
#pragma unroll
      for (int kk = 0; kk < 4; kk++) wgmma_ss128<1>(acc, adesc + kk * 2, bdesc + kk * 128, kk != 0);
      WG_COMMIT();
      pb = 0; slot = 1;
    }
#pragma unroll
    for (int kb = 0; kb < 8; kb++) {
      const int sa = slot;
      mbar_wait(c.bar + (B_P1F + slot) * 8, par);
      if (kb == 0) PROF(c.wg, 5);
      next();
      mbar_wait(c.bar + (B_P1F + slot) * 8, par);
      PROF(c.wg, 6 + 2 * kb);
      WG_FENCE();
#pragma unroll
      for (int kk = 0; kk < 4; kk++)
        wgmma_ss128<1>(acc, desc_lo(c.sm + SM_RING + c.wg * 8192, 16) + sa * 1024 + kk * 2, bdesc + slot * 1024 + kk * 128, (kb | kk) != 0 ? 1 : type);
      WG_COMMIT();
      if (kb == 1 && c.wg == 0) bar_arrive(ORDER + 1, 256);
#pragma unroll
      for (int kk = 0; kk < 4; kk++) ldsm4((base ^ (kk << 5)) + sa * 16384, A[kb * 16 + kk * 4], A[kb * 16 + kk * 4 + 1], A[kb * 16 + kk * 4 + 2], A[kb * 16 + kk * 4 + 3]);
      WG_WAIT(1);
      if (kb > 0) release(c, B_P1E + pa);
      if (kb > 0 || pb >= 0) release(c, B_P1E + pb);
      pa = sa; pb = slot;
      next();
    }
    WG_WAIT(0);
    __syncwarp();
    release(c, B_P1E + pa);
    release(c, B_P1E + pb);
    pin(acc);
    PROF(c.wg, 1);
    p1_epilogue(p, c, acc, 0, type);
    PROF(c.wg, 2);
  }
  for (int t = 1; t < n; t++) {
    bar_sync(ORDER + c.wg, 256);
    int prev1 = -1, prev2 = -1;
    if (type) {
      mbar_wait(c.bar + (B_P1F + slot) * 8, par);
      WG_FENCE();
#pragma unroll
      for (int kk = 0; kk < 4; kk++) wgmma_ss128<1>(acc, adesc + kk * 2, bdesc + slot * 1024 + kk * 128, kk != 0);
      WG_COMMIT();
      prev1 = slot;
      next();
    }
#pragma unroll
    for (int kb = 0; kb < 8; kb++) {
      mbar_wait(c.bar + (B_P1F + slot) * 8, par);
      WG_FENCE();
      const uint32_t d = bdesc + slot * 1024;
#pragma unroll
      for (int kk = 0; kk < 4; kk++)
        wgmma_rs128<1>(acc, A[kb * 16 + kk * 4], A[kb * 16 + kk * 4 + 1], A[kb * 16 + kk * 4 + 2], A[kb * 16 + kk * 4 + 3], d + kk * 128, (kb | kk) != 0 ? 1 : type);
      WG_COMMIT();
      if (kb == 7) {
        if (t + 1 < n || c.wg == 0) bar_arrive(ORDER + (c.wg ^ 1), 256);
      }
      if (kb > 0) { WG_WAIT(2); if (kb > 1 || prev2 >= 0) release(c, B_P1E + prev2); }
      prev2 = prev1; prev1 = slot;
      next();
    }
    WG_WAIT(1);
    release(c, B_P1E + prev2);
    WG_WAIT(0);
    pin(acc);
    release(c, B_P1E + prev1);
    p1_epilogue(p, c, acc, t, type);
    PROF(c.wg, 3);
  }
}

__device__ __forceinline__ void p1_producer(const Params& p, const Ctx& c) {
  const int n = p.s.r[c.cl].n1;
  const int type = p.s.r[c.cl].slab >> 3, grp = p.s.r[c.cl].slab & 7;
  int slot = 2 - type, par = 1;
#pragma unroll 1
  for (int t = 0; t < n; t++) {
    const int tile = p.s.r[c.cl].tile[t];
    const CUtensorMap* m = &p.map_w[type * 2 + (tile >> 5)];
    const int n0 = (tile & 31) * 128 + c.rank * 64;
    const int ptile = p.s.r[c.cl].tile[t + PF1 < n ? t + PF1 : t];
    const CUtensorMap* pm = &p.map_w[type * 2 + (ptile >> 5)];
#pragma unroll 1
    for (int kb = (t == 0) - type; kb < 8; kb++) {
      if (t == 0) {
        mbar_wait(c.bar + (B_P1E + slot) * 8, par);
        mbar_expect(c.bar + (B_P1F + slot) * 8, 16384);
        tma2d(c.sm + SM_RING + slot * 16384, &p.map_a[type], kb * 64, grp * 256 + c.rank * 128, c.bar + (B_P1F + slot) * 8);
        if (++slot == 10) { slot = 0; par ^= 1; }
      }
      mbar_wait(c.bar + (B_P1E + slot) * 8, par);
      mbar_expect(c.bar + (B_P1F + slot) * 8, 16384);
      tma2d_mc(c.sm + SM_RING + slot * 16384 + c.rank * 8192, m, n0, kb < 0 ? 512 : kb * 64, c.bar + (B_P1F + slot) * 8);
      if (t == 0 && kb == 1) PROF(2, 61);
      if (t == 0 && kb == 3) PROF(2, 62);
      if (t + PF1 < n && (t > 0 || kb >= 3) && ((kb ^ grp) & PFM) == 0) tma2d_prefetch(pm, (ptile & 31) * 128 + c.rank * 64, kb < 0 ? 512 : kb * 64);
      if (++slot == 10) { slot = 0; par ^= 1; }
    }
  }
}

__device__ __forceinline__ void p1_storer(const Params& p, const Ctx& c) {
  const int n = p.s.r[c.cl].n1;
  const int type = p.s.r[c.cl].slab >> 3, grp = p.s.r[c.cl].slab & 7;
  int pf = -1;
  for (int i = 0; i < 2 * n; i++) {
    const int t = i >> 1, w = i & 1, b = w * 2 + 1;
    const int tile = p.s.r[c.cl].tile[t];
    mbar_wait(c.bar + (B_SF + b) * 8, t & 1);
    const uint32_t src = c.sm + SM_BUF + b * 16384;
    int f = F_HEAD + (tile & 31);
    if (type == 0) {
      const int h = tile & 31, ring = p.s.r[c.cl].ring;
      if (h >= ring && w == 0) flag_wait<false>(F_CTX + max(c.lane & 7, grp) * 64 + h - ring, 4);
      uint8_t* dst = g_KV + (size_t)((h >= ring ? tile - ring : tile) * 16 + grp * 2 + c.rank) * 32768 + w * 8192;
      bulk_store(dst, src, 8192);
      bulk_store(dst + 16384, src + 8192, 8192);
    } else if (tile < 32) {
      bulk_store(g_Q + (size_t)(tile * 32 + grp * 4 + c.rank * 2 + w) * 16384, src, 16384);
    } else {
      tma3d_store(&p.map_t[2], src, 8 + (grp * 4 + c.rank * 2 + w) * 32, 0, (tile - 32) * 64);
      f = F_QKVA + grp * 4 + ((0xE4390900u >> (2 * (tile - 30))) & 3);
    }
    BULK_COMMIT();
    BULK_WAIT_READ(0);
    mbar_arrive_one(c.bar + (B_SE + b) * 8);
    if (pf >= 0) {
      BULK_WAIT(1);
      flag_add_rx(pf);
    }
    pf = f;
  }
  BULK_WAIT(0);
  flag_add_rx(pf);
}

__device__ __forceinline__ int p2_buf(int w, int i) { return w * 2 + (i & 1); }
__device__ __forceinline__ int p2_blk(int rank, int w, int i) { return ((i ^ w) & 1) == 0 ? 3 - rank : rank; }

template <int N>
__device__ __forceinline__ void row_max(const float (&s)[N], float& m0, float& m1) {
  float a0 = fmaxf(s[0], s[1]), a1 = fmaxf(s[2], s[3]);
#pragma unroll
  for (int i = 1; i < N / 4; i++) {
    m0 = fmaxf(m0, s[4 * i]); a0 = fmaxf(a0, s[4 * i + 1]);
    m1 = fmaxf(m1, s[4 * i + 2]); a1 = fmaxf(a1, s[4 * i + 3]);
  }
  m0 = fmaxf(m0, a0); m1 = fmaxf(m1, a1);
  m0 = fmaxf(m0, __shfl_xor_sync(0xffffffffu, m0, 1));
  m1 = fmaxf(m1, __shfl_xor_sync(0xffffffffu, m1, 1));
  m0 = fmaxf(m0, __shfl_xor_sync(0xffffffffu, m0, 2));
  m1 = fmaxf(m1, __shfl_xor_sync(0xffffffffu, m1, 2));
}
template <bool SUB, int N>
__device__ __forceinline__ void row_exp(const float (&s)[N], uint32_t (&P)[32], float m0, float m1, float& t0, float& t1) {
  float u0 = 0.f, u1 = 0.f;
  t0 = t1 = 0.f;
#pragma unroll
  for (int i = 0; i < N / 4; i++) {
    const float e0 = ex2(SUB ? s[4 * i] - m0 : s[4 * i]), e1 = ex2(SUB ? s[4 * i + 1] - m0 : s[4 * i + 1]);
    const float e2 = ex2(SUB ? s[4 * i + 2] - m1 : s[4 * i + 2]), e3 = ex2(SUB ? s[4 * i + 3] - m1 : s[4 * i + 3]);
    if (i == 0) { t0 = e0; u0 = e1; t1 = e2; u1 = e3; }
    else { t0 += e0; u0 += e1; t1 += e2; u1 += e3; }
    P[2 * i] = pack_bf16(e0, e1);
    P[2 * i + 1] = pack_bf16(e2, e3);
  }
#pragma unroll
  for (int i = N / 2; i < 32; i++) P[i] = 0;
  pin(P);
  t0 += u0; t1 += u1;
}
template <int N>
__device__ __forceinline__ void causal_mask(float (&s)[N], int thr) {
#pragma unroll
  for (int i = 0; i < 8; i++) {
    if (8 * i > thr) s[N - 32 + 4 * i] = -INFINITY;
    if (8 * i + 1 > thr) s[N - 32 + 4 * i + 1] = -INFINITY;
    if (8 * i - 8 > thr) s[N - 32 + 4 * i + 2] = -INFINITY;
    if (8 * i - 7 > thr) s[N - 32 + 4 * i + 3] = -INFINITY;
  }
}
__device__ __forceinline__ void issue_qk(float (&s)[32], uint32_t qd, uint32_t kd) {
  WG_FENCE();
#pragma unroll
  for (int kk = 0; kk < 8; kk++) wgmma_ss64<0>(s, qd + (kk >> 2) * 512 + (kk & 3) * 2, kd + (kk >> 2) * 1024 + (kk & 3) * 2, kk != 0);
  WG_COMMIT();
}
__device__ __forceinline__ void issue_qk(float (&s)[64], uint32_t qd, uint32_t kd) {
  WG_FENCE();
#pragma unroll
  for (int kk = 0; kk < 8; kk++) wgmma_ss128<0>(s, qd + (kk >> 2) * 512 + (kk & 3) * 2, kd + (kk >> 2) * 1024 + (kk & 3) * 2, kk != 0);
  WG_COMMIT();
}
template <int NK>
__device__ __forceinline__ void issue_pv(float (&o)[64], const uint32_t (&P)[32], uint32_t vd, int acc) {
  WG_FENCE();
#pragma unroll
  for (int kk = 0; kk < NK; kk++) wgmma_rs128<1>(o, P[4 * kk], P[4 * kk + 1], P[4 * kk + 2], P[4 * kk + 3], vd + kk * 128, kk != 0 ? 1 : acc);
  WG_COMMIT();
}
__device__ __forceinline__ void stage_done(const Ctx& c, int b) {
  FENCE_ASYNC_SMEM();
  __syncwarp();
  if (c.lane == 0) mbar_arrive(c.bar + (B_SF + b) * 8);
}
__device__ __forceinline__ void p2_epilogue(const float (&o)[64], float s0, float s1, const Ctx& c, int b) {
  stage_tile(o, c.sm + SM_BUF + b * 16384, c, s0, s1);
  stage_done(c, b);
}

struct P2State {
  float m0, m1, l0, l1;
  bool shift;
  float e0, e1;
  float g0, g1;
  int ks;
  int wi, ai;
  uint32_t wb, ab;
  uint32_t qd;
};
#define PROFZ()
__device__ __forceinline__ int wrap5(int q) { return q >= 5 ? q - 5 : q; }
__device__ __forceinline__ void turn_wait(uint32_t ring, int i) { mbar_wait(ring + (i & 3) * 8, (i >> 2) & 1); }
__device__ __forceinline__ void turn_pass(const Ctx& c, uint32_t ring, int i) { if (c.lane == 0) mbar_arrive(ring + (i & 3) * 8); }
__device__ __forceinline__ void p2_gate(P2State& z, const Ctx& c, int row0) {
  const float* g = g_gate + row0 + c.warp * 16 + (c.lane >> 2);
  asm volatile("ld.global.cg.f32 %0, [%2];\nld.global.cg.f32 %1, [%2+32];" : "=f"(z.g0), "=f"(z.g1) : "l"(g) : "memory");
}
__device__ __forceinline__ void p2_scales(P2State& z) {
  float l0 = z.l0, l1 = z.l1;
  l0 += __shfl_xor_sync(0xffffffffu, l0, 1);
  l1 += __shfl_xor_sync(0xffffffffu, l1, 1);
  l0 += __shfl_xor_sync(0xffffffffu, l0, 2);
  l1 += __shfl_xor_sync(0xffffffffu, l1, 2);
  z.e0 = __fdividef(1.f - z.g0, l0); z.e1 = __fdividef(1.f - z.g1, l1);
}
template <int N, bool PV>
__device__ __forceinline__ void p2_first(const Params& p, const Ctx& c, P2State& z, float (&o)[64], uint32_t (&Pc)[32], uint32_t (&Pn)[32],
                                         int ks, int vs, int cnt, int acc, int row0) {
  float s[N] = {};
  issue_qk(s, z.qd, desc_lo(c.sm + SM_RING, 16) + ks * 2048);
  if (PV) {
    if (p.zero == 0) p2_scales(z);
    issue_pv<8>(o, Pc, desc_lo(c.sm + SM_RING, 16384) + vs * 2048, acc);
  }
  if (cnt == 1 && c.warp == 0) mbar_expect(z.ab + (z.ai & 3) * 8, 32768); else turn_pass(c, z.ab, z.ai);
  z.ai++;
  PROFZ();
  if (PV) WG_WAIT(1); else WG_WAIT(0);
  PROFZ();
  pin(s);
  release(c, B_P2E + ks, cnt);
  p2_gate(z, c, row0);
  causal_mask(s, c.warp * 16 + (c.lane >> 2) - 2 * (c.lane & 3));
  z.m0 = z.m1 = 0.f;
  row_exp<false>(s, Pn, 0.f, 0.f, z.l0, z.l1);
  z.shift = __any_sync(0xffffffffu, !(z.l0 + z.l1 <= SM_HI) || ((c.lane & 3) == 0 && !(fminf(z.l0, z.l1) >= SM_LO)));
  if (__builtin_expect(z.shift, 0)) {
    z.m0 = z.m1 = -INFINITY;
    row_max(s, z.m0, z.m1);
    row_exp<true>(s, Pn, z.m0, z.m1, z.l0, z.l1);
  }
  if (PV) {
    WG_WAIT(0);
    pin(o);
    release(c, B_P2E + vs, 1);
  }
}

template <bool SECOND>
__device__ __forceinline__ void p2_turn(const Ctx& c, P2State& z, float (&o)[64], uint32_t (&Pc)[32], uint32_t (&Pn)[32],
                                        int eb = -1, bool half = false, int vcnt = 1) {
  float s[64] = {};
  const int ks = z.ks, vs = wrap5(ks + 1);
  PROFZ();
  turn_wait(z.wb, z.wi++);
  PROFZ();
  issue_qk(s, z.qd, desc_lo(c.sm + SM_RING, 16) + ks * 2048);
  const uint32_t vd = desc_lo(c.sm + SM_RING, 16384) + vs * 2048;
  if (SECOND) {
    if (eb >= 0) stage_tile(o, c.sm + SM_BUF + eb * 16384, c, z.e0, z.e1);
    if (half) issue_pv<4>(o, Pc, vd, 0); else issue_pv<8>(o, Pc, vd, 0);
  } else {
    issue_pv<8>(o, Pc, vd, 1);
  }
  turn_pass(c, z.ab, z.ai++);
  if (SECOND) { if (eb >= 0) stage_done(c, eb); }
  PROFZ();
  z.ks = wrap5(ks + 2);
  WG_WAIT(1);
  PROFZ();
  pin(s);
  release(c, B_P2E + ks, 1);
  float t0, t1, a0 = 1.f, a1 = 1.f;
  row_exp<false>(s, Pn, 0.f, 0.f, t0, t1);
  z.shift = __any_sync(0xffffffffu, z.shift || !(t0 + t1 <= SM_HI));
  const bool redo = z.shift;
  if (__builtin_expect(redo, 0)) {
    float n0 = z.m0, n1 = z.m1;
    row_max(s, n0, n1);
    a0 = ex2(z.m0 - n0); a1 = ex2(z.m1 - n1);
    z.m0 = n0; z.m1 = n1;
    z.l0 *= a0; z.l1 *= a1;
    row_exp<true>(s, Pn, z.m0, z.m1, t0, t1);
  }
  WG_WAIT(0);
  pin(o);
  release(c, B_P2E + vs, vcnt);
  if (__builtin_expect(redo, 0)) {
#pragma unroll
    for (int i = 0; i < 16; i++) { o[4 * i] *= a0; o[4 * i + 1] *= a0; o[4 * i + 2] *= a1; o[4 * i + 3] *= a1; }
  }
  z.l0 += t0; z.l1 += t1;
}
__device__ __forceinline__ void copy_p(uint32_t (&d)[32], const uint32_t (&s)[32], int zero) {
#pragma unroll
  for (int i = 0; i < 32; i++) asm volatile("add.s32 %0, %1, %2;" : "=r"(d[i]) : "r"(s[i]), "r"(zero));
}

__device__ __forceinline__ void p2_consumer(const Params& p, const Ctx& c, int rot) {
  const int nit = p.s.r[c.cl].n2;
  const uint32_t fring = c.bar + B_P2F * 8, oring = c.bar + B_ORD * 8;
  float o[64] = {};
  uint32_t Pa[32] = {}, Pb[32] = {};
  P2State z;
  z.e0 = z.e1 = z.l0 = z.l1 = z.g0 = z.g1 = 0.f; z.ks = rot; z.shift = false;
  int acc = 0, n = 0;
  for (int it = 0; it < nit; it++) {
    const int j = p.s.r[c.cl].item[it] & 7, blk = p2_blk(c.rank, c.wg, it), row0 = (j * 4 + blk) * 64;
    const int lng = ((it ^ c.wg) & 1) ^ 1;
    z.qd = desc_lo(c.sm + SM_BUF, 16) + p2_buf(c.wg, it) * 1024;
    if (lng) { z.wb = oring; z.wi = n - it; z.ab = fring; z.ai = n + 1; }
    else { z.wb = fring; z.wi = n + 2; z.ab = oring; z.ai = n - it; }
    PROFZ();
    mbar_wait(c.bar + (B_QF + p2_buf(c.wg, it)) * 8, (it >> 1) & 1);
    turn_wait(fring, n + 1 - lng);
    PROFZ();
    if (it == 0) {
      const int ks = wrap5(rot + c.wg);
      if (blk & 1) p2_first<64, false>(p, c, z, o, Pa, Pb, ks, 0, 1 + lng, 0, row0);
      else p2_first<32, false>(p, c, z, o, Pa, Pb, ks, 0, 1 + lng, 0, row0);
      z.ks = wrap5(rot + 1 + 2 * c.wg);
    } else {
      const int vs = wrap5(z.ks + 1), ks = lng ? z.ks : wrap5(z.ks + 2);
      if (blk & 1) p2_first<64, true>(p, c, z, o, Pa, Pb, ks, vs, 1 + lng, acc, row0);
      else p2_first<32, true>(p, c, z, o, Pa, Pb, ks, vs, 1 + lng, acc, row0);
      z.ks = wrap5(ks + 2);
    }
    PROF(c.wg, 24 + it);
    n += 2 * j + 2;
    int left = 2 * j + lng;
    acc = left != 0;
    if (left == 0) { copy_p(Pa, Pb, p.zero); continue; }
    p2_turn<true>(c, z, o, Pb, Pa, it > 0 ? p2_buf(c.wg, it - 1) : -1, !(blk & 1), 1 + lng);
    while (--left > 0) {
      p2_turn<false>(c, z, o, Pa, Pb);
      if (--left == 0) { copy_p(Pa, Pb, p.zero); break; }
      p2_turn<false>(c, z, o, Pb, Pa);
    }
  }
  {
    if (!acc && nit > 1) p2_epilogue(o, z.e0, z.e1, c, p2_buf(c.wg, nit));
    turn_wait(z.wb, z.wi);
    issue_pv<8>(o, Pa, desc_lo(c.sm + SM_RING, 16384) + z.ks * 2048, acc);
    if (((nit - 1) ^ c.wg) & 1) turn_pass(c, z.ab, z.ai);
    p2_scales(z);
    WG_WAIT(0);
    pin(o);
    release(c, B_P2E + z.ks);
    p2_epilogue(o, z.e0, z.e1, c, p2_buf(c.wg, nit - 1));
    PROF(c.wg, 24 + nit);
  }
}

__device__ __forceinline__ void p2_load_q(const Params& p, const Ctx& c, int it, int w) {
  const int item = p.s.r[c.cl].item[it], h = item >> 3, j = item & 7, b = p2_buf(w, it);
  mbar_expect(c.bar + (B_QF + b) * 8, 16384);
  bulk_load(c.sm + SM_BUF + b * 16384, g_Q + (size_t)(h * 32 + j * 4 + p2_blk(c.rank, w, it)) * 16384, 16384, c.bar + (B_QF + b) * 8, POL(4));
}
__device__ __forceinline__ void wait_p1_free(const Ctx& c, int u1, int s) {
  mbar_wait(c.bar + (B_P1E + 2 * s) * 8, ((u1 - 1 - 2 * s) / 10) & 1);
  mbar_wait(c.bar + (B_P1E + 2 * s + 1) * 8, ((u1 - 2 - 2 * s) / 10) & 1);
}
__device__ __forceinline__ void p2_producer(const Params& p, const Ctx& c, int u1, int rot) {
  const int nit = p.s.r[c.cl].n2;
  int slot = rot, cnt = 0, par = 1, n = 0;
  const int ring = p.s.r[c.cl].ring;
  const uint8_t* pv = nullptr;
  bool pl = false;
  auto load = [&](const uint8_t* src, int expect, uint32_t fb, bool last) {
    if (cnt < 5) {
      if (u1) {
        wait_p1_free(c, u1, slot);
        if (cnt == 0) p2_load_q(p, c, 0, 1);
      }
      cnt++;
    } else {
      if (slot == rot) par ^= 1;
      mbar_wait(c.bar + (B_P2E + slot) * 8, par);
    }
    if (expect) mbar_expect(fb, expect);
    bulk_load_mc(c.sm + SM_RING + slot * 32768 + c.rank * 16384, src, 16384, fb, last ? POL(5) : L2_NORMAL);
    slot = wrap5(slot + 1);
  };
  if (c.phases & 16) flag_wait<true>(F_GATE, 256);
  for (int it = 0; it < nit; it++) {
    const int item = p.s.r[c.cl].item[it], h = item >> 3, j = item & 7;
    if (c.phases & 16) flag_wait<false>(F_HEAD + h, 96);
    if (it == 0) { mbar_wait(c.bar + B_LAD * 8, 0); p2_load_q(p, c, 0, 0); if (!u1) p2_load_q(p, c, 0, 1); }
    for (int t = 2 * j + 1; t >= 0; t--) {
      const uint8_t* k = g_KV + (size_t)((h >= ring ? h - ring : h) * 16 + t) * 32768 + c.rank * 16384;
      const uint32_t fb = c.bar + (B_P2F + (n & 3)) * 8;
      const bool last = (p.s.r[c.cl].last[it] >> (t >> 1)) & 1;
      load(k, pv && t != 2 * j ? 65536 : 32768, fb, last);
      if (pv) load(pv, 0, t != 2 * j ? fb : c.bar + (B_ORD + ((n - 1 - it) & 3)) * 8, pl);
      pl = last;
      pv = k + (size_t)NH * 16 * 32768;
      n++;
    }
  }
  load(pv, 32768, c.bar + (B_P2F + (n & 3)) * 8, pl);
}

__device__ __forceinline__ void p2_storer(const Params& p, const Ctx& c, int sfpar) {
  const int nit = p.s.r[c.cl].n2;
  auto load_q = [&](int it, int w) {
    if (c.phases & 16) flag_wait<false>(F_HEAD + (p.s.r[c.cl].item[it] >> 3), 96);
    p2_load_q(p, c, it, w);
  };
  if (nit > 1) {
    load_q(1, 1); p2_load_q(p, c, 1, 0); }
  for (int i = 0; i < 2 * nit; i++) {
    const int it = i >> 1, w = (it ^ i ^ 1) & 1, b = p2_buf(w, it);
    const int item = p.s.r[c.cl].item[it], h = item >> 3, j = item & 7;
    mbar_wait(c.bar + (B_SF + b) * 8, (sfpar >> b) & 1);
    sfpar ^= 1 << b;
    bulk_store(g_Q + (size_t)(h * 32 + j * 4 + p2_blk(c.rank, w, it)) * 16384, c.sm + SM_BUF + b * 16384, 16384, POL(1));
    BULK_COMMIT();
    BULK_WAIT(0);
    flag_add_rx(F_CTX + j * 64 + h);
    if ((i & 1) && it + 2 < nit) { load_q(it + 2, w); p2_load_q(p, c, it + 2, w ^ 1); }
  }
  release(c, B_DONE);
}

__device__ __forceinline__ int p3_pos(int i, int x) { return i < 4 ? (i + x) & 3 : 4; }
__device__ __forceinline__ void p3_consumer(const Params& p, const Ctx& c, int x) {
  const bool first = p.s.r[c.cl].p3 >= 24;
  const int tile = p.s.r[c.cl].p3 - (first ? 24 : 0), j = tile / 3, nt = tile - 3 * j;
  const int na = first ? 9 : 0, nb = first ? 2 * p.s.nh[tile] : 64 - 2 * p.s.nh[tile];
  const uint32_t ad = desc_lo(c.sm + SM_RING + c.wg * 8192, 16), bd = desc_lo(c.sm + SM_RING + 16384, 4096);
  float acc[96] = {};
  int slot = 0, par = 0, prev = 0;
#pragma unroll 1
  for (int kb = 0; kb < na; kb++) {
    mbar_wait(c.bar + (B_P3F + slot) * 8, par);
    if (kb == 0) PROF(c.wg, 39);
    WG_FENCE();
#pragma unroll
    for (int kk = 0; kk < 4; kk++) wgmma_ss192<1, 1>(acc, ad + p3_pos(slot, x) * 2560 + kk * 128, bd + p3_pos(slot, x) * 2560 + (kk >> 1) * 768 + (kk & 1) * 128, kk != 0 ? 1 : kb != 0);
    WG_COMMIT();
    WG_WAIT(1);
    if (kb > 0) release(c, B_P3E + prev);
    prev = slot;
    if (++slot == 5) { slot = 0; par ^= 1; }
  }
#pragma unroll 1
  for (int kb = na; kb < na + nb; kb++) {
    mbar_wait(c.bar + (B_P3F + slot) * 8, par);
    if (kb == 0) PROF(c.wg, 39);
    WG_FENCE();
#pragma unroll
    for (int kk = 0; kk < 4; kk++) wgmma_ss192<1>(acc, ad + p3_pos(slot, x) * 2560 + kk * 2, bd + p3_pos(slot, x) * 2560 + (kk >> 1) * 768 + (kk & 1) * 128, kk != 0 ? 1 : kb != 0);
    WG_COMMIT();
    WG_WAIT(1);
    if (kb > 0) release(c, B_P3E + prev);
    prev = slot;
    if (++slot == 5) { slot = 0; par ^= 1; }
  }
  WG_WAIT(0);
  pin(acc);
  PROF(c.wg, 40);
  if (first) bar_sync(4 + c.wg, 128);
  mbar_wait(c.bar + B_OUT * 8, 0);
  const int row = (c.lane & 7) + ((c.lane >> 3) & 1) * 8;
  const uint32_t wbase = c.sm + SM_RING + c.wg * 8192 + c.warp * 2048;
  const uint32_t base = wbase + row * 128 + (((c.lane >> 4) ^ (row & 7)) << 4);
#pragma unroll
  for (int i = 0; i < 12; i++) {
    stsm4((base ^ ((i & 3) << 5)) + (i >> 2) * 40960, pack_bf16(acc[8 * i], acc[8 * i + 1]), pack_bf16(acc[8 * i + 2], acc[8 * i + 3]),
          pack_bf16(acc[8 * i + 4], acc[8 * i + 5]), pack_bf16(acc[8 * i + 6], acc[8 * i + 7]));
    if ((i & 3) == 3) {
      FENCE_ASYNC_SMEM();
      __syncwarp();
      const int c0 = nt * 192 + (i >> 2) * 64, c1 = j * 256 + c.rank * 128 + c.wg * 64 + c.warp * 16;
      tma2d_add(&p.map_out, wbase + (i >> 2) * 40960, c0, c1);
    }
  }
  BULK_COMMIT();
  PROF(c.wg, 43);
  BULK_WAIT_READ(0);
  PROF(c.wg, 44);
}

__device__ __forceinline__ void p3_producer(const Params& p, const Ctx& c, int u1, int u2, int rot, int x) {
  const bool first = p.s.r[c.cl].p3 >= 24;
  const int tile = p.s.r[c.cl].p3 - (first ? 24 : 0), j = tile / 3, nt = tile - 3 * j;
  int slot = 0, par = 1, cnt = 0;
  auto wait_free = [&](int s) {
    const int f = wrap5(s + 5 - rot);
    if (f < u2) mbar_wait(c.bar + (B_P2E + s) * 8, ((u2 - 1 - f) / 5) & 1);
    else if (u1) wait_p1_free(c, u1, s);
  };
  asm volatile(ELECT("prefetch.tensormap [%0];") ::"l"(&p.map_o[first]) : "memory");
  asm volatile(ELECT("prefetch.tensormap [%0];") ::"l"(&p.map_out) : "memory");
  const int q1 = first ? p.s.nh[tile] : 32;
  for (int q = first ? -1 : p.s.nh[tile]; q < q1; q++) {
    const int g = q < 0 ? 32 : p.s.p3_order[j][q];
    if (c.phases & 16) flag_wait<false>(F_CTX + j * 64 + g, q < 0 ? 16 : 4);
    const int nk = q < 0 ? 9 : 2, k0 = (q < 0 ? 0 : g * 128) + c.rank * 32;
    const uint8_t* a = q < 0 ? g_oA + (j * 4 + c.rank * 2) * 73728 : g_Q + (size_t)(g * 32 + j * 4 + c.rank * 2) * 16384;
    const CUtensorMap* m = &p.map_o[q < 0];
    for (int i = 0; i < nk; i++) {
      const uint32_t st = c.sm + SM_RING + p3_pos(slot, x) * 40960, fb = c.bar + (B_P3F + slot) * 8;
      if (cnt < 4) { wait_free(p3_pos(cnt, x)); wait_free(p3_pos(cnt, x) + 1); }
      else if (cnt == 4) mbar_wait(c.bar + B_DONE * 8, 0);
      else mbar_wait(c.bar + (B_P3E + slot) * 8, par);
      cnt++;
      mbar_expect(fb, 40960);
      bulk_load(st, a + i * 8192, 8192, fb, POL(3));
      bulk_load(st + 8192, a + (nk + i) * 8192, 8192, fb, POL(3));
      tma3d_mc(st + 16384 + c.rank * 12288, m, 0, k0 + i * 64, nt * 3, fb);
      if (++slot == 5) { slot = 0; par ^= 1; }
    }
  }
}

__device__ __forceinline__ float bf_lo(uint32_t w) { return __uint_as_float(w << 16); }
__device__ __forceinline__ float bf_hi(uint32_t w) { return __uint_as_float(w & 0xffff0000u); }

__device__ __forceinline__ void gate_rows(const Params& p, int row0, int lane) {
  const uint4* x = reinterpret_cast<const uint4*>(p.x + (size_t)(row0 + (lane >> 2)) * DM) + (lane & 3);
  const uint4* w = reinterpret_cast<const uint4*>(p.gate_w) + (lane & 3);
  float a = 0.f;
#pragma unroll 1
  for (int b = 0; b < 3; b++) {
    uint4 u[6];
#pragma unroll
    for (int i = 0; i < 6; i++) u[i] = __ldg(x + (b * 6 + i) * 4);
#pragma unroll
    for (int i = 0; i < 6; i++) {
      const uint4 v = __ldg(w + (b * 6 + i) * 4);
      a = fmaf(bf_lo(u[i].x), bf_lo(v.x), a); a = fmaf(bf_hi(u[i].x), bf_hi(v.x), a);
      a = fmaf(bf_lo(u[i].y), bf_lo(v.y), a); a = fmaf(bf_hi(u[i].y), bf_hi(v.y), a);
      a = fmaf(bf_lo(u[i].z), bf_lo(v.z), a); a = fmaf(bf_hi(u[i].z), bf_hi(v.z), a);
      a = fmaf(bf_lo(u[i].w), bf_lo(v.w), a); a = fmaf(bf_hi(u[i].w), bf_hi(v.w), a);
    }
  }
  a += __shfl_xor_sync(0xffffffffu, a, 1);
  a += __shfl_xor_sync(0xffffffffu, a, 2);
  if ((lane & 3) == 0) g_gate[row0 + (lane >> 2)] = 1.f / (1.f + __expf(-a));
}

__device__ __forceinline__ void lds10(uint32_t (&k)[10], uint32_t a) {
  asm volatile("ld.shared.v2.u32 {%0, %1}, [%10];\nld.shared.v2.u32 {%2, %3}, [%10+8];\nld.shared.v2.u32 {%4, %5}, [%10+16];\n"
               "ld.shared.v2.u32 {%6, %7}, [%10+24];\nld.shared.v2.u32 {%8, %9}, [%10+32];"
               : "=r"(k[0]), "=r"(k[1]), "=r"(k[2]), "=r"(k[3]), "=r"(k[4]), "=r"(k[5]), "=r"(k[6]), "=r"(k[7]), "=r"(k[8]), "=r"(k[9]) : "r"(a));
}
__device__ __forceinline__ void local_attn(const Params& p, const Ctx& c, int rb, int hs) {
  const int lane = c.lane, grp = rb >> 2, par = lane >> 4, i0 = 2 * (lane & 15);
  const uint32_t buf = c.sm + SM_BUF + (c.warp - 2) * 8192, bqk = c.bar + (B_LA + (c.warp - 2) * 2) * 8, bv = bqk + 8;
  const uint32_t mine = buf + 2304 + par * 160 + i0 * 4;
  const bool flags = c.phases & 16;
  auto fetch_qk = [&](int i) {
    if (flags && !(i & 1)) {
      const int q = i >> 1;
      const int tgt = q == 0 ? 24 : q == 3 ? 8 : 12;
      flag_wait<false>(F_QKVA + (grp - (grp > 0 && (rb & 3) == 0 ? par : 0)) * 4 + q, tgt);
    }
    mbar_expect(bqk, 5184);
    tma3d(buf, &p.map_t[0], rb * 32 + 8, 0, 9 * (4 * i + hs), bqk, POL(2));
    tma3d(buf + 2304, &p.map_t[1], rb * 32, 0, 288 + 9 * (4 * i + hs), bqk, POL(2));
  };
  auto fetch_v = [&](int i) { mbar_expect(bv, 2880); tma3d(buf + 5248, &p.map_t[1], rb * 32, 0, 576 + 9 * (4 * i + hs), bv, POL(2)); };
  fetch_qk(0);
  if (flags) flag_wait<true>(F_GATE, 256);
#pragma unroll 1
  for (int q = 0; q < 8; q++) {
    fetch_v(q);
    float a[8], b[8];
#pragma unroll
    for (int w = 0; w < 8; w++) a[w] = b[w] = 0.f;
    mbar_wait(bqk, q & 1);
    PROFB(1 + 2 * q);
#pragma unroll 1
    for (int j = 0; j < 9; j++) {
      uint32_t x, y, k[10];
      asm volatile("ld.shared.v2.u32 {%0, %1}, [%2];" : "=r"(x), "=r"(y) : "r"(buf + lane * 8 + j * 256));
      lds10(k, mine + j * 320);
      const float xl = bf_lo(x), xh = bf_hi(x), yl = bf_lo(y), yh = bf_hi(y);
#pragma unroll
      for (int m = 1; m < 10; m++) {
        const float kl = bf_lo(k[m]), kh = bf_hi(k[m]);
        if (m < 9) a[8 - m] = fmaf(xl, kl, fmaf(xh, kh, a[8 - m]));
        if (m > 1) b[9 - m] = fmaf(yl, kl, fmaf(yh, kh, b[9 - m]));
      }
    }
    __syncwarp();
    if (q < 7) fetch_qk(q + 1);
    constexpr float SC = 0.23570226039551584f * 1.4426950408889634f;
    const float* gp = g_gate + rb * 64 + 2 * i0 + par;
    const float ga = __ldcg(gp), gb = __ldcg(gp + 2);
    float ma = a[0], mb = b[0];
#pragma unroll
    for (int w = 1; w < 8; w++) {
      if (rb == 0) {
        if (i0 < w) a[w] = -INFINITY;
        if (i0 + 1 < w) b[w] = -INFINITY;
      }
      ma = fmaxf(ma, a[w]); mb = fmaxf(mb, b[w]);
    }
    float la = 0.f, lb = 0.f;
#pragma unroll
    for (int w = 0; w < 8; w++) {
      a[w] = ex2((a[w] - ma) * SC); b[w] = ex2((b[w] - mb) * SC);
      la += a[w]; lb += b[w];
    }
    la = __fdividef(ga, la); lb = __fdividef(gb, lb);
#pragma unroll
    for (int w = 0; w < 8; w++) { a[w] *= la; b[w] *= lb; }
    uint8_t* dst = g_oA + rb * 73728 + ((i0 & 2) + par) * 4;
    mbar_wait(bv, q & 1);
#pragma unroll 1
    for (int j = 0; j < 9; j++) {
      uint32_t v[10];
      lds10(v, mine + 2944 + j * 320);
      float a0 = 0.f, a1 = 0.f, b0 = 0.f, b1 = 0.f;
#pragma unroll
      for (int m = 1; m < 10; m++) {
        const float vl = bf_lo(v[m]), vh = bf_hi(v[m]);
        if (m < 9) { a0 = fmaf(a[8 - m], vl, a0); a1 = fmaf(a[8 - m], vh, a1); }
        if (m > 1) { b0 = fmaf(b[9 - m], vl, b0); b1 = fmaf(b[9 - m], vh, b1); }
      }
      const uint32_t wa = pack_bf16(a0, a1), wb = pack_bf16(b0, b1);
      const uint32_t got = __shfl_xor_sync(0xffffffffu, par ? wa : wb, 16);
      const uint32_t r0 = par ? got : wa, r1 = par ? wb : got;
      const int col = 18 * (4 * q + hs) + 2 * j, o = col * 128 + ((((i0 >> 2) ^ col) & 7) << 4);
      *reinterpret_cast<uint32_t*>(dst + o) = __byte_perm(r0, r1, 0x5410);
      *reinterpret_cast<uint32_t*>(dst + ((o + 128) ^ 16)) = __byte_perm(r0, r1, 0x7632);
    }
    __syncwarp();
    PROFB(2 + 2 * q);
  }
  mbar_arrive_one(c.bar + B_LAD * 8);
  flag_add(F_CTX + grp * 64 + 32);
}

__global__ void __cluster_dims__(2, 1, 1) __launch_bounds__(384, 1) fused_kernel(const __grid_constant__ Params p) {
  extern __shared__ uint8_t smem_raw[];
  Ctx c;
  c.sm = ((uint32_t)__cvta_generic_to_shared(smem_raw) + 1023u) & ~1023u;
  c.bar = c.sm + SM_BAR;
  c.lane = threadIdx.x & 31;
  const int wid = __shfl_sync(0xffffffffu, threadIdx.x >> 5, 0);
  if (wid < NPF) asm volatile("prefetch.tensormap [%0];" ::"l"(&p.map_a[0] + wid) : "memory");
  c.wg = wid >> 2;
  c.warp = wid & 3;
  PROF(c.wg, 0);
  PROFG(61);
  c.cl = (blockIdx.x + (wid >> 4)) >> 1;
  c.rank = blockIdx.x & 1;
  c.rbar = mapa(c.bar, c.lane & 1);
  {
    const int w = wid, cnt = (((int)(B_CNT >> (4 * w)) - 1) & 15) + 1;
    if (w < 11) {
#pragma unroll
      for (int i = 0; i < 8; i++) asm volatile("mbarrier.init.shared::cta.b64 [%0], %1;" ::"r"(c.bar + w * 64 + i * 8), "r"(cnt));
    }
    asm volatile("fence.mbarrier_init.release.cluster;" ::: "memory");
  }
  if (c.wg == 2) PROF(2, 56);
  asm volatile("barrier.cluster.arrive.relaxed;" ::: "memory");
  c.phases = p.s.r[c.cl].phases;
  const bool do1 = p.s.r[c.cl].n1 > 0, do2 = p.s.r[c.cl].n2 > 0, do3 = p.s.r[c.cl].p3 != 255;
  if (do1 && c.wg == 2 && c.warp == 0) {
    const int type = p.s.r[c.cl].slab >> 3;
    PROF(2, 57);
    FENCE_ASYNC_SMEM();
    mbar_expect(c.bar + B_P1F * 8, type ? 32768 : 16384);
    tma2d(type ? c.sm + SM_BUF + 32768 : c.sm + SM_RING, &p.map_a[type], type ? 512 : 0, (p.s.r[c.cl].slab & 7) * 256 + c.rank * 128, c.bar + B_P1F * 8);
    PROF(2, 58);
  }
  asm volatile("barrier.cluster.wait.acquire;" ::: "memory");
  if (c.wg == 2) PROF(2, 59);
  if (do1 && c.wg == 2 && c.warp == 0) {
    const int type = p.s.r[c.cl].slab >> 3, tile = p.s.r[c.cl].tile[0];
    if (!type) mbar_expect(c.bar + (B_P1F + 1) * 8, 16384);
    tma2d_mc(c.sm + SM_RING + (1 - type) * 16384 + c.rank * 8192, &p.map_w[type * 2 + (tile >> 5)], (tile & 31) * 128 + c.rank * 64, type ? 512 : 0, c.bar + (B_P1F + 1 - type) * 8);
  }

  if (c.wg < 2) {
    PROF(c.wg, 4);
    asm volatile("setmaxnreg.inc.sync.aligned.u32 224;");
    if (c.wg == 1) {
      if (do1) bar_arrive(ORDER, 256);
      if (c.lane == 0) mbar_arrive(c.bar + B_P2F * 8);
    }
    if (do1) p1_consumer(p, c);
    if (do2) p2_consumer(p, c, p.s.r[c.cl].rot);
    if (do3) p3_consumer(p, c, p.s.r[c.cl].x3);
    PROF(c.wg, 63);
    PROFG(62);
    if (c.lane == 0) mbar_arrive(c.bar + B_FIN * 8);
    __syncwarp();
    cluster_sync();
  } else {
    asm volatile("setmaxnreg.dec.sync.aligned.u32 56;");
    if (c.warp == 0) {
      PROF(2, 60);
      if (do1) p1_producer(p, c);
      if (do2) p2_producer(p, c, p.s.r[c.cl].u1, p.s.r[c.cl].rot);
      if (do3) p3_producer(p, c, p.s.r[c.cl].u1, p.s.r[c.cl].u2, p.s.r[c.cl].rot, p.s.r[c.cl].x3);
    } else if (c.warp == 1) {
      int sfpar = 0;
      if (do1) {
        p1_storer(p, c);
        sfpar = (p.s.r[c.cl].n1 & 1) * 10;
      }
      if (do2) p2_storer(p, c, sfpar);
      else { mbar_wait(c.bar + B_LAD * 8, 0); release(c, B_DONE); }
      if (do3) {
        const int task = p.s.r[c.cl].p3;
        if (task >= 24) {
          const int j = (task - 24) / 3, nt = task - 24 - 3 * j;
          uint4* o = reinterpret_cast<uint4*>(p.out + (size_t)(j * 256 + c.rank * 128 + (c.lane >> 3)) * DM + nt * 192) + (c.lane & 7);
#pragma unroll 4
          for (int r = 0; r < 32; r++) o[r * 288] = o[r * 288 + 8] = o[r * 288 + 16] = make_uint4(0u, 0u, 0u, 0u);
          __syncwarp();
          flag_add(F_OUT + (task - 24) * 2 + c.rank);
        } else if (c.phases & 16) {
          flag_wait<false, 256>(F_OUT + task * 2 + c.rank, 1);
        }
        mbar_arrive_one(c.bar + B_OUT * 8);
      }
    } else {
      const int bw = blockIdx.x * 2 + (c.warp - 2);
      if ((c.phases & 1) && bw < 256) {
        gate_rows(p, bw * 8, c.lane);
        __syncwarp();
        flag_add(F_GATE);
      }
      if (p.s.r[c.cl].bg != 255) local_attn(p, c, p.s.r[c.cl].bg, bw & 3);
      else if (c.lane == 0) mbar_arrive(c.bar + B_LAD * 8);
    }
    __syncwarp();
    bar_sync(3, 128);
    if (c.warp == 0 && (c.phases & 4)) {
      int last = 0;
      if (c.lane == 0) { __threadfence(); last = atomicAdd(g_flags + F_DONE, 1) == 2 * NCL - 1; }
      if (__shfl_sync(0xffffffffu, last, 0)) for (int i = c.lane; i < F_NUM; i += 32) g_flags[i] = 0;
    }
    if (c.warp == 1) mbar_wait(c.bar + B_FIN * 8, 0);
    __syncwarp();
    cluster_sync();
  }
}

static const Sched k_sched = {
  {{0,26,1,33,0,{206,0,0,0,0,0,0,0,0,0,0},{0,0,0,0,0,0,0,0,0,0,0},{0,2,4,6,8,10,12,45,15,16,17,18,19,20,21,22,23,24,25,26,27,28,29,30,31,63,0,0,0,0}},
   {0,24,3,255,1,{184,204,244,0,0,0,0,0,0,0,0},{0,0,0,0,0,0,0,0,0,0,0},{32,34,36,38,40,42,44,14,47,48,49,50,51,52,53,54,55,56,57,58,59,60,61,62,0,0,0,0,0,0}},
   {0,8,7,43,255,{56,66,54,123,153,179,211,0,0,0,0},{0,0,0,0,0,0,0,0,0,0,0},{1,3,5,7,9,11,13,46,0,0,0,0,0,0,0,0,0,0,0,0,0,0,0,0,0,0,0,0,0,0}},
   {0,6,7,21,255,{58,5,91,122,132,201,232,0,0,0,0},{0,0,0,0,0,0,0,0,0,0,0},{33,35,37,39,41,43,0,0,0,0,0,0,0,0,0,0,0,0,0,0,0,0,0,0,0,0,0,0,0,0}},
   {8,17,3,40,2,{96,172,237,0,0,0,0,0,0,0,0},{0,0,0,0,0,0,0,0,0,0,0},{0,32,41,37,34,38,43,35,39,44,40,45,18,20,22,24,26,0,0,0,0,0,0,0,0,0,0,0,0,0}},
   {8,21,2,24,3,{194,221,0,0,0,0,0,0,0,0,0},{0,32,0,0,0,0,0,0,0,0,0},{1,4,6,8,10,11,12,13,14,15,16,17,19,21,23,25,27,28,29,30,31,0,0,0,0,0,0,0,0,0}},
   {8,4,8,255,255,{43,42,69,114,146,189,220,241,0,0,0},{0,0,0,0,0,0,31,3,0,0,0},{2,36,33,42,0,0,0,0,0,0,0,0,0,0,0,0,0,0,0,0,0,0,0,0,0,0,0,0,0,0}},
   {8,4,6,255,255,{26,82,62,116,181,255,0,0,0,0,0},{0,0,0,0,0,255,0,0,0,0,0},{3,5,7,9,0,0,0,0,0,0,0,0,0,0,0,0,0,0,0,0,0,0,0,0,0,0,0,0,0,0}},
   {1,24,1,6,4,{187,0,0,0,0,0,0,0,0,0,0},{0,0,0,0,0,0,0,0,0,0,0},{0,2,4,6,8,10,12,45,15,16,17,18,19,20,21,22,23,24,25,26,27,28,29,30,0,0,0,0,0,0}},
   {1,26,0,22,5,{0,0,0,0,0,0,0,0,0,0,0},{0,0,0,0,0,0,0,0,0,0,0},{32,34,36,38,40,42,44,14,47,48,49,50,51,52,53,54,55,56,57,58,59,60,61,62,31,63,0,0,0,0}},
   {1,8,5,34,255,{64,29,92,190,205,0,0,0,0,0,0},{0,0,0,0,0,0,0,0,0,0,0},{1,3,5,7,9,11,13,46,0,0,0,0,0,0,0,0,0,0,0,0,0,0,0,0,0,0,0,0,0,0}},
   {1,6,5,14,255,{22,89,98,115,142,0,0,0,0,0,0},{0,0,0,0,0,0,0,0,0,0,0},{33,35,37,39,41,43,0,0,0,0,0,0,0,0,0,0,0,0,0,0,0,0,0,0,0,0,0,0,0,0}},
   {9,20,3,255,6,{174,225,251,0,0,0,0,0,0,0,0},{0,0,0,0,0,0,0,0,0,0,0},{0,32,41,37,34,38,43,35,39,44,40,45,18,20,22,24,26,28,30,31,0,0,0,0,0,0,0,0,0,0}},
   {9,18,2,12,7,{120,164,0,0,0,0,0,0,0,0,0},{0,0,0,0,0,0,0,0,0,0,0},{1,4,6,8,10,11,12,13,14,15,16,17,19,21,23,25,27,29,0,0,0,0,0,0,0,0,0,0,0,0}},
   {9,4,6,42,255,{16,50,39,117,149,212,0,0,0,0,0},{0,0,255,0,0,0,0,0,0,0,0},{2,36,33,42,0,0,0,0,0,0,0,0,0,0,0,0,0,0,0,0,0,0,0,0,0,0,0,0,0,0}},
   {9,4,5,255,255,{30,63,129,151,253,0,0,0,0,0,0},{0,255,0,255,0,0,0,0,0,0,0},{3,5,7,9,0,0,0,0,0,0,0,0,0,0,0,0,0,0,0,0,0,0,0,0,0,0,0,0,0,0}},
   {2,26,1,10,8,{224,0,0,0,0,0,0,0,0,0,0},{0,0,0,0,0,0,0,0,0,0,0},{0,34,5,7,9,11,13,14,15,16,17,18,19,20,21,22,23,24,25,26,27,28,29,30,31,63,0,0,0,0}},
   {2,24,1,44,9,{199,0,0,0,0,0,0,0,0,0,0},{255,0,0,0,0,0,0,0,0,0,0},{32,3,37,39,41,43,45,46,47,48,49,50,51,52,53,54,55,56,57,58,59,60,61,62,0,0,0,0,0,0}},
   {2,6,5,255,255,{52,47,131,150,238,0,0,0,0,0,0},{0,255,0,0,96,0,0,0,0,0,0},{1,35,6,8,10,12,0,0,0,0,0,0,0,0,0,0,0,0,0,0,0,0,0,0,0,0,0,0,0,0}},
   {2,2,6,28,255,{1,12,84,125,158,219,0,0,0,0,0},{0,0,0,0,0,0,0,0,0,0,0},{33,4,0,0,0,0,0,0,0,0,0,0,0,0,0,0,0,0,0,0,0,0,0,0,0,0,0,0,0,0}},
   {2,6,8,255,255,{0,41,20,90,108,138,171,239,0,0,0},{0,0,31,0,0,0,0,128,0,0,0},{2,36,38,40,42,44,0,0,0,0,0,0,0,0,0,0,0,0,0,0,0,0,0,0,0,0,0,0,0,0}},
   {10,18,2,4,10,{136,156,0,0,0,0,0,0,0,0,0},{0,0,0,0,0,0,0,0,0,0,0},{0,32,41,37,34,38,43,35,39,44,40,45,18,20,22,24,26,28,0,0,0,0,0,0,0,0,0,0,0,0}},
   {10,20,2,2,11,{160,186,0,0,0,0,0,0,0,0,0},{0,0,0,0,0,0,0,0,0,0,0},{1,4,6,8,10,11,12,13,14,15,16,17,19,21,23,25,27,29,30,31,0,0,0,0,0,0,0,0,0,0}},
   {10,4,8,255,255,{9,67,51,93,139,177,197,243,0,0,0},{0,0,0,0,0,0,0,15,0,0,0},{2,36,33,42,0,0,0,0,0,0,0,0,0,0,0,0,0,0,0,0,0,0,0,0,0,0,0,0,0,0}},
   {10,4,5,255,255,{15,85,127,209,254,0,0,0,0,0,0},{255,0,255,0,0,0,0,0,0,0,0},{3,5,7,9,0,0,0,0,0,0,0,0,0,0,0,0,0,0,0,0,0,0,0,0,0,0,0,0,0,0}},
   {3,26,1,5,12,{216,0,0,0,0,0,0,0,0,0,0},{0,0,0,0,0,0,0,0,0,0,0},{0,2,4,6,8,10,43,13,46,16,17,18,19,20,21,22,23,24,25,26,27,28,29,30,31,63,0,0,0,0}},
   {3,24,2,255,13,{223,242,0,0,0,0,0,0,0,0,0},{192,0,0,0,0,0,0,0,0,0,0},{32,34,36,38,40,42,12,45,15,48,49,50,51,52,53,54,55,56,57,58,59,60,61,62,0,0,0,0,0,0}},
   {3,5,6,19,255,{32,13,78,121,137,157,0,0,0,0,0},{0,0,0,0,0,0,0,0,0,0,0},{1,3,5,7,9,0,0,0,0,0,0,0,0,0,0,0,0,0,0,0,0,0,0,0,0,0,0,0,0,0}},
   {3,9,5,27,255,{80,37,100,124,231,0,0,0,0,0,0},{0,0,0,0,128,0,0,0,0,0,0},{33,35,37,39,41,11,44,14,47,0,0,0,0,0,0,0,0,0,0,0,0,0,0,0,0,0,0,0,0,0}},
   {11,19,3,37,14,{154,210,214,0,0,0,0,0,0,0,0},{0,0,127,0,0,0,0,0,0,0,0},{0,32,41,37,34,38,43,35,39,44,40,45,18,20,22,24,26,28,30,0,0,0,0,0,0,0,0,0,0,0}},
   {11,19,1,8,15,{173,0,0,0,0,0,0,0,0,0,0},{0,0,0,0,0,0,0,0,0,0,0},{1,4,6,8,10,11,12,13,14,15,16,17,19,21,23,25,27,29,31,0,0,0,0,0,0,0,0,0,0,0}},
   {11,4,5,11,255,{3,35,83,103,227,0,0,0,0,0,0},{0,0,0,255,0,0,0,0,0,0,0},{2,36,33,42,0,0,0,0,0,0,0,0,0,0,0,0,0,0,0,0,0,0,0,0,0,0,0,0,0,0}},
   {11,4,6,47,255,{8,17,6,94,140,207,0,0,0,0,0},{0,0,127,0,0,255,0,0,0,0,0},{3,5,7,9,0,0,0,0,0,0,0,0,0,0,0,0,0,0,0,0,0,0,0,0,0,0,0,0,0,0}},
   {4,24,2,41,16,{180,252,0,0,0,0,0,0,0,0,0},{0,0,0,0,0,0,0,0,0,0,0},{0,2,4,6,8,10,43,13,46,16,17,18,19,20,21,22,23,24,25,26,27,28,29,30,0,0,0,0,0,0}},
   {4,26,0,3,17,{0,0,0,0,0,0,0,0,0,0,0},{0,0,0,0,0,0,0,0,0,0,0},{32,34,36,38,40,42,12,45,15,48,49,50,51,52,53,54,55,56,57,58,59,60,61,62,31,63,0,0,0,0}},
   {4,5,4,45,255,{23,79,162,183,0,0,0,0,0,0,0},{224,255,0,128,0,0,0,0,0,0,0},{1,3,5,7,9,0,0,0,0,0,0,0,0,0,0,0,0,0,0,0,0,0,0,0,0,0,0,0,0,0}},
   {4,9,7,255,255,{88,45,97,118,222,233,250,0,0,0,0},{0,0,0,0,0,0,0,0,0,0,0},{33,35,37,39,41,11,44,14,47,0,0,0,0,0,0,0,0,0,0,0,0,0,0,0,0,0,0,0,0,0}},
   {12,18,3,25,18,{128,170,191,0,0,0,0,0,0,0,0},{0,0,255,0,0,0,0,0,0,0,0},{0,32,41,37,34,38,43,35,39,44,40,45,18,20,22,24,26,28,0,0,0,0,0,0,0,0,0,0,0,0}},
   {12,20,1,31,19,{175,0,0,0,0,0,0,0,0,0,0},{255,0,0,0,0,0,0,0,0,0,0},{1,4,6,8,10,11,12,13,14,15,16,17,19,21,23,25,27,29,30,31,0,0,0,0,0,0,0,0,0,0}},
   {12,4,8,255,255,{10,74,57,75,113,119,195,245,0,0,0},{0,0,0,0,0,255,0,63,0,0,0},{2,36,33,42,0,0,0,0,0,0,0,0,0,0,0,0,0,0,0,0,0,0,0,0,0,0,0,0,0,0}},
   {12,4,6,255,255,{27,44,86,133,196,236,0,0,0,0,0},{0,0,0,0,0,31,0,0,0,0,0},{3,5,7,9,0,0,0,0,0,0,0,0,0,0,0,0,0,0,0,0,0,0,0,0,0,0,0,0,0,0}},
   {5,25,0,23,20,{0,0,0,0,0,0,0,0,0,0,0},{0,0,0,0,0,0,0,0,0,0,0},{0,34,5,39,10,12,13,14,15,16,17,18,19,20,21,22,23,24,25,26,27,28,29,30,31,0,0,0,0,0}},
   {5,25,0,17,21,{0,0,0,0,0,0,0,0,0,0,0},{0,0,0,0,0,0,0,0,0,0,0},{32,3,37,8,42,44,45,46,47,48,49,50,51,52,53,54,55,56,57,58,59,60,61,62,63,0,0,0,0,0}},
   {5,5,5,1,255,{21,61,106,130,148,0,0,0,0,0,0},{0,0,0,0,0,0,0,0,0,0,0},{1,35,6,40,11,0,0,0,0,0,0,0,0,0,0,0,0,0,0,0,0,0,0,0,0,0,0,0,0,0}},
   {5,4,5,16,255,{24,11,53,101,165,0,0,0,0,0,0},{0,0,0,0,0,0,0,0,0,0,0},{33,4,38,9,0,0,0,0,0,0,0,0,0,0,0,0,0,0,0,0,0,0,0,0,0,0,0,0,0,0}},
   {5,5,5,38,255,{19,31,105,126,198,0,0,0,0,0,0},{0,255,0,0,0,0,0,0,0,0,0},{2,36,7,41,43,0,0,0,0,0,0,0,0,0,0,0,0,0,0,0,0,0,0,0,0,0,0,0,0,0}},
   {13,17,6,255,22,{112,145,185,193,202,229,0,0,0,0,0},{0,0,0,0,0,63,0,0,0,0,0},{0,32,41,37,34,38,43,35,39,44,40,45,18,20,22,24,26,0,0,0,0,0,0,0,0,0,0,0,0,0}},
   {13,21,2,46,23,{178,213,0,0,0,0,0,0,0,0,0},{0,0,0,0,0,0,0,0,0,0,0},{1,4,6,8,10,11,12,13,14,15,16,17,19,21,23,25,27,28,29,30,31,0,0,0,0,0,0,0,0,0}},
   {13,4,4,15,255,{7,81,95,147,0,0,0,0,0,0,0},{128,0,255,0,0,0,0,0,0,0,0},{2,36,33,42,0,0,0,0,0,0,0,0,0,0,0,0,0,0,0,0,0,0,0,0,0,0,0,0,0,0}},
   {13,4,6,36,255,{38,65,70,141,203,234,0,0,0,0,0},{0,0,0,0,0,0,0,0,0,0,0},{3,5,7,9,0,0,0,0,0,0,0,0,0,0,0,0,0,0,0,0,0,0,0,0,0,0,0,0,0,0}},
   {6,24,2,7,24,{218,208,0,0,0,0,0,0,0,0,0},{0,0,0,0,0,0,0,0,0,0,0},{0,2,4,6,8,10,12,14,15,16,17,18,19,20,21,22,23,24,25,26,27,28,29,30,0,0,0,0,0,0}},
   {6,26,1,39,25,{246,0,0,0,0,0,0,0,0,0,0},{0,0,0,0,0,0,0,0,0,0,0},{32,34,36,38,40,42,44,46,47,48,49,50,51,52,53,54,55,56,57,58,59,60,61,62,31,63,0,0,0,0}},
   {6,7,4,13,255,{60,77,110,168,0,0,0,0,0,0,0},{0,0,0,0,0,0,0,0,0,0,0},{1,3,5,7,9,11,13,0,0,0,0,0,0,0,0,0,0,0,0,0,0,0,0,0,0,0,0,0,0,0}},
   {6,7,6,35,255,{25,46,102,169,166,240,0,0,0,0,0},{0,0,0,0,0,0,0,0,0,0,0},{33,35,37,39,41,43,45,0,0,0,0,0,0,0,0,0,0,0,0,0,0,0,0,0,0,0,0,0,0,0}},
   {14,17,5,255,26,{104,155,188,235,248,0,0,0,0,0,0},{0,0,0,0,0,0,0,0,0,0,0},{0,32,41,37,34,38,43,35,39,44,40,45,18,20,22,24,26,0,0,0,0,0,0,0,0,0,0,0,0,0}},
   {14,21,2,18,27,{176,200,0,0,0,0,0,0,0,0,0},{0,0,0,0,0,0,0,0,0,0,0},{1,4,6,8,10,11,12,13,14,15,16,17,19,21,23,25,27,28,29,30,31,0,0,0,0,0,0,0,0,0}},
   {14,4,5,20,255,{18,49,34,55,134,0,0,0,0,0,0},{0,0,0,255,0,0,0,0,0,0,0},{2,36,33,42,0,0,0,0,0,0,0,0,0,0,0,0,0,0,0,0,0,0,0,0,0,0,0,0,0,0}},
   {14,4,6,255,255,{40,36,73,71,135,230,0,0,0,0,0},{0,0,0,255,255,64,0,0,0,0,0},{3,5,7,9,0,0,0,0,0,0,0,0,0,0,0,0,0,0,0,0,0,0,0,0,0,0,0,0,0,0}},
   {7,26,0,0,28,{0,0,0,0,0,0,0,0,0,0,0},{0,0,0,0,0,0,0,0,0,0,0},{0,2,4,6,8,10,12,45,15,16,17,18,19,20,21,22,23,24,25,26,27,28,29,30,31,63,0,0,0,0}},
   {7,24,1,32,29,{182,0,0,0,0,0,0,0,0,0,0},{127,0,0,0,0,0,0,0,0,0,0},{32,34,36,38,40,42,44,14,47,48,49,50,51,52,53,54,55,56,57,58,59,60,61,62,0,0,0,0,0,0}},
   {7,8,5,9,255,{72,28,99,111,192,0,0,0,0,0,0},{0,0,0,255,0,0,0,0,0,0,0},{1,3,5,7,9,11,13,46,0,0,0,0,0,0,0,0,0,0,0,0,0,0,0,0,0,0,0,0,0,0}},
   {7,6,8,26,255,{48,33,2,76,107,143,217,226,0,0,0},{0,0,0,0,0,255,0,0,0,0,0},{33,35,37,39,41,43,0,0,0,0,0,0,0,0,0,0,0,0,0,0,0,0,0,0,0,0,0,0,0,0}},
   {15,19,2,30,30,{144,167,0,0,0,0,0,0,0,0,0},{0,255,0,0,0,0,0,0,0,0,0},{0,32,41,37,34,38,43,35,39,44,40,45,18,20,22,24,26,28,30,0,0,0,0,0,0,0,0,0,0,0}},
   {15,19,3,255,31,{152,163,247,0,0,0,0,0,0,0,0},{0,0,192,0,0,0,0,0,0,0,0},{1,4,6,8,10,11,12,13,14,15,16,17,19,21,23,25,27,29,31,0,0,0,0,0,0,0,0,0,0,0}},
   {15,4,5,29,255,{14,68,109,161,215,0,0,0,0,0,0},{0,0,0,0,128,0,0,0,0,0,0},{2,36,33,42,0,0,0,0,0,0,0,0,0,0,0,0,0,0,0,0,0,0,0,0,0,0,0,0,0,0}},
   {15,4,6,255,255,{4,59,87,159,228,249,0,0,0,0,0},{0,0,255,255,0,3,0,0,0,0,0},{3,5,7,9,0,0,0,0,0,0,0,0,0,0,0,0,0,0,0,0,0,0,0,0,0,0,0,0,0,0}}},
  32, {5,6,7,5,6,8,10,10,9,4,8,9,6,1,8,4,7,2,5,9,6,10,5,2},
  {{1,2,3,4,5,0,6,7,8,9,10,11,12,13,14,15,16,17,18,19,21,20,24,22,23,25,27,28,26,29,30,31},
   {0,1,2,3,4,5,6,7,9,8,11,10,12,14,13,15,16,17,18,21,19,20,23,22,24,25,26,27,28,29,30,31},
   {1,2,3,7,6,9,10,0,5,8,4,11,12,13,14,15,16,18,20,17,21,19,23,22,24,27,26,25,28,29,30,31},
   {0,2,3,5,1,8,4,7,6,9,10,12,11,13,14,16,15,17,18,19,20,28,21,23,22,24,25,26,27,29,30,31},
   {0,6,4,7,1,2,5,3,9,10,8,11,12,13,14,15,16,19,20,18,17,21,22,23,25,24,26,31,27,28,30,29},
   {2,1,0,3,4,5,6,7,9,8,10,11,12,15,13,14,16,17,20,21,19,22,18,23,25,24,29,26,27,31,30,28},
   {1,3,4,2,0,5,7,6,9,8,10,11,12,13,14,15,23,16,17,18,19,21,22,20,27,24,25,30,26,31,28,29},
   {0,1,2,3,4,5,7,6,8,9,10,11,12,13,14,15,17,16,18,19,20,21,22,26,24,23,28,27,25,30,29,31}}};

typedef CUresult (*EncodeFn)(CUtensorMap*, CUtensorMapDataType, cuuint32_t, void*, const cuuint64_t*, const cuuint64_t*, const cuuint32_t*,
                             const cuuint32_t*, CUtensorMapInterleave, CUtensorMapSwizzle, CUtensorMapL2promotion, CUtensorMapFloatOOBfill);

void make_map2(EncodeFn enc, CUtensorMap* m, const void* ptr, int rows, int cols, int box_rows) {
  cuuint64_t dim[2] = {(cuuint64_t)cols, (cuuint64_t)rows}, str[1] = {(cuuint64_t)cols * 2};
  cuuint32_t box[2] = {64, (cuuint32_t)box_rows}, es[2] = {1, 1};
  enc(m, CU_TENSOR_MAP_DATA_TYPE_BFLOAT16, 2, const_cast<void*>(ptr), dim, str, box, es, CU_TENSOR_MAP_INTERLEAVE_NONE, CU_TENSOR_MAP_SWIZZLE_128B,
      CU_TENSOR_MAP_L2_PROMOTION_L2_128B, CU_TENSOR_MAP_FLOAT_OOB_FILL_NONE);
}
void make_map3(EncodeFn enc, CUtensorMap* m, const void* ptr, int rows) {
  cuuint64_t dim[3] = {64, (cuuint64_t)rows, 9}, str[2] = {DM * 2, 128};
  cuuint32_t box[3] = {64, 32, 3}, es[3] = {1, 1, 1};
  enc(m, CU_TENSOR_MAP_DATA_TYPE_BFLOAT16, 3, const_cast<void*>(ptr), dim, str, box, es, CU_TENSOR_MAP_INTERLEAVE_NONE, CU_TENSOR_MAP_SWIZZLE_128B,
      CU_TENSOR_MAP_L2_PROMOTION_L2_128B, CU_TENSOR_MAP_FLOAT_OOB_FILL_NONE);
}

void make_map_t(EncodeFn enc, CUtensorMap* m, void* ptr, int width, int cols) {
  cuuint64_t dim[3] = {TP / 2, 2, 864}, str[2] = {TP * 2, TP * 4};
  cuuint32_t box[3] = {(cuuint32_t)width, 2, (cuuint32_t)cols}, es[3] = {1, 1, 1};
  enc(m, CU_TENSOR_MAP_DATA_TYPE_UINT32, 3, ptr, dim, str, box, es, CU_TENSOR_MAP_INTERLEAVE_NONE, cols == 64 ? CU_TENSOR_MAP_SWIZZLE_128B : CU_TENSOR_MAP_SWIZZLE_NONE,
      CU_TENSOR_MAP_L2_PROMOTION_NONE, CU_TENSOR_MAP_FLOAT_OOB_FILL_NONE);
}

int g_mode = -1;

}

extern "C" void kernel_launch(void* const* d_in, const int* in_sizes, int n_in, void* d_out, int out_size) {
  static EncodeFn enc = nullptr;
  static void* t_ptr = nullptr;
  if (!enc) {
    void* fn = nullptr;
    cudaDriverEntryPointQueryResult st;
    cudaGetDriverEntryPoint("cuTensorMapEncodeTiled", &fn, cudaEnableDefault, &st);
    enc = (EncodeFn)fn;
    cudaGetSymbolAddress(&t_ptr, g_T);
    cudaFuncSetAttribute(fused_kernel, cudaFuncAttributeMaxDynamicSharedMemorySize, SMEM_BYTES);
    if (g_mode < 0) {
      cudaLaunchConfig_t cfg = {};
      cfg.gridDim = dim3(2 * NCL); cfg.blockDim = dim3(384); cfg.dynamicSmemBytes = SMEM_BYTES;
      cudaLaunchAttribute at; at.id = cudaLaunchAttributeClusterDimension;
      at.val.clusterDim.x = 2; at.val.clusterDim.y = 1; at.val.clusterDim.z = 1;
      cfg.attrs = &at; cfg.numAttrs = 1;
      int nc = 0;
      g_mode = (cudaOccupancyMaxActiveClusters(&nc, fused_kernel, &cfg) == cudaSuccess && nc >= NCL) ? 1 : 0;
      (void)cudaGetLastError();
    }
  }
  Params p;
  make_map2(enc, &p.map_a[0], d_in[4], SEQ, DC, 128);
  make_map2(enc, &p.map_a[1], d_in[0], SEQ, DM, 128);
  make_map2(enc, &p.map_w[0], d_in[6], DC, 4096, 64);
  make_map2(enc, &p.map_w[1], d_in[7], DC, 4096, 64);
  make_map2(enc, &p.map_w[2], d_in[5], DM, 4096, 64);
  make_map2(enc, &p.map_w[3], d_in[1], DM, 1728, 64);
  make_map3(enc, &p.map_o[0], d_in[8], 4096);
  make_map3(enc, &p.map_o[1], d_in[2], DM);
  make_map_t(enc, &p.map_t[0], t_ptr, 32, 9);
  make_map_t(enc, &p.map_t[1], t_ptr, 40, 9);
  make_map_t(enc, &p.map_t[2], t_ptr, 32, 64);
  p.x = (const __nv_bfloat16*)d_in[0];
  p.gate_w = (const __nv_bfloat16*)d_in[9];
  make_map2(enc, &p.map_out, d_out, SEQ, DM, 16);
  p.out = (__nv_bfloat16*)d_out;
  p.zero = 0;
  auto launch = [&](int phases) {
    p.s = k_sched;
    for (int i = 0; i < NCL; i++) {
      Rec& r = p.s.r[i];
      if (!(phases & 1)) r.n1 = 0;
      if (!(phases & 2)) r.n2 = 0;
      if (!(phases & (r.p3 < 24 ? 4 : 32))) r.p3 = 255;
      if (!(phases & 8)) r.bg = 255;
      const int u1 = r.n1 ? 8 + r.n1 * (8 + (r.slab >> 3)) : 0;
      int u2 = 0;
      for (int k = 0; k < r.n2; k++) u2 += 4 * (r.item[k] & 7) + 4;
      r.u1 = (uint8_t)u1; r.u2 = (uint8_t)u2;
      r.rot = (uint8_t)(((u1 % 10 + 1) >> 1) % 5);
      r.x3 = (uint8_t)((r.rot + u2) % 5 & 3);
      r.ring = (phases & 16) ? p.s.ring : 32;
      r.phases = (uint8_t)phases;
    }
    fused_kernel<<<2 * NCL, 384, SMEM_BYTES>>>(p);
  };
  if (g_mode == 1) launch(63);
  else { launch(1); launch(10); launch(32); launch(4); }
}
```

```cpp
#include <cuda_runtime.h>
#include <cuda_bf16.h>
#include <cuda.h>
#include <stdint.h>

namespace {

constexpr int SEQ = 2048, DM = 576, DC = 512, NH = 32;
constexpr int NCL = 66;
constexpr uint32_t DESC_HI = 0x40000040u;

constexpr int SM_RING = 0;
constexpr int SM_BUF = 163840;
constexpr int SM_BAR = 229376;
constexpr int B_P1E = 0, B_P2E = 10, B_P3E = 15, B_P2F = 24, B_SF = 32, B_ORD = 36, B_LAD = 40, B_DONE = 41, B_FIN = 48;
constexpr int B_P3F = 56, B_OUT = 61, B_P1F = 64, B_SE = 74, B_QF = 80, B_LA = 84, B_NUM = 88;
constexpr uint64_t B_CNT = 0x11118245000ull;
constexpr int SMEM_BYTES = SM_BAR + B_NUM * 8 + 1024;

constexpr int F_HEAD = 0;
constexpr int F_QKVA = 32;
constexpr int F_GATE = 64;
constexpr int F_DONE = 65;
constexpr int F_CTX = 96;
constexpr int F_OUT = 96 + 8 * 64;
constexpr int F_NUM = F_OUT + 48;

struct Rec {
  uint8_t slab;
  uint8_t n1, n2;
  uint8_t p3;
  uint8_t bg;
  uint8_t item[11];
  uint8_t last[11];
  uint8_t tile[31];
  uint8_t ring;
  uint8_t u1, u2;
  uint8_t rot, x3;
  uint8_t phases;
};
struct Sched {
  Rec r[NCL];
  uint8_t ring;
  uint8_t nh[24];
  uint8_t p3_order[8][32];
};

struct Params {
  CUtensorMap map_a[2];
  CUtensorMap map_w[4];
  CUtensorMap map_o[2];
  CUtensorMap map_t[3];
  CUtensorMap map_out;
  const __nv_bfloat16* x;
  const __nv_bfloat16* gate_w;
  __nv_bfloat16* out;
  int zero;
  alignas(64) Sched s;
};

__device__ __align__(1024) uint8_t g_Q[NH * 32 * 16384];
__device__ __align__(1024) uint8_t g_KV[2 * NH * 16 * 32768];
__device__ __align__(1024) uint8_t g_oA[32 * 576 * 128];
constexpr int TP = SEQ + 16;
__device__ __align__(1024) uint32_t g_T[864 * TP];
__device__ float g_gate[SEQ];
__device__ int g_flags[F_NUM];

__device__ __forceinline__ void mbar_arrive(uint32_t b) { asm volatile("mbarrier.arrive.shared::cta.b64 _, [%0];" ::"r"(b) : "memory"); }
__device__ __forceinline__ void mbar_arrive_cl(uint32_t b, int cnt) {
  asm volatile("mbarrier.arrive.shared::cluster.b64 _, [%0], %1;" ::"r"(b), "r"(cnt) : "memory");
}
__device__ __forceinline__ void mbar_wait(uint32_t b, int par) {
  asm volatile(
      "{\n.reg .pred p;\n.reg .u32 c;\n"
      "mbarrier.try_wait.parity.shared::cta.b64 p, [%0], %1;\n@p bra DN;\nmov.u32 c, 0;\n"
      "LP:\nmbarrier.try_wait.parity.shared::cta.b64 p, [%0], %1;\n@p bra DN;\n"
      "add.u32 c, c, 1;\nsetp.lt.u32 p, c, 4000000;\n@p bra LP;\ntrap;\nDN:\n}" ::"r"(b), "r"(par) : "memory");
}
__device__ __forceinline__ uint32_t mapa(uint32_t a, uint32_t cta) {
  uint32_t r; asm("mapa.shared::cluster.u32 %0, %1, %2;" : "=r"(r) : "r"(a), "r"(cta)); return r;
}
#define ELECT(ins) "{\n.reg .pred e;\nelect.sync _|e, 0xffffffff;\n@e " ins "\n}"
__device__ __forceinline__ void mbar_expect(uint32_t b, int bytes) {
  asm volatile(ELECT("mbarrier.arrive.expect_tx.shared::cta.b64 _, [%0], %1;") ::"r"(b), "r"(bytes) : "memory");
}
__device__ __forceinline__ void mbar_arrive_one(uint32_t b) { asm volatile(ELECT("mbarrier.arrive.shared::cta.b64 _, [%0];") ::"r"(b) : "memory"); }
constexpr uint64_t L2_NORMAL = 0x1000000000000000ull, L2_FIRST = 0x12F0000000000000ull;
__device__ __forceinline__ void bulk_load(uint32_t dst, const void* src, int bytes, uint32_t bar, uint64_t pol = L2_NORMAL) {
  asm volatile(ELECT("cp.async.bulk.shared::cluster.global.mbarrier::complete_tx::bytes.L2::cache_hint [%0], [%1], %2, [%3], %4;") ::"r"(dst), "l"(src), "r"(bytes), "r"(bar), "l"(pol) : "memory");
}
__device__ __forceinline__ void bulk_load_mc(uint32_t dst, const void* src, int bytes, uint32_t bar, uint64_t pol = L2_NORMAL) {
  asm volatile(ELECT("cp.async.bulk.shared::cluster.global.mbarrier::complete_tx::bytes.multicast::cluster.L2::cache_hint [%0], [%1], %2, [%3], %4, %5;") ::"r"(dst), "l"(src), "r"(bytes), "r"(bar), "h"((uint16_t)3), "l"(pol) : "memory");
}
__device__ __forceinline__ void bulk_store(void* dst, uint32_t src, int bytes, uint64_t pol = L2_NORMAL) {
  asm volatile(ELECT("cp.async.bulk.global.shared::cta.bulk_group.L2::cache_hint [%0], [%1], %2, %3;") ::"l"(dst), "r"(src), "r"(bytes), "l"(pol) : "memory");
}
__device__ __forceinline__ void tma2d(uint32_t dst, const CUtensorMap* m, int c0, int c1, uint32_t bar, uint64_t pol = L2_NORMAL) {
  asm volatile(ELECT("cp.async.bulk.tensor.2d.shared::cluster.global.mbarrier::complete_tx::bytes.L2::cache_hint [%0], [%1, {%3, %4}], [%2], %5;") ::"r"(dst), "l"(m), "r"(bar), "r"(c0), "r"(c1), "l"(pol) : "memory");
}
__device__ __forceinline__ void tma2d_mc(uint32_t dst, const CUtensorMap* m, int c0, int c1, uint32_t bar, uint64_t pol = L2_NORMAL) {
  asm volatile(ELECT("cp.async.bulk.tensor.2d.shared::cluster.global.mbarrier::complete_tx::bytes.multicast::cluster.L2::cache_hint [%0], [%1, {%3, %4}], [%2], %5, %6;") ::"r"(dst), "l"(m), "r"(bar), "r"(c0), "r"(c1), "h"((uint16_t)3), "l"(pol) : "memory");
}
__device__ __forceinline__ void tma3d(uint32_t dst, const CUtensorMap* m, int c0, int c1, int c2, uint32_t bar, uint64_t pol = L2_NORMAL) {
  asm volatile(ELECT("cp.async.bulk.tensor.3d.shared::cluster.global.mbarrier::complete_tx::bytes.L2::cache_hint [%0], [%1, {%3, %4, %5}], [%2], %6;") ::"r"(dst), "l"(m), "r"(bar), "r"(c0), "r"(c1), "r"(c2), "l"(pol) : "memory");
}
__device__ __forceinline__ void tma3d_mc(uint32_t dst, const CUtensorMap* m, int c0, int c1, int c2, uint32_t bar, uint64_t pol = L2_NORMAL) {
  asm volatile(ELECT("cp.async.bulk.tensor.3d.shared::cluster.global.mbarrier::complete_tx::bytes.multicast::cluster.L2::cache_hint [%0], [%1, {%3, %4, %5}], [%2], %6, %7;") ::"r"(dst), "l"(m), "r"(bar), "r"(c0), "r"(c1), "r"(c2), "h"((uint16_t)3), "l"(pol) : "memory");
}
__device__ __forceinline__ void tma2d_add(const CUtensorMap* m, uint32_t src, int c0, int c1) {
  asm volatile(ELECT("cp.reduce.async.bulk.tensor.2d.global.shared::cta.add.bulk_group [%0, {%2, %3}], [%1];") ::"l"(m), "r"(src), "r"(c0), "r"(c1) : "memory");
}
__device__ __forceinline__ void tma3d_store(const CUtensorMap* m, uint32_t src, int c0, int c1, int c2, uint64_t pol = L2_NORMAL) {
  asm volatile(ELECT("cp.async.bulk.tensor.3d.global.shared::cta.bulk_group.L2::cache_hint [%0, {%2, %3, %4}], [%1], %5;") ::"l"(m), "r"(src), "r"(c0), "r"(c1), "r"(c2), "l"(pol) : "memory");
}
__device__ __forceinline__ void tma2d_prefetch(const CUtensorMap* m, int c0, int c1, uint64_t pol = L2_NORMAL) {
  asm volatile(ELECT("cp.async.bulk.prefetch.tensor.2d.L2.global.L2::cache_hint [%0, {%1, %2}], %3;") ::"l"(m), "r"(c0), "r"(c1), "l"(pol) : "memory");
}
#define HINT 62
#define POL(bit) ((HINT >> (bit)) & 1 ? L2_FIRST : L2_NORMAL)
#define BULK_COMMIT() asm volatile("cp.async.bulk.commit_group;" ::: "memory")
#define BULK_WAIT(n) asm volatile("cp.async.bulk.wait_group %0;" ::"n"(n) : "memory")
#define BULK_WAIT_READ(n) asm volatile("cp.async.bulk.wait_group.read %0;" ::"n"(n) : "memory")
#define FENCE_ASYNC_SMEM() asm volatile("fence.proxy.async.shared::cta;" ::: "memory")
#define FENCE_ASYNC_ALL() asm volatile("fence.proxy.async;" ::: "memory")
#define WG_FENCE() asm volatile("wgmma.fence.sync.aligned;" ::: "memory")
#define WG_COMMIT() asm volatile("wgmma.commit_group.sync.aligned;" ::: "memory")
#define WG_WAIT(n) asm volatile("wgmma.wait_group.sync.aligned %0;" ::"n"(n) : "memory")
__device__ __forceinline__ void bar_sync(int id, int n) { asm volatile("bar.sync %0, %1;" ::"r"(id), "r"(n) : "memory"); }
__device__ __forceinline__ void bar_arrive(int id, int n) { asm volatile("bar.arrive %0, %1;" ::"r"(id), "r"(n) : "memory"); }
__device__ __forceinline__ void cluster_sync() {
  asm volatile("barrier.cluster.arrive.relaxed;\nbarrier.cluster.wait.acquire;" ::: "memory");
}
template <int N> __device__ __forceinline__ void pin(float (&r)[N]) {
#pragma unroll
  for (int i = 0; i < N; i++) asm volatile("" : "+f"(r[i])::"memory");
}
template <int N> __device__ __forceinline__ void pin(uint32_t (&r)[N]) {
#pragma unroll
  for (int i = 0; i < N; i++) asm volatile("" : "+r"(r[i])::"memory");
}
__device__ __forceinline__ uint32_t pack_bf16(float lo, float hi) {
  uint32_t r; asm("cvt.rn.bf16x2.f32 %0, %1, %2;" : "=r"(r) : "f"(hi), "f"(lo)); return r;
}
__device__ __forceinline__ float ex2(float x) { float r; asm("ex2.approx.ftz.f32 %0, %1;" : "=f"(r) : "f"(x)); return r; }
__device__ __forceinline__ void ldsm4(uint32_t a, uint32_t& r0, uint32_t& r1, uint32_t& r2, uint32_t& r3) {
  asm volatile("ldmatrix.sync.aligned.m8n8.x4.shared.b16 {%0,%1,%2,%3}, [%4];" : "=r"(r0), "=r"(r1), "=r"(r2), "=r"(r3) : "r"(a) : "memory");
}
__device__ __forceinline__ void stsm4(uint32_t a, uint32_t r0, uint32_t r1, uint32_t r2, uint32_t r3) {
  asm volatile("stmatrix.sync.aligned.m8n8.x4.shared.b16 [%0], {%1,%2,%3,%4};" ::"r"(a), "r"(r0), "r"(r1), "r"(r2), "r"(r3) : "memory");
}
__device__ __forceinline__ void flag_add(int idx) {
  asm volatile(ELECT("red.release.gpu.global.add.s32 [%0], 1;") ::"l"(g_flags + idx) : "memory");
}
__device__ __forceinline__ void flag_add_rx(int idx) {
  asm volatile(ELECT("red.relaxed.gpu.global.add.s32 [%0], 1;") ::"l"(g_flags + idx) : "memory");
}
template <bool ACQ, int NS = 32> __device__ __forceinline__ void flag_wait(int idx, int target) {
  int n = 0;
  while (true) {
    int v;
    if (ACQ) asm volatile("ld.acquire.gpu.global.s32 %0, [%1];" : "=r"(v) : "l"(g_flags + idx) : "memory");
    else asm volatile("ld.relaxed.gpu.global.s32 %0, [%1];" : "=r"(v) : "l"(g_flags + idx) : "memory");
    if (__all_sync(0xffffffffu, v >= target)) break;
    if (++n > 20000000) __trap();
    __nanosleep(NS);
  }
}
__device__ __forceinline__ uint32_t desc_lo(uint32_t addr, uint32_t lbo) { return ((addr & 0x3FFFFu) >> 4) | ((lbo >> 4) << 16); }
#define PROF(role, i)
#define PROFX(cond, i)
#define PROFB(i)
#define PROFG(i)

template <int TB, int TA = 0> __device__ __forceinline__ void wgmma_ss64(float (&d)[32], uint32_t alo, uint32_t blo, int sd) {
  asm volatile("{\n.reg .pred p;\n.reg .b64 da, db;\n"
    "setp.ne.b32 p, %34, 0;\nmov.b64 da, {%32, %36};\nmov.b64 db, {%33, %36};\n"
    "wgmma.mma_async.sync.aligned.m64n64k16.f32.bf16.bf16 "
    "{%0,%1,%2,%3,%4,%5,%6,%7,%8,%9,%10,%11,%12,%13,%14,%15,%16,%17,%18,%19,%20,%21,%22,%23,"
    "%24,%25,%26,%27,%28,%29,%30,%31}, "
    "da, db, p, 1, 1, %37, %35;\n}\n"
    : "+f"(d[0]),"+f"(d[1]),"+f"(d[2]),"+f"(d[3]),"+f"(d[4]),"+f"(d[5]),"+f"(d[6]),"+f"(d[7]),"+f"(d[8]),"+f"(d[9]),"+f"(d[10]),"+f"(d[11]),
      "+f"(d[12]),"+f"(d[13]),"+f"(d[14]),"+f"(d[15]),"+f"(d[16]),"+f"(d[17]),"+f"(d[18]),"+f"(d[19]),"+f"(d[20]),"+f"(d[21]),"+f"(d[22]),"+f"(d[23]),
      "+f"(d[24]),"+f"(d[25]),"+f"(d[26]),"+f"(d[27]),"+f"(d[28]),"+f"(d[29]),"+f"(d[30]),"+f"(d[31])
    : "r"(alo), "r"(blo), "r"(sd), "n"(TB), "r"(DESC_HI), "n"(TA));
}
template <int TB, int TA = 0> __device__ __forceinline__ void wgmma_ss128(float (&d)[64], uint32_t alo, uint32_t blo, int sd) {
  asm volatile("{\n.reg .pred p;\n.reg .b64 da, db;\n"
    "setp.ne.b32 p, %66, 0;\nmov.b64 da, {%64, %68};\nmov.b64 db, {%65, %68};\n"
    "wgmma.mma_async.sync.aligned.m64n128k16.f32.bf16.bf16 "
    "{%0,%1,%2,%3,%4,%5,%6,%7,%8,%9,%10,%11,%12,%13,%14,%15,%16,%17,%18,%19,%20,%21,%22,%23,"
    "%24,%25,%26,%27,%28,%29,%30,%31,%32,%33,%34,%35,%36,%37,%38,%39,%40,%41,%42,%43,%44,%45,%46,%47,"
    "%48,%49,%50,%51,%52,%53,%54,%55,%56,%57,%58,%59,%60,%61,%62,%63}, "
    "da, db, p, 1, 1, %69, %67;\n}\n"
    : "+f"(d[0]),"+f"(d[1]),"+f"(d[2]),"+f"(d[3]),"+f"(d[4]),"+f"(d[5]),"+f"(d[6]),"+f"(d[7]),"+f"(d[8]),"+f"(d[9]),"+f"(d[10]),"+f"(d[11]),
      "+f"(d[12]),"+f"(d[13]),"+f"(d[14]),"+f"(d[15]),"+f"(d[16]),"+f"(d[17]),"+f"(d[18]),"+f"(d[19]),"+f"(d[20]),"+f"(d[21]),"+f"(d[22]),"+f"(d[23]),
      "+f"(d[24]),"+f"(d[25]),"+f"(d[26]),"+f"(d[27]),"+f"(d[28]),"+f"(d[29]),"+f"(d[30]),"+f"(d[31]),"+f"(d[32]),"+f"(d[33]),"+f"(d[34]),"+f"(d[35]),
      "+f"(d[36]),"+f"(d[37]),"+f"(d[38]),"+f"(d[39]),"+f"(d[40]),"+f"(d[41]),"+f"(d[42]),"+f"(d[43]),"+f"(d[44]),"+f"(d[45]),"+f"(d[46]),"+f"(d[47]),
      "+f"(d[48]),"+f"(d[49]),"+f"(d[50]),"+f"(d[51]),"+f"(d[52]),"+f"(d[53]),"+f"(d[54]),"+f"(d[55]),"+f"(d[56]),"+f"(d[57]),"+f"(d[58]),"+f"(d[59]),
      "+f"(d[60]),"+f"(d[61]),"+f"(d[62]),"+f"(d[63])
    : "r"(alo), "r"(blo), "r"(sd), "n"(TB), "r"(DESC_HI), "n"(TA));
}
template <int TB> __device__ __forceinline__ void wgmma_rs128(float (&d)[64], uint32_t a0, uint32_t a1, uint32_t a2, uint32_t a3, uint32_t blo, int sd) {
  asm volatile("{\n.reg .pred p;\n.reg .b64 db;\n"
    "setp.ne.b32 p, %69, 0;\nmov.b64 db, {%68, %71};\n"
    "wgmma.mma_async.sync.aligned.m64n128k16.f32.bf16.bf16 "
    "{%0,%1,%2,%3,%4,%5,%6,%7,%8,%9,%10,%11,%12,%13,%14,%15,%16,%17,%18,%19,%20,%21,%22,%23,"
    "%24,%25,%26,%27,%28,%29,%30,%31,%32,%33,%34,%35,%36,%37,%38,%39,%40,%41,%42,%43,%44,%45,%46,%47,"
    "%48,%49,%50,%51,%52,%53,%54,%55,%56,%57,%58,%59,%60,%61,%62,%63}, "
    "{%64,%65,%66,%67}, db, p, 1, 1, %70;\n}\n"
    : "+f"(d[0]),"+f"(d[1]),"+f"(d[2]),"+f"(d[3]),"+f"(d[4]),"+f"(d[5]),"+f"(d[6]),"+f"(d[7]),"+f"(d[8]),"+f"(d[9]),"+f"(d[10]),"+f"(d[11]),
      "+f"(d[12]),"+f"(d[13]),"+f"(d[14]),"+f"(d[15]),"+f"(d[16]),"+f"(d[17]),"+f"(d[18]),"+f"(d[19]),"+f"(d[20]),"+f"(d[21]),"+f"(d[22]),"+f"(d[23]),
      "+f"(d[24]),"+f"(d[25]),"+f"(d[26]),"+f"(d[27]),"+f"(d[28]),"+f"(d[29]),"+f"(d[30]),"+f"(d[31]),"+f"(d[32]),"+f"(d[33]),"+f"(d[34]),"+f"(d[35]),
      "+f"(d[36]),"+f"(d[37]),"+f"(d[38]),"+f"(d[39]),"+f"(d[40]),"+f"(d[41]),"+f"(d[42]),"+f"(d[43]),"+f"(d[44]),"+f"(d[45]),"+f"(d[46]),"+f"(d[47]),
      "+f"(d[48]),"+f"(d[49]),"+f"(d[50]),"+f"(d[51]),"+f"(d[52]),"+f"(d[53]),"+f"(d[54]),"+f"(d[55]),"+f"(d[56]),"+f"(d[57]),"+f"(d[58]),"+f"(d[59]),
      "+f"(d[60]),"+f"(d[61]),"+f"(d[62]),"+f"(d[63])
    : "r"(a0), "r"(a1), "r"(a2), "r"(a3), "r"(blo), "r"(sd), "n"(TB), "r"(DESC_HI));
}
template <int TB, int TA = 0> __device__ __forceinline__ void wgmma_ss192(float (&d)[96], uint32_t alo, uint32_t blo, int sd) {
  asm volatile("{\n.reg .pred p;\n.reg .b64 da, db;\n"
    "setp.ne.b32 p, %98, 0;\nmov.b64 da, {%96, %100};\nmov.b64 db, {%97, %100};\n"
    "wgmma.mma_async.sync.aligned.m64n192k16.f32.bf16.bf16 "
    "{%0,%1,%2,%3,%4,%5,%6,%7,%8,%9,%10,%11,%12,%13,%14,%15,%16,%17,%18,%19,%20,%21,%22,%23,"
    "%24,%25,%26,%27,%28,%29,%30,%31,%32,%33,%34,%35,%36,%37,%38,%39,%40,%41,%42,%43,%44,%45,%46,%47,"
    "%48,%49,%50,%51,%52,%53,%54,%55,%56,%57,%58,%59,%60,%61,%62,%63,%64,%65,%66,%67,%68,%69,%70,%71,"
    "%72,%73,%74,%75,%76,%77,%78,%79,%80,%81,%82,%83,%84,%85,%86,%87,%88,%89,%90,%91,%92,%93,%94,%95}, "
    "da, db, p, 1, 1, %101, %99;\n}\n"
    : "+f"(d[0]),"+f"(d[1]),"+f"(d[2]),"+f"(d[3]),"+f"(d[4]),"+f"(d[5]),"+f"(d[6]),"+f"(d[7]),"+f"(d[8]),"+f"(d[9]),"+f"(d[10]),"+f"(d[11]),
      "+f"(d[12]),"+f"(d[13]),"+f"(d[14]),"+f"(d[15]),"+f"(d[16]),"+f"(d[17]),"+f"(d[18]),"+f"(d[19]),"+f"(d[20]),"+f"(d[21]),"+f"(d[22]),"+f"(d[23]),
      "+f"(d[24]),"+f"(d[25]),"+f"(d[26]),"+f"(d[27]),"+f"(d[28]),"+f"(d[29]),"+f"(d[30]),"+f"(d[31]),"+f"(d[32]),"+f"(d[33]),"+f"(d[34]),"+f"(d[35]),
      "+f"(d[36]),"+f"(d[37]),"+f"(d[38]),"+f"(d[39]),"+f"(d[40]),"+f"(d[41]),"+f"(d[42]),"+f"(d[43]),"+f"(d[44]),"+f"(d[45]),"+f"(d[46]),"+f"(d[47]),
      "+f"(d[48]),"+f"(d[49]),"+f"(d[50]),"+f"(d[51]),"+f"(d[52]),"+f"(d[53]),"+f"(d[54]),"+f"(d[55]),"+f"(d[56]),"+f"(d[57]),"+f"(d[58]),"+f"(d[59]),
      "+f"(d[60]),"+f"(d[61]),"+f"(d[62]),"+f"(d[63]),"+f"(d[64]),"+f"(d[65]),"+f"(d[66]),"+f"(d[67]),"+f"(d[68]),"+f"(d[69]),"+f"(d[70]),"+f"(d[71]),
      "+f"(d[72]),"+f"(d[73]),"+f"(d[74]),"+f"(d[75]),"+f"(d[76]),"+f"(d[77]),"+f"(d[78]),"+f"(d[79]),"+f"(d[80]),"+f"(d[81]),"+f"(d[82]),"+f"(d[83]),
      "+f"(d[84]),"+f"(d[85]),"+f"(d[86]),"+f"(d[87]),"+f"(d[88]),"+f"(d[89]),"+f"(d[90]),"+f"(d[91]),"+f"(d[92]),"+f"(d[93]),"+f"(d[94]),"+f"(d[95])
    : "r"(alo), "r"(blo), "r"(sd), "n"(TB), "r"(DESC_HI), "n"(TA));
}

struct Ctx {
  uint32_t sm;
  uint32_t bar;
  uint32_t rbar;
  int cl, rank, wg, warp, lane, phases;
};
__device__ __forceinline__ void release(const Ctx& c, int b, int cnt = 1) {
  if (c.lane < 2) mbar_arrive_cl(c.rbar + b * 8, cnt);
}
#define NPF 6
#define PFM 7
#define PF1 1
constexpr float SM_SCALE = 0.08838834764831845f * 1.4426950408889634f;
constexpr float SM_HI = 1.8446744e19f, SM_LO = 5.4210109e-20f;
constexpr int ORDER = 1;

__device__ __forceinline__ void stage_tile(const float (&a)[64], uint32_t buf, const Ctx& c, float s0, float s1) {
  const int row = (c.lane & 7) + ((c.lane >> 3) & 1) * 8;
  const uint32_t base = buf + (c.warp * 16 + row) * 128 + (((c.lane >> 4) ^ (row & 7)) << 4);
#pragma unroll
  for (int i = 0; i < 8; i++)
    stsm4((base ^ ((i & 3) << 5)) + (i >> 2) * 8192, pack_bf16(a[8 * i] * s0, a[8 * i + 1] * s0), pack_bf16(a[8 * i + 2] * s1, a[8 * i + 3] * s1),
          pack_bf16(a[8 * i + 4] * s0, a[8 * i + 5] * s0), pack_bf16(a[8 * i + 6] * s1, a[8 * i + 7] * s1));
}

__device__ __forceinline__ void p1_epilogue(const Params& p, const Ctx& c, const float (&acc)[64], int t, int type) {
  const int tile = p.s.r[c.cl].tile[t], b = c.wg * 2 + 1;
  mbar_wait(c.bar + (B_SE + b) * 8, (t & 1) ^ 1);
  if (type && tile >= 32) {
    const int r = 2 * (c.lane & 3) + ((c.lane >> 2) & 1);
    const uint32_t dst = c.sm + SM_BUF + b * 16384 + r * 128 + (((c.warp * 2) ^ r) << 4) + (c.lane >> 3) * 4;
#pragma unroll
    for (int i = 0; i < 16; i++) {
      asm volatile("st.shared.u32 [%0], %1;" ::"r"(dst + i * 1024), "r"(pack_bf16(acc[4 * i], acc[4 * i + 1])) : "memory");
      asm volatile("st.shared.u32 [%0], %1;" ::"r"((dst ^ 16) + i * 1024), "r"(pack_bf16(acc[4 * i + 2], acc[4 * i + 3])) : "memory");
    }
  } else {
    if (type) stage_tile(acc, c.sm + SM_BUF + b * 16384, c, SM_SCALE, SM_SCALE);
    else stage_tile(acc, c.sm + SM_BUF + b * 16384, c, 1.f, 1.f);
  }
  FENCE_ASYNC_SMEM();
  __syncwarp();
  if (c.lane == 0) mbar_arrive(c.bar + (B_SF + b) * 8);
}

__device__ __forceinline__ void p1_consumer(const Params& p, const Ctx& c) {
  const int n = p.s.r[c.cl].n1;
  const int type = p.s.r[c.cl].slab >> 3;
  const uint32_t bdesc = desc_lo(c.sm + SM_RING, 8192), adesc = desc_lo(c.sm + SM_BUF + 32768 + c.wg * 8192, 16);
  uint32_t A[128];
  float acc[64] = {};
  int slot = 0, par = 0;
  auto next = [&]() { if (++slot == 10) { slot = 0; par ^= 1; } };
  {
    const int row = (c.lane & 7) + ((c.lane >> 3) & 1) * 8;
    const uint32_t base = c.sm + SM_RING + (c.wg * 64 + c.warp * 16 + row) * 128 + (((c.lane >> 4) ^ (row & 7)) << 4);
    if (c.wg == 1) bar_sync(ORDER + 1, 256);
    int pa = -1, pb = -1;
    if (type) {
      mbar_wait(c.bar + B_P1F * 8, 0);
      WG_FENCE();
#pragma unroll
      for (int kk = 0; kk < 4; kk++) wgmma_ss128<1>(acc, adesc + kk * 2, bdesc + kk * 128, kk != 0);
      WG_COMMIT();
      pb = 0; slot = 1;
    }
#pragma unroll
    for (int kb = 0; kb < 8; kb++) {
      const int sa = slot;
      mbar_wait(c.bar + (B_P1F + slot) * 8, par);
      if (kb == 0) PROF(c.wg, 5);
      next();
      mbar_wait(c.bar + (B_P1F + slot) * 8, par);
      PROF(c.wg, 6 + 2 * kb);
      WG_FENCE();
#pragma unroll
      for (int kk = 0; kk < 4; kk++)
        wgmma_ss128<1>(acc, desc_lo(c.sm + SM_RING + c.wg * 8192, 16) + sa * 1024 + kk * 2, bdesc + slot * 1024 + kk * 128, (kb | kk) != 0 ? 1 : type);
      WG_COMMIT();
      if (kb == 1 && c.wg == 0) bar_arrive(ORDER + 1, 256);
#pragma unroll
      for (int kk = 0; kk < 4; kk++) ldsm4((base ^ (kk << 5)) + sa * 16384, A[kb * 16 + kk * 4], A[kb * 16 + kk * 4 + 1], A[kb * 16 + kk * 4 + 2], A[kb * 16 + kk * 4 + 3]);
      WG_WAIT(1);
      if (kb > 0) release(c, B_P1E + pa);
      if (kb > 0 || pb >= 0) release(c, B_P1E + pb);
      pa = sa; pb = slot;
      next();
    }
    WG_WAIT(0);
    __syncwarp();
    release(c, B_P1E + pa);
    release(c, B_P1E + pb);
    pin(acc);
    PROF(c.wg, 1);
    p1_epilogue(p, c, acc, 0, type);
    PROF(c.wg, 2);
  }
  for (int t = 1; t < n; t++) {
    bar_sync(ORDER + c.wg, 256);
    int prev1 = -1, prev2 = -1;
    if (type) {
      mbar_wait(c.bar + (B_P1F + slot) * 8, par);
      WG_FENCE();
#pragma unroll
      for (int kk = 0; kk < 4; kk++) wgmma_ss128<1>(acc, adesc + kk * 2, bdesc + slot * 1024 + kk * 128, kk != 0);
      WG_COMMIT();
      prev1 = slot;
      next();
    }
#pragma unroll
    for (int kb = 0; kb < 8; kb++) {
      mbar_wait(c.bar + (B_P1F + slot) * 8, par);
      WG_FENCE();
      const uint32_t d = bdesc + slot * 1024;
#pragma unroll
      for (int kk = 0; kk < 4; kk++)
        wgmma_rs128<1>(acc, A[kb * 16 + kk * 4], A[kb * 16 + kk * 4 + 1], A[kb * 16 + kk * 4 + 2], A[kb * 16 + kk * 4 + 3], d + kk * 128, (kb | kk) != 0 ? 1 : type);
      WG_COMMIT();
      if (kb == 7) {
        if (t + 1 < n || c.wg == 0) bar_arrive(ORDER + (c.wg ^ 1), 256);
      }
      if (kb > 0) { WG_WAIT(2); if (kb > 1 || prev2 >= 0) release(c, B_P1E + prev2); }
      prev2 = prev1; prev1 = slot;
      next();
    }
    WG_WAIT(1);
    release(c, B_P1E + prev2);
    WG_WAIT(0);
    pin(acc);
    release(c, B_P1E + prev1);
    p1_epilogue(p, c, acc, t, type);
    PROF(c.wg, 3);
  }
}

__device__ __forceinline__ void p1_producer(const Params& p, const Ctx& c) {
  const int n = p.s.r[c.cl].n1;
  const int type = p.s.r[c.cl].slab >> 3, grp = p.s.r[c.cl].slab & 7;
  int slot = 2 - type, par = 1;
#pragma unroll 1
  for (int t = 0; t < n; t++) {
    const int tile = p.s.r[c.cl].tile[t];
    const CUtensorMap* m = &p.map_w[type * 2 + (tile >> 5)];
    const int n0 = (tile & 31) * 128 + c.rank * 64;
    const int ptile = p.s.r[c.cl].tile[t + PF1 < n ? t + PF1 : t];
    const CUtensorMap* pm = &p.map_w[type * 2 + (ptile >> 5)];
#pragma unroll 1
    for (int kb = (t == 0) - type; kb < 8; kb++) {
      if (t == 0) {
        mbar_wait(c.bar + (B_P1E + slot) * 8, par);
        mbar_expect(c.bar + (B_P1F + slot) * 8, 16384);
        tma2d(c.sm + SM_RING + slot * 16384, &p.map_a[type], kb * 64, grp * 256 + c.rank * 128, c.bar + (B_P1F + slot) * 8);
        if (++slot == 10) { slot = 0; par ^= 1; }
      }
      mbar_wait(c.bar + (B_P1E + slot) * 8, par);
      mbar_expect(c.bar + (B_P1F + slot) * 8, 16384);
      tma2d_mc(c.sm + SM_RING + slot * 16384 + c.rank * 8192, m, n0, kb < 0 ? 512 : kb * 64, c.bar + (B_P1F + slot) * 8);
      if (t == 0 && kb == 1) PROF(2, 61);
      if (t == 0 && kb == 3) PROF(2, 62);
      if (t + PF1 < n && (t > 0 || kb >= 3) && ((kb ^ grp) & PFM) == 0) tma2d_prefetch(pm, (ptile & 31) * 128 + c.rank * 64, kb < 0 ? 512 : kb * 64);
      if (++slot == 10) { slot = 0; par ^= 1; }
    }
  }
}

__device__ __forceinline__ void p1_storer(const Params& p, const Ctx& c) {
  const int n = p.s.r[c.cl].n1;
  const int type = p.s.r[c.cl].slab >> 3, grp = p.s.r[c.cl].slab & 7;
  int pf = -1;
  for (int i = 0; i < 2 * n; i++) {
    const int t = i >> 1, w = i & 1, b = w * 2 + 1;
    const int tile = p.s.r[c.cl].tile[t];
    mbar_wait(c.bar + (B_SF + b) * 8, t & 1);
    const uint32_t src = c.sm + SM_BUF + b * 16384;
    int f = F_HEAD + (tile & 31);
    if (type == 0) {
      const int h = tile & 31, ring = p.s.r[c.cl].ring;
      if (h >= ring && w == 0) flag_wait<false>(F_CTX + max(c.lane & 7, grp) * 64 + h - ring, 4);
      uint8_t* dst = g_KV + (size_t)((h >= ring ? tile - ring : tile) * 16 + grp * 2 + c.rank) * 32768 + w * 8192;
      bulk_store(dst, src, 8192);
      bulk_store(dst + 16384, src + 8192, 8192);
    } else if (tile < 32) {
      bulk_store(g_Q + (size_t)(tile * 32 + grp * 4 + c.rank * 2 + w) * 16384, src, 16384);
    } else {
      tma3d_store(&p.map_t[2], src, 8 + (grp * 4 + c.rank * 2 + w) * 32, 0, (tile - 32) * 64);
      f = F_QKVA + grp * 4 + ((0xE4390900u >> (2 * (tile - 30))) & 3);
    }
    BULK_COMMIT();
    BULK_WAIT_READ(0);
    mbar_arrive_one(c.bar + (B_SE + b) * 8);
    if (pf >= 0) {
      BULK_WAIT(1);
      flag_add_rx(pf);
    }
    pf = f;
  }
  BULK_WAIT(0);
  flag_add_rx(pf);
}

__device__ __forceinline__ int p2_buf(int w, int i) { return w * 2 + (i & 1); }
__device__ __forceinline__ int p2_blk(int rank, int w, int i) { return ((i ^ w) & 1) == 0 ? 3 - rank : rank; }

template <int N>
__device__ __forceinline__ void row_max(const float (&s)[N], float& m0, float& m1) {
  float a0 = fmaxf(s[0], s[1]), a1 = fmaxf(s[2], s[3]);
#pragma unroll
  for (int i = 1; i < N / 4; i++) {
    m0 = fmaxf(m0, s[4 * i]); a0 = fmaxf(a0, s[4 * i + 1]);
    m1 = fmaxf(m1, s[4 * i + 2]); a1 = fmaxf(a1, s[4 * i + 3]);
  }
  m0 = fmaxf(m0, a0); m1 = fmaxf(m1, a1);
  m0 = fmaxf(m0, __shfl_xor_sync(0xffffffffu, m0, 1));
  m1 = fmaxf(m1, __shfl_xor_sync(0xffffffffu, m1, 1));
  m0 = fmaxf(m0, __shfl_xor_sync(0xffffffffu, m0, 2));
  m1 = fmaxf(m1, __shfl_xor_sync(0xffffffffu, m1, 2));
}
template <bool SUB, int N>
__device__ __forceinline__ void row_exp(const float (&s)[N], uint32_t (&P)[32], float m0, float m1, float& t0, float& t1) {
  float u0 = 0.f, u1 = 0.f;
  t0 = t1 = 0.f;
#pragma unroll
  for (int i = 0; i < N / 4; i++) {
    const float e0 = ex2(SUB ? s[4 * i] - m0 : s[4 * i]), e1 = ex2(SUB ? s[4 * i + 1] - m0 : s[4 * i + 1]);
    const float e2 = ex2(SUB ? s[4 * i + 2] - m1 : s[4 * i + 2]), e3 = ex2(SUB ? s[4 * i + 3] - m1 : s[4 * i + 3]);
    if (i == 0) { t0 = e0; u0 = e1; t1 = e2; u1 = e3; }
    else { t0 += e0; u0 += e1; t1 += e2; u1 += e3; }
    P[2 * i] = pack_bf16(e0, e1);
    P[2 * i + 1] = pack_bf16(e2, e3);
  }
#pragma unroll
  for (int i = N / 2; i < 32; i++) P[i] = 0;
  pin(P);
  t0 += u0; t1 += u1;
}
template <int N>
__device__ __forceinline__ void causal_mask(float (&s)[N], int thr) {
#pragma unroll
  for (int i = 0; i < 8; i++) {
    if (8 * i > thr) s[N - 32 + 4 * i] = -INFINITY;
    if (8 * i + 1 > thr) s[N - 32 + 4 * i + 1] = -INFINITY;
    if (8 * i - 8 > thr) s[N - 32 + 4 * i + 2] = -INFINITY;
    if (8 * i - 7 > thr) s[N - 32 + 4 * i + 3] = -INFINITY;
  }
}
__device__ __forceinline__ void issue_qk(float (&s)[32], uint32_t qd, uint32_t kd) {
  WG_FENCE();
#pragma unroll
  for (int kk = 0; kk < 8; kk++) wgmma_ss64<0>(s, qd + (kk >> 2) * 512 + (kk & 3) * 2, kd + (kk >> 2) * 1024 + (kk & 3) * 2, kk != 0);
  WG_COMMIT();
}
__device__ __forceinline__ void issue_qk(float (&s)[64], uint32_t qd, uint32_t kd) {
  WG_FENCE();
#pragma unroll
  for (int kk = 0; kk < 8; kk++) wgmma_ss128<0>(s, qd + (kk >> 2) * 512 + (kk & 3) * 2, kd + (kk >> 2) * 1024 + (kk & 3) * 2, kk != 0);
  WG_COMMIT();
}
template <int NK>
__device__ __forceinline__ void issue_pv(float (&o)[64], const uint32_t (&P)[32], uint32_t vd, int acc) {
  WG_FENCE();
#pragma unroll
  for (int kk = 0; kk < NK; kk++) wgmma_rs128<1>(o, P[4 * kk], P[4 * kk + 1], P[4 * kk + 2], P[4 * kk + 3], vd + kk * 128, kk != 0 ? 1 : acc);
  WG_COMMIT();
}
__device__ __forceinline__ void stage_done(const Ctx& c, int b) {
  FENCE_ASYNC_SMEM();
  __syncwarp();
  if (c.lane == 0) mbar_arrive(c.bar + (B_SF + b) * 8);
}
__device__ __forceinline__ void p2_epilogue(const float (&o)[64], float s0, float s1, const Ctx& c, int b) {
  stage_tile(o, c.sm + SM_BUF + b * 16384, c, s0, s1);
  stage_done(c, b);
}

struct P2State {
  float m0, m1, l0, l1;
  bool shift;
  float e0, e1;
  float g0, g1;
  int ks;
  int wi, ai;
  uint32_t wb, ab;
  uint32_t qd;
};
#define PROFZ()
__device__ __forceinline__ int wrap5(int q) { return q >= 5 ? q - 5 : q; }
__device__ __forceinline__ void turn_wait(uint32_t ring, int i) { mbar_wait(ring + (i & 3) * 8, (i >> 2) & 1); }
__device__ __forceinline__ void turn_pass(const Ctx& c, uint32_t ring, int i) { if (c.lane == 0) mbar_arrive(ring + (i & 3) * 8); }
__device__ __forceinline__ void p2_gate(P2State& z, const Ctx& c, int row0) {
  const float* g = g_gate + row0 + c.warp * 16 + (c.lane >> 2);
  asm volatile("ld.global.cg.f32 %0, [%2];\nld.global.cg.f32 %1, [%2+32];" : "=f"(z.g0), "=f"(z.g1) : "l"(g) : "memory");
}
__device__ __forceinline__ void p2_scales(P2State& z) {
  float l0 = z.l0, l1 = z.l1;
  l0 += __shfl_xor_sync(0xffffffffu, l0, 1);
  l1 += __shfl_xor_sync(0xffffffffu, l1, 1);
  l0 += __shfl_xor_sync(0xffffffffu, l0, 2);
  l1 += __shfl_xor_sync(0xffffffffu, l1, 2);
  z.e0 = __fdividef(1.f - z.g0, l0); z.e1 = __fdividef(1.f - z.g1, l1);
}
template <int N>
__device__ __forceinline__ void p2_first(const Ctx& c, P2State& z, float (&o)[64], uint32_t (&Pc)[32], uint32_t (&Pn)[32],
                                         int ks, int vs, int cnt, int acc, int row0) {
  float s[N] = {};
  issue_qk(s, z.qd, desc_lo(c.sm + SM_RING, 16) + ks * 2048);
  if (vs >= 0) {
    p2_scales(z);
    issue_pv<8>(o, Pc, desc_lo(c.sm + SM_RING, 16384) + vs * 2048, acc);
  } else {
    WG_COMMIT();
  }
  mbar_expect(z.ab + (z.ai++ & 3) * 8, cnt == 1 ? 8192 : 0);
  PROFZ();
  WG_WAIT(1);
  PROFZ();
  pin(s);
  release(c, B_P2E + ks, cnt);
  p2_gate(z, c, row0);
  causal_mask(s, c.warp * 16 + (c.lane >> 2) - 2 * (c.lane & 3));
  z.m0 = z.m1 = 0.f;
  row_exp<false>(s, Pn, 0.f, 0.f, z.l0, z.l1);
  z.shift = __any_sync(0xffffffffu, !(z.l0 + z.l1 <= SM_HI) || ((c.lane & 3) == 0 && !(fminf(z.l0, z.l1) >= SM_LO)));
  if (__builtin_expect(z.shift, 0)) {
    z.m0 = z.m1 = -INFINITY;
    row_max(s, z.m0, z.m1);
    row_exp<true>(s, Pn, z.m0, z.m1, z.l0, z.l1);
  }
  WG_WAIT(0);
  pin(o);
  if (vs >= 0) release(c, B_P2E + vs, 1);
}

template <bool SECOND>
__device__ __forceinline__ void p2_turn(const Ctx& c, P2State& z, float (&o)[64], uint32_t (&Pc)[32], uint32_t (&Pn)[32],
                                        int eb = -1, bool half = false, int vcnt = 1) {
  float s[64] = {};
  const int ks = z.ks, vs = wrap5(ks + 1);
  PROFZ();
  turn_wait(z.wb, z.wi++);
  PROFZ();
  issue_qk(s, z.qd, desc_lo(c.sm + SM_RING, 16) + ks * 2048);
  const uint32_t vd = desc_lo(c.sm + SM_RING, 16384) + vs * 2048;
  if (SECOND) {
    if (eb >= 0) stage_tile(o, c.sm + SM_BUF + eb * 16384, c, z.e0, z.e1);
    if (half) issue_pv<4>(o, Pc, vd, 0); else issue_pv<8>(o, Pc, vd, 0);
  } else {
    issue_pv<8>(o, Pc, vd, 1);
  }
  turn_pass(c, z.ab, z.ai++);
  if (SECOND) { if (eb >= 0) stage_done(c, eb); }
  PROFZ();
  z.ks = wrap5(ks + 2);
  WG_WAIT(1);
  PROFZ();
  pin(s);
  release(c, B_P2E + ks, 1);
  float t0, t1, a0 = 1.f, a1 = 1.f;
  row_exp<false>(s, Pn, 0.f, 0.f, t0, t1);
  z.shift = __any_sync(0xffffffffu, z.shift || !(t0 + t1 <= SM_HI));
  const bool redo = z.shift;
  if (__builtin_expect(redo, 0)) {
    float n0 = z.m0, n1 = z.m1;
    row_max(s, n0, n1);
    a0 = ex2(z.m0 - n0); a1 = ex2(z.m1 - n1);
    z.m0 = n0; z.m1 = n1;
    z.l0 *= a0; z.l1 *= a1;
    row_exp<true>(s, Pn, z.m0, z.m1, t0, t1);
  }
  WG_WAIT(0);
  pin(o);
  release(c, B_P2E + vs, vcnt);
  if (__builtin_expect(redo, 0)) {
#pragma unroll
    for (int i = 0; i < 16; i++) { o[4 * i] *= a0; o[4 * i + 1] *= a0; o[4 * i + 2] *= a1; o[4 * i + 3] *= a1; }
  }
  z.l0 += t0; z.l1 += t1;
}
__device__ __forceinline__ void copy_p(uint32_t (&d)[32], const uint32_t (&s)[32], int zero) {
#pragma unroll
  for (int i = 0; i < 32; i++) asm volatile("add.s32 %0, %1, %2;" : "=r"(d[i]) : "r"(s[i]), "r"(zero));
}

__device__ __forceinline__ void p2_consumer(const Params& p, const Ctx& c, int rot) {
  const int nit = p.s.r[c.cl].n2;
  const uint32_t fring = c.bar + B_P2F * 8, oring = c.bar + B_ORD * 8;
  float o[64] = {};
  uint32_t Pa[32] = {}, Pb[32] = {};
  P2State z;
  z.e0 = z.e1 = z.l0 = z.l1 = z.g0 = z.g1 = 0.f; z.ks = rot; z.shift = false;
  int acc = 0, n = 0;
  for (int it = 0; it < nit; it++) {
    const int j = p.s.r[c.cl].item[it] & 7, blk = p2_blk(c.rank, c.wg, it), row0 = (j * 4 + blk) * 64;
    const int lng = ((it ^ c.wg) & 1) ^ 1;
    z.qd = desc_lo(c.sm + SM_BUF, 16) + p2_buf(c.wg, it) * 1024;
    if (lng) { z.wb = oring; z.wi = n - it; z.ab = fring; z.ai = n + 1; }
    else { z.wb = fring; z.wi = n + 2; z.ab = oring; z.ai = n - it; }
    PROFZ();
    mbar_wait(c.bar + (B_QF + p2_buf(c.wg, it)) * 8, (it >> 1) & 1);
    turn_wait(fring, n + 1 - lng);
    PROFZ();
    const int vs = it ? wrap5(z.ks + 1) : -1, ks = lng ? z.ks : wrap5(z.ks + (it ? 2 : 1));
    if (blk & 1) p2_first<64>(c, z, o, Pa, Pb, ks, vs, 1 + lng, acc, row0);
    else p2_first<32>(c, z, o, Pa, Pb, ks, vs, 1 + lng, acc, row0);
    z.ks = wrap5(ks + (it == 0 && lng ? 1 : 2));
    PROF(c.wg, 24 + it);
    n += 2 * j + 2;
    int left = 2 * j + lng;
    acc = left != 0;
    if (left == 0) { copy_p(Pa, Pb, p.zero); continue; }
    p2_turn<true>(c, z, o, Pb, Pa, it > 0 ? p2_buf(c.wg, it - 1) : -1, !(blk & 1), 1 + lng);
    while (--left > 0) {
      p2_turn<false>(c, z, o, Pa, Pb);
      if (--left == 0) { copy_p(Pa, Pb, p.zero); break; }
      p2_turn<false>(c, z, o, Pb, Pa);
    }
  }
  {
    if (!acc && nit > 1) p2_epilogue(o, z.e0, z.e1, c, p2_buf(c.wg, nit));
    turn_wait(z.wb, z.wi);
    issue_pv<8>(o, Pa, desc_lo(c.sm + SM_RING, 16384) + z.ks * 2048, acc);
    if (((nit - 1) ^ c.wg) & 1) turn_pass(c, z.ab, z.ai);
    p2_scales(z);
    WG_WAIT(0);
    pin(o);
    release(c, B_P2E + z.ks);
    p2_epilogue(o, z.e0, z.e1, c, p2_buf(c.wg, nit - 1));
    PROF(c.wg, 24 + nit);
  }
}

__device__ __forceinline__ void p2_load_q(const Params& p, const Ctx& c, int it, int w) {
  const int item = p.s.r[c.cl].item[it], h = item >> 3, j = item & 7, b = p2_buf(w, it);
  mbar_expect(c.bar + (B_QF + b) * 8, 16384);
  bulk_load(c.sm + SM_BUF + b * 16384, g_Q + (size_t)(h * 32 + j * 4 + p2_blk(c.rank, w, it)) * 16384, 16384, c.bar + (B_QF + b) * 8, POL(4));
}
__device__ __forceinline__ void wait_p1_free(const Ctx& c, int u1, int s) {
  mbar_wait(c.bar + (B_P1E + 2 * s) * 8, ((u1 - 1 - 2 * s) / 10) & 1);
  mbar_wait(c.bar + (B_P1E + 2 * s + 1) * 8, ((u1 - 2 - 2 * s) / 10) & 1);
}
__device__ __forceinline__ void p2_producer(const Params& p, const Ctx& c, int u1, int rot) {
  const int nit = p.s.r[c.cl].n2;
  int slot = rot, cnt = 0, par = 1, n = 0;
  const int ring = p.s.r[c.cl].ring;
  const uint8_t* pv = nullptr;
  bool pl = false;
  auto load = [&](const uint8_t* src, int expect, uint32_t fb, bool last) {
    if (cnt < 5) {
      if (u1) {
        wait_p1_free(c, u1, slot);
        if (cnt == 0) p2_load_q(p, c, 0, 1);
      }
      cnt++;
    } else {
      if (slot == rot) par ^= 1;
      mbar_wait(c.bar + (B_P2E + slot) * 8, par);
    }
    if (expect) mbar_expect(fb, expect);
    bulk_load_mc(c.sm + SM_RING + slot * 32768 + c.rank * 16384, src, 16384, fb, last ? POL(5) : L2_NORMAL);
    slot = wrap5(slot + 1);
  };
  if (c.phases & 16) flag_wait<true>(F_GATE, 256);
  for (int it = 0; it < nit; it++) {
    const int item = p.s.r[c.cl].item[it], h = item >> 3, j = item & 7;
    if (c.phases & 16) flag_wait<false>(F_HEAD + h, 96);
    if (it == 0) { mbar_wait(c.bar + B_LAD * 8, 0); p2_load_q(p, c, 0, 0); if (!u1) p2_load_q(p, c, 0, 1); }
    for (int t = 2 * j + 1; t >= 0; t--) {
      const uint8_t* k = g_KV + (size_t)((h >= ring ? h - ring : h) * 16 + t) * 32768 + c.rank * 16384;
      const uint32_t fb = c.bar + (B_P2F + (n & 3)) * 8;
      const bool last = (p.s.r[c.cl].last[it] >> (t >> 1)) & 1;
      load(k, pv && t != 2 * j ? 65536 : 32768, fb, last);
      if (pv) load(pv, 0, t != 2 * j ? fb : c.bar + (B_ORD + ((n - 1 - it) & 3)) * 8, pl);
      pl = last;
      pv = k + (size_t)NH * 16 * 32768;
      n++;
    }
  }
  load(pv, 32768, c.bar + (B_P2F + (n & 3)) * 8, pl);
}

__device__ __forceinline__ void p2_storer(const Params& p, const Ctx& c, int sfpar) {
  const int nit = p.s.r[c.cl].n2;
  auto load_q = [&](int it, int w) {
    if (c.phases & 16) flag_wait<false>(F_HEAD + (p.s.r[c.cl].item[it] >> 3), 96);
    p2_load_q(p, c, it, w);
  };
  if (nit > 1) {
    load_q(1, 1); p2_load_q(p, c, 1, 0); }
  for (int i = 0; i < 2 * nit; i++) {
    const int it = i >> 1, w = (it ^ i ^ 1) & 1, b = p2_buf(w, it);
    const int item = p.s.r[c.cl].item[it], h = item >> 3, j = item & 7;
    mbar_wait(c.bar + (B_SF + b) * 8, (sfpar >> b) & 1);
    sfpar ^= 1 << b;
    bulk_store(g_Q + (size_t)(h * 32 + j * 4 + p2_blk(c.rank, w, it)) * 16384, c.sm + SM_BUF + b * 16384, 16384, POL(1));
    BULK_COMMIT();
    BULK_WAIT(0);
    flag_add_rx(F_CTX + j * 64 + h);
    if ((i & 1) && it + 2 < nit) { load_q(it + 2, w); p2_load_q(p, c, it + 2, w ^ 1); }
  }
  release(c, B_DONE);
}

__device__ __forceinline__ int p3_pos(int i, int x) { return i < 4 ? (i + x) & 3 : 4; }
__device__ __forceinline__ void p3_consumer(const Params& p, const Ctx& c, int x) {
  const bool first = p.s.r[c.cl].p3 >= 24;
  const int tile = p.s.r[c.cl].p3 - (first ? 24 : 0), j = tile / 3, nt = tile - 3 * j;
  const int na = first ? 9 : 0, nb = first ? 2 * p.s.nh[tile] : 64 - 2 * p.s.nh[tile];
  const uint32_t ad = desc_lo(c.sm + SM_RING + c.wg * 8192, 16), bd = desc_lo(c.sm + SM_RING + 16384, 4096);
  float acc[96] = {};
  int slot = 0, par = 0, prev = 0;
#pragma unroll 1
  for (int kb = 0; kb < na; kb++) {
    mbar_wait(c.bar + (B_P3F + slot) * 8, par);
    if (kb == 0) PROF(c.wg, 39);
    WG_FENCE();
#pragma unroll
    for (int kk = 0; kk < 4; kk++) wgmma_ss192<1, 1>(acc, ad + p3_pos(slot, x) * 2560 + kk * 128, bd + p3_pos(slot, x) * 2560 + (kk >> 1) * 768 + (kk & 1) * 128, kk != 0 ? 1 : kb != 0);
    WG_COMMIT();
    WG_WAIT(1);
    if (kb > 0) release(c, B_P3E + prev);
    prev = slot;
    if (++slot == 5) { slot = 0; par ^= 1; }
  }
#pragma unroll 1
  for (int kb = na; kb < na + nb; kb++) {
    mbar_wait(c.bar + (B_P3F + slot) * 8, par);
    if (kb == 0) PROF(c.wg, 39);
    WG_FENCE();
#pragma unroll
    for (int kk = 0; kk < 4; kk++) wgmma_ss192<1>(acc, ad + p3_pos(slot, x) * 2560 + kk * 2, bd + p3_pos(slot, x) * 2560 + (kk >> 1) * 768 + (kk & 1) * 128, kk != 0 ? 1 : kb != 0);
    WG_COMMIT();
    WG_WAIT(1);
    if (kb > 0) release(c, B_P3E + prev);
    prev = slot;
    if (++slot == 5) { slot = 0; par ^= 1; }
  }
  WG_WAIT(0);
  pin(acc);
  PROF(c.wg, 40);
  if (first) bar_sync(4 + c.wg, 128);
  mbar_wait(c.bar + B_OUT * 8, 0);
  const int row = (c.lane & 7) + ((c.lane >> 3) & 1) * 8;
  const uint32_t wbase = c.sm + SM_RING + c.wg * 8192 + c.warp * 2048;
  const uint32_t base = wbase + row * 128 + (((c.lane >> 4) ^ (row & 7)) << 4);
#pragma unroll
  for (int i = 0; i < 12; i++) {
    stsm4((base ^ ((i & 3) << 5)) + (i >> 2) * 40960, pack_bf16(acc[8 * i], acc[8 * i + 1]), pack_bf16(acc[8 * i + 2], acc[8 * i + 3]),
          pack_bf16(acc[8 * i + 4], acc[8 * i + 5]), pack_bf16(acc[8 * i + 6], acc[8 * i + 7]));
    if ((i & 3) == 3) {
      FENCE_ASYNC_SMEM();
      __syncwarp();
      const int c0 = nt * 192 + (i >> 2) * 64, c1 = j * 256 + c.rank * 128 + c.wg * 64 + c.warp * 16;
      tma2d_add(&p.map_out, wbase + (i >> 2) * 40960, c0, c1);
    }
  }
  BULK_COMMIT();
  PROF(c.wg, 43);
  BULK_WAIT_READ(0);
  PROF(c.wg, 44);
}

__device__ __forceinline__ void p3_producer(const Params& p, const Ctx& c, int u1, int u2, int rot, int x) {
  const bool first = p.s.r[c.cl].p3 >= 24;
  const int tile = p.s.r[c.cl].p3 - (first ? 24 : 0), j = tile / 3, nt = tile - 3 * j;
  int slot = 0, par = 1, cnt = 0;
  auto wait_free = [&](int s) {
    const int f = wrap5(s + 5 - rot);
    if (f < u2) mbar_wait(c.bar + (B_P2E + s) * 8, ((u2 - 1 - f) / 5) & 1);
    else if (u1) wait_p1_free(c, u1, s);
  };
  asm volatile(ELECT("prefetch.tensormap [%0];") ::"l"(&p.map_o[first]) : "memory");
  asm volatile(ELECT("prefetch.tensormap [%0];") ::"l"(&p.map_out) : "memory");
  const int q1 = first ? p.s.nh[tile] : 32;
  for (int q = first ? -1 : p.s.nh[tile]; q < q1; q++) {
    const int g = q < 0 ? 32 : p.s.p3_order[j][q];
    if (c.phases & 16) flag_wait<false>(F_CTX + j * 64 + g, q < 0 ? 16 : 4);
    const int nk = q < 0 ? 9 : 2, k0 = (q < 0 ? 0 : g * 128) + c.rank * 32;
    const uint8_t* a = q < 0 ? g_oA + (j * 4 + c.rank * 2) * 73728 : g_Q + (size_t)(g * 32 + j * 4 + c.rank * 2) * 16384;
    const CUtensorMap* m = &p.map_o[q < 0];
    for (int i = 0; i < nk; i++) {
      const uint32_t st = c.sm + SM_RING + p3_pos(slot, x) * 40960, fb = c.bar + (B_P3F + slot) * 8;
      if (cnt < 4) { wait_free(p3_pos(cnt, x)); wait_free(p3_pos(cnt, x) + 1); }
      else if (cnt == 4) mbar_wait(c.bar + B_DONE * 8, 0);
      else mbar_wait(c.bar + (B_P3E + slot) * 8, par);
      cnt++;
      mbar_expect(fb, 40960);
      bulk_load(st, a + i * 8192, 8192, fb, POL(3));
      bulk_load(st + 8192, a + (nk + i) * 8192, 8192, fb, POL(3));
      tma3d_mc(st + 16384 + c.rank * 12288, m, 0, k0 + i * 64, nt * 3, fb);
      if (++slot == 5) { slot = 0; par ^= 1; }
    }
  }
}

__device__ __forceinline__ float bf_lo(uint32_t w) { return __uint_as_float(w << 16); }
__device__ __forceinline__ float bf_hi(uint32_t w) { return __uint_as_float(w & 0xffff0000u); }

__device__ __forceinline__ void gate_rows(const Params& p, int row0, int lane) {
  const uint4* x = reinterpret_cast<const uint4*>(p.x + (size_t)(row0 + (lane >> 2)) * DM) + (lane & 3);
  const uint4* w = reinterpret_cast<const uint4*>(p.gate_w) + (lane & 3);
  float a = 0.f;
#pragma unroll 1
  for (int b = 0; b < 3; b++) {
    uint4 u[6];
#pragma unroll
    for (int i = 0; i < 6; i++) u[i] = __ldg(x + (b * 6 + i) * 4);
#pragma unroll
    for (int i = 0; i < 6; i++) {
      const uint4 v = __ldg(w + (b * 6 + i) * 4);
      a = fmaf(bf_lo(u[i].x), bf_lo(v.x), a); a = fmaf(bf_hi(u[i].x), bf_hi(v.x), a);
      a = fmaf(bf_lo(u[i].y), bf_lo(v.y), a); a = fmaf(bf_hi(u[i].y), bf_hi(v.y), a);
      a = fmaf(bf_lo(u[i].z), bf_lo(v.z), a); a = fmaf(bf_hi(u[i].z), bf_hi(v.z), a);
      a = fmaf(bf_lo(u[i].w), bf_lo(v.w), a); a = fmaf(bf_hi(u[i].w), bf_hi(v.w), a);
    }
  }
  a += __shfl_xor_sync(0xffffffffu, a, 1);
  a += __shfl_xor_sync(0xffffffffu, a, 2);
  if ((lane & 3) == 0) g_gate[row0 + (lane >> 2)] = 1.f / (1.f + __expf(-a));
}

__device__ __forceinline__ void lds10(uint32_t (&k)[10], uint32_t a) {
  asm volatile("ld.shared.v2.u32 {%0, %1}, [%10];\nld.shared.v2.u32 {%2, %3}, [%10+8];\nld.shared.v2.u32 {%4, %5}, [%10+16];\n"
               "ld.shared.v2.u32 {%6, %7}, [%10+24];\nld.shared.v2.u32 {%8, %9}, [%10+32];"
               : "=r"(k[0]), "=r"(k[1]), "=r"(k[2]), "=r"(k[3]), "=r"(k[4]), "=r"(k[5]), "=r"(k[6]), "=r"(k[7]), "=r"(k[8]), "=r"(k[9]) : "r"(a));
}
__device__ __forceinline__ void local_attn(const Params& p, const Ctx& c, int rb, int hs) {
  const int lane = c.lane, grp = rb >> 2, par = lane >> 4, i0 = 2 * (lane & 15);
  const uint32_t buf = c.sm + SM_BUF + (c.warp - 2) * 8192, bqk = c.bar + (B_LA + (c.warp - 2) * 2) * 8, bv = bqk + 8;
  const uint32_t mine = buf + 2304 + par * 160 + i0 * 4;
  const bool flags = c.phases & 16;
  auto fetch_qk = [&](int i) {
    if (flags && !(i & 1)) {
      const int q = i >> 1;
      const int tgt = q == 0 ? 24 : q == 3 ? 8 : 12;
      flag_wait<false>(F_QKVA + (grp - (grp > 0 && (rb & 3) == 0 ? par : 0)) * 4 + q, tgt);
    }
    mbar_expect(bqk, 5184);
    tma3d(buf, &p.map_t[0], rb * 32 + 8, 0, 9 * (4 * i + hs), bqk, POL(2));
    tma3d(buf + 2304, &p.map_t[1], rb * 32, 0, 288 + 9 * (4 * i + hs), bqk, POL(2));
  };
  auto fetch_v = [&](int i) { mbar_expect(bv, 2880); tma3d(buf + 5248, &p.map_t[1], rb * 32, 0, 576 + 9 * (4 * i + hs), bv, POL(2)); };
  fetch_qk(0);
  if (flags) flag_wait<true>(F_GATE, 256);
#pragma unroll 1
  for (int q = 0; q < 8; q++) {
    fetch_v(q);
    float a[8], b[8];
#pragma unroll
    for (int w = 0; w < 8; w++) a[w] = b[w] = 0.f;
    mbar_wait(bqk, q & 1);
    PROFB(1 + 2 * q);
#pragma unroll 1
    for (int j = 0; j < 9; j++) {
      uint32_t x, y, k[10];
      asm volatile("ld.shared.v2.u32 {%0, %1}, [%2];" : "=r"(x), "=r"(y) : "r"(buf + lane * 8 + j * 256));
      lds10(k, mine + j * 320);
      const float xl = bf_lo(x), xh = bf_hi(x), yl = bf_lo(y), yh = bf_hi(y);
#pragma unroll
      for (int m = 1; m < 10; m++) {
        const float kl = bf_lo(k[m]), kh = bf_hi(k[m]);
        if (m < 9) a[8 - m] = fmaf(xl, kl, fmaf(xh, kh, a[8 - m]));
        if (m > 1) b[9 - m] = fmaf(yl, kl, fmaf(yh, kh, b[9 - m]));
      }
    }
    __syncwarp();
    if (q < 7) fetch_qk(q + 1);
    constexpr float SC = 0.23570226039551584f * 1.4426950408889634f;
    const float* gp = g_gate + rb * 64 + 2 * i0 + par;
    const float ga = __ldcg(gp), gb = __ldcg(gp + 2);
    float ma = a[0], mb = b[0];
#pragma unroll
    for (int w = 1; w < 8; w++) {
      if (rb == 0) {
        if (i0 < w) a[w] = -INFINITY;
        if (i0 + 1 < w) b[w] = -INFINITY;
      }
      ma = fmaxf(ma, a[w]); mb = fmaxf(mb, b[w]);
    }
    float la = 0.f, lb = 0.f;
#pragma unroll
    for (int w = 0; w < 8; w++) {
      a[w] = ex2((a[w] - ma) * SC); b[w] = ex2((b[w] - mb) * SC);
      la += a[w]; lb += b[w];
    }
    la = __fdividef(ga, la); lb = __fdividef(gb, lb);
#pragma unroll
    for (int w = 0; w < 8; w++) { a[w] *= la; b[w] *= lb; }
    uint8_t* dst = g_oA + rb * 73728 + ((i0 & 2) + par) * 4;
    mbar_wait(bv, q & 1);
#pragma unroll 1
    for (int j = 0; j < 9; j++) {
      uint32_t v[10];
      lds10(v, mine + 2944 + j * 320);
      float a0 = 0.f, a1 = 0.f, b0 = 0.f, b1 = 0.f;
#pragma unroll
      for (int m = 1; m < 10; m++) {
        const float vl = bf_lo(v[m]), vh = bf_hi(v[m]);
        if (m < 9) { a0 = fmaf(a[8 - m], vl, a0); a1 = fmaf(a[8 - m], vh, a1); }
        if (m > 1) { b0 = fmaf(b[9 - m], vl, b0); b1 = fmaf(b[9 - m], vh, b1); }
      }
      const uint32_t wa = pack_bf16(a0, a1), wb = pack_bf16(b0, b1);
      const uint32_t got = __shfl_xor_sync(0xffffffffu, par ? wa : wb, 16);
      const uint32_t r0 = par ? got : wa, r1 = par ? wb : got;
      const int col = 18 * (4 * q + hs) + 2 * j, o = col * 128 + ((((i0 >> 2) ^ col) & 7) << 4);
      *reinterpret_cast<uint32_t*>(dst + o) = __byte_perm(r0, r1, 0x5410);
      *reinterpret_cast<uint32_t*>(dst + ((o + 128) ^ 16)) = __byte_perm(r0, r1, 0x7632);
    }
    __syncwarp();
    PROFB(2 + 2 * q);
  }
  mbar_arrive_one(c.bar + B_LAD * 8);
  flag_add(F_CTX + grp * 64 + 32);
}

__global__ void __cluster_dims__(2, 1, 1) __launch_bounds__(384, 1) fused_kernel(const __grid_constant__ Params p) {
  extern __shared__ uint8_t smem_raw[];
  Ctx c;
  c.sm = ((uint32_t)__cvta_generic_to_shared(smem_raw) + 1023u) & ~1023u;
  c.bar = c.sm + SM_BAR;
  c.lane = threadIdx.x & 31;
  const int wid = __shfl_sync(0xffffffffu, threadIdx.x >> 5, 0);
  if (wid < NPF) asm volatile("prefetch.tensormap [%0];" ::"l"(&p.map_a[0] + wid) : "memory");
  c.wg = wid >> 2;
  c.warp = wid & 3;
  PROF(c.wg, 0);
  PROFG(61);
  c.cl = (blockIdx.x + (wid >> 4)) >> 1;
  c.rank = blockIdx.x & 1;
  c.rbar = mapa(c.bar, c.lane & 1);
  {
    const int w = wid, cnt = (((int)(B_CNT >> (4 * w)) - 1) & 15) + 1;
    if (w < 11) {
#pragma unroll
      for (int i = 0; i < 8; i++) asm volatile("mbarrier.init.shared::cta.b64 [%0], %1;" ::"r"(c.bar + w * 64 + i * 8), "r"(cnt));
    }
    asm volatile("fence.mbarrier_init.release.cluster;" ::: "memory");
  }
  if (c.wg == 2) PROF(2, 56);
  asm volatile("barrier.cluster.arrive.relaxed;" ::: "memory");
  c.phases = p.s.r[c.cl].phases;
  const bool do1 = p.s.r[c.cl].n1 > 0, do2 = p.s.r[c.cl].n2 > 0, do3 = p.s.r[c.cl].p3 != 255;
  if (do1 && c.wg == 2 && c.warp == 0) {
    const int type = p.s.r[c.cl].slab >> 3;
    PROF(2, 57);
    FENCE_ASYNC_SMEM();
    mbar_expect(c.bar + B_P1F * 8, type ? 32768 : 16384);
    tma2d(type ? c.sm + SM_BUF + 32768 : c.sm + SM_RING, &p.map_a[type], type ? 512 : 0, (p.s.r[c.cl].slab & 7) * 256 + c.rank * 128, c.bar + B_P1F * 8);
    PROF(2, 58);
  }
  asm volatile("barrier.cluster.wait.acquire;" ::: "memory");
  if (c.wg == 2) PROF(2, 59);
  if (do1 && c.wg == 2 && c.warp == 0) {
    const int type = p.s.r[c.cl].slab >> 3, tile = p.s.r[c.cl].tile[0];
    if (!type) mbar_expect(c.bar + (B_P1F + 1) * 8, 16384);
    tma2d_mc(c.sm + SM_RING + (1 - type) * 16384 + c.rank * 8192, &p.map_w[type * 2 + (tile >> 5)], (tile & 31) * 128 + c.rank * 64, type ? 512 : 0, c.bar + (B_P1F + 1 - type) * 8);
  }

  if (c.wg < 2) {
    PROF(c.wg, 4);
    asm volatile("setmaxnreg.inc.sync.aligned.u32 224;");
    if (c.wg == 1) {
      if (do1) bar_arrive(ORDER, 256);
      if (c.lane == 0) mbar_arrive(c.bar + B_P2F * 8);
    }
    if (do1) p1_consumer(p, c);
    if (do2) p2_consumer(p, c, p.s.r[c.cl].rot);
    if (do3) p3_consumer(p, c, p.s.r[c.cl].x3);
    PROF(c.wg, 63);
    PROFG(62);
    if (c.lane == 0) mbar_arrive(c.bar + B_FIN * 8);
    __syncwarp();
    cluster_sync();
  } else {
    asm volatile("setmaxnreg.dec.sync.aligned.u32 56;");
    if (c.warp == 0) {
      PROF(2, 60);
      if (do1) p1_producer(p, c);
      if (do2) p2_producer(p, c, p.s.r[c.cl].u1, p.s.r[c.cl].rot);
      if (do3) p3_producer(p, c, p.s.r[c.cl].u1, p.s.r[c.cl].u2, p.s.r[c.cl].rot, p.s.r[c.cl].x3);
    } else if (c.warp == 1) {
      int sfpar = 0;
      if (do1) {
        p1_storer(p, c);
        sfpar = (p.s.r[c.cl].n1 & 1) * 10;
      }
      if (do2) p2_storer(p, c, sfpar);
      else { mbar_wait(c.bar + B_LAD * 8, 0); release(c, B_DONE); }
      if (do3) {
        const int task = p.s.r[c.cl].p3;
        if (task >= 24) {
          const int j = (task - 24) / 3, nt = task - 24 - 3 * j;
          uint4* o = reinterpret_cast<uint4*>(p.out + (size_t)(j * 256 + c.rank * 128 + (c.lane >> 3)) * DM + nt * 192) + (c.lane & 7);
#pragma unroll 4
          for (int r = 0; r < 32; r++) o[r * 288] = o[r * 288 + 8] = o[r * 288 + 16] = make_uint4(0u, 0u, 0u, 0u);
          __syncwarp();
          flag_add(F_OUT + (task - 24) * 2 + c.rank);
        } else if (c.phases & 16) {
          flag_wait<false, 256>(F_OUT + task * 2 + c.rank, 1);
        }
        mbar_arrive_one(c.bar + B_OUT * 8);
      }
    } else {
      const int bw = blockIdx.x * 2 + (c.warp - 2);
      if ((c.phases & 1) && bw < 256) {
        gate_rows(p, bw * 8, c.lane);
        __syncwarp();
        flag_add(F_GATE);
      }
      if (p.s.r[c.cl].bg != 255) local_attn(p, c, p.s.r[c.cl].bg, bw & 3);
      else if (c.lane == 0) mbar_arrive(c.bar + B_LAD * 8);
    }
    __syncwarp();
    bar_sync(3, 128);
    if (c.warp == 0 && (c.phases & 4)) {
      int last = 0;
      if (c.lane == 0) { __threadfence(); last = atomicAdd(g_flags + F_DONE, 1) == 2 * NCL - 1; }
      if (__shfl_sync(0xffffffffu, last, 0)) for (int i = c.lane; i < F_NUM; i += 32) g_flags[i] = 0;
    }
    if (c.warp == 1) mbar_wait(c.bar + B_FIN * 8, 0);
    __syncwarp();
    cluster_sync();
  }
}

static const Sched k_sched = {
  {{0,26,1,33,0,{206,0,0,0,0,0,0,0,0,0,0},{0,0,0,0,0,0,0,0,0,0,0},{0,2,4,6,8,10,12,45,15,16,17,18,19,20,21,22,23,24,25,26,27,28,29,30,31,63,0,0,0,0}},
   {0,24,3,255,1,{184,204,244,0,0,0,0,0,0,0,0},{0,0,0,0,0,0,0,0,0,0,0},{32,34,36,38,40,42,44,14,47,48,49,50,51,52,53,54,55,56,57,58,59,60,61,62,0,0,0,0,0,0}},
   {0,8,7,43,255,{56,66,54,123,153,179,211,0,0,0,0},{0,0,0,0,0,0,0,0,0,0,0},{1,3,5,7,9,11,13,46,0,0,0,0,0,0,0,0,0,0,0,0,0,0,0,0,0,0,0,0,0,0}},
   {0,6,7,21,255,{58,5,91,122,132,201,232,0,0,0,0},{0,0,0,0,0,0,0,0,0,0,0},{33,35,37,39,41,43,0,0,0,0,0,0,0,0,0,0,0,0,0,0,0,0,0,0,0,0,0,0,0,0}},
   {8,17,3,40,2,{96,172,237,0,0,0,0,0,0,0,0},{0,0,0,0,0,0,0,0,0,0,0},{0,32,41,37,34,38,43,35,39,44,40,45,18,20,22,24,26,0,0,0,0,0,0,0,0,0,0,0,0,0}},
   {8,21,2,24,3,{194,221,0,0,0,0,0,0,0,0,0},{0,32,0,0,0,0,0,0,0,0,0},{1,4,6,8,10,11,12,13,14,15,16,17,19,21,23,25,27,28,29,30,31,0,0,0,0,0,0,0,0,0}},
   {8,4,8,255,255,{43,42,69,114,146,189,220,241,0,0,0},{0,0,0,0,0,0,31,3,0,0,0},{2,36,33,42,0,0,0,0,0,0,0,0,0,0,0,0,0,0,0,0,0,0,0,0,0,0,0,0,0,0}},
   {8,4,6,255,255,{26,82,62,116,181,255,0,0,0,0,0},{0,0,0,0,0,255,0,0,0,0,0},{3,5,7,9,0,0,0,0,0,0,0,0,0,0,0,0,0,0,0,0,0,0,0,0,0,0,0,0,0,0}},
   {1,24,1,6,4,{187,0,0,0,0,0,0,0,0,0,0},{0,0,0,0,0,0,0,0,0,0,0},{0,2,4,6,8,10,12,45,15,16,17,18,19,20,21,22,23,24,25,26,27,28,29,30,0,0,0,0,0,0}},
   {1,26,0,22,5,{0,0,0,0,0,0,0,0,0,0,0},{0,0,0,0,0,0,0,0,0,0,0},{32,34,36,38,40,42,44,14,47,48,49,50,51,52,53,54,55,56,57,58,59,60,61,62,31,63,0,0,0,0}},
   {1,8,5,34,255,{64,29,92,190,205,0,0,0,0,0,0},{0,0,0,0,0,0,0,0,0,0,0},{1,3,5,7,9,11,13,46,0,0,0,0,0,0,0,0,0,0,0,0,0,0,0,0,0,0,0,0,0,0}},
   {1,6,5,14,255,{22,89,98,115,142,0,0,0,0,0,0},{0,0,0,0,0,0,0,0,0,0,0},{33,35,37,39,41,43,0,0,0,0,0,0,0,0,0,0,0,0,0,0,0,0,0,0,0,0,0,0,0,0}},
   {9,20,3,255,6,{174,225,251,0,0,0,0,0,0,0,0},{0,0,0,0,0,0,0,0,0,0,0},{0,32,41,37,34,38,43,35,39,44,40,45,18,20,22,24,26,28,30,31,0,0,0,0,0,0,0,0,0,0}},
   {9,18,2,12,7,{120,164,0,0,0,0,0,0,0,0,0},{0,0,0,0,0,0,0,0,0,0,0},{1,4,6,8,10,11,12,13,14,15,16,17,19,21,23,25,27,29,0,0,0,0,0,0,0,0,0,0,0,0}},
   {9,4,6,42,255,{16,50,39,117,149,212,0,0,0,0,0},{0,0,255,0,0,0,0,0,0,0,0},{2,36,33,42,0,0,0,0,0,0,0,0,0,0,0,0,0,0,0,0,0,0,0,0,0,0,0,0,0,0}},
   {9,4,5,255,255,{30,63,129,151,253,0,0,0,0,0,0},{0,255,0,255,0,0,0,0,0,0,0},{3,5,7,9,0,0,0,0,0,0,0,0,0,0,0,0,0,0,0,0,0,0,0,0,0,0,0,0,0,0}},
   {2,26,1,10,8,{224,0,0,0,0,0,0,0,0,0,0},{0,0,0,0,0,0,0,0,0,0,0},{0,34,5,7,9,11,13,14,15,16,17,18,19,20,21,22,23,24,25,26,27,28,29,30,31,63,0,0,0,0}},
   {2,24,1,44,9,{199,0,0,0,0,0,0,0,0,0,0},{255,0,0,0,0,0,0,0,0,0,0},{32,3,37,39,41,43,45,46,47,48,49,50,51,52,53,54,55,56,57,58,59,60,61,62,0,0,0,0,0,0}},
   {2,6,5,255,255,{52,47,131,150,238,0,0,0,0,0,0},{0,255,0,0,96,0,0,0,0,0,0},{1,35,6,8,10,12,0,0,0,0,0,0,0,0,0,0,0,0,0,0,0,0,0,0,0,0,0,0,0,0}},
   {2,2,6,28,255,{1,12,84,125,158,219,0,0,0,0,0},{0,0,0,0,0,0,0,0,0,0,0},{33,4,0,0,0,0,0,0,0,0,0,0,0,0,0,0,0,0,0,0,0,0,0,0,0,0,0,0,0,0}},
   {2,6,8,255,255,{0,41,20,90,108,138,171,239,0,0,0},{0,0,31,0,0,0,0,128,0,0,0},{2,36,38,40,42,44,0,0,0,0,0,0,0,0,0,0,0,0,0,0,0,0,0,0,0,0,0,0,0,0}},
   {10,18,2,4,10,{136,156,0,0,0,0,0,0,0,0,0},{0,0,0,0,0,0,0,0,0,0,0},{0,32,41,37,34,38,43,35,39,44,40,45,18,20,22,24,26,28,0,0,0,0,0,0,0,0,0,0,0,0}},
   {10,20,2,2,11,{160,186,0,0,0,0,0,0,0,0,0},{0,0,0,0,0,0,0,0,0,0,0},{1,4,6,8,10,11,12,13,14,15,16,17,19,21,23,25,27,29,30,31,0,0,0,0,0,0,0,0,0,0}},
   {10,4,8,255,255,{9,67,51,93,139,177,197,243,0,0,0},{0,0,0,0,0,0,0,15,0,0,0},{2,36,33,42,0,0,0,0,0,0,0,0,0,0,0,0,0,0,0,0,0,0,0,0,0,0,0,0,0,0}},
   {10,4,5,255,255,{15,85,127,209,254,0,0,0,0,0,0},{255,0,255,0,0,0,0,0,0,0,0},{3,5,7,9,0,0,0,0,0,0,0,0,0,0,0,0,0,0,0,0,0,0,0,0,0,0,0,0,0,0}},
   {3,26,1,5,12,{216,0,0,0,0,0,0,0,0,0,0},{0,0,0,0,0,0,0,0,0,0,0},{0,2,4,6,8,10,43,13,46,16,17,18,19,20,21,22,23,24,25,26,27,28,29,30,31,63,0,0,0,0}},
   {3,24,2,255,13,{223,242,0,0,0,0,0,0,0,0,0},{192,0,0,0,0,0,0,0,0,0,0},{32,34,36,38,40,42,12,45,15,48,49,50,51,52,53,54,55,56,57,58,59,60,61,62,0,0,0,0,0,0}},
   {3,5,6,19,255,{32,13,78,121,137,157,0,0,0,0,0},{0,0,0,0,0,0,0,0,0,0,0},{1,3,5,7,9,0,0,0,0,0,0,0,0,0,0,0,0,0,0,0,0,0,0,0,0,0,0,0,0,0}},
   {3,9,5,27,255,{80,37,100,124,231,0,0,0,0,0,0},{0,0,0,0,128,0,0,0,0,0,0},{33,35,37,39,41,11,44,14,47,0,0,0,0,0,0,0,0,0,0,0,0,0,0,0,0,0,0,0,0,0}},
   {11,19,3,37,14,{154,210,214,0,0,0,0,0,0,0,0},{0,0,127,0,0,0,0,0,0,0,0},{0,32,41,37,34,38,43,35,39,44,40,45,18,20,22,24,26,28,30,0,0,0,0,0,0,0,0,0,0,0}},
   {11,19,1,8,15,{173,0,0,0,0,0,0,0,0,0,0},{0,0,0,0,0,0,0,0,0,0,0},{1,4,6,8,10,11,12,13,14,15,16,17,19,21,23,25,27,29,31,0,0,0,0,0,0,0,0,0,0,0}},
   {11,4,5,11,255,{3,35,83,103,227,0,0,0,0,0,0},{0,0,0,255,0,0,0,0,0,0,0},{2,36,33,42,0,0,0,0,0,0,0,0,0,0,0,0,0,0,0,0,0,0,0,0,0,0,0,0,0,0}},
   {11,4,6,47,255,{8,17,6,94,140,207,0,0,0,0,0},{0,0,127,0,0,255,0,0,0,0,0},{3,5,7,9,0,0,0,0,0,0,0,0,0,0,0,0,0,0,0,0,0,0,0,0,0,0,0,0,0,0}},
   {4,24,2,41,16,{180,252,0,0,0,0,0,0,0,0,0},{0,0,0,0,0,0,0,0,0,0,0},{0,2,4,6,8,10,43,13,46,16,17,18,19,20,21,22,23,24,25,26,27,28,29,30,0,0,0,0,0,0}},
   {4,26,0,3,17,{0,0,0,0,0,0,0,0,0,0,0},{0,0,0,0,0,0,0,0,0,0,0},{32,34,36,38,40,42,12,45,15,48,49,50,51,52,53,54,55,56,57,58,59,60,61,62,31,63,0,0,0,0}},
   {4,5,4,45,255,{23,79,162,183,0,0,0,0,0,0,0},{224,255,0,128,0,0,0,0,0,0,0},{1,3,5,7,9,0,0,0,0,0,0,0,0,0,0,0,0,0,0,0,0,0,0,0,0,0,0,0,0,0}},
   {4,9,7,255,255,{88,45,97,118,222,233,250,0,0,0,0},{0,0,0,0,0,0,0,0,0,0,0},{33,35,37,39,41,11,44,14,47,0,0,0,0,0,0,0,0,0,0,0,0,0,0,0,0,0,0,0,0,0}},
   {12,18,3,25,18,{128,170,191,0,0,0,0,0,0,0,0},{0,0,255,0,0,0,0,0,0,0,0},{0,32,41,37,34,38,43,35,39,44,40,45,18,20,22,24,26,28,0,0,0,0,0,0,0,0,0,0,0,0}},
   {12,20,1,31,19,{175,0,0,0,0,0,0,0,0,0,0},{255,0,0,0,0,0,0,0,0,0,0},{1,4,6,8,10,11,12,13,14,15,16,17,19,21,23,25,27,29,30,31,0,0,0,0,0,0,0,0,0,0}},
   {12,4,8,255,255,{10,74,57,75,113,119,195,245,0,0,0},{0,0,0,0,0,255,0,63,0,0,0},{2,36,33,42,0,0,0,0,0,0,0,0,0,0,0,0,0,0,0,0,0,0,0,0,0,0,0,0,0,0}},
   {12,4,6,255,255,{27,44,86,133,196,236,0,0,0,0,0},{0,0,0,0,0,31,0,0,0,0,0},{3,5,7,9,0,0,0,0,0,0,0,0,0,0,0,0,0,0,0,0,0,0,0,0,0,0,0,0,0,0}},
   {5,25,0,23,20,{0,0,0,0,0,0,0,0,0,0,0},{0,0,0,0,0,0,0,0,0,0,0},{0,34,5,39,10,12,13,14,15,16,17,18,19,20,21,22,23,24,25,26,27,28,29,30,31,0,0,0,0,0}},
   {5,25,0,17,21,{0,0,0,0,0,0,0,0,0,0,0},{0,0,0,0,0,0,0,0,0,0,0},{32,3,37,8,42,44,45,46,47,48,49,50,51,52,53,54,55,56,57,58,59,60,61,62,63,0,0,0,0,0}},
   {5,5,5,1,255,{21,61,106,130,148,0,0,0,0,0,0},{0,0,0,0,0,0,0,0,0,0,0},{1,35,6,40,11,0,0,0,0,0,0,0,0,0,0,0,0,0,0,0,0,0,0,0,0,0,0,0,0,0}},
   {5,4,5,16,255,{24,11,53,101,165,0,0,0,0,0,0},{0,0,0,0,0,0,0,0,0,0,0},{33,4,38,9,0,0,0,0,0,0,0,0,0,0,0,0,0,0,0,0,0,0,0,0,0,0,0,0,0,0}},
   {5,5,5,38,255,{19,31,105,126,198,0,0,0,0,0,0},{0,255,0,0,0,0,0,0,0,0,0},{2,36,7,41,43,0,0,0,0,0,0,0,0,0,0,0,0,0,0,0,0,0,0,0,0,0,0,0,0,0}},
   {13,17,6,255,22,{112,145,185,193,202,229,0,0,0,0,0},{0,0,0,0,0,63,0,0,0,0,0},{0,32,41,37,34,38,43,35,39,44,40,45,18,20,22,24,26,0,0,0,0,0,0,0,0,0,0,0,0,0}},
   {13,21,2,46,23,{178,213,0,0,0,0,0,0,0,0,0},{0,0,0,0,0,0,0,0,0,0,0},{1,4,6,8,10,11,12,13,14,15,16,17,19,21,23,25,27,28,29,30,31,0,0,0,0,0,0,0,0,0}},
   {13,4,4,15,255,{7,81,95,147,0,0,0,0,0,0,0},{128,0,255,0,0,0,0,0,0,0,0},{2,36,33,42,0,0,0,0,0,0,0,0,0,0,0,0,0,0,0,0,0,0,0,0,0,0,0,0,0,0}},
   {13,4,6,36,255,{38,65,70,141,203,234,0,0,0,0,0},{0,0,0,0,0,0,0,0,0,0,0},{3,5,7,9,0,0,0,0,0,0,0,0,0,0,0,0,0,0,0,0,0,0,0,0,0,0,0,0,0,0}},
   {6,24,2,7,24,{218,208,0,0,0,0,0,0,0,0,0},{0,0,0,0,0,0,0,0,0,0,0},{0,2,4,6,8,10,12,14,15,16,17,18,19,20,21,22,23,24,25,26,27,28,29,30,0,0,0,0,0,0}},
   {6,26,1,39,25,{246,0,0,0,0,0,0,0,0,0,0},{0,0,0,0,0,0,0,0,0,0,0},{32,34,36,38,40,42,44,46,47,48,49,50,51,52,53,54,55,56,57,58,59,60,61,62,31,63,0,0,0,0}},
   {6,7,4,13,255,{60,77,110,168,0,0,0,0,0,0,0},{0,0,0,0,0,0,0,0,0,0,0},{1,3,5,7,9,11,13,0,0,0,0,0,0,0,0,0,0,0,0,0,0,0,0,0,0,0,0,0,0,0}},
   {6,7,6,35,255,{25,46,102,169,166,240,0,0,0,0,0},{0,0,0,0,0,0,0,0,0,0,0},{33,35,37,39,41,43,45,0,0,0,0,0,0,0,0,0,0,0,0,0,0,0,0,0,0,0,0,0,0,0}},
   {14,17,5,255,26,{104,155,188,235,248,0,0,0,0,0,0},{0,0,0,0,0,0,0,0,0,0,0},{0,32,41,37,34,38,43,35,39,44,40,45,18,20,22,24,26,0,0,0,0,0,0,0,0,0,0,0,0,0}},
   {14,21,2,18,27,{176,200,0,0,0,0,0,0,0,0,0},{0,0,0,0,0,0,0,0,0,0,0},{1,4,6,8,10,11,12,13,14,15,16,17,19,21,23,25,27,28,29,30,31,0,0,0,0,0,0,0,0,0}},
   {14,4,5,20,255,{18,49,34,55,134,0,0,0,0,0,0},{0,0,0,255,0,0,0,0,0,0,0},{2,36,33,42,0,0,0,0,0,0,0,0,0,0,0,0,0,0,0,0,0,0,0,0,0,0,0,0,0,0}},
   {14,4,6,255,255,{40,36,73,71,135,230,0,0,0,0,0},{0,0,0,255,255,64,0,0,0,0,0},{3,5,7,9,0,0,0,0,0,0,0,0,0,0,0,0,0,0,0,0,0,0,0,0,0,0,0,0,0,0}},
   {7,26,0,0,28,{0,0,0,0,0,0,0,0,0,0,0},{0,0,0,0,0,0,0,0,0,0,0},{0,2,4,6,8,10,12,45,15,16,17,18,19,20,21,22,23,24,25,26,27,28,29,30,31,63,0,0,0,0}},
   {7,24,1,32,29,{182,0,0,0,0,0,0,0,0,0,0},{127,0,0,0,0,0,0,0,0,0,0},{32,34,36,38,40,42,44,14,47,48,49,50,51,52,53,54,55,56,57,58,59,60,61,62,0,0,0,0,0,0}},
   {7,8,5,9,255,{72,28,99,111,192,0,0,0,0,0,0},{0,0,0,255,0,0,0,0,0,0,0},{1,3,5,7,9,11,13,46,0,0,0,0,0,0,0,0,0,0,0,0,0,0,0,0,0,0,0,0,0,0}},
   {7,6,8,26,255,{48,33,2,76,107,143,217,226,0,0,0},{0,0,0,0,0,255,0,0,0,0,0},{33,35,37,39,41,43,0,0,0,0,0,0,0,0,0,0,0,0,0,0,0,0,0,0,0,0,0,0,0,0}},
   {15,19,2,30,30,{144,167,0,0,0,0,0,0,0,0,0},{0,255,0,0,0,0,0,0,0,0,0},{0,32,41,37,34,38,43,35,39,44,40,45,18,20,22,24,26,28,30,0,0,0,0,0,0,0,0,0,0,0}},
   {15,19,3,255,31,{152,163,247,0,0,0,0,0,0,0,0},{0,0,192,0,0,0,0,0,0,0,0},{1,4,6,8,10,11,12,13,14,15,16,17,19,21,23,25,27,29,31,0,0,0,0,0,0,0,0,0,0,0}},
   {15,4,5,29,255,{14,68,109,161,215,0,0,0,0,0,0},{0,0,0,0,128,0,0,0,0,0,0},{2,36,33,42,0,0,0,0,0,0,0,0,0,0,0,0,0,0,0,0,0,0,0,0,0,0,0,0,0,0}},
   {15,4,6,255,255,{4,59,87,159,228,249,0,0,0,0,0},{0,0,255,255,0,3,0,0,0,0,0},{3,5,7,9,0,0,0,0,0,0,0,0,0,0,0,0,0,0,0,0,0,0,0,0,0,0,0,0,0,0}}},
  32, {5,6,7,5,6,8,10,10,9,4,8,9,6,1,8,4,7,2,5,9,6,10,5,2},
  {{1,2,3,4,5,0,6,7,8,9,10,11,12,13,14,15,16,17,18,19,21,20,24,22,23,25,27,28,26,29,30,31},
   {0,1,2,3,4,5,6,7,9,8,11,10,12,14,13,15,16,17,18,21,19,20,23,22,24,25,26,27,28,29,30,31},
   {1,2,3,7,6,9,10,0,5,8,4,11,12,13,14,15,16,18,20,17,21,19,23,22,24,27,26,25,28,29,30,31},
   {0,2,3,5,1,8,4,7,6,9,10,12,11,13,14,16,15,17,18,19,20,28,21,23,22,24,25,26,27,29,30,31},
   {0,6,4,7,1,2,5,3,9,10,8,11,12,13,14,15,16,19,20,18,17,21,22,23,25,24,26,31,27,28,30,29},
   {2,1,0,3,4,5,6,7,9,8,10,11,12,15,13,14,16,17,20,21,19,22,18,23,25,24,29,26,27,31,30,28},
   {1,3,4,2,0,5,7,6,9,8,10,11,12,13,14,15,23,16,17,18,19,21,22,20,27,24,25,30,26,31,28,29},
   {0,1,2,3,4,5,7,6,8,9,10,11,12,13,14,15,17,16,18,19,20,21,22,26,24,23,28,27,25,30,29,31}}};

typedef CUresult (*EncodeFn)(CUtensorMap*, CUtensorMapDataType, cuuint32_t, void*, const cuuint64_t*, const cuuint64_t*, const cuuint32_t*,
                             const cuuint32_t*, CUtensorMapInterleave, CUtensorMapSwizzle, CUtensorMapL2promotion, CUtensorMapFloatOOBfill);

void make_map2(EncodeFn enc, CUtensorMap* m, const void* ptr, int rows, int cols, int box_rows) {
  cuuint64_t dim[2] = {(cuuint64_t)cols, (cuuint64_t)rows}, str[1] = {(cuuint64_t)cols * 2};
  cuuint32_t box[2] = {64, (cuuint32_t)box_rows}, es[2] = {1, 1};
  enc(m, CU_TENSOR_MAP_DATA_TYPE_BFLOAT16, 2, const_cast<void*>(ptr), dim, str, box, es, CU_TENSOR_MAP_INTERLEAVE_NONE, CU_TENSOR_MAP_SWIZZLE_128B,
      CU_TENSOR_MAP_L2_PROMOTION_L2_128B, CU_TENSOR_MAP_FLOAT_OOB_FILL_NONE);
}
void make_map3(EncodeFn enc, CUtensorMap* m, const void* ptr, int rows) {
  cuuint64_t dim[3] = {64, (cuuint64_t)rows, 9}, str[2] = {DM * 2, 128};
  cuuint32_t box[3] = {64, 32, 3}, es[3] = {1, 1, 1};
  enc(m, CU_TENSOR_MAP_DATA_TYPE_BFLOAT16, 3, const_cast<void*>(ptr), dim, str, box, es, CU_TENSOR_MAP_INTERLEAVE_NONE, CU_TENSOR_MAP_SWIZZLE_128B,
      CU_TENSOR_MAP_L2_PROMOTION_L2_128B, CU_TENSOR_MAP_FLOAT_OOB_FILL_NONE);
}

void make_map_t(EncodeFn enc, CUtensorMap* m, void* ptr, int width, int cols) {
  cuuint64_t dim[3] = {TP / 2, 2, 864}, str[2] = {TP * 2, TP * 4};
  cuuint32_t box[3] = {(cuuint32_t)width, 2, (cuuint32_t)cols}, es[3] = {1, 1, 1};
  enc(m, CU_TENSOR_MAP_DATA_TYPE_UINT32, 3, ptr, dim, str, box, es, CU_TENSOR_MAP_INTERLEAVE_NONE, cols == 64 ? CU_TENSOR_MAP_SWIZZLE_128B : CU_TENSOR_MAP_SWIZZLE_NONE,
      CU_TENSOR_MAP_L2_PROMOTION_NONE, CU_TENSOR_MAP_FLOAT_OOB_FILL_NONE);
}

int g_mode = -1;

}

extern "C" void kernel_launch(void* const* d_in, const int* in_sizes, int n_in, void* d_out, int out_size) {
  static EncodeFn enc = nullptr;
  static void* t_ptr = nullptr;
  if (!enc) {
    void* fn = nullptr;
    cudaDriverEntryPointQueryResult st;
    cudaGetDriverEntryPoint("cuTensorMapEncodeTiled", &fn, cudaEnableDefault, &st);
    enc = (EncodeFn)fn;
    cudaGetSymbolAddress(&t_ptr, g_T);
    cudaFuncSetAttribute(fused_kernel, cudaFuncAttributeMaxDynamicSharedMemorySize, SMEM_BYTES);
    if (g_mode < 0) {
      cudaLaunchConfig_t cfg = {};
      cfg.gridDim = dim3(2 * NCL); cfg.blockDim = dim3(384); cfg.dynamicSmemBytes = SMEM_BYTES;
      cudaLaunchAttribute at; at.id = cudaLaunchAttributeClusterDimension;
      at.val.clusterDim.x = 2; at.val.clusterDim.y = 1; at.val.clusterDim.z = 1;
      cfg.attrs = &at; cfg.numAttrs = 1;
      int nc = 0;
      g_mode = (cudaOccupancyMaxActiveClusters(&nc, fused_kernel, &cfg) == cudaSuccess && nc >= NCL) ? 1 : 0;
      (void)cudaGetLastError();
    }
  }
  Params p;
  make_map2(enc, &p.map_a[0], d_in[4], SEQ, DC, 128);
  make_map2(enc, &p.map_a[1], d_in[0], SEQ, DM, 128);
  make_map2(enc, &p.map_w[0], d_in[6], DC, 4096, 64);
  make_map2(enc, &p.map_w[1], d_in[7], DC, 4096, 64);
  make_map2(enc, &p.map_w[2], d_in[5], DM, 4096, 64);
  make_map2(enc, &p.map_w[3], d_in[1], DM, 1728, 64);
  make_map3(enc, &p.map_o[0], d_in[8], 4096);
  make_map3(enc, &p.map_o[1], d_in[2], DM);
  make_map_t(enc, &p.map_t[0], t_ptr, 32, 9);
  make_map_t(enc, &p.map_t[1], t_ptr, 40, 9);
  make_map_t(enc, &p.map_t[2], t_ptr, 32, 64);
  p.x = (const __nv_bfloat16*)d_in[0];
  p.gate_w = (const __nv_bfloat16*)d_in[9];
  make_map2(enc, &p.map_out, d_out, SEQ, DM, 16);
  p.out = (__nv_bfloat16*)d_out;
  p.zero = 0;
  auto launch = [&](int phases) {
    p.s = k_sched;
    for (int i = 0; i < NCL; i++) {
      Rec& r = p.s.r[i];
      if (!(phases & 1)) r.n1 = 0;
      if (!(phases & 2)) r.n2 = 0;
      if (!(phases & (r.p3 < 24 ? 4 : 32))) r.p3 = 255;
      if (!(phases & 8)) r.bg = 255;
      const int u1 = r.n1 ? 8 + r.n1 * (8 + (r.slab >> 3)) : 0;
      int u2 = 0;
      for (int k = 0; k < r.n2; k++) u2 += 4 * (r.item[k] & 7) + 4;
      r.u1 = (uint8_t)u1; r.u2 = (uint8_t)u2;
      r.rot = (uint8_t)(((u1 % 10 + 1) >> 1) % 5);
      r.x3 = (uint8_t)((r.rot + u2) % 5 & 3);
      r.ring = (phases & 16) ? p.s.ring : 32;
      r.phases = (uint8_t)phases;
    }
    fused_kernel<<<2 * NCL, 384, SMEM_BYTES>>>(p);
  };
  if (g_mode == 1) launch(63);
  else { launch(1); launch(10); launch(32); launch(4); }
}
```

```cpp
#include <cuda_runtime.h>
#include <cuda_bf16.h>
#include <cuda.h>
#include <stdint.h>

namespace {

constexpr int SEQ = 2048, DM = 576, DC = 512, NH = 32;
constexpr int NCL = 66;
constexpr uint32_t DESC_HI = 0x40000040u;

constexpr int SM_RING = 0;
constexpr int SM_BUF = 163840;
constexpr int SM_BAR = 229376;
constexpr int B_P1E = 0, B_P2E = 10, B_P3E = 15, B_P2F = 24, B_SF = 32, B_ORD = 36, B_LAD = 40, B_DONE = 41, B_FIN = 48;
constexpr int B_P3F = 56, B_OUT = 61, B_P1F = 64, B_SE = 74, B_QF = 80, B_LA = 84, B_NUM = 88;
constexpr uint64_t B_CNT = 0x11118245000ull;
constexpr int SMEM_BYTES = SM_BAR + B_NUM * 8 + 1024;

constexpr int F_HEAD = 0;
constexpr int F_QKVA = 32;
constexpr int F_GATE = 64;
constexpr int F_DONE = 65;
constexpr int F_CTX = 96;
constexpr int F_OUT = 96 + 8 * 64;
constexpr int F_NUM = F_OUT + 48;

struct Rec {
  uint8_t slab;
  uint8_t n1, n2;
  uint8_t p3;
  uint8_t bg;
  uint8_t item[11];
  uint8_t last[11];
  uint8_t tile[31];
  uint8_t ring;
  uint8_t u1, u2;
  uint8_t rot, x3;
  uint8_t phases;
};
struct Sched {
  Rec r[NCL];
  uint8_t ring;
  uint8_t nh[24];
  uint8_t p3_order[8][32];
};

struct Params {
  CUtensorMap map_a[2];
  CUtensorMap map_w[4];
  CUtensorMap map_o[2];
  CUtensorMap map_t[3];
  CUtensorMap map_out;
  const __nv_bfloat16* x;
  const __nv_bfloat16* gate_w;
  __nv_bfloat16* out;
  int zero;
  alignas(64) Sched s;
};

__device__ __align__(1024) uint8_t g_Q[NH * 32 * 16384];
__device__ __align__(1024) uint8_t g_KV[2 * NH * 16 * 32768];
__device__ __align__(1024) uint8_t g_oA[32 * 576 * 128];
constexpr int TP = SEQ + 16;
__device__ __align__(1024) uint32_t g_T[864 * TP];
__device__ float g_gate[SEQ];
__device__ int g_flags[F_NUM];

__device__ __forceinline__ void mbar_arrive(uint32_t b) { asm volatile("mbarrier.arrive.shared::cta.b64 _, [%0];" ::"r"(b) : "memory"); }
__device__ __forceinline__ void mbar_arrive_cl(uint32_t b, int cnt) {
  asm volatile("mbarrier.arrive.shared::cluster.b64 _, [%0], %1;" ::"r"(b), "r"(cnt) : "memory");
}
__device__ __forceinline__ void mbar_wait(uint32_t b, int par) {
  asm volatile(
      "{\n.reg .pred p;\n.reg .u32 c;\n"
      "mbarrier.try_wait.parity.shared::cta.b64 p, [%0], %1;\n@p bra DN;\nmov.u32 c, 0;\n"
      "LP:\nmbarrier.try_wait.parity.shared::cta.b64 p, [%0], %1;\n@p bra DN;\n"
      "add.u32 c, c, 1;\nsetp.lt.u32 p, c, 4000000;\n@p bra LP;\ntrap;\nDN:\n}" ::"r"(b), "r"(par) : "memory");
}
__device__ __forceinline__ uint32_t mapa(uint32_t a, uint32_t cta) {
  uint32_t r; asm("mapa.shared::cluster.u32 %0, %1, %2;" : "=r"(r) : "r"(a), "r"(cta)); return r;
}
#define ELECT(ins) "{\n.reg .pred e;\nelect.sync _|e, 0xffffffff;\n@e " ins "\n}"
__device__ __forceinline__ void mbar_expect(uint32_t b, int bytes) {
  asm volatile(ELECT("mbarrier.arrive.expect_tx.shared::cta.b64 _, [%0], %1;") ::"r"(b), "r"(bytes) : "memory");
}
__device__ __forceinline__ void mbar_arrive_one(uint32_t b) { asm volatile(ELECT("mbarrier.arrive.shared::cta.b64 _, [%0];") ::"r"(b) : "memory"); }
constexpr uint64_t L2_NORMAL = 0x1000000000000000ull, L2_FIRST = 0x12F0000000000000ull;
__device__ __forceinline__ void bulk_load(uint32_t dst, const void* src, int bytes, uint32_t bar, uint64_t pol = L2_NORMAL) {
  asm volatile(ELECT("cp.async.bulk.shared::cluster.global.mbarrier::complete_tx::bytes.L2::cache_hint [%0], [%1], %2, [%3], %4;") ::"r"(dst), "l"(src), "r"(bytes), "r"(bar), "l"(pol) : "memory");
}
__device__ __forceinline__ void bulk_load_mc(uint32_t dst, const void* src, int bytes, uint32_t bar, uint64_t pol = L2_NORMAL) {
  asm volatile(ELECT("cp.async.bulk.shared::cluster.global.mbarrier::complete_tx::bytes.multicast::cluster.L2::cache_hint [%0], [%1], %2, [%3], %4, %5;") ::"r"(dst), "l"(src), "r"(bytes), "r"(bar), "h"((uint16_t)3), "l"(pol) : "memory");
}
__device__ __forceinline__ void bulk_store(void* dst, uint32_t src, int bytes, uint64_t pol = L2_NORMAL) {
  asm volatile(ELECT("cp.async.bulk.global.shared::cta.bulk_group.L2::cache_hint [%0], [%1], %2, %3;") ::"l"(dst), "r"(src), "r"(bytes), "l"(pol) : "memory");
}
__device__ __forceinline__ void tma2d(uint32_t dst, const CUtensorMap* m, int c0, int c1, uint32_t bar, uint64_t pol = L2_NORMAL) {
  asm volatile(ELECT("cp.async.bulk.tensor.2d.shared::cluster.global.mbarrier::complete_tx::bytes.L2::cache_hint [%0], [%1, {%3, %4}], [%2], %5;") ::"r"(dst), "l"(m), "r"(bar), "r"(c0), "r"(c1), "l"(pol) : "memory");
}
__device__ __forceinline__ void tma2d_mc(uint32_t dst, const CUtensorMap* m, int c0, int c1, uint32_t bar, uint64_t pol = L2_NORMAL) {
  asm volatile(ELECT("cp.async.bulk.tensor.2d.shared::cluster.global.mbarrier::complete_tx::bytes.multicast::cluster.L2::cache_hint [%0], [%1, {%3, %4}], [%2], %5, %6;") ::"r"(dst), "l"(m), "r"(bar), "r"(c0), "r"(c1), "h"((uint16_t)3), "l"(pol) : "memory");
}
__device__ __forceinline__ void tma3d(uint32_t dst, const CUtensorMap* m, int c0, int c1, int c2, uint32_t bar, uint64_t pol = L2_NORMAL) {
  asm volatile(ELECT("cp.async.bulk.tensor.3d.shared::cluster.global.mbarrier::complete_tx::bytes.L2::cache_hint [%0], [%1, {%3, %4, %5}], [%2], %6;") ::"r"(dst), "l"(m), "r"(bar), "r"(c0), "r"(c1), "r"(c2), "l"(pol) : "memory");
}
__device__ __forceinline__ void tma3d_mc(uint32_t dst, const CUtensorMap* m, int c0, int c1, int c2, uint32_t bar, uint64_t pol = L2_NORMAL) {
  asm volatile(ELECT("cp.async.bulk.tensor.3d.shared::cluster.global.mbarrier::complete_tx::bytes.multicast::cluster.L2::cache_hint [%0], [%1, {%3, %4, %5}], [%2], %6, %7;") ::"r"(dst), "l"(m), "r"(bar), "r"(c0), "r"(c1), "r"(c2), "h"((uint16_t)3), "l"(pol) : "memory");
}
__device__ __forceinline__ void tma2d_add(const CUtensorMap* m, uint32_t src, int c0, int c1) {
  asm volatile(ELECT("cp.reduce.async.bulk.tensor.2d.global.shared::cta.add.bulk_group [%0, {%2, %3}], [%1];") ::"l"(m), "r"(src), "r"(c0), "r"(c1) : "memory");
}
__device__ __forceinline__ void tma3d_store(const CUtensorMap* m, uint32_t src, int c0, int c1, int c2, uint64_t pol = L2_NORMAL) {
  asm volatile(ELECT("cp.async.bulk.tensor.3d.global.shared::cta.bulk_group.L2::cache_hint [%0, {%2, %3, %4}], [%1], %5;") ::"l"(m), "r"(src), "r"(c0), "r"(c1), "r"(c2), "l"(pol) : "memory");
}
__device__ __forceinline__ void tma2d_prefetch(const CUtensorMap* m, int c0, int c1, uint64_t pol = L2_NORMAL) {
  asm volatile(ELECT("cp.async.bulk.prefetch.tensor.2d.L2.global.L2::cache_hint [%0, {%1, %2}], %3;") ::"l"(m), "r"(c0), "r"(c1), "l"(pol) : "memory");
}
#define HINT 62
#define POL(bit) ((HINT >> (bit)) & 1 ? L2_FIRST : L2_NORMAL)
#define BULK_COMMIT() asm volatile("cp.async.bulk.commit_group;" ::: "memory")
#define BULK_WAIT(n) asm volatile("cp.async.bulk.wait_group %0;" ::"n"(n) : "memory")
#define BULK_WAIT_READ(n) asm volatile("cp.async.bulk.wait_group.read %0;" ::"n"(n) : "memory")
#define FENCE_ASYNC_SMEM() asm volatile("fence.proxy.async.shared::cta;" ::: "memory")
#define FENCE_ASYNC_ALL() asm volatile("fence.proxy.async;" ::: "memory")
#define WG_FENCE() asm volatile("wgmma.fence.sync.aligned;" ::: "memory")
#define WG_COMMIT() asm volatile("wgmma.commit_group.sync.aligned;" ::: "memory")
#define WG_WAIT(n) asm volatile("wgmma.wait_group.sync.aligned %0;" ::"n"(n) : "memory")
__device__ __forceinline__ void bar_sync(int id, int n) { asm volatile("bar.sync %0, %1;" ::"r"(id), "r"(n) : "memory"); }
__device__ __forceinline__ void bar_arrive(int id, int n) { asm volatile("bar.arrive %0, %1;" ::"r"(id), "r"(n) : "memory"); }
__device__ __forceinline__ void cluster_sync() {
  asm volatile("barrier.cluster.arrive.relaxed;\nbarrier.cluster.wait.acquire;" ::: "memory");
}
template <int N> __device__ __forceinline__ void pin(float (&r)[N]) {
#pragma unroll
  for (int i = 0; i < N; i++) asm volatile("" : "+f"(r[i])::"memory");
}
template <int N> __device__ __forceinline__ void pin(uint32_t (&r)[N]) {
#pragma unroll
  for (int i = 0; i < N; i++) asm volatile("" : "+r"(r[i])::"memory");
}
__device__ __forceinline__ uint32_t pack_bf16(float lo, float hi) {
  uint32_t r; asm("cvt.rn.bf16x2.f32 %0, %1, %2;" : "=r"(r) : "f"(hi), "f"(lo)); return r;
}
__device__ __forceinline__ float ex2(float x) { float r; asm("ex2.approx.ftz.f32 %0, %1;" : "=f"(r) : "f"(x)); return r; }
__device__ __forceinline__ void ldsm4(uint32_t a, uint32_t& r0, uint32_t& r1, uint32_t& r2, uint32_t& r3) {
  asm volatile("ldmatrix.sync.aligned.m8n8.x4.shared.b16 {%0,%1,%2,%3}, [%4];" : "=r"(r0), "=r"(r1), "=r"(r2), "=r"(r3) : "r"(a) : "memory");
}
__device__ __forceinline__ void stsm4(uint32_t a, uint32_t r0, uint32_t r1, uint32_t r2, uint32_t r3) {
  asm volatile("stmatrix.sync.aligned.m8n8.x4.shared.b16 [%0], {%1,%2,%3,%4};" ::"r"(a), "r"(r0), "r"(r1), "r"(r2), "r"(r3) : "memory");
}
__device__ __forceinline__ void flag_add(int idx) {
  asm volatile(ELECT("red.release.gpu.global.add.s32 [%0], 1;") ::"l"(g_flags + idx) : "memory");
}
__device__ __forceinline__ void flag_add_rx(int idx) {
  asm volatile(ELECT("red.relaxed.gpu.global.add.s32 [%0], 1;") ::"l"(g_flags + idx) : "memory");
}
template <bool ACQ, int NS = 32> __device__ __forceinline__ void flag_wait(int idx, int target) {
  int n = 0;
  while (true) {
    int v;
    if (ACQ) asm volatile("ld.acquire.gpu.global.s32 %0, [%1];" : "=r"(v) : "l"(g_flags + idx) : "memory");
    else asm volatile("ld.relaxed.gpu.global.s32 %0, [%1];" : "=r"(v) : "l"(g_flags + idx) : "memory");
    if (__all_sync(0xffffffffu, v >= target)) break;
    if (++n > 20000000) __trap();
    __nanosleep(NS);
  }
}
__device__ __forceinline__ uint32_t desc_lo(uint32_t addr, uint32_t lbo) { return ((addr & 0x3FFFFu) >> 4) | ((lbo >> 4) << 16); }
#define PROF(role, i)
#define PROFX(cond, i)
#define PROFB(i)
#define PROFG(i)

template <int TB, int TA = 0> __device__ __forceinline__ void wgmma_ss64(float (&d)[32], uint32_t alo, uint32_t blo, int sd) {
  asm volatile("{\n.reg .pred p;\n.reg .b64 da, db;\n"
    "setp.ne.b32 p, %34, 0;\nmov.b64 da, {%32, %36};\nmov.b64 db, {%33, %36};\n"
    "wgmma.mma_async.sync.aligned.m64n64k16.f32.bf16.bf16 "
    "{%0,%1,%2,%3,%4,%5,%6,%7,%8,%9,%10,%11,%12,%13,%14,%15,%16,%17,%18,%19,%20,%21,%22,%23,"
    "%24,%25,%26,%27,%28,%29,%30,%31}, "
    "da, db, p, 1, 1, %37, %35;\n}\n"
    : "+f"(d[0]),"+f"(d[1]),"+f"(d[2]),"+f"(d[3]),"+f"(d[4]),"+f"(d[5]),"+f"(d[6]),"+f"(d[7]),"+f"(d[8]),"+f"(d[9]),"+f"(d[10]),"+f"(d[11]),
      "+f"(d[12]),"+f"(d[13]),"+f"(d[14]),"+f"(d[15]),"+f"(d[16]),"+f"(d[17]),"+f"(d[18]),"+f"(d[19]),"+f"(d[20]),"+f"(d[21]),"+f"(d[22]),"+f"(d[23]),
      "+f"(d[24]),"+f"(d[25]),"+f"(d[26]),"+f"(d[27]),"+f"(d[28]),"+f"(d[29]),"+f"(d[30]),"+f"(d[31])
    : "r"(alo), "r"(blo), "r"(sd), "n"(TB), "r"(DESC_HI), "n"(TA));
}
template <int TB, int TA = 0> __device__ __forceinline__ void wgmma_ss128(float (&d)[64], uint32_t alo, uint32_t blo, int sd) {
  asm volatile("{\n.reg .pred p;\n.reg .b64 da, db;\n"
    "setp.ne.b32 p, %66, 0;\nmov.b64 da, {%64, %68};\nmov.b64 db, {%65, %68};\n"
    "wgmma.mma_async.sync.aligned.m64n128k16.f32.bf16.bf16 "
    "{%0,%1,%2,%3,%4,%5,%6,%7,%8,%9,%10,%11,%12,%13,%14,%15,%16,%17,%18,%19,%20,%21,%22,%23,"
    "%24,%25,%26,%27,%28,%29,%30,%31,%32,%33,%34,%35,%36,%37,%38,%39,%40,%41,%42,%43,%44,%45,%46,%47,"
    "%48,%49,%50,%51,%52,%53,%54,%55,%56,%57,%58,%59,%60,%61,%62,%63}, "
    "da, db, p, 1, 1, %69, %67;\n}\n"
    : "+f"(d[0]),"+f"(d[1]),"+f"(d[2]),"+f"(d[3]),"+f"(d[4]),"+f"(d[5]),"+f"(d[6]),"+f"(d[7]),"+f"(d[8]),"+f"(d[9]),"+f"(d[10]),"+f"(d[11]),
      "+f"(d[12]),"+f"(d[13]),"+f"(d[14]),"+f"(d[15]),"+f"(d[16]),"+f"(d[17]),"+f"(d[18]),"+f"(d[19]),"+f"(d[20]),"+f"(d[21]),"+f"(d[22]),"+f"(d[23]),
      "+f"(d[24]),"+f"(d[25]),"+f"(d[26]),"+f"(d[27]),"+f"(d[28]),"+f"(d[29]),"+f"(d[30]),"+f"(d[31]),"+f"(d[32]),"+f"(d[33]),"+f"(d[34]),"+f"(d[35]),
      "+f"(d[36]),"+f"(d[37]),"+f"(d[38]),"+f"(d[39]),"+f"(d[40]),"+f"(d[41]),"+f"(d[42]),"+f"(d[43]),"+f"(d[44]),"+f"(d[45]),"+f"(d[46]),"+f"(d[47]),
      "+f"(d[48]),"+f"(d[49]),"+f"(d[50]),"+f"(d[51]),"+f"(d[52]),"+f"(d[53]),"+f"(d[54]),"+f"(d[55]),"+f"(d[56]),"+f"(d[57]),"+f"(d[58]),"+f"(d[59]),
      "+f"(d[60]),"+f"(d[61]),"+f"(d[62]),"+f"(d[63])
    : "r"(alo), "r"(blo), "r"(sd), "n"(TB), "r"(DESC_HI), "n"(TA));
}
template <int TB> __device__ __forceinline__ void wgmma_rs128(float (&d)[64], uint32_t a0, uint32_t a1, uint32_t a2, uint32_t a3, uint32_t blo, int sd) {
  asm volatile("{\n.reg .pred p;\n.reg .b64 db;\n"
    "setp.ne.b32 p, %69, 0;\nmov.b64 db, {%68, %71};\n"
    "wgmma.mma_async.sync.aligned.m64n128k16.f32.bf16.bf16 "
    "{%0,%1,%2,%3,%4,%5,%6,%7,%8,%9,%10,%11,%12,%13,%14,%15,%16,%17,%18,%19,%20,%21,%22,%23,"
    "%24,%25,%26,%27,%28,%29,%30,%31,%32,%33,%34,%35,%36,%37,%38,%39,%40,%41,%42,%43,%44,%45,%46,%47,"
    "%48,%49,%50,%51,%52,%53,%54,%55,%56,%57,%58,%59,%60,%61,%62,%63}, "
    "{%64,%65,%66,%67}, db, p, 1, 1, %70;\n}\n"
    : "+f"(d[0]),"+f"(d[1]),"+f"(d[2]),"+f"(d[3]),"+f"(d[4]),"+f"(d[5]),"+f"(d[6]),"+f"(d[7]),"+f"(d[8]),"+f"(d[9]),"+f"(d[10]),"+f"(d[11]),
      "+f"(d[12]),"+f"(d[13]),"+f"(d[14]),"+f"(d[15]),"+f"(d[16]),"+f"(d[17]),"+f"(d[18]),"+f"(d[19]),"+f"(d[20]),"+f"(d[21]),"+f"(d[22]),"+f"(d[23]),
      "+f"(d[24]),"+f"(d[25]),"+f"(d[26]),"+f"(d[27]),"+f"(d[28]),"+f"(d[29]),"+f"(d[30]),"+f"(d[31]),"+f"(d[32]),"+f"(d[33]),"+f"(d[34]),"+f"(d[35]),
      "+f"(d[36]),"+f"(d[37]),"+f"(d[38]),"+f"(d[39]),"+f"(d[40]),"+f"(d[41]),"+f"(d[42]),"+f"(d[43]),"+f"(d[44]),"+f"(d[45]),"+f"(d[46]),"+f"(d[47]),
      "+f"(d[48]),"+f"(d[49]),"+f"(d[50]),"+f"(d[51]),"+f"(d[52]),"+f"(d[53]),"+f"(d[54]),"+f"(d[55]),"+f"(d[56]),"+f"(d[57]),"+f"(d[58]),"+f"(d[59]),
      "+f"(d[60]),"+f"(d[61]),"+f"(d[62]),"+f"(d[63])
    : "r"(a0), "r"(a1), "r"(a2), "r"(a3), "r"(blo), "r"(sd), "n"(TB), "r"(DESC_HI));
}
template <int TB, int TA = 0> __device__ __forceinline__ void wgmma_ss192(float (&d)[96], uint32_t alo, uint32_t blo, int sd) {
  asm volatile("{\n.reg .pred p;\n.reg .b64 da, db;\n"
    "setp.ne.b32 p, %98, 0;\nmov.b64 da, {%96, %100};\nmov.b64 db, {%97, %100};\n"
    "wgmma.mma_async.sync.aligned.m64n192k16.f32.bf16.bf16 "
    "{%0,%1,%2,%3,%4,%5,%6,%7,%8,%9,%10,%11,%12,%13,%14,%15,%16,%17,%18,%19,%20,%21,%22,%23,"
    "%24,%25,%26,%27,%28,%29,%30,%31,%32,%33,%34,%35,%36,%37,%38,%39,%40,%41,%42,%43,%44,%45,%46,%47,"
    "%48,%49,%50,%51,%52,%53,%54,%55,%56,%57,%58,%59,%60,%61,%62,%63,%64,%65,%66,%67,%68,%69,%70,%71,"
    "%72,%73,%74,%75,%76,%77,%78,%79,%80,%81,%82,%83,%84,%85,%86,%87,%88,%89,%90,%91,%92,%93,%94,%95}, "
    "da, db, p, 1, 1, %101, %99;\n}\n"
    : "+f"(d[0]),"+f"(d[1]),"+f"(d[2]),"+f"(d[3]),"+f"(d[4]),"+f"(d[5]),"+f"(d[6]),"+f"(d[7]),"+f"(d[8]),"+f"(d[9]),"+f"(d[10]),"+f"(d[11]),
      "+f"(d[12]),"+f"(d[13]),"+f"(d[14]),"+f"(d[15]),"+f"(d[16]),"+f"(d[17]),"+f"(d[18]),"+f"(d[19]),"+f"(d[20]),"+f"(d[21]),"+f"(d[22]),"+f"(d[23]),
      "+f"(d[24]),"+f"(d[25]),"+f"(d[26]),"+f"(d[27]),"+f"(d[28]),"+f"(d[29]),"+f"(d[30]),"+f"(d[31]),"+f"(d[32]),"+f"(d[33]),"+f"(d[34]),"+f"(d[35]),
      "+f"(d[36]),"+f"(d[37]),"+f"(d[38]),"+f"(d[39]),"+f"(d[40]),"+f"(d[41]),"+f"(d[42]),"+f"(d[43]),"+f"(d[44]),"+f"(d[45]),"+f"(d[46]),"+f"(d[47]),
      "+f"(d[48]),"+f"(d[49]),"+f"(d[50]),"+f"(d[51]),"+f"(d[52]),"+f"(d[53]),"+f"(d[54]),"+f"(d[55]),"+f"(d[56]),"+f"(d[57]),"+f"(d[58]),"+f"(d[59]),
      "+f"(d[60]),"+f"(d[61]),"+f"(d[62]),"+f"(d[63]),"+f"(d[64]),"+f"(d[65]),"+f"(d[66]),"+f"(d[67]),"+f"(d[68]),"+f"(d[69]),"+f"(d[70]),"+f"(d[71]),
      "+f"(d[72]),"+f"(d[73]),"+f"(d[74]),"+f"(d[75]),"+f"(d[76]),"+f"(d[77]),"+f"(d[78]),"+f"(d[79]),"+f"(d[80]),"+f"(d[81]),"+f"(d[82]),"+f"(d[83]),
      "+f"(d[84]),"+f"(d[85]),"+f"(d[86]),"+f"(d[87]),"+f"(d[88]),"+f"(d[89]),"+f"(d[90]),"+f"(d[91]),"+f"(d[92]),"+f"(d[93]),"+f"(d[94]),"+f"(d[95])
    : "r"(alo), "r"(blo), "r"(sd), "n"(TB), "r"(DESC_HI), "n"(TA));
}

struct Ctx {
  uint32_t sm;
  uint32_t bar;
  uint32_t rbar;
  int cl, rank, wg, warp, lane, phases;
};
__device__ __forceinline__ void release(const Ctx& c, int b, int cnt = 1) {
  if (c.lane < 2) mbar_arrive_cl(c.rbar + b * 8, cnt);
}
#define PFM 7
#define PF1 1
constexpr float SM_SCALE = 0.08838834764831845f * 1.4426950408889634f;
constexpr float SM_HI = 1.8446744e19f, SM_LO = 5.4210109e-20f;
constexpr int ORDER = 1;

__device__ __forceinline__ void stage_tile(const float (&a)[64], uint32_t buf, const Ctx& c, float s0, float s1) {
  const int row = (c.lane & 7) + ((c.lane >> 3) & 1) * 8;
  const uint32_t base = buf + (c.warp * 16 + row) * 128 + (((c.lane >> 4) ^ (row & 7)) << 4);
#pragma unroll
  for (int i = 0; i < 8; i++)
    stsm4((base ^ ((i & 3) << 5)) + (i >> 2) * 8192, pack_bf16(a[8 * i] * s0, a[8 * i + 1] * s0), pack_bf16(a[8 * i + 2] * s1, a[8 * i + 3] * s1),
          pack_bf16(a[8 * i + 4] * s0, a[8 * i + 5] * s0), pack_bf16(a[8 * i + 6] * s1, a[8 * i + 7] * s1));
}

__device__ __forceinline__ void p1_epilogue(const Params& p, const Ctx& c, const float (&acc)[64], int t, int type) {
  const int tile = p.s.r[c.cl].tile[t], b = c.wg * 2 + 1;
  mbar_wait(c.bar + (B_SE + b) * 8, (t & 1) ^ 1);
  if (type && tile >= 32) {
    const int r = 2 * (c.lane & 3) + ((c.lane >> 2) & 1);
    const uint32_t dst = c.sm + SM_BUF + b * 16384 + r * 128 + (((c.warp * 2) ^ r) << 4) + (c.lane >> 3) * 4;
#pragma unroll
    for (int i = 0; i < 16; i++) {
      asm volatile("st.shared.u32 [%0], %1;" ::"r"(dst + i * 1024), "r"(pack_bf16(acc[4 * i], acc[4 * i + 1])) : "memory");
      asm volatile("st.shared.u32 [%0], %1;" ::"r"((dst ^ 16) + i * 1024), "r"(pack_bf16(acc[4 * i + 2], acc[4 * i + 3])) : "memory");
    }
  } else {
    if (type) stage_tile(acc, c.sm + SM_BUF + b * 16384, c, SM_SCALE, SM_SCALE);
    else stage_tile(acc, c.sm + SM_BUF + b * 16384, c, 1.f, 1.f);
  }
  FENCE_ASYNC_SMEM();
  __syncwarp();
  if (c.lane == 0) mbar_arrive(c.bar + (B_SF + b) * 8);
}

__device__ __forceinline__ void p1_consumer(const Params& p, const Ctx& c) {
  const int n = p.s.r[c.cl].n1;
  const int type = p.s.r[c.cl].slab >> 3;
  const uint32_t bdesc = desc_lo(c.sm + SM_RING, 8192), adesc = desc_lo(c.sm + SM_BUF + 32768 + c.wg * 8192, 16);
  uint32_t A[128];
  float acc[64] = {};
  int slot = 0, par = 0;
  auto next = [&]() { if (++slot == 10) { slot = 0; par ^= 1; } };
  {
    const int row = (c.lane & 7) + ((c.lane >> 3) & 1) * 8;
    const uint32_t base = c.sm + SM_RING + (c.wg * 64 + c.warp * 16 + row) * 128 + (((c.lane >> 4) ^ (row & 7)) << 4);
    if (c.wg == 1) bar_sync(ORDER + 1, 256);
    int pa = -1, pb = -1;
    if (type) {
      mbar_wait(c.bar + B_P1F * 8, 0);
      WG_FENCE();
#pragma unroll
      for (int kk = 0; kk < 4; kk++) wgmma_ss128<1>(acc, adesc + kk * 2, bdesc + kk * 128, kk != 0);
      WG_COMMIT();
      pb = 0; slot = 1;
    }
#pragma unroll
    for (int kb = 0; kb < 8; kb++) {
      const int sa = slot;
      mbar_wait(c.bar + (B_P1F + slot) * 8, par);
      if (kb == 0) PROF(c.wg, 5);
      next();
      mbar_wait(c.bar + (B_P1F + slot) * 8, par);
      PROF(c.wg, 6 + 2 * kb);
      WG_FENCE();
#pragma unroll
      for (int kk = 0; kk < 4; kk++)
        wgmma_ss128<1>(acc, desc_lo(c.sm + SM_RING + c.wg * 8192, 16) + sa * 1024 + kk * 2, bdesc + slot * 1024 + kk * 128, (kb | kk) != 0 ? 1 : type);
      WG_COMMIT();
      if (kb == 1 && c.wg == 0) bar_arrive(ORDER + 1, 256);
#pragma unroll
      for (int kk = 0; kk < 4; kk++) ldsm4((base ^ (kk << 5)) + sa * 16384, A[kb * 16 + kk * 4], A[kb * 16 + kk * 4 + 1], A[kb * 16 + kk * 4 + 2], A[kb * 16 + kk * 4 + 3]);
      WG_WAIT(1);
      if (kb > 0) release(c, B_P1E + pa);
      if (kb > 0 || pb >= 0) release(c, B_P1E + pb);
      pa = sa; pb = slot;
      next();
    }
    WG_WAIT(0);
    __syncwarp();
    release(c, B_P1E + pa);
    release(c, B_P1E + pb);
    pin(acc);
    PROF(c.wg, 1);
    p1_epilogue(p, c, acc, 0, type);
    PROF(c.wg, 2);
  }
  for (int t = 1; t < n; t++) {
    bar_sync(ORDER + c.wg, 256);
    int prev1 = -1, prev2 = -1;
    if (type) {
      mbar_wait(c.bar + (B_P1F + slot) * 8, par);
      WG_FENCE();
#pragma unroll
      for (int kk = 0; kk < 4; kk++) wgmma_ss128<1>(acc, adesc + kk * 2, bdesc + slot * 1024 + kk * 128, kk != 0);
      WG_COMMIT();
      prev1 = slot;
      next();
    }
#pragma unroll
    for (int kb = 0; kb < 8; kb++) {
      mbar_wait(c.bar + (B_P1F + slot) * 8, par);
      WG_FENCE();
      const uint32_t d = bdesc + slot * 1024;
#pragma unroll
      for (int kk = 0; kk < 4; kk++)
        wgmma_rs128<1>(acc, A[kb * 16 + kk * 4], A[kb * 16 + kk * 4 + 1], A[kb * 16 + kk * 4 + 2], A[kb * 16 + kk * 4 + 3], d + kk * 128, (kb | kk) != 0 ? 1 : type);
      WG_COMMIT();
      if (kb == 7) {
        if (t + 1 < n || c.wg == 0) bar_arrive(ORDER + (c.wg ^ 1), 256);
      }
      if (kb > 0) { WG_WAIT(2); if (kb > 1 || prev2 >= 0) release(c, B_P1E + prev2); }
      prev2 = prev1; prev1 = slot;
      next();
    }
    WG_WAIT(1);
    release(c, B_P1E + prev2);
    WG_WAIT(0);
    pin(acc);
    release(c, B_P1E + prev1);
    p1_epilogue(p, c, acc, t, type);
    PROF(c.wg, 3);
  }
}

__device__ __forceinline__ void p1_producer(const Params& p, const Ctx& c) {
  const int n = p.s.r[c.cl].n1;
  const int type = p.s.r[c.cl].slab >> 3, grp = p.s.r[c.cl].slab & 7;
  int slot = 2 - type, par = 1;
#pragma unroll 1
  for (int t = 0; t < n; t++) {
    const int tile = p.s.r[c.cl].tile[t];
    const CUtensorMap* m = &p.map_w[type * 2 + (tile >> 5)];
    const int n0 = (tile & 31) * 128 + c.rank * 64;
    const int ptile = p.s.r[c.cl].tile[t + PF1 < n ? t + PF1 : t];
    const CUtensorMap* pm = &p.map_w[type * 2 + (ptile >> 5)];
#pragma unroll 1
    for (int kb = (t == 0) - type; kb < 8; kb++) {
      if (t == 0) {
        mbar_wait(c.bar + (B_P1E + slot) * 8, par);
        mbar_expect(c.bar + (B_P1F + slot) * 8, 16384);
        tma2d(c.sm + SM_RING + slot * 16384, &p.map_a[type], kb * 64, grp * 256 + c.rank * 128, c.bar + (B_P1F + slot) * 8);
        if (++slot == 10) { slot = 0; par ^= 1; }
      }
      mbar_wait(c.bar + (B_P1E + slot) * 8, par);
      mbar_expect(c.bar + (B_P1F + slot) * 8, 16384);
      tma2d_mc(c.sm + SM_RING + slot * 16384 + c.rank * 8192, m, n0, kb < 0 ? 512 : kb * 64, c.bar + (B_P1F + slot) * 8);
      if (t == 0 && kb == 1) PROF(2, 61);
      if (t == 0 && kb == 3) PROF(2, 62);
      if (t + PF1 < n && t > 0 && ((kb ^ grp) & PFM) == 0) tma2d_prefetch(pm, (ptile & 31) * 128 + c.rank * 64, kb < 0 ? 512 : kb * 64);
      if (++slot == 10) { slot = 0; par ^= 1; }
    }
  }
}

__device__ __forceinline__ void p1_storer(const Params& p, const Ctx& c) {
  const int n = p.s.r[c.cl].n1;
  const int type = p.s.r[c.cl].slab >> 3, grp = p.s.r[c.cl].slab & 7;
  int pf = -1;
  for (int i = 0; i < 2 * n; i++) {
    const int t = i >> 1, w = i & 1, b = w * 2 + 1;
    const int tile = p.s.r[c.cl].tile[t];
    mbar_wait(c.bar + (B_SF + b) * 8, t & 1);
    const uint32_t src = c.sm + SM_BUF + b * 16384;
    int f = F_HEAD + (tile & 31);
    if (type == 0) {
      const int h = tile & 31, ring = p.s.r[c.cl].ring;
      if (h >= ring && w == 0) flag_wait<false>(F_CTX + max(c.lane & 7, grp) * 64 + h - ring, 4);
      uint8_t* dst = g_KV + (size_t)((h >= ring ? tile - ring : tile) * 16 + grp * 2 + c.rank) * 32768 + w * 8192;
      bulk_store(dst, src, 8192);
      bulk_store(dst + 16384, src + 8192, 8192);
    } else if (tile < 32) {
      bulk_store(g_Q + (size_t)(tile * 32 + grp * 4 + c.rank * 2 + w) * 16384, src, 16384);
    } else {
      tma3d_store(&p.map_t[2], src, 8 + (grp * 4 + c.rank * 2 + w) * 32, 0, (tile - 32) * 64);
      f = F_QKVA + grp * 4 + ((0xE4390900u >> (2 * (tile - 30))) & 3);
    }
    BULK_COMMIT();
    BULK_WAIT_READ(0);
    mbar_arrive_one(c.bar + (B_SE + b) * 8);
    if (pf >= 0) {
      BULK_WAIT(1);
      flag_add_rx(pf);
    }
    pf = f;
  }
  BULK_WAIT(0);
  flag_add_rx(pf);
}

__device__ __forceinline__ int p2_buf(int w, int i) { return w * 2 + (i & 1); }
__device__ __forceinline__ int p2_blk(int rank, int w, int i) { return ((i ^ w) & 1) == 0 ? 3 - rank : rank; }

template <int N>
__device__ __forceinline__ void row_max(const float (&s)[N], float& m0, float& m1) {
  float a0 = fmaxf(s[0], s[1]), a1 = fmaxf(s[2], s[3]);
#pragma unroll
  for (int i = 1; i < N / 4; i++) {
    m0 = fmaxf(m0, s[4 * i]); a0 = fmaxf(a0, s[4 * i + 1]);
    m1 = fmaxf(m1, s[4 * i + 2]); a1 = fmaxf(a1, s[4 * i + 3]);
  }
  m0 = fmaxf(m0, a0); m1 = fmaxf(m1, a1);
  m0 = fmaxf(m0, __shfl_xor_sync(0xffffffffu, m0, 1));
  m1 = fmaxf(m1, __shfl_xor_sync(0xffffffffu, m1, 1));
  m0 = fmaxf(m0, __shfl_xor_sync(0xffffffffu, m0, 2));
  m1 = fmaxf(m1, __shfl_xor_sync(0xffffffffu, m1, 2));
}
template <bool SUB, int N>
__device__ __forceinline__ void row_exp(const float (&s)[N], uint32_t (&P)[32], float m0, float m1, float& t0, float& t1) {
  float u0 = 0.f, u1 = 0.f;
  t0 = t1 = 0.f;
#pragma unroll
  for (int i = 0; i < N / 4; i++) {
    const float e0 = ex2(SUB ? s[4 * i] - m0 : s[4 * i]), e1 = ex2(SUB ? s[4 * i + 1] - m0 : s[4 * i + 1]);
    const float e2 = ex2(SUB ? s[4 * i + 2] - m1 : s[4 * i + 2]), e3 = ex2(SUB ? s[4 * i + 3] - m1 : s[4 * i + 3]);
    if (i == 0) { t0 = e0; u0 = e1; t1 = e2; u1 = e3; }
    else { t0 += e0; u0 += e1; t1 += e2; u1 += e3; }
    P[2 * i] = pack_bf16(e0, e1);
    P[2 * i + 1] = pack_bf16(e2, e3);
  }
#pragma unroll
  for (int i = N / 2; i < 32; i++) P[i] = 0;
  pin(P);
  t0 += u0; t1 += u1;
}
template <int N>
__device__ __forceinline__ void causal_mask(float (&s)[N], int thr) {
#pragma unroll
  for (int i = 0; i < 8; i++) {
    if (8 * i > thr) s[N - 32 + 4 * i] = -INFINITY;
    if (8 * i + 1 > thr) s[N - 32 + 4 * i + 1] = -INFINITY;
    if (8 * i - 8 > thr) s[N - 32 + 4 * i + 2] = -INFINITY;
    if (8 * i - 7 > thr) s[N - 32 + 4 * i + 3] = -INFINITY;
  }
}
__device__ __forceinline__ void issue_qk(float (&s)[32], uint32_t qd, uint32_t kd) {
  WG_FENCE();
#pragma unroll
  for (int kk = 0; kk < 8; kk++) wgmma_ss64<0>(s, qd + (kk >> 2) * 512 + (kk & 3) * 2, kd + (kk >> 2) * 1024 + (kk & 3) * 2, kk != 0);
  WG_COMMIT();
}
__device__ __forceinline__ void issue_qk(float (&s)[64], uint32_t qd, uint32_t kd) {
  WG_FENCE();
#pragma unroll
  for (int kk = 0; kk < 8; kk++) wgmma_ss128<0>(s, qd + (kk >> 2) * 512 + (kk & 3) * 2, kd + (kk >> 2) * 1024 + (kk & 3) * 2, kk != 0);
  WG_COMMIT();
}
template <int NK>
__device__ __forceinline__ void issue_pv(float (&o)[64], const uint32_t (&P)[32], uint32_t vd, int acc) {
  WG_FENCE();
#pragma unroll
  for (int kk = 0; kk < NK; kk++) wgmma_rs128<1>(o, P[4 * kk], P[4 * kk + 1], P[4 * kk + 2], P[4 * kk + 3], vd + kk * 128, kk != 0 ? 1 : acc);
  WG_COMMIT();
}
__device__ __forceinline__ void stage_done(const Ctx& c, int b) {
  FENCE_ASYNC_SMEM();
  __syncwarp();
  if (c.lane == 0) mbar_arrive(c.bar + (B_SF + b) * 8);
}
__device__ __forceinline__ void p2_epilogue(const float (&o)[64], float s0, float s1, const Ctx& c, int b) {
  stage_tile(o, c.sm + SM_BUF + b * 16384, c, s0, s1);
  stage_done(c, b);
}

struct P2State {
  float m0, m1, l0, l1;
  bool shift;
  float e0, e1;
  float g0, g1;
  int ks;
  int wi, ai;
  uint32_t wb, ab;
  uint32_t qd;
};
#define PROFZ()
__device__ __forceinline__ int wrap5(int q) { return q >= 5 ? q - 5 : q; }
__device__ __forceinline__ void turn_wait(uint32_t ring, int i) { mbar_wait(ring + (i & 3) * 8, (i >> 2) & 1); }
__device__ __forceinline__ void turn_pass(const Ctx& c, uint32_t ring, int i) { if (c.lane == 0) mbar_arrive(ring + (i & 3) * 8); }
__device__ __forceinline__ void p2_gate(P2State& z, const Ctx& c, int row0) {
  const float* g = g_gate + row0 + c.warp * 16 + (c.lane >> 2);
  asm volatile("ld.global.cg.f32 %0, [%2];\nld.global.cg.f32 %1, [%2+32];" : "=f"(z.g0), "=f"(z.g1) : "l"(g) : "memory");
}
__device__ __forceinline__ void p2_scales(P2State& z) {
  float l0 = z.l0, l1 = z.l1;
  l0 += __shfl_xor_sync(0xffffffffu, l0, 1);
  l1 += __shfl_xor_sync(0xffffffffu, l1, 1);
  l0 += __shfl_xor_sync(0xffffffffu, l0, 2);
  l1 += __shfl_xor_sync(0xffffffffu, l1, 2);
  z.e0 = __fdividef(1.f - z.g0, l0); z.e1 = __fdividef(1.f - z.g1, l1);
}
template <int N>
__device__ __forceinline__ void p2_first(const Ctx& c, P2State& z, float (&o)[64], uint32_t (&Pc)[32], uint32_t (&Pn)[32],
                                         int ks, int vs, int cnt, int acc, int row0) {
  float s[N] = {};
  issue_qk(s, z.qd, desc_lo(c.sm + SM_RING, 16) + ks * 2048);
  if (vs >= 0) {
    p2_scales(z);
    issue_pv<8>(o, Pc, desc_lo(c.sm + SM_RING, 16384) + vs * 2048, acc);
  } else {
    WG_COMMIT();
  }
  mbar_expect(z.ab + (z.ai++ & 3) * 8, cnt == 1 ? 8192 : 0);
  PROFZ();
  WG_WAIT(1);
  PROFZ();
  pin(s);
  release(c, B_P2E + ks, cnt);
  p2_gate(z, c, row0);
  causal_mask(s, c.warp * 16 + (c.lane >> 2) - 2 * (c.lane & 3));
  z.m0 = z.m1 = 0.f;
  row_exp<false>(s, Pn, 0.f, 0.f, z.l0, z.l1);
  z.shift = __any_sync(0xffffffffu, !(z.l0 + z.l1 <= SM_HI) || ((c.lane & 3) == 0 && !(fminf(z.l0, z.l1) >= SM_LO)));
  if (__builtin_expect(z.shift, 0)) {
    z.m0 = z.m1 = -INFINITY;
    row_max(s, z.m0, z.m1);
    row_exp<true>(s, Pn, z.m0, z.m1, z.l0, z.l1);
  }
  WG_WAIT(0);
  pin(o);
  if (vs >= 0) release(c, B_P2E + vs, 1);
}

template <bool SECOND>
__device__ __forceinline__ void p2_turn(const Ctx& c, P2State& z, float (&o)[64], uint32_t (&Pc)[32], uint32_t (&Pn)[32],
                                        int eb = -1, bool half = false, int vcnt = 1) {
  float s[64] = {};
  const int ks = z.ks, vs = wrap5(ks + 1);
  PROFZ();
  turn_wait(z.wb, z.wi++);
  PROFZ();
  issue_qk(s, z.qd, desc_lo(c.sm + SM_RING, 16) + ks * 2048);
  const uint32_t vd = desc_lo(c.sm + SM_RING, 16384) + vs * 2048;
  if (SECOND) {
    if (eb >= 0) stage_tile(o, c.sm + SM_BUF + eb * 16384, c, z.e0, z.e1);
    if (half) issue_pv<4>(o, Pc, vd, 0); else issue_pv<8>(o, Pc, vd, 0);
  } else {
    issue_pv<8>(o, Pc, vd, 1);
  }
  turn_pass(c, z.ab, z.ai++);
  if (SECOND) { if (eb >= 0) stage_done(c, eb); }
  PROFZ();
  z.ks = wrap5(ks + 2);
  WG_WAIT(1);
  PROFZ();
  pin(s);
  release(c, B_P2E + ks, 1);
  float t0, t1, a0 = 1.f, a1 = 1.f;
  row_exp<false>(s, Pn, 0.f, 0.f, t0, t1);
  z.shift = __any_sync(0xffffffffu, z.shift || !(t0 + t1 <= SM_HI));
  const bool redo = z.shift;
  if (__builtin_expect(redo, 0)) {
    float n0 = z.m0, n1 = z.m1;
    row_max(s, n0, n1);
    a0 = ex2(z.m0 - n0); a1 = ex2(z.m1 - n1);
    z.m0 = n0; z.m1 = n1;
    z.l0 *= a0; z.l1 *= a1;
    row_exp<true>(s, Pn, z.m0, z.m1, t0, t1);
  }
  WG_WAIT(0);
  pin(o);
  release(c, B_P2E + vs, vcnt);
  if (__builtin_expect(redo, 0)) {
#pragma unroll
    for (int i = 0; i < 16; i++) { o[4 * i] *= a0; o[4 * i + 1] *= a0; o[4 * i + 2] *= a1; o[4 * i + 3] *= a1; }
  }
  z.l0 += t0; z.l1 += t1;
}
__device__ __forceinline__ void copy_p(uint32_t (&d)[32], const uint32_t (&s)[32], int zero) {
#pragma unroll
  for (int i = 0; i < 32; i++) asm volatile("add.s32 %0, %1, %2;" : "=r"(d[i]) : "r"(s[i]), "r"(zero));
}

__device__ __forceinline__ void p2_consumer(const Params& p, const Ctx& c, int rot) {
  const int nit = p.s.r[c.cl].n2;
  const uint32_t fring = c.bar + B_P2F * 8, oring = c.bar + B_ORD * 8;
  float o[64] = {};
  uint32_t Pa[32] = {}, Pb[32] = {};
  P2State z;
  z.e0 = z.e1 = z.l0 = z.l1 = z.g0 = z.g1 = 0.f; z.ks = rot; z.shift = false;
  int acc = 0, n = 0;
  for (int it = 0; it < nit; it++) {
    const int j = p.s.r[c.cl].item[it] & 7, blk = p2_blk(c.rank, c.wg, it), row0 = (j * 4 + blk) * 64;
    const int lng = ((it ^ c.wg) & 1) ^ 1;
    z.qd = desc_lo(c.sm + SM_BUF, 16) + p2_buf(c.wg, it) * 1024;
    if (lng) { z.wb = oring; z.wi = n - it; z.ab = fring; z.ai = n + 1; }
    else { z.wb = fring; z.wi = n + 2; z.ab = oring; z.ai = n - it; }
    PROFZ();
    mbar_wait(c.bar + (B_QF + p2_buf(c.wg, it)) * 8, (it >> 1) & 1);
    turn_wait(fring, n + 1 - lng);
    PROFZ();
    const int vs = it ? wrap5(z.ks + 1) : -1, ks = lng ? z.ks : wrap5(z.ks + (it ? 2 : 1));
    if (blk & 1) p2_first<64>(c, z, o, Pa, Pb, ks, vs, 1 + lng, acc, row0);
    else p2_first<32>(c, z, o, Pa, Pb, ks, vs, 1 + lng, acc, row0);
    z.ks = wrap5(ks + (it == 0 && lng ? 1 : 2));
    PROF(c.wg, 24 + it);
    n += 2 * j + 2;
    int left = 2 * j + lng;
    acc = left != 0;
    if (left == 0) { copy_p(Pa, Pb, p.zero); continue; }
    p2_turn<true>(c, z, o, Pb, Pa, it > 0 ? p2_buf(c.wg, it - 1) : -1, !(blk & 1), 1 + lng);
    while (--left > 0) {
      p2_turn<false>(c, z, o, Pa, Pb);
      if (--left == 0) { copy_p(Pa, Pb, p.zero); break; }
      p2_turn<false>(c, z, o, Pb, Pa);
    }
  }
  {
    if (!acc && nit > 1) p2_epilogue(o, z.e0, z.e1, c, p2_buf(c.wg, nit));
    turn_wait(z.wb, z.wi);
    issue_pv<8>(o, Pa, desc_lo(c.sm + SM_RING, 16384) + z.ks * 2048, acc);
    if (((nit - 1) ^ c.wg) & 1) turn_pass(c, z.ab, z.ai);
    p2_scales(z);
    WG_WAIT(0);
    pin(o);
    release(c, B_P2E + z.ks);
    p2_epilogue(o, z.e0, z.e1, c, p2_buf(c.wg, nit - 1));
    PROF(c.wg, 24 + nit);
  }
}

__device__ __forceinline__ void p2_load_q(const Params& p, const Ctx& c, int it, int w) {
  const int item = p.s.r[c.cl].item[it], h = item >> 3, j = item & 7, b = p2_buf(w, it);
  mbar_expect(c.bar + (B_QF + b) * 8, 16384);
  bulk_load(c.sm + SM_BUF + b * 16384, g_Q + (size_t)(h * 32 + j * 4 + p2_blk(c.rank, w, it)) * 16384, 16384, c.bar + (B_QF + b) * 8, POL(4));
}
__device__ __forceinline__ void wait_p1_free(const Ctx& c, int u1, int s) {
  mbar_wait(c.bar + (B_P1E + 2 * s) * 8, ((u1 - 1 - 2 * s) / 10) & 1);
  mbar_wait(c.bar + (B_P1E + 2 * s + 1) * 8, ((u1 - 2 - 2 * s) / 10) & 1);
}
__device__ __forceinline__ void p2_producer(const Params& p, const Ctx& c, int u1, int rot) {
  const int nit = p.s.r[c.cl].n2;
  int slot = rot, cnt = 0, par = 1, n = 0;
  const int ring = p.s.r[c.cl].ring;
  const uint8_t* pv = nullptr;
  bool pl = false;
  auto load = [&](const uint8_t* src, int expect, uint32_t fb, bool last) {
    if (cnt < 5) {
      if (u1) {
        wait_p1_free(c, u1, slot);
        if (cnt == 0) p2_load_q(p, c, 0, 1);
      }
      cnt++;
    } else {
      if (slot == rot) par ^= 1;
      mbar_wait(c.bar + (B_P2E + slot) * 8, par);
    }
    if (expect) mbar_expect(fb, expect);
    bulk_load_mc(c.sm + SM_RING + slot * 32768 + c.rank * 16384, src, 16384, fb, last ? POL(5) : L2_NORMAL);
    slot = wrap5(slot + 1);
  };
  if (c.phases & 16) flag_wait<true>(F_GATE, 256);
  for (int it = 0; it < nit; it++) {
    const int item = p.s.r[c.cl].item[it], h = item >> 3, j = item & 7;
    if (c.phases & 16) flag_wait<false>(F_HEAD + h, 96);
    if (it == 0) { mbar_wait(c.bar + B_LAD * 8, 0); p2_load_q(p, c, 0, 0); if (!u1) p2_load_q(p, c, 0, 1); }
    for (int t = 2 * j + 1; t >= 0; t--) {
      const uint8_t* k = g_KV + (size_t)((h >= ring ? h - ring : h) * 16 + t) * 32768 + c.rank * 16384;
      const uint32_t fb = c.bar + (B_P2F + (n & 3)) * 8;
      const bool last = (p.s.r[c.cl].last[it] >> (t >> 1)) & 1;
      load(k, pv && t != 2 * j ? 65536 : 32768, fb, last);
      if (pv) load(pv, 0, t != 2 * j ? fb : c.bar + (B_ORD + ((n - 1 - it) & 3)) * 8, pl);
      pl = last;
      pv = k + (size_t)NH * 16 * 32768;
      n++;
    }
  }
  load(pv, 32768, c.bar + (B_P2F + (n & 3)) * 8, pl);
}

__device__ __forceinline__ void p2_storer(const Params& p, const Ctx& c, int sfpar) {
  const int nit = p.s.r[c.cl].n2;
  auto load_q = [&](int it, int w) {
    if (c.phases & 16) flag_wait<false>(F_HEAD + (p.s.r[c.cl].item[it] >> 3), 96);
    p2_load_q(p, c, it, w);
  };
  if (nit > 1) {
    load_q(1, 1); p2_load_q(p, c, 1, 0); }
  for (int i = 0; i < 2 * nit; i++) {
    const int it = i >> 1, w = (it ^ i ^ 1) & 1, b = p2_buf(w, it);
    const int item = p.s.r[c.cl].item[it], h = item >> 3, j = item & 7;
    mbar_wait(c.bar + (B_SF + b) * 8, (sfpar >> b) & 1);
    sfpar ^= 1 << b;
    bulk_store(g_Q + (size_t)(h * 32 + j * 4 + p2_blk(c.rank, w, it)) * 16384, c.sm + SM_BUF + b * 16384, 16384, POL(1));
    BULK_COMMIT();
    BULK_WAIT(0);
    flag_add_rx(F_CTX + j * 64 + h);
    if ((i & 1) && it + 2 < nit) { load_q(it + 2, w); p2_load_q(p, c, it + 2, w ^ 1); }
  }
  release(c, B_DONE);
}

__device__ __forceinline__ int p3_pos(int i, int x) { return i < 4 ? (i + x) & 3 : 4; }
__device__ __forceinline__ void p3_consumer(const Params& p, const Ctx& c, int x) {
  const bool first = p.s.r[c.cl].p3 >= 24;
  const int tile = p.s.r[c.cl].p3 - (first ? 24 : 0), j = tile / 3, nt = tile - 3 * j;
  const int na = first ? 9 : 0, nb = first ? 2 * p.s.nh[tile] : 64 - 2 * p.s.nh[tile];
  const uint32_t ad = desc_lo(c.sm + SM_RING + c.wg * 8192, 16), bd = desc_lo(c.sm + SM_RING + 16384, 4096);
  float acc[96] = {};
  int slot = 0, par = 0, prev = 0;
#pragma unroll 1
  for (int kb = 0; kb < na; kb++) {
    mbar_wait(c.bar + (B_P3F + slot) * 8, par);
    if (kb == 0) PROF(c.wg, 39);
    WG_FENCE();
#pragma unroll
    for (int kk = 0; kk < 4; kk++) wgmma_ss192<1, 1>(acc, ad + p3_pos(slot, x) * 2560 + kk * 128, bd + p3_pos(slot, x) * 2560 + (kk >> 1) * 768 + (kk & 1) * 128, kk != 0 ? 1 : kb != 0);
    WG_COMMIT();
    WG_WAIT(1);
    if (kb > 0) release(c, B_P3E + prev);
    prev = slot;
    if (++slot == 5) { slot = 0; par ^= 1; }
  }
#pragma unroll 1
  for (int kb = na; kb < na + nb; kb++) {
    mbar_wait(c.bar + (B_P3F + slot) * 8, par);
    if (kb == 0) PROF(c.wg, 39);
    WG_FENCE();
#pragma unroll
    for (int kk = 0; kk < 4; kk++) wgmma_ss192<1>(acc, ad + p3_pos(slot, x) * 2560 + kk * 2, bd + p3_pos(slot, x) * 2560 + (kk >> 1) * 768 + (kk & 1) * 128, kk != 0 ? 1 : kb != 0);
    WG_COMMIT();
    WG_WAIT(1);
    if (kb > 0) release(c, B_P3E + prev);
    prev = slot;
    if (++slot == 5) { slot = 0; par ^= 1; }
  }
  WG_WAIT(0);
  pin(acc);
  PROF(c.wg, 40);
  if (first) bar_sync(4 + c.wg, 128);
  mbar_wait(c.bar + B_OUT * 8, 0);
  const int row = (c.lane & 7) + ((c.lane >> 3) & 1) * 8;
  const uint32_t wbase = c.sm + SM_RING + c.wg * 8192 + c.warp * 2048;
  const uint32_t base = wbase + row * 128 + (((c.lane >> 4) ^ (row & 7)) << 4);
#pragma unroll
  for (int i = 0; i < 12; i++) {
    stsm4((base ^ ((i & 3) << 5)) + (i >> 2) * 40960, pack_bf16(acc[8 * i], acc[8 * i + 1]), pack_bf16(acc[8 * i + 2], acc[8 * i + 3]),
          pack_bf16(acc[8 * i + 4], acc[8 * i + 5]), pack_bf16(acc[8 * i + 6], acc[8 * i + 7]));
    if ((i & 3) == 3) {
      FENCE_ASYNC_SMEM();
      __syncwarp();
      const int c0 = nt * 192 + (i >> 2) * 64, c1 = j * 256 + c.rank * 128 + c.wg * 64 + c.warp * 16;
      tma2d_add(&p.map_out, wbase + (i >> 2) * 40960, c0, c1);
    }
  }
  BULK_COMMIT();
  PROF(c.wg, 43);
  BULK_WAIT_READ(0);
  PROF(c.wg, 44);
}

__device__ __forceinline__ void p3_producer(const Params& p, const Ctx& c, int u1, int u2, int rot, int x) {
  const bool first = p.s.r[c.cl].p3 >= 24;
  const int tile = p.s.r[c.cl].p3 - (first ? 24 : 0), j = tile / 3, nt = tile - 3 * j;
  int slot = 0, par = 1, cnt = 0;
  auto wait_free = [&](int s) {
    const int f = wrap5(s + 5 - rot);
    if (f < u2) mbar_wait(c.bar + (B_P2E + s) * 8, ((u2 - 1 - f) / 5) & 1);
    else if (u1) wait_p1_free(c, u1, s);
  };
  asm volatile(ELECT("prefetch.tensormap [%0];") ::"l"(&p.map_o[first]) : "memory");
  asm volatile(ELECT("prefetch.tensormap [%0];") ::"l"(&p.map_out) : "memory");
  const int q1 = first ? p.s.nh[tile] : 32;
  for (int q = first ? -1 : p.s.nh[tile]; q < q1; q++) {
    const int g = q < 0 ? 32 : p.s.p3_order[j][q];
    if (c.phases & 16) flag_wait<false>(F_CTX + j * 64 + g, q < 0 ? 16 : 4);
    const int nk = q < 0 ? 9 : 2, k0 = (q < 0 ? 0 : g * 128) + c.rank * 32;
    const uint8_t* a = q < 0 ? g_oA + (j * 4 + c.rank * 2) * 73728 : g_Q + (size_t)(g * 32 + j * 4 + c.rank * 2) * 16384;
    const CUtensorMap* m = &p.map_o[q < 0];
    for (int i = 0; i < nk; i++) {
      const uint32_t st = c.sm + SM_RING + p3_pos(slot, x) * 40960, fb = c.bar + (B_P3F + slot) * 8;
      if (cnt < 4) { wait_free(p3_pos(cnt, x)); wait_free(p3_pos(cnt, x) + 1); }
      else if (cnt == 4) mbar_wait(c.bar + B_DONE * 8, 0);
      else mbar_wait(c.bar + (B_P3E + slot) * 8, par);
      cnt++;
      mbar_expect(fb, 40960);
      bulk_load(st, a + i * 8192, 8192, fb, POL(3));
      bulk_load(st + 8192, a + (nk + i) * 8192, 8192, fb, POL(3));
      tma3d_mc(st + 16384 + c.rank * 12288, m, 0, k0 + i * 64, nt * 3, fb);
      if (++slot == 5) { slot = 0; par ^= 1; }
    }
  }
}

__device__ __forceinline__ float bf_lo(uint32_t w) { return __uint_as_float(w << 16); }
__device__ __forceinline__ float bf_hi(uint32_t w) { return __uint_as_float(w & 0xffff0000u); }

__device__ __forceinline__ void gate_rows(const Params& p, int row0, int lane) {
  const uint4* x = reinterpret_cast<const uint4*>(p.x + (size_t)(row0 + (lane >> 2)) * DM) + (lane & 3);
  const uint4* w = reinterpret_cast<const uint4*>(p.gate_w) + (lane & 3);
  float a = 0.f;
#pragma unroll 1
  for (int b = 0; b < 3; b++) {
    uint4 u[6];
#pragma unroll
    for (int i = 0; i < 6; i++) u[i] = __ldg(x + (b * 6 + i) * 4);
#pragma unroll
    for (int i = 0; i < 6; i++) {
      const uint4 v = __ldg(w + (b * 6 + i) * 4);
      a = fmaf(bf_lo(u[i].x), bf_lo(v.x), a); a = fmaf(bf_hi(u[i].x), bf_hi(v.x), a);
      a = fmaf(bf_lo(u[i].y), bf_lo(v.y), a); a = fmaf(bf_hi(u[i].y), bf_hi(v.y), a);
      a = fmaf(bf_lo(u[i].z), bf_lo(v.z), a); a = fmaf(bf_hi(u[i].z), bf_hi(v.z), a);
      a = fmaf(bf_lo(u[i].w), bf_lo(v.w), a); a = fmaf(bf_hi(u[i].w), bf_hi(v.w), a);
    }
  }
  a += __shfl_xor_sync(0xffffffffu, a, 1);
  a += __shfl_xor_sync(0xffffffffu, a, 2);
  if ((lane & 3) == 0) g_gate[row0 + (lane >> 2)] = 1.f / (1.f + __expf(-a));
}

__device__ __forceinline__ void lds10(uint32_t (&k)[10], uint32_t a) {
  asm volatile("ld.shared.v2.u32 {%0, %1}, [%10];\nld.shared.v2.u32 {%2, %3}, [%10+8];\nld.shared.v2.u32 {%4, %5}, [%10+16];\n"
               "ld.shared.v2.u32 {%6, %7}, [%10+24];\nld.shared.v2.u32 {%8, %9}, [%10+32];"
               : "=r"(k[0]), "=r"(k[1]), "=r"(k[2]), "=r"(k[3]), "=r"(k[4]), "=r"(k[5]), "=r"(k[6]), "=r"(k[7]), "=r"(k[8]), "=r"(k[9]) : "r"(a));
}
__device__ __forceinline__ void local_attn(const Params& p, const Ctx& c, int rb, int hs) {
  const int lane = c.lane, grp = rb >> 2, par = lane >> 4, i0 = 2 * (lane & 15);
  const uint32_t buf = c.sm + SM_BUF + (c.warp - 2) * 8192, bqk = c.bar + (B_LA + (c.warp - 2) * 2) * 8, bv = bqk + 8;
  const uint32_t mine = buf + 2304 + par * 160 + i0 * 4;
  const bool flags = c.phases & 16;
  auto fetch_qk = [&](int i) {
    if (flags && !(i & 1)) {
      const int q = i >> 1;
      const int tgt = q == 0 ? 24 : q == 3 ? 8 : 12;
      flag_wait<false>(F_QKVA + (grp - (grp > 0 && (rb & 3) == 0 ? par : 0)) * 4 + q, tgt);
    }
    mbar_expect(bqk, 5184);
    tma3d(buf, &p.map_t[0], rb * 32 + 8, 0, 9 * (4 * i + hs), bqk, POL(2));
    tma3d(buf + 2304, &p.map_t[1], rb * 32, 0, 288 + 9 * (4 * i + hs), bqk, POL(2));
  };
  auto fetch_v = [&](int i) { mbar_expect(bv, 2880); tma3d(buf + 5248, &p.map_t[1], rb * 32, 0, 576 + 9 * (4 * i + hs), bv, POL(2)); };
  fetch_qk(0);
  if (flags) flag_wait<true>(F_GATE, 256);
#pragma unroll 1
  for (int q = 0; q < 8; q++) {
    fetch_v(q);
    float a[8], b[8];
#pragma unroll
    for (int w = 0; w < 8; w++) a[w] = b[w] = 0.f;
    mbar_wait(bqk, q & 1);
    PROFB(1 + 2 * q);
#pragma unroll 1
    for (int j = 0; j < 9; j++) {
      uint32_t x, y, k[10];
      asm volatile("ld.shared.v2.u32 {%0, %1}, [%2];" : "=r"(x), "=r"(y) : "r"(buf + lane * 8 + j * 256));
      lds10(k, mine + j * 320);
      const float xl = bf_lo(x), xh = bf_hi(x), yl = bf_lo(y), yh = bf_hi(y);
#pragma unroll
      for (int m = 1; m < 10; m++) {
        const float kl = bf_lo(k[m]), kh = bf_hi(k[m]);
        if (m < 9) a[8 - m] = fmaf(xl, kl, fmaf(xh, kh, a[8 - m]));
        if (m > 1) b[9 - m] = fmaf(yl, kl, fmaf(yh, kh, b[9 - m]));
      }
    }
    __syncwarp();
    if (q < 7) fetch_qk(q + 1);
    constexpr float SC = 0.23570226039551584f * 1.4426950408889634f;
    const float* gp = g_gate + rb * 64 + 2 * i0 + par;
    const float ga = __ldcg(gp), gb = __ldcg(gp + 2);
    float ma = a[0], mb = b[0];
#pragma unroll
    for (int w = 1; w < 8; w++) {
      if (rb == 0) {
        if (i0 < w) a[w] = -INFINITY;
        if (i0 + 1 < w) b[w] = -INFINITY;
      }
      ma = fmaxf(ma, a[w]); mb = fmaxf(mb, b[w]);
    }
    float la = 0.f, lb = 0.f;
#pragma unroll
    for (int w = 0; w < 8; w++) {
      a[w] = ex2((a[w] - ma) * SC); b[w] = ex2((b[w] - mb) * SC);
      la += a[w]; lb += b[w];
    }
    la = __fdividef(ga, la); lb = __fdividef(gb, lb);
#pragma unroll
    for (int w = 0; w < 8; w++) { a[w] *= la; b[w] *= lb; }
    uint8_t* dst = g_oA + rb * 73728 + ((i0 & 2) + par) * 4;
    mbar_wait(bv, q & 1);
#pragma unroll 1
    for (int j = 0; j < 9; j++) {
      uint32_t v[10];
      lds10(v, mine + 2944 + j * 320);
      float a0 = 0.f, a1 = 0.f, b0 = 0.f, b1 = 0.f;
#pragma unroll
      for (int m = 1; m < 10; m++) {
        const float vl = bf_lo(v[m]), vh = bf_hi(v[m]);
        if (m < 9) { a0 = fmaf(a[8 - m], vl, a0); a1 = fmaf(a[8 - m], vh, a1); }
        if (m > 1) { b0 = fmaf(b[9 - m], vl, b0); b1 = fmaf(b[9 - m], vh, b1); }
      }
      const uint32_t wa = pack_bf16(a0, a1), wb = pack_bf16(b0, b1);
      const uint32_t got = __shfl_xor_sync(0xffffffffu, par ? wa : wb, 16);
      const uint32_t r0 = par ? got : wa, r1 = par ? wb : got;
      const int col = 18 * (4 * q + hs) + 2 * j, o = col * 128 + ((((i0 >> 2) ^ col) & 7) << 4);
      *reinterpret_cast<uint32_t*>(dst + o) = __byte_perm(r0, r1, 0x5410);
      *reinterpret_cast<uint32_t*>(dst + ((o + 128) ^ 16)) = __byte_perm(r0, r1, 0x7632);
    }
    __syncwarp();
    PROFB(2 + 2 * q);
  }
  mbar_arrive_one(c.bar + B_LAD * 8);
  flag_add(F_CTX + grp * 64 + 32);
}

__global__ void __cluster_dims__(2, 1, 1) __launch_bounds__(384, 1) fused_kernel(const __grid_constant__ Params p) {
  extern __shared__ uint8_t smem_raw[];
  Ctx c;
  c.sm = ((uint32_t)__cvta_generic_to_shared(smem_raw) + 1023u) & ~1023u;
  c.bar = c.sm + SM_BAR;
  c.lane = threadIdx.x & 31;
  const int wid = __shfl_sync(0xffffffffu, threadIdx.x >> 5, 0);
  if (wid < 6) asm volatile("prefetch.tensormap [%0];" ::"l"(&p.map_a[0] + wid) : "memory");
  c.wg = wid >> 2;
  c.warp = wid & 3;
  PROF(c.wg, 0);
  PROFG(61);
  c.cl = (blockIdx.x + (wid >> 4)) >> 1;
  c.rank = blockIdx.x & 1;
  c.rbar = mapa(c.bar, c.lane & 1);
  {
    const int w = wid, cnt = (((int)(B_CNT >> (4 * w)) - 1) & 15) + 1;
    if (w < 11) {
#pragma unroll
      for (int i = 0; i < 8; i++) asm volatile("mbarrier.init.shared::cta.b64 [%0], %1;" ::"r"(c.bar + w * 64 + i * 8), "r"(cnt));
    }
    asm volatile("fence.mbarrier_init.release.cluster;" ::: "memory");
  }
  if (c.wg == 2) PROF(2, 56);
  asm volatile("barrier.cluster.arrive.relaxed;" ::: "memory");
  c.phases = p.s.r[c.cl].phases;
  const bool do1 = p.s.r[c.cl].n1 > 0, do2 = p.s.r[c.cl].n2 > 0, do3 = p.s.r[c.cl].p3 != 255;
  if (do1 && c.wg == 2 && c.warp == 0) {
    const int type = p.s.r[c.cl].slab >> 3;
    PROF(2, 57);
    FENCE_ASYNC_SMEM();
    mbar_expect(c.bar + B_P1F * 8, type ? 32768 : 16384);
    tma2d(type ? c.sm + SM_BUF + 32768 : c.sm + SM_RING, &p.map_a[type], type ? 512 : 0, (p.s.r[c.cl].slab & 7) * 256 + c.rank * 128, c.bar + B_P1F * 8);
    PROF(2, 58);
  }
  asm volatile("barrier.cluster.wait.acquire;" ::: "memory");
  if (c.wg == 2) PROF(2, 59);
  if (do1 && c.wg == 2 && c.warp == 0) {
    const int type = p.s.r[c.cl].slab >> 3, tile = p.s.r[c.cl].tile[0];
    if (!type) mbar_expect(c.bar + (B_P1F + 1) * 8, 16384);
    tma2d_mc(c.sm + SM_RING + (1 - type) * 16384 + c.rank * 8192, &p.map_w[type * 2 + (tile >> 5)], (tile & 31) * 128 + c.rank * 64, type ? 512 : 0, c.bar + (B_P1F + 1 - type) * 8);
  }

  if (c.wg < 2) {
    PROF(c.wg, 4);
    asm volatile("setmaxnreg.inc.sync.aligned.u32 224;");
    if (c.wg == 1) {
      if (do1) bar_arrive(ORDER, 256);
      if (c.lane == 0) mbar_arrive(c.bar + B_P2F * 8);
    }
    if (do1) p1_consumer(p, c);
    if (do2) p2_consumer(p, c, p.s.r[c.cl].rot);
    if (do3) p3_consumer(p, c, p.s.r[c.cl].x3);
    PROF(c.wg, 63);
    PROFG(62);
    if (c.lane == 0) mbar_arrive(c.bar + B_FIN * 8);
    __syncwarp();
    cluster_sync();
  } else {
    asm volatile("setmaxnreg.dec.sync.aligned.u32 56;");
    if (c.warp == 0) {
      PROF(2, 60);
      if (do1) p1_producer(p, c);
      if (do2) p2_producer(p, c, p.s.r[c.cl].u1, p.s.r[c.cl].rot);
      if (do3) p3_producer(p, c, p.s.r[c.cl].u1, p.s.r[c.cl].u2, p.s.r[c.cl].rot, p.s.r[c.cl].x3);
    } else if (c.warp == 1) {
      int sfpar = 0;
      if (do1) {
        p1_storer(p, c);
        sfpar = (p.s.r[c.cl].n1 & 1) * 10;
      }
      if (do2) p2_storer(p, c, sfpar);
      else { mbar_wait(c.bar + B_LAD * 8, 0); release(c, B_DONE); }
      if (do3) {
        const int task = p.s.r[c.cl].p3;
        if (task >= 24) {
          const int j = (task - 24) / 3, nt = task - 24 - 3 * j;
          uint4* o = reinterpret_cast<uint4*>(p.out + (size_t)(j * 256 + c.rank * 128 + (c.lane >> 3)) * DM + nt * 192) + (c.lane & 7);
#pragma unroll 4
          for (int r = 0; r < 32; r++) o[r * 288] = o[r * 288 + 8] = o[r * 288 + 16] = make_uint4(0u, 0u, 0u, 0u);
          __syncwarp();
          flag_add(F_OUT + (task - 24) * 2 + c.rank);
        } else if (c.phases & 16) {
          flag_wait<false, 256>(F_OUT + task * 2 + c.rank, 1);
        }
        mbar_arrive_one(c.bar + B_OUT * 8);
      }
    } else {
      const int bw = blockIdx.x * 2 + (c.warp - 2);
      if ((c.phases & 1) && bw < 256) {
        gate_rows(p, bw * 8, c.lane);
        __syncwarp();
        flag_add(F_GATE);
      }
      if (p.s.r[c.cl].bg != 255) local_attn(p, c, p.s.r[c.cl].bg, bw & 3);
      else if (c.lane == 0) mbar_arrive(c.bar + B_LAD * 8);
    }
    __syncwarp();
    bar_sync(3, 128);
    if (c.warp == 0 && (c.phases & 4)) {
      int last = 0;
      if (c.lane == 0) { __threadfence(); last = atomicAdd(g_flags + F_DONE, 1) == 2 * NCL - 1; }
      if (__shfl_sync(0xffffffffu, last, 0)) for (int i = c.lane; i < F_NUM; i += 32) g_flags[i] = 0;
    }
    if (c.warp == 1) mbar_wait(c.bar + B_FIN * 8, 0);
    __syncwarp();
    cluster_sync();
  }
}

static const Sched k_sched = {
  {{0,26,0,6,0,{0,0,0,0,0,0,0,0,0,0,0},{0,0,0,0,0,0,0,0,0,0,0},{0,2,4,6,8,10,43,13,14,15,16,17,18,19,20,21,22,23,24,25,26,27,28,29,30,31,0,0,0,0}},
   {1,26,0,23,4,{0,0,0,0,0,0,0,0,0,0,0},{0,0,0,0,0,0,0,0,0,0,0},{0,2,4,6,8,10,43,13,14,15,16,17,18,19,20,21,22,23,24,25,26,27,28,29,30,31,0,0,0,0}},
   {2,26,2,37,8,{204,248,0,0,0,0,0,0,0,0,0},{0,0,0,0,0,0,0,0,0,0,0},{0,34,5,7,9,11,12,13,14,15,16,17,18,19,20,21,22,23,24,25,26,27,28,29,30,31,0,0,0,0}},
   {3,26,0,17,12,{0,0,0,0,0,0,0,0,0,0,0},{0,0,0,0,0,0,0,0,0,0,0},{0,2,4,6,8,41,11,44,14,15,16,17,18,19,20,21,22,23,24,25,26,27,28,29,30,31,0,0,0,0}},
   {4,26,1,21,16,{200,0,0,0,0,0,0,0,0,0,0},{0,0,0,0,0,0,0,0,0,0,0},{0,2,4,6,8,10,43,13,14,15,16,17,18,19,20,21,22,23,24,25,26,27,28,29,30,31,0,0,0,0}},
   {5,26,2,255,20,{201,254,0,0,0,0,0,0,0,0,0},{0,0,0,0,0,0,0,0,0,0,0},{0,34,5,39,10,11,12,13,14,15,16,17,18,19,20,21,22,23,24,25,26,27,28,29,30,31,0,0,0,0}},
   {6,26,0,16,24,{0,0,0,0,0,0,0,0,0,0,0},{0,0,0,0,0,0,0,0,0,0,0},{0,2,4,6,8,10,43,13,14,15,16,17,18,19,20,21,22,23,24,25,26,27,28,29,30,31,0,0,0,0}},
   {7,26,0,5,28,{0,0,0,0,0,0,0,0,0,0,0},{0,0,0,0,0,0,0,0,0,0,0},{0,2,4,6,8,10,43,13,14,15,16,17,18,19,20,21,22,23,24,25,26,27,28,29,30,31,0,0,0,0}},
   {0,26,0,0,1,{0,0,0,0,0,0,0,0,0,0,0},{0,0,0,0,0,0,0,0,0,0,0},{32,34,36,38,40,42,12,45,46,47,48,49,50,51,52,53,54,55,56,57,58,59,60,61,62,63,0,0,0,0}},
   {1,26,2,255,5,{197,242,0,0,0,0,0,0,0,0,0},{0,0,0,0,0,0,0,0,0,0,0},{32,34,36,38,40,42,12,45,46,47,48,49,50,51,52,53,54,55,56,57,58,59,60,61,62,63,0,0,0,0}},
   {2,26,2,255,9,{203,236,0,0,0,0,0,0,0,0,0},{0,31,0,0,0,0,0,0,0,0,0},{32,3,37,39,41,43,44,45,46,47,48,49,50,51,52,53,54,55,56,57,58,59,60,61,62,63,0,0,0,0}},
   {3,26,2,255,13,{208,255,0,0,0,0,0,0,0,0,0},{0,192,0,0,0,0,0,0,0,0,0},{32,34,36,38,40,10,43,13,46,47,48,49,50,51,52,53,54,55,56,57,58,59,60,61,62,63,0,0,0,0}},
   {4,26,0,15,17,{0,0,0,0,0,0,0,0,0,0,0},{0,0,0,0,0,0,0,0,0,0,0},{32,34,36,38,40,42,12,45,46,47,48,49,50,51,52,53,54,55,56,57,58,59,60,61,62,63,0,0,0,0}},
   {5,26,0,1,21,{0,0,0,0,0,0,0,0,0,0,0},{0,0,0,0,0,0,0,0,0,0,0},{32,3,37,8,42,43,44,45,46,47,48,49,50,51,52,53,54,55,56,57,58,59,60,61,62,63,0,0,0,0}},
   {6,26,0,7,25,{0,0,0,0,0,0,0,0,0,0,0},{0,0,0,0,0,0,0,0,0,0,0},{32,34,36,38,40,42,12,45,46,47,48,49,50,51,52,53,54,55,56,57,58,59,60,61,62,63,0,0,0,0}},
   {7,26,0,10,29,{0,0,0,0,0,0,0,0,0,0,0},{0,0,0,0,0,0,0,0,0,0,0},{32,34,36,38,40,42,12,45,46,47,48,49,50,51,52,53,54,55,56,57,58,59,60,61,62,63,0,0,0,0}},
   {0,7,8,255,255,{64,58,89,79,139,182,225,250,0,0,0},{0,0,0,255,0,0,0,0,0,0,0},{1,3,5,7,9,11,44,0,0,0,0,0,0,0,0,0,0,0,0,0,0,0,0,0,0,0,0,0,0,0}},
   {1,5,5,35,255,{4,69,111,183,232,0,0,0,0,0,0},{0,0,255,255,0,0,0,0,0,0,0},{1,3,5,7,9,0,0,0,0,0,0,0,0,0,0,0,0,0,0,0,0,0,0,0,0,0,0,0,0,0}},
   {2,5,8,47,255,{18,35,75,99,129,156,210,220,0,0,0},{0,0,0,0,0,0,0,0,0,0,0},{1,35,6,8,10,0,0,0,0,0,0,0,0,0,0,0,0,0,0,0,0,0,0,0,0,0,0,0,0,0}},
   {3,8,5,33,255,{88,50,71,143,212,0,0,0,0,0,0},{0,0,255,255,0,0,0,0,0,0,0},{1,3,5,7,9,42,12,45,0,0,0,0,0,0,0,0,0,0,0,0,0,0,0,0,0,0,0,0,0,0}},
   {4,5,6,11,255,{7,78,153,154,178,216,0,0,0,0,0},{255,0,0,0,0,0,0,0,0,0,0},{1,3,5,7,9,0,0,0,0,0,0,0,0,0,0,0,0,0,0,0,0,0,0,0,0,0,0,0,0,0}},
   {5,4,6,255,255,{9,21,70,132,181,229,0,0,0,0,0},{0,0,0,0,0,0,0,0,0,0,0},{1,35,6,40,0,0,0,0,0,0,0,0,0,0,0,0,0,0,0,0,0,0,0,0,0,0,0,0,0,0}},
   {6,5,5,26,255,{38,84,114,133,207,0,0,0,0,0,0},{0,0,0,0,192,0,0,0,0,0,0},{1,3,5,7,9,0,0,0,0,0,0,0,0,0,0,0,0,0,0,0,0,0,0,0,0,0,0,0,0,0}},
   {7,5,4,45,255,{15,86,141,206,0,0,0,0,0,0,0},{255,0,0,0,0,0,0,0,0,0,0},{1,3,5,7,9,0,0,0,0,0,0,0,0,0,0,0,0,0,0,0,0,0,0,0,0,0,0,0,0,0}},
   {0,5,7,32,255,{56,19,47,116,161,193,214,0,0,0,0},{0,0,255,0,0,0,0,0,0,0,0},{33,35,37,39,41,0,0,0,0,0,0,0,0,0,0,0,0,0,0,0,0,0,0,0,0,0,0,0,0,0}},
   {1,7,5,44,255,{33,31,123,148,223,0,0,0,0,0,0},{0,255,0,0,192,0,0,0,0,0,0},{33,35,37,39,41,11,44,0,0,0,0,0,0,0,0,0,0,0,0,0,0,0,0,0,0,0,0,0,0,0}},
   {2,2,7,30,255,{1,10,65,67,101,150,245,0,0,0,0},{0,0,0,0,0,0,0,0,0,0,0},{33,4,0,0,0,0,0,0,0,0,0,0,0,0,0,0,0,0,0,0,0,0,0,0,0,0,0,0,0,0}},
   {3,4,7,255,255,{8,26,20,77,124,191,251,0,0,0,0},{0,0,31,0,0,128,0,0,0,0,0},{33,35,37,39,0,0,0,0,0,0,0,0,0,0,0,0,0,0,0,0,0,0,0,0,0,0,0,0,0,0}},
   {4,7,7,24,255,{72,43,83,113,122,149,238,0,0,0,0},{0,0,0,0,0,0,0,0,0,0,0},{33,35,37,39,41,11,44,0,0,0,0,0,0,0,0,0,0,0,0,0,0,0,0,0,0,0,0,0,0,0}},
   {5,4,7,41,255,{17,28,52,106,130,155,199,0,0,0,0},{0,0,0,0,0,0,255,0,0,0,0},{33,4,38,9,0,0,0,0,0,0,0,0,0,0,0,0,0,0,0,0,0,0,0,0,0,0,0,0,0,0}},
   {6,7,7,13,255,{80,36,98,107,140,217,192,0,0,0,0},{0,0,0,0,0,0,0,0,0,0,0},{33,35,37,39,41,11,44,0,0,0,0,0,0,0,0,0,0,0,0,0,0,0,0,0,0,0,0,0,0,0}},
   {7,7,6,255,255,{48,30,102,146,188,221,0,0,0,0,0},{0,0,0,0,0,63,0,0,0,0,0},{33,35,37,39,41,11,44,0,0,0,0,0,0,0,0,0,0,0,0,0,0,0,0,0,0,0,0,0,0,0}},
   {8,21,2,255,2,{194,247,0,0,0,0,0,0,0,0,0},{0,240,0,0,0,0,0,0,0,0,0},{0,32,41,37,34,38,43,35,39,44,40,45,18,20,22,24,26,28,29,30,31,0,0,0,0,0,0,0,0,0}},
   {9,18,2,12,6,{136,165,0,0,0,0,0,0,0,0,0},{0,0,0,0,0,0,0,0,0,0,0},{0,32,41,37,34,38,43,35,39,44,40,45,18,20,22,24,26,28,0,0,0,0,0,0,0,0,0,0,0,0}},
   {10,21,2,28,10,{176,231,0,0,0,0,0,0,0,0,0},{0,128,0,0,0,0,0,0,0,0,0},{0,32,41,37,34,38,43,35,39,44,40,45,18,20,22,24,26,28,29,30,31,0,0,0,0,0,0,0,0,0}},
   {11,18,2,255,14,{157,239,0,0,0,0,0,0,0,0,0},{0,224,0,0,0,0,0,0,0,0,0},{0,32,41,37,34,38,43,35,39,44,40,45,18,20,22,24,26,28,0,0,0,0,0,0,0,0,0,0,0,0}},
   {12,17,4,39,18,{96,162,222,233,0,0,0,0,0,0,0},{0,0,0,0,0,0,0,0,0,0,0},{0,32,41,37,34,38,43,35,39,44,40,45,18,20,22,24,26,0,0,0,0,0,0,0,0,0,0,0,0,0}},
   {13,18,4,255,22,{120,163,189,243,0,0,0,0,0,0,0},{0,0,63,15,0,0,0,0,0,0,0},{0,32,41,37,34,38,43,35,39,44,40,45,18,20,22,24,26,28,0,0,0,0,0,0,0,0,0,0,0,0}},
   {14,19,3,38,26,{144,174,224,0,0,0,0,0,0,0,0},{0,0,0,0,0,0,0,0,0,0,0},{0,32,41,37,34,38,43,35,39,44,40,45,18,20,22,24,26,28,30,0,0,0,0,0,0,0,0,0,0,0}},
   {15,20,1,22,30,{196,0,0,0,0,0,0,0,0,0,0},{0,0,0,0,0,0,0,0,0,0,0},{0,32,41,37,34,38,43,35,39,44,40,45,18,20,22,24,26,28,30,31,0,0,0,0,0,0,0,0,0,0}},
   {8,17,5,255,3,{104,147,195,226,234,0,0,0,0,0,0},{0,0,0,0,0,0,0,0,0,0,0},{1,4,6,8,10,11,12,13,14,15,16,17,19,21,23,25,27,0,0,0,0,0,0,0,0,0,0,0,0,0}},
   {9,20,3,34,7,{168,187,228,0,0,0,0,0,0,0,0},{0,0,0,0,0,0,0,0,0,0,0},{1,4,6,8,10,11,12,13,14,15,16,17,19,21,23,25,27,29,30,31,0,0,0,0,0,0,0,0,0,0}},
   {10,17,4,31,11,{112,172,218,235,0,0,0,0,0,0,0},{0,0,0,0,0,0,0,0,0,0,0},{1,4,6,8,10,11,12,13,14,15,16,17,19,21,23,25,27,0,0,0,0,0,0,0,0,0,0,0,0,0}},
   {11,20,3,29,15,{160,186,213,0,0,0,0,0,0,0,0},{0,0,0,0,0,0,0,0,0,0,0},{1,4,6,8,10,11,12,13,14,15,16,17,19,21,23,25,27,29,30,31,0,0,0,0,0,0,0,0,0,0}},
   {12,21,2,42,19,{190,240,0,0,0,0,0,0,0,0,0},{64,0,0,0,0,0,0,0,0,0,0},{1,4,6,8,10,11,12,13,14,15,16,17,19,21,23,25,27,28,29,30,31,0,0,0,0,0,0,0,0,0}},
   {13,20,2,25,23,{177,215,0,0,0,0,0,0,0,0,0},{0,255,0,0,0,0,0,0,0,0,0},{1,4,6,8,10,11,12,13,14,15,16,17,19,21,23,25,27,29,30,31,0,0,0,0,0,0,0,0,0,0}},
   {14,19,3,40,27,{152,171,205,0,0,0,0,0,0,0,0},{0,0,63,0,0,0,0,0,0,0,0},{1,4,6,8,10,11,12,13,14,15,16,17,19,21,23,25,27,29,31,0,0,0,0,0,0,0,0,0,0,0}},
   {15,18,3,255,31,{128,167,244,0,0,0,0,0,0,0,0},{0,255,0,0,0,0,0,0,0,0,0},{1,4,6,8,10,11,12,13,14,15,16,17,19,21,23,25,27,29,0,0,0,0,0,0,0,0,0,0,0,0}},
   {8,4,5,255,255,{6,62,138,159,230,0,0,0,0,0,0},{0,0,0,255,127,0,0,0,0,0,0},{2,36,33,42,0,0,0,0,0,0,0,0,0,0,0,0,0,0,0,0,0,0,0,0,0,0,0,0,0,0}},
   {9,4,6,27,255,{40,13,55,131,164,246,0,0,0,0,0},{0,0,255,0,0,0,0,0,0,0,0},{2,36,33,42,0,0,0,0,0,0,0,0,0,0,0,0,0,0,0,0,0,0,0,0,0,0,0,0,0,0}},
   {10,4,6,14,255,{27,82,73,85,127,209,0,0,0,0,0},{0,0,0,0,255,0,0,0,0,0,0},{2,36,33,42,0,0,0,0,0,0,0,0,0,0,0,0,0,0,0,0,0,0,0,0,0,0,0,0,0,0}},
   {11,4,5,36,255,{37,54,121,125,198,0,0,0,0,0,0},{0,0,0,0,0,0,0,0,0,0,0},{2,36,33,42,0,0,0,0,0,0,0,0,0,0,0,0,0,0,0,0,0,0,0,0,0,0,0,0,0,0}},
   {12,4,7,43,255,{2,81,60,97,108,158,211,0,0,0,0},{0,0,0,0,0,0,0,0,0,0,0},{2,36,33,42,0,0,0,0,0,0,0,0,0,0,0,0,0,0,0,0,0,0,0,0,0,0,0,0,0,0}},
   {13,4,7,255,255,{11,41,49,63,135,237,241,0,0,0,0},{0,0,0,255,255,0,0,0,0,0,0},{2,36,33,42,0,0,0,0,0,0,0,0,0,0,0,0,0,0,0,0,0,0,0,0,0,0,0,0,0,0}},
   {14,4,5,255,255,{29,91,95,151,253,0,0,0,0,0,0},{0,0,255,255,63,0,0,0,0,0,0},{2,36,33,42,0,0,0,0,0,0,0,0,0,0,0,0,0,0,0,0,0,0,0,0,0,0,0,0,0,0}},
   {15,4,5,255,255,{44,61,103,175,252,0,0,0,0,0,0},{0,0,255,255,31,0,0,0,0,0,0},{2,36,33,42,0,0,0,0,0,0,0,0,0,0,0,0,0,0,0,0,0,0,0,0,0,0,0,0,0,0}},
   {8,4,6,19,255,{22,74,93,137,145,180,0,0,0,0,0},{0,0,0,0,0,0,0,0,0,0,0},{3,5,7,9,0,0,0,0,0,0,0,0,0,0,0,0,0,0,0,0,0,0,0,0,0,0,0,0,0,0}},
   {9,4,7,255,255,{32,5,76,110,166,227,249,0,0,0,0},{0,0,0,0,0,0,0,0,0,0,0},{3,5,7,9,0,0,0,0,0,0,0,0,0,0,0,0,0,0,0,0,0,0,0,0,0,0,0,0,0,0}},
   {10,4,3,3,255,{23,92,119,0,0,0,0,0,0,0,0},{224,0,255,0,0,0,0,0,0,0,0},{3,5,7,9,0,0,0,0,0,0,0,0,0,0,0,0,0,0,0,0,0,0,0,0,0,0,0,0,0,0}},
   {11,4,7,4,255,{34,57,59,90,105,126,185,0,0,0,0},{0,0,0,0,0,0,0,0,0,0,0},{3,5,7,9,0,0,0,0,0,0,0,0,0,0,0,0,0,0,0,0,0,0,0,0,0,0,0,0,0,0}},
   {12,4,5,9,255,{16,3,39,118,202,0,0,0,0,0,0},{0,0,255,0,0,0,0,0,0,0,0},{3,5,7,9,0,0,0,0,0,0,0,0,0,0,0,0,0,0,0,0,0,0,0,0,0,0,0,0,0,0}},
   {13,4,4,20,255,{14,100,115,134,0,0,0,0,0,0,0},{0,0,0,0,0,0,0,0,0,0,0},{3,5,7,9,0,0,0,0,0,0,0,0,0,0,0,0,0,0,0,0,0,0,0,0,0,0,0,0,0,0}},
   {14,4,4,18,255,{12,51,87,173,0,0,0,0,0,0,0},{0,0,255,0,0,0,0,0,0,0,0},{3,5,7,9,0,0,0,0,0,0,0,0,0,0,0,0,0,0,0,0,0,0,0,0,0,0,0,0,0,0}},
   {15,4,7,8,255,{0,25,66,46,117,170,184,0,0,0,0},{0,0,0,0,0,0,0,0,0,0,0},{3,5,7,9,0,0,0,0,0,0,0,0,0,0,0,0,0,0,0,0,0,0,0,0,0,0,0,0,0,0}},
   {2,5,4,2,255,{42,45,94,142,0,0,0,0,0,0,0},{0,0,0,0,0,0,0,0,0,0,0},{2,36,38,40,42,0,0,0,0,0,0,0,0,0,0,0,0,0,0,0,0,0,0,0,0,0,0,0,0,0}},
   {5,4,7,46,255,{24,53,68,109,169,179,219,0,0,0,0},{0,0,0,0,0,0,0,0,0,0,0},{2,36,7,41,0,0,0,0,0,0,0,0,0,0,0,0,0,0,0,0,0,0,0,0,0,0,0,0,0,0}}},
  32, {5,5,6,1,4,5,5,5,5,6,5,8,9,7,10,5,5,5,6,10,6,8,10,5},
  {{1,3,0,2,4,5,7,6,8,9,10,11,12,13,14,15,16,17,18,19,20,21,22,23,24,25,27,26,28,29,31,30},
   {0,1,2,3,4,7,10,5,8,6,11,9,12,13,14,15,16,19,17,18,21,20,22,23,24,27,26,25,29,28,30,31},
   {0,4,2,5,3,1,8,7,10,6,9,11,12,13,14,15,17,16,19,18,20,21,25,22,23,24,26,27,28,29,30,31},
   {1,3,0,2,4,5,7,6,11,8,9,10,12,13,14,15,16,17,19,18,20,21,22,23,24,25,26,27,29,28,31,30},
   {1,5,0,3,2,4,7,6,8,9,12,10,11,13,14,15,16,17,18,19,21,24,22,20,23,25,26,27,28,30,29,31},
   {3,4,6,0,1,2,5,7,8,10,9,11,12,13,14,15,16,17,21,18,19,20,22,23,25,30,26,24,29,27,28,31},
   {0,1,2,4,3,5,6,7,8,9,10,11,12,13,14,15,16,17,18,19,20,21,22,24,25,27,23,26,29,30,31,28},
   {2,0,1,3,4,5,6,7,8,9,10,11,12,13,14,15,16,17,19,18,20,21,22,23,25,27,24,26,28,29,30,31}}};

typedef CUresult (*EncodeFn)(CUtensorMap*, CUtensorMapDataType, cuuint32_t, void*, const cuuint64_t*, const cuuint64_t*, const cuuint32_t*,
                             const cuuint32_t*, CUtensorMapInterleave, CUtensorMapSwizzle, CUtensorMapL2promotion, CUtensorMapFloatOOBfill);

void make_map2(EncodeFn enc, CUtensorMap* m, const void* ptr, int rows, int cols, int box_rows) {
  cuuint64_t dim[2] = {(cuuint64_t)cols, (cuuint64_t)rows}, str[1] = {(cuuint64_t)cols * 2};
  cuuint32_t box[2] = {64, (cuuint32_t)box_rows}, es[2] = {1, 1};
  enc(m, CU_TENSOR_MAP_DATA_TYPE_BFLOAT16, 2, const_cast<void*>(ptr), dim, str, box, es, CU_TENSOR_MAP_INTERLEAVE_NONE, CU_TENSOR_MAP_SWIZZLE_128B,
      CU_TENSOR_MAP_L2_PROMOTION_L2_128B, CU_TENSOR_MAP_FLOAT_OOB_FILL_NONE);
}
void make_map3(EncodeFn enc, CUtensorMap* m, const void* ptr, int rows) {
  cuuint64_t dim[3] = {64, (cuuint64_t)rows, 9}, str[2] = {DM * 2, 128};
  cuuint32_t box[3] = {64, 32, 3}, es[3] = {1, 1, 1};
  enc(m, CU_TENSOR_MAP_DATA_TYPE_BFLOAT16, 3, const_cast<void*>(ptr), dim, str, box, es, CU_TENSOR_MAP_INTERLEAVE_NONE, CU_TENSOR_MAP_SWIZZLE_128B,
      CU_TENSOR_MAP_L2_PROMOTION_L2_128B, CU_TENSOR_MAP_FLOAT_OOB_FILL_NONE);
}

void make_map_t(EncodeFn enc, CUtensorMap* m, void* ptr, int width, int cols) {
  cuuint64_t dim[3] = {TP / 2, 2, 864}, str[2] = {TP * 2, TP * 4};
  cuuint32_t box[3] = {(cuuint32_t)width, 2, (cuuint32_t)cols}, es[3] = {1, 1, 1};
  enc(m, CU_TENSOR_MAP_DATA_TYPE_UINT32, 3, ptr, dim, str, box, es, CU_TENSOR_MAP_INTERLEAVE_NONE, cols == 64 ? CU_TENSOR_MAP_SWIZZLE_128B : CU_TENSOR_MAP_SWIZZLE_NONE,
      CU_TENSOR_MAP_L2_PROMOTION_NONE, CU_TENSOR_MAP_FLOAT_OOB_FILL_NONE);
}

int g_mode = -1;

}

extern "C" void kernel_launch(void* const* d_in, const int* in_sizes, int n_in, void* d_out, int out_size) {
  static EncodeFn enc = nullptr;
  static void* t_ptr = nullptr;
  if (!enc) {
    void* fn = nullptr;
    cudaDriverEntryPointQueryResult st;
    cudaGetDriverEntryPoint("cuTensorMapEncodeTiled", &fn, cudaEnableDefault, &st);
    enc = (EncodeFn)fn;
    cudaGetSymbolAddress(&t_ptr, g_T);
    cudaFuncSetAttribute(fused_kernel, cudaFuncAttributeMaxDynamicSharedMemorySize, SMEM_BYTES);
    if (g_mode < 0) {
      cudaLaunchConfig_t cfg = {};
      cfg.gridDim = dim3(2 * NCL); cfg.blockDim = dim3(384); cfg.dynamicSmemBytes = SMEM_BYTES;
      cudaLaunchAttribute at; at.id = cudaLaunchAttributeClusterDimension;
      at.val.clusterDim.x = 2; at.val.clusterDim.y = 1; at.val.clusterDim.z = 1;
      cfg.attrs = &at; cfg.numAttrs = 1;
      int nc = 0;
      g_mode = (cudaOccupancyMaxActiveClusters(&nc, fused_kernel, &cfg) == cudaSuccess && nc >= NCL) ? 1 : 0;
      (void)cudaGetLastError();
    }
  }
  Params p;
  make_map2(enc, &p.map_a[0], d_in[4], SEQ, DC, 128);
  make_map2(enc, &p.map_a[1], d_in[0], SEQ, DM, 128);
  make_map2(enc, &p.map_w[0], d_in[6], DC, 4096, 64);
  make_map2(enc, &p.map_w[1], d_in[7], DC, 4096, 64);
  make_map2(enc, &p.map_w[2], d_in[5], DM, 4096, 64);
  make_map2(enc, &p.map_w[3], d_in[1], DM, 1728, 64);
  make_map3(enc, &p.map_o[0], d_in[8], 4096);
  make_map3(enc, &p.map_o[1], d_in[2], DM);
  make_map_t(enc, &p.map_t[0], t_ptr, 32, 9);
  make_map_t(enc, &p.map_t[1], t_ptr, 40, 9);
  make_map_t(enc, &p.map_t[2], t_ptr, 32, 64);
  p.x = (const __nv_bfloat16*)d_in[0];
  p.gate_w = (const __nv_bfloat16*)d_in[9];
  make_map2(enc, &p.map_out, d_out, SEQ, DM, 16);
  p.out = (__nv_bfloat16*)d_out;
  p.zero = 0;
  auto launch = [&](int phases) {
    p.s = k_sched;
    for (int i = 0; i < NCL; i++) {
      Rec& r = p.s.r[i];
      if (!(phases & 1)) r.n1 = 0;
      if (!(phases & 2)) r.n2 = 0;
      if (!(phases & (r.p3 < 24 ? 4 : 32))) r.p3 = 255;
      if (!(phases & 8)) r.bg = 255;
      const int u1 = r.n1 ? 8 + r.n1 * (8 + (r.slab >> 3)) : 0;
      int u2 = 0;
      for (int k = 0; k < r.n2; k++) u2 += 4 * (r.item[k] & 7) + 4;
      r.u1 = (uint8_t)u1; r.u2 = (uint8_t)u2;
      r.rot = (uint8_t)(((u1 % 10 + 1) >> 1) % 5);
      r.x3 = (uint8_t)((r.rot + u2) % 5 & 3);
      r.ring = (phases & 16) ? p.s.ring : 32;
      r.phases = (uint8_t)phases;
    }
    fused_kernel<<<2 * NCL, 384, SMEM_BYTES>>>(p);
  };
  if (g_mode == 1) launch(63);
  else { launch(1); launch(10); launch(32); launch(4); }
}
```

```cpp
#include <cuda_runtime.h>
#include <cuda_bf16.h>
#include <cuda.h>
#include <stdint.h>

namespace {

constexpr int SEQ = 2048, DM = 576, DC = 512, NH = 32;
constexpr int NCL = 66;
constexpr uint32_t DESC_HI = 0x40000040u;

constexpr int SM_RING = 0;
constexpr int SM_BUF = 163840;
constexpr int SM_BAR = 229376;
constexpr int B_P1E = 0, B_P2E = 10, B_P3E = 15, B_P2F = 24, B_SF = 32, B_ORD = 36, B_LAD = 40, B_DONE = 41, B_FIN = 48;
constexpr int B_P3F = 56, B_OUT = 61, B_P1F = 64, B_SE = 74, B_QF = 80, B_LA = 84, B_NUM = 88;
constexpr uint64_t B_CNT = 0x11118245000ull;
constexpr int SMEM_BYTES = SM_BAR + B_NUM * 8 + 1024;

constexpr int F_QKVA = 32;
constexpr int F_GATE = 64;
constexpr int F_DONE = 65;
constexpr int F_CTX = 96;
constexpr int F_OUT = 96 + 8 * 64;
constexpr int F_KV = F_OUT + 64;
constexpr int F_Q = F_KV + 256;
constexpr int F_RD = F_Q + 256;
constexpr int F_NUM = F_RD + 256;

struct Rec {
  uint8_t slab;
  uint8_t n1, n2;
  uint8_t p3;
  uint8_t bg;
  uint8_t item[11];
  uint8_t last[11];
  uint8_t tile[32];
  uint8_t u1, u2;
  uint8_t rot, x3;
  uint8_t phases;
};
struct Sched {
  Rec r[NCL];
  uint8_t nh[24];
  uint8_t p3_order[8][32];
  uint8_t slot[32][8];
  uint8_t prev[32][8];
};

struct Params {
  CUtensorMap map_a[2];
  CUtensorMap map_w[4];
  CUtensorMap map_o[2];
  CUtensorMap map_t[3];
  CUtensorMap map_out;
  const __nv_bfloat16* x;
  const __nv_bfloat16* gate_w;
  __nv_bfloat16* out;
  int zero;
  alignas(64) Sched s;
};

__device__ __align__(1024) uint8_t g_Q[NH * 32 * 16384];
__device__ __align__(1024) uint8_t g_KV[2 * NH * 16 * 32768];
__device__ __align__(1024) uint8_t g_oA[32 * 576 * 128];
constexpr int TP = SEQ + 16;
__device__ __align__(1024) uint32_t g_T[864 * TP];
__device__ float g_gate[SEQ];
__device__ int g_flags[F_NUM];

__device__ __forceinline__ void mbar_arrive(uint32_t b) { asm volatile("mbarrier.arrive.shared::cta.b64 _, [%0];" ::"r"(b) : "memory"); }
__device__ __forceinline__ void mbar_arrive_cl(uint32_t b, int cnt) {
  asm volatile("mbarrier.arrive.shared::cluster.b64 _, [%0], %1;" ::"r"(b), "r"(cnt) : "memory");
}
__device__ __forceinline__ void mbar_wait(uint32_t b, int par) {
  asm volatile(
      "{\n.reg .pred p;\n.reg .u32 c;\n"
      "mbarrier.try_wait.parity.shared::cta.b64 p, [%0], %1;\n@p bra DN;\nmov.u32 c, 0;\n"
      "LP:\nmbarrier.try_wait.parity.shared::cta.b64 p, [%0], %1;\n@p bra DN;\n"
      "add.u32 c, c, 1;\nsetp.lt.u32 p, c, 4000000;\n@p bra LP;\ntrap;\nDN:\n}" ::"r"(b), "r"(par) : "memory");
}
__device__ __forceinline__ uint32_t mapa(uint32_t a, uint32_t cta) {
  uint32_t r; asm("mapa.shared::cluster.u32 %0, %1, %2;" : "=r"(r) : "r"(a), "r"(cta)); return r;
}
#define ELECT(ins) "{\n.reg .pred e;\nelect.sync _|e, 0xffffffff;\n@e " ins "\n}"
__device__ __forceinline__ void mbar_expect(uint32_t b, int bytes) {
  asm volatile(ELECT("mbarrier.arrive.expect_tx.shared::cta.b64 _, [%0], %1;") ::"r"(b), "r"(bytes) : "memory");
}
__device__ __forceinline__ void mbar_arrive_one(uint32_t b) { asm volatile(ELECT("mbarrier.arrive.shared::cta.b64 _, [%0];") ::"r"(b) : "memory"); }
constexpr uint64_t L2_NORMAL = 0x1000000000000000ull, L2_FIRST = 0x12F0000000000000ull;
__device__ __forceinline__ void bulk_load(uint32_t dst, const void* src, int bytes, uint32_t bar, uint64_t pol = L2_NORMAL) {
  asm volatile(ELECT("cp.async.bulk.shared::cluster.global.mbarrier::complete_tx::bytes.L2::cache_hint [%0], [%1], %2, [%3], %4;") ::"r"(dst), "l"(src), "r"(bytes), "r"(bar), "l"(pol) : "memory");
}
__device__ __forceinline__ void bulk_load_mc(uint32_t dst, const void* src, int bytes, uint32_t bar, uint64_t pol = L2_NORMAL) {
  asm volatile(ELECT("cp.async.bulk.shared::cluster.global.mbarrier::complete_tx::bytes.multicast::cluster.L2::cache_hint [%0], [%1], %2, [%3], %4, %5;") ::"r"(dst), "l"(src), "r"(bytes), "r"(bar), "h"((uint16_t)3), "l"(pol) : "memory");
}
__device__ __forceinline__ void bulk_store(void* dst, uint32_t src, int bytes, uint64_t pol = L2_NORMAL) {
  asm volatile(ELECT("cp.async.bulk.global.shared::cta.bulk_group.L2::cache_hint [%0], [%1], %2, %3;") ::"l"(dst), "r"(src), "r"(bytes), "l"(pol) : "memory");
}
__device__ __forceinline__ void tma2d(uint32_t dst, const CUtensorMap* m, int c0, int c1, uint32_t bar, uint64_t pol = L2_NORMAL) {
  asm volatile(ELECT("cp.async.bulk.tensor.2d.shared::cluster.global.mbarrier::complete_tx::bytes.L2::cache_hint [%0], [%1, {%3, %4}], [%2], %5;") ::"r"(dst), "l"(m), "r"(bar), "r"(c0), "r"(c1), "l"(pol) : "memory");
}
__device__ __forceinline__ void tma2d_mc(uint32_t dst, const CUtensorMap* m, int c0, int c1, uint32_t bar, uint64_t pol = L2_NORMAL) {
  asm volatile(ELECT("cp.async.bulk.tensor.2d.shared::cluster.global.mbarrier::complete_tx::bytes.multicast::cluster.L2::cache_hint [%0], [%1, {%3, %4}], [%2], %5, %6;") ::"r"(dst), "l"(m), "r"(bar), "r"(c0), "r"(c1), "h"((uint16_t)3), "l"(pol) : "memory");
}
__device__ __forceinline__ void tma3d(uint32_t dst, const CUtensorMap* m, int c0, int c1, int c2, uint32_t bar, uint64_t pol = L2_NORMAL) {
  asm volatile(ELECT("cp.async.bulk.tensor.3d.shared::cluster.global.mbarrier::complete_tx::bytes.L2::cache_hint [%0], [%1, {%3, %4, %5}], [%2], %6;") ::"r"(dst), "l"(m), "r"(bar), "r"(c0), "r"(c1), "r"(c2), "l"(pol) : "memory");
}
__device__ __forceinline__ void tma3d_mc(uint32_t dst, const CUtensorMap* m, int c0, int c1, int c2, uint32_t bar, uint64_t pol = L2_NORMAL) {
  asm volatile(ELECT("cp.async.bulk.tensor.3d.shared::cluster.global.mbarrier::complete_tx::bytes.multicast::cluster.L2::cache_hint [%0], [%1, {%3, %4, %5}], [%2], %6, %7;") ::"r"(dst), "l"(m), "r"(bar), "r"(c0), "r"(c1), "r"(c2), "h"((uint16_t)3), "l"(pol) : "memory");
}
__device__ __forceinline__ void tma2d_add(const CUtensorMap* m, uint32_t src, int c0, int c1) {
  asm volatile(ELECT("cp.reduce.async.bulk.tensor.2d.global.shared::cta.add.bulk_group [%0, {%2, %3}], [%1];") ::"l"(m), "r"(src), "r"(c0), "r"(c1) : "memory");
}
__device__ __forceinline__ void tma3d_store(const CUtensorMap* m, uint32_t src, int c0, int c1, int c2, uint64_t pol = L2_NORMAL) {
  asm volatile(ELECT("cp.async.bulk.tensor.3d.global.shared::cta.bulk_group.L2::cache_hint [%0, {%2, %3, %4}], [%1], %5;") ::"l"(m), "r"(src), "r"(c0), "r"(c1), "r"(c2), "l"(pol) : "memory");
}
__device__ __forceinline__ void tma2d_prefetch(const CUtensorMap* m, int c0, int c1, uint64_t pol = L2_NORMAL) {
  asm volatile(ELECT("cp.async.bulk.prefetch.tensor.2d.L2.global.L2::cache_hint [%0, {%1, %2}], %3;") ::"l"(m), "r"(c0), "r"(c1), "l"(pol) : "memory");
}
#define HINT 62
#define POL(bit) ((HINT >> (bit)) & 1 ? L2_FIRST : L2_NORMAL)
#define BULK_COMMIT() asm volatile("cp.async.bulk.commit_group;" ::: "memory")
#define BULK_WAIT(n) asm volatile("cp.async.bulk.wait_group %0;" ::"n"(n) : "memory")
#define BULK_WAIT_READ(n) asm volatile("cp.async.bulk.wait_group.read %0;" ::"n"(n) : "memory")
#define FENCE_ASYNC_SMEM() asm volatile("fence.proxy.async.shared::cta;" ::: "memory")
#define FENCE_ASYNC_ALL() asm volatile("fence.proxy.async;" ::: "memory")
#define WG_FENCE() asm volatile("wgmma.fence.sync.aligned;" ::: "memory")
#define WG_COMMIT() asm volatile("wgmma.commit_group.sync.aligned;" ::: "memory")
#define WG_WAIT(n) asm volatile("wgmma.wait_group.sync.aligned %0;" ::"n"(n) : "memory")
__device__ __forceinline__ void bar_sync(int id, int n) { asm volatile("bar.sync %0, %1;" ::"r"(id), "r"(n) : "memory"); }
__device__ __forceinline__ void bar_arrive(int id, int n) { asm volatile("bar.arrive %0, %1;" ::"r"(id), "r"(n) : "memory"); }
__device__ __forceinline__ void cluster_sync() {
  asm volatile("barrier.cluster.arrive.relaxed;\nbarrier.cluster.wait.acquire;" ::: "memory");
}
template <int N> __device__ __forceinline__ void pin(float (&r)[N]) {
#pragma unroll
  for (int i = 0; i < N; i++) asm volatile("" : "+f"(r[i])::"memory");
}
template <int N> __device__ __forceinline__ void pin(uint32_t (&r)[N]) {
#pragma unroll
  for (int i = 0; i < N; i++) asm volatile("" : "+r"(r[i])::"memory");
}
__device__ __forceinline__ uint32_t pack_bf16(float lo, float hi) {
  uint32_t r; asm("cvt.rn.bf16x2.f32 %0, %1, %2;" : "=r"(r) : "f"(hi), "f"(lo)); return r;
}
__device__ __forceinline__ float ex2(float x) { float r; asm("ex2.approx.ftz.f32 %0, %1;" : "=f"(r) : "f"(x)); return r; }
__device__ __forceinline__ void ldsm4(uint32_t a, uint32_t& r0, uint32_t& r1, uint32_t& r2, uint32_t& r3) {
  asm volatile("ldmatrix.sync.aligned.m8n8.x4.shared.b16 {%0,%1,%2,%3}, [%4];" : "=r"(r0), "=r"(r1), "=r"(r2), "=r"(r3) : "r"(a) : "memory");
}
__device__ __forceinline__ void stsm4(uint32_t a, uint32_t r0, uint32_t r1, uint32_t r2, uint32_t r3) {
  asm volatile("stmatrix.sync.aligned.m8n8.x4.shared.b16 [%0], {%1,%2,%3,%4};" ::"r"(a), "r"(r0), "r"(r1), "r"(r2), "r"(r3) : "memory");
}
__device__ __forceinline__ void flag_add(int idx) {
  asm volatile(ELECT("red.release.gpu.global.add.s32 [%0], 1;") ::"l"(g_flags + idx) : "memory");
}
__device__ __forceinline__ void flag_add_rx(int idx) {
  asm volatile(ELECT("red.relaxed.gpu.global.add.s32 [%0], 1;") ::"l"(g_flags + idx) : "memory");
}
template <bool ACQ, int NS = 32> __device__ __forceinline__ void flag_wait(int idx, int target) {
  int n = 0;
  while (true) {
    int v;
    if (ACQ) asm volatile("ld.acquire.gpu.global.s32 %0, [%1];" : "=r"(v) : "l"(g_flags + idx) : "memory");
    else asm volatile("ld.relaxed.gpu.global.s32 %0, [%1];" : "=r"(v) : "l"(g_flags + idx) : "memory");
    if (__all_sync(0xffffffffu, v >= target)) break;
    if (++n > 20000000) __trap();
    __nanosleep(NS);
  }
}
__device__ __forceinline__ uint32_t desc_lo(uint32_t addr, uint32_t lbo) { return ((addr & 0x3FFFFu) >> 4) | ((lbo >> 4) << 16); }
#define PROF(role, i)
#define PROFX(cond, i)
#define PROFB(i)
#define PROFG(i)

template <int TB, int TA = 0> __device__ __forceinline__ void wgmma_ss64(float (&d)[32], uint32_t alo, uint32_t blo, int sd) {
  asm volatile("{\n.reg .pred p;\n.reg .b64 da, db;\n"
    "setp.ne.b32 p, %34, 0;\nmov.b64 da, {%32, %36};\nmov.b64 db, {%33, %36};\n"
    "wgmma.mma_async.sync.aligned.m64n64k16.f32.bf16.bf16 "
    "{%0,%1,%2,%3,%4,%5,%6,%7,%8,%9,%10,%11,%12,%13,%14,%15,%16,%17,%18,%19,%20,%21,%22,%23,"
    "%24,%25,%26,%27,%28,%29,%30,%31}, "
    "da, db, p, 1, 1, %37, %35;\n}\n"
    : "+f"(d[0]),"+f"(d[1]),"+f"(d[2]),"+f"(d[3]),"+f"(d[4]),"+f"(d[5]),"+f"(d[6]),"+f"(d[7]),"+f"(d[8]),"+f"(d[9]),"+f"(d[10]),"+f"(d[11]),
      "+f"(d[12]),"+f"(d[13]),"+f"(d[14]),"+f"(d[15]),"+f"(d[16]),"+f"(d[17]),"+f"(d[18]),"+f"(d[19]),"+f"(d[20]),"+f"(d[21]),"+f"(d[22]),"+f"(d[23]),
      "+f"(d[24]),"+f"(d[25]),"+f"(d[26]),"+f"(d[27]),"+f"(d[28]),"+f"(d[29]),"+f"(d[30]),"+f"(d[31])
    : "r"(alo), "r"(blo), "r"(sd), "n"(TB), "r"(DESC_HI), "n"(TA));
}
template <int TB, int TA = 0> __device__ __forceinline__ void wgmma_ss128(float (&d)[64], uint32_t alo, uint32_t blo, int sd) {
  asm volatile("{\n.reg .pred p;\n.reg .b64 da, db;\n"
    "setp.ne.b32 p, %66, 0;\nmov.b64 da, {%64, %68};\nmov.b64 db, {%65, %68};\n"
    "wgmma.mma_async.sync.aligned.m64n128k16.f32.bf16.bf16 "
    "{%0,%1,%2,%3,%4,%5,%6,%7,%8,%9,%10,%11,%12,%13,%14,%15,%16,%17,%18,%19,%20,%21,%22,%23,"
    "%24,%25,%26,%27,%28,%29,%30,%31,%32,%33,%34,%35,%36,%37,%38,%39,%40,%41,%42,%43,%44,%45,%46,%47,"
    "%48,%49,%50,%51,%52,%53,%54,%55,%56,%57,%58,%59,%60,%61,%62,%63}, "
    "da, db, p, 1, 1, %69, %67;\n}\n"
    : "+f"(d[0]),"+f"(d[1]),"+f"(d[2]),"+f"(d[3]),"+f"(d[4]),"+f"(d[5]),"+f"(d[6]),"+f"(d[7]),"+f"(d[8]),"+f"(d[9]),"+f"(d[10]),"+f"(d[11]),
      "+f"(d[12]),"+f"(d[13]),"+f"(d[14]),"+f"(d[15]),"+f"(d[16]),"+f"(d[17]),"+f"(d[18]),"+f"(d[19]),"+f"(d[20]),"+f"(d[21]),"+f"(d[22]),"+f"(d[23]),
      "+f"(d[24]),"+f"(d[25]),"+f"(d[26]),"+f"(d[27]),"+f"(d[28]),"+f"(d[29]),"+f"(d[30]),"+f"(d[31]),"+f"(d[32]),"+f"(d[33]),"+f"(d[34]),"+f"(d[35]),
      "+f"(d[36]),"+f"(d[37]),"+f"(d[38]),"+f"(d[39]),"+f"(d[40]),"+f"(d[41]),"+f"(d[42]),"+f"(d[43]),"+f"(d[44]),"+f"(d[45]),"+f"(d[46]),"+f"(d[47]),
      "+f"(d[48]),"+f"(d[49]),"+f"(d[50]),"+f"(d[51]),"+f"(d[52]),"+f"(d[53]),"+f"(d[54]),"+f"(d[55]),"+f"(d[56]),"+f"(d[57]),"+f"(d[58]),"+f"(d[59]),
      "+f"(d[60]),"+f"(d[61]),"+f"(d[62]),"+f"(d[63])
    : "r"(alo), "r"(blo), "r"(sd), "n"(TB), "r"(DESC_HI), "n"(TA));
}
template <int TB> __device__ __forceinline__ void wgmma_rs128(float (&d)[64], uint32_t a0, uint32_t a1, uint32_t a2, uint32_t a3, uint32_t blo, int sd) {
  asm volatile("{\n.reg .pred p;\n.reg .b64 db;\n"
    "setp.ne.b32 p, %69, 0;\nmov.b64 db, {%68, %71};\n"
    "wgmma.mma_async.sync.aligned.m64n128k16.f32.bf16.bf16 "
    "{%0,%1,%2,%3,%4,%5,%6,%7,%8,%9,%10,%11,%12,%13,%14,%15,%16,%17,%18,%19,%20,%21,%22,%23,"
    "%24,%25,%26,%27,%28,%29,%30,%31,%32,%33,%34,%35,%36,%37,%38,%39,%40,%41,%42,%43,%44,%45,%46,%47,"
    "%48,%49,%50,%51,%52,%53,%54,%55,%56,%57,%58,%59,%60,%61,%62,%63}, "
    "{%64,%65,%66,%67}, db, p, 1, 1, %70;\n}\n"
    : "+f"(d[0]),"+f"(d[1]),"+f"(d[2]),"+f"(d[3]),"+f"(d[4]),"+f"(d[5]),"+f"(d[6]),"+f"(d[7]),"+f"(d[8]),"+f"(d[9]),"+f"(d[10]),"+f"(d[11]),
      "+f"(d[12]),"+f"(d[13]),"+f"(d[14]),"+f"(d[15]),"+f"(d[16]),"+f"(d[17]),"+f"(d[18]),"+f"(d[19]),"+f"(d[20]),"+f"(d[21]),"+f"(d[22]),"+f"(d[23]),
      "+f"(d[24]),"+f"(d[25]),"+f"(d[26]),"+f"(d[27]),"+f"(d[28]),"+f"(d[29]),"+f"(d[30]),"+f"(d[31]),"+f"(d[32]),"+f"(d[33]),"+f"(d[34]),"+f"(d[35]),
      "+f"(d[36]),"+f"(d[37]),"+f"(d[38]),"+f"(d[39]),"+f"(d[40]),"+f"(d[41]),"+f"(d[42]),"+f"(d[43]),"+f"(d[44]),"+f"(d[45]),"+f"(d[46]),"+f"(d[47]),
      "+f"(d[48]),"+f"(d[49]),"+f"(d[50]),"+f"(d[51]),"+f"(d[52]),"+f"(d[53]),"+f"(d[54]),"+f"(d[55]),"+f"(d[56]),"+f"(d[57]),"+f"(d[58]),"+f"(d[59]),
      "+f"(d[60]),"+f"(d[61]),"+f"(d[62]),"+f"(d[63])
    : "r"(a0), "r"(a1), "r"(a2), "r"(a3), "r"(blo), "r"(sd), "n"(TB), "r"(DESC_HI));
}
template <int TB, int TA = 0> __device__ __forceinline__ void wgmma_ss192(float (&d)[96], uint32_t alo, uint32_t blo, int sd) {
  asm volatile("{\n.reg .pred p;\n.reg .b64 da, db;\n"
    "setp.ne.b32 p, %98, 0;\nmov.b64 da, {%96, %100};\nmov.b64 db, {%97, %100};\n"
    "wgmma.mma_async.sync.aligned.m64n192k16.f32.bf16.bf16 "
    "{%0,%1,%2,%3,%4,%5,%6,%7,%8,%9,%10,%11,%12,%13,%14,%15,%16,%17,%18,%19,%20,%21,%22,%23,"
    "%24,%25,%26,%27,%28,%29,%30,%31,%32,%33,%34,%35,%36,%37,%38,%39,%40,%41,%42,%43,%44,%45,%46,%47,"
    "%48,%49,%50,%51,%52,%53,%54,%55,%56,%57,%58,%59,%60,%61,%62,%63,%64,%65,%66,%67,%68,%69,%70,%71,"
    "%72,%73,%74,%75,%76,%77,%78,%79,%80,%81,%82,%83,%84,%85,%86,%87,%88,%89,%90,%91,%92,%93,%94,%95}, "
    "da, db, p, 1, 1, %101, %99;\n}\n"
    : "+f"(d[0]),"+f"(d[1]),"+f"(d[2]),"+f"(d[3]),"+f"(d[4]),"+f"(d[5]),"+f"(d[6]),"+f"(d[7]),"+f"(d[8]),"+f"(d[9]),"+f"(d[10]),"+f"(d[11]),
      "+f"(d[12]),"+f"(d[13]),"+f"(d[14]),"+f"(d[15]),"+f"(d[16]),"+f"(d[17]),"+f"(d[18]),"+f"(d[19]),"+f"(d[20]),"+f"(d[21]),"+f"(d[22]),"+f"(d[23]),
      "+f"(d[24]),"+f"(d[25]),"+f"(d[26]),"+f"(d[27]),"+f"(d[28]),"+f"(d[29]),"+f"(d[30]),"+f"(d[31]),"+f"(d[32]),"+f"(d[33]),"+f"(d[34]),"+f"(d[35]),
      "+f"(d[36]),"+f"(d[37]),"+f"(d[38]),"+f"(d[39]),"+f"(d[40]),"+f"(d[41]),"+f"(d[42]),"+f"(d[43]),"+f"(d[44]),"+f"(d[45]),"+f"(d[46]),"+f"(d[47]),
      "+f"(d[48]),"+f"(d[49]),"+f"(d[50]),"+f"(d[51]),"+f"(d[52]),"+f"(d[53]),"+f"(d[54]),"+f"(d[55]),"+f"(d[56]),"+f"(d[57]),"+f"(d[58]),"+f"(d[59]),
      "+f"(d[60]),"+f"(d[61]),"+f"(d[62]),"+f"(d[63]),"+f"(d[64]),"+f"(d[65]),"+f"(d[66]),"+f"(d[67]),"+f"(d[68]),"+f"(d[69]),"+f"(d[70]),"+f"(d[71]),
      "+f"(d[72]),"+f"(d[73]),"+f"(d[74]),"+f"(d[75]),"+f"(d[76]),"+f"(d[77]),"+f"(d[78]),"+f"(d[79]),"+f"(d[80]),"+f"(d[81]),"+f"(d[82]),"+f"(d[83]),
      "+f"(d[84]),"+f"(d[85]),"+f"(d[86]),"+f"(d[87]),"+f"(d[88]),"+f"(d[89]),"+f"(d[90]),"+f"(d[91]),"+f"(d[92]),"+f"(d[93]),"+f"(d[94]),"+f"(d[95])
    : "r"(alo), "r"(blo), "r"(sd), "n"(TB), "r"(DESC_HI), "n"(TA));
}

struct Ctx {
  uint32_t sm;
  uint32_t bar;
  uint32_t rbar;
  int cl, rank, wg, warp, lane, phases;
};
__device__ __forceinline__ void release(const Ctx& c, int b, int cnt = 1) {
  if (c.lane < 2) mbar_arrive_cl(c.rbar + b * 8, cnt);
}
#define PFM 7
#define PF1 1
constexpr float SM_SCALE = 0.08838834764831845f * 1.4426950408889634f;
constexpr float SM_HI = 1.8446744e19f, SM_LO = 5.4210109e-20f;
constexpr int ORDER = 1;

__device__ __forceinline__ void stage_tile(const float (&a)[64], uint32_t buf, const Ctx& c, float s0, float s1) {
  const int row = (c.lane & 7) + ((c.lane >> 3) & 1) * 8;
  const uint32_t base = buf + (c.warp * 16 + row) * 128 + (((c.lane >> 4) ^ (row & 7)) << 4);
#pragma unroll
  for (int i = 0; i < 8; i++)
    stsm4((base ^ ((i & 3) << 5)) + (i >> 2) * 8192, pack_bf16(a[8 * i] * s0, a[8 * i + 1] * s0), pack_bf16(a[8 * i + 2] * s1, a[8 * i + 3] * s1),
          pack_bf16(a[8 * i + 4] * s0, a[8 * i + 5] * s0), pack_bf16(a[8 * i + 6] * s1, a[8 * i + 7] * s1));
}

__device__ __forceinline__ void p1_epilogue(const Params& p, const Ctx& c, const float (&acc)[64], int t, int type) {
  const int tile = p.s.r[c.cl].tile[t], b = c.wg * 2 + 1;
  mbar_wait(c.bar + (B_SE + b) * 8, (t & 1) ^ 1);
  if (type && tile >= 32) {
    const int r = 2 * (c.lane & 3) + ((c.lane >> 2) & 1);
    const uint32_t dst = c.sm + SM_BUF + b * 16384 + r * 128 + (((c.warp * 2) ^ r) << 4) + (c.lane >> 3) * 4;
#pragma unroll
    for (int i = 0; i < 16; i++) {
      asm volatile("st.shared.u32 [%0], %1;" ::"r"(dst + i * 1024), "r"(pack_bf16(acc[4 * i], acc[4 * i + 1])) : "memory");
      asm volatile("st.shared.u32 [%0], %1;" ::"r"((dst ^ 16) + i * 1024), "r"(pack_bf16(acc[4 * i + 2], acc[4 * i + 3])) : "memory");
    }
  } else {
    if (type) stage_tile(acc, c.sm + SM_BUF + b * 16384, c, SM_SCALE, SM_SCALE);
    else stage_tile(acc, c.sm + SM_BUF + b * 16384, c, 1.f, 1.f);
  }
  FENCE_ASYNC_SMEM();
  __syncwarp();
  if (c.lane == 0) mbar_arrive(c.bar + (B_SF + b) * 8);
}

__device__ __forceinline__ void p1_consumer(const Params& p, const Ctx& c) {
  const int n = p.s.r[c.cl].n1;
  const int type = p.s.r[c.cl].slab >> 3;
  const uint32_t bdesc = desc_lo(c.sm + SM_RING, 8192), adesc = desc_lo(c.sm + SM_BUF + 32768 + c.wg * 8192, 16);
  uint32_t A[128];
  float acc[64] = {};
  int slot = 0, par = 0;
  auto next = [&]() { if (++slot == 10) { slot = 0; par ^= 1; } };
  {
    const int row = (c.lane & 7) + ((c.lane >> 3) & 1) * 8;
    const uint32_t base = c.sm + SM_RING + (c.wg * 64 + c.warp * 16 + row) * 128 + (((c.lane >> 4) ^ (row & 7)) << 4);
    if (c.wg == 1) bar_sync(ORDER + 1, 256);
    int pa = -1, pb = -1;
    if (type) {
      mbar_wait(c.bar + B_P1F * 8, 0);
      WG_FENCE();
#pragma unroll
      for (int kk = 0; kk < 4; kk++) wgmma_ss128<1>(acc, adesc + kk * 2, bdesc + kk * 128, kk != 0);
      WG_COMMIT();
      pb = 0; slot = 1;
    }
#pragma unroll
    for (int kb = 0; kb < 8; kb++) {
      const int sa = slot;
      mbar_wait(c.bar + (B_P1F + slot) * 8, par);
      if (kb == 0) PROF(c.wg, 5);
      next();
      mbar_wait(c.bar + (B_P1F + slot) * 8, par);
      PROF(c.wg, 6 + 2 * kb);
      WG_FENCE();
#pragma unroll
      for (int kk = 0; kk < 4; kk++)
        wgmma_ss128<1>(acc, desc_lo(c.sm + SM_RING + c.wg * 8192, 16) + sa * 1024 + kk * 2, bdesc + slot * 1024 + kk * 128, (kb | kk) != 0 ? 1 : type);
      WG_COMMIT();
      if (kb == 1 && c.wg == 0) bar_arrive(ORDER + 1, 256);
#pragma unroll
      for (int kk = 0; kk < 4; kk++) ldsm4((base ^ (kk << 5)) + sa * 16384, A[kb * 16 + kk * 4], A[kb * 16 + kk * 4 + 1], A[kb * 16 + kk * 4 + 2], A[kb * 16 + kk * 4 + 3]);
      WG_WAIT(1);
      if (kb > 0) release(c, B_P1E + pa);
      if (kb > 0 || pb >= 0) release(c, B_P1E + pb);
      pa = sa; pb = slot;
      next();
    }
    WG_WAIT(0);
    __syncwarp();
    release(c, B_P1E + pa);
    release(c, B_P1E + pb);
    pin(acc);
    PROF(c.wg, 1);
    p1_epilogue(p, c, acc, 0, type);
    PROF(c.wg, 2);
  }
  for (int t = 1; t < n; t++) {
    bar_sync(ORDER + c.wg, 256);
    int prev1 = -1, prev2 = -1;
    if (type) {
      mbar_wait(c.bar + (B_P1F + slot) * 8, par);
      WG_FENCE();
#pragma unroll
      for (int kk = 0; kk < 4; kk++) wgmma_ss128<1>(acc, adesc + kk * 2, bdesc + slot * 1024 + kk * 128, kk != 0);
      WG_COMMIT();
      prev1 = slot;
      next();
    }
#pragma unroll
    for (int kb = 0; kb < 8; kb++) {
      mbar_wait(c.bar + (B_P1F + slot) * 8, par);
      WG_FENCE();
      const uint32_t d = bdesc + slot * 1024;
#pragma unroll
      for (int kk = 0; kk < 4; kk++)
        wgmma_rs128<1>(acc, A[kb * 16 + kk * 4], A[kb * 16 + kk * 4 + 1], A[kb * 16 + kk * 4 + 2], A[kb * 16 + kk * 4 + 3], d + kk * 128, (kb | kk) != 0 ? 1 : type);
      WG_COMMIT();
      if (kb == 7) {
        if (t + 1 < n || c.wg == 0) bar_arrive(ORDER + (c.wg ^ 1), 256);
      }
      if (kb > 0) { WG_WAIT(2); if (kb > 1 || prev2 >= 0) release(c, B_P1E + prev2); }
      prev2 = prev1; prev1 = slot;
      next();
    }
    WG_WAIT(1);
    release(c, B_P1E + prev2);
    WG_WAIT(0);
    pin(acc);
    release(c, B_P1E + prev1);
    p1_epilogue(p, c, acc, t, type);
    PROF(c.wg, 3);
  }
}

__device__ __forceinline__ void p1_producer(const Params& p, const Ctx& c) {
  const int n = p.s.r[c.cl].n1;
  const int type = p.s.r[c.cl].slab >> 3, grp = p.s.r[c.cl].slab & 7;
  int slot = 2 - type, par = 1;
#pragma unroll 1
  for (int t = 0; t < n; t++) {
    const int tile = p.s.r[c.cl].tile[t];
    const CUtensorMap* m = &p.map_w[type * 2 + (tile >> 5)];
    const int n0 = (tile & 31) * 128 + c.rank * 64;
    const int ptile = p.s.r[c.cl].tile[t + PF1 < n ? t + PF1 : t];
    const CUtensorMap* pm = &p.map_w[type * 2 + (ptile >> 5)];
#pragma unroll 1
    for (int kb = (t == 0) - type; kb < 8; kb++) {
      if (t == 0) {
        mbar_wait(c.bar + (B_P1E + slot) * 8, par);
        mbar_expect(c.bar + (B_P1F + slot) * 8, 16384);
        tma2d(c.sm + SM_RING + slot * 16384, &p.map_a[type], kb * 64, grp * 256 + c.rank * 128, c.bar + (B_P1F + slot) * 8);
        if (++slot == 10) { slot = 0; par ^= 1; }
      }
      mbar_wait(c.bar + (B_P1E + slot) * 8, par);
      mbar_expect(c.bar + (B_P1F + slot) * 8, 16384);
      tma2d_mc(c.sm + SM_RING + slot * 16384 + c.rank * 8192, m, n0, kb < 0 ? 512 : kb * 64, c.bar + (B_P1F + slot) * 8);
      if (t == 0 && kb == 1) PROF(2, 61);
      if (t == 0 && kb == 3) PROF(2, 62);
      if (t + PF1 < n && t > 0 && ((kb ^ grp) & PFM) == 0) tma2d_prefetch(pm, (ptile & 31) * 128 + c.rank * 64, kb < 0 ? 512 : kb * 64);
      if (++slot == 10) { slot = 0; par ^= 1; }
    }
  }
}

__device__ __forceinline__ void p1_storer(const Params& p, const Ctx& c) {
  const int n = p.s.r[c.cl].n1;
  const int type = p.s.r[c.cl].slab >> 3, grp = p.s.r[c.cl].slab & 7;
  for (int i = 0; i < 2 * n; i++) {
    const int t = i >> 1, w = i & 1, b = w * 2 + 1;
    const int tile = p.s.r[c.cl].tile[t];
    mbar_wait(c.bar + (B_SF + b) * 8, t & 1);
    const uint32_t src = c.sm + SM_BUF + b * 16384;
    int f = (type ? F_Q : F_KV) + (tile & 31) * 8 + grp;
    if (type == 0) {
      const int prev = p.s.prev[tile & 31][grp];
      if (prev != 255 && w == 0) {
        if (grp >= 2) flag_wait<false>(F_RD + prev * 8 + grp, 8 - grp);
        else flag_wait<false>(F_CTX + max(c.lane & 7, grp) * 64 + prev, 4);
      }
      uint8_t* dst = g_KV + (size_t)(((tile & 32) + p.s.slot[tile & 31][grp]) * 16 + grp * 2 + c.rank) * 32768 + w * 8192;
      bulk_store(dst, src, 8192);
      bulk_store(dst + 16384, src + 8192, 8192);
    } else if (tile < 32) {
      bulk_store(g_Q + (size_t)(tile * 32 + grp * 4 + c.rank * 2 + w) * 16384, src, 16384);
    } else {
      tma3d_store(&p.map_t[2], src, 8 + (grp * 4 + c.rank * 2 + w) * 32, 0, (tile - 32) * 64);
      f = F_QKVA + grp * 4 + ((0xE4390900u >> (2 * (tile - 30))) & 3);
    }
    BULK_COMMIT();
    BULK_WAIT(0);
    mbar_arrive_one(c.bar + (B_SE + b) * 8);
    flag_add_rx(f);
  }
}

__device__ __forceinline__ int p2_buf(int w, int i) { return w * 2 + (i & 1); }
__device__ __forceinline__ int p2_blk(int rank, int w, int i) { return ((i ^ w) & 1) == 0 ? 3 - rank : rank; }

template <int N>
__device__ __forceinline__ void row_max(const float (&s)[N], float& m0, float& m1) {
  float a0 = fmaxf(s[0], s[1]), a1 = fmaxf(s[2], s[3]);
#pragma unroll
  for (int i = 1; i < N / 4; i++) {
    m0 = fmaxf(m0, s[4 * i]); a0 = fmaxf(a0, s[4 * i + 1]);
    m1 = fmaxf(m1, s[4 * i + 2]); a1 = fmaxf(a1, s[4 * i + 3]);
  }
  m0 = fmaxf(m0, a0); m1 = fmaxf(m1, a1);
  m0 = fmaxf(m0, __shfl_xor_sync(0xffffffffu, m0, 1));
  m1 = fmaxf(m1, __shfl_xor_sync(0xffffffffu, m1, 1));
  m0 = fmaxf(m0, __shfl_xor_sync(0xffffffffu, m0, 2));
  m1 = fmaxf(m1, __shfl_xor_sync(0xffffffffu, m1, 2));
}
template <bool SUB, int N>
__device__ __forceinline__ void row_exp(const float (&s)[N], uint32_t (&P)[32], float m0, float m1, float& t0, float& t1) {
  float u0 = 0.f, u1 = 0.f;
  t0 = t1 = 0.f;
#pragma unroll
  for (int i = 0; i < N / 4; i++) {
    const float e0 = ex2(SUB ? s[4 * i] - m0 : s[4 * i]), e1 = ex2(SUB ? s[4 * i + 1] - m0 : s[4 * i + 1]);
    const float e2 = ex2(SUB ? s[4 * i + 2] - m1 : s[4 * i + 2]), e3 = ex2(SUB ? s[4 * i + 3] - m1 : s[4 * i + 3]);
    if (i == 0) { t0 = e0; u0 = e1; t1 = e2; u1 = e3; }
    else { t0 += e0; u0 += e1; t1 += e2; u1 += e3; }
    P[2 * i] = pack_bf16(e0, e1);
    P[2 * i + 1] = pack_bf16(e2, e3);
  }
#pragma unroll
  for (int i = N / 2; i < 32; i++) P[i] = 0;
  pin(P);
  t0 += u0; t1 += u1;
}
template <int N>
__device__ __forceinline__ void causal_mask(float (&s)[N], int thr) {
#pragma unroll
  for (int i = 0; i < 8; i++) {
    if (8 * i > thr) s[N - 32 + 4 * i] = -INFINITY;
    if (8 * i + 1 > thr) s[N - 32 + 4 * i + 1] = -INFINITY;
    if (8 * i - 8 > thr) s[N - 32 + 4 * i + 2] = -INFINITY;
    if (8 * i - 7 > thr) s[N - 32 + 4 * i + 3] = -INFINITY;
  }
}
__device__ __forceinline__ void issue_qk(float (&s)[32], uint32_t qd, uint32_t kd) {
  WG_FENCE();
#pragma unroll
  for (int kk = 0; kk < 8; kk++) wgmma_ss64<0>(s, qd + (kk >> 2) * 512 + (kk & 3) * 2, kd + (kk >> 2) * 1024 + (kk & 3) * 2, kk != 0);
  WG_COMMIT();
}
__device__ __forceinline__ void issue_qk(float (&s)[64], uint32_t qd, uint32_t kd) {
  WG_FENCE();
#pragma unroll
  for (int kk = 0; kk < 8; kk++) wgmma_ss128<0>(s, qd + (kk >> 2) * 512 + (kk & 3) * 2, kd + (kk >> 2) * 1024 + (kk & 3) * 2, kk != 0);
  WG_COMMIT();
}
template <int NK>
__device__ __forceinline__ void issue_pv(float (&o)[64], const uint32_t (&P)[32], uint32_t vd, int acc) {
  WG_FENCE();
#pragma unroll
  for (int kk = 0; kk < NK; kk++) wgmma_rs128<1>(o, P[4 * kk], P[4 * kk + 1], P[4 * kk + 2], P[4 * kk + 3], vd + kk * 128, kk != 0 ? 1 : acc);
  WG_COMMIT();
}
__device__ __forceinline__ void stage_done(const Ctx& c, int b) {
  FENCE_ASYNC_SMEM();
  __syncwarp();
  if (c.lane == 0) mbar_arrive(c.bar + (B_SF + b) * 8);
}
__device__ __forceinline__ void p2_epilogue(const float (&o)[64], float s0, float s1, const Ctx& c, int b) {
  stage_tile(o, c.sm + SM_BUF + b * 16384, c, s0, s1);
  stage_done(c, b);
}

struct P2State {
  float m0, m1, l0, l1;
  bool shift;
  float e0, e1;
  float g0, g1;
  int ks;
  int wi, ai;
  uint32_t wb, ab;
  uint32_t qd;
};
#define PROFZ()
__device__ __forceinline__ int wrap5(int q) { return q >= 5 ? q - 5 : q; }
__device__ __forceinline__ void turn_wait(uint32_t ring, int i) { mbar_wait(ring + (i & 3) * 8, (i >> 2) & 1); }
__device__ __forceinline__ void turn_pass(const Ctx& c, uint32_t ring, int i) { if (c.lane == 0) mbar_arrive(ring + (i & 3) * 8); }
__device__ __forceinline__ void p2_gate(P2State& z, const Ctx& c, int row0) {
  const float* g = g_gate + row0 + c.warp * 16 + (c.lane >> 2);
  asm volatile("ld.global.cg.f32 %0, [%2];\nld.global.cg.f32 %1, [%2+32];" : "=f"(z.g0), "=f"(z.g1) : "l"(g) : "memory");
}
__device__ __forceinline__ void p2_scales(P2State& z) {
  float l0 = z.l0, l1 = z.l1;
  l0 += __shfl_xor_sync(0xffffffffu, l0, 1);
  l1 += __shfl_xor_sync(0xffffffffu, l1, 1);
  l0 += __shfl_xor_sync(0xffffffffu, l0, 2);
  l1 += __shfl_xor_sync(0xffffffffu, l1, 2);
  z.e0 = __fdividef(1.f - z.g0, l0); z.e1 = __fdividef(1.f - z.g1, l1);
}
template <int N>
__device__ __forceinline__ void p2_first(const Ctx& c, P2State& z, float (&o)[64], uint32_t (&Pc)[32], uint32_t (&Pn)[32],
                                         int ks, int vs, int cnt, int acc, int row0) {
  float s[N] = {};
  issue_qk(s, z.qd, desc_lo(c.sm + SM_RING, 16) + ks * 2048);
  if (vs >= 0) {
    p2_scales(z);
    issue_pv<8>(o, Pc, desc_lo(c.sm + SM_RING, 16384) + vs * 2048, acc);
  } else {
    WG_COMMIT();
  }
  mbar_expect(z.ab + (z.ai++ & 3) * 8, cnt == 1 ? 8192 : 0);
  PROFZ();
  WG_WAIT(1);
  PROFZ();
  pin(s);
  release(c, B_P2E + ks, cnt);
  p2_gate(z, c, row0);
  causal_mask(s, c.warp * 16 + (c.lane >> 2) - 2 * (c.lane & 3));
  z.m0 = z.m1 = 0.f;
  row_exp<false>(s, Pn, 0.f, 0.f, z.l0, z.l1);
  z.shift = __any_sync(0xffffffffu, !(z.l0 + z.l1 <= SM_HI) || ((c.lane & 3) == 0 && !(fminf(z.l0, z.l1) >= SM_LO)));
  if (__builtin_expect(z.shift, 0)) {
    z.m0 = z.m1 = -INFINITY;
    row_max(s, z.m0, z.m1);
    row_exp<true>(s, Pn, z.m0, z.m1, z.l0, z.l1);
  }
  WG_WAIT(0);
  pin(o);
  if (vs >= 0) release(c, B_P2E + vs, 1);
}

template <bool SECOND>
__device__ __forceinline__ void p2_turn(const Ctx& c, P2State& z, float (&o)[64], uint32_t (&Pc)[32], uint32_t (&Pn)[32],
                                        int eb = -1, bool half = false, int vcnt = 1) {
  float s[64] = {};
  const int ks = z.ks, vs = wrap5(ks + 1);
  PROFZ();
  turn_wait(z.wb, z.wi++);
  PROFZ();
  issue_qk(s, z.qd, desc_lo(c.sm + SM_RING, 16) + ks * 2048);
  const uint32_t vd = desc_lo(c.sm + SM_RING, 16384) + vs * 2048;
  if (SECOND) {
    if (eb >= 0) stage_tile(o, c.sm + SM_BUF + eb * 16384, c, z.e0, z.e1);
    if (half) issue_pv<4>(o, Pc, vd, 0); else issue_pv<8>(o, Pc, vd, 0);
  } else {
    issue_pv<8>(o, Pc, vd, 1);
  }
  turn_pass(c, z.ab, z.ai++);
  if (SECOND) { if (eb >= 0) stage_done(c, eb); }
  PROFZ();
  z.ks = wrap5(ks + 2);
  WG_WAIT(1);
  PROFZ();
  pin(s);
  release(c, B_P2E + ks, 1);
  float t0, t1, a0 = 1.f, a1 = 1.f;
  row_exp<false>(s, Pn, 0.f, 0.f, t0, t1);
  z.shift = __any_sync(0xffffffffu, z.shift || !(t0 + t1 <= SM_HI));
  const bool redo = z.shift;
  if (__builtin_expect(redo, 0)) {
    float n0 = z.m0, n1 = z.m1;
    row_max(s, n0, n1);
    a0 = ex2(z.m0 - n0); a1 = ex2(z.m1 - n1);
    z.m0 = n0; z.m1 = n1;
    z.l0 *= a0; z.l1 *= a1;
    row_exp<true>(s, Pn, z.m0, z.m1, t0, t1);
  }
  WG_WAIT(0);
  pin(o);
  release(c, B_P2E + vs, vcnt);
  if (__builtin_expect(redo, 0)) {
#pragma unroll
    for (int i = 0; i < 16; i++) { o[4 * i] *= a0; o[4 * i + 1] *= a0; o[4 * i + 2] *= a1; o[4 * i + 3] *= a1; }
  }
  z.l0 += t0; z.l1 += t1;
}
__device__ __forceinline__ void copy_p(uint32_t (&d)[32], const uint32_t (&s)[32], int zero) {
#pragma unroll
  for (int i = 0; i < 32; i++) asm volatile("add.s32 %0, %1, %2;" : "=r"(d[i]) : "r"(s[i]), "r"(zero));
}

__device__ __forceinline__ void p2_consumer(const Params& p, const Ctx& c, int rot) {
  const int nit = p.s.r[c.cl].n2;
  const uint32_t fring = c.bar + B_P2F * 8, oring = c.bar + B_ORD * 8;
  float o[64] = {};
  uint32_t Pa[32] = {}, Pb[32] = {};
  P2State z;
  z.e0 = z.e1 = z.l0 = z.l1 = z.g0 = z.g1 = 0.f; z.ks = rot; z.shift = false;
  int acc = 0, n = 0;
  for (int it = 0; it < nit; it++) {
    const int j = p.s.r[c.cl].item[it] & 7, blk = p2_blk(c.rank, c.wg, it), row0 = (j * 4 + blk) * 64;
    const int lng = ((it ^ c.wg) & 1) ^ 1;
    z.qd = desc_lo(c.sm + SM_BUF, 16) + p2_buf(c.wg, it) * 1024;
    if (lng) { z.wb = oring; z.wi = n - it; z.ab = fring; z.ai = n + 1; }
    else { z.wb = fring; z.wi = n + 2; z.ab = oring; z.ai = n - it; }
    PROFZ();
    mbar_wait(c.bar + (B_QF + p2_buf(c.wg, it)) * 8, (it >> 1) & 1);
    turn_wait(fring, n + 1 - lng);
    PROFZ();
    const int vs = it ? wrap5(z.ks + 1) : -1, ks = lng ? z.ks : wrap5(z.ks + (it ? 2 : 1));
    if (blk & 1) p2_first<64>(c, z, o, Pa, Pb, ks, vs, 1 + lng, acc, row0);
    else p2_first<32>(c, z, o, Pa, Pb, ks, vs, 1 + lng, acc, row0);
    z.ks = wrap5(ks + (it == 0 && lng ? 1 : 2));
    PROF(c.wg, 24 + it);
    n += 2 * j + 2;
    int left = 2 * j + lng;
    acc = left != 0;
    if (left == 0) { copy_p(Pa, Pb, p.zero); continue; }
    p2_turn<true>(c, z, o, Pb, Pa, it > 0 ? p2_buf(c.wg, it - 1) : -1, !(blk & 1), 1 + lng);
    while (--left > 0) {
      p2_turn<false>(c, z, o, Pa, Pb);
      if (--left == 0) { copy_p(Pa, Pb, p.zero); break; }
      p2_turn<false>(c, z, o, Pb, Pa);
    }
  }
  {
    if (!acc && nit > 1) p2_epilogue(o, z.e0, z.e1, c, p2_buf(c.wg, nit));
    turn_wait(z.wb, z.wi);
    issue_pv<8>(o, Pa, desc_lo(c.sm + SM_RING, 16384) + z.ks * 2048, acc);
    if (((nit - 1) ^ c.wg) & 1) turn_pass(c, z.ab, z.ai);
    p2_scales(z);
    WG_WAIT(0);
    pin(o);
    release(c, B_P2E + z.ks);
    p2_epilogue(o, z.e0, z.e1, c, p2_buf(c.wg, nit - 1));
    PROF(c.wg, 24 + nit);
  }
}

__device__ __forceinline__ void p2_load_q(const Params& p, const Ctx& c, int it, int w) {
  const int item = p.s.r[c.cl].item[it], h = item >> 3, j = item & 7, b = p2_buf(w, it);
  mbar_expect(c.bar + (B_QF + b) * 8, 16384);
  bulk_load(c.sm + SM_BUF + b * 16384, g_Q + (size_t)(h * 32 + j * 4 + p2_blk(c.rank, w, it)) * 16384, 16384, c.bar + (B_QF + b) * 8, POL(4));
}
__device__ __forceinline__ void wait_p1_free(const Ctx& c, int u1, int s) {
  mbar_wait(c.bar + (B_P1E + 2 * s) * 8, ((u1 - 1 - 2 * s) / 10) & 1);
  mbar_wait(c.bar + (B_P1E + 2 * s + 1) * 8, ((u1 - 2 - 2 * s) / 10) & 1);
}
__device__ __forceinline__ void p2_producer(const Params& p, const Ctx& c, int u1, int rot) {
  const int nit = p.s.r[c.cl].n2;
  int slot = rot, cnt = 0, par = 1, n = 0;
  const uint8_t* pv = nullptr;
  bool pl = false;
  auto load = [&](const uint8_t* src, int expect, uint32_t fb, bool last) {
    if (cnt < 5) {
      if (u1) {
        wait_p1_free(c, u1, slot);
        if (cnt == 0) p2_load_q(p, c, 0, 1);
      }
      cnt++;
    } else {
      if (slot == rot) par ^= 1;
      mbar_wait(c.bar + (B_P2E + slot) * 8, par);
    }
    if (expect) mbar_expect(fb, expect);
    bulk_load_mc(c.sm + SM_RING + slot * 32768 + c.rank * 16384, src, 16384, fb, last ? POL(5) : L2_NORMAL);
    slot = wrap5(slot + 1);
  };
  if (c.phases & 16) flag_wait<true>(F_GATE, 256);
  for (int it = 0; it < nit; it++) {
    const int item = p.s.r[c.cl].item[it], h = item >> 3, j = item & 7;
    uint32_t ready = (c.phases & 16) ? 0u : 255u;
    if (it == 0) { if (c.phases & 16) flag_wait<false>(F_Q + item, 4); mbar_wait(c.bar + B_LAD * 8, 0); p2_load_q(p, c, 0, 0); if (!u1) p2_load_q(p, c, 0, 1); }
    for (int t = 2 * j + 1; t >= 0; t--) {
      for (int n1 = 0; !((ready >> (t >> 1)) & 1); n1++) {
        int v;
        if (n1) { __nanosleep(32); if (n1 > 20000000) __trap(); }
        asm volatile("ld.relaxed.gpu.global.s32 %0, [%1];" : "=r"(v) : "l"(g_flags + F_KV + h * 8 + (c.lane & 7)) : "memory");
        ready = __ballot_sync(0xffffffffu, v >= 8);
      }
      const uint8_t* k = g_KV + (size_t)(p.s.slot[h][t >> 1] * 16 + t) * 32768 + c.rank * 16384;
      const uint32_t fb = c.bar + (B_P2F + (n & 3)) * 8;
      const bool last = (p.s.r[c.cl].last[it] >> (t >> 1)) & 1;
      load(k, pv && t != 2 * j ? 65536 : 32768, fb, last);
      if (!(t & 1) && t + 4 <= 2 * j && c.rank == 0) flag_add_rx(F_RD + h * 8 + (t >> 1) + 2);
      if (pv) load(pv, 0, t != 2 * j ? fb : c.bar + (B_ORD + ((n - 1 - it) & 3)) * 8, pl);
      pl = last;
      pv = k + (size_t)NH * 16 * 32768;
      n++;
    }
  }
  load(pv, 32768, c.bar + (B_P2F + (n & 3)) * 8, pl);
}

__device__ __forceinline__ void p2_storer(const Params& p, const Ctx& c, int sfpar) {
  const int nit = p.s.r[c.cl].n2;
  auto load_q = [&](int it, int w) {
    if (c.phases & 16) flag_wait<false>(F_Q + p.s.r[c.cl].item[it], 4);
    p2_load_q(p, c, it, w);
  };
  if (nit > 1) {
    load_q(1, 1); p2_load_q(p, c, 1, 0); }
  for (int i = 0; i < 2 * nit; i++) {
    const int it = i >> 1, w = (it ^ i ^ 1) & 1, b = p2_buf(w, it);
    const int item = p.s.r[c.cl].item[it], h = item >> 3, j = item & 7;
    mbar_wait(c.bar + (B_SF + b) * 8, (sfpar >> b) & 1);
    sfpar ^= 1 << b;
    bulk_store(g_Q + (size_t)(h * 32 + j * 4 + p2_blk(c.rank, w, it)) * 16384, c.sm + SM_BUF + b * 16384, 16384, POL(1));
    BULK_COMMIT();
    BULK_WAIT(0);
    flag_add_rx(F_CTX + j * 64 + h);
    if ((i & 1) && it + 2 < nit) { load_q(it + 2, w); p2_load_q(p, c, it + 2, w ^ 1); }
  }
  release(c, B_DONE);
}

__device__ __forceinline__ int p3_pos(int i, int x) { return i < 4 ? (i + x) & 3 : 4; }
__device__ __forceinline__ void p3_consumer(const Params& p, const Ctx& c, int x) {
  const bool first = p.s.r[c.cl].p3 >= 24;
  const int tile = p.s.r[c.cl].p3 - (first ? 24 : 0), j = tile / 3, nt = tile - 3 * j;
  const int na = first ? 9 : 0, nb = first ? 2 * p.s.nh[tile] : 64 - 2 * p.s.nh[tile];
  const uint32_t ad = desc_lo(c.sm + SM_RING + c.wg * 8192, 16), bd = desc_lo(c.sm + SM_RING + 16384, 4096);
  float acc[96] = {};
  int slot = 0, par = 0, prev = 0;
#pragma unroll 1
  for (int kb = 0; kb < na; kb++) {
    mbar_wait(c.bar + (B_P3F + slot) * 8, par);
    if (kb == 0) PROF(c.wg, 39);
    WG_FENCE();
#pragma unroll
    for (int kk = 0; kk < 4; kk++) wgmma_ss192<1, 1>(acc, ad + p3_pos(slot, x) * 2560 + kk * 128, bd + p3_pos(slot, x) * 2560 + (kk >> 1) * 768 + (kk & 1) * 128, kk != 0 ? 1 : kb != 0);
    WG_COMMIT();
    WG_WAIT(1);
    if (kb > 0) release(c, B_P3E + prev);
    prev = slot;
    if (++slot == 5) { slot = 0; par ^= 1; }
  }
#pragma unroll 1
  for (int kb = na; kb < na + nb; kb++) {
    mbar_wait(c.bar + (B_P3F + slot) * 8, par);
    if (kb == 0) PROF(c.wg, 39);
    WG_FENCE();
#pragma unroll
    for (int kk = 0; kk < 4; kk++) wgmma_ss192<1>(acc, ad + p3_pos(slot, x) * 2560 + kk * 2, bd + p3_pos(slot, x) * 2560 + (kk >> 1) * 768 + (kk & 1) * 128, kk != 0 ? 1 : kb != 0);
    WG_COMMIT();
    WG_WAIT(1);
    if (kb > 0) release(c, B_P3E + prev);
    prev = slot;
    if (++slot == 5) { slot = 0; par ^= 1; }
  }
  WG_WAIT(0);
  pin(acc);
  PROF(c.wg, 40);
  if (first) bar_sync(4 + c.wg, 128);
  mbar_wait(c.bar + B_OUT * 8, 0);
  const int row = (c.lane & 7) + ((c.lane >> 3) & 1) * 8;
  const uint32_t wbase = c.sm + SM_RING + c.wg * 8192 + c.warp * 2048;
  const uint32_t base = wbase + row * 128 + (((c.lane >> 4) ^ (row & 7)) << 4);
#pragma unroll
  for (int i = 0; i < 12; i++) {
    stsm4((base ^ ((i & 3) << 5)) + (i >> 2) * 40960, pack_bf16(acc[8 * i], acc[8 * i + 1]), pack_bf16(acc[8 * i + 2], acc[8 * i + 3]),
          pack_bf16(acc[8 * i + 4], acc[8 * i + 5]), pack_bf16(acc[8 * i + 6], acc[8 * i + 7]));
    if ((i & 3) == 3) {
      FENCE_ASYNC_SMEM();
      __syncwarp();
      const int c0 = nt * 192 + (i >> 2) * 64, c1 = j * 256 + c.rank * 128 + c.wg * 64 + c.warp * 16;
      tma2d_add(&p.map_out, wbase + (i >> 2) * 40960, c0, c1);
    }
  }
  BULK_COMMIT();
  PROF(c.wg, 43);
  BULK_WAIT_READ(0);
  PROF(c.wg, 44);
}

__device__ __forceinline__ void p3_producer(const Params& p, const Ctx& c, int u1, int u2, int rot, int x) {
  const bool first = p.s.r[c.cl].p3 >= 24;
  const int tile = p.s.r[c.cl].p3 - (first ? 24 : 0), j = tile / 3, nt = tile - 3 * j;
  int slot = 0, par = 1, cnt = 0;
  auto wait_free = [&](int s) {
    const int f = wrap5(s + 5 - rot);
    if (f < u2) mbar_wait(c.bar + (B_P2E + s) * 8, ((u2 - 1 - f) / 5) & 1);
    else if (u1) wait_p1_free(c, u1, s);
  };
  asm volatile(ELECT("prefetch.tensormap [%0];") ::"l"(&p.map_o[first]) : "memory");
  asm volatile(ELECT("prefetch.tensormap [%0];") ::"l"(&p.map_out) : "memory");
  const int q1 = first ? p.s.nh[tile] : 32;
  for (int q = first ? -1 : p.s.nh[tile]; q < q1; q++) {
    const int g = q < 0 ? 32 : p.s.p3_order[j][q];
    if (c.phases & 16) flag_wait<false>(F_CTX + j * 64 + g, q < 0 ? 16 : 4);
    const int nk = q < 0 ? 9 : 2, k0 = (q < 0 ? 0 : g * 128) + c.rank * 32;
    const uint8_t* a = q < 0 ? g_oA + (j * 4 + c.rank * 2) * 73728 : g_Q + (size_t)(g * 32 + j * 4 + c.rank * 2) * 16384;
    const CUtensorMap* m = &p.map_o[q < 0];
    for (int i = 0; i < nk; i++) {
      const uint32_t st = c.sm + SM_RING + p3_pos(slot, x) * 40960, fb = c.bar + (B_P3F + slot) * 8;
      if (cnt < 4) { wait_free(p3_pos(cnt, x)); wait_free(p3_pos(cnt, x) + 1); }
      else if (cnt == 4) mbar_wait(c.bar + B_DONE * 8, 0);
      else mbar_wait(c.bar + (B_P3E + slot) * 8, par);
      cnt++;
      mbar_expect(fb, 40960);
      bulk_load(st, a + i * 8192, 8192, fb, POL(3));
      bulk_load(st + 8192, a + (nk + i) * 8192, 8192, fb, POL(3));
      tma3d_mc(st + 16384 + c.rank * 12288, m, 0, k0 + i * 64, nt * 3, fb);
      if (++slot == 5) { slot = 0; par ^= 1; }
    }
  }
}

__device__ __forceinline__ float bf_lo(uint32_t w) { return __uint_as_float(w << 16); }
__device__ __forceinline__ float bf_hi(uint32_t w) { return __uint_as_float(w & 0xffff0000u); }

__device__ __forceinline__ void gate_rows(const Params& p, int row0, int lane) {
  const uint4* x = reinterpret_cast<const uint4*>(p.x + (size_t)(row0 + (lane >> 2)) * DM) + (lane & 3);
  const uint4* w = reinterpret_cast<const uint4*>(p.gate_w) + (lane & 3);
  float a = 0.f;
#pragma unroll 1
  for (int b = 0; b < 3; b++) {
    uint4 u[6];
#pragma unroll
    for (int i = 0; i < 6; i++) u[i] = __ldg(x + (b * 6 + i) * 4);
#pragma unroll
    for (int i = 0; i < 6; i++) {
      const uint4 v = __ldg(w + (b * 6 + i) * 4);
      a = fmaf(bf_lo(u[i].x), bf_lo(v.x), a); a = fmaf(bf_hi(u[i].x), bf_hi(v.x), a);
      a = fmaf(bf_lo(u[i].y), bf_lo(v.y), a); a = fmaf(bf_hi(u[i].y), bf_hi(v.y), a);
      a = fmaf(bf_lo(u[i].z), bf_lo(v.z), a); a = fmaf(bf_hi(u[i].z), bf_hi(v.z), a);
      a = fmaf(bf_lo(u[i].w), bf_lo(v.w), a); a = fmaf(bf_hi(u[i].w), bf_hi(v.w), a);
    }
  }
  a += __shfl_xor_sync(0xffffffffu, a, 1);
  a += __shfl_xor_sync(0xffffffffu, a, 2);
  if ((lane & 3) == 0) g_gate[row0 + (lane >> 2)] = 1.f / (1.f + __expf(-a));
}

__device__ __forceinline__ void lds10(uint32_t (&k)[10], uint32_t a) {
  asm volatile("ld.shared.v2.u32 {%0, %1}, [%10];\nld.shared.v2.u32 {%2, %3}, [%10+8];\nld.shared.v2.u32 {%4, %5}, [%10+16];\n"
               "ld.shared.v2.u32 {%6, %7}, [%10+24];\nld.shared.v2.u32 {%8, %9}, [%10+32];"
               : "=r"(k[0]), "=r"(k[1]), "=r"(k[2]), "=r"(k[3]), "=r"(k[4]), "=r"(k[5]), "=r"(k[6]), "=r"(k[7]), "=r"(k[8]), "=r"(k[9]) : "r"(a));
}
__device__ __forceinline__ void local_attn(const Params& p, const Ctx& c, int rb, int hs) {
  const int lane = c.lane, grp = rb >> 2, par = lane >> 4, i0 = 2 * (lane & 15);
  const uint32_t buf = c.sm + SM_BUF + (c.warp - 2) * 8192, bqk = c.bar + (B_LA + (c.warp - 2) * 2) * 8, bv = bqk + 8;
  const uint32_t mine = buf + 2304 + par * 160 + i0 * 4;
  const bool flags = c.phases & 16;
  auto fetch_qk = [&](int i) {
    if (flags && !(i & 1)) {
      const int q = i >> 1;
      const int tgt = q == 0 ? 24 : q == 3 ? 8 : 12;
      flag_wait<false>(F_QKVA + (grp - (grp > 0 && (rb & 3) == 0 ? par : 0)) * 4 + q, tgt);
    }
    mbar_expect(bqk, 5184);
    tma3d(buf, &p.map_t[0], rb * 32 + 8, 0, 9 * (4 * i + hs), bqk, POL(2));
    tma3d(buf + 2304, &p.map_t[1], rb * 32, 0, 288 + 9 * (4 * i + hs), bqk, POL(2));
  };
  auto fetch_v = [&](int i) { mbar_expect(bv, 2880); tma3d(buf + 5248, &p.map_t[1], rb * 32, 0, 576 + 9 * (4 * i + hs), bv, POL(2)); };
  fetch_qk(0);
  if (flags) flag_wait<true>(F_GATE, 256);
#pragma unroll 1
  for (int q = 0; q < 8; q++) {
    fetch_v(q);
    float a[8], b[8];
#pragma unroll
    for (int w = 0; w < 8; w++) a[w] = b[w] = 0.f;
    mbar_wait(bqk, q & 1);
    PROFB(1 + 2 * q);
#pragma unroll 1
    for (int j = 0; j < 9; j++) {
      uint32_t x, y, k[10];
      asm volatile("ld.shared.v2.u32 {%0, %1}, [%2];" : "=r"(x), "=r"(y) : "r"(buf + lane * 8 + j * 256));
      lds10(k, mine + j * 320);
      const float xl = bf_lo(x), xh = bf_hi(x), yl = bf_lo(y), yh = bf_hi(y);
#pragma unroll
      for (int m = 1; m < 10; m++) {
        const float kl = bf_lo(k[m]), kh = bf_hi(k[m]);
        if (m < 9) a[8 - m] = fmaf(xl, kl, fmaf(xh, kh, a[8 - m]));
        if (m > 1) b[9 - m] = fmaf(yl, kl, fmaf(yh, kh, b[9 - m]));
      }
    }
    __syncwarp();
    if (q < 7) fetch_qk(q + 1);
    constexpr float SC = 0.23570226039551584f * 1.4426950408889634f;
    const float* gp = g_gate + rb * 64 + 2 * i0 + par;
    const float ga = __ldcg(gp), gb = __ldcg(gp + 2);
    float ma = a[0], mb = b[0];
#pragma unroll
    for (int w = 1; w < 8; w++) {
      if (rb == 0) {
        if (i0 < w) a[w] = -INFINITY;
        if (i0 + 1 < w) b[w] = -INFINITY;
      }
      ma = fmaxf(ma, a[w]); mb = fmaxf(mb, b[w]);
    }
    float la = 0.f, lb = 0.f;
#pragma unroll
    for (int w = 0; w < 8; w++) {
      a[w] = ex2((a[w] - ma) * SC); b[w] = ex2((b[w] - mb) * SC);
      la += a[w]; lb += b[w];
    }
    la = __fdividef(ga, la); lb = __fdividef(gb, lb);
#pragma unroll
    for (int w = 0; w < 8; w++) { a[w] *= la; b[w] *= lb; }
    uint8_t* dst = g_oA + rb * 73728 + ((i0 & 2) + par) * 4;
    mbar_wait(bv, q & 1);
#pragma unroll 1
    for (int j = 0; j < 9; j++) {
      uint32_t v[10];
      lds10(v, mine + 2944 + j * 320);
      float a0 = 0.f, a1 = 0.f, b0 = 0.f, b1 = 0.f;
#pragma unroll
      for (int m = 1; m < 10; m++) {
        const float vl = bf_lo(v[m]), vh = bf_hi(v[m]);
        if (m < 9) { a0 = fmaf(a[8 - m], vl, a0); a1 = fmaf(a[8 - m], vh, a1); }
        if (m > 1) { b0 = fmaf(b[9 - m], vl, b0); b1 = fmaf(b[9 - m], vh, b1); }
      }
      const uint32_t wa = pack_bf16(a0, a1), wb = pack_bf16(b0, b1);
      const uint32_t got = __shfl_xor_sync(0xffffffffu, par ? wa : wb, 16);
      const uint32_t r0 = par ? got : wa, r1 = par ? wb : got;
      const int col = 18 * (4 * q + hs) + 2 * j, o = col * 128 + ((((i0 >> 2) ^ col) & 7) << 4);
      *reinterpret_cast<uint32_t*>(dst + o) = __byte_perm(r0, r1, 0x5410);
      *reinterpret_cast<uint32_t*>(dst + ((o + 128) ^ 16)) = __byte_perm(r0, r1, 0x7632);
    }
    __syncwarp();
    PROFB(2 + 2 * q);
  }
  mbar_arrive_one(c.bar + B_LAD * 8);
  flag_add(F_CTX + grp * 64 + 32);
}

__global__ void __cluster_dims__(2, 1, 1) __launch_bounds__(384, 1) fused_kernel(const __grid_constant__ Params p) {
  extern __shared__ uint8_t smem_raw[];
  Ctx c;
  c.sm = ((uint32_t)__cvta_generic_to_shared(smem_raw) + 1023u) & ~1023u;
  c.bar = c.sm + SM_BAR;
  c.lane = threadIdx.x & 31;
  const int wid = __shfl_sync(0xffffffffu, threadIdx.x >> 5, 0);
  if (wid < 6) asm volatile("prefetch.tensormap [%0];" ::"l"(&p.map_a[0] + wid) : "memory");
  c.wg = wid >> 2;
  c.warp = wid & 3;
  PROF(c.wg, 0);
  PROFG(61);
  c.cl = (blockIdx.x + (wid >> 4)) >> 1;
  c.rank = blockIdx.x & 1;
  c.rbar = mapa(c.bar, c.lane & 1);
  {
    const int w = wid, cnt = (((int)(B_CNT >> (4 * w)) - 1) & 15) + 1;
    if (w < 11) {
#pragma unroll
      for (int i = 0; i < 8; i++) asm volatile("mbarrier.init.shared::cta.b64 [%0], %1;" ::"r"(c.bar + w * 64 + i * 8), "r"(cnt));
    }
    asm volatile("fence.mbarrier_init.release.cluster;" ::: "memory");
  }
  if (c.wg == 2) PROF(2, 56);
  asm volatile("barrier.cluster.arrive.relaxed;" ::: "memory");
  c.phases = p.s.r[c.cl].phases;
  const bool do1 = p.s.r[c.cl].n1 > 0, do2 = p.s.r[c.cl].n2 > 0, do3 = p.s.r[c.cl].p3 != 255;
  if (do1 && c.wg == 2 && c.warp == 0) {
    const int type = p.s.r[c.cl].slab >> 3;
    PROF(2, 57);
    FENCE_ASYNC_SMEM();
    mbar_expect(c.bar + B_P1F * 8, type ? 32768 : 16384);
    tma2d(type ? c.sm + SM_BUF + 32768 : c.sm + SM_RING, &p.map_a[type], type ? 512 : 0, (p.s.r[c.cl].slab & 7) * 256 + c.rank * 128, c.bar + B_P1F * 8);
    PROF(2, 58);
  }
  asm volatile("barrier.cluster.wait.acquire;" ::: "memory");
  if (c.wg == 2) PROF(2, 59);
  if (do1 && c.wg == 2 && c.warp == 0) {
    const int type = p.s.r[c.cl].slab >> 3, tile = p.s.r[c.cl].tile[0];
    if (!type) mbar_expect(c.bar + (B_P1F + 1) * 8, 16384);
    tma2d_mc(c.sm + SM_RING + (1 - type) * 16384 + c.rank * 8192, &p.map_w[type * 2 + (tile >> 5)], (tile & 31) * 128 + c.rank * 64, type ? 512 : 0, c.bar + (B_P1F + 1 - type) * 8);
  }

  if (c.wg < 2) {
    PROF(c.wg, 4);
    asm volatile("setmaxnreg.inc.sync.aligned.u32 224;");
    if (c.wg == 1) {
      if (do1) bar_arrive(ORDER, 256);
      if (c.lane == 0) mbar_arrive(c.bar + B_P2F * 8);
    }
    if (do1) p1_consumer(p, c);
    if (do2) p2_consumer(p, c, p.s.r[c.cl].rot);
    if (do3) p3_consumer(p, c, p.s.r[c.cl].x3);
    PROF(c.wg, 63);
    PROFG(62);
    if (c.lane == 0) mbar_arrive(c.bar + B_FIN * 8);
    __syncwarp();
    cluster_sync();
  } else {
    asm volatile("setmaxnreg.dec.sync.aligned.u32 56;");
    if (c.warp == 0) {
      PROF(2, 60);
      if (do1) p1_producer(p, c);
      if (do2) p2_producer(p, c, p.s.r[c.cl].u1, p.s.r[c.cl].rot);
      if (do3) p3_producer(p, c, p.s.r[c.cl].u1, p.s.r[c.cl].u2, p.s.r[c.cl].rot, p.s.r[c.cl].x3);
    } else if (c.warp == 1) {
      int sfpar = 0;
      if (do1) {
        p1_storer(p, c);
        sfpar = (p.s.r[c.cl].n1 & 1) * 10;
      }
      if (do2) p2_storer(p, c, sfpar);
      else { mbar_wait(c.bar + B_LAD * 8, 0); release(c, B_DONE); }
      if (do3) {
        const int task = p.s.r[c.cl].p3;
        if (task >= 24) {
          const int j = (task - 24) / 3, nt = task - 24 - 3 * j;
          uint4* o = reinterpret_cast<uint4*>(p.out + (size_t)(j * 256 + c.rank * 128 + (c.lane >> 3)) * DM + nt * 192) + (c.lane & 7);
#pragma unroll 4
          for (int r = 0; r < 32; r++) o[r * 288] = o[r * 288 + 8] = o[r * 288 + 16] = make_uint4(0u, 0u, 0u, 0u);
          __syncwarp();
          flag_add(F_OUT + (task - 24) * 2 + c.rank);
        } else if (c.phases & 16) {
          flag_wait<false, 256>(F_OUT + task * 2 + c.rank, 1);
        }
        mbar_arrive_one(c.bar + B_OUT * 8);
      }
    } else {
      const int bw = blockIdx.x * 2 + (c.warp - 2);
      if ((c.phases & 1) && bw < 256) {
        gate_rows(p, bw * 8, c.lane);
        __syncwarp();
        flag_add(F_GATE);
      }
      if (p.s.r[c.cl].bg != 255) local_attn(p, c, p.s.r[c.cl].bg, bw & 3);
      else if (c.lane == 0) mbar_arrive(c.bar + B_LAD * 8);
    }
    __syncwarp();
    bar_sync(3, 128);
    if (c.warp == 0 && (c.phases & 4)) {
      int last = 0;
      if (c.lane == 0) { __threadfence(); last = atomicAdd(g_flags + F_DONE, 1) == 2 * NCL - 1; }
      if (__shfl_sync(0xffffffffu, last, 0)) for (int i = c.lane; i < F_NUM; i += 32) g_flags[i] = 0;
    }
    if (c.warp == 1) mbar_wait(c.bar + B_FIN * 8, 0);
    __syncwarp();
    cluster_sync();
  }
}

static const Sched k_sched = {
  {{0,29,1,255,0,{149,0,0,0,0,0,0,0,0,0,0},{0,0,0,0,0,0,0,0,0,0,0},{11,40,0,34,3,9,22,12,31,24,4,16,15,21,25,13,6,17,10,20,19,26,29,23,28,30,27,14,18,0}},
   {1,30,1,45,1,{113,0,0,0,0,0,0,0,0,0,0},{0,0,0,0,0,0,0,0,0,0,0},{11,34,1,32,8,3,5,22,12,31,24,4,16,25,15,6,13,17,10,21,20,19,26,23,29,30,28,14,27,18}},
   {2,30,1,31,2,{243,0,0,0,0,0,0,0,0,0,0},{15,0,0,0,0,0,0,0,0,0,0},{7,34,0,43,3,5,9,22,12,31,24,4,16,15,6,25,13,21,17,10,19,20,26,23,29,28,30,14,27,18}},
   {3,29,1,38,3,{242,0,0,0,0,0,0,0,0,0,0},{0,0,0,0,0,0,0,0,0,0,0},{1,39,11,34,3,37,41,54,63,44,48,56,36,47,38,57,45,42,49,53,51,52,58,55,61,60,62,46,59,0}},
   {4,29,1,34,4,{241,0,0,0,0,0,0,0,0,0,0},{0,0,0,0,0,0,0,0,0,0,0},{2,43,0,40,3,9,31,22,12,24,4,15,16,25,6,21,17,10,13,19,20,26,23,29,28,30,14,27,18,0}},
   {5,28,0,2,5,{0,0,0,0,0,0,0,0,0,0,0},{0,0,0,0,0,0,0,0,0,0,0},{11,39,2,40,3,9,63,12,24,4,16,25,15,6,21,17,10,13,19,20,26,23,29,28,30,14,27,18,0,0}},
   {6,27,2,24,6,{224,234,0,0,0,0,0,0,0,0,0},{0,0,0,0,0,0,0,0,0,0,0},{2,8,0,33,5,22,63,24,4,16,25,15,6,10,17,13,19,21,20,26,23,29,28,30,27,14,18,0,0,0}},
   {7,26,0,16,7,{0,0,0,0,0,0,0,0,0,0,0},{0,0,0,0,0,0,0,0,0,0,0},{2,7,1,3,9,24,12,4,16,25,15,6,10,17,13,21,19,20,26,23,29,30,28,27,14,18,0,0,0,0}},
   {0,29,1,33,8,{233,0,0,0,0,0,0,0,0,0,0},{0,0,0,0,0,0,0,0,0,0,0},{43,7,32,5,35,41,54,44,63,56,36,48,47,53,57,45,38,49,42,52,51,58,61,55,60,62,59,46,50,0}},
   {1,30,1,255,9,{220,0,0,0,0,0,0,0,0,0,0},{0,0,0,0,0,0,0,0,0,0,0},{43,7,33,9,40,35,37,54,44,63,56,36,48,57,47,38,45,49,42,53,52,51,58,55,61,62,60,46,59,50}},
   {2,30,1,41,10,{216,0,0,0,0,0,0,0,0,0,0},{0,0,0,0,0,0,0,0,0,0,0},{39,1,32,8,35,37,41,54,44,63,56,36,48,47,38,57,45,53,49,42,51,52,58,55,61,60,62,46,59,50}},
   {3,30,1,255,11,{116,0,0,0,0,0,0,0,0,0,0},{0,0,0,0,0,0,0,0,0,0,0},{33,0,43,8,35,9,22,31,12,16,24,4,15,6,25,13,10,17,21,19,20,26,23,29,28,30,14,27,18,50}},
   {4,29,1,28,12,{225,0,0,0,0,0,0,0,0,0,0},{0,0,0,0,0,0,0,0,0,0,0},{34,7,32,1,35,41,63,54,44,56,36,47,48,57,38,53,49,42,45,51,52,58,55,61,60,62,46,59,50,0}},
   {5,28,0,5,13,{0,0,0,0,0,0,0,0,0,0,0},{0,0,0,0,0,0,0,0,0,0,0},{43,0,34,1,35,41,22,44,56,36,48,57,47,38,53,49,42,45,51,52,58,55,61,60,62,46,59,50,0,0}},
   {6,27,0,21,14,{0,0,0,0,0,0,0,0,0,0,0},{0,0,0,0,0,0,0,0,0,0,0},{34,40,32,3,37,54,12,56,36,48,57,47,38,42,49,45,51,53,52,58,55,61,60,62,59,46,50,0,0,0}},
   {7,26,3,30,15,{232,236,144,0,0,0,0,0,0,0,0},{0,31,0,0,0,0,0,0,0,0,0},{34,39,33,35,41,56,44,36,48,57,47,38,42,49,45,53,51,52,58,55,61,62,60,59,46,50,0,0,0,0}},
   {0,6,6,18,255,{9,90,27,101,121,84,0,0,0,0,0},{0,0,0,0,0,0,0,0,0,0,0},{8,39,2,37,1,33,0,0,0,0,0,0,0,0,0,0,0,0,0,0,0,0,0,0,0,0,0,0,0,0}},
   {1,4,5,46,255,{63,103,137,215,227,0,0,0,0,0,0},{243,128,0,0,15,0,0,0,0,0,0},{2,39,0,41,0,0,0,0,0,0,0,0,0,0,0,0,0,0,0,0,0,0,0,0,0,0,0,0,0,0}},
   {2,4,5,25,255,{11,91,179,207,239,0,0,0,0,0,0},{0,0,0,0,224,0,0,0,0,0,0},{2,33,11,40,0,0,0,0,0,0,0,0,0,0,0,0,0,0,0,0,0,0,0,0,0,0,0,0,0,0}},
   {3,5,6,8,255,{16,31,34,33,195,165,0,0,0,0,0},{0,0,0,0,0,0,0,0,0,0,0},{7,32,2,40,5,0,0,0,0,0,0,0,0,0,0,0,0,0,0,0,0,0,0,0,0,0,0,0,0,0}},
   {4,6,7,255,255,{24,47,38,83,210,235,147,0,0,0,0},{0,0,0,0,0,0,15,0,0,0,0},{11,39,8,33,5,37,0,0,0,0,0,0,0,0,0,0,0,0,0,0,0,0,0,0,0,0,0,0,0,0}},
   {5,8,4,7,255,{72,2,255,53,0,0,0,0,0,0,0},{0,0,0,0,0,0,0,0,0,0,0},{7,32,8,33,5,37,31,54,0,0,0,0,0,0,0,0,0,0,0,0,0,0,0,0,0,0,0,0,0,0}},
   {6,8,5,14,255,{8,12,252,87,184,0,0,0,0,0,0},{0,0,0,0,0,0,0,0,0,0,0},{11,7,1,35,9,41,31,44,0,0,0,0,0,0,0,0,0,0,0,0,0,0,0,0,0,0,0,0,0,0}},
   {7,6,7,44,255,{19,67,194,196,203,189,112,0,0,0,0},{0,0,0,0,0,0,0,0,0,0,0},{11,0,8,5,22,31,0,0,0,0,0,0,0,0,0,0,0,0,0,0,0,0,0,0,0,0,0,0,0,0}},
   {8,17,3,35,16,{200,85,212,0,0,0,0,0,0,0,0},{0,0,31,0,0,0,0,0,0,0,0},{32,42,2,43,39,40,31,15,4,12,25,16,6,29,28,30,27,0,0,0,0,0,0,0,0,0,0,0,0,0}},
   {9,16,2,1,17,{51,108,0,0,0,0,0,0,0,0,0},{0,0,0,0,0,0,0,0,0,0,0},{11,37,0,9,8,5,40,24,22,16,13,17,10,21,23,30,0,0,0,0,0,0,0,0,0,0,0,0,0,0}},
   {10,17,2,255,18,{143,119,0,0,0,0,0,0,0,0,0},{253,240,0,0,0,0,0,0,0,0,0},{32,42,38,35,12,4,40,22,16,6,13,17,19,26,29,30,27,0,0,0,0,0,0,0,0,0,0,0,0,0}},
   {11,17,3,37,19,{192,167,228,0,0,0,0,0,0,0,0},{0,128,0,0,0,0,0,0,0,0,0},{32,42,34,3,22,40,12,16,24,15,25,17,19,20,29,30,14,0,0,0,0,0,0,0,0,0,0,0,0,0}},
   {12,17,3,10,20,{176,106,156,0,0,0,0,0,0,0,0},{0,0,0,0,0,0,0,0,0,0,0},{32,42,34,3,5,22,40,12,15,16,6,17,13,19,23,28,14,0,0,0,0,0,0,0,0,0,0,0,0,0}},
   {13,16,2,17,21,{248,111,0,0,0,0,0,0,0,0,0},{0,255,0,0,0,0,0,0,0,0,0},{32,42,1,3,44,22,40,4,16,6,21,10,19,23,26,30,0,0,0,0,0,0,0,0,0,0,0,0,0,0}},
   {14,17,2,26,22,{54,188,0,0,0,0,0,0,0,0,0},{3,0,0,0,0,0,0,0,0,0,0},{32,42,0,9,44,31,40,4,16,25,17,10,21,26,29,30,14,0,0,0,0,0,0,0,0,0,0,0,0,0}},
   {15,17,3,29,23,{96,172,213,0,0,0,0,0,0,0,0},{1,0,31,0,0,0,0,0,0,0,0},{32,42,1,34,39,31,12,40,16,15,10,13,19,26,29,28,14,0,0,0,0,0,0,0,0,0,0,0,0,0}},
   {8,18,4,255,24,{128,157,245,217,0,0,0,0,0,0,0},{0,0,0,0,0,0,0,0,0,0,0},{36,11,5,1,44,45,22,21,24,13,17,10,26,23,19,20,14,18,0,0,0,0,0,0,0,0,0,0,0,0}},
   {9,20,3,255,25,{171,229,146,0,0,0,0,0,0,0,0},{0,0,0,0,0,0,0,0,0,0,0},{32,42,34,35,3,12,45,31,4,25,15,6,20,19,26,28,29,14,27,18,0,0,0,0,0,0,0,0,0,0}},
   {10,17,3,255,26,{104,159,118,0,0,0,0,0,0,0,0},{0,3,0,0,0,0,0,0,0,0,0},{36,7,43,39,24,5,45,31,15,25,21,10,20,23,28,14,18,0,0,0,0,0,0,0,0,0,0,0,0,0}},
   {11,17,3,9,27,{168,142,240,0,0,0,0,0,0,0,0},{0,0,0,0,0,0,0,0,0,0,0},{36,1,38,35,5,45,31,4,6,13,10,21,26,23,28,27,18,0,0,0,0,0,0,0,0,0,0,0,0,0}},
   {12,18,2,32,28,{158,187,0,0,0,0,0,0,0,0,0},{0,15,0,0,0,0,0,0,0,0,0},{36,2,38,35,9,31,45,4,24,21,25,10,20,26,29,30,27,18,0,0,0,0,0,0,0,0,0,0,0,0}},
   {13,18,4,0,29,{136,81,82,185,0,0,0,0,0,0,0},{0,0,0,0,0,0,0,0,0,0,0},{36,11,8,9,5,12,45,24,15,25,17,13,20,29,28,14,18,27,0,0,0,0,0,0,0,0,0,0,0,0}},
   {14,17,3,3,30,{32,110,152,0,0,0,0,0,0,0,0},{0,0,0,0,0,0,0,0,0,0,0},{36,2,1,3,22,12,45,24,15,6,13,19,20,23,28,27,18,0,0,0,0,0,0,0,0,0,0,0,0,0}},
   {15,17,5,255,31,{120,49,161,155,222,0,0,0,0,0,0},{0,0,0,0,64,0,0,0,0,0,0},{36,2,8,38,44,24,4,45,25,6,17,21,20,23,30,27,18,0,0,0,0,0,0,0,0,0,0,0,0,0}},
   {8,4,6,39,255,{59,10,45,127,163,117,0,0,0,0,0},{0,0,0,0,0,0,0,0,0,0,0},{41,7,3,9,0,0,0,0,0,0,0,0,0,0,0,0,0,0,0,0,0,0,0,0,0,0,0,0,0,0}},
   {9,4,5,255,255,{5,28,135,164,151,0,0,0,0,0,0},{0,0,0,0,240,0,0,0,0,0,0},{36,2,38,39,0,0,0,0,0,0,0,0,0,0,0,0,0,0,0,0,0,0,0,0,0,0,0,0,0,0}},
   {10,4,7,40,255,{70,66,97,36,170,214,114,0,0,0,0},{0,0,0,0,0,64,0,0,0,0,0},{41,2,1,44,0,0,0,0,0,0,0,0,0,0,0,0,0,0,0,0,0,0,0,0,0,0,0,0,0,0}},
   {11,4,8,255,255,{88,21,182,50,107,162,209,221,0,0,0},{0,0,0,0,0,0,0,56,0,0,0},{41,7,43,39,0,0,0,0,0,0,0,0,0,0,0,0,0,0,0,0,0,0,0,0,0,0,0,0,0,0}},
   {12,3,3,13,255,{23,199,141,0,0,0,0,0,0,0,0},{47,0,0,0,0,0,0,0,0,0,0},{41,11,43,0,0,0,0,0,0,0,0,0,0,0,0,0,0,0,0,0,0,0,0,0,0,0,0,0,0,0}},
   {13,4,6,20,255,{6,65,43,129,201,86,0,0,0,0,0},{0,0,0,0,0,127,0,0,0,0,0},{41,7,34,31,0,0,0,0,0,0,0,0,0,0,0,0,0,0,0,0,0,0,0,0,0,0,0,0,0,0}},
   {14,4,4,11,255,{7,74,37,174,0,0,0,0,0,0,0},{255,0,0,0,0,0,0,0,0,0,0},{41,11,34,5,0,0,0,0,0,0,0,0,0,0,0,0,0,0,0,0,0,0,0,0,0,0,0,0,0,0}},
   {15,4,5,15,255,{92,29,193,134,80,0,0,0,0,0,0},{0,0,0,0,0,0,0,0,0,0,0},{41,11,3,43,0,0,0,0,0,0,0,0,0,0,0,0,0,0,0,0,0,0,0,0,0,0,0,0,0,0}},
   {8,4,7,255,255,{4,77,178,133,153,246,218,0,0,0,0},{0,0,0,0,0,0,7,0,0,0,0},{33,8,34,35,0,0,0,0,0,0,0,0,0,0,0,0,0,0,0,0,0,0,0,0,0,0,0,0,0,0}},
   {9,2,7,255,255,{17,14,254,105,138,238,115,0,0,0,0},{0,0,0,0,0,0,15,0,0,0,0},{41,7,0,0,0,0,0,0,0,0,0,0,0,0,0,0,0,0,0,0,0,0,0,0,0,0,0,0,0,0}},
   {10,4,7,6,255,{57,1,78,99,132,169,208,0,0,0,0},{0,0,0,0,0,0,0,0,0,0,0},{33,11,0,8,0,0,0,0,0,0,0,0,0,0,0,0,0,0,0,0,0,0,0,0,0,0,0,0,0,0}},
   {11,4,5,12,255,{93,26,180,206,48,0,0,0,0,0,0},{0,0,0,0,0,0,0,0,0,0,0},{33,0,11,44,0,0,0,0,0,0,0,0,0,0,0,0,0,0,0,0,0,0,0,0,0,0,0,0,0,0}},
   {12,4,5,36,255,{62,76,131,173,231,0,0,0,0,0,0},{0,0,0,0,255,0,0,0,0,0,0},{33,0,1,39,0,0,0,0,0,0,0,0,0,0,0,0,0,0,0,0,0,0,0,0,0,0,0,0,0,0}},
   {13,4,6,42,255,{20,68,42,35,52,230,0,0,0,0,0},{0,0,0,0,0,0,0,0,0,0,0},{33,0,38,35,0,0,0,0,0,0,0,0,0,0,0,0,0,0,0,0,0,0,0,0,0,0,0,0,0,0}},
   {14,4,5,43,255,{61,253,197,166,244,0,0,0,0,0,0},{0,0,0,3,16,0,0,0,0,0,0},{33,8,38,35,0,0,0,0,0,0,0,0,0,0,0,0,0,0,0,0,0,0,0,0,0,0,0,0,0,0}},
   {15,4,5,27,255,{64,71,102,202,191,0,0,0,0,0,0},{0,128,0,0,32,0,0,0,0,0,0},{33,7,5,22,0,0,0,0,0,0,0,0,0,0,0,0,0,0,0,0,0,0,0,0,0,0,0,0,0,0}},
   {8,3,5,255,255,{60,46,124,109,223,0,0,0,0,0,0},{0,0,0,0,128,0,0,0,0,0,0},{37,0,38,0,0,0,0,0,0,0,0,0,0,0,0,0,0,0,0,0,0,0,0,0,0,0,0,0,0,0}},
   {9,4,5,19,255,{22,44,177,122,204,0,0,0,0,0,0},{0,0,0,0,0,0,0,0,0,0,0},{33,1,43,44,0,0,0,0,0,0,0,0,0,0,0,0,0,0,0,0,0,0,0,0,0,0,0,0,0,0}},
   {10,4,6,255,255,{56,15,39,140,186,150,0,0,0,0,0},{0,64,0,0,0,0,0,0,0,0,0},{37,34,3,9,0,0,0,0,0,0,0,0,0,0,0,0,0,0,0,0,0,0,0,0,0,0,0,0,0,0}},
   {11,4,6,255,255,{94,181,130,123,190,148,0,0,0,0,0},{0,0,0,0,0,0,0,0,0,0,0},{37,2,8,9,0,0,0,0,0,0,0,0,0,0,0,0,0,0,0,0,0,0,0,0,0,0,0,0,0,0}},
   {12,4,7,255,255,{0,18,73,183,55,247,145,0,0,0,0},{0,0,0,0,0,224,0,0,0,0,0},{37,7,8,44,0,0,0,0,0,0,0,0,0,0,0,0,0,0,0,0,0,0,0,0,0,0,0,0,0,0}},
   {13,4,7,47,255,{58,69,98,249,126,211,226,0,0,0,0},{0,0,0,0,0,0,0,0,0,0,0},{37,2,43,39,0,0,0,0,0,0,0,0,0,0,0,0,0,0,0,0,0,0,0,0,0,0,0,0,0,0}},
   {14,4,4,23,255,{3,30,100,175,0,0,0,0,0,0,0},{0,0,0,0,0,0,0,0,0,0,0},{37,7,43,39,0,0,0,0,0,0,0,0,0,0,0,0,0,0,0,0,0,0,0,0,0,0,0,0,0,0}},
   {15,4,7,4,255,{95,25,41,250,125,154,160,0,0,0,0},{220,0,0,0,0,0,0,0,0,0,0},{37,0,9,35,0,0,0,0,0,0,0,0,0,0,0,0,0,0,0,0,0,0,0,0,0,0,0,0,0,0}},
   {6,2,5,22,255,{89,13,75,251,205,0,0,0,0,0,0},{0,0,0,0,0,0,0,0,0,0,0},{43,39,0,0,0,0,0,0,0,0,0,0,0,0,0,0,0,0,0,0,0,0,0,0,0,0,0,0,0,0}},
   {7,6,6,255,255,{40,79,198,139,237,219,0,0,0,0,0},{0,0,0,0,0,0,0,0,0,0,0},{43,32,40,37,54,63,0,0,0,0,0,0,0,0,0,0,0,0,0,0,0,0,0,0,0,0,0,0,0,0}}},
  {10,8,9,10,10,9,5,2,9,10,10,9,3,4,7,1,4,9,6,3,8,7,3,9},
  {{0,7,8,11,2,3,5,1,9,31,4,12,13,15,21,22,24,25,16,17,10,6,26,23,29,19,30,20,28,27,14,18},
   {2,7,11,1,0,9,8,3,5,12,24,31,22,4,16,25,13,15,17,6,10,20,21,19,23,26,28,29,30,14,27,18},
   {7,2,11,1,0,3,8,9,12,24,4,5,22,31,16,15,6,25,13,21,17,10,19,20,26,23,29,28,30,14,27,18},
   {0,1,7,2,11,8,3,9,22,5,12,31,16,4,24,6,15,13,25,10,17,21,19,26,20,23,29,28,30,27,14,18},
   {0,2,7,11,1,8,3,5,9,22,31,12,4,15,24,16,25,21,6,17,10,13,19,20,26,23,29,28,30,14,27,18},
   {0,7,11,2,1,8,3,9,31,5,22,12,4,24,16,6,15,25,17,21,10,13,20,19,26,23,29,28,30,14,18,27},
   {0,2,7,8,11,1,9,3,5,22,31,12,4,24,16,15,25,6,10,21,13,17,19,20,26,23,29,28,30,27,14,18},
   {0,2,7,11,1,8,3,5,9,22,31,12,24,4,16,25,15,6,10,13,21,17,19,20,26,23,29,28,30,27,14,18}},
  {{3,4,3,2,3,2,4,3},{7,3,2,0,5,5,5,4},{4,1,1,4,0,3,0,0},{6,7,6,6,6,6,6,6},
   {13,13,13,1,0,0,0,0},{5,8,7,7,7,7,7,7},{1,3,5,5,7,7,7,4},{2,2,0,1,2,1,3,2},
   {1,6,5,5,4,4,2,5},{8,5,8,8,8,8,8,8},{5,8,10,8,11,9,13,9},{0,0,4,3,1,0,1,1},
   {10,10,10,11,11,11,11,12},{7,6,7,7,9,11,10,10},{15,0,9,11,0,0,11,7},{15,0,2,0,5,6,6,8},
   {14,14,0,12,4,4,2,6},{6,7,8,9,10,10,9,13},{16,7,11,10,5,4,8,8},{17,11,11,10,12,12,11,0},
   {8,9,12,13,0,0,12,6},{16,5,9,11,8,8,0,11},{9,9,9,9,10,10,9,9},{12,12,0,12,5,6,8,8},
   {12,12,12,13,12,12,12,11},{0,15,6,6,6,5,8,7},{11,10,13,1,4,4,2,7},{0,5,12,13,12,12,12,0},
   {13,15,6,6,7,7,7,11},{9,13,2,0,6,5,6,4},{14,14,5,5,8,8,0,9},{11,11,11,10,9,9,10,10}},
  {{255,255,255,255,255,255,255,255},{255,255,255,255,255,255,255,255},{255,255,255,255,255,255,255,255},{255,255,255,255,255,255,255,255},
   {255,255,255,7,2,11,2,2},{255,255,255,255,255,255,255,255},{8,1,8,8,5,5,5,1},{255,255,255,255,255,255,255,255},
   {255,255,255,255,255,255,255,255},{255,255,255,255,255,255,255,255},{5,5,12,9,12,31,255,22},{255,255,255,255,255,255,255,255},
   {255,255,255,255,255,255,255,255},{1,8,5,5,31,12,31,31},{15,15,21,21,20,20,19,26},{255,11,1,1,1,3,3,9},
   {255,255,7,255,8,8,8,3},{3,3,9,22,22,22,22,255},{21,17,19,19,23,26,23,23},{255,31,31,31,24,24,12,4},
   {9,22,24,24,4,4,24,16},{255,9,22,12,9,9,4,24},{255,255,255,255,255,255,255,255},{24,24,16,16,15,15,25,15},
   {255,255,255,255,255,255,255,255},{11,255,3,3,3,1,9,5},{31,12,4,4,16,16,16,25},{25,21,20,20,19,19,20,19},
   {4,25,25,25,6,6,6,21},{22,4,15,15,25,25,15,6},{16,16,6,6,21,21,21,10},{255,255,255,255,255,255,255,255}}};

typedef CUresult (*EncodeFn)(CUtensorMap*, CUtensorMapDataType, cuuint32_t, void*, const cuuint64_t*, const cuuint64_t*, const cuuint32_t*,
                             const cuuint32_t*, CUtensorMapInterleave, CUtensorMapSwizzle, CUtensorMapL2promotion, CUtensorMapFloatOOBfill);

void make_map2(EncodeFn enc, CUtensorMap* m, const void* ptr, int rows, int cols, int box_rows) {
  cuuint64_t dim[2] = {(cuuint64_t)cols, (cuuint64_t)rows}, str[1] = {(cuuint64_t)cols * 2};
  cuuint32_t box[2] = {64, (cuuint32_t)box_rows}, es[2] = {1, 1};
  enc(m, CU_TENSOR_MAP_DATA_TYPE_BFLOAT16, 2, const_cast<void*>(ptr), dim, str, box, es, CU_TENSOR_MAP_INTERLEAVE_NONE, CU_TENSOR_MAP_SWIZZLE_128B,
      CU_TENSOR_MAP_L2_PROMOTION_L2_128B, CU_TENSOR_MAP_FLOAT_OOB_FILL_NONE);
}
void make_map3(EncodeFn enc, CUtensorMap* m, const void* ptr, int rows) {
  cuuint64_t dim[3] = {64, (cuuint64_t)rows, 9}, str[2] = {DM * 2, 128};
  cuuint32_t box[3] = {64, 32, 3}, es[3] = {1, 1, 1};
  enc(m, CU_TENSOR_MAP_DATA_TYPE_BFLOAT16, 3, const_cast<void*>(ptr), dim, str, box, es, CU_TENSOR_MAP_INTERLEAVE_NONE, CU_TENSOR_MAP_SWIZZLE_128B,
      CU_TENSOR_MAP_L2_PROMOTION_L2_128B, CU_TENSOR_MAP_FLOAT_OOB_FILL_NONE);
}

void make_map_t(EncodeFn enc, CUtensorMap* m, void* ptr, int width, int cols) {
  cuuint64_t dim[3] = {TP / 2, 2, 864}, str[2] = {TP * 2, TP * 4};
  cuuint32_t box[3] = {(cuuint32_t)width, 2, (cuuint32_t)cols}, es[3] = {1, 1, 1};
  enc(m, CU_TENSOR_MAP_DATA_TYPE_UINT32, 3, ptr, dim, str, box, es, CU_TENSOR_MAP_INTERLEAVE_NONE, cols == 64 ? CU_TENSOR_MAP_SWIZZLE_128B : CU_TENSOR_MAP_SWIZZLE_NONE,
      CU_TENSOR_MAP_L2_PROMOTION_NONE, CU_TENSOR_MAP_FLOAT_OOB_FILL_NONE);
}

int g_mode = -1;

}

extern "C" void kernel_launch(void* const* d_in, const int* in_sizes, int n_in, void* d_out, int out_size) {
  static EncodeFn enc = nullptr;
  static void* t_ptr = nullptr;
  if (!enc) {
    void* fn = nullptr;
    cudaDriverEntryPointQueryResult st;
    cudaGetDriverEntryPoint("cuTensorMapEncodeTiled", &fn, cudaEnableDefault, &st);
    enc = (EncodeFn)fn;
    cudaGetSymbolAddress(&t_ptr, g_T);
    cudaFuncSetAttribute(fused_kernel, cudaFuncAttributeMaxDynamicSharedMemorySize, SMEM_BYTES);
    if (g_mode < 0) {
      cudaLaunchConfig_t cfg = {};
      cfg.gridDim = dim3(2 * NCL); cfg.blockDim = dim3(384); cfg.dynamicSmemBytes = SMEM_BYTES;
      cudaLaunchAttribute at; at.id = cudaLaunchAttributeClusterDimension;
      at.val.clusterDim.x = 2; at.val.clusterDim.y = 1; at.val.clusterDim.z = 1;
      cfg.attrs = &at; cfg.numAttrs = 1;
      int nc = 0;
      g_mode = (cudaOccupancyMaxActiveClusters(&nc, fused_kernel, &cfg) == cudaSuccess && nc >= NCL) ? 1 : 0;
      (void)cudaGetLastError();
    }
  }
  Params p;
  make_map2(enc, &p.map_a[0], d_in[4], SEQ, DC, 128);
  make_map2(enc, &p.map_a[1], d_in[0], SEQ, DM, 128);
  make_map2(enc, &p.map_w[0], d_in[6], DC, 4096, 64);
  make_map2(enc, &p.map_w[1], d_in[7], DC, 4096, 64);
  make_map2(enc, &p.map_w[2], d_in[5], DM, 4096, 64);
  make_map2(enc, &p.map_w[3], d_in[1], DM, 1728, 64);
  make_map3(enc, &p.map_o[0], d_in[8], 4096);
  make_map3(enc, &p.map_o[1], d_in[2], DM);
  make_map_t(enc, &p.map_t[0], t_ptr, 32, 9);
  make_map_t(enc, &p.map_t[1], t_ptr, 40, 9);
  make_map_t(enc, &p.map_t[2], t_ptr, 32, 64);
  p.x = (const __nv_bfloat16*)d_in[0];
  p.gate_w = (const __nv_bfloat16*)d_in[9];
  make_map2(enc, &p.map_out, d_out, SEQ, DM, 16);
  p.out = (__nv_bfloat16*)d_out;
  p.zero = 0;
  auto launch = [&](int phases) {
    p.s = k_sched;
    for (int i = 0; i < NCL; i++) {
      Rec& r = p.s.r[i];
      if (!(phases & 1)) r.n1 = 0;
      if (!(phases & 2)) r.n2 = 0;
      if (!(phases & (r.p3 < 24 ? 4 : 32))) r.p3 = 255;
      if (!(phases & 8)) r.bg = 255;
      const int u1 = r.n1 ? 8 + r.n1 * (8 + (r.slab >> 3)) : 0;
      int u2 = 0;
      for (int k = 0; k < r.n2; k++) u2 += 4 * (r.item[k] & 7) + 4;
      r.u1 = (uint8_t)u1; r.u2 = (uint8_t)u2;
      r.rot = (uint8_t)(((u1 % 10 + 1) >> 1) % 5);
      r.x3 = (uint8_t)((r.rot + u2) % 5 & 3);
      r.phases = (uint8_t)phases;
    }
    if (!(phases & 16))
      for (int i = 0; i < 256; i++) { p.s.slot[i >> 3][i & 7] = (uint8_t)(i >> 3); p.s.prev[i >> 3][i & 7] = 255; }
    fused_kernel<<<2 * NCL, 384, SMEM_BYTES>>>(p);
  };
  if (g_mode == 1) launch(63);
  else { launch(1); launch(10); launch(32); launch(4); }
}
```

```cpp
#include <cuda_runtime.h>
#include <cuda_bf16.h>
#include <cuda.h>
#include <stdint.h>

namespace {

constexpr int SEQ = 2048, DM = 576, DC = 512, NH = 32;
constexpr int NCL = 66;
constexpr uint32_t DESC_HI = 0x40000040u;

constexpr int SM_RING = 0;
constexpr int SM_BUF = 163840;
constexpr int SM_BAR = 229376;
constexpr int B_P1E = 0, B_P2E = 10, B_P3E = 15, B_P2F = 24, B_SF = 32, B_ORD = 36, B_LAD = 40, B_DONE = 41, B_FIN = 48;
constexpr int B_P3F = 56, B_OUT = 61, B_P1F = 64, B_SE = 74, B_QF = 80, B_LA = 84, B_NUM = 88;
constexpr uint64_t B_CNT = 0x11118245000ull;
constexpr int SMEM_BYTES = SM_BAR + B_NUM * 8 + 1024;

constexpr int F_QKVA = 32;
constexpr int F_GATE = 64;
constexpr int F_DONE = 65;
constexpr int F_CTX = 96;
constexpr int F_OUT = 96 + 8 * 64;
constexpr int F_KV = F_OUT + 64;
constexpr int F_Q = F_KV + 256;
constexpr int F_RD = F_Q + 256;
constexpr int F_NUM = F_RD + 256;

struct Rec {
  uint8_t slab;
  uint8_t n1, n2;
  uint8_t p3;
  uint8_t bg;
  uint8_t item[11];
  uint8_t last[11];
  uint8_t tile[32];
  uint8_t u1, u2;
  uint8_t rot, x3;
  uint8_t phases;
};
struct Sched {
  Rec r[NCL];
  uint8_t nh[24];
  uint8_t p3_order[8][32];
  uint8_t slot[32][8];
  uint8_t prev[32][8];
};

struct Params {
  CUtensorMap map_a[2];
  CUtensorMap map_w[4];
  CUtensorMap map_o[2];
  CUtensorMap map_t[3];
  CUtensorMap map_out;
  const __nv_bfloat16* x;
  const __nv_bfloat16* gate_w;
  __nv_bfloat16* out;
  int zero;
  alignas(64) Sched s;
};

__device__ __align__(1024) uint8_t g_Q[NH * 32 * 16384];
__device__ __align__(1024) uint8_t g_KV[2 * NH * 16 * 32768];
__device__ __align__(1024) uint8_t g_oA[32 * 576 * 128];
constexpr int TP = SEQ + 16;
__device__ __align__(1024) uint32_t g_T[864 * TP];
__device__ float g_gate[SEQ];
__device__ int g_flags[F_NUM];

__device__ __forceinline__ void mbar_arrive(uint32_t b) { asm volatile("mbarrier.arrive.shared::cta.b64 _, [%0];" ::"r"(b) : "memory"); }
__device__ __forceinline__ void mbar_arrive_cl(uint32_t b, int cnt) {
  asm volatile("mbarrier.arrive.shared::cluster.b64 _, [%0], %1;" ::"r"(b), "r"(cnt) : "memory");
}
__device__ __forceinline__ void mbar_wait(uint32_t b, int par) {
  asm volatile(
      "{\n.reg .pred p;\n.reg .u32 c;\n"
      "mbarrier.try_wait.parity.shared::cta.b64 p, [%0], %1;\n@p bra DN;\nmov.u32 c, 0;\n"
      "LP:\nmbarrier.try_wait.parity.shared::cta.b64 p, [%0], %1;\n@p bra DN;\n"
      "add.u32 c, c, 1;\nsetp.lt.u32 p, c, 4000000;\n@p bra LP;\ntrap;\nDN:\n}" ::"r"(b), "r"(par) : "memory");
}
__device__ __forceinline__ uint32_t mapa(uint32_t a, uint32_t cta) {
  uint32_t r; asm("mapa.shared::cluster.u32 %0, %1, %2;" : "=r"(r) : "r"(a), "r"(cta)); return r;
}
#define ELECT(ins) "{\n.reg .pred e;\nelect.sync _|e, 0xffffffff;\n@e " ins "\n}"
__device__ __forceinline__ void mbar_expect(uint32_t b, int bytes) {
  asm volatile(ELECT("mbarrier.arrive.expect_tx.shared::cta.b64 _, [%0], %1;") ::"r"(b), "r"(bytes) : "memory");
}
__device__ __forceinline__ void mbar_arrive_one(uint32_t b) { asm volatile(ELECT("mbarrier.arrive.shared::cta.b64 _, [%0];") ::"r"(b) : "memory"); }
constexpr uint64_t L2_NORMAL = 0x1000000000000000ull, L2_FIRST = 0x12F0000000000000ull;
__device__ __forceinline__ void bulk_load(uint32_t dst, const void* src, int bytes, uint32_t bar, uint64_t pol = L2_NORMAL) {
  asm volatile(ELECT("cp.async.bulk.shared::cluster.global.mbarrier::complete_tx::bytes.L2::cache_hint [%0], [%1], %2, [%3], %4;") ::"r"(dst), "l"(src), "r"(bytes), "r"(bar), "l"(pol) : "memory");
}
__device__ __forceinline__ void bulk_load_mc(uint32_t dst, const void* src, int bytes, uint32_t bar, uint64_t pol = L2_NORMAL) {
  asm volatile(ELECT("cp.async.bulk.shared::cluster.global.mbarrier::complete_tx::bytes.multicast::cluster.L2::cache_hint [%0], [%1], %2, [%3], %4, %5;") ::"r"(dst), "l"(src), "r"(bytes), "r"(bar), "h"((uint16_t)3), "l"(pol) : "memory");
}
__device__ __forceinline__ void bulk_store(void* dst, uint32_t src, int bytes, uint64_t pol = L2_NORMAL) {
  asm volatile(ELECT("cp.async.bulk.global.shared::cta.bulk_group.L2::cache_hint [%0], [%1], %2, %3;") ::"l"(dst), "r"(src), "r"(bytes), "l"(pol) : "memory");
}
__device__ __forceinline__ void tma2d(uint32_t dst, const CUtensorMap* m, int c0, int c1, uint32_t bar, uint64_t pol = L2_NORMAL) {
  asm volatile(ELECT("cp.async.bulk.tensor.2d.shared::cluster.global.mbarrier::complete_tx::bytes.L2::cache_hint [%0], [%1, {%3, %4}], [%2], %5;") ::"r"(dst), "l"(m), "r"(bar), "r"(c0), "r"(c1), "l"(pol) : "memory");
}
__device__ __forceinline__ void tma2d_mc(uint32_t dst, const CUtensorMap* m, int c0, int c1, uint32_t bar, uint64_t pol = L2_NORMAL) {
  asm volatile(ELECT("cp.async.bulk.tensor.2d.shared::cluster.global.mbarrier::complete_tx::bytes.multicast::cluster.L2::cache_hint [%0], [%1, {%3, %4}], [%2], %5, %6;") ::"r"(dst), "l"(m), "r"(bar), "r"(c0), "r"(c1), "h"((uint16_t)3), "l"(pol) : "memory");
}
__device__ __forceinline__ void tma3d(uint32_t dst, const CUtensorMap* m, int c0, int c1, int c2, uint32_t bar, uint64_t pol = L2_NORMAL) {
  asm volatile(ELECT("cp.async.bulk.tensor.3d.shared::cluster.global.mbarrier::complete_tx::bytes.L2::cache_hint [%0], [%1, {%3, %4, %5}], [%2], %6;") ::"r"(dst), "l"(m), "r"(bar), "r"(c0), "r"(c1), "r"(c2), "l"(pol) : "memory");
}
__device__ __forceinline__ void tma3d_mc(uint32_t dst, const CUtensorMap* m, int c0, int c1, int c2, uint32_t bar, uint64_t pol = L2_NORMAL) {
  asm volatile(ELECT("cp.async.bulk.tensor.3d.shared::cluster.global.mbarrier::complete_tx::bytes.multicast::cluster.L2::cache_hint [%0], [%1, {%3, %4, %5}], [%2], %6, %7;") ::"r"(dst), "l"(m), "r"(bar), "r"(c0), "r"(c1), "r"(c2), "h"((uint16_t)3), "l"(pol) : "memory");
}
__device__ __forceinline__ void tma2d_add(const CUtensorMap* m, uint32_t src, int c0, int c1) {
  asm volatile(ELECT("cp.reduce.async.bulk.tensor.2d.global.shared::cta.add.bulk_group [%0, {%2, %3}], [%1];") ::"l"(m), "r"(src), "r"(c0), "r"(c1) : "memory");
}
__device__ __forceinline__ void tma3d_store(const CUtensorMap* m, uint32_t src, int c0, int c1, int c2, uint64_t pol = L2_NORMAL) {
  asm volatile(ELECT("cp.async.bulk.tensor.3d.global.shared::cta.bulk_group.L2::cache_hint [%0, {%2, %3, %4}], [%1], %5;") ::"l"(m), "r"(src), "r"(c0), "r"(c1), "r"(c2), "l"(pol) : "memory");
}
__device__ __forceinline__ void tma2d_prefetch(const CUtensorMap* m, int c0, int c1, uint64_t pol = L2_NORMAL) {
  asm volatile(ELECT("cp.async.bulk.prefetch.tensor.2d.L2.global.L2::cache_hint [%0, {%1, %2}], %3;") ::"l"(m), "r"(c0), "r"(c1), "l"(pol) : "memory");
}
#define HINT 62
#define POL(bit) ((HINT >> (bit)) & 1 ? L2_FIRST : L2_NORMAL)
#define BULK_COMMIT() asm volatile("cp.async.bulk.commit_group;" ::: "memory")
#define BULK_WAIT(n) asm volatile("cp.async.bulk.wait_group %0;" ::"n"(n) : "memory")
#define BULK_WAIT_READ(n) asm volatile("cp.async.bulk.wait_group.read %0;" ::"n"(n) : "memory")
#define FENCE_ASYNC_SMEM() asm volatile("fence.proxy.async.shared::cta;" ::: "memory")
#define FENCE_ASYNC_ALL() asm volatile("fence.proxy.async;" ::: "memory")
#define WG_FENCE() asm volatile("wgmma.fence.sync.aligned;" ::: "memory")
#define WG_COMMIT() asm volatile("wgmma.commit_group.sync.aligned;" ::: "memory")
#define WG_WAIT(n) asm volatile("wgmma.wait_group.sync.aligned %0;" ::"n"(n) : "memory")
__device__ __forceinline__ void bar_sync(int id, int n) { asm volatile("bar.sync %0, %1;" ::"r"(id), "r"(n) : "memory"); }
__device__ __forceinline__ void bar_arrive(int id, int n) { asm volatile("bar.arrive %0, %1;" ::"r"(id), "r"(n) : "memory"); }
__device__ __forceinline__ void cluster_sync() {
  asm volatile("barrier.cluster.arrive.relaxed;\nbarrier.cluster.wait.acquire;" ::: "memory");
}
template <int N> __device__ __forceinline__ void pin(float (&r)[N]) {
#pragma unroll
  for (int i = 0; i < N; i++) asm volatile("" : "+f"(r[i])::"memory");
}
template <int N> __device__ __forceinline__ void pin(uint32_t (&r)[N]) {
#pragma unroll
  for (int i = 0; i < N; i++) asm volatile("" : "+r"(r[i])::"memory");
}
__device__ __forceinline__ uint32_t pack_bf16(float lo, float hi) {
  uint32_t r; asm("cvt.rn.bf16x2.f32 %0, %1, %2;" : "=r"(r) : "f"(hi), "f"(lo)); return r;
}
__device__ __forceinline__ float ex2(float x) { float r; asm("ex2.approx.ftz.f32 %0, %1;" : "=f"(r) : "f"(x)); return r; }
__device__ __forceinline__ void ldsm4(uint32_t a, uint32_t& r0, uint32_t& r1, uint32_t& r2, uint32_t& r3) {
  asm volatile("ldmatrix.sync.aligned.m8n8.x4.shared.b16 {%0,%1,%2,%3}, [%4];" : "=r"(r0), "=r"(r1), "=r"(r2), "=r"(r3) : "r"(a) : "memory");
}
__device__ __forceinline__ void stsm4(uint32_t a, uint32_t r0, uint32_t r1, uint32_t r2, uint32_t r3) {
  asm volatile("stmatrix.sync.aligned.m8n8.x4.shared.b16 [%0], {%1,%2,%3,%4};" ::"r"(a), "r"(r0), "r"(r1), "r"(r2), "r"(r3) : "memory");
}
__device__ __forceinline__ void flag_add(int idx) {
  asm volatile(ELECT("red.release.gpu.global.add.s32 [%0], 1;") ::"l"(g_flags + idx) : "memory");
}
__device__ __forceinline__ void flag_add_rx(int idx) {
  asm volatile(ELECT("red.relaxed.gpu.global.add.s32 [%0], 1;") ::"l"(g_flags + idx) : "memory");
}
template <bool ACQ, int NS = 32> __device__ __forceinline__ void flag_wait(int idx, int target) {
  int n = 0;
  while (true) {
    int v;
    if (ACQ) asm volatile("ld.acquire.gpu.global.s32 %0, [%1];" : "=r"(v) : "l"(g_flags + idx) : "memory");
    else asm volatile("ld.relaxed.gpu.global.s32 %0, [%1];" : "=r"(v) : "l"(g_flags + idx) : "memory");
    if (__all_sync(0xffffffffu, v >= target)) break;
    if (++n > 20000000) __trap();
    __nanosleep(NS);
  }
}
__device__ __forceinline__ uint32_t desc_lo(uint32_t addr, uint32_t lbo) { return ((addr & 0x3FFFFu) >> 4) | ((lbo >> 4) << 16); }
#define PROF(role, i)
#define PROFX(cond, i)
#define PROFB(i)
#define PROFG(i)

template <int TB, int TA = 0> __device__ __forceinline__ void wgmma_ss64(float (&d)[32], uint32_t alo, uint32_t blo, int sd) {
  asm volatile("{\n.reg .pred p;\n.reg .b64 da, db;\n"
    "setp.ne.b32 p, %34, 0;\nmov.b64 da, {%32, %36};\nmov.b64 db, {%33, %36};\n"
    "wgmma.mma_async.sync.aligned.m64n64k16.f32.bf16.bf16 "
    "{%0,%1,%2,%3,%4,%5,%6,%7,%8,%9,%10,%11,%12,%13,%14,%15,%16,%17,%18,%19,%20,%21,%22,%23,"
    "%24,%25,%26,%27,%28,%29,%30,%31}, "
    "da, db, p, 1, 1, %37, %35;\n}\n"
    : "+f"(d[0]),"+f"(d[1]),"+f"(d[2]),"+f"(d[3]),"+f"(d[4]),"+f"(d[5]),"+f"(d[6]),"+f"(d[7]),"+f"(d[8]),"+f"(d[9]),"+f"(d[10]),"+f"(d[11]),
      "+f"(d[12]),"+f"(d[13]),"+f"(d[14]),"+f"(d[15]),"+f"(d[16]),"+f"(d[17]),"+f"(d[18]),"+f"(d[19]),"+f"(d[20]),"+f"(d[21]),"+f"(d[22]),"+f"(d[23]),
      "+f"(d[24]),"+f"(d[25]),"+f"(d[26]),"+f"(d[27]),"+f"(d[28]),"+f"(d[29]),"+f"(d[30]),"+f"(d[31])
    : "r"(alo), "r"(blo), "r"(sd), "n"(TB), "r"(DESC_HI), "n"(TA));
}
template <int TB, int TA = 0> __device__ __forceinline__ void wgmma_ss128(float (&d)[64], uint32_t alo, uint32_t blo, int sd) {
  asm volatile("{\n.reg .pred p;\n.reg .b64 da, db;\n"
    "setp.ne.b32 p, %66, 0;\nmov.b64 da, {%64, %68};\nmov.b64 db, {%65, %68};\n"
    "wgmma.mma_async.sync.aligned.m64n128k16.f32.bf16.bf16 "
    "{%0,%1,%2,%3,%4,%5,%6,%7,%8,%9,%10,%11,%12,%13,%14,%15,%16,%17,%18,%19,%20,%21,%22,%23,"
    "%24,%25,%26,%27,%28,%29,%30,%31,%32,%33,%34,%35,%36,%37,%38,%39,%40,%41,%42,%43,%44,%45,%46,%47,"
    "%48,%49,%50,%51,%52,%53,%54,%55,%56,%57,%58,%59,%60,%61,%62,%63}, "
    "da, db, p, 1, 1, %69, %67;\n}\n"
    : "+f"(d[0]),"+f"(d[1]),"+f"(d[2]),"+f"(d[3]),"+f"(d[4]),"+f"(d[5]),"+f"(d[6]),"+f"(d[7]),"+f"(d[8]),"+f"(d[9]),"+f"(d[10]),"+f"(d[11]),
      "+f"(d[12]),"+f"(d[13]),"+f"(d[14]),"+f"(d[15]),"+f"(d[16]),"+f"(d[17]),"+f"(d[18]),"+f"(d[19]),"+f"(d[20]),"+f"(d[21]),"+f"(d[22]),"+f"(d[23]),
      "+f"(d[24]),"+f"(d[25]),"+f"(d[26]),"+f"(d[27]),"+f"(d[28]),"+f"(d[29]),"+f"(d[30]),"+f"(d[31]),"+f"(d[32]),"+f"(d[33]),"+f"(d[34]),"+f"(d[35]),
      "+f"(d[36]),"+f"(d[37]),"+f"(d[38]),"+f"(d[39]),"+f"(d[40]),"+f"(d[41]),"+f"(d[42]),"+f"(d[43]),"+f"(d[44]),"+f"(d[45]),"+f"(d[46]),"+f"(d[47]),
      "+f"(d[48]),"+f"(d[49]),"+f"(d[50]),"+f"(d[51]),"+f"(d[52]),"+f"(d[53]),"+f"(d[54]),"+f"(d[55]),"+f"(d[56]),"+f"(d[57]),"+f"(d[58]),"+f"(d[59]),
      "+f"(d[60]),"+f"(d[61]),"+f"(d[62]),"+f"(d[63])
    : "r"(alo), "r"(blo), "r"(sd), "n"(TB), "r"(DESC_HI), "n"(TA));
}
template <int TB> __device__ __forceinline__ void wgmma_rs128(float (&d)[64], uint32_t a0, uint32_t a1, uint32_t a2, uint32_t a3, uint32_t blo, int sd) {
  asm volatile("{\n.reg .pred p;\n.reg .b64 db;\n"
    "setp.ne.b32 p, %69, 0;\nmov.b64 db, {%68, %71};\n"
    "wgmma.mma_async.sync.aligned.m64n128k16.f32.bf16.bf16 "
    "{%0,%1,%2,%3,%4,%5,%6,%7,%8,%9,%10,%11,%12,%13,%14,%15,%16,%17,%18,%19,%20,%21,%22,%23,"
    "%24,%25,%26,%27,%28,%29,%30,%31,%32,%33,%34,%35,%36,%37,%38,%39,%40,%41,%42,%43,%44,%45,%46,%47,"
    "%48,%49,%50,%51,%52,%53,%54,%55,%56,%57,%58,%59,%60,%61,%62,%63}, "
    "{%64,%65,%66,%67}, db, p, 1, 1, %70;\n}\n"
    : "+f"(d[0]),"+f"(d[1]),"+f"(d[2]),"+f"(d[3]),"+f"(d[4]),"+f"(d[5]),"+f"(d[6]),"+f"(d[7]),"+f"(d[8]),"+f"(d[9]),"+f"(d[10]),"+f"(d[11]),
      "+f"(d[12]),"+f"(d[13]),"+f"(d[14]),"+f"(d[15]),"+f"(d[16]),"+f"(d[17]),"+f"(d[18]),"+f"(d[19]),"+f"(d[20]),"+f"(d[21]),"+f"(d[22]),"+f"(d[23]),
      "+f"(d[24]),"+f"(d[25]),"+f"(d[26]),"+f"(d[27]),"+f"(d[28]),"+f"(d[29]),"+f"(d[30]),"+f"(d[31]),"+f"(d[32]),"+f"(d[33]),"+f"(d[34]),"+f"(d[35]),
      "+f"(d[36]),"+f"(d[37]),"+f"(d[38]),"+f"(d[39]),"+f"(d[40]),"+f"(d[41]),"+f"(d[42]),"+f"(d[43]),"+f"(d[44]),"+f"(d[45]),"+f"(d[46]),"+f"(d[47]),
      "+f"(d[48]),"+f"(d[49]),"+f"(d[50]),"+f"(d[51]),"+f"(d[52]),"+f"(d[53]),"+f"(d[54]),"+f"(d[55]),"+f"(d[56]),"+f"(d[57]),"+f"(d[58]),"+f"(d[59]),
      "+f"(d[60]),"+f"(d[61]),"+f"(d[62]),"+f"(d[63])
    : "r"(a0), "r"(a1), "r"(a2), "r"(a3), "r"(blo), "r"(sd), "n"(TB), "r"(DESC_HI));
}
template <int TB, int TA = 0> __device__ __forceinline__ void wgmma_ss192(float (&d)[96], uint32_t alo, uint32_t blo, int sd) {
  asm volatile("{\n.reg .pred p;\n.reg .b64 da, db;\n"
    "setp.ne.b32 p, %98, 0;\nmov.b64 da, {%96, %100};\nmov.b64 db, {%97, %100};\n"
    "wgmma.mma_async.sync.aligned.m64n192k16.f32.bf16.bf16 "
    "{%0,%1,%2,%3,%4,%5,%6,%7,%8,%9,%10,%11,%12,%13,%14,%15,%16,%17,%18,%19,%20,%21,%22,%23,"
    "%24,%25,%26,%27,%28,%29,%30,%31,%32,%33,%34,%35,%36,%37,%38,%39,%40,%41,%42,%43,%44,%45,%46,%47,"
    "%48,%49,%50,%51,%52,%53,%54,%55,%56,%57,%58,%59,%60,%61,%62,%63,%64,%65,%66,%67,%68,%69,%70,%71,"
    "%72,%73,%74,%75,%76,%77,%78,%79,%80,%81,%82,%83,%84,%85,%86,%87,%88,%89,%90,%91,%92,%93,%94,%95}, "
    "da, db, p, 1, 1, %101, %99;\n}\n"
    : "+f"(d[0]),"+f"(d[1]),"+f"(d[2]),"+f"(d[3]),"+f"(d[4]),"+f"(d[5]),"+f"(d[6]),"+f"(d[7]),"+f"(d[8]),"+f"(d[9]),"+f"(d[10]),"+f"(d[11]),
      "+f"(d[12]),"+f"(d[13]),"+f"(d[14]),"+f"(d[15]),"+f"(d[16]),"+f"(d[17]),"+f"(d[18]),"+f"(d[19]),"+f"(d[20]),"+f"(d[21]),"+f"(d[22]),"+f"(d[23]),
      "+f"(d[24]),"+f"(d[25]),"+f"(d[26]),"+f"(d[27]),"+f"(d[28]),"+f"(d[29]),"+f"(d[30]),"+f"(d[31]),"+f"(d[32]),"+f"(d[33]),"+f"(d[34]),"+f"(d[35]),
      "+f"(d[36]),"+f"(d[37]),"+f"(d[38]),"+f"(d[39]),"+f"(d[40]),"+f"(d[41]),"+f"(d[42]),"+f"(d[43]),"+f"(d[44]),"+f"(d[45]),"+f"(d[46]),"+f"(d[47]),
      "+f"(d[48]),"+f"(d[49]),"+f"(d[50]),"+f"(d[51]),"+f"(d[52]),"+f"(d[53]),"+f"(d[54]),"+f"(d[55]),"+f"(d[56]),"+f"(d[57]),"+f"(d[58]),"+f"(d[59]),
      "+f"(d[60]),"+f"(d[61]),"+f"(d[62]),"+f"(d[63]),"+f"(d[64]),"+f"(d[65]),"+f"(d[66]),"+f"(d[67]),"+f"(d[68]),"+f"(d[69]),"+f"(d[70]),"+f"(d[71]),
      "+f"(d[72]),"+f"(d[73]),"+f"(d[74]),"+f"(d[75]),"+f"(d[76]),"+f"(d[77]),"+f"(d[78]),"+f"(d[79]),"+f"(d[80]),"+f"(d[81]),"+f"(d[82]),"+f"(d[83]),
      "+f"(d[84]),"+f"(d[85]),"+f"(d[86]),"+f"(d[87]),"+f"(d[88]),"+f"(d[89]),"+f"(d[90]),"+f"(d[91]),"+f"(d[92]),"+f"(d[93]),"+f"(d[94]),"+f"(d[95])
    : "r"(alo), "r"(blo), "r"(sd), "n"(TB), "r"(DESC_HI), "n"(TA));
}

struct Ctx {
  uint32_t sm;
  uint32_t bar;
  uint32_t rbar;
  int cl, rank, wg, warp, lane, phases;
};
__device__ __forceinline__ void release(const Ctx& c, int b, int cnt = 1) {
  if (c.lane < 2) mbar_arrive_cl(c.rbar + b * 8, cnt);
}
#define PFM 7
#define PF1 1
constexpr float SM_SCALE = 0.08838834764831845f * 1.4426950408889634f;
constexpr float SM_HI = 1.8446744e19f, SM_LO = 5.4210109e-20f;
constexpr int ORDER = 1;

__device__ __forceinline__ void stage_tile(const float (&a)[64], uint32_t buf, const Ctx& c, float s0, float s1) {
  const int row = (c.lane & 7) + ((c.lane >> 3) & 1) * 8;
  const uint32_t base = buf + (c.warp * 16 + row) * 128 + (((c.lane >> 4) ^ (row & 7)) << 4);
#pragma unroll
  for (int i = 0; i < 8; i++)
    stsm4((base ^ ((i & 3) << 5)) + (i >> 2) * 8192, pack_bf16(a[8 * i] * s0, a[8 * i + 1] * s0), pack_bf16(a[8 * i + 2] * s1, a[8 * i + 3] * s1),
          pack_bf16(a[8 * i + 4] * s0, a[8 * i + 5] * s0), pack_bf16(a[8 * i + 6] * s1, a[8 * i + 7] * s1));
}

__device__ __forceinline__ void p1_epilogue(const Params& p, const Ctx& c, const float (&acc)[64], int t, int type) {
  const int tile = p.s.r[c.cl].tile[t] & 63, b = c.wg * 2 + 1;
  mbar_wait(c.bar + (B_SE + b) * 8, (t & 1) ^ 1);
  if (type && tile >= 32) {
    const int r = 2 * (c.lane & 3) + ((c.lane >> 2) & 1);
    const uint32_t dst = c.sm + SM_BUF + b * 16384 + r * 128 + (((c.warp * 2) ^ r) << 4) + (c.lane >> 3) * 4;
#pragma unroll
    for (int i = 0; i < 16; i++) {
      asm volatile("st.shared.u32 [%0], %1;" ::"r"(dst + i * 1024), "r"(pack_bf16(acc[4 * i], acc[4 * i + 1])) : "memory");
      asm volatile("st.shared.u32 [%0], %1;" ::"r"((dst ^ 16) + i * 1024), "r"(pack_bf16(acc[4 * i + 2], acc[4 * i + 3])) : "memory");
    }
  } else {
    if (type) stage_tile(acc, c.sm + SM_BUF + b * 16384, c, SM_SCALE, SM_SCALE);
    else stage_tile(acc, c.sm + SM_BUF + b * 16384, c, 1.f, 1.f);
  }
  FENCE_ASYNC_SMEM();
  __syncwarp();
  if (c.lane == 0) mbar_arrive(c.bar + (B_SF + b) * 8);
}

__device__ __forceinline__ void p1_consumer(const Params& p, const Ctx& c) {
  const int n = p.s.r[c.cl].n1;
  const int type = p.s.r[c.cl].slab >> 3;
  const uint32_t bdesc = desc_lo(c.sm + SM_RING, 8192), adesc = desc_lo(c.sm + SM_BUF + 32768 + c.wg * 8192, 16);
  uint32_t A[128];
  float acc[64] = {};
  int slot = 0, par = 0;
  auto next = [&]() { if (++slot == 10) { slot = 0; par ^= 1; } };
  {
    const int row = (c.lane & 7) + ((c.lane >> 3) & 1) * 8;
    const uint32_t base = c.sm + SM_RING + (c.wg * 64 + c.warp * 16 + row) * 128 + (((c.lane >> 4) ^ (row & 7)) << 4);
    if (c.wg == 1) bar_sync(ORDER + 1, 256);
    int pa = -1, pb = -1;
    if (type) {
      mbar_wait(c.bar + B_P1F * 8, 0);
      WG_FENCE();
#pragma unroll
      for (int kk = 0; kk < 4; kk++) wgmma_ss128<1>(acc, adesc + kk * 2, bdesc + kk * 128, kk != 0);
      WG_COMMIT();
      pb = 0; slot = 1;
    }
#pragma unroll
    for (int kb = 0; kb < 8; kb++) {
      const int sa = slot;
      mbar_wait(c.bar + (B_P1F + slot) * 8, par);
      if (kb == 0) PROF(c.wg, 5);
      next();
      mbar_wait(c.bar + (B_P1F + slot) * 8, par);
      PROF(c.wg, 6 + 2 * kb);
      WG_FENCE();
#pragma unroll
      for (int kk = 0; kk < 4; kk++)
        wgmma_ss128<1>(acc, desc_lo(c.sm + SM_RING + c.wg * 8192, 16) + sa * 1024 + kk * 2, bdesc + slot * 1024 + kk * 128, (kb | kk) != 0 ? 1 : type);
      WG_COMMIT();
      if (kb == 1 && c.wg == 0) bar_arrive(ORDER + 1, 256);
#pragma unroll
      for (int kk = 0; kk < 4; kk++) ldsm4((base ^ (kk << 5)) + sa * 16384, A[kb * 16 + kk * 4], A[kb * 16 + kk * 4 + 1], A[kb * 16 + kk * 4 + 2], A[kb * 16 + kk * 4 + 3]);
      WG_WAIT(1);
      if (kb > 0) release(c, B_P1E + pa);
      if (kb > 0 || pb >= 0) release(c, B_P1E + pb);
      pa = sa; pb = slot;
      next();
    }
    WG_WAIT(0);
    __syncwarp();
    release(c, B_P1E + pa);
    release(c, B_P1E + pb);
    pin(acc);
    PROF(c.wg, 1);
    p1_epilogue(p, c, acc, 0, type);
    PROF(c.wg, 2);
  }
  for (int t = 1; t < n; t++) {
    bar_sync(ORDER + c.wg, 256);
    int prev1 = -1, prev2 = -1;
    if (type) {
      mbar_wait(c.bar + (B_P1F + slot) * 8, par);
      WG_FENCE();
#pragma unroll
      for (int kk = 0; kk < 4; kk++) wgmma_ss128<1>(acc, adesc + kk * 2, bdesc + slot * 1024 + kk * 128, kk != 0);
      WG_COMMIT();
      prev1 = slot;
      next();
    }
#pragma unroll
    for (int kb = 0; kb < 8; kb++) {
      mbar_wait(c.bar + (B_P1F + slot) * 8, par);
      WG_FENCE();
      const uint32_t d = bdesc + slot * 1024;
#pragma unroll
      for (int kk = 0; kk < 4; kk++)
        wgmma_rs128<1>(acc, A[kb * 16 + kk * 4], A[kb * 16 + kk * 4 + 1], A[kb * 16 + kk * 4 + 2], A[kb * 16 + kk * 4 + 3], d + kk * 128, (kb | kk) != 0 ? 1 : type);
      WG_COMMIT();
      if (kb == 7) {
        if (t + 1 < n || c.wg == 0) bar_arrive(ORDER + (c.wg ^ 1), 256);
      }
      if (kb > 0) { WG_WAIT(2); if (kb > 1 || prev2 >= 0) release(c, B_P1E + prev2); }
      prev2 = prev1; prev1 = slot;
      next();
    }
    WG_WAIT(1);
    release(c, B_P1E + prev2);
    WG_WAIT(0);
    pin(acc);
    release(c, B_P1E + prev1);
    p1_epilogue(p, c, acc, t, type);
    PROF(c.wg, 3);
  }
}

__device__ __forceinline__ void p1_producer(const Params& p, const Ctx& c) {
  const int n = p.s.r[c.cl].n1;
  const int type = p.s.r[c.cl].slab >> 3, grp = p.s.r[c.cl].slab & 7;
  int slot = 2 - type, par = 1;
#pragma unroll 1
  for (int t = 0; t < n; t++) {
    const int tile = p.s.r[c.cl].tile[t] & 63;
    const CUtensorMap* m = &p.map_w[type * 2 + (tile >> 5)];
    const int n0 = (tile & 31) * 128 + c.rank * 64;
    const int ptile = p.s.r[c.cl].tile[t + PF1 < n ? t + PF1 : t];
    const CUtensorMap* pm = &p.map_w[type * 2 + ((ptile >> 5) & 1)];
#pragma unroll 1
    for (int kb = (t == 0) - type; kb < 8; kb++) {
      if (t == 0) {
        mbar_wait(c.bar + (B_P1E + slot) * 8, par);
        mbar_expect(c.bar + (B_P1F + slot) * 8, 16384);
        tma2d(c.sm + SM_RING + slot * 16384, &p.map_a[type], kb * 64, grp * 256 + c.rank * 128, c.bar + (B_P1F + slot) * 8);
        if (++slot == 10) { slot = 0; par ^= 1; }
      }
      mbar_wait(c.bar + (B_P1E + slot) * 8, par);
      mbar_expect(c.bar + (B_P1F + slot) * 8, 16384);
      tma2d_mc(c.sm + SM_RING + slot * 16384 + c.rank * 8192, m, n0, kb < 0 ? 512 : kb * 64, c.bar + (B_P1F + slot) * 8);
      if (t == 0 && kb == 1) PROF(2, 61);
      if (t == 0 && kb == 3) PROF(2, 62);
      if (t + PF1 < n && t > 0 && ((ptile & 64) || ((ptile & 128) && ((kb ^ grp) & PFM) == 0))) tma2d_prefetch(pm, (ptile & 31) * 128 + c.rank * 64, kb < 0 ? 512 : kb * 64);
      if (++slot == 10) { slot = 0; par ^= 1; }
    }
  }
}

__device__ __forceinline__ void p1_storer(const Params& p, const Ctx& c) {
  const int n = p.s.r[c.cl].n1;
  const int type = p.s.r[c.cl].slab >> 3, grp = p.s.r[c.cl].slab & 7;
  for (int i = 0; i < 2 * n; i++) {
    const int t = i >> 1, w = i & 1, b = w * 2 + 1;
    const int tile = p.s.r[c.cl].tile[t] & 63;
    mbar_wait(c.bar + (B_SF + b) * 8, t & 1);
    const uint32_t src = c.sm + SM_BUF + b * 16384;
    int f = (type ? F_Q : F_KV) + (tile & 31) * 8 + grp;
    if (type == 0) {
      const int prev = p.s.prev[tile & 31][grp];
      if (prev != 255 && w == 0) {
        if (grp >= 2) flag_wait<false>(F_RD + prev * 8 + grp, 8 - grp);
        else flag_wait<false>(F_CTX + max(c.lane & 7, grp) * 64 + prev, 4);
      }
      uint8_t* dst = g_KV + (size_t)(((tile & 32) + p.s.slot[tile & 31][grp]) * 16 + grp * 2 + c.rank) * 32768 + w * 8192;
      bulk_store(dst, src, 8192);
      bulk_store(dst + 16384, src + 8192, 8192);
    } else if (tile < 32) {
      bulk_store(g_Q + (size_t)(tile * 32 + grp * 4 + c.rank * 2 + w) * 16384, src, 16384);
    } else {
      tma3d_store(&p.map_t[2], src, 8 + (grp * 4 + c.rank * 2 + w) * 32, 0, (tile - 32) * 64);
      f = F_QKVA + grp * 4 + ((0xE4390900u >> (2 * (tile - 30))) & 3);
    }
    BULK_COMMIT();
    BULK_WAIT(0);
    mbar_arrive_one(c.bar + (B_SE + b) * 8);
    flag_add_rx(f);
  }
}

__device__ __forceinline__ int p2_buf(int w, int i) { return w * 2 + (i & 1); }
__device__ __forceinline__ int p2_blk(int rank, int w, int i) { return ((i ^ w) & 1) == 0 ? 3 - rank : rank; }

template <int N>
__device__ __forceinline__ void row_max(const float (&s)[N], float& m0, float& m1) {
  float a0 = fmaxf(s[0], s[1]), a1 = fmaxf(s[2], s[3]);
#pragma unroll
  for (int i = 1; i < N / 4; i++) {
    m0 = fmaxf(m0, s[4 * i]); a0 = fmaxf(a0, s[4 * i + 1]);
    m1 = fmaxf(m1, s[4 * i + 2]); a1 = fmaxf(a1, s[4 * i + 3]);
  }
  m0 = fmaxf(m0, a0); m1 = fmaxf(m1, a1);
  m0 = fmaxf(m0, __shfl_xor_sync(0xffffffffu, m0, 1));
  m1 = fmaxf(m1, __shfl_xor_sync(0xffffffffu, m1, 1));
  m0 = fmaxf(m0, __shfl_xor_sync(0xffffffffu, m0, 2));
  m1 = fmaxf(m1, __shfl_xor_sync(0xffffffffu, m1, 2));
}
template <bool SUB, int N>
__device__ __forceinline__ void row_exp(const float (&s)[N], uint32_t (&P)[32], float m0, float m1, float& t0, float& t1) {
  float u0 = 0.f, u1 = 0.f;
  t0 = t1 = 0.f;
#pragma unroll
  for (int i = 0; i < N / 4; i++) {
    const float e0 = ex2(SUB ? s[4 * i] - m0 : s[4 * i]), e1 = ex2(SUB ? s[4 * i + 1] - m0 : s[4 * i + 1]);
    const float e2 = ex2(SUB ? s[4 * i + 2] - m1 : s[4 * i + 2]), e3 = ex2(SUB ? s[4 * i + 3] - m1 : s[4 * i + 3]);
    if (i == 0) { t0 = e0; u0 = e1; t1 = e2; u1 = e3; }
    else { t0 += e0; u0 += e1; t1 += e2; u1 += e3; }
    P[2 * i] = pack_bf16(e0, e1);
    P[2 * i + 1] = pack_bf16(e2, e3);
  }
#pragma unroll
  for (int i = N / 2; i < 32; i++) P[i] = 0;
  pin(P);
  t0 += u0; t1 += u1;
}
template <int N>
__device__ __forceinline__ void causal_mask(float (&s)[N], int thr) {
#pragma unroll
  for (int i = 0; i < 8; i++) {
    if (8 * i > thr) s[N - 32 + 4 * i] = -INFINITY;
    if (8 * i + 1 > thr) s[N - 32 + 4 * i + 1] = -INFINITY;
    if (8 * i - 8 > thr) s[N - 32 + 4 * i + 2] = -INFINITY;
    if (8 * i - 7 > thr) s[N - 32 + 4 * i + 3] = -INFINITY;
  }
}
__device__ __forceinline__ void issue_qk(float (&s)[32], uint32_t qd, uint32_t kd) {
  WG_FENCE();
#pragma unroll
  for (int kk = 0; kk < 8; kk++) wgmma_ss64<0>(s, qd + (kk >> 2) * 512 + (kk & 3) * 2, kd + (kk >> 2) * 1024 + (kk & 3) * 2, kk != 0);
  WG_COMMIT();
}
__device__ __forceinline__ void issue_qk(float (&s)[64], uint32_t qd, uint32_t kd) {
  WG_FENCE();
#pragma unroll
  for (int kk = 0; kk < 8; kk++) wgmma_ss128<0>(s, qd + (kk >> 2) * 512 + (kk & 3) * 2, kd + (kk >> 2) * 1024 + (kk & 3) * 2, kk != 0);
  WG_COMMIT();
}
template <int NK>
__device__ __forceinline__ void issue_pv(float (&o)[64], const uint32_t (&P)[32], uint32_t vd, int acc) {
  WG_FENCE();
#pragma unroll
  for (int kk = 0; kk < NK; kk++) wgmma_rs128<1>(o, P[4 * kk], P[4 * kk + 1], P[4 * kk + 2], P[4 * kk + 3], vd + kk * 128, kk != 0 ? 1 : acc);
  WG_COMMIT();
}
__device__ __forceinline__ void stage_done(const Ctx& c, int b) {
  FENCE_ASYNC_SMEM();
  __syncwarp();
  if (c.lane == 0) mbar_arrive(c.bar + (B_SF + b) * 8);
}
__device__ __forceinline__ void p2_epilogue(const float (&o)[64], float s0, float s1, const Ctx& c, int b) {
  stage_tile(o, c.sm + SM_BUF + b * 16384, c, s0, s1);
  stage_done(c, b);
}

struct P2State {
  float m0, m1, l0, l1;
  bool shift;
  float e0, e1;
  float g0, g1;
  int ks;
  int wi, ai;
  uint32_t wb, ab;
  uint32_t qd;
};
#define PROFZ()
__device__ __forceinline__ int wrap5(int q) { return q >= 5 ? q - 5 : q; }
__device__ __forceinline__ void turn_wait(uint32_t ring, int i) { mbar_wait(ring + (i & 3) * 8, (i >> 2) & 1); }
__device__ __forceinline__ void turn_pass(const Ctx& c, uint32_t ring, int i) { if (c.lane == 0) mbar_arrive(ring + (i & 3) * 8); }
__device__ __forceinline__ void p2_gate(P2State& z, const Ctx& c, int row0) {
  const float* g = g_gate + row0 + c.warp * 16 + (c.lane >> 2);
  asm volatile("ld.global.cg.f32 %0, [%2];\nld.global.cg.f32 %1, [%2+32];" : "=f"(z.g0), "=f"(z.g1) : "l"(g) : "memory");
}
__device__ __forceinline__ void p2_scales(P2State& z) {
  float l0 = z.l0, l1 = z.l1;
  l0 += __shfl_xor_sync(0xffffffffu, l0, 1);
  l1 += __shfl_xor_sync(0xffffffffu, l1, 1);
  l0 += __shfl_xor_sync(0xffffffffu, l0, 2);
  l1 += __shfl_xor_sync(0xffffffffu, l1, 2);
  z.e0 = __fdividef(1.f - z.g0, l0); z.e1 = __fdividef(1.f - z.g1, l1);
}
template <int N>
__device__ __forceinline__ void p2_first(const Ctx& c, P2State& z, float (&o)[64], uint32_t (&Pc)[32], uint32_t (&Pn)[32],
                                         int ks, int vs, int cnt, int acc, int row0) {
  float s[N] = {};
  issue_qk(s, z.qd, desc_lo(c.sm + SM_RING, 16) + ks * 2048);
  if (vs >= 0) {
    p2_scales(z);
    issue_pv<8>(o, Pc, desc_lo(c.sm + SM_RING, 16384) + vs * 2048, acc);
  } else {
    WG_COMMIT();
  }
  mbar_expect(z.ab + (z.ai++ & 3) * 8, cnt == 1 ? 8192 : 0);
  PROFZ();
  WG_WAIT(1);
  PROFZ();
  pin(s);
  release(c, B_P2E + ks, cnt);
  p2_gate(z, c, row0);
  causal_mask(s, c.warp * 16 + (c.lane >> 2) - 2 * (c.lane & 3));
  z.m0 = z.m1 = 0.f;
  row_exp<false>(s, Pn, 0.f, 0.f, z.l0, z.l1);
  z.shift = __any_sync(0xffffffffu, !(z.l0 + z.l1 <= SM_HI) || ((c.lane & 3) == 0 && !(fminf(z.l0, z.l1) >= SM_LO)));
  if (__builtin_expect(z.shift, 0)) {
    z.m0 = z.m1 = -INFINITY;
    row_max(s, z.m0, z.m1);
    row_exp<true>(s, Pn, z.m0, z.m1, z.l0, z.l1);
  }
  WG_WAIT(0);
  pin(o);
  if (vs >= 0) release(c, B_P2E + vs, 1);
}

template <bool SECOND>
__device__ __forceinline__ void p2_turn(const Ctx& c, P2State& z, float (&o)[64], uint32_t (&Pc)[32], uint32_t (&Pn)[32],
                                        int eb = -1, bool half = false, int vcnt = 1) {
  float s[64] = {};
  const int ks = z.ks, vs = wrap5(ks + 1);
  PROFZ();
  turn_wait(z.wb, z.wi++);
  PROFZ();
  issue_qk(s, z.qd, desc_lo(c.sm + SM_RING, 16) + ks * 2048);
  const uint32_t vd = desc_lo(c.sm + SM_RING, 16384) + vs * 2048;
  if (SECOND) {
    if (eb >= 0) stage_tile(o, c.sm + SM_BUF + eb * 16384, c, z.e0, z.e1);
    if (half) issue_pv<4>(o, Pc, vd, 0); else issue_pv<8>(o, Pc, vd, 0);
  } else {
    issue_pv<8>(o, Pc, vd, 1);
  }
  turn_pass(c, z.ab, z.ai++);
  if (SECOND) { if (eb >= 0) stage_done(c, eb); }
  PROFZ();
  z.ks = wrap5(ks + 2);
  WG_WAIT(1);
  PROFZ();
  pin(s);
  release(c, B_P2E + ks, 1);
  float t0, t1, a0 = 1.f, a1 = 1.f;
  row_exp<false>(s, Pn, 0.f, 0.f, t0, t1);
  z.shift = __any_sync(0xffffffffu, z.shift || !(t0 + t1 <= SM_HI));
  const bool redo = z.shift;
  if (__builtin_expect(redo, 0)) {
    float n0 = z.m0, n1 = z.m1;
    row_max(s, n0, n1);
    a0 = ex2(z.m0 - n0); a1 = ex2(z.m1 - n1);
    z.m0 = n0; z.m1 = n1;
    z.l0 *= a0; z.l1 *= a1;
    row_exp<true>(s, Pn, z.m0, z.m1, t0, t1);
  }
  WG_WAIT(0);
  pin(o);
  release(c, B_P2E + vs, vcnt);
  if (__builtin_expect(redo, 0)) {
#pragma unroll
    for (int i = 0; i < 16; i++) { o[4 * i] *= a0; o[4 * i + 1] *= a0; o[4 * i + 2] *= a1; o[4 * i + 3] *= a1; }
  }
  z.l0 += t0; z.l1 += t1;
}
__device__ __forceinline__ void copy_p(uint32_t (&d)[32], const uint32_t (&s)[32], int zero) {
#pragma unroll
  for (int i = 0; i < 32; i++) asm volatile("add.s32 %0, %1, %2;" : "=r"(d[i]) : "r"(s[i]), "r"(zero));
}

__device__ __forceinline__ void p2_consumer(const Params& p, const Ctx& c, int rot) {
  const int nit = p.s.r[c.cl].n2;
  const uint32_t fring = c.bar + B_P2F * 8, oring = c.bar + B_ORD * 8;
  float o[64] = {};
  uint32_t Pa[32] = {}, Pb[32] = {};
  P2State z;
  z.e0 = z.e1 = z.l0 = z.l1 = z.g0 = z.g1 = 0.f; z.ks = rot; z.shift = false;
  int acc = 0, n = 0;
  for (int it = 0; it < nit; it++) {
    const int j = p.s.r[c.cl].item[it] & 7, blk = p2_blk(c.rank, c.wg, it), row0 = (j * 4 + blk) * 64;
    const int lng = ((it ^ c.wg) & 1) ^ 1;
    z.qd = desc_lo(c.sm + SM_BUF, 16) + p2_buf(c.wg, it) * 1024;
    if (lng) { z.wb = oring; z.wi = n - it; z.ab = fring; z.ai = n + 1; }
    else { z.wb = fring; z.wi = n + 2; z.ab = oring; z.ai = n - it; }
    PROFZ();
    mbar_wait(c.bar + (B_QF + p2_buf(c.wg, it)) * 8, (it >> 1) & 1);
    turn_wait(fring, n + 1 - lng);
    PROFZ();
    const int vs = it ? wrap5(z.ks + 1) : -1, ks = lng ? z.ks : wrap5(z.ks + (it ? 2 : 1));
    if (blk & 1) p2_first<64>(c, z, o, Pa, Pb, ks, vs, 1 + lng, acc, row0);
    else p2_first<32>(c, z, o, Pa, Pb, ks, vs, 1 + lng, acc, row0);
    z.ks = wrap5(ks + (it == 0 && lng ? 1 : 2));
    PROF(c.wg, 24 + it);
    n += 2 * j + 2;
    int left = 2 * j + lng;
    acc = left != 0;
    if (left == 0) { copy_p(Pa, Pb, p.zero); continue; }
    p2_turn<true>(c, z, o, Pb, Pa, it > 0 ? p2_buf(c.wg, it - 1) : -1, !(blk & 1), 1 + lng);
    while (--left > 0) {
      p2_turn<false>(c, z, o, Pa, Pb);
      if (--left == 0) { copy_p(Pa, Pb, p.zero); break; }
      p2_turn<false>(c, z, o, Pb, Pa);
    }
  }
  {
    if (!acc && nit > 1) p2_epilogue(o, z.e0, z.e1, c, p2_buf(c.wg, nit));
    turn_wait(z.wb, z.wi);
    issue_pv<8>(o, Pa, desc_lo(c.sm + SM_RING, 16384) + z.ks * 2048, acc);
    if (((nit - 1) ^ c.wg) & 1) turn_pass(c, z.ab, z.ai);
    p2_scales(z);
    WG_WAIT(0);
    pin(o);
    release(c, B_P2E + z.ks);
    p2_epilogue(o, z.e0, z.e1, c, p2_buf(c.wg, nit - 1));
    PROF(c.wg, 24 + nit);
  }
}

__device__ __forceinline__ void p2_load_q(const Params& p, const Ctx& c, int it, int w) {
  const int item = p.s.r[c.cl].item[it], h = item >> 3, j = item & 7, b = p2_buf(w, it);
  mbar_expect(c.bar + (B_QF + b) * 8, 16384);
  bulk_load(c.sm + SM_BUF + b * 16384, g_Q + (size_t)(h * 32 + j * 4 + p2_blk(c.rank, w, it)) * 16384, 16384, c.bar + (B_QF + b) * 8, POL(4));
}
__device__ __forceinline__ void wait_p1_free(const Ctx& c, int u1, int s) {
  mbar_wait(c.bar + (B_P1E + 2 * s) * 8, ((u1 - 1 - 2 * s) / 10) & 1);
  mbar_wait(c.bar + (B_P1E + 2 * s + 1) * 8, ((u1 - 2 - 2 * s) / 10) & 1);
}
__device__ __forceinline__ void p2_producer(const Params& p, const Ctx& c, int u1, int rot) {
  const int nit = p.s.r[c.cl].n2;
  int slot = rot, cnt = 0, par = 1, n = 0;
  const uint8_t* pv = nullptr;
  bool pl = false;
  auto load = [&](const uint8_t* src, int expect, uint32_t fb, bool last) {
    if (cnt < 5) {
      if (u1) {
        wait_p1_free(c, u1, slot);
        if (cnt == 0) p2_load_q(p, c, 0, 1);
      }
      cnt++;
    } else {
      if (slot == rot) par ^= 1;
      mbar_wait(c.bar + (B_P2E + slot) * 8, par);
    }
    if (expect) mbar_expect(fb, expect);
    bulk_load_mc(c.sm + SM_RING + slot * 32768 + c.rank * 16384, src, 16384, fb, last ? POL(5) : L2_NORMAL);
    slot = wrap5(slot + 1);
  };
  if (c.phases & 16) flag_wait<true>(F_GATE, 256);
  for (int it = 0; it < nit; it++) {
    const int item = p.s.r[c.cl].item[it], h = item >> 3, j = item & 7;
    uint32_t ready = (c.phases & 16) ? 0u : 255u;
    if (it == 0) { if (c.phases & 16) flag_wait<false>(F_Q + item, 4); mbar_wait(c.bar + B_LAD * 8, 0); p2_load_q(p, c, 0, 0); if (!u1) p2_load_q(p, c, 0, 1); }
    for (int t = 2 * j + 1; t >= 0; t--) {
      for (int n1 = 0; !((ready >> (t >> 1)) & 1); n1++) {
        int v;
        if (n1) { __nanosleep(32); if (n1 > 20000000) __trap(); }
        asm volatile("ld.relaxed.gpu.global.s32 %0, [%1];" : "=r"(v) : "l"(g_flags + F_KV + h * 8 + (c.lane & 7)) : "memory");
        ready = __ballot_sync(0xffffffffu, v >= 8);
      }
      const uint8_t* k = g_KV + (size_t)(p.s.slot[h][t >> 1] * 16 + t) * 32768 + c.rank * 16384;
      const uint32_t fb = c.bar + (B_P2F + (n & 3)) * 8;
      const bool last = (p.s.r[c.cl].last[it] >> (t >> 1)) & 1;
      load(k, pv && t != 2 * j ? 65536 : 32768, fb, last);
      if (!(t & 1) && t + 4 <= 2 * j && c.rank == 0) flag_add_rx(F_RD + h * 8 + (t >> 1) + 2);
      if (pv) load(pv, 0, t != 2 * j ? fb : c.bar + (B_ORD + ((n - 1 - it) & 3)) * 8, pl);
      pl = last;
      pv = k + (size_t)NH * 16 * 32768;
      n++;
    }
  }
  load(pv, 32768, c.bar + (B_P2F + (n & 3)) * 8, pl);
}

__device__ __forceinline__ void p2_storer(const Params& p, const Ctx& c, int sfpar) {
  const int nit = p.s.r[c.cl].n2;
  auto load_q = [&](int it, int w) {
    if (c.phases & 16) flag_wait<false>(F_Q + p.s.r[c.cl].item[it], 4);
    p2_load_q(p, c, it, w);
  };
  if (nit > 1) {
    load_q(1, 1); p2_load_q(p, c, 1, 0); }
  for (int i = 0; i < 2 * nit; i++) {
    const int it = i >> 1, w = (it ^ i ^ 1) & 1, b = p2_buf(w, it);
    const int item = p.s.r[c.cl].item[it], h = item >> 3, j = item & 7;
    mbar_wait(c.bar + (B_SF + b) * 8, (sfpar >> b) & 1);
    sfpar ^= 1 << b;
    bulk_store(g_Q + (size_t)(h * 32 + j * 4 + p2_blk(c.rank, w, it)) * 16384, c.sm + SM_BUF + b * 16384, 16384, POL(1));
    BULK_COMMIT();
    BULK_WAIT(0);
    flag_add_rx(F_CTX + j * 64 + h);
    if ((i & 1) && it + 2 < nit) { load_q(it + 2, w); p2_load_q(p, c, it + 2, w ^ 1); }
  }
  release(c, B_DONE);
}

__device__ __forceinline__ int p3_pos(int i, int x) { return i < 4 ? (i + x) & 3 : 4; }
__device__ __forceinline__ void p3_consumer(const Params& p, const Ctx& c, int x) {
  const bool first = p.s.r[c.cl].p3 >= 24;
  const int tile = p.s.r[c.cl].p3 - (first ? 24 : 0), j = tile / 3, nt = tile - 3 * j;
  const int na = first ? 9 : 0, nb = first ? 2 * p.s.nh[tile] : 64 - 2 * p.s.nh[tile];
  const uint32_t ad = desc_lo(c.sm + SM_RING + c.wg * 8192, 16), bd = desc_lo(c.sm + SM_RING + 16384, 4096);
  float acc[96] = {};
  int slot = 0, par = 0, prev = 0;
#pragma unroll 1
  for (int kb = 0; kb < na; kb++) {
    mbar_wait(c.bar + (B_P3F + slot) * 8, par);
    if (kb == 0) PROF(c.wg, 39);
    WG_FENCE();
#pragma unroll
    for (int kk = 0; kk < 4; kk++) wgmma_ss192<1, 1>(acc, ad + p3_pos(slot, x) * 2560 + kk * 128, bd + p3_pos(slot, x) * 2560 + (kk >> 1) * 768 + (kk & 1) * 128, kk != 0 ? 1 : kb != 0);
    WG_COMMIT();
    WG_WAIT(1);
    if (kb > 0) release(c, B_P3E + prev);
    prev = slot;
    if (++slot == 5) { slot = 0; par ^= 1; }
  }
#pragma unroll 1
  for (int kb = na; kb < na + nb; kb++) {
    mbar_wait(c.bar + (B_P3F + slot) * 8, par);
    if (kb == 0) PROF(c.wg, 39);
    WG_FENCE();
#pragma unroll
    for (int kk = 0; kk < 4; kk++) wgmma_ss192<1>(acc, ad + p3_pos(slot, x) * 2560 + kk * 2, bd + p3_pos(slot, x) * 2560 + (kk >> 1) * 768 + (kk & 1) * 128, kk != 0 ? 1 : kb != 0);
    WG_COMMIT();
    WG_WAIT(1);
    if (kb > 0) release(c, B_P3E + prev);
    prev = slot;
    if (++slot == 5) { slot = 0; par ^= 1; }
  }
  WG_WAIT(0);
  pin(acc);
  PROF(c.wg, 40);
  if (first) bar_sync(4 + c.wg, 128);
  mbar_wait(c.bar + B_OUT * 8, 0);
  const int row = (c.lane & 7) + ((c.lane >> 3) & 1) * 8;
  const uint32_t wbase = c.sm + SM_RING + c.wg * 8192 + c.warp * 2048;
  const uint32_t base = wbase + row * 128 + (((c.lane >> 4) ^ (row & 7)) << 4);
#pragma unroll
  for (int i = 0; i < 12; i++) {
    stsm4((base ^ ((i & 3) << 5)) + (i >> 2) * 40960, pack_bf16(acc[8 * i], acc[8 * i + 1]), pack_bf16(acc[8 * i + 2], acc[8 * i + 3]),
          pack_bf16(acc[8 * i + 4], acc[8 * i + 5]), pack_bf16(acc[8 * i + 6], acc[8 * i + 7]));
    if ((i & 3) == 3) {
      FENCE_ASYNC_SMEM();
      __syncwarp();
      const int c0 = nt * 192 + (i >> 2) * 64, c1 = j * 256 + c.rank * 128 + c.wg * 64 + c.warp * 16;
      tma2d_add(&p.map_out, wbase + (i >> 2) * 40960, c0, c1);
    }
  }
  BULK_COMMIT();
  PROF(c.wg, 43);
  BULK_WAIT_READ(0);
  PROF(c.wg, 44);
}

__device__ __forceinline__ void p3_producer(const Params& p, const Ctx& c, int u1, int u2, int rot, int x) {
  const bool first = p.s.r[c.cl].p3 >= 24;
  const int tile = p.s.r[c.cl].p3 - (first ? 24 : 0), j = tile / 3, nt = tile - 3 * j;
  int slot = 0, par = 1, cnt = 0;
  auto wait_free = [&](int s) {
    const int f = wrap5(s + 5 - rot);
    if (f < u2) mbar_wait(c.bar + (B_P2E + s) * 8, ((u2 - 1 - f) / 5) & 1);
    else if (u1) wait_p1_free(c, u1, s);
  };
  asm volatile(ELECT("prefetch.tensormap [%0];") ::"l"(&p.map_o[first]) : "memory");
  asm volatile(ELECT("prefetch.tensormap [%0];") ::"l"(&p.map_out) : "memory");
  const int q1 = first ? p.s.nh[tile] : 32;
  for (int q = first ? -1 : p.s.nh[tile]; q < q1; q++) {
    const int g = q < 0 ? 32 : p.s.p3_order[j][q];
    if (c.phases & 16) flag_wait<false>(F_CTX + j * 64 + g, q < 0 ? 16 : 4);
    const int nk = q < 0 ? 9 : 2, k0 = (q < 0 ? 0 : g * 128) + c.rank * 32;
    const uint8_t* a = q < 0 ? g_oA + (j * 4 + c.rank * 2) * 73728 : g_Q + (size_t)(g * 32 + j * 4 + c.rank * 2) * 16384;
    const CUtensorMap* m = &p.map_o[q < 0];
    for (int i = 0; i < nk; i++) {
      const uint32_t st = c.sm + SM_RING + p3_pos(slot, x) * 40960, fb = c.bar + (B_P3F + slot) * 8;
      if (cnt < 4) { wait_free(p3_pos(cnt, x)); wait_free(p3_pos(cnt, x) + 1); }
      else if (cnt == 4) mbar_wait(c.bar + B_DONE * 8, 0);
      else mbar_wait(c.bar + (B_P3E + slot) * 8, par);
      cnt++;
      mbar_expect(fb, 40960);
      bulk_load(st, a + i * 8192, 8192, fb, POL(3));
      bulk_load(st + 8192, a + (nk + i) * 8192, 8192, fb, POL(3));
      tma3d_mc(st + 16384 + c.rank * 12288, m, 0, k0 + i * 64, nt * 3, fb);
      if (++slot == 5) { slot = 0; par ^= 1; }
    }
  }
}

__device__ __forceinline__ float bf_lo(uint32_t w) { return __uint_as_float(w << 16); }
__device__ __forceinline__ float bf_hi(uint32_t w) { return __uint_as_float(w & 0xffff0000u); }

__device__ __forceinline__ void gate_rows(const Params& p, int row0, int lane) {
  const uint4* x = reinterpret_cast<const uint4*>(p.x + (size_t)(row0 + (lane >> 2)) * DM) + (lane & 3);
  const uint4* w = reinterpret_cast<const uint4*>(p.gate_w) + (lane & 3);
  float a = 0.f;
#pragma unroll 1
  for (int b = 0; b < 3; b++) {
    uint4 u[6];
#pragma unroll
    for (int i = 0; i < 6; i++) u[i] = __ldg(x + (b * 6 + i) * 4);
#pragma unroll
    for (int i = 0; i < 6; i++) {
      const uint4 v = __ldg(w + (b * 6 + i) * 4);
      a = fmaf(bf_lo(u[i].x), bf_lo(v.x), a); a = fmaf(bf_hi(u[i].x), bf_hi(v.x), a);
      a = fmaf(bf_lo(u[i].y), bf_lo(v.y), a); a = fmaf(bf_hi(u[i].y), bf_hi(v.y), a);
      a = fmaf(bf_lo(u[i].z), bf_lo(v.z), a); a = fmaf(bf_hi(u[i].z), bf_hi(v.z), a);
      a = fmaf(bf_lo(u[i].w), bf_lo(v.w), a); a = fmaf(bf_hi(u[i].w), bf_hi(v.w), a);
    }
  }
  a += __shfl_xor_sync(0xffffffffu, a, 1);
  a += __shfl_xor_sync(0xffffffffu, a, 2);
  if ((lane & 3) == 0) g_gate[row0 + (lane >> 2)] = 1.f / (1.f + __expf(-a));
}

__device__ __forceinline__ void lds10(uint32_t (&k)[10], uint32_t a) {
  asm volatile("ld.shared.v2.u32 {%0, %1}, [%10];\nld.shared.v2.u32 {%2, %3}, [%10+8];\nld.shared.v2.u32 {%4, %5}, [%10+16];\n"
               "ld.shared.v2.u32 {%6, %7}, [%10+24];\nld.shared.v2.u32 {%8, %9}, [%10+32];"
               : "=r"(k[0]), "=r"(k[1]), "=r"(k[2]), "=r"(k[3]), "=r"(k[4]), "=r"(k[5]), "=r"(k[6]), "=r"(k[7]), "=r"(k[8]), "=r"(k[9]) : "r"(a));
}
__device__ __forceinline__ void local_attn(const Params& p, const Ctx& c, int rb, int hs) {
  const int lane = c.lane, grp = rb >> 2, par = lane >> 4, i0 = 2 * (lane & 15);
  const uint32_t buf = c.sm + SM_BUF + (c.warp - 2) * 8192, bqk = c.bar + (B_LA + (c.warp - 2) * 2) * 8, bv = bqk + 8;
  const uint32_t mine = buf + 2304 + par * 160 + i0 * 4;
  const bool flags = c.phases & 16;
  auto fetch_qk = [&](int i) {
    if (flags && !(i & 1)) {
      const int q = i >> 1;
      const int tgt = q == 0 ? 24 : q == 3 ? 8 : 12;
      flag_wait<false>(F_QKVA + (grp - (grp > 0 && (rb & 3) == 0 ? par : 0)) * 4 + q, tgt);
    }
    mbar_expect(bqk, 5184);
    tma3d(buf, &p.map_t[0], rb * 32 + 8, 0, 9 * (4 * i + hs), bqk, POL(2));
    tma3d(buf + 2304, &p.map_t[1], rb * 32, 0, 288 + 9 * (4 * i + hs), bqk, POL(2));
  };
  auto fetch_v = [&](int i) { mbar_expect(bv, 2880); tma3d(buf + 5248, &p.map_t[1], rb * 32, 0, 576 + 9 * (4 * i + hs), bv, POL(2)); };
  fetch_qk(0);
  if (flags) flag_wait<true>(F_GATE, 256);
#pragma unroll 1
  for (int q = 0; q < 8; q++) {
    fetch_v(q);
    float a[8], b[8];
#pragma unroll
    for (int w = 0; w < 8; w++) a[w] = b[w] = 0.f;
    mbar_wait(bqk, q & 1);
    PROFB(1 + 2 * q);
#pragma unroll 1
    for (int j = 0; j < 9; j++) {
      uint32_t x, y, k[10];
      asm volatile("ld.shared.v2.u32 {%0, %1}, [%2];" : "=r"(x), "=r"(y) : "r"(buf + lane * 8 + j * 256));
      lds10(k, mine + j * 320);
      const float xl = bf_lo(x), xh = bf_hi(x), yl = bf_lo(y), yh = bf_hi(y);
#pragma unroll
      for (int m = 1; m < 10; m++) {
        const float kl = bf_lo(k[m]), kh = bf_hi(k[m]);
        if (m < 9) a[8 - m] = fmaf(xl, kl, fmaf(xh, kh, a[8 - m]));
        if (m > 1) b[9 - m] = fmaf(yl, kl, fmaf(yh, kh, b[9 - m]));
      }
    }
    __syncwarp();
    if (q < 7) fetch_qk(q + 1);
    constexpr float SC = 0.23570226039551584f * 1.4426950408889634f;
    const float* gp = g_gate + rb * 64 + 2 * i0 + par;
    const float ga = __ldcg(gp), gb = __ldcg(gp + 2);
    float ma = a[0], mb = b[0];
#pragma unroll
    for (int w = 1; w < 8; w++) {
      if (rb == 0) {
        if (i0 < w) a[w] = -INFINITY;
        if (i0 + 1 < w) b[w] = -INFINITY;
      }
      ma = fmaxf(ma, a[w]); mb = fmaxf(mb, b[w]);
    }
    float la = 0.f, lb = 0.f;
#pragma unroll
    for (int w = 0; w < 8; w++) {
      a[w] = ex2((a[w] - ma) * SC); b[w] = ex2((b[w] - mb) * SC);
      la += a[w]; lb += b[w];
    }
    la = __fdividef(ga, la); lb = __fdividef(gb, lb);
#pragma unroll
    for (int w = 0; w < 8; w++) { a[w] *= la; b[w] *= lb; }
    uint8_t* dst = g_oA + rb * 73728 + ((i0 & 2) + par) * 4;
    mbar_wait(bv, q & 1);
#pragma unroll 1
    for (int j = 0; j < 9; j++) {
      uint32_t v[10];
      lds10(v, mine + 2944 + j * 320);
      float a0 = 0.f, a1 = 0.f, b0 = 0.f, b1 = 0.f;
#pragma unroll
      for (int m = 1; m < 10; m++) {
        const float vl = bf_lo(v[m]), vh = bf_hi(v[m]);
        if (m < 9) { a0 = fmaf(a[8 - m], vl, a0); a1 = fmaf(a[8 - m], vh, a1); }
        if (m > 1) { b0 = fmaf(b[9 - m], vl, b0); b1 = fmaf(b[9 - m], vh, b1); }
      }
      const uint32_t wa = pack_bf16(a0, a1), wb = pack_bf16(b0, b1);
      const uint32_t got = __shfl_xor_sync(0xffffffffu, par ? wa : wb, 16);
      const uint32_t r0 = par ? got : wa, r1 = par ? wb : got;
      const int col = 18 * (4 * q + hs) + 2 * j, o = col * 128 + ((((i0 >> 2) ^ col) & 7) << 4);
      *reinterpret_cast<uint32_t*>(dst + o) = __byte_perm(r0, r1, 0x5410);
      *reinterpret_cast<uint32_t*>(dst + ((o + 128) ^ 16)) = __byte_perm(r0, r1, 0x7632);
    }
    __syncwarp();
    PROFB(2 + 2 * q);
  }
  mbar_arrive_one(c.bar + B_LAD * 8);
  flag_add(F_CTX + grp * 64 + 32);
}

__global__ void __cluster_dims__(2, 1, 1) __launch_bounds__(384, 1) fused_kernel(const __grid_constant__ Params p) {
  extern __shared__ uint8_t smem_raw[];
  Ctx c;
  c.sm = ((uint32_t)__cvta_generic_to_shared(smem_raw) + 1023u) & ~1023u;
  c.bar = c.sm + SM_BAR;
  c.lane = threadIdx.x & 31;
  const int wid = __shfl_sync(0xffffffffu, threadIdx.x >> 5, 0);
  if (wid < 6) asm volatile("prefetch.tensormap [%0];" ::"l"(&p.map_a[0] + wid) : "memory");
  c.wg = wid >> 2;
  c.warp = wid & 3;
  PROF(c.wg, 0);
  PROFG(61);
  c.cl = (blockIdx.x + (wid >> 4)) >> 1;
  c.rank = blockIdx.x & 1;
  c.rbar = mapa(c.bar, c.lane & 1);
  {
    const int w = wid, cnt = (((int)(B_CNT >> (4 * w)) - 1) & 15) + 1;
    if (w < 11) {
#pragma unroll
      for (int i = 0; i < 8; i++) asm volatile("mbarrier.init.shared::cta.b64 [%0], %1;" ::"r"(c.bar + w * 64 + i * 8), "r"(cnt));
    }
    asm volatile("fence.mbarrier_init.release.cluster;" ::: "memory");
  }
  if (c.wg == 2) PROF(2, 56);
  asm volatile("barrier.cluster.arrive.relaxed;" ::: "memory");
  c.phases = p.s.r[c.cl].phases;
  const bool do1 = p.s.r[c.cl].n1 > 0, do2 = p.s.r[c.cl].n2 > 0, do3 = p.s.r[c.cl].p3 != 255;
  if (do1 && c.wg == 2 && c.warp == 0) {
    const int type = p.s.r[c.cl].slab >> 3;
    PROF(2, 57);
    FENCE_ASYNC_SMEM();
    mbar_expect(c.bar + B_P1F * 8, type ? 32768 : 16384);
    tma2d(type ? c.sm + SM_BUF + 32768 : c.sm + SM_RING, &p.map_a[type], type ? 512 : 0, (p.s.r[c.cl].slab & 7) * 256 + c.rank * 128, c.bar + B_P1F * 8);
    PROF(2, 58);
  }
  asm volatile("barrier.cluster.wait.acquire;" ::: "memory");
  if (c.wg == 2) PROF(2, 59);
  if (do1 && c.wg == 2 && c.warp == 0) {
    const int type = p.s.r[c.cl].slab >> 3, tile = p.s.r[c.cl].tile[0] & 63;
    if (!type) mbar_expect(c.bar + (B_P1F + 1) * 8, 16384);
    tma2d_mc(c.sm + SM_RING + (1 - type) * 16384 + c.rank * 8192, &p.map_w[type * 2 + (tile >> 5)], (tile & 31) * 128 + c.rank * 64, type ? 512 : 0, c.bar + (B_P1F + 1 - type) * 8);
  }

  if (c.wg < 2) {
    PROF(c.wg, 4);
    asm volatile("setmaxnreg.inc.sync.aligned.u32 224;");
    if (c.wg == 1) {
      if (do1) bar_arrive(ORDER, 256);
      if (c.lane == 0) mbar_arrive(c.bar + B_P2F * 8);
    }
    if (do1) p1_consumer(p, c);
    if (do2) p2_consumer(p, c, p.s.r[c.cl].rot);
    if (do3) p3_consumer(p, c, p.s.r[c.cl].x3);
    PROF(c.wg, 63);
    PROFG(62);
    if (c.lane == 0) mbar_arrive(c.bar + B_FIN * 8);
    __syncwarp();
    cluster_sync();
  } else {
    asm volatile("setmaxnreg.dec.sync.aligned.u32 56;");
    if (c.warp == 0) {
      PROF(2, 60);
      if (do1) p1_producer(p, c);
      if (do2) p2_producer(p, c, p.s.r[c.cl].u1, p.s.r[c.cl].rot);
      if (do3) p3_producer(p, c, p.s.r[c.cl].u1, p.s.r[c.cl].u2, p.s.r[c.cl].rot, p.s.r[c.cl].x3);
    } else if (c.warp == 1) {
      int sfpar = 0;
      if (do1) {
        p1_storer(p, c);
        sfpar = (p.s.r[c.cl].n1 & 1) * 10;
      }
      if (do2) p2_storer(p, c, sfpar);
      else { mbar_wait(c.bar + B_LAD * 8, 0); release(c, B_DONE); }
      if (do3) {
        const int task = p.s.r[c.cl].p3;
        if (task >= 24) {
          const int j = (task - 24) / 3, nt = task - 24 - 3 * j;
          uint4* o = reinterpret_cast<uint4*>(p.out + (size_t)(j * 256 + c.rank * 128 + (c.lane >> 3)) * DM + nt * 192) + (c.lane & 7);
#pragma unroll 4
          for (int r = 0; r < 32; r++) o[r * 288] = o[r * 288 + 8] = o[r * 288 + 16] = make_uint4(0u, 0u, 0u, 0u);
          __syncwarp();
          flag_add(F_OUT + (task - 24) * 2 + c.rank);
        } else if (c.phases & 16) {
          flag_wait<false, 256>(F_OUT + task * 2 + c.rank, 1);
        }
        mbar_arrive_one(c.bar + B_OUT * 8);
      }
    } else {
      const int bw = blockIdx.x * 2 + (c.warp - 2);
      if ((c.phases & 1) && bw < 256) {
        gate_rows(p, bw * 8, c.lane);
        __syncwarp();
        flag_add(F_GATE);
      }
      if (p.s.r[c.cl].bg != 255) local_attn(p, c, p.s.r[c.cl].bg, bw & 3);
      else if (c.lane == 0) mbar_arrive(c.bar + B_LAD * 8);
    }
    __syncwarp();
    bar_sync(3, 128);
    if (c.warp == 0 && (c.phases & 4)) {
      int last = 0;
      if (c.lane == 0) { __threadfence(); last = atomicAdd(g_flags + F_DONE, 1) == 2 * NCL - 1; }
      if (__shfl_sync(0xffffffffu, last, 0)) for (int i = c.lane; i < F_NUM; i += 32) g_flags[i] = 0;
    }
    if (c.warp == 1) mbar_wait(c.bar + B_FIN * 8, 0);
    __syncwarp();
    cluster_sync();
  }
}

static const Sched k_sched = {
  {{0,30,1,47,0,{176,0,0,0,0,0,0,0,0,0,0},{0,0,0,0,0,0,0,0,0,0,0},{67,40,7,50,6,5,9,2,1,14,10,20,11,13,24,30,23,15,16,27,17,12,25,29,22,26,31,21,28,19}},
   {1,30,1,42,1,{251,0,0,0,0,0,0,0,0,0,0},{15,0,0,0,0,0,0,0,0,0,0},{67,40,18,32,5,6,9,2,1,14,10,20,11,13,24,30,23,15,16,27,17,12,25,29,22,26,31,28,21,19}},
   {2,30,2,29,2,{224,226,0,0,0,0,0,0,0,0,0},{0,0,0,0,0,0,0,0,0,0,0},{71,50,8,35,5,6,9,2,1,14,10,20,11,24,13,30,15,23,17,16,27,12,25,29,22,26,31,28,21,19}},
   {3,30,1,255,3,{228,0,0,0,0,0,0,0,0,0,0},{31,0,0,0,0,0,0,0,0,0,0},{71,50,3,40,5,6,9,2,1,14,10,11,20,13,30,15,24,23,17,16,27,12,25,29,22,26,31,28,21,19}},
   {4,29,1,255,4,{229,0,0,0,0,0,0,0,0,0,0},{32,0,0,0,0,0,0,0,0,0,0},{82,32,4,35,6,9,1,2,14,10,11,20,13,30,15,24,23,16,17,27,12,25,29,26,22,31,28,21,19,0}},
   {5,28,0,10,5,{0,0,0,0,0,0,0,0,0,0,0},{0,0,0,0,0,0,0,0,0,0,0},{72,100,18,39,6,9,33,14,10,11,20,13,15,30,24,23,17,27,16,12,25,29,26,22,31,28,21,19,0,0}},
   {6,27,0,2,6,{0,0,0,0,0,0,0,0,0,0,0},{0,0,0,0,0,0,0,0,0,0,0},{82,0,4,35,5,2,33,10,11,20,13,15,24,30,23,17,27,16,12,25,26,29,22,31,28,21,19,0,0,0}},
   {7,26,1,24,7,{212,0,0,0,0,0,0,0,0,0,0},{0,0,0,0,0,0,0,0,0,0,0},{64,7,3,70,73,78,74,75,84,77,79,88,94,87,81,91,80,76,89,90,93,86,95,92,85,83,0,0,0,0}},
   {0,30,1,43,8,{209,0,0,0,0,0,0,0,0,0,0},{0,0,0,0,0,0,0,0,0,0,0},{99,0,39,4,38,37,41,34,33,46,42,52,43,45,56,62,55,47,48,59,49,44,57,61,54,58,63,53,60,51}},
   {1,30,1,255,9,{172,0,0,0,0,0,0,0,0,0,0},{0,0,0,0,0,0,0,0,0,0,0},{99,7,50,4,37,38,41,34,33,46,42,52,43,45,56,62,55,47,48,59,49,44,57,61,54,58,63,60,53,51}},
   {2,30,2,31,10,{168,152,0,0,0,0,0,0,0,0,0},{0,0,0,0,0,0,0,0,0,0,0},{103,0,40,4,37,38,41,34,33,46,42,52,43,56,45,62,47,55,49,48,59,44,57,61,54,58,63,60,53,51}},
   {3,30,2,255,11,{208,227,0,0,0,0,0,0,0,0,0},{0,0,0,0,0,0,0,0,0,0,0},{103,0,35,4,37,38,41,34,33,46,42,43,52,45,62,47,56,55,49,48,59,44,57,61,54,58,63,60,53,51}},
   {4,29,1,34,12,{249,0,0,0,0,0,0,0,0,0,0},{0,0,0,0,0,0,0,0,0,0,0},{114,8,36,7,38,41,33,34,46,42,43,52,45,62,47,56,55,48,49,59,44,57,61,58,54,63,60,53,51,0}},
   {5,28,0,3,13,{0,0,0,0,0,0,0,0,0,0,0},{0,0,0,0,0,0,0,0,0,0,0},{104,3,50,0,38,41,2,46,42,43,52,45,47,62,56,55,49,59,48,44,57,61,58,54,63,60,53,51,0,0}},
   {6,27,0,19,14,{0,0,0,0,0,0,0,0,0,0,0},{0,0,0,0,0,0,0,0,0,0,0},{114,32,36,70,37,34,14,42,43,52,45,47,56,62,55,49,59,48,44,57,58,61,54,63,60,53,51,0,0,0}},
   {7,26,1,7,15,{184,0,0,0,0,0,0,0,0,0,0},{1,0,0,0,0,0,0,0,0,0,0},{96,39,35,102,105,110,106,107,116,109,111,120,126,119,113,123,112,108,121,122,125,118,127,124,117,115,0,0,0,0}},
   {0,4,7,37,255,{0,149,44,161,107,141,211,0,0,0,0},{0,0,0,0,0,0,0,0,0,0,0},{72,32,18,36,0,0,0,0,0,0,0,0,0,0,0,0,0,0,0,0,0,0,0,0,0,0,0,0,0,0}},
   {1,4,4,15,255,{62,52,166,139,0,0,0,0,0,0,0},{0,0,0,0,0,0,0,0,0,0,0},{72,39,0,36,0,0,0,0,0,0,0,0,0,0,0,0,0,0,0,0,0,0,0,0,0,0,0,0,0,0}},
   {2,4,6,30,255,{146,67,13,165,101,178,0,0,0,0,0},{0,0,0,0,0,0,0,0,0,0,0},{82,32,3,36,0,0,0,0,0,0,0,0,0,0,0,0,0,0,0,0,0,0,0,0,0,0,0,0,0,0}},
   {3,4,4,4,255,{151,118,143,232,0,0,0,0,0,0,0},{162,0,0,0,0,0,0,0,0,0,0},{82,32,8,36,0,0,0,0,0,0,0,0,0,0,0,0,0,0,0,0,0,0,0,0,0,0,0,0,0,0}},
   {4,6,7,36,255,{48,28,49,94,122,131,213,0,0,0,0},{0,0,0,0,0,0,63,0,0,0,0},{64,40,3,39,5,37,0,0,0,0,0,0,0,0,0,0,0,0,0,0,0,0,0,0,0,0,0,0,0,0}},
   {5,8,5,23,255,{36,18,10,90,222,0,0,0,0,0,0},{0,0,0,0,3,0,0,0,0,0,0},{68,35,7,32,5,37,1,34,0,0,0,0,0,0,0,0,0,0,0,0,0,0,0,0,0,0,0,0,0,0}},
   {6,8,5,32,255,{54,85,186,130,204,0,0,0,0,0,0},{0,0,0,0,0,0,0,0,0,0,0},{71,8,3,102,73,41,1,46,0,0,0,0,0,0,0,0,0,0,0,0,0,0,0,0,0,0,0,0,0,0}},
   {7,6,8,255,255,{144,55,81,114,108,99,252,154,0,0,0},{0,0,0,0,0,0,0,0,0,0,0},{72,18,4,69,66,65,0,0,0,0,0,0,0,0,0,0,0,0,0,0,0,0,0,0,0,0,0,0,0,0}},
   {8,21,1,5,16,{192,0,0,0,0,0,0,0,0,0,0},{0,0,0,0,0,0,0,0,0,0,0},{160,170,4,38,39,104,9,14,2,11,20,13,15,12,23,17,28,22,26,19,31,0,0,0,0,0,0,0,0,0}},
   {9,20,1,6,17,{220,0,0,0,0,0,0,0,0,0,0},{0,0,0,0,0,0,0,0,0,0,0},{67,37,0,163,6,104,1,10,20,13,30,11,27,17,12,22,26,28,21,19,0,0,0,0,0,0,0,0,0,0}},
   {10,18,4,255,18,{240,243,97,175,0,0,0,0,0,0,0},{0,0,0,192,0,0,0,0,0,0,0},{160,170,162,4,9,104,1,14,88,94,23,81,27,153,22,159,21,83,0,0,0,0,0,0,0,0,0,0,0,0}},
   {11,16,4,17,19,{40,185,123,216,0,0,0,0,0,0,0},{0,0,0,0,0,0,0,0,0,0,0},{160,170,162,5,6,104,1,10,77,24,30,81,27,153,29,159,0,0,0,0,0,0,0,0,0,0,0,0,0,0}},
   {12,18,4,8,20,{104,193,98,233,0,0,0,0,0,0,0},{0,0,0,0,0,0,0,0,0,0,0},{160,170,162,163,9,2,45,10,11,94,24,16,27,93,26,159,28,83,0,0,0,0,0,0,0,0,0,0,0,0}},
   {13,18,2,255,21,{102,159,0,0,0,0,0,0,0,0,0},{0,128,0,0,0,0,0,0,0,0,0},{160,170,7,6,65,9,40,10,20,79,24,81,27,153,22,159,21,83,0,0,0,0,0,0,0,0,0,0,0,0}},
   {14,18,2,16,22,{160,187,0,0,0,0,0,0,0,0,0},{0,0,0,0,0,0,0,0,0,0,0},{160,170,4,6,9,1,74,40,20,79,30,81,16,153,26,159,21,83,0,0,0,0,0,0,0,0,0,0,0,0}},
   {15,18,2,21,23,{128,133,0,0,0,0,0,0,0,0,0},{0,0,0,0,0,0,0,0,0,0,0},{160,170,3,43,39,1,74,40,20,79,30,81,16,153,29,159,21,83,0,0,0,0,0,0,0,0,0,0,0,0}},
   {8,16,3,18,24,{8,244,120,0,0,0,0,0,0,0,0},{1,0,0,0,0,0,0,0,0,0,0},{164,136,18,43,44,109,1,5,10,94,80,24,27,153,29,85,0,0,0,0,0,0,0,0,0,0,0,0,0,0}},
   {9,16,3,0,25,{112,223,136,0,0,0,0,0,0,0,0},{0,0,0,0,0,0,0,0,0,0,0},{160,170,162,103,5,109,14,9,2,87,15,16,24,153,29,159,0,0,0,0,0,0,0,0,0,0,0,0,0,0}},
   {10,16,5,255,26,{80,241,217,219,231,0,0,0,0,0,0},{0,0,0,0,192,0,0,0,0,0,0},{164,71,166,6,2,109,74,84,11,79,13,16,12,93,26,92,0,0,0,0,0,0,0,0,0,0,0,0,0,0}},
   {11,18,3,255,27,{188,203,173,0,0,0,0,0,0,0,0},{0,0,63,0,0,0,0,0,0,0,0},{164,71,166,163,2,109,14,11,20,79,23,16,12,86,26,85,28,83,0,0,0,0,0,0,0,0,0,0,0,0}},
   {12,16,4,255,28,{125,202,235,171,0,0,0,0,0,0,0},{0,0,0,0,0,0,0,0,0,0,0},{164,146,166,103,78,104,1,84,77,79,23,81,12,153,22,85,0,0,0,0,0,0,0,0,0,0,0,0,0,0}},
   {13,16,5,38,29,{72,121,129,100,230,0,0,0,0,0,0},{1,0,0,0,0,0,0,0,0,0,0},{164,136,0,5,2,14,45,11,77,94,23,16,12,93,26,92,0,0,0,0,0,0,0,0,0,0,0,0,0,0}},
   {14,16,3,26,30,{88,190,181,0,0,0,0,0,0,0,0},{0,0,0,0,0,0,0,0,0,0,0},{164,146,3,5,2,14,75,45,77,24,23,76,27,93,22,92,0,0,0,0,0,0,0,0,0,0,0,0,0,0}},
   {15,16,6,255,31,{16,242,138,201,179,156,0,0,0,0,0},{1,0,0,0,0,31,0,0,0,0,0},{164,64,4,5,44,14,75,45,77,24,23,91,12,90,22,92,0,0,0,0,0,0,0,0,0,0,0,0,0,0}},
   {8,2,5,14,255,{145,1,42,78,110,0,0,0,0,0,0},{0,0,0,0,0,0,0,0,0,0,0},{169,64,0,0,0,0,0,0,0,0,0,0,0,0,0,0,0,0,0,0,0,0,0,0,0,0,0,0,0,0}},
   {9,4,7,27,255,{64,61,74,9,82,126,205,0,0,0,0},{0,0,0,0,0,127,63,0,0,0,0},{164,136,166,108,0,0,0,0,0,0,0,0,0,0,0,0,0,0,0,0,0,0,0,0,0,0,0,0,0,0}},
   {10,4,7,255,255,{65,2,79,162,197,234,174,0,0,0,0},{0,0,0,0,0,0,0,0,0,0,0},{169,146,107,163,0,0,0,0,0,0,0,0,0,0,0,0,0,0,0,0,0,0,0,0,0,0,0,0,0,0}},
   {11,4,6,35,255,{6,77,83,195,137,180,0,0,0,0,0},{0,0,0,0,0,0,0,0,0,0,0},{169,146,107,103,0,0,0,0,0,0,0,0,0,0,0,0,0,0,0,0,0,0,0,0,0,0,0,0,0,0}},
   {12,4,6,255,255,{3,33,45,111,215,155,0,0,0,0,0},{0,0,0,0,128,0,0,0,0,0,0},{169,64,107,108,0,0,0,0,0,0,0,0,0,0,0,0,0,0,0,0,0,0,0,0,0,0,0,0,0,0}},
   {13,4,8,255,255,{29,50,20,194,142,177,210,170,0,0,0},{0,0,0,0,68,0,0,0,0,0,0},{169,68,162,163,0,0,0,0,0,0,0,0,0,0,0,0,0,0,0,0,0,0,0,0,0,0,0,0,0,0}},
   {14,4,6,12,255,{37,43,113,84,106,218,0,0,0,0,0},{0,0,0,0,0,0,0,0,0,0,0},{169,71,162,163,0,0,0,0,0,0,0,0,0,0,0,0,0,0,0,0,0,0,0,0,0,0,0,0,0,0}},
   {15,4,4,45,255,{7,117,109,239,0,0,0,0,0,0,0},{46,0,0,255,0,0,0,0,0,0,0},{169,136,70,73,0,0,0,0,0,0,0,0,0,0,0,0,0,0,0,0,0,0,0,0,0,0,0,0,0,0}},
   {8,4,5,255,255,{147,47,164,103,158,0,0,0,0,0,0},{0,128,0,3,96,0,0,0,0,0,0},{161,3,70,163,0,0,0,0,0,0,0,0,0,0,0,0,0,0,0,0,0,0,0,0,0,0,0,0,0,0}},
   {9,3,4,22,255,{31,95,89,132,0,0,0,0,0,0,0},{220,0,0,0,0,0,0,0,0,0,0},{169,71,107,0,0,0,0,0,0,0,0,0,0,0,0,0,0,0,0,0,0,0,0,0,0,0,0,0,0,0}},
   {10,4,4,11,255,{39,116,91,134,0,0,0,0,0,0,0},{192,0,0,0,0,0,0,0,0,0,0},{161,64,69,103,0,0,0,0,0,0,0,0,0,0,0,0,0,0,0,0,0,0,0,0,0,0,0,0,0,0}},
   {11,4,5,25,255,{4,35,86,189,182,0,0,0,0,0,0},{0,0,0,0,127,0,0,0,0,0,0},{161,64,8,108,0,0,0,0,0,0,0,0,0,0,0,0,0,0,0,0,0,0,0,0,0,0,0,0,0,0}},
   {12,4,6,46,255,{24,27,53,11,198,214,0,0,0,0,0},{0,0,0,0,0,64,0,0,0,0,0},{161,136,7,5,0,0,0,0,0,0,0,0,0,0,0,0,0,0,0,0,0,0,0,0,0,0,0,0,0,0}},
   {13,4,4,40,255,{70,15,191,254,0,0,0,0,0,0,0},{0,0,130,112,0,0,0,0,0,0,0},{161,3,166,103,0,0,0,0,0,0,0,0,0,0,0,0,0,0,0,0,0,0,0,0,0,0,0,0,0,0}},
   {14,4,6,255,255,{148,46,17,199,255,153,0,0,0,0,0},{0,0,0,255,128,0,0,0,0,0,0},{161,64,166,103,0,0,0,0,0,0,0,0,0,0,0,0,0,0,0,0,0,0,0,0,0,0,0,0,0,0}},
   {15,4,6,255,255,{56,30,87,124,236,157,0,0,0,0,0},{0,0,0,0,0,0,0,0,0,0,0},{161,71,162,66,0,0,0,0,0,0,0,0,0,0,0,0,0,0,0,0,0,0,0,0,0,0,0,0,0,0}},
   {8,3,4,44,255,{71,76,127,238,0,0,0,0,0,0,0},{92,0,0,127,0,0,0,0,0,0,0},{165,71,162,0,0,0,0,0,0,0,0,0,0,0,0,0,0,0,0,0,0,0,0,0,0,0,0,0,0,0}},
   {9,3,7,41,255,{59,26,21,93,206,250,248,0,0,0,0},{0,0,0,0,0,0,0,0,0,0,0},{161,146,4,0,0,0,0,0,0,0,0,0,0,0,0,0,0,0,0,0,0,0,0,0,0,0,0,0,0,0}},
   {10,4,4,1,255,{38,119,246,96,0,0,0,0,0,0,0},{0,0,0,0,0,0,0,0,0,0,0},{165,136,3,108,0,0,0,0,0,0,0,0,0,0,0,0,0,0,0,0,0,0,0,0,0,0,0,0,0,0}},
   {11,4,6,39,255,{57,66,34,22,245,183,0,0,0,0,0},{0,0,0,0,0,128,0,0,0,0,0},{165,3,4,73,0,0,0,0,0,0,0,0,0,0,0,0,0,0,0,0,0,0,0,0,0,0,0,0,0,0}},
   {12,4,6,28,255,{63,41,12,105,196,237,0,0,0,0,0},{50,0,0,0,0,0,0,0,0,0,0},{165,3,4,6,0,0,0,0,0,0,0,0,0,0,0,0,0,0,0,0,0,0,0,0,0,0,0,0,0,0}},
   {13,4,4,9,255,{69,23,247,200,0,0,0,0,0,0,0},{0,0,0,0,0,0,0,0,0,0,0},{165,146,107,108,0,0,0,0,0,0,0,0,0,0,0,0,0,0,0,0,0,0,0,0,0,0,0,0,0,0}},
   {14,4,5,33,255,{150,75,167,207,225,0,0,0,0,0,0},{0,0,0,0,0,0,0,0,0,0,0},{165,136,107,108,0,0,0,0,0,0,0,0,0,0,0,0,0,0,0,0,0,0,0,0,0,0,0,0,0,0}},
   {15,4,5,20,255,{58,60,19,115,135,0,0,0,0,0,0},{0,0,0,0,0,0,0,0,0,0,0},{165,146,166,163,0,0,0,0,0,0,0,0,0,0,0,0,0,0,0,0,0,0,0,0,0,0,0,0,0,0}},
   {6,2,7,255,255,{25,5,14,163,140,253,169,0,0,0,0},{0,0,0,0,0,0,0,0,0,0,0},{103,40,0,0,0,0,0,0,0,0,0,0,0,0,0,0,0,0,0,0,0,0,0,0,0,0,0,0,0,0}},
   {7,6,6,13,255,{32,68,51,73,92,221,0,0,0,0,0},{0,0,0,0,0,0,0,0,0,0,0},{104,50,36,101,98,97,0,0,0,0,0,0,0,0,0,0,0,0,0,0,0,0,0,0,0,0,0,0,0,0}}},
  {10,6,7,9,9,2,9,7,10,6,10,9,5,9,0,6,3,4,2,7,8,8,6,9},
  {{0,3,7,8,4,6,18,1,2,5,9,10,11,14,13,16,20,30,24,15,27,12,25,23,29,17,22,21,26,28,19,31},
   {3,7,8,18,0,4,6,5,1,14,10,9,20,2,13,15,23,30,11,16,27,24,17,25,12,29,22,31,26,28,21,19},
   {7,18,0,8,5,3,4,6,9,2,1,10,14,20,24,11,30,15,23,13,17,27,16,12,25,29,22,26,31,28,21,19},
   {0,7,18,3,8,4,5,9,6,2,1,14,10,11,13,20,24,23,15,30,17,16,27,12,25,26,22,29,31,21,28,19},
   {0,18,3,8,7,4,5,6,9,14,2,1,10,20,11,13,30,15,24,23,16,27,17,12,29,25,26,22,31,21,28,19},
   {3,4,8,7,18,0,6,5,1,2,9,14,10,11,20,13,15,30,24,23,16,27,17,12,25,29,22,26,31,28,21,19},
   {0,4,7,8,18,3,6,5,9,2,1,14,10,11,20,13,15,24,30,23,16,27,17,12,25,29,26,22,31,28,21,19},
   {0,3,4,7,8,18,6,5,9,2,1,14,10,11,20,13,15,24,30,16,17,23,27,12,25,29,26,22,31,28,21,19}},
  {{2,4,2,2,1,5,2,0},{10,10,10,10,9,9,10,10},{9,9,9,9,10,10,9,9},{0,0,4,3,4,2,5,4},
   {5,5,5,5,3,1,4,5},{7,6,6,6,7,7,7,7},{6,7,7,7,6,6,6,6},{3,2,0,0,5,4,1,2},
   {1,1,3,4,2,0,3,1},{8,8,8,8,8,8,8,8},{12,12,12,12,12,12,12,12},{14,14,5,0,3,0,0,0},
   {11,11,9,5,0,1,1,1},{15,15,1,1,1,2,6,6},{11,11,11,11,11,11,11,11},{6,6,7,7,7,7,2,2},
   {2,7,11,12,11,10,11,11},{4,10,10,11,12,11,12,0},{4,3,1,1,0,3,0,3},{4,10,11,11,12,11,9,6},
   {13,13,13,5,0,1,1,1},{5,7,9,12,11,10,11,12},{13,13,1,6,9,9,10,0},{1,1,8,10,9,9,10,10},
   {0,0,0,8,8,8,7,8},{12,12,13,0,3,0,9,6},{15,15,6,10,6,6,6,2},{3,8,12,9,10,12,0,12},
   {2,5,12,5,0,1,1,1},{7,9,5,1,1,2,8,9},{5,5,6,6,6,6,8,9},{14,14,8,9,10,12,0,11}},
  {{255,255,255,255,255,255,255,255},{255,255,255,255,255,255,255,255},{255,255,255,255,255,255,255,255},{255,255,255,255,255,255,255,255},
   {255,255,255,255,255,255,255,255},{255,255,255,255,255,255,255,255},{255,255,255,255,255,255,255,255},{255,255,255,255,255,255,255,255},
   {255,255,255,255,255,255,255,255},{255,255,255,255,255,255,255,255},{255,255,255,255,255,255,255,255},{255,255,4,7,4,8,18,0},
   {14,14,2,20,20,20,20,20},{255,255,18,18,0,3,6,6},{255,255,255,255,255,255,255,255},{6,5,6,6,5,5,0,7},
   {0,6,14,10,14,2,14,14},{18,1,1,14,10,14,10,11},{255,255,255,255,255,255,255,255},{17,17,16,17,17,17,25,25},
   {255,255,255,4,18,4,7,8},{30,16,12,16,16,16,16,27},{20,20,13,30,23,23,23,17},{8,8,9,1,1,1,1,1},
   {3,3,7,9,9,9,5,9},{10,10,20,11,11,11,2,13},{13,13,30,23,30,30,13,15},{7,9,10,2,2,10,11,10},
   {16,30,27,12,12,12,12,12},{5,2,11,13,13,13,30,30},{4,4,5,5,6,6,9,2},{11,11,23,27,27,27,27,16}}};

typedef CUresult (*EncodeFn)(CUtensorMap*, CUtensorMapDataType, cuuint32_t, void*, const cuuint64_t*, const cuuint64_t*, const cuuint32_t*,
                             const cuuint32_t*, CUtensorMapInterleave, CUtensorMapSwizzle, CUtensorMapL2promotion, CUtensorMapFloatOOBfill);

void make_map2(EncodeFn enc, CUtensorMap* m, const void* ptr, int rows, int cols, int box_rows) {
  cuuint64_t dim[2] = {(cuuint64_t)cols, (cuuint64_t)rows}, str[1] = {(cuuint64_t)cols * 2};
  cuuint32_t box[2] = {64, (cuuint32_t)box_rows}, es[2] = {1, 1};
  enc(m, CU_TENSOR_MAP_DATA_TYPE_BFLOAT16, 2, const_cast<void*>(ptr), dim, str, box, es, CU_TENSOR_MAP_INTERLEAVE_NONE, CU_TENSOR_MAP_SWIZZLE_128B,
      CU_TENSOR_MAP_L2_PROMOTION_L2_128B, CU_TENSOR_MAP_FLOAT_OOB_FILL_NONE);
}
void make_map3(EncodeFn enc, CUtensorMap* m, const void* ptr, int rows) {
  cuuint64_t dim[3] = {64, (cuuint64_t)rows, 9}, str[2] = {DM * 2, 128};
  cuuint32_t box[3] = {64, 32, 3}, es[3] = {1, 1, 1};
  enc(m, CU_TENSOR_MAP_DATA_TYPE_BFLOAT16, 3, const_cast<void*>(ptr), dim, str, box, es, CU_TENSOR_MAP_INTERLEAVE_NONE, CU_TENSOR_MAP_SWIZZLE_128B,
      CU_TENSOR_MAP_L2_PROMOTION_L2_128B, CU_TENSOR_MAP_FLOAT_OOB_FILL_NONE);
}

void make_map_t(EncodeFn enc, CUtensorMap* m, void* ptr, int width, int cols) {
  cuuint64_t dim[3] = {TP / 2, 2, 864}, str[2] = {TP * 2, TP * 4};
  cuuint32_t box[3] = {(cuuint32_t)width, 2, (cuuint32_t)cols}, es[3] = {1, 1, 1};
  enc(m, CU_TENSOR_MAP_DATA_TYPE_UINT32, 3, ptr, dim, str, box, es, CU_TENSOR_MAP_INTERLEAVE_NONE, cols == 64 ? CU_TENSOR_MAP_SWIZZLE_128B : CU_TENSOR_MAP_SWIZZLE_NONE,
      CU_TENSOR_MAP_L2_PROMOTION_NONE, CU_TENSOR_MAP_FLOAT_OOB_FILL_NONE);
}

int g_mode = -1;

}

extern "C" void kernel_launch(void* const* d_in, const int* in_sizes, int n_in, void* d_out, int out_size) {
  static EncodeFn enc = nullptr;
  static void* t_ptr = nullptr;
  if (!enc) {
    void* fn = nullptr;
    cudaDriverEntryPointQueryResult st;
    cudaGetDriverEntryPoint("cuTensorMapEncodeTiled", &fn, cudaEnableDefault, &st);
    enc = (EncodeFn)fn;
    cudaGetSymbolAddress(&t_ptr, g_T);
    cudaFuncSetAttribute(fused_kernel, cudaFuncAttributeMaxDynamicSharedMemorySize, SMEM_BYTES);
    if (g_mode < 0) {
      cudaLaunchConfig_t cfg = {};
      cfg.gridDim = dim3(2 * NCL); cfg.blockDim = dim3(384); cfg.dynamicSmemBytes = SMEM_BYTES;
      cudaLaunchAttribute at; at.id = cudaLaunchAttributeClusterDimension;
      at.val.clusterDim.x = 2; at.val.clusterDim.y = 1; at.val.clusterDim.z = 1;
      cfg.attrs = &at; cfg.numAttrs = 1;
      int nc = 0;
      g_mode = (cudaOccupancyMaxActiveClusters(&nc, fused_kernel, &cfg) == cudaSuccess && nc >= NCL) ? 1 : 0;
      (void)cudaGetLastError();
    }
  }
  Params p;
  make_map2(enc, &p.map_a[0], d_in[4], SEQ, DC, 128);
  make_map2(enc, &p.map_a[1], d_in[0], SEQ, DM, 128);
  make_map2(enc, &p.map_w[0], d_in[6], DC, 4096, 64);
  make_map2(enc, &p.map_w[1], d_in[7], DC, 4096, 64);
  make_map2(enc, &p.map_w[2], d_in[5], DM, 4096, 64);
  make_map2(enc, &p.map_w[3], d_in[1], DM, 1728, 64);
  make_map3(enc, &p.map_o[0], d_in[8], 4096);
  make_map3(enc, &p.map_o[1], d_in[2], DM);
  make_map_t(enc, &p.map_t[0], t_ptr, 32, 9);
  make_map_t(enc, &p.map_t[1], t_ptr, 40, 9);
  make_map_t(enc, &p.map_t[2], t_ptr, 32, 64);
  p.x = (const __nv_bfloat16*)d_in[0];
  p.gate_w = (const __nv_bfloat16*)d_in[9];
  make_map2(enc, &p.map_out, d_out, SEQ, DM, 16);
  p.out = (__nv_bfloat16*)d_out;
  p.zero = 0;
  auto launch = [&](int phases) {
    p.s = k_sched;
    for (int i = 0; i < NCL; i++) {
      Rec& r = p.s.r[i];
      if (!(phases & 1)) r.n1 = 0;
      if (!(phases & 2)) r.n2 = 0;
      if (!(phases & (r.p3 < 24 ? 4 : 32))) r.p3 = 255;
      if (!(phases & 8)) r.bg = 255;
      const int u1 = r.n1 ? 8 + r.n1 * (8 + (r.slab >> 3)) : 0;
      int u2 = 0;
      for (int k = 0; k < r.n2; k++) u2 += 4 * (r.item[k] & 7) + 4;
      r.u1 = (uint8_t)u1; r.u2 = (uint8_t)u2;
      r.rot = (uint8_t)(((u1 % 10 + 1) >> 1) % 5);
      r.x3 = (uint8_t)((r.rot + u2) % 5 & 3);
      r.phases = (uint8_t)phases;
    }
    if (!(phases & 16))
      for (int i = 0; i < 256; i++) { p.s.slot[i >> 3][i & 7] = (uint8_t)(i >> 3); p.s.prev[i >> 3][i & 7] = 255; }
    fused_kernel<<<2 * NCL, 384, SMEM_BYTES>>>(p);
  };
  if (g_mode == 1) launch(63);
  else { launch(1); launch(10); launch(32); launch(4); }
}
```

```cpp
#include <cuda_runtime.h>
#include <cuda_bf16.h>
#include <cuda.h>
#include <stdint.h>

namespace {

constexpr int SEQ = 2048, DM = 576, DC = 512, NH = 32;
constexpr int NCL = 66;
constexpr uint32_t DESC_HI = 0x40000040u;

constexpr int SM_RING = 0;
constexpr int SM_BUF = 163840;
constexpr int SM_BAR = 229376;
constexpr int B_P1E = 0, B_P2E = 10, B_P3E = 15, B_P2F = 24, B_SF = 32, B_ORD = 36, B_LAD = 40, B_DONE = 41, B_FIN = 48;
constexpr int B_P3F = 56, B_OUT = 61, B_P1F = 64, B_SE = 74, B_QF = 80, B_LA = 84, B_NUM = 88;
constexpr uint64_t B_CNT = 0x11118245000ull;
constexpr int SMEM_BYTES = SM_BAR + B_NUM * 8 + 1024;

constexpr int F_QKVA = 32;
constexpr int F_GATE = 64;
constexpr int F_DONE = 65;
constexpr int F_CTX = 96;
constexpr int F_OUT = 96 + 8 * 64;
constexpr int F_KV = F_OUT + 64;
constexpr int F_Q = F_KV + 256;
constexpr int F_RD = F_Q + 256;
constexpr int F_NUM = F_RD + 256;

struct Rec {
  uint8_t slab;
  uint8_t n1, n2;
  uint8_t p3;
  uint8_t bg;
  uint8_t item[11];
  uint8_t last[11];
  uint8_t tile[32];
  uint8_t u1, u2;
  uint8_t rot, x3;
  uint8_t phases;
};
struct Sched {
  Rec r[NCL];
  uint8_t nh[24];
  uint8_t p3_order[8][32];
  uint8_t slot[32][8];
  uint8_t prev[32][8];
};

#define SCHED_DECL static const

struct Params {
  CUtensorMap map_a[2];
  CUtensorMap map_w[4];
  CUtensorMap map_o[2];
  CUtensorMap map_t[3];
  CUtensorMap map_out;
  const __nv_bfloat16* x;
  const __nv_bfloat16* gate_w;
  __nv_bfloat16* out;
  int zero;
  alignas(64) Sched s;
};

__device__ __align__(1024) uint8_t g_Q[NH * 32 * 16384];
__device__ __align__(1024) uint8_t g_KV[2 * NH * 16 * 32768];
__device__ __align__(1024) uint8_t g_oA[32 * 576 * 128];
constexpr int TP = SEQ + 16;
__device__ __align__(1024) uint32_t g_T[864 * TP];
__device__ float g_gate[SEQ];
__device__ int g_flags[F_NUM];

__device__ __forceinline__ void mbar_arrive(uint32_t b) { asm volatile("mbarrier.arrive.shared::cta.b64 _, [%0];" ::"r"(b) : "memory"); }
__device__ __forceinline__ void mbar_arrive_cl(uint32_t b, int cnt) {
  asm volatile("mbarrier.arrive.shared::cluster.b64 _, [%0], %1;" ::"r"(b), "r"(cnt) : "memory");
}
__device__ __forceinline__ void mbar_wait(uint32_t b, int par) {
  asm volatile(
      "{\n.reg .pred p;\n.reg .u32 c;\n"
      "mbarrier.try_wait.parity.shared::cta.b64 p, [%0], %1;\n@p bra DN;\nmov.u32 c, 0;\n"
      "LP:\nmbarrier.try_wait.parity.shared::cta.b64 p, [%0], %1;\n@p bra DN;\n"
      "add.u32 c, c, 1;\nsetp.lt.u32 p, c, 4000000;\n@p bra LP;\ntrap;\nDN:\n}" ::"r"(b), "r"(par) : "memory");
}
__device__ __forceinline__ uint32_t mapa(uint32_t a, uint32_t cta) {
  uint32_t r; asm("mapa.shared::cluster.u32 %0, %1, %2;" : "=r"(r) : "r"(a), "r"(cta)); return r;
}
#define ELECT(ins) "{\n.reg .pred e;\nelect.sync _|e, 0xffffffff;\n@e " ins "\n}"
__device__ __forceinline__ void mbar_expect(uint32_t b, int bytes) {
  asm volatile(ELECT("mbarrier.arrive.expect_tx.shared::cta.b64 _, [%0], %1;") ::"r"(b), "r"(bytes) : "memory");
}
__device__ __forceinline__ void mbar_arrive_one(uint32_t b) { asm volatile(ELECT("mbarrier.arrive.shared::cta.b64 _, [%0];") ::"r"(b) : "memory"); }
constexpr uint64_t L2_NORMAL = 0x1000000000000000ull, L2_FIRST = 0x12F0000000000000ull;
__device__ __forceinline__ void bulk_load(uint32_t dst, const void* src, int bytes, uint32_t bar, uint64_t pol = L2_NORMAL) {
  asm volatile(ELECT("cp.async.bulk.shared::cluster.global.mbarrier::complete_tx::bytes.L2::cache_hint [%0], [%1], %2, [%3], %4;") ::"r"(dst), "l"(src), "r"(bytes), "r"(bar), "l"(pol) : "memory");
}
__device__ __forceinline__ void bulk_load_mc(uint32_t dst, const void* src, int bytes, uint32_t bar, uint64_t pol = L2_NORMAL) {
  asm volatile(ELECT("cp.async.bulk.shared::cluster.global.mbarrier::complete_tx::bytes.multicast::cluster.L2::cache_hint [%0], [%1], %2, [%3], %4, %5;") ::"r"(dst), "l"(src), "r"(bytes), "r"(bar), "h"((uint16_t)3), "l"(pol) : "memory");
}
__device__ __forceinline__ void bulk_store(void* dst, uint32_t src, int bytes, uint64_t pol = L2_NORMAL) {
  asm volatile(ELECT("cp.async.bulk.global.shared::cta.bulk_group.L2::cache_hint [%0], [%1], %2, %3;") ::"l"(dst), "r"(src), "r"(bytes), "l"(pol) : "memory");
}
__device__ __forceinline__ void tma2d(uint32_t dst, const CUtensorMap* m, int c0, int c1, uint32_t bar, uint64_t pol = L2_NORMAL) {
  asm volatile(ELECT("cp.async.bulk.tensor.2d.shared::cluster.global.mbarrier::complete_tx::bytes.L2::cache_hint [%0], [%1, {%3, %4}], [%2], %5;") ::"r"(dst), "l"(m), "r"(bar), "r"(c0), "r"(c1), "l"(pol) : "memory");
}
__device__ __forceinline__ void tma2d_mc(uint32_t dst, const CUtensorMap* m, int c0, int c1, uint32_t bar, uint64_t pol = L2_NORMAL) {
  asm volatile(ELECT("cp.async.bulk.tensor.2d.shared::cluster.global.mbarrier::complete_tx::bytes.multicast::cluster.L2::cache_hint [%0], [%1, {%3, %4}], [%2], %5, %6;") ::"r"(dst), "l"(m), "r"(bar), "r"(c0), "r"(c1), "h"((uint16_t)3), "l"(pol) : "memory");
}
__device__ __forceinline__ void tma3d(uint32_t dst, const CUtensorMap* m, int c0, int c1, int c2, uint32_t bar, uint64_t pol = L2_NORMAL) {
  asm volatile(ELECT("cp.async.bulk.tensor.3d.shared::cluster.global.mbarrier::complete_tx::bytes.L2::cache_hint [%0], [%1, {%3, %4, %5}], [%2], %6;") ::"r"(dst), "l"(m), "r"(bar), "r"(c0), "r"(c1), "r"(c2), "l"(pol) : "memory");
}
__device__ __forceinline__ void tma3d_mc(uint32_t dst, const CUtensorMap* m, int c0, int c1, int c2, uint32_t bar, uint64_t pol = L2_NORMAL) {
  asm volatile(ELECT("cp.async.bulk.tensor.3d.shared::cluster.global.mbarrier::complete_tx::bytes.multicast::cluster.L2::cache_hint [%0], [%1, {%3, %4, %5}], [%2], %6, %7;") ::"r"(dst), "l"(m), "r"(bar), "r"(c0), "r"(c1), "r"(c2), "h"((uint16_t)3), "l"(pol) : "memory");
}
__device__ __forceinline__ void tma2d_add(const CUtensorMap* m, uint32_t src, int c0, int c1) {
  asm volatile(ELECT("cp.reduce.async.bulk.tensor.2d.global.shared::cta.add.bulk_group [%0, {%2, %3}], [%1];") ::"l"(m), "r"(src), "r"(c0), "r"(c1) : "memory");
}
__device__ __forceinline__ void tma3d_store(const CUtensorMap* m, uint32_t src, int c0, int c1, int c2, uint64_t pol = L2_NORMAL) {
  asm volatile(ELECT("cp.async.bulk.tensor.3d.global.shared::cta.bulk_group.L2::cache_hint [%0, {%2, %3, %4}], [%1], %5;") ::"l"(m), "r"(src), "r"(c0), "r"(c1), "r"(c2), "l"(pol) : "memory");
}
__device__ __forceinline__ void tma2d_prefetch(const CUtensorMap* m, int c0, int c1, uint64_t pol = L2_NORMAL) {
  asm volatile(ELECT("cp.async.bulk.prefetch.tensor.2d.L2.global.L2::cache_hint [%0, {%1, %2}], %3;") ::"l"(m), "r"(c0), "r"(c1), "l"(pol) : "memory");
}
#define HINT 62
#define POL(bit) ((HINT >> (bit)) & 1 ? L2_FIRST : L2_NORMAL)
#define BULK_COMMIT() asm volatile("cp.async.bulk.commit_group;" ::: "memory")
#define BULK_WAIT(n) asm volatile("cp.async.bulk.wait_group %0;" ::"n"(n) : "memory")
#define BULK_WAIT_READ(n) asm volatile("cp.async.bulk.wait_group.read %0;" ::"n"(n) : "memory")
#define FENCE_ASYNC_SMEM() asm volatile("fence.proxy.async.shared::cta;" ::: "memory")
#define FENCE_ASYNC_ALL() asm volatile("fence.proxy.async;" ::: "memory")
#define WG_FENCE() asm volatile("wgmma.fence.sync.aligned;" ::: "memory")
#define WG_COMMIT() asm volatile("wgmma.commit_group.sync.aligned;" ::: "memory")
#define WG_WAIT(n) asm volatile("wgmma.wait_group.sync.aligned %0;" ::"n"(n) : "memory")
__device__ __forceinline__ void bar_sync(int id, int n) { asm volatile("bar.sync %0, %1;" ::"r"(id), "r"(n) : "memory"); }
__device__ __forceinline__ void bar_arrive(int id, int n) { asm volatile("bar.arrive %0, %1;" ::"r"(id), "r"(n) : "memory"); }
__device__ __forceinline__ void cluster_sync() {
  asm volatile("barrier.cluster.arrive.relaxed;\nbarrier.cluster.wait.acquire;" ::: "memory");
}
template <int N> __device__ __forceinline__ void pin(float (&r)[N]) {
#pragma unroll
  for (int i = 0; i < N; i++) asm volatile("" : "+f"(r[i])::"memory");
}
template <int N> __device__ __forceinline__ void pin(uint32_t (&r)[N]) {
#pragma unroll
  for (int i = 0; i < N; i++) asm volatile("" : "+r"(r[i])::"memory");
}
__device__ __forceinline__ uint32_t pack_bf16(float lo, float hi) {
  uint32_t r; asm("cvt.rn.bf16x2.f32 %0, %1, %2;" : "=r"(r) : "f"(hi), "f"(lo)); return r;
}
__device__ __forceinline__ float ex2(float x) { float r; asm("ex2.approx.ftz.f32 %0, %1;" : "=f"(r) : "f"(x)); return r; }
__device__ __forceinline__ void ldsm4(uint32_t a, uint32_t& r0, uint32_t& r1, uint32_t& r2, uint32_t& r3) {
  asm volatile("ldmatrix.sync.aligned.m8n8.x4.shared.b16 {%0,%1,%2,%3}, [%4];" : "=r"(r0), "=r"(r1), "=r"(r2), "=r"(r3) : "r"(a) : "memory");
}
__device__ __forceinline__ void stsm4(uint32_t a, uint32_t r0, uint32_t r1, uint32_t r2, uint32_t r3) {
  asm volatile("stmatrix.sync.aligned.m8n8.x4.shared.b16 [%0], {%1,%2,%3,%4};" ::"r"(a), "r"(r0), "r"(r1), "r"(r2), "r"(r3) : "memory");
}
__device__ __forceinline__ void flag_add(int idx) {
  asm volatile(ELECT("red.release.gpu.global.add.s32 [%0], 1;") ::"l"(g_flags + idx) : "memory");
}
__device__ __forceinline__ void flag_add_rx(int idx) {
  asm volatile(ELECT("red.relaxed.gpu.global.add.s32 [%0], 1;") ::"l"(g_flags + idx) : "memory");
}
template <bool ACQ, int NS = 32> __device__ __forceinline__ void flag_wait(int idx, int target) {
  int n = 0;
  while (true) {
    int v;
    if (ACQ) asm volatile("ld.acquire.gpu.global.s32 %0, [%1];" : "=r"(v) : "l"(g_flags + idx) : "memory");
    else asm volatile("ld.relaxed.gpu.global.s32 %0, [%1];" : "=r"(v) : "l"(g_flags + idx) : "memory");
    if (__all_sync(0xffffffffu, v >= target)) break;
    if (++n > 20000000) __trap();
    __nanosleep(NS);
  }
}
__device__ __forceinline__ uint32_t desc_lo(uint32_t addr, uint32_t lbo) { return ((addr & 0x3FFFFu) >> 4) | ((lbo >> 4) << 16); }
#define PROF(role, i)
#define PROFX(cond, i)
#define PROFB(i)
#define PROFG(i)

template <int TB, int TA = 0> __device__ __forceinline__ void wgmma_ss64(float (&d)[32], uint32_t alo, uint32_t blo, int sd) {
  asm volatile("{\n.reg .pred p;\n.reg .b64 da, db;\n"
    "setp.ne.b32 p, %34, 0;\nmov.b64 da, {%32, %36};\nmov.b64 db, {%33, %36};\n"
    "wgmma.mma_async.sync.aligned.m64n64k16.f32.bf16.bf16 "
    "{%0,%1,%2,%3,%4,%5,%6,%7,%8,%9,%10,%11,%12,%13,%14,%15,%16,%17,%18,%19,%20,%21,%22,%23,"
    "%24,%25,%26,%27,%28,%29,%30,%31}, "
    "da, db, p, 1, 1, %37, %35;\n}\n"
    : "+f"(d[0]),"+f"(d[1]),"+f"(d[2]),"+f"(d[3]),"+f"(d[4]),"+f"(d[5]),"+f"(d[6]),"+f"(d[7]),"+f"(d[8]),"+f"(d[9]),"+f"(d[10]),"+f"(d[11]),
      "+f"(d[12]),"+f"(d[13]),"+f"(d[14]),"+f"(d[15]),"+f"(d[16]),"+f"(d[17]),"+f"(d[18]),"+f"(d[19]),"+f"(d[20]),"+f"(d[21]),"+f"(d[22]),"+f"(d[23]),
      "+f"(d[24]),"+f"(d[25]),"+f"(d[26]),"+f"(d[27]),"+f"(d[28]),"+f"(d[29]),"+f"(d[30]),"+f"(d[31])
    : "r"(alo), "r"(blo), "r"(sd), "n"(TB), "r"(DESC_HI), "n"(TA));
}
template <int TB, int TA = 0> __device__ __forceinline__ void wgmma_ss128(float (&d)[64], uint32_t alo, uint32_t blo, int sd) {
  asm volatile("{\n.reg .pred p;\n.reg .b64 da, db;\n"
    "setp.ne.b32 p, %66, 0;\nmov.b64 da, {%64, %68};\nmov.b64 db, {%65, %68};\n"
    "wgmma.mma_async.sync.aligned.m64n128k16.f32.bf16.bf16 "
    "{%0,%1,%2,%3,%4,%5,%6,%7,%8,%9,%10,%11,%12,%13,%14,%15,%16,%17,%18,%19,%20,%21,%22,%23,"
    "%24,%25,%26,%27,%28,%29,%30,%31,%32,%33,%34,%35,%36,%37,%38,%39,%40,%41,%42,%43,%44,%45,%46,%47,"
    "%48,%49,%50,%51,%52,%53,%54,%55,%56,%57,%58,%59,%60,%61,%62,%63}, "
    "da, db, p, 1, 1, %69, %67;\n}\n"
    : "+f"(d[0]),"+f"(d[1]),"+f"(d[2]),"+f"(d[3]),"+f"(d[4]),"+f"(d[5]),"+f"(d[6]),"+f"(d[7]),"+f"(d[8]),"+f"(d[9]),"+f"(d[10]),"+f"(d[11]),
      "+f"(d[12]),"+f"(d[13]),"+f"(d[14]),"+f"(d[15]),"+f"(d[16]),"+f"(d[17]),"+f"(d[18]),"+f"(d[19]),"+f"(d[20]),"+f"(d[21]),"+f"(d[22]),"+f"(d[23]),
      "+f"(d[24]),"+f"(d[25]),"+f"(d[26]),"+f"(d[27]),"+f"(d[28]),"+f"(d[29]),"+f"(d[30]),"+f"(d[31]),"+f"(d[32]),"+f"(d[33]),"+f"(d[34]),"+f"(d[35]),
      "+f"(d[36]),"+f"(d[37]),"+f"(d[38]),"+f"(d[39]),"+f"(d[40]),"+f"(d[41]),"+f"(d[42]),"+f"(d[43]),"+f"(d[44]),"+f"(d[45]),"+f"(d[46]),"+f"(d[47]),
      "+f"(d[48]),"+f"(d[49]),"+f"(d[50]),"+f"(d[51]),"+f"(d[52]),"+f"(d[53]),"+f"(d[54]),"+f"(d[55]),"+f"(d[56]),"+f"(d[57]),"+f"(d[58]),"+f"(d[59]),
      "+f"(d[60]),"+f"(d[61]),"+f"(d[62]),"+f"(d[63])
    : "r"(alo), "r"(blo), "r"(sd), "n"(TB), "r"(DESC_HI), "n"(TA));
}
template <int TB> __device__ __forceinline__ void wgmma_rs128(float (&d)[64], uint32_t a0, uint32_t a1, uint32_t a2, uint32_t a3, uint32_t blo, int sd) {
  asm volatile("{\n.reg .pred p;\n.reg .b64 db;\n"
    "setp.ne.b32 p, %69, 0;\nmov.b64 db, {%68, %71};\n"
    "wgmma.mma_async.sync.aligned.m64n128k16.f32.bf16.bf16 "
    "{%0,%1,%2,%3,%4,%5,%6,%7,%8,%9,%10,%11,%12,%13,%14,%15,%16,%17,%18,%19,%20,%21,%22,%23,"
    "%24,%25,%26,%27,%28,%29,%30,%31,%32,%33,%34,%35,%36,%37,%38,%39,%40,%41,%42,%43,%44,%45,%46,%47,"
    "%48,%49,%50,%51,%52,%53,%54,%55,%56,%57,%58,%59,%60,%61,%62,%63}, "
    "{%64,%65,%66,%67}, db, p, 1, 1, %70;\n}\n"
    : "+f"(d[0]),"+f"(d[1]),"+f"(d[2]),"+f"(d[3]),"+f"(d[4]),"+f"(d[5]),"+f"(d[6]),"+f"(d[7]),"+f"(d[8]),"+f"(d[9]),"+f"(d[10]),"+f"(d[11]),
      "+f"(d[12]),"+f"(d[13]),"+f"(d[14]),"+f"(d[15]),"+f"(d[16]),"+f"(d[17]),"+f"(d[18]),"+f"(d[19]),"+f"(d[20]),"+f"(d[21]),"+f"(d[22]),"+f"(d[23]),
      "+f"(d[24]),"+f"(d[25]),"+f"(d[26]),"+f"(d[27]),"+f"(d[28]),"+f"(d[29]),"+f"(d[30]),"+f"(d[31]),"+f"(d[32]),"+f"(d[33]),"+f"(d[34]),"+f"(d[35]),
      "+f"(d[36]),"+f"(d[37]),"+f"(d[38]),"+f"(d[39]),"+f"(d[40]),"+f"(d[41]),"+f"(d[42]),"+f"(d[43]),"+f"(d[44]),"+f"(d[45]),"+f"(d[46]),"+f"(d[47]),
      "+f"(d[48]),"+f"(d[49]),"+f"(d[50]),"+f"(d[51]),"+f"(d[52]),"+f"(d[53]),"+f"(d[54]),"+f"(d[55]),"+f"(d[56]),"+f"(d[57]),"+f"(d[58]),"+f"(d[59]),
      "+f"(d[60]),"+f"(d[61]),"+f"(d[62]),"+f"(d[63])
    : "r"(a0), "r"(a1), "r"(a2), "r"(a3), "r"(blo), "r"(sd), "n"(TB), "r"(DESC_HI));
}
template <int TB, int TA = 0> __device__ __forceinline__ void wgmma_ss192(float (&d)[96], uint32_t alo, uint32_t blo, int sd) {
  asm volatile("{\n.reg .pred p;\n.reg .b64 da, db;\n"
    "setp.ne.b32 p, %98, 0;\nmov.b64 da, {%96, %100};\nmov.b64 db, {%97, %100};\n"
    "wgmma.mma_async.sync.aligned.m64n192k16.f32.bf16.bf16 "
    "{%0,%1,%2,%3,%4,%5,%6,%7,%8,%9,%10,%11,%12,%13,%14,%15,%16,%17,%18,%19,%20,%21,%22,%23,"
    "%24,%25,%26,%27,%28,%29,%30,%31,%32,%33,%34,%35,%36,%37,%38,%39,%40,%41,%42,%43,%44,%45,%46,%47,"
    "%48,%49,%50,%51,%52,%53,%54,%55,%56,%57,%58,%59,%60,%61,%62,%63,%64,%65,%66,%67,%68,%69,%70,%71,"
    "%72,%73,%74,%75,%76,%77,%78,%79,%80,%81,%82,%83,%84,%85,%86,%87,%88,%89,%90,%91,%92,%93,%94,%95}, "
    "da, db, p, 1, 1, %101, %99;\n}\n"
    : "+f"(d[0]),"+f"(d[1]),"+f"(d[2]),"+f"(d[3]),"+f"(d[4]),"+f"(d[5]),"+f"(d[6]),"+f"(d[7]),"+f"(d[8]),"+f"(d[9]),"+f"(d[10]),"+f"(d[11]),
      "+f"(d[12]),"+f"(d[13]),"+f"(d[14]),"+f"(d[15]),"+f"(d[16]),"+f"(d[17]),"+f"(d[18]),"+f"(d[19]),"+f"(d[20]),"+f"(d[21]),"+f"(d[22]),"+f"(d[23]),
      "+f"(d[24]),"+f"(d[25]),"+f"(d[26]),"+f"(d[27]),"+f"(d[28]),"+f"(d[29]),"+f"(d[30]),"+f"(d[31]),"+f"(d[32]),"+f"(d[33]),"+f"(d[34]),"+f"(d[35]),
      "+f"(d[36]),"+f"(d[37]),"+f"(d[38]),"+f"(d[39]),"+f"(d[40]),"+f"(d[41]),"+f"(d[42]),"+f"(d[43]),"+f"(d[44]),"+f"(d[45]),"+f"(d[46]),"+f"(d[47]),
      "+f"(d[48]),"+f"(d[49]),"+f"(d[50]),"+f"(d[51]),"+f"(d[52]),"+f"(d[53]),"+f"(d[54]),"+f"(d[55]),"+f"(d[56]),"+f"(d[57]),"+f"(d[58]),"+f"(d[59]),
      "+f"(d[60]),"+f"(d[61]),"+f"(d[62]),"+f"(d[63]),"+f"(d[64]),"+f"(d[65]),"+f"(d[66]),"+f"(d[67]),"+f"(d[68]),"+f"(d[69]),"+f"(d[70]),"+f"(d[71]),
      "+f"(d[72]),"+f"(d[73]),"+f"(d[74]),"+f"(d[75]),"+f"(d[76]),"+f"(d[77]),"+f"(d[78]),"+f"(d[79]),"+f"(d[80]),"+f"(d[81]),"+f"(d[82]),"+f"(d[83]),
      "+f"(d[84]),"+f"(d[85]),"+f"(d[86]),"+f"(d[87]),"+f"(d[88]),"+f"(d[89]),"+f"(d[90]),"+f"(d[91]),"+f"(d[92]),"+f"(d[93]),"+f"(d[94]),"+f"(d[95])
    : "r"(alo), "r"(blo), "r"(sd), "n"(TB), "r"(DESC_HI), "n"(TA));
}

struct Ctx {
  uint32_t sm;
  uint32_t bar;
  uint32_t rbar;
  int cl, rank, wg, warp, lane, phases;
};
__device__ __forceinline__ void release(const Ctx& c, int b, int cnt = 1) {
  if (c.lane < 2) mbar_arrive_cl(c.rbar + b * 8, cnt);
}
#define PFM 7
#define PF1 1
constexpr float SM_SCALE = 0.08838834764831845f * 1.4426950408889634f;
constexpr float SM_HI = 1.8446744e19f, SM_LO = 5.4210109e-20f;
constexpr int ORDER = 1;

__device__ __forceinline__ void stage_tile(const float (&a)[64], uint32_t buf, const Ctx& c, float s0, float s1) {
  const int row = (c.lane & 7) + ((c.lane >> 3) & 1) * 8;
  const uint32_t base = buf + (c.warp * 16 + row) * 128 + (((c.lane >> 4) ^ (row & 7)) << 4);
#pragma unroll
  for (int i = 0; i < 8; i++)
    stsm4((base ^ ((i & 3) << 5)) + (i >> 2) * 8192, pack_bf16(a[8 * i] * s0, a[8 * i + 1] * s0), pack_bf16(a[8 * i + 2] * s1, a[8 * i + 3] * s1),
          pack_bf16(a[8 * i + 4] * s0, a[8 * i + 5] * s0), pack_bf16(a[8 * i + 6] * s1, a[8 * i + 7] * s1));
}

__device__ __forceinline__ void p1_epilogue(const Params& p, const Ctx& c, const float (&acc)[64], int t, int type) {
  const int tile = p.s.r[c.cl].tile[t] & 63, b = c.wg * 2 + 1;
  mbar_wait(c.bar + (B_SE + b) * 8, (t & 1) ^ 1);
  if (type && tile >= 32) {
    const int r = 2 * (c.lane & 3) + ((c.lane >> 2) & 1);
    const uint32_t dst = c.sm + SM_BUF + b * 16384 + r * 128 + (((c.warp * 2) ^ r) << 4) + (c.lane >> 3) * 4;
#pragma unroll
    for (int i = 0; i < 16; i++) {
      asm volatile("st.shared.u32 [%0], %1;" ::"r"(dst + i * 1024), "r"(pack_bf16(acc[4 * i], acc[4 * i + 1])) : "memory");
      asm volatile("st.shared.u32 [%0], %1;" ::"r"((dst ^ 16) + i * 1024), "r"(pack_bf16(acc[4 * i + 2], acc[4 * i + 3])) : "memory");
    }
  } else {
    if (type) stage_tile(acc, c.sm + SM_BUF + b * 16384, c, SM_SCALE, SM_SCALE);
    else stage_tile(acc, c.sm + SM_BUF + b * 16384, c, 1.f, 1.f);
  }
  FENCE_ASYNC_SMEM();
  __syncwarp();
  if (c.lane == 0) mbar_arrive(c.bar + (B_SF + b) * 8);
}

__device__ __forceinline__ void p1_consumer(const Params& p, const Ctx& c) {
  const int n = p.s.r[c.cl].n1;
  const int type = p.s.r[c.cl].slab >> 3;
  const uint32_t bdesc = desc_lo(c.sm + SM_RING, 8192), adesc = desc_lo(c.sm + SM_BUF + 32768 + c.wg * 8192, 16);
  uint32_t A[128];
  float acc[64] = {};
  int slot = 0, par = 0;
  auto next = [&]() { if (++slot == 10) { slot = 0; par ^= 1; } };
  {
    const int row = (c.lane & 7) + ((c.lane >> 3) & 1) * 8;
    const uint32_t base = c.sm + SM_RING + (c.wg * 64 + c.warp * 16 + row) * 128 + (((c.lane >> 4) ^ (row & 7)) << 4);
    if (c.wg == 1) bar_sync(ORDER + 1, 256);
    int pa = -1, pb = -1;
    if (type) {
      mbar_wait(c.bar + B_P1F * 8, 0);
      WG_FENCE();
#pragma unroll
      for (int kk = 0; kk < 4; kk++) wgmma_ss128<1>(acc, adesc + kk * 2, bdesc + kk * 128, kk != 0);
      WG_COMMIT();
      pb = 0; slot = 1;
    }
#pragma unroll
    for (int kb = 0; kb < 8; kb++) {
      const int sa = slot;
      mbar_wait(c.bar + (B_P1F + slot) * 8, par);
      if (kb == 0) PROF(c.wg, 5);
      next();
      mbar_wait(c.bar + (B_P1F + slot) * 8, par);
      PROF(c.wg, 6 + 2 * kb);
      WG_FENCE();
#pragma unroll
      for (int kk = 0; kk < 4; kk++)
        wgmma_ss128<1>(acc, desc_lo(c.sm + SM_RING + c.wg * 8192, 16) + sa * 1024 + kk * 2, bdesc + slot * 1024 + kk * 128, (kb | kk) != 0 ? 1 : type);
      WG_COMMIT();
      if (kb == 1 && c.wg == 0) bar_arrive(ORDER + 1, 256);
#pragma unroll
      for (int kk = 0; kk < 4; kk++) ldsm4((base ^ (kk << 5)) + sa * 16384, A[kb * 16 + kk * 4], A[kb * 16 + kk * 4 + 1], A[kb * 16 + kk * 4 + 2], A[kb * 16 + kk * 4 + 3]);
      WG_WAIT(1);
      if (kb > 0) release(c, B_P1E + pa);
      if (kb > 0 || pb >= 0) release(c, B_P1E + pb);
      pa = sa; pb = slot;
      next();
    }
    WG_WAIT(0);
    __syncwarp();
    release(c, B_P1E + pa);
    release(c, B_P1E + pb);
    pin(acc);
    PROF(c.wg, 1);
    p1_epilogue(p, c, acc, 0, type);
    PROF(c.wg, 2);
  }
  for (int t = 1; t < n; t++) {
    bar_sync(ORDER + c.wg, 256);
    int prev1 = -1, prev2 = -1;
    if (type) {
      mbar_wait(c.bar + (B_P1F + slot) * 8, par);
      WG_FENCE();
#pragma unroll
      for (int kk = 0; kk < 4; kk++) wgmma_ss128<1>(acc, adesc + kk * 2, bdesc + slot * 1024 + kk * 128, kk != 0);
      WG_COMMIT();
      prev1 = slot;
      next();
    }
#pragma unroll
    for (int kb = 0; kb < 8; kb++) {
      mbar_wait(c.bar + (B_P1F + slot) * 8, par);
      WG_FENCE();
      const uint32_t d = bdesc + slot * 1024;
#pragma unroll
      for (int kk = 0; kk < 4; kk++)
        wgmma_rs128<1>(acc, A[kb * 16 + kk * 4], A[kb * 16 + kk * 4 + 1], A[kb * 16 + kk * 4 + 2], A[kb * 16 + kk * 4 + 3], d + kk * 128, (kb | kk) != 0 ? 1 : type);
      WG_COMMIT();
      if (kb == 7) {
        if (t + 1 < n || c.wg == 0) bar_arrive(ORDER + (c.wg ^ 1), 256);
      }
      if (kb > 0) { WG_WAIT(2); if (kb > 1 || prev2 >= 0) release(c, B_P1E + prev2); }
      prev2 = prev1; prev1 = slot;
      next();
    }
    WG_WAIT(1);
    release(c, B_P1E + prev2);
    WG_WAIT(0);
    pin(acc);
    release(c, B_P1E + prev1);
    p1_epilogue(p, c, acc, t, type);
    PROF(c.wg, 3);
  }
}

__device__ __forceinline__ void p1_producer(const Params& p, const Ctx& c) {
  const int n = p.s.r[c.cl].n1;
  const int type = p.s.r[c.cl].slab >> 3, grp = p.s.r[c.cl].slab & 7;
  int slot = 2 - type, par = 1;
#pragma unroll 1
  for (int t = 0; t < n; t++) {
    const int tile = p.s.r[c.cl].tile[t] & 63;
    const CUtensorMap* m = &p.map_w[type * 2 + (tile >> 5)];
    const int n0 = (tile & 31) * 128 + c.rank * 64;
    const int ptile = p.s.r[c.cl].tile[t + PF1 < n ? t + PF1 : t];
    const CUtensorMap* pm = &p.map_w[type * 2 + ((ptile >> 5) & 1)];
#pragma unroll 1
    for (int kb = (t == 0) - type; kb < 8; kb++) {
      if (t == 0) {
        mbar_wait(c.bar + (B_P1E + slot) * 8, par);
        mbar_expect(c.bar + (B_P1F + slot) * 8, 16384);
        tma2d(c.sm + SM_RING + slot * 16384, &p.map_a[type], kb * 64, grp * 256 + c.rank * 128, c.bar + (B_P1F + slot) * 8);
        if (++slot == 10) { slot = 0; par ^= 1; }
      }
      mbar_wait(c.bar + (B_P1E + slot) * 8, par);
      mbar_expect(c.bar + (B_P1F + slot) * 8, 16384);
      tma2d_mc(c.sm + SM_RING + slot * 16384 + c.rank * 8192, m, n0, kb < 0 ? 512 : kb * 64, c.bar + (B_P1F + slot) * 8);
      if (t == 0 && kb == 1) PROF(2, 61);
      if (t == 0 && kb == 3) PROF(2, 62);
      if (t + PF1 < n && t > 0 && ((ptile & 64) || ((ptile & 128) && ((kb ^ grp) & PFM) == 0))) tma2d_prefetch(pm, (ptile & 31) * 128 + c.rank * 64, kb < 0 ? 512 : kb * 64);
      if (++slot == 10) { slot = 0; par ^= 1; }
    }
  }
}

__device__ __forceinline__ void p1_storer(const Params& p, const Ctx& c) {
  const int n = p.s.r[c.cl].n1;
  const int type = p.s.r[c.cl].slab >> 3, grp = p.s.r[c.cl].slab & 7;
  for (int i = 0; i < 2 * n; i++) {
    const int t = i >> 1, w = i & 1, b = w * 2 + 1;
    const int tile = p.s.r[c.cl].tile[t] & 63;
    mbar_wait(c.bar + (B_SF + b) * 8, t & 1);
    const uint32_t src = c.sm + SM_BUF + b * 16384;
    int f = (type ? F_Q : F_KV) + (tile & 31) * 8 + grp;
    if (type == 0) {
      const int prev = p.s.prev[tile & 31][grp];
      if (prev != 255 && w == 0) {
        if (grp >= 2) flag_wait<false>(F_RD + prev * 8 + grp, 8 - grp);
        else flag_wait<false>(F_CTX + max(c.lane & 7, grp) * 64 + prev, 4);
      }
      uint8_t* dst = g_KV + (size_t)(((tile & 32) + p.s.slot[tile & 31][grp]) * 16 + grp * 2 + c.rank) * 32768 + w * 8192;
      bulk_store(dst, src, 8192);
      bulk_store(dst + 16384, src + 8192, 8192);
    } else if (tile < 32) {
      bulk_store(g_Q + (size_t)(tile * 32 + grp * 4 + c.rank * 2 + w) * 16384, src, 16384);
    } else {
      tma3d_store(&p.map_t[2], src, 8 + (grp * 4 + c.rank * 2 + w) * 32, 0, (tile - 32) * 64);
      f = F_QKVA + grp * 4 + ((0xE4390900u >> (2 * (tile - 30))) & 3);
    }
    BULK_COMMIT();
    BULK_WAIT(0);
    mbar_arrive_one(c.bar + (B_SE + b) * 8);
    flag_add_rx(f);
  }
}

__device__ __forceinline__ int p2_buf(int w, int i) { return w * 2 + (i & 1); }
__device__ __forceinline__ int p2_blk(int rank, int w, int i) { return ((i ^ w) & 1) == 0 ? 3 - rank : rank; }

template <int N>
__device__ __forceinline__ void row_max(const float (&s)[N], float& m0, float& m1) {
  float a0 = fmaxf(s[0], s[1]), a1 = fmaxf(s[2], s[3]);
#pragma unroll
  for (int i = 1; i < N / 4; i++) {
    m0 = fmaxf(m0, s[4 * i]); a0 = fmaxf(a0, s[4 * i + 1]);
    m1 = fmaxf(m1, s[4 * i + 2]); a1 = fmaxf(a1, s[4 * i + 3]);
  }
  m0 = fmaxf(m0, a0); m1 = fmaxf(m1, a1);
  m0 = fmaxf(m0, __shfl_xor_sync(0xffffffffu, m0, 1));
  m1 = fmaxf(m1, __shfl_xor_sync(0xffffffffu, m1, 1));
  m0 = fmaxf(m0, __shfl_xor_sync(0xffffffffu, m0, 2));
  m1 = fmaxf(m1, __shfl_xor_sync(0xffffffffu, m1, 2));
}
template <bool SUB, int N>
__device__ __forceinline__ void row_exp(const float (&s)[N], uint32_t (&P)[32], float m0, float m1, float& t0, float& t1) {
  float u0 = 0.f, u1 = 0.f;
  t0 = t1 = 0.f;
#pragma unroll
  for (int i = 0; i < N / 4; i++) {
    const float e0 = ex2(SUB ? s[4 * i] - m0 : s[4 * i]), e1 = ex2(SUB ? s[4 * i + 1] - m0 : s[4 * i + 1]);
    const float e2 = ex2(SUB ? s[4 * i + 2] - m1 : s[4 * i + 2]), e3 = ex2(SUB ? s[4 * i + 3] - m1 : s[4 * i + 3]);
    if (i == 0) { t0 = e0; u0 = e1; t1 = e2; u1 = e3; }
    else { t0 += e0; u0 += e1; t1 += e2; u1 += e3; }
    P[2 * i] = pack_bf16(e0, e1);
    P[2 * i + 1] = pack_bf16(e2, e3);
  }
#pragma unroll
  for (int i = N / 2; i < 32; i++) P[i] = 0;
  pin(P);
  t0 += u0; t1 += u1;
}
template <int N>
__device__ __forceinline__ void causal_mask(float (&s)[N], int thr) {
#pragma unroll
  for (int i = 0; i < 8; i++) {
    if (8 * i > thr) s[N - 32 + 4 * i] = -INFINITY;
    if (8 * i + 1 > thr) s[N - 32 + 4 * i + 1] = -INFINITY;
    if (8 * i - 8 > thr) s[N - 32 + 4 * i + 2] = -INFINITY;
    if (8 * i - 7 > thr) s[N - 32 + 4 * i + 3] = -INFINITY;
  }
}
__device__ __forceinline__ void issue_qk(float (&s)[32], uint32_t qd, uint32_t kd) {
  WG_FENCE();
#pragma unroll
  for (int kk = 0; kk < 8; kk++) wgmma_ss64<0>(s, qd + (kk >> 2) * 512 + (kk & 3) * 2, kd + (kk >> 2) * 1024 + (kk & 3) * 2, kk != 0);
  WG_COMMIT();
}
__device__ __forceinline__ void issue_qk(float (&s)[64], uint32_t qd, uint32_t kd) {
  WG_FENCE();
#pragma unroll
  for (int kk = 0; kk < 8; kk++) wgmma_ss128<0>(s, qd + (kk >> 2) * 512 + (kk & 3) * 2, kd + (kk >> 2) * 1024 + (kk & 3) * 2, kk != 0);
  WG_COMMIT();
}
template <int NK>
__device__ __forceinline__ void issue_pv(float (&o)[64], const uint32_t (&P)[32], uint32_t vd, int acc) {
  WG_FENCE();
#pragma unroll
  for (int kk = 0; kk < NK; kk++) wgmma_rs128<1>(o, P[4 * kk], P[4 * kk + 1], P[4 * kk + 2], P[4 * kk + 3], vd + kk * 128, kk != 0 ? 1 : acc);
  WG_COMMIT();
}
__device__ __forceinline__ void stage_done(const Ctx& c, int b) {
  FENCE_ASYNC_SMEM();
  __syncwarp();
  if (c.lane == 0) mbar_arrive(c.bar + (B_SF + b) * 8);
}
__device__ __forceinline__ void p2_epilogue(const float (&o)[64], float s0, float s1, const Ctx& c, int b) {
  stage_tile(o, c.sm + SM_BUF + b * 16384, c, s0, s1);
  stage_done(c, b);
}

struct P2State {
  float m0, m1, l0, l1;
  bool shift;
  float e0, e1;
  int ks;
  int wi, ai;
  uint32_t wb, ab;
  uint32_t qd;
};
#define PROFZ()
__device__ __forceinline__ int wrap5(int q) { return q >= 5 ? q - 5 : q; }
__device__ __forceinline__ void turn_wait(uint32_t ring, int i) { mbar_wait(ring + (i & 3) * 8, (i >> 2) & 1); }
__device__ __forceinline__ void turn_pass(const Ctx& c, uint32_t ring, int i) { if (c.lane == 0) mbar_arrive(ring + (i & 3) * 8); }
__device__ __forceinline__ void p2_scales(P2State& z) {
  float l0 = z.l0, l1 = z.l1;
  l0 += __shfl_xor_sync(0xffffffffu, l0, 1);
  l1 += __shfl_xor_sync(0xffffffffu, l1, 1);
  l0 += __shfl_xor_sync(0xffffffffu, l0, 2);
  l1 += __shfl_xor_sync(0xffffffffu, l1, 2);
  asm("rcp.approx.ftz.f32 %0, %1;" : "=f"(z.e0) : "f"(l0));
  asm("rcp.approx.ftz.f32 %0, %1;" : "=f"(z.e1) : "f"(l1));
}
template <int N>
__device__ __forceinline__ void p2_first(const Ctx& c, P2State& z, float (&o)[64], uint32_t (&Pc)[32], uint32_t (&Pn)[32],
                                         int ks, int vs, int cnt, int acc) {
  float s[N] = {};
  issue_qk(s, z.qd, desc_lo(c.sm + SM_RING, 16) + ks * 2048);
  if (vs >= 0) {
    p2_scales(z);
    issue_pv<8>(o, Pc, desc_lo(c.sm + SM_RING, 16384) + vs * 2048, acc);
  } else {
    WG_COMMIT();
  }
  mbar_expect(z.ab + (z.ai++ & 3) * 8, cnt == 1 ? 8192 : 0);
  PROFZ();
  WG_WAIT(1);
  PROFZ();
  pin(s);
  release(c, B_P2E + ks, cnt);
  causal_mask(s, c.warp * 16 + (c.lane >> 2) - 2 * (c.lane & 3));
  z.m0 = z.m1 = 0.f;
  row_exp<false>(s, Pn, 0.f, 0.f, z.l0, z.l1);
  z.shift = __any_sync(0xffffffffu, !(z.l0 + z.l1 <= SM_HI) || ((c.lane & 3) == 0 && !(fminf(z.l0, z.l1) >= SM_LO)));
  if (__builtin_expect(z.shift, 0)) {
    z.m0 = z.m1 = -INFINITY;
    row_max(s, z.m0, z.m1);
    row_exp<true>(s, Pn, z.m0, z.m1, z.l0, z.l1);
  }
  WG_WAIT(0);
  pin(o);
  if (vs >= 0) release(c, B_P2E + vs, 1);
}

template <bool SECOND>
__device__ __forceinline__ void p2_turn(const Ctx& c, P2State& z, float (&o)[64], uint32_t (&Pc)[32], uint32_t (&Pn)[32],
                                        int eb = -1, bool half = false, int vcnt = 1) {
  float s[64] = {};
  const int ks = z.ks, vs = wrap5(ks + 1);
  PROFZ();
  turn_wait(z.wb, z.wi++);
  PROFZ();
  issue_qk(s, z.qd, desc_lo(c.sm + SM_RING, 16) + ks * 2048);
  const uint32_t vd = desc_lo(c.sm + SM_RING, 16384) + vs * 2048;
  if (SECOND) {
    if (eb >= 0) stage_tile(o, c.sm + SM_BUF + eb * 16384, c, z.e0, z.e1);
    if (half) issue_pv<4>(o, Pc, vd, 0); else issue_pv<8>(o, Pc, vd, 0);
  } else {
    issue_pv<8>(o, Pc, vd, 1);
  }
  turn_pass(c, z.ab, z.ai++);
  if (SECOND) { if (eb >= 0) stage_done(c, eb); }
  PROFZ();
  z.ks = wrap5(ks + 2);
  WG_WAIT(1);
  PROFZ();
  pin(s);
  release(c, B_P2E + ks, 1);
  float t0, t1, a0 = 1.f, a1 = 1.f;
  row_exp<false>(s, Pn, 0.f, 0.f, t0, t1);
  z.shift = __any_sync(0xffffffffu, z.shift || !(t0 + t1 <= SM_HI));
  const bool redo = z.shift;
  if (__builtin_expect(redo, 0)) {
    float n0 = z.m0, n1 = z.m1;
    row_max(s, n0, n1);
    a0 = ex2(z.m0 - n0); a1 = ex2(z.m1 - n1);
    z.m0 = n0; z.m1 = n1;
    z.l0 *= a0; z.l1 *= a1;
    row_exp<true>(s, Pn, z.m0, z.m1, t0, t1);
  }
  WG_WAIT(0);
  pin(o);
  release(c, B_P2E + vs, vcnt);
  if (__builtin_expect(redo, 0)) {
#pragma unroll
    for (int i = 0; i < 16; i++) { o[4 * i] *= a0; o[4 * i + 1] *= a0; o[4 * i + 2] *= a1; o[4 * i + 3] *= a1; }
  }
  z.l0 += t0; z.l1 += t1;
}
__device__ __forceinline__ void copy_p(uint32_t (&d)[32], const uint32_t (&s)[32], int zero) {
#pragma unroll
  for (int i = 0; i < 32; i++) asm volatile("add.s32 %0, %1, %2;" : "=r"(d[i]) : "r"(s[i]), "r"(zero));
}

__device__ __forceinline__ void p2_consumer(const Params& p, const Ctx& c, int rot) {
  const int nit = p.s.r[c.cl].n2;
  const uint32_t fring = c.bar + B_P2F * 8, oring = c.bar + B_ORD * 8;
  float o[64] = {};
  uint32_t Pa[32] = {}, Pb[32] = {};
  P2State z;
  z.e0 = z.e1 = z.l0 = z.l1 = 0.f; z.ks = rot; z.shift = false;
  int acc = 0, n = 0;
  for (int it = 0; it < nit; it++) {
    const int j = p.s.r[c.cl].item[it] & 7, blk = p2_blk(c.rank, c.wg, it);
    const int lng = ((it ^ c.wg) & 1) ^ 1;
    z.qd = desc_lo(c.sm + SM_BUF, 16) + p2_buf(c.wg, it) * 1024;
    if (lng) { z.wb = oring; z.wi = n - it; z.ab = fring; z.ai = n + 1; }
    else { z.wb = fring; z.wi = n + 2; z.ab = oring; z.ai = n - it; }
    PROFZ();
    mbar_wait(c.bar + (B_QF + p2_buf(c.wg, it)) * 8, (it >> 1) & 1);
    turn_wait(fring, n + 1 - lng);
    PROFZ();
    const int vs = it ? wrap5(z.ks + 1) : -1, ks = lng ? z.ks : wrap5(z.ks + (it ? 2 : 1));
    if (blk & 1) p2_first<64>(c, z, o, Pa, Pb, ks, vs, 1 + lng, acc);
    else p2_first<32>(c, z, o, Pa, Pb, ks, vs, 1 + lng, acc);
    z.ks = wrap5(ks + (it == 0 && lng ? 1 : 2));
    PROF(c.wg, 24 + it);
    n += 2 * j + 2;
    int left = 2 * j + lng;
    acc = left != 0;
    if (left == 0) { copy_p(Pa, Pb, p.zero); continue; }
    p2_turn<true>(c, z, o, Pb, Pa, it > 0 ? p2_buf(c.wg, it - 1) : -1, !(blk & 1), 1 + lng);
    while (--left > 0) {
      p2_turn<false>(c, z, o, Pa, Pb);
      if (--left == 0) { copy_p(Pa, Pb, p.zero); break; }
      p2_turn<false>(c, z, o, Pb, Pa);
    }
  }
  {
    if (!acc && nit > 1) p2_epilogue(o, z.e0, z.e1, c, p2_buf(c.wg, nit));
    turn_wait(z.wb, z.wi);
    issue_pv<8>(o, Pa, desc_lo(c.sm + SM_RING, 16384) + z.ks * 2048, acc);
    if (((nit - 1) ^ c.wg) & 1) turn_pass(c, z.ab, z.ai);
    p2_scales(z);
    WG_WAIT(0);
    pin(o);
    release(c, B_P2E + z.ks);
    p2_epilogue(o, z.e0, z.e1, c, p2_buf(c.wg, nit - 1));
    PROF(c.wg, 24 + nit);
  }
}

__device__ __forceinline__ void p2_load_q(const Params& p, const Ctx& c, int it, int w) {
  const int item = p.s.r[c.cl].item[it], h = item >> 3, j = item & 7, b = p2_buf(w, it);
  mbar_expect(c.bar + (B_QF + b) * 8, 16384);
  bulk_load(c.sm + SM_BUF + b * 16384, g_Q + (size_t)(h * 32 + j * 4 + p2_blk(c.rank, w, it)) * 16384, 16384, c.bar + (B_QF + b) * 8, POL(4));
}
__device__ __forceinline__ void wait_p1_free(const Ctx& c, int u1, int s) {
  mbar_wait(c.bar + (B_P1E + 2 * s) * 8, ((u1 - 1 - 2 * s) / 10) & 1);
  mbar_wait(c.bar + (B_P1E + 2 * s + 1) * 8, ((u1 - 2 - 2 * s) / 10) & 1);
}
__device__ __forceinline__ void p2_producer(const Params& p, const Ctx& c, int u1, int rot) {
  const int nit = p.s.r[c.cl].n2;
  int slot = rot, cnt = 0, par = 1, n = 0;
  const uint8_t* pv = nullptr;
  bool pl = false;
  auto load = [&](const uint8_t* src, int expect, uint32_t fb, bool last) {
    if (cnt < 5) {
      if (u1) {
        wait_p1_free(c, u1, slot);
        if (cnt == 0) p2_load_q(p, c, 0, 1);
      }
      cnt++;
    } else {
      if (slot == rot) par ^= 1;
      mbar_wait(c.bar + (B_P2E + slot) * 8, par);
    }
    if (expect) mbar_expect(fb, expect);
    bulk_load_mc(c.sm + SM_RING + slot * 32768 + c.rank * 16384, src, 16384, fb, last ? POL(5) : L2_NORMAL);
    slot = wrap5(slot + 1);
  };
  for (int it = 0; it < nit; it++) {
    const int item = p.s.r[c.cl].item[it], h = item >> 3, j = item & 7;
    uint32_t ready = (c.phases & 16) ? 0u : 255u;
    if (it == 0) { if (c.phases & 16) flag_wait<false>(F_Q + item, 4); mbar_wait(c.bar + B_LAD * 8, 0); p2_load_q(p, c, 0, 0); if (!u1) p2_load_q(p, c, 0, 1); }
    for (int t = 2 * j + 1; t >= 0; t--) {
      for (int n1 = 0; !((ready >> (t >> 1)) & 1); n1++) {
        int v;
        if (n1) { __nanosleep(32); if (n1 > 20000000) __trap(); }
        asm volatile("ld.relaxed.gpu.global.s32 %0, [%1];" : "=r"(v) : "l"(g_flags + F_KV + h * 8 + (c.lane & 7)) : "memory");
        ready = __ballot_sync(0xffffffffu, v >= 8);
      }
      const uint8_t* k = g_KV + (size_t)(p.s.slot[h][t >> 1] * 16 + t) * 32768 + c.rank * 16384;
      const uint32_t fb = c.bar + (B_P2F + (n & 3)) * 8;
      const bool last = (p.s.r[c.cl].last[it] >> (t >> 1)) & 1;
      load(k, pv && t != 2 * j ? 65536 : 32768, fb, last);
      if (!(t & 1) && t + 4 <= 2 * j && c.rank == 0) flag_add_rx(F_RD + h * 8 + (t >> 1) + 2);
      if (pv) load(pv, 0, t != 2 * j ? fb : c.bar + (B_ORD + ((n - 1 - it) & 3)) * 8, pl);
      pl = last;
      pv = k + (size_t)NH * 16 * 32768;
      n++;
    }
  }
  load(pv, 32768, c.bar + (B_P2F + (n & 3)) * 8, pl);
}

__device__ __forceinline__ void p2_storer(const Params& p, const Ctx& c, int sfpar) {
  const int nit = p.s.r[c.cl].n2;
  auto load_q = [&](int it, int w) {
    if (c.phases & 16) flag_wait<false>(F_Q + p.s.r[c.cl].item[it], 4);
    p2_load_q(p, c, it, w);
  };
  if (nit > 1) {
    load_q(1, 1); p2_load_q(p, c, 1, 0); }
  for (int i = 0; i < 2 * nit; i++) {
    const int it = i >> 1, w = (it ^ i ^ 1) & 1, b = p2_buf(w, it);
    const int item = p.s.r[c.cl].item[it], h = item >> 3, j = item & 7;
    mbar_wait(c.bar + (B_SF + b) * 8, (sfpar >> b) & 1);
    sfpar ^= 1 << b;
    bulk_store(g_Q + (size_t)(h * 32 + j * 4 + p2_blk(c.rank, w, it)) * 16384, c.sm + SM_BUF + b * 16384, 16384, POL(1));
    BULK_COMMIT();
    BULK_WAIT(0);
    flag_add_rx(F_CTX + j * 64 + h);
    if ((i & 1) && it + 2 < nit) { load_q(it + 2, w); p2_load_q(p, c, it + 2, w ^ 1); }
  }
  release(c, B_DONE);
}

__device__ __forceinline__ int p3_pos(int i, int x) { return i < 4 ? (i + x) & 3 : 4; }
__device__ __forceinline__ void p3_consumer(const Params& p, const Ctx& c, int x) {
  const bool first = p.s.r[c.cl].p3 >= 24;
  const int tile = p.s.r[c.cl].p3 - (first ? 24 : 0), j = tile / 3, nt = tile - 3 * j;
  const int na = first ? 9 : 0, nb = first ? 2 * p.s.nh[tile] : 64 - 2 * p.s.nh[tile];
  const uint32_t ad = desc_lo(c.sm + SM_RING + c.wg * 8192, 16), bd = desc_lo(c.sm + SM_RING + 16384, 4096);
  float acc[96] = {};
  int slot = 0, par = 0, prev = 0;
  float g0 = 0.f, g1 = 0.f;
#pragma unroll 1
  for (int kb = 0; kb < nb; kb++) {
    mbar_wait(c.bar + (B_P3F + slot) * 8, par);
    if (kb == 0) PROF(c.wg, 39);
    WG_FENCE();
#pragma unroll
    for (int kk = 0; kk < 4; kk++) wgmma_ss192<1>(acc, ad + p3_pos(slot, x) * 2560 + kk * 2, bd + p3_pos(slot, x) * 2560 + (kk >> 1) * 768 + (kk & 1) * 128, kk != 0 ? 1 : kb != 0);
    WG_COMMIT();
    WG_WAIT(1);
    if (kb > 0) release(c, B_P3E + prev);
    else {
      const float* g = g_gate + j * 256 + c.rank * 128 + c.wg * 64 + c.warp * 16 + (c.lane >> 2);
      g0 = __ldcg(g); g1 = __ldcg(g + 8);
    }
    prev = slot;
    if (++slot == 5) { slot = 0; par ^= 1; }
  }
  WG_WAIT(0);
  pin(acc);
  g0 = 1.f - g0; g1 = 1.f - g1;
#pragma unroll
  for (int i = 0; i < 24; i++) { acc[4 * i] *= g0; acc[4 * i + 1] *= g0; acc[4 * i + 2] *= g1; acc[4 * i + 3] *= g1; }
#pragma unroll 1
  for (int kb = nb; kb < nb + na; kb++) {
    mbar_wait(c.bar + (B_P3F + slot) * 8, par);
    if (kb == 0) PROF(c.wg, 39);
    WG_FENCE();
#pragma unroll
    for (int kk = 0; kk < 4; kk++) wgmma_ss192<1, 1>(acc, ad + p3_pos(slot, x) * 2560 + kk * 128, bd + p3_pos(slot, x) * 2560 + (kk >> 1) * 768 + (kk & 1) * 128, 1);
    WG_COMMIT();
    WG_WAIT(1);
    if (kb > 0) release(c, B_P3E + prev);
    prev = slot;
    if (++slot == 5) { slot = 0; par ^= 1; }
  }
  WG_WAIT(0);
  pin(acc);
  PROF(c.wg, 40);
  if (first) bar_sync(4 + c.wg, 128);
  mbar_wait(c.bar + B_OUT * 8, 0);
  const int row = (c.lane & 7) + ((c.lane >> 3) & 1) * 8;
  const uint32_t wbase = c.sm + SM_RING + c.wg * 8192 + c.warp * 2048;
  const uint32_t base = wbase + row * 128 + (((c.lane >> 4) ^ (row & 7)) << 4);
#pragma unroll
  for (int i = 0; i < 12; i++) {
    stsm4((base ^ ((i & 3) << 5)) + (i >> 2) * 40960, pack_bf16(acc[8 * i], acc[8 * i + 1]), pack_bf16(acc[8 * i + 2], acc[8 * i + 3]),
          pack_bf16(acc[8 * i + 4], acc[8 * i + 5]), pack_bf16(acc[8 * i + 6], acc[8 * i + 7]));
    if ((i & 3) == 3) {
      FENCE_ASYNC_SMEM();
      __syncwarp();
      const int c0 = nt * 192 + (i >> 2) * 64, c1 = j * 256 + c.rank * 128 + c.wg * 64 + c.warp * 16;
      tma2d_add(&p.map_out, wbase + (i >> 2) * 40960, c0, c1);
    }
  }
  BULK_COMMIT();
  PROF(c.wg, 43);
  BULK_WAIT_READ(0);
  PROF(c.wg, 44);
}

__device__ __forceinline__ void p3_producer(const Params& p, const Ctx& c, int u1, int u2, int rot, int x) {
  const bool first = p.s.r[c.cl].p3 >= 24;
  const int tile = p.s.r[c.cl].p3 - (first ? 24 : 0), j = tile / 3, nt = tile - 3 * j;
  int slot = 0, par = 1, cnt = 0;
  auto wait_free = [&](int s) {
    const int f = wrap5(s + 5 - rot);
    if (f < u2) mbar_wait(c.bar + (B_P2E + s) * 8, ((u2 - 1 - f) / 5) & 1);
    else if (u1) wait_p1_free(c, u1, s);
  };
  asm volatile(ELECT("prefetch.tensormap [%0];") ::"l"(&p.map_o[0]) : "memory");
  asm volatile(ELECT("prefetch.tensormap [%0];") ::"l"(&p.map_out) : "memory");
  if (c.phases & 16) flag_wait<true>(F_GATE, 256);
  const int q1 = first ? p.s.nh[tile] : 31;
  for (int q = first ? 0 : p.s.nh[tile]; q <= q1; q++) {
    const bool brA = first && q == q1;
    const int g = brA ? 32 : p.s.p3_order[j][q];
    if (c.phases & 16) flag_wait<false>(F_CTX + j * 64 + g, brA ? 16 : 4);
    const int nk = brA ? 9 : 2, k0 = (brA ? 0 : g * 128) + c.rank * 32;
    const uint8_t* a = brA ? g_oA + (j * 4 + c.rank * 2) * 73728 : g_Q + (size_t)(g * 32 + j * 4 + c.rank * 2) * 16384;
    const CUtensorMap* m = &p.map_o[brA];
    for (int i = 0; i < nk; i++) {
      const uint32_t st = c.sm + SM_RING + p3_pos(slot, x) * 40960, fb = c.bar + (B_P3F + slot) * 8;
      if (cnt < 4) { wait_free(p3_pos(cnt, x)); wait_free(p3_pos(cnt, x) + 1); }
      else if (cnt == 4) mbar_wait(c.bar + B_DONE * 8, 0);
      else mbar_wait(c.bar + (B_P3E + slot) * 8, par);
      cnt++;
      mbar_expect(fb, 40960);
      bulk_load(st, a + i * 8192, 8192, fb, POL(3));
      bulk_load(st + 8192, a + (nk + i) * 8192, 8192, fb, POL(3));
      tma3d_mc(st + 16384 + c.rank * 12288, m, 0, k0 + i * 64, nt * 3, fb);
      if (++slot == 5) { slot = 0; par ^= 1; }
    }
  }
}

__device__ __forceinline__ float bf_lo(uint32_t w) { return __uint_as_float(w << 16); }
__device__ __forceinline__ float bf_hi(uint32_t w) { return __uint_as_float(w & 0xffff0000u); }

__device__ __forceinline__ void gate_rows(const Params& p, int row0, int lane) {
  const uint4* x = reinterpret_cast<const uint4*>(p.x + (size_t)(row0 + (lane >> 2)) * DM) + (lane & 3);
  const uint4* w = reinterpret_cast<const uint4*>(p.gate_w) + (lane & 3);
  float a = 0.f;
#pragma unroll 1
  for (int b = 0; b < 3; b++) {
    uint4 u[6];
#pragma unroll
    for (int i = 0; i < 6; i++) u[i] = __ldg(x + (b * 6 + i) * 4);
#pragma unroll
    for (int i = 0; i < 6; i++) {
      const uint4 v = __ldg(w + (b * 6 + i) * 4);
      a = fmaf(bf_lo(u[i].x), bf_lo(v.x), a); a = fmaf(bf_hi(u[i].x), bf_hi(v.x), a);
      a = fmaf(bf_lo(u[i].y), bf_lo(v.y), a); a = fmaf(bf_hi(u[i].y), bf_hi(v.y), a);
      a = fmaf(bf_lo(u[i].z), bf_lo(v.z), a); a = fmaf(bf_hi(u[i].z), bf_hi(v.z), a);
      a = fmaf(bf_lo(u[i].w), bf_lo(v.w), a); a = fmaf(bf_hi(u[i].w), bf_hi(v.w), a);
    }
  }
  a += __shfl_xor_sync(0xffffffffu, a, 1);
  a += __shfl_xor_sync(0xffffffffu, a, 2);
  if ((lane & 3) == 0) g_gate[row0 + (lane >> 2)] = 1.f / (1.f + __expf(-a));
}

__device__ __forceinline__ void lds10(uint32_t (&k)[10], uint32_t a) {
  asm volatile("ld.shared.v2.u32 {%0, %1}, [%10];\nld.shared.v2.u32 {%2, %3}, [%10+8];\nld.shared.v2.u32 {%4, %5}, [%10+16];\n"
               "ld.shared.v2.u32 {%6, %7}, [%10+24];\nld.shared.v2.u32 {%8, %9}, [%10+32];"
               : "=r"(k[0]), "=r"(k[1]), "=r"(k[2]), "=r"(k[3]), "=r"(k[4]), "=r"(k[5]), "=r"(k[6]), "=r"(k[7]), "=r"(k[8]), "=r"(k[9]) : "r"(a));
}
__device__ __forceinline__ void local_attn(const Params& p, const Ctx& c, int rb, int hs) {
  const int lane = c.lane, grp = rb >> 2, par = lane >> 4, i0 = 2 * (lane & 15);
  const uint32_t buf = c.sm + SM_BUF + (c.warp - 2) * 8192, bqk = c.bar + (B_LA + (c.warp - 2) * 2) * 8, bv = bqk + 8;
  const uint32_t mine = buf + 2304 + par * 160 + i0 * 4;
  const bool flags = c.phases & 16;
  auto fetch_qk = [&](int i) {
    if (flags && !(i & 1)) {
      const int q = i >> 1;
      const int tgt = q == 0 ? 24 : q == 3 ? 8 : 12;
      flag_wait<false>(F_QKVA + (grp - (grp > 0 && (rb & 3) == 0 ? par : 0)) * 4 + q, tgt);
    }
    mbar_expect(bqk, 5184);
    tma3d(buf, &p.map_t[0], rb * 32 + 8, 0, 9 * (4 * i + hs), bqk, POL(2));
    tma3d(buf + 2304, &p.map_t[1], rb * 32, 0, 288 + 9 * (4 * i + hs), bqk, POL(2));
  };
  auto fetch_v = [&](int i) { mbar_expect(bv, 2880); tma3d(buf + 5248, &p.map_t[1], rb * 32, 0, 576 + 9 * (4 * i + hs), bv, POL(2)); };
  fetch_qk(0);
  if (flags) flag_wait<true>(F_GATE, 256);
#pragma unroll 1
  for (int q = 0; q < 8; q++) {
    fetch_v(q);
    float a[8], b[8];
#pragma unroll
    for (int w = 0; w < 8; w++) a[w] = b[w] = 0.f;
    mbar_wait(bqk, q & 1);
    PROFB(1 + 2 * q);
#pragma unroll 1
    for (int j = 0; j < 9; j++) {
      uint32_t x, y, k[10];
      asm volatile("ld.shared.v2.u32 {%0, %1}, [%2];" : "=r"(x), "=r"(y) : "r"(buf + lane * 8 + j * 256));
      lds10(k, mine + j * 320);
      const float xl = bf_lo(x), xh = bf_hi(x), yl = bf_lo(y), yh = bf_hi(y);
#pragma unroll
      for (int m = 1; m < 10; m++) {
        const float kl = bf_lo(k[m]), kh = bf_hi(k[m]);
        if (m < 9) a[8 - m] = fmaf(xl, kl, fmaf(xh, kh, a[8 - m]));
        if (m > 1) b[9 - m] = fmaf(yl, kl, fmaf(yh, kh, b[9 - m]));
      }
    }
    __syncwarp();
    if (q < 7) fetch_qk(q + 1);
    constexpr float SC = 0.23570226039551584f * 1.4426950408889634f;
    const float* gp = g_gate + rb * 64 + 2 * i0 + par;
    const float ga = __ldcg(gp), gb = __ldcg(gp + 2);
    float ma = a[0], mb = b[0];
#pragma unroll
    for (int w = 1; w < 8; w++) {
      if (rb == 0) {
        if (i0 < w) a[w] = -INFINITY;
        if (i0 + 1 < w) b[w] = -INFINITY;
      }
      ma = fmaxf(ma, a[w]); mb = fmaxf(mb, b[w]);
    }
    float la = 0.f, lb = 0.f;
#pragma unroll
    for (int w = 0; w < 8; w++) {
      a[w] = ex2((a[w] - ma) * SC); b[w] = ex2((b[w] - mb) * SC);
      la += a[w]; lb += b[w];
    }
    la = __fdividef(ga, la); lb = __fdividef(gb, lb);
#pragma unroll
    for (int w = 0; w < 8; w++) { a[w] *= la; b[w] *= lb; }
    uint8_t* dst = g_oA + rb * 73728 + ((i0 & 2) + par) * 4;
    mbar_wait(bv, q & 1);
#pragma unroll 1
    for (int j = 0; j < 9; j++) {
      uint32_t v[10];
      lds10(v, mine + 2944 + j * 320);
      float a0 = 0.f, a1 = 0.f, b0 = 0.f, b1 = 0.f;
#pragma unroll
      for (int m = 1; m < 10; m++) {
        const float vl = bf_lo(v[m]), vh = bf_hi(v[m]);
        if (m < 9) { a0 = fmaf(a[8 - m], vl, a0); a1 = fmaf(a[8 - m], vh, a1); }
        if (m > 1) { b0 = fmaf(b[9 - m], vl, b0); b1 = fmaf(b[9 - m], vh, b1); }
      }
      const uint32_t wa = pack_bf16(a0, a1), wb = pack_bf16(b0, b1);
      const uint32_t got = __shfl_xor_sync(0xffffffffu, par ? wa : wb, 16);
      const uint32_t r0 = par ? got : wa, r1 = par ? wb : got;
      const int col = 18 * (4 * q + hs) + 2 * j, o = col * 128 + ((((i0 >> 2) ^ col) & 7) << 4);
      *reinterpret_cast<uint32_t*>(dst + o) = __byte_perm(r0, r1, 0x5410);
      *reinterpret_cast<uint32_t*>(dst + ((o + 128) ^ 16)) = __byte_perm(r0, r1, 0x7632);
    }
    __syncwarp();
    PROFB(2 + 2 * q);
  }
  mbar_arrive_one(c.bar + B_LAD * 8);
  flag_add(F_CTX + grp * 64 + 32);
}

__global__ void __cluster_dims__(2, 1, 1) __launch_bounds__(384, 1) fused_kernel(const __grid_constant__ Params p) {
  extern __shared__ uint8_t smem_raw[];
  Ctx c;
  c.sm = ((uint32_t)__cvta_generic_to_shared(smem_raw) + 1023u) & ~1023u;
  c.bar = c.sm + SM_BAR;
  c.lane = threadIdx.x & 31;
  const int wid = __shfl_sync(0xffffffffu, threadIdx.x >> 5, 0);
  if (wid < 6) asm volatile("prefetch.tensormap [%0];" ::"l"(&p.map_a[0] + wid) : "memory");
  c.wg = wid >> 2;
  c.warp = wid & 3;
  PROF(c.wg, 0);
  PROFG(61);
  c.cl = (blockIdx.x + (wid >> 4)) >> 1;
  c.rank = blockIdx.x & 1;
  c.rbar = mapa(c.bar, c.lane & 1);
  {
    const int w = wid, cnt = (((int)(B_CNT >> (4 * w)) - 1) & 15) + 1;
    if (w < 11) {
#pragma unroll
      for (int i = 0; i < 8; i++) asm volatile("mbarrier.init.shared::cta.b64 [%0], %1;" ::"r"(c.bar + w * 64 + i * 8), "r"(cnt));
    }
    asm volatile("fence.mbarrier_init.release.cluster;" ::: "memory");
  }
  if (c.wg == 2) PROF(2, 56);
  asm volatile("barrier.cluster.arrive.relaxed;" ::: "memory");
  c.phases = p.s.r[c.cl].phases;
  const bool do1 = p.s.r[c.cl].n1 > 0, do2 = p.s.r[c.cl].n2 > 0, do3 = p.s.r[c.cl].p3 != 255;
  if (do1 && c.wg == 2 && c.warp == 0) {
    const int type = p.s.r[c.cl].slab >> 3;
    PROF(2, 57);
    FENCE_ASYNC_SMEM();
    mbar_expect(c.bar + B_P1F * 8, type ? 32768 : 16384);
    tma2d(type ? c.sm + SM_BUF + 32768 : c.sm + SM_RING, &p.map_a[type], type ? 512 : 0, (p.s.r[c.cl].slab & 7) * 256 + c.rank * 128, c.bar + B_P1F * 8);
    PROF(2, 58);
  }
  asm volatile("barrier.cluster.wait.acquire;" ::: "memory");
  if (c.wg == 2) PROF(2, 59);
  if (do1 && c.wg == 2 && c.warp == 0) {
    const int type = p.s.r[c.cl].slab >> 3, tile = p.s.r[c.cl].tile[0] & 63;
    if (!type) mbar_expect(c.bar + (B_P1F + 1) * 8, 16384);
    tma2d_mc(c.sm + SM_RING + (1 - type) * 16384 + c.rank * 8192, &p.map_w[type * 2 + (tile >> 5)], (tile & 31) * 128 + c.rank * 64, type ? 512 : 0, c.bar + (B_P1F + 1 - type) * 8);
  }

  if (c.wg < 2) {
    PROF(c.wg, 4);
    asm volatile("setmaxnreg.inc.sync.aligned.u32 224;");
    if (c.wg == 1) {
      if (do1) bar_arrive(ORDER, 256);
      if (c.lane == 0) mbar_arrive(c.bar + B_P2F * 8);
    }
    if (do1) p1_consumer(p, c);
    if (do2) p2_consumer(p, c, p.s.r[c.cl].rot);
    if (do3) p3_consumer(p, c, p.s.r[c.cl].x3);
    PROF(c.wg, 63);
    PROFG(62);
    if (c.lane == 0) mbar_arrive(c.bar + B_FIN * 8);
    __syncwarp();
    cluster_sync();
  } else {
    asm volatile("setmaxnreg.dec.sync.aligned.u32 56;");
    if (c.warp == 0) {
      PROF(2, 60);
      if (do1) p1_producer(p, c);
      if (do2) p2_producer(p, c, p.s.r[c.cl].u1, p.s.r[c.cl].rot);
      if (do3) p3_producer(p, c, p.s.r[c.cl].u1, p.s.r[c.cl].u2, p.s.r[c.cl].rot, p.s.r[c.cl].x3);
    } else if (c.warp == 1) {
      int sfpar = 0;
      if (do1) {
        p1_storer(p, c);
        sfpar = (p.s.r[c.cl].n1 & 1) * 10;
      }
      if (do2) p2_storer(p, c, sfpar);
      else { mbar_wait(c.bar + B_LAD * 8, 0); release(c, B_DONE); }
      if (do3) {
        const int task = p.s.r[c.cl].p3;
        if (task >= 24) {
          const int j = (task - 24) / 3, nt = task - 24 - 3 * j;
          uint4* o = reinterpret_cast<uint4*>(p.out + (size_t)(j * 256 + c.rank * 128 + (c.lane >> 3)) * DM + nt * 192) + (c.lane & 7);
#pragma unroll 4
          for (int r = 0; r < 32; r++) o[r * 288] = o[r * 288 + 8] = o[r * 288 + 16] = make_uint4(0u, 0u, 0u, 0u);
          __syncwarp();
          flag_add(F_OUT + (task - 24) * 2 + c.rank);
        } else if (c.phases & 16) {
          flag_wait<false, 256>(F_OUT + task * 2 + c.rank, 1);
        }
        mbar_arrive_one(c.bar + B_OUT * 8);
      }
    } else {
      const int bw = blockIdx.x * 2 + (c.warp - 2);
      if ((c.phases & 1) && bw < 256) {
        gate_rows(p, bw * 8, c.lane);
        __syncwarp();
        flag_add(F_GATE);
      }
      if (p.s.r[c.cl].bg != 255) local_attn(p, c, p.s.r[c.cl].bg, bw & 3);
      else if (c.lane == 0) mbar_arrive(c.bar + B_LAD * 8);
    }
    __syncwarp();
    bar_sync(3, 128);
    if (c.warp == 0 && (c.phases & 4)) {
      int last = 0;
      if (c.lane == 0) { __threadfence(); last = atomicAdd(g_flags + F_DONE, 1) == 2 * NCL - 1; }
      if (__shfl_sync(0xffffffffu, last, 0)) for (int i = c.lane; i < F_NUM; i += 32) g_flags[i] = 0;
    }
    if (c.warp == 1) mbar_wait(c.bar + B_FIN * 8, 0);
    __syncwarp();
    cluster_sync();
  }
}

SCHED_DECL Sched k_sched = {
  {{0,29,2,26,0,{232,248,0,0,0,0,0,0,0,0,0},{0,0,0,0,0,0,0,0,0,0,0},{71,38,3,32,5,4,2,11,9,24,21,12,19,17,74,20,13,22,16,18,28,14,29,26,31,23,27,30,25,0}},
   {1,29,2,255,1,{216,244,0,0,0,0,0,0,0,0,0},{0,0,0,0,0,0,0,0,0,0,0},{71,38,0,40,79,4,2,11,9,24,21,19,17,12,20,13,10,22,16,18,28,14,29,26,31,23,27,30,25,0}},
   {2,29,2,255,2,{217,243,0,0,0,0,0,0,0,0,0},{0,0,0,0,0,0,0,0,0,0,0},{67,40,7,32,1,15,4,9,11,24,19,21,17,12,13,20,16,22,10,18,28,14,29,31,26,23,27,30,25,0}},
   {3,29,1,255,3,{188,0,0,0,0,0,0,0,0,0,0},{0,0,0,0,0,0,0,0,0,0,0},{70,35,0,40,1,2,4,9,11,24,21,19,17,12,13,20,22,16,10,18,28,14,26,29,31,23,27,30,25,0}},
   {4,28,0,15,4,{0,0,0,0,0,0,0,0,0,0,0},{0,0,0,0,0,0,0,0,0,0,0},{64,39,8,38,1,2,36,24,11,21,12,19,17,20,13,22,16,10,18,28,14,29,26,31,23,27,30,25,0,0}},
   {5,28,0,14,5,{0,0,0,0,0,0,0,0,0,0,0},{0,0,0,0,0,0,0,0,0,0,0},{72,35,0,38,1,2,36,24,11,21,12,19,17,20,13,22,16,10,18,28,14,29,26,31,23,27,30,25,0,0}},
   {6,27,1,44,6,{212,0,0,0,0,0,0,0,0,0,0},{24,0,0,0,0,0,0,0,0,0,0},{71,8,6,37,2,15,41,11,21,12,19,17,20,13,86,16,10,18,28,14,29,26,31,27,23,30,25,0,0,0}},
   {7,26,2,36,7,{112,252,0,0,0,0,0,0,0,0,0},{0,0,0,0,0,0,0,0,0,0,0},{70,7,3,65,68,75,88,85,76,83,81,84,77,80,74,22,82,92,78,93,90,95,91,87,94,89,0,0,0,0}},
   {0,29,1,25,8,{251,0,0,0,0,0,0,0,0,0,0},{0,0,0,0,0,0,0,0,0,0,0},{103,8,35,65,37,36,34,43,41,56,53,44,51,49,106,52,45,54,48,50,60,46,61,58,63,55,59,62,57,0}},
   {1,29,1,255,9,{245,0,0,0,0,0,0,0,0,0,0},{56,0,0,0,0,0,0,0,0,0,0},{103,3,32,5,111,36,34,43,41,56,53,51,49,44,52,45,42,54,48,50,60,46,61,58,63,55,59,62,57,0}},
   {2,29,1,27,10,{210,0,0,0,0,0,0,0,0,0,0},{7,0,0,0,0,0,0,0,0,0,0},{99,6,39,5,33,47,36,41,43,56,51,53,49,44,45,52,48,54,42,50,60,46,61,63,58,55,59,62,57,0}},
   {3,29,2,255,11,{218,202,0,0,0,0,0,0,0,0,0},{0,0,0,0,0,0,0,0,0,0,0},{102,7,32,5,33,34,36,41,43,56,53,51,49,44,45,52,54,48,42,50,60,46,58,61,63,55,59,62,57,0}},
   {4,28,0,21,12,{0,0,0,0,0,0,0,0,0,0,0},{0,0,0,0,0,0,0,0,0,0,0},{96,3,40,5,33,34,9,56,43,53,44,51,49,52,45,54,48,42,50,60,46,61,58,63,55,59,62,57,0,0}},
   {5,28,0,4,13,{0,0,0,0,0,0,0,0,0,0,0},{0,0,0,0,0,0,0,0,0,0,0},{104,7,32,5,33,34,9,56,43,53,44,51,49,52,45,54,48,42,50,60,46,61,58,63,55,59,62,57,0,0}},
   {6,27,0,12,14,{0,0,0,0,0,0,0,0,0,0,0},{0,0,0,0,0,0,0,0,0,0,0},{103,40,38,65,34,47,88,43,53,44,51,49,52,45,118,48,42,50,60,46,61,58,63,59,55,62,57,0,0,0}},
   {7,26,0,9,15,{0,0,0,0,0,0,0,0,0,0,0},{0,0,0,0,0,0,0,0,0,0,0},{102,39,35,97,100,107,120,117,108,115,113,116,109,112,106,54,114,124,110,125,122,127,123,119,126,121,0,0,0,0}},
   {0,6,6,46,255,{0,59,22,194,107,215,0,0,0,0,0},{0,0,0,0,0,192,0,0,0,0,0},{70,40,0,97,79,47,0,0,0,0,0,0,0,0,0,0,0,0,0,0,0,0,0,0,0,0,0,0,0,0}},
   {1,6,6,8,255,{61,10,174,179,233,224,0,0,0,0,0},{0,0,0,0,0,0,0,0,0,0,0},{70,35,8,37,1,33,0,0,0,0,0,0,0,0,0,0,0,0,0,0,0,0,0,0,0,0,0,0,0,0}},
   {2,6,4,23,255,{47,93,100,226,0,0,0,0,0,0,0},{0,0,0,0,0,0,0,0,0,0,0},{72,38,0,37,2,34,0,0,0,0,0,0,0,0,0,0,0,0,0,0,0,0,0,0,0,0,0,0,0,0}},
   {3,6,7,29,255,{41,44,89,74,193,141,238,0,0,0,0},{0,0,0,0,0,0,0,0,0,0,0},{67,39,8,37,79,47,0,0,0,0,0,0,0,0,0,0,0,0,0,0,0,0,0,0,0,0,0,0,0,0}},
   {4,8,5,33,255,{58,125,102,239,241,0,0,0,0,0,0},{0,0,0,0,0,0,0,0,0,0,0},{71,35,6,37,79,47,4,41,0,0,0,0,0,0,0,0,0,0,0,0,0,0,0,0,0,0,0,0,0,0}},
   {5,8,5,37,255,{120,23,195,134,190,0,0,0,0,0,0},{0,0,0,0,0,0,0,0,0,0,0},{67,39,6,37,79,47,4,41,0,0,0,0,0,0,0,0,0,0,0,0,0,0,0,0,0,0,0,0,0,0}},
   {6,8,7,255,255,{40,43,34,159,83,211,219,0,0,0,0},{0,0,0,0,0,0,0,0,0,0,0},{64,3,69,97,68,36,9,56,0,0,0,0,0,0,0,0,0,0,0,0,0,0,0,0,0,0,0,0,0,0}},
   {7,6,6,31,255,{46,73,75,101,113,237,0,0,0,0,0},{0,0,0,0,0,63,0,0,0,0,0},{64,8,69,66,79,73,0,0,0,0,0,0,0,0,0,0,0,0,0,0,0,0,0,0,0,0,0,0,0,0}},
   {8,16,5,255,16,{192,170,148,250,220,0,0,0,0,0,0},{0,0,0,0,31,0,0,0,0,0,0},{160,170,0,43,35,44,45,4,11,12,21,19,16,22,14,27,0,0,0,0,0,0,0,0,0,0,0,0,0,0}},
   {9,19,1,11,17,{131,0,0,0,0,0,0,0,0,0,0},{0,0,0,0,0,0,0,0,0,0,0},{71,37,8,43,1,75,2,45,21,19,20,10,16,28,29,23,27,30,25,0,0,0,0,0,0,0,0,0,0,0}},
   {10,18,4,32,18,{152,130,229,184,0,0,0,0,0,0,0},{0,0,7,0,0,0,0,0,0,0,0},{160,170,166,163,15,40,9,83,81,21,20,10,92,22,95,26,89,30,0,0,0,0,0,0,0,0,0,0,0,0}},
   {11,17,4,255,19,{168,162,227,247,0,0,0,0,0,0,0},{0,0,0,192,0,0,0,0,0,0,0},{160,170,166,163,2,109,4,24,19,12,22,20,18,14,29,31,30,0,0,0,0,0,0,0,0,0,0,0,0,0}},
   {12,16,3,13,20,{72,156,144,0,0,0,0,0,0,0,0},{0,0,0,0,0,0,0,0,0,0,0},{160,170,6,1,15,9,45,24,12,17,20,16,18,14,95,23,0,0,0,0,0,0,0,0,0,0,0,0,0,0}},
   {13,16,3,18,21,{88,161,85,0,0,0,0,0,0,0,0},{0,0,0,0,0,0,0,0,0,0,0},{160,170,0,43,2,9,24,45,12,17,13,16,18,14,26,23,0,0,0,0,0,0,0,0,0,0,0,0,0,0}},
   {14,16,3,39,22,{137,108,117,0,0,0,0,0,0,0,0},{0,0,0,0,0,0,0,0,0,0,0},{160,170,6,1,4,88,40,21,19,84,13,10,92,93,95,23,0,0,0,0,0,0,0,0,0,0,0,0,0,0}},
   {15,16,5,255,23,{16,99,82,223,200,0,0,0,0,0,0},{1,0,0,192,0,0,0,0,0,0,0},{160,170,3,43,39,9,24,40,12,17,13,10,18,14,26,27,0,0,0,0,0,0,0,0,0,0,0,0,0,0}},
   {8,21,4,255,24,{128,234,209,205,0,0,0,0,0,0,0},{0,0,0,63,0,0,0,0,0,0,0},{164,70,65,5,39,40,2,9,24,17,74,13,18,20,28,29,31,23,26,25,30,0,0,0,0,0,0,0,0,0}},
   {9,16,3,3,25,{32,105,133,0,0,0,0,0,0,0,0},{1,0,0,0,0,0,0,0,0,0,0},{160,170,133,163,4,9,40,24,81,12,13,22,18,14,26,31,0,0,0,0,0,0,0,0,0,0,0,0,0,0}},
   {10,16,3,19,26,{96,165,176,0,0,0,0,0,0,0,0},{0,0,0,0,0,0,0,0,0,0,0},{164,131,107,103,4,109,11,24,12,77,80,82,78,93,91,23,0,0,0,0,0,0,0,0,0,0,0,0,0,0}},
   {11,17,4,47,27,{136,177,163,213,0,0,0,0,0,0,0},{0,0,0,32,0,0,0,0,0,0,0},{164,70,107,103,104,9,11,21,81,77,80,10,92,90,87,27,89,0,0,0,0,0,0,0,0,0,0,0,0,0}},
   {12,18,2,255,28,{231,221,0,0,0,0,0,0,0,0,0},{0,32,0,0,0,0,0,0,0,0,0},{164,64,34,163,4,40,11,21,19,77,22,10,92,93,26,27,30,25,0,0,0,0,0,0,0,0,0,0,0,0}},
   {13,18,3,255,29,{104,150,206,0,0,0,0,0,0,0,0},{0,3,0,0,0,0,0,0,0,0,0},{164,72,133,15,4,75,40,21,19,84,22,10,92,93,95,27,30,25,0,0,0,0,0,0,0,0,0,0,0,0}},
   {14,17,3,35,30,{80,181,254,0,0,0,0,0,0,0,0},{0,0,127,0,0,0,0,0,0,0,0},{164,7,133,15,73,75,45,76,81,86,80,82,78,90,91,94,89,0,0,0,0,0,0,0,0,0,0,0,0,0}},
   {15,18,3,41,31,{129,119,208,0,0,0,0,0,0,0,0},{0,0,0,0,0,0,0,0,0,0,0},{164,70,133,66,44,75,85,45,19,84,80,22,92,93,95,23,30,25,0,0,0,0,0,0,0,0,0,0,0,0}},
   {8,4,6,40,255,{25,15,17,173,164,191,0,0,0,0,0},{0,0,0,0,18,255,0,0,0,0,0},{169,7,34,15,0,0,0,0,0,0,0,0,0,0,0,0,0,0,0,0,0,0,0,0,0,0,0,0,0,0}},
   {9,4,4,10,255,{69,12,196,110,0,0,0,0,0,0,0},{0,0,0,0,0,0,0,0,0,0,0},{164,70,79,103,0,0,0,0,0,0,0,0,0,0,0,0,0,0,0,0,0,0,0,0,0,0,0,0,0,0}},
   {10,4,6,255,255,{55,33,175,132,253,242,0,0,0,0,0},{0,0,0,0,0,6,0,0,0,0,0},{169,72,7,108,0,0,0,0,0,0,0,0,0,0,0,0,0,0,0,0,0,0,0,0,0,0,0,0,0,0}},
   {11,4,4,5,255,{63,20,154,183,0,0,0,0,0,0,0},{188,0,0,131,0,0,0,0,0,0,0},{169,131,8,108,0,0,0,0,0,0,0,0,0,0,0,0,0,0,0,0,0,0,0,0,0,0,0,0,0,0}},
   {12,4,5,34,255,{7,124,158,146,189,0,0,0,0,0,0},{111,0,0,0,0,0,0,0,0,0,0},{169,7,166,103,0,0,0,0,0,0,0,0,0,0,0,0,0,0,0,0,0,0,0,0,0,0,0,0,0,0}},
   {13,4,7,38,255,{51,14,91,153,81,145,118,0,0,0,0},{0,0,0,0,0,0,95,0,0,0,0},{169,131,65,163,0,0,0,0,0,0,0,0,0,0,0,0,0,0,0,0,0,0,0,0,0,0,0,0,0,0}},
   {14,5,6,30,255,{54,36,169,138,180,236,0,0,0,0,0},{0,0,0,0,0,0,0,0,0,0,0},{169,64,34,66,44,0,0,0,0,0,0,0,0,0,0,0,0,0,0,0,0,0,0,0,0,0,0,0,0,0}},
   {15,4,8,43,255,{49,5,122,35,157,115,185,186,0,0,0},{0,0,0,0,47,0,0,0,0,0,0},{169,64,65,68,0,0,0,0,0,0,0,0,0,0,0,0,0,0,0,0,0,0,0,0,0,0,0,0,0,0}},
   {8,3,6,255,255,{70,18,197,109,116,204,0,0,0,0,0},{0,0,0,0,0,0,0,0,0,0,0},{161,72,166,0,0,0,0,0,0,0,0,0,0,0,0,0,0,0,0,0,0,0,0,0,0,0,0,0,0,0}},
   {9,3,4,0,255,{4,39,90,182,0,0,0,0,0,0,0},{0,0,0,0,0,0,0,0,0,0,0},{169,131,34,0,0,0,0,0,0,0,0,0,0,0,0,0,0,0,0,0,0,0,0,0,0,0,0,0,0,0}},
   {10,4,6,7,255,{48,28,42,76,172,228,0,0,0,0,0},{0,0,0,0,0,0,0,0,0,0,0},{161,70,0,66,0,0,0,0,0,0,0,0,0,0,0,0,0,0,0,0,0,0,0,0,0,0,0,0,0,0}},
   {11,4,6,255,255,{62,123,103,225,214,203,0,0,0,0,0},{0,0,0,0,0,0,0,0,0,0,0},{161,7,0,1,0,0,0,0,0,0,0,0,0,0,0,0,0,0,0,0,0,0,0,0,0,0,0,0,0,0}},
   {12,4,6,22,255,{64,65,68,21,142,114,0,0,0,0,0},{0,0,0,0,0,0,0,0,0,0,0},{161,131,107,108,0,0,0,0,0,0,0,0,0,0,0,0,0,0,0,0,0,0,0,0,0,0,0,0,0,0}},
   {13,4,5,24,255,{30,9,19,143,255,0,0,0,0,0,0},{0,0,0,0,128,0,0,0,0,0,0},{161,7,34,103,0,0,0,0,0,0,0,0,0,0,0,0,0,0,0,0,0,0,0,0,0,0,0,0,0,0}},
   {14,4,7,42,255,{24,1,13,77,139,149,187,0,0,0,0},{0,0,0,0,0,0,0,0,0,0,0},{161,72,166,163,0,0,0,0,0,0,0,0,0,0,0,0,0,0,0,0,0,0,0,0,0,0,0,0,0,0}},
   {15,4,4,6,255,{60,127,167,178,0,0,0,0,0,0,0},{0,0,0,0,0,0,0,0,0,0,0},{161,7,34,15,0,0,0,0,0,0,0,0,0,0,0,0,0,0,0,0,0,0,0,0,0,0,0,0,0,0}},
   {8,2,7,28,255,{26,121,2,38,155,230,249,0,0,0,0},{0,0,0,0,0,0,0,0,0,0,0},{165,131,0,0,0,0,0,0,0,0,0,0,0,0,0,0,0,0,0,0,0,0,0,0,0,0,0,0,0,0}},
   {9,4,4,16,255,{66,52,95,140,0,0,0,0,0,0,0},{0,0,0,0,0,0,0,0,0,0,0},{161,64,166,108,0,0,0,0,0,0,0,0,0,0,0,0,0,0,0,0,0,0,0,0,0,0,0,0,0,0}},
   {10,4,5,255,255,{6,11,92,151,207,0,0,0,0,0,0},{0,0,0,0,192,0,0,0,0,0,0},{165,98,133,1,0,0,0,0,0,0,0,0,0,0,0,0,0,0,0,0,0,0,0,0,0,0,0,0,0,0}},
   {11,4,4,17,255,{29,126,171,86,0,0,0,0,0,0,0},{0,0,0,124,0,0,0,0,0,0,0},{165,98,133,15,0,0,0,0,0,0,0,0,0,0,0,0,0,0,0,0,0,0,0,0,0,0,0,0,0,0}},
   {12,4,6,255,255,{71,198,98,84,222,201,0,0,0,0,0},{222,0,0,0,0,0,0,0,0,0,0},{165,72,133,66,0,0,0,0,0,0,0,0,0,0,0,0,0,0,0,0,0,0,0,0,0,0,0,0,0,0}},
   {13,4,7,255,255,{56,50,67,79,135,246,240,0,0,0,0},{0,0,0,192,255,0,1,0,0,0,0},{165,70,166,108,0,0,0,0,0,0,0,0,0,0,0,0,0,0,0,0,0,0,0,0,0,0,0,0,0,0}},
   {14,4,7,45,255,{27,3,78,97,106,147,235,0,0,0,0},{0,0,0,0,0,0,0,0,0,0,0},{165,131,107,103,0,0,0,0,0,0,0,0,0,0,0,0,0,0,0,0,0,0,0,0,0,0,0,0,0,0}},
   {15,4,3,1,255,{31,37,111,0,0,0,0,0,0,0,0},{242,0,0,0,0,0,0,0,0,0,0},{165,72,166,163,0,0,0,0,0,0,0,0,0,0,0,0,0,0,0,0,0,0,0,0,0,0,0,0,0,0}},
   {6,2,4,2,255,{57,53,199,87,0,0,0,0,0,0,0},{0,0,0,128,0,0,0,0,0,0,0},{96,35,0,0,0,0,0,0,0,0,0,0,0,0,0,0,0,0,0,0,0,0,0,0,0,0,0,0,0,0}},
   {7,6,5,20,255,{8,45,94,166,160,0,0,0,0,0,0},{0,0,0,0,1,0,0,0,0,0,0},{96,40,101,98,111,105,0,0,0,0,0,0,0,0,0,0,0,0,0,0,0,0,0,0,0,0,0,0,0,0}}},
  {6,4,9,7,10,9,9,8,9,5,6,4,7,2,10,10,1,9,7,5,7,10,8,7},
  {{3,6,7,8,0,1,5,15,2,4,9,11,12,24,10,17,21,13,19,18,16,22,20,28,14,27,29,31,23,26,25,30},
   {3,6,7,0,8,5,15,1,4,11,9,2,24,21,17,12,19,13,20,10,22,16,18,28,14,29,26,23,31,27,30,25},
   {3,8,6,7,0,5,2,1,15,4,9,11,19,24,17,12,21,13,20,16,10,28,14,18,22,29,31,26,23,27,25,30},
   {3,6,7,8,0,5,1,15,2,9,4,11,24,21,19,17,12,13,22,16,20,10,18,28,14,29,26,23,31,27,30,25},
   {0,7,3,8,6,5,1,2,15,4,9,11,24,21,17,12,19,13,20,22,28,10,16,18,14,29,31,26,23,27,30,25},
   {3,8,7,0,6,5,1,15,2,4,9,11,24,21,12,19,17,20,13,10,16,22,18,14,28,29,26,23,31,27,30,25},
   {0,3,7,8,6,5,1,15,2,4,9,24,11,21,12,19,17,13,22,20,10,16,18,28,14,29,26,31,23,27,30,25},
   {0,3,6,7,8,5,1,2,4,15,9,11,24,21,12,19,17,20,13,10,22,16,18,28,14,26,29,31,23,27,30,25}},
  {{4,3,4,3,0,3,1,1},{5,7,6,6,6,6,6,6},{9,9,7,8,8,8,7,7},{3,2,0,1,2,1,3,4},
   {8,8,9,9,9,9,8,8},{6,5,5,5,5,5,5,5},{1,1,2,0,4,4,4,0},{0,0,3,2,1,2,0,2},
   {2,4,1,4,3,0,2,3},{11,11,10,10,10,10,10,10},{1,7,9,11,11,12,12,11},{10,10,11,11,12,12,12,11},
   {14,16,5,6,4,5,5,5},{5,5,6,1,7,8,7,9},{10,10,10,13,13,5,6,5},{7,6,8,7,7,7,9,9},
   {7,6,8,9,9,11,11,7},{16,15,2,5,6,0,0,1},{2,9,11,12,12,4,4,0},{15,14,13,0,5,6,6,6},
   {6,1,0,7,0,7,9,8},{13,13,14,13,13,4,4,0},{0,0,7,8,8,9,8,12},{14,16,0,1,7,9,5,6},
   {12,12,12,12,11,11,11,12},{1,7,11,10,10,5,0,8},{11,11,2,6,6,7,9,9},{16,15,6,8,8,4,8,0},
   {3,8,12,10,10,10,5,6},{12,12,14,5,4,0,0,8},{5,5,7,12,12,10,4,5},{13,13,5,7,5,8,7,1}},
  {{255,255,255,255,255,255,255,255},{255,255,255,255,255,255,255,255},{255,255,255,255,255,255,255,255},{255,255,255,255,255,255,255,255},
   {255,255,255,255,255,255,255,255},{255,255,255,255,255,255,255,255},{255,255,255,255,255,255,255,255},{255,255,255,255,255,255,255,255},
   {255,255,255,255,255,255,255,255},{255,255,255,255,255,255,255,255},{6,1,4,11,24,11,11,11},{255,255,255,255,255,255,255,255},
   {255,255,5,1,6,5,5,5},{1,5,1,3,15,2,2,15},{11,11,9,21,21,12,19,12},{255,255,255,255,255,255,255,255},
   {15,15,15,4,4,24,24,2},{255,255,6,5,1,8,7,0},{8,2,11,24,11,21,21,21},{255,255,255,6,5,1,1,1},
   {5,6,3,15,0,15,15,4},{255,255,255,255,255,6,6,6},{7,7,2,2,2,4,4,24},{12,12,20,13,13,22,28,28},
   {255,255,255,255,255,255,255,255},{10,10,18,28,28,14,29,29},{9,9,17,12,17,20,20,13},{17,17,13,22,22,18,22,18},
   {3,4,24,9,9,9,12,19},{24,24,21,17,12,17,17,20},{13,13,22,18,18,28,18,14},{21,21,12,20,19,13,13,17}}};

typedef CUresult (*EncodeFn)(CUtensorMap*, CUtensorMapDataType, cuuint32_t, void*, const cuuint64_t*, const cuuint64_t*, const cuuint32_t*,
                             const cuuint32_t*, CUtensorMapInterleave, CUtensorMapSwizzle, CUtensorMapL2promotion, CUtensorMapFloatOOBfill);

void make_map2(EncodeFn enc, CUtensorMap* m, const void* ptr, int rows, int cols, int box_rows) {
  cuuint64_t dim[2] = {(cuuint64_t)cols, (cuuint64_t)rows}, str[1] = {(cuuint64_t)cols * 2};
  cuuint32_t box[2] = {64, (cuuint32_t)box_rows}, es[2] = {1, 1};
  enc(m, CU_TENSOR_MAP_DATA_TYPE_BFLOAT16, 2, const_cast<void*>(ptr), dim, str, box, es, CU_TENSOR_MAP_INTERLEAVE_NONE, CU_TENSOR_MAP_SWIZZLE_128B,
      CU_TENSOR_MAP_L2_PROMOTION_L2_128B, CU_TENSOR_MAP_FLOAT_OOB_FILL_NONE);
}
void make_map3(EncodeFn enc, CUtensorMap* m, const void* ptr, int rows) {
  cuuint64_t dim[3] = {64, (cuuint64_t)rows, 9}, str[2] = {DM * 2, 128};
  cuuint32_t box[3] = {64, 32, 3}, es[3] = {1, 1, 1};
  enc(m, CU_TENSOR_MAP_DATA_TYPE_BFLOAT16, 3, const_cast<void*>(ptr), dim, str, box, es, CU_TENSOR_MAP_INTERLEAVE_NONE, CU_TENSOR_MAP_SWIZZLE_128B,
      CU_TENSOR_MAP_L2_PROMOTION_L2_128B, CU_TENSOR_MAP_FLOAT_OOB_FILL_NONE);
}

void make_map_t(EncodeFn enc, CUtensorMap* m, void* ptr, int width, int cols) {
  cuuint64_t dim[3] = {TP / 2, 2, 864}, str[2] = {TP * 2, TP * 4};
  cuuint32_t box[3] = {(cuuint32_t)width, 2, (cuuint32_t)cols}, es[3] = {1, 1, 1};
  enc(m, CU_TENSOR_MAP_DATA_TYPE_UINT32, 3, ptr, dim, str, box, es, CU_TENSOR_MAP_INTERLEAVE_NONE, cols == 64 ? CU_TENSOR_MAP_SWIZZLE_128B : CU_TENSOR_MAP_SWIZZLE_NONE,
      CU_TENSOR_MAP_L2_PROMOTION_NONE, CU_TENSOR_MAP_FLOAT_OOB_FILL_NONE);
}

int g_mode = -1;

}

extern "C" void kernel_launch(void* const* d_in, const int* in_sizes, int n_in, void* d_out, int out_size) {
  static EncodeFn enc = nullptr;
  static void* t_ptr = nullptr;
  if (!enc) {
    void* fn = nullptr;
    cudaDriverEntryPointQueryResult st;
    cudaGetDriverEntryPoint("cuTensorMapEncodeTiled", &fn, cudaEnableDefault, &st);
    enc = (EncodeFn)fn;
    cudaGetSymbolAddress(&t_ptr, g_T);
    cudaFuncSetAttribute(fused_kernel, cudaFuncAttributeMaxDynamicSharedMemorySize, SMEM_BYTES);
    if (g_mode < 0) {
      cudaLaunchConfig_t cfg = {};
      cfg.gridDim = dim3(2 * NCL); cfg.blockDim = dim3(384); cfg.dynamicSmemBytes = SMEM_BYTES;
      cudaLaunchAttribute at; at.id = cudaLaunchAttributeClusterDimension;
      at.val.clusterDim.x = 2; at.val.clusterDim.y = 1; at.val.clusterDim.z = 1;
      cfg.attrs = &at; cfg.numAttrs = 1;
      int nc = 0;
      g_mode = (cudaOccupancyMaxActiveClusters(&nc, fused_kernel, &cfg) == cudaSuccess && nc >= NCL) ? 1 : 0;
      (void)cudaGetLastError();
    }
  }
  Params p;
  make_map2(enc, &p.map_a[0], d_in[4], SEQ, DC, 128);
  make_map2(enc, &p.map_a[1], d_in[0], SEQ, DM, 128);
  make_map2(enc, &p.map_w[0], d_in[6], DC, 4096, 64);
  make_map2(enc, &p.map_w[1], d_in[7], DC, 4096, 64);
  make_map2(enc, &p.map_w[2], d_in[5], DM, 4096, 64);
  make_map2(enc, &p.map_w[3], d_in[1], DM, 1728, 64);
  make_map3(enc, &p.map_o[0], d_in[8], 4096);
  make_map3(enc, &p.map_o[1], d_in[2], DM);
  make_map_t(enc, &p.map_t[0], t_ptr, 32, 9);
  make_map_t(enc, &p.map_t[1], t_ptr, 40, 9);
  make_map_t(enc, &p.map_t[2], t_ptr, 32, 64);
  p.x = (const __nv_bfloat16*)d_in[0];
  p.gate_w = (const __nv_bfloat16*)d_in[9];
  make_map2(enc, &p.map_out, d_out, SEQ, DM, 16);
  p.out = (__nv_bfloat16*)d_out;
  p.zero = 0;
  auto launch = [&](int phases) {
    p.s = k_sched;
    for (int i = 0; i < NCL; i++) {
      Rec& r = p.s.r[i];
      if (!(phases & 1)) r.n1 = 0;
      if (!(phases & 2)) r.n2 = 0;
      if (!(phases & (r.p3 < 24 ? 4 : 32))) r.p3 = 255;
      if (!(phases & 8)) r.bg = 255;
      const int u1 = r.n1 ? 8 + r.n1 * (8 + (r.slab >> 3)) : 0;
      int u2 = 0;
      for (int k = 0; k < r.n2; k++) u2 += 4 * (r.item[k] & 7) + 4;
      r.u1 = (uint8_t)u1; r.u2 = (uint8_t)u2;
      r.rot = (uint8_t)(((u1 % 10 + 1) >> 1) % 5);
      r.x3 = (uint8_t)((r.rot + u2) % 5 & 3);
      r.phases = (uint8_t)phases;
    }
    if (!(phases & 16))
      for (int i = 0; i < 256; i++) { p.s.slot[i >> 3][i & 7] = (uint8_t)(i >> 3); p.s.prev[i >> 3][i & 7] = 255; }
    fused_kernel<<<2 * NCL, 384, SMEM_BYTES>>>(p);
  };
  if (g_mode == 1) launch(63);
  else { launch(1); launch(10); launch(32); launch(4); }
}
```

```cpp
#include <cuda_runtime.h>
#include <cuda_bf16.h>
#include <cuda.h>
#include <stdint.h>

namespace {

constexpr int SEQ = 2048, DM = 576, DC = 512, NH = 32;
constexpr int NCL = 66;
constexpr uint32_t DESC_HI = 0x40000040u;

constexpr int SM_RING = 0;
constexpr int SM_BUF = 163840;
constexpr int SM_BAR = 229376;
constexpr int B_P1E = 0, B_P2E = 10, B_P3E = 15, B_P2F = 24, B_SF = 32, B_ORD = 36, B_LAD = 40, B_DONE = 41, B_FIN = 48;
constexpr int B_P3F = 56, B_OUT = 61, B_P1F = 64, B_SE = 74, B_QF = 80, B_LA = 84, B_NUM = 88;
constexpr uint64_t B_CNT = 0x11118245000ull;
constexpr int SMEM_BYTES = SM_BAR + B_NUM * 8 + 1024;

constexpr int F_QKVA = 32;
constexpr int F_GATE = 64;
constexpr int F_DONE = 65;
constexpr int F_CTX = 96;
constexpr int F_OUT = 96 + 8 * 64;
constexpr int F_KV = F_OUT + 64;
constexpr int F_Q = F_KV + 256;
constexpr int F_RD = F_Q + 256;
constexpr int F_NUM = F_RD + 256;

struct Rec {
  uint8_t slab;
  uint8_t n1, n2;
  uint8_t p3;
  uint8_t bg;
  uint8_t item[11];
  uint8_t last[11];
  uint8_t tile[32];
  uint8_t u1, u2;
  uint8_t rot, x3;
  uint8_t phases;
};
struct Sched {
  Rec r[NCL];
  uint8_t nh[24];
  uint8_t p3_order[8][32];
  uint8_t slot[32][8];
  uint8_t prev[32][8];
};

#define SCHED_DECL static const

struct Params {
  CUtensorMap map_a[2];
  CUtensorMap map_w[4];
  CUtensorMap map_o[2];
  CUtensorMap map_t[3];
  CUtensorMap map_out;
  const __nv_bfloat16* x;
  const __nv_bfloat16* gate_w;
  __nv_bfloat16* out;
  int zero;
  alignas(64) Sched s;
};

__device__ __align__(1024) uint8_t g_Q[NH * 32 * 16384];
__device__ __align__(1024) uint8_t g_KV[2 * NH * 16 * 32768];
__device__ __align__(1024) uint8_t g_oA[32 * 576 * 128];
constexpr int TP = SEQ + 16;
__device__ __align__(1024) uint32_t g_T[864 * TP];
__device__ float g_gate[SEQ];
__device__ int g_flags[F_NUM];

__device__ __forceinline__ void mbar_arrive(uint32_t b) { asm volatile("mbarrier.arrive.shared::cta.b64 _, [%0];" ::"r"(b) : "memory"); }
__device__ __forceinline__ void mbar_arrive_cl(uint32_t b, int cnt) {
  asm volatile("mbarrier.arrive.shared::cluster.b64 _, [%0], %1;" ::"r"(b), "r"(cnt) : "memory");
}
__device__ __forceinline__ void mbar_wait(uint32_t b, int par) {
  asm volatile(
      "{\n.reg .pred p;\n.reg .u32 c;\n"
      "mbarrier.try_wait.parity.shared::cta.b64 p, [%0], %1;\n@p bra DN;\nmov.u32 c, 0;\n"
      "LP:\nmbarrier.try_wait.parity.shared::cta.b64 p, [%0], %1;\n@p bra DN;\n"
      "add.u32 c, c, 1;\nsetp.lt.u32 p, c, 4000000;\n@p bra LP;\ntrap;\nDN:\n}" ::"r"(b), "r"(par) : "memory");
}
__device__ __forceinline__ uint32_t mapa(uint32_t a, uint32_t cta) {
  uint32_t r; asm("mapa.shared::cluster.u32 %0, %1, %2;" : "=r"(r) : "r"(a), "r"(cta)); return r;
}
#define ELECT(ins) "{\n.reg .pred e;\nelect.sync _|e, 0xffffffff;\n@e " ins "\n}"
__device__ __forceinline__ void mbar_expect(uint32_t b, int bytes) {
  asm volatile(ELECT("mbarrier.arrive.expect_tx.shared::cta.b64 _, [%0], %1;") ::"r"(b), "r"(bytes) : "memory");
}
__device__ __forceinline__ void mbar_arrive_one(uint32_t b) { asm volatile(ELECT("mbarrier.arrive.shared::cta.b64 _, [%0];") ::"r"(b) : "memory"); }
constexpr uint64_t L2_NORMAL = 0x1000000000000000ull, L2_FIRST = 0x12F0000000000000ull;
__device__ __forceinline__ void bulk_load(uint32_t dst, const void* src, int bytes, uint32_t bar, uint64_t pol = L2_NORMAL) {
  asm volatile(ELECT("cp.async.bulk.shared::cluster.global.mbarrier::complete_tx::bytes.L2::cache_hint [%0], [%1], %2, [%3], %4;") ::"r"(dst), "l"(src), "r"(bytes), "r"(bar), "l"(pol) : "memory");
}
__device__ __forceinline__ void bulk_load_mc(uint32_t dst, const void* src, int bytes, uint32_t bar, uint64_t pol = L2_NORMAL) {
  asm volatile(ELECT("cp.async.bulk.shared::cluster.global.mbarrier::complete_tx::bytes.multicast::cluster.L2::cache_hint [%0], [%1], %2, [%3], %4, %5;") ::"r"(dst), "l"(src), "r"(bytes), "r"(bar), "h"((uint16_t)3), "l"(pol) : "memory");
}
__device__ __forceinline__ void bulk_store(void* dst, uint32_t src, int bytes, uint64_t pol = L2_NORMAL) {
  asm volatile(ELECT("cp.async.bulk.global.shared::cta.bulk_group.L2::cache_hint [%0], [%1], %2, %3;") ::"l"(dst), "r"(src), "r"(bytes), "l"(pol) : "memory");
}
__device__ __forceinline__ void tma2d(uint32_t dst, const CUtensorMap* m, int c0, int c1, uint32_t bar, uint64_t pol = L2_NORMAL) {
  asm volatile(ELECT("cp.async.bulk.tensor.2d.shared::cluster.global.mbarrier::complete_tx::bytes.L2::cache_hint [%0], [%1, {%3, %4}], [%2], %5;") ::"r"(dst), "l"(m), "r"(bar), "r"(c0), "r"(c1), "l"(pol) : "memory");
}
__device__ __forceinline__ void tma2d_mc(uint32_t dst, const CUtensorMap* m, int c0, int c1, uint32_t bar, uint64_t pol = L2_NORMAL) {
  asm volatile(ELECT("cp.async.bulk.tensor.2d.shared::cluster.global.mbarrier::complete_tx::bytes.multicast::cluster.L2::cache_hint [%0], [%1, {%3, %4}], [%2], %5, %6;") ::"r"(dst), "l"(m), "r"(bar), "r"(c0), "r"(c1), "h"((uint16_t)3), "l"(pol) : "memory");
}
__device__ __forceinline__ void tma3d(uint32_t dst, const CUtensorMap* m, int c0, int c1, int c2, uint32_t bar, uint64_t pol = L2_NORMAL) {
  asm volatile(ELECT("cp.async.bulk.tensor.3d.shared::cluster.global.mbarrier::complete_tx::bytes.L2::cache_hint [%0], [%1, {%3, %4, %5}], [%2], %6;") ::"r"(dst), "l"(m), "r"(bar), "r"(c0), "r"(c1), "r"(c2), "l"(pol) : "memory");
}
__device__ __forceinline__ void tma3d_mc(uint32_t dst, const CUtensorMap* m, int c0, int c1, int c2, uint32_t bar, uint64_t pol = L2_NORMAL) {
  asm volatile(ELECT("cp.async.bulk.tensor.3d.shared::cluster.global.mbarrier::complete_tx::bytes.multicast::cluster.L2::cache_hint [%0], [%1, {%3, %4, %5}], [%2], %6, %7;") ::"r"(dst), "l"(m), "r"(bar), "r"(c0), "r"(c1), "r"(c2), "h"((uint16_t)3), "l"(pol) : "memory");
}
__device__ __forceinline__ void tma2d_add(const CUtensorMap* m, uint32_t src, int c0, int c1) {
  asm volatile(ELECT("cp.reduce.async.bulk.tensor.2d.global.shared::cta.add.bulk_group [%0, {%2, %3}], [%1];") ::"l"(m), "r"(src), "r"(c0), "r"(c1) : "memory");
}
__device__ __forceinline__ void tma3d_store(const CUtensorMap* m, uint32_t src, int c0, int c1, int c2, uint64_t pol = L2_NORMAL) {
  asm volatile(ELECT("cp.async.bulk.tensor.3d.global.shared::cta.bulk_group.L2::cache_hint [%0, {%2, %3, %4}], [%1], %5;") ::"l"(m), "r"(src), "r"(c0), "r"(c1), "r"(c2), "l"(pol) : "memory");
}
__device__ __forceinline__ void tma2d_prefetch(const CUtensorMap* m, int c0, int c1, uint64_t pol = L2_NORMAL) {
  asm volatile(ELECT("cp.async.bulk.prefetch.tensor.2d.L2.global.L2::cache_hint [%0, {%1, %2}], %3;") ::"l"(m), "r"(c0), "r"(c1), "l"(pol) : "memory");
}
#define LAG 3
#define HINT 62
#define POL(bit) ((HINT >> (bit)) & 1 ? L2_FIRST : L2_NORMAL)
#define BULK_COMMIT() asm volatile("cp.async.bulk.commit_group;" ::: "memory")
#define BULK_WAIT(n) asm volatile("cp.async.bulk.wait_group %0;" ::"n"(n) : "memory")
#define BULK_WAIT_READ(n) asm volatile("cp.async.bulk.wait_group.read %0;" ::"n"(n) : "memory")
#define FENCE_ASYNC_SMEM() asm volatile("fence.proxy.async.shared::cta;" ::: "memory")
#define FENCE_ASYNC_ALL() asm volatile("fence.proxy.async;" ::: "memory")
#define WG_FENCE() asm volatile("wgmma.fence.sync.aligned;" ::: "memory")
#define WG_COMMIT() asm volatile("wgmma.commit_group.sync.aligned;" ::: "memory")
#define WG_WAIT(n) asm volatile("wgmma.wait_group.sync.aligned %0;" ::"n"(n) : "memory")
__device__ __forceinline__ void bar_sync(int id, int n) { asm volatile("bar.sync %0, %1;" ::"r"(id), "r"(n) : "memory"); }
__device__ __forceinline__ void bar_arrive(int id, int n) { asm volatile("bar.arrive %0, %1;" ::"r"(id), "r"(n) : "memory"); }
__device__ __forceinline__ void cluster_sync() {
  asm volatile("barrier.cluster.arrive.relaxed;\nbarrier.cluster.wait.acquire;" ::: "memory");
}
template <int N> __device__ __forceinline__ void pin(float (&r)[N]) {
#pragma unroll
  for (int i = 0; i < N; i++) asm volatile("" : "+f"(r[i])::"memory");
}
template <int N> __device__ __forceinline__ void pin(uint32_t (&r)[N]) {
#pragma unroll
  for (int i = 0; i < N; i++) asm volatile("" : "+r"(r[i])::"memory");
}
__device__ __forceinline__ uint32_t pack_bf16(float lo, float hi) {
  uint32_t r; asm("cvt.rn.bf16x2.f32 %0, %1, %2;" : "=r"(r) : "f"(hi), "f"(lo)); return r;
}
__device__ __forceinline__ float ex2(float x) { float r; asm("ex2.approx.ftz.f32 %0, %1;" : "=f"(r) : "f"(x)); return r; }
__device__ __forceinline__ void ldsm4(uint32_t a, uint32_t& r0, uint32_t& r1, uint32_t& r2, uint32_t& r3) {
  asm volatile("ldmatrix.sync.aligned.m8n8.x4.shared.b16 {%0,%1,%2,%3}, [%4];" : "=r"(r0), "=r"(r1), "=r"(r2), "=r"(r3) : "r"(a) : "memory");
}
__device__ __forceinline__ void stsm4(uint32_t a, uint32_t r0, uint32_t r1, uint32_t r2, uint32_t r3) {
  asm volatile("stmatrix.sync.aligned.m8n8.x4.shared.b16 [%0], {%1,%2,%3,%4};" ::"r"(a), "r"(r0), "r"(r1), "r"(r2), "r"(r3) : "memory");
}
__device__ __forceinline__ void flag_add(int idx) {
  asm volatile(ELECT("red.release.gpu.global.add.s32 [%0], 1;") ::"l"(g_flags + idx) : "memory");
}
__device__ __forceinline__ void flag_add_rx(int idx) {
  asm volatile(ELECT("red.relaxed.gpu.global.add.s32 [%0], 1;") ::"l"(g_flags + idx) : "memory");
}
template <bool ACQ, int NS = 32> __device__ __forceinline__ void flag_wait(int idx, int target) {
  int n = 0;
  while (true) {
    int v;
    if (ACQ) asm volatile("ld.acquire.gpu.global.s32 %0, [%1];" : "=r"(v) : "l"(g_flags + idx) : "memory");
    else asm volatile("ld.relaxed.gpu.global.s32 %0, [%1];" : "=r"(v) : "l"(g_flags + idx) : "memory");
    if (__all_sync(0xffffffffu, v >= target)) break;
    if (++n > 20000000) __trap();
    __nanosleep(NS);
  }
}
__device__ __forceinline__ uint32_t desc_lo(uint32_t addr, uint32_t lbo) { return ((addr & 0x3FFFFu) >> 4) | ((lbo >> 4) << 16); }
#define PROF(role, i)
#define PROFX(cond, i)
#define PROFB(i)
#define PROFG(i)

template <int TB, int TA = 0> __device__ __forceinline__ void wgmma_ss64(float (&d)[32], uint32_t alo, uint32_t blo, int sd) {
  asm volatile("{\n.reg .pred p;\n.reg .b64 da, db;\n"
    "setp.ne.b32 p, %34, 0;\nmov.b64 da, {%32, %36};\nmov.b64 db, {%33, %36};\n"
    "wgmma.mma_async.sync.aligned.m64n64k16.f32.bf16.bf16 "
    "{%0,%1,%2,%3,%4,%5,%6,%7,%8,%9,%10,%11,%12,%13,%14,%15,%16,%17,%18,%19,%20,%21,%22,%23,"
    "%24,%25,%26,%27,%28,%29,%30,%31}, "
    "da, db, p, 1, 1, %37, %35;\n}\n"
    : "+f"(d[0]),"+f"(d[1]),"+f"(d[2]),"+f"(d[3]),"+f"(d[4]),"+f"(d[5]),"+f"(d[6]),"+f"(d[7]),"+f"(d[8]),"+f"(d[9]),"+f"(d[10]),"+f"(d[11]),
      "+f"(d[12]),"+f"(d[13]),"+f"(d[14]),"+f"(d[15]),"+f"(d[16]),"+f"(d[17]),"+f"(d[18]),"+f"(d[19]),"+f"(d[20]),"+f"(d[21]),"+f"(d[22]),"+f"(d[23]),
      "+f"(d[24]),"+f"(d[25]),"+f"(d[26]),"+f"(d[27]),"+f"(d[28]),"+f"(d[29]),"+f"(d[30]),"+f"(d[31])
    : "r"(alo), "r"(blo), "r"(sd), "n"(TB), "r"(DESC_HI), "n"(TA));
}
template <int TB, int TA = 0> __device__ __forceinline__ void wgmma_ss128(float (&d)[64], uint32_t alo, uint32_t blo, int sd) {
  asm volatile("{\n.reg .pred p;\n.reg .b64 da, db;\n"
    "setp.ne.b32 p, %66, 0;\nmov.b64 da, {%64, %68};\nmov.b64 db, {%65, %68};\n"
    "wgmma.mma_async.sync.aligned.m64n128k16.f32.bf16.bf16 "
    "{%0,%1,%2,%3,%4,%5,%6,%7,%8,%9,%10,%11,%12,%13,%14,%15,%16,%17,%18,%19,%20,%21,%22,%23,"
    "%24,%25,%26,%27,%28,%29,%30,%31,%32,%33,%34,%35,%36,%37,%38,%39,%40,%41,%42,%43,%44,%45,%46,%47,"
    "%48,%49,%50,%51,%52,%53,%54,%55,%56,%57,%58,%59,%60,%61,%62,%63}, "
    "da, db, p, 1, 1, %69, %67;\n}\n"
    : "+f"(d[0]),"+f"(d[1]),"+f"(d[2]),"+f"(d[3]),"+f"(d[4]),"+f"(d[5]),"+f"(d[6]),"+f"(d[7]),"+f"(d[8]),"+f"(d[9]),"+f"(d[10]),"+f"(d[11]),
      "+f"(d[12]),"+f"(d[13]),"+f"(d[14]),"+f"(d[15]),"+f"(d[16]),"+f"(d[17]),"+f"(d[18]),"+f"(d[19]),"+f"(d[20]),"+f"(d[21]),"+f"(d[22]),"+f"(d[23]),
      "+f"(d[24]),"+f"(d[25]),"+f"(d[26]),"+f"(d[27]),"+f"(d[28]),"+f"(d[29]),"+f"(d[30]),"+f"(d[31]),"+f"(d[32]),"+f"(d[33]),"+f"(d[34]),"+f"(d[35]),
      "+f"(d[36]),"+f"(d[37]),"+f"(d[38]),"+f"(d[39]),"+f"(d[40]),"+f"(d[41]),"+f"(d[42]),"+f"(d[43]),"+f"(d[44]),"+f"(d[45]),"+f"(d[46]),"+f"(d[47]),
      "+f"(d[48]),"+f"(d[49]),"+f"(d[50]),"+f"(d[51]),"+f"(d[52]),"+f"(d[53]),"+f"(d[54]),"+f"(d[55]),"+f"(d[56]),"+f"(d[57]),"+f"(d[58]),"+f"(d[59]),
      "+f"(d[60]),"+f"(d[61]),"+f"(d[62]),"+f"(d[63])
    : "r"(alo), "r"(blo), "r"(sd), "n"(TB), "r"(DESC_HI), "n"(TA));
}
template <int TB> __device__ __forceinline__ void wgmma_rs128(float (&d)[64], uint32_t a0, uint32_t a1, uint32_t a2, uint32_t a3, uint32_t blo, int sd) {
  asm volatile("{\n.reg .pred p;\n.reg .b64 db;\n"
    "setp.ne.b32 p, %69, 0;\nmov.b64 db, {%68, %71};\n"
    "wgmma.mma_async.sync.aligned.m64n128k16.f32.bf16.bf16 "
    "{%0,%1,%2,%3,%4,%5,%6,%7,%8,%9,%10,%11,%12,%13,%14,%15,%16,%17,%18,%19,%20,%21,%22,%23,"
    "%24,%25,%26,%27,%28,%29,%30,%31,%32,%33,%34,%35,%36,%37,%38,%39,%40,%41,%42,%43,%44,%45,%46,%47,"
    "%48,%49,%50,%51,%52,%53,%54,%55,%56,%57,%58,%59,%60,%61,%62,%63}, "
    "{%64,%65,%66,%67}, db, p, 1, 1, %70;\n}\n"
    : "+f"(d[0]),"+f"(d[1]),"+f"(d[2]),"+f"(d[3]),"+f"(d[4]),"+f"(d[5]),"+f"(d[6]),"+f"(d[7]),"+f"(d[8]),"+f"(d[9]),"+f"(d[10]),"+f"(d[11]),
      "+f"(d[12]),"+f"(d[13]),"+f"(d[14]),"+f"(d[15]),"+f"(d[16]),"+f"(d[17]),"+f"(d[18]),"+f"(d[19]),"+f"(d[20]),"+f"(d[21]),"+f"(d[22]),"+f"(d[23]),
      "+f"(d[24]),"+f"(d[25]),"+f"(d[26]),"+f"(d[27]),"+f"(d[28]),"+f"(d[29]),"+f"(d[30]),"+f"(d[31]),"+f"(d[32]),"+f"(d[33]),"+f"(d[34]),"+f"(d[35]),
      "+f"(d[36]),"+f"(d[37]),"+f"(d[38]),"+f"(d[39]),"+f"(d[40]),"+f"(d[41]),"+f"(d[42]),"+f"(d[43]),"+f"(d[44]),"+f"(d[45]),"+f"(d[46]),"+f"(d[47]),
      "+f"(d[48]),"+f"(d[49]),"+f"(d[50]),"+f"(d[51]),"+f"(d[52]),"+f"(d[53]),"+f"(d[54]),"+f"(d[55]),"+f"(d[56]),"+f"(d[57]),"+f"(d[58]),"+f"(d[59]),
      "+f"(d[60]),"+f"(d[61]),"+f"(d[62]),"+f"(d[63])
    : "r"(a0), "r"(a1), "r"(a2), "r"(a3), "r"(blo), "r"(sd), "n"(TB), "r"(DESC_HI));
}
template <int TB, int TA = 0> __device__ __forceinline__ void wgmma_ss192(float (&d)[96], uint32_t alo, uint32_t blo, int sd) {
  asm volatile("{\n.reg .pred p;\n.reg .b64 da, db;\n"
    "setp.ne.b32 p, %98, 0;\nmov.b64 da, {%96, %100};\nmov.b64 db, {%97, %100};\n"
    "wgmma.mma_async.sync.aligned.m64n192k16.f32.bf16.bf16 "
    "{%0,%1,%2,%3,%4,%5,%6,%7,%8,%9,%10,%11,%12,%13,%14,%15,%16,%17,%18,%19,%20,%21,%22,%23,"
    "%24,%25,%26,%27,%28,%29,%30,%31,%32,%33,%34,%35,%36,%37,%38,%39,%40,%41,%42,%43,%44,%45,%46,%47,"
    "%48,%49,%50,%51,%52,%53,%54,%55,%56,%57,%58,%59,%60,%61,%62,%63,%64,%65,%66,%67,%68,%69,%70,%71,"
    "%72,%73,%74,%75,%76,%77,%78,%79,%80,%81,%82,%83,%84,%85,%86,%87,%88,%89,%90,%91,%92,%93,%94,%95}, "
    "da, db, p, 1, 1, %101, %99;\n}\n"
    : "+f"(d[0]),"+f"(d[1]),"+f"(d[2]),"+f"(d[3]),"+f"(d[4]),"+f"(d[5]),"+f"(d[6]),"+f"(d[7]),"+f"(d[8]),"+f"(d[9]),"+f"(d[10]),"+f"(d[11]),
      "+f"(d[12]),"+f"(d[13]),"+f"(d[14]),"+f"(d[15]),"+f"(d[16]),"+f"(d[17]),"+f"(d[18]),"+f"(d[19]),"+f"(d[20]),"+f"(d[21]),"+f"(d[22]),"+f"(d[23]),
      "+f"(d[24]),"+f"(d[25]),"+f"(d[26]),"+f"(d[27]),"+f"(d[28]),"+f"(d[29]),"+f"(d[30]),"+f"(d[31]),"+f"(d[32]),"+f"(d[33]),"+f"(d[34]),"+f"(d[35]),
      "+f"(d[36]),"+f"(d[37]),"+f"(d[38]),"+f"(d[39]),"+f"(d[40]),"+f"(d[41]),"+f"(d[42]),"+f"(d[43]),"+f"(d[44]),"+f"(d[45]),"+f"(d[46]),"+f"(d[47]),
      "+f"(d[48]),"+f"(d[49]),"+f"(d[50]),"+f"(d[51]),"+f"(d[52]),"+f"(d[53]),"+f"(d[54]),"+f"(d[55]),"+f"(d[56]),"+f"(d[57]),"+f"(d[58]),"+f"(d[59]),
      "+f"(d[60]),"+f"(d[61]),"+f"(d[62]),"+f"(d[63]),"+f"(d[64]),"+f"(d[65]),"+f"(d[66]),"+f"(d[67]),"+f"(d[68]),"+f"(d[69]),"+f"(d[70]),"+f"(d[71]),
      "+f"(d[72]),"+f"(d[73]),"+f"(d[74]),"+f"(d[75]),"+f"(d[76]),"+f"(d[77]),"+f"(d[78]),"+f"(d[79]),"+f"(d[80]),"+f"(d[81]),"+f"(d[82]),"+f"(d[83]),
      "+f"(d[84]),"+f"(d[85]),"+f"(d[86]),"+f"(d[87]),"+f"(d[88]),"+f"(d[89]),"+f"(d[90]),"+f"(d[91]),"+f"(d[92]),"+f"(d[93]),"+f"(d[94]),"+f"(d[95])
    : "r"(alo), "r"(blo), "r"(sd), "n"(TB), "r"(DESC_HI), "n"(TA));
}

struct Ctx {
  uint32_t sm;
  uint32_t bar;
  uint32_t rbar;
  int cl, rank, wg, warp, lane, phases;
};
__device__ __forceinline__ void release(const Ctx& c, int b, int cnt = 1) {
  if (c.lane < 2) mbar_arrive_cl(c.rbar + b * 8, cnt);
}
#define PFM 7
#define PF1 1
constexpr float SM_SCALE = 0.08838834764831845f * 1.4426950408889634f;
constexpr float SM_HI = 1.8446744e19f, SM_LO = 5.4210109e-20f;
constexpr int ORDER = 1;

__device__ __forceinline__ void stage_tile(const float (&a)[64], uint32_t buf, const Ctx& c, float s0, float s1) {
  const int row = (c.lane & 7) + ((c.lane >> 3) & 1) * 8;
  const uint32_t base = buf + (c.warp * 16 + row) * 128 + (((c.lane >> 4) ^ (row & 7)) << 4);
#pragma unroll
  for (int i = 0; i < 8; i++)
    stsm4((base ^ ((i & 3) << 5)) + (i >> 2) * 8192, pack_bf16(a[8 * i] * s0, a[8 * i + 1] * s0), pack_bf16(a[8 * i + 2] * s1, a[8 * i + 3] * s1),
          pack_bf16(a[8 * i + 4] * s0, a[8 * i + 5] * s0), pack_bf16(a[8 * i + 6] * s1, a[8 * i + 7] * s1));
}

__device__ __forceinline__ void p1_epilogue(const Params& p, const Ctx& c, const float (&acc)[64], int t, int type) {
  const int tile = p.s.r[c.cl].tile[t] & 63, b = c.wg * 2 + 1;
  mbar_wait(c.bar + (B_SE + b) * 8, (t & 1) ^ 1);
  if (type && tile >= 32) {
    const int r = 2 * (c.lane & 3) + ((c.lane >> 2) & 1);
    const uint32_t dst = c.sm + SM_BUF + b * 16384 + r * 128 + (((c.warp * 2) ^ r) << 4) + (c.lane >> 3) * 4;
#pragma unroll
    for (int i = 0; i < 16; i++) {
      asm volatile("st.shared.u32 [%0], %1;" ::"r"(dst + i * 1024), "r"(pack_bf16(acc[4 * i], acc[4 * i + 1])) : "memory");
      asm volatile("st.shared.u32 [%0], %1;" ::"r"((dst ^ 16) + i * 1024), "r"(pack_bf16(acc[4 * i + 2], acc[4 * i + 3])) : "memory");
    }
  } else {
    if (type) stage_tile(acc, c.sm + SM_BUF + b * 16384, c, SM_SCALE, SM_SCALE);
    else stage_tile(acc, c.sm + SM_BUF + b * 16384, c, 1.f, 1.f);
  }
  FENCE_ASYNC_SMEM();
  __syncwarp();
  if (c.lane == 0) mbar_arrive(c.bar + (B_SF + b) * 8);
}

__device__ __forceinline__ void p1_consumer(const Params& p, const Ctx& c) {
  const int n = p.s.r[c.cl].n1;
  const int type = p.s.r[c.cl].slab >> 3;
  const uint32_t bdesc = desc_lo(c.sm + SM_RING, 8192), adesc = desc_lo(c.sm + SM_BUF + 32768 + c.wg * 8192, 16);
  uint32_t A[128];
  float acc[64] = {};
  int slot = 0, par = 0;
  auto next = [&]() { if (++slot == 10) { slot = 0; par ^= 1; } };
  {
    const int row = (c.lane & 7) + ((c.lane >> 3) & 1) * 8;
    const uint32_t base = c.sm + SM_RING + (c.wg * 64 + c.warp * 16 + row) * 128 + (((c.lane >> 4) ^ (row & 7)) << 4);
    if (c.wg == 1) bar_sync(ORDER + 1, 256);
    int pa = -1, pb = -1;
    if (type) {
      mbar_wait(c.bar + B_P1F * 8, 0);
      WG_FENCE();
#pragma unroll
      for (int kk = 0; kk < 4; kk++) wgmma_ss128<1>(acc, adesc + kk * 2, bdesc + kk * 128, kk != 0);
      WG_COMMIT();
      pb = 0; slot = 1;
    }
#pragma unroll
    for (int kb = 0; kb < 8; kb++) {
      const int sa = slot;
      mbar_wait(c.bar + (B_P1F + slot) * 8, par);
      if (kb == 0) PROF(c.wg, 5);
      next();
      mbar_wait(c.bar + (B_P1F + slot) * 8, par);
      PROF(c.wg, 6 + 2 * kb);
      WG_FENCE();
#pragma unroll
      for (int kk = 0; kk < 4; kk++)
        wgmma_ss128<1>(acc, desc_lo(c.sm + SM_RING + c.wg * 8192, 16) + sa * 1024 + kk * 2, bdesc + slot * 1024 + kk * 128, (kb | kk) != 0 ? 1 : type);
      WG_COMMIT();
      if (kb == 1 && c.wg == 0) bar_arrive(ORDER + 1, 256);
#pragma unroll
      for (int kk = 0; kk < 4; kk++) ldsm4((base ^ (kk << 5)) + sa * 16384, A[kb * 16 + kk * 4], A[kb * 16 + kk * 4 + 1], A[kb * 16 + kk * 4 + 2], A[kb * 16 + kk * 4 + 3]);
      WG_WAIT(1);
      if (kb > 0) release(c, B_P1E + pa);
      if (kb > 0 || pb >= 0) release(c, B_P1E + pb);
      pa = sa; pb = slot;
      next();
    }
    WG_WAIT(0);
    __syncwarp();
    release(c, B_P1E + pa);
    release(c, B_P1E + pb);
    pin(acc);
    PROF(c.wg, 1);
    p1_epilogue(p, c, acc, 0, type);
    PROF(c.wg, 2);
  }
  for (int t = 1; t < n; t++) {
    bar_sync(ORDER + c.wg, 256);
    int prev1 = -1, prev2 = -1;
    if (type) {
      mbar_wait(c.bar + (B_P1F + slot) * 8, par);
      WG_FENCE();
#pragma unroll
      for (int kk = 0; kk < 4; kk++) wgmma_ss128<1>(acc, adesc + kk * 2, bdesc + slot * 1024 + kk * 128, kk != 0);
      WG_COMMIT();
      prev1 = slot;
      next();
    }
#pragma unroll
    for (int kb = 0; kb < 8; kb++) {
      mbar_wait(c.bar + (B_P1F + slot) * 8, par);
      WG_FENCE();
      const uint32_t d = bdesc + slot * 1024;
#pragma unroll
      for (int kk = 0; kk < 4; kk++)
        wgmma_rs128<1>(acc, A[kb * 16 + kk * 4], A[kb * 16 + kk * 4 + 1], A[kb * 16 + kk * 4 + 2], A[kb * 16 + kk * 4 + 3], d + kk * 128, (kb | kk) != 0 ? 1 : type);
      WG_COMMIT();
      if (kb == 7) {
        if (t + 1 < n || c.wg == 0) bar_arrive(ORDER + (c.wg ^ 1), 256);
      }
      if (kb > 0) { WG_WAIT(2); if (kb > 1 || prev2 >= 0) release(c, B_P1E + prev2); }
      prev2 = prev1; prev1 = slot;
      next();
    }
    WG_WAIT(1);
    release(c, B_P1E + prev2);
    WG_WAIT(0);
    pin(acc);
    release(c, B_P1E + prev1);
    p1_epilogue(p, c, acc, t, type);
    PROF(c.wg, 3);
  }
}

__device__ __forceinline__ void p1_producer(const Params& p, const Ctx& c) {
  const int n = p.s.r[c.cl].n1;
  const int type = p.s.r[c.cl].slab >> 3, grp = p.s.r[c.cl].slab & 7;
  int slot = 2 - type, par = 1;
#pragma unroll 1
  for (int t = 0; t < n; t++) {
    const int tile = p.s.r[c.cl].tile[t] & 63;
    const CUtensorMap* m = &p.map_w[type * 2 + (tile >> 5)];
    const int n0 = (tile & 31) * 128 + c.rank * 64;
    const int ptile = p.s.r[c.cl].tile[t + PF1 < n ? t + PF1 : t];
    const CUtensorMap* pm = &p.map_w[type * 2 + ((ptile >> 5) & 1)];
#pragma unroll 1
    for (int kb = (t == 0) - type; kb < 8; kb++) {
      if (t == 0) {
        mbar_wait(c.bar + (B_P1E + slot) * 8, par);
        mbar_expect(c.bar + (B_P1F + slot) * 8, 16384);
        tma2d(c.sm + SM_RING + slot * 16384, &p.map_a[type], kb * 64, grp * 256 + c.rank * 128, c.bar + (B_P1F + slot) * 8);
        if (++slot == 10) { slot = 0; par ^= 1; }
      }
      mbar_wait(c.bar + (B_P1E + slot) * 8, par);
      mbar_expect(c.bar + (B_P1F + slot) * 8, 16384);
      tma2d_mc(c.sm + SM_RING + slot * 16384 + c.rank * 8192, m, n0, kb < 0 ? 512 : kb * 64, c.bar + (B_P1F + slot) * 8);
      if (t == 0 && kb == 1) PROF(2, 61);
      if (t == 0 && kb == 3) PROF(2, 62);
      if (t + PF1 < n && t > 0 && ((ptile & 64) || ((ptile & 128) && ((kb ^ grp) & PFM) == 0))) tma2d_prefetch(pm, (ptile & 31) * 128 + c.rank * 64, kb < 0 ? 512 : kb * 64);
      if (++slot == 10) { slot = 0; par ^= 1; }
    }
  }
}

__device__ __forceinline__ void p1_storer(const Params& p, const Ctx& c) {
  const int n = p.s.r[c.cl].n1;
  const int type = p.s.r[c.cl].slab >> 3, grp = p.s.r[c.cl].slab & 7;
  for (int i = 0; i < 2 * n; i++) {
    const int t = i >> 1, w = i & 1, b = w * 2 + 1;
    const int tile = p.s.r[c.cl].tile[t] & 63;
    mbar_wait(c.bar + (B_SF + b) * 8, t & 1);
    const uint32_t src = c.sm + SM_BUF + b * 16384;
    int f = (type ? F_Q : F_KV) + (tile & 31) * 8 + grp;
    if (type == 0) {
      const int prev = p.s.prev[tile & 31][grp];
      if (prev != 255 && w == 0) {
        if (grp >= 2) flag_wait<false>(F_RD + prev * 8 + grp, 8 - grp);
        else flag_wait<false>(F_CTX + max(c.lane & 7, grp) * 64 + prev, 4);
      }
      uint8_t* dst = g_KV + (size_t)(((tile & 32) + p.s.slot[tile & 31][grp]) * 16 + grp * 2 + c.rank) * 32768 + w * 8192;
      bulk_store(dst, src, 8192);
      bulk_store(dst + 16384, src + 8192, 8192);
    } else if (tile < 32) {
      bulk_store(g_Q + (size_t)(tile * 32 + grp * 4 + c.rank * 2 + w) * 16384, src, 16384);
    } else {
      tma3d_store(&p.map_t[2], src, 8 + (grp * 4 + c.rank * 2 + w) * 32, 0, (tile - 32) * 64);
      f = F_QKVA + grp * 4 + ((0xE4390900u >> (2 * (tile - 30))) & 3);
    }
    BULK_COMMIT();
    BULK_WAIT(0);
    mbar_arrive_one(c.bar + (B_SE + b) * 8);
    flag_add_rx(f);
  }
}

__device__ __forceinline__ int p2_buf(int w, int i) { return w * 2 + (i & 1); }
__device__ __forceinline__ int p2_blk(int rank, int w, int i) { return ((i ^ w) & 1) == 0 ? 3 - rank : rank; }

template <int N>
__device__ __forceinline__ void row_max(const float (&s)[N], float& m0, float& m1) {
  float a0 = fmaxf(s[0], s[1]), a1 = fmaxf(s[2], s[3]);
#pragma unroll
  for (int i = 1; i < N / 4; i++) {
    m0 = fmaxf(m0, s[4 * i]); a0 = fmaxf(a0, s[4 * i + 1]);
    m1 = fmaxf(m1, s[4 * i + 2]); a1 = fmaxf(a1, s[4 * i + 3]);
  }
  m0 = fmaxf(m0, a0); m1 = fmaxf(m1, a1);
  m0 = fmaxf(m0, __shfl_xor_sync(0xffffffffu, m0, 1));
  m1 = fmaxf(m1, __shfl_xor_sync(0xffffffffu, m1, 1));
  m0 = fmaxf(m0, __shfl_xor_sync(0xffffffffu, m0, 2));
  m1 = fmaxf(m1, __shfl_xor_sync(0xffffffffu, m1, 2));
}
template <bool SUB, int N>
__device__ __forceinline__ void row_exp(const float (&s)[N], uint32_t (&P)[32], float m0, float m1, float& t0, float& t1) {
  float u0 = 0.f, u1 = 0.f;
  t0 = t1 = 0.f;
#pragma unroll
  for (int i = 0; i < N / 4; i++) {
    const float e0 = ex2(SUB ? s[4 * i] - m0 : s[4 * i]), e1 = ex2(SUB ? s[4 * i + 1] - m0 : s[4 * i + 1]);
    const float e2 = ex2(SUB ? s[4 * i + 2] - m1 : s[4 * i + 2]), e3 = ex2(SUB ? s[4 * i + 3] - m1 : s[4 * i + 3]);
    if (i == 0) { t0 = e0; u0 = e1; t1 = e2; u1 = e3; }
    else { t0 += e0; u0 += e1; t1 += e2; u1 += e3; }
    P[2 * i] = pack_bf16(e0, e1);
    P[2 * i + 1] = pack_bf16(e2, e3);
  }
#pragma unroll
  for (int i = N / 2; i < 32; i++) P[i] = 0;
  pin(P);
  t0 += u0; t1 += u1;
}
template <int N>
__device__ __forceinline__ void causal_mask(float (&s)[N], int thr) {
#pragma unroll
  for (int i = 0; i < 8; i++) {
    if (8 * i > thr) s[N - 32 + 4 * i] = -INFINITY;
    if (8 * i + 1 > thr) s[N - 32 + 4 * i + 1] = -INFINITY;
    if (8 * i - 8 > thr) s[N - 32 + 4 * i + 2] = -INFINITY;
    if (8 * i - 7 > thr) s[N - 32 + 4 * i + 3] = -INFINITY;
  }
}
__device__ __forceinline__ void issue_qk(float (&s)[32], uint32_t qd, uint32_t kd) {
  WG_FENCE();
#pragma unroll
  for (int kk = 0; kk < 8; kk++) wgmma_ss64<0>(s, qd + (kk >> 2) * 512 + (kk & 3) * 2, kd + (kk >> 2) * 1024 + (kk & 3) * 2, kk != 0);
  WG_COMMIT();
}
__device__ __forceinline__ void issue_qk(float (&s)[64], uint32_t qd, uint32_t kd) {
  WG_FENCE();
#pragma unroll
  for (int kk = 0; kk < 8; kk++) wgmma_ss128<0>(s, qd + (kk >> 2) * 512 + (kk & 3) * 2, kd + (kk >> 2) * 1024 + (kk & 3) * 2, kk != 0);
  WG_COMMIT();
}
template <int NK>
__device__ __forceinline__ void issue_pv(float (&o)[64], const uint32_t (&P)[32], uint32_t vd, int acc) {
  WG_FENCE();
#pragma unroll
  for (int kk = 0; kk < NK; kk++) wgmma_rs128<1>(o, P[4 * kk], P[4 * kk + 1], P[4 * kk + 2], P[4 * kk + 3], vd + kk * 128, kk != 0 ? 1 : acc);
  WG_COMMIT();
}
__device__ __forceinline__ void stage_done(const Ctx& c, int b) {
  FENCE_ASYNC_SMEM();
  __syncwarp();
  if (c.lane == 0) mbar_arrive(c.bar + (B_SF + b) * 8);
}
__device__ __forceinline__ void p2_epilogue(const float (&o)[64], float s0, float s1, const Ctx& c, int b) {
  stage_tile(o, c.sm + SM_BUF + b * 16384, c, s0, s1);
  stage_done(c, b);
}

struct P2State {
  float m0, m1, l0, l1;
  bool shift;
  float e0, e1;
  int ks;
  int wi, ai;
  uint32_t wb, ab;
  uint32_t qd;
};
#define PROFZ()
__device__ __forceinline__ int wrap5(int q) { return q >= 5 ? q - 5 : q; }
__device__ __forceinline__ void turn_wait(uint32_t ring, int i) { mbar_wait(ring + (i & 3) * 8, (i >> 2) & 1); }
__device__ __forceinline__ void turn_pass(const Ctx& c, uint32_t ring, int i) { if (c.lane == 0) mbar_arrive(ring + (i & 3) * 8); }
__device__ __forceinline__ void p2_scales(P2State& z) {
  float l0 = z.l0, l1 = z.l1;
  l0 += __shfl_xor_sync(0xffffffffu, l0, 1);
  l1 += __shfl_xor_sync(0xffffffffu, l1, 1);
  l0 += __shfl_xor_sync(0xffffffffu, l0, 2);
  l1 += __shfl_xor_sync(0xffffffffu, l1, 2);
  asm("rcp.approx.ftz.f32 %0, %1;" : "=f"(z.e0) : "f"(l0));
  asm("rcp.approx.ftz.f32 %0, %1;" : "=f"(z.e1) : "f"(l1));
}
template <int N>
__device__ __forceinline__ void p2_first(const Ctx& c, P2State& z, float (&o)[64], uint32_t (&Pc)[32], uint32_t (&Pn)[32],
                                         int ks, int vs, int cnt, int acc) {
  float s[N] = {};
  issue_qk(s, z.qd, desc_lo(c.sm + SM_RING, 16) + ks * 2048);
  if (vs >= 0) {
    p2_scales(z);
    issue_pv<8>(o, Pc, desc_lo(c.sm + SM_RING, 16384) + vs * 2048, acc);
  } else {
    WG_COMMIT();
  }
  mbar_expect(z.ab + (z.ai++ & 3) * 8, cnt == 1 ? 8192 : 0);
  PROFZ();
  WG_WAIT(1);
  PROFZ();
  pin(s);
  release(c, B_P2E + ks, cnt);
  causal_mask(s, c.warp * 16 + (c.lane >> 2) - 2 * (c.lane & 3));
  z.m0 = z.m1 = 0.f;
  row_exp<false>(s, Pn, 0.f, 0.f, z.l0, z.l1);
  z.shift = __any_sync(0xffffffffu, !(z.l0 + z.l1 <= SM_HI) || ((c.lane & 3) == 0 && !(fminf(z.l0, z.l1) >= SM_LO)));
  if (__builtin_expect(z.shift, 0)) {
    z.m0 = z.m1 = -INFINITY;
    row_max(s, z.m0, z.m1);
    row_exp<true>(s, Pn, z.m0, z.m1, z.l0, z.l1);
  }
  WG_WAIT(0);
  pin(o);
  if (vs >= 0) release(c, B_P2E + vs, 1);
}

template <bool SECOND>
__device__ __forceinline__ void p2_turn(const Ctx& c, P2State& z, float (&o)[64], uint32_t (&Pc)[32], uint32_t (&Pn)[32],
                                        int eb = -1, bool half = false, int vcnt = 1) {
  float s[64] = {};
  const int ks = z.ks, vs = wrap5(ks + 1);
  PROFZ();
  turn_wait(z.wb, z.wi++);
  PROFZ();
  issue_qk(s, z.qd, desc_lo(c.sm + SM_RING, 16) + ks * 2048);
  const uint32_t vd = desc_lo(c.sm + SM_RING, 16384) + vs * 2048;
  if (SECOND) {
    if (eb >= 0) stage_tile(o, c.sm + SM_BUF + eb * 16384, c, z.e0, z.e1);
    if (half) issue_pv<4>(o, Pc, vd, 0); else issue_pv<8>(o, Pc, vd, 0);
  } else {
    issue_pv<8>(o, Pc, vd, 1);
  }
  turn_pass(c, z.ab, z.ai++);
  if (SECOND) { if (eb >= 0) stage_done(c, eb); }
  PROFZ();
  z.ks = wrap5(ks + 2);
  WG_WAIT(1);
  PROFZ();
  pin(s);
  release(c, B_P2E + ks, 1);
  float t0, t1, a0 = 1.f, a1 = 1.f;
  row_exp<false>(s, Pn, 0.f, 0.f, t0, t1);
  z.shift = __any_sync(0xffffffffu, z.shift || !(t0 + t1 <= SM_HI));
  const bool redo = z.shift;
  if (__builtin_expect(redo, 0)) {
    float n0 = z.m0, n1 = z.m1;
    row_max(s, n0, n1);
    a0 = ex2(z.m0 - n0); a1 = ex2(z.m1 - n1);
    z.m0 = n0; z.m1 = n1;
    z.l0 *= a0; z.l1 *= a1;
    row_exp<true>(s, Pn, z.m0, z.m1, t0, t1);
  }
  WG_WAIT(0);
  pin(o);
  release(c, B_P2E + vs, vcnt);
  if (__builtin_expect(redo, 0)) {
#pragma unroll
    for (int i = 0; i < 16; i++) { o[4 * i] *= a0; o[4 * i + 1] *= a0; o[4 * i + 2] *= a1; o[4 * i + 3] *= a1; }
  }
  z.l0 += t0; z.l1 += t1;
}
__device__ __forceinline__ void copy_p(uint32_t (&d)[32], const uint32_t (&s)[32], int zero) {
#pragma unroll
  for (int i = 0; i < 32; i++) asm volatile("add.s32 %0, %1, %2;" : "=r"(d[i]) : "r"(s[i]), "r"(zero));
}

__device__ __forceinline__ void p2_consumer(const Params& p, const Ctx& c, int rot) {
  const int nit = p.s.r[c.cl].n2;
  const uint32_t fring = c.bar + B_P2F * 8, oring = c.bar + B_ORD * 8;
  float o[64] = {};
  uint32_t Pa[32] = {}, Pb[32] = {};
  P2State z;
  z.e0 = z.e1 = z.l0 = z.l1 = 0.f; z.ks = rot; z.shift = false;
  int acc = 0, n = 0;
  for (int it = 0; it < nit; it++) {
    const int j = p.s.r[c.cl].item[it] & 7, blk = p2_blk(c.rank, c.wg, it);
    const int lng = ((it ^ c.wg) & 1) ^ 1;
    z.qd = desc_lo(c.sm + SM_BUF, 16) + p2_buf(c.wg, it) * 1024;
    if (lng) { z.wb = oring; z.wi = n - it; z.ab = fring; z.ai = n + 1; }
    else { z.wb = fring; z.wi = n + 2; z.ab = oring; z.ai = n - it; }
    PROFZ();
    mbar_wait(c.bar + (B_QF + p2_buf(c.wg, it)) * 8, (it >> 1) & 1);
    turn_wait(fring, n + 1 - lng);
    PROFZ();
    const int vs = it ? wrap5(z.ks + 1) : -1, ks = lng ? z.ks : wrap5(z.ks + (it ? 2 : 1));
    if (blk & 1) p2_first<64>(c, z, o, Pa, Pb, ks, vs, 1 + lng, acc);
    else p2_first<32>(c, z, o, Pa, Pb, ks, vs, 1 + lng, acc);
    z.ks = wrap5(ks + (it == 0 && lng ? 1 : 2));
    PROF(c.wg, 24 + it);
    n += 2 * j + 2;
    int left = 2 * j + lng;
    acc = left != 0;
    if (left == 0) { copy_p(Pa, Pb, p.zero); continue; }
    p2_turn<true>(c, z, o, Pb, Pa, it > 0 ? p2_buf(c.wg, it - 1) : -1, !(blk & 1), 1 + lng);
    while (--left > 0) {
      p2_turn<false>(c, z, o, Pa, Pb);
      if (--left == 0) { copy_p(Pa, Pb, p.zero); break; }
      p2_turn<false>(c, z, o, Pb, Pa);
    }
  }
  {
    if (!acc && nit > 1) p2_epilogue(o, z.e0, z.e1, c, p2_buf(c.wg, nit));
    turn_wait(z.wb, z.wi);
    issue_pv<8>(o, Pa, desc_lo(c.sm + SM_RING, 16384) + z.ks * 2048, acc);
    if (((nit - 1) ^ c.wg) & 1) turn_pass(c, z.ab, z.ai);
    p2_scales(z);
    WG_WAIT(0);
    pin(o);
    release(c, B_P2E + z.ks);
    p2_epilogue(o, z.e0, z.e1, c, p2_buf(c.wg, nit - 1));
    PROF(c.wg, 24 + nit);
  }
}

__device__ __forceinline__ void p2_load_q(const Params& p, const Ctx& c, int it, int w) {
  const int item = p.s.r[c.cl].item[it], h = item >> 3, j = item & 7, b = p2_buf(w, it);
  mbar_expect(c.bar + (B_QF + b) * 8, 16384);
  bulk_load(c.sm + SM_BUF + b * 16384, g_Q + (size_t)(h * 32 + j * 4 + p2_blk(c.rank, w, it)) * 16384, 16384, c.bar + (B_QF + b) * 8, POL(4));
}
__device__ __forceinline__ void wait_p1_free(const Ctx& c, int u1, int s) {
  mbar_wait(c.bar + (B_P1E + 2 * s) * 8, ((u1 - 1 - 2 * s) / 10) & 1);
  mbar_wait(c.bar + (B_P1E + 2 * s + 1) * 8, ((u1 - 2 - 2 * s) / 10) & 1);
}
__device__ __forceinline__ void p2_producer(const Params& p, const Ctx& c, int u1, int rot) {
  const int nit = p.s.r[c.cl].n2;
  int slot = rot, cnt = 0, par = 1, n = 0;
  const uint8_t* pv = nullptr;
  bool pl = false;
  auto load = [&](const uint8_t* src, int expect, uint32_t fb, bool last) {
    if (cnt < 5) {
      if (u1) {
        wait_p1_free(c, u1, slot);
        if (cnt == 0) p2_load_q(p, c, 0, 1);
      }
      cnt++;
    } else {
      if (slot == rot) par ^= 1;
      mbar_wait(c.bar + (B_P2E + slot) * 8, par);
    }
    if (expect) mbar_expect(fb, expect);
    bulk_load_mc(c.sm + SM_RING + slot * 32768 + c.rank * 16384, src, 16384, fb, last ? POL(5) : L2_NORMAL);
    slot = wrap5(slot + 1);
  };
  for (int it = 0; it < nit; it++) {
    const int item = p.s.r[c.cl].item[it], h = item >> 3, j = item & 7;
    uint32_t ready = (c.phases & 16) ? 0u : 255u;
    if (it == 0) { if (c.phases & 16) flag_wait<false>(F_Q + item, 4); mbar_wait(c.bar + B_LAD * 8, 0); p2_load_q(p, c, 0, 0); if (!u1) p2_load_q(p, c, 0, 1); }
    for (int t = 2 * j + 1; t >= 0; t--) {
      for (int n1 = 0; !((ready >> (t >> 1)) & 1); n1++) {
        int v;
        if (n1) { __nanosleep(32); if (n1 > 20000000) __trap(); }
        asm volatile("ld.relaxed.gpu.global.s32 %0, [%1];" : "=r"(v) : "l"(g_flags + F_KV + h * 8 + (c.lane & 7)) : "memory");
        ready = __ballot_sync(0xffffffffu, v >= 8);
      }
      const uint8_t* k = g_KV + (size_t)(p.s.slot[h][t >> 1] * 16 + t) * 32768 + c.rank * 16384;
      const uint32_t fb = c.bar + (B_P2F + (n & 3)) * 8;
      const bool last = (p.s.r[c.cl].last[it] >> (t >> 1)) & 1;
      load(k, pv && t != 2 * j ? 65536 : 32768, fb, last);
      if (!(t & 1) && t + 4 <= 2 * j && c.rank == 0) flag_add_rx(F_RD + h * 8 + (t >> 1) + 2);
      if (pv) load(pv, 0, t != 2 * j ? fb : c.bar + (B_ORD + ((n - 1 - it) & 3)) * 8, pl);
      pl = last;
      pv = k + (size_t)NH * 16 * 32768;
      n++;
    }
  }
  load(pv, 32768, c.bar + (B_P2F + (n & 3)) * 8, pl);
}

__device__ __forceinline__ void p2_storer(const Params& p, const Ctx& c, int sfpar) {
  const int nit = p.s.r[c.cl].n2;
  auto load_q = [&](int it, int w) {
    if (c.phases & 16) flag_wait<false>(F_Q + p.s.r[c.cl].item[it], 4);
    p2_load_q(p, c, it, w);
  };
  if (nit > 1) {
    load_q(1, 1); p2_load_q(p, c, 1, 0); }
  for (int i = 0; i < 2 * nit; i++) {
    const int it = i >> 1, w = (it ^ i ^ 1) & 1, b = p2_buf(w, it);
    const int item = p.s.r[c.cl].item[it], h = item >> 3, j = item & 7;
    mbar_wait(c.bar + (B_SF + b) * 8, (sfpar >> b) & 1);
    sfpar ^= 1 << b;
    bulk_store(g_Q + (size_t)(h * 32 + j * 4 + p2_blk(c.rank, w, it)) * 16384, c.sm + SM_BUF + b * 16384, 16384, POL(1));
    BULK_COMMIT();
    BULK_WAIT(0);
    flag_add_rx(F_CTX + j * 64 + h);
    if ((i & 1) && it + 2 < nit) { load_q(it + 2, w); p2_load_q(p, c, it + 2, w ^ 1); }
  }
  release(c, B_DONE);
}

__device__ __forceinline__ int p3_pos(int i, int x) { return i < 4 ? (i + x) & 3 : 4; }
__device__ __forceinline__ void p3_consumer(const Params& p, const Ctx& c, int x) {
  const bool first = p.s.r[c.cl].p3 >= 24;
  const int tile = p.s.r[c.cl].p3 - (first ? 24 : 0), j = tile / 3, nt = tile - 3 * j;
  const int na = first ? 9 : 0, nb = first ? 2 * p.s.nh[tile] : 64 - 2 * p.s.nh[tile];
  const uint32_t ad = desc_lo(c.sm + SM_RING + c.wg * 8192, 16), bd = desc_lo(c.sm + SM_RING + 16384, 4096);
  float acc[96] = {};
  int slot = 0, par = 0, prev = 0;
  float g0 = 0.f, g1 = 0.f;
  const int hold = c.wg && LAG ? na + nb - LAG : -1, pass = c.wg || !LAG ? -1 : na + nb - 1;
#pragma unroll 1
  for (int kb = 0; kb < nb; kb++) {
    if (kb == hold) bar_sync(6, 256);
    mbar_wait(c.bar + (B_P3F + slot) * 8, par);
    if (kb == 0) PROF(c.wg, 39);
    WG_FENCE();
#pragma unroll
    for (int kk = 0; kk < 4; kk++) wgmma_ss192<1>(acc, ad + p3_pos(slot, x) * 2560 + kk * 2, bd + p3_pos(slot, x) * 2560 + (kk >> 1) * 768 + (kk & 1) * 128, kk != 0 ? 1 : kb != 0);
    WG_COMMIT();
    if (kb == pass) bar_arrive(6, 256);
    WG_WAIT(1);
    if (kb > 0) release(c, B_P3E + prev);
    else {
      const float* g = g_gate + j * 256 + c.rank * 128 + c.wg * 64 + c.warp * 16 + (c.lane >> 2);
      g0 = __ldcg(g); g1 = __ldcg(g + 8);
    }
    prev = slot;
    if (++slot == 5) { slot = 0; par ^= 1; }
  }
  WG_WAIT(0);
  pin(acc);
  g0 = 1.f - g0; g1 = 1.f - g1;
#pragma unroll
  for (int i = 0; i < 24; i++) { acc[4 * i] *= g0; acc[4 * i + 1] *= g0; acc[4 * i + 2] *= g1; acc[4 * i + 3] *= g1; }
#pragma unroll 1
  for (int kb = nb; kb < nb + na; kb++) {
    if (kb == hold) bar_sync(6, 256);
    mbar_wait(c.bar + (B_P3F + slot) * 8, par);
    if (kb == 0) PROF(c.wg, 39);
    WG_FENCE();
#pragma unroll
    for (int kk = 0; kk < 4; kk++) wgmma_ss192<1, 1>(acc, ad + p3_pos(slot, x) * 2560 + kk * 128, bd + p3_pos(slot, x) * 2560 + (kk >> 1) * 768 + (kk & 1) * 128, 1);
    WG_COMMIT();
    if (kb == pass) bar_arrive(6, 256);
    WG_WAIT(1);
    if (kb > 0) release(c, B_P3E + prev);
    prev = slot;
    if (++slot == 5) { slot = 0; par ^= 1; }
  }
  WG_WAIT(0);
  pin(acc);
  PROF(c.wg, 40);
  if (first) bar_sync(4 + c.wg, 128);
  mbar_wait(c.bar + B_OUT * 8, 0);
  const int row = (c.lane & 7) + ((c.lane >> 3) & 1) * 8;
  const uint32_t wbase = c.sm + SM_RING + c.wg * 8192 + c.warp * 2048;
  const uint32_t base = wbase + row * 128 + (((c.lane >> 4) ^ (row & 7)) << 4);
#pragma unroll
  for (int i = 0; i < 12; i++) {
    stsm4((base ^ ((i & 3) << 5)) + (i >> 2) * 40960, pack_bf16(acc[8 * i], acc[8 * i + 1]), pack_bf16(acc[8 * i + 2], acc[8 * i + 3]),
          pack_bf16(acc[8 * i + 4], acc[8 * i + 5]), pack_bf16(acc[8 * i + 6], acc[8 * i + 7]));
    if ((i & 3) == 3) {
      FENCE_ASYNC_SMEM();
      bar_sync(4 + c.wg, 128);
      if (c.warp == (i >> 2)) tma2d_add(&p.map_out, c.sm + SM_RING + c.wg * 8192 + c.warp * 40960, nt * 192 + c.warp * 64, j * 256 + c.rank * 128 + c.wg * 64);
    }
  }
  BULK_COMMIT();
  PROF(c.wg, 43);
  BULK_WAIT_READ(0);
  PROF(c.wg, 44);
}

__device__ __forceinline__ void p3_producer(const Params& p, const Ctx& c, int u1, int u2, int rot, int x) {
  const bool first = p.s.r[c.cl].p3 >= 24;
  const int tile = p.s.r[c.cl].p3 - (first ? 24 : 0), j = tile / 3, nt = tile - 3 * j;
  int slot = 0, par = 1, cnt = 0;
  auto wait_free = [&](int s) {
    const int f = wrap5(s + 5 - rot);
    if (f < u2) mbar_wait(c.bar + (B_P2E + s) * 8, ((u2 - 1 - f) / 5) & 1);
    else if (u1) wait_p1_free(c, u1, s);
  };
  asm volatile(ELECT("prefetch.tensormap [%0];") ::"l"(&p.map_o[0]) : "memory");
  asm volatile(ELECT("prefetch.tensormap [%0];") ::"l"(&p.map_out) : "memory");
  if (c.phases & 16) flag_wait<true>(F_GATE, 256);
  const int q1 = first ? p.s.nh[tile] : 31;
  for (int q = first ? 0 : p.s.nh[tile]; q <= q1; q++) {
    const bool brA = first && q == q1;
    const int g = brA ? 32 : p.s.p3_order[j][q];
    if (c.phases & 16) flag_wait<false>(F_CTX + j * 64 + g, brA ? 16 : 4);
    const int nk = brA ? 9 : 2, k0 = (brA ? 0 : g * 128) + c.rank * 32;
    const uint8_t* a = brA ? g_oA + (j * 4 + c.rank * 2) * 73728 : g_Q + (size_t)(g * 32 + j * 4 + c.rank * 2) * 16384;
    const CUtensorMap* m = &p.map_o[brA];
    for (int i = 0; i < nk; i++) {
      const uint32_t st = c.sm + SM_RING + p3_pos(slot, x) * 40960, fb = c.bar + (B_P3F + slot) * 8;
      if (cnt < 4) { wait_free(p3_pos(cnt, x)); wait_free(p3_pos(cnt, x) + 1); }
      else if (cnt == 4) mbar_wait(c.bar + B_DONE * 8, 0);
      else mbar_wait(c.bar + (B_P3E + slot) * 8, par);
      cnt++;
      mbar_expect(fb, 40960);
      bulk_load(st, a + i * 8192, 8192, fb, POL(3));
      bulk_load(st + 8192, a + (nk + i) * 8192, 8192, fb, POL(3));
      tma3d_mc(st + 16384 + c.rank * 12288, m, 0, k0 + i * 64, nt * 3, fb);
      if (++slot == 5) { slot = 0; par ^= 1; }
    }
  }
}

__device__ __forceinline__ float bf_lo(uint32_t w) { return __uint_as_float(w << 16); }
__device__ __forceinline__ float bf_hi(uint32_t w) { return __uint_as_float(w & 0xffff0000u); }

__device__ __forceinline__ void gate_rows(const Params& p, int row0, int lane) {
  const uint4* x = reinterpret_cast<const uint4*>(p.x + (size_t)(row0 + (lane >> 2)) * DM) + (lane & 3);
  const uint4* w = reinterpret_cast<const uint4*>(p.gate_w) + (lane & 3);
  float a = 0.f;
#pragma unroll 1
  for (int b = 0; b < 3; b++) {
    uint4 u[6];
#pragma unroll
    for (int i = 0; i < 6; i++) u[i] = __ldg(x + (b * 6 + i) * 4);
#pragma unroll
    for (int i = 0; i < 6; i++) {
      const uint4 v = __ldg(w + (b * 6 + i) * 4);
      a = fmaf(bf_lo(u[i].x), bf_lo(v.x), a); a = fmaf(bf_hi(u[i].x), bf_hi(v.x), a);
      a = fmaf(bf_lo(u[i].y), bf_lo(v.y), a); a = fmaf(bf_hi(u[i].y), bf_hi(v.y), a);
      a = fmaf(bf_lo(u[i].z), bf_lo(v.z), a); a = fmaf(bf_hi(u[i].z), bf_hi(v.z), a);
      a = fmaf(bf_lo(u[i].w), bf_lo(v.w), a); a = fmaf(bf_hi(u[i].w), bf_hi(v.w), a);
    }
  }
  a += __shfl_xor_sync(0xffffffffu, a, 1);
  a += __shfl_xor_sync(0xffffffffu, a, 2);
  if ((lane & 3) == 0) g_gate[row0 + (lane >> 2)] = 1.f / (1.f + __expf(-a));
}

__device__ __forceinline__ void lds10(uint32_t (&k)[10], uint32_t a) {
  asm volatile("ld.shared.v2.u32 {%0, %1}, [%10];\nld.shared.v2.u32 {%2, %3}, [%10+8];\nld.shared.v2.u32 {%4, %5}, [%10+16];\n"
               "ld.shared.v2.u32 {%6, %7}, [%10+24];\nld.shared.v2.u32 {%8, %9}, [%10+32];"
               : "=r"(k[0]), "=r"(k[1]), "=r"(k[2]), "=r"(k[3]), "=r"(k[4]), "=r"(k[5]), "=r"(k[6]), "=r"(k[7]), "=r"(k[8]), "=r"(k[9]) : "r"(a));
}
__device__ __forceinline__ void local_attn(const Params& p, const Ctx& c, int rb, int hs) {
  const int lane = c.lane, grp = rb >> 2, par = lane >> 4, i0 = 2 * (lane & 15);
  const uint32_t buf = c.sm + SM_BUF + (c.warp - 2) * 8192, bqk = c.bar + (B_LA + (c.warp - 2) * 2) * 8, bv = bqk + 8;
  const uint32_t mine = buf + 2304 + par * 160 + i0 * 4;
  const bool flags = c.phases & 16;
  auto fetch_qk = [&](int i) {
    if (flags && !(i & 1)) {
      const int q = i >> 1;
      const int tgt = q == 0 ? 24 : q == 3 ? 8 : 12;
      flag_wait<false>(F_QKVA + (grp - (grp > 0 && (rb & 3) == 0 ? par : 0)) * 4 + q, tgt);
    }
    mbar_expect(bqk, 5184);
    tma3d(buf, &p.map_t[0], rb * 32 + 8, 0, 9 * (4 * i + hs), bqk, POL(2));
    tma3d(buf + 2304, &p.map_t[1], rb * 32, 0, 288 + 9 * (4 * i + hs), bqk, POL(2));
  };
  auto fetch_v = [&](int i) { mbar_expect(bv, 2880); tma3d(buf + 5248, &p.map_t[1], rb * 32, 0, 576 + 9 * (4 * i + hs), bv, POL(2)); };
  fetch_qk(0);
  if (flags) flag_wait<true>(F_GATE, 256);
#pragma unroll 1
  for (int q = 0; q < 8; q++) {
    fetch_v(q);
    float a[8], b[8];
#pragma unroll
    for (int w = 0; w < 8; w++) a[w] = b[w] = 0.f;
    mbar_wait(bqk, q & 1);
    PROFB(1 + 2 * q);
#pragma unroll 1
    for (int j = 0; j < 9; j++) {
      uint32_t x, y, k[10];
      asm volatile("ld.shared.v2.u32 {%0, %1}, [%2];" : "=r"(x), "=r"(y) : "r"(buf + lane * 8 + j * 256));
      lds10(k, mine + j * 320);
      const float xl = bf_lo(x), xh = bf_hi(x), yl = bf_lo(y), yh = bf_hi(y);
#pragma unroll
      for (int m = 1; m < 10; m++) {
        const float kl = bf_lo(k[m]), kh = bf_hi(k[m]);
        if (m < 9) a[8 - m] = fmaf(xl, kl, fmaf(xh, kh, a[8 - m]));
        if (m > 1) b[9 - m] = fmaf(yl, kl, fmaf(yh, kh, b[9 - m]));
      }
    }
    __syncwarp();
    if (q < 7) fetch_qk(q + 1);
    constexpr float SC = 0.23570226039551584f * 1.4426950408889634f;
    const float* gp = g_gate + rb * 64 + 2 * i0 + par;
    const float ga = __ldcg(gp), gb = __ldcg(gp + 2);
    float ma = a[0], mb = b[0];
#pragma unroll
    for (int w = 1; w < 8; w++) {
      if (rb == 0) {
        if (i0 < w) a[w] = -INFINITY;
        if (i0 + 1 < w) b[w] = -INFINITY;
      }
      ma = fmaxf(ma, a[w]); mb = fmaxf(mb, b[w]);
    }
    float la = 0.f, lb = 0.f;
#pragma unroll
    for (int w = 0; w < 8; w++) {
      a[w] = ex2((a[w] - ma) * SC); b[w] = ex2((b[w] - mb) * SC);
      la += a[w]; lb += b[w];
    }
    la = __fdividef(ga, la); lb = __fdividef(gb, lb);
#pragma unroll
    for (int w = 0; w < 8; w++) { a[w] *= la; b[w] *= lb; }
    uint8_t* dst = g_oA + rb * 73728 + ((i0 & 2) + par) * 4;
    mbar_wait(bv, q & 1);
#pragma unroll 1
    for (int j = 0; j < 9; j++) {
      uint32_t v[10];
      lds10(v, mine + 2944 + j * 320);
      float a0 = 0.f, a1 = 0.f, b0 = 0.f, b1 = 0.f;
#pragma unroll
      for (int m = 1; m < 10; m++) {
        const float vl = bf_lo(v[m]), vh = bf_hi(v[m]);
        if (m < 9) { a0 = fmaf(a[8 - m], vl, a0); a1 = fmaf(a[8 - m], vh, a1); }
        if (m > 1) { b0 = fmaf(b[9 - m], vl, b0); b1 = fmaf(b[9 - m], vh, b1); }
      }
      const uint32_t wa = pack_bf16(a0, a1), wb = pack_bf16(b0, b1);
      const uint32_t got = __shfl_xor_sync(0xffffffffu, par ? wa : wb, 16);
      const uint32_t r0 = par ? got : wa, r1 = par ? wb : got;
      const int col = 18 * (4 * q + hs) + 2 * j, o = col * 128 + ((((i0 >> 2) ^ col) & 7) << 4);
      *reinterpret_cast<uint32_t*>(dst + o) = __byte_perm(r0, r1, 0x5410);
      *reinterpret_cast<uint32_t*>(dst + ((o + 128) ^ 16)) = __byte_perm(r0, r1, 0x7632);
    }
    __syncwarp();
    PROFB(2 + 2 * q);
  }
  mbar_arrive_one(c.bar + B_LAD * 8);
  flag_add(F_CTX + grp * 64 + 32);
}

__global__ void __cluster_dims__(2, 1, 1) __launch_bounds__(384, 1) fused_kernel(const __grid_constant__ Params p) {
  extern __shared__ uint8_t smem_raw[];
  Ctx c;
  c.sm = ((uint32_t)__cvta_generic_to_shared(smem_raw) + 1023u) & ~1023u;
  c.bar = c.sm + SM_BAR;
  c.lane = threadIdx.x & 31;
  const int wid = __shfl_sync(0xffffffffu, threadIdx.x >> 5, 0);
  if (wid < 6) asm volatile("prefetch.tensormap [%0];" ::"l"(&p.map_a[0] + wid) : "memory");
  c.wg = wid >> 2;
  c.warp = wid & 3;
  PROF(c.wg, 0);
  PROFG(61);
  c.cl = (blockIdx.x + (wid >> 4)) >> 1;
  c.rank = blockIdx.x & 1;
  c.rbar = mapa(c.bar, c.lane & 1);
  {
    const int w = wid, cnt = (((int)(B_CNT >> (4 * w)) - 1) & 15) + 1;
    if (w < 11) {
#pragma unroll
      for (int i = 0; i < 8; i++) asm volatile("mbarrier.init.shared::cta.b64 [%0], %1;" ::"r"(c.bar + w * 64 + i * 8), "r"(cnt));
    }
    asm volatile("fence.mbarrier_init.release.cluster;" ::: "memory");
  }
  if (c.wg == 2) PROF(2, 56);
  asm volatile("barrier.cluster.arrive.relaxed;" ::: "memory");
  c.phases = p.s.r[c.cl].phases;
  const bool do1 = p.s.r[c.cl].n1 > 0, do2 = p.s.r[c.cl].n2 > 0, do3 = p.s.r[c.cl].p3 != 255;
  if (do1 && c.wg == 2 && c.warp == 0) {
    const int type = p.s.r[c.cl].slab >> 3;
    PROF(2, 57);
    FENCE_ASYNC_SMEM();
    mbar_expect(c.bar + B_P1F * 8, type ? 32768 : 16384);
    tma2d(type ? c.sm + SM_BUF + 32768 : c.sm + SM_RING, &p.map_a[type], type ? 512 : 0, (p.s.r[c.cl].slab & 7) * 256 + c.rank * 128, c.bar + B_P1F * 8);
    PROF(2, 58);
  }
  asm volatile("barrier.cluster.wait.acquire;" ::: "memory");
  if (c.wg == 2) PROF(2, 59);
  if (do1 && c.wg == 2 && c.warp == 0) {
    const int type = p.s.r[c.cl].slab >> 3, tile = p.s.r[c.cl].tile[0] & 63;
    if (!type) mbar_expect(c.bar + (B_P1F + 1) * 8, 16384);
    tma2d_mc(c.sm + SM_RING + (1 - type) * 16384 + c.rank * 8192, &p.map_w[type * 2 + (tile >> 5)], (tile & 31) * 128 + c.rank * 64, type ? 512 : 0, c.bar + (B_P1F + 1 - type) * 8);
  }

  if (c.wg < 2) {
    PROF(c.wg, 4);
    asm volatile("setmaxnreg.inc.sync.aligned.u32 224;");
    if (c.wg == 1) {
      if (do1) bar_arrive(ORDER, 256);
      if (c.lane == 0) mbar_arrive(c.bar + B_P2F * 8);
    }
    if (do1) p1_consumer(p, c);
    if (do2) p2_consumer(p, c, p.s.r[c.cl].rot);
    if (do3) p3_consumer(p, c, p.s.r[c.cl].x3);
    PROF(c.wg, 63);
    PROFG(62);
    if (c.lane == 0) mbar_arrive(c.bar + B_FIN * 8);
    __syncwarp();
    cluster_sync();
  } else {
    asm volatile("setmaxnreg.dec.sync.aligned.u32 56;");
    if (c.warp == 0) {
      PROF(2, 60);
      if (do1) p1_producer(p, c);
      if (do2) p2_producer(p, c, p.s.r[c.cl].u1, p.s.r[c.cl].rot);
      if (do3) p3_producer(p, c, p.s.r[c.cl].u1, p.s.r[c.cl].u2, p.s.r[c.cl].rot, p.s.r[c.cl].x3);
    } else if (c.warp == 1) {
      int sfpar = 0;
      if (do1) {
        p1_storer(p, c);
        sfpar = (p.s.r[c.cl].n1 & 1) * 10;
      }
      if (do2) p2_storer(p, c, sfpar);
      else { mbar_wait(c.bar + B_LAD * 8, 0); release(c, B_DONE); }
      if (do3) {
        const int task = p.s.r[c.cl].p3;
        if (task >= 24) {
          const int j = (task - 24) / 3, nt = task - 24 - 3 * j;
          uint4* o = reinterpret_cast<uint4*>(p.out + (size_t)(j * 256 + c.rank * 128 + (c.lane >> 3)) * DM + nt * 192) + (c.lane & 7);
#pragma unroll 4
          for (int r = 0; r < 32; r++) o[r * 288] = o[r * 288 + 8] = o[r * 288 + 16] = make_uint4(0u, 0u, 0u, 0u);
          __syncwarp();
          flag_add(F_OUT + (task - 24) * 2 + c.rank);
        } else if (c.phases & 16) {
          flag_wait<false, 256>(F_OUT + task * 2 + c.rank, 1);
        }
        mbar_arrive_one(c.bar + B_OUT * 8);
      }
    } else {
      const int bw = blockIdx.x * 2 + (c.warp - 2);
      if ((c.phases & 1) && bw < 256) {
        gate_rows(p, bw * 8, c.lane);
        __syncwarp();
        flag_add(F_GATE);
      }
      if (p.s.r[c.cl].bg != 255) local_attn(p, c, p.s.r[c.cl].bg, bw & 3);
      else if (c.lane == 0) mbar_arrive(c.bar + B_LAD * 8);
    }
    __syncwarp();
    bar_sync(3, 128);
    if (c.warp == 0 && (c.phases & 4)) {
      int last = 0;
      if (c.lane == 0) { __threadfence(); last = atomicAdd(g_flags + F_DONE, 1) == 2 * NCL - 1; }
      if (__shfl_sync(0xffffffffu, last, 0)) for (int i = c.lane; i < F_NUM; i += 32) g_flags[i] = 0;
    }
    if (c.warp == 1) mbar_wait(c.bar + B_FIN * 8, 0);
    __syncwarp();
    cluster_sync();
  }
}

SCHED_DECL Sched k_sched = {
  {{0,29,2,26,0,{232,248,0,0,0,0,0,0,0,0,0},{0,0,0,0,0,0,0,0,0,0,0},{71,38,3,32,5,4,2,11,9,24,21,12,19,17,74,20,13,22,16,18,28,14,29,26,31,23,27,30,25,0}},
   {1,29,2,255,1,{216,244,0,0,0,0,0,0,0,0,0},{0,0,0,0,0,0,0,0,0,0,0},{71,38,0,40,79,4,2,11,9,24,21,19,17,12,20,13,10,22,16,18,28,14,29,26,31,23,27,30,25,0}},
   {2,29,2,255,2,{217,243,0,0,0,0,0,0,0,0,0},{0,0,0,0,0,0,0,0,0,0,0},{67,40,7,32,1,15,4,9,11,24,19,21,17,12,13,20,16,22,10,18,28,14,29,31,26,23,27,30,25,0}},
   {3,29,1,255,3,{188,0,0,0,0,0,0,0,0,0,0},{0,0,0,0,0,0,0,0,0,0,0},{70,35,0,40,1,2,4,9,11,24,21,19,17,12,13,20,22,16,10,18,28,14,26,29,31,23,27,30,25,0}},
   {4,28,0,15,4,{0,0,0,0,0,0,0,0,0,0,0},{0,0,0,0,0,0,0,0,0,0,0},{64,39,8,38,1,2,36,24,11,21,12,19,17,20,13,22,16,10,18,28,14,29,26,31,23,27,30,25,0,0}},
   {5,28,0,14,5,{0,0,0,0,0,0,0,0,0,0,0},{0,0,0,0,0,0,0,0,0,0,0},{72,35,0,38,1,2,36,24,11,21,12,19,17,20,13,22,16,10,18,28,14,29,26,31,23,27,30,25,0,0}},
   {6,27,1,44,6,{212,0,0,0,0,0,0,0,0,0,0},{24,0,0,0,0,0,0,0,0,0,0},{71,8,6,37,2,15,41,11,21,12,19,17,20,13,86,16,10,18,28,14,29,26,31,27,23,30,25,0,0,0}},
   {7,26,2,36,7,{112,252,0,0,0,0,0,0,0,0,0},{0,0,0,0,0,0,0,0,0,0,0},{70,7,3,65,68,75,88,85,76,83,81,84,77,80,74,22,82,92,78,93,90,95,91,87,94,89,0,0,0,0}},
   {0,29,1,25,8,{251,0,0,0,0,0,0,0,0,0,0},{0,0,0,0,0,0,0,0,0,0,0},{103,8,35,65,37,36,34,43,41,56,53,44,51,49,106,52,45,54,48,50,60,46,61,58,63,55,59,62,57,0}},
   {1,29,1,255,9,{245,0,0,0,0,0,0,0,0,0,0},{56,0,0,0,0,0,0,0,0,0,0},{103,3,32,5,111,36,34,43,41,56,53,51,49,44,52,45,42,54,48,50,60,46,61,58,63,55,59,62,57,0}},
   {2,29,1,27,10,{210,0,0,0,0,0,0,0,0,0,0},{7,0,0,0,0,0,0,0,0,0,0},{99,6,39,5,33,47,36,41,43,56,51,53,49,44,45,52,48,54,42,50,60,46,61,63,58,55,59,62,57,0}},
   {3,29,2,255,11,{218,202,0,0,0,0,0,0,0,0,0},{0,0,0,0,0,0,0,0,0,0,0},{102,7,32,5,33,34,36,41,43,56,53,51,49,44,45,52,54,48,42,50,60,46,58,61,63,55,59,62,57,0}},
   {4,28,0,21,12,{0,0,0,0,0,0,0,0,0,0,0},{0,0,0,0,0,0,0,0,0,0,0},{96,3,40,5,33,34,9,56,43,53,44,51,49,52,45,54,48,42,50,60,46,61,58,63,55,59,62,57,0,0}},
   {5,28,0,4,13,{0,0,0,0,0,0,0,0,0,0,0},{0,0,0,0,0,0,0,0,0,0,0},{104,7,32,5,33,34,9,56,43,53,44,51,49,52,45,54,48,42,50,60,46,61,58,63,55,59,62,57,0,0}},
   {6,27,0,12,14,{0,0,0,0,0,0,0,0,0,0,0},{0,0,0,0,0,0,0,0,0,0,0},{103,40,38,65,34,47,88,43,53,44,51,49,52,45,118,48,42,50,60,46,61,58,63,59,55,62,57,0,0,0}},
   {7,26,0,9,15,{0,0,0,0,0,0,0,0,0,0,0},{0,0,0,0,0,0,0,0,0,0,0},{102,39,35,97,100,107,120,117,108,115,113,116,109,112,106,54,114,124,110,125,122,127,123,119,126,121,0,0,0,0}},
   {0,6,6,46,255,{0,59,22,194,107,215,0,0,0,0,0},{0,0,0,0,0,192,0,0,0,0,0},{70,40,0,97,79,47,0,0,0,0,0,0,0,0,0,0,0,0,0,0,0,0,0,0,0,0,0,0,0,0}},
   {1,6,6,8,255,{61,10,174,179,233,224,0,0,0,0,0},{0,0,0,0,0,0,0,0,0,0,0},{70,35,8,37,1,33,0,0,0,0,0,0,0,0,0,0,0,0,0,0,0,0,0,0,0,0,0,0,0,0}},
   {2,6,4,23,255,{47,93,100,226,0,0,0,0,0,0,0},{0,0,0,0,0,0,0,0,0,0,0},{72,38,0,37,2,34,0,0,0,0,0,0,0,0,0,0,0,0,0,0,0,0,0,0,0,0,0,0,0,0}},
   {3,6,7,29,255,{41,44,89,74,193,141,238,0,0,0,0},{0,0,0,0,0,0,0,0,0,0,0},{67,39,8,37,79,47,0,0,0,0,0,0,0,0,0,0,0,0,0,0,0,0,0,0,0,0,0,0,0,0}},
   {4,8,5,33,255,{58,125,102,239,241,0,0,0,0,0,0},{0,0,0,0,0,0,0,0,0,0,0},{71,35,6,37,79,47,4,41,0,0,0,0,0,0,0,0,0,0,0,0,0,0,0,0,0,0,0,0,0,0}},
   {5,8,5,37,255,{120,23,195,134,190,0,0,0,0,0,0},{0,0,0,0,0,0,0,0,0,0,0},{67,39,6,37,79,47,4,41,0,0,0,0,0,0,0,0,0,0,0,0,0,0,0,0,0,0,0,0,0,0}},
   {6,8,7,255,255,{40,43,34,159,83,211,219,0,0,0,0},{0,0,0,0,0,0,0,0,0,0,0},{64,3,69,97,68,36,9,56,0,0,0,0,0,0,0,0,0,0,0,0,0,0,0,0,0,0,0,0,0,0}},
   {7,6,6,31,255,{46,73,75,101,113,237,0,0,0,0,0},{0,0,0,0,0,63,0,0,0,0,0},{64,8,69,66,79,73,0,0,0,0,0,0,0,0,0,0,0,0,0,0,0,0,0,0,0,0,0,0,0,0}},
   {8,16,5,255,16,{192,170,148,250,220,0,0,0,0,0,0},{0,0,0,0,31,0,0,0,0,0,0},{160,170,0,43,35,44,45,4,11,12,21,19,16,22,14,27,0,0,0,0,0,0,0,0,0,0,0,0,0,0}},
   {9,19,1,11,17,{131,0,0,0,0,0,0,0,0,0,0},{0,0,0,0,0,0,0,0,0,0,0},{71,37,8,43,1,75,2,45,21,19,20,10,16,28,29,23,27,30,25,0,0,0,0,0,0,0,0,0,0,0}},
   {10,18,4,32,18,{152,130,229,184,0,0,0,0,0,0,0},{0,0,7,0,0,0,0,0,0,0,0},{160,170,166,163,15,40,9,83,81,21,20,10,92,22,95,26,89,30,0,0,0,0,0,0,0,0,0,0,0,0}},
   {11,17,4,255,19,{168,162,227,247,0,0,0,0,0,0,0},{0,0,0,192,0,0,0,0,0,0,0},{160,170,166,163,2,109,4,24,19,12,22,20,18,14,29,31,30,0,0,0,0,0,0,0,0,0,0,0,0,0}},
   {12,16,3,13,20,{72,156,144,0,0,0,0,0,0,0,0},{0,0,0,0,0,0,0,0,0,0,0},{160,170,6,1,15,9,45,24,12,17,20,16,18,14,95,23,0,0,0,0,0,0,0,0,0,0,0,0,0,0}},
   {13,16,3,18,21,{88,161,85,0,0,0,0,0,0,0,0},{0,0,0,0,0,0,0,0,0,0,0},{160,170,0,43,2,9,24,45,12,17,13,16,18,14,26,23,0,0,0,0,0,0,0,0,0,0,0,0,0,0}},
   {14,16,3,39,22,{137,108,117,0,0,0,0,0,0,0,0},{0,0,0,0,0,0,0,0,0,0,0},{160,170,6,1,4,88,40,21,19,84,13,10,92,93,95,23,0,0,0,0,0,0,0,0,0,0,0,0,0,0}},
   {15,16,5,255,23,{16,99,82,223,200,0,0,0,0,0,0},{1,0,0,192,0,0,0,0,0,0,0},{160,170,3,43,39,9,24,40,12,17,13,10,18,14,26,27,0,0,0,0,0,0,0,0,0,0,0,0,0,0}},
   {8,21,4,255,24,{128,234,209,205,0,0,0,0,0,0,0},{0,0,0,63,0,0,0,0,0,0,0},{164,70,65,5,39,40,2,9,24,17,74,13,18,20,28,29,31,23,26,25,30,0,0,0,0,0,0,0,0,0}},
   {9,16,3,3,25,{32,105,133,0,0,0,0,0,0,0,0},{1,0,0,0,0,0,0,0,0,0,0},{160,170,133,163,4,9,40,24,81,12,13,22,18,14,26,31,0,0,0,0,0,0,0,0,0,0,0,0,0,0}},
   {10,16,3,19,26,{96,165,176,0,0,0,0,0,0,0,0},{0,0,0,0,0,0,0,0,0,0,0},{164,131,107,103,4,109,11,24,12,77,80,82,78,93,91,23,0,0,0,0,0,0,0,0,0,0,0,0,0,0}},
   {11,17,4,47,27,{136,177,163,213,0,0,0,0,0,0,0},{0,0,0,32,0,0,0,0,0,0,0},{164,70,107,103,104,9,11,21,81,77,80,10,92,90,87,27,89,0,0,0,0,0,0,0,0,0,0,0,0,0}},
   {12,18,2,255,28,{231,221,0,0,0,0,0,0,0,0,0},{0,32,0,0,0,0,0,0,0,0,0},{164,64,34,163,4,40,11,21,19,77,22,10,92,93,26,27,30,25,0,0,0,0,0,0,0,0,0,0,0,0}},
   {13,18,3,255,29,{104,150,206,0,0,0,0,0,0,0,0},{0,3,0,0,0,0,0,0,0,0,0},{164,72,133,15,4,75,40,21,19,84,22,10,92,93,95,27,30,25,0,0,0,0,0,0,0,0,0,0,0,0}},
   {14,17,3,35,30,{80,181,254,0,0,0,0,0,0,0,0},{0,0,127,0,0,0,0,0,0,0,0},{164,7,133,15,73,75,45,76,81,86,80,82,78,90,91,94,89,0,0,0,0,0,0,0,0,0,0,0,0,0}},
   {15,18,3,41,31,{129,119,208,0,0,0,0,0,0,0,0},{0,0,0,0,0,0,0,0,0,0,0},{164,70,133,66,44,75,85,45,19,84,80,22,92,93,95,23,30,25,0,0,0,0,0,0,0,0,0,0,0,0}},
   {8,4,6,40,255,{25,15,17,173,164,191,0,0,0,0,0},{0,0,0,0,18,255,0,0,0,0,0},{169,7,34,15,0,0,0,0,0,0,0,0,0,0,0,0,0,0,0,0,0,0,0,0,0,0,0,0,0,0}},
   {9,4,4,10,255,{69,12,196,110,0,0,0,0,0,0,0},{0,0,0,0,0,0,0,0,0,0,0},{164,70,79,103,0,0,0,0,0,0,0,0,0,0,0,0,0,0,0,0,0,0,0,0,0,0,0,0,0,0}},
   {10,4,6,255,255,{55,33,175,132,253,242,0,0,0,0,0},{0,0,0,0,0,6,0,0,0,0,0},{169,72,7,108,0,0,0,0,0,0,0,0,0,0,0,0,0,0,0,0,0,0,0,0,0,0,0,0,0,0}},
   {11,4,4,5,255,{63,20,154,183,0,0,0,0,0,0,0},{188,0,0,131,0,0,0,0,0,0,0},{169,131,8,108,0,0,0,0,0,0,0,0,0,0,0,0,0,0,0,0,0,0,0,0,0,0,0,0,0,0}},
   {12,4,5,34,255,{7,124,158,146,189,0,0,0,0,0,0},{111,0,0,0,0,0,0,0,0,0,0},{169,7,166,103,0,0,0,0,0,0,0,0,0,0,0,0,0,0,0,0,0,0,0,0,0,0,0,0,0,0}},
   {13,4,7,38,255,{51,14,91,153,81,145,118,0,0,0,0},{0,0,0,0,0,0,95,0,0,0,0},{169,131,65,163,0,0,0,0,0,0,0,0,0,0,0,0,0,0,0,0,0,0,0,0,0,0,0,0,0,0}},
   {14,5,6,30,255,{54,36,169,138,180,236,0,0,0,0,0},{0,0,0,0,0,0,0,0,0,0,0},{169,64,34,66,44,0,0,0,0,0,0,0,0,0,0,0,0,0,0,0,0,0,0,0,0,0,0,0,0,0}},
   {15,4,8,43,255,{49,5,122,35,157,115,185,186,0,0,0},{0,0,0,0,47,0,0,0,0,0,0},{169,64,65,68,0,0,0,0,0,0,0,0,0,0,0,0,0,0,0,0,0,0,0,0,0,0,0,0,0,0}},
   {8,3,6,255,255,{70,18,197,109,116,204,0,0,0,0,0},{0,0,0,0,0,0,0,0,0,0,0},{161,72,166,0,0,0,0,0,0,0,0,0,0,0,0,0,0,0,0,0,0,0,0,0,0,0,0,0,0,0}},
   {9,3,4,0,255,{4,39,90,182,0,0,0,0,0,0,0},{0,0,0,0,0,0,0,0,0,0,0},{169,131,34,0,0,0,0,0,0,0,0,0,0,0,0,0,0,0,0,0,0,0,0,0,0,0,0,0,0,0}},
   {10,4,6,7,255,{48,28,42,76,172,228,0,0,0,0,0},{0,0,0,0,0,0,0,0,0,0,0},{161,70,0,66,0,0,0,0,0,0,0,0,0,0,0,0,0,0,0,0,0,0,0,0,0,0,0,0,0,0}},
   {11,4,6,255,255,{62,123,103,225,214,203,0,0,0,0,0},{0,0,0,0,0,0,0,0,0,0,0},{161,7,0,1,0,0,0,0,0,0,0,0,0,0,0,0,0,0,0,0,0,0,0,0,0,0,0,0,0,0}},
   {12,4,6,22,255,{64,65,68,21,142,114,0,0,0,0,0},{0,0,0,0,0,0,0,0,0,0,0},{161,131,107,108,0,0,0,0,0,0,0,0,0,0,0,0,0,0,0,0,0,0,0,0,0,0,0,0,0,0}},
   {13,4,5,24,255,{30,9,19,143,255,0,0,0,0,0,0},{0,0,0,0,128,0,0,0,0,0,0},{161,7,34,103,0,0,0,0,0,0,0,0,0,0,0,0,0,0,0,0,0,0,0,0,0,0,0,0,0,0}},
   {14,4,7,42,255,{24,1,13,77,139,149,187,0,0,0,0},{0,0,0,0,0,0,0,0,0,0,0},{161,72,166,163,0,0,0,0,0,0,0,0,0,0,0,0,0,0,0,0,0,0,0,0,0,0,0,0,0,0}},
   {15,4,4,6,255,{60,127,167,178,0,0,0,0,0,0,0},{0,0,0,0,0,0,0,0,0,0,0},{161,7,34,15,0,0,0,0,0,0,0,0,0,0,0,0,0,0,0,0,0,0,0,0,0,0,0,0,0,0}},
   {8,2,7,28,255,{26,121,2,38,155,230,249,0,0,0,0},{0,0,0,0,0,0,0,0,0,0,0},{165,131,0,0,0,0,0,0,0,0,0,0,0,0,0,0,0,0,0,0,0,0,0,0,0,0,0,0,0,0}},
   {9,4,4,16,255,{66,52,95,140,0,0,0,0,0,0,0},{0,0,0,0,0,0,0,0,0,0,0},{161,64,166,108,0,0,0,0,0,0,0,0,0,0,0,0,0,0,0,0,0,0,0,0,0,0,0,0,0,0}},
   {10,4,5,255,255,{6,11,92,151,207,0,0,0,0,0,0},{0,0,0,0,192,0,0,0,0,0,0},{165,98,133,1,0,0,0,0,0,0,0,0,0,0,0,0,0,0,0,0,0,0,0,0,0,0,0,0,0,0}},
   {11,4,4,17,255,{29,126,171,86,0,0,0,0,0,0,0},{0,0,0,124,0,0,0,0,0,0,0},{165,98,133,15,0,0,0,0,0,0,0,0,0,0,0,0,0,0,0,0,0,0,0,0,0,0,0,0,0,0}},
   {12,4,6,255,255,{71,198,98,84,222,201,0,0,0,0,0},{222,0,0,0,0,0,0,0,0,0,0},{165,72,133,66,0,0,0,0,0,0,0,0,0,0,0,0,0,0,0,0,0,0,0,0,0,0,0,0,0,0}},
   {13,4,7,255,255,{56,50,67,79,135,246,240,0,0,0,0},{0,0,0,192,255,0,1,0,0,0,0},{165,70,166,108,0,0,0,0,0,0,0,0,0,0,0,0,0,0,0,0,0,0,0,0,0,0,0,0,0,0}},
   {14,4,7,45,255,{27,3,78,97,106,147,235,0,0,0,0},{0,0,0,0,0,0,0,0,0,0,0},{165,131,107,103,0,0,0,0,0,0,0,0,0,0,0,0,0,0,0,0,0,0,0,0,0,0,0,0,0,0}},
   {15,4,3,1,255,{31,37,111,0,0,0,0,0,0,0,0},{242,0,0,0,0,0,0,0,0,0,0},{165,72,166,163,0,0,0,0,0,0,0,0,0,0,0,0,0,0,0,0,0,0,0,0,0,0,0,0,0,0}},
   {6,2,4,2,255,{57,53,199,87,0,0,0,0,0,0,0},{0,0,0,128,0,0,0,0,0,0,0},{96,35,0,0,0,0,0,0,0,0,0,0,0,0,0,0,0,0,0,0,0,0,0,0,0,0,0,0,0,0}},
   {7,6,5,20,255,{8,45,94,166,160,0,0,0,0,0,0},{0,0,0,0,1,0,0,0,0,0,0},{96,40,101,98,111,105,0,0,0,0,0,0,0,0,0,0,0,0,0,0,0,0,0,0,0,0,0,0,0,0}}},
  {6,4,9,7,10,9,9,8,9,5,6,4,7,2,10,10,1,9,7,5,7,10,8,7},
  {{3,6,7,8,0,1,5,15,2,4,9,11,12,24,10,17,21,13,19,18,16,22,20,28,14,27,29,31,23,26,25,30},
   {3,6,7,0,8,5,15,1,4,11,9,2,24,21,17,12,19,13,20,10,22,16,18,28,14,29,26,23,31,27,30,25},
   {3,8,6,7,0,5,2,1,15,4,9,11,19,24,17,12,21,13,20,16,10,28,14,18,22,29,31,26,23,27,25,30},
   {3,6,7,8,0,5,1,15,2,9,4,11,24,21,19,17,12,13,22,16,20,10,18,28,14,29,26,23,31,27,30,25},
   {0,7,3,8,6,5,1,2,15,4,9,11,24,21,17,12,19,13,20,22,28,10,16,18,14,29,31,26,23,27,30,25},
   {3,8,7,0,6,5,1,15,2,4,9,11,24,21,12,19,17,20,13,10,16,22,18,14,28,29,26,23,31,27,30,25},
   {0,3,7,8,6,5,1,15,2,4,9,24,11,21,12,19,17,13,22,20,10,16,18,28,14,29,26,31,23,27,30,25},
   {0,3,6,7,8,5,1,2,4,15,9,11,24,21,12,19,17,20,13,10,22,16,18,28,14,26,29,31,23,27,30,25}},
  {{4,3,4,3,0,3,1,1},{5,7,6,6,6,6,6,6},{9,9,7,8,8,8,7,7},{3,2,0,1,2,1,3,4},
   {8,8,9,9,9,9,8,8},{6,5,5,5,5,5,5,5},{1,1,2,0,4,4,4,0},{0,0,3,2,1,2,0,2},
   {2,4,1,4,3,0,2,3},{11,11,10,10,10,10,10,10},{1,7,9,11,11,12,12,11},{10,10,11,11,12,12,12,11},
   {14,16,5,6,4,5,5,5},{5,5,6,1,7,8,7,9},{10,10,10,13,13,5,6,5},{7,6,8,7,7,7,9,9},
   {7,6,8,9,9,11,11,7},{16,15,2,5,6,0,0,1},{2,9,11,12,12,4,4,0},{15,14,13,0,5,6,6,6},
   {6,1,0,7,0,7,9,8},{13,13,14,13,13,4,4,0},{0,0,7,8,8,9,8,12},{14,16,0,1,7,9,5,6},
   {12,12,12,12,11,11,11,12},{1,7,11,10,10,5,0,8},{11,11,2,6,6,7,9,9},{16,15,6,8,8,4,8,0},
   {3,8,12,10,10,10,5,6},{12,12,14,5,4,0,0,8},{5,5,7,12,12,10,4,5},{13,13,5,7,5,8,7,1}},
  {{255,255,255,255,255,255,255,255},{255,255,255,255,255,255,255,255},{255,255,255,255,255,255,255,255},{255,255,255,255,255,255,255,255},
   {255,255,255,255,255,255,255,255},{255,255,255,255,255,255,255,255},{255,255,255,255,255,255,255,255},{255,255,255,255,255,255,255,255},
   {255,255,255,255,255,255,255,255},{255,255,255,255,255,255,255,255},{6,1,4,11,24,11,11,11},{255,255,255,255,255,255,255,255},
   {255,255,5,1,6,5,5,5},{1,5,1,3,15,2,2,15},{11,11,9,21,21,12,19,12},{255,255,255,255,255,255,255,255},
   {15,15,15,4,4,24,24,2},{255,255,6,5,1,8,7,0},{8,2,11,24,11,21,21,21},{255,255,255,6,5,1,1,1},
   {5,6,3,15,0,15,15,4},{255,255,255,255,255,6,6,6},{7,7,2,2,2,4,4,24},{12,12,20,13,13,22,28,28},
   {255,255,255,255,255,255,255,255},{10,10,18,28,28,14,29,29},{9,9,17,12,17,20,20,13},{17,17,13,22,22,18,22,18},
   {3,4,24,9,9,9,12,19},{24,24,21,17,12,17,17,20},{13,13,22,18,18,28,18,14},{21,21,12,20,19,13,13,17}}};

typedef CUresult (*EncodeFn)(CUtensorMap*, CUtensorMapDataType, cuuint32_t, void*, const cuuint64_t*, const cuuint64_t*, const cuuint32_t*,
                             const cuuint32_t*, CUtensorMapInterleave, CUtensorMapSwizzle, CUtensorMapL2promotion, CUtensorMapFloatOOBfill);

void make_map2(EncodeFn enc, CUtensorMap* m, const void* ptr, int rows, int cols, int box_rows) {
  cuuint64_t dim[2] = {(cuuint64_t)cols, (cuuint64_t)rows}, str[1] = {(cuuint64_t)cols * 2};
  cuuint32_t box[2] = {64, (cuuint32_t)box_rows}, es[2] = {1, 1};
  enc(m, CU_TENSOR_MAP_DATA_TYPE_BFLOAT16, 2, const_cast<void*>(ptr), dim, str, box, es, CU_TENSOR_MAP_INTERLEAVE_NONE, CU_TENSOR_MAP_SWIZZLE_128B,
      CU_TENSOR_MAP_L2_PROMOTION_L2_128B, CU_TENSOR_MAP_FLOAT_OOB_FILL_NONE);
}
void make_map3(EncodeFn enc, CUtensorMap* m, const void* ptr, int rows) {
  cuuint64_t dim[3] = {64, (cuuint64_t)rows, 9}, str[2] = {DM * 2, 128};
  cuuint32_t box[3] = {64, 32, 3}, es[3] = {1, 1, 1};
  enc(m, CU_TENSOR_MAP_DATA_TYPE_BFLOAT16, 3, const_cast<void*>(ptr), dim, str, box, es, CU_TENSOR_MAP_INTERLEAVE_NONE, CU_TENSOR_MAP_SWIZZLE_128B,
      CU_TENSOR_MAP_L2_PROMOTION_L2_128B, CU_TENSOR_MAP_FLOAT_OOB_FILL_NONE);
}

void make_map_t(EncodeFn enc, CUtensorMap* m, void* ptr, int width, int cols) {
  cuuint64_t dim[3] = {TP / 2, 2, 864}, str[2] = {TP * 2, TP * 4};
  cuuint32_t box[3] = {(cuuint32_t)width, 2, (cuuint32_t)cols}, es[3] = {1, 1, 1};
  enc(m, CU_TENSOR_MAP_DATA_TYPE_UINT32, 3, ptr, dim, str, box, es, CU_TENSOR_MAP_INTERLEAVE_NONE, cols == 64 ? CU_TENSOR_MAP_SWIZZLE_128B : CU_TENSOR_MAP_SWIZZLE_NONE,
      CU_TENSOR_MAP_L2_PROMOTION_NONE, CU_TENSOR_MAP_FLOAT_OOB_FILL_NONE);
}

int g_mode = -1;

}

extern "C" void kernel_launch(void* const* d_in, const int* in_sizes, int n_in, void* d_out, int out_size) {
  static EncodeFn enc = nullptr;
  static void* t_ptr = nullptr;
  if (!enc) {
    void* fn = nullptr;
    cudaDriverEntryPointQueryResult st;
    cudaGetDriverEntryPoint("cuTensorMapEncodeTiled", &fn, cudaEnableDefault, &st);
    enc = (EncodeFn)fn;
    cudaGetSymbolAddress(&t_ptr, g_T);
    cudaFuncSetAttribute(fused_kernel, cudaFuncAttributeMaxDynamicSharedMemorySize, SMEM_BYTES);
    if (g_mode < 0) {
      cudaLaunchConfig_t cfg = {};
      cfg.gridDim = dim3(2 * NCL); cfg.blockDim = dim3(384); cfg.dynamicSmemBytes = SMEM_BYTES;
      cudaLaunchAttribute at; at.id = cudaLaunchAttributeClusterDimension;
      at.val.clusterDim.x = 2; at.val.clusterDim.y = 1; at.val.clusterDim.z = 1;
      cfg.attrs = &at; cfg.numAttrs = 1;
      int nc = 0;
      g_mode = (cudaOccupancyMaxActiveClusters(&nc, fused_kernel, &cfg) == cudaSuccess && nc >= NCL) ? 1 : 0;
      (void)cudaGetLastError();
    }
  }
  Params p;
  make_map2(enc, &p.map_a[0], d_in[4], SEQ, DC, 128);
  make_map2(enc, &p.map_a[1], d_in[0], SEQ, DM, 128);
  make_map2(enc, &p.map_w[0], d_in[6], DC, 4096, 64);
  make_map2(enc, &p.map_w[1], d_in[7], DC, 4096, 64);
  make_map2(enc, &p.map_w[2], d_in[5], DM, 4096, 64);
  make_map2(enc, &p.map_w[3], d_in[1], DM, 1728, 64);
  make_map3(enc, &p.map_o[0], d_in[8], 4096);
  make_map3(enc, &p.map_o[1], d_in[2], DM);
  make_map_t(enc, &p.map_t[0], t_ptr, 32, 9);
  make_map_t(enc, &p.map_t[1], t_ptr, 40, 9);
  make_map_t(enc, &p.map_t[2], t_ptr, 32, 64);
  p.x = (const __nv_bfloat16*)d_in[0];
  p.gate_w = (const __nv_bfloat16*)d_in[9];
  make_map2(enc, &p.map_out, d_out, SEQ, DM, 64);
  p.out = (__nv_bfloat16*)d_out;
  p.zero = 0;
  auto launch = [&](int phases) {
    p.s = k_sched;
    for (int i = 0; i < NCL; i++) {
      Rec& r = p.s.r[i];
      if (!(phases & 1)) r.n1 = 0;
      if (!(phases & 2)) r.n2 = 0;
      if (!(phases & (r.p3 < 24 ? 4 : 32))) r.p3 = 255;
      if (!(phases & 8)) r.bg = 255;
      const int u1 = r.n1 ? 8 + r.n1 * (8 + (r.slab >> 3)) : 0;
      int u2 = 0;
      for (int k = 0; k < r.n2; k++) u2 += 4 * (r.item[k] & 7) + 4;
      r.u1 = (uint8_t)u1; r.u2 = (uint8_t)u2;
      r.rot = (uint8_t)(((u1 % 10 + 1) >> 1) % 5);
      r.x3 = (uint8_t)((r.rot + u2) % 5 & 3);
      r.phases = (uint8_t)phases;
    }
    if (!(phases & 16))
      for (int i = 0; i < 256; i++) { p.s.slot[i >> 3][i & 7] = (uint8_t)(i >> 3); p.s.prev[i >> 3][i & 7] = 255; }
    fused_kernel<<<2 * NCL, 384, SMEM_BYTES>>>(p);
  };
  if (g_mode == 1) launch(63);
  else { launch(1); launch(10); launch(32); launch(4); }
}
```

```cpp
#include <cuda_runtime.h>
#include <cuda_bf16.h>
#include <cuda.h>
#include <stdint.h>

namespace {

constexpr int SEQ = 2048, DM = 576, DC = 512, NH = 32;
constexpr int NCL = 66;
constexpr uint32_t DESC_HI = 0x40000040u;

constexpr int SM_RING = 0;
constexpr int SM_BUF = 163840;
constexpr int SM_BAR = 229376;
constexpr int B_P1E = 0, B_P2E = 10, B_P3E = 15, B_P2F = 24, B_SF = 32, B_ORD = 36, B_LAD = 40, B_DONE = 41, B_FIN = 48;
constexpr int B_P3F = 56, B_OUT = 61, B_P1F = 64, B_SE = 74, B_QF = 80, B_LA = 84, B_NUM = 88;
constexpr uint64_t B_CNT = 0x11118245000ull;
constexpr int SMEM_BYTES = SM_BAR + B_NUM * 8 + 1024;

constexpr int F_QKVA = 32;
constexpr int F_GATE = 64;
constexpr int F_DONE = 65;
constexpr int F_CTX = 96;
constexpr int F_OUT = 96 + 8 * 64;
constexpr int F_KV = F_OUT + 64;
constexpr int F_Q = F_KV + 256;
constexpr int F_RD = F_Q + 256;
constexpr int F_NUM = F_RD + 256;

struct Rec {
  uint8_t slab;
  uint8_t n1, n2;
  uint8_t p3;
  uint8_t bg;
  uint8_t item[11];
  uint8_t last[11];
  uint8_t tile[32];
  uint8_t u1, u2;
  uint8_t rot, x3;
  uint8_t phases;
};
struct Sched {
  Rec r[NCL];
  uint8_t nh[24];
  uint8_t p3_order[8][32];
  uint8_t slot[32][8];
  uint8_t prev[32][8];
};

#define SCHED_DECL static const

struct Params {
  CUtensorMap map_a[2];
  CUtensorMap map_w[4];
  CUtensorMap map_o[2];
  CUtensorMap map_t[3];
  CUtensorMap map_out;
  const __nv_bfloat16* x;
  const __nv_bfloat16* gate_w;
  __nv_bfloat16* out;
  int zero;
  alignas(64) Sched s;
};

__device__ __align__(1024) uint8_t g_Q[NH * 32 * 16384];
__device__ __align__(1024) uint8_t g_KV[2 * NH * 16 * 32768];
__device__ __align__(1024) uint8_t g_oA[32 * 576 * 128];
constexpr int TP = SEQ + 16;
__device__ __align__(1024) uint32_t g_T[864 * TP];
__device__ float g_gate[SEQ];
__device__ int g_flags[F_NUM];

__device__ __forceinline__ void mbar_arrive(uint32_t b) { asm volatile("mbarrier.arrive.shared::cta.b64 _, [%0];" ::"r"(b) : "memory"); }
__device__ __forceinline__ void mbar_arrive_cl(uint32_t b, int cnt) {
  asm volatile("mbarrier.arrive.shared::cluster.b64 _, [%0], %1;" ::"r"(b), "r"(cnt) : "memory");
}
__device__ __forceinline__ void mbar_wait(uint32_t b, int par) {
  asm volatile(
      "{\n.reg .pred p;\n.reg .u32 c;\n"
      "mbarrier.try_wait.parity.shared::cta.b64 p, [%0], %1;\n@p bra DN;\nmov.u32 c, 0;\n"
      "LP:\nmbarrier.try_wait.parity.shared::cta.b64 p, [%0], %1;\n@p bra DN;\n"
      "add.u32 c, c, 1;\nsetp.lt.u32 p, c, 4000000;\n@p bra LP;\ntrap;\nDN:\n}" ::"r"(b), "r"(par) : "memory");
}
__device__ __forceinline__ uint32_t mapa(uint32_t a, uint32_t cta) {
  uint32_t r; asm("mapa.shared::cluster.u32 %0, %1, %2;" : "=r"(r) : "r"(a), "r"(cta)); return r;
}
#define ELECT(ins) "{\n.reg .pred e;\nelect.sync _|e, 0xffffffff;\n@e " ins "\n}"
__device__ __forceinline__ void mbar_expect(uint32_t b, int bytes) {
  asm volatile(ELECT("mbarrier.arrive.expect_tx.shared::cta.b64 _, [%0], %1;") ::"r"(b), "r"(bytes) : "memory");
}
__device__ __forceinline__ void mbar_arrive_one(uint32_t b) { asm volatile(ELECT("mbarrier.arrive.shared::cta.b64 _, [%0];") ::"r"(b) : "memory"); }
constexpr uint64_t L2_NORMAL = 0x1000000000000000ull, L2_FIRST = 0x12F0000000000000ull;
__device__ __forceinline__ void bulk_load(uint32_t dst, const void* src, int bytes, uint32_t bar, uint64_t pol = L2_NORMAL) {
  asm volatile(ELECT("cp.async.bulk.shared::cluster.global.mbarrier::complete_tx::bytes.L2::cache_hint [%0], [%1], %2, [%3], %4;") ::"r"(dst), "l"(src), "r"(bytes), "r"(bar), "l"(pol) : "memory");
}
__device__ __forceinline__ void bulk_load_mc(uint32_t dst, const void* src, int bytes, uint32_t bar, uint64_t pol = L2_NORMAL) {
  asm volatile(ELECT("cp.async.bulk.shared::cluster.global.mbarrier::complete_tx::bytes.multicast::cluster.L2::cache_hint [%0], [%1], %2, [%3], %4, %5;") ::"r"(dst), "l"(src), "r"(bytes), "r"(bar), "h"((uint16_t)3), "l"(pol) : "memory");
}
__device__ __forceinline__ void bulk_store(void* dst, uint32_t src, int bytes, uint64_t pol = L2_NORMAL) {
  asm volatile(ELECT("cp.async.bulk.global.shared::cta.bulk_group.L2::cache_hint [%0], [%1], %2, %3;") ::"l"(dst), "r"(src), "r"(bytes), "l"(pol) : "memory");
}
__device__ __forceinline__ void tma2d(uint32_t dst, const CUtensorMap* m, int c0, int c1, uint32_t bar, uint64_t pol = L2_NORMAL) {
  asm volatile(ELECT("cp.async.bulk.tensor.2d.shared::cluster.global.mbarrier::complete_tx::bytes.L2::cache_hint [%0], [%1, {%3, %4}], [%2], %5;") ::"r"(dst), "l"(m), "r"(bar), "r"(c0), "r"(c1), "l"(pol) : "memory");
}
__device__ __forceinline__ void tma2d_mc(uint32_t dst, const CUtensorMap* m, int c0, int c1, uint32_t bar, uint64_t pol = L2_NORMAL) {
  asm volatile(ELECT("cp.async.bulk.tensor.2d.shared::cluster.global.mbarrier::complete_tx::bytes.multicast::cluster.L2::cache_hint [%0], [%1, {%3, %4}], [%2], %5, %6;") ::"r"(dst), "l"(m), "r"(bar), "r"(c0), "r"(c1), "h"((uint16_t)3), "l"(pol) : "memory");
}
__device__ __forceinline__ void tma3d(uint32_t dst, const CUtensorMap* m, int c0, int c1, int c2, uint32_t bar, uint64_t pol = L2_NORMAL) {
  asm volatile(ELECT("cp.async.bulk.tensor.3d.shared::cluster.global.mbarrier::complete_tx::bytes.L2::cache_hint [%0], [%1, {%3, %4, %5}], [%2], %6;") ::"r"(dst), "l"(m), "r"(bar), "r"(c0), "r"(c1), "r"(c2), "l"(pol) : "memory");
}
__device__ __forceinline__ void tma3d_mc(uint32_t dst, const CUtensorMap* m, int c0, int c1, int c2, uint32_t bar, uint64_t pol = L2_NORMAL) {
  asm volatile(ELECT("cp.async.bulk.tensor.3d.shared::cluster.global.mbarrier::complete_tx::bytes.multicast::cluster.L2::cache_hint [%0], [%1, {%3, %4, %5}], [%2], %6, %7;") ::"r"(dst), "l"(m), "r"(bar), "r"(c0), "r"(c1), "r"(c2), "h"((uint16_t)3), "l"(pol) : "memory");
}
__device__ __forceinline__ void tma2d_add(const CUtensorMap* m, uint32_t src, int c0, int c1) {
  asm volatile(ELECT("cp.reduce.async.bulk.tensor.2d.global.shared::cta.add.bulk_group [%0, {%2, %3}], [%1];") ::"l"(m), "r"(src), "r"(c0), "r"(c1) : "memory");
}
__device__ __forceinline__ void tma3d_store(const CUtensorMap* m, uint32_t src, int c0, int c1, int c2, uint64_t pol = L2_NORMAL) {
  asm volatile(ELECT("cp.async.bulk.tensor.3d.global.shared::cta.bulk_group.L2::cache_hint [%0, {%2, %3, %4}], [%1], %5;") ::"l"(m), "r"(src), "r"(c0), "r"(c1), "r"(c2), "l"(pol) : "memory");
}
__device__ __forceinline__ void tma2d_prefetch(const CUtensorMap* m, int c0, int c1, uint64_t pol = L2_NORMAL) {
  asm volatile(ELECT("cp.async.bulk.prefetch.tensor.2d.L2.global.L2::cache_hint [%0, {%1, %2}], %3;") ::"l"(m), "r"(c0), "r"(c1), "l"(pol) : "memory");
}
#define LAG 3
#define HINT 62
#define POL(bit) ((HINT >> (bit)) & 1 ? L2_FIRST : L2_NORMAL)
#define BULK_COMMIT() asm volatile("cp.async.bulk.commit_group;" ::: "memory")
#define BULK_WAIT(n) asm volatile("cp.async.bulk.wait_group %0;" ::"n"(n) : "memory")
#define BULK_WAIT_READ(n) asm volatile("cp.async.bulk.wait_group.read %0;" ::"n"(n) : "memory")
#define FENCE_ASYNC_SMEM() asm volatile("fence.proxy.async.shared::cta;" ::: "memory")
#define FENCE_ASYNC_ALL() asm volatile("fence.proxy.async;" ::: "memory")
#define WG_FENCE() asm volatile("wgmma.fence.sync.aligned;" ::: "memory")
#define WG_COMMIT() asm volatile("wgmma.commit_group.sync.aligned;" ::: "memory")
#define WG_WAIT(n) asm volatile("wgmma.wait_group.sync.aligned %0;" ::"n"(n) : "memory")
__device__ __forceinline__ void bar_sync(int id, int n) { asm volatile("bar.sync %0, %1;" ::"r"(id), "r"(n) : "memory"); }
__device__ __forceinline__ void bar_arrive(int id, int n) { asm volatile("bar.arrive %0, %1;" ::"r"(id), "r"(n) : "memory"); }
__device__ __forceinline__ void cluster_sync() {
  asm volatile("barrier.cluster.arrive.relaxed;\nbarrier.cluster.wait.acquire;" ::: "memory");
}
template <int N> __device__ __forceinline__ void pin(float (&r)[N]) {
#pragma unroll
  for (int i = 0; i < N; i++) asm volatile("" : "+f"(r[i])::"memory");
}
template <int N> __device__ __forceinline__ void pin(uint32_t (&r)[N]) {
#pragma unroll
  for (int i = 0; i < N; i++) asm volatile("" : "+r"(r[i])::"memory");
}
__device__ __forceinline__ uint32_t pack_bf16(float lo, float hi) {
  uint32_t r; asm("cvt.rn.bf16x2.f32 %0, %1, %2;" : "=r"(r) : "f"(hi), "f"(lo)); return r;
}
__device__ __forceinline__ float ex2(float x) { float r; asm("ex2.approx.ftz.f32 %0, %1;" : "=f"(r) : "f"(x)); return r; }
__device__ __forceinline__ void ldsm4(uint32_t a, uint32_t& r0, uint32_t& r1, uint32_t& r2, uint32_t& r3) {
  asm volatile("ldmatrix.sync.aligned.m8n8.x4.shared.b16 {%0,%1,%2,%3}, [%4];" : "=r"(r0), "=r"(r1), "=r"(r2), "=r"(r3) : "r"(a) : "memory");
}
__device__ __forceinline__ void stsm4(uint32_t a, uint32_t r0, uint32_t r1, uint32_t r2, uint32_t r3) {
  asm volatile("stmatrix.sync.aligned.m8n8.x4.shared.b16 [%0], {%1,%2,%3,%4};" ::"r"(a), "r"(r0), "r"(r1), "r"(r2), "r"(r3) : "memory");
}
__device__ __forceinline__ void flag_add(int idx) {
  asm volatile(ELECT("red.release.gpu.global.add.s32 [%0], 1;") ::"l"(g_flags + idx) : "memory");
}
__device__ __forceinline__ void flag_add_rx(int idx) {
  asm volatile(ELECT("red.relaxed.gpu.global.add.s32 [%0], 1;") ::"l"(g_flags + idx) : "memory");
}
template <bool ACQ, int NS = 32> __device__ __forceinline__ void flag_wait(int idx, int target) {
  int n = 0;
  while (true) {
    int v;
    if (ACQ) asm volatile("ld.acquire.gpu.global.s32 %0, [%1];" : "=r"(v) : "l"(g_flags + idx) : "memory");
    else asm volatile("ld.relaxed.gpu.global.s32 %0, [%1];" : "=r"(v) : "l"(g_flags + idx) : "memory");
    if (__all_sync(0xffffffffu, v >= target)) break;
    if (++n > 20000000) __trap();
    __nanosleep(NS);
  }
}
__device__ __forceinline__ void mask_wait(uint32_t& ready, int bit, int idx, int target) {
  for (int n = 0; !((ready >> bit) & 1); n++) {
    int v;
    if (n) { __nanosleep(32); if (n > 20000000) __trap(); }
    asm volatile("ld.relaxed.gpu.global.s32 %0, [%1];" : "=r"(v) : "l"(g_flags + idx) : "memory");
    ready = __ballot_sync(0xffffffffu, v >= target);
  }
}
__device__ __forceinline__ uint32_t desc_lo(uint32_t addr, uint32_t lbo) { return ((addr & 0x3FFFFu) >> 4) | ((lbo >> 4) << 16); }
#define PROF(role, i)
#define PROFX(cond, i)
#define PROFB(i)
#define PROFG(i)

template <int TB, int TA = 0> __device__ __forceinline__ void wgmma_ss64(float (&d)[32], uint32_t alo, uint32_t blo, int sd) {
  asm volatile("{\n.reg .pred p;\n.reg .b64 da, db;\n"
    "setp.ne.b32 p, %34, 0;\nmov.b64 da, {%32, %36};\nmov.b64 db, {%33, %36};\n"
    "wgmma.mma_async.sync.aligned.m64n64k16.f32.bf16.bf16 "
    "{%0,%1,%2,%3,%4,%5,%6,%7,%8,%9,%10,%11,%12,%13,%14,%15,%16,%17,%18,%19,%20,%21,%22,%23,"
    "%24,%25,%26,%27,%28,%29,%30,%31}, "
    "da, db, p, 1, 1, %37, %35;\n}\n"
    : "+f"(d[0]),"+f"(d[1]),"+f"(d[2]),"+f"(d[3]),"+f"(d[4]),"+f"(d[5]),"+f"(d[6]),"+f"(d[7]),"+f"(d[8]),"+f"(d[9]),"+f"(d[10]),"+f"(d[11]),
      "+f"(d[12]),"+f"(d[13]),"+f"(d[14]),"+f"(d[15]),"+f"(d[16]),"+f"(d[17]),"+f"(d[18]),"+f"(d[19]),"+f"(d[20]),"+f"(d[21]),"+f"(d[22]),"+f"(d[23]),
      "+f"(d[24]),"+f"(d[25]),"+f"(d[26]),"+f"(d[27]),"+f"(d[28]),"+f"(d[29]),"+f"(d[30]),"+f"(d[31])
    : "r"(alo), "r"(blo), "r"(sd), "n"(TB), "r"(DESC_HI), "n"(TA));
}
template <int TB, int TA = 0> __device__ __forceinline__ void wgmma_ss128(float (&d)[64], uint32_t alo, uint32_t blo, int sd) {
  asm volatile("{\n.reg .pred p;\n.reg .b64 da, db;\n"
    "setp.ne.b32 p, %66, 0;\nmov.b64 da, {%64, %68};\nmov.b64 db, {%65, %68};\n"
    "wgmma.mma_async.sync.aligned.m64n128k16.f32.bf16.bf16 "
    "{%0,%1,%2,%3,%4,%5,%6,%7,%8,%9,%10,%11,%12,%13,%14,%15,%16,%17,%18,%19,%20,%21,%22,%23,"
    "%24,%25,%26,%27,%28,%29,%30,%31,%32,%33,%34,%35,%36,%37,%38,%39,%40,%41,%42,%43,%44,%45,%46,%47,"
    "%48,%49,%50,%51,%52,%53,%54,%55,%56,%57,%58,%59,%60,%61,%62,%63}, "
    "da, db, p, 1, 1, %69, %67;\n}\n"
    : "+f"(d[0]),"+f"(d[1]),"+f"(d[2]),"+f"(d[3]),"+f"(d[4]),"+f"(d[5]),"+f"(d[6]),"+f"(d[7]),"+f"(d[8]),"+f"(d[9]),"+f"(d[10]),"+f"(d[11]),
      "+f"(d[12]),"+f"(d[13]),"+f"(d[14]),"+f"(d[15]),"+f"(d[16]),"+f"(d[17]),"+f"(d[18]),"+f"(d[19]),"+f"(d[20]),"+f"(d[21]),"+f"(d[22]),"+f"(d[23]),
      "+f"(d[24]),"+f"(d[25]),"+f"(d[26]),"+f"(d[27]),"+f"(d[28]),"+f"(d[29]),"+f"(d[30]),"+f"(d[31]),"+f"(d[32]),"+f"(d[33]),"+f"(d[34]),"+f"(d[35]),
      "+f"(d[36]),"+f"(d[37]),"+f"(d[38]),"+f"(d[39]),"+f"(d[40]),"+f"(d[41]),"+f"(d[42]),"+f"(d[43]),"+f"(d[44]),"+f"(d[45]),"+f"(d[46]),"+f"(d[47]),
      "+f"(d[48]),"+f"(d[49]),"+f"(d[50]),"+f"(d[51]),"+f"(d[52]),"+f"(d[53]),"+f"(d[54]),"+f"(d[55]),"+f"(d[56]),"+f"(d[57]),"+f"(d[58]),"+f"(d[59]),
      "+f"(d[60]),"+f"(d[61]),"+f"(d[62]),"+f"(d[63])
    : "r"(alo), "r"(blo), "r"(sd), "n"(TB), "r"(DESC_HI), "n"(TA));
}
template <int TB> __device__ __forceinline__ void wgmma_rs128(float (&d)[64], uint32_t a0, uint32_t a1, uint32_t a2, uint32_t a3, uint32_t blo, int sd) {
  asm volatile("{\n.reg .pred p;\n.reg .b64 db;\n"
    "setp.ne.b32 p, %69, 0;\nmov.b64 db, {%68, %71};\n"
    "wgmma.mma_async.sync.aligned.m64n128k16.f32.bf16.bf16 "
    "{%0,%1,%2,%3,%4,%5,%6,%7,%8,%9,%10,%11,%12,%13,%14,%15,%16,%17,%18,%19,%20,%21,%22,%23,"
    "%24,%25,%26,%27,%28,%29,%30,%31,%32,%33,%34,%35,%36,%37,%38,%39,%40,%41,%42,%43,%44,%45,%46,%47,"
    "%48,%49,%50,%51,%52,%53,%54,%55,%56,%57,%58,%59,%60,%61,%62,%63}, "
    "{%64,%65,%66,%67}, db, p, 1, 1, %70;\n}\n"
    : "+f"(d[0]),"+f"(d[1]),"+f"(d[2]),"+f"(d[3]),"+f"(d[4]),"+f"(d[5]),"+f"(d[6]),"+f"(d[7]),"+f"(d[8]),"+f"(d[9]),"+f"(d[10]),"+f"(d[11]),
      "+f"(d[12]),"+f"(d[13]),"+f"(d[14]),"+f"(d[15]),"+f"(d[16]),"+f"(d[17]),"+f"(d[18]),"+f"(d[19]),"+f"(d[20]),"+f"(d[21]),"+f"(d[22]),"+f"(d[23]),
      "+f"(d[24]),"+f"(d[25]),"+f"(d[26]),"+f"(d[27]),"+f"(d[28]),"+f"(d[29]),"+f"(d[30]),"+f"(d[31]),"+f"(d[32]),"+f"(d[33]),"+f"(d[34]),"+f"(d[35]),
      "+f"(d[36]),"+f"(d[37]),"+f"(d[38]),"+f"(d[39]),"+f"(d[40]),"+f"(d[41]),"+f"(d[42]),"+f"(d[43]),"+f"(d[44]),"+f"(d[45]),"+f"(d[46]),"+f"(d[47]),
      "+f"(d[48]),"+f"(d[49]),"+f"(d[50]),"+f"(d[51]),"+f"(d[52]),"+f"(d[53]),"+f"(d[54]),"+f"(d[55]),"+f"(d[56]),"+f"(d[57]),"+f"(d[58]),"+f"(d[59]),
      "+f"(d[60]),"+f"(d[61]),"+f"(d[62]),"+f"(d[63])
    : "r"(a0), "r"(a1), "r"(a2), "r"(a3), "r"(blo), "r"(sd), "n"(TB), "r"(DESC_HI));
}
template <int TB, int TA = 0> __device__ __forceinline__ void wgmma_ss192(float (&d)[96], uint32_t alo, uint32_t blo, int sd) {
  asm volatile("{\n.reg .pred p;\n.reg .b64 da, db;\n"
    "setp.ne.b32 p, %98, 0;\nmov.b64 da, {%96, %100};\nmov.b64 db, {%97, %100};\n"
    "wgmma.mma_async.sync.aligned.m64n192k16.f32.bf16.bf16 "
    "{%0,%1,%2,%3,%4,%5,%6,%7,%8,%9,%10,%11,%12,%13,%14,%15,%16,%17,%18,%19,%20,%21,%22,%23,"
    "%24,%25,%26,%27,%28,%29,%30,%31,%32,%33,%34,%35,%36,%37,%38,%39,%40,%41,%42,%43,%44,%45,%46,%47,"
    "%48,%49,%50,%51,%52,%53,%54,%55,%56,%57,%58,%59,%60,%61,%62,%63,%64,%65,%66,%67,%68,%69,%70,%71,"
    "%72,%73,%74,%75,%76,%77,%78,%79,%80,%81,%82,%83,%84,%85,%86,%87,%88,%89,%90,%91,%92,%93,%94,%95}, "
    "da, db, p, 1, 1, %101, %99;\n}\n"
    : "+f"(d[0]),"+f"(d[1]),"+f"(d[2]),"+f"(d[3]),"+f"(d[4]),"+f"(d[5]),"+f"(d[6]),"+f"(d[7]),"+f"(d[8]),"+f"(d[9]),"+f"(d[10]),"+f"(d[11]),
      "+f"(d[12]),"+f"(d[13]),"+f"(d[14]),"+f"(d[15]),"+f"(d[16]),"+f"(d[17]),"+f"(d[18]),"+f"(d[19]),"+f"(d[20]),"+f"(d[21]),"+f"(d[22]),"+f"(d[23]),
      "+f"(d[24]),"+f"(d[25]),"+f"(d[26]),"+f"(d[27]),"+f"(d[28]),"+f"(d[29]),"+f"(d[30]),"+f"(d[31]),"+f"(d[32]),"+f"(d[33]),"+f"(d[34]),"+f"(d[35]),
      "+f"(d[36]),"+f"(d[37]),"+f"(d[38]),"+f"(d[39]),"+f"(d[40]),"+f"(d[41]),"+f"(d[42]),"+f"(d[43]),"+f"(d[44]),"+f"(d[45]),"+f"(d[46]),"+f"(d[47]),
      "+f"(d[48]),"+f"(d[49]),"+f"(d[50]),"+f"(d[51]),"+f"(d[52]),"+f"(d[53]),"+f"(d[54]),"+f"(d[55]),"+f"(d[56]),"+f"(d[57]),"+f"(d[58]),"+f"(d[59]),
      "+f"(d[60]),"+f"(d[61]),"+f"(d[62]),"+f"(d[63]),"+f"(d[64]),"+f"(d[65]),"+f"(d[66]),"+f"(d[67]),"+f"(d[68]),"+f"(d[69]),"+f"(d[70]),"+f"(d[71]),
      "+f"(d[72]),"+f"(d[73]),"+f"(d[74]),"+f"(d[75]),"+f"(d[76]),"+f"(d[77]),"+f"(d[78]),"+f"(d[79]),"+f"(d[80]),"+f"(d[81]),"+f"(d[82]),"+f"(d[83]),
      "+f"(d[84]),"+f"(d[85]),"+f"(d[86]),"+f"(d[87]),"+f"(d[88]),"+f"(d[89]),"+f"(d[90]),"+f"(d[91]),"+f"(d[92]),"+f"(d[93]),"+f"(d[94]),"+f"(d[95])
    : "r"(alo), "r"(blo), "r"(sd), "n"(TB), "r"(DESC_HI), "n"(TA));
}

struct Ctx {
  uint32_t sm;
  uint32_t bar;
  uint32_t rbar;
  int cl, rank, wg, warp, lane, phases;
};
__device__ __forceinline__ void release(const Ctx& c, int b, int cnt = 1) {
  if (c.lane < 2) mbar_arrive_cl(c.rbar + b * 8, cnt);
}
#define PFM 7
#define PF1 1
constexpr float SM_SCALE = 0.08838834764831845f * 1.4426950408889634f;
constexpr float SM_HI = 1.8446744e19f, SM_LO = 5.4210109e-20f;
constexpr int ORDER = 1;

__device__ __forceinline__ void stage_tile(const float (&a)[64], uint32_t buf, const Ctx& c, float s0, float s1) {
  const int row = (c.lane & 7) + ((c.lane >> 3) & 1) * 8;
  const uint32_t base = buf + (c.warp * 16 + row) * 128 + (((c.lane >> 4) ^ (row & 7)) << 4);
#pragma unroll
  for (int i = 0; i < 8; i++)
    stsm4((base ^ ((i & 3) << 5)) + (i >> 2) * 8192, pack_bf16(a[8 * i] * s0, a[8 * i + 1] * s0), pack_bf16(a[8 * i + 2] * s1, a[8 * i + 3] * s1),
          pack_bf16(a[8 * i + 4] * s0, a[8 * i + 5] * s0), pack_bf16(a[8 * i + 6] * s1, a[8 * i + 7] * s1));
}

__device__ __forceinline__ void p1_epilogue(const Params& p, const Ctx& c, const float (&acc)[64], int t, int type) {
  const int tile = p.s.r[c.cl].tile[t] & 63, b = c.wg * 2 + 1;
  mbar_wait(c.bar + (B_SE + b) * 8, (t & 1) ^ 1);
  if (type && tile >= 32) {
    const int r = 2 * (c.lane & 3) + ((c.lane >> 2) & 1);
    const uint32_t dst = c.sm + SM_BUF + b * 16384 + r * 128 + (((c.warp * 2) ^ r) << 4) + (c.lane >> 3) * 4;
#pragma unroll
    for (int i = 0; i < 16; i++) {
      asm volatile("st.shared.u32 [%0], %1;" ::"r"(dst + i * 1024), "r"(pack_bf16(acc[4 * i], acc[4 * i + 1])) : "memory");
      asm volatile("st.shared.u32 [%0], %1;" ::"r"((dst ^ 16) + i * 1024), "r"(pack_bf16(acc[4 * i + 2], acc[4 * i + 3])) : "memory");
    }
  } else {
    if (type) stage_tile(acc, c.sm + SM_BUF + b * 16384, c, SM_SCALE, SM_SCALE);
    else stage_tile(acc, c.sm + SM_BUF + b * 16384, c, 1.f, 1.f);
  }
  FENCE_ASYNC_SMEM();
  __syncwarp();
  if (c.lane == 0) mbar_arrive(c.bar + (B_SF + b) * 8);
}

__device__ __forceinline__ void p1_consumer(const Params& p, const Ctx& c) {
  const int n = p.s.r[c.cl].n1;
  const int type = p.s.r[c.cl].slab >> 3;
  const uint32_t bdesc = desc_lo(c.sm + SM_RING, 8192), adesc = desc_lo(c.sm + SM_BUF + 32768 + c.wg * 8192, 16);
  uint32_t A[128];
  float acc[64] = {};
  int slot = 0, par = 0;
  auto next = [&]() { if (++slot == 10) { slot = 0; par ^= 1; } };
  {
    const int row = (c.lane & 7) + ((c.lane >> 3) & 1) * 8;
    const uint32_t base = c.sm + SM_RING + (c.wg * 64 + c.warp * 16 + row) * 128 + (((c.lane >> 4) ^ (row & 7)) << 4);
    if (c.wg == 1) bar_sync(ORDER + 1, 256);
    int pa = -1, pb = -1;
    if (type) {
      mbar_wait(c.bar + B_P1F * 8, 0);
      WG_FENCE();
#pragma unroll
      for (int kk = 0; kk < 4; kk++) wgmma_ss128<1>(acc, adesc + kk * 2, bdesc + kk * 128, kk != 0);
      WG_COMMIT();
      pb = 0; slot = 1;
    }
#pragma unroll
    for (int kb = 0; kb < 8; kb++) {
      const int sa = slot;
      mbar_wait(c.bar + (B_P1F + slot) * 8, par);
      if (kb == 0) PROF(c.wg, 5);
      next();
      mbar_wait(c.bar + (B_P1F + slot) * 8, par);
      PROF(c.wg, 6 + 2 * kb);
      WG_FENCE();
#pragma unroll
      for (int kk = 0; kk < 4; kk++)
        wgmma_ss128<1>(acc, desc_lo(c.sm + SM_RING + c.wg * 8192, 16) + sa * 1024 + kk * 2, bdesc + slot * 1024 + kk * 128, (kb | kk) != 0 ? 1 : type);
      WG_COMMIT();
      if (kb == 1 && c.wg == 0) bar_arrive(ORDER + 1, 256);
#pragma unroll
      for (int kk = 0; kk < 4; kk++) ldsm4((base ^ (kk << 5)) + sa * 16384, A[kb * 16 + kk * 4], A[kb * 16 + kk * 4 + 1], A[kb * 16 + kk * 4 + 2], A[kb * 16 + kk * 4 + 3]);
      WG_WAIT(1);
      if (kb > 0) release(c, B_P1E + pa);
      if (kb > 0 || pb >= 0) release(c, B_P1E + pb);
      pa = sa; pb = slot;
      next();
    }
    WG_WAIT(0);
    __syncwarp();
    release(c, B_P1E + pa);
    release(c, B_P1E + pb);
    pin(acc);
    PROF(c.wg, 1);
    p1_epilogue(p, c, acc, 0, type);
    PROF(c.wg, 2);
  }
  for (int t = 1; t < n; t++) {
    bar_sync(ORDER + c.wg, 256);
    int prev1 = -1, prev2 = -1;
    if (type) {
      mbar_wait(c.bar + (B_P1F + slot) * 8, par);
      WG_FENCE();
#pragma unroll
      for (int kk = 0; kk < 4; kk++) wgmma_ss128<1>(acc, adesc + kk * 2, bdesc + slot * 1024 + kk * 128, kk != 0);
      WG_COMMIT();
      prev1 = slot;
      next();
    }
#pragma unroll
    for (int kb = 0; kb < 8; kb++) {
      mbar_wait(c.bar + (B_P1F + slot) * 8, par);
      WG_FENCE();
      const uint32_t d = bdesc + slot * 1024;
#pragma unroll
      for (int kk = 0; kk < 4; kk++)
        wgmma_rs128<1>(acc, A[kb * 16 + kk * 4], A[kb * 16 + kk * 4 + 1], A[kb * 16 + kk * 4 + 2], A[kb * 16 + kk * 4 + 3], d + kk * 128, (kb | kk) != 0 ? 1 : type);
      WG_COMMIT();
      if (kb == 7) {
        if (t + 1 < n || c.wg == 0) bar_arrive(ORDER + (c.wg ^ 1), 256);
      }
      if (kb > 0) { WG_WAIT(2); if (kb > 1 || prev2 >= 0) release(c, B_P1E + prev2); }
      prev2 = prev1; prev1 = slot;
      next();
    }
    WG_WAIT(1);
    release(c, B_P1E + prev2);
    WG_WAIT(0);
    pin(acc);
    release(c, B_P1E + prev1);
    p1_epilogue(p, c, acc, t, type);
    PROF(c.wg, 3);
  }
}

__device__ __forceinline__ void p1_producer(const Params& p, const Ctx& c) {
  const int n = p.s.r[c.cl].n1;
  const int type = p.s.r[c.cl].slab >> 3, grp = p.s.r[c.cl].slab & 7;
  int slot = 2 - type, par = 1;
#pragma unroll 1
  for (int t = 0; t < n; t++) {
    const int tile = p.s.r[c.cl].tile[t] & 63;
    const CUtensorMap* m = &p.map_w[type * 2 + (tile >> 5)];
    const int n0 = (tile & 31) * 128 + c.rank * 64;
    const int ptile = p.s.r[c.cl].tile[t + PF1 < n ? t + PF1 : t];
    const CUtensorMap* pm = &p.map_w[type * 2 + ((ptile >> 5) & 1)];
    if (t == 7 && (c.phases & 16)) flag_wait<true>(F_GATE, 256);
#pragma unroll 1
    for (int kb = (t == 0) - type; kb < 8; kb++) {
      if (t == 0) {
        mbar_wait(c.bar + (B_P1E + slot) * 8, par);
        mbar_expect(c.bar + (B_P1F + slot) * 8, 16384);
        tma2d(c.sm + SM_RING + slot * 16384, &p.map_a[type], kb * 64, grp * 256 + c.rank * 128, c.bar + (B_P1F + slot) * 8);
        if (++slot == 10) { slot = 0; par ^= 1; }
      }
      mbar_wait(c.bar + (B_P1E + slot) * 8, par);
      mbar_expect(c.bar + (B_P1F + slot) * 8, 16384);
      tma2d_mc(c.sm + SM_RING + slot * 16384 + c.rank * 8192, m, n0, kb < 0 ? 512 : kb * 64, c.bar + (B_P1F + slot) * 8);
      if (t == 0 && kb == 1) PROF(2, 61);
      if (t == 0 && kb == 3) PROF(2, 62);
      if (t + PF1 < n && t > 0 && ((ptile & 64) || ((ptile & 128) && ((kb ^ grp) & PFM) == 0))) tma2d_prefetch(pm, (ptile & 31) * 128 + c.rank * 64, kb < 0 ? 512 : kb * 64);
      if (++slot == 10) { slot = 0; par ^= 1; }
    }
  }
}

__device__ __forceinline__ void p1_storer(const Params& p, const Ctx& c) {
  const int n = p.s.r[c.cl].n1;
  const int type = p.s.r[c.cl].slab >> 3, grp = p.s.r[c.cl].slab & 7;
  for (int i = 0; i < 2 * n; i++) {
    const int t = i >> 1, w = i & 1, b = w * 2 + 1;
    const int tile = p.s.r[c.cl].tile[t] & 63;
    mbar_wait(c.bar + (B_SF + b) * 8, t & 1);
    const uint32_t src = c.sm + SM_BUF + b * 16384;
    int f = (type ? F_Q : F_KV) + (tile & 31) * 8 + grp;
    if (type == 0) {
      const int prev = p.s.prev[tile & 31][grp];
      if (prev != 255 && w == 0) {
        if (grp >= 2) flag_wait<false>(F_RD + prev * 8 + grp, 8 - grp);
        else flag_wait<false>(F_CTX + max(c.lane & 7, grp) * 64 + prev, 4);
      }
      uint8_t* dst = g_KV + (size_t)(((tile & 32) + p.s.slot[tile & 31][grp]) * 16 + grp * 2 + c.rank) * 32768 + w * 8192;
      bulk_store(dst, src, 8192);
      bulk_store(dst + 16384, src + 8192, 8192);
    } else if (tile < 32) {
      bulk_store(g_Q + (size_t)(tile * 32 + grp * 4 + c.rank * 2 + w) * 16384, src, 16384);
    } else {
      tma3d_store(&p.map_t[2], src, 8 + (grp * 4 + c.rank * 2 + w) * 32, 0, (tile - 32) * 64);
      f = F_QKVA + grp * 4 + ((0xE4390900u >> (2 * (tile - 30))) & 3);
    }
    BULK_COMMIT();
    BULK_WAIT(0);
    mbar_arrive_one(c.bar + (B_SE + b) * 8);
    flag_add_rx(f);
  }
}

__device__ __forceinline__ int p2_buf(int w, int i) { return w * 2 + (i & 1); }
__device__ __forceinline__ int p2_blk(int rank, int w, int i) { return ((i ^ w) & 1) == 0 ? 3 - rank : rank; }

template <int N>
__device__ __forceinline__ void row_max(const float (&s)[N], float& m0, float& m1) {
  float a0 = fmaxf(s[0], s[1]), a1 = fmaxf(s[2], s[3]);
#pragma unroll
  for (int i = 1; i < N / 4; i++) {
    m0 = fmaxf(m0, s[4 * i]); a0 = fmaxf(a0, s[4 * i + 1]);
    m1 = fmaxf(m1, s[4 * i + 2]); a1 = fmaxf(a1, s[4 * i + 3]);
  }
  m0 = fmaxf(m0, a0); m1 = fmaxf(m1, a1);
  m0 = fmaxf(m0, __shfl_xor_sync(0xffffffffu, m0, 1));
  m1 = fmaxf(m1, __shfl_xor_sync(0xffffffffu, m1, 1));
  m0 = fmaxf(m0, __shfl_xor_sync(0xffffffffu, m0, 2));
  m1 = fmaxf(m1, __shfl_xor_sync(0xffffffffu, m1, 2));
}
template <bool SUB, int N>
__device__ __forceinline__ void row_exp(const float (&s)[N], uint32_t (&P)[32], float m0, float m1, float& t0, float& t1) {
  float u0 = 0.f, u1 = 0.f;
  t0 = t1 = 0.f;
#pragma unroll
  for (int i = 0; i < N / 4; i++) {
    const float e0 = ex2(SUB ? s[4 * i] - m0 : s[4 * i]), e1 = ex2(SUB ? s[4 * i + 1] - m0 : s[4 * i + 1]);
    const float e2 = ex2(SUB ? s[4 * i + 2] - m1 : s[4 * i + 2]), e3 = ex2(SUB ? s[4 * i + 3] - m1 : s[4 * i + 3]);
    if (i == 0) { t0 = e0; u0 = e1; t1 = e2; u1 = e3; }
    else { t0 += e0; u0 += e1; t1 += e2; u1 += e3; }
    P[2 * i] = pack_bf16(e0, e1);
    P[2 * i + 1] = pack_bf16(e2, e3);
  }
#pragma unroll
  for (int i = N / 2; i < 32; i++) P[i] = 0;
  pin(P);
  t0 += u0; t1 += u1;
}
template <int N>
__device__ __forceinline__ void causal_mask(float (&s)[N], int thr) {
#pragma unroll
  for (int i = 0; i < 8; i++) {
    if (8 * i > thr) s[N - 32 + 4 * i] = -INFINITY;
    if (8 * i + 1 > thr) s[N - 32 + 4 * i + 1] = -INFINITY;
    if (8 * i - 8 > thr) s[N - 32 + 4 * i + 2] = -INFINITY;
    if (8 * i - 7 > thr) s[N - 32 + 4 * i + 3] = -INFINITY;
  }
}
__device__ __forceinline__ void issue_qk(float (&s)[32], uint32_t qd, uint32_t kd) {
  WG_FENCE();
#pragma unroll
  for (int kk = 0; kk < 8; kk++) wgmma_ss64<0>(s, qd + (kk >> 2) * 512 + (kk & 3) * 2, kd + (kk >> 2) * 1024 + (kk & 3) * 2, kk != 0);
  WG_COMMIT();
}
__device__ __forceinline__ void issue_qk(float (&s)[64], uint32_t qd, uint32_t kd) {
  WG_FENCE();
#pragma unroll
  for (int kk = 0; kk < 8; kk++) wgmma_ss128<0>(s, qd + (kk >> 2) * 512 + (kk & 3) * 2, kd + (kk >> 2) * 1024 + (kk & 3) * 2, kk != 0);
  WG_COMMIT();
}
template <int NK>
__device__ __forceinline__ void issue_pv(float (&o)[64], const uint32_t (&P)[32], uint32_t vd, int acc) {
  WG_FENCE();
#pragma unroll
  for (int kk = 0; kk < NK; kk++) wgmma_rs128<1>(o, P[4 * kk], P[4 * kk + 1], P[4 * kk + 2], P[4 * kk + 3], vd + kk * 128, kk != 0 ? 1 : acc);
  WG_COMMIT();
}
__device__ __forceinline__ void stage_done(const Ctx& c, int b) {
  FENCE_ASYNC_SMEM();
  __syncwarp();
  if (c.lane == 0) mbar_arrive(c.bar + (B_SF + b) * 8);
}
__device__ __forceinline__ void p2_epilogue(const float (&o)[64], float s0, float s1, const Ctx& c, int b) {
  stage_tile(o, c.sm + SM_BUF + b * 16384, c, s0, s1);
  stage_done(c, b);
}

struct P2State {
  float m0, m1, l0, l1;
  bool shift;
  float e0, e1;
  int ks;
  int wi, ai;
  uint32_t wb, ab;
  uint32_t qd;
};
#define PROFZ()
__device__ __forceinline__ int wrap5(int q) { return q >= 5 ? q - 5 : q; }
__device__ __forceinline__ void turn_wait(uint32_t ring, int i) { mbar_wait(ring + (i & 3) * 8, (i >> 2) & 1); }
__device__ __forceinline__ void turn_pass(const Ctx& c, uint32_t ring, int i) { if (c.lane == 0) mbar_arrive(ring + (i & 3) * 8); }
__device__ __forceinline__ void p2_scales(P2State& z) {
  float l0 = z.l0, l1 = z.l1;
  l0 += __shfl_xor_sync(0xffffffffu, l0, 1);
  l1 += __shfl_xor_sync(0xffffffffu, l1, 1);
  l0 += __shfl_xor_sync(0xffffffffu, l0, 2);
  l1 += __shfl_xor_sync(0xffffffffu, l1, 2);
  asm("rcp.approx.ftz.f32 %0, %1;" : "=f"(z.e0) : "f"(l0));
  asm("rcp.approx.ftz.f32 %0, %1;" : "=f"(z.e1) : "f"(l1));
}
template <int N>
__device__ __forceinline__ void p2_first(const Ctx& c, P2State& z, float (&o)[64], uint32_t (&Pc)[32], uint32_t (&Pn)[32],
                                         int ks, int vs, int cnt, int acc) {
  float s[N] = {};
  issue_qk(s, z.qd, desc_lo(c.sm + SM_RING, 16) + ks * 2048);
  if (vs >= 0) {
    p2_scales(z);
    issue_pv<8>(o, Pc, desc_lo(c.sm + SM_RING, 16384) + vs * 2048, acc);
  } else {
    WG_COMMIT();
  }
  mbar_expect(z.ab + (z.ai++ & 3) * 8, cnt == 1 ? 8192 : 0);
  PROFZ();
  WG_WAIT(1);
  PROFZ();
  pin(s);
  release(c, B_P2E + ks, cnt);
  causal_mask(s, c.warp * 16 + (c.lane >> 2) - 2 * (c.lane & 3));
  z.m0 = z.m1 = 0.f;
  row_exp<false>(s, Pn, 0.f, 0.f, z.l0, z.l1);
  z.shift = __any_sync(0xffffffffu, !(z.l0 + z.l1 <= SM_HI) || ((c.lane & 3) == 0 && !(fminf(z.l0, z.l1) >= SM_LO)));
  if (__builtin_expect(z.shift, 0)) {
    z.m0 = z.m1 = -INFINITY;
    row_max(s, z.m0, z.m1);
    row_exp<true>(s, Pn, z.m0, z.m1, z.l0, z.l1);
  }
  WG_WAIT(0);
  pin(o);
  if (vs >= 0) release(c, B_P2E + vs, 1);
}

template <bool SECOND>
__device__ __forceinline__ void p2_turn(const Ctx& c, P2State& z, float (&o)[64], uint32_t (&Pc)[32], uint32_t (&Pn)[32],
                                        int eb = -1, bool half = false, int vcnt = 1) {
  float s[64] = {};
  const int ks = z.ks, vs = wrap5(ks + 1);
  PROFZ();
  turn_wait(z.wb, z.wi++);
  PROFZ();
  issue_qk(s, z.qd, desc_lo(c.sm + SM_RING, 16) + ks * 2048);
  const uint32_t vd = desc_lo(c.sm + SM_RING, 16384) + vs * 2048;
  if (SECOND) {
    if (eb >= 0) stage_tile(o, c.sm + SM_BUF + eb * 16384, c, z.e0, z.e1);
    if (half) issue_pv<4>(o, Pc, vd, 0); else issue_pv<8>(o, Pc, vd, 0);
  } else {
    issue_pv<8>(o, Pc, vd, 1);
  }
  turn_pass(c, z.ab, z.ai++);
  if (SECOND) { if (eb >= 0) stage_done(c, eb); }
  PROFZ();
  z.ks = wrap5(ks + 2);
  WG_WAIT(1);
  PROFZ();
  pin(s);
  release(c, B_P2E + ks, 1);
  float t0, t1, a0 = 1.f, a1 = 1.f;
  row_exp<false>(s, Pn, 0.f, 0.f, t0, t1);
  z.shift = __any_sync(0xffffffffu, z.shift || !(t0 + t1 <= SM_HI));
  const bool redo = z.shift;
  if (__builtin_expect(redo, 0)) {
    float n0 = z.m0, n1 = z.m1;
    row_max(s, n0, n1);
    a0 = ex2(z.m0 - n0); a1 = ex2(z.m1 - n1);
    z.m0 = n0; z.m1 = n1;
    z.l0 *= a0; z.l1 *= a1;
    row_exp<true>(s, Pn, z.m0, z.m1, t0, t1);
  }
  WG_WAIT(0);
  pin(o);
  release(c, B_P2E + vs, vcnt);
  if (__builtin_expect(redo, 0)) {
#pragma unroll
    for (int i = 0; i < 16; i++) { o[4 * i] *= a0; o[4 * i + 1] *= a0; o[4 * i + 2] *= a1; o[4 * i + 3] *= a1; }
  }
  z.l0 += t0; z.l1 += t1;
}
__device__ __forceinline__ void copy_p(uint32_t (&d)[32], const uint32_t (&s)[32], int zero) {
#pragma unroll
  for (int i = 0; i < 32; i++) asm volatile("add.s32 %0, %1, %2;" : "=r"(d[i]) : "r"(s[i]), "r"(zero));
}

__device__ __forceinline__ void p2_consumer(const Params& p, const Ctx& c, int rot) {
  const int nit = p.s.r[c.cl].n2;
  const uint32_t fring = c.bar + B_P2F * 8, oring = c.bar + B_ORD * 8;
  float o[64] = {};
  uint32_t Pa[32] = {}, Pb[32] = {};
  P2State z;
  z.e0 = z.e1 = z.l0 = z.l1 = 0.f; z.ks = rot; z.shift = false;
  int acc = 0, n = 0;
  for (int it = 0; it < nit; it++) {
    const int j = p.s.r[c.cl].item[it] & 7, blk = p2_blk(c.rank, c.wg, it);
    const int lng = ((it ^ c.wg) & 1) ^ 1;
    z.qd = desc_lo(c.sm + SM_BUF, 16) + p2_buf(c.wg, it) * 1024;
    if (lng) { z.wb = oring; z.wi = n - it; z.ab = fring; z.ai = n + 1; }
    else { z.wb = fring; z.wi = n + 2; z.ab = oring; z.ai = n - it; }
    PROFZ();
    mbar_wait(c.bar + (B_QF + p2_buf(c.wg, it)) * 8, (it >> 1) & 1);
    turn_wait(fring, n + 1 - lng);
    PROFZ();
    const int vs = it ? wrap5(z.ks + 1) : -1, ks = lng ? z.ks : wrap5(z.ks + (it ? 2 : 1));
    if (blk & 1) p2_first<64>(c, z, o, Pa, Pb, ks, vs, 1 + lng, acc);
    else p2_first<32>(c, z, o, Pa, Pb, ks, vs, 1 + lng, acc);
    z.ks = wrap5(ks + (it == 0 && lng ? 1 : 2));
    PROF(c.wg, 24 + it);
    n += 2 * j + 2;
    int left = 2 * j + lng;
    acc = left != 0;
    if (left == 0) { copy_p(Pa, Pb, p.zero); continue; }
    p2_turn<true>(c, z, o, Pb, Pa, it > 0 ? p2_buf(c.wg, it - 1) : -1, !(blk & 1), 1 + lng);
    while (--left > 0) {
      p2_turn<false>(c, z, o, Pa, Pb);
      if (--left == 0) { copy_p(Pa, Pb, p.zero); break; }
      p2_turn<false>(c, z, o, Pb, Pa);
    }
  }
  {
    if (!acc && nit > 1) p2_epilogue(o, z.e0, z.e1, c, p2_buf(c.wg, nit));
    turn_wait(z.wb, z.wi);
    issue_pv<8>(o, Pa, desc_lo(c.sm + SM_RING, 16384) + z.ks * 2048, acc);
    if (((nit - 1) ^ c.wg) & 1) turn_pass(c, z.ab, z.ai);
    p2_scales(z);
    WG_WAIT(0);
    pin(o);
    release(c, B_P2E + z.ks);
    p2_epilogue(o, z.e0, z.e1, c, p2_buf(c.wg, nit - 1));
    PROF(c.wg, 24 + nit);
  }
}

__device__ __forceinline__ void p2_load_q(const Params& p, const Ctx& c, int it, int w) {
  const int item = p.s.r[c.cl].item[it], h = item >> 3, j = item & 7, b = p2_buf(w, it);
  mbar_expect(c.bar + (B_QF + b) * 8, 16384);
  bulk_load(c.sm + SM_BUF + b * 16384, g_Q + (size_t)(h * 32 + j * 4 + p2_blk(c.rank, w, it)) * 16384, 16384, c.bar + (B_QF + b) * 8, POL(4));
}
__device__ __forceinline__ void wait_p1_free(const Ctx& c, int u1, int s) {
  mbar_wait(c.bar + (B_P1E + 2 * s) * 8, ((u1 - 1 - 2 * s) / 10) & 1);
  mbar_wait(c.bar + (B_P1E + 2 * s + 1) * 8, ((u1 - 2 - 2 * s) / 10) & 1);
}
__device__ __forceinline__ void p2_producer(const Params& p, const Ctx& c, int u1, int rot) {
  const int nit = p.s.r[c.cl].n2;
  int slot = rot, cnt = 0, par = 1, n = 0;
  const uint8_t* pv = nullptr;
  bool pl = false;
  auto load = [&](const uint8_t* src, int expect, uint32_t fb, bool last) {
    if (cnt < 5) {
      if (u1) {
        wait_p1_free(c, u1, slot);
        if (cnt == 0) p2_load_q(p, c, 0, 1);
      }
      cnt++;
    } else {
      if (slot == rot) par ^= 1;
      mbar_wait(c.bar + (B_P2E + slot) * 8, par);
    }
    if (expect) mbar_expect(fb, expect);
    bulk_load_mc(c.sm + SM_RING + slot * 32768 + c.rank * 16384, src, 16384, fb, last ? POL(5) : L2_NORMAL);
    slot = wrap5(slot + 1);
  };
  for (int it = 0; it < nit; it++) {
    const int item = p.s.r[c.cl].item[it], h = item >> 3, j = item & 7;
    if (it == 1 && (c.phases & 16) && p.s.r[c.cl].n1 < 8) flag_wait<true>(F_GATE, 256);
    uint32_t ready = (c.phases & 16) ? 0u : 255u;
    if (it == 0) { if (c.phases & 16) flag_wait<false>(F_Q + item, 4); mbar_wait(c.bar + B_LAD * 8, 0); p2_load_q(p, c, 0, 0); if (!u1) p2_load_q(p, c, 0, 1); }
    for (int t = 2 * j + 1; t >= 0; t--) {
      mask_wait(ready, t >> 1, F_KV + h * 8 + (c.lane & 7), 8);
      const uint8_t* k = g_KV + (size_t)(p.s.slot[h][t >> 1] * 16 + t) * 32768 + c.rank * 16384;
      const uint32_t fb = c.bar + (B_P2F + (n & 3)) * 8;
      const bool last = (p.s.r[c.cl].last[it] >> (t >> 1)) & 1;
      load(k, pv && t != 2 * j ? 65536 : 32768, fb, last);
      if (!(t & 1) && t + 4 <= 2 * j && c.rank == 0) flag_add_rx(F_RD + h * 8 + (t >> 1) + 2);
      if (pv) load(pv, 0, t != 2 * j ? fb : c.bar + (B_ORD + ((n - 1 - it) & 3)) * 8, pl);
      pl = last;
      pv = k + (size_t)NH * 16 * 32768;
      n++;
    }
  }
  load(pv, 32768, c.bar + (B_P2F + (n & 3)) * 8, pl);
}

__device__ __forceinline__ void p2_storer(const Params& p, const Ctx& c, int sfpar) {
  const int nit = p.s.r[c.cl].n2;
  auto load_q = [&](int it, int w) {
    if (c.phases & 16) flag_wait<false>(F_Q + p.s.r[c.cl].item[it], 4);
    p2_load_q(p, c, it, w);
  };
  if (nit > 1) {
    load_q(1, 1); p2_load_q(p, c, 1, 0); }
  for (int i = 0; i < 2 * nit; i++) {
    const int it = i >> 1, w = (it ^ i ^ 1) & 1, b = p2_buf(w, it);
    const int item = p.s.r[c.cl].item[it], h = item >> 3, j = item & 7;
    mbar_wait(c.bar + (B_SF + b) * 8, (sfpar >> b) & 1);
    sfpar ^= 1 << b;
    bulk_store(g_Q + (size_t)(h * 32 + j * 4 + p2_blk(c.rank, w, it)) * 16384, c.sm + SM_BUF + b * 16384, 16384, POL(1));
    BULK_COMMIT();
    BULK_WAIT(0);
    flag_add_rx(F_CTX + j * 64 + h);
    if ((i & 1) && it + 2 < nit) { load_q(it + 2, w); p2_load_q(p, c, it + 2, w ^ 1); }
  }
  release(c, B_DONE);
}

__device__ __forceinline__ int p3_pos(int i, int x) { return i < 4 ? (i + x) & 3 : 4; }
__device__ __forceinline__ void p3_consumer(const Params& p, const Ctx& c, int x) {
  const bool first = p.s.r[c.cl].p3 >= 24;
  const int tile = p.s.r[c.cl].p3 - (first ? 24 : 0), j = tile / 3, nt = tile - 3 * j;
  const int na = first ? 9 : 0, nb = first ? 2 * p.s.nh[tile] : 64 - 2 * p.s.nh[tile];
  const uint32_t ad = desc_lo(c.sm + SM_RING + c.wg * 8192, 16), bd = desc_lo(c.sm + SM_RING + 16384, 4096);
  float acc[96] = {};
  int slot = 0, par = 0, prev = 0;
  float g0 = 0.f, g1 = 0.f;
  const int hold = c.wg && LAG ? na + nb - LAG : -1, pass = c.wg || !LAG ? -1 : na + nb - 1;
#pragma unroll 1
  for (int kb = 0; kb < nb; kb++) {
    if (kb == hold) bar_sync(6, 256);
    mbar_wait(c.bar + (B_P3F + slot) * 8, par);
    if (kb == 0) PROF(c.wg, 39);
    WG_FENCE();
#pragma unroll
    for (int kk = 0; kk < 4; kk++) wgmma_ss192<1>(acc, ad + p3_pos(slot, x) * 2560 + kk * 2, bd + p3_pos(slot, x) * 2560 + (kk >> 1) * 768 + (kk & 1) * 128, kk != 0 ? 1 : kb != 0);
    WG_COMMIT();
    if (kb == pass) bar_arrive(6, 256);
    WG_WAIT(1);
    if (kb > 0) release(c, B_P3E + prev);
    else {
      const float* g = g_gate + j * 256 + c.rank * 128 + c.wg * 64 + c.warp * 16 + (c.lane >> 2);
      g0 = __ldcg(g); g1 = __ldcg(g + 8);
    }
    prev = slot;
    if (++slot == 5) { slot = 0; par ^= 1; }
  }
  WG_WAIT(0);
  pin(acc);
  g0 = 1.f - g0; g1 = 1.f - g1;
#pragma unroll
  for (int i = 0; i < 24; i++) { acc[4 * i] *= g0; acc[4 * i + 1] *= g0; acc[4 * i + 2] *= g1; acc[4 * i + 3] *= g1; }
#pragma unroll 1
  for (int kb = nb; kb < nb + na; kb++) {
    if (kb == hold) bar_sync(6, 256);
    mbar_wait(c.bar + (B_P3F + slot) * 8, par);
    if (kb == 0) PROF(c.wg, 39);
    WG_FENCE();
#pragma unroll
    for (int kk = 0; kk < 4; kk++) wgmma_ss192<1, 1>(acc, ad + p3_pos(slot, x) * 2560 + kk * 128, bd + p3_pos(slot, x) * 2560 + (kk >> 1) * 768 + (kk & 1) * 128, 1);
    WG_COMMIT();
    if (kb == pass) bar_arrive(6, 256);
    WG_WAIT(1);
    if (kb > 0) release(c, B_P3E + prev);
    prev = slot;
    if (++slot == 5) { slot = 0; par ^= 1; }
  }
  WG_WAIT(0);
  pin(acc);
  PROF(c.wg, 40);
  if (first) bar_sync(4 + c.wg, 128);
  mbar_wait(c.bar + B_OUT * 8, 0);
  const int row = (c.lane & 7) + ((c.lane >> 3) & 1) * 8;
  const uint32_t wbase = c.sm + SM_RING + c.wg * 8192 + c.warp * 2048;
  const uint32_t base = wbase + row * 128 + (((c.lane >> 4) ^ (row & 7)) << 4);
#pragma unroll
  for (int i = 0; i < 12; i++) {
    stsm4((base ^ ((i & 3) << 5)) + (i >> 2) * 40960, pack_bf16(acc[8 * i], acc[8 * i + 1]), pack_bf16(acc[8 * i + 2], acc[8 * i + 3]),
          pack_bf16(acc[8 * i + 4], acc[8 * i + 5]), pack_bf16(acc[8 * i + 6], acc[8 * i + 7]));
    if ((i & 3) == 3) {
      FENCE_ASYNC_SMEM();
      bar_sync(4 + c.wg, 128);
      if (c.warp == (i >> 2)) tma2d_add(&p.map_out, c.sm + SM_RING + c.wg * 8192 + c.warp * 40960, nt * 192 + c.warp * 64, j * 256 + c.rank * 128 + c.wg * 64);
    }
  }
  BULK_COMMIT();
  PROF(c.wg, 43);
  BULK_WAIT_READ(0);
  PROF(c.wg, 44);
}

__device__ __forceinline__ void p3_producer(const Params& p, const Ctx& c, int u1, int u2, int rot, int x) {
  const bool first = p.s.r[c.cl].p3 >= 24;
  const int tile = p.s.r[c.cl].p3 - (first ? 24 : 0), j = tile / 3, nt = tile - 3 * j;
  int slot = 0, par = 1, cnt = 0;
  auto wait_free = [&](int s) {
    const int f = wrap5(s + 5 - rot);
    if (f < u2) mbar_wait(c.bar + (B_P2E + s) * 8, ((u2 - 1 - f) / 5) & 1);
    else if (u1) wait_p1_free(c, u1, s);
  };
  asm volatile(ELECT("prefetch.tensormap [%0];") ::"l"(&p.map_o[0]) : "memory");
  asm volatile(ELECT("prefetch.tensormap [%0];") ::"l"(&p.map_out) : "memory");
  if ((c.phases & 16) && p.s.r[c.cl].n1 < 8 && p.s.r[c.cl].n2 < 2) flag_wait<true>(F_GATE, 256);
  uint32_t ready = (c.phases & 16) ? 0u : ~0u;
  const int q1 = first ? p.s.nh[tile] : 31;
  for (int q = first ? 0 : p.s.nh[tile]; q <= q1; q++) {
    const bool brA = first && q == q1;
    const int g = brA ? 32 : p.s.p3_order[j][q];
    if (brA) { if (c.phases & 16) flag_wait<false>(F_CTX + j * 64 + 32, 16); }
    else mask_wait(ready, g, F_CTX + j * 64 + c.lane, 4);
    const int nk = brA ? 9 : 2, k0 = (brA ? 0 : g * 128) + c.rank * 32;
    const uint8_t* a = brA ? g_oA + (j * 4 + c.rank * 2) * 73728 : g_Q + (size_t)(g * 32 + j * 4 + c.rank * 2) * 16384;
    const CUtensorMap* m = &p.map_o[brA];
    for (int i = 0; i < nk; i++) {
      const uint32_t st = c.sm + SM_RING + p3_pos(slot, x) * 40960, fb = c.bar + (B_P3F + slot) * 8;
      if (cnt < 4) { wait_free(p3_pos(cnt, x)); wait_free(p3_pos(cnt, x) + 1); }
      else if (cnt == 4) mbar_wait(c.bar + B_DONE * 8, 0);
      else mbar_wait(c.bar + (B_P3E + slot) * 8, par);
      cnt++;
      mbar_expect(fb, 40960);
      bulk_load(st, a + i * 8192, 8192, fb, POL(3));
      bulk_load(st + 8192, a + (nk + i) * 8192, 8192, fb, POL(3));
      tma3d_mc(st + 16384 + c.rank * 12288, m, 0, k0 + i * 64, nt * 3, fb);
      if (++slot == 5) { slot = 0; par ^= 1; }
    }
  }
}

__device__ __forceinline__ float bf_lo(uint32_t w) { return __uint_as_float(w << 16); }
__device__ __forceinline__ float bf_hi(uint32_t w) { return __uint_as_float(w & 0xffff0000u); }

__device__ __forceinline__ void gate_rows(const Params& p, int row0, int lane) {
  const uint4* x = reinterpret_cast<const uint4*>(p.x + (size_t)(row0 + (lane >> 2)) * DM) + (lane & 3);
  const uint4* w = reinterpret_cast<const uint4*>(p.gate_w) + (lane & 3);
  float a = 0.f;
#pragma unroll 1
  for (int b = 0; b < 3; b++) {
    uint4 u[6];
#pragma unroll
    for (int i = 0; i < 6; i++) u[i] = __ldg(x + (b * 6 + i) * 4);
#pragma unroll
    for (int i = 0; i < 6; i++) {
      const uint4 v = __ldg(w + (b * 6 + i) * 4);
      a = fmaf(bf_lo(u[i].x), bf_lo(v.x), a); a = fmaf(bf_hi(u[i].x), bf_hi(v.x), a);
      a = fmaf(bf_lo(u[i].y), bf_lo(v.y), a); a = fmaf(bf_hi(u[i].y), bf_hi(v.y), a);
      a = fmaf(bf_lo(u[i].z), bf_lo(v.z), a); a = fmaf(bf_hi(u[i].z), bf_hi(v.z), a);
      a = fmaf(bf_lo(u[i].w), bf_lo(v.w), a); a = fmaf(bf_hi(u[i].w), bf_hi(v.w), a);
    }
  }
  a += __shfl_xor_sync(0xffffffffu, a, 1);
  a += __shfl_xor_sync(0xffffffffu, a, 2);
  if ((lane & 3) == 0) g_gate[row0 + (lane >> 2)] = 1.f / (1.f + __expf(-a));
}

__device__ __forceinline__ void lds10(uint32_t (&k)[10], uint32_t a) {
  asm volatile("ld.shared.v2.u32 {%0, %1}, [%10];\nld.shared.v2.u32 {%2, %3}, [%10+8];\nld.shared.v2.u32 {%4, %5}, [%10+16];\n"
               "ld.shared.v2.u32 {%6, %7}, [%10+24];\nld.shared.v2.u32 {%8, %9}, [%10+32];"
               : "=r"(k[0]), "=r"(k[1]), "=r"(k[2]), "=r"(k[3]), "=r"(k[4]), "=r"(k[5]), "=r"(k[6]), "=r"(k[7]), "=r"(k[8]), "=r"(k[9]) : "r"(a));
}
__device__ __forceinline__ void local_attn(const Params& p, const Ctx& c, int rb, int hs) {
  const int lane = c.lane, grp = rb >> 2, par = lane >> 4, i0 = 2 * (lane & 15);
  const uint32_t buf = c.sm + SM_BUF + (c.warp - 2) * 8192, bqk = c.bar + (B_LA + (c.warp - 2) * 2) * 8, bv = bqk + 8;
  const uint32_t mine = buf + 2304 + par * 160 + i0 * 4;
  const bool flags = c.phases & 16;
  auto fetch_qk = [&](int i) {
    if (flags && !(i & 1)) {
      const int q = i >> 1;
      const int tgt = q == 0 ? 24 : q == 3 ? 8 : 12;
      flag_wait<false>(F_QKVA + (grp - (grp > 0 && (rb & 3) == 0 ? par : 0)) * 4 + q, tgt);
    }
    mbar_expect(bqk, 5184);
    tma3d(buf, &p.map_t[0], rb * 32 + 8, 0, 9 * (4 * i + hs), bqk, POL(2));
    tma3d(buf + 2304, &p.map_t[1], rb * 32, 0, 288 + 9 * (4 * i + hs), bqk, POL(2));
  };
  auto fetch_v = [&](int i) { mbar_expect(bv, 2880); tma3d(buf + 5248, &p.map_t[1], rb * 32, 0, 576 + 9 * (4 * i + hs), bv, POL(2)); };
  fetch_qk(0);
  if (flags) flag_wait<true>(F_GATE, 256);
#pragma unroll 1
  for (int q = 0; q < 8; q++) {
    fetch_v(q);
    float a[8], b[8];
#pragma unroll
    for (int w = 0; w < 8; w++) a[w] = b[w] = 0.f;
    mbar_wait(bqk, q & 1);
    PROFB(1 + 2 * q);
#pragma unroll 1
    for (int j = 0; j < 9; j++) {
      uint32_t x, y, k[10];
      asm volatile("ld.shared.v2.u32 {%0, %1}, [%2];" : "=r"(x), "=r"(y) : "r"(buf + lane * 8 + j * 256));
      lds10(k, mine + j * 320);
      const float xl = bf_lo(x), xh = bf_hi(x), yl = bf_lo(y), yh = bf_hi(y);
#pragma unroll
      for (int m = 1; m < 10; m++) {
        const float kl = bf_lo(k[m]), kh = bf_hi(k[m]);
        if (m < 9) a[8 - m] = fmaf(xl, kl, fmaf(xh, kh, a[8 - m]));
        if (m > 1) b[9 - m] = fmaf(yl, kl, fmaf(yh, kh, b[9 - m]));
      }
    }
    __syncwarp();
    if (q < 7) fetch_qk(q + 1);
    constexpr float SC = 0.23570226039551584f * 1.4426950408889634f;
    const float* gp = g_gate + rb * 64 + 2 * i0 + par;
    const float ga = __ldcg(gp), gb = __ldcg(gp + 2);
    float ma = a[0], mb = b[0];
#pragma unroll
    for (int w = 1; w < 8; w++) {
      if (rb == 0) {
        if (i0 < w) a[w] = -INFINITY;
        if (i0 + 1 < w) b[w] = -INFINITY;
      }
      ma = fmaxf(ma, a[w]); mb = fmaxf(mb, b[w]);
    }
    float la = 0.f, lb = 0.f;
#pragma unroll
    for (int w = 0; w < 8; w++) {
      a[w] = ex2((a[w] - ma) * SC); b[w] = ex2((b[w] - mb) * SC);
      la += a[w]; lb += b[w];
    }
    la = __fdividef(ga, la); lb = __fdividef(gb, lb);
#pragma unroll
    for (int w = 0; w < 8; w++) { a[w] *= la; b[w] *= lb; }
    uint8_t* dst = g_oA + rb * 73728 + ((i0 & 2) + par) * 4;
    mbar_wait(bv, q & 1);
#pragma unroll 1
    for (int j = 0; j < 9; j++) {
      uint32_t v[10];
      lds10(v, mine + 2944 + j * 320);
      float a0 = 0.f, a1 = 0.f, b0 = 0.f, b1 = 0.f;
#pragma unroll
      for (int m = 1; m < 10; m++) {
        const float vl = bf_lo(v[m]), vh = bf_hi(v[m]);
        if (m < 9) { a0 = fmaf(a[8 - m], vl, a0); a1 = fmaf(a[8 - m], vh, a1); }
        if (m > 1) { b0 = fmaf(b[9 - m], vl, b0); b1 = fmaf(b[9 - m], vh, b1); }
      }
      const uint32_t wa = pack_bf16(a0, a1), wb = pack_bf16(b0, b1);
      const uint32_t got = __shfl_xor_sync(0xffffffffu, par ? wa : wb, 16);
      const uint32_t r0 = par ? got : wa, r1 = par ? wb : got;
      const int col = 18 * (4 * q + hs) + 2 * j, o = col * 128 + ((((i0 >> 2) ^ col) & 7) << 4);
      *reinterpret_cast<uint32_t*>(dst + o) = __byte_perm(r0, r1, 0x5410);
      *reinterpret_cast<uint32_t*>(dst + ((o + 128) ^ 16)) = __byte_perm(r0, r1, 0x7632);
    }
    __syncwarp();
    PROFB(2 + 2 * q);
  }
  mbar_arrive_one(c.bar + B_LAD * 8);
  flag_add(F_CTX + grp * 64 + 32);
}

__global__ void __cluster_dims__(2, 1, 1) __launch_bounds__(384, 1) fused_kernel(const __grid_constant__ Params p) {
  extern __shared__ uint8_t smem_raw[];
  Ctx c;
  c.sm = ((uint32_t)__cvta_generic_to_shared(smem_raw) + 1023u) & ~1023u;
  c.bar = c.sm + SM_BAR;
  c.lane = threadIdx.x & 31;
  const int wid = __shfl_sync(0xffffffffu, threadIdx.x >> 5, 0);
  if (wid < 6) asm volatile("prefetch.tensormap [%0];" ::"l"(&p.map_a[0] + wid) : "memory");
  c.wg = wid >> 2;
  c.warp = wid & 3;
  PROF(c.wg, 0);
  PROFG(61);
  c.cl = (blockIdx.x + (wid >> 4)) >> 1;
  c.rank = blockIdx.x & 1;
  c.rbar = mapa(c.bar, c.lane & 1);
  {
    const int w = wid, cnt = (((int)(B_CNT >> (4 * w)) - 1) & 15) + 1;
    if (w < 11) {
#pragma unroll
      for (int i = 0; i < 8; i++) asm volatile("mbarrier.init.shared::cta.b64 [%0], %1;" ::"r"(c.bar + w * 64 + i * 8), "r"(cnt));
    }
    asm volatile("fence.mbarrier_init.release.cluster;" ::: "memory");
  }
  if (c.wg == 2) PROF(2, 56);
  asm volatile("barrier.cluster.arrive.relaxed;" ::: "memory");
  c.phases = p.s.r[c.cl].phases;
  const bool do1 = p.s.r[c.cl].n1 > 0, do2 = p.s.r[c.cl].n2 > 0, do3 = p.s.r[c.cl].p3 != 255;
  if (do1 && c.wg == 2 && c.warp == 0) {
    const int type = p.s.r[c.cl].slab >> 3;
    PROF(2, 57);
    FENCE_ASYNC_SMEM();
    mbar_expect(c.bar + B_P1F * 8, type ? 32768 : 16384);
    tma2d(type ? c.sm + SM_BUF + 32768 : c.sm + SM_RING, &p.map_a[type], type ? 512 : 0, (p.s.r[c.cl].slab & 7) * 256 + c.rank * 128, c.bar + B_P1F * 8);
    PROF(2, 58);
  }
  asm volatile("barrier.cluster.wait.acquire;" ::: "memory");
  if (c.wg == 2) PROF(2, 59);
  if (do1 && c.wg == 2 && c.warp == 0) {
    const int type = p.s.r[c.cl].slab >> 3, tile = p.s.r[c.cl].tile[0] & 63;
    if (!type) mbar_expect(c.bar + (B_P1F + 1) * 8, 16384);
    tma2d_mc(c.sm + SM_RING + (1 - type) * 16384 + c.rank * 8192, &p.map_w[type * 2 + (tile >> 5)], (tile & 31) * 128 + c.rank * 64, type ? 512 : 0, c.bar + (B_P1F + 1 - type) * 8);
  }

  if (c.wg < 2) {
    PROF(c.wg, 4);
    asm volatile("setmaxnreg.inc.sync.aligned.u32 224;");
    if (c.wg == 1) {
      if (do1) bar_arrive(ORDER, 256);
      if (c.lane == 0) mbar_arrive(c.bar + B_P2F * 8);
    }
    if (do1) p1_consumer(p, c);
    if (do2) p2_consumer(p, c, p.s.r[c.cl].rot);
    if (do3) p3_consumer(p, c, p.s.r[c.cl].x3);
    PROF(c.wg, 63);
    PROFG(62);
    if (c.lane == 0) mbar_arrive(c.bar + B_FIN * 8);
    __syncwarp();
    cluster_sync();
  } else {
    asm volatile("setmaxnreg.dec.sync.aligned.u32 56;");
    if (c.warp == 0) {
      PROF(2, 60);
      if (do1) p1_producer(p, c);
      if (do2) p2_producer(p, c, p.s.r[c.cl].u1, p.s.r[c.cl].rot);
      if (do3) p3_producer(p, c, p.s.r[c.cl].u1, p.s.r[c.cl].u2, p.s.r[c.cl].rot, p.s.r[c.cl].x3);
    } else if (c.warp == 1) {
      int sfpar = 0;
      if (do1) {
        p1_storer(p, c);
        sfpar = (p.s.r[c.cl].n1 & 1) * 10;
      }
      if (do2) p2_storer(p, c, sfpar);
      else { mbar_wait(c.bar + B_LAD * 8, 0); release(c, B_DONE); }
      if (do3) {
        const int task = p.s.r[c.cl].p3;
        if (task >= 24) {
          const int j = (task - 24) / 3, nt = task - 24 - 3 * j;
          uint4* o = reinterpret_cast<uint4*>(p.out + (size_t)(j * 256 + c.rank * 128 + (c.lane >> 3)) * DM + nt * 192) + (c.lane & 7);
#pragma unroll 4
          for (int r = 0; r < 32; r++) o[r * 288] = o[r * 288 + 8] = o[r * 288 + 16] = make_uint4(0u, 0u, 0u, 0u);
          __syncwarp();
          flag_add(F_OUT + (task - 24) * 2 + c.rank);
        } else if (c.phases & 16) {
          flag_wait<false, 256>(F_OUT + task * 2 + c.rank, 1);
        }
        mbar_arrive_one(c.bar + B_OUT * 8);
      }
    } else {
      const int bw = blockIdx.x * 2 + (c.warp - 2);
      if ((c.phases & 1) && bw < 256) {
        gate_rows(p, bw * 8, c.lane);
        __syncwarp();
        flag_add(F_GATE);
      }
      if (p.s.r[c.cl].bg != 255) local_attn(p, c, p.s.r[c.cl].bg, bw & 3);
      else if (c.lane == 0) mbar_arrive(c.bar + B_LAD * 8);
    }
    __syncwarp();
    bar_sync(3, 128);
    if (c.warp == 0 && (c.phases & 4)) {
      int last = 0;
      if (c.lane == 0) { __threadfence(); last = atomicAdd(g_flags + F_DONE, 1) == 2 * NCL - 1; }
      if (__shfl_sync(0xffffffffu, last, 0)) for (int i = c.lane; i < F_NUM; i += 32) g_flags[i] = 0;
    }
    if (c.warp == 1) mbar_wait(c.bar + B_FIN * 8, 0);
    __syncwarp();
    cluster_sync();
  }
}

SCHED_DECL Sched k_sched = {
  {{0,29,2,26,0,{232,248,0,0,0,0,0,0,0,0,0},{0,0,0,0,0,0,0,0,0,0,0},{71,38,3,32,5,4,2,11,9,24,21,12,19,17,74,20,13,22,16,18,28,14,29,26,31,23,27,30,25,0}},
   {1,29,2,255,1,{216,244,0,0,0,0,0,0,0,0,0},{0,0,0,0,0,0,0,0,0,0,0},{71,38,0,40,79,4,2,11,9,24,21,19,17,12,20,13,10,22,16,18,28,14,29,26,31,23,27,30,25,0}},
   {2,29,2,255,2,{217,243,0,0,0,0,0,0,0,0,0},{0,0,0,0,0,0,0,0,0,0,0},{67,40,7,32,1,15,4,9,11,24,19,21,17,12,13,20,16,22,10,18,28,14,29,31,26,23,27,30,25,0}},
   {3,29,1,255,3,{188,0,0,0,0,0,0,0,0,0,0},{0,0,0,0,0,0,0,0,0,0,0},{70,35,0,40,1,2,4,9,11,24,21,19,17,12,13,20,22,16,10,18,28,14,26,29,31,23,27,30,25,0}},
   {4,28,0,15,4,{0,0,0,0,0,0,0,0,0,0,0},{0,0,0,0,0,0,0,0,0,0,0},{64,39,8,38,1,2,36,24,11,21,12,19,17,20,13,22,16,10,18,28,14,29,26,31,23,27,30,25,0,0}},
   {5,28,0,14,5,{0,0,0,0,0,0,0,0,0,0,0},{0,0,0,0,0,0,0,0,0,0,0},{72,35,0,38,1,2,36,24,11,21,12,19,17,20,13,22,16,10,18,28,14,29,26,31,23,27,30,25,0,0}},
   {6,27,1,44,6,{212,0,0,0,0,0,0,0,0,0,0},{24,0,0,0,0,0,0,0,0,0,0},{71,8,6,37,2,15,41,11,21,12,19,17,20,13,86,16,10,18,28,14,29,26,31,27,23,30,25,0,0,0}},
   {7,26,2,36,7,{112,252,0,0,0,0,0,0,0,0,0},{0,0,0,0,0,0,0,0,0,0,0},{70,7,3,65,68,75,88,85,76,83,81,84,77,80,74,22,82,92,78,93,90,95,91,87,94,89,0,0,0,0}},
   {0,29,1,25,8,{251,0,0,0,0,0,0,0,0,0,0},{0,0,0,0,0,0,0,0,0,0,0},{103,8,35,65,37,36,34,43,41,56,53,44,51,49,106,52,45,54,48,50,60,46,61,58,63,55,59,62,57,0}},
   {1,29,1,255,9,{245,0,0,0,0,0,0,0,0,0,0},{56,0,0,0,0,0,0,0,0,0,0},{103,3,32,5,111,36,34,43,41,56,53,51,49,44,52,45,42,54,48,50,60,46,61,58,63,55,59,62,57,0}},
   {2,29,1,27,10,{210,0,0,0,0,0,0,0,0,0,0},{7,0,0,0,0,0,0,0,0,0,0},{99,6,39,5,33,47,36,41,43,56,51,53,49,44,45,52,48,54,42,50,60,46,61,63,58,55,59,62,57,0}},
   {3,29,2,255,11,{218,202,0,0,0,0,0,0,0,0,0},{0,0,0,0,0,0,0,0,0,0,0},{102,7,32,5,33,34,36,41,43,56,53,51,49,44,45,52,54,48,42,50,60,46,58,61,63,55,59,62,57,0}},
   {4,28,0,21,12,{0,0,0,0,0,0,0,0,0,0,0},{0,0,0,0,0,0,0,0,0,0,0},{96,3,40,5,33,34,9,56,43,53,44,51,49,52,45,54,48,42,50,60,46,61,58,63,55,59,62,57,0,0}},
   {5,28,0,4,13,{0,0,0,0,0,0,0,0,0,0,0},{0,0,0,0,0,0,0,0,0,0,0},{104,7,32,5,33,34,9,56,43,53,44,51,49,52,45,54,48,42,50,60,46,61,58,63,55,59,62,57,0,0}},
   {6,27,0,12,14,{0,0,0,0,0,0,0,0,0,0,0},{0,0,0,0,0,0,0,0,0,0,0},{103,40,38,65,34,47,88,43,53,44,51,49,52,45,118,48,42,50,60,46,61,58,63,59,55,62,57,0,0,0}},
   {7,26,0,9,15,{0,0,0,0,0,0,0,0,0,0,0},{0,0,0,0,0,0,0,0,0,0,0},{102,39,35,97,100,107,120,117,108,115,113,116,109,112,106,54,114,124,110,125,122,127,123,119,126,121,0,0,0,0}},
   {0,6,6,46,255,{0,59,22,194,107,215,0,0,0,0,0},{0,0,0,0,0,192,0,0,0,0,0},{70,40,0,97,79,47,0,0,0,0,0,0,0,0,0,0,0,0,0,0,0,0,0,0,0,0,0,0,0,0}},
   {1,6,6,8,255,{61,10,174,179,233,224,0,0,0,0,0},{0,0,0,0,0,0,0,0,0,0,0},{70,35,8,37,1,33,0,0,0,0,0,0,0,0,0,0,0,0,0,0,0,0,0,0,0,0,0,0,0,0}},
   {2,6,4,23,255,{47,93,100,226,0,0,0,0,0,0,0},{0,0,0,0,0,0,0,0,0,0,0},{72,38,0,37,2,34,0,0,0,0,0,0,0,0,0,0,0,0,0,0,0,0,0,0,0,0,0,0,0,0}},
   {3,6,7,29,255,{41,44,89,74,193,141,238,0,0,0,0},{0,0,0,0,0,0,0,0,0,0,0},{67,39,8,37,79,47,0,0,0,0,0,0,0,0,0,0,0,0,0,0,0,0,0,0,0,0,0,0,0,0}},
   {4,8,5,33,255,{58,125,102,239,241,0,0,0,0,0,0},{0,0,0,0,0,0,0,0,0,0,0},{71,35,6,37,79,47,4,41,0,0,0,0,0,0,0,0,0,0,0,0,0,0,0,0,0,0,0,0,0,0}},
   {5,8,5,37,255,{120,23,195,134,190,0,0,0,0,0,0},{0,0,0,0,0,0,0,0,0,0,0},{67,39,6,37,79,47,4,41,0,0,0,0,0,0,0,0,0,0,0,0,0,0,0,0,0,0,0,0,0,0}},
   {6,8,7,255,255,{40,43,34,159,83,211,219,0,0,0,0},{0,0,0,0,0,0,0,0,0,0,0},{64,3,69,97,68,36,9,56,0,0,0,0,0,0,0,0,0,0,0,0,0,0,0,0,0,0,0,0,0,0}},
   {7,6,6,31,255,{46,73,75,101,113,237,0,0,0,0,0},{0,0,0,0,0,63,0,0,0,0,0},{64,8,69,66,79,73,0,0,0,0,0,0,0,0,0,0,0,0,0,0,0,0,0,0,0,0,0,0,0,0}},
   {8,16,5,255,16,{192,170,148,250,220,0,0,0,0,0,0},{0,0,0,0,31,0,0,0,0,0,0},{160,170,0,43,35,44,45,4,11,12,21,19,16,22,14,27,0,0,0,0,0,0,0,0,0,0,0,0,0,0}},
   {9,19,1,11,17,{131,0,0,0,0,0,0,0,0,0,0},{0,0,0,0,0,0,0,0,0,0,0},{71,37,8,43,1,75,2,45,21,19,20,10,16,28,29,23,27,30,25,0,0,0,0,0,0,0,0,0,0,0}},
   {10,18,4,32,18,{152,130,229,184,0,0,0,0,0,0,0},{0,0,7,0,0,0,0,0,0,0,0},{160,170,166,163,15,40,9,83,81,21,20,10,92,22,95,26,89,30,0,0,0,0,0,0,0,0,0,0,0,0}},
   {11,17,4,255,19,{168,162,227,247,0,0,0,0,0,0,0},{0,0,0,192,0,0,0,0,0,0,0},{160,170,166,163,2,109,4,24,19,12,22,20,18,14,29,31,30,0,0,0,0,0,0,0,0,0,0,0,0,0}},
   {12,16,3,13,20,{72,156,144,0,0,0,0,0,0,0,0},{0,0,0,0,0,0,0,0,0,0,0},{160,170,6,1,15,9,45,24,12,17,20,16,18,14,95,23,0,0,0,0,0,0,0,0,0,0,0,0,0,0}},
   {13,16,3,18,21,{88,161,85,0,0,0,0,0,0,0,0},{0,0,0,0,0,0,0,0,0,0,0},{160,170,0,43,2,9,24,45,12,17,13,16,18,14,26,23,0,0,0,0,0,0,0,0,0,0,0,0,0,0}},
   {14,16,3,39,22,{137,108,117,0,0,0,0,0,0,0,0},{0,0,0,0,0,0,0,0,0,0,0},{160,170,6,1,4,88,40,21,19,84,13,10,92,93,95,23,0,0,0,0,0,0,0,0,0,0,0,0,0,0}},
   {15,16,5,255,23,{16,99,82,223,200,0,0,0,0,0,0},{1,0,0,192,0,0,0,0,0,0,0},{160,170,3,43,39,9,24,40,12,17,13,10,18,14,26,27,0,0,0,0,0,0,0,0,0,0,0,0,0,0}},
   {8,21,4,255,24,{128,234,209,205,0,0,0,0,0,0,0},{0,0,0,63,0,0,0,0,0,0,0},{164,70,65,5,39,40,2,9,24,17,74,13,18,20,28,29,31,23,26,25,30,0,0,0,0,0,0,0,0,0}},
   {9,16,3,3,25,{32,105,133,0,0,0,0,0,0,0,0},{1,0,0,0,0,0,0,0,0,0,0},{160,170,133,163,4,9,40,24,81,12,13,22,18,14,26,31,0,0,0,0,0,0,0,0,0,0,0,0,0,0}},
   {10,16,3,19,26,{96,165,176,0,0,0,0,0,0,0,0},{0,0,0,0,0,0,0,0,0,0,0},{164,131,107,103,4,109,11,24,12,77,80,82,78,93,91,23,0,0,0,0,0,0,0,0,0,0,0,0,0,0}},
   {11,17,4,47,27,{136,177,163,213,0,0,0,0,0,0,0},{0,0,0,32,0,0,0,0,0,0,0},{164,70,107,103,104,9,11,21,81,77,80,10,92,90,87,27,89,0,0,0,0,0,0,0,0,0,0,0,0,0}},
   {12,18,2,255,28,{231,221,0,0,0,0,0,0,0,0,0},{0,32,0,0,0,0,0,0,0,0,0},{164,64,34,163,4,40,11,21,19,77,22,10,92,93,26,27,30,25,0,0,0,0,0,0,0,0,0,0,0,0}},
   {13,18,3,255,29,{104,150,206,0,0,0,0,0,0,0,0},{0,3,0,0,0,0,0,0,0,0,0},{164,72,133,15,4,75,40,21,19,84,22,10,92,93,95,27,30,25,0,0,0,0,0,0,0,0,0,0,0,0}},
   {14,17,3,35,30,{80,181,254,0,0,0,0,0,0,0,0},{0,0,127,0,0,0,0,0,0,0,0},{164,7,133,15,73,75,45,76,81,86,80,82,78,90,91,94,89,0,0,0,0,0,0,0,0,0,0,0,0,0}},
   {15,18,3,41,31,{129,119,208,0,0,0,0,0,0,0,0},{0,0,0,0,0,0,0,0,0,0,0},{164,70,133,66,44,75,85,45,19,84,80,22,92,93,95,23,30,25,0,0,0,0,0,0,0,0,0,0,0,0}},
   {8,4,6,40,255,{25,15,17,173,164,191,0,0,0,0,0},{0,0,0,0,18,255,0,0,0,0,0},{169,7,34,15,0,0,0,0,0,0,0,0,0,0,0,0,0,0,0,0,0,0,0,0,0,0,0,0,0,0}},
   {9,4,4,10,255,{69,12,196,110,0,0,0,0,0,0,0},{0,0,0,0,0,0,0,0,0,0,0},{164,70,79,103,0,0,0,0,0,0,0,0,0,0,0,0,0,0,0,0,0,0,0,0,0,0,0,0,0,0}},
   {10,4,6,255,255,{55,33,175,132,253,242,0,0,0,0,0},{0,0,0,0,0,6,0,0,0,0,0},{169,72,7,108,0,0,0,0,0,0,0,0,0,0,0,0,0,0,0,0,0,0,0,0,0,0,0,0,0,0}},
   {11,4,4,5,255,{63,20,154,183,0,0,0,0,0,0,0},{188,0,0,131,0,0,0,0,0,0,0},{169,131,8,108,0,0,0,0,0,0,0,0,0,0,0,0,0,0,0,0,0,0,0,0,0,0,0,0,0,0}},
   {12,4,5,34,255,{7,124,158,146,189,0,0,0,0,0,0},{111,0,0,0,0,0,0,0,0,0,0},{169,7,166,103,0,0,0,0,0,0,0,0,0,0,0,0,0,0,0,0,0,0,0,0,0,0,0,0,0,0}},
   {13,4,7,38,255,{51,14,91,153,81,145,118,0,0,0,0},{0,0,0,0,0,0,95,0,0,0,0},{169,131,65,163,0,0,0,0,0,0,0,0,0,0,0,0,0,0,0,0,0,0,0,0,0,0,0,0,0,0}},
   {14,5,6,30,255,{54,36,169,138,180,236,0,0,0,0,0},{0,0,0,0,0,0,0,0,0,0,0},{169,64,34,66,44,0,0,0,0,0,0,0,0,0,0,0,0,0,0,0,0,0,0,0,0,0,0,0,0,0}},
   {15,4,8,43,255,{49,5,122,35,157,115,185,186,0,0,0},{0,0,0,0,47,0,0,0,0,0,0},{169,64,65,68,0,0,0,0,0,0,0,0,0,0,0,0,0,0,0,0,0,0,0,0,0,0,0,0,0,0}},
   {8,3,6,255,255,{70,18,197,109,116,204,0,0,0,0,0},{0,0,0,0,0,0,0,0,0,0,0},{161,72,166,0,0,0,0,0,0,0,0,0,0,0,0,0,0,0,0,0,0,0,0,0,0,0,0,0,0,0}},
   {9,3,4,0,255,{4,39,90,182,0,0,0,0,0,0,0},{0,0,0,0,0,0,0,0,0,0,0},{169,131,34,0,0,0,0,0,0,0,0,0,0,0,0,0,0,0,0,0,0,0,0,0,0,0,0,0,0,0}},
   {10,4,6,7,255,{48,28,42,76,172,228,0,0,0,0,0},{0,0,0,0,0,0,0,0,0,0,0},{161,70,0,66,0,0,0,0,0,0,0,0,0,0,0,0,0,0,0,0,0,0,0,0,0,0,0,0,0,0}},
   {11,4,6,255,255,{62,123,103,225,214,203,0,0,0,0,0},{0,0,0,0,0,0,0,0,0,0,0},{161,7,0,1,0,0,0,0,0,0,0,0,0,0,0,0,0,0,0,0,0,0,0,0,0,0,0,0,0,0}},
   {12,4,6,22,255,{64,65,68,21,142,114,0,0,0,0,0},{0,0,0,0,0,0,0,0,0,0,0},{161,131,107,108,0,0,0,0,0,0,0,0,0,0,0,0,0,0,0,0,0,0,0,0,0,0,0,0,0,0}},
   {13,4,5,24,255,{30,9,19,143,255,0,0,0,0,0,0},{0,0,0,0,128,0,0,0,0,0,0},{161,7,34,103,0,0,0,0,0,0,0,0,0,0,0,0,0,0,0,0,0,0,0,0,0,0,0,0,0,0}},
   {14,4,7,42,255,{24,1,13,77,139,149,187,0,0,0,0},{0,0,0,0,0,0,0,0,0,0,0},{161,72,166,163,0,0,0,0,0,0,0,0,0,0,0,0,0,0,0,0,0,0,0,0,0,0,0,0,0,0}},
   {15,4,4,6,255,{60,127,167,178,0,0,0,0,0,0,0},{0,0,0,0,0,0,0,0,0,0,0},{161,7,34,15,0,0,0,0,0,0,0,0,0,0,0,0,0,0,0,0,0,0,0,0,0,0,0,0,0,0}},
   {8,2,7,28,255,{26,121,2,38,155,230,249,0,0,0,0},{0,0,0,0,0,0,0,0,0,0,0},{165,131,0,0,0,0,0,0,0,0,0,0,0,0,0,0,0,0,0,0,0,0,0,0,0,0,0,0,0,0}},
   {9,4,4,16,255,{66,52,95,140,0,0,0,0,0,0,0},{0,0,0,0,0,0,0,0,0,0,0},{161,64,166,108,0,0,0,0,0,0,0,0,0,0,0,0,0,0,0,0,0,0,0,0,0,0,0,0,0,0}},
   {10,4,5,255,255,{6,11,92,151,207,0,0,0,0,0,0},{0,0,0,0,192,0,0,0,0,0,0},{165,98,133,1,0,0,0,0,0,0,0,0,0,0,0,0,0,0,0,0,0,0,0,0,0,0,0,0,0,0}},
   {11,4,4,17,255,{29,126,171,86,0,0,0,0,0,0,0},{0,0,0,124,0,0,0,0,0,0,0},{165,98,133,15,0,0,0,0,0,0,0,0,0,0,0,0,0,0,0,0,0,0,0,0,0,0,0,0,0,0}},
   {12,4,6,255,255,{71,198,98,84,222,201,0,0,0,0,0},{222,0,0,0,0,0,0,0,0,0,0},{165,72,133,66,0,0,0,0,0,0,0,0,0,0,0,0,0,0,0,0,0,0,0,0,0,0,0,0,0,0}},
   {13,4,7,255,255,{56,50,67,79,135,246,240,0,0,0,0},{0,0,0,192,255,0,1,0,0,0,0},{165,70,166,108,0,0,0,0,0,0,0,0,0,0,0,0,0,0,0,0,0,0,0,0,0,0,0,0,0,0}},
   {14,4,7,45,255,{27,3,78,97,106,147,235,0,0,0,0},{0,0,0,0,0,0,0,0,0,0,0},{165,131,107,103,0,0,0,0,0,0,0,0,0,0,0,0,0,0,0,0,0,0,0,0,0,0,0,0,0,0}},
   {15,4,3,1,255,{31,37,111,0,0,0,0,0,0,0,0},{242,0,0,0,0,0,0,0,0,0,0},{165,72,166,163,0,0,0,0,0,0,0,0,0,0,0,0,0,0,0,0,0,0,0,0,0,0,0,0,0,0}},
   {6,2,4,2,255,{57,53,199,87,0,0,0,0,0,0,0},{0,0,0,128,0,0,0,0,0,0,0},{96,35,0,0,0,0,0,0,0,0,0,0,0,0,0,0,0,0,0,0,0,0,0,0,0,0,0,0,0,0}},
   {7,6,5,20,255,{8,45,94,166,160,0,0,0,0,0,0},{0,0,0,0,1,0,0,0,0,0,0},{96,40,101,98,111,105,0,0,0,0,0,0,0,0,0,0,0,0,0,0,0,0,0,0,0,0,0,0,0,0}}},
  {6,4,9,7,10,9,9,8,9,5,6,4,7,2,10,10,1,9,7,5,7,10,8,7},
  {{3,6,7,8,0,1,5,15,2,4,9,11,12,24,10,17,21,13,19,18,16,22,20,28,14,27,29,31,23,26,25,30},
   {3,6,7,0,8,5,15,1,4,11,9,2,24,21,17,12,19,13,20,10,22,16,18,28,14,29,26,23,31,27,30,25},
   {3,8,6,7,0,5,2,1,15,4,9,11,19,24,17,12,21,13,20,16,10,28,14,18,22,29,31,26,23,27,25,30},
   {3,6,7,8,0,5,1,15,2,9,4,11,24,21,19,17,12,13,22,16,20,10,18,28,14,29,26,23,31,27,30,25},
   {0,7,3,8,6,5,1,2,15,4,9,11,24,21,17,12,19,13,20,22,28,10,16,18,14,29,31,26,23,27,30,25},
   {3,8,7,0,6,5,1,15,2,4,9,11,24,21,12,19,17,20,13,10,16,22,18,14,28,29,26,23,31,27,30,25},
   {0,3,7,8,6,5,1,15,2,4,9,24,11,21,12,19,17,13,22,20,10,16,18,28,14,29,26,31,23,27,30,25},
   {0,3,6,7,8,5,1,2,4,15,9,11,24,21,12,19,17,20,13,10,22,16,18,28,14,26,29,31,23,27,30,25}},
  {{4,3,4,3,0,3,1,1},{5,7,6,6,6,6,6,6},{9,9,7,8,8,8,7,7},{3,2,0,1,2,1,3,4},
   {8,8,9,9,9,9,8,8},{6,5,5,5,5,5,5,5},{1,1,2,0,4,4,4,0},{0,0,3,2,1,2,0,2},
   {2,4,1,4,3,0,2,3},{11,11,10,10,10,10,10,10},{1,7,9,11,11,12,12,11},{10,10,11,11,12,12,12,11},
   {14,16,5,6,4,5,5,5},{5,5,6,1,7,8,7,9},{10,10,10,13,13,5,6,5},{7,6,8,7,7,7,9,9},
   {7,6,8,9,9,11,11,7},{16,15,2,5,6,0,0,1},{2,9,11,12,12,4,4,0},{15,14,13,0,5,6,6,6},
   {6,1,0,7,0,7,9,8},{13,13,14,13,13,4,4,0},{0,0,7,8,8,9,8,12},{14,16,0,1,7,9,5,6},
   {12,12,12,12,11,11,11,12},{1,7,11,10,10,5,0,8},{11,11,2,6,6,7,9,9},{16,15,6,8,8,4,8,0},
   {3,8,12,10,10,10,5,6},{12,12,14,5,4,0,0,8},{5,5,7,12,12,10,4,5},{13,13,5,7,5,8,7,1}},
  {{255,255,255,255,255,255,255,255},{255,255,255,255,255,255,255,255},{255,255,255,255,255,255,255,255},{255,255,255,255,255,255,255,255},
   {255,255,255,255,255,255,255,255},{255,255,255,255,255,255,255,255},{255,255,255,255,255,255,255,255},{255,255,255,255,255,255,255,255},
   {255,255,255,255,255,255,255,255},{255,255,255,255,255,255,255,255},{6,1,4,11,24,11,11,11},{255,255,255,255,255,255,255,255},
   {255,255,5,1,6,5,5,5},{1,5,1,3,15,2,2,15},{11,11,9,21,21,12,19,12},{255,255,255,255,255,255,255,255},
   {15,15,15,4,4,24,24,2},{255,255,6,5,1,8,7,0},{8,2,11,24,11,21,21,21},{255,255,255,6,5,1,1,1},
   {5,6,3,15,0,15,15,4},{255,255,255,255,255,6,6,6},{7,7,2,2,2,4,4,24},{12,12,20,13,13,22,28,28},
   {255,255,255,255,255,255,255,255},{10,10,18,28,28,14,29,29},{9,9,17,12,17,20,20,13},{17,17,13,22,22,18,22,18},
   {3,4,24,9,9,9,12,19},{24,24,21,17,12,17,17,20},{13,13,22,18,18,28,18,14},{21,21,12,20,19,13,13,17}}};

typedef CUresult (*EncodeFn)(CUtensorMap*, CUtensorMapDataType, cuuint32_t, void*, const cuuint64_t*, const cuuint64_t*, const cuuint32_t*,
                             const cuuint32_t*, CUtensorMapInterleave, CUtensorMapSwizzle, CUtensorMapL2promotion, CUtensorMapFloatOOBfill);

void make_map2(EncodeFn enc, CUtensorMap* m, const void* ptr, int rows, int cols, int box_rows) {
  cuuint64_t dim[2] = {(cuuint64_t)cols, (cuuint64_t)rows}, str[1] = {(cuuint64_t)cols * 2};
  cuuint32_t box[2] = {64, (cuuint32_t)box_rows}, es[2] = {1, 1};
  enc(m, CU_TENSOR_MAP_DATA_TYPE_BFLOAT16, 2, const_cast<void*>(ptr), dim, str, box, es, CU_TENSOR_MAP_INTERLEAVE_NONE, CU_TENSOR_MAP_SWIZZLE_128B,
      CU_TENSOR_MAP_L2_PROMOTION_L2_128B, CU_TENSOR_MAP_FLOAT_OOB_FILL_NONE);
}
void make_map3(EncodeFn enc, CUtensorMap* m, const void* ptr, int rows) {
  cuuint64_t dim[3] = {64, (cuuint64_t)rows, 9}, str[2] = {DM * 2, 128};
  cuuint32_t box[3] = {64, 32, 3}, es[3] = {1, 1, 1};
  enc(m, CU_TENSOR_MAP_DATA_TYPE_BFLOAT16, 3, const_cast<void*>(ptr), dim, str, box, es, CU_TENSOR_MAP_INTERLEAVE_NONE, CU_TENSOR_MAP_SWIZZLE_128B,
      CU_TENSOR_MAP_L2_PROMOTION_L2_128B, CU_TENSOR_MAP_FLOAT_OOB_FILL_NONE);
}

void make_map_t(EncodeFn enc, CUtensorMap* m, void* ptr, int width, int cols) {
  cuuint64_t dim[3] = {TP / 2, 2, 864}, str[2] = {TP * 2, TP * 4};
  cuuint32_t box[3] = {(cuuint32_t)width, 2, (cuuint32_t)cols}, es[3] = {1, 1, 1};
  enc(m, CU_TENSOR_MAP_DATA_TYPE_UINT32, 3, ptr, dim, str, box, es, CU_TENSOR_MAP_INTERLEAVE_NONE, cols == 64 ? CU_TENSOR_MAP_SWIZZLE_128B : CU_TENSOR_MAP_SWIZZLE_NONE,
      CU_TENSOR_MAP_L2_PROMOTION_NONE, CU_TENSOR_MAP_FLOAT_OOB_FILL_NONE);
}

int g_mode = -1;

}

extern "C" void kernel_launch(void* const* d_in, const int* in_sizes, int n_in, void* d_out, int out_size) {
  static EncodeFn enc = nullptr;
  static void* t_ptr = nullptr;
  if (!enc) {
    void* fn = nullptr;
    cudaDriverEntryPointQueryResult st;
    cudaGetDriverEntryPoint("cuTensorMapEncodeTiled", &fn, cudaEnableDefault, &st);
    enc = (EncodeFn)fn;
    cudaGetSymbolAddress(&t_ptr, g_T);
    cudaFuncSetAttribute(fused_kernel, cudaFuncAttributeMaxDynamicSharedMemorySize, SMEM_BYTES);
    if (g_mode < 0) {
      cudaLaunchConfig_t cfg = {};
      cfg.gridDim = dim3(2 * NCL); cfg.blockDim = dim3(384); cfg.dynamicSmemBytes = SMEM_BYTES;
      cudaLaunchAttribute at; at.id = cudaLaunchAttributeClusterDimension;
      at.val.clusterDim.x = 2; at.val.clusterDim.y = 1; at.val.clusterDim.z = 1;
      cfg.attrs = &at; cfg.numAttrs = 1;
      int nc = 0;
      g_mode = (cudaOccupancyMaxActiveClusters(&nc, fused_kernel, &cfg) == cudaSuccess && nc >= NCL) ? 1 : 0;
      (void)cudaGetLastError();
    }
  }
  Params p;
  make_map2(enc, &p.map_a[0], d_in[4], SEQ, DC, 128);
  make_map2(enc, &p.map_a[1], d_in[0], SEQ, DM, 128);
  make_map2(enc, &p.map_w[0], d_in[6], DC, 4096, 64);
  make_map2(enc, &p.map_w[1], d_in[7], DC, 4096, 64);
  make_map2(enc, &p.map_w[2], d_in[5], DM, 4096, 64);
  make_map2(enc, &p.map_w[3], d_in[1], DM, 1728, 64);
  make_map3(enc, &p.map_o[0], d_in[8], 4096);
  make_map3(enc, &p.map_o[1], d_in[2], DM);
  make_map_t(enc, &p.map_t[0], t_ptr, 32, 9);
  make_map_t(enc, &p.map_t[1], t_ptr, 40, 9);
  make_map_t(enc, &p.map_t[2], t_ptr, 32, 64);
  p.x = (const __nv_bfloat16*)d_in[0];
  p.gate_w = (const __nv_bfloat16*)d_in[9];
  make_map2(enc, &p.map_out, d_out, SEQ, DM, 64);
  p.out = (__nv_bfloat16*)d_out;
  p.zero = 0;
  auto launch = [&](int phases) {
    p.s = k_sched;
    for (int i = 0; i < NCL; i++) {
      Rec& r = p.s.r[i];
      if (!(phases & 1)) r.n1 = 0;
      if (!(phases & 2)) r.n2 = 0;
      if (!(phases & (r.p3 < 24 ? 4 : 32))) r.p3 = 255;
      if (!(phases & 8)) r.bg = 255;
      const int u1 = r.n1 ? 8 + r.n1 * (8 + (r.slab >> 3)) : 0;
      int u2 = 0;
      for (int k = 0; k < r.n2; k++) u2 += 4 * (r.item[k] & 7) + 4;
      r.u1 = (uint8_t)u1; r.u2 = (uint8_t)u2;
      r.rot = (uint8_t)(((u1 % 10 + 1) >> 1) % 5);
      r.x3 = (uint8_t)((r.rot + u2) % 5 & 3);
      r.phases = (uint8_t)phases;
    }
    if (!(phases & 16))
      for (int i = 0; i < 256; i++) { p.s.slot[i >> 3][i & 7] = (uint8_t)(i >> 3); p.s.prev[i >> 3][i & 7] = 255; }
    fused_kernel<<<2 * NCL, 384, SMEM_BYTES>>>(p);
  };
  if (g_mode == 1) launch(63);
  else { launch(1); launch(10); launch(32); launch(4); }
}
```

```cpp
#include <cuda_runtime.h>
#include <cuda_bf16.h>
#include <cuda.h>
#include <stdint.h>

namespace {

constexpr int SEQ = 2048, DM = 576, DC = 512, NH = 32;
constexpr int NCL = 66;
constexpr uint32_t DESC_HI = 0x40000040u;

constexpr int SM_RING = 0;
constexpr int SM_BUF = 163840;
constexpr int SM_BAR = 229376;
constexpr int B_P1E = 0, B_P2E = 10, B_P3E = 15, B_P2F = 24, B_SF = 32, B_ORD = 36, B_LAD = 40, B_DONE = 41, B_FIN = 48;
constexpr int B_P3F = 56, B_OUT = 61, B_P1F = 64, B_SE = 74, B_QF = 80, B_LA = 84, B_NUM = 88;
constexpr uint64_t B_CNT = 0x11118245000ull;
constexpr int SMEM_BYTES = SM_BAR + B_NUM * 8 + 1024;

constexpr int F_QKVA = 32;
constexpr int F_GATE = 64;
constexpr int F_DONE = 65;
constexpr int F_CTX = 96;
constexpr int F_OUT = 96 + 8 * 64;
constexpr int F_KV = F_OUT + 64;
constexpr int F_Q = F_KV + 256;
constexpr int F_RD = F_Q + 256;
constexpr int F_NUM = F_RD + 256;

struct Rec {
  uint8_t slab;
  uint8_t n1, n2;
  uint8_t p3;
  uint8_t bg;
  uint8_t item[11];
  uint8_t last[11];
  uint8_t tile[32];
  uint8_t u1, u2;
  uint8_t rot, x3;
  uint8_t phases;
};
struct Sched {
  Rec r[NCL];
  uint8_t nh[24];
  uint8_t p3_order[8][32];
  uint8_t slot[32][8];
  uint8_t prev[32][8];
};

#define SCHED_DECL static const

struct Params {
  CUtensorMap map_a[2];
  CUtensorMap map_w[4];
  CUtensorMap map_o[2];
  CUtensorMap map_t[3];
  CUtensorMap map_out;
  const __nv_bfloat16* x;
  const __nv_bfloat16* gate_w;
  __nv_bfloat16* out;
  int zero;
  alignas(64) Sched s;
};

__device__ __align__(1024) uint8_t g_Q[NH * 32 * 16384];
__device__ __align__(1024) uint8_t g_KV[2 * NH * 16 * 32768];
__device__ __align__(1024) uint8_t g_oA[32 * 576 * 128];
constexpr int TP = SEQ + 16;
__device__ __align__(1024) uint32_t g_T[864 * TP];
__device__ float g_gate[SEQ];
__device__ int g_flags[F_NUM];

__device__ __forceinline__ void mbar_arrive(uint32_t b) { asm volatile("mbarrier.arrive.shared::cta.b64 _, [%0];" ::"r"(b) : "memory"); }
__device__ __forceinline__ void mbar_arrive_cl(uint32_t b, int cnt) {
  asm volatile("mbarrier.arrive.shared::cluster.b64 _, [%0], %1;" ::"r"(b), "r"(cnt) : "memory");
}
__device__ __forceinline__ void mbar_wait(uint32_t b, int par) {
  asm volatile(
      "{\n.reg .pred p;\n.reg .u32 c;\n"
      "mbarrier.try_wait.parity.shared::cta.b64 p, [%0], %1;\n@p bra DN;\nmov.u32 c, 0;\n"
      "LP:\nmbarrier.try_wait.parity.shared::cta.b64 p, [%0], %1;\n@p bra DN;\n"
      "add.u32 c, c, 1;\nsetp.lt.u32 p, c, 4000000;\n@p bra LP;\ntrap;\nDN:\n}" ::"r"(b), "r"(par) : "memory");
}
__device__ __forceinline__ uint32_t mapa(uint32_t a, uint32_t cta) {
  uint32_t r; asm("mapa.shared::cluster.u32 %0, %1, %2;" : "=r"(r) : "r"(a), "r"(cta)); return r;
}
#define ELECT(ins) "{\n.reg .pred e;\nelect.sync _|e, 0xffffffff;\n@e " ins "\n}"
__device__ __forceinline__ void mbar_expect(uint32_t b, int bytes) {
  asm volatile(ELECT("mbarrier.arrive.expect_tx.shared::cta.b64 _, [%0], %1;") ::"r"(b), "r"(bytes) : "memory");
}
__device__ __forceinline__ void mbar_arrive_one(uint32_t b) { asm volatile(ELECT("mbarrier.arrive.shared::cta.b64 _, [%0];") ::"r"(b) : "memory"); }
constexpr uint64_t L2_NORMAL = 0x1000000000000000ull, L2_FIRST = 0x12F0000000000000ull;
__device__ __forceinline__ void bulk_load(uint32_t dst, const void* src, int bytes, uint32_t bar, uint64_t pol = L2_NORMAL) {
  asm volatile(ELECT("cp.async.bulk.shared::cluster.global.mbarrier::complete_tx::bytes.L2::cache_hint [%0], [%1], %2, [%3], %4;") ::"r"(dst), "l"(src), "r"(bytes), "r"(bar), "l"(pol) : "memory");
}
__device__ __forceinline__ void bulk_load_mc(uint32_t dst, const void* src, int bytes, uint32_t bar, uint64_t pol = L2_NORMAL) {
  asm volatile(ELECT("cp.async.bulk.shared::cluster.global.mbarrier::complete_tx::bytes.multicast::cluster.L2::cache_hint [%0], [%1], %2, [%3], %4, %5;") ::"r"(dst), "l"(src), "r"(bytes), "r"(bar), "h"((uint16_t)3), "l"(pol) : "memory");
}
__device__ __forceinline__ void bulk_store(void* dst, uint32_t src, int bytes, uint64_t pol = L2_NORMAL) {
  asm volatile(ELECT("cp.async.bulk.global.shared::cta.bulk_group.L2::cache_hint [%0], [%1], %2, %3;") ::"l"(dst), "r"(src), "r"(bytes), "l"(pol) : "memory");
}
__device__ __forceinline__ void tma2d(uint32_t dst, const CUtensorMap* m, int c0, int c1, uint32_t bar, uint64_t pol = L2_NORMAL) {
  asm volatile(ELECT("cp.async.bulk.tensor.2d.shared::cluster.global.mbarrier::complete_tx::bytes.L2::cache_hint [%0], [%1, {%3, %4}], [%2], %5;") ::"r"(dst), "l"(m), "r"(bar), "r"(c0), "r"(c1), "l"(pol) : "memory");
}
__device__ __forceinline__ void tma2d_mc(uint32_t dst, const CUtensorMap* m, int c0, int c1, uint32_t bar, uint64_t pol = L2_NORMAL) {
  asm volatile(ELECT("cp.async.bulk.tensor.2d.shared::cluster.global.mbarrier::complete_tx::bytes.multicast::cluster.L2::cache_hint [%0], [%1, {%3, %4}], [%2], %5, %6;") ::"r"(dst), "l"(m), "r"(bar), "r"(c0), "r"(c1), "h"((uint16_t)3), "l"(pol) : "memory");
}
__device__ __forceinline__ void tma3d(uint32_t dst, const CUtensorMap* m, int c0, int c1, int c2, uint32_t bar, uint64_t pol = L2_NORMAL) {
  asm volatile(ELECT("cp.async.bulk.tensor.3d.shared::cluster.global.mbarrier::complete_tx::bytes.L2::cache_hint [%0], [%1, {%3, %4, %5}], [%2], %6;") ::"r"(dst), "l"(m), "r"(bar), "r"(c0), "r"(c1), "r"(c2), "l"(pol) : "memory");
}
__device__ __forceinline__ void tma3d_mc(uint32_t dst, const CUtensorMap* m, int c0, int c1, int c2, uint32_t bar, uint64_t pol = L2_NORMAL) {
  asm volatile(ELECT("cp.async.bulk.tensor.3d.shared::cluster.global.mbarrier::complete_tx::bytes.multicast::cluster.L2::cache_hint [%0], [%1, {%3, %4, %5}], [%2], %6, %7;") ::"r"(dst), "l"(m), "r"(bar), "r"(c0), "r"(c1), "r"(c2), "h"((uint16_t)3), "l"(pol) : "memory");
}
__device__ __forceinline__ void tma2d_add(const CUtensorMap* m, uint32_t src, int c0, int c1) {
  asm volatile(ELECT("cp.reduce.async.bulk.tensor.2d.global.shared::cta.add.bulk_group [%0, {%2, %3}], [%1];") ::"l"(m), "r"(src), "r"(c0), "r"(c1) : "memory");
}
__device__ __forceinline__ void tma3d_store(const CUtensorMap* m, uint32_t src, int c0, int c1, int c2, uint64_t pol = L2_NORMAL) {
  asm volatile(ELECT("cp.async.bulk.tensor.3d.global.shared::cta.bulk_group.L2::cache_hint [%0, {%2, %3, %4}], [%1], %5;") ::"l"(m), "r"(src), "r"(c0), "r"(c1), "r"(c2), "l"(pol) : "memory");
}
__device__ __forceinline__ void tma2d_prefetch(const CUtensorMap* m, int c0, int c1, uint64_t pol = L2_NORMAL) {
  asm volatile(ELECT("cp.async.bulk.prefetch.tensor.2d.L2.global.L2::cache_hint [%0, {%1, %2}], %3;") ::"l"(m), "r"(c0), "r"(c1), "l"(pol) : "memory");
}
#define LAG 3
#define HINT 62
#define POL(bit) ((HINT >> (bit)) & 1 ? L2_FIRST : L2_NORMAL)
#define BULK_COMMIT() asm volatile("cp.async.bulk.commit_group;" ::: "memory")
#define BULK_WAIT(n) asm volatile("cp.async.bulk.wait_group %0;" ::"n"(n) : "memory")
#define BULK_WAIT_READ(n) asm volatile("cp.async.bulk.wait_group.read %0;" ::"n"(n) : "memory")
#define FENCE_ASYNC_SMEM() asm volatile("fence.proxy.async.shared::cta;" ::: "memory")
#define FENCE_ASYNC_ALL() asm volatile("fence.proxy.async;" ::: "memory")
#define WG_FENCE() asm volatile("wgmma.fence.sync.aligned;" ::: "memory")
#define WG_COMMIT() asm volatile("wgmma.commit_group.sync.aligned;" ::: "memory")
#define WG_WAIT(n) asm volatile("wgmma.wait_group.sync.aligned %0;" ::"n"(n) : "memory")
__device__ __forceinline__ void bar_sync(int id, int n) { asm volatile("bar.sync %0, %1;" ::"r"(id), "r"(n) : "memory"); }
__device__ __forceinline__ void bar_arrive(int id, int n) { asm volatile("bar.arrive %0, %1;" ::"r"(id), "r"(n) : "memory"); }
__device__ __forceinline__ void cluster_sync() {
  asm volatile("barrier.cluster.arrive.relaxed;\nbarrier.cluster.wait.acquire;" ::: "memory");
}
template <int N> __device__ __forceinline__ void pin(float (&r)[N]) {
#pragma unroll
  for (int i = 0; i < N; i++) asm volatile("" : "+f"(r[i])::"memory");
}
template <int N> __device__ __forceinline__ void pin(uint32_t (&r)[N]) {
#pragma unroll
  for (int i = 0; i < N; i++) asm volatile("" : "+r"(r[i])::"memory");
}
__device__ __forceinline__ uint32_t pack_bf16(float lo, float hi) {
  uint32_t r; asm("cvt.rn.bf16x2.f32 %0, %1, %2;" : "=r"(r) : "f"(hi), "f"(lo)); return r;
}
__device__ __forceinline__ float ex2(float x) { float r; asm("ex2.approx.ftz.f32 %0, %1;" : "=f"(r) : "f"(x)); return r; }
__device__ __forceinline__ void ldsm4(uint32_t a, uint32_t& r0, uint32_t& r1, uint32_t& r2, uint32_t& r3) {
  asm volatile("ldmatrix.sync.aligned.m8n8.x4.shared.b16 {%0,%1,%2,%3}, [%4];" : "=r"(r0), "=r"(r1), "=r"(r2), "=r"(r3) : "r"(a) : "memory");
}
__device__ __forceinline__ void stsm4(uint32_t a, uint32_t r0, uint32_t r1, uint32_t r2, uint32_t r3) {
  asm volatile("stmatrix.sync.aligned.m8n8.x4.shared.b16 [%0], {%1,%2,%3,%4};" ::"r"(a), "r"(r0), "r"(r1), "r"(r2), "r"(r3) : "memory");
}
__device__ __forceinline__ void flag_add(int idx) {
  asm volatile(ELECT("red.release.gpu.global.add.s32 [%0], 1;") ::"l"(g_flags + idx) : "memory");
}
__device__ __forceinline__ void flag_add_rx(int idx) {
  asm volatile(ELECT("red.relaxed.gpu.global.add.s32 [%0], 1;") ::"l"(g_flags + idx) : "memory");
}
template <bool ACQ, int NS = 32> __device__ __forceinline__ void flag_wait(int idx, int target) {
  int n = 0;
  while (true) {
    int v;
    if (ACQ) asm volatile("ld.acquire.gpu.global.s32 %0, [%1];" : "=r"(v) : "l"(g_flags + idx) : "memory");
    else asm volatile("ld.relaxed.gpu.global.s32 %0, [%1];" : "=r"(v) : "l"(g_flags + idx) : "memory");
    if (__all_sync(0xffffffffu, v >= target)) break;
    if (++n > 20000000) __trap();
    __nanosleep(NS);
  }
}
__device__ __forceinline__ void mask_wait(uint32_t& ready, int bit, int idx, int target) {
  for (int n = 0; !((ready >> bit) & 1); n++) {
    int v;
    if (n) { __nanosleep(32); if (n > 20000000) __trap(); }
    asm volatile("ld.relaxed.gpu.global.s32 %0, [%1];" : "=r"(v) : "l"(g_flags + idx) : "memory");
    ready = __ballot_sync(0xffffffffu, v >= target);
  }
}
__device__ __forceinline__ uint32_t desc_lo(uint32_t addr, uint32_t lbo) { return ((addr & 0x3FFFFu) >> 4) | ((lbo >> 4) << 16); }
#define PROF(role, i)
#define PROFX(cond, i)
#define PROFB(i)
#define PROFG(i)

template <int TB, int TA = 0> __device__ __forceinline__ void wgmma_ss64(float (&d)[32], uint32_t alo, uint32_t blo, int sd) {
  asm volatile("{\n.reg .pred p;\n.reg .b64 da, db;\n"
    "setp.ne.b32 p, %34, 0;\nmov.b64 da, {%32, %36};\nmov.b64 db, {%33, %36};\n"
    "wgmma.mma_async.sync.aligned.m64n64k16.f32.bf16.bf16 "
    "{%0,%1,%2,%3,%4,%5,%6,%7,%8,%9,%10,%11,%12,%13,%14,%15,%16,%17,%18,%19,%20,%21,%22,%23,"
    "%24,%25,%26,%27,%28,%29,%30,%31}, "
    "da, db, p, 1, 1, %37, %35;\n}\n"
    : "+f"(d[0]),"+f"(d[1]),"+f"(d[2]),"+f"(d[3]),"+f"(d[4]),"+f"(d[5]),"+f"(d[6]),"+f"(d[7]),"+f"(d[8]),"+f"(d[9]),"+f"(d[10]),"+f"(d[11]),
      "+f"(d[12]),"+f"(d[13]),"+f"(d[14]),"+f"(d[15]),"+f"(d[16]),"+f"(d[17]),"+f"(d[18]),"+f"(d[19]),"+f"(d[20]),"+f"(d[21]),"+f"(d[22]),"+f"(d[23]),
      "+f"(d[24]),"+f"(d[25]),"+f"(d[26]),"+f"(d[27]),"+f"(d[28]),"+f"(d[29]),"+f"(d[30]),"+f"(d[31])
    : "r"(alo), "r"(blo), "r"(sd), "n"(TB), "r"(DESC_HI), "n"(TA));
}
template <int TB, int TA = 0> __device__ __forceinline__ void wgmma_ss128(float (&d)[64], uint32_t alo, uint32_t blo, int sd) {
  asm volatile("{\n.reg .pred p;\n.reg .b64 da, db;\n"
    "setp.ne.b32 p, %66, 0;\nmov.b64 da, {%64, %68};\nmov.b64 db, {%65, %68};\n"
    "wgmma.mma_async.sync.aligned.m64n128k16.f32.bf16.bf16 "
    "{%0,%1,%2,%3,%4,%5,%6,%7,%8,%9,%10,%11,%12,%13,%14,%15,%16,%17,%18,%19,%20,%21,%22,%23,"
    "%24,%25,%26,%27,%28,%29,%30,%31,%32,%33,%34,%35,%36,%37,%38,%39,%40,%41,%42,%43,%44,%45,%46,%47,"
    "%48,%49,%50,%51,%52,%53,%54,%55,%56,%57,%58,%59,%60,%61,%62,%63}, "
    "da, db, p, 1, 1, %69, %67;\n}\n"
    : "+f"(d[0]),"+f"(d[1]),"+f"(d[2]),"+f"(d[3]),"+f"(d[4]),"+f"(d[5]),"+f"(d[6]),"+f"(d[7]),"+f"(d[8]),"+f"(d[9]),"+f"(d[10]),"+f"(d[11]),
      "+f"(d[12]),"+f"(d[13]),"+f"(d[14]),"+f"(d[15]),"+f"(d[16]),"+f"(d[17]),"+f"(d[18]),"+f"(d[19]),"+f"(d[20]),"+f"(d[21]),"+f"(d[22]),"+f"(d[23]),
      "+f"(d[24]),"+f"(d[25]),"+f"(d[26]),"+f"(d[27]),"+f"(d[28]),"+f"(d[29]),"+f"(d[30]),"+f"(d[31]),"+f"(d[32]),"+f"(d[33]),"+f"(d[34]),"+f"(d[35]),
      "+f"(d[36]),"+f"(d[37]),"+f"(d[38]),"+f"(d[39]),"+f"(d[40]),"+f"(d[41]),"+f"(d[42]),"+f"(d[43]),"+f"(d[44]),"+f"(d[45]),"+f"(d[46]),"+f"(d[47]),
      "+f"(d[48]),"+f"(d[49]),"+f"(d[50]),"+f"(d[51]),"+f"(d[52]),"+f"(d[53]),"+f"(d[54]),"+f"(d[55]),"+f"(d[56]),"+f"(d[57]),"+f"(d[58]),"+f"(d[59]),
      "+f"(d[60]),"+f"(d[61]),"+f"(d[62]),"+f"(d[63])
    : "r"(alo), "r"(blo), "r"(sd), "n"(TB), "r"(DESC_HI), "n"(TA));
}
template <int TB> __device__ __forceinline__ void wgmma_rs128(float (&d)[64], uint32_t a0, uint32_t a1, uint32_t a2, uint32_t a3, uint32_t blo, int sd) {
  asm volatile("{\n.reg .pred p;\n.reg .b64 db;\n"
    "setp.ne.b32 p, %69, 0;\nmov.b64 db, {%68, %71};\n"
    "wgmma.mma_async.sync.aligned.m64n128k16.f32.bf16.bf16 "
    "{%0,%1,%2,%3,%4,%5,%6,%7,%8,%9,%10,%11,%12,%13,%14,%15,%16,%17,%18,%19,%20,%21,%22,%23,"
    "%24,%25,%26,%27,%28,%29,%30,%31,%32,%33,%34,%35,%36,%37,%38,%39,%40,%41,%42,%43,%44,%45,%46,%47,"
    "%48,%49,%50,%51,%52,%53,%54,%55,%56,%57,%58,%59,%60,%61,%62,%63}, "
    "{%64,%65,%66,%67}, db, p, 1, 1, %70;\n}\n"
    : "+f"(d[0]),"+f"(d[1]),"+f"(d[2]),"+f"(d[3]),"+f"(d[4]),"+f"(d[5]),"+f"(d[6]),"+f"(d[7]),"+f"(d[8]),"+f"(d[9]),"+f"(d[10]),"+f"(d[11]),
      "+f"(d[12]),"+f"(d[13]),"+f"(d[14]),"+f"(d[15]),"+f"(d[16]),"+f"(d[17]),"+f"(d[18]),"+f"(d[19]),"+f"(d[20]),"+f"(d[21]),"+f"(d[22]),"+f"(d[23]),
      "+f"(d[24]),"+f"(d[25]),"+f"(d[26]),"+f"(d[27]),"+f"(d[28]),"+f"(d[29]),"+f"(d[30]),"+f"(d[31]),"+f"(d[32]),"+f"(d[33]),"+f"(d[34]),"+f"(d[35]),
      "+f"(d[36]),"+f"(d[37]),"+f"(d[38]),"+f"(d[39]),"+f"(d[40]),"+f"(d[41]),"+f"(d[42]),"+f"(d[43]),"+f"(d[44]),"+f"(d[45]),"+f"(d[46]),"+f"(d[47]),
      "+f"(d[48]),"+f"(d[49]),"+f"(d[50]),"+f"(d[51]),"+f"(d[52]),"+f"(d[53]),"+f"(d[54]),"+f"(d[55]),"+f"(d[56]),"+f"(d[57]),"+f"(d[58]),"+f"(d[59]),
      "+f"(d[60]),"+f"(d[61]),"+f"(d[62]),"+f"(d[63])
    : "r"(a0), "r"(a1), "r"(a2), "r"(a3), "r"(blo), "r"(sd), "n"(TB), "r"(DESC_HI));
}
template <int TB, int TA = 0> __device__ __forceinline__ void wgmma_ss192(float (&d)[96], uint32_t alo, uint32_t blo, int sd) {
  asm volatile("{\n.reg .pred p;\n.reg .b64 da, db;\n"
    "setp.ne.b32 p, %98, 0;\nmov.b64 da, {%96, %100};\nmov.b64 db, {%97, %100};\n"
    "wgmma.mma_async.sync.aligned.m64n192k16.f32.bf16.bf16 "
    "{%0,%1,%2,%3,%4,%5,%6,%7,%8,%9,%10,%11,%12,%13,%14,%15,%16,%17,%18,%19,%20,%21,%22,%23,"
    "%24,%25,%26,%27,%28,%29,%30,%31,%32,%33,%34,%35,%36,%37,%38,%39,%40,%41,%42,%43,%44,%45,%46,%47,"
    "%48,%49,%50,%51,%52,%53,%54,%55,%56,%57,%58,%59,%60,%61,%62,%63,%64,%65,%66,%67,%68,%69,%70,%71,"
    "%72,%73,%74,%75,%76,%77,%78,%79,%80,%81,%82,%83,%84,%85,%86,%87,%88,%89,%90,%91,%92,%93,%94,%95}, "
    "da, db, p, 1, 1, %101, %99;\n}\n"
    : "+f"(d[0]),"+f"(d[1]),"+f"(d[2]),"+f"(d[3]),"+f"(d[4]),"+f"(d[5]),"+f"(d[6]),"+f"(d[7]),"+f"(d[8]),"+f"(d[9]),"+f"(d[10]),"+f"(d[11]),
      "+f"(d[12]),"+f"(d[13]),"+f"(d[14]),"+f"(d[15]),"+f"(d[16]),"+f"(d[17]),"+f"(d[18]),"+f"(d[19]),"+f"(d[20]),"+f"(d[21]),"+f"(d[22]),"+f"(d[23]),
      "+f"(d[24]),"+f"(d[25]),"+f"(d[26]),"+f"(d[27]),"+f"(d[28]),"+f"(d[29]),"+f"(d[30]),"+f"(d[31]),"+f"(d[32]),"+f"(d[33]),"+f"(d[34]),"+f"(d[35]),
      "+f"(d[36]),"+f"(d[37]),"+f"(d[38]),"+f"(d[39]),"+f"(d[40]),"+f"(d[41]),"+f"(d[42]),"+f"(d[43]),"+f"(d[44]),"+f"(d[45]),"+f"(d[46]),"+f"(d[47]),
      "+f"(d[48]),"+f"(d[49]),"+f"(d[50]),"+f"(d[51]),"+f"(d[52]),"+f"(d[53]),"+f"(d[54]),"+f"(d[55]),"+f"(d[56]),"+f"(d[57]),"+f"(d[58]),"+f"(d[59]),
      "+f"(d[60]),"+f"(d[61]),"+f"(d[62]),"+f"(d[63]),"+f"(d[64]),"+f"(d[65]),"+f"(d[66]),"+f"(d[67]),"+f"(d[68]),"+f"(d[69]),"+f"(d[70]),"+f"(d[71]),
      "+f"(d[72]),"+f"(d[73]),"+f"(d[74]),"+f"(d[75]),"+f"(d[76]),"+f"(d[77]),"+f"(d[78]),"+f"(d[79]),"+f"(d[80]),"+f"(d[81]),"+f"(d[82]),"+f"(d[83]),
      "+f"(d[84]),"+f"(d[85]),"+f"(d[86]),"+f"(d[87]),"+f"(d[88]),"+f"(d[89]),"+f"(d[90]),"+f"(d[91]),"+f"(d[92]),"+f"(d[93]),"+f"(d[94]),"+f"(d[95])
    : "r"(alo), "r"(blo), "r"(sd), "n"(TB), "r"(DESC_HI), "n"(TA));
}

struct Ctx {
  uint32_t sm;
  uint32_t bar;
  uint32_t rbar;
  int cl, rank, wg, warp, lane, phases;
};
__device__ __forceinline__ void release(const Ctx& c, int b, int cnt = 1) {
  if (c.lane < 2) mbar_arrive_cl(c.rbar + b * 8, cnt);
}
#define HK 5
#define PFM 7
#define PF1 1
constexpr float SM_SCALE = 0.08838834764831845f * 1.4426950408889634f;
constexpr float SM_HI = 1.8446744e19f, SM_LO = 5.4210109e-20f;
constexpr int ORDER = 1;

__device__ __forceinline__ void stage_tile(const float (&a)[64], uint32_t buf, const Ctx& c, float s0, float s1) {
  const int row = (c.lane & 7) + ((c.lane >> 3) & 1) * 8;
  const uint32_t base = buf + (c.warp * 16 + row) * 128 + (((c.lane >> 4) ^ (row & 7)) << 4);
#pragma unroll
  for (int i = 0; i < 8; i++)
    stsm4((base ^ ((i & 3) << 5)) + (i >> 2) * 8192, pack_bf16(a[8 * i] * s0, a[8 * i + 1] * s0), pack_bf16(a[8 * i + 2] * s1, a[8 * i + 3] * s1),
          pack_bf16(a[8 * i + 4] * s0, a[8 * i + 5] * s0), pack_bf16(a[8 * i + 6] * s1, a[8 * i + 7] * s1));
}

__device__ __forceinline__ void p1_epilogue(const Params& p, const Ctx& c, const float (&acc)[64], int t, int type) {
  const int tile = p.s.r[c.cl].tile[t] & 63, b = c.wg * 2 + 1;
  mbar_wait(c.bar + (B_SE + b) * 8, (t & 1) ^ 1);
  if (type && tile >= 32) {
    const int r = 2 * (c.lane & 3) + ((c.lane >> 2) & 1);
    const uint32_t dst = c.sm + SM_BUF + b * 16384 + r * 128 + (((c.warp * 2) ^ r) << 4) + (c.lane >> 3) * 4;
#pragma unroll
    for (int i = 0; i < 16; i++) {
      asm volatile("st.shared.u32 [%0], %1;" ::"r"(dst + i * 1024), "r"(pack_bf16(acc[4 * i], acc[4 * i + 1])) : "memory");
      asm volatile("st.shared.u32 [%0], %1;" ::"r"((dst ^ 16) + i * 1024), "r"(pack_bf16(acc[4 * i + 2], acc[4 * i + 3])) : "memory");
    }
  } else {
    if (type) stage_tile(acc, c.sm + SM_BUF + b * 16384, c, SM_SCALE, SM_SCALE);
    else stage_tile(acc, c.sm + SM_BUF + b * 16384, c, 1.f, 1.f);
  }
  FENCE_ASYNC_SMEM();
  __syncwarp();
  if (c.lane == 0) mbar_arrive(c.bar + (B_SF + b) * 8);
}

__device__ __forceinline__ void p1_consumer(const Params& p, const Ctx& c) {
  const int n = p.s.r[c.cl].n1;
  const int type = p.s.r[c.cl].slab >> 3;
  const uint32_t bdesc = desc_lo(c.sm + SM_RING, 8192), adesc = desc_lo(c.sm + SM_BUF + 32768 + c.wg * 8192, 16);
  uint32_t A[128];
  float acc[64] = {};
  int slot = 0, par = 0;
  auto next = [&]() { if (++slot == 10) { slot = 0; par ^= 1; } };
  {
    const int row = (c.lane & 7) + ((c.lane >> 3) & 1) * 8;
    const uint32_t base = c.sm + SM_RING + (c.wg * 64 + c.warp * 16 + row) * 128 + (((c.lane >> 4) ^ (row & 7)) << 4);
    if (c.wg == 1) bar_sync(ORDER + 1, 256);
    int pa = -1, pb = -1;
    if (type) {
      mbar_wait(c.bar + B_P1F * 8, 0);
      WG_FENCE();
#pragma unroll
      for (int kk = 0; kk < 4; kk++) wgmma_ss128<1>(acc, adesc + kk * 2, bdesc + kk * 128, kk != 0);
      WG_COMMIT();
      pb = 0; slot = 1;
    }
#pragma unroll
    for (int kb = 0; kb < 8; kb++) {
      const int sa = slot;
      mbar_wait(c.bar + (B_P1F + slot) * 8, par);
      if (kb == 0) PROF(c.wg, 5);
      next();
      mbar_wait(c.bar + (B_P1F + slot) * 8, par);
      PROF(c.wg, 6 + 2 * kb);
      WG_FENCE();
#pragma unroll
      for (int kk = 0; kk < 4; kk++)
        wgmma_ss128<1>(acc, desc_lo(c.sm + SM_RING + c.wg * 8192, 16) + sa * 1024 + kk * 2, bdesc + slot * 1024 + kk * 128, (kb | kk) != 0 ? 1 : type);
      WG_COMMIT();
      if (kb == 1 && c.wg == 0) bar_arrive(ORDER + 1, 256);
#pragma unroll
      for (int kk = 0; kk < 4; kk++) ldsm4((base ^ (kk << 5)) + sa * 16384, A[kb * 16 + kk * 4], A[kb * 16 + kk * 4 + 1], A[kb * 16 + kk * 4 + 2], A[kb * 16 + kk * 4 + 3]);
      WG_WAIT(1);
      if (kb > 0) release(c, B_P1E + pa);
      if (kb > 0 || pb >= 0) release(c, B_P1E + pb);
      pa = sa; pb = slot;
      next();
    }
    WG_WAIT(0);
    __syncwarp();
    release(c, B_P1E + pa);
    release(c, B_P1E + pb);
    pin(acc);
    PROF(c.wg, 1);
    p1_epilogue(p, c, acc, 0, type);
    PROF(c.wg, 2);
  }
  for (int t = 1; t < n; t++) {
    bar_sync(ORDER + c.wg, 256);
    int prev1 = -1, prev2 = -1;
    if (type) {
      mbar_wait(c.bar + (B_P1F + slot) * 8, par);
      WG_FENCE();
#pragma unroll
      for (int kk = 0; kk < 4; kk++) wgmma_ss128<1>(acc, adesc + kk * 2, bdesc + slot * 1024 + kk * 128, kk != 0);
      WG_COMMIT();
      prev1 = slot;
      next();
    }
#pragma unroll
    for (int kb = 0; kb < 8; kb++) {
      mbar_wait(c.bar + (B_P1F + slot) * 8, par);
      WG_FENCE();
      const uint32_t d = bdesc + slot * 1024;
#pragma unroll
      for (int kk = 0; kk < 4; kk++)
        wgmma_rs128<1>(acc, A[kb * 16 + kk * 4], A[kb * 16 + kk * 4 + 1], A[kb * 16 + kk * 4 + 2], A[kb * 16 + kk * 4 + 3], d + kk * 128, (kb | kk) != 0 ? 1 : type);
      WG_COMMIT();
      if (kb == HK) {
        if (t + 1 < n || c.wg == 0) bar_arrive(ORDER + (c.wg ^ 1), 256);
      }
      if (kb > 0) { WG_WAIT(2); if (kb > 1 || prev2 >= 0) release(c, B_P1E + prev2); }
      prev2 = prev1; prev1 = slot;
      next();
    }
    WG_WAIT(1);
    release(c, B_P1E + prev2);
    WG_WAIT(0);
    pin(acc);
    release(c, B_P1E + prev1);
    p1_epilogue(p, c, acc, t, type);
    PROF(c.wg, 3);
  }
}

__device__ __forceinline__ void p1_producer(const Params& p, const Ctx& c) {
  const int n = p.s.r[c.cl].n1;
  const int type = p.s.r[c.cl].slab >> 3, grp = p.s.r[c.cl].slab & 7;
  int slot = 2 - type, par = 1;
#pragma unroll 1
  for (int t = 0; t < n; t++) {
    const int tile = p.s.r[c.cl].tile[t] & 63;
    const CUtensorMap* m = &p.map_w[type * 2 + (tile >> 5)];
    const int n0 = (tile & 31) * 128 + c.rank * 64;
    const int ptile = p.s.r[c.cl].tile[t + PF1 < n ? t + PF1 : t];
    const CUtensorMap* pm = &p.map_w[type * 2 + ((ptile >> 5) & 1)];
    if (t == 7 && (c.phases & 16)) flag_wait<true>(F_GATE, 256);
#pragma unroll 1
    for (int kb = (t == 0) - type; kb < 8; kb++) {
      if (t == 0) {
        mbar_wait(c.bar + (B_P1E + slot) * 8, par);
        mbar_expect(c.bar + (B_P1F + slot) * 8, 16384);
        tma2d(c.sm + SM_RING + slot * 16384, &p.map_a[type], kb * 64, grp * 256 + c.rank * 128, c.bar + (B_P1F + slot) * 8);
        if (++slot == 10) { slot = 0; par ^= 1; }
      }
      mbar_wait(c.bar + (B_P1E + slot) * 8, par);
      mbar_expect(c.bar + (B_P1F + slot) * 8, 16384);
      tma2d_mc(c.sm + SM_RING + slot * 16384 + c.rank * 8192, m, n0, kb < 0 ? 512 : kb * 64, c.bar + (B_P1F + slot) * 8);
      if (t == 0 && kb == 1) PROF(2, 61);
      if (t == 0 && kb == 3) PROF(2, 62);
      if (t + PF1 < n && t > 0 && ((ptile & 64) || ((ptile & 128) && ((kb ^ grp) & PFM) == 0))) tma2d_prefetch(pm, (ptile & 31) * 128 + c.rank * 64, kb < 0 ? 512 : kb * 64);
      if (++slot == 10) { slot = 0; par ^= 1; }
    }
  }
}

__device__ __forceinline__ void p1_storer(const Params& p, const Ctx& c) {
  const int n = p.s.r[c.cl].n1;
  const int type = p.s.r[c.cl].slab >> 3, grp = p.s.r[c.cl].slab & 7;
  for (int i = 0; i < 2 * n; i++) {
    const int t = i >> 1, w = i & 1, b = w * 2 + 1;
    const int tile = p.s.r[c.cl].tile[t] & 63;
    mbar_wait(c.bar + (B_SF + b) * 8, t & 1);
    const uint32_t src = c.sm + SM_BUF + b * 16384;
    int f = (type ? F_Q : F_KV) + (tile & 31) * 8 + grp;
    if (type == 0) {
      const int prev = p.s.prev[tile & 31][grp];
      if (prev != 255 && w == 0) {
        if (grp >= 2) flag_wait<false>(F_RD + prev * 8 + grp, 8 - grp);
        else flag_wait<false>(F_CTX + max(c.lane & 7, grp) * 64 + prev, 4);
      }
      uint8_t* dst = g_KV + (size_t)(((tile & 32) + p.s.slot[tile & 31][grp]) * 16 + grp * 2 + c.rank) * 32768 + w * 8192;
      bulk_store(dst, src, 8192);
      bulk_store(dst + 16384, src + 8192, 8192);
    } else if (tile < 32) {
      bulk_store(g_Q + (size_t)(tile * 32 + grp * 4 + c.rank * 2 + w) * 16384, src, 16384);
    } else {
      tma3d_store(&p.map_t[2], src, 8 + (grp * 4 + c.rank * 2 + w) * 32, 0, (tile - 32) * 64);
      f = F_QKVA + grp * 4 + ((0xE4390900u >> (2 * (tile - 30))) & 3);
    }
    BULK_COMMIT();
    BULK_WAIT(0);
    mbar_arrive_one(c.bar + (B_SE + b) * 8);
    flag_add_rx(f);
  }
}

__device__ __forceinline__ int p2_buf(int w, int i) { return w * 2 + (i & 1); }
__device__ __forceinline__ int p2_blk(int rank, int w, int i) { return ((i ^ w) & 1) == 0 ? 3 - rank : rank; }

template <int N>
__device__ __forceinline__ void row_max(const float (&s)[N], float& m0, float& m1) {
  float a0 = fmaxf(s[0], s[1]), a1 = fmaxf(s[2], s[3]);
#pragma unroll
  for (int i = 1; i < N / 4; i++) {
    m0 = fmaxf(m0, s[4 * i]); a0 = fmaxf(a0, s[4 * i + 1]);
    m1 = fmaxf(m1, s[4 * i + 2]); a1 = fmaxf(a1, s[4 * i + 3]);
  }
  m0 = fmaxf(m0, a0); m1 = fmaxf(m1, a1);
  m0 = fmaxf(m0, __shfl_xor_sync(0xffffffffu, m0, 1));
  m1 = fmaxf(m1, __shfl_xor_sync(0xffffffffu, m1, 1));
  m0 = fmaxf(m0, __shfl_xor_sync(0xffffffffu, m0, 2));
  m1 = fmaxf(m1, __shfl_xor_sync(0xffffffffu, m1, 2));
}
template <bool SUB, int N>
__device__ __forceinline__ void row_exp(const float (&s)[N], uint32_t (&P)[32], float m0, float m1, float& t0, float& t1) {
  float u0 = 0.f, u1 = 0.f;
  t0 = t1 = 0.f;
#pragma unroll
  for (int i = 0; i < N / 4; i++) {
    const float e0 = ex2(SUB ? s[4 * i] - m0 : s[4 * i]), e1 = ex2(SUB ? s[4 * i + 1] - m0 : s[4 * i + 1]);
    const float e2 = ex2(SUB ? s[4 * i + 2] - m1 : s[4 * i + 2]), e3 = ex2(SUB ? s[4 * i + 3] - m1 : s[4 * i + 3]);
    if (i == 0) { t0 = e0; u0 = e1; t1 = e2; u1 = e3; }
    else { t0 += e0; u0 += e1; t1 += e2; u1 += e3; }
    P[2 * i] = pack_bf16(e0, e1);
    P[2 * i + 1] = pack_bf16(e2, e3);
  }
#pragma unroll
  for (int i = N / 2; i < 32; i++) P[i] = 0;
  pin(P);
  t0 += u0; t1 += u1;
}
template <int N>
__device__ __forceinline__ void causal_mask(float (&s)[N], int thr) {
#pragma unroll
  for (int i = 0; i < 8; i++) {
    if (8 * i > thr) s[N - 32 + 4 * i] = -INFINITY;
    if (8 * i + 1 > thr) s[N - 32 + 4 * i + 1] = -INFINITY;
    if (8 * i - 8 > thr) s[N - 32 + 4 * i + 2] = -INFINITY;
    if (8 * i - 7 > thr) s[N - 32 + 4 * i + 3] = -INFINITY;
  }
}
__device__ __forceinline__ void issue_qk(float (&s)[32], uint32_t qd, uint32_t kd) {
  WG_FENCE();
#pragma unroll
  for (int kk = 0; kk < 8; kk++) wgmma_ss64<0>(s, qd + (kk >> 2) * 512 + (kk & 3) * 2, kd + (kk >> 2) * 1024 + (kk & 3) * 2, kk != 0);
  WG_COMMIT();
}
__device__ __forceinline__ void issue_qk(float (&s)[64], uint32_t qd, uint32_t kd) {
  WG_FENCE();
#pragma unroll
  for (int kk = 0; kk < 8; kk++) wgmma_ss128<0>(s, qd + (kk >> 2) * 512 + (kk & 3) * 2, kd + (kk >> 2) * 1024 + (kk & 3) * 2, kk != 0);
  WG_COMMIT();
}
template <int NK>
__device__ __forceinline__ void issue_pv(float (&o)[64], const uint32_t (&P)[32], uint32_t vd, int acc) {
  WG_FENCE();
#pragma unroll
  for (int kk = 0; kk < NK; kk++) wgmma_rs128<1>(o, P[4 * kk], P[4 * kk + 1], P[4 * kk + 2], P[4 * kk + 3], vd + kk * 128, kk != 0 ? 1 : acc);
  WG_COMMIT();
}
__device__ __forceinline__ void stage_done(const Ctx& c, int b) {
  FENCE_ASYNC_SMEM();
  __syncwarp();
  if (c.lane == 0) mbar_arrive(c.bar + (B_SF + b) * 8);
}
__device__ __forceinline__ void p2_epilogue(const float (&o)[64], float s0, float s1, const Ctx& c, int b) {
  stage_tile(o, c.sm + SM_BUF + b * 16384, c, s0, s1);
  stage_done(c, b);
}

struct P2State {
  float m0, m1, l0, l1;
  bool shift;
  float e0, e1;
  int ks;
  int wi, ai;
  uint32_t wb, ab;
  uint32_t qd;
};
#define PROFZ()
__device__ __forceinline__ int wrap5(int q) { return q >= 5 ? q - 5 : q; }
__device__ __forceinline__ void turn_wait(uint32_t ring, int i) { mbar_wait(ring + (i & 3) * 8, (i >> 2) & 1); }
__device__ __forceinline__ void turn_pass(const Ctx& c, uint32_t ring, int i) { if (c.lane == 0) mbar_arrive(ring + (i & 3) * 8); }
__device__ __forceinline__ void p2_scales(P2State& z) {
  float l0 = z.l0, l1 = z.l1;
  l0 += __shfl_xor_sync(0xffffffffu, l0, 1);
  l1 += __shfl_xor_sync(0xffffffffu, l1, 1);
  l0 += __shfl_xor_sync(0xffffffffu, l0, 2);
  l1 += __shfl_xor_sync(0xffffffffu, l1, 2);
  asm("rcp.approx.ftz.f32 %0, %1;" : "=f"(z.e0) : "f"(l0));
  asm("rcp.approx.ftz.f32 %0, %1;" : "=f"(z.e1) : "f"(l1));
}
template <int N>
__device__ __forceinline__ void p2_first(const Ctx& c, P2State& z, float (&o)[64], uint32_t (&Pc)[32], uint32_t (&Pn)[32],
                                         int ks, int vs, int cnt, int acc) {
  float s[N] = {};
  issue_qk(s, z.qd, desc_lo(c.sm + SM_RING, 16) + ks * 2048);
  if (vs >= 0) {
    p2_scales(z);
    issue_pv<8>(o, Pc, desc_lo(c.sm + SM_RING, 16384) + vs * 2048, acc);
  } else {
    WG_COMMIT();
  }
  mbar_expect(z.ab + (z.ai++ & 3) * 8, cnt == 1 ? 8192 : 0);
  PROFZ();
  WG_WAIT(1);
  PROFZ();
  pin(s);
  release(c, B_P2E + ks, cnt);
  causal_mask(s, c.warp * 16 + (c.lane >> 2) - 2 * (c.lane & 3));
  z.m0 = z.m1 = 0.f;
  row_exp<false>(s, Pn, 0.f, 0.f, z.l0, z.l1);
  z.shift = __any_sync(0xffffffffu, !(z.l0 + z.l1 <= SM_HI) || ((c.lane & 3) == 0 && !(fminf(z.l0, z.l1) >= SM_LO)));
  if (__builtin_expect(z.shift, 0)) {
    z.m0 = z.m1 = -INFINITY;
    row_max(s, z.m0, z.m1);
    row_exp<true>(s, Pn, z.m0, z.m1, z.l0, z.l1);
  }
  WG_WAIT(0);
  pin(o);
  if (vs >= 0) release(c, B_P2E + vs, 1);
}

template <bool SECOND>
__device__ __forceinline__ void p2_turn(const Ctx& c, P2State& z, float (&o)[64], uint32_t (&Pc)[32], uint32_t (&Pn)[32],
                                        int eb = -1, bool half = false, int vcnt = 1) {
  float s[64] = {};
  const int ks = z.ks, vs = wrap5(ks + 1);
  PROFZ();
  turn_wait(z.wb, z.wi++);
  PROFZ();
  issue_qk(s, z.qd, desc_lo(c.sm + SM_RING, 16) + ks * 2048);
  const uint32_t vd = desc_lo(c.sm + SM_RING, 16384) + vs * 2048;
  if (SECOND) {
    if (eb >= 0) stage_tile(o, c.sm + SM_BUF + eb * 16384, c, z.e0, z.e1);
    if (half) issue_pv<4>(o, Pc, vd, 0); else issue_pv<8>(o, Pc, vd, 0);
  } else {
    issue_pv<8>(o, Pc, vd, 1);
  }
  turn_pass(c, z.ab, z.ai++);
  if (SECOND) { if (eb >= 0) stage_done(c, eb); }
  PROFZ();
  z.ks = wrap5(ks + 2);
  WG_WAIT(1);
  PROFZ();
  pin(s);
  release(c, B_P2E + ks, 1);
  float t0, t1, a0 = 1.f, a1 = 1.f;
  row_exp<false>(s, Pn, 0.f, 0.f, t0, t1);
  z.shift = __any_sync(0xffffffffu, z.shift || !(t0 + t1 <= SM_HI));
  const bool redo = z.shift;
  if (__builtin_expect(redo, 0)) {
    float n0 = z.m0, n1 = z.m1;
    row_max(s, n0, n1);
    a0 = ex2(z.m0 - n0); a1 = ex2(z.m1 - n1);
    z.m0 = n0; z.m1 = n1;
    z.l0 *= a0; z.l1 *= a1;
    row_exp<true>(s, Pn, z.m0, z.m1, t0, t1);
  }
  WG_WAIT(0);
  pin(o);
  release(c, B_P2E + vs, vcnt);
  if (__builtin_expect(redo, 0)) {
#pragma unroll
    for (int i = 0; i < 16; i++) { o[4 * i] *= a0; o[4 * i + 1] *= a0; o[4 * i + 2] *= a1; o[4 * i + 3] *= a1; }
  }
  z.l0 += t0; z.l1 += t1;
}
__device__ __forceinline__ void copy_p(uint32_t (&d)[32], const uint32_t (&s)[32], int zero) {
#pragma unroll
  for (int i = 0; i < 32; i++) asm volatile("add.s32 %0, %1, %2;" : "=r"(d[i]) : "r"(s[i]), "r"(zero));
}

__device__ __forceinline__ void p2_consumer(const Params& p, const Ctx& c, int rot) {
  const int nit = p.s.r[c.cl].n2;
  const uint32_t fring = c.bar + B_P2F * 8, oring = c.bar + B_ORD * 8;
  float o[64] = {};
  uint32_t Pa[32] = {}, Pb[32] = {};
  P2State z;
  z.e0 = z.e1 = z.l0 = z.l1 = 0.f; z.ks = rot; z.shift = false;
  int acc = 0, n = 0;
  for (int it = 0; it < nit; it++) {
    const int j = p.s.r[c.cl].item[it] & 7, blk = p2_blk(c.rank, c.wg, it);
    const int lng = ((it ^ c.wg) & 1) ^ 1;
    z.qd = desc_lo(c.sm + SM_BUF, 16) + p2_buf(c.wg, it) * 1024;
    if (lng) { z.wb = oring; z.wi = n - it; z.ab = fring; z.ai = n + 1; }
    else { z.wb = fring; z.wi = n + 2; z.ab = oring; z.ai = n - it; }
    PROFZ();
    mbar_wait(c.bar + (B_QF + p2_buf(c.wg, it)) * 8, (it >> 1) & 1);
    turn_wait(fring, n + 1 - lng);
    PROFZ();
    const int vs = it ? wrap5(z.ks + 1) : -1, ks = lng ? z.ks : wrap5(z.ks + (it ? 2 : 1));
    if (blk & 1) p2_first<64>(c, z, o, Pa, Pb, ks, vs, 1 + lng, acc);
    else p2_first<32>(c, z, o, Pa, Pb, ks, vs, 1 + lng, acc);
    z.ks = wrap5(ks + (it == 0 && lng ? 1 : 2));
    PROF(c.wg, 24 + it);
    n += 2 * j + 2;
    int left = 2 * j + lng;
    acc = left != 0;
    if (left == 0) { copy_p(Pa, Pb, p.zero); continue; }
    p2_turn<true>(c, z, o, Pb, Pa, it > 0 ? p2_buf(c.wg, it - 1) : -1, !(blk & 1), 1 + lng);
    while (--left > 0) {
      p2_turn<false>(c, z, o, Pa, Pb);
      if (--left == 0) { copy_p(Pa, Pb, p.zero); break; }
      p2_turn<false>(c, z, o, Pb, Pa);
    }
  }
  {
    if (!acc && nit > 1) p2_epilogue(o, z.e0, z.e1, c, p2_buf(c.wg, nit));
    turn_wait(z.wb, z.wi);
    issue_pv<8>(o, Pa, desc_lo(c.sm + SM_RING, 16384) + z.ks * 2048, acc);
    if (((nit - 1) ^ c.wg) & 1) turn_pass(c, z.ab, z.ai);
    p2_scales(z);
    WG_WAIT(0);
    pin(o);
    release(c, B_P2E + z.ks);
    p2_epilogue(o, z.e0, z.e1, c, p2_buf(c.wg, nit - 1));
    PROF(c.wg, 24 + nit);
  }
}

__device__ __forceinline__ void p2_load_q(const Params& p, const Ctx& c, int it, int w) {
  const int item = p.s.r[c.cl].item[it], h = item >> 3, j = item & 7, b = p2_buf(w, it);
  mbar_expect(c.bar + (B_QF + b) * 8, 16384);
  bulk_load(c.sm + SM_BUF + b * 16384, g_Q + (size_t)(h * 32 + j * 4 + p2_blk(c.rank, w, it)) * 16384, 16384, c.bar + (B_QF + b) * 8, POL(4));
}
__device__ __forceinline__ void wait_p1_free(const Ctx& c, int u1, int s) {
  mbar_wait(c.bar + (B_P1E + 2 * s) * 8, ((u1 - 1 - 2 * s) / 10) & 1);
  mbar_wait(c.bar + (B_P1E + 2 * s + 1) * 8, ((u1 - 2 - 2 * s) / 10) & 1);
}
__device__ __forceinline__ void p2_producer(const Params& p, const Ctx& c, int u1, int rot) {
  const int nit = p.s.r[c.cl].n2;
  int slot = rot, cnt = 0, par = 1, n = 0;
  const uint8_t* pv = nullptr;
  bool pl = false;
  auto load = [&](const uint8_t* src, int expect, uint32_t fb, bool last) {
    if (cnt < 5) {
      if (u1) {
        wait_p1_free(c, u1, slot);
        if (cnt == 0) p2_load_q(p, c, 0, 1);
      }
      cnt++;
    } else {
      if (slot == rot) par ^= 1;
      mbar_wait(c.bar + (B_P2E + slot) * 8, par);
    }
    if (expect) mbar_expect(fb, expect);
    bulk_load_mc(c.sm + SM_RING + slot * 32768 + c.rank * 16384, src, 16384, fb, last ? POL(5) : L2_NORMAL);
    slot = wrap5(slot + 1);
  };
  for (int it = 0; it < nit; it++) {
    const int item = p.s.r[c.cl].item[it], h = item >> 3, j = item & 7;
    if (it == 1 && (c.phases & 16) && p.s.r[c.cl].n1 < 8) flag_wait<true>(F_GATE, 256);
    uint32_t ready = (c.phases & 16) ? 0u : 255u;
    if (it == 0) { if (c.phases & 16) flag_wait<false>(F_Q + item, 4); mbar_wait(c.bar + B_LAD * 8, 0); p2_load_q(p, c, 0, 0); if (!u1) p2_load_q(p, c, 0, 1); }
    for (int t = 2 * j + 1; t >= 0; t--) {
      mask_wait(ready, t >> 1, F_KV + h * 8 + (c.lane & 7), 8);
      const uint8_t* k = g_KV + (size_t)(p.s.slot[h][t >> 1] * 16 + t) * 32768 + c.rank * 16384;
      const uint32_t fb = c.bar + (B_P2F + (n & 3)) * 8;
      const bool last = (p.s.r[c.cl].last[it] >> (t >> 1)) & 1;
      load(k, pv && t != 2 * j ? 65536 : 32768, fb, last);
      if (!(t & 1) && t + 4 <= 2 * j && c.rank == 0) flag_add_rx(F_RD + h * 8 + (t >> 1) + 2);
      if (pv) load(pv, 0, t != 2 * j ? fb : c.bar + (B_ORD + ((n - 1 - it) & 3)) * 8, pl);
      pl = last;
      pv = k + (size_t)NH * 16 * 32768;
      n++;
    }
  }
  load(pv, 32768, c.bar + (B_P2F + (n & 3)) * 8, pl);
}

__device__ __forceinline__ void p2_storer(const Params& p, const Ctx& c, int sfpar) {
  const int nit = p.s.r[c.cl].n2;
  auto load_q = [&](int it, int w) {
    if (c.phases & 16) flag_wait<false>(F_Q + p.s.r[c.cl].item[it], 4);
    p2_load_q(p, c, it, w);
  };
  if (nit > 1) {
    load_q(1, 1); p2_load_q(p, c, 1, 0); }
  for (int i = 0; i < 2 * nit; i++) {
    const int it = i >> 1, w = (it ^ i ^ 1) & 1, b = p2_buf(w, it);
    const int item = p.s.r[c.cl].item[it], h = item >> 3, j = item & 7;
    mbar_wait(c.bar + (B_SF + b) * 8, (sfpar >> b) & 1);
    sfpar ^= 1 << b;
    bulk_store(g_Q + (size_t)(h * 32 + j * 4 + p2_blk(c.rank, w, it)) * 16384, c.sm + SM_BUF + b * 16384, 16384, POL(1));
    BULK_COMMIT();
    BULK_WAIT(0);
    flag_add_rx(F_CTX + j * 64 + h);
    if ((i & 1) && it + 2 < nit) { load_q(it + 2, w); p2_load_q(p, c, it + 2, w ^ 1); }
  }
  release(c, B_DONE);
}

__device__ __forceinline__ int p3_pos(int i, int x) { return i < 4 ? (i + x) & 3 : 4; }
__device__ __forceinline__ void p3_consumer(const Params& p, const Ctx& c, int x) {
  const bool first = p.s.r[c.cl].p3 >= 24;
  const int tile = p.s.r[c.cl].p3 - (first ? 24 : 0), j = tile / 3, nt = tile - 3 * j;
  const int na = first ? 9 : 0, nb = first ? 2 * p.s.nh[tile] : 64 - 2 * p.s.nh[tile];
  const uint32_t ad = desc_lo(c.sm + SM_RING + c.wg * 8192, 16), bd = desc_lo(c.sm + SM_RING + 16384, 4096);
  float acc[96] = {};
  int slot = 0, par = 0, prev = 0;
  float g0 = 0.f, g1 = 0.f;
  const int hold = c.wg && LAG ? na + nb - LAG : -1, pass = c.wg || !LAG ? -1 : na + nb - 1;
#pragma unroll 1
  for (int kb = 0; kb < nb; kb++) {
    if (kb == hold) bar_sync(6, 256);
    mbar_wait(c.bar + (B_P3F + slot) * 8, par);
    if (kb == 0) PROF(c.wg, 39);
    WG_FENCE();
#pragma unroll
    for (int kk = 0; kk < 4; kk++) wgmma_ss192<1>(acc, ad + p3_pos(slot, x) * 2560 + kk * 2, bd + p3_pos(slot, x) * 2560 + (kk >> 1) * 768 + (kk & 1) * 128, kk != 0 ? 1 : kb != 0);
    WG_COMMIT();
    if (kb == pass) bar_arrive(6, 256);
    WG_WAIT(1);
    if (kb > 0) release(c, B_P3E + prev);
    else {
      const float* g = g_gate + j * 256 + c.rank * 128 + c.wg * 64 + c.warp * 16 + (c.lane >> 2);
      g0 = __ldcg(g); g1 = __ldcg(g + 8);
    }
    prev = slot;
    if (++slot == 5) { slot = 0; par ^= 1; }
  }
  WG_WAIT(0);
  pin(acc);
  g0 = 1.f - g0; g1 = 1.f - g1;
#pragma unroll
  for (int i = 0; i < 24; i++) { acc[4 * i] *= g0; acc[4 * i + 1] *= g0; acc[4 * i + 2] *= g1; acc[4 * i + 3] *= g1; }
#pragma unroll 1
  for (int kb = nb; kb < nb + na; kb++) {
    if (kb == hold) bar_sync(6, 256);
    mbar_wait(c.bar + (B_P3F + slot) * 8, par);
    if (kb == 0) PROF(c.wg, 39);
    WG_FENCE();
#pragma unroll
    for (int kk = 0; kk < 4; kk++) wgmma_ss192<1, 1>(acc, ad + p3_pos(slot, x) * 2560 + kk * 128, bd + p3_pos(slot, x) * 2560 + (kk >> 1) * 768 + (kk & 1) * 128, 1);
    WG_COMMIT();
    if (kb == pass) bar_arrive(6, 256);
    WG_WAIT(1);
    if (kb > 0) release(c, B_P3E + prev);
    prev = slot;
    if (++slot == 5) { slot = 0; par ^= 1; }
  }
  WG_WAIT(0);
  pin(acc);
  PROF(c.wg, 40);
  if (first) bar_sync(4 + c.wg, 128);
  mbar_wait(c.bar + B_OUT * 8, 0);
  const int row = (c.lane & 7) + ((c.lane >> 3) & 1) * 8;
  const uint32_t wbase = c.sm + SM_RING + c.wg * 8192 + c.warp * 2048;
  const uint32_t base = wbase + row * 128 + (((c.lane >> 4) ^ (row & 7)) << 4);
#pragma unroll
  for (int i = 0; i < 12; i++) {
    stsm4((base ^ ((i & 3) << 5)) + (i >> 2) * 40960, pack_bf16(acc[8 * i], acc[8 * i + 1]), pack_bf16(acc[8 * i + 2], acc[8 * i + 3]),
          pack_bf16(acc[8 * i + 4], acc[8 * i + 5]), pack_bf16(acc[8 * i + 6], acc[8 * i + 7]));
    if ((i & 3) == 3) {
      FENCE_ASYNC_SMEM();
      bar_sync(4 + c.wg, 128);
      if (c.warp == (i >> 2)) tma2d_add(&p.map_out, c.sm + SM_RING + c.wg * 8192 + c.warp * 40960, nt * 192 + c.warp * 64, j * 256 + c.rank * 128 + c.wg * 64);
    }
  }
  BULK_COMMIT();
  PROF(c.wg, 43);
  BULK_WAIT_READ(0);
  PROF(c.wg, 44);
}

__device__ __forceinline__ void p3_producer(const Params& p, const Ctx& c, int u1, int u2, int rot, int x) {
  const bool first = p.s.r[c.cl].p3 >= 24;
  const int tile = p.s.r[c.cl].p3 - (first ? 24 : 0), j = tile / 3, nt = tile - 3 * j;
  int slot = 0, par = 1, cnt = 0;
  auto wait_free = [&](int s) {
    const int f = wrap5(s + 5 - rot);
    if (f < u2) mbar_wait(c.bar + (B_P2E + s) * 8, ((u2 - 1 - f) / 5) & 1);
    else if (u1) wait_p1_free(c, u1, s);
  };
  asm volatile(ELECT("prefetch.tensormap [%0];") ::"l"(&p.map_o[0]) : "memory");
  asm volatile(ELECT("prefetch.tensormap [%0];") ::"l"(&p.map_out) : "memory");
  if ((c.phases & 16) && p.s.r[c.cl].n1 < 8 && p.s.r[c.cl].n2 < 2) flag_wait<true>(F_GATE, 256);
  uint32_t ready = (c.phases & 16) ? 0u : ~0u;
  const int q1 = first ? p.s.nh[tile] : 31;
  for (int q = first ? 0 : p.s.nh[tile]; q <= q1; q++) {
    const bool brA = first && q == q1;
    const int g = brA ? 32 : p.s.p3_order[j][q];
    if (brA) { if (c.phases & 16) flag_wait<false>(F_CTX + j * 64 + 32, 16); }
    else mask_wait(ready, g, F_CTX + j * 64 + c.lane, 4);
    const int nk = brA ? 9 : 2, k0 = (brA ? 0 : g * 128) + c.rank * 32;
    const uint8_t* a = brA ? g_oA + (j * 4 + c.rank * 2) * 73728 : g_Q + (size_t)(g * 32 + j * 4 + c.rank * 2) * 16384;
    const CUtensorMap* m = &p.map_o[brA];
    for (int i = 0; i < nk; i++) {
      const uint32_t st = c.sm + SM_RING + p3_pos(slot, x) * 40960, fb = c.bar + (B_P3F + slot) * 8;
      if (cnt < 4) { wait_free(p3_pos(cnt, x)); wait_free(p3_pos(cnt, x) + 1); }
      else if (cnt == 4) mbar_wait(c.bar + B_DONE * 8, 0);
      else mbar_wait(c.bar + (B_P3E + slot) * 8, par);
      cnt++;
      mbar_expect(fb, 40960);
      bulk_load(st, a + i * 8192, 8192, fb, POL(3));
      bulk_load(st + 8192, a + (nk + i) * 8192, 8192, fb, POL(3));
      tma3d_mc(st + 16384 + c.rank * 12288, m, 0, k0 + i * 64, nt * 3, fb);
      if (++slot == 5) { slot = 0; par ^= 1; }
    }
  }
}

__device__ __forceinline__ float bf_lo(uint32_t w) { return __uint_as_float(w << 16); }
__device__ __forceinline__ float bf_hi(uint32_t w) { return __uint_as_float(w & 0xffff0000u); }

__device__ __forceinline__ void gate_rows(const Params& p, int row0, int lane) {
  const uint4* x = reinterpret_cast<const uint4*>(p.x + (size_t)(row0 + (lane >> 2)) * DM) + (lane & 3);
  const uint4* w = reinterpret_cast<const uint4*>(p.gate_w) + (lane & 3);
  float a = 0.f;
#pragma unroll 1
  for (int b = 0; b < 3; b++) {
    uint4 u[6];
#pragma unroll
    for (int i = 0; i < 6; i++) u[i] = __ldg(x + (b * 6 + i) * 4);
#pragma unroll
    for (int i = 0; i < 6; i++) {
      const uint4 v = __ldg(w + (b * 6 + i) * 4);
      a = fmaf(bf_lo(u[i].x), bf_lo(v.x), a); a = fmaf(bf_hi(u[i].x), bf_hi(v.x), a);
      a = fmaf(bf_lo(u[i].y), bf_lo(v.y), a); a = fmaf(bf_hi(u[i].y), bf_hi(v.y), a);
      a = fmaf(bf_lo(u[i].z), bf_lo(v.z), a); a = fmaf(bf_hi(u[i].z), bf_hi(v.z), a);
      a = fmaf(bf_lo(u[i].w), bf_lo(v.w), a); a = fmaf(bf_hi(u[i].w), bf_hi(v.w), a);
    }
  }
  a += __shfl_xor_sync(0xffffffffu, a, 1);
  a += __shfl_xor_sync(0xffffffffu, a, 2);
  if ((lane & 3) == 0) g_gate[row0 + (lane >> 2)] = 1.f / (1.f + __expf(-a));
}

__device__ __forceinline__ void lds10(uint32_t (&k)[10], uint32_t a) {
  asm volatile("ld.shared.v2.u32 {%0, %1}, [%10];\nld.shared.v2.u32 {%2, %3}, [%10+8];\nld.shared.v2.u32 {%4, %5}, [%10+16];\n"
               "ld.shared.v2.u32 {%6, %7}, [%10+24];\nld.shared.v2.u32 {%8, %9}, [%10+32];"
               : "=r"(k[0]), "=r"(k[1]), "=r"(k[2]), "=r"(k[3]), "=r"(k[4]), "=r"(k[5]), "=r"(k[6]), "=r"(k[7]), "=r"(k[8]), "=r"(k[9]) : "r"(a));
}
__device__ __forceinline__ void local_attn(const Params& p, const Ctx& c, int rb, int hs) {
  const int lane = c.lane, grp = rb >> 2, par = lane >> 4, i0 = 2 * (lane & 15);
  const uint32_t buf = c.sm + SM_BUF + (c.warp - 2) * 8192, bqk = c.bar + (B_LA + (c.warp - 2) * 2) * 8, bv = bqk + 8;
  const uint32_t mine = buf + 2304 + par * 160 + i0 * 4;
  const bool flags = c.phases & 16;
  auto fetch_qk = [&](int i) {
    if (flags && !(i & 1)) {
      const int q = i >> 1;
      const int tgt = q == 0 ? 24 : q == 3 ? 8 : 12;
      flag_wait<false>(F_QKVA + (grp - (grp > 0 && (rb & 3) == 0 ? par : 0)) * 4 + q, tgt);
    }
    mbar_expect(bqk, 5184);
    tma3d(buf, &p.map_t[0], rb * 32 + 8, 0, 9 * (4 * i + hs), bqk, POL(2));
    tma3d(buf + 2304, &p.map_t[1], rb * 32, 0, 288 + 9 * (4 * i + hs), bqk, POL(2));
  };
  auto fetch_v = [&](int i) { mbar_expect(bv, 2880); tma3d(buf + 5248, &p.map_t[1], rb * 32, 0, 576 + 9 * (4 * i + hs), bv, POL(2)); };
  fetch_qk(0);
  if (flags) flag_wait<true>(F_GATE, 256);
#pragma unroll 1
  for (int q = 0; q < 8; q++) {
    fetch_v(q);
    float a[8], b[8];
#pragma unroll
    for (int w = 0; w < 8; w++) a[w] = b[w] = 0.f;
    mbar_wait(bqk, q & 1);
    PROFB(1 + 2 * q);
#pragma unroll 1
    for (int j = 0; j < 9; j++) {
      uint32_t x, y, k[10];
      asm volatile("ld.shared.v2.u32 {%0, %1}, [%2];" : "=r"(x), "=r"(y) : "r"(buf + lane * 8 + j * 256));
      lds10(k, mine + j * 320);
      const float xl = bf_lo(x), xh = bf_hi(x), yl = bf_lo(y), yh = bf_hi(y);
#pragma unroll
      for (int m = 1; m < 10; m++) {
        const float kl = bf_lo(k[m]), kh = bf_hi(k[m]);
        if (m < 9) a[8 - m] = fmaf(xl, kl, fmaf(xh, kh, a[8 - m]));
        if (m > 1) b[9 - m] = fmaf(yl, kl, fmaf(yh, kh, b[9 - m]));
      }
    }
    __syncwarp();
    if (q < 7) fetch_qk(q + 1);
    constexpr float SC = 0.23570226039551584f * 1.4426950408889634f;
    const float* gp = g_gate + rb * 64 + 2 * i0 + par;
    const float ga = __ldcg(gp), gb = __ldcg(gp + 2);
    float ma = a[0], mb = b[0];
#pragma unroll
    for (int w = 1; w < 8; w++) {
      if (rb == 0) {
        if (i0 < w) a[w] = -INFINITY;
        if (i0 + 1 < w) b[w] = -INFINITY;
      }
      ma = fmaxf(ma, a[w]); mb = fmaxf(mb, b[w]);
    }
    float la = 0.f, lb = 0.f;
#pragma unroll
    for (int w = 0; w < 8; w++) {
      a[w] = ex2((a[w] - ma) * SC); b[w] = ex2((b[w] - mb) * SC);
      la += a[w]; lb += b[w];
    }
    la = __fdividef(ga, la); lb = __fdividef(gb, lb);
#pragma unroll
    for (int w = 0; w < 8; w++) { a[w] *= la; b[w] *= lb; }
    uint8_t* dst = g_oA + rb * 73728 + ((i0 & 2) + par) * 4;
    mbar_wait(bv, q & 1);
#pragma unroll 1
    for (int j = 0; j < 9; j++) {
      uint32_t v[10];
      lds10(v, mine + 2944 + j * 320);
      float a0 = 0.f, a1 = 0.f, b0 = 0.f, b1 = 0.f;
#pragma unroll
      for (int m = 1; m < 10; m++) {
        const float vl = bf_lo(v[m]), vh = bf_hi(v[m]);
        if (m < 9) { a0 = fmaf(a[8 - m], vl, a0); a1 = fmaf(a[8 - m], vh, a1); }
        if (m > 1) { b0 = fmaf(b[9 - m], vl, b0); b1 = fmaf(b[9 - m], vh, b1); }
      }
      const uint32_t wa = pack_bf16(a0, a1), wb = pack_bf16(b0, b1);
      const uint32_t got = __shfl_xor_sync(0xffffffffu, par ? wa : wb, 16);
      const uint32_t r0 = par ? got : wa, r1 = par ? wb : got;
      const int col = 18 * (4 * q + hs) + 2 * j, o = col * 128 + ((((i0 >> 2) ^ col) & 7) << 4);
      *reinterpret_cast<uint32_t*>(dst + o) = __byte_perm(r0, r1, 0x5410);
      *reinterpret_cast<uint32_t*>(dst + ((o + 128) ^ 16)) = __byte_perm(r0, r1, 0x7632);
    }
    __syncwarp();
    PROFB(2 + 2 * q);
  }
  mbar_arrive_one(c.bar + B_LAD * 8);
  flag_add(F_CTX + grp * 64 + 32);
}

__global__ void __cluster_dims__(2, 1, 1) __launch_bounds__(384, 1) fused_kernel(const __grid_constant__ Params p) {
  extern __shared__ uint8_t smem_raw[];
  Ctx c;
  c.sm = ((uint32_t)__cvta_generic_to_shared(smem_raw) + 1023u) & ~1023u;
  c.bar = c.sm + SM_BAR;
  c.lane = threadIdx.x & 31;
  const int wid = __shfl_sync(0xffffffffu, threadIdx.x >> 5, 0);
  if (wid < 6) asm volatile("prefetch.tensormap [%0];" ::"l"(&p.map_a[0] + wid) : "memory");
  c.wg = wid >> 2;
  c.warp = wid & 3;
  PROF(c.wg, 0);
  PROFG(61);
  c.cl = (blockIdx.x + (wid >> 4)) >> 1;
  c.rank = blockIdx.x & 1;
  c.rbar = mapa(c.bar, c.lane & 1);
  {
    const int w = wid, cnt = (((int)(B_CNT >> (4 * w)) - 1) & 15) + 1;
    if (w < 11) {
#pragma unroll
      for (int i = 0; i < 8; i++) asm volatile("mbarrier.init.shared::cta.b64 [%0], %1;" ::"r"(c.bar + w * 64 + i * 8), "r"(cnt));
    }
    asm volatile("fence.mbarrier_init.release.cluster;" ::: "memory");
  }
  if (c.wg == 2) PROF(2, 56);
  asm volatile("barrier.cluster.arrive.relaxed;" ::: "memory");
  c.phases = p.s.r[c.cl].phases;
  const bool do1 = p.s.r[c.cl].n1 > 0, do2 = p.s.r[c.cl].n2 > 0, do3 = p.s.r[c.cl].p3 != 255;
  if (do1 && c.wg == 2 && c.warp == 0) {
    const int type = p.s.r[c.cl].slab >> 3;
    PROF(2, 57);
    FENCE_ASYNC_SMEM();
    mbar_expect(c.bar + B_P1F * 8, type ? 32768 : 16384);
    tma2d(type ? c.sm + SM_BUF + 32768 : c.sm + SM_RING, &p.map_a[type], type ? 512 : 0, (p.s.r[c.cl].slab & 7) * 256 + c.rank * 128, c.bar + B_P1F * 8);
    PROF(2, 58);
  }
  asm volatile("barrier.cluster.wait.acquire;" ::: "memory");
  if (c.wg == 2) PROF(2, 59);
  if (do1 && c.wg == 2 && c.warp == 0) {
    const int type = p.s.r[c.cl].slab >> 3, tile = p.s.r[c.cl].tile[0] & 63;
    if (!type) mbar_expect(c.bar + (B_P1F + 1) * 8, 16384);
    tma2d_mc(c.sm + SM_RING + (1 - type) * 16384 + c.rank * 8192, &p.map_w[type * 2 + (tile >> 5)], (tile & 31) * 128 + c.rank * 64, type ? 512 : 0, c.bar + (B_P1F + 1 - type) * 8);
  }

  if (c.wg < 2) {
    PROF(c.wg, 4);
    asm volatile("setmaxnreg.inc.sync.aligned.u32 224;");
    if (c.wg == 1) {
      if (do1) bar_arrive(ORDER, 256);
      if (c.lane == 0) mbar_arrive(c.bar + B_P2F * 8);
    }
    if (do1) p1_consumer(p, c);
    if (do2) p2_consumer(p, c, p.s.r[c.cl].rot);
    if (do3) p3_consumer(p, c, p.s.r[c.cl].x3);
    PROF(c.wg, 63);
    PROFG(62);
    if (c.lane == 0) mbar_arrive(c.bar + B_FIN * 8);
    __syncwarp();
    cluster_sync();
  } else {
    asm volatile("setmaxnreg.dec.sync.aligned.u32 56;");
    if (c.warp == 0) {
      PROF(2, 60);
      if (do1) p1_producer(p, c);
      if (do2) p2_producer(p, c, p.s.r[c.cl].u1, p.s.r[c.cl].rot);
      if (do3) p3_producer(p, c, p.s.r[c.cl].u1, p.s.r[c.cl].u2, p.s.r[c.cl].rot, p.s.r[c.cl].x3);
    } else if (c.warp == 1) {
      int sfpar = 0;
      if (do1) {
        p1_storer(p, c);
        sfpar = (p.s.r[c.cl].n1 & 1) * 10;
      }
      if (do2) p2_storer(p, c, sfpar);
      else { mbar_wait(c.bar + B_LAD * 8, 0); release(c, B_DONE); }
      if (do3) {
        const int task = p.s.r[c.cl].p3;
        if (task >= 24) {
          const int j = (task - 24) / 3, nt = task - 24 - 3 * j;
          uint4* o = reinterpret_cast<uint4*>(p.out + (size_t)(j * 256 + c.rank * 128 + (c.lane >> 3)) * DM + nt * 192) + (c.lane & 7);
#pragma unroll 4
          for (int r = 0; r < 32; r++) o[r * 288] = o[r * 288 + 8] = o[r * 288 + 16] = make_uint4(0u, 0u, 0u, 0u);
          __syncwarp();
          flag_add(F_OUT + (task - 24) * 2 + c.rank);
        } else if (c.phases & 16) {
          flag_wait<false, 256>(F_OUT + task * 2 + c.rank, 1);
        }
        mbar_arrive_one(c.bar + B_OUT * 8);
      }
    } else {
      const int bw = blockIdx.x * 2 + (c.warp - 2);
      if ((c.phases & 1) && bw < 256) {
        gate_rows(p, bw * 8, c.lane);
        __syncwarp();
        flag_add(F_GATE);
      }
      if (p.s.r[c.cl].bg != 255) local_attn(p, c, p.s.r[c.cl].bg, bw & 3);
      else if (c.lane == 0) mbar_arrive(c.bar + B_LAD * 8);
    }
    __syncwarp();
    bar_sync(3, 128);
    if (c.warp == 0 && (c.phases & 4)) {
      int last = 0;
      if (c.lane == 0) { __threadfence(); last = atomicAdd(g_flags + F_DONE, 1) == 2 * NCL - 1; }
      if (__shfl_sync(0xffffffffu, last, 0)) for (int i = c.lane; i < F_NUM; i += 32) g_flags[i] = 0;
    }
    if (c.warp == 1) mbar_wait(c.bar + B_FIN * 8, 0);
    __syncwarp();
    cluster_sync();
  }
}

SCHED_DECL Sched k_sched = {
  {{0,30,3,255,0,{225,153,240,0,0,0,0,0,0,0,0},{0,0,0,0,0,0,0,0,0,0,0},{67,108,1,32,24,38,42,37,63,59,54,46,52,43,34,39,47,57,50,40,45,61,58,55,48,41,60,51,49,62}},
   {1,30,2,255,1,{224,139,0,0,0,0,0,0,0,0,0},{0,0,0,0,0,0,0,0,0,0,0},{67,32,1,44,6,10,24,5,31,27,22,14,20,11,15,2,7,18,25,8,13,29,23,9,26,16,28,19,17,30}},
   {2,30,1,42,2,{226,0,0,0,0,0,0,0,0,0,0},{0,0,0,0,0,0,0,0,0,0,0},{65,108,3,53,6,24,10,31,27,22,5,14,11,20,2,7,15,25,8,18,13,23,29,16,26,9,28,19,17,30}},
   {3,29,1,255,3,{141,0,0,0,0,0,0,0,0,0,0},{32,0,0,0,0,0,0,0,0,0,0},{64,35,1,53,6,10,27,5,31,22,14,11,20,2,25,15,7,8,18,13,23,29,16,26,9,28,19,17,30,0}},
   {4,28,1,47,4,{132,0,0,0,0,0,0,0,0,0,0},{0,0,0,0,0,0,0,0,0,0,0},{67,32,1,53,6,27,42,5,22,14,11,20,89,2,15,7,8,18,13,23,29,16,26,9,28,19,17,30,0,0}},
   {5,27,2,41,5,{184,212,0,0,0,0,0,0,0,0,0},{0,16,0,0,0,0,0,0,0,0,0},{65,53,3,32,6,10,63,5,46,11,20,2,7,15,25,77,18,8,23,29,16,26,9,28,19,17,30,0,0,0}},
   {6,26,3,255,6,{208,73,157,0,0,0,0,0,0,0,0},{0,0,63,0,0,0,0,0,0,0,0},{67,0,1,36,24,95,59,14,54,20,7,2,15,25,8,18,13,23,29,26,16,92,9,19,17,30,0,0,0,0}},
   {7,25,0,12,7,{0,0,0,0,0,0,0,0,0,0,0},{0,0,0,0,0,0,0,0,0,0,0},{67,1,68,70,74,69,86,84,75,71,66,79,89,72,82,77,87,93,90,80,73,83,28,81,94,0,0,0,0,0}},
   {0,29,1,37,8,{211,0,0,0,0,0,0,0,0,0,0},{15,0,0,0,0,0,0,0,0,0,0},{99,21,33,4,56,10,5,31,27,22,14,20,11,2,7,15,25,18,8,13,29,26,23,16,9,28,19,17,30,0}},
   {1,30,1,28,9,{130,0,0,0,0,0,0,0,0,0,0},{0,0,0,0,0,0,0,0,0,0,0},{99,21,33,4,38,42,56,37,63,59,54,46,52,43,47,34,39,50,57,40,45,61,55,41,58,48,60,51,49,62}},
   {2,30,1,255,10,{140,0,0,0,0,0,0,0,0,0,0},{28,0,0,0,0,0,0,0,0,0,0},{97,0,35,4,38,56,42,63,59,54,37,46,43,52,34,39,47,57,40,50,45,55,61,48,58,41,60,51,49,62}},
   {3,29,1,39,11,{228,0,0,0,0,0,0,0,0,0,0},{16,0,0,0,0,0,0,0,0,0,0},{96,12,33,4,38,42,59,37,63,54,46,43,52,34,57,47,39,40,50,45,55,61,48,58,41,60,51,49,62,0}},
   {4,28,1,31,12,{76,0,0,0,0,0,0,0,0,0,0},{0,0,0,0,0,0,0,0,0,0,0},{99,12,33,4,38,59,31,37,54,46,43,52,121,34,47,39,40,50,45,55,61,48,58,41,60,51,49,62,0,0}},
   {5,27,2,255,13,{128,142,0,0,0,0,0,0,0,0,0},{0,64,0,0,0,0,0,0,0,0,0},{97,12,35,4,38,42,27,37,22,43,52,34,39,47,57,109,50,40,55,61,48,58,41,60,51,49,62,0,0,0}},
   {6,26,2,255,14,{232,143,0,0,0,0,0,0,0,0,0},{0,128,0,0,0,0,0,0,0,0,0},{99,32,33,70,56,127,5,46,75,52,39,34,47,57,40,50,45,55,61,58,48,124,41,51,49,62,0,0,0,0}},
   {7,25,0,21,15,{0,0,0,0,0,0,0,0,0,0,0},{0,0,0,0,0,0,0,0,0,0,0},{99,33,100,102,106,101,118,116,107,103,98,111,121,104,114,109,119,125,122,112,105,115,60,113,126,0,0,0,0,0}},
   {0,5,7,33,255,{8,101,255,145,148,235,210,0,0,0,0},{0,0,0,0,0,0,0,0,0,0,0},{76,53,0,36,6,0,0,0,0,0,0,0,0,0,0,0,0,0,0,0,0,0,0,0,0,0,0,0,0,0}},
   {1,4,3,6,255,{31,253,166,0,0,0,0,0,0,0,0},{0,0,71,0,0,0,0,0,0,0,0},{64,53,12,36,0,0,0,0,0,0,0,0,0,0,0,0,0,0,0,0,0,0,0,0,0,0,0,0,0,0}},
   {2,4,5,25,255,{102,86,127,133,72,0,0,0,0,0,0},{0,0,251,0,0,0,0,0,0,0,0},{76,32,21,36,0,0,0,0,0,0,0,0,0,0,0,0,0,0,0,0,0,0,0,0,0,0,0,0,0,0}},
   {3,6,7,255,255,{170,81,51,252,126,189,154,0,0,0,0},{0,0,0,0,0,63,0,0,0,0,0},{67,108,21,36,24,56,0,0,0,0,0,0,0,0,0,0,0,0,0,0,0,0,0,0,0,0,0,0,0,0}},
   {4,8,7,22,255,{0,36,82,161,90,123,104,0,0,0,0},{0,0,0,0,0,0,0,0,0,0,0},{64,108,21,36,24,56,10,63,0,0,0,0,0,0,0,0,0,0,0,0,0,0,0,0,0,0,0,0,0,0}},
   {5,10,4,0,255,{34,194,179,164,0,0,0,0,0,0,0},{0,0,0,0,0,0,0,0,0,0,0},{85,108,0,36,24,56,31,59,14,54,0,0,0,0,0,0,0,0,0,0,0,0,0,0,0,0,0,0,0,0}},
   {6,10,4,2,255,{48,197,115,20,0,0,0,0,0,0,0},{0,0,0,0,0,0,0,0,0,0,0},{85,12,68,102,74,42,27,37,22,43,0,0,0,0,0,0,0,0,0,0,0,0,0,0,0,0,0,0,0,0}},
   {7,7,8,255,255,{192,54,217,177,165,108,209,244,0,0,0},{0,0,0,0,0,3,0,31,0,0,0},{85,0,12,88,91,95,78,0,0,0,0,0,0,0,0,0,0,0,0,0,0,0,0,0,0,0,0,0,0,0}},
   {8,17,2,14,16,{120,69,0,0,0,0,0,0,0,0,0},{0,0,0,0,0,0,0,0,0,0,0},{160,170,132,0,104,66,27,10,71,79,14,136,141,90,16,9,145,0,0,0,0,0,0,0,0,0,0,0,0,0}},
   {9,17,4,43,17,{56,204,214,152,0,0,0,0,0,0,0},{0,0,0,0,0,0,0,0,0,0,0},{67,37,12,6,24,31,45,14,20,79,7,25,141,73,26,16,158,0,0,0,0,0,0,0,0,0,0,0,0,0}},
   {10,17,4,24,18,{17,59,237,155,0,0,0,0,0,0,0},{0,0,63,0,0,0,0,0,0,0,0},{160,170,34,163,24,10,45,5,139,2,15,136,141,23,92,9,145,0,0,0,0,0,0,0,0,0,0,0,0,0}},
   {11,17,4,40,19,{16,122,147,213,0,0,0,0,0,0,0},{0,0,1,32,0,0,0,0,0,0,0},{160,170,166,24,10,5,45,31,139,25,15,136,141,23,9,28,145,0,0,0,0,0,0,0,0,0,0,0,0,0}},
   {12,17,3,11,20,{112,203,88,0,0,0,0,0,0,0,0},{0,0,0,0,0,0,0,0,0,0,0},{160,170,1,6,91,40,31,22,139,25,15,136,141,23,16,28,145,0,0,0,0,0,0,0,0,0,0,0,0,0}},
   {13,17,1,9,21,{22,0,0,0,0,0,0,0,0,0,0},{123,0,0,0,0,0,0,0,0,0,0},{160,170,3,6,10,27,40,22,20,7,15,136,141,23,9,28,145,0,0,0,0,0,0,0,0,0,0,0,0,0}},
   {14,17,4,34,22,{80,19,106,78,0,0,0,0,0,0,0},{0,0,0,0,0,0,0,0,0,0,0},{160,170,1,6,10,27,78,40,139,79,25,136,141,29,16,9,145,0,0,0,0,0,0,0,0,0,0,0,0,0}},
   {15,17,3,38,23,{18,202,135,0,0,0,0,0,0,0,0},{0,0,128,0,0,0,0,0,0,0,0},{160,170,132,43,44,31,78,40,20,7,15,136,141,29,16,147,145,0,0,0,0,0,0,0,0,0,0,0,0,0}},
   {8,17,4,255,24,{200,201,239,156,0,0,0,0,0,0,0},{0,0,0,0,0,0,0,0,0,0,0},{164,76,88,6,109,84,5,89,31,22,82,11,93,23,92,147,158,0,0,0,0,0,0,0,0,0,0,0,0,0}},
   {9,17,3,29,25,{248,110,158,0,0,0,0,0,0,0,0},{1,0,64,0,0,0,0,0,0,0,0},{160,170,132,74,69,40,27,22,139,2,82,136,93,23,92,147,145,0,0,0,0,0,0,0,0,0,0,0,0,0}},
   {10,17,3,36,26,{40,111,229,0,0,0,0,0,0,0,0},{0,128,32,0,0,0,0,0,0,0,0},{164,65,166,167,86,40,27,14,20,7,25,18,93,90,16,147,158,0,0,0,0,0,0,0,0,0,0,0,0,0}},
   {11,17,1,3,27,{62,0,0,0,0,0,0,0,0,0,0},{84,0,0,0,0,0,0,0,0,0,0},{164,128,171,6,91,40,22,14,20,2,7,18,93,80,26,147,158,0,0,0,0,0,0,0,0,0,0,0,0,0}},
   {12,17,2,19,28,{176,149,0,0,0,0,0,0,0,0,0},{0,0,0,0,0,0,0,0,0,0,0},{164,3,34,163,10,45,5,14,20,2,7,18,93,90,9,147,158,0,0,0,0,0,0,0,0,0,0,0,0,0}},
   {13,17,1,16,29,{206,0,0,0,0,0,0,0,0,0,0},{111,0,0,0,0,0,0,0,0,0,0},{164,65,132,163,31,5,45,14,139,2,82,25,93,80,26,147,158,0,0,0,0,0,0,0,0,0,0,0,0,0}},
   {14,17,2,1,30,{160,205,0,0,0,0,0,0,0,0,0},{0,0,0,0,0,0,0,0,0,0,0},{164,3,132,163,31,5,22,45,20,2,7,18,87,90,92,147,158,0,0,0,0,0,0,0,0,0,0,0,0,0}},
   {15,17,3,30,31,{216,109,231,0,0,0,0,0,0,0,0},{1,0,224,0,0,0,0,0,0,0,0},{164,3,12,24,91,5,22,45,139,2,25,18,87,90,9,28,158,0,0,0,0,0,0,0,0,0,0,0,0,0}},
   {8,4,3,5,255,{28,199,95,0,0,0,0,0,0,0,0},{0,0,188,0,0,0,0,0,0,0,0},{169,149,34,163,0,0,0,0,0,0,0,0,0,0,0,0,0,0,0,0,0,0,0,0,0,0,0,0,0,0}},
   {9,4,6,255,255,{30,193,221,151,188,243,0,0,0,0,0},{0,0,0,0,0,0,0,0,0,0,0},{164,128,34,163,0,0,0,0,0,0,0,0,0,0,0,0,0,0,0,0,0,0,0,0,0,0,0,0,0,0}},
   {10,4,4,4,255,{6,85,117,146,0,0,0,0,0,0,0},{0,0,0,0,0,0,0,0,0,0,0},{169,76,171,172,0,0,0,0,0,0,0,0,0,0,0,0,0,0,0,0,0,0,0,0,0,0,0,0,0,0}},
   {11,4,4,13,255,{100,11,183,60,0,0,0,0,0,0,0},{0,0,0,0,0,0,0,0,0,0,0},{169,3,12,163,0,0,0,0,0,0,0,0,0,0,0,0,0,0,0,0,0,0,0,0,0,0,0,0,0,0}},
   {12,4,7,32,255,{3,49,195,182,124,236,227,0,0,0,0},{0,0,0,0,0,0,15,0,0,0,0},{169,128,166,167,0,0,0,0,0,0,0,0,0,0,0,0,0,0,0,0,0,0,0,0,0,0,0,0,0,0}},
   {13,4,8,255,255,{27,99,219,251,91,238,74,241,0,0,0},{0,0,0,0,0,64,0,0,0,0,0},{169,149,34,167,0,0,0,0,0,0,0,0,0,0,0,0,0,0,0,0,0,0,0,0,0,0,0,0,0,0}},
   {14,4,5,15,255,{15,46,162,65,64,0,0,0,0,0,0},{0,0,0,0,0,0,0,0,0,0,0},{169,149,34,167,0,0,0,0,0,0,0,0,0,0,0,0,0,0,0,0,0,0,0,0,0,0,0,0,0,0}},
   {15,4,4,17,255,{10,37,118,21,0,0,0,0,0,0,0},{0,0,0,0,0,0,0,0,0,0,0},{169,149,70,74,0,0,0,0,0,0,0,0,0,0,0,0,0,0,0,0,0,0,0,0,0,0,0,0,0,0}},
   {8,4,4,20,255,{9,172,198,23,0,0,0,0,0,0,0},{0,0,2,0,0,0,0,0,0,0,0},{161,3,166,167,0,0,0,0,0,0,0,0,0,0,0,0,0,0,0,0,0,0,0,0,0,0,0,0,0,0}},
   {9,4,3,10,255,{175,196,167,0,0,0,0,0,0,0,0},{28,0,128,0,0,0,0,0,0,0,0},{169,149,166,167,0,0,0,0,0,0,0,0,0,0,0,0,0,0,0,0,0,0,0,0,0,0,0,0,0,0}},
   {10,4,7,255,255,{168,97,12,254,71,77,242,0,0,0,0},{0,0,0,0,0,0,0,0,0,0,0},{161,128,3,95,0,0,0,0,0,0,0,0,0,0,0,0,0,0,0,0,0,0,0,0,0,0,0,0,0,0}},
   {11,4,8,255,255,{4,35,43,94,105,234,131,138,0,0,0},{0,0,0,0,0,0,0,0,0,0,0},{161,149,132,167,0,0,0,0,0,0,0,0,0,0,0,0,0,0,0,0,0,0,0,0,0,0,0,0,0,0}},
   {12,4,6,255,255,{7,50,180,125,233,247,0,0,0,0,0},{32,0,0,0,0,192,0,0,0,0,0},{161,76,171,172,0,0,0,0,0,0,0,0,0,0,0,0,0,0,0,0,0,0,0,0,0,0,0,0,0,0}},
   {13,4,4,18,255,{39,220,116,67,0,0,0,0,0,0,0},{0,0,0,0,0,0,0,0,0,0,0},{161,76,166,172,0,0,0,0,0,0,0,0,0,0,0,0,0,0,0,0,0,0,0,0,0,0,0,0,0,0}},
   {14,4,5,27,255,{169,5,222,93,215,0,0,0,0,0,0},{0,0,0,0,192,0,0,0,0,0,0},{161,128,166,172,0,0,0,0,0,0,0,0,0,0,0,0,0,0,0,0,0,0,0,0,0,0,0,0,0,0}},
   {15,4,7,255,255,{24,55,84,89,150,230,137,0,0,0,0},{0,0,0,0,0,0,3,0,0,0,0},{161,65,34,163,0,0,0,0,0,0,0,0,0,0,0,0,0,0,0,0,0,0,0,0,0,0,0,0,0,0}},
   {8,4,5,8,255,{98,171,223,92,144,0,0,0,0,0,0},{0,0,0,0,0,0,0,0,0,0,0},{165,65,171,172,0,0,0,0,0,0,0,0,0,0,0,0,0,0,0,0,0,0,0,0,0,0,0,0,0,0}},
   {9,4,4,35,255,{173,87,207,79,0,0,0,0,0,0,0},{0,0,128,255,0,0,0,0,0,0,0},{161,65,171,172,0,0,0,0,0,0,0,0,0,0,0,0,0,0,0,0,0,0,0,0,0,0,0,0,0,0}},
   {10,4,4,7,255,{174,83,44,61,0,0,0,0,0,0,0},{0,0,0,0,0,0,0,0,0,0,0},{165,149,132,6,0,0,0,0,0,0,0,0,0,0,0,0,0,0,0,0,0,0,0,0,0,0,0,0,0,0}},
   {11,4,7,44,255,{2,33,26,41,45,70,134,0,0,0,0},{0,0,0,0,0,0,127,0,0,0,0},{165,98,1,172,0,0,0,0,0,0,0,0,0,0,0,0,0,0,0,0,0,0,0,0,0,0,0,0,0,0}},
   {12,4,4,23,255,{103,250,218,63,0,0,0,0,0,0,0},{130,0,0,128,0,0,0,0,0,0,0},{165,149,132,24,0,0,0,0,0,0,0,0,0,0,0,0,0,0,0,0,0,0,0,0,0,0,0,0,0,0}},
   {13,4,7,255,255,{96,14,119,58,66,186,246,0,0,0,0},{0,0,0,0,0,0,0,0,0,0,0},{165,128,171,24,0,0,0,0,0,0,0,0,0,0,0,0,0,0,0,0,0,0,0,0,0,0,0,0,0,0}},
   {14,4,7,46,255,{1,29,47,163,107,187,129,0,0,0,0},{0,0,0,0,0,0,3,0,0,0,0},{165,76,171,24,0,0,0,0,0,0,0,0,0,0,0,0,0,0,0,0,0,0,0,0,0,0,0,0,0,0}},
   {15,4,6,26,255,{13,52,181,191,75,136,0,0,0,0,0},{0,0,0,0,0,0,0,0,0,0,0},{165,128,166,167,0,0,0,0,0,0,0,0,0,0,0,0,0,0,0,0,0,0,0,0,0,0,0,0,0,0}},
   {6,2,8,45,255,{25,38,249,113,114,57,68,159,0,0,0},{0,0,0,0,0,0,0,128,0,0,0},{117,108,0,0,0,0,0,0,0,0,0,0,0,0,0,0,0,0,0,0,0,0,0,0,0,0,0,0,0,0}},
   {7,7,8,255,255,{32,53,178,42,121,190,185,245,0,0,0},{0,0,0,0,0,0,0,63,0,0,0},{117,32,44,120,123,127,110,0,0,0,0,0,0,0,0,0,0,0,0,0,0,0,0,0,0,0,0,0,0,0}}},
  {0,5,3,5,4,2,2,4,1,5,2,2,2,4,5,1,5,4,4,5,4,2,4,4},
  {{3,12,21,1,4,24,0,6,2,5,7,10,14,15,20,22,25,27,31,18,8,11,13,26,29,16,23,28,9,19,17,30},
   {0,1,3,21,12,4,6,10,24,5,31,27,14,22,20,11,15,2,7,18,25,8,13,29,9,23,26,28,16,19,30,17},
   {0,1,12,21,3,4,6,31,24,22,10,27,5,14,11,20,2,7,15,25,18,8,13,29,23,26,16,28,9,19,17,30},
   {0,3,21,12,1,4,24,6,10,27,5,22,31,14,11,20,2,25,15,7,8,18,13,29,23,16,26,9,28,19,17,30},
   {0,3,12,21,1,4,6,24,27,10,31,5,22,14,20,11,2,7,25,15,8,18,13,29,23,26,9,16,28,19,17,30},
   {1,21,12,0,3,4,6,24,10,31,27,5,22,14,20,11,2,7,8,18,25,15,13,29,23,16,26,9,28,19,17,30},
   {0,3,12,21,1,4,6,24,10,31,27,5,14,22,11,20,2,7,25,15,8,18,13,23,29,26,16,9,19,28,17,30},
   {0,1,3,4,12,21,6,24,10,27,31,5,14,22,11,20,7,2,15,25,8,18,13,23,29,26,16,9,19,28,17,30}},
  {{4,1,2,0,1,4,2,3},{3,3,0,3,3,0,4,2},{16,5,0,3,6,6,2,2},{0,0,3,1,0,3,0,0},
   {5,5,5,5,5,5,5,4},{9,9,12,10,11,11,11,11},{7,6,6,6,6,6,6,6},{0,3,6,2,3,1,6,1},
   {1,2,8,8,9,11,8,8},{9,12,2,5,5,5,9,2},{8,7,8,8,9,8,8,8},{15,15,1,0,0,0,1,6},
   {1,4,1,2,2,2,3,5},{2,7,12,10,11,8,12,12},{13,13,13,13,13,12,12,12},{5,0,2,1,2,2,3,3},
   {12,13,13,13,13,12,7,4},{0,2,12,10,11,8,0,13},{7,6,9,11,10,9,9,10},{15,3,8,8,9,11,8,10},
   {14,14,5,5,5,5,5,0},{2,2,4,4,4,1,1,1},{12,12,11,12,12,13,0,13},{8,9,11,12,12,13,0,13},
   {6,8,7,7,7,7,7,7},{3,1,3,6,1,3,4,7},{4,11,7,7,7,7,10,9},{11,11,10,9,8,10,10,9},
   {13,15,9,11,10,9,1,8},{6,10,10,9,8,10,11,11},{1,6,0,2,1,1,12,11},{10,10,9,11,10,9,9,10}},
  {{255,255,255,255,255,255,255,255},{255,255,255,255,255,255,255,255},{255,4,1,1,6,6,0,1},{255,255,255,255,255,255,255,255},
   {255,255,255,255,255,255,255,255},{255,255,255,255,255,255,255,255},{255,255,255,255,255,255,255,255},{3,1,6,12,1,21,6,21},
   {12,21,10,10,10,5,10,10},{5,22,15,20,20,20,18,2},{255,255,255,255,255,255,255,255},{255,255,12,0,3,1,21,6},
   {255,255,255,255,255,255,255,255},{21,10,5,5,5,10,14,14},{255,255,255,255,255,255,255,255},{4,3,0,3,12,12,12,0},
   {22,14,14,14,14,14,24,4},{7,8,13,13,13,13,23,23},{6,6,31,31,31,31,31,31},{11,7,8,8,8,8,8,18},
   {255,255,4,4,4,4,4,3},{255,255,255,255,255,255,255,255},{255,255,255,255,255,255,3,255},{10,5,22,22,22,22,22,22},
   {255,255,255,255,255,255,255,255},{1,0,3,6,0,3,1,24},{0,27,24,24,24,24,27,27},{255,255,255,255,255,255,255,255},
   {14,11,18,18,18,18,11,8},{24,31,27,27,27,27,5,5},{8,18,2,7,25,7,13,29},{255,255,255,255,255,255,255,255}}};

typedef CUresult (*EncodeFn)(CUtensorMap*, CUtensorMapDataType, cuuint32_t, void*, const cuuint64_t*, const cuuint64_t*, const cuuint32_t*,
                             const cuuint32_t*, CUtensorMapInterleave, CUtensorMapSwizzle, CUtensorMapL2promotion, CUtensorMapFloatOOBfill);

void make_map2(EncodeFn enc, CUtensorMap* m, const void* ptr, int rows, int cols, int box_rows) {
  cuuint64_t dim[2] = {(cuuint64_t)cols, (cuuint64_t)rows}, str[1] = {(cuuint64_t)cols * 2};
  cuuint32_t box[2] = {64, (cuuint32_t)box_rows}, es[2] = {1, 1};
  enc(m, CU_TENSOR_MAP_DATA_TYPE_BFLOAT16, 2, const_cast<void*>(ptr), dim, str, box, es, CU_TENSOR_MAP_INTERLEAVE_NONE, CU_TENSOR_MAP_SWIZZLE_128B,
      CU_TENSOR_MAP_L2_PROMOTION_L2_128B, CU_TENSOR_MAP_FLOAT_OOB_FILL_NONE);
}
void make_map3(EncodeFn enc, CUtensorMap* m, const void* ptr, int rows) {
  cuuint64_t dim[3] = {64, (cuuint64_t)rows, 9}, str[2] = {DM * 2, 128};
  cuuint32_t box[3] = {64, 32, 3}, es[3] = {1, 1, 1};
  enc(m, CU_TENSOR_MAP_DATA_TYPE_BFLOAT16, 3, const_cast<void*>(ptr), dim, str, box, es, CU_TENSOR_MAP_INTERLEAVE_NONE, CU_TENSOR_MAP_SWIZZLE_128B,
      CU_TENSOR_MAP_L2_PROMOTION_L2_128B, CU_TENSOR_MAP_FLOAT_OOB_FILL_NONE);
}

void make_map_t(EncodeFn enc, CUtensorMap* m, void* ptr, int width, int cols) {
  cuuint64_t dim[3] = {TP / 2, 2, 864}, str[2] = {TP * 2, TP * 4};
  cuuint32_t box[3] = {(cuuint32_t)width, 2, (cuuint32_t)cols}, es[3] = {1, 1, 1};
  enc(m, CU_TENSOR_MAP_DATA_TYPE_UINT32, 3, ptr, dim, str, box, es, CU_TENSOR_MAP_INTERLEAVE_NONE, cols == 64 ? CU_TENSOR_MAP_SWIZZLE_128B : CU_TENSOR_MAP_SWIZZLE_NONE,
      CU_TENSOR_MAP_L2_PROMOTION_NONE, CU_TENSOR_MAP_FLOAT_OOB_FILL_NONE);
}

int g_mode = -1;

}

extern "C" void kernel_launch(void* const* d_in, const int* in_sizes, int n_in, void* d_out, int out_size) {
  static EncodeFn enc = nullptr;
  static void* t_ptr = nullptr;
  if (!enc) {
    void* fn = nullptr;
    cudaDriverEntryPointQueryResult st;
    cudaGetDriverEntryPoint("cuTensorMapEncodeTiled", &fn, cudaEnableDefault, &st);
    enc = (EncodeFn)fn;
    cudaGetSymbolAddress(&t_ptr, g_T);
    cudaFuncSetAttribute(fused_kernel, cudaFuncAttributeMaxDynamicSharedMemorySize, SMEM_BYTES);
    if (g_mode < 0) {
      cudaLaunchConfig_t cfg = {};
      cfg.gridDim = dim3(2 * NCL); cfg.blockDim = dim3(384); cfg.dynamicSmemBytes = SMEM_BYTES;
      cudaLaunchAttribute at; at.id = cudaLaunchAttributeClusterDimension;
      at.val.clusterDim.x = 2; at.val.clusterDim.y = 1; at.val.clusterDim.z = 1;
      cfg.attrs = &at; cfg.numAttrs = 1;
      int nc = 0;
      g_mode = (cudaOccupancyMaxActiveClusters(&nc, fused_kernel, &cfg) == cudaSuccess && nc >= NCL) ? 1 : 0;
      (void)cudaGetLastError();
    }
  }
  Params p;
  make_map2(enc, &p.map_a[0], d_in[4], SEQ, DC, 128);
  make_map2(enc, &p.map_a[1], d_in[0], SEQ, DM, 128);
  make_map2(enc, &p.map_w[0], d_in[6], DC, 4096, 64);
  make_map2(enc, &p.map_w[1], d_in[7], DC, 4096, 64);
  make_map2(enc, &p.map_w[2], d_in[5], DM, 4096, 64);
  make_map2(enc, &p.map_w[3], d_in[1], DM, 1728, 64);
  make_map3(enc, &p.map_o[0], d_in[8], 4096);
  make_map3(enc, &p.map_o[1], d_in[2], DM);
  make_map_t(enc, &p.map_t[0], t_ptr, 32, 9);
  make_map_t(enc, &p.map_t[1], t_ptr, 40, 9);
  make_map_t(enc, &p.map_t[2], t_ptr, 32, 64);
  p.x = (const __nv_bfloat16*)d_in[0];
  p.gate_w = (const __nv_bfloat16*)d_in[9];
  make_map2(enc, &p.map_out, d_out, SEQ, DM, 64);
  p.out = (__nv_bfloat16*)d_out;
  p.zero = 0;
  auto launch = [&](int phases) {
    p.s = k_sched;
    for (int i = 0; i < NCL; i++) {
      Rec& r = p.s.r[i];
      if (!(phases & 1)) r.n1 = 0;
      if (!(phases & 2)) r.n2 = 0;
      if (!(phases & (r.p3 < 24 ? 4 : 32))) r.p3 = 255;
      if (!(phases & 8)) r.bg = 255;
      const int u1 = r.n1 ? 8 + r.n1 * (8 + (r.slab >> 3)) : 0;
      int u2 = 0;
      for (int k = 0; k < r.n2; k++) u2 += 4 * (r.item[k] & 7) + 4;
      r.u1 = (uint8_t)u1; r.u2 = (uint8_t)u2;
      r.rot = (uint8_t)(((u1 % 10 + 1) >> 1) % 5);
      r.x3 = (uint8_t)((r.rot + u2) % 5 & 3);
      r.phases = (uint8_t)phases;
    }
    if (!(phases & 16))
      for (int i = 0; i < 256; i++) { p.s.slot[i >> 3][i & 7] = (uint8_t)(i >> 3); p.s.prev[i >> 3][i & 7] = 255; }
    fused_kernel<<<2 * NCL, 384, SMEM_BYTES>>>(p);
  };
  if (g_mode == 1) launch(63);
  else { launch(1); launch(10); launch(32); launch(4); }
}
```

```cpp
#include <cuda_runtime.h>
#include <cuda_bf16.h>
#include <cuda.h>
#include <stdint.h>

namespace {

constexpr int SEQ = 2048, DM = 576, DC = 512, NH = 32;
constexpr int NCL = 66;
constexpr uint32_t DESC_HI = 0x40000040u;

constexpr int SM_RING = 0;
constexpr int SM_BUF = 163840;
constexpr int SM_BAR = 229376;
constexpr int B_P1E = 0, B_P2E = 10, B_P3E = 15, B_P2F = 24, B_SF = 32, B_ORD = 36, B_LAD = 40, B_DONE = 41, B_FIN = 48;
constexpr int B_P3F = 56, B_OUT = 61, B_P1F = 64, B_SE = 74, B_QF = 80, B_LA = 84, B_NUM = 88;
constexpr uint64_t B_CNT = 0x11118245000ull;
constexpr int SMEM_BYTES = SM_BAR + B_NUM * 8 + 1024;

constexpr int F_QKVA = 32;
constexpr int F_GATE = 64;
constexpr int F_DONE = 65;
constexpr int F_CTX = 96;
constexpr int F_OUT = 96 + 8 * 64;
constexpr int F_KV = F_OUT + 64;
constexpr int F_Q = F_KV + 256;
constexpr int F_RD = F_Q + 256;
constexpr int F_NUM = F_RD + 256;

struct Rec {
  uint8_t slab;
  uint8_t n1, n2;
  uint8_t p3;
  uint8_t bg;
  uint8_t item[11];
  uint8_t last[11];
  uint8_t tile[32];
  uint8_t u1, u2;
  uint8_t rot, x3;
  uint8_t phases;
};
struct Sched {
  Rec r[NCL];
  uint8_t nh[24];
  uint8_t p3_order[8][32];
  uint8_t slot[32][8];
  uint8_t prev[32][8];
};

#define SCHED_DECL static const

struct Params {
  CUtensorMap map_a[2];
  CUtensorMap map_w[4];
  CUtensorMap map_o[2];
  CUtensorMap map_t[3];
  CUtensorMap map_out;
  const __nv_bfloat16* x;
  const __nv_bfloat16* gate_w;
  __nv_bfloat16* out;
  int zero;
  alignas(64) Sched s;
};

__device__ __align__(1024) uint8_t g_Q[NH * 32 * 16384];
__device__ __align__(1024) uint8_t g_KV[2 * NH * 16 * 32768];
__device__ __align__(1024) uint8_t g_oA[32 * 576 * 128];
constexpr int TP = SEQ + 16;
__device__ __align__(1024) uint32_t g_T[864 * TP];
__device__ float g_gate[SEQ];
__device__ int g_flags[F_NUM];

__device__ __forceinline__ void mbar_arrive(uint32_t b) { asm volatile("mbarrier.arrive.shared::cta.b64 _, [%0];" ::"r"(b) : "memory"); }
__device__ __forceinline__ void mbar_arrive_cl(uint32_t b, int cnt) {
  asm volatile("mbarrier.arrive.shared::cluster.b64 _, [%0], %1;" ::"r"(b), "r"(cnt) : "memory");
}
__device__ __forceinline__ void mbar_wait(uint32_t b, int par) {
  asm volatile(
      "{\n.reg .pred p;\n.reg .u32 c;\n"
      "mbarrier.try_wait.parity.shared::cta.b64 p, [%0], %1;\n@p bra DN;\nmov.u32 c, 0;\n"
      "LP:\nmbarrier.try_wait.parity.shared::cta.b64 p, [%0], %1;\n@p bra DN;\n"
      "add.u32 c, c, 1;\nsetp.lt.u32 p, c, 4000000;\n@p bra LP;\ntrap;\nDN:\n}" ::"r"(b), "r"(par) : "memory");
}
__device__ __forceinline__ uint32_t mapa(uint32_t a, uint32_t cta) {
  uint32_t r; asm("mapa.shared::cluster.u32 %0, %1, %2;" : "=r"(r) : "r"(a), "r"(cta)); return r;
}
#define ELECT(ins) "{\n.reg .pred e;\nelect.sync _|e, 0xffffffff;\n@e " ins "\n}"
__device__ __forceinline__ void mbar_expect(uint32_t b, int bytes) {
  asm volatile(ELECT("mbarrier.arrive.expect_tx.shared::cta.b64 _, [%0], %1;") ::"r"(b), "r"(bytes) : "memory");
}
__device__ __forceinline__ void mbar_arrive_one(uint32_t b) { asm volatile(ELECT("mbarrier.arrive.shared::cta.b64 _, [%0];") ::"r"(b) : "memory"); }
constexpr uint64_t L2_NORMAL = 0x1000000000000000ull, L2_FIRST = 0x12F0000000000000ull;
__device__ __forceinline__ void bulk_load(uint32_t dst, const void* src, int bytes, uint32_t bar, uint64_t pol = L2_NORMAL) {
  asm volatile(ELECT("cp.async.bulk.shared::cluster.global.mbarrier::complete_tx::bytes.L2::cache_hint [%0], [%1], %2, [%3], %4;") ::"r"(dst), "l"(src), "r"(bytes), "r"(bar), "l"(pol) : "memory");
}
__device__ __forceinline__ void bulk_load_mc(uint32_t dst, const void* src, int bytes, uint32_t bar, uint64_t pol = L2_NORMAL) {
  asm volatile(ELECT("cp.async.bulk.shared::cluster.global.mbarrier::complete_tx::bytes.multicast::cluster.L2::cache_hint [%0], [%1], %2, [%3], %4, %5;") ::"r"(dst), "l"(src), "r"(bytes), "r"(bar), "h"((uint16_t)3), "l"(pol) : "memory");
}
__device__ __forceinline__ void bulk_store(void* dst, uint32_t src, int bytes, uint64_t pol = L2_NORMAL) {
  asm volatile(ELECT("cp.async.bulk.global.shared::cta.bulk_group.L2::cache_hint [%0], [%1], %2, %3;") ::"l"(dst), "r"(src), "r"(bytes), "l"(pol) : "memory");
}
__device__ __forceinline__ void tma2d(uint32_t dst, const CUtensorMap* m, int c0, int c1, uint32_t bar, uint64_t pol = L2_NORMAL) {
  asm volatile(ELECT("cp.async.bulk.tensor.2d.shared::cluster.global.mbarrier::complete_tx::bytes.L2::cache_hint [%0], [%1, {%3, %4}], [%2], %5;") ::"r"(dst), "l"(m), "r"(bar), "r"(c0), "r"(c1), "l"(pol) : "memory");
}
__device__ __forceinline__ void tma2d_mc(uint32_t dst, const CUtensorMap* m, int c0, int c1, uint32_t bar, uint64_t pol = L2_NORMAL) {
  asm volatile(ELECT("cp.async.bulk.tensor.2d.shared::cluster.global.mbarrier::complete_tx::bytes.multicast::cluster.L2::cache_hint [%0], [%1, {%3, %4}], [%2], %5, %6;") ::"r"(dst), "l"(m), "r"(bar), "r"(c0), "r"(c1), "h"((uint16_t)3), "l"(pol) : "memory");
}
__device__ __forceinline__ void tma3d(uint32_t dst, const CUtensorMap* m, int c0, int c1, int c2, uint32_t bar, uint64_t pol = L2_NORMAL) {
  asm volatile(ELECT("cp.async.bulk.tensor.3d.shared::cluster.global.mbarrier::complete_tx::bytes.L2::cache_hint [%0], [%1, {%3, %4, %5}], [%2], %6;") ::"r"(dst), "l"(m), "r"(bar), "r"(c0), "r"(c1), "r"(c2), "l"(pol) : "memory");
}
__device__ __forceinline__ void tma3d_mc(uint32_t dst, const CUtensorMap* m, int c0, int c1, int c2, uint32_t bar, uint64_t pol = L2_NORMAL) {
  asm volatile(ELECT("cp.async.bulk.tensor.3d.shared::cluster.global.mbarrier::complete_tx::bytes.multicast::cluster.L2::cache_hint [%0], [%1, {%3, %4, %5}], [%2], %6, %7;") ::"r"(dst), "l"(m), "r"(bar), "r"(c0), "r"(c1), "r"(c2), "h"((uint16_t)3), "l"(pol) : "memory");
}
__device__ __forceinline__ void tma2d_add(const CUtensorMap* m, uint32_t src, int c0, int c1) {
  asm volatile(ELECT("cp.reduce.async.bulk.tensor.2d.global.shared::cta.add.bulk_group [%0, {%2, %3}], [%1];") ::"l"(m), "r"(src), "r"(c0), "r"(c1) : "memory");
}
__device__ __forceinline__ void tma3d_store(const CUtensorMap* m, uint32_t src, int c0, int c1, int c2, uint64_t pol = L2_NORMAL) {
  asm volatile(ELECT("cp.async.bulk.tensor.3d.global.shared::cta.bulk_group.L2::cache_hint [%0, {%2, %3, %4}], [%1], %5;") ::"l"(m), "r"(src), "r"(c0), "r"(c1), "r"(c2), "l"(pol) : "memory");
}
__device__ __forceinline__ void tma2d_prefetch(const CUtensorMap* m, int c0, int c1, uint64_t pol = L2_NORMAL) {
  asm volatile(ELECT("cp.async.bulk.prefetch.tensor.2d.L2.global.L2::cache_hint [%0, {%1, %2}], %3;") ::"l"(m), "r"(c0), "r"(c1), "l"(pol) : "memory");
}
#define LAG 3
#define HINT 62
#define POL(bit) ((HINT >> (bit)) & 1 ? L2_FIRST : L2_NORMAL)
#define BULK_COMMIT() asm volatile("cp.async.bulk.commit_group;" ::: "memory")
#define BULK_WAIT(n) asm volatile("cp.async.bulk.wait_group %0;" ::"n"(n) : "memory")
#define BULK_WAIT_READ(n) asm volatile("cp.async.bulk.wait_group.read %0;" ::"n"(n) : "memory")
#define FENCE_ASYNC_SMEM() asm volatile("fence.proxy.async.shared::cta;" ::: "memory")
#define FENCE_ASYNC_ALL() asm volatile("fence.proxy.async;" ::: "memory")
#define WG_FENCE() asm volatile("wgmma.fence.sync.aligned;" ::: "memory")
#define WG_COMMIT() asm volatile("wgmma.commit_group.sync.aligned;" ::: "memory")
#define WG_WAIT(n) asm volatile("wgmma.wait_group.sync.aligned %0;" ::"n"(n) : "memory")
__device__ __forceinline__ void bar_sync(int id, int n) { asm volatile("bar.sync %0, %1;" ::"r"(id), "r"(n) : "memory"); }
__device__ __forceinline__ void bar_arrive(int id, int n) { asm volatile("bar.arrive %0, %1;" ::"r"(id), "r"(n) : "memory"); }
__device__ __forceinline__ void cluster_sync() {
  asm volatile("barrier.cluster.arrive.relaxed;\nbarrier.cluster.wait.acquire;" ::: "memory");
}
template <int N> __device__ __forceinline__ void pin(float (&r)[N]) {
#pragma unroll
  for (int i = 0; i < N; i++) asm volatile("" : "+f"(r[i])::"memory");
}
template <int N> __device__ __forceinline__ void pin(uint32_t (&r)[N]) {
#pragma unroll
  for (int i = 0; i < N; i++) asm volatile("" : "+r"(r[i])::"memory");
}
__device__ __forceinline__ uint32_t pack_bf16(float lo, float hi) {
  uint32_t r; asm("cvt.rn.bf16x2.f32 %0, %1, %2;" : "=r"(r) : "f"(hi), "f"(lo)); return r;
}
__device__ __forceinline__ float ex2(float x) { float r; asm("ex2.approx.ftz.f32 %0, %1;" : "=f"(r) : "f"(x)); return r; }
__device__ __forceinline__ void ldsm4(uint32_t a, uint32_t& r0, uint32_t& r1, uint32_t& r2, uint32_t& r3) {
  asm volatile("ldmatrix.sync.aligned.m8n8.x4.shared.b16 {%0,%1,%2,%3}, [%4];" : "=r"(r0), "=r"(r1), "=r"(r2), "=r"(r3) : "r"(a) : "memory");
}
__device__ __forceinline__ void stsm4(uint32_t a, uint32_t r0, uint32_t r1, uint32_t r2, uint32_t r3) {
  asm volatile("stmatrix.sync.aligned.m8n8.x4.shared.b16 [%0], {%1,%2,%3,%4};" ::"r"(a), "r"(r0), "r"(r1), "r"(r2), "r"(r3) : "memory");
}
__device__ __forceinline__ void flag_add(int idx) {
  asm volatile(ELECT("red.release.gpu.global.add.s32 [%0], 1;") ::"l"(g_flags + idx) : "memory");
}
__device__ __forceinline__ void flag_add_rx(int idx) {
  asm volatile(ELECT("red.relaxed.gpu.global.add.s32 [%0], 1;") ::"l"(g_flags + idx) : "memory");
}
template <bool ACQ, int NS = 32> __device__ __forceinline__ void flag_wait(int idx, int target) {
  int n = 0;
  while (true) {
    int v;
    if (ACQ) asm volatile("ld.acquire.gpu.global.s32 %0, [%1];" : "=r"(v) : "l"(g_flags + idx) : "memory");
    else asm volatile("ld.relaxed.gpu.global.s32 %0, [%1];" : "=r"(v) : "l"(g_flags + idx) : "memory");
    if (__all_sync(0xffffffffu, v >= target)) break;
    if (++n > 20000000) __trap();
    __nanosleep(NS);
  }
}
__device__ __forceinline__ void mask_wait(uint32_t& ready, int bit, int idx, int target) {
  for (int n = 0; !((ready >> bit) & 1); n++) {
    int v;
    if (n) { __nanosleep(32); if (n > 20000000) __trap(); }
    asm volatile("ld.relaxed.gpu.global.s32 %0, [%1];" : "=r"(v) : "l"(g_flags + idx) : "memory");
    ready = __ballot_sync(0xffffffffu, v >= target);
  }
}
__device__ __forceinline__ uint32_t desc_lo(uint32_t addr, uint32_t lbo) { return ((addr & 0x3FFFFu) >> 4) | ((lbo >> 4) << 16); }
#define PROF(role, i)
#define PROFX(cond, i)
#define PROFB(i)
#define PROFG(i)

template <int TB, int TA = 0> __device__ __forceinline__ void wgmma_ss64(float (&d)[32], uint32_t alo, uint32_t blo, int sd) {
  asm volatile("{\n.reg .pred p;\n.reg .b64 da, db;\n"
    "setp.ne.b32 p, %34, 0;\nmov.b64 da, {%32, %36};\nmov.b64 db, {%33, %36};\n"
    "wgmma.mma_async.sync.aligned.m64n64k16.f32.bf16.bf16 "
    "{%0,%1,%2,%3,%4,%5,%6,%7,%8,%9,%10,%11,%12,%13,%14,%15,%16,%17,%18,%19,%20,%21,%22,%23,"
    "%24,%25,%26,%27,%28,%29,%30,%31}, "
    "da, db, p, 1, 1, %37, %35;\n}\n"
    : "+f"(d[0]),"+f"(d[1]),"+f"(d[2]),"+f"(d[3]),"+f"(d[4]),"+f"(d[5]),"+f"(d[6]),"+f"(d[7]),"+f"(d[8]),"+f"(d[9]),"+f"(d[10]),"+f"(d[11]),
      "+f"(d[12]),"+f"(d[13]),"+f"(d[14]),"+f"(d[15]),"+f"(d[16]),"+f"(d[17]),"+f"(d[18]),"+f"(d[19]),"+f"(d[20]),"+f"(d[21]),"+f"(d[22]),"+f"(d[23]),
      "+f"(d[24]),"+f"(d[25]),"+f"(d[26]),"+f"(d[27]),"+f"(d[28]),"+f"(d[29]),"+f"(d[30]),"+f"(d[31])
    : "r"(alo), "r"(blo), "r"(sd), "n"(TB), "r"(DESC_HI), "n"(TA));
}
template <int TB, int TA = 0> __device__ __forceinline__ void wgmma_ss128(float (&d)[64], uint32_t alo, uint32_t blo, int sd) {
  asm volatile("{\n.reg .pred p;\n.reg .b64 da, db;\n"
    "setp.ne.b32 p, %66, 0;\nmov.b64 da, {%64, %68};\nmov.b64 db, {%65, %68};\n"
    "wgmma.mma_async.sync.aligned.m64n128k16.f32.bf16.bf16 "
    "{%0,%1,%2,%3,%4,%5,%6,%7,%8,%9,%10,%11,%12,%13,%14,%15,%16,%17,%18,%19,%20,%21,%22,%23,"
    "%24,%25,%26,%27,%28,%29,%30,%31,%32,%33,%34,%35,%36,%37,%38,%39,%40,%41,%42,%43,%44,%45,%46,%47,"
    "%48,%49,%50,%51,%52,%53,%54,%55,%56,%57,%58,%59,%60,%61,%62,%63}, "
    "da, db, p, 1, 1, %69, %67;\n}\n"
    : "+f"(d[0]),"+f"(d[1]),"+f"(d[2]),"+f"(d[3]),"+f"(d[4]),"+f"(d[5]),"+f"(d[6]),"+f"(d[7]),"+f"(d[8]),"+f"(d[9]),"+f"(d[10]),"+f"(d[11]),
      "+f"(d[12]),"+f"(d[13]),"+f"(d[14]),"+f"(d[15]),"+f"(d[16]),"+f"(d[17]),"+f"(d[18]),"+f"(d[19]),"+f"(d[20]),"+f"(d[21]),"+f"(d[22]),"+f"(d[23]),
      "+f"(d[24]),"+f"(d[25]),"+f"(d[26]),"+f"(d[27]),"+f"(d[28]),"+f"(d[29]),"+f"(d[30]),"+f"(d[31]),"+f"(d[32]),"+f"(d[33]),"+f"(d[34]),"+f"(d[35]),
      "+f"(d[36]),"+f"(d[37]),"+f"(d[38]),"+f"(d[39]),"+f"(d[40]),"+f"(d[41]),"+f"(d[42]),"+f"(d[43]),"+f"(d[44]),"+f"(d[45]),"+f"(d[46]),"+f"(d[47]),
      "+f"(d[48]),"+f"(d[49]),"+f"(d[50]),"+f"(d[51]),"+f"(d[52]),"+f"(d[53]),"+f"(d[54]),"+f"(d[55]),"+f"(d[56]),"+f"(d[57]),"+f"(d[58]),"+f"(d[59]),
      "+f"(d[60]),"+f"(d[61]),"+f"(d[62]),"+f"(d[63])
    : "r"(alo), "r"(blo), "r"(sd), "n"(TB), "r"(DESC_HI), "n"(TA));
}
template <int TB> __device__ __forceinline__ void wgmma_rs128(float (&d)[64], uint32_t a0, uint32_t a1, uint32_t a2, uint32_t a3, uint32_t blo, int sd) {
  asm volatile("{\n.reg .pred p;\n.reg .b64 db;\n"
    "setp.ne.b32 p, %69, 0;\nmov.b64 db, {%68, %71};\n"
    "wgmma.mma_async.sync.aligned.m64n128k16.f32.bf16.bf16 "
    "{%0,%1,%2,%3,%4,%5,%6,%7,%8,%9,%10,%11,%12,%13,%14,%15,%16,%17,%18,%19,%20,%21,%22,%23,"
    "%24,%25,%26,%27,%28,%29,%30,%31,%32,%33,%34,%35,%36,%37,%38,%39,%40,%41,%42,%43,%44,%45,%46,%47,"
    "%48,%49,%50,%51,%52,%53,%54,%55,%56,%57,%58,%59,%60,%61,%62,%63}, "
    "{%64,%65,%66,%67}, db, p, 1, 1, %70;\n}\n"
    : "+f"(d[0]),"+f"(d[1]),"+f"(d[2]),"+f"(d[3]),"+f"(d[4]),"+f"(d[5]),"+f"(d[6]),"+f"(d[7]),"+f"(d[8]),"+f"(d[9]),"+f"(d[10]),"+f"(d[11]),
      "+f"(d[12]),"+f"(d[13]),"+f"(d[14]),"+f"(d[15]),"+f"(d[16]),"+f"(d[17]),"+f"(d[18]),"+f"(d[19]),"+f"(d[20]),"+f"(d[21]),"+f"(d[22]),"+f"(d[23]),
      "+f"(d[24]),"+f"(d[25]),"+f"(d[26]),"+f"(d[27]),"+f"(d[28]),"+f"(d[29]),"+f"(d[30]),"+f"(d[31]),"+f"(d[32]),"+f"(d[33]),"+f"(d[34]),"+f"(d[35]),
      "+f"(d[36]),"+f"(d[37]),"+f"(d[38]),"+f"(d[39]),"+f"(d[40]),"+f"(d[41]),"+f"(d[42]),"+f"(d[43]),"+f"(d[44]),"+f"(d[45]),"+f"(d[46]),"+f"(d[47]),
      "+f"(d[48]),"+f"(d[49]),"+f"(d[50]),"+f"(d[51]),"+f"(d[52]),"+f"(d[53]),"+f"(d[54]),"+f"(d[55]),"+f"(d[56]),"+f"(d[57]),"+f"(d[58]),"+f"(d[59]),
      "+f"(d[60]),"+f"(d[61]),"+f"(d[62]),"+f"(d[63])
    : "r"(a0), "r"(a1), "r"(a2), "r"(a3), "r"(blo), "r"(sd), "n"(TB), "r"(DESC_HI));
}
template <int TB, int TA = 0> __device__ __forceinline__ void wgmma_ss192(float (&d)[96], uint32_t alo, uint32_t blo, int sd) {
  asm volatile("{\n.reg .pred p;\n.reg .b64 da, db;\n"
    "setp.ne.b32 p, %98, 0;\nmov.b64 da, {%96, %100};\nmov.b64 db, {%97, %100};\n"
    "wgmma.mma_async.sync.aligned.m64n192k16.f32.bf16.bf16 "
    "{%0,%1,%2,%3,%4,%5,%6,%7,%8,%9,%10,%11,%12,%13,%14,%15,%16,%17,%18,%19,%20,%21,%22,%23,"
    "%24,%25,%26,%27,%28,%29,%30,%31,%32,%33,%34,%35,%36,%37,%38,%39,%40,%41,%42,%43,%44,%45,%46,%47,"
    "%48,%49,%50,%51,%52,%53,%54,%55,%56,%57,%58,%59,%60,%61,%62,%63,%64,%65,%66,%67,%68,%69,%70,%71,"
    "%72,%73,%74,%75,%76,%77,%78,%79,%80,%81,%82,%83,%84,%85,%86,%87,%88,%89,%90,%91,%92,%93,%94,%95}, "
    "da, db, p, 1, 1, %101, %99;\n}\n"
    : "+f"(d[0]),"+f"(d[1]),"+f"(d[2]),"+f"(d[3]),"+f"(d[4]),"+f"(d[5]),"+f"(d[6]),"+f"(d[7]),"+f"(d[8]),"+f"(d[9]),"+f"(d[10]),"+f"(d[11]),
      "+f"(d[12]),"+f"(d[13]),"+f"(d[14]),"+f"(d[15]),"+f"(d[16]),"+f"(d[17]),"+f"(d[18]),"+f"(d[19]),"+f"(d[20]),"+f"(d[21]),"+f"(d[22]),"+f"(d[23]),
      "+f"(d[24]),"+f"(d[25]),"+f"(d[26]),"+f"(d[27]),"+f"(d[28]),"+f"(d[29]),"+f"(d[30]),"+f"(d[31]),"+f"(d[32]),"+f"(d[33]),"+f"(d[34]),"+f"(d[35]),
      "+f"(d[36]),"+f"(d[37]),"+f"(d[38]),"+f"(d[39]),"+f"(d[40]),"+f"(d[41]),"+f"(d[42]),"+f"(d[43]),"+f"(d[44]),"+f"(d[45]),"+f"(d[46]),"+f"(d[47]),
      "+f"(d[48]),"+f"(d[49]),"+f"(d[50]),"+f"(d[51]),"+f"(d[52]),"+f"(d[53]),"+f"(d[54]),"+f"(d[55]),"+f"(d[56]),"+f"(d[57]),"+f"(d[58]),"+f"(d[59]),
      "+f"(d[60]),"+f"(d[61]),"+f"(d[62]),"+f"(d[63]),"+f"(d[64]),"+f"(d[65]),"+f"(d[66]),"+f"(d[67]),"+f"(d[68]),"+f"(d[69]),"+f"(d[70]),"+f"(d[71]),
      "+f"(d[72]),"+f"(d[73]),"+f"(d[74]),"+f"(d[75]),"+f"(d[76]),"+f"(d[77]),"+f"(d[78]),"+f"(d[79]),"+f"(d[80]),"+f"(d[81]),"+f"(d[82]),"+f"(d[83]),
      "+f"(d[84]),"+f"(d[85]),"+f"(d[86]),"+f"(d[87]),"+f"(d[88]),"+f"(d[89]),"+f"(d[90]),"+f"(d[91]),"+f"(d[92]),"+f"(d[93]),"+f"(d[94]),"+f"(d[95])
    : "r"(alo), "r"(blo), "r"(sd), "n"(TB), "r"(DESC_HI), "n"(TA));
}

struct Ctx {
  uint32_t sm;
  uint32_t bar;
  uint32_t rbar;
  int cl, rank, wg, warp, lane, phases;
};
__device__ __forceinline__ void release(const Ctx& c, int b, int cnt = 1) {
  if (c.lane < 2) mbar_arrive_cl(c.rbar + b * 8, cnt);
}
#define HK 5
#define PFM 7
#define PF1 1
constexpr float SM_SCALE = 0.08838834764831845f * 1.4426950408889634f;
constexpr float SM_HI = 1.8446744e19f, SM_LO = 5.4210109e-20f;
constexpr int ORDER = 1;

__device__ __forceinline__ void stage_tile(const float (&a)[64], uint32_t buf, const Ctx& c, float s0, float s1) {
  const int row = (c.lane & 7) + ((c.lane >> 3) & 1) * 8;
  const uint32_t base = buf + (c.warp * 16 + row) * 128 + (((c.lane >> 4) ^ (row & 7)) << 4);
#pragma unroll
  for (int i = 0; i < 8; i++)
    stsm4((base ^ ((i & 3) << 5)) + (i >> 2) * 8192, pack_bf16(a[8 * i] * s0, a[8 * i + 1] * s0), pack_bf16(a[8 * i + 2] * s1, a[8 * i + 3] * s1),
          pack_bf16(a[8 * i + 4] * s0, a[8 * i + 5] * s0), pack_bf16(a[8 * i + 6] * s1, a[8 * i + 7] * s1));
}

__device__ __forceinline__ void p1_epilogue(const Params& p, const Ctx& c, const float (&acc)[64], int t, int type) {
  const int tile = p.s.r[c.cl].tile[t] & 63, b = c.wg * 2 + 1;
  mbar_wait(c.bar + (B_SE + b) * 8, (t & 1) ^ 1);
  if (type && tile >= 32) {
    const int r = 2 * (c.lane & 3) + ((c.lane >> 2) & 1);
    const uint32_t dst = c.sm + SM_BUF + b * 16384 + r * 128 + (((c.warp * 2) ^ r) << 4) + (c.lane >> 3) * 4;
#pragma unroll
    for (int i = 0; i < 16; i++) {
      asm volatile("st.shared.u32 [%0], %1;" ::"r"(dst + i * 1024), "r"(pack_bf16(acc[4 * i], acc[4 * i + 1])) : "memory");
      asm volatile("st.shared.u32 [%0], %1;" ::"r"((dst ^ 16) + i * 1024), "r"(pack_bf16(acc[4 * i + 2], acc[4 * i + 3])) : "memory");
    }
  } else {
    if (type) stage_tile(acc, c.sm + SM_BUF + b * 16384, c, SM_SCALE, SM_SCALE);
    else stage_tile(acc, c.sm + SM_BUF + b * 16384, c, 1.f, 1.f);
  }
  FENCE_ASYNC_SMEM();
  __syncwarp();
  if (c.lane == 0) mbar_arrive(c.bar + (B_SF + b) * 8);
}

__device__ __forceinline__ void p1_consumer(const Params& p, const Ctx& c) {
  const int n = p.s.r[c.cl].n1;
  const int type = p.s.r[c.cl].slab >> 3;
  const uint32_t bdesc = desc_lo(c.sm + SM_RING, 8192), adesc = desc_lo(c.sm + SM_BUF + 32768 + c.wg * 8192, 16);
  uint32_t A[128];
  float acc[64] = {};
  int slot = 0, par = 0;
  auto next = [&]() { if (++slot == 10) { slot = 0; par ^= 1; } };
  {
    const int row = (c.lane & 7) + ((c.lane >> 3) & 1) * 8;
    const uint32_t base = c.sm + SM_RING + (c.wg * 64 + c.warp * 16 + row) * 128 + (((c.lane >> 4) ^ (row & 7)) << 4);
    if (c.wg == 1) bar_sync(ORDER + 1, 256);
    int pa = -1, pb = -1;
    if (type) {
      mbar_wait(c.bar + B_P1F * 8, 0);
      WG_FENCE();
#pragma unroll
      for (int kk = 0; kk < 4; kk++) wgmma_ss128<1>(acc, adesc + kk * 2, bdesc + kk * 128, kk != 0);
      WG_COMMIT();
      pb = 0; slot = 1;
    }
#pragma unroll
    for (int kb = 0; kb < 8; kb++) {
      const int sa = slot;
      mbar_wait(c.bar + (B_P1F + slot) * 8, par);
      if (kb == 0) PROF(c.wg, 5);
      next();
      mbar_wait(c.bar + (B_P1F + slot) * 8, par);
      PROF(c.wg, 6 + 2 * kb);
      WG_FENCE();
#pragma unroll
      for (int kk = 0; kk < 4; kk++)
        wgmma_ss128<1>(acc, desc_lo(c.sm + SM_RING + c.wg * 8192, 16) + sa * 1024 + kk * 2, bdesc + slot * 1024 + kk * 128, (kb | kk) != 0 ? 1 : type);
      WG_COMMIT();
      if (kb == 1 && c.wg == 0) bar_arrive(ORDER + 1, 256);
#pragma unroll
      for (int kk = 0; kk < 4; kk++) ldsm4((base ^ (kk << 5)) + sa * 16384, A[kb * 16 + kk * 4], A[kb * 16 + kk * 4 + 1], A[kb * 16 + kk * 4 + 2], A[kb * 16 + kk * 4 + 3]);
      WG_WAIT(1);
      if (kb > 0) release(c, B_P1E + pa);
      if (kb > 0 || pb >= 0) release(c, B_P1E + pb);
      pa = sa; pb = slot;
      next();
    }
    WG_WAIT(0);
    __syncwarp();
    release(c, B_P1E + pa);
    release(c, B_P1E + pb);
    pin(acc);
    PROF(c.wg, 1);
    p1_epilogue(p, c, acc, 0, type);
    PROF(c.wg, 2);
  }
  for (int t = 1; t < n; t++) {
    bar_sync(ORDER + c.wg, 256);
    int prev1 = -1, prev2 = -1;
    if (type) {
      mbar_wait(c.bar + (B_P1F + slot) * 8, par);
      WG_FENCE();
#pragma unroll
      for (int kk = 0; kk < 4; kk++) wgmma_ss128<1>(acc, adesc + kk * 2, bdesc + slot * 1024 + kk * 128, kk != 0);
      WG_COMMIT();
      prev1 = slot;
      next();
    }
#pragma unroll
    for (int kb = 0; kb < 8; kb++) {
      mbar_wait(c.bar + (B_P1F + slot) * 8, par);
      WG_FENCE();
      const uint32_t d = bdesc + slot * 1024;
#pragma unroll
      for (int kk = 0; kk < 4; kk++)
        wgmma_rs128<1>(acc, A[kb * 16 + kk * 4], A[kb * 16 + kk * 4 + 1], A[kb * 16 + kk * 4 + 2], A[kb * 16 + kk * 4 + 3], d + kk * 128, (kb | kk) != 0 ? 1 : type);
      WG_COMMIT();
      if (kb == HK) {
        if (t + 1 < n || c.wg == 0) bar_arrive(ORDER + (c.wg ^ 1), 256);
      }
      if (kb > 0) { WG_WAIT(2); if (kb > 1 || prev2 >= 0) release(c, B_P1E + prev2); }
      prev2 = prev1; prev1 = slot;
      next();
    }
    WG_WAIT(1);
    release(c, B_P1E + prev2);
    WG_WAIT(0);
    pin(acc);
    release(c, B_P1E + prev1);
    p1_epilogue(p, c, acc, t, type);
    PROF(c.wg, 3);
  }
}

__device__ __forceinline__ void p1_producer(const Params& p, const Ctx& c) {
  const int n = p.s.r[c.cl].n1;
  const int type = p.s.r[c.cl].slab >> 3, grp = p.s.r[c.cl].slab & 7;
  int slot = 2 - type, par = 1;
#pragma unroll 1
  for (int t = 0; t < n; t++) {
    const int tile = p.s.r[c.cl].tile[t] & 63;
    const CUtensorMap* m = &p.map_w[type * 2 + (tile >> 5)];
    const int n0 = (tile & 31) * 128 + c.rank * 64;
    const int ptile = p.s.r[c.cl].tile[t + PF1 < n ? t + PF1 : t];
    const CUtensorMap* pm = &p.map_w[type * 2 + ((ptile >> 5) & 1)];
    if (t == 7 && (c.phases & 16)) flag_wait<true>(F_GATE, 256);
#pragma unroll 1
    for (int kb = (t == 0) - type; kb < 8; kb++) {
      if (t == 0) {
        mbar_wait(c.bar + (B_P1E + slot) * 8, par);
        mbar_expect(c.bar + (B_P1F + slot) * 8, 16384);
        tma2d(c.sm + SM_RING + slot * 16384, &p.map_a[type], kb * 64, grp * 256 + c.rank * 128, c.bar + (B_P1F + slot) * 8);
        if (++slot == 10) { slot = 0; par ^= 1; }
      }
      mbar_wait(c.bar + (B_P1E + slot) * 8, par);
      mbar_expect(c.bar + (B_P1F + slot) * 8, 16384);
      tma2d_mc(c.sm + SM_RING + slot * 16384 + c.rank * 8192, m, n0, kb < 0 ? 512 : kb * 64, c.bar + (B_P1F + slot) * 8);
      if (t == 0 && kb == 1) PROF(2, 61);
      if (t == 0 && kb == 3) PROF(2, 62);
      if (t + PF1 < n && t > 0 && ((ptile & 64) || ((ptile & 128) && ((kb ^ grp) & PFM) == 0))) tma2d_prefetch(pm, (ptile & 31) * 128 + c.rank * 64, kb < 0 ? 512 : kb * 64);
      if (++slot == 10) { slot = 0; par ^= 1; }
    }
  }
}

__device__ __forceinline__ void p1_storer(const Params& p, const Ctx& c) {
  const int n = p.s.r[c.cl].n1;
  const int type = p.s.r[c.cl].slab >> 3, grp = p.s.r[c.cl].slab & 7;
  for (int i = 0; i < 2 * n; i++) {
    const int t = i >> 1, w = i & 1, b = w * 2 + 1;
    const int tile = p.s.r[c.cl].tile[t] & 63;
    mbar_wait(c.bar + (B_SF + b) * 8, t & 1);
    const uint32_t src = c.sm + SM_BUF + b * 16384;
    int f = (type ? F_Q : F_KV) + (tile & 31) * 8 + grp;
    if (type == 0) {
      const int prev = p.s.prev[tile & 31][grp];
      if (prev != 255 && w == 0) {
        if (grp >= 2) flag_wait<false>(F_RD + prev * 8 + grp, 8 - grp);
        else flag_wait<false>(F_CTX + max(c.lane & 7, grp) * 64 + prev, 4);
      }
      uint8_t* dst = g_KV + (size_t)(((tile & 32) + p.s.slot[tile & 31][grp]) * 16 + grp * 2 + c.rank) * 32768 + w * 8192;
      bulk_store(dst, src, 8192);
      bulk_store(dst + 16384, src + 8192, 8192);
    } else if (tile < 32) {
      bulk_store(g_Q + (size_t)(tile * 32 + grp * 4 + c.rank * 2 + w) * 16384, src, 16384);
    } else {
      tma3d_store(&p.map_t[2], src, 8 + (grp * 4 + c.rank * 2 + w) * 32, 0, (tile - 32) * 64);
      f = F_QKVA + grp * 4 + ((0xE4390900u >> (2 * (tile - 30))) & 3);
    }
    BULK_COMMIT();
    BULK_WAIT(0);
    mbar_arrive_one(c.bar + (B_SE + b) * 8);
    flag_add_rx(f);
  }
}

__device__ __forceinline__ int p2_buf(int w, int i) { return w * 2 + (i & 1); }
__device__ __forceinline__ int p2_blk(int rank, int w, int i) { return ((i ^ w) & 1) == 0 ? 3 - rank : rank; }

template <int N>
__device__ __forceinline__ void row_max(const float (&s)[N], float& m0, float& m1) {
  float a0 = fmaxf(s[0], s[1]), a1 = fmaxf(s[2], s[3]);
#pragma unroll
  for (int i = 1; i < N / 4; i++) {
    m0 = fmaxf(m0, s[4 * i]); a0 = fmaxf(a0, s[4 * i + 1]);
    m1 = fmaxf(m1, s[4 * i + 2]); a1 = fmaxf(a1, s[4 * i + 3]);
  }
  m0 = fmaxf(m0, a0); m1 = fmaxf(m1, a1);
  m0 = fmaxf(m0, __shfl_xor_sync(0xffffffffu, m0, 1));
  m1 = fmaxf(m1, __shfl_xor_sync(0xffffffffu, m1, 1));
  m0 = fmaxf(m0, __shfl_xor_sync(0xffffffffu, m0, 2));
  m1 = fmaxf(m1, __shfl_xor_sync(0xffffffffu, m1, 2));
}
template <bool SUB, int N>
__device__ __forceinline__ void row_exp(const float (&s)[N], uint32_t (&P)[32], float m0, float m1, float& t0, float& t1) {
  float u0 = 0.f, u1 = 0.f;
  t0 = t1 = 0.f;
#pragma unroll
  for (int i = 0; i < N / 4; i++) {
    const float e0 = ex2(SUB ? s[4 * i] - m0 : s[4 * i]), e1 = ex2(SUB ? s[4 * i + 1] - m0 : s[4 * i + 1]);
    const float e2 = ex2(SUB ? s[4 * i + 2] - m1 : s[4 * i + 2]), e3 = ex2(SUB ? s[4 * i + 3] - m1 : s[4 * i + 3]);
    if (i == 0) { t0 = e0; u0 = e1; t1 = e2; u1 = e3; }
    else { t0 += e0; u0 += e1; t1 += e2; u1 += e3; }
    P[2 * i] = pack_bf16(e0, e1);
    P[2 * i + 1] = pack_bf16(e2, e3);
  }
#pragma unroll
  for (int i = N / 2; i < 32; i++) P[i] = 0;
  pin(P);
  t0 += u0; t1 += u1;
}
template <int N>
__device__ __forceinline__ void causal_mask(float (&s)[N], int thr) {
#pragma unroll
  for (int i = 0; i < 8; i++) {
    if (8 * i > thr) s[N - 32 + 4 * i] = -INFINITY;
    if (8 * i + 1 > thr) s[N - 32 + 4 * i + 1] = -INFINITY;
    if (8 * i - 8 > thr) s[N - 32 + 4 * i + 2] = -INFINITY;
    if (8 * i - 7 > thr) s[N - 32 + 4 * i + 3] = -INFINITY;
  }
}
__device__ __forceinline__ void issue_qk(float (&s)[32], uint32_t qd, uint32_t kd) {
  WG_FENCE();
#pragma unroll
  for (int kk = 0; kk < 8; kk++) wgmma_ss64<0>(s, qd + (kk >> 2) * 512 + (kk & 3) * 2, kd + (kk >> 2) * 1024 + (kk & 3) * 2, kk != 0);
  WG_COMMIT();
}
__device__ __forceinline__ void issue_qk(float (&s)[64], uint32_t qd, uint32_t kd) {
  WG_FENCE();
#pragma unroll
  for (int kk = 0; kk < 8; kk++) wgmma_ss128<0>(s, qd + (kk >> 2) * 512 + (kk & 3) * 2, kd + (kk >> 2) * 1024 + (kk & 3) * 2, kk != 0);
  WG_COMMIT();
}
template <int NK>
__device__ __forceinline__ void issue_pv(float (&o)[64], const uint32_t (&P)[32], uint32_t vd, int acc) {
  WG_FENCE();
#pragma unroll
  for (int kk = 0; kk < NK; kk++) wgmma_rs128<1>(o, P[4 * kk], P[4 * kk + 1], P[4 * kk + 2], P[4 * kk + 3], vd + kk * 128, kk != 0 ? 1 : acc);
  WG_COMMIT();
}
__device__ __forceinline__ void stage_done(const Ctx& c, int b) {
  FENCE_ASYNC_SMEM();
  __syncwarp();
  if (c.lane == 0) mbar_arrive(c.bar + (B_SF + b) * 8);
}
__device__ __forceinline__ void p2_epilogue(const float (&o)[64], float s0, float s1, const Ctx& c, int b) {
  stage_tile(o, c.sm + SM_BUF + b * 16384, c, s0, s1);
  stage_done(c, b);
}

struct P2State {
  float m0, m1, l0, l1;
  bool shift;
  float e0, e1;
  int ks;
  int wi, ai;
  uint32_t wb, ab;
  uint32_t qd;
};
#define PROFZ()
__device__ __forceinline__ int wrap5(int q) { return q >= 5 ? q - 5 : q; }
__device__ __forceinline__ void turn_wait(uint32_t ring, int i) { mbar_wait(ring + (i & 3) * 8, (i >> 2) & 1); }
__device__ __forceinline__ void turn_pass(const Ctx& c, uint32_t ring, int i) { if (c.lane == 0) mbar_arrive(ring + (i & 3) * 8); }
__device__ __forceinline__ void p2_scales(P2State& z) {
  float l0 = z.l0, l1 = z.l1;
  l0 += __shfl_xor_sync(0xffffffffu, l0, 1);
  l1 += __shfl_xor_sync(0xffffffffu, l1, 1);
  l0 += __shfl_xor_sync(0xffffffffu, l0, 2);
  l1 += __shfl_xor_sync(0xffffffffu, l1, 2);
  asm("rcp.approx.ftz.f32 %0, %1;" : "=f"(z.e0) : "f"(l0));
  asm("rcp.approx.ftz.f32 %0, %1;" : "=f"(z.e1) : "f"(l1));
}
template <int N>
__device__ __forceinline__ void p2_first(const Ctx& c, P2State& z, float (&o)[64], uint32_t (&Pc)[32], uint32_t (&Pn)[32],
                                         int ks, int vs, int cnt, int acc) {
  float s[N] = {};
  issue_qk(s, z.qd, desc_lo(c.sm + SM_RING, 16) + ks * 2048);
  if (vs >= 0) {
    p2_scales(z);
    issue_pv<8>(o, Pc, desc_lo(c.sm + SM_RING, 16384) + vs * 2048, acc);
  } else {
    WG_COMMIT();
  }
  mbar_expect(z.ab + (z.ai++ & 3) * 8, cnt == 1 ? 8192 : 0);
  PROFZ();
  WG_WAIT(1);
  PROFZ();
  pin(s);
  release(c, B_P2E + ks, cnt);
  causal_mask(s, c.warp * 16 + (c.lane >> 2) - 2 * (c.lane & 3));
  z.m0 = z.m1 = 0.f;
  row_exp<false>(s, Pn, 0.f, 0.f, z.l0, z.l1);
  z.shift = __any_sync(0xffffffffu, !(z.l0 + z.l1 <= SM_HI) || ((c.lane & 3) == 0 && !(fminf(z.l0, z.l1) >= SM_LO)));
  if (__builtin_expect(z.shift, 0)) {
    z.m0 = z.m1 = -INFINITY;
    row_max(s, z.m0, z.m1);
    row_exp<true>(s, Pn, z.m0, z.m1, z.l0, z.l1);
  }
  WG_WAIT(0);
  pin(o);
  if (vs >= 0) release(c, B_P2E + vs, 1);
}

template <bool SECOND>
__device__ __forceinline__ void p2_turn(const Ctx& c, P2State& z, float (&o)[64], uint32_t (&Pc)[32], uint32_t (&Pn)[32],
                                        int eb = -1, bool half = false, int vcnt = 1) {
  float s[64] = {};
  const int ks = z.ks, vs = wrap5(ks + 1);
  PROFZ();
  turn_wait(z.wb, z.wi++);
  PROFZ();
  issue_qk(s, z.qd, desc_lo(c.sm + SM_RING, 16) + ks * 2048);
  const uint32_t vd = desc_lo(c.sm + SM_RING, 16384) + vs * 2048;
  if (SECOND) {
    if (eb >= 0) stage_tile(o, c.sm + SM_BUF + eb * 16384, c, z.e0, z.e1);
    if (half) issue_pv<4>(o, Pc, vd, 0); else issue_pv<8>(o, Pc, vd, 0);
  } else {
    issue_pv<8>(o, Pc, vd, 1);
  }
  turn_pass(c, z.ab, z.ai++);
  if (SECOND) { if (eb >= 0) stage_done(c, eb); }
  PROFZ();
  z.ks = wrap5(ks + 2);
  WG_WAIT(1);
  PROFZ();
  pin(s);
  release(c, B_P2E + ks, 1);
  float t0, t1, a0 = 1.f, a1 = 1.f;
  row_exp<false>(s, Pn, 0.f, 0.f, t0, t1);
  z.shift = __any_sync(0xffffffffu, z.shift || !(t0 + t1 <= SM_HI));
  const bool redo = z.shift;
  if (__builtin_expect(redo, 0)) {
    float n0 = z.m0, n1 = z.m1;
    row_max(s, n0, n1);
    a0 = ex2(z.m0 - n0); a1 = ex2(z.m1 - n1);
    z.m0 = n0; z.m1 = n1;
    z.l0 *= a0; z.l1 *= a1;
    row_exp<true>(s, Pn, z.m0, z.m1, t0, t1);
  }
  WG_WAIT(0);
  pin(o);
  release(c, B_P2E + vs, vcnt);
  if (__builtin_expect(redo, 0)) {
#pragma unroll
    for (int i = 0; i < 16; i++) { o[4 * i] *= a0; o[4 * i + 1] *= a0; o[4 * i + 2] *= a1; o[4 * i + 3] *= a1; }
  }
  z.l0 += t0; z.l1 += t1;
}
__device__ __forceinline__ void copy_p(uint32_t (&d)[32], const uint32_t (&s)[32], int zero) {
#pragma unroll
  for (int i = 0; i < 32; i++) asm volatile("add.s32 %0, %1, %2;" : "=r"(d[i]) : "r"(s[i]), "r"(zero));
}

__device__ __forceinline__ void p2_consumer(const Params& p, const Ctx& c, int rot) {
  const int nit = p.s.r[c.cl].n2;
  const uint32_t fring = c.bar + B_P2F * 8, oring = c.bar + B_ORD * 8;
  float o[64] = {};
  uint32_t Pa[32] = {}, Pb[32] = {};
  P2State z;
  z.e0 = z.e1 = z.l0 = z.l1 = 0.f; z.ks = rot; z.shift = false;
  int acc = 0, n = 0;
  for (int it = 0; it < nit; it++) {
    const int j = p.s.r[c.cl].item[it] & 7, blk = p2_blk(c.rank, c.wg, it);
    const int lng = ((it ^ c.wg) & 1) ^ 1;
    z.qd = desc_lo(c.sm + SM_BUF, 16) + p2_buf(c.wg, it) * 1024;
    if (lng) { z.wb = oring; z.wi = n - it; z.ab = fring; z.ai = n + 1; }
    else { z.wb = fring; z.wi = n + 2; z.ab = oring; z.ai = n - it; }
    PROFZ();
    mbar_wait(c.bar + (B_QF + p2_buf(c.wg, it)) * 8, (it >> 1) & 1);
    turn_wait(fring, n + 1 - lng);
    PROFZ();
    const int vs = it ? wrap5(z.ks + 1) : -1, ks = lng ? z.ks : wrap5(z.ks + (it ? 2 : 1));
    if (blk & 1) p2_first<64>(c, z, o, Pa, Pb, ks, vs, 1 + lng, acc);
    else p2_first<32>(c, z, o, Pa, Pb, ks, vs, 1 + lng, acc);
    z.ks = wrap5(ks + (it == 0 && lng ? 1 : 2));
    PROF(c.wg, 24 + it);
    n += 2 * j + 2;
    int left = 2 * j + lng;
    acc = left != 0;
    if (left == 0) { copy_p(Pa, Pb, p.zero); continue; }
    p2_turn<true>(c, z, o, Pb, Pa, it > 0 ? p2_buf(c.wg, it - 1) : -1, !(blk & 1), 1 + lng);
    while (--left > 0) {
      p2_turn<false>(c, z, o, Pa, Pb);
      if (--left == 0) { copy_p(Pa, Pb, p.zero); break; }
      p2_turn<false>(c, z, o, Pb, Pa);
    }
  }
  {
    if (!acc && nit > 1) p2_epilogue(o, z.e0, z.e1, c, p2_buf(c.wg, nit));
    turn_wait(z.wb, z.wi);
    issue_pv<8>(o, Pa, desc_lo(c.sm + SM_RING, 16384) + z.ks * 2048, acc);
    if (((nit - 1) ^ c.wg) & 1) turn_pass(c, z.ab, z.ai);
    p2_scales(z);
    WG_WAIT(0);
    pin(o);
    release(c, B_P2E + z.ks);
    p2_epilogue(o, z.e0, z.e1, c, p2_buf(c.wg, nit - 1));
    PROF(c.wg, 24 + nit);
  }
}

__device__ __forceinline__ void p2_load_q(const Params& p, const Ctx& c, int it, int w) {
  const int item = p.s.r[c.cl].item[it], h = item >> 3, j = item & 7, b = p2_buf(w, it);
  mbar_expect(c.bar + (B_QF + b) * 8, 16384);
  bulk_load(c.sm + SM_BUF + b * 16384, g_Q + (size_t)(h * 32 + j * 4 + p2_blk(c.rank, w, it)) * 16384, 16384, c.bar + (B_QF + b) * 8, POL(4));
}
__device__ __forceinline__ void wait_p1_free(const Ctx& c, int u1, int s) {
  mbar_wait(c.bar + (B_P1E + 2 * s) * 8, ((u1 - 1 - 2 * s) / 10) & 1);
  mbar_wait(c.bar + (B_P1E + 2 * s + 1) * 8, ((u1 - 2 - 2 * s) / 10) & 1);
}
__device__ __forceinline__ void p2_producer(const Params& p, const Ctx& c, int u1, int rot) {
  const int nit = p.s.r[c.cl].n2;
  int slot = rot, cnt = 0, par = 1, n = 0;
  const uint8_t* pv = nullptr;
  bool pl = false;
  auto load = [&](const uint8_t* src, int expect, uint32_t fb, bool last) {
    if (cnt < 5) {
      if (u1) {
        wait_p1_free(c, u1, slot);
        if (cnt == 0) p2_load_q(p, c, 0, 1);
      }
      cnt++;
    } else {
      if (slot == rot) par ^= 1;
      mbar_wait(c.bar + (B_P2E + slot) * 8, par);
    }
    if (expect) mbar_expect(fb, expect);
    bulk_load_mc(c.sm + SM_RING + slot * 32768 + c.rank * 16384, src, 16384, fb, last ? POL(5) : L2_NORMAL);
    slot = wrap5(slot + 1);
  };
  for (int it = 0; it < nit; it++) {
    const int item = p.s.r[c.cl].item[it], h = item >> 3, j = item & 7;
    if (it == 1 && (c.phases & 16) && p.s.r[c.cl].n1 < 8) flag_wait<true>(F_GATE, 256);
    uint32_t ready = (c.phases & 16) ? 0u : 255u;
    if (it == 0) { if (c.phases & 16) flag_wait<false>(F_Q + item, 4); mbar_wait(c.bar + B_LAD * 8, 0); p2_load_q(p, c, 0, 0); if (!u1) p2_load_q(p, c, 0, 1); }
    for (int t = 2 * j + 1; t >= 0; t--) {
      mask_wait(ready, t >> 1, F_KV + h * 8 + (c.lane & 7), 8);
      const uint8_t* k = g_KV + (size_t)(p.s.slot[h][t >> 1] * 16 + t) * 32768 + c.rank * 16384;
      const uint32_t fb = c.bar + (B_P2F + (n & 3)) * 8;
      const bool last = (p.s.r[c.cl].last[it] >> (t >> 1)) & 1;
      load(k, pv && t != 2 * j ? 65536 : 32768, fb, last);
      if (!(t & 1) && t + 4 <= 2 * j && c.rank == 0) flag_add_rx(F_RD + h * 8 + (t >> 1) + 2);
      if (pv) load(pv, 0, t != 2 * j ? fb : c.bar + (B_ORD + ((n - 1 - it) & 3)) * 8, pl);
      pl = last;
      pv = k + (size_t)NH * 16 * 32768;
      n++;
    }
  }
  load(pv, 32768, c.bar + (B_P2F + (n & 3)) * 8, pl);
}

__device__ __forceinline__ void p2_storer(const Params& p, const Ctx& c, int sfpar) {
  const int nit = p.s.r[c.cl].n2;
  auto load_q = [&](int it, int w) {
    if (c.phases & 16) flag_wait<false>(F_Q + p.s.r[c.cl].item[it], 4);
    p2_load_q(p, c, it, w);
  };
  if (nit > 1) {
    load_q(1, 1); p2_load_q(p, c, 1, 0); }
  for (int i = 0; i < 2 * nit; i++) {
    const int it = i >> 1, w = (it ^ i ^ 1) & 1, b = p2_buf(w, it);
    const int item = p.s.r[c.cl].item[it], h = item >> 3, j = item & 7;
    mbar_wait(c.bar + (B_SF + b) * 8, (sfpar >> b) & 1);
    sfpar ^= 1 << b;
    bulk_store(g_Q + (size_t)(h * 32 + j * 4 + p2_blk(c.rank, w, it)) * 16384, c.sm + SM_BUF + b * 16384, 16384, POL(1));
    BULK_COMMIT();
    BULK_WAIT(0);
    flag_add_rx(F_CTX + j * 64 + h);
    if ((i & 1) && it + 2 < nit) { load_q(it + 2, w); p2_load_q(p, c, it + 2, w ^ 1); }
  }
  release(c, B_DONE);
}

__device__ __forceinline__ int p3_pos(int i, int x) { return i < 4 ? (i + x) & 3 : 4; }
__device__ __forceinline__ void p3_consumer(const Params& p, const Ctx& c, int x) {
  const bool first = p.s.r[c.cl].p3 >= 24;
  const int tile = p.s.r[c.cl].p3 - (first ? 24 : 0), j = tile / 3, nt = tile - 3 * j;
  const int na = first ? 9 : 0, nb = first ? 2 * p.s.nh[tile] : 64 - 2 * p.s.nh[tile];
  const uint32_t ad = desc_lo(c.sm + SM_RING + c.wg * 8192, 16), bd = desc_lo(c.sm + SM_RING + 16384, 4096);
  float acc[96] = {};
  int slot = 0, par = 0, prev = 0;
  float g0 = 0.f, g1 = 0.f;
  const int hold = c.wg && LAG ? na + nb - LAG : -1, pass = c.wg || !LAG ? -1 : na + nb - 1;
#pragma unroll 1
  for (int kb = 0; kb < nb; kb++) {
    if (kb == hold) bar_sync(6, 256);
    mbar_wait(c.bar + (B_P3F + slot) * 8, par);
    if (kb == 0) PROF(c.wg, 39);
    WG_FENCE();
#pragma unroll
    for (int kk = 0; kk < 4; kk++) wgmma_ss192<1>(acc, ad + p3_pos(slot, x) * 2560 + kk * 2, bd + p3_pos(slot, x) * 2560 + (kk >> 1) * 768 + (kk & 1) * 128, kk != 0 ? 1 : kb != 0);
    WG_COMMIT();
    if (kb == pass) bar_arrive(6, 256);
    WG_WAIT(1);
    if (kb > 0) release(c, B_P3E + prev);
    else {
      const float* g = g_gate + j * 256 + c.rank * 128 + c.wg * 64 + c.warp * 16 + (c.lane >> 2);
      g0 = __ldcg(g); g1 = __ldcg(g + 8);
    }
    prev = slot;
    if (++slot == 5) { slot = 0; par ^= 1; }
  }
  WG_WAIT(0);
  pin(acc);
  g0 = 1.f - g0; g1 = 1.f - g1;
#pragma unroll
  for (int i = 0; i < 24; i++) { acc[4 * i] *= g0; acc[4 * i + 1] *= g0; acc[4 * i + 2] *= g1; acc[4 * i + 3] *= g1; }
#pragma unroll 1
  for (int kb = nb; kb < nb + na; kb++) {
    if (kb == hold) bar_sync(6, 256);
    mbar_wait(c.bar + (B_P3F + slot) * 8, par);
    if (kb == 0) PROF(c.wg, 39);
    WG_FENCE();
#pragma unroll
    for (int kk = 0; kk < 4; kk++) wgmma_ss192<1, 1>(acc, ad + p3_pos(slot, x) * 2560 + kk * 128, bd + p3_pos(slot, x) * 2560 + (kk >> 1) * 768 + (kk & 1) * 128, 1);
    WG_COMMIT();
    if (kb == pass) bar_arrive(6, 256);
    WG_WAIT(1);
    if (kb > 0) release(c, B_P3E + prev);
    prev = slot;
    if (++slot == 5) { slot = 0; par ^= 1; }
  }
  WG_WAIT(0);
  pin(acc);
  PROF(c.wg, 40);
  if (first) bar_sync(4 + c.wg, 128);
  mbar_wait(c.bar + B_OUT * 8, 0);
  const int row = (c.lane & 7) + ((c.lane >> 3) & 1) * 8;
  const uint32_t wbase = c.sm + SM_RING + c.wg * 8192 + c.warp * 2048;
  const uint32_t base = wbase + row * 128 + (((c.lane >> 4) ^ (row & 7)) << 4);
#pragma unroll
  for (int i = 0; i < 12; i++) {
    stsm4((base ^ ((i & 3) << 5)) + (i >> 2) * 40960, pack_bf16(acc[8 * i], acc[8 * i + 1]), pack_bf16(acc[8 * i + 2], acc[8 * i + 3]),
          pack_bf16(acc[8 * i + 4], acc[8 * i + 5]), pack_bf16(acc[8 * i + 6], acc[8 * i + 7]));
    if ((i & 3) == 3) {
      FENCE_ASYNC_SMEM();
      bar_sync(4 + c.wg, 128);
      if (c.warp == (i >> 2)) tma2d_add(&p.map_out, c.sm + SM_RING + c.wg * 8192 + c.warp * 40960, nt * 192 + c.warp * 64, j * 256 + c.rank * 128 + c.wg * 64);
    }
  }
  BULK_COMMIT();
  PROF(c.wg, 43);
  BULK_WAIT_READ(0);
  PROF(c.wg, 44);
}

__device__ __forceinline__ void p3_producer(const Params& p, const Ctx& c, int u1, int u2, int rot, int x) {
  const bool first = p.s.r[c.cl].p3 >= 24;
  const int tile = p.s.r[c.cl].p3 - (first ? 24 : 0), j = tile / 3, nt = tile - 3 * j;
  int slot = 0, par = 1, cnt = 0;
  auto wait_free = [&](int s) {
    const int f = wrap5(s + 5 - rot);
    if (f < u2) mbar_wait(c.bar + (B_P2E + s) * 8, ((u2 - 1 - f) / 5) & 1);
    else if (u1) wait_p1_free(c, u1, s);
  };
  asm volatile(ELECT("prefetch.tensormap [%0];") ::"l"(&p.map_o[0]) : "memory");
  asm volatile(ELECT("prefetch.tensormap [%0];") ::"l"(&p.map_out) : "memory");
  if ((c.phases & 16) && p.s.r[c.cl].n1 < 8 && p.s.r[c.cl].n2 < 2) flag_wait<true>(F_GATE, 256);
  uint32_t ready = (c.phases & 16) ? 0u : ~0u;
  const int q1 = first ? p.s.nh[tile] : 31;
  for (int q = first ? 0 : p.s.nh[tile]; q <= q1; q++) {
    const bool brA = first && q == q1;
    const int g = brA ? 32 : p.s.p3_order[j][q];
    if (brA) { if (c.phases & 16) flag_wait<false>(F_CTX + j * 64 + 32, 16); }
    else mask_wait(ready, g, F_CTX + j * 64 + c.lane, 4);
    const int nk = brA ? 9 : 2, k0 = (brA ? 0 : g * 128) + c.rank * 32;
    const uint8_t* a = brA ? g_oA + (j * 4 + c.rank * 2) * 73728 : g_Q + (size_t)(g * 32 + j * 4 + c.rank * 2) * 16384;
    const CUtensorMap* m = &p.map_o[brA];
    for (int i = 0; i < nk; i++) {
      const uint32_t st = c.sm + SM_RING + p3_pos(slot, x) * 40960, fb = c.bar + (B_P3F + slot) * 8;
      if (cnt < 4) { wait_free(p3_pos(cnt, x)); wait_free(p3_pos(cnt, x) + 1); }
      else if (cnt == 4) mbar_wait(c.bar + B_DONE * 8, 0);
      else mbar_wait(c.bar + (B_P3E + slot) * 8, par);
      cnt++;
      mbar_expect(fb, 40960);
      bulk_load(st, a + i * 8192, 8192, fb, POL(3));
      bulk_load(st + 8192, a + (nk + i) * 8192, 8192, fb, POL(3));
      tma3d_mc(st + 16384 + c.rank * 12288, m, 0, k0 + i * 64, nt * 3, fb);
      if (++slot == 5) { slot = 0; par ^= 1; }
    }
  }
}

__device__ __forceinline__ float bf_lo(uint32_t w) { return __uint_as_float(w << 16); }
__device__ __forceinline__ float bf_hi(uint32_t w) { return __uint_as_float(w & 0xffff0000u); }

__device__ __forceinline__ void gate_rows(const Params& p, int row0, int lane) {
  const uint4* x = reinterpret_cast<const uint4*>(p.x + (size_t)(row0 + (lane >> 2)) * DM) + (lane & 3);
  const uint4* w = reinterpret_cast<const uint4*>(p.gate_w) + (lane & 3);
  float a = 0.f;
#pragma unroll 1
  for (int b = 0; b < 3; b++) {
    uint4 u[6];
#pragma unroll
    for (int i = 0; i < 6; i++) u[i] = __ldg(x + (b * 6 + i) * 4);
#pragma unroll
    for (int i = 0; i < 6; i++) {
      const uint4 v = __ldg(w + (b * 6 + i) * 4);
      a = fmaf(bf_lo(u[i].x), bf_lo(v.x), a); a = fmaf(bf_hi(u[i].x), bf_hi(v.x), a);
      a = fmaf(bf_lo(u[i].y), bf_lo(v.y), a); a = fmaf(bf_hi(u[i].y), bf_hi(v.y), a);
      a = fmaf(bf_lo(u[i].z), bf_lo(v.z), a); a = fmaf(bf_hi(u[i].z), bf_hi(v.z), a);
      a = fmaf(bf_lo(u[i].w), bf_lo(v.w), a); a = fmaf(bf_hi(u[i].w), bf_hi(v.w), a);
    }
  }
  a += __shfl_xor_sync(0xffffffffu, a, 1);
  a += __shfl_xor_sync(0xffffffffu, a, 2);
  if ((lane & 3) == 0) g_gate[row0 + (lane >> 2)] = 1.f / (1.f + __expf(-a));
}

__device__ __forceinline__ void lds10(uint32_t (&k)[10], uint32_t a) {
  asm volatile("ld.shared.v2.u32 {%0, %1}, [%10];\nld.shared.v2.u32 {%2, %3}, [%10+8];\nld.shared.v2.u32 {%4, %5}, [%10+16];\n"
               "ld.shared.v2.u32 {%6, %7}, [%10+24];\nld.shared.v2.u32 {%8, %9}, [%10+32];"
               : "=r"(k[0]), "=r"(k[1]), "=r"(k[2]), "=r"(k[3]), "=r"(k[4]), "=r"(k[5]), "=r"(k[6]), "=r"(k[7]), "=r"(k[8]), "=r"(k[9]) : "r"(a));
}
__device__ __forceinline__ void local_attn(const Params& p, const Ctx& c, int rb, int hs) {
  const int lane = c.lane, grp = rb >> 2, par = lane >> 4, i0 = 2 * (lane & 15);
  const uint32_t buf = c.sm + SM_BUF + (c.warp - 2) * 8192, bqk = c.bar + (B_LA + (c.warp - 2) * 2) * 8, bv = bqk + 8;
  const uint32_t mine = buf + 2304 + par * 160 + i0 * 4;
  const bool flags = c.phases & 16;
  auto fetch_qk = [&](int i) {
    if (flags && !(i & 1)) {
      const int q = i >> 1;
      const int tgt = q == 0 ? 24 : q == 3 ? 8 : 12;
      flag_wait<false>(F_QKVA + (grp - (grp > 0 && (rb & 3) == 0 ? par : 0)) * 4 + q, tgt);
    }
    mbar_expect(bqk, 5184);
    tma3d(buf, &p.map_t[0], rb * 32 + 8, 0, 9 * (4 * i + hs), bqk, POL(2));
    tma3d(buf + 2304, &p.map_t[1], rb * 32, 0, 288 + 9 * (4 * i + hs), bqk, POL(2));
  };
  auto fetch_v = [&](int i) { mbar_expect(bv, 2880); tma3d(buf + 5248, &p.map_t[1], rb * 32, 0, 576 + 9 * (4 * i + hs), bv, POL(2)); };
  fetch_qk(0);
  if (flags) flag_wait<true>(F_GATE, 256);
#pragma unroll 1
  for (int q = 0; q < 8; q++) {
    fetch_v(q);
    float a[8], b[8];
#pragma unroll
    for (int w = 0; w < 8; w++) a[w] = b[w] = 0.f;
    mbar_wait(bqk, q & 1);
    PROFB(1 + 2 * q);
#pragma unroll 1
    for (int j = 0; j < 9; j++) {
      uint32_t x, y, k[10];
      asm volatile("ld.shared.v2.u32 {%0, %1}, [%2];" : "=r"(x), "=r"(y) : "r"(buf + lane * 8 + j * 256));
      lds10(k, mine + j * 320);
      const float xl = bf_lo(x), xh = bf_hi(x), yl = bf_lo(y), yh = bf_hi(y);
#pragma unroll
      for (int m = 1; m < 10; m++) {
        const float kl = bf_lo(k[m]), kh = bf_hi(k[m]);
        if (m < 9) a[8 - m] = fmaf(xl, kl, fmaf(xh, kh, a[8 - m]));
        if (m > 1) b[9 - m] = fmaf(yl, kl, fmaf(yh, kh, b[9 - m]));
      }
    }
    __syncwarp();
    if (q < 7) fetch_qk(q + 1);
    constexpr float SC = 0.23570226039551584f * 1.4426950408889634f;
    const float* gp = g_gate + rb * 64 + 2 * i0 + par;
    const float ga = __ldcg(gp), gb = __ldcg(gp + 2);
    float ma = a[0], mb = b[0];
#pragma unroll
    for (int w = 1; w < 8; w++) {
      if (rb == 0) {
        if (i0 < w) a[w] = -INFINITY;
        if (i0 + 1 < w) b[w] = -INFINITY;
      }
      ma = fmaxf(ma, a[w]); mb = fmaxf(mb, b[w]);
    }
    float la = 0.f, lb = 0.f;
#pragma unroll
    for (int w = 0; w < 8; w++) {
      a[w] = ex2((a[w] - ma) * SC); b[w] = ex2((b[w] - mb) * SC);
      la += a[w]; lb += b[w];
    }
    la = __fdividef(ga, la); lb = __fdividef(gb, lb);
#pragma unroll
    for (int w = 0; w < 8; w++) { a[w] *= la; b[w] *= lb; }
    uint8_t* dst = g_oA + rb * 73728 + ((i0 & 2) + par) * 4;
    mbar_wait(bv, q & 1);
#pragma unroll 1
    for (int j = 0; j < 9; j++) {
      uint32_t v[10];
      lds10(v, mine + 2944 + j * 320);
      float a0 = 0.f, a1 = 0.f, b0 = 0.f, b1 = 0.f;
#pragma unroll
      for (int m = 1; m < 10; m++) {
        const float vl = bf_lo(v[m]), vh = bf_hi(v[m]);
        if (m < 9) { a0 = fmaf(a[8 - m], vl, a0); a1 = fmaf(a[8 - m], vh, a1); }
        if (m > 1) { b0 = fmaf(b[9 - m], vl, b0); b1 = fmaf(b[9 - m], vh, b1); }
      }
      const uint32_t wa = pack_bf16(a0, a1), wb = pack_bf16(b0, b1);
      const uint32_t got = __shfl_xor_sync(0xffffffffu, par ? wa : wb, 16);
      const uint32_t r0 = par ? got : wa, r1 = par ? wb : got;
      const int col = 18 * (4 * q + hs) + 2 * j, o = col * 128 + ((((i0 >> 2) ^ col) & 7) << 4);
      *reinterpret_cast<uint32_t*>(dst + o) = __byte_perm(r0, r1, 0x5410);
      *reinterpret_cast<uint32_t*>(dst + ((o + 128) ^ 16)) = __byte_perm(r0, r1, 0x7632);
    }
    __syncwarp();
    PROFB(2 + 2 * q);
  }
  mbar_arrive_one(c.bar + B_LAD * 8);
  flag_add(F_CTX + grp * 64 + 32);
}

__global__ void __cluster_dims__(2, 1, 1) __launch_bounds__(384, 1) fused_kernel(const __grid_constant__ Params p) {
  extern __shared__ uint8_t smem_raw[];
  Ctx c;
  c.sm = ((uint32_t)__cvta_generic_to_shared(smem_raw) + 1023u) & ~1023u;
  c.bar = c.sm + SM_BAR;
  c.lane = threadIdx.x & 31;
  const int wid = __shfl_sync(0xffffffffu, threadIdx.x >> 5, 0);
  if (wid < 6) asm volatile("prefetch.tensormap [%0];" ::"l"(&p.map_a[0] + wid) : "memory");
  c.wg = wid >> 2;
  c.warp = wid & 3;
  PROF(c.wg, 0);
  PROFG(61);
  c.cl = (blockIdx.x + (wid >> 4)) >> 1;
  c.rank = blockIdx.x & 1;
  c.rbar = mapa(c.bar, c.lane & 1);
  {
    const int w = wid, cnt = (((int)(B_CNT >> (4 * w)) - 1) & 15) + 1;
    if (w < 11) {
#pragma unroll
      for (int i = 0; i < 8; i++) asm volatile("mbarrier.init.shared::cta.b64 [%0], %1;" ::"r"(c.bar + w * 64 + i * 8), "r"(cnt));
    }
    asm volatile("fence.mbarrier_init.release.cluster;" ::: "memory");
  }
  if (c.wg == 2) PROF(2, 56);
  asm volatile("barrier.cluster.arrive.relaxed;" ::: "memory");
  c.phases = p.s.r[c.cl].phases;
  const bool do1 = p.s.r[c.cl].n1 > 0, do2 = p.s.r[c.cl].n2 > 0, do3 = p.s.r[c.cl].p3 != 255;
  if (do1 && c.wg == 2 && c.warp == 0) {
    const int type = p.s.r[c.cl].slab >> 3;
    PROF(2, 57);
    FENCE_ASYNC_SMEM();
    mbar_expect(c.bar + B_P1F * 8, type ? 32768 : 16384);
    tma2d(type ? c.sm + SM_BUF + 32768 : c.sm + SM_RING, &p.map_a[type], type ? 512 : 0, (p.s.r[c.cl].slab & 7) * 256 + c.rank * 128, c.bar + B_P1F * 8);
    PROF(2, 58);
  }
  asm volatile("barrier.cluster.wait.acquire;" ::: "memory");
  if (c.wg == 2) PROF(2, 59);
  if (do1 && c.wg == 2 && c.warp == 0) {
    const int type = p.s.r[c.cl].slab >> 3, tile = p.s.r[c.cl].tile[0] & 63;
    if (!type) mbar_expect(c.bar + (B_P1F + 1) * 8, 16384);
    tma2d_mc(c.sm + SM_RING + (1 - type) * 16384 + c.rank * 8192, &p.map_w[type * 2 + (tile >> 5)], (tile & 31) * 128 + c.rank * 64, type ? 512 : 0, c.bar + (B_P1F + 1 - type) * 8);
  }

  if (c.wg < 2) {
    PROF(c.wg, 4);
    asm volatile("setmaxnreg.inc.sync.aligned.u32 224;");
    if (c.wg == 1) {
      if (do1) bar_arrive(ORDER, 256);
      if (c.lane == 0) mbar_arrive(c.bar + B_P2F * 8);
    }
    if (do1) p1_consumer(p, c);
    if (do2) p2_consumer(p, c, p.s.r[c.cl].rot);
    if (do3) p3_consumer(p, c, p.s.r[c.cl].x3);
    PROF(c.wg, 63);
    PROFG(62);
    if (c.lane == 0) mbar_arrive(c.bar + B_FIN * 8);
    __syncwarp();
    cluster_sync();
  } else {
    asm volatile("setmaxnreg.dec.sync.aligned.u32 56;");
    if (c.warp == 0) {
      PROF(2, 60);
      if (do1) p1_producer(p, c);
      if (do2) p2_producer(p, c, p.s.r[c.cl].u1, p.s.r[c.cl].rot);
      if (do3) p3_producer(p, c, p.s.r[c.cl].u1, p.s.r[c.cl].u2, p.s.r[c.cl].rot, p.s.r[c.cl].x3);
    } else if (c.warp == 1) {
      int sfpar = 0;
      if (do1) {
        p1_storer(p, c);
        sfpar = (p.s.r[c.cl].n1 & 1) * 10;
      }
      if (do2) p2_storer(p, c, sfpar);
      else { mbar_wait(c.bar + B_LAD * 8, 0); release(c, B_DONE); }
      if (do3) {
        const int task = p.s.r[c.cl].p3;
        if (task >= 24) {
          const int j = (task - 24) / 3, nt = task - 24 - 3 * j;
          uint4* o = reinterpret_cast<uint4*>(p.out + (size_t)(j * 256 + c.rank * 128 + (c.lane >> 3)) * DM + nt * 192) + (c.lane & 7);
#pragma unroll 4
          for (int r = 0; r < 32; r++) o[r * 288] = o[r * 288 + 8] = o[r * 288 + 16] = make_uint4(0u, 0u, 0u, 0u);
          __syncwarp();
          flag_add(F_OUT + (task - 24) * 2 + c.rank);
        } else if (c.phases & 16) {
          flag_wait<false, 256>(F_OUT + task * 2 + c.rank, 1);
        }
        mbar_arrive_one(c.bar + B_OUT * 8);
      }
    } else {
      const int bw = blockIdx.x * 2 + (c.warp - 2);
      if ((c.phases & 1) && bw < 256) {
        gate_rows(p, bw * 8, c.lane);
        __syncwarp();
        flag_add(F_GATE);
      }
      if (p.s.r[c.cl].bg != 255) local_attn(p, c, p.s.r[c.cl].bg, bw & 3);
      else if (c.lane == 0) mbar_arrive(c.bar + B_LAD * 8);
    }
    __syncwarp();
    bar_sync(3, 128);
    if (c.warp == 0 && (c.phases & 4)) {
      int last = 0;
      if (c.lane == 0) { __threadfence(); last = atomicAdd(g_flags + F_DONE, 1) == 2 * NCL - 1; }
      if (__shfl_sync(0xffffffffu, last, 0)) for (int i = c.lane; i < F_NUM; i += 32) g_flags[i] = 0;
    }
    if (c.warp == 1) mbar_wait(c.bar + B_FIN * 8, 0);
    __syncwarp();
    cluster_sync();
  }
}

SCHED_DECL Sched k_sched = {
  {{0,29,1,28,0,{203,0,0,0,0,0,0,0,0,0,0},{0,0,0,0,0,0,0,0,0,0,0},{69,40,70,35,1,14,9,4,29,18,15,31,12,17,2,11,20,27,13,23,16,22,28,26,19,25,21,30,24,0}},
   {1,30,1,45,1,{202,0,0,0,0,0,0,0,0,0,0},{0,0,0,0,0,0,0,0,0,0,0},{69,40,3,32,6,1,9,4,29,14,18,15,31,12,17,2,11,20,27,13,23,26,28,16,19,22,25,30,21,24}},
   {2,30,2,255,2,{242,169,0,0,0,0,0,0,0,0,0},{0,0,0,0,0,0,0,0,0,0,0},{71,40,3,32,6,1,4,14,15,9,18,29,12,31,20,2,11,17,13,27,23,28,16,22,26,19,25,30,21,24}},
   {3,28,2,255,3,{208,173,0,0,0,0,0,0,0,0,0},{0,63,0,0,0,0,0,0,0,0,0},{72,39,5,32,6,14,9,4,15,18,29,12,31,2,11,20,17,13,27,23,16,28,22,26,19,25,30,21,0,0}},
   {4,29,1,33,4,{130,0,0,0,0,0,0,0,0,0,0},{0,0,0,0,0,0,0,0,0,0,0},{71,40,128,37,6,14,4,9,18,15,29,31,12,2,17,20,11,13,27,23,16,28,22,26,19,25,21,30,24,0}},
   {5,28,1,25,5,{205,0,0,0,0,0,0,0,0,0,0},{32,0,0,0,0,0,0,0,0,0,0},{67,39,128,37,6,14,41,15,18,29,31,12,2,17,11,20,13,27,23,16,28,22,26,25,19,21,30,24,0,0}},
   {6,27,0,2,6,{0,0,0,0,0,0,0,0,0,0,0},{0,0,0,0,0,0,0,0,0,0,0},{71,8,128,42,1,9,36,18,29,31,12,2,17,11,20,13,27,23,16,28,22,26,25,19,85,30,24,0,0,0}},
   {7,26,0,6,7,{0,0,0,0,0,0,0,0,0,0,0},{0,0,0,0,0,0,0,0,0,0,0},{69,7,128,6,78,100,82,93,95,76,66,81,75,84,77,91,87,80,92,86,90,89,83,94,85,88,0,0,0,0}},
   {0,29,1,37,8,{204,0,0,0,0,0,0,0,0,0,0},{31,0,0,0,0,0,0,0,0,0,0},{101,7,102,0,33,46,41,36,61,50,47,63,44,49,34,43,52,59,45,55,48,54,60,58,51,57,53,62,56,0}},
   {1,30,3,255,9,{201,241,240,0,0,0,0,0,0,0,0},{0,0,1,0,0,0,0,0,0,0,0},{101,7,35,10,38,33,41,36,61,46,50,47,63,44,49,34,43,52,59,45,55,58,60,48,51,54,57,62,53,56}},
   {2,30,1,44,10,{154,0,0,0,0,0,0,0,0,0,0},{7,0,0,0,0,0,0,0,0,0,0},{103,5,35,10,38,33,36,46,47,41,50,61,44,63,52,34,43,49,45,59,55,60,48,54,58,51,57,62,53,56}},
   {3,30,1,41,11,{210,0,0,0,0,0,0,0,0,0,0},{7,0,0,0,0,0,0,0,0,0,0},{104,3,37,10,38,46,41,36,47,50,61,44,63,34,43,52,49,45,59,55,48,60,54,58,51,57,62,53,24,56}},
   {4,29,2,43,12,{200,129,0,0,0,0,0,0,0,0,0},{0,0,0,0,0,0,0,0,0,0,0},{103,3,96,10,38,46,36,41,50,47,61,63,44,34,49,52,43,45,59,55,48,60,54,58,51,57,53,62,56,0}},
   {5,28,1,34,13,{179,0,0,0,0,0,0,0,0,0,0},{8,0,0,0,0,0,0,0,0,0,0},{99,8,96,10,38,46,4,47,50,61,63,44,34,49,43,52,45,59,55,48,60,54,58,57,51,53,62,56,0,0}},
   {6,27,0,9,14,{0,0,0,0,0,0,0,0,0,0,0},{0,0,0,0,0,0,0,0,0,0,0},{103,40,96,6,33,41,15,50,61,63,44,34,49,43,52,45,59,55,48,60,54,58,57,51,117,62,56,0,0,0}},
   {7,26,1,32,15,{181,0,0,0,0,0,0,0,0,0,0},{48,0,0,0,0,0,0,0,0,0,0},{101,39,96,38,110,79,114,125,127,108,98,113,107,116,109,123,119,112,124,118,122,121,115,126,117,120,0,0,0,0}},
   {0,6,5,255,255,{86,126,251,183,171,0,0,0,0,0,0},{0,0,0,128,0,0,0,0,0,0,0},{72,39,3,32,10,42,0,0,0,0,0,0,0,0,0,0,0,0,0,0,0,0,0,0,0,0,0,0,0,0}},
   {1,4,7,5,255,{27,3,38,97,19,185,176,0,0,0,0},{0,0,0,0,0,0,0,0,0,0,0},{72,39,128,42,0,0,0,0,0,0,0,0,0,0,0,0,0,0,0,0,0,0,0,0,0,0,0,0,0,0}},
   {2,4,6,39,255,{70,50,123,95,182,168,0,0,0,0,0},{0,0,0,128,64,0,0,0,0,0,0},{72,37,128,42,0,0,0,0,0,0,0,0,0,0,0,0,0,0,0,0,0,0,0,0,0,0,0,0,0,0}},
   {3,6,5,255,255,{85,127,141,228,172,0,0,0,0,0,0},{0,128,0,0,0,0,0,0,0,0,0},{71,35,128,42,1,33,0,0,0,0,0,0,0,0,0,0,0,0,0,0,0,0,0,0,0,0,0,0,0,0}},
   {4,6,6,10,255,{0,25,119,121,223,88,0,0,0,0,0},{0,0,0,0,0,1,0,0,0,0,0},{72,35,5,42,1,33,0,0,0,0,0,0,0,0,0,0,0,0,0,0,0,0,0,0,0,0,0,0,0,0}},
   {5,8,6,8,255,{80,83,122,23,186,224,0,0,0,0,0},{0,0,0,0,0,0,0,0,0,0,0},{71,40,5,42,1,33,9,36,0,0,0,0,0,0,0,0,0,0,0,0,0,0,0,0,0,0,0,0,0,0}},
   {6,8,7,21,255,{112,84,113,236,250,105,136,0,0,0,0},{0,0,0,0,0,0,0,0,0,0,0},{67,5,74,38,78,46,4,47,0,0,0,0,0,0,0,0,0,0,0,0,0,0,0,0,0,0,0,0,0,0}},
   {7,7,6,12,255,{8,1,79,234,109,184,0,0,0,0,0},{0,0,0,0,0,0,0,0,0,0,0},{67,8,74,65,73,68,111,0,0,0,0,0,0,0,0,0,0,0,0,0,0,0,0,0,0,0,0,0,0,0}},
   {8,19,3,35,16,{16,219,247,0,0,0,0,0,0,0,0},{0,0,128,0,0,0,0,0,0,0,0},{135,36,3,43,14,39,104,18,15,76,31,20,13,80,11,28,25,21,24,0,0,0,0,0,0,0,0,0,0,0}},
   {9,18,4,255,17,{96,231,178,170,0,0,0,0,0,0,0},{0,0,4,0,0,0,0,0,0,0,0},{69,41,0,10,108,93,14,45,4,76,130,91,20,90,28,89,94,88,0,0,0,0,0,0,0,0,0,0,0,0}},
   {10,19,2,29,18,{108,157,0,0,0,0,0,0,0,0,0},{0,48,0,0,0,0,0,0,0,0,0},{135,41,102,6,35,44,79,45,18,84,130,11,17,27,16,19,26,21,24,0,0,0,0,0,0,0,0,0,0,0}},
   {11,18,3,19,19,{98,161,209,0,0,0,0,0,0,0,0},{0,0,0,0,0,0,0,0,0,0,0},{136,41,0,6,35,44,14,18,45,29,31,11,17,27,28,22,19,30,0,0,0,0,0,0,0,0,0,0,0,0}},
   {12,18,3,27,20,{18,187,206,0,0,0,0,0,0,0,0},{0,0,64,0,0,0,0,0,0,0,0},{135,161,0,6,39,14,9,40,15,31,130,20,13,27,22,26,25,21,0,0,0,0,0,0,0,0,0,0,0,0}},
   {13,20,3,40,21,{160,106,213,0,0,0,0,0,0,0,0},{0,0,56,0,0,0,0,0,0,0,0},{67,36,5,38,14,35,44,18,29,45,12,17,13,27,16,22,26,30,21,24,0,0,0,0,0,0,0,0,0,0}},
   {14,18,4,255,22,{232,221,174,192,0,0,0,0,0,0,0},{0,1,0,0,0,0,0,0,0,0,0},{135,36,0,43,73,39,4,18,40,31,130,20,13,23,28,26,25,30,0,0,0,0,0,0,0,0,0,0,0,0}},
   {15,18,3,255,23,{89,188,175,0,0,0,0,0,0,0,0},{0,0,192,0,0,0,0,0,0,0,0},{69,74,37,38,14,4,39,15,29,40,12,17,20,27,16,22,25,30,0,0,0,0,0,0,0,0,0,0,0,0}},
   {8,18,5,38,24,{32,90,218,227,177,0,0,0,0,0,0},{0,0,0,15,3,0,0,0,0,0,0},{136,41,0,10,35,44,109,9,4,29,130,17,27,86,23,26,19,30,0,0,0,0,0,0,0,0,0,0,0,0}},
   {9,17,2,14,25,{144,165,0,0,0,0,0,0,0,0,0},{0,0,0,0,0,0,0,0,0,0,0},{136,161,34,1,73,82,104,15,95,81,75,77,23,83,16,22,85,0,0,0,0,0,0,0,0,0,0,0,0,0}},
   {10,17,3,36,26,{72,91,215,0,0,0,0,0,0,0,0},{0,0,128,0,0,0,0,0,0,0,0},{136,161,107,68,39,14,104,9,29,31,12,87,13,92,22,89,94,0,0,0,0,0,0,0,0,0,0,0,0,0}},
   {11,19,2,31,27,{107,158,0,0,0,0,0,0,0,0,0},{0,112,0,0,0,0,0,0,0,0,0},{135,161,34,1,39,9,79,40,4,76,130,20,13,23,26,16,25,21,24,0,0,0,0,0,0,0,0,0,0,0}},
   {12,18,2,15,28,{92,128,0,0,0,0,0,0,0,0,0},{0,0,0,0,0,0,0,0,0,0,0},{136,165,34,1,108,4,18,45,29,76,17,11,23,80,28,19,94,88,0,0,0,0,0,0,0,0,0,0,0,0}},
   {13,17,3,24,29,{120,135,131,0,0,0,0,0,0,0,0},{1,0,15,0,0,0,0,0,0,0,0},{135,41,10,43,73,39,4,15,40,31,130,11,20,23,28,19,25,0,0,0,0,0,0,0,0,0,0,0,0,0}},
   {14,18,3,18,30,{248,139,216,0,0,0,0,0,0,0,0},{0,0,0,0,0,0,0,0,0,0,0},{67,41,10,1,35,44,79,29,45,76,75,17,27,80,22,19,85,88,0,0,0,0,0,0,0,0,0,0,0,0}},
   {15,19,2,255,31,{134,245,0,0,0,0,0,0,0,0,0},{0,0,0,0,0,0,0,0,0,0,0},{67,32,42,43,73,35,44,18,95,45,130,11,13,23,28,26,19,21,24,0,0,0,0,0,0,0,0,0,0,0}},
   {8,3,4,13,255,{68,14,74,22,0,0,0,0,0,0,0},{0,0,0,0,0,0,0,0,0,0,0},{69,161,65,0,0,0,0,0,0,0,0,0,0,0,0,0,0,0,0,0,0,0,0,0,0,0,0,0,0,0}},
   {9,3,4,3,255,{59,13,37,101,0,0,0,0,0,0,0},{0,0,0,0,0,0,0,0,0,0,0},{135,165,102,0,0,0,0,0,0,0,0,0,0,0,0,0,0,0,0,0,0,0,0,0,0,0,0,0,0,0}},
   {10,4,4,20,255,{7,239,164,104,0,0,0,0,0,0,0},{0,0,0,0,0,0,0,0,0,0,0},{69,165,3,1,0,0,0,0,0,0,0,0,0,0,0,0,0,0,0,0,0,0,0,0,0,0,0,0,0,0}},
   {11,3,5,255,255,{62,117,253,189,246,0,0,0,0,0,0},{0,0,0,0,126,0,0,0,0,0,0},{67,165,102,0,0,0,0,0,0,0,0,0,0,0,0,0,0,0,0,0,0,0,0,0,0,0,0,0,0,0}},
   {12,3,6,255,255,{66,54,150,110,212,195,0,0,0,0,0},{0,0,0,0,0,0,0,0,0,0,0},{160,170,102,0,0,0,0,0,0,0,0,0,0,0,0,0,0,0,0,0,0,0,0,0,0,0,0,0,0,0}},
   {13,3,7,255,255,{56,5,118,99,217,133,198,0,0,0,0},{0,0,0,0,0,0,0,0,0,0,0},{136,161,65,0,0,0,0,0,0,0,0,0,0,0,0,0,0,0,0,0,0,0,0,0,0,0,0,0,0,0}},
   {14,3,6,255,255,{29,82,151,20,226,199,0,0,0,0,0},{0,0,0,0,0,255,0,0,0,0,0},{136,161,6,0,0,0,0,0,0,0,0,0,0,0,0,0,0,0,0,0,0,0,0,0,0,0,0,0,0,0}},
   {15,3,6,255,255,{67,4,114,103,230,197,0,0,0,0,0},{0,0,0,0,0,0,0,0,0,0,0},{135,36,6,0,0,0,0,0,0,0,0,0,0,0,0,0,0,0,0,0,0,0,0,0,0,0,0,0,0,0}},
   {8,3,6,47,255,{58,28,34,125,252,207,0,0,0,0,0},{0,0,0,0,31,128,0,0,0,0,0},{70,165,34,0,0,0,0,0,0,0,0,0,0,0,0,0,0,0,0,0,0,0,0,0,0,0,0,0,0,0}},
   {9,4,6,255,255,{87,75,235,140,180,244,0,0,0,0,0},{0,0,0,0,0,0,0,0,0,0,0},{160,170,107,99,0,0,0,0,0,0,0,0,0,0,0,0,0,0,0,0,0,0,0,0,0,0,0,0,0,0}},
   {10,3,8,30,255,{60,26,11,124,162,220,153,155,0,0,0},{0,0,0,0,0,0,0,8,0,0,0},{160,170,0,0,0,0,0,0,0,0,0,0,0,0,0,0,0,0,0,0,0,0,0,0,0,0,0,0,0,0}},
   {11,3,6,255,255,{63,77,33,21,229,196,0,0,0,0,0},{160,0,0,0,0,31,0,0,0,0,0},{160,170,107,0,0,0,0,0,0,0,0,0,0,0,0,0,0,0,0,0,0,0,0,0,0,0,0,0,0,0}},
   {12,3,5,16,255,{30,49,233,149,94,0,0,0,0,0,0},{0,0,0,0,126,0,0,0,0,0,0},{100,5,107,0,0,0,0,0,0,0,0,0,0,0,0,0,0,0,0,0,0,0,0,0,0,0,0,0,0,0}},
   {13,3,4,11,255,{61,52,237,100,0,0,0,0,0,0,0},{0,0,0,3,0,0,0,0,0,0,0},{64,165,6,0,0,0,0,0,0,0,0,0,0,0,0,0,0,0,0,0,0,0,0,0,0,0,0,0,0,0}},
   {14,3,5,22,255,{65,6,116,102,138,0,0,0,0,0,0},{0,0,0,0,0,0,0,0,0,0,0},{69,165,34,0,0,0,0,0,0,0,0,0,0,0,0,0,0,0,0,0,0,0,0,0,0,0,0,0,0,0}},
   {15,3,7,255,255,{71,10,148,17,163,159,194,0,0,0,0},{224,0,0,0,0,128,0,0,0,0,0},{136,41,65,0,0,0,0,0,0,0,0,0,0,0,0,0,0,0,0,0,0,0,0,0,0,0,0,0,0,0}},
   {8,3,5,7,255,{47,9,76,249,166,0,0,0,0,0,0},{64,0,0,0,127,0,0,0,0,0,0},{160,170,102,0,0,0,0,0,0,0,0,0,0,0,0,0,0,0,0,0,0,0,0,0,0,0,0,0,0,0}},
   {9,4,4,17,255,{42,53,238,93,0,0,0,0,0,0,0},{0,0,0,0,0,0,0,0,0,0,0},{100,3,6,103,0,0,0,0,0,0,0,0,0,0,0,0,0,0,0,0,0,0,0,0,0,0,0,0,0,0}},
   {10,3,4,1,255,{57,55,115,143,0,0,0,0,0,0,0},{0,0,0,0,0,0,0,0,0,0,0},{100,98,10,0,0,0,0,0,0,0,0,0,0,0,0,0,0,0,0,0,0,0,0,0,0,0,0,0,0,0}},
   {11,3,3,0,255,{31,39,191,0,0,0,0,0,0,0,0},{30,128,0,0,0,0,0,0,0,0,0},{100,5,10,0,0,0,0,0,0,0,0,0,0,0,0,0,0,0,0,0,0,0,0,0,0,0,0,0,0,0}},
   {12,4,6,23,255,{48,44,81,36,146,142,0,0,0,0,0},{0,0,0,0,0,112,0,0,0,0,0},{105,3,10,99,0,0,0,0,0,0,0,0,0,0,0,0,0,0,0,0,0,0,0,0,0,0,0,0,0,0}},
   {13,3,6,46,255,{69,2,73,147,167,214,0,0,0,0,0},{0,0,0,0,0,64,0,0,0,0,0},{160,170,34,0,0,0,0,0,0,0,0,0,0,0,0,0,0,0,0,0,0,0,0,0,0,0,0,0,0,0}},
   {14,4,8,255,255,{40,45,12,254,132,225,243,193,0,0,0},{0,0,0,0,0,0,0,0,0,0,0},{160,170,102,78,0,0,0,0,0,0,0,0,0,0,0,0,0,0,0,0,0,0,0,0,0,0,0,0,0,0}},
   {15,3,4,4,255,{64,46,78,111,0,0,0,0,0,0,0},{0,0,0,0,0,0,0,0,0,0,0},{64,161,34,0,0,0,0,0,0,0,0,0,0,0,0,0,0,0,0,0,0,0,0,0,0,0,0,0,0,0}},
   {6,2,7,26,255,{41,15,145,35,137,222,156,0,0,0,0},{0,0,0,0,0,0,0,0,0,0,0},{99,37,0,0,0,0,0,0,0,0,0,0,0,0,0,0,0,0,0,0,0,0,0,0,0,0,0,0,0,0}},
   {7,5,7,42,255,{24,43,51,255,190,211,152,0,0,0,0},{0,0,0,0,3,0,0,0,0,0,0},{99,40,106,97,105,0,0,0,0,0,0,0,0,0,0,0,0,0,0,0,0,0,0,0,0,0,0,0,0,0}}},
  {7,1,7,1,4,6,5,6,7,7,7,1,7,1,5,5,6,4,5,7,4,4,6,6},
  {{7,8,5,6,3,0,1,10,14,9,15,18,4,12,29,31,2,20,17,13,27,16,22,11,23,28,26,25,19,21,30,24},
   {5,7,8,3,0,6,10,1,9,29,18,14,15,4,31,12,17,2,11,27,13,20,23,26,19,28,16,22,25,30,21,24},
   {7,8,5,3,0,10,6,4,1,14,15,9,18,29,20,31,2,12,11,17,23,13,27,28,16,22,19,25,26,30,21,24},
   {7,8,3,5,0,10,6,1,9,14,15,18,4,29,12,31,2,11,20,17,13,27,23,28,22,16,26,19,25,30,21,24},
   {7,8,5,3,0,10,6,1,14,4,9,18,15,29,12,31,2,17,20,11,13,23,27,16,22,28,19,26,25,30,21,24},
   {3,7,8,0,5,10,1,6,14,9,4,15,18,29,31,12,2,11,17,20,13,27,23,16,28,22,19,26,25,30,21,24},
   {3,7,8,5,0,10,6,1,14,9,4,15,18,29,31,12,2,11,20,17,13,27,23,16,28,26,19,22,25,30,21,24},
   {3,5,7,8,0,10,1,6,14,9,4,15,18,29,31,12,2,17,13,11,20,27,23,16,28,22,26,25,19,30,21,24}},
  {{5,4,4,4,3,3,4,4},{6,7,7,7,7,7,7,7},{5,5,0,6,0,7,7,5},{4,3,3,2,2,0,1,1},
   {10,9,8,10,9,10,10,10},{0,0,2,3,4,4,3,0},{3,6,6,6,6,6,6,6},{2,2,0,1,0,1,0,2},
   {1,1,1,0,1,2,2,3},{9,8,11,9,10,9,9,9},{7,5,5,5,5,5,5,5},{7,6,7,0,10,8,8,9},
   {15,0,4,4,6,3,4,7},{6,11,11,9,11,4,0,0},{8,11,9,8,8,8,8,8},{13,13,10,11,4,11,11,11},
   {2,12,8,11,9,6,6,7},{0,4,9,8,7,0,1,8},{12,12,12,12,11,4,0,0},{11,9,4,6,11,5,5,4},
   {3,1,6,7,8,9,9,1},{5,11,2,3,9,6,6,5},{4,2,1,1,0,3,7,8},{8,8,2,3,4,11,11,6},
   {6,7,9,8,1,10,11,1},{12,5,11,9,3,4,0,6},{10,13,0,4,6,7,10,0},{1,7,12,12,3,5,5,4},
   {9,10,10,10,1,10,4,5},{11,10,2,3,3,5,5,4},{0,4,12,12,4,11,4,7},{14,14,5,5,5,6,6,6}},
  {{255,255,255,255,255,255,255,255},{255,255,255,255,255,255,255,255},{0,10,7,6,7,1,1,10},{255,255,255,255,255,255,255,255},
   {255,255,255,255,255,255,255,255},{255,255,255,255,255,255,255,255},{255,255,255,255,255,255,255,255},{255,255,255,255,255,255,255,255},
   {255,255,255,255,255,255,255,255},{255,255,255,255,255,255,255,255},{255,255,255,255,255,255,255,255},{10,6,1,8,9,14,14,9},
   {255,5,0,0,6,0,0,1},{1,14,9,9,18,18,18,18},{255,255,255,255,255,255,255,255},{255,255,255,255,5,255,255,255},
   {7,18,4,15,4,31,31,12},{5,0,14,14,1,3,3,14},{255,255,255,255,255,5,7,5},{29,4,12,2,13,27,27,27},
   {6,8,6,1,14,9,9,3},{2,13,23,23,16,16,16,28},{3,7,8,7,2,12,2,17},{14,9,29,29,15,15,15,31},
   {13,27,17,17,28,28,23,20},{18,2,13,13,27,13,13,23},{4,15,2,12,12,2,4,13},{8,1,18,18,29,29,29,29},
   {9,29,15,4,8,4,12,2},{255,255,5,5,0,10,10,0},{17,17,27,27,23,23,28,16},{255,255,10,10,10,6,6,6}}};

typedef CUresult (*EncodeFn)(CUtensorMap*, CUtensorMapDataType, cuuint32_t, void*, const cuuint64_t*, const cuuint64_t*, const cuuint32_t*,
                             const cuuint32_t*, CUtensorMapInterleave, CUtensorMapSwizzle, CUtensorMapL2promotion, CUtensorMapFloatOOBfill);

void make_map2(EncodeFn enc, CUtensorMap* m, const void* ptr, int rows, int cols, int box_rows) {
  cuuint64_t dim[2] = {(cuuint64_t)cols, (cuuint64_t)rows}, str[1] = {(cuuint64_t)cols * 2};
  cuuint32_t box[2] = {64, (cuuint32_t)box_rows}, es[2] = {1, 1};
  enc(m, CU_TENSOR_MAP_DATA_TYPE_BFLOAT16, 2, const_cast<void*>(ptr), dim, str, box, es, CU_TENSOR_MAP_INTERLEAVE_NONE, CU_TENSOR_MAP_SWIZZLE_128B,
      CU_TENSOR_MAP_L2_PROMOTION_L2_128B, CU_TENSOR_MAP_FLOAT_OOB_FILL_NONE);
}
void make_map3(EncodeFn enc, CUtensorMap* m, const void* ptr, int rows) {
  cuuint64_t dim[3] = {64, (cuuint64_t)rows, 9}, str[2] = {DM * 2, 128};
  cuuint32_t box[3] = {64, 32, 3}, es[3] = {1, 1, 1};
  enc(m, CU_TENSOR_MAP_DATA_TYPE_BFLOAT16, 3, const_cast<void*>(ptr), dim, str, box, es, CU_TENSOR_MAP_INTERLEAVE_NONE, CU_TENSOR_MAP_SWIZZLE_128B,
      CU_TENSOR_MAP_L2_PROMOTION_L2_128B, CU_TENSOR_MAP_FLOAT_OOB_FILL_NONE);
}

void make_map_t(EncodeFn enc, CUtensorMap* m, void* ptr, int width, int cols) {
  cuuint64_t dim[3] = {TP / 2, 2, 864}, str[2] = {TP * 2, TP * 4};
  cuuint32_t box[3] = {(cuuint32_t)width, 2, (cuuint32_t)cols}, es[3] = {1, 1, 1};
  enc(m, CU_TENSOR_MAP_DATA_TYPE_UINT32, 3, ptr, dim, str, box, es, CU_TENSOR_MAP_INTERLEAVE_NONE, cols == 64 ? CU_TENSOR_MAP_SWIZZLE_128B : CU_TENSOR_MAP_SWIZZLE_NONE,
      CU_TENSOR_MAP_L2_PROMOTION_NONE, CU_TENSOR_MAP_FLOAT_OOB_FILL_NONE);
}

int g_mode = -1;

}

extern "C" void kernel_launch(void* const* d_in, const int* in_sizes, int n_in, void* d_out, int out_size) {
  static EncodeFn enc = nullptr;
  static void* t_ptr = nullptr;
  if (!enc) {
    void* fn = nullptr;
    cudaDriverEntryPointQueryResult st;
    cudaGetDriverEntryPoint("cuTensorMapEncodeTiled", &fn, cudaEnableDefault, &st);
    enc = (EncodeFn)fn;
    cudaGetSymbolAddress(&t_ptr, g_T);
    cudaFuncSetAttribute(fused_kernel, cudaFuncAttributeMaxDynamicSharedMemorySize, SMEM_BYTES);
    if (g_mode < 0) {
      cudaLaunchConfig_t cfg = {};
      cfg.gridDim = dim3(2 * NCL); cfg.blockDim = dim3(384); cfg.dynamicSmemBytes = SMEM_BYTES;
      cudaLaunchAttribute at; at.id = cudaLaunchAttributeClusterDimension;
      at.val.clusterDim.x = 2; at.val.clusterDim.y = 1; at.val.clusterDim.z = 1;
      cfg.attrs = &at; cfg.numAttrs = 1;
      int nc = 0;
      g_mode = (cudaOccupancyMaxActiveClusters(&nc, fused_kernel, &cfg) == cudaSuccess && nc >= NCL) ? 1 : 0;
      (void)cudaGetLastError();
    }
  }
  Params p;
  make_map2(enc, &p.map_a[0], d_in[4], SEQ, DC, 128);
  make_map2(enc, &p.map_a[1], d_in[0], SEQ, DM, 128);
  make_map2(enc, &p.map_w[0], d_in[6], DC, 4096, 64);
  make_map2(enc, &p.map_w[1], d_in[7], DC, 4096, 64);
  make_map2(enc, &p.map_w[2], d_in[5], DM, 4096, 64);
  make_map2(enc, &p.map_w[3], d_in[1], DM, 1728, 64);
  make_map3(enc, &p.map_o[0], d_in[8], 4096);
  make_map3(enc, &p.map_o[1], d_in[2], DM);
  make_map_t(enc, &p.map_t[0], t_ptr, 32, 9);
  make_map_t(enc, &p.map_t[1], t_ptr, 40, 9);
  make_map_t(enc, &p.map_t[2], t_ptr, 32, 64);
  p.x = (const __nv_bfloat16*)d_in[0];
  p.gate_w = (const __nv_bfloat16*)d_in[9];
  make_map2(enc, &p.map_out, d_out, SEQ, DM, 64);
  p.out = (__nv_bfloat16*)d_out;
  p.zero = 0;
  auto launch = [&](int phases) {
    p.s = k_sched;
    for (int i = 0; i < NCL; i++) {
      Rec& r = p.s.r[i];
      if (!(phases & 1)) r.n1 = 0;
      if (!(phases & 2)) r.n2 = 0;
      if (!(phases & (r.p3 < 24 ? 4 : 32))) r.p3 = 255;
      if (!(phases & 8)) r.bg = 255;
      const int u1 = r.n1 ? 8 + r.n1 * (8 + (r.slab >> 3)) : 0;
      int u2 = 0;
      for (int k = 0; k < r.n2; k++) u2 += 4 * (r.item[k] & 7) + 4;
      r.u1 = (uint8_t)u1; r.u2 = (uint8_t)u2;
      r.rot = (uint8_t)(((u1 % 10 + 1) >> 1) % 5);
      r.x3 = (uint8_t)((r.rot + u2) % 5 & 3);
      r.phases = (uint8_t)phases;
    }
    if (!(phases & 16))
      for (int i = 0; i < 256; i++) { p.s.slot[i >> 3][i & 7] = (uint8_t)(i >> 3); p.s.prev[i >> 3][i & 7] = 255; }
    fused_kernel<<<2 * NCL, 384, SMEM_BYTES>>>(p);
  };
  if (g_mode == 1) launch(63);
  else { launch(1); launch(10); launch(32); launch(4); }
}
```

```cpp
#include <cuda_runtime.h>
#include <cuda_bf16.h>
#include <cuda.h>
#include <stdint.h>

namespace {

constexpr int SEQ = 2048, DM = 576, DC = 512, NH = 32;
constexpr int NCL = 66;
constexpr uint32_t DESC_HI = 0x40000040u;

constexpr int SM_RING = 0;
constexpr int SM_BUF = 163840;
constexpr int SM_BAR = 229376;
constexpr int B_P1E = 0, B_P2E = 10, B_P3E = 15, B_P2F = 24, B_SF = 32, B_ORD = 36, B_LAD = 40, B_DONE = 41, B_FIN = 48;
constexpr int B_P3F = 56, B_OUT = 61, B_P1F = 64, B_SE = 74, B_QF = 80, B_LA = 84, B_NUM = 88;
constexpr uint64_t B_CNT = 0x11118245000ull;
constexpr int SMEM_BYTES = SM_BAR + B_NUM * 8 + 1024;

constexpr int F_QKVA = 32;
constexpr int F_GATE = 64;
constexpr int F_DONE = 65;
constexpr int F_CTX = 96;
constexpr int F_OUT = 96 + 8 * 64;
constexpr int F_KV = F_OUT + 64;
constexpr int F_Q = F_KV + 256;
constexpr int F_RD = F_Q + 256;
constexpr int F_NUM = F_RD + 256;

struct Rec {
  uint8_t slab;
  uint8_t n1, n2;
  uint8_t p3;
  uint8_t bg;
  uint8_t item[11];
  uint8_t last[11];
  uint8_t tile[32];
  uint8_t u1, u2;
  uint8_t rot, x3;
  uint8_t phases;
};
struct Sched {
  Rec r[NCL];
  uint8_t nh[24];
  uint8_t p3_order[8][32];
  uint8_t slot[32][8];
  uint8_t prev[32][8];
};

#define SCHED_DECL static const

struct Params {
  CUtensorMap map_a[2];
  CUtensorMap map_w[4];
  CUtensorMap map_o[2];
  CUtensorMap map_t[3];
  CUtensorMap map_out;
  const __nv_bfloat16* x;
  const __nv_bfloat16* gate_w;
  __nv_bfloat16* out;
  int zero;
  alignas(64) Sched s;
};

__device__ __align__(1024) uint8_t g_Q[NH * 32 * 16384];
__device__ __align__(1024) uint8_t g_KV[2 * NH * 16 * 32768];
__device__ __align__(1024) uint8_t g_oA[32 * 576 * 128];
constexpr int TP = SEQ + 16;
__device__ __align__(1024) uint32_t g_T[864 * TP];
__device__ float g_gate[SEQ];
__device__ int g_flags[F_NUM];

__device__ __forceinline__ void mbar_arrive(uint32_t b) { asm volatile("mbarrier.arrive.shared::cta.b64 _, [%0];" ::"r"(b) : "memory"); }
__device__ __forceinline__ void mbar_arrive_cl(uint32_t b, int cnt) {
  asm volatile("mbarrier.arrive.shared::cluster.b64 _, [%0], %1;" ::"r"(b), "r"(cnt) : "memory");
}
__device__ __forceinline__ void mbar_wait(uint32_t b, int par) {
  asm volatile(
      "{\n.reg .pred p;\n.reg .u32 c;\n"
      "mbarrier.try_wait.parity.shared::cta.b64 p, [%0], %1;\n@p bra DN;\nmov.u32 c, 0;\n"
      "LP:\nmbarrier.try_wait.parity.shared::cta.b64 p, [%0], %1;\n@p bra DN;\n"
      "add.u32 c, c, 1;\nsetp.lt.u32 p, c, 4000000;\n@p bra LP;\ntrap;\nDN:\n}" ::"r"(b), "r"(par) : "memory");
}
__device__ __forceinline__ uint32_t mapa(uint32_t a, uint32_t cta) {
  uint32_t r; asm("mapa.shared::cluster.u32 %0, %1, %2;" : "=r"(r) : "r"(a), "r"(cta)); return r;
}
#define ELECT(ins) "{\n.reg .pred e;\nelect.sync _|e, 0xffffffff;\n@e " ins "\n}"
__device__ __forceinline__ void mbar_expect(uint32_t b, int bytes) {
  asm volatile(ELECT("mbarrier.arrive.expect_tx.shared::cta.b64 _, [%0], %1;") ::"r"(b), "r"(bytes) : "memory");
}
__device__ __forceinline__ void mbar_arrive_one(uint32_t b) { asm volatile(ELECT("mbarrier.arrive.shared::cta.b64 _, [%0];") ::"r"(b) : "memory"); }
constexpr uint64_t L2_NORMAL = 0x1000000000000000ull, L2_FIRST = 0x12F0000000000000ull;
__device__ __forceinline__ void bulk_load(uint32_t dst, const void* src, int bytes, uint32_t bar, uint64_t pol = L2_NORMAL) {
  asm volatile(ELECT("cp.async.bulk.shared::cluster.global.mbarrier::complete_tx::bytes.L2::cache_hint [%0], [%1], %2, [%3], %4;") ::"r"(dst), "l"(src), "r"(bytes), "r"(bar), "l"(pol) : "memory");
}
__device__ __forceinline__ void bulk_load_mc(uint32_t dst, const void* src, int bytes, uint32_t bar, uint64_t pol = L2_NORMAL) {
  asm volatile(ELECT("cp.async.bulk.shared::cluster.global.mbarrier::complete_tx::bytes.multicast::cluster.L2::cache_hint [%0], [%1], %2, [%3], %4, %5;") ::"r"(dst), "l"(src), "r"(bytes), "r"(bar), "h"((uint16_t)3), "l"(pol) : "memory");
}
__device__ __forceinline__ void bulk_store(void* dst, uint32_t src, int bytes, uint64_t pol = L2_NORMAL) {
  asm volatile(ELECT("cp.async.bulk.global.shared::cta.bulk_group.L2::cache_hint [%0], [%1], %2, %3;") ::"l"(dst), "r"(src), "r"(bytes), "l"(pol) : "memory");
}
__device__ __forceinline__ void tma2d(uint32_t dst, const CUtensorMap* m, int c0, int c1, uint32_t bar, uint64_t pol = L2_NORMAL) {
  asm volatile(ELECT("cp.async.bulk.tensor.2d.shared::cluster.global.mbarrier::complete_tx::bytes.L2::cache_hint [%0], [%1, {%3, %4}], [%2], %5;") ::"r"(dst), "l"(m), "r"(bar), "r"(c0), "r"(c1), "l"(pol) : "memory");
}
__device__ __forceinline__ void tma2d_mc(uint32_t dst, const CUtensorMap* m, int c0, int c1, uint32_t bar, uint64_t pol = L2_NORMAL) {
  asm volatile(ELECT("cp.async.bulk.tensor.2d.shared::cluster.global.mbarrier::complete_tx::bytes.multicast::cluster.L2::cache_hint [%0], [%1, {%3, %4}], [%2], %5, %6;") ::"r"(dst), "l"(m), "r"(bar), "r"(c0), "r"(c1), "h"((uint16_t)3), "l"(pol) : "memory");
}
__device__ __forceinline__ void tma3d(uint32_t dst, const CUtensorMap* m, int c0, int c1, int c2, uint32_t bar, uint64_t pol = L2_NORMAL) {
  asm volatile(ELECT("cp.async.bulk.tensor.3d.shared::cluster.global.mbarrier::complete_tx::bytes.L2::cache_hint [%0], [%1, {%3, %4, %5}], [%2], %6;") ::"r"(dst), "l"(m), "r"(bar), "r"(c0), "r"(c1), "r"(c2), "l"(pol) : "memory");
}
__device__ __forceinline__ void tma3d_mc(uint32_t dst, const CUtensorMap* m, int c0, int c1, int c2, uint32_t bar, uint64_t pol = L2_NORMAL) {
  asm volatile(ELECT("cp.async.bulk.tensor.3d.shared::cluster.global.mbarrier::complete_tx::bytes.multicast::cluster.L2::cache_hint [%0], [%1, {%3, %4, %5}], [%2], %6, %7;") ::"r"(dst), "l"(m), "r"(bar), "r"(c0), "r"(c1), "r"(c2), "h"((uint16_t)3), "l"(pol) : "memory");
}
__device__ __forceinline__ void tma2d_add(const CUtensorMap* m, uint32_t src, int c0, int c1) {
  asm volatile(ELECT("cp.reduce.async.bulk.tensor.2d.global.shared::cta.add.bulk_group [%0, {%2, %3}], [%1];") ::"l"(m), "r"(src), "r"(c0), "r"(c1) : "memory");
}
__device__ __forceinline__ void tma3d_store(const CUtensorMap* m, uint32_t src, int c0, int c1, int c2, uint64_t pol = L2_NORMAL) {
  asm volatile(ELECT("cp.async.bulk.tensor.3d.global.shared::cta.bulk_group.L2::cache_hint [%0, {%2, %3, %4}], [%1], %5;") ::"l"(m), "r"(src), "r"(c0), "r"(c1), "r"(c2), "l"(pol) : "memory");
}
__device__ __forceinline__ void tma2d_prefetch(const CUtensorMap* m, int c0, int c1, uint64_t pol = L2_NORMAL) {
  asm volatile(ELECT("cp.async.bulk.prefetch.tensor.2d.L2.global.L2::cache_hint [%0, {%1, %2}], %3;") ::"l"(m), "r"(c0), "r"(c1), "l"(pol) : "memory");
}
#define LAG 3
#define HINT 62
#define POL(bit) ((HINT >> (bit)) & 1 ? L2_FIRST : L2_NORMAL)
#define BULK_COMMIT() asm volatile("cp.async.bulk.commit_group;" ::: "memory")
#define BULK_WAIT(n) asm volatile("cp.async.bulk.wait_group %0;" ::"n"(n) : "memory")
#define BULK_WAIT_READ(n) asm volatile("cp.async.bulk.wait_group.read %0;" ::"n"(n) : "memory")
#define FENCE_ASYNC_SMEM() asm volatile("fence.proxy.async.shared::cta;" ::: "memory")
#define FENCE_ASYNC_ALL() asm volatile("fence.proxy.async;" ::: "memory")
#define WG_FENCE() asm volatile("wgmma.fence.sync.aligned;" ::: "memory")
#define WG_COMMIT() asm volatile("wgmma.commit_group.sync.aligned;" ::: "memory")
#define WG_WAIT(n) asm volatile("wgmma.wait_group.sync.aligned %0;" ::"n"(n) : "memory")
__device__ __forceinline__ void bar_sync(int id, int n) { asm volatile("bar.sync %0, %1;" ::"r"(id), "r"(n) : "memory"); }
__device__ __forceinline__ void bar_arrive(int id, int n) { asm volatile("bar.arrive %0, %1;" ::"r"(id), "r"(n) : "memory"); }
__device__ __forceinline__ void cluster_sync() {
  asm volatile("barrier.cluster.arrive.relaxed;\nbarrier.cluster.wait.acquire;" ::: "memory");
}
template <int N> __device__ __forceinline__ void pin(float (&r)[N]) {
#pragma unroll
  for (int i = 0; i < N; i++) asm volatile("" : "+f"(r[i])::"memory");
}
template <int N> __device__ __forceinline__ void pin(uint32_t (&r)[N]) {
#pragma unroll
  for (int i = 0; i < N; i++) asm volatile("" : "+r"(r[i])::"memory");
}
__device__ __forceinline__ uint32_t pack_bf16(float lo, float hi) {
  uint32_t r; asm("cvt.rn.bf16x2.f32 %0, %1, %2;" : "=r"(r) : "f"(hi), "f"(lo)); return r;
}
__device__ __forceinline__ float ex2(float x) { float r; asm("ex2.approx.ftz.f32 %0, %1;" : "=f"(r) : "f"(x)); return r; }
__device__ __forceinline__ void ldsm4(uint32_t a, uint32_t& r0, uint32_t& r1, uint32_t& r2, uint32_t& r3) {
  asm volatile("ldmatrix.sync.aligned.m8n8.x4.shared.b16 {%0,%1,%2,%3}, [%4];" : "=r"(r0), "=r"(r1), "=r"(r2), "=r"(r3) : "r"(a) : "memory");
}
__device__ __forceinline__ void stsm4(uint32_t a, uint32_t r0, uint32_t r1, uint32_t r2, uint32_t r3) {
  asm volatile("stmatrix.sync.aligned.m8n8.x4.shared.b16 [%0], {%1,%2,%3,%4};" ::"r"(a), "r"(r0), "r"(r1), "r"(r2), "r"(r3) : "memory");
}
__device__ __forceinline__ void flag_add(int idx) {
  asm volatile(ELECT("red.release.gpu.global.add.s32 [%0], 1;") ::"l"(g_flags + idx) : "memory");
}
__device__ __forceinline__ void flag_add_rx(int idx) {
  asm volatile(ELECT("red.relaxed.gpu.global.add.s32 [%0], 1;") ::"l"(g_flags + idx) : "memory");
}
template <bool ACQ, int NS = 32> __device__ __forceinline__ void flag_wait(int idx, int target) {
  int n = 0;
  while (true) {
    int v;
    if (ACQ) asm volatile("ld.acquire.gpu.global.s32 %0, [%1];" : "=r"(v) : "l"(g_flags + idx) : "memory");
    else asm volatile("ld.relaxed.gpu.global.s32 %0, [%1];" : "=r"(v) : "l"(g_flags + idx) : "memory");
    if (__all_sync(0xffffffffu, v >= target)) break;
    if (++n > 20000000) __trap();
    __nanosleep(NS);
  }
}
__device__ __forceinline__ void mask_wait(uint32_t& ready, int bit, int idx, int target) {
  for (int n = 0; !((ready >> bit) & 1); n++) {
    int v;
    if (n) { __nanosleep(32); if (n > 20000000) __trap(); }
    asm volatile("ld.relaxed.gpu.global.s32 %0, [%1];" : "=r"(v) : "l"(g_flags + idx) : "memory");
    ready = __ballot_sync(0xffffffffu, v >= target);
  }
}
__device__ __forceinline__ uint32_t desc_lo(uint32_t addr, uint32_t lbo) { return ((addr & 0x3FFFFu) >> 4) | ((lbo >> 4) << 16); }
#define PROF(role, i)
#define PROFX(cond, i)
#define PROFB(i)
#define PROFG(i)

template <int TB, int TA = 0> __device__ __forceinline__ void wgmma_ss64(float (&d)[32], uint32_t alo, uint32_t blo, int sd) {
  asm volatile("{\n.reg .pred p;\n.reg .b64 da, db;\n"
    "setp.ne.b32 p, %34, 0;\nmov.b64 da, {%32, %36};\nmov.b64 db, {%33, %36};\n"
    "wgmma.mma_async.sync.aligned.m64n64k16.f32.bf16.bf16 "
    "{%0,%1,%2,%3,%4,%5,%6,%7,%8,%9,%10,%11,%12,%13,%14,%15,%16,%17,%18,%19,%20,%21,%22,%23,"
    "%24,%25,%26,%27,%28,%29,%30,%31}, "
    "da, db, p, 1, 1, %37, %35;\n}\n"
    : "+f"(d[0]),"+f"(d[1]),"+f"(d[2]),"+f"(d[3]),"+f"(d[4]),"+f"(d[5]),"+f"(d[6]),"+f"(d[7]),"+f"(d[8]),"+f"(d[9]),"+f"(d[10]),"+f"(d[11]),
      "+f"(d[12]),"+f"(d[13]),"+f"(d[14]),"+f"(d[15]),"+f"(d[16]),"+f"(d[17]),"+f"(d[18]),"+f"(d[19]),"+f"(d[20]),"+f"(d[21]),"+f"(d[22]),"+f"(d[23]),
      "+f"(d[24]),"+f"(d[25]),"+f"(d[26]),"+f"(d[27]),"+f"(d[28]),"+f"(d[29]),"+f"(d[30]),"+f"(d[31])
    : "r"(alo), "r"(blo), "r"(sd), "n"(TB), "r"(DESC_HI), "n"(TA));
}
template <int TB, int TA = 0> __device__ __forceinline__ void wgmma_ss128(float (&d)[64], uint32_t alo, uint32_t blo, int sd) {
  asm volatile("{\n.reg .pred p;\n.reg .b64 da, db;\n"
    "setp.ne.b32 p, %66, 0;\nmov.b64 da, {%64, %68};\nmov.b64 db, {%65, %68};\n"
    "wgmma.mma_async.sync.aligned.m64n128k16.f32.bf16.bf16 "
    "{%0,%1,%2,%3,%4,%5,%6,%7,%8,%9,%10,%11,%12,%13,%14,%15,%16,%17,%18,%19,%20,%21,%22,%23,"
    "%24,%25,%26,%27,%28,%29,%30,%31,%32,%33,%34,%35,%36,%37,%38,%39,%40,%41,%42,%43,%44,%45,%46,%47,"
    "%48,%49,%50,%51,%52,%53,%54,%55,%56,%57,%58,%59,%60,%61,%62,%63}, "
    "da, db, p, 1, 1, %69, %67;\n}\n"
    : "+f"(d[0]),"+f"(d[1]),"+f"(d[2]),"+f"(d[3]),"+f"(d[4]),"+f"(d[5]),"+f"(d[6]),"+f"(d[7]),"+f"(d[8]),"+f"(d[9]),"+f"(d[10]),"+f"(d[11]),
      "+f"(d[12]),"+f"(d[13]),"+f"(d[14]),"+f"(d[15]),"+f"(d[16]),"+f"(d[17]),"+f"(d[18]),"+f"(d[19]),"+f"(d[20]),"+f"(d[21]),"+f"(d[22]),"+f"(d[23]),
      "+f"(d[24]),"+f"(d[25]),"+f"(d[26]),"+f"(d[27]),"+f"(d[28]),"+f"(d[29]),"+f"(d[30]),"+f"(d[31]),"+f"(d[32]),"+f"(d[33]),"+f"(d[34]),"+f"(d[35]),
      "+f"(d[36]),"+f"(d[37]),"+f"(d[38]),"+f"(d[39]),"+f"(d[40]),"+f"(d[41]),"+f"(d[42]),"+f"(d[43]),"+f"(d[44]),"+f"(d[45]),"+f"(d[46]),"+f"(d[47]),
      "+f"(d[48]),"+f"(d[49]),"+f"(d[50]),"+f"(d[51]),"+f"(d[52]),"+f"(d[53]),"+f"(d[54]),"+f"(d[55]),"+f"(d[56]),"+f"(d[57]),"+f"(d[58]),"+f"(d[59]),
      "+f"(d[60]),"+f"(d[61]),"+f"(d[62]),"+f"(d[63])
    : "r"(alo), "r"(blo), "r"(sd), "n"(TB), "r"(DESC_HI), "n"(TA));
}
template <int TB> __device__ __forceinline__ void wgmma_rs128(float (&d)[64], uint32_t a0, uint32_t a1, uint32_t a2, uint32_t a3, uint32_t blo, int sd) {
  asm volatile("{\n.reg .pred p;\n.reg .b64 db;\n"
    "setp.ne.b32 p, %69, 0;\nmov.b64 db, {%68, %71};\n"
    "wgmma.mma_async.sync.aligned.m64n128k16.f32.bf16.bf16 "
    "{%0,%1,%2,%3,%4,%5,%6,%7,%8,%9,%10,%11,%12,%13,%14,%15,%16,%17,%18,%19,%20,%21,%22,%23,"
    "%24,%25,%26,%27,%28,%29,%30,%31,%32,%33,%34,%35,%36,%37,%38,%39,%40,%41,%42,%43,%44,%45,%46,%47,"
    "%48,%49,%50,%51,%52,%53,%54,%55,%56,%57,%58,%59,%60,%61,%62,%63}, "
    "{%64,%65,%66,%67}, db, p, 1, 1, %70;\n}\n"
    : "+f"(d[0]),"+f"(d[1]),"+f"(d[2]),"+f"(d[3]),"+f"(d[4]),"+f"(d[5]),"+f"(d[6]),"+f"(d[7]),"+f"(d[8]),"+f"(d[9]),"+f"(d[10]),"+f"(d[11]),
      "+f"(d[12]),"+f"(d[13]),"+f"(d[14]),"+f"(d[15]),"+f"(d[16]),"+f"(d[17]),"+f"(d[18]),"+f"(d[19]),"+f"(d[20]),"+f"(d[21]),"+f"(d[22]),"+f"(d[23]),
      "+f"(d[24]),"+f"(d[25]),"+f"(d[26]),"+f"(d[27]),"+f"(d[28]),"+f"(d[29]),"+f"(d[30]),"+f"(d[31]),"+f"(d[32]),"+f"(d[33]),"+f"(d[34]),"+f"(d[35]),
      "+f"(d[36]),"+f"(d[37]),"+f"(d[38]),"+f"(d[39]),"+f"(d[40]),"+f"(d[41]),"+f"(d[42]),"+f"(d[43]),"+f"(d[44]),"+f"(d[45]),"+f"(d[46]),"+f"(d[47]),
      "+f"(d[48]),"+f"(d[49]),"+f"(d[50]),"+f"(d[51]),"+f"(d[52]),"+f"(d[53]),"+f"(d[54]),"+f"(d[55]),"+f"(d[56]),"+f"(d[57]),"+f"(d[58]),"+f"(d[59]),
      "+f"(d[60]),"+f"(d[61]),"+f"(d[62]),"+f"(d[63])
    : "r"(a0), "r"(a1), "r"(a2), "r"(a3), "r"(blo), "r"(sd), "n"(TB), "r"(DESC_HI));
}
template <int TB, int TA = 0> __device__ __forceinline__ void wgmma_ss192(float (&d)[96], uint32_t alo, uint32_t blo, int sd) {
  asm volatile("{\n.reg .pred p;\n.reg .b64 da, db;\n"
    "setp.ne.b32 p, %98, 0;\nmov.b64 da, {%96, %100};\nmov.b64 db, {%97, %100};\n"
    "wgmma.mma_async.sync.aligned.m64n192k16.f32.bf16.bf16 "
    "{%0,%1,%2,%3,%4,%5,%6,%7,%8,%9,%10,%11,%12,%13,%14,%15,%16,%17,%18,%19,%20,%21,%22,%23,"
    "%24,%25,%26,%27,%28,%29,%30,%31,%32,%33,%34,%35,%36,%37,%38,%39,%40,%41,%42,%43,%44,%45,%46,%47,"
    "%48,%49,%50,%51,%52,%53,%54,%55,%56,%57,%58,%59,%60,%61,%62,%63,%64,%65,%66,%67,%68,%69,%70,%71,"
    "%72,%73,%74,%75,%76,%77,%78,%79,%80,%81,%82,%83,%84,%85,%86,%87,%88,%89,%90,%91,%92,%93,%94,%95}, "
    "da, db, p, 1, 1, %101, %99;\n}\n"
    : "+f"(d[0]),"+f"(d[1]),"+f"(d[2]),"+f"(d[3]),"+f"(d[4]),"+f"(d[5]),"+f"(d[6]),"+f"(d[7]),"+f"(d[8]),"+f"(d[9]),"+f"(d[10]),"+f"(d[11]),
      "+f"(d[12]),"+f"(d[13]),"+f"(d[14]),"+f"(d[15]),"+f"(d[16]),"+f"(d[17]),"+f"(d[18]),"+f"(d[19]),"+f"(d[20]),"+f"(d[21]),"+f"(d[22]),"+f"(d[23]),
      "+f"(d[24]),"+f"(d[25]),"+f"(d[26]),"+f"(d[27]),"+f"(d[28]),"+f"(d[29]),"+f"(d[30]),"+f"(d[31]),"+f"(d[32]),"+f"(d[33]),"+f"(d[34]),"+f"(d[35]),
      "+f"(d[36]),"+f"(d[37]),"+f"(d[38]),"+f"(d[39]),"+f"(d[40]),"+f"(d[41]),"+f"(d[42]),"+f"(d[43]),"+f"(d[44]),"+f"(d[45]),"+f"(d[46]),"+f"(d[47]),
      "+f"(d[48]),"+f"(d[49]),"+f"(d[50]),"+f"(d[51]),"+f"(d[52]),"+f"(d[53]),"+f"(d[54]),"+f"(d[55]),"+f"(d[56]),"+f"(d[57]),"+f"(d[58]),"+f"(d[59]),
      "+f"(d[60]),"+f"(d[61]),"+f"(d[62]),"+f"(d[63]),"+f"(d[64]),"+f"(d[65]),"+f"(d[66]),"+f"(d[67]),"+f"(d[68]),"+f"(d[69]),"+f"(d[70]),"+f"(d[71]),
      "+f"(d[72]),"+f"(d[73]),"+f"(d[74]),"+f"(d[75]),"+f"(d[76]),"+f"(d[77]),"+f"(d[78]),"+f"(d[79]),"+f"(d[80]),"+f"(d[81]),"+f"(d[82]),"+f"(d[83]),
      "+f"(d[84]),"+f"(d[85]),"+f"(d[86]),"+f"(d[87]),"+f"(d[88]),"+f"(d[89]),"+f"(d[90]),"+f"(d[91]),"+f"(d[92]),"+f"(d[93]),"+f"(d[94]),"+f"(d[95])
    : "r"(alo), "r"(blo), "r"(sd), "n"(TB), "r"(DESC_HI), "n"(TA));
}

struct Ctx {
  uint32_t sm;
  uint32_t bar;
  uint32_t rbar;
  int cl, rank, wg, warp, lane, phases;
};
__device__ __forceinline__ void release(const Ctx& c, int b, int cnt = 1) {
  if (c.lane < 2) mbar_arrive_cl(c.rbar + b * 8, cnt);
}
#define HK 5
#define NPRO 6
#define PFM 7
#define PF1 1
constexpr float SM_SCALE = 0.08838834764831845f * 1.4426950408889634f;
constexpr float SM_HI = 1.8446744e19f, SM_LO = 5.4210109e-20f;
constexpr int ORDER = 1;

__device__ __forceinline__ void stage_tile(const float (&a)[64], uint32_t buf, const Ctx& c, float s0, float s1) {
  const int row = (c.lane & 7) + ((c.lane >> 3) & 1) * 8;
  const uint32_t base = buf + (c.warp * 16 + row) * 128 + (((c.lane >> 4) ^ (row & 7)) << 4);
#pragma unroll
  for (int i = 0; i < 8; i++)
    stsm4((base ^ ((i & 3) << 5)) + (i >> 2) * 8192, pack_bf16(a[8 * i] * s0, a[8 * i + 1] * s0), pack_bf16(a[8 * i + 2] * s1, a[8 * i + 3] * s1),
          pack_bf16(a[8 * i + 4] * s0, a[8 * i + 5] * s0), pack_bf16(a[8 * i + 6] * s1, a[8 * i + 7] * s1));
}

__device__ __forceinline__ void p1_epilogue(const Params& p, const Ctx& c, const float (&acc)[64], int t, int type) {
  const int tile = p.s.r[c.cl].tile[t] & 63, b = c.wg * 2 + 1;
  mbar_wait(c.bar + (B_SE + b) * 8, (t & 1) ^ 1);
  if (type && tile >= 32) {
    const int r = 2 * (c.lane & 3) + ((c.lane >> 2) & 1);
    const uint32_t dst = c.sm + SM_BUF + b * 16384 + r * 128 + (((c.warp * 2) ^ r) << 4) + (c.lane >> 3) * 4;
#pragma unroll
    for (int i = 0; i < 16; i++) {
      asm volatile("st.shared.u32 [%0], %1;" ::"r"(dst + i * 1024), "r"(pack_bf16(acc[4 * i], acc[4 * i + 1])) : "memory");
      asm volatile("st.shared.u32 [%0], %1;" ::"r"((dst ^ 16) + i * 1024), "r"(pack_bf16(acc[4 * i + 2], acc[4 * i + 3])) : "memory");
    }
  } else {
    if (type) stage_tile(acc, c.sm + SM_BUF + b * 16384, c, SM_SCALE, SM_SCALE);
    else stage_tile(acc, c.sm + SM_BUF + b * 16384, c, 1.f, 1.f);
  }
  FENCE_ASYNC_SMEM();
  __syncwarp();
  if (c.lane == 0) mbar_arrive(c.bar + (B_SF + b) * 8);
}

__device__ __forceinline__ void p1_consumer(const Params& p, const Ctx& c) {
  const int n = p.s.r[c.cl].n1;
  const int type = p.s.r[c.cl].slab >> 3;
  const uint32_t bdesc = desc_lo(c.sm + SM_RING, 8192), adesc = desc_lo(c.sm + SM_BUF + 32768 + c.wg * 8192, 16);
  uint32_t A[128];
  float acc[64] = {};
  int slot = 0, par = 0;
  auto next = [&]() { if (++slot == 10) { slot = 0; par ^= 1; } };
  {
    const int row = (c.lane & 7) + ((c.lane >> 3) & 1) * 8;
    const uint32_t base = c.sm + SM_RING + (c.wg * 64 + c.warp * 16 + row) * 128 + (((c.lane >> 4) ^ (row & 7)) << 4);
    if (c.wg == 1) bar_sync(ORDER + 1, 256);
    int pa = -1, pb = -1;
    if (type) {
      mbar_wait(c.bar + B_P1F * 8, 0);
      WG_FENCE();
#pragma unroll
      for (int kk = 0; kk < 4; kk++) wgmma_ss128<1>(acc, adesc + kk * 2, bdesc + kk * 128, kk != 0);
      WG_COMMIT();
      pb = 0; slot = 1;
    }
#pragma unroll
    for (int kb = 0; kb < 8; kb++) {
      const int sa = slot;
      mbar_wait(c.bar + (B_P1F + slot) * 8, par);
      if (kb == 0) PROF(c.wg, 5);
      next();
      mbar_wait(c.bar + (B_P1F + slot) * 8, par);
      PROF(c.wg, 6 + 2 * kb);
      WG_FENCE();
#pragma unroll
      for (int kk = 0; kk < 4; kk++)
        wgmma_ss128<1>(acc, desc_lo(c.sm + SM_RING + c.wg * 8192, 16) + sa * 1024 + kk * 2, bdesc + slot * 1024 + kk * 128, (kb | kk) != 0 ? 1 : type);
      WG_COMMIT();
      if (kb == 1 && c.wg == 0) bar_arrive(ORDER + 1, 256);
#pragma unroll
      for (int kk = 0; kk < 4; kk++) ldsm4((base ^ (kk << 5)) + sa * 16384, A[kb * 16 + kk * 4], A[kb * 16 + kk * 4 + 1], A[kb * 16 + kk * 4 + 2], A[kb * 16 + kk * 4 + 3]);
      WG_WAIT(1);
      if (kb > 0) release(c, B_P1E + pa);
      if (kb > 0 || pb >= 0) release(c, B_P1E + pb);
      pa = sa; pb = slot;
      next();
    }
    WG_WAIT(0);
    __syncwarp();
    release(c, B_P1E + pa);
    release(c, B_P1E + pb);
    pin(acc);
    PROF(c.wg, 1);
    p1_epilogue(p, c, acc, 0, type);
    PROF(c.wg, 2);
  }
  for (int t = 1; t < n; t++) {
    bar_sync(ORDER + c.wg, 256);
    int prev1 = -1, prev2 = -1;
    if (type) {
      mbar_wait(c.bar + (B_P1F + slot) * 8, par);
      WG_FENCE();
#pragma unroll
      for (int kk = 0; kk < 4; kk++) wgmma_ss128<1>(acc, adesc + kk * 2, bdesc + slot * 1024 + kk * 128, kk != 0);
      WG_COMMIT();
      prev1 = slot;
      next();
    }
#pragma unroll
    for (int kb = 0; kb < 8; kb++) {
      mbar_wait(c.bar + (B_P1F + slot) * 8, par);
      WG_FENCE();
      const uint32_t d = bdesc + slot * 1024;
#pragma unroll
      for (int kk = 0; kk < 4; kk++)
        wgmma_rs128<1>(acc, A[kb * 16 + kk * 4], A[kb * 16 + kk * 4 + 1], A[kb * 16 + kk * 4 + 2], A[kb * 16 + kk * 4 + 3], d + kk * 128, (kb | kk) != 0 ? 1 : type);
      WG_COMMIT();
      if (kb == HK) {
        if (t + 1 < n || c.wg == 0) bar_arrive(ORDER + (c.wg ^ 1), 256);
      }
      if (kb > 0) { WG_WAIT(2); if (kb > 1 || prev2 >= 0) release(c, B_P1E + prev2); }
      prev2 = prev1; prev1 = slot;
      next();
    }
    WG_WAIT(1);
    release(c, B_P1E + prev2);
    WG_WAIT(0);
    pin(acc);
    release(c, B_P1E + prev1);
    p1_epilogue(p, c, acc, t, type);
    PROF(c.wg, 3);
  }
}

__device__ __forceinline__ void p1_producer(const Params& p, const Ctx& c) {
  const int n = p.s.r[c.cl].n1;
  const int type = p.s.r[c.cl].slab >> 3, grp = p.s.r[c.cl].slab & 7;
  int slot = NPRO % 10, par = NPRO < 10;
#pragma unroll 1
  for (int t = 0; t < n; t++) {
    const int tile = p.s.r[c.cl].tile[t] & 63;
    const CUtensorMap* m = &p.map_w[type * 2 + (tile >> 5)];
    const int n0 = (tile & 31) * 128 + c.rank * 64;
    const int ptile = p.s.r[c.cl].tile[t + PF1 < n ? t + PF1 : t];
    const CUtensorMap* pm = &p.map_w[type * 2 + ((ptile >> 5) & 1)];
    if (t == 7 && (c.phases & 16)) flag_wait<true>(F_GATE, 256);
#pragma unroll 1
    for (int kb = t ? -type : (NPRO - type) >> 1; kb < 8; kb++) {
      if (t == 0 && 2 * kb + type >= NPRO) {
        mbar_wait(c.bar + (B_P1E + slot) * 8, par);
        mbar_expect(c.bar + (B_P1F + slot) * 8, 16384);
        tma2d(c.sm + SM_RING + slot * 16384, &p.map_a[type], kb * 64, grp * 256 + c.rank * 128, c.bar + (B_P1F + slot) * 8);
        if (++slot == 10) { slot = 0; par ^= 1; }
      }
      mbar_wait(c.bar + (B_P1E + slot) * 8, par);
      mbar_expect(c.bar + (B_P1F + slot) * 8, 16384);
      tma2d_mc(c.sm + SM_RING + slot * 16384 + c.rank * 8192, m, n0, kb < 0 ? 512 : kb * 64, c.bar + (B_P1F + slot) * 8);
      if (t == 0 && kb == 1) PROF(2, 61);
      if (t == 0 && kb == 3) PROF(2, 62);
      if (t + PF1 < n && t > 0 && ((ptile & 64) || ((ptile & 128) && ((kb ^ grp) & PFM) == 0))) tma2d_prefetch(pm, (ptile & 31) * 128 + c.rank * 64, kb < 0 ? 512 : kb * 64);
      if (++slot == 10) { slot = 0; par ^= 1; }
    }
  }
}

__device__ __forceinline__ void p1_storer(const Params& p, const Ctx& c) {
  const int n = p.s.r[c.cl].n1;
  const int type = p.s.r[c.cl].slab >> 3, grp = p.s.r[c.cl].slab & 7;
  for (int i = 0; i < 2 * n; i++) {
    const int t = i >> 1, w = i & 1, b = w * 2 + 1;
    const int tile = p.s.r[c.cl].tile[t] & 63;
    mbar_wait(c.bar + (B_SF + b) * 8, t & 1);
    const uint32_t src = c.sm + SM_BUF + b * 16384;
    int f = (type ? F_Q : F_KV) + (tile & 31) * 8 + grp;
    if (type == 0) {
      const int prev = p.s.prev[tile & 31][grp];
      if (prev != 255 && w == 0) {
        if (grp >= 2) flag_wait<false>(F_RD + prev * 8 + grp, 8 - grp);
        else flag_wait<false>(F_CTX + max(c.lane & 7, grp) * 64 + prev, 4);
      }
      uint8_t* dst = g_KV + (size_t)(((tile & 32) + p.s.slot[tile & 31][grp]) * 16 + grp * 2 + c.rank) * 32768 + w * 8192;
      bulk_store(dst, src, 8192);
      bulk_store(dst + 16384, src + 8192, 8192);
    } else if (tile < 32) {
      bulk_store(g_Q + (size_t)(tile * 32 + grp * 4 + c.rank * 2 + w) * 16384, src, 16384);
    } else {
      tma3d_store(&p.map_t[2], src, 8 + (grp * 4 + c.rank * 2 + w) * 32, 0, (tile - 32) * 64);
      f = F_QKVA + grp * 4 + ((0xE4390900u >> (2 * (tile - 30))) & 3);
    }
    BULK_COMMIT();
    BULK_WAIT(0);
    mbar_arrive_one(c.bar + (B_SE + b) * 8);
    flag_add_rx(f);
  }
}

__device__ __forceinline__ int p2_buf(int w, int i) { return w * 2 + (i & 1); }
__device__ __forceinline__ int p2_blk(int rank, int w, int i) { return ((i ^ w) & 1) == 0 ? 3 - rank : rank; }

template <int N>
__device__ __forceinline__ void row_max(const float (&s)[N], float& m0, float& m1) {
  float a0 = fmaxf(s[0], s[1]), a1 = fmaxf(s[2], s[3]);
#pragma unroll
  for (int i = 1; i < N / 4; i++) {
    m0 = fmaxf(m0, s[4 * i]); a0 = fmaxf(a0, s[4 * i + 1]);
    m1 = fmaxf(m1, s[4 * i + 2]); a1 = fmaxf(a1, s[4 * i + 3]);
  }
  m0 = fmaxf(m0, a0); m1 = fmaxf(m1, a1);
  m0 = fmaxf(m0, __shfl_xor_sync(0xffffffffu, m0, 1));
  m1 = fmaxf(m1, __shfl_xor_sync(0xffffffffu, m1, 1));
  m0 = fmaxf(m0, __shfl_xor_sync(0xffffffffu, m0, 2));
  m1 = fmaxf(m1, __shfl_xor_sync(0xffffffffu, m1, 2));
}
template <bool SUB, int N>
__device__ __forceinline__ void row_exp(const float (&s)[N], uint32_t (&P)[32], float m0, float m1, float& t0, float& t1) {
  float u0 = 0.f, u1 = 0.f;
  t0 = t1 = 0.f;
#pragma unroll
  for (int i = 0; i < N / 4; i++) {
    const float e0 = ex2(SUB ? s[4 * i] - m0 : s[4 * i]), e1 = ex2(SUB ? s[4 * i + 1] - m0 : s[4 * i + 1]);
    const float e2 = ex2(SUB ? s[4 * i + 2] - m1 : s[4 * i + 2]), e3 = ex2(SUB ? s[4 * i + 3] - m1 : s[4 * i + 3]);
    if (i == 0) { t0 = e0; u0 = e1; t1 = e2; u1 = e3; }
    else { t0 += e0; u0 += e1; t1 += e2; u1 += e3; }
    P[2 * i] = pack_bf16(e0, e1);
    P[2 * i + 1] = pack_bf16(e2, e3);
  }
#pragma unroll
  for (int i = N / 2; i < 32; i++) P[i] = 0;
  pin(P);
  t0 += u0; t1 += u1;
}
template <int N>
__device__ __forceinline__ void causal_mask(float (&s)[N], int thr) {
#pragma unroll
  for (int i = 0; i < 8; i++) {
    if (8 * i > thr) s[N - 32 + 4 * i] = -INFINITY;
    if (8 * i + 1 > thr) s[N - 32 + 4 * i + 1] = -INFINITY;
    if (8 * i - 8 > thr) s[N - 32 + 4 * i + 2] = -INFINITY;
    if (8 * i - 7 > thr) s[N - 32 + 4 * i + 3] = -INFINITY;
  }
}
__device__ __forceinline__ void issue_qk(float (&s)[32], uint32_t qd, uint32_t kd) {
  WG_FENCE();
#pragma unroll
  for (int kk = 0; kk < 8; kk++) wgmma_ss64<0>(s, qd + (kk >> 2) * 512 + (kk & 3) * 2, kd + (kk >> 2) * 1024 + (kk & 3) * 2, kk != 0);
  WG_COMMIT();
}
__device__ __forceinline__ void issue_qk(float (&s)[64], uint32_t qd, uint32_t kd) {
  WG_FENCE();
#pragma unroll
  for (int kk = 0; kk < 8; kk++) wgmma_ss128<0>(s, qd + (kk >> 2) * 512 + (kk & 3) * 2, kd + (kk >> 2) * 1024 + (kk & 3) * 2, kk != 0);
  WG_COMMIT();
}
template <int NK>
__device__ __forceinline__ void issue_pv(float (&o)[64], const uint32_t (&P)[32], uint32_t vd, int acc) {
  WG_FENCE();
#pragma unroll
  for (int kk = 0; kk < NK; kk++) wgmma_rs128<1>(o, P[4 * kk], P[4 * kk + 1], P[4 * kk + 2], P[4 * kk + 3], vd + kk * 128, kk != 0 ? 1 : acc);
  WG_COMMIT();
}
__device__ __forceinline__ void stage_done(const Ctx& c, int b) {
  FENCE_ASYNC_SMEM();
  __syncwarp();
  if (c.lane == 0) mbar_arrive(c.bar + (B_SF + b) * 8);
}
__device__ __forceinline__ void p2_epilogue(const float (&o)[64], float s0, float s1, const Ctx& c, int b) {
  stage_tile(o, c.sm + SM_BUF + b * 16384, c, s0, s1);
  stage_done(c, b);
}

struct P2State {
  float m0, m1, l0, l1;
  bool shift;
  float e0, e1;
  int ks;
  int wi, ai;
  uint32_t wb, ab;
  uint32_t qd;
};
#define PROFZ()
__device__ __forceinline__ int wrap5(int q) { return q >= 5 ? q - 5 : q; }
__device__ __forceinline__ void turn_wait(uint32_t ring, int i) { mbar_wait(ring + (i & 3) * 8, (i >> 2) & 1); }
__device__ __forceinline__ void turn_pass(const Ctx& c, uint32_t ring, int i) { if (c.lane == 0) mbar_arrive(ring + (i & 3) * 8); }
__device__ __forceinline__ void p2_scales(P2State& z) {
  float l0 = z.l0, l1 = z.l1;
  l0 += __shfl_xor_sync(0xffffffffu, l0, 1);
  l1 += __shfl_xor_sync(0xffffffffu, l1, 1);
  l0 += __shfl_xor_sync(0xffffffffu, l0, 2);
  l1 += __shfl_xor_sync(0xffffffffu, l1, 2);
  asm("rcp.approx.ftz.f32 %0, %1;" : "=f"(z.e0) : "f"(l0));
  asm("rcp.approx.ftz.f32 %0, %1;" : "=f"(z.e1) : "f"(l1));
}
template <int N>
__device__ __forceinline__ void p2_first(const Ctx& c, P2State& z, float (&o)[64], uint32_t (&Pc)[32], uint32_t (&Pn)[32],
                                         int ks, int vs, int cnt, int acc) {
  float s[N] = {};
  issue_qk(s, z.qd, desc_lo(c.sm + SM_RING, 16) + ks * 2048);
  if (vs >= 0) {
    p2_scales(z);
    issue_pv<8>(o, Pc, desc_lo(c.sm + SM_RING, 16384) + vs * 2048, acc);
  } else {
    WG_COMMIT();
  }
  mbar_expect(z.ab + (z.ai++ & 3) * 8, cnt == 1 ? 8192 : 0);
  PROFZ();
  WG_WAIT(1);
  PROFZ();
  pin(s);
  release(c, B_P2E + ks, cnt);
  causal_mask(s, c.warp * 16 + (c.lane >> 2) - 2 * (c.lane & 3));
  z.m0 = z.m1 = 0.f;
  row_exp<false>(s, Pn, 0.f, 0.f, z.l0, z.l1);
  z.shift = __any_sync(0xffffffffu, !(z.l0 + z.l1 <= SM_HI) || ((c.lane & 3) == 0 && !(fminf(z.l0, z.l1) >= SM_LO)));
  if (__builtin_expect(z.shift, 0)) {
    z.m0 = z.m1 = -INFINITY;
    row_max(s, z.m0, z.m1);
    row_exp<true>(s, Pn, z.m0, z.m1, z.l0, z.l1);
  }
  WG_WAIT(0);
  pin(o);
  if (vs >= 0) release(c, B_P2E + vs, 1);
}

template <bool SECOND>
__device__ __forceinline__ void p2_turn(const Ctx& c, P2State& z, float (&o)[64], uint32_t (&Pc)[32], uint32_t (&Pn)[32],
                                        int eb = -1, bool half = false, int vcnt = 1) {
  float s[64] = {};
  const int ks = z.ks, vs = wrap5(ks + 1);
  PROFZ();
  turn_wait(z.wb, z.wi++);
  PROFZ();
  issue_qk(s, z.qd, desc_lo(c.sm + SM_RING, 16) + ks * 2048);
  const uint32_t vd = desc_lo(c.sm + SM_RING, 16384) + vs * 2048;
  if (SECOND) {
    if (eb >= 0) stage_tile(o, c.sm + SM_BUF + eb * 16384, c, z.e0, z.e1);
    if (half) issue_pv<4>(o, Pc, vd, 0); else issue_pv<8>(o, Pc, vd, 0);
  } else {
    issue_pv<8>(o, Pc, vd, 1);
  }
  turn_pass(c, z.ab, z.ai++);
  if (SECOND) { if (eb >= 0) stage_done(c, eb); }
  PROFZ();
  z.ks = wrap5(ks + 2);
  WG_WAIT(1);
  PROFZ();
  pin(s);
  release(c, B_P2E + ks, 1);
  float t0, t1, a0 = 1.f, a1 = 1.f;
  row_exp<false>(s, Pn, 0.f, 0.f, t0, t1);
  z.shift = __any_sync(0xffffffffu, z.shift || !(t0 + t1 <= SM_HI));
  const bool redo = z.shift;
  if (__builtin_expect(redo, 0)) {
    float n0 = z.m0, n1 = z.m1;
    row_max(s, n0, n1);
    a0 = ex2(z.m0 - n0); a1 = ex2(z.m1 - n1);
    z.m0 = n0; z.m1 = n1;
    z.l0 *= a0; z.l1 *= a1;
    row_exp<true>(s, Pn, z.m0, z.m1, t0, t1);
  }
  WG_WAIT(0);
  pin(o);
  release(c, B_P2E + vs, vcnt);
  if (__builtin_expect(redo, 0)) {
#pragma unroll
    for (int i = 0; i < 16; i++) { o[4 * i] *= a0; o[4 * i + 1] *= a0; o[4 * i + 2] *= a1; o[4 * i + 3] *= a1; }
  }
  z.l0 += t0; z.l1 += t1;
}
__device__ __forceinline__ void copy_p(uint32_t (&d)[32], const uint32_t (&s)[32], int zero) {
#pragma unroll
  for (int i = 0; i < 32; i++) asm volatile("add.s32 %0, %1, %2;" : "=r"(d[i]) : "r"(s[i]), "r"(zero));
}

__device__ __forceinline__ void p2_consumer(const Params& p, const Ctx& c, int rot) {
  const int nit = p.s.r[c.cl].n2;
  const uint32_t fring = c.bar + B_P2F * 8, oring = c.bar + B_ORD * 8;
  float o[64] = {};
  uint32_t Pa[32] = {}, Pb[32] = {};
  P2State z;
  z.e0 = z.e1 = z.l0 = z.l1 = 0.f; z.ks = rot; z.shift = false;
  int acc = 0, n = 0;
  for (int it = 0; it < nit; it++) {
    const int j = p.s.r[c.cl].item[it] & 7, blk = p2_blk(c.rank, c.wg, it);
    const int lng = ((it ^ c.wg) & 1) ^ 1;
    z.qd = desc_lo(c.sm + SM_BUF, 16) + p2_buf(c.wg, it) * 1024;
    if (lng) { z.wb = oring; z.wi = n - it; z.ab = fring; z.ai = n + 1; }
    else { z.wb = fring; z.wi = n + 2; z.ab = oring; z.ai = n - it; }
    PROFZ();
    mbar_wait(c.bar + (B_QF + p2_buf(c.wg, it)) * 8, (it >> 1) & 1);
    turn_wait(fring, n + 1 - lng);
    PROFZ();
    const int vs = it ? wrap5(z.ks + 1) : -1, ks = lng ? z.ks : wrap5(z.ks + (it ? 2 : 1));
    if (blk & 1) p2_first<64>(c, z, o, Pa, Pb, ks, vs, 1 + lng, acc);
    else p2_first<32>(c, z, o, Pa, Pb, ks, vs, 1 + lng, acc);
    z.ks = wrap5(ks + (it == 0 && lng ? 1 : 2));
    PROF(c.wg, 24 + it);
    n += 2 * j + 2;
    int left = 2 * j + lng;
    acc = left != 0;
    if (left == 0) { copy_p(Pa, Pb, p.zero); continue; }
    p2_turn<true>(c, z, o, Pb, Pa, it > 0 ? p2_buf(c.wg, it - 1) : -1, !(blk & 1), 1 + lng);
    while (--left > 0) {
      p2_turn<false>(c, z, o, Pa, Pb);
      if (--left == 0) { copy_p(Pa, Pb, p.zero); break; }
      p2_turn<false>(c, z, o, Pb, Pa);
    }
  }
  {
    if (!acc && nit > 1) p2_epilogue(o, z.e0, z.e1, c, p2_buf(c.wg, nit));
    turn_wait(z.wb, z.wi);
    issue_pv<8>(o, Pa, desc_lo(c.sm + SM_RING, 16384) + z.ks * 2048, acc);
    if (((nit - 1) ^ c.wg) & 1) turn_pass(c, z.ab, z.ai);
    p2_scales(z);
    WG_WAIT(0);
    pin(o);
    release(c, B_P2E + z.ks);
    p2_epilogue(o, z.e0, z.e1, c, p2_buf(c.wg, nit - 1));
    PROF(c.wg, 24 + nit);
  }
}

__device__ __forceinline__ void p2_load_q(const Params& p, const Ctx& c, int it, int w) {
  const int item = p.s.r[c.cl].item[it], h = item >> 3, j = item & 7, b = p2_buf(w, it);
  mbar_expect(c.bar + (B_QF + b) * 8, 16384);
  bulk_load(c.sm + SM_BUF + b * 16384, g_Q + (size_t)(h * 32 + j * 4 + p2_blk(c.rank, w, it)) * 16384, 16384, c.bar + (B_QF + b) * 8, POL(4));
}
__device__ __forceinline__ void wait_p1_free(const Ctx& c, int u1, int s) {
  mbar_wait(c.bar + (B_P1E + 2 * s) * 8, ((u1 - 1 - 2 * s) / 10) & 1);
  mbar_wait(c.bar + (B_P1E + 2 * s + 1) * 8, ((u1 - 2 - 2 * s) / 10) & 1);
}
__device__ __forceinline__ void p2_producer(const Params& p, const Ctx& c, int u1, int rot) {
  const int nit = p.s.r[c.cl].n2;
  int slot = rot, cnt = 0, par = 1, n = 0;
  const uint8_t* pv = nullptr;
  bool pl = false;
  auto load = [&](const uint8_t* src, int expect, uint32_t fb, bool last) {
    if (cnt < 5) {
      if (u1) {
        wait_p1_free(c, u1, slot);
        if (cnt == 0) p2_load_q(p, c, 0, 1);
      }
      cnt++;
    } else {
      if (slot == rot) par ^= 1;
      mbar_wait(c.bar + (B_P2E + slot) * 8, par);
    }
    if (expect) mbar_expect(fb, expect);
    bulk_load_mc(c.sm + SM_RING + slot * 32768 + c.rank * 16384, src, 16384, fb, last ? POL(5) : L2_NORMAL);
    slot = wrap5(slot + 1);
  };
  for (int it = 0; it < nit; it++) {
    const int item = p.s.r[c.cl].item[it], h = item >> 3, j = item & 7;
    if (it == 1 && (c.phases & 16) && p.s.r[c.cl].n1 < 8) flag_wait<true>(F_GATE, 256);
    uint32_t ready = (c.phases & 16) ? 0u : 255u;
    if (it == 0) { if (c.phases & 16) flag_wait<false>(F_Q + item, 4); mbar_wait(c.bar + B_LAD * 8, 0); p2_load_q(p, c, 0, 0); if (!u1) p2_load_q(p, c, 0, 1); }
    for (int t = 2 * j + 1; t >= 0; t--) {
      mask_wait(ready, t >> 1, F_KV + h * 8 + (c.lane & 7), 8);
      const uint8_t* k = g_KV + (size_t)(p.s.slot[h][t >> 1] * 16 + t) * 32768 + c.rank * 16384;
      const uint32_t fb = c.bar + (B_P2F + (n & 3)) * 8;
      const bool last = (p.s.r[c.cl].last[it] >> (t >> 1)) & 1;
      load(k, pv && t != 2 * j ? 65536 : 32768, fb, last);
      if (!(t & 1) && t + 4 <= 2 * j && c.rank == 0) flag_add_rx(F_RD + h * 8 + (t >> 1) + 2);
      if (pv) load(pv, 0, t != 2 * j ? fb : c.bar + (B_ORD + ((n - 1 - it) & 3)) * 8, pl);
      pl = last;
      pv = k + (size_t)NH * 16 * 32768;
      n++;
    }
  }
  load(pv, 32768, c.bar + (B_P2F + (n & 3)) * 8, pl);
}

__device__ __forceinline__ void p2_storer(const Params& p, const Ctx& c, int sfpar) {
  const int nit = p.s.r[c.cl].n2;
  auto load_q = [&](int it, int w) {
    if (c.phases & 16) flag_wait<false>(F_Q + p.s.r[c.cl].item[it], 4);
    p2_load_q(p, c, it, w);
  };
  if (nit > 1) {
    load_q(1, 1); p2_load_q(p, c, 1, 0); }
  for (int i = 0; i < 2 * nit; i++) {
    const int it = i >> 1, w = (it ^ i ^ 1) & 1, b = p2_buf(w, it);
    const int item = p.s.r[c.cl].item[it], h = item >> 3, j = item & 7;
    mbar_wait(c.bar + (B_SF + b) * 8, (sfpar >> b) & 1);
    sfpar ^= 1 << b;
    bulk_store(g_Q + (size_t)(h * 32 + j * 4 + p2_blk(c.rank, w, it)) * 16384, c.sm + SM_BUF + b * 16384, 16384, POL(1));
    BULK_COMMIT();
    BULK_WAIT(0);
    flag_add_rx(F_CTX + j * 64 + h);
    if ((i & 1) && it + 2 < nit) { load_q(it + 2, w); p2_load_q(p, c, it + 2, w ^ 1); }
  }
  release(c, B_DONE);
}

__device__ __forceinline__ int p3_pos(int i, int x) { return i < 4 ? (i + x) & 3 : 4; }
__device__ __forceinline__ void p3_consumer(const Params& p, const Ctx& c, int x) {
  const bool first = p.s.r[c.cl].p3 >= 24;
  const int tile = p.s.r[c.cl].p3 - (first ? 24 : 0), j = tile / 3, nt = tile - 3 * j;
  const int na = first ? 9 : 0, nb = first ? 2 * p.s.nh[tile] : 64 - 2 * p.s.nh[tile];
  const uint32_t ad = desc_lo(c.sm + SM_RING + c.wg * 8192, 16), bd = desc_lo(c.sm + SM_RING + 16384, 4096);
  float acc[96] = {};
  int slot = 0, par = 0, prev = 0;
  float g0 = 0.f, g1 = 0.f;
  const int hold = c.wg && LAG ? na + nb - LAG : -1, pass = c.wg || !LAG ? -1 : na + nb - 1;
#pragma unroll 1
  for (int kb = 0; kb < nb; kb++) {
    if (kb == hold) bar_sync(6, 256);
    mbar_wait(c.bar + (B_P3F + slot) * 8, par);
    if (kb == 0) PROF(c.wg, 39);
    WG_FENCE();
#pragma unroll
    for (int kk = 0; kk < 4; kk++) wgmma_ss192<1>(acc, ad + p3_pos(slot, x) * 2560 + kk * 2, bd + p3_pos(slot, x) * 2560 + (kk >> 1) * 768 + (kk & 1) * 128, kk != 0 ? 1 : kb != 0);
    WG_COMMIT();
    if (kb == pass) bar_arrive(6, 256);
    WG_WAIT(1);
    if (kb > 0) release(c, B_P3E + prev);
    else {
      const float* g = g_gate + j * 256 + c.rank * 128 + c.wg * 64 + c.warp * 16 + (c.lane >> 2);
      g0 = __ldcg(g); g1 = __ldcg(g + 8);
    }
    prev = slot;
    if (++slot == 5) { slot = 0; par ^= 1; }
  }
  WG_WAIT(0);
  pin(acc);
  g0 = 1.f - g0; g1 = 1.f - g1;
#pragma unroll
  for (int i = 0; i < 24; i++) { acc[4 * i] *= g0; acc[4 * i + 1] *= g0; acc[4 * i + 2] *= g1; acc[4 * i + 3] *= g1; }
#pragma unroll 1
  for (int kb = nb; kb < nb + na; kb++) {
    if (kb == hold) bar_sync(6, 256);
    mbar_wait(c.bar + (B_P3F + slot) * 8, par);
    if (kb == 0) PROF(c.wg, 39);
    WG_FENCE();
#pragma unroll
    for (int kk = 0; kk < 4; kk++) wgmma_ss192<1, 1>(acc, ad + p3_pos(slot, x) * 2560 + kk * 128, bd + p3_pos(slot, x) * 2560 + (kk >> 1) * 768 + (kk & 1) * 128, 1);
    WG_COMMIT();
    if (kb == pass) bar_arrive(6, 256);
    WG_WAIT(1);
    if (kb > 0) release(c, B_P3E + prev);
    prev = slot;
    if (++slot == 5) { slot = 0; par ^= 1; }
  }
  WG_WAIT(0);
  pin(acc);
  PROF(c.wg, 40);
  if (first) bar_sync(4 + c.wg, 128);
  mbar_wait(c.bar + B_OUT * 8, 0);
  const int row = (c.lane & 7) + ((c.lane >> 3) & 1) * 8;
  const uint32_t wbase = c.sm + SM_RING + c.wg * 8192 + c.warp * 2048;
  const uint32_t base = wbase + row * 128 + (((c.lane >> 4) ^ (row & 7)) << 4);
#pragma unroll
  for (int i = 0; i < 12; i++) {
    stsm4((base ^ ((i & 3) << 5)) + (i >> 2) * 40960, pack_bf16(acc[8 * i], acc[8 * i + 1]), pack_bf16(acc[8 * i + 2], acc[8 * i + 3]),
          pack_bf16(acc[8 * i + 4], acc[8 * i + 5]), pack_bf16(acc[8 * i + 6], acc[8 * i + 7]));
    if ((i & 3) == 3) {
      FENCE_ASYNC_SMEM();
      bar_sync(4 + c.wg, 128);
      if (c.warp == (i >> 2)) tma2d_add(&p.map_out, c.sm + SM_RING + c.wg * 8192 + c.warp * 40960, nt * 192 + c.warp * 64, j * 256 + c.rank * 128 + c.wg * 64);
    }
  }
  BULK_COMMIT();
  PROF(c.wg, 43);
  BULK_WAIT_READ(0);
  PROF(c.wg, 44);
}

__device__ __forceinline__ void p3_producer(const Params& p, const Ctx& c, int u1, int u2, int rot, int x) {
  const bool first = p.s.r[c.cl].p3 >= 24;
  const int tile = p.s.r[c.cl].p3 - (first ? 24 : 0), j = tile / 3, nt = tile - 3 * j;
  int slot = 0, par = 1, cnt = 0;
  auto wait_free = [&](int s) {
    const int f = wrap5(s + 5 - rot);
    if (f < u2) mbar_wait(c.bar + (B_P2E + s) * 8, ((u2 - 1 - f) / 5) & 1);
    else if (u1) wait_p1_free(c, u1, s);
  };
  asm volatile(ELECT("prefetch.tensormap [%0];") ::"l"(&p.map_o[0]) : "memory");
  asm volatile(ELECT("prefetch.tensormap [%0];") ::"l"(&p.map_out) : "memory");
  if ((c.phases & 16) && p.s.r[c.cl].n1 < 8 && p.s.r[c.cl].n2 < 2) flag_wait<true>(F_GATE, 256);
  uint32_t ready = (c.phases & 16) ? 0u : ~0u;
  const int q1 = first ? p.s.nh[tile] : 31;
  for (int q = first ? 0 : p.s.nh[tile]; q <= q1; q++) {
    const bool brA = first && q == q1;
    const int g = brA ? 32 : p.s.p3_order[j][q];
    if (brA) { if (c.phases & 16) flag_wait<false>(F_CTX + j * 64 + 32, 16); }
    else mask_wait(ready, g, F_CTX + j * 64 + c.lane, 4);
    const int nk = brA ? 9 : 2, k0 = (brA ? 0 : g * 128) + c.rank * 32;
    const uint8_t* a = brA ? g_oA + (j * 4 + c.rank * 2) * 73728 : g_Q + (size_t)(g * 32 + j * 4 + c.rank * 2) * 16384;
    const CUtensorMap* m = &p.map_o[brA];
    for (int i = 0; i < nk; i++) {
      const uint32_t st = c.sm + SM_RING + p3_pos(slot, x) * 40960, fb = c.bar + (B_P3F + slot) * 8;
      if (cnt < 4) { wait_free(p3_pos(cnt, x)); wait_free(p3_pos(cnt, x) + 1); }
      else if (cnt == 4) mbar_wait(c.bar + B_DONE * 8, 0);
      else mbar_wait(c.bar + (B_P3E + slot) * 8, par);
      cnt++;
      mbar_expect(fb, 40960);
      bulk_load(st, a + i * 8192, 8192, fb, POL(3));
      bulk_load(st + 8192, a + (nk + i) * 8192, 8192, fb, POL(3));
      tma3d_mc(st + 16384 + c.rank * 12288, m, 0, k0 + i * 64, nt * 3, fb);
      if (++slot == 5) { slot = 0; par ^= 1; }
    }
  }
}

__device__ __forceinline__ float bf_lo(uint32_t w) { return __uint_as_float(w << 16); }
__device__ __forceinline__ float bf_hi(uint32_t w) { return __uint_as_float(w & 0xffff0000u); }

__device__ __forceinline__ void gate_rows(const Params& p, int row0, int lane) {
  const uint4* x = reinterpret_cast<const uint4*>(p.x + (size_t)(row0 + (lane >> 2)) * DM) + (lane & 3);
  const uint4* w = reinterpret_cast<const uint4*>(p.gate_w) + (lane & 3);
  float a = 0.f;
#pragma unroll 1
  for (int b = 0; b < 3; b++) {
    uint4 u[6];
#pragma unroll
    for (int i = 0; i < 6; i++) u[i] = __ldg(x + (b * 6 + i) * 4);
#pragma unroll
    for (int i = 0; i < 6; i++) {
      const uint4 v = __ldg(w + (b * 6 + i) * 4);
      a = fmaf(bf_lo(u[i].x), bf_lo(v.x), a); a = fmaf(bf_hi(u[i].x), bf_hi(v.x), a);
      a = fmaf(bf_lo(u[i].y), bf_lo(v.y), a); a = fmaf(bf_hi(u[i].y), bf_hi(v.y), a);
      a = fmaf(bf_lo(u[i].z), bf_lo(v.z), a); a = fmaf(bf_hi(u[i].z), bf_hi(v.z), a);
      a = fmaf(bf_lo(u[i].w), bf_lo(v.w), a); a = fmaf(bf_hi(u[i].w), bf_hi(v.w), a);
    }
  }
  a += __shfl_xor_sync(0xffffffffu, a, 1);
  a += __shfl_xor_sync(0xffffffffu, a, 2);
  if ((lane & 3) == 0) g_gate[row0 + (lane >> 2)] = 1.f / (1.f + __expf(-a));
}

__device__ __forceinline__ void lds10(uint32_t (&k)[10], uint32_t a) {
  asm volatile("ld.shared.v2.u32 {%0, %1}, [%10];\nld.shared.v2.u32 {%2, %3}, [%10+8];\nld.shared.v2.u32 {%4, %5}, [%10+16];\n"
               "ld.shared.v2.u32 {%6, %7}, [%10+24];\nld.shared.v2.u32 {%8, %9}, [%10+32];"
               : "=r"(k[0]), "=r"(k[1]), "=r"(k[2]), "=r"(k[3]), "=r"(k[4]), "=r"(k[5]), "=r"(k[6]), "=r"(k[7]), "=r"(k[8]), "=r"(k[9]) : "r"(a));
}
__device__ __forceinline__ void local_attn(const Params& p, const Ctx& c, int rb, int hs) {
  const int lane = c.lane, grp = rb >> 2, par = lane >> 4, i0 = 2 * (lane & 15);
  const uint32_t buf = c.sm + SM_BUF + (c.warp - 2) * 8192, bqk = c.bar + (B_LA + (c.warp - 2) * 2) * 8, bv = bqk + 8;
  const uint32_t mine = buf + 2304 + par * 160 + i0 * 4;
  const bool flags = c.phases & 16;
  auto fetch_qk = [&](int i) {
    if (flags && !(i & 1)) {
      const int q = i >> 1;
      const int tgt = q == 0 ? 24 : q == 3 ? 8 : 12;
      flag_wait<false>(F_QKVA + (grp - (grp > 0 && (rb & 3) == 0 ? par : 0)) * 4 + q, tgt);
    }
    mbar_expect(bqk, 5184);
    tma3d(buf, &p.map_t[0], rb * 32 + 8, 0, 9 * (4 * i + hs), bqk, POL(2));
    tma3d(buf + 2304, &p.map_t[1], rb * 32, 0, 288 + 9 * (4 * i + hs), bqk, POL(2));
  };
  auto fetch_v = [&](int i) { mbar_expect(bv, 2880); tma3d(buf + 5248, &p.map_t[1], rb * 32, 0, 576 + 9 * (4 * i + hs), bv, POL(2)); };
  fetch_qk(0);
  if (flags) flag_wait<true>(F_GATE, 256);
#pragma unroll 1
  for (int q = 0; q < 8; q++) {
    fetch_v(q);
    float a[8], b[8];
#pragma unroll
    for (int w = 0; w < 8; w++) a[w] = b[w] = 0.f;
    mbar_wait(bqk, q & 1);
    PROFB(1 + 2 * q);
#pragma unroll 1
    for (int j = 0; j < 9; j++) {
      uint32_t x, y, k[10];
      asm volatile("ld.shared.v2.u32 {%0, %1}, [%2];" : "=r"(x), "=r"(y) : "r"(buf + lane * 8 + j * 256));
      lds10(k, mine + j * 320);
      const float xl = bf_lo(x), xh = bf_hi(x), yl = bf_lo(y), yh = bf_hi(y);
#pragma unroll
      for (int m = 1; m < 10; m++) {
        const float kl = bf_lo(k[m]), kh = bf_hi(k[m]);
        if (m < 9) a[8 - m] = fmaf(xl, kl, fmaf(xh, kh, a[8 - m]));
        if (m > 1) b[9 - m] = fmaf(yl, kl, fmaf(yh, kh, b[9 - m]));
      }
    }
    __syncwarp();
    if (q < 7) fetch_qk(q + 1);
    constexpr float SC = 0.23570226039551584f * 1.4426950408889634f;
    const float* gp = g_gate + rb * 64 + 2 * i0 + par;
    const float ga = __ldcg(gp), gb = __ldcg(gp + 2);
    float ma = a[0], mb = b[0];
#pragma unroll
    for (int w = 1; w < 8; w++) {
      if (rb == 0) {
        if (i0 < w) a[w] = -INFINITY;
        if (i0 + 1 < w) b[w] = -INFINITY;
      }
      ma = fmaxf(ma, a[w]); mb = fmaxf(mb, b[w]);
    }
    float la = 0.f, lb = 0.f;
#pragma unroll
    for (int w = 0; w < 8; w++) {
      a[w] = ex2((a[w] - ma) * SC); b[w] = ex2((b[w] - mb) * SC);
      la += a[w]; lb += b[w];
    }
    la = __fdividef(ga, la); lb = __fdividef(gb, lb);
#pragma unroll
    for (int w = 0; w < 8; w++) { a[w] *= la; b[w] *= lb; }
    uint8_t* dst = g_oA + rb * 73728 + ((i0 & 2) + par) * 4;
    mbar_wait(bv, q & 1);
#pragma unroll 1
    for (int j = 0; j < 9; j++) {
      uint32_t v[10];
      lds10(v, mine + 2944 + j * 320);
      float a0 = 0.f, a1 = 0.f, b0 = 0.f, b1 = 0.f;
#pragma unroll
      for (int m = 1; m < 10; m++) {
        const float vl = bf_lo(v[m]), vh = bf_hi(v[m]);
        if (m < 9) { a0 = fmaf(a[8 - m], vl, a0); a1 = fmaf(a[8 - m], vh, a1); }
        if (m > 1) { b0 = fmaf(b[9 - m], vl, b0); b1 = fmaf(b[9 - m], vh, b1); }
      }
      const uint32_t wa = pack_bf16(a0, a1), wb = pack_bf16(b0, b1);
      const uint32_t got = __shfl_xor_sync(0xffffffffu, par ? wa : wb, 16);
      const uint32_t r0 = par ? got : wa, r1 = par ? wb : got;
      const int col = 18 * (4 * q + hs) + 2 * j, o = col * 128 + ((((i0 >> 2) ^ col) & 7) << 4);
      *reinterpret_cast<uint32_t*>(dst + o) = __byte_perm(r0, r1, 0x5410);
      *reinterpret_cast<uint32_t*>(dst + ((o + 128) ^ 16)) = __byte_perm(r0, r1, 0x7632);
    }
    __syncwarp();
    PROFB(2 + 2 * q);
  }
  mbar_arrive_one(c.bar + B_LAD * 8);
  flag_add(F_CTX + grp * 64 + 32);
}

__global__ void __cluster_dims__(2, 1, 1) __launch_bounds__(384, 1) fused_kernel(const __grid_constant__ Params p) {
  extern __shared__ uint8_t smem_raw[];
  Ctx c;
  c.sm = ((uint32_t)__cvta_generic_to_shared(smem_raw) + 1023u) & ~1023u;
  c.bar = c.sm + SM_BAR;
  c.lane = threadIdx.x & 31;
  const int wid = __shfl_sync(0xffffffffu, threadIdx.x >> 5, 0);
  if (wid < 6) asm volatile("prefetch.tensormap [%0];" ::"l"(&p.map_a[0] + wid) : "memory");
  c.wg = wid >> 2;
  c.warp = wid & 3;
  PROF(c.wg, 0);
  PROFG(61);
  c.cl = (blockIdx.x + (wid >> 4)) >> 1;
  c.rank = blockIdx.x & 1;
  c.rbar = mapa(c.bar, c.lane & 1);
  {
    const int w = wid, cnt = (((int)(B_CNT >> (4 * w)) - 1) & 15) + 1;
    if (w < 11) {
#pragma unroll
      for (int i = 0; i < 8; i++) asm volatile("mbarrier.init.shared::cta.b64 [%0], %1;" ::"r"(c.bar + w * 64 + i * 8), "r"(cnt));
    }
    asm volatile("fence.mbarrier_init.release.cluster;" ::: "memory");
  }
  if (c.wg == 2) PROF(2, 56);
  asm volatile("barrier.cluster.arrive.relaxed;" ::: "memory");
  c.phases = p.s.r[c.cl].phases;
  const bool do1 = p.s.r[c.cl].n1 > 0, do2 = p.s.r[c.cl].n2 > 0, do3 = p.s.r[c.cl].p3 != 255;
  if (do1 && c.wg == 2 && c.warp == 0) {
    const int type = p.s.r[c.cl].slab >> 3;
    PROF(2, 57);
    FENCE_ASYNC_SMEM();
    mbar_expect(c.bar + B_P1F * 8, type ? 32768 : 16384);
    tma2d(type ? c.sm + SM_BUF + 32768 : c.sm + SM_RING, &p.map_a[type], type ? 512 : 0, (p.s.r[c.cl].slab & 7) * 256 + c.rank * 128, c.bar + B_P1F * 8);
    PROF(2, 58);
  }
  asm volatile("barrier.cluster.wait.acquire;" ::: "memory");
  if (c.wg == 2) PROF(2, 59);
  if (do1 && c.wg == 2 && c.warp == 0) {
    const int type = p.s.r[c.cl].slab >> 3, tile = p.s.r[c.cl].tile[0] & 63;
    const CUtensorMap* m = &p.map_w[type * 2 + (tile >> 5)];
#pragma unroll 1
    for (int s = 1 - type; s < NPRO; s++) {
      const int kb = (s - type) >> 1;
      const uint32_t fb = c.bar + (B_P1F + s) * 8;
      if (s) mbar_expect(fb, 16384);
      if ((s ^ type) & 1) tma2d_mc(c.sm + SM_RING + s * 16384 + c.rank * 8192, m, (tile & 31) * 128 + c.rank * 64, kb < 0 ? 512 : kb * 64, fb);
      else tma2d(c.sm + SM_RING + s * 16384, &p.map_a[type], kb * 64, (p.s.r[c.cl].slab & 7) * 256 + c.rank * 128, fb);
    }
  }

  if (c.wg < 2) {
    PROF(c.wg, 4);
    asm volatile("setmaxnreg.inc.sync.aligned.u32 224;");
    if (c.wg == 1) {
      if (do1) bar_arrive(ORDER, 256);
      if (c.lane == 0) mbar_arrive(c.bar + B_P2F * 8);
    }
    if (do1) p1_consumer(p, c);
    if (do2) p2_consumer(p, c, p.s.r[c.cl].rot);
    if (do3) p3_consumer(p, c, p.s.r[c.cl].x3);
    PROF(c.wg, 63);
    PROFG(62);
    if (c.lane == 0) mbar_arrive(c.bar + B_FIN * 8);
    __syncwarp();
    cluster_sync();
  } else {
    asm volatile("setmaxnreg.dec.sync.aligned.u32 56;");
    if (c.warp == 0) {
      PROF(2, 60);
      if (do1) p1_producer(p, c);
      if (do2) p2_producer(p, c, p.s.r[c.cl].u1, p.s.r[c.cl].rot);
      if (do3) p3_producer(p, c, p.s.r[c.cl].u1, p.s.r[c.cl].u2, p.s.r[c.cl].rot, p.s.r[c.cl].x3);
    } else if (c.warp == 1) {
      int sfpar = 0;
      if (do1) {
        p1_storer(p, c);
        sfpar = (p.s.r[c.cl].n1 & 1) * 10;
      }
      if (do2) p2_storer(p, c, sfpar);
      else { mbar_wait(c.bar + B_LAD * 8, 0); release(c, B_DONE); }
      if (do3) {
        const int task = p.s.r[c.cl].p3;
        if (task >= 24) {
          const int j = (task - 24) / 3, nt = task - 24 - 3 * j;
          uint4* o = reinterpret_cast<uint4*>(p.out + (size_t)(j * 256 + c.rank * 128 + (c.lane >> 3)) * DM + nt * 192) + (c.lane & 7);
#pragma unroll 4
          for (int r = 0; r < 32; r++) o[r * 288] = o[r * 288 + 8] = o[r * 288 + 16] = make_uint4(0u, 0u, 0u, 0u);
          __syncwarp();
          flag_add(F_OUT + (task - 24) * 2 + c.rank);
        } else if (c.phases & 16) {
          flag_wait<false, 256>(F_OUT + task * 2 + c.rank, 1);
        }
        mbar_arrive_one(c.bar + B_OUT * 8);
      }
    } else {
      const int bw = blockIdx.x * 2 + (c.warp - 2);
      if ((c.phases & 1) && bw < 256) {
        gate_rows(p, bw * 8, c.lane);
        __syncwarp();
        flag_add(F_GATE);
      }
      if (p.s.r[c.cl].bg != 255) local_attn(p, c, p.s.r[c.cl].bg, bw & 3);
      else if (c.lane == 0) mbar_arrive(c.bar + B_LAD * 8);
    }
    __syncwarp();
    bar_sync(3, 128);
    if (c.warp == 0 && (c.phases & 4)) {
      int last = 0;
      if (c.lane == 0) { __threadfence(); last = atomicAdd(g_flags + F_DONE, 1) == 2 * NCL - 1; }
      if (__shfl_sync(0xffffffffu, last, 0)) for (int i = c.lane; i < F_NUM; i += 32) g_flags[i] = 0;
    }
    if (c.warp == 1) mbar_wait(c.bar + B_FIN * 8, 0);
    __syncwarp();
    cluster_sync();
  }
}

SCHED_DECL Sched k_sched = {
  {{0,29,1,28,0,{203,0,0,0,0,0,0,0,0,0,0},{0,0,0,0,0,0,0,0,0,0,0},{69,40,70,35,1,14,9,4,29,18,15,31,12,17,2,11,20,27,13,23,16,22,28,26,19,25,21,30,24,0}},
   {1,30,1,45,1,{202,0,0,0,0,0,0,0,0,0,0},{0,0,0,0,0,0,0,0,0,0,0},{69,40,3,32,6,1,9,4,29,14,18,15,31,12,17,2,11,20,27,13,23,26,28,16,19,22,25,30,21,24}},
   {2,30,2,255,2,{242,169,0,0,0,0,0,0,0,0,0},{0,0,0,0,0,0,0,0,0,0,0},{71,40,3,32,6,1,4,14,15,9,18,29,12,31,20,2,11,17,13,27,23,28,16,22,26,19,25,30,21,24}},
   {3,28,2,255,3,{208,173,0,0,0,0,0,0,0,0,0},{0,63,0,0,0,0,0,0,0,0,0},{72,39,5,32,6,14,9,4,15,18,29,12,31,2,11,20,17,13,27,23,16,28,22,26,19,25,30,21,0,0}},
   {4,29,1,33,4,{130,0,0,0,0,0,0,0,0,0,0},{0,0,0,0,0,0,0,0,0,0,0},{71,40,128,37,6,14,4,9,18,15,29,31,12,2,17,20,11,13,27,23,16,28,22,26,19,25,21,30,24,0}},
   {5,28,1,25,5,{205,0,0,0,0,0,0,0,0,0,0},{32,0,0,0,0,0,0,0,0,0,0},{67,39,128,37,6,14,41,15,18,29,31,12,2,17,11,20,13,27,23,16,28,22,26,25,19,21,30,24,0,0}},
   {6,27,0,2,6,{0,0,0,0,0,0,0,0,0,0,0},{0,0,0,0,0,0,0,0,0,0,0},{71,8,128,42,1,9,36,18,29,31,12,2,17,11,20,13,27,23,16,28,22,26,25,19,85,30,24,0,0,0}},
   {7,26,0,6,7,{0,0,0,0,0,0,0,0,0,0,0},{0,0,0,0,0,0,0,0,0,0,0},{69,7,128,6,78,100,82,93,95,76,66,81,75,84,77,91,87,80,92,86,90,89,83,94,85,88,0,0,0,0}},
   {0,29,1,37,8,{204,0,0,0,0,0,0,0,0,0,0},{31,0,0,0,0,0,0,0,0,0,0},{101,7,102,0,33,46,41,36,61,50,47,63,44,49,34,43,52,59,45,55,48,54,60,58,51,57,53,62,56,0}},
   {1,30,3,255,9,{201,241,240,0,0,0,0,0,0,0,0},{0,0,1,0,0,0,0,0,0,0,0},{101,7,35,10,38,33,41,36,61,46,50,47,63,44,49,34,43,52,59,45,55,58,60,48,51,54,57,62,53,56}},
   {2,30,1,44,10,{154,0,0,0,0,0,0,0,0,0,0},{7,0,0,0,0,0,0,0,0,0,0},{103,5,35,10,38,33,36,46,47,41,50,61,44,63,52,34,43,49,45,59,55,60,48,54,58,51,57,62,53,56}},
   {3,30,1,41,11,{210,0,0,0,0,0,0,0,0,0,0},{7,0,0,0,0,0,0,0,0,0,0},{104,3,37,10,38,46,41,36,47,50,61,44,63,34,43,52,49,45,59,55,48,60,54,58,51,57,62,53,24,56}},
   {4,29,2,43,12,{200,129,0,0,0,0,0,0,0,0,0},{0,0,0,0,0,0,0,0,0,0,0},{103,3,96,10,38,46,36,41,50,47,61,63,44,34,49,52,43,45,59,55,48,60,54,58,51,57,53,62,56,0}},
   {5,28,1,34,13,{179,0,0,0,0,0,0,0,0,0,0},{8,0,0,0,0,0,0,0,0,0,0},{99,8,96,10,38,46,4,47,50,61,63,44,34,49,43,52,45,59,55,48,60,54,58,57,51,53,62,56,0,0}},
   {6,27,0,9,14,{0,0,0,0,0,0,0,0,0,0,0},{0,0,0,0,0,0,0,0,0,0,0},{103,40,96,6,33,41,15,50,61,63,44,34,49,43,52,45,59,55,48,60,54,58,57,51,117,62,56,0,0,0}},
   {7,26,1,32,15,{181,0,0,0,0,0,0,0,0,0,0},{48,0,0,0,0,0,0,0,0,0,0},{101,39,96,38,110,79,114,125,127,108,98,113,107,116,109,123,119,112,124,118,122,121,115,126,117,120,0,0,0,0}},
   {0,6,5,255,255,{86,126,251,183,171,0,0,0,0,0,0},{0,0,0,128,0,0,0,0,0,0,0},{72,39,3,32,10,42,0,0,0,0,0,0,0,0,0,0,0,0,0,0,0,0,0,0,0,0,0,0,0,0}},
   {1,4,7,5,255,{27,3,38,97,19,185,176,0,0,0,0},{0,0,0,0,0,0,0,0,0,0,0},{72,39,128,42,0,0,0,0,0,0,0,0,0,0,0,0,0,0,0,0,0,0,0,0,0,0,0,0,0,0}},
   {2,4,6,39,255,{70,50,123,95,182,168,0,0,0,0,0},{0,0,0,128,64,0,0,0,0,0,0},{72,37,128,42,0,0,0,0,0,0,0,0,0,0,0,0,0,0,0,0,0,0,0,0,0,0,0,0,0,0}},
   {3,6,5,255,255,{85,127,141,228,172,0,0,0,0,0,0},{0,128,0,0,0,0,0,0,0,0,0},{71,35,128,42,1,33,0,0,0,0,0,0,0,0,0,0,0,0,0,0,0,0,0,0,0,0,0,0,0,0}},
   {4,6,6,10,255,{0,25,119,121,223,88,0,0,0,0,0},{0,0,0,0,0,1,0,0,0,0,0},{72,35,5,42,1,33,0,0,0,0,0,0,0,0,0,0,0,0,0,0,0,0,0,0,0,0,0,0,0,0}},
   {5,8,6,8,255,{80,83,122,23,186,224,0,0,0,0,0},{0,0,0,0,0,0,0,0,0,0,0},{71,40,5,42,1,33,9,36,0,0,0,0,0,0,0,0,0,0,0,0,0,0,0,0,0,0,0,0,0,0}},
   {6,8,7,21,255,{112,84,113,236,250,105,136,0,0,0,0},{0,0,0,0,0,0,0,0,0,0,0},{67,5,74,38,78,46,4,47,0,0,0,0,0,0,0,0,0,0,0,0,0,0,0,0,0,0,0,0,0,0}},
   {7,7,6,12,255,{8,1,79,234,109,184,0,0,0,0,0},{0,0,0,0,0,0,0,0,0,0,0},{67,8,74,65,73,68,111,0,0,0,0,0,0,0,0,0,0,0,0,0,0,0,0,0,0,0,0,0,0,0}},
   {8,19,3,35,16,{16,219,247,0,0,0,0,0,0,0,0},{0,0,128,0,0,0,0,0,0,0,0},{135,36,3,43,14,39,104,18,15,76,31,20,13,80,11,28,25,21,24,0,0,0,0,0,0,0,0,0,0,0}},
   {9,18,4,255,17,{96,231,178,170,0,0,0,0,0,0,0},{0,0,4,0,0,0,0,0,0,0,0},{69,41,0,10,108,93,14,45,4,76,130,91,20,90,28,89,94,88,0,0,0,0,0,0,0,0,0,0,0,0}},
   {10,19,2,29,18,{108,157,0,0,0,0,0,0,0,0,0},{0,48,0,0,0,0,0,0,0,0,0},{135,41,102,6,35,44,79,45,18,84,130,11,17,27,16,19,26,21,24,0,0,0,0,0,0,0,0,0,0,0}},
   {11,18,3,19,19,{98,161,209,0,0,0,0,0,0,0,0},{0,0,0,0,0,0,0,0,0,0,0},{136,41,0,6,35,44,14,18,45,29,31,11,17,27,28,22,19,30,0,0,0,0,0,0,0,0,0,0,0,0}},
   {12,18,3,27,20,{18,187,206,0,0,0,0,0,0,0,0},{0,0,64,0,0,0,0,0,0,0,0},{135,161,0,6,39,14,9,40,15,31,130,20,13,27,22,26,25,21,0,0,0,0,0,0,0,0,0,0,0,0}},
   {13,20,3,40,21,{160,106,213,0,0,0,0,0,0,0,0},{0,0,56,0,0,0,0,0,0,0,0},{67,36,5,38,14,35,44,18,29,45,12,17,13,27,16,22,26,30,21,24,0,0,0,0,0,0,0,0,0,0}},
   {14,18,4,255,22,{232,221,174,192,0,0,0,0,0,0,0},{0,1,0,0,0,0,0,0,0,0,0},{135,36,0,43,73,39,4,18,40,31,130,20,13,23,28,26,25,30,0,0,0,0,0,0,0,0,0,0,0,0}},
   {15,18,3,255,23,{89,188,175,0,0,0,0,0,0,0,0},{0,0,192,0,0,0,0,0,0,0,0},{69,74,37,38,14,4,39,15,29,40,12,17,20,27,16,22,25,30,0,0,0,0,0,0,0,0,0,0,0,0}},
   {8,18,5,38,24,{32,90,218,227,177,0,0,0,0,0,0},{0,0,0,15,3,0,0,0,0,0,0},{136,41,0,10,35,44,109,9,4,29,130,17,27,86,23,26,19,30,0,0,0,0,0,0,0,0,0,0,0,0}},
   {9,17,2,14,25,{144,165,0,0,0,0,0,0,0,0,0},{0,0,0,0,0,0,0,0,0,0,0},{136,161,34,1,73,82,104,15,95,81,75,77,23,83,16,22,85,0,0,0,0,0,0,0,0,0,0,0,0,0}},
   {10,17,3,36,26,{72,91,215,0,0,0,0,0,0,0,0},{0,0,128,0,0,0,0,0,0,0,0},{136,161,107,68,39,14,104,9,29,31,12,87,13,92,22,89,94,0,0,0,0,0,0,0,0,0,0,0,0,0}},
   {11,19,2,31,27,{107,158,0,0,0,0,0,0,0,0,0},{0,112,0,0,0,0,0,0,0,0,0},{135,161,34,1,39,9,79,40,4,76,130,20,13,23,26,16,25,21,24,0,0,0,0,0,0,0,0,0,0,0}},
   {12,18,2,15,28,{92,128,0,0,0,0,0,0,0,0,0},{0,0,0,0,0,0,0,0,0,0,0},{136,165,34,1,108,4,18,45,29,76,17,11,23,80,28,19,94,88,0,0,0,0,0,0,0,0,0,0,0,0}},
   {13,17,3,24,29,{120,135,131,0,0,0,0,0,0,0,0},{1,0,15,0,0,0,0,0,0,0,0},{135,41,10,43,73,39,4,15,40,31,130,11,20,23,28,19,25,0,0,0,0,0,0,0,0,0,0,0,0,0}},
   {14,18,3,18,30,{248,139,216,0,0,0,0,0,0,0,0},{0,0,0,0,0,0,0,0,0,0,0},{67,41,10,1,35,44,79,29,45,76,75,17,27,80,22,19,85,88,0,0,0,0,0,0,0,0,0,0,0,0}},
   {15,19,2,255,31,{134,245,0,0,0,0,0,0,0,0,0},{0,0,0,0,0,0,0,0,0,0,0},{67,32,42,43,73,35,44,18,95,45,130,11,13,23,28,26,19,21,24,0,0,0,0,0,0,0,0,0,0,0}},
   {8,3,4,13,255,{68,14,74,22,0,0,0,0,0,0,0},{0,0,0,0,0,0,0,0,0,0,0},{69,161,65,0,0,0,0,0,0,0,0,0,0,0,0,0,0,0,0,0,0,0,0,0,0,0,0,0,0,0}},
   {9,3,4,3,255,{59,13,37,101,0,0,0,0,0,0,0},{0,0,0,0,0,0,0,0,0,0,0},{135,165,102,0,0,0,0,0,0,0,0,0,0,0,0,0,0,0,0,0,0,0,0,0,0,0,0,0,0,0}},
   {10,4,4,20,255,{7,239,164,104,0,0,0,0,0,0,0},{0,0,0,0,0,0,0,0,0,0,0},{69,165,3,1,0,0,0,0,0,0,0,0,0,0,0,0,0,0,0,0,0,0,0,0,0,0,0,0,0,0}},
   {11,3,5,255,255,{62,117,253,189,246,0,0,0,0,0,0},{0,0,0,0,126,0,0,0,0,0,0},{67,165,102,0,0,0,0,0,0,0,0,0,0,0,0,0,0,0,0,0,0,0,0,0,0,0,0,0,0,0}},
   {12,3,6,255,255,{66,54,150,110,212,195,0,0,0,0,0},{0,0,0,0,0,0,0,0,0,0,0},{160,170,102,0,0,0,0,0,0,0,0,0,0,0,0,0,0,0,0,0,0,0,0,0,0,0,0,0,0,0}},
   {13,3,7,255,255,{56,5,118,99,217,133,198,0,0,0,0},{0,0,0,0,0,0,0,0,0,0,0},{136,161,65,0,0,0,0,0,0,0,0,0,0,0,0,0,0,0,0,0,0,0,0,0,0,0,0,0,0,0}},
   {14,3,6,255,255,{29,82,151,20,226,199,0,0,0,0,0},{0,0,0,0,0,255,0,0,0,0,0},{136,161,6,0,0,0,0,0,0,0,0,0,0,0,0,0,0,0,0,0,0,0,0,0,0,0,0,0,0,0}},
   {15,3,6,255,255,{67,4,114,103,230,197,0,0,0,0,0},{0,0,0,0,0,0,0,0,0,0,0},{135,36,6,0,0,0,0,0,0,0,0,0,0,0,0,0,0,0,0,0,0,0,0,0,0,0,0,0,0,0}},
   {8,3,6,47,255,{58,28,34,125,252,207,0,0,0,0,0},{0,0,0,0,31,128,0,0,0,0,0},{70,165,34,0,0,0,0,0,0,0,0,0,0,0,0,0,0,0,0,0,0,0,0,0,0,0,0,0,0,0}},
   {9,4,6,255,255,{87,75,235,140,180,244,0,0,0,0,0},{0,0,0,0,0,0,0,0,0,0,0},{160,170,107,99,0,0,0,0,0,0,0,0,0,0,0,0,0,0,0,0,0,0,0,0,0,0,0,0,0,0}},
   {10,3,8,30,255,{60,26,11,124,162,220,153,155,0,0,0},{0,0,0,0,0,0,0,8,0,0,0},{160,170,0,0,0,0,0,0,0,0,0,0,0,0,0,0,0,0,0,0,0,0,0,0,0,0,0,0,0,0}},
   {11,3,6,255,255,{63,77,33,21,229,196,0,0,0,0,0},{160,0,0,0,0,31,0,0,0,0,0},{160,170,107,0,0,0,0,0,0,0,0,0,0,0,0,0,0,0,0,0,0,0,0,0,0,0,0,0,0,0}},
   {12,3,5,16,255,{30,49,233,149,94,0,0,0,0,0,0},{0,0,0,0,126,0,0,0,0,0,0},{100,5,107,0,0,0,0,0,0,0,0,0,0,0,0,0,0,0,0,0,0,0,0,0,0,0,0,0,0,0}},
   {13,3,4,11,255,{61,52,237,100,0,0,0,0,0,0,0},{0,0,0,3,0,0,0,0,0,0,0},{64,165,6,0,0,0,0,0,0,0,0,0,0,0,0,0,0,0,0,0,0,0,0,0,0,0,0,0,0,0}},
   {14,3,5,22,255,{65,6,116,102,138,0,0,0,0,0,0},{0,0,0,0,0,0,0,0,0,0,0},{69,165,34,0,0,0,0,0,0,0,0,0,0,0,0,0,0,0,0,0,0,0,0,0,0,0,0,0,0,0}},
   {15,3,7,255,255,{71,10,148,17,163,159,194,0,0,0,0},{224,0,0,0,0,128,0,0,0,0,0},{136,41,65,0,0,0,0,0,0,0,0,0,0,0,0,0,0,0,0,0,0,0,0,0,0,0,0,0,0,0}},
   {8,3,5,7,255,{47,9,76,249,166,0,0,0,0,0,0},{64,0,0,0,127,0,0,0,0,0,0},{160,170,102,0,0,0,0,0,0,0,0,0,0,0,0,0,0,0,0,0,0,0,0,0,0,0,0,0,0,0}},
   {9,4,4,17,255,{42,53,238,93,0,0,0,0,0,0,0},{0,0,0,0,0,0,0,0,0,0,0},{100,3,6,103,0,0,0,0,0,0,0,0,0,0,0,0,0,0,0,0,0,0,0,0,0,0,0,0,0,0}},
   {10,3,4,1,255,{57,55,115,143,0,0,0,0,0,0,0},{0,0,0,0,0,0,0,0,0,0,0},{100,98,10,0,0,0,0,0,0,0,0,0,0,0,0,0,0,0,0,0,0,0,0,0,0,0,0,0,0,0}},
   {11,3,3,0,255,{31,39,191,0,0,0,0,0,0,0,0},{30,128,0,0,0,0,0,0,0,0,0},{100,5,10,0,0,0,0,0,0,0,0,0,0,0,0,0,0,0,0,0,0,0,0,0,0,0,0,0,0,0}},
   {12,4,6,23,255,{48,44,81,36,146,142,0,0,0,0,0},{0,0,0,0,0,112,0,0,0,0,0},{105,3,10,99,0,0,0,0,0,0,0,0,0,0,0,0,0,0,0,0,0,0,0,0,0,0,0,0,0,0}},
   {13,3,6,46,255,{69,2,73,147,167,214,0,0,0,0,0},{0,0,0,0,0,64,0,0,0,0,0},{160,170,34,0,0,0,0,0,0,0,0,0,0,0,0,0,0,0,0,0,0,0,0,0,0,0,0,0,0,0}},
   {14,4,8,255,255,{40,45,12,254,132,225,243,193,0,0,0},{0,0,0,0,0,0,0,0,0,0,0},{160,170,102,78,0,0,0,0,0,0,0,0,0,0,0,0,0,0,0,0,0,0,0,0,0,0,0,0,0,0}},
   {15,3,4,4,255,{64,46,78,111,0,0,0,0,0,0,0},{0,0,0,0,0,0,0,0,0,0,0},{64,161,34,0,0,0,0,0,0,0,0,0,0,0,0,0,0,0,0,0,0,0,0,0,0,0,0,0,0,0}},
   {6,2,7,26,255,{41,15,145,35,137,222,156,0,0,0,0},{0,0,0,0,0,0,0,0,0,0,0},{99,37,0,0,0,0,0,0,0,0,0,0,0,0,0,0,0,0,0,0,0,0,0,0,0,0,0,0,0,0}},
   {7,5,7,42,255,{24,43,51,255,190,211,152,0,0,0,0},{0,0,0,0,3,0,0,0,0,0,0},{99,40,106,97,105,0,0,0,0,0,0,0,0,0,0,0,0,0,0,0,0,0,0,0,0,0,0,0,0,0}}},
  {7,1,7,1,4,6,5,6,7,7,7,1,7,1,5,5,6,4,5,7,4,4,6,6},
  {{7,8,5,6,3,0,1,10,14,9,15,18,4,12,29,31,2,20,17,13,27,16,22,11,23,28,26,25,19,21,30,24},
   {5,7,8,3,0,6,10,1,9,29,18,14,15,4,31,12,17,2,11,27,13,20,23,26,19,28,16,22,25,30,21,24},
   {7,8,5,3,0,10,6,4,1,14,15,9,18,29,20,31,2,12,11,17,23,13,27,28,16,22,19,25,26,30,21,24},
   {7,8,3,5,0,10,6,1,9,14,15,18,4,29,12,31,2,11,20,17,13,27,23,28,22,16,26,19,25,30,21,24},
   {7,8,5,3,0,10,6,1,14,4,9,18,15,29,12,31,2,17,20,11,13,23,27,16,22,28,19,26,25,30,21,24},
   {3,7,8,0,5,10,1,6,14,9,4,15,18,29,31,12,2,11,17,20,13,27,23,16,28,22,19,26,25,30,21,24},
   {3,7,8,5,0,10,6,1,14,9,4,15,18,29,31,12,2,11,20,17,13,27,23,16,28,26,19,22,25,30,21,24},
   {3,5,7,8,0,10,1,6,14,9,4,15,18,29,31,12,2,17,13,11,20,27,23,16,28,22,26,25,19,30,21,24}},
  {{5,4,4,4,3,3,4,4},{6,7,7,7,7,7,7,7},{5,5,0,6,0,7,7,5},{4,3,3,2,2,0,1,1},
   {10,9,8,10,9,10,10,10},{0,0,2,3,4,4,3,0},{3,6,6,6,6,6,6,6},{2,2,0,1,0,1,0,2},
   {1,1,1,0,1,2,2,3},{9,8,11,9,10,9,9,9},{7,5,5,5,5,5,5,5},{7,6,7,0,10,8,8,9},
   {15,0,4,4,6,3,4,7},{6,11,11,9,11,4,0,0},{8,11,9,8,8,8,8,8},{13,13,10,11,4,11,11,11},
   {2,12,8,11,9,6,6,7},{0,4,9,8,7,0,1,8},{12,12,12,12,11,4,0,0},{11,9,4,6,11,5,5,4},
   {3,1,6,7,8,9,9,1},{5,11,2,3,9,6,6,5},{4,2,1,1,0,3,7,8},{8,8,2,3,4,11,11,6},
   {6,7,9,8,1,10,11,1},{12,5,11,9,3,4,0,6},{10,13,0,4,6,7,10,0},{1,7,12,12,3,5,5,4},
   {9,10,10,10,1,10,4,5},{11,10,2,3,3,5,5,4},{0,4,12,12,4,11,4,7},{14,14,5,5,5,6,6,6}},
  {{255,255,255,255,255,255,255,255},{255,255,255,255,255,255,255,255},{0,10,7,6,7,1,1,10},{255,255,255,255,255,255,255,255},
   {255,255,255,255,255,255,255,255},{255,255,255,255,255,255,255,255},{255,255,255,255,255,255,255,255},{255,255,255,255,255,255,255,255},
   {255,255,255,255,255,255,255,255},{255,255,255,255,255,255,255,255},{255,255,255,255,255,255,255,255},{10,6,1,8,9,14,14,9},
   {255,5,0,0,6,0,0,1},{1,14,9,9,18,18,18,18},{255,255,255,255,255,255,255,255},{255,255,255,255,5,255,255,255},
   {7,18,4,15,4,31,31,12},{5,0,14,14,1,3,3,14},{255,255,255,255,255,5,7,5},{29,4,12,2,13,27,27,27},
   {6,8,6,1,14,9,9,3},{2,13,23,23,16,16,16,28},{3,7,8,7,2,12,2,17},{14,9,29,29,15,15,15,31},
   {13,27,17,17,28,28,23,20},{18,2,13,13,27,13,13,23},{4,15,2,12,12,2,4,13},{8,1,18,18,29,29,29,29},
   {9,29,15,4,8,4,12,2},{255,255,5,5,0,10,10,0},{17,17,27,27,23,23,28,16},{255,255,10,10,10,6,6,6}}};

typedef CUresult (*EncodeFn)(CUtensorMap*, CUtensorMapDataType, cuuint32_t, void*, const cuuint64_t*, const cuuint64_t*, const cuuint32_t*,
                             const cuuint32_t*, CUtensorMapInterleave, CUtensorMapSwizzle, CUtensorMapL2promotion, CUtensorMapFloatOOBfill);

void make_map2(EncodeFn enc, CUtensorMap* m, const void* ptr, int rows, int cols, int box_rows) {
  cuuint64_t dim[2] = {(cuuint64_t)cols, (cuuint64_t)rows}, str[1] = {(cuuint64_t)cols * 2};
  cuuint32_t box[2] = {64, (cuuint32_t)box_rows}, es[2] = {1, 1};
  enc(m, CU_TENSOR_MAP_DATA_TYPE_BFLOAT16, 2, const_cast<void*>(ptr), dim, str, box, es, CU_TENSOR_MAP_INTERLEAVE_NONE, CU_TENSOR_MAP_SWIZZLE_128B,
      CU_TENSOR_MAP_L2_PROMOTION_L2_128B, CU_TENSOR_MAP_FLOAT_OOB_FILL_NONE);
}
void make_map3(EncodeFn enc, CUtensorMap* m, const void* ptr, int rows) {
  cuuint64_t dim[3] = {64, (cuuint64_t)rows, 9}, str[2] = {DM * 2, 128};
  cuuint32_t box[3] = {64, 32, 3}, es[3] = {1, 1, 1};
  enc(m, CU_TENSOR_MAP_DATA_TYPE_BFLOAT16, 3, const_cast<void*>(ptr), dim, str, box, es, CU_TENSOR_MAP_INTERLEAVE_NONE, CU_TENSOR_MAP_SWIZZLE_128B,
      CU_TENSOR_MAP_L2_PROMOTION_L2_128B, CU_TENSOR_MAP_FLOAT_OOB_FILL_NONE);
}

void make_map_t(EncodeFn enc, CUtensorMap* m, void* ptr, int width, int cols) {
  cuuint64_t dim[3] = {TP / 2, 2, 864}, str[2] = {TP * 2, TP * 4};
  cuuint32_t box[3] = {(cuuint32_t)width, 2, (cuuint32_t)cols}, es[3] = {1, 1, 1};
  enc(m, CU_TENSOR_MAP_DATA_TYPE_UINT32, 3, ptr, dim, str, box, es, CU_TENSOR_MAP_INTERLEAVE_NONE, cols == 64 ? CU_TENSOR_MAP_SWIZZLE_128B : CU_TENSOR_MAP_SWIZZLE_NONE,
      CU_TENSOR_MAP_L2_PROMOTION_NONE, CU_TENSOR_MAP_FLOAT_OOB_FILL_NONE);
}

int g_mode = -1;

}

extern "C" void kernel_launch(void* const* d_in, const int* in_sizes, int n_in, void* d_out, int out_size) {
  static EncodeFn enc = nullptr;
  static void* t_ptr = nullptr;
  if (!enc) {
    void* fn = nullptr;
    cudaDriverEntryPointQueryResult st;
    cudaGetDriverEntryPoint("cuTensorMapEncodeTiled", &fn, cudaEnableDefault, &st);
    enc = (EncodeFn)fn;
    cudaGetSymbolAddress(&t_ptr, g_T);
    cudaFuncSetAttribute(fused_kernel, cudaFuncAttributeMaxDynamicSharedMemorySize, SMEM_BYTES);
    if (g_mode < 0) {
      cudaLaunchConfig_t cfg = {};
      cfg.gridDim = dim3(2 * NCL); cfg.blockDim = dim3(384); cfg.dynamicSmemBytes = SMEM_BYTES;
      cudaLaunchAttribute at; at.id = cudaLaunchAttributeClusterDimension;
      at.val.clusterDim.x = 2; at.val.clusterDim.y = 1; at.val.clusterDim.z = 1;
      cfg.attrs = &at; cfg.numAttrs = 1;
      int nc = 0;
      g_mode = (cudaOccupancyMaxActiveClusters(&nc, fused_kernel, &cfg) == cudaSuccess && nc >= NCL) ? 1 : 0;
      (void)cudaGetLastError();
    }
  }
  Params p;
  make_map2(enc, &p.map_a[0], d_in[4], SEQ, DC, 128);
  make_map2(enc, &p.map_a[1], d_in[0], SEQ, DM, 128);
  make_map2(enc, &p.map_w[0], d_in[6], DC, 4096, 64);
  make_map2(enc, &p.map_w[1], d_in[7], DC, 4096, 64);
  make_map2(enc, &p.map_w[2], d_in[5], DM, 4096, 64);
  make_map2(enc, &p.map_w[3], d_in[1], DM, 1728, 64);
  make_map3(enc, &p.map_o[0], d_in[8], 4096);
  make_map3(enc, &p.map_o[1], d_in[2], DM);
  make_map_t(enc, &p.map_t[0], t_ptr, 32, 9);
  make_map_t(enc, &p.map_t[1], t_ptr, 40, 9);
  make_map_t(enc, &p.map_t[2], t_ptr, 32, 64);
  p.x = (const __nv_bfloat16*)d_in[0];
  p.gate_w = (const __nv_bfloat16*)d_in[9];
  make_map2(enc, &p.map_out, d_out, SEQ, DM, 64);
  p.out = (__nv_bfloat16*)d_out;
  p.zero = 0;
  auto launch = [&](int phases) {
    p.s = k_sched;
    for (int i = 0; i < NCL; i++) {
      Rec& r = p.s.r[i];
      if (!(phases & 1)) r.n1 = 0;
      if (!(phases & 2)) r.n2 = 0;
      if (!(phases & (r.p3 < 24 ? 4 : 32))) r.p3 = 255;
      if (!(phases & 8)) r.bg = 255;
      const int u1 = r.n1 ? 8 + r.n1 * (8 + (r.slab >> 3)) : 0;
      int u2 = 0;
      for (int k = 0; k < r.n2; k++) u2 += 4 * (r.item[k] & 7) + 4;
      r.u1 = (uint8_t)u1; r.u2 = (uint8_t)u2;
      r.rot = (uint8_t)(((u1 % 10 + 1) >> 1) % 5);
      r.x3 = (uint8_t)((r.rot + u2) % 5 & 3);
      r.phases = (uint8_t)phases;
    }
    if (!(phases & 16))
      for (int i = 0; i < 256; i++) { p.s.slot[i >> 3][i & 7] = (uint8_t)(i >> 3); p.s.prev[i >> 3][i & 7] = 255; }
    fused_kernel<<<2 * NCL, 384, SMEM_BYTES>>>(p);
  };
  if (g_mode == 1) launch(63);
  else { launch(1); launch(10); launch(32); launch(4); }
}
```

```cpp
#include <cuda_runtime.h>
#include <cuda_bf16.h>
#include <cuda.h>
#include <stdint.h>

namespace {

constexpr int SEQ = 2048, DM = 576, DC = 512, NH = 32;
constexpr int NCL = 66;
constexpr uint32_t DESC_HI = 0x40000040u;

constexpr int SM_RING = 0;
constexpr int SM_BUF = 163840;
constexpr int SM_BAR = 229376;
constexpr int B_P1E = 0, B_P2E = 10, B_P3E = 15, B_P2F = 24, B_SF = 32, B_ORD = 36, B_LAD = 40, B_DONE = 41, B_FIN = 48;
constexpr int B_P3F = 56, B_OUT = 61, B_P1F = 64, B_SE = 74, B_QF = 80, B_LA = 84, B_NUM = 88;
constexpr uint64_t B_CNT = 0x11118245000ull;
constexpr int SMEM_BYTES = SM_BAR + B_NUM * 8 + 1024;

constexpr int F_QKVA = 32;
constexpr int F_GATE = 64;
constexpr int F_DONE = 65;
constexpr int F_CTX = 96;
constexpr int F_OUT = 96 + 8 * 64;
constexpr int F_KV = F_OUT + 64;
constexpr int F_Q = F_KV + 256;
constexpr int F_RD = F_Q + 256;
constexpr int F_NUM = F_RD + 256;

struct Rec {
  uint8_t slab;
  uint8_t n1, n2;
  uint8_t p3;
  uint8_t bg;
  uint8_t item[11];
  uint8_t last[11];
  uint8_t tile[32];
  uint8_t u1, u2;
  uint8_t rot, x3;
  uint8_t phases;
};
struct Sched {
  Rec r[NCL];
  uint8_t task[NCL][4];
  uint8_t p3_order[8][32];
  uint8_t slot[32][8];
  uint8_t prev[32][8];
};

#define SCHED_DECL static const

struct Params {
  CUtensorMap map_a[2];
  CUtensorMap map_w[4];
  CUtensorMap map_o[2];
  CUtensorMap map_t[3];
  CUtensorMap map_out;
  const __nv_bfloat16* x;
  const __nv_bfloat16* gate_w;
  __nv_bfloat16* out;
  int zero;
  alignas(64) Sched s;
};

__device__ __align__(1024) uint8_t g_Q[NH * 32 * 16384];
__device__ __align__(1024) uint8_t g_KV[2 * NH * 16 * 32768];
__device__ __align__(1024) uint8_t g_oA[32 * 576 * 128];
constexpr int TP = SEQ + 16;
__device__ __align__(1024) uint32_t g_T[864 * TP];
__device__ float g_gate[SEQ];
__device__ int g_flags[F_NUM];

__device__ __forceinline__ void mbar_arrive(uint32_t b) { asm volatile("mbarrier.arrive.shared::cta.b64 _, [%0];" ::"r"(b) : "memory"); }
__device__ __forceinline__ void mbar_arrive_cl(uint32_t b, int cnt) {
  asm volatile("mbarrier.arrive.shared::cluster.b64 _, [%0], %1;" ::"r"(b), "r"(cnt) : "memory");
}
__device__ __forceinline__ void mbar_wait(uint32_t b, int par) {
  asm volatile(
      "{\n.reg .pred p;\n.reg .u32 c;\n"
      "mbarrier.try_wait.parity.shared::cta.b64 p, [%0], %1;\n@p bra DN;\nmov.u32 c, 0;\n"
      "LP:\nmbarrier.try_wait.parity.shared::cta.b64 p, [%0], %1;\n@p bra DN;\n"
      "add.u32 c, c, 1;\nsetp.lt.u32 p, c, 4000000;\n@p bra LP;\ntrap;\nDN:\n}" ::"r"(b), "r"(par) : "memory");
}
__device__ __forceinline__ uint32_t mapa(uint32_t a, uint32_t cta) {
  uint32_t r; asm("mapa.shared::cluster.u32 %0, %1, %2;" : "=r"(r) : "r"(a), "r"(cta)); return r;
}
#define ELECT(ins) "{\n.reg .pred e;\nelect.sync _|e, 0xffffffff;\n@e " ins "\n}"
__device__ __forceinline__ void mbar_expect(uint32_t b, int bytes) {
  asm volatile(ELECT("mbarrier.arrive.expect_tx.shared::cta.b64 _, [%0], %1;") ::"r"(b), "r"(bytes) : "memory");
}
__device__ __forceinline__ void mbar_arrive_one(uint32_t b) { asm volatile(ELECT("mbarrier.arrive.shared::cta.b64 _, [%0];") ::"r"(b) : "memory"); }
constexpr uint64_t L2_NORMAL = 0x1000000000000000ull, L2_FIRST = 0x12F0000000000000ull;
__device__ __forceinline__ void bulk_load(uint32_t dst, const void* src, int bytes, uint32_t bar, uint64_t pol = L2_NORMAL) {
  asm volatile(ELECT("cp.async.bulk.shared::cluster.global.mbarrier::complete_tx::bytes.L2::cache_hint [%0], [%1], %2, [%3], %4;") ::"r"(dst), "l"(src), "r"(bytes), "r"(bar), "l"(pol) : "memory");
}
__device__ __forceinline__ void bulk_load_mc(uint32_t dst, const void* src, int bytes, uint32_t bar, uint64_t pol = L2_NORMAL) {
  asm volatile(ELECT("cp.async.bulk.shared::cluster.global.mbarrier::complete_tx::bytes.multicast::cluster.L2::cache_hint [%0], [%1], %2, [%3], %4, %5;") ::"r"(dst), "l"(src), "r"(bytes), "r"(bar), "h"((uint16_t)3), "l"(pol) : "memory");
}
__device__ __forceinline__ void bulk_store(void* dst, uint32_t src, int bytes, uint64_t pol = L2_NORMAL) {
  asm volatile(ELECT("cp.async.bulk.global.shared::cta.bulk_group.L2::cache_hint [%0], [%1], %2, %3;") ::"l"(dst), "r"(src), "r"(bytes), "l"(pol) : "memory");
}
__device__ __forceinline__ void tma2d(uint32_t dst, const CUtensorMap* m, int c0, int c1, uint32_t bar, uint64_t pol = L2_NORMAL) {
  asm volatile(ELECT("cp.async.bulk.tensor.2d.shared::cluster.global.mbarrier::complete_tx::bytes.L2::cache_hint [%0], [%1, {%3, %4}], [%2], %5;") ::"r"(dst), "l"(m), "r"(bar), "r"(c0), "r"(c1), "l"(pol) : "memory");
}
__device__ __forceinline__ void tma2d_mc(uint32_t dst, const CUtensorMap* m, int c0, int c1, uint32_t bar, uint64_t pol = L2_NORMAL) {
  asm volatile(ELECT("cp.async.bulk.tensor.2d.shared::cluster.global.mbarrier::complete_tx::bytes.multicast::cluster.L2::cache_hint [%0], [%1, {%3, %4}], [%2], %5, %6;") ::"r"(dst), "l"(m), "r"(bar), "r"(c0), "r"(c1), "h"((uint16_t)3), "l"(pol) : "memory");
}
__device__ __forceinline__ void tma3d(uint32_t dst, const CUtensorMap* m, int c0, int c1, int c2, uint32_t bar, uint64_t pol = L2_NORMAL) {
  asm volatile(ELECT("cp.async.bulk.tensor.3d.shared::cluster.global.mbarrier::complete_tx::bytes.L2::cache_hint [%0], [%1, {%3, %4, %5}], [%2], %6;") ::"r"(dst), "l"(m), "r"(bar), "r"(c0), "r"(c1), "r"(c2), "l"(pol) : "memory");
}
__device__ __forceinline__ void tma3d_mc(uint32_t dst, const CUtensorMap* m, int c0, int c1, int c2, uint32_t bar, uint64_t pol = L2_NORMAL) {
  asm volatile(ELECT("cp.async.bulk.tensor.3d.shared::cluster.global.mbarrier::complete_tx::bytes.multicast::cluster.L2::cache_hint [%0], [%1, {%3, %4, %5}], [%2], %6, %7;") ::"r"(dst), "l"(m), "r"(bar), "r"(c0), "r"(c1), "r"(c2), "h"((uint16_t)3), "l"(pol) : "memory");
}
__device__ __forceinline__ void tma2d_add(const CUtensorMap* m, uint32_t src, int c0, int c1) {
  asm volatile(ELECT("cp.reduce.async.bulk.tensor.2d.global.shared::cta.add.bulk_group [%0, {%2, %3}], [%1];") ::"l"(m), "r"(src), "r"(c0), "r"(c1) : "memory");
}
__device__ __forceinline__ void tma3d_store(const CUtensorMap* m, uint32_t src, int c0, int c1, int c2, uint64_t pol = L2_NORMAL) {
  asm volatile(ELECT("cp.async.bulk.tensor.3d.global.shared::cta.bulk_group.L2::cache_hint [%0, {%2, %3, %4}], [%1], %5;") ::"l"(m), "r"(src), "r"(c0), "r"(c1), "r"(c2), "l"(pol) : "memory");
}
__device__ __forceinline__ void tma2d_prefetch(const CUtensorMap* m, int c0, int c1, uint64_t pol = L2_NORMAL) {
  asm volatile(ELECT("cp.async.bulk.prefetch.tensor.2d.L2.global.L2::cache_hint [%0, {%1, %2}], %3;") ::"l"(m), "r"(c0), "r"(c1), "l"(pol) : "memory");
}
#define LAG 3
#define HINT 62
#define POL(bit) ((HINT >> (bit)) & 1 ? L2_FIRST : L2_NORMAL)
#define BULK_COMMIT() asm volatile("cp.async.bulk.commit_group;" ::: "memory")
#define BULK_WAIT(n) asm volatile("cp.async.bulk.wait_group %0;" ::"n"(n) : "memory")
#define BULK_WAIT_READ(n) asm volatile("cp.async.bulk.wait_group.read %0;" ::"n"(n) : "memory")
#define FENCE_ASYNC_SMEM() asm volatile("fence.proxy.async.shared::cta;" ::: "memory")
#define FENCE_ASYNC_ALL() asm volatile("fence.proxy.async;" ::: "memory")
#define WG_FENCE() asm volatile("wgmma.fence.sync.aligned;" ::: "memory")
#define WG_COMMIT() asm volatile("wgmma.commit_group.sync.aligned;" ::: "memory")
#define WG_WAIT(n) asm volatile("wgmma.wait_group.sync.aligned %0;" ::"n"(n) : "memory")
__device__ __forceinline__ void bar_sync(int id, int n) { asm volatile("bar.sync %0, %1;" ::"r"(id), "r"(n) : "memory"); }
__device__ __forceinline__ void bar_arrive(int id, int n) { asm volatile("bar.arrive %0, %1;" ::"r"(id), "r"(n) : "memory"); }
__device__ __forceinline__ void cluster_sync() {
  asm volatile("barrier.cluster.arrive.relaxed;\nbarrier.cluster.wait.acquire;" ::: "memory");
}
template <int N> __device__ __forceinline__ void pin(float (&r)[N]) {
#pragma unroll
  for (int i = 0; i < N; i++) asm volatile("" : "+f"(r[i])::"memory");
}
template <int N> __device__ __forceinline__ void pin(uint32_t (&r)[N]) {
#pragma unroll
  for (int i = 0; i < N; i++) asm volatile("" : "+r"(r[i])::"memory");
}
__device__ __forceinline__ uint32_t pack_bf16(float lo, float hi) {
  uint32_t r; asm("cvt.rn.bf16x2.f32 %0, %1, %2;" : "=r"(r) : "f"(hi), "f"(lo)); return r;
}
__device__ __forceinline__ float ex2(float x) { float r; asm("ex2.approx.ftz.f32 %0, %1;" : "=f"(r) : "f"(x)); return r; }
__device__ __forceinline__ void ldsm4(uint32_t a, uint32_t& r0, uint32_t& r1, uint32_t& r2, uint32_t& r3) {
  asm volatile("ldmatrix.sync.aligned.m8n8.x4.shared.b16 {%0,%1,%2,%3}, [%4];" : "=r"(r0), "=r"(r1), "=r"(r2), "=r"(r3) : "r"(a) : "memory");
}
__device__ __forceinline__ void stsm4(uint32_t a, uint32_t r0, uint32_t r1, uint32_t r2, uint32_t r3) {
  asm volatile("stmatrix.sync.aligned.m8n8.x4.shared.b16 [%0], {%1,%2,%3,%4};" ::"r"(a), "r"(r0), "r"(r1), "r"(r2), "r"(r3) : "memory");
}
__device__ __forceinline__ void flag_add(int idx) {
  asm volatile(ELECT("red.release.gpu.global.add.s32 [%0], 1;") ::"l"(g_flags + idx) : "memory");
}
__device__ __forceinline__ void flag_add_rx(int idx) {
  asm volatile(ELECT("red.relaxed.gpu.global.add.s32 [%0], 1;") ::"l"(g_flags + idx) : "memory");
}
template <bool ACQ, int NS = 32> __device__ __forceinline__ void flag_wait(int idx, int target) {
  int n = 0;
  while (true) {
    int v;
    if (ACQ) asm volatile("ld.acquire.gpu.global.s32 %0, [%1];" : "=r"(v) : "l"(g_flags + idx) : "memory");
    else asm volatile("ld.relaxed.gpu.global.s32 %0, [%1];" : "=r"(v) : "l"(g_flags + idx) : "memory");
    if (__all_sync(0xffffffffu, v >= target)) break;
    if (++n > 20000000) __trap();
    __nanosleep(NS);
  }
}
__device__ __forceinline__ void mask_wait(uint32_t& ready, int bit, int idx, int target) {
  for (int n = 0; !((ready >> bit) & 1); n++) {
    int v;
    if (n) { __nanosleep(32); if (n > 20000000) __trap(); }
    asm volatile("ld.relaxed.gpu.global.s32 %0, [%1];" : "=r"(v) : "l"(g_flags + idx) : "memory");
    ready = __ballot_sync(0xffffffffu, v >= target);
  }
}
__device__ __forceinline__ uint32_t desc_lo(uint32_t addr, uint32_t lbo) { return ((addr & 0x3FFFFu) >> 4) | ((lbo >> 4) << 16); }
#define PROF(role, i)
#define PROFX(cond, i)
#define PROFB(i)
#define PROFG(i)

template <int TB, int TA = 0> __device__ __forceinline__ void wgmma_ss64(float (&d)[32], uint32_t alo, uint32_t blo, int sd) {
  asm volatile("{\n.reg .pred p;\n.reg .b64 da, db;\n"
    "setp.ne.b32 p, %34, 0;\nmov.b64 da, {%32, %36};\nmov.b64 db, {%33, %36};\n"
    "wgmma.mma_async.sync.aligned.m64n64k16.f32.bf16.bf16 "
    "{%0,%1,%2,%3,%4,%5,%6,%7,%8,%9,%10,%11,%12,%13,%14,%15,%16,%17,%18,%19,%20,%21,%22,%23,"
    "%24,%25,%26,%27,%28,%29,%30,%31}, "
    "da, db, p, 1, 1, %37, %35;\n}\n"
    : "+f"(d[0]),"+f"(d[1]),"+f"(d[2]),"+f"(d[3]),"+f"(d[4]),"+f"(d[5]),"+f"(d[6]),"+f"(d[7]),"+f"(d[8]),"+f"(d[9]),"+f"(d[10]),"+f"(d[11]),
      "+f"(d[12]),"+f"(d[13]),"+f"(d[14]),"+f"(d[15]),"+f"(d[16]),"+f"(d[17]),"+f"(d[18]),"+f"(d[19]),"+f"(d[20]),"+f"(d[21]),"+f"(d[22]),"+f"(d[23]),
      "+f"(d[24]),"+f"(d[25]),"+f"(d[26]),"+f"(d[27]),"+f"(d[28]),"+f"(d[29]),"+f"(d[30]),"+f"(d[31])
    : "r"(alo), "r"(blo), "r"(sd), "n"(TB), "r"(DESC_HI), "n"(TA));
}
template <int TB, int TA = 0> __device__ __forceinline__ void wgmma_ss128(float (&d)[64], uint32_t alo, uint32_t blo, int sd) {
  asm volatile("{\n.reg .pred p;\n.reg .b64 da, db;\n"
    "setp.ne.b32 p, %66, 0;\nmov.b64 da, {%64, %68};\nmov.b64 db, {%65, %68};\n"
    "wgmma.mma_async.sync.aligned.m64n128k16.f32.bf16.bf16 "
    "{%0,%1,%2,%3,%4,%5,%6,%7,%8,%9,%10,%11,%12,%13,%14,%15,%16,%17,%18,%19,%20,%21,%22,%23,"
    "%24,%25,%26,%27,%28,%29,%30,%31,%32,%33,%34,%35,%36,%37,%38,%39,%40,%41,%42,%43,%44,%45,%46,%47,"
    "%48,%49,%50,%51,%52,%53,%54,%55,%56,%57,%58,%59,%60,%61,%62,%63}, "
    "da, db, p, 1, 1, %69, %67;\n}\n"
    : "+f"(d[0]),"+f"(d[1]),"+f"(d[2]),"+f"(d[3]),"+f"(d[4]),"+f"(d[5]),"+f"(d[6]),"+f"(d[7]),"+f"(d[8]),"+f"(d[9]),"+f"(d[10]),"+f"(d[11]),
      "+f"(d[12]),"+f"(d[13]),"+f"(d[14]),"+f"(d[15]),"+f"(d[16]),"+f"(d[17]),"+f"(d[18]),"+f"(d[19]),"+f"(d[20]),"+f"(d[21]),"+f"(d[22]),"+f"(d[23]),
      "+f"(d[24]),"+f"(d[25]),"+f"(d[26]),"+f"(d[27]),"+f"(d[28]),"+f"(d[29]),"+f"(d[30]),"+f"(d[31]),"+f"(d[32]),"+f"(d[33]),"+f"(d[34]),"+f"(d[35]),
      "+f"(d[36]),"+f"(d[37]),"+f"(d[38]),"+f"(d[39]),"+f"(d[40]),"+f"(d[41]),"+f"(d[42]),"+f"(d[43]),"+f"(d[44]),"+f"(d[45]),"+f"(d[46]),"+f"(d[47]),
      "+f"(d[48]),"+f"(d[49]),"+f"(d[50]),"+f"(d[51]),"+f"(d[52]),"+f"(d[53]),"+f"(d[54]),"+f"(d[55]),"+f"(d[56]),"+f"(d[57]),"+f"(d[58]),"+f"(d[59]),
      "+f"(d[60]),"+f"(d[61]),"+f"(d[62]),"+f"(d[63])
    : "r"(alo), "r"(blo), "r"(sd), "n"(TB), "r"(DESC_HI), "n"(TA));
}
template <int TB> __device__ __forceinline__ void wgmma_rs128(float (&d)[64], uint32_t a0, uint32_t a1, uint32_t a2, uint32_t a3, uint32_t blo, int sd) {
  asm volatile("{\n.reg .pred p;\n.reg .b64 db;\n"
    "setp.ne.b32 p, %69, 0;\nmov.b64 db, {%68, %71};\n"
    "wgmma.mma_async.sync.aligned.m64n128k16.f32.bf16.bf16 "
    "{%0,%1,%2,%3,%4,%5,%6,%7,%8,%9,%10,%11,%12,%13,%14,%15,%16,%17,%18,%19,%20,%21,%22,%23,"
    "%24,%25,%26,%27,%28,%29,%30,%31,%32,%33,%34,%35,%36,%37,%38,%39,%40,%41,%42,%43,%44,%45,%46,%47,"
    "%48,%49,%50,%51,%52,%53,%54,%55,%56,%57,%58,%59,%60,%61,%62,%63}, "
    "{%64,%65,%66,%67}, db, p, 1, 1, %70;\n}\n"
    : "+f"(d[0]),"+f"(d[1]),"+f"(d[2]),"+f"(d[3]),"+f"(d[4]),"+f"(d[5]),"+f"(d[6]),"+f"(d[7]),"+f"(d[8]),"+f"(d[9]),"+f"(d[10]),"+f"(d[11]),
      "+f"(d[12]),"+f"(d[13]),"+f"(d[14]),"+f"(d[15]),"+f"(d[16]),"+f"(d[17]),"+f"(d[18]),"+f"(d[19]),"+f"(d[20]),"+f"(d[21]),"+f"(d[22]),"+f"(d[23]),
      "+f"(d[24]),"+f"(d[25]),"+f"(d[26]),"+f"(d[27]),"+f"(d[28]),"+f"(d[29]),"+f"(d[30]),"+f"(d[31]),"+f"(d[32]),"+f"(d[33]),"+f"(d[34]),"+f"(d[35]),
      "+f"(d[36]),"+f"(d[37]),"+f"(d[38]),"+f"(d[39]),"+f"(d[40]),"+f"(d[41]),"+f"(d[42]),"+f"(d[43]),"+f"(d[44]),"+f"(d[45]),"+f"(d[46]),"+f"(d[47]),
      "+f"(d[48]),"+f"(d[49]),"+f"(d[50]),"+f"(d[51]),"+f"(d[52]),"+f"(d[53]),"+f"(d[54]),"+f"(d[55]),"+f"(d[56]),"+f"(d[57]),"+f"(d[58]),"+f"(d[59]),
      "+f"(d[60]),"+f"(d[61]),"+f"(d[62]),"+f"(d[63])
    : "r"(a0), "r"(a1), "r"(a2), "r"(a3), "r"(blo), "r"(sd), "n"(TB), "r"(DESC_HI));
}
template <int TB, int TA = 0> __device__ __forceinline__ void wgmma_ss192(float (&d)[96], uint32_t alo, uint32_t blo, int sd) {
  asm volatile("{\n.reg .pred p;\n.reg .b64 da, db;\n"
    "setp.ne.b32 p, %98, 0;\nmov.b64 da, {%96, %100};\nmov.b64 db, {%97, %100};\n"
    "wgmma.mma_async.sync.aligned.m64n192k16.f32.bf16.bf16 "
    "{%0,%1,%2,%3,%4,%5,%6,%7,%8,%9,%10,%11,%12,%13,%14,%15,%16,%17,%18,%19,%20,%21,%22,%23,"
    "%24,%25,%26,%27,%28,%29,%30,%31,%32,%33,%34,%35,%36,%37,%38,%39,%40,%41,%42,%43,%44,%45,%46,%47,"
    "%48,%49,%50,%51,%52,%53,%54,%55,%56,%57,%58,%59,%60,%61,%62,%63,%64,%65,%66,%67,%68,%69,%70,%71,"
    "%72,%73,%74,%75,%76,%77,%78,%79,%80,%81,%82,%83,%84,%85,%86,%87,%88,%89,%90,%91,%92,%93,%94,%95}, "
    "da, db, p, 1, 1, %101, %99;\n}\n"
    : "+f"(d[0]),"+f"(d[1]),"+f"(d[2]),"+f"(d[3]),"+f"(d[4]),"+f"(d[5]),"+f"(d[6]),"+f"(d[7]),"+f"(d[8]),"+f"(d[9]),"+f"(d[10]),"+f"(d[11]),
      "+f"(d[12]),"+f"(d[13]),"+f"(d[14]),"+f"(d[15]),"+f"(d[16]),"+f"(d[17]),"+f"(d[18]),"+f"(d[19]),"+f"(d[20]),"+f"(d[21]),"+f"(d[22]),"+f"(d[23]),
      "+f"(d[24]),"+f"(d[25]),"+f"(d[26]),"+f"(d[27]),"+f"(d[28]),"+f"(d[29]),"+f"(d[30]),"+f"(d[31]),"+f"(d[32]),"+f"(d[33]),"+f"(d[34]),"+f"(d[35]),
      "+f"(d[36]),"+f"(d[37]),"+f"(d[38]),"+f"(d[39]),"+f"(d[40]),"+f"(d[41]),"+f"(d[42]),"+f"(d[43]),"+f"(d[44]),"+f"(d[45]),"+f"(d[46]),"+f"(d[47]),
      "+f"(d[48]),"+f"(d[49]),"+f"(d[50]),"+f"(d[51]),"+f"(d[52]),"+f"(d[53]),"+f"(d[54]),"+f"(d[55]),"+f"(d[56]),"+f"(d[57]),"+f"(d[58]),"+f"(d[59]),
      "+f"(d[60]),"+f"(d[61]),"+f"(d[62]),"+f"(d[63]),"+f"(d[64]),"+f"(d[65]),"+f"(d[66]),"+f"(d[67]),"+f"(d[68]),"+f"(d[69]),"+f"(d[70]),"+f"(d[71]),
      "+f"(d[72]),"+f"(d[73]),"+f"(d[74]),"+f"(d[75]),"+f"(d[76]),"+f"(d[77]),"+f"(d[78]),"+f"(d[79]),"+f"(d[80]),"+f"(d[81]),"+f"(d[82]),"+f"(d[83]),
      "+f"(d[84]),"+f"(d[85]),"+f"(d[86]),"+f"(d[87]),"+f"(d[88]),"+f"(d[89]),"+f"(d[90]),"+f"(d[91]),"+f"(d[92]),"+f"(d[93]),"+f"(d[94]),"+f"(d[95])
    : "r"(alo), "r"(blo), "r"(sd), "n"(TB), "r"(DESC_HI), "n"(TA));
}

struct Ctx {
  uint32_t sm;
  uint32_t bar;
  uint32_t rbar;
  int cl, rank, wg, warp, lane, phases;
};
__device__ __forceinline__ void release(const Ctx& c, int b, int cnt = 1) {
  if (c.lane < 2) mbar_arrive_cl(c.rbar + b * 8, cnt);
}
#define HK 5
#define NPRO 6
#define PFM 7
#define PF1 1
constexpr float SM_SCALE = 0.08838834764831845f * 1.4426950408889634f;
constexpr float SM_HI = 1.8446744e19f, SM_LO = 5.4210109e-20f;
constexpr int ORDER = 1;

__device__ __forceinline__ void stage_tile(const float (&a)[64], uint32_t buf, const Ctx& c, float s0, float s1) {
  const int row = (c.lane & 7) + ((c.lane >> 3) & 1) * 8;
  const uint32_t base = buf + (c.warp * 16 + row) * 128 + (((c.lane >> 4) ^ (row & 7)) << 4);
#pragma unroll
  for (int i = 0; i < 8; i++)
    stsm4((base ^ ((i & 3) << 5)) + (i >> 2) * 8192, pack_bf16(a[8 * i] * s0, a[8 * i + 1] * s0), pack_bf16(a[8 * i + 2] * s1, a[8 * i + 3] * s1),
          pack_bf16(a[8 * i + 4] * s0, a[8 * i + 5] * s0), pack_bf16(a[8 * i + 6] * s1, a[8 * i + 7] * s1));
}

__device__ __forceinline__ void p1_epilogue(const Params& p, const Ctx& c, const float (&acc)[64], int t, int type) {
  const int tile = p.s.r[c.cl].tile[t] & 63, b = c.wg * 2 + 1;
  mbar_wait(c.bar + (B_SE + b) * 8, (t & 1) ^ 1);
  if (type && tile >= 32) {
    const int r = 2 * (c.lane & 3) + ((c.lane >> 2) & 1);
    const uint32_t dst = c.sm + SM_BUF + b * 16384 + r * 128 + (((c.warp * 2) ^ r) << 4) + (c.lane >> 3) * 4;
#pragma unroll
    for (int i = 0; i < 16; i++) {
      asm volatile("st.shared.u32 [%0], %1;" ::"r"(dst + i * 1024), "r"(pack_bf16(acc[4 * i], acc[4 * i + 1])) : "memory");
      asm volatile("st.shared.u32 [%0], %1;" ::"r"((dst ^ 16) + i * 1024), "r"(pack_bf16(acc[4 * i + 2], acc[4 * i + 3])) : "memory");
    }
  } else {
    if (type) stage_tile(acc, c.sm + SM_BUF + b * 16384, c, SM_SCALE, SM_SCALE);
    else stage_tile(acc, c.sm + SM_BUF + b * 16384, c, 1.f, 1.f);
  }
  FENCE_ASYNC_SMEM();
  __syncwarp();
  if (c.lane == 0) mbar_arrive(c.bar + (B_SF + b) * 8);
}

__device__ __forceinline__ void p1_consumer(const Params& p, const Ctx& c) {
  const int n = p.s.r[c.cl].n1;
  const int type = p.s.r[c.cl].slab >> 3;
  const uint32_t bdesc = desc_lo(c.sm + SM_RING, 8192), adesc = desc_lo(c.sm + SM_BUF + 32768 + c.wg * 8192, 16);
  uint32_t A[128];
  float acc[64] = {};
  int slot = 0, par = 0;
  auto next = [&]() { if (++slot == 10) { slot = 0; par ^= 1; } };
  {
    const int row = (c.lane & 7) + ((c.lane >> 3) & 1) * 8;
    const uint32_t base = c.sm + SM_RING + (c.wg * 64 + c.warp * 16 + row) * 128 + (((c.lane >> 4) ^ (row & 7)) << 4);
    if (c.wg == 1) bar_sync(ORDER + 1, 256);
    int pa = -1, pb = -1;
    if (type) {
      mbar_wait(c.bar + B_P1F * 8, 0);
      WG_FENCE();
#pragma unroll
      for (int kk = 0; kk < 4; kk++) wgmma_ss128<1>(acc, adesc + kk * 2, bdesc + kk * 128, kk != 0);
      WG_COMMIT();
      pb = 0; slot = 1;
    }
#pragma unroll
    for (int kb = 0; kb < 8; kb++) {
      const int sa = slot;
      mbar_wait(c.bar + (B_P1F + slot) * 8, par);
      if (kb == 0) PROF(c.wg, 5);
      next();
      mbar_wait(c.bar + (B_P1F + slot) * 8, par);
      PROF(c.wg, 6 + 2 * kb);
      WG_FENCE();
#pragma unroll
      for (int kk = 0; kk < 4; kk++)
        wgmma_ss128<1>(acc, desc_lo(c.sm + SM_RING + c.wg * 8192, 16) + sa * 1024 + kk * 2, bdesc + slot * 1024 + kk * 128, (kb | kk) != 0 ? 1 : type);
      WG_COMMIT();
      if (kb == 1 && c.wg == 0) bar_arrive(ORDER + 1, 256);
#pragma unroll
      for (int kk = 0; kk < 4; kk++) ldsm4((base ^ (kk << 5)) + sa * 16384, A[kb * 16 + kk * 4], A[kb * 16 + kk * 4 + 1], A[kb * 16 + kk * 4 + 2], A[kb * 16 + kk * 4 + 3]);
      WG_WAIT(1);
      if (kb > 0) release(c, B_P1E + pa);
      if (kb > 0 || pb >= 0) release(c, B_P1E + pb);
      pa = sa; pb = slot;
      next();
    }
    WG_WAIT(0);
    __syncwarp();
    release(c, B_P1E + pa);
    release(c, B_P1E + pb);
    pin(acc);
    PROF(c.wg, 1);
    p1_epilogue(p, c, acc, 0, type);
    PROF(c.wg, 2);
  }
  for (int t = 1; t < n; t++) {
    bar_sync(ORDER + c.wg, 256);
    int prev1 = -1, prev2 = -1;
    if (type) {
      mbar_wait(c.bar + (B_P1F + slot) * 8, par);
      WG_FENCE();
#pragma unroll
      for (int kk = 0; kk < 4; kk++) wgmma_ss128<1>(acc, adesc + kk * 2, bdesc + slot * 1024 + kk * 128, kk != 0);
      WG_COMMIT();
      prev1 = slot;
      next();
    }
#pragma unroll
    for (int kb = 0; kb < 8; kb++) {
      mbar_wait(c.bar + (B_P1F + slot) * 8, par);
      WG_FENCE();
      const uint32_t d = bdesc + slot * 1024;
#pragma unroll
      for (int kk = 0; kk < 4; kk++)
        wgmma_rs128<1>(acc, A[kb * 16 + kk * 4], A[kb * 16 + kk * 4 + 1], A[kb * 16 + kk * 4 + 2], A[kb * 16 + kk * 4 + 3], d + kk * 128, (kb | kk) != 0 ? 1 : type);
      WG_COMMIT();
      if (kb == HK) {
        if (t + 1 < n || c.wg == 0) bar_arrive(ORDER + (c.wg ^ 1), 256);
      }
      if (kb > 0) { WG_WAIT(2); if (kb > 1 || prev2 >= 0) release(c, B_P1E + prev2); }
      prev2 = prev1; prev1 = slot;
      next();
    }
    WG_WAIT(1);
    release(c, B_P1E + prev2);
    WG_WAIT(0);
    pin(acc);
    release(c, B_P1E + prev1);
    p1_epilogue(p, c, acc, t, type);
    PROF(c.wg, 3);
  }
}

__device__ __forceinline__ void p1_producer(const Params& p, const Ctx& c) {
  const int n = p.s.r[c.cl].n1;
  const int type = p.s.r[c.cl].slab >> 3, grp = p.s.r[c.cl].slab & 7;
  int slot = NPRO % 10, par = NPRO < 10;
#pragma unroll 1
  for (int t = 0; t < n; t++) {
    const int tile = p.s.r[c.cl].tile[t] & 63;
    const CUtensorMap* m = &p.map_w[type * 2 + (tile >> 5)];
    const int n0 = (tile & 31) * 128 + c.rank * 64;
    const int ptile = p.s.r[c.cl].tile[t + PF1 < n ? t + PF1 : t];
    const CUtensorMap* pm = &p.map_w[type * 2 + ((ptile >> 5) & 1)];
    if (t == 7 && (c.phases & 16)) flag_wait<true>(F_GATE, 256);
#pragma unroll 1
    for (int kb = t ? -type : (NPRO - type) >> 1; kb < 8; kb++) {
      if (t == 0 && 2 * kb + type >= NPRO) {
        mbar_wait(c.bar + (B_P1E + slot) * 8, par);
        mbar_expect(c.bar + (B_P1F + slot) * 8, 16384);
        tma2d(c.sm + SM_RING + slot * 16384, &p.map_a[type], kb * 64, grp * 256 + c.rank * 128, c.bar + (B_P1F + slot) * 8);
        if (++slot == 10) { slot = 0; par ^= 1; }
      }
      mbar_wait(c.bar + (B_P1E + slot) * 8, par);
      mbar_expect(c.bar + (B_P1F + slot) * 8, 16384);
      tma2d_mc(c.sm + SM_RING + slot * 16384 + c.rank * 8192, m, n0, kb < 0 ? 512 : kb * 64, c.bar + (B_P1F + slot) * 8);
      if (t == 0 && kb == 1) PROF(2, 61);
      if (t == 0 && kb == 3) PROF(2, 62);
      if (t + PF1 < n && t > 0 && ((ptile & 64) || ((ptile & 128) && ((kb ^ grp) & PFM) == 0))) tma2d_prefetch(pm, (ptile & 31) * 128 + c.rank * 64, kb < 0 ? 512 : kb * 64);
      if (++slot == 10) { slot = 0; par ^= 1; }
    }
  }
}

__device__ __forceinline__ void p1_storer(const Params& p, const Ctx& c) {
  const int n = p.s.r[c.cl].n1;
  const int type = p.s.r[c.cl].slab >> 3, grp = p.s.r[c.cl].slab & 7;
  for (int i = 0; i < 2 * n; i++) {
    const int t = i >> 1, w = i & 1, b = w * 2 + 1;
    const int tile = p.s.r[c.cl].tile[t] & 63;
    mbar_wait(c.bar + (B_SF + b) * 8, t & 1);
    const uint32_t src = c.sm + SM_BUF + b * 16384;
    int f = (type ? F_Q : F_KV) + (tile & 31) * 8 + grp;
    if (type == 0) {
      const int prev = p.s.prev[tile & 31][grp];
      if (prev != 255 && w == 0) {
        if (grp >= 2) flag_wait<false>(F_RD + prev * 8 + grp, 8 - grp);
        else flag_wait<false>(F_CTX + max(c.lane & 7, grp) * 64 + prev, 4);
      }
      uint8_t* dst = g_KV + (size_t)(((tile & 32) + p.s.slot[tile & 31][grp]) * 16 + grp * 2 + c.rank) * 32768 + w * 8192;
      bulk_store(dst, src, 8192);
      bulk_store(dst + 16384, src + 8192, 8192);
    } else if (tile < 32) {
      bulk_store(g_Q + (size_t)(tile * 32 + grp * 4 + c.rank * 2 + w) * 16384, src, 16384);
    } else {
      tma3d_store(&p.map_t[2], src, 8 + (grp * 4 + c.rank * 2 + w) * 32, 0, (tile - 32) * 64);
      f = F_QKVA + grp * 4 + ((0xE4390900u >> (2 * (tile - 30))) & 3);
    }
    BULK_COMMIT();
    BULK_WAIT(0);
    mbar_arrive_one(c.bar + (B_SE + b) * 8);
    flag_add_rx(f);
  }
}

__device__ __forceinline__ int p2_buf(int w, int i) { return w * 2 + (i & 1); }
__device__ __forceinline__ int p2_blk(int rank, int w, int i) { return ((i ^ w) & 1) == 0 ? 3 - rank : rank; }

template <int N>
__device__ __forceinline__ void row_max(const float (&s)[N], float& m0, float& m1) {
  float a0 = fmaxf(s[0], s[1]), a1 = fmaxf(s[2], s[3]);
#pragma unroll
  for (int i = 1; i < N / 4; i++) {
    m0 = fmaxf(m0, s[4 * i]); a0 = fmaxf(a0, s[4 * i + 1]);
    m1 = fmaxf(m1, s[4 * i + 2]); a1 = fmaxf(a1, s[4 * i + 3]);
  }
  m0 = fmaxf(m0, a0); m1 = fmaxf(m1, a1);
  m0 = fmaxf(m0, __shfl_xor_sync(0xffffffffu, m0, 1));
  m1 = fmaxf(m1, __shfl_xor_sync(0xffffffffu, m1, 1));
  m0 = fmaxf(m0, __shfl_xor_sync(0xffffffffu, m0, 2));
  m1 = fmaxf(m1, __shfl_xor_sync(0xffffffffu, m1, 2));
}
template <bool SUB, int N>
__device__ __forceinline__ void row_exp(const float (&s)[N], uint32_t (&P)[32], float m0, float m1, float& t0, float& t1) {
  float u0 = 0.f, u1 = 0.f;
  t0 = t1 = 0.f;
#pragma unroll
  for (int i = 0; i < N / 4; i++) {
    const float e0 = ex2(SUB ? s[4 * i] - m0 : s[4 * i]), e1 = ex2(SUB ? s[4 * i + 1] - m0 : s[4 * i + 1]);
    const float e2 = ex2(SUB ? s[4 * i + 2] - m1 : s[4 * i + 2]), e3 = ex2(SUB ? s[4 * i + 3] - m1 : s[4 * i + 3]);
    if (i == 0) { t0 = e0; u0 = e1; t1 = e2; u1 = e3; }
    else { t0 += e0; u0 += e1; t1 += e2; u1 += e3; }
    P[2 * i] = pack_bf16(e0, e1);
    P[2 * i + 1] = pack_bf16(e2, e3);
  }
#pragma unroll
  for (int i = N / 2; i < 32; i++) P[i] = 0;
  pin(P);
  t0 += u0; t1 += u1;
}
template <int N>
__device__ __forceinline__ void causal_mask(float (&s)[N], int thr) {
#pragma unroll
  for (int i = 0; i < 8; i++) {
    if (8 * i > thr) s[N - 32 + 4 * i] = -INFINITY;
    if (8 * i + 1 > thr) s[N - 32 + 4 * i + 1] = -INFINITY;
    if (8 * i - 8 > thr) s[N - 32 + 4 * i + 2] = -INFINITY;
    if (8 * i - 7 > thr) s[N - 32 + 4 * i + 3] = -INFINITY;
  }
}
__device__ __forceinline__ void issue_qk(float (&s)[32], uint32_t qd, uint32_t kd) {
  WG_FENCE();
#pragma unroll
  for (int kk = 0; kk < 8; kk++) wgmma_ss64<0>(s, qd + (kk >> 2) * 512 + (kk & 3) * 2, kd + (kk >> 2) * 1024 + (kk & 3) * 2, kk != 0);
  WG_COMMIT();
}
__device__ __forceinline__ void issue_qk(float (&s)[64], uint32_t qd, uint32_t kd) {
  WG_FENCE();
#pragma unroll
  for (int kk = 0; kk < 8; kk++) wgmma_ss128<0>(s, qd + (kk >> 2) * 512 + (kk & 3) * 2, kd + (kk >> 2) * 1024 + (kk & 3) * 2, kk != 0);
  WG_COMMIT();
}
template <int NK>
__device__ __forceinline__ void issue_pv(float (&o)[64], const uint32_t (&P)[32], uint32_t vd, int acc) {
  WG_FENCE();
#pragma unroll
  for (int kk = 0; kk < NK; kk++) wgmma_rs128<1>(o, P[4 * kk], P[4 * kk + 1], P[4 * kk + 2], P[4 * kk + 3], vd + kk * 128, kk != 0 ? 1 : acc);
  WG_COMMIT();
}
__device__ __forceinline__ void stage_done(const Ctx& c, int b) {
  FENCE_ASYNC_SMEM();
  __syncwarp();
  if (c.lane == 0) mbar_arrive(c.bar + (B_SF + b) * 8);
}
__device__ __forceinline__ void p2_epilogue(const float (&o)[64], float s0, float s1, const Ctx& c, int b) {
  stage_tile(o, c.sm + SM_BUF + b * 16384, c, s0, s1);
  stage_done(c, b);
}

struct P2State {
  float m0, m1, l0, l1;
  bool shift;
  float e0, e1;
  int ks;
  int wi, ai;
  uint32_t wb, ab;
  uint32_t qd;
};
#define PROFZ()
__device__ __forceinline__ int wrap5(int q) { return q >= 5 ? q - 5 : q; }
__device__ __forceinline__ void turn_wait(uint32_t ring, int i) { mbar_wait(ring + (i & 3) * 8, (i >> 2) & 1); }
__device__ __forceinline__ void turn_pass(const Ctx& c, uint32_t ring, int i) { if (c.lane == 0) mbar_arrive(ring + (i & 3) * 8); }
__device__ __forceinline__ void p2_scales(P2State& z) {
  float l0 = z.l0, l1 = z.l1;
  l0 += __shfl_xor_sync(0xffffffffu, l0, 1);
  l1 += __shfl_xor_sync(0xffffffffu, l1, 1);
  l0 += __shfl_xor_sync(0xffffffffu, l0, 2);
  l1 += __shfl_xor_sync(0xffffffffu, l1, 2);
  asm("rcp.approx.ftz.f32 %0, %1;" : "=f"(z.e0) : "f"(l0));
  asm("rcp.approx.ftz.f32 %0, %1;" : "=f"(z.e1) : "f"(l1));
}
template <int N>
__device__ __forceinline__ void p2_first(const Ctx& c, P2State& z, float (&o)[64], uint32_t (&Pc)[32], uint32_t (&Pn)[32],
                                         int ks, int vs, int cnt, int acc) {
  float s[N] = {};
  issue_qk(s, z.qd, desc_lo(c.sm + SM_RING, 16) + ks * 2048);
  if (vs >= 0) {
    p2_scales(z);
    issue_pv<8>(o, Pc, desc_lo(c.sm + SM_RING, 16384) + vs * 2048, acc);
  } else {
    WG_COMMIT();
  }
  mbar_expect(z.ab + (z.ai++ & 3) * 8, cnt == 1 ? 8192 : 0);
  PROFZ();
  WG_WAIT(1);
  PROFZ();
  pin(s);
  release(c, B_P2E + ks, cnt);
  causal_mask(s, c.warp * 16 + (c.lane >> 2) - 2 * (c.lane & 3));
  z.m0 = z.m1 = 0.f;
  row_exp<false>(s, Pn, 0.f, 0.f, z.l0, z.l1);
  z.shift = __any_sync(0xffffffffu, !(z.l0 + z.l1 <= SM_HI) || ((c.lane & 3) == 0 && !(fminf(z.l0, z.l1) >= SM_LO)));
  if (__builtin_expect(z.shift, 0)) {
    z.m0 = z.m1 = -INFINITY;
    row_max(s, z.m0, z.m1);
    row_exp<true>(s, Pn, z.m0, z.m1, z.l0, z.l1);
  }
  WG_WAIT(0);
  pin(o);
  if (vs >= 0) release(c, B_P2E + vs, 1);
}

template <bool SECOND>
__device__ __forceinline__ void p2_turn(const Ctx& c, P2State& z, float (&o)[64], uint32_t (&Pc)[32], uint32_t (&Pn)[32],
                                        int eb = -1, bool half = false, int vcnt = 1) {
  float s[64] = {};
  const int ks = z.ks, vs = wrap5(ks + 1);
  PROFZ();
  turn_wait(z.wb, z.wi++);
  PROFZ();
  issue_qk(s, z.qd, desc_lo(c.sm + SM_RING, 16) + ks * 2048);
  const uint32_t vd = desc_lo(c.sm + SM_RING, 16384) + vs * 2048;
  if (SECOND) {
    if (eb >= 0) stage_tile(o, c.sm + SM_BUF + eb * 16384, c, z.e0, z.e1);
    if (half) issue_pv<4>(o, Pc, vd, 0); else issue_pv<8>(o, Pc, vd, 0);
  } else {
    issue_pv<8>(o, Pc, vd, 1);
  }
  turn_pass(c, z.ab, z.ai++);
  if (SECOND) { if (eb >= 0) stage_done(c, eb); }
  PROFZ();
  z.ks = wrap5(ks + 2);
  WG_WAIT(1);
  PROFZ();
  pin(s);
  release(c, B_P2E + ks, 1);
  float t0, t1, a0 = 1.f, a1 = 1.f;
  row_exp<false>(s, Pn, 0.f, 0.f, t0, t1);
  z.shift = __any_sync(0xffffffffu, z.shift || !(t0 + t1 <= SM_HI));
  const bool redo = z.shift;
  if (__builtin_expect(redo, 0)) {
    float n0 = z.m0, n1 = z.m1;
    row_max(s, n0, n1);
    a0 = ex2(z.m0 - n0); a1 = ex2(z.m1 - n1);
    z.m0 = n0; z.m1 = n1;
    z.l0 *= a0; z.l1 *= a1;
    row_exp<true>(s, Pn, z.m0, z.m1, t0, t1);
  }
  WG_WAIT(0);
  pin(o);
  release(c, B_P2E + vs, vcnt);
  if (__builtin_expect(redo, 0)) {
#pragma unroll
    for (int i = 0; i < 16; i++) { o[4 * i] *= a0; o[4 * i + 1] *= a0; o[4 * i + 2] *= a1; o[4 * i + 3] *= a1; }
  }
  z.l0 += t0; z.l1 += t1;
}
__device__ __forceinline__ void copy_p(uint32_t (&d)[32], const uint32_t (&s)[32], int zero) {
#pragma unroll
  for (int i = 0; i < 32; i++) asm volatile("add.s32 %0, %1, %2;" : "=r"(d[i]) : "r"(s[i]), "r"(zero));
}

__device__ __forceinline__ void p2_consumer(const Params& p, const Ctx& c, int rot) {
  const int nit = p.s.r[c.cl].n2;
  const uint32_t fring = c.bar + B_P2F * 8, oring = c.bar + B_ORD * 8;
  float o[64] = {};
  uint32_t Pa[32] = {}, Pb[32] = {};
  P2State z;
  z.e0 = z.e1 = z.l0 = z.l1 = 0.f; z.ks = rot; z.shift = false;
  int acc = 0, n = 0;
  for (int it = 0; it < nit; it++) {
    const int j = p.s.r[c.cl].item[it] & 7, blk = p2_blk(c.rank, c.wg, it);
    const int lng = ((it ^ c.wg) & 1) ^ 1;
    z.qd = desc_lo(c.sm + SM_BUF, 16) + p2_buf(c.wg, it) * 1024;
    if (lng) { z.wb = oring; z.wi = n - it; z.ab = fring; z.ai = n + 1; }
    else { z.wb = fring; z.wi = n + 2; z.ab = oring; z.ai = n - it; }
    PROFZ();
    mbar_wait(c.bar + (B_QF + p2_buf(c.wg, it)) * 8, (it >> 1) & 1);
    turn_wait(fring, n + 1 - lng);
    PROFZ();
    const int vs = it ? wrap5(z.ks + 1) : -1, ks = lng ? z.ks : wrap5(z.ks + (it ? 2 : 1));
    if (blk & 1) p2_first<64>(c, z, o, Pa, Pb, ks, vs, 1 + lng, acc);
    else p2_first<32>(c, z, o, Pa, Pb, ks, vs, 1 + lng, acc);
    z.ks = wrap5(ks + (it == 0 && lng ? 1 : 2));
    PROF(c.wg, 24 + it);
    n += 2 * j + 2;
    int left = 2 * j + lng;
    acc = left != 0;
    if (left == 0) { copy_p(Pa, Pb, p.zero); continue; }
    p2_turn<true>(c, z, o, Pb, Pa, it > 0 ? p2_buf(c.wg, it - 1) : -1, !(blk & 1), 1 + lng);
    while (--left > 0) {
      p2_turn<false>(c, z, o, Pa, Pb);
      if (--left == 0) { copy_p(Pa, Pb, p.zero); break; }
      p2_turn<false>(c, z, o, Pb, Pa);
    }
  }
  {
    if (!acc && nit > 1) p2_epilogue(o, z.e0, z.e1, c, p2_buf(c.wg, nit));
    turn_wait(z.wb, z.wi);
    issue_pv<8>(o, Pa, desc_lo(c.sm + SM_RING, 16384) + z.ks * 2048, acc);
    if (((nit - 1) ^ c.wg) & 1) turn_pass(c, z.ab, z.ai);
    p2_scales(z);
    WG_WAIT(0);
    pin(o);
    release(c, B_P2E + z.ks);
    p2_epilogue(o, z.e0, z.e1, c, p2_buf(c.wg, nit - 1));
    PROF(c.wg, 24 + nit);
  }
}

__device__ __forceinline__ void p2_load_q(const Params& p, const Ctx& c, int it, int w) {
  const int item = p.s.r[c.cl].item[it], h = item >> 3, j = item & 7, b = p2_buf(w, it);
  mbar_expect(c.bar + (B_QF + b) * 8, 16384);
  bulk_load(c.sm + SM_BUF + b * 16384, g_Q + (size_t)(h * 32 + j * 4 + p2_blk(c.rank, w, it)) * 16384, 16384, c.bar + (B_QF + b) * 8, POL(4));
}
__device__ __forceinline__ void wait_p1_free(const Ctx& c, int u1, int s) {
  mbar_wait(c.bar + (B_P1E + 2 * s) * 8, ((u1 - 1 - 2 * s) / 10) & 1);
  mbar_wait(c.bar + (B_P1E + 2 * s + 1) * 8, ((u1 - 2 - 2 * s) / 10) & 1);
}
__device__ __forceinline__ void p2_producer(const Params& p, const Ctx& c, int u1, int rot) {
  const int nit = p.s.r[c.cl].n2;
  int slot = rot, cnt = 0, par = 1, n = 0;
  const uint8_t* pv = nullptr;
  bool pl = false;
  auto load = [&](const uint8_t* src, int expect, uint32_t fb, bool last) {
    if (cnt < 5) {
      if (u1) {
        wait_p1_free(c, u1, slot);
        if (cnt == 0) p2_load_q(p, c, 0, 1);
      }
      cnt++;
    } else {
      if (slot == rot) par ^= 1;
      mbar_wait(c.bar + (B_P2E + slot) * 8, par);
    }
    if (expect) mbar_expect(fb, expect);
    bulk_load_mc(c.sm + SM_RING + slot * 32768 + c.rank * 16384, src, 16384, fb, last ? POL(5) : L2_NORMAL);
    slot = wrap5(slot + 1);
  };
  for (int it = 0; it < nit; it++) {
    const int item = p.s.r[c.cl].item[it], h = item >> 3, j = item & 7;
    if (it == 1 && (c.phases & 16) && p.s.r[c.cl].n1 < 8) flag_wait<true>(F_GATE, 256);
    uint32_t ready = (c.phases & 16) ? 0u : 255u;
    if (it == 0) { if (c.phases & 16) flag_wait<false>(F_Q + item, 4); mbar_wait(c.bar + B_LAD * 8, 0); p2_load_q(p, c, 0, 0); if (!u1) p2_load_q(p, c, 0, 1); }
    for (int t = 2 * j + 1; t >= 0; t--) {
      mask_wait(ready, t >> 1, F_KV + h * 8 + (c.lane & 7), 8);
      const uint8_t* k = g_KV + (size_t)(p.s.slot[h][t >> 1] * 16 + t) * 32768 + c.rank * 16384;
      const uint32_t fb = c.bar + (B_P2F + (n & 3)) * 8;
      const bool last = (p.s.r[c.cl].last[it] >> (t >> 1)) & 1;
      load(k, pv && t != 2 * j ? 65536 : 32768, fb, last);
      if (!(t & 1) && t + 4 <= 2 * j && c.rank == 0) flag_add_rx(F_RD + h * 8 + (t >> 1) + 2);
      if (pv) load(pv, 0, t != 2 * j ? fb : c.bar + (B_ORD + ((n - 1 - it) & 3)) * 8, pl);
      pl = last;
      pv = k + (size_t)NH * 16 * 32768;
      n++;
    }
  }
  load(pv, 32768, c.bar + (B_P2F + (n & 3)) * 8, pl);
}

__device__ __forceinline__ void p2_storer(const Params& p, const Ctx& c, int sfpar) {
  const int nit = p.s.r[c.cl].n2;
  auto load_q = [&](int it, int w) {
    if (c.phases & 16) flag_wait<false>(F_Q + p.s.r[c.cl].item[it], 4);
    p2_load_q(p, c, it, w);
  };
  if (nit > 1) {
    load_q(1, 1); p2_load_q(p, c, 1, 0); }
  for (int i = 0; i < 2 * nit; i++) {
    const int it = i >> 1, w = (it ^ i ^ 1) & 1, b = p2_buf(w, it);
    const int item = p.s.r[c.cl].item[it], h = item >> 3, j = item & 7;
    mbar_wait(c.bar + (B_SF + b) * 8, (sfpar >> b) & 1);
    sfpar ^= 1 << b;
    bulk_store(g_Q + (size_t)(h * 32 + j * 4 + p2_blk(c.rank, w, it)) * 16384, c.sm + SM_BUF + b * 16384, 16384, POL(1));
    BULK_COMMIT();
    BULK_WAIT(0);
    flag_add_rx(F_CTX + j * 64 + h);
    if ((i & 1) && it + 2 < nit) { load_q(it + 2, w); p2_load_q(p, c, it + 2, w ^ 1); }
  }
  release(c, B_DONE);
}

__device__ __forceinline__ int p3_pos(int i, int x) { return i < 4 ? (i + x) & 3 : 4; }
__device__ __forceinline__ void p3_consumer(const Params& p, const Ctx& c, int x) {
  const bool first = p.s.r[c.cl].p3 >= 24;
  const int tile = p.s.r[c.cl].p3 - (first ? 24 : 0), j = tile / 3, nt = tile - 3 * j;
  const int na = first ? 9 : 0, nb = 2 * (p.s.task[c.cl][1] - p.s.task[c.cl][0]);
  const uint32_t ad = desc_lo(c.sm + SM_RING + c.wg * 8192, 16), bd = desc_lo(c.sm + SM_RING + 16384, 4096);
  float acc[96] = {};
  int slot = 0, par = 0, prev = 0;
  float g0 = 0.f, g1 = 0.f;
  const int hold = c.wg && LAG ? na + nb - LAG : -1, pass = c.wg || !LAG ? -1 : na + nb - 1;
#pragma unroll 1
  for (int kb = 0; kb < nb; kb++) {
    if (kb == hold) bar_sync(6, 256);
    mbar_wait(c.bar + (B_P3F + slot) * 8, par);
    if (kb == 0) PROF(c.wg, 39);
    WG_FENCE();
#pragma unroll
    for (int kk = 0; kk < 4; kk++) wgmma_ss192<1>(acc, ad + p3_pos(slot, x) * 2560 + kk * 2, bd + p3_pos(slot, x) * 2560 + (kk >> 1) * 768 + (kk & 1) * 128, kk != 0 ? 1 : kb != 0);
    WG_COMMIT();
    if (kb == pass) bar_arrive(6, 256);
    WG_WAIT(1);
    if (kb > 0) release(c, B_P3E + prev);
    else {
      const float* g = g_gate + j * 256 + c.rank * 128 + c.wg * 64 + c.warp * 16 + (c.lane >> 2);
      g0 = __ldcg(g); g1 = __ldcg(g + 8);
    }
    prev = slot;
    if (++slot == 5) { slot = 0; par ^= 1; }
  }
  WG_WAIT(0);
  pin(acc);
  g0 = 1.f - g0; g1 = 1.f - g1;
#pragma unroll
  for (int i = 0; i < 24; i++) { acc[4 * i] *= g0; acc[4 * i + 1] *= g0; acc[4 * i + 2] *= g1; acc[4 * i + 3] *= g1; }
#pragma unroll 1
  for (int kb = nb; kb < nb + na; kb++) {
    if (kb == hold) bar_sync(6, 256);
    mbar_wait(c.bar + (B_P3F + slot) * 8, par);
    if (kb == 0) PROF(c.wg, 39);
    WG_FENCE();
#pragma unroll
    for (int kk = 0; kk < 4; kk++) wgmma_ss192<1, 1>(acc, ad + p3_pos(slot, x) * 2560 + kk * 128, bd + p3_pos(slot, x) * 2560 + (kk >> 1) * 768 + (kk & 1) * 128, 1);
    WG_COMMIT();
    if (kb == pass) bar_arrive(6, 256);
    WG_WAIT(1);
    if (kb > 0) release(c, B_P3E + prev);
    prev = slot;
    if (++slot == 5) { slot = 0; par ^= 1; }
  }
  WG_WAIT(0);
  pin(acc);
  PROF(c.wg, 40);
  if (first) bar_sync(4 + c.wg, 128);
  mbar_wait(c.bar + B_OUT * 8, 0);
  const int row = (c.lane & 7) + ((c.lane >> 3) & 1) * 8;
  const uint32_t wbase = c.sm + SM_RING + c.wg * 8192 + c.warp * 2048;
  const uint32_t base = wbase + row * 128 + (((c.lane >> 4) ^ (row & 7)) << 4);
#pragma unroll
  for (int i = 0; i < 12; i++) {
    stsm4((base ^ ((i & 3) << 5)) + (i >> 2) * 40960, pack_bf16(acc[8 * i], acc[8 * i + 1]), pack_bf16(acc[8 * i + 2], acc[8 * i + 3]),
          pack_bf16(acc[8 * i + 4], acc[8 * i + 5]), pack_bf16(acc[8 * i + 6], acc[8 * i + 7]));
    if ((i & 3) == 3) {
      FENCE_ASYNC_SMEM();
      bar_sync(4 + c.wg, 128);
      if (c.warp == (i >> 2)) tma2d_add(&p.map_out, c.sm + SM_RING + c.wg * 8192 + c.warp * 40960, nt * 192 + c.warp * 64, j * 256 + c.rank * 128 + c.wg * 64);
    }
  }
  BULK_COMMIT();
  PROF(c.wg, 43);
  BULK_WAIT_READ(0);
  PROF(c.wg, 44);
}

__device__ __forceinline__ void p3_producer(const Params& p, const Ctx& c, int u1, int u2, int rot, int x) {
  const bool first = p.s.r[c.cl].p3 >= 24;
  const int tile = p.s.r[c.cl].p3 - (first ? 24 : 0), j = tile / 3, nt = tile - 3 * j;
  int slot = 0, par = 1, cnt = 0;
  auto wait_free = [&](int s) {
    const int f = wrap5(s + 5 - rot);
    if (f < u2) mbar_wait(c.bar + (B_P2E + s) * 8, ((u2 - 1 - f) / 5) & 1);
    else if (u1) wait_p1_free(c, u1, s);
  };
  asm volatile(ELECT("prefetch.tensormap [%0];") ::"l"(&p.map_o[0]) : "memory");
  asm volatile(ELECT("prefetch.tensormap [%0];") ::"l"(&p.map_out) : "memory");
  if ((c.phases & 16) && p.s.r[c.cl].n1 < 8 && p.s.r[c.cl].n2 < 2) flag_wait<true>(F_GATE, 256);
  uint32_t ready = (c.phases & 16) ? 0u : ~0u;
  const int q1 = p.s.task[c.cl][1] - !first;
  for (int q = p.s.task[c.cl][0]; q <= q1; q++) {
    const bool brA = first && q == q1;
    const int g = brA ? 32 : p.s.p3_order[j][q];
    if (brA) { if (c.phases & 16) flag_wait<false>(F_CTX + j * 64 + 32, 16); }
    else mask_wait(ready, g, F_CTX + j * 64 + c.lane, 4);
    const int nk = brA ? 9 : 2, k0 = (brA ? 0 : g * 128) + c.rank * 32;
    const uint8_t* a = brA ? g_oA + (j * 4 + c.rank * 2) * 73728 : g_Q + (size_t)(g * 32 + j * 4 + c.rank * 2) * 16384;
    const CUtensorMap* m = &p.map_o[brA];
    for (int i = 0; i < nk; i++) {
      const uint32_t st = c.sm + SM_RING + p3_pos(slot, x) * 40960, fb = c.bar + (B_P3F + slot) * 8;
      if (cnt < 4) { wait_free(p3_pos(cnt, x)); wait_free(p3_pos(cnt, x) + 1); }
      else if (cnt == 4) mbar_wait(c.bar + B_DONE * 8, 0);
      else mbar_wait(c.bar + (B_P3E + slot) * 8, par);
      cnt++;
      mbar_expect(fb, 40960);
      bulk_load(st, a + i * 8192, 8192, fb, POL(3));
      bulk_load(st + 8192, a + (nk + i) * 8192, 8192, fb, POL(3));
      tma3d_mc(st + 16384 + c.rank * 12288, m, 0, k0 + i * 64, nt * 3, fb);
      if (++slot == 5) { slot = 0; par ^= 1; }
    }
  }
}

__device__ __forceinline__ float bf_lo(uint32_t w) { return __uint_as_float(w << 16); }
__device__ __forceinline__ float bf_hi(uint32_t w) { return __uint_as_float(w & 0xffff0000u); }

__device__ __forceinline__ void gate_rows(const Params& p, int row0, int lane) {
  const uint4* x = reinterpret_cast<const uint4*>(p.x + (size_t)(row0 + (lane >> 2)) * DM) + (lane & 3);
  const uint4* w = reinterpret_cast<const uint4*>(p.gate_w) + (lane & 3);
  float a = 0.f;
#pragma unroll 1
  for (int b = 0; b < 3; b++) {
    uint4 u[6];
#pragma unroll
    for (int i = 0; i < 6; i++) u[i] = __ldg(x + (b * 6 + i) * 4);
#pragma unroll
    for (int i = 0; i < 6; i++) {
      const uint4 v = __ldg(w + (b * 6 + i) * 4);
      a = fmaf(bf_lo(u[i].x), bf_lo(v.x), a); a = fmaf(bf_hi(u[i].x), bf_hi(v.x), a);
      a = fmaf(bf_lo(u[i].y), bf_lo(v.y), a); a = fmaf(bf_hi(u[i].y), bf_hi(v.y), a);
      a = fmaf(bf_lo(u[i].z), bf_lo(v.z), a); a = fmaf(bf_hi(u[i].z), bf_hi(v.z), a);
      a = fmaf(bf_lo(u[i].w), bf_lo(v.w), a); a = fmaf(bf_hi(u[i].w), bf_hi(v.w), a);
    }
  }
  a += __shfl_xor_sync(0xffffffffu, a, 1);
  a += __shfl_xor_sync(0xffffffffu, a, 2);
  if ((lane & 3) == 0) g_gate[row0 + (lane >> 2)] = 1.f / (1.f + __expf(-a));
}

__device__ __forceinline__ void lds10(uint32_t (&k)[10], uint32_t a) {
  asm volatile("ld.shared.v2.u32 {%0, %1}, [%10];\nld.shared.v2.u32 {%2, %3}, [%10+8];\nld.shared.v2.u32 {%4, %5}, [%10+16];\n"
               "ld.shared.v2.u32 {%6, %7}, [%10+24];\nld.shared.v2.u32 {%8, %9}, [%10+32];"
               : "=r"(k[0]), "=r"(k[1]), "=r"(k[2]), "=r"(k[3]), "=r"(k[4]), "=r"(k[5]), "=r"(k[6]), "=r"(k[7]), "=r"(k[8]), "=r"(k[9]) : "r"(a));
}
__device__ __forceinline__ void local_attn(const Params& p, const Ctx& c, int rb, int hs) {
  const int lane = c.lane, grp = rb >> 2, par = lane >> 4, i0 = 2 * (lane & 15);
  const uint32_t buf = c.sm + SM_BUF + (c.warp - 2) * 8192, bqk = c.bar + (B_LA + (c.warp - 2) * 2) * 8, bv = bqk + 8;
  const uint32_t mine = buf + 2304 + par * 160 + i0 * 4;
  const bool flags = c.phases & 16;
  auto fetch_qk = [&](int i) {
    if (flags && !(i & 1)) {
      const int q = i >> 1;
      const int tgt = q == 0 ? 24 : q == 3 ? 8 : 12;
      flag_wait<false>(F_QKVA + (grp - (grp > 0 && (rb & 3) == 0 ? par : 0)) * 4 + q, tgt);
    }
    mbar_expect(bqk, 5184);
    tma3d(buf, &p.map_t[0], rb * 32 + 8, 0, 9 * (4 * i + hs), bqk, POL(2));
    tma3d(buf + 2304, &p.map_t[1], rb * 32, 0, 288 + 9 * (4 * i + hs), bqk, POL(2));
  };
  auto fetch_v = [&](int i) { mbar_expect(bv, 2880); tma3d(buf + 5248, &p.map_t[1], rb * 32, 0, 576 + 9 * (4 * i + hs), bv, POL(2)); };
  fetch_qk(0);
  if (flags) flag_wait<true>(F_GATE, 256);
#pragma unroll 1
  for (int q = 0; q < 8; q++) {
    fetch_v(q);
    float a[8], b[8];
#pragma unroll
    for (int w = 0; w < 8; w++) a[w] = b[w] = 0.f;
    mbar_wait(bqk, q & 1);
    PROFB(1 + 2 * q);
#pragma unroll 1
    for (int j = 0; j < 9; j++) {
      uint32_t x, y, k[10];
      asm volatile("ld.shared.v2.u32 {%0, %1}, [%2];" : "=r"(x), "=r"(y) : "r"(buf + lane * 8 + j * 256));
      lds10(k, mine + j * 320);
      const float xl = bf_lo(x), xh = bf_hi(x), yl = bf_lo(y), yh = bf_hi(y);
#pragma unroll
      for (int m = 1; m < 10; m++) {
        const float kl = bf_lo(k[m]), kh = bf_hi(k[m]);
        if (m < 9) a[8 - m] = fmaf(xl, kl, fmaf(xh, kh, a[8 - m]));
        if (m > 1) b[9 - m] = fmaf(yl, kl, fmaf(yh, kh, b[9 - m]));
      }
    }
    __syncwarp();
    if (q < 7) fetch_qk(q + 1);
    constexpr float SC = 0.23570226039551584f * 1.4426950408889634f;
    const float* gp = g_gate + rb * 64 + 2 * i0 + par;
    const float ga = __ldcg(gp), gb = __ldcg(gp + 2);
    float ma = a[0], mb = b[0];
#pragma unroll
    for (int w = 1; w < 8; w++) {
      if (rb == 0) {
        if (i0 < w) a[w] = -INFINITY;
        if (i0 + 1 < w) b[w] = -INFINITY;
      }
      ma = fmaxf(ma, a[w]); mb = fmaxf(mb, b[w]);
    }
    float la = 0.f, lb = 0.f;
#pragma unroll
    for (int w = 0; w < 8; w++) {
      a[w] = ex2((a[w] - ma) * SC); b[w] = ex2((b[w] - mb) * SC);
      la += a[w]; lb += b[w];
    }
    la = __fdividef(ga, la); lb = __fdividef(gb, lb);
#pragma unroll
    for (int w = 0; w < 8; w++) { a[w] *= la; b[w] *= lb; }
    uint8_t* dst = g_oA + rb * 73728 + ((i0 & 2) + par) * 4;
    mbar_wait(bv, q & 1);
#pragma unroll 1
    for (int j = 0; j < 9; j++) {
      uint32_t v[10];
      lds10(v, mine + 2944 + j * 320);
      float a0 = 0.f, a1 = 0.f, b0 = 0.f, b1 = 0.f;
#pragma unroll
      for (int m = 1; m < 10; m++) {
        const float vl = bf_lo(v[m]), vh = bf_hi(v[m]);
        if (m < 9) { a0 = fmaf(a[8 - m], vl, a0); a1 = fmaf(a[8 - m], vh, a1); }
        if (m > 1) { b0 = fmaf(b[9 - m], vl, b0); b1 = fmaf(b[9 - m], vh, b1); }
      }
      const uint32_t wa = pack_bf16(a0, a1), wb = pack_bf16(b0, b1);
      const uint32_t got = __shfl_xor_sync(0xffffffffu, par ? wa : wb, 16);
      const uint32_t r0 = par ? got : wa, r1 = par ? wb : got;
      const int col = 18 * (4 * q + hs) + 2 * j, o = col * 128 + ((((i0 >> 2) ^ col) & 7) << 4);
      *reinterpret_cast<uint32_t*>(dst + o) = __byte_perm(r0, r1, 0x5410);
      *reinterpret_cast<uint32_t*>(dst + ((o + 128) ^ 16)) = __byte_perm(r0, r1, 0x7632);
    }
    __syncwarp();
    PROFB(2 + 2 * q);
  }
  mbar_arrive_one(c.bar + B_LAD * 8);
  flag_add(F_CTX + grp * 64 + 32);
}

__global__ void __cluster_dims__(2, 1, 1) __launch_bounds__(384, 1) fused_kernel(const __grid_constant__ Params p) {
  extern __shared__ uint8_t smem_raw[];
  Ctx c;
  c.sm = ((uint32_t)__cvta_generic_to_shared(smem_raw) + 1023u) & ~1023u;
  c.bar = c.sm + SM_BAR;
  c.lane = threadIdx.x & 31;
  const int wid = __shfl_sync(0xffffffffu, threadIdx.x >> 5, 0);
  if (wid < 6) asm volatile("prefetch.tensormap [%0];" ::"l"(&p.map_a[0] + wid) : "memory");
  c.wg = wid >> 2;
  c.warp = wid & 3;
  PROF(c.wg, 0);
  PROFG(61);
  c.cl = (blockIdx.x + (wid >> 4)) >> 1;
  c.rank = blockIdx.x & 1;
  c.rbar = mapa(c.bar, c.lane & 1);
  {
    const int w = wid, cnt = (((int)(B_CNT >> (4 * w)) - 1) & 15) + 1;
    if (w < 11) {
#pragma unroll
      for (int i = 0; i < 8; i++) asm volatile("mbarrier.init.shared::cta.b64 [%0], %1;" ::"r"(c.bar + w * 64 + i * 8), "r"(cnt));
    }
    asm volatile("fence.mbarrier_init.release.cluster;" ::: "memory");
  }
  if (c.wg == 2) PROF(2, 56);
  asm volatile("barrier.cluster.arrive.relaxed;" ::: "memory");
  c.phases = p.s.r[c.cl].phases;
  const bool do1 = p.s.r[c.cl].n1 > 0, do2 = p.s.r[c.cl].n2 > 0, do3 = p.s.r[c.cl].p3 != 255;
  if (do1 && c.wg == 2 && c.warp == 0) {
    const int type = p.s.r[c.cl].slab >> 3;
    PROF(2, 57);
    FENCE_ASYNC_SMEM();
    mbar_expect(c.bar + B_P1F * 8, type ? 32768 : 16384);
    tma2d(type ? c.sm + SM_BUF + 32768 : c.sm + SM_RING, &p.map_a[type], type ? 512 : 0, (p.s.r[c.cl].slab & 7) * 256 + c.rank * 128, c.bar + B_P1F * 8);
    PROF(2, 58);
  }
  asm volatile("barrier.cluster.wait.acquire;" ::: "memory");
  if (c.wg == 2) PROF(2, 59);
  if (do1 && c.wg == 2 && c.warp == 0) {
    const int type = p.s.r[c.cl].slab >> 3, tile = p.s.r[c.cl].tile[0] & 63;
    const CUtensorMap* m = &p.map_w[type * 2 + (tile >> 5)];
#pragma unroll 1
    for (int s = 1 - type; s < NPRO; s++) {
      const int kb = (s - type) >> 1;
      const uint32_t fb = c.bar + (B_P1F + s) * 8;
      if (s) mbar_expect(fb, 16384);
      if ((s ^ type) & 1) tma2d_mc(c.sm + SM_RING + s * 16384 + c.rank * 8192, m, (tile & 31) * 128 + c.rank * 64, kb < 0 ? 512 : kb * 64, fb);
      else tma2d(c.sm + SM_RING + s * 16384, &p.map_a[type], kb * 64, (p.s.r[c.cl].slab & 7) * 256 + c.rank * 128, fb);
    }
  }

  if (c.wg < 2) {
    PROF(c.wg, 4);
    asm volatile("setmaxnreg.inc.sync.aligned.u32 224;");
    if (c.wg == 1) {
      if (do1) bar_arrive(ORDER, 256);
      if (c.lane == 0) mbar_arrive(c.bar + B_P2F * 8);
    }
    if (do1) p1_consumer(p, c);
    if (do2) p2_consumer(p, c, p.s.r[c.cl].rot);
    if (do3) p3_consumer(p, c, p.s.r[c.cl].x3);
    PROF(c.wg, 63);
    PROFG(62);
    if (c.lane == 0) mbar_arrive(c.bar + B_FIN * 8);
    __syncwarp();
    cluster_sync();
  } else {
    asm volatile("setmaxnreg.dec.sync.aligned.u32 56;");
    if (c.warp == 0) {
      PROF(2, 60);
      if (do1) p1_producer(p, c);
      if (do2) p2_producer(p, c, p.s.r[c.cl].u1, p.s.r[c.cl].rot);
      if (do3) p3_producer(p, c, p.s.r[c.cl].u1, p.s.r[c.cl].u2, p.s.r[c.cl].rot, p.s.r[c.cl].x3);
    } else if (c.warp == 1) {
      int sfpar = 0;
      if (do1) {
        p1_storer(p, c);
        sfpar = (p.s.r[c.cl].n1 & 1) * 10;
      }
      if (do2) p2_storer(p, c, sfpar);
      else { mbar_wait(c.bar + B_LAD * 8, 0); release(c, B_DONE); }
      if (do3) {
        const int task = p.s.r[c.cl].p3;
        if (task >= 24) {
          const int j = (task - 24) / 3, nt = task - 24 - 3 * j;
          uint4* o = reinterpret_cast<uint4*>(p.out + (size_t)(j * 256 + c.rank * 128 + (c.lane >> 3)) * DM + nt * 192) + (c.lane & 7);
#pragma unroll 4
          for (int r = 0; r < 32; r++) o[r * 288] = o[r * 288 + 8] = o[r * 288 + 16] = make_uint4(0u, 0u, 0u, 0u);
          __syncwarp();
          flag_add(F_OUT + (task - 24) * 2 + c.rank);
        } else if (c.phases & 16) {
          flag_wait<false, 256>(F_OUT + task * 2 + c.rank, 1);
        }
        mbar_arrive_one(c.bar + B_OUT * 8);
      }
    } else {
      const int bw = blockIdx.x * 2 + (c.warp - 2);
      if ((c.phases & 1) && bw < 256) {
        gate_rows(p, bw * 8, c.lane);
        __syncwarp();
        flag_add(F_GATE);
      }
      if (p.s.r[c.cl].bg != 255) local_attn(p, c, p.s.r[c.cl].bg, bw & 3);
      else if (c.lane == 0) mbar_arrive(c.bar + B_LAD * 8);
    }
    __syncwarp();
    bar_sync(3, 128);
    if (c.warp == 0 && (c.phases & 4)) {
      int last = 0;
      if (c.lane == 0) { __threadfence(); last = atomicAdd(g_flags + F_DONE, 1) == 2 * NCL - 1; }
      if (__shfl_sync(0xffffffffu, last, 0)) for (int i = c.lane; i < F_NUM; i += 32) g_flags[i] = 0;
    }
    if (c.warp == 1) mbar_wait(c.bar + B_FIN * 8, 0);
    __syncwarp();
    cluster_sync();
  }
}

SCHED_DECL Sched k_sched = {
  {{0,29,2,32,0,{248,251,0,0,0,0,0,0,0,0,0},{0,0,0,0,0,0,0,0,0,0,0},{64,35,5,39,15,8,10,13,12,1,22,9,14,18,25,29,21,27,16,26,28,17,24,30,11,23,31,19,20,0}},
   {1,29,0,14,1,{0,0,0,0,0,0,0,0,0,0,0},{0,0,0,0,0,0,0,0,0,0,0},{64,35,6,39,15,8,10,13,12,1,22,9,14,18,25,29,21,27,16,26,28,17,24,30,23,11,31,19,20,0}},
   {2,29,1,27,2,{156,0,0,0,0,0,0,0,0,0,0},{0,0,0,0,0,0,0,0,0,0,0},{64,37,3,39,15,2,10,13,12,1,22,9,14,18,25,29,21,27,16,26,28,17,24,30,23,11,31,19,20,0}},
   {3,29,1,35,3,{250,0,0,0,0,0,0,0,0,0,0},{0,0,0,0,0,0,0,0,0,0,0},{69,38,0,39,15,2,10,13,12,1,22,9,14,18,25,29,21,27,26,16,28,17,24,30,11,23,31,19,20,0}},
   {4,28,1,46,4,{91,0,0,0,0,0,0,0,0,0,0},{0,0,0,0,0,0,0,0,0,0,0},{64,35,6,39,15,10,34,12,1,9,22,14,18,25,29,21,27,26,16,28,17,24,30,11,23,31,19,20,0,0}},
   {5,27,0,21,5,{0,0,0,0,0,0,0,0,0,0,0},{0,0,0,0,0,0,0,0,0,0,0},{69,32,6,39,15,2,42,12,33,22,14,18,25,29,21,27,16,26,28,17,24,30,11,23,31,19,20,0,0,0}},
   {6,26,2,34,6,{224,196,0,0,0,0,0,0,0,0,0},{0,0,0,0,0,0,0,0,0,0,0},{67,5,135,36,8,10,45,1,41,14,18,25,29,21,27,26,16,28,17,24,75,30,23,31,19,20,0,0,0,0}},
   {7,25,2,29,7,{208,159,0,0,0,0,0,0,0,0,0},{0,128,0,0,0,0,0,0,0,0,0},{69,6,135,79,66,77,108,73,118,82,89,93,85,91,90,80,92,81,88,94,75,87,95,83,84,0,0,0,0,0}},
   {0,29,0,0,8,{0,0,0,0,0,0,0,0,0,0,0},{0,0,0,0,0,0,0,0,0,0,0},{96,6,37,4,47,40,42,45,44,33,54,41,46,50,57,61,53,59,48,58,60,49,56,62,43,55,63,51,52,0}},
   {1,29,0,4,9,{0,0,0,0,0,0,0,0,0,0,0},{0,0,0,0,0,0,0,0,0,0,0},{96,5,38,4,47,40,42,45,44,33,54,41,46,50,57,61,53,59,48,58,60,49,56,62,55,43,63,51,52,0}},
   {2,29,2,4,10,{185,162,0,0,0,0,0,0,0,0,0},{0,0,0,0,0,0,0,0,0,0,0},{96,6,35,4,47,34,42,45,44,33,54,41,46,50,57,61,53,59,48,58,60,49,56,62,55,43,63,51,52,0}},
   {3,29,0,2,11,{0,0,0,0,0,0,0,0,0,0,0},{0,0,0,0,0,0,0,0,0,0,0},{101,3,32,4,47,34,42,45,44,33,54,41,46,50,57,61,53,59,58,48,60,49,56,62,43,55,63,51,52,0}},
   {4,28,2,43,12,{88,252,0,0,0,0,0,0,0,0,0},{0,0,0,0,0,0,0,0,0,0,0},{96,5,38,4,47,106,13,44,33,41,54,46,50,57,61,53,59,58,48,60,49,56,62,43,55,63,51,52,0,0}},
   {5,27,1,44,13,{254,0,0,0,0,0,0,0,0,0,0},{127,0,0,0,0,0,0,0,0,0,0},{101,3,38,4,47,34,13,44,9,54,46,50,57,61,53,59,48,58,60,49,56,62,43,55,63,51,52,0,0,0}},
   {6,26,1,14,14,{190,0,0,0,0,0,0,0,0,0,0},{64,0,0,0,0,0,0,0,0,0,0},{99,37,103,79,40,106,76,97,86,110,50,57,61,53,59,58,48,60,49,56,107,62,55,63,51,52,0,0,0,0}},
   {7,25,1,22,15,{191,0,0,0,0,0,0,0,0,0,0},{128,0,0,0,0,0,0,0,0,0,0},{101,38,103,111,98,109,65,105,78,114,121,125,117,123,122,112,124,113,120,126,107,119,127,115,116,0,0,0,0,0}},
   {0,6,5,41,255,{32,35,111,149,199,0,0,0,0,0,0},{0,0,0,0,255,0,0,0,0,0,0},{67,38,135,36,66,34,0,0,0,0,0,0,0,0,0,0,0,0,0,0,0,0,0,0,0,0,0,0,0,0}},
   {1,6,5,1,255,{56,38,106,150,171,0,0,0,0,0,0},{0,0,0,0,15,0,0,0,0,0,0},{67,37,135,36,66,34,0,0,0,0,0,0,0,0,0,0,0,0,0,0,0,0,0,0,0,0,0,0,0,0}},
   {2,6,8,28,255,{61,18,13,147,129,226,89,152,0,0,0},{0,0,0,0,0,0,0,0,0,0,0},{69,38,135,36,8,40,0,0,0,0,0,0,0,0,0,0,0,0,0,0,0,0,0,0,0,0,0,0,0,0}},
   {3,6,4,10,255,{127,14,134,158,0,0,0,0,0,0,0},{0,0,0,127,0,0,0,0,0,0,0},{70,35,135,36,8,40,0,0,0,0,0,0,0,0,0,0,0,0,0,0,0,0,0,0,0,0,0,0,0,0}},
   {4,8,6,9,255,{120,87,105,75,212,93,0,0,0,0,0},{0,0,0,0,0,63,0,0,0,0,0},{67,37,135,36,8,40,2,45,0,0,0,0,0,0,0,0,0,0,0,0,0,0,0,0,0,0,0,0,0,0}},
   {5,10,4,3,255,{16,124,151,168,0,0,0,0,0,0,0},{0,0,0,0,0,0,0,0,0,0,0},{64,35,135,36,8,40,10,45,1,41,0,0,0,0,0,0,0,0,0,0,0,0,0,0,0,0,0,0,0,0}},
   {6,10,7,20,255,{80,123,97,99,74,218,255,0,0,0,0},{0,0,0,0,3,0,128,0,0,0,0},{70,0,68,111,66,34,13,44,9,54,0,0,0,0,0,0,0,0,0,0,0,0,0,0,0,0,0,0,0,0}},
   {7,4,4,15,255,{44,36,102,237,0,0,0,0,0,0,0},{0,0,0,48,0,0,0,0,0,0,0},{67,0,68,72,0,0,0,0,0,0,0,0,0,0,0,0,0,0,0,0,0,0,0,0,0,0,0,0,0,0}},
   {8,17,2,5,16,{104,222,0,0,0,0,0,0,0,0,0},{0,0,0,0,0,0,0,0,0,0,0},{131,36,7,43,2,35,44,109,13,78,1,157,21,26,17,24,11,0,0,0,0,0,0,0,0,0,0,0,0,0}},
   {9,19,1,16,17,{221,0,0,0,0,0,0,0,0,0,0},{48,0,0,0,0,0,0,0,0,0,0},{128,41,162,7,39,2,10,40,1,13,14,25,21,16,28,24,11,83,31,0,0,0,0,0,0,0,0,0,0,0}},
   {10,17,3,5,18,{148,139,188,0,0,0,0,0,0,0,0},{4,0,0,0,0,0,0,0,0,0,0},{128,161,162,99,108,2,15,40,12,22,14,25,21,16,17,158,95,0,0,0,0,0,0,0,0,0,0,0,0,0}},
   {11,19,3,39,19,{213,193,194,0,0,0,0,0,0,0,0},{0,0,0,0,0,0,0,0,0,0,0},{133,36,7,15,2,39,10,40,1,22,14,25,21,26,16,24,11,83,20,0,0,0,0,0,0,0,0,0,0,0}},
   {12,19,2,17,20,{220,192,0,0,0,0,0,0,0,0,0},{0,0,0,0,0,0,0,0,0,0,0},{128,36,7,72,35,44,13,109,1,22,146,157,155,16,17,158,23,83,20,0,0,0,0,0,0,0,0,0,0,0}},
   {13,18,4,33,21,{72,235,138,157,0,0,0,0,0,0,0},{0,0,0,0,0,0,0,0,0,0,0},{133,41,7,15,77,35,44,65,45,78,146,157,80,26,17,158,23,83,0,0,0,0,0,0,0,0,0,0,0,0}},
   {14,18,3,24,22,{144,172,197,0,0,0,0,0,0,0,0},{0,0,0,0,0,0,0,0,0,0,0},{131,36,7,15,10,39,13,65,45,9,146,157,155,16,17,158,23,83,0,0,0,0,0,0,0,0,0,0,0,0}},
   {15,17,3,40,23,{96,236,198,0,0,0,0,0,0,0,0},{1,0,0,0,0,0,0,0,0,0,0},{133,32,42,43,2,13,39,12,73,45,14,25,21,26,28,24,11,0,0,0,0,0,0,0,0,0,0,0,0,0}},
   {8,20,2,12,24,{200,219,0,0,0,0,0,0,0,0,0},{0,12,0,0,0,0,0,0,0,0,0},{128,41,132,72,10,39,104,12,86,9,146,25,155,16,28,158,23,31,19,20,0,0,0,0,0,0,0,0,0,0}},
   {9,18,4,18,25,{112,146,209,94,0,0,0,0,0,0,0},{0,0,0,64,0,0,0,0,0,0,0},{131,161,166,99,108,8,76,109,86,9,146,157,155,26,17,158,23,84,0,0,0,0,0,0,0,0,0,0,0,0}},
   {10,20,4,0,26,{233,141,153,160,0,0,0,0,0,0,0},{0,0,0,0,0,0,0,0,0,0,0},{133,165,166,103,8,10,13,109,1,9,146,157,155,26,28,87,24,11,20,19,0,0,0,0,0,0,0,0,0,0}},
   {11,18,4,8,27,{176,133,242,90,0,0,0,0,0,0,0},{0,0,0,0,0,0,0,0,0,0,0},{70,41,132,72,35,44,13,109,12,9,146,157,155,81,28,158,23,31,0,0,0,0,0,0,0,0,0,0,0,0}},
   {12,17,1,19,28,{116,0,0,0,0,0,0,0,0,0,0},{24,0,0,0,0,0,0,0,0,0,0},{131,41,162,15,39,2,104,12,73,78,89,85,90,92,88,75,95,0,0,0,0,0,0,0,0,0,0,0,0,0}},
   {13,18,3,45,29,{214,243,154,0,0,0,0,0,0,0,0},{0,0,0,0,0,0,0,0,0,0,0},{128,161,132,72,10,39,76,40,86,9,89,85,155,92,88,75,95,84,0,0,0,0,0,0,0,0,0,0,0,0}},
   {14,18,2,23,30,{8,203,0,0,0,0,0,0,0,0,0},{0,0,0,0,0,0,0,0,0,0,0},{70,41,132,72,35,44,76,40,86,78,89,85,90,92,88,75,95,84,0,0,0,0,0,0,0,0,0,0,0,0}},
   {15,20,3,22,31,{232,140,184,0,0,0,0,0,0,0,0},{0,0,0,0,0,0,0,0,0,0,0},{131,36,132,72,10,35,44,65,40,22,146,157,155,16,17,158,23,31,19,20,0,0,0,0,0,0,0,0,0,0}},
   {8,3,6,47,255,{4,34,19,183,234,246,0,0,0,0,0},{0,0,0,32,0,127,0,0,0,0,0},{70,161,79,0,0,0,0,0,0,0,0,0,0,0,0,0,0,0,0,0,0,0,0,0,0,0,0,0,0,0}},
   {9,3,7,12,255,{5,22,118,169,210,186,163,0,0,0,0},{0,0,64,0,0,0,0,0,0,0,0},{133,165,107,0,0,0,0,0,0,0,0,0,0,0,0,0,0,0,0,0,0,0,0,0,0,0,0,0,0,0}},
   {10,3,6,8,255,{2,62,122,12,173,240,0,0,0,0,0},{0,0,0,0,0,0,0,0,0,0,0},{160,170,107,0,0,0,0,0,0,0,0,0,0,0,0,0,0,0,0,0,0,0,0,0,0,0,0,0,0,0}},
   {11,3,6,2,255,{24,29,69,117,230,187,0,0,0,0,0},{0,0,0,0,0,0,0,0,0,0,0},{131,161,162,0,0,0,0,0,0,0,0,0,0,0,0,0,0,0,0,0,0,0,0,0,0,0,0,0,0,0}},
   {12,3,6,31,255,{46,21,76,114,142,161,0,0,0,0,0},{0,0,0,0,127,0,0,0,0,0,0},{133,161,166,0,0,0,0,0,0,0,0,0,0,0,0,0,0,0,0,0,0,0,0,0,0,0,0,0,0,0}},
   {13,4,7,21,255,{40,53,85,206,217,137,253,0,0,0,0},{0,0,0,0,0,0,0,0,0,0,0},{131,165,162,66,0,0,0,0,0,0,0,0,0,0,0,0,0,0,0,0,0,0,0,0,0,0,0,0,0,0}},
   {14,3,6,38,255,{27,37,15,113,143,249,0,0,0,0,0},{0,0,128,0,255,0,0,0,0,0,0},{133,161,162,0,0,0,0,0,0,0,0,0,0,0,0,0,0,0,0,0,0,0,0,0,0,0,0,0,0,0}},
   {15,3,4,13,255,{31,110,175,136,0,0,0,0,0,0,0},{4,0,0,0,0,0,0,0,0,0,0},{70,41,79,0,0,0,0,0,0,0,0,0,0,0,0,0,0,0,0,0,0,0,0,0,0,0,0,0,0,0}},
   {8,3,6,17,255,{48,63,108,178,174,167,0,0,0,0,0},{0,0,0,0,0,128,0,0,0,0,0},{133,165,162,0,0,0,0,0,0,0,0,0,0,0,0,0,0,0,0,0,0,0,0,0,0,0,0,0,0,0}},
   {9,3,6,20,255,{0,52,70,78,170,128,0,0,0,0,0},{0,0,0,64,0,0,0,0,0,0,0},{160,170,132,0,0,0,0,0,0,0,0,0,0,0,0,0,0,0,0,0,0,0,0,0,0,0,0,0,0,0}},
   {10,3,5,1,255,{30,86,179,231,165,0,0,0,0,0,0},{0,0,0,3,63,0,0,0,0,0,0},{100,7,3,0,0,0,0,0,0,0,0,0,0,0,0,0,0,0,0,0,0,0,0,0,0,0,0,0,0,0}},
   {11,3,7,42,255,{42,49,26,109,77,132,189,0,0,0,0},{0,0,0,0,0,0,63,0,0,0,0},{128,165,166,0,0,0,0,0,0,0,0,0,0,0,0,0,0,0,0,0,0,0,0,0,0,0,0,0,0,0}},
   {12,4,5,13,255,{6,84,207,211,92,0,0,0,0,0,0},{0,0,0,0,0,0,0,0,0,0,0},{70,165,107,74,0,0,0,0,0,0,0,0,0,0,0,0,0,0,0,0,0,0,0,0,0,0,0,0,0,0}},
   {13,3,6,26,255,{43,50,125,181,229,244,0,0,0,0,0},{0,0,62,0,0,0,0,0,0,0,0},{160,170,166,0,0,0,0,0,0,0,0,0,0,0,0,0,0,0,0,0,0,0,0,0,0,0,0,0,0,0}},
   {14,3,7,36,255,{41,58,71,182,201,225,245,0,0,0,0},{0,0,0,0,0,0,0,0,0,0,0},{128,165,166,0,0,0,0,0,0,0,0,0,0,0,0,0,0,0,0,0,0,0,0,0,0,0,0,0,0,0}},
   {15,3,5,6,255,{55,20,177,238,227,0,0,0,0,0,0},{18,0,0,0,0,0,0,0,0,0,0},{128,161,162,0,0,0,0,0,0,0,0,0,0,0,0,0,0,0,0,0,0,0,0,0,0,0,0,0,0,0}},
   {8,3,6,37,255,{51,60,103,215,241,164,0,0,0,0,0},{0,0,0,3,0,0,0,0,0,0,0},{160,170,166,0,0,0,0,0,0,0,0,0,0,0,0,0,0,0,0,0,0,0,0,0,0,0,0,0,0,0}},
   {9,3,6,25,255,{7,17,83,73,205,95,0,0,0,0,0},{72,0,0,0,0,128,0,0,0,0,0},{100,6,79,0,0,0,0,0,0,0,0,0,0,0,0,0,0,0,0,0,0,0,0,0,0,0,0,0,0,0}},
   {10,3,7,10,255,{54,121,82,98,180,145,131,0,0,0,0},{0,0,0,0,0,3,7,0,0,0,0},{105,6,132,0,0,0,0,0,0,0,0,0,0,0,0,0,0,0,0,0,0,0,0,0,0,0,0,0,0,0}},
   {11,3,6,30,255,{25,59,68,79,202,247,0,0,0,0,0},{0,0,0,0,0,128,0,0,0,0,0},{160,170,107,0,0,0,0,0,0,0,0,0,0,0,0,0,0,0,0,0,0,0,0,0,0,0,0,0,0,0}},
   {12,3,6,6,255,{47,66,107,239,195,155,0,0,0,0,0},{1,0,0,0,0,0,0,0,0,0,0},{160,170,132,0,0,0,0,0,0,0,0,0,0,0,0,0,0,0,0,0,0,0,0,0,0,0,0,0,0,0}},
   {13,3,6,11,255,{45,33,67,100,115,130,0,0,0,0,0},{0,0,0,0,0,0,0,0,0,0,0},{100,6,107,0,0,0,0,0,0,0,0,0,0,0,0,0,0,0,0,0,0,0,0,0,0,0,0,0,0,0}},
   {14,4,5,16,255,{3,126,119,228,166,0,0,0,0,0,0},{0,0,128,0,64,0,0,0,0,0,0},{160,170,107,66,0,0,0,0,0,0,0,0,0,0,0,0,0,0,0,0,0,0,0,0,0,0,0,0,0,0}},
   {15,3,5,7,255,{28,23,11,204,216,0,0,0,0,0,0},{0,0,0,0,0,0,0,0,0,0,0},{71,165,166,0,0,0,0,0,0,0,0,0,0,0,0,0,0,0,0,0,0,0,0,0,0,0,0,0,0,0}},
   {6,2,6,9,255,{1,39,81,9,10,223,0,0,0,0,0},{0,0,0,0,0,192,0,0,0,0,0},{102,32,0,0,0,0,0,0,0,0,0,0,0,0,0,0,0,0,0,0,0,0,0,0,0,0,0,0,0,0}},
   {7,10,5,18,255,{64,57,65,101,135,0,0,0,0,0,0},{0,0,0,0,0,0,0,0,0,0,0},{99,32,100,104,74,106,76,97,86,110,0,0,0,0,0,0,0,0,0,0,0,0,0,0,0,0,0,0,0,0}}},
  {{0,1,0,0},{13,32,0,0},{0,1,0,0},{0,6,0,0},{0,6,0,0},{8,32,0,0},{0,6,0,0},{0,1,0,0},{13,32,0,0},{13,32,0,0},{7,13,0,0},
   {13,32,0,0},{0,1,0,0},{0,1,0,0},{5,13,0,0},{6,14,0,0},{0,5,0,0},{8,32,0,0},{0,7,0,0},{6,11,0,0},{1,9,0,0},{1,32,0,0},
   {1,7,0,0},{6,32,0,0},{9,32,0,0},{9,32,0,0},{1,9,0,0},{0,6,0,0},{9,32,0,0},{0,1,0,0},{0,5,0,0},{0,5,0,0},{10,32,0,0},
   {3,11,0,0},{5,13,0,0},{1,9,0,0},{1,32,0,0},{0,1,0,0},{5,32,0,0},{14,32,0,0},{0,5,0,0},{5,10,0,0},{9,32,0,0},{5,13,0,0},
   {0,5,0,0},{1,8,0,0},{0,5,0,0},{8,32,0,0},{5,9,0,0},{7,32,0,0},{5,8,0,0},{0,3,0,0},{0,8,0,0},{0,5,0,0},{0,5,0,0},
   {12,32,0,0},{0,0,0,0},{0,5,0,0},{11,32,0,0},{0,5,0,0},{5,12,0,0},{6,32,0,0},{5,9,0,0},{5,32,0,0},{9,32,0,0},{11,32,0,0}},
  {{0,3,6,5,4,7,15,2,8,10,12,13,1,9,14,18,22,21,25,29,27,16,26,17,24,30,28,23,11,31,19,20},
   {0,3,5,6,4,15,7,2,8,10,12,1,22,13,9,14,18,25,29,21,27,16,26,28,17,24,30,11,23,20,31,19},
   {0,5,7,6,3,4,8,2,10,15,13,12,1,22,9,14,18,25,29,16,21,27,26,17,28,30,23,31,24,11,20,19},
   {3,5,6,0,7,4,15,2,8,10,13,1,12,22,9,14,18,25,29,21,27,16,26,28,17,24,30,11,23,19,31,20},
   {0,3,5,6,7,4,8,15,10,2,13,12,1,9,22,14,18,25,29,21,27,26,16,28,17,24,30,11,23,31,19,20},
   {0,5,3,6,7,4,15,8,2,13,10,12,1,22,14,9,18,25,29,21,27,16,26,28,17,24,30,11,23,31,19,20},
   {3,5,6,0,7,4,15,8,2,10,13,12,1,22,9,14,18,25,29,27,21,26,16,28,17,24,30,11,23,31,19,20},
   {0,3,5,6,7,4,15,8,2,10,13,12,1,9,22,14,18,25,29,21,27,16,26,28,17,24,11,30,23,31,19,20}},
  {{0,0,0,3,0,1,3,3},{12,12,12,12,12,0,0,1},{7,7,8,8,9,8,8,8},{1,1,3,2,1,2,0,1},
   {5,5,5,5,5,5,5,5},{3,2,1,0,2,0,2,0},{2,3,2,1,3,3,1,2},{4,4,4,4,4,4,4,4},
   {8,8,7,7,7,7,7,7},{14,14,0,1,0,1,1,4},{9,9,9,9,8,9,9,9},{13,15,4,2,4,4,6,9},
   {11,11,11,11,11,11,11,0},{10,10,10,10,10,10,10,10},{15,15,1,5,5,5,5,5},{6,6,6,6,6,6,6,6},
   {7,7,10,11,11,7,11,0},{6,8,12,1,0,1,2,6},{0,0,5,4,4,4,4,2},{5,5,7,12,12,0,0,4},
   {2,2,11,11,11,7,11,0},{4,4,8,9,8,9,9,8},{13,13,13,0,1,2,2,6},{15,13,1,8,8,9,9,8},
   {10,11,13,0,1,5,4,2},{1,1,4,2,2,3,6,3},{9,9,7,7,7,11,7,7},{2,2,9,10,10,10,10,10},
   {8,10,11,12,12,0,0,4},{5,5,2,8,9,8,8,9},{12,12,0,4,2,3,8,3},{1,1,2,7,7,11,7,7}},
  {{255,255,255,255,255,255,255,255},{255,255,255,255,255,5,3,3},{255,255,255,255,255,255,255,255},{255,255,255,255,255,255,255,255},
   {255,255,255,255,255,255,255,255},{255,255,255,255,255,255,255,255},{255,255,255,255,255,255,255,255},{255,255,255,255,255,255,255,255},
   {255,255,255,255,255,255,255,255},{255,255,0,6,0,0,6,7},{255,255,255,255,255,255,255,255},{22,14,25,25,18,18,25,29},
   {255,255,255,255,255,255,255,5},{255,255,255,255,255,255,255,255},{255,255,5,4,4,4,4,4},{255,255,255,255,255,255,255,255},
   {2,2,13,12,12,8,12,12},{15,8,1,9,9,9,22,22},{0,0,4,7,7,7,7,6},{29,29,26,28,28,28,28,28},
   {27,27,28,16,16,16,16,16},{7,7,2,10,10,10,10,2},{255,255,255,5,3,3,5,15},{14,22,14,29,21,21,21,21},
   {13,12,22,22,22,14,18,18},{3,3,7,3,5,6,15,0},{10,10,8,8,8,12,8,8},{6,5,10,13,13,13,13,13},
   {8,13,12,1,1,1,1,9},{4,4,6,2,2,2,2,10},{1,1,9,18,25,25,29,25},{25,25,29,26,26,26,26,26}}};

typedef CUresult (*EncodeFn)(CUtensorMap*, CUtensorMapDataType, cuuint32_t, void*, const cuuint64_t*, const cuuint64_t*, const cuuint32_t*,
                             const cuuint32_t*, CUtensorMapInterleave, CUtensorMapSwizzle, CUtensorMapL2promotion, CUtensorMapFloatOOBfill);

void make_map2(EncodeFn enc, CUtensorMap* m, const void* ptr, int rows, int cols, int box_rows) {
  cuuint64_t dim[2] = {(cuuint64_t)cols, (cuuint64_t)rows}, str[1] = {(cuuint64_t)cols * 2};
  cuuint32_t box[2] = {64, (cuuint32_t)box_rows}, es[2] = {1, 1};
  enc(m, CU_TENSOR_MAP_DATA_TYPE_BFLOAT16, 2, const_cast<void*>(ptr), dim, str, box, es, CU_TENSOR_MAP_INTERLEAVE_NONE, CU_TENSOR_MAP_SWIZZLE_128B,
      CU_TENSOR_MAP_L2_PROMOTION_L2_128B, CU_TENSOR_MAP_FLOAT_OOB_FILL_NONE);
}
void make_map3(EncodeFn enc, CUtensorMap* m, const void* ptr, int rows) {
  cuuint64_t dim[3] = {64, (cuuint64_t)rows, 9}, str[2] = {DM * 2, 128};
  cuuint32_t box[3] = {64, 32, 3}, es[3] = {1, 1, 1};
  enc(m, CU_TENSOR_MAP_DATA_TYPE_BFLOAT16, 3, const_cast<void*>(ptr), dim, str, box, es, CU_TENSOR_MAP_INTERLEAVE_NONE, CU_TENSOR_MAP_SWIZZLE_128B,
      CU_TENSOR_MAP_L2_PROMOTION_L2_128B, CU_TENSOR_MAP_FLOAT_OOB_FILL_NONE);
}

void make_map_t(EncodeFn enc, CUtensorMap* m, void* ptr, int width, int cols) {
  cuuint64_t dim[3] = {TP / 2, 2, 864}, str[2] = {TP * 2, TP * 4};
  cuuint32_t box[3] = {(cuuint32_t)width, 2, (cuuint32_t)cols}, es[3] = {1, 1, 1};
  enc(m, CU_TENSOR_MAP_DATA_TYPE_UINT32, 3, ptr, dim, str, box, es, CU_TENSOR_MAP_INTERLEAVE_NONE, cols == 64 ? CU_TENSOR_MAP_SWIZZLE_128B : CU_TENSOR_MAP_SWIZZLE_NONE,
      CU_TENSOR_MAP_L2_PROMOTION_NONE, CU_TENSOR_MAP_FLOAT_OOB_FILL_NONE);
}

int g_mode = -1;

}

extern "C" void kernel_launch(void* const* d_in, const int* in_sizes, int n_in, void* d_out, int out_size) {
  static EncodeFn enc = nullptr;
  static void* t_ptr = nullptr;
  if (!enc) {
    void* fn = nullptr;
    cudaDriverEntryPointQueryResult st;
    cudaGetDriverEntryPoint("cuTensorMapEncodeTiled", &fn, cudaEnableDefault, &st);
    enc = (EncodeFn)fn;
    cudaGetSymbolAddress(&t_ptr, g_T);
    cudaFuncSetAttribute(fused_kernel, cudaFuncAttributeMaxDynamicSharedMemorySize, SMEM_BYTES);
    if (g_mode < 0) {
      cudaLaunchConfig_t cfg = {};
      cfg.gridDim = dim3(2 * NCL); cfg.blockDim = dim3(384); cfg.dynamicSmemBytes = SMEM_BYTES;
      cudaLaunchAttribute at; at.id = cudaLaunchAttributeClusterDimension;
      at.val.clusterDim.x = 2; at.val.clusterDim.y = 1; at.val.clusterDim.z = 1;
      cfg.attrs = &at; cfg.numAttrs = 1;
      int nc = 0;
      g_mode = (cudaOccupancyMaxActiveClusters(&nc, fused_kernel, &cfg) == cudaSuccess && nc >= NCL) ? 1 : 0;
      (void)cudaGetLastError();
    }
  }
  Params p;
  make_map2(enc, &p.map_a[0], d_in[4], SEQ, DC, 128);
  make_map2(enc, &p.map_a[1], d_in[0], SEQ, DM, 128);
  make_map2(enc, &p.map_w[0], d_in[6], DC, 4096, 64);
  make_map2(enc, &p.map_w[1], d_in[7], DC, 4096, 64);
  make_map2(enc, &p.map_w[2], d_in[5], DM, 4096, 64);
  make_map2(enc, &p.map_w[3], d_in[1], DM, 1728, 64);
  make_map3(enc, &p.map_o[0], d_in[8], 4096);
  make_map3(enc, &p.map_o[1], d_in[2], DM);
  make_map_t(enc, &p.map_t[0], t_ptr, 32, 9);
  make_map_t(enc, &p.map_t[1], t_ptr, 40, 9);
  make_map_t(enc, &p.map_t[2], t_ptr, 32, 64);
  p.x = (const __nv_bfloat16*)d_in[0];
  p.gate_w = (const __nv_bfloat16*)d_in[9];
  make_map2(enc, &p.map_out, d_out, SEQ, DM, 64);
  p.out = (__nv_bfloat16*)d_out;
  p.zero = 0;
  auto launch = [&](int phases) {
    p.s = k_sched;
    for (int i = 0; i < NCL; i++) {
      Rec& r = p.s.r[i];
      if (!(phases & 1)) r.n1 = 0;
      if (!(phases & 2)) r.n2 = 0;
      if (!(phases & (r.p3 < 24 ? 4 : 32))) r.p3 = 255;
      if (!(phases & 8)) r.bg = 255;
      const int u1 = r.n1 ? 8 + r.n1 * (8 + (r.slab >> 3)) : 0;
      int u2 = 0;
      for (int k = 0; k < r.n2; k++) u2 += 4 * (r.item[k] & 7) + 4;
      r.u1 = (uint8_t)u1; r.u2 = (uint8_t)u2;
      r.rot = (uint8_t)(((u1 % 10 + 1) >> 1) % 5);
      r.x3 = (uint8_t)((r.rot + u2) % 5 & 3);
      r.phases = (uint8_t)phases;
    }
    if (!(phases & 16))
      for (int i = 0; i < 256; i++) { p.s.slot[i >> 3][i & 7] = (uint8_t)(i >> 3); p.s.prev[i >> 3][i & 7] = 255; }
    fused_kernel<<<2 * NCL, 384, SMEM_BYTES>>>(p);
  };
  if (g_mode == 1) launch(63);
  else { launch(1); launch(10); launch(32); launch(4); }
}
```

```cpp
#include <cuda_runtime.h>
#include <cuda_bf16.h>
#include <cuda.h>
#include <stdint.h>

namespace {

constexpr int SEQ = 2048, DM = 576, DC = 512, NH = 32;
constexpr int NCL = 66;
constexpr uint32_t DESC_HI = 0x40000040u;

constexpr int SM_RING = 0;
constexpr int SM_BUF = 163840;
constexpr int SM_BAR = 229376;
constexpr int B_P1E = 0, B_P2E = 10, B_P3E = 15, B_P2F = 24, B_SF = 32, B_ORD = 36, B_LAD = 40, B_DONE = 41, B_FIN = 48;
constexpr int B_P3F = 56, B_OUT = 61, B_P1F = 64, B_SE = 74, B_QF = 80, B_LA = 84, B_NUM = 88;
constexpr uint64_t B_CNT = 0x11118245000ull;
constexpr int SMEM_BYTES = SM_BAR + B_NUM * 8 + 1024;

constexpr int F_QKVA = 32;
constexpr int F_GATE = 64;
constexpr int F_DONE = 65;
constexpr int F_CTX = 96;
constexpr int F_OUT = 96 + 8 * 64;
constexpr int F_KV = F_OUT + 64;
constexpr int F_Q = F_KV + 256;
constexpr int F_RD = F_Q + 256;
constexpr int F_NUM = F_RD + 256;

struct Rec {
  uint8_t slab;
  uint8_t n1, n2;
  uint8_t p3;
  uint8_t bg;
  uint8_t item[11];
  uint8_t last[11];
  uint8_t tile[32];
  uint8_t u1, u2;
  uint8_t rot, x3;
  uint8_t phases;
};
struct Sched {
  Rec r[NCL];
  uint8_t task[NCL][4];
  uint8_t p3_order[8][32];
  uint8_t slot[32][8];
  uint8_t prev[32][8];
};

#define SCHED_DECL static const

struct Params {
  CUtensorMap map_a[2];
  CUtensorMap map_w[4];
  CUtensorMap map_o[2];
  CUtensorMap map_t[3];
  CUtensorMap map_out;
  const __nv_bfloat16* x;
  const __nv_bfloat16* gate_w;
  __nv_bfloat16* out;
  int zero;
  alignas(64) Sched s;
};

__device__ __align__(1024) uint8_t g_Q[NH * 32 * 16384];
__device__ __align__(1024) uint8_t g_KV[2 * NH * 16 * 32768];
__device__ __align__(1024) uint8_t g_oA[32 * 576 * 128];
constexpr int TP = SEQ + 16;
__device__ __align__(1024) uint32_t g_T[864 * TP];
__device__ float g_gate[SEQ];
__device__ int g_flags[F_NUM];

__device__ __forceinline__ void mbar_arrive(uint32_t b) { asm volatile("mbarrier.arrive.shared::cta.b64 _, [%0];" ::"r"(b) : "memory"); }
__device__ __forceinline__ void mbar_arrive_cl(uint32_t b, int cnt) {
  asm volatile("mbarrier.arrive.shared::cluster.b64 _, [%0], %1;" ::"r"(b), "r"(cnt) : "memory");
}
__device__ __forceinline__ void mbar_wait(uint32_t b, int par) {
  asm volatile(
      "{\n.reg .pred p;\n.reg .u32 c;\n"
      "mbarrier.try_wait.parity.shared::cta.b64 p, [%0], %1;\n@p bra DN;\nmov.u32 c, 0;\n"
      "LP:\nmbarrier.try_wait.parity.shared::cta.b64 p, [%0], %1;\n@p bra DN;\n"
      "add.u32 c, c, 1;\nsetp.lt.u32 p, c, 4000000;\n@p bra LP;\ntrap;\nDN:\n}" ::"r"(b), "r"(par) : "memory");
}
__device__ __forceinline__ uint32_t mapa(uint32_t a, uint32_t cta) {
  uint32_t r; asm("mapa.shared::cluster.u32 %0, %1, %2;" : "=r"(r) : "r"(a), "r"(cta)); return r;
}
#define ELECT(ins) "{\n.reg .pred e;\nelect.sync _|e, 0xffffffff;\n@e " ins "\n}"
__device__ __forceinline__ void mbar_expect(uint32_t b, int bytes) {
  asm volatile(ELECT("mbarrier.arrive.expect_tx.shared::cta.b64 _, [%0], %1;") ::"r"(b), "r"(bytes) : "memory");
}
__device__ __forceinline__ void mbar_arrive_one(uint32_t b) { asm volatile(ELECT("mbarrier.arrive.shared::cta.b64 _, [%0];") ::"r"(b) : "memory"); }
constexpr uint64_t L2_NORMAL = 0x1000000000000000ull, L2_FIRST = 0x12F0000000000000ull;
__device__ __forceinline__ void bulk_load(uint32_t dst, const void* src, int bytes, uint32_t bar, uint64_t pol = L2_NORMAL) {
  asm volatile(ELECT("cp.async.bulk.shared::cluster.global.mbarrier::complete_tx::bytes.L2::cache_hint [%0], [%1], %2, [%3], %4;") ::"r"(dst), "l"(src), "r"(bytes), "r"(bar), "l"(pol) : "memory");
}
__device__ __forceinline__ void bulk_load_mc(uint32_t dst, const void* src, int bytes, uint32_t bar, uint64_t pol = L2_NORMAL) {
  asm volatile(ELECT("cp.async.bulk.shared::cluster.global.mbarrier::complete_tx::bytes.multicast::cluster.L2::cache_hint [%0], [%1], %2, [%3], %4, %5;") ::"r"(dst), "l"(src), "r"(bytes), "r"(bar), "h"((uint16_t)3), "l"(pol) : "memory");
}
__device__ __forceinline__ void bulk_store(void* dst, uint32_t src, int bytes, uint64_t pol = L2_NORMAL) {
  asm volatile(ELECT("cp.async.bulk.global.shared::cta.bulk_group.L2::cache_hint [%0], [%1], %2, %3;") ::"l"(dst), "r"(src), "r"(bytes), "l"(pol) : "memory");
}
__device__ __forceinline__ void tma2d(uint32_t dst, const CUtensorMap* m, int c0, int c1, uint32_t bar, uint64_t pol = L2_NORMAL) {
  asm volatile(ELECT("cp.async.bulk.tensor.2d.shared::cluster.global.mbarrier::complete_tx::bytes.L2::cache_hint [%0], [%1, {%3, %4}], [%2], %5;") ::"r"(dst), "l"(m), "r"(bar), "r"(c0), "r"(c1), "l"(pol) : "memory");
}
__device__ __forceinline__ void tma2d_mc(uint32_t dst, const CUtensorMap* m, int c0, int c1, uint32_t bar, uint64_t pol = L2_NORMAL) {
  asm volatile(ELECT("cp.async.bulk.tensor.2d.shared::cluster.global.mbarrier::complete_tx::bytes.multicast::cluster.L2::cache_hint [%0], [%1, {%3, %4}], [%2], %5, %6;") ::"r"(dst), "l"(m), "r"(bar), "r"(c0), "r"(c1), "h"((uint16_t)3), "l"(pol) : "memory");
}
__device__ __forceinline__ void tma3d(uint32_t dst, const CUtensorMap* m, int c0, int c1, int c2, uint32_t bar, uint64_t pol = L2_NORMAL) {
  asm volatile(ELECT("cp.async.bulk.tensor.3d.shared::cluster.global.mbarrier::complete_tx::bytes.L2::cache_hint [%0], [%1, {%3, %4, %5}], [%2], %6;") ::"r"(dst), "l"(m), "r"(bar), "r"(c0), "r"(c1), "r"(c2), "l"(pol) : "memory");
}
__device__ __forceinline__ void tma3d_mc(uint32_t dst, const CUtensorMap* m, int c0, int c1, int c2, uint32_t bar, uint64_t pol = L2_NORMAL) {
  asm volatile(ELECT("cp.async.bulk.tensor.3d.shared::cluster.global.mbarrier::complete_tx::bytes.multicast::cluster.L2::cache_hint [%0], [%1, {%3, %4, %5}], [%2], %6, %7;") ::"r"(dst), "l"(m), "r"(bar), "r"(c0), "r"(c1), "r"(c2), "h"((uint16_t)3), "l"(pol) : "memory");
}
__device__ __forceinline__ void tma2d_add(const CUtensorMap* m, uint32_t src, int c0, int c1) {
  asm volatile(ELECT("cp.reduce.async.bulk.tensor.2d.global.shared::cta.add.bulk_group [%0, {%2, %3}], [%1];") ::"l"(m), "r"(src), "r"(c0), "r"(c1) : "memory");
}
__device__ __forceinline__ void tma3d_store(const CUtensorMap* m, uint32_t src, int c0, int c1, int c2, uint64_t pol = L2_NORMAL) {
  asm volatile(ELECT("cp.async.bulk.tensor.3d.global.shared::cta.bulk_group.L2::cache_hint [%0, {%2, %3, %4}], [%1], %5;") ::"l"(m), "r"(src), "r"(c0), "r"(c1), "r"(c2), "l"(pol) : "memory");
}
__device__ __forceinline__ void tma2d_prefetch(const CUtensorMap* m, int c0, int c1, uint64_t pol = L2_NORMAL) {
  asm volatile(ELECT("cp.async.bulk.prefetch.tensor.2d.L2.global.L2::cache_hint [%0, {%1, %2}], %3;") ::"l"(m), "r"(c0), "r"(c1), "l"(pol) : "memory");
}
#define LAG 3
#define HINT 62
#define POL(bit) ((HINT >> (bit)) & 1 ? L2_FIRST : L2_NORMAL)
#define BULK_COMMIT() asm volatile("cp.async.bulk.commit_group;" ::: "memory")
#define BULK_WAIT(n) asm volatile("cp.async.bulk.wait_group %0;" ::"n"(n) : "memory")
#define BULK_WAIT_READ(n) asm volatile("cp.async.bulk.wait_group.read %0;" ::"n"(n) : "memory")
#define FENCE_ASYNC_SMEM() asm volatile("fence.proxy.async.shared::cta;" ::: "memory")
#define FENCE_ASYNC_ALL() asm volatile("fence.proxy.async;" ::: "memory")
#define WG_FENCE() asm volatile("wgmma.fence.sync.aligned;" ::: "memory")
#define WG_COMMIT() asm volatile("wgmma.commit_group.sync.aligned;" ::: "memory")
#define WG_WAIT(n) asm volatile("wgmma.wait_group.sync.aligned %0;" ::"n"(n) : "memory")
__device__ __forceinline__ void bar_sync(int id, int n) { asm volatile("bar.sync %0, %1;" ::"r"(id), "r"(n) : "memory"); }
__device__ __forceinline__ void bar_arrive(int id, int n) { asm volatile("bar.arrive %0, %1;" ::"r"(id), "r"(n) : "memory"); }
__device__ __forceinline__ void cluster_sync() {
  asm volatile("barrier.cluster.arrive.relaxed;\nbarrier.cluster.wait.acquire;" ::: "memory");
}
template <int N> __device__ __forceinline__ void pin(float (&r)[N]) {
#pragma unroll
  for (int i = 0; i < N; i++) asm volatile("" : "+f"(r[i])::"memory");
}
template <int N> __device__ __forceinline__ void pin(uint32_t (&r)[N]) {
#pragma unroll
  for (int i = 0; i < N; i++) asm volatile("" : "+r"(r[i])::"memory");
}
__device__ __forceinline__ uint32_t pack_bf16(float lo, float hi) {
  uint32_t r; asm("cvt.rn.bf16x2.f32 %0, %1, %2;" : "=r"(r) : "f"(hi), "f"(lo)); return r;
}
__device__ __forceinline__ float ex2(float x) { float r; asm("ex2.approx.ftz.f32 %0, %1;" : "=f"(r) : "f"(x)); return r; }
__device__ __forceinline__ void ldsm4(uint32_t a, uint32_t& r0, uint32_t& r1, uint32_t& r2, uint32_t& r3) {
  asm volatile("ldmatrix.sync.aligned.m8n8.x4.shared.b16 {%0,%1,%2,%3}, [%4];" : "=r"(r0), "=r"(r1), "=r"(r2), "=r"(r3) : "r"(a) : "memory");
}
__device__ __forceinline__ void stsm4(uint32_t a, uint32_t r0, uint32_t r1, uint32_t r2, uint32_t r3) {
  asm volatile("stmatrix.sync.aligned.m8n8.x4.shared.b16 [%0], {%1,%2,%3,%4};" ::"r"(a), "r"(r0), "r"(r1), "r"(r2), "r"(r3) : "memory");
}
__device__ __forceinline__ void flag_add(int idx) {
  asm volatile(ELECT("red.release.gpu.global.add.s32 [%0], 1;") ::"l"(g_flags + idx) : "memory");
}
__device__ __forceinline__ void flag_add_rx(int idx) {
  asm volatile(ELECT("red.relaxed.gpu.global.add.s32 [%0], 1;") ::"l"(g_flags + idx) : "memory");
}
template <bool ACQ, int NS = 32> __device__ __forceinline__ void flag_wait(int idx, int target) {
  int n = 0;
  while (true) {
    int v;
    if (ACQ) asm volatile("ld.acquire.gpu.global.s32 %0, [%1];" : "=r"(v) : "l"(g_flags + idx) : "memory");
    else asm volatile("ld.relaxed.gpu.global.s32 %0, [%1];" : "=r"(v) : "l"(g_flags + idx) : "memory");
    if (__all_sync(0xffffffffu, v >= target)) break;
    if (++n > 20000000) __trap();
    __nanosleep(NS);
  }
}
__device__ __forceinline__ void mask_wait(uint32_t& ready, int bit, int idx, int target) {
  for (int n = 0; !((ready >> bit) & 1); n++) {
    int v;
    if (n) { __nanosleep(32); if (n > 20000000) __trap(); }
    asm volatile("ld.relaxed.gpu.global.s32 %0, [%1];" : "=r"(v) : "l"(g_flags + idx) : "memory");
    ready = __ballot_sync(0xffffffffu, v >= target);
  }
}
__device__ __forceinline__ uint32_t desc_lo(uint32_t addr, uint32_t lbo) { return ((addr & 0x3FFFFu) >> 4) | ((lbo >> 4) << 16); }
#define PROF(role, i)
#define PROFX(cond, i)
#define PROFB(i)
#define PROFG(i)

template <int TB, int TA = 0> __device__ __forceinline__ void wgmma_ss64(float (&d)[32], uint32_t alo, uint32_t blo, int sd) {
  asm volatile("{\n.reg .pred p;\n.reg .b64 da, db;\n"
    "setp.ne.b32 p, %34, 0;\nmov.b64 da, {%32, %36};\nmov.b64 db, {%33, %36};\n"
    "wgmma.mma_async.sync.aligned.m64n64k16.f32.bf16.bf16 "
    "{%0,%1,%2,%3,%4,%5,%6,%7,%8,%9,%10,%11,%12,%13,%14,%15,%16,%17,%18,%19,%20,%21,%22,%23,"
    "%24,%25,%26,%27,%28,%29,%30,%31}, "
    "da, db, p, 1, 1, %37, %35;\n}\n"
    : "+f"(d[0]),"+f"(d[1]),"+f"(d[2]),"+f"(d[3]),"+f"(d[4]),"+f"(d[5]),"+f"(d[6]),"+f"(d[7]),"+f"(d[8]),"+f"(d[9]),"+f"(d[10]),"+f"(d[11]),
      "+f"(d[12]),"+f"(d[13]),"+f"(d[14]),"+f"(d[15]),"+f"(d[16]),"+f"(d[17]),"+f"(d[18]),"+f"(d[19]),"+f"(d[20]),"+f"(d[21]),"+f"(d[22]),"+f"(d[23]),
      "+f"(d[24]),"+f"(d[25]),"+f"(d[26]),"+f"(d[27]),"+f"(d[28]),"+f"(d[29]),"+f"(d[30]),"+f"(d[31])
    : "r"(alo), "r"(blo), "r"(sd), "n"(TB), "r"(DESC_HI), "n"(TA));
}
template <int TB, int TA = 0> __device__ __forceinline__ void wgmma_ss128(float (&d)[64], uint32_t alo, uint32_t blo, int sd) {
  asm volatile("{\n.reg .pred p;\n.reg .b64 da, db;\n"
    "setp.ne.b32 p, %66, 0;\nmov.b64 da, {%64, %68};\nmov.b64 db, {%65, %68};\n"
    "wgmma.mma_async.sync.aligned.m64n128k16.f32.bf16.bf16 "
    "{%0,%1,%2,%3,%4,%5,%6,%7,%8,%9,%10,%11,%12,%13,%14,%15,%16,%17,%18,%19,%20,%21,%22,%23,"
    "%24,%25,%26,%27,%28,%29,%30,%31,%32,%33,%34,%35,%36,%37,%38,%39,%40,%41,%42,%43,%44,%45,%46,%47,"
    "%48,%49,%50,%51,%52,%53,%54,%55,%56,%57,%58,%59,%60,%61,%62,%63}, "
    "da, db, p, 1, 1, %69, %67;\n}\n"
    : "+f"(d[0]),"+f"(d[1]),"+f"(d[2]),"+f"(d[3]),"+f"(d[4]),"+f"(d[5]),"+f"(d[6]),"+f"(d[7]),"+f"(d[8]),"+f"(d[9]),"+f"(d[10]),"+f"(d[11]),
      "+f"(d[12]),"+f"(d[13]),"+f"(d[14]),"+f"(d[15]),"+f"(d[16]),"+f"(d[17]),"+f"(d[18]),"+f"(d[19]),"+f"(d[20]),"+f"(d[21]),"+f"(d[22]),"+f"(d[23]),
      "+f"(d[24]),"+f"(d[25]),"+f"(d[26]),"+f"(d[27]),"+f"(d[28]),"+f"(d[29]),"+f"(d[30]),"+f"(d[31]),"+f"(d[32]),"+f"(d[33]),"+f"(d[34]),"+f"(d[35]),
      "+f"(d[36]),"+f"(d[37]),"+f"(d[38]),"+f"(d[39]),"+f"(d[40]),"+f"(d[41]),"+f"(d[42]),"+f"(d[43]),"+f"(d[44]),"+f"(d[45]),"+f"(d[46]),"+f"(d[47]),
      "+f"(d[48]),"+f"(d[49]),"+f"(d[50]),"+f"(d[51]),"+f"(d[52]),"+f"(d[53]),"+f"(d[54]),"+f"(d[55]),"+f"(d[56]),"+f"(d[57]),"+f"(d[58]),"+f"(d[59]),
      "+f"(d[60]),"+f"(d[61]),"+f"(d[62]),"+f"(d[63])
    : "r"(alo), "r"(blo), "r"(sd), "n"(TB), "r"(DESC_HI), "n"(TA));
}
template <int TB> __device__ __forceinline__ void wgmma_rs128(float (&d)[64], uint32_t a0, uint32_t a1, uint32_t a2, uint32_t a3, uint32_t blo, int sd) {
  asm volatile("{\n.reg .pred p;\n.reg .b64 db;\n"
    "setp.ne.b32 p, %69, 0;\nmov.b64 db, {%68, %71};\n"
    "wgmma.mma_async.sync.aligned.m64n128k16.f32.bf16.bf16 "
    "{%0,%1,%2,%3,%4,%5,%6,%7,%8,%9,%10,%11,%12,%13,%14,%15,%16,%17,%18,%19,%20,%21,%22,%23,"
    "%24,%25,%26,%27,%28,%29,%30,%31,%32,%33,%34,%35,%36,%37,%38,%39,%40,%41,%42,%43,%44,%45,%46,%47,"
    "%48,%49,%50,%51,%52,%53,%54,%55,%56,%57,%58,%59,%60,%61,%62,%63}, "
    "{%64,%65,%66,%67}, db, p, 1, 1, %70;\n}\n"
    : "+f"(d[0]),"+f"(d[1]),"+f"(d[2]),"+f"(d[3]),"+f"(d[4]),"+f"(d[5]),"+f"(d[6]),"+f"(d[7]),"+f"(d[8]),"+f"(d[9]),"+f"(d[10]),"+f"(d[11]),
      "+f"(d[12]),"+f"(d[13]),"+f"(d[14]),"+f"(d[15]),"+f"(d[16]),"+f"(d[17]),"+f"(d[18]),"+f"(d[19]),"+f"(d[20]),"+f"(d[21]),"+f"(d[22]),"+f"(d[23]),
      "+f"(d[24]),"+f"(d[25]),"+f"(d[26]),"+f"(d[27]),"+f"(d[28]),"+f"(d[29]),"+f"(d[30]),"+f"(d[31]),"+f"(d[32]),"+f"(d[33]),"+f"(d[34]),"+f"(d[35]),
      "+f"(d[36]),"+f"(d[37]),"+f"(d[38]),"+f"(d[39]),"+f"(d[40]),"+f"(d[41]),"+f"(d[42]),"+f"(d[43]),"+f"(d[44]),"+f"(d[45]),"+f"(d[46]),"+f"(d[47]),
      "+f"(d[48]),"+f"(d[49]),"+f"(d[50]),"+f"(d[51]),"+f"(d[52]),"+f"(d[53]),"+f"(d[54]),"+f"(d[55]),"+f"(d[56]),"+f"(d[57]),"+f"(d[58]),"+f"(d[59]),
      "+f"(d[60]),"+f"(d[61]),"+f"(d[62]),"+f"(d[63])
    : "r"(a0), "r"(a1), "r"(a2), "r"(a3), "r"(blo), "r"(sd), "n"(TB), "r"(DESC_HI));
}
template <int TB, int TA = 0> __device__ __forceinline__ void wgmma_ss192(float (&d)[96], uint32_t alo, uint32_t blo, int sd) {
  asm volatile("{\n.reg .pred p;\n.reg .b64 da, db;\n"
    "setp.ne.b32 p, %98, 0;\nmov.b64 da, {%96, %100};\nmov.b64 db, {%97, %100};\n"
    "wgmma.mma_async.sync.aligned.m64n192k16.f32.bf16.bf16 "
    "{%0,%1,%2,%3,%4,%5,%6,%7,%8,%9,%10,%11,%12,%13,%14,%15,%16,%17,%18,%19,%20,%21,%22,%23,"
    "%24,%25,%26,%27,%28,%29,%30,%31,%32,%33,%34,%35,%36,%37,%38,%39,%40,%41,%42,%43,%44,%45,%46,%47,"
    "%48,%49,%50,%51,%52,%53,%54,%55,%56,%57,%58,%59,%60,%61,%62,%63,%64,%65,%66,%67,%68,%69,%70,%71,"
    "%72,%73,%74,%75,%76,%77,%78,%79,%80,%81,%82,%83,%84,%85,%86,%87,%88,%89,%90,%91,%92,%93,%94,%95}, "
    "da, db, p, 1, 1, %101, %99;\n}\n"
    : "+f"(d[0]),"+f"(d[1]),"+f"(d[2]),"+f"(d[3]),"+f"(d[4]),"+f"(d[5]),"+f"(d[6]),"+f"(d[7]),"+f"(d[8]),"+f"(d[9]),"+f"(d[10]),"+f"(d[11]),
      "+f"(d[12]),"+f"(d[13]),"+f"(d[14]),"+f"(d[15]),"+f"(d[16]),"+f"(d[17]),"+f"(d[18]),"+f"(d[19]),"+f"(d[20]),"+f"(d[21]),"+f"(d[22]),"+f"(d[23]),
      "+f"(d[24]),"+f"(d[25]),"+f"(d[26]),"+f"(d[27]),"+f"(d[28]),"+f"(d[29]),"+f"(d[30]),"+f"(d[31]),"+f"(d[32]),"+f"(d[33]),"+f"(d[34]),"+f"(d[35]),
      "+f"(d[36]),"+f"(d[37]),"+f"(d[38]),"+f"(d[39]),"+f"(d[40]),"+f"(d[41]),"+f"(d[42]),"+f"(d[43]),"+f"(d[44]),"+f"(d[45]),"+f"(d[46]),"+f"(d[47]),
      "+f"(d[48]),"+f"(d[49]),"+f"(d[50]),"+f"(d[51]),"+f"(d[52]),"+f"(d[53]),"+f"(d[54]),"+f"(d[55]),"+f"(d[56]),"+f"(d[57]),"+f"(d[58]),"+f"(d[59]),
      "+f"(d[60]),"+f"(d[61]),"+f"(d[62]),"+f"(d[63]),"+f"(d[64]),"+f"(d[65]),"+f"(d[66]),"+f"(d[67]),"+f"(d[68]),"+f"(d[69]),"+f"(d[70]),"+f"(d[71]),
      "+f"(d[72]),"+f"(d[73]),"+f"(d[74]),"+f"(d[75]),"+f"(d[76]),"+f"(d[77]),"+f"(d[78]),"+f"(d[79]),"+f"(d[80]),"+f"(d[81]),"+f"(d[82]),"+f"(d[83]),
      "+f"(d[84]),"+f"(d[85]),"+f"(d[86]),"+f"(d[87]),"+f"(d[88]),"+f"(d[89]),"+f"(d[90]),"+f"(d[91]),"+f"(d[92]),"+f"(d[93]),"+f"(d[94]),"+f"(d[95])
    : "r"(alo), "r"(blo), "r"(sd), "n"(TB), "r"(DESC_HI), "n"(TA));
}

struct Ctx {
  uint32_t sm;
  uint32_t bar;
  uint32_t rbar;
  int cl, rank, wg, warp, lane, phases;
};
__device__ __forceinline__ void release(const Ctx& c, int b, int cnt = 1) {
  if (c.lane < 2) mbar_arrive_cl(c.rbar + b * 8, cnt);
}
#define HK 5
#define NPRO 6
#define ZLEAD 14
#define PFM 7
#define PF1 1
constexpr float SM_SCALE = 0.08838834764831845f * 1.4426950408889634f;
constexpr float SM_HI = 1.8446744e19f, SM_LO = 5.4210109e-20f;
constexpr int ORDER = 1;

__device__ __forceinline__ void stage_tile(const float (&a)[64], uint32_t buf, const Ctx& c, float s0, float s1) {
  const int row = (c.lane & 7) + ((c.lane >> 3) & 1) * 8;
  const uint32_t base = buf + (c.warp * 16 + row) * 128 + (((c.lane >> 4) ^ (row & 7)) << 4);
#pragma unroll
  for (int i = 0; i < 8; i++)
    stsm4((base ^ ((i & 3) << 5)) + (i >> 2) * 8192, pack_bf16(a[8 * i] * s0, a[8 * i + 1] * s0), pack_bf16(a[8 * i + 2] * s1, a[8 * i + 3] * s1),
          pack_bf16(a[8 * i + 4] * s0, a[8 * i + 5] * s0), pack_bf16(a[8 * i + 6] * s1, a[8 * i + 7] * s1));
}

__device__ __forceinline__ void p1_epilogue(const Params& p, const Ctx& c, const float (&acc)[64], int t, int type) {
  const int tile = p.s.r[c.cl].tile[t] & 63, b = c.wg * 2 + 1;
  mbar_wait(c.bar + (B_SE + b) * 8, (t & 1) ^ 1);
  if (type && tile >= 32) {
    const int r = 2 * (c.lane & 3) + ((c.lane >> 2) & 1);
    const uint32_t dst = c.sm + SM_BUF + b * 16384 + r * 128 + (((c.warp * 2) ^ r) << 4) + (c.lane >> 3) * 4;
#pragma unroll
    for (int i = 0; i < 16; i++) {
      asm volatile("st.shared.u32 [%0], %1;" ::"r"(dst + i * 1024), "r"(pack_bf16(acc[4 * i], acc[4 * i + 1])) : "memory");
      asm volatile("st.shared.u32 [%0], %1;" ::"r"((dst ^ 16) + i * 1024), "r"(pack_bf16(acc[4 * i + 2], acc[4 * i + 3])) : "memory");
    }
  } else {
    if (type) stage_tile(acc, c.sm + SM_BUF + b * 16384, c, SM_SCALE, SM_SCALE);
    else stage_tile(acc, c.sm + SM_BUF + b * 16384, c, 1.f, 1.f);
  }
  FENCE_ASYNC_SMEM();
  __syncwarp();
  if (c.lane == 0) mbar_arrive(c.bar + (B_SF + b) * 8);
}

__device__ __forceinline__ void p1_consumer(const Params& p, const Ctx& c) {
  const int n = p.s.r[c.cl].n1;
  const int type = p.s.r[c.cl].slab >> 3;
  const uint32_t bdesc = desc_lo(c.sm + SM_RING, 8192), adesc = desc_lo(c.sm + SM_BUF + 32768 + c.wg * 8192, 16);
  uint32_t A[128];
  float acc[64] = {};
  int slot = 0, par = 0;
  auto next = [&]() { if (++slot == 10) { slot = 0; par ^= 1; } };
  {
    const int row = (c.lane & 7) + ((c.lane >> 3) & 1) * 8;
    const uint32_t base = c.sm + SM_RING + (c.wg * 64 + c.warp * 16 + row) * 128 + (((c.lane >> 4) ^ (row & 7)) << 4);
    if (c.wg == 1) bar_sync(ORDER + 1, 256);
    int pa = -1, pb = -1;
    if (type) {
      mbar_wait(c.bar + B_P1F * 8, 0);
      WG_FENCE();
#pragma unroll
      for (int kk = 0; kk < 4; kk++) wgmma_ss128<1>(acc, adesc + kk * 2, bdesc + kk * 128, kk != 0);
      WG_COMMIT();
      pb = 0; slot = 1;
    }
#pragma unroll
    for (int kb = 0; kb < 8; kb++) {
      const int sa = slot;
      mbar_wait(c.bar + (B_P1F + slot) * 8, par);
      if (kb == 0) PROF(c.wg, 5);
      next();
      mbar_wait(c.bar + (B_P1F + slot) * 8, par);
      PROF(c.wg, 6 + 2 * kb);
      WG_FENCE();
#pragma unroll
      for (int kk = 0; kk < 4; kk++)
        wgmma_ss128<1>(acc, desc_lo(c.sm + SM_RING + c.wg * 8192, 16) + sa * 1024 + kk * 2, bdesc + slot * 1024 + kk * 128, (kb | kk) != 0 ? 1 : type);
      WG_COMMIT();
      if (kb == 1 && c.wg == 0) bar_arrive(ORDER + 1, 256);
#pragma unroll
      for (int kk = 0; kk < 4; kk++) ldsm4((base ^ (kk << 5)) + sa * 16384, A[kb * 16 + kk * 4], A[kb * 16 + kk * 4 + 1], A[kb * 16 + kk * 4 + 2], A[kb * 16 + kk * 4 + 3]);
      WG_WAIT(1);
      if (kb > 0) release(c, B_P1E + pa);
      if (kb > 0 || pb >= 0) release(c, B_P1E + pb);
      pa = sa; pb = slot;
      next();
    }
    WG_WAIT(0);
    __syncwarp();
    release(c, B_P1E + pa);
    release(c, B_P1E + pb);
    pin(acc);
    PROF(c.wg, 1);
    p1_epilogue(p, c, acc, 0, type);
    PROF(c.wg, 2);
  }
  for (int t = 1; t < n; t++) {
    bar_sync(ORDER + c.wg, 256);
    int prev1 = -1, prev2 = -1;
    if (type) {
      mbar_wait(c.bar + (B_P1F + slot) * 8, par);
      WG_FENCE();
#pragma unroll
      for (int kk = 0; kk < 4; kk++) wgmma_ss128<1>(acc, adesc + kk * 2, bdesc + slot * 1024 + kk * 128, kk != 0);
      WG_COMMIT();
      prev1 = slot;
      next();
    }
#pragma unroll
    for (int kb = 0; kb < 8; kb++) {
      mbar_wait(c.bar + (B_P1F + slot) * 8, par);
      WG_FENCE();
      const uint32_t d = bdesc + slot * 1024;
#pragma unroll
      for (int kk = 0; kk < 4; kk++)
        wgmma_rs128<1>(acc, A[kb * 16 + kk * 4], A[kb * 16 + kk * 4 + 1], A[kb * 16 + kk * 4 + 2], A[kb * 16 + kk * 4 + 3], d + kk * 128, (kb | kk) != 0 ? 1 : type);
      WG_COMMIT();
      if (kb == HK) {
        if (t + 1 < n || c.wg == 0) bar_arrive(ORDER + (c.wg ^ 1), 256);
      }
      if (kb > 0) { WG_WAIT(2); if (kb > 1 || prev2 >= 0) release(c, B_P1E + prev2); }
      prev2 = prev1; prev1 = slot;
      next();
    }
    WG_WAIT(1);
    release(c, B_P1E + prev2);
    WG_WAIT(0);
    pin(acc);
    release(c, B_P1E + prev1);
    p1_epilogue(p, c, acc, t, type);
    PROF(c.wg, 3);
  }
}

__device__ __forceinline__ void p1_producer(const Params& p, const Ctx& c) {
  const int n = p.s.r[c.cl].n1;
  const int type = p.s.r[c.cl].slab >> 3, grp = p.s.r[c.cl].slab & 7;
  int slot = NPRO % 10, par = NPRO < 10;
#pragma unroll 1
  for (int t = 0; t < n; t++) {
    const int tile = p.s.r[c.cl].tile[t] & 63;
    const CUtensorMap* m = &p.map_w[type * 2 + (tile >> 5)];
    const int n0 = (tile & 31) * 128 + c.rank * 64;
    const int ptile = p.s.r[c.cl].tile[t + PF1 < n ? t + PF1 : t];
    const CUtensorMap* pm = &p.map_w[type * 2 + ((ptile >> 5) & 1)];
    if (t == 7 && (c.phases & 16)) flag_wait<true>(F_GATE, 256);
#pragma unroll 1
    for (int kb = t ? -type : (NPRO - type) >> 1; kb < 8; kb++) {
      if (t == 0 && 2 * kb + type >= NPRO) {
        mbar_wait(c.bar + (B_P1E + slot) * 8, par);
        mbar_expect(c.bar + (B_P1F + slot) * 8, 16384);
        tma2d(c.sm + SM_RING + slot * 16384, &p.map_a[type], kb * 64, grp * 256 + c.rank * 128, c.bar + (B_P1F + slot) * 8);
        if (++slot == 10) { slot = 0; par ^= 1; }
      }
      mbar_wait(c.bar + (B_P1E + slot) * 8, par);
      mbar_expect(c.bar + (B_P1F + slot) * 8, 16384);
      tma2d_mc(c.sm + SM_RING + slot * 16384 + c.rank * 8192, m, n0, kb < 0 ? 512 : kb * 64, c.bar + (B_P1F + slot) * 8);
      if (t == 0 && kb == 1) PROF(2, 61);
      if (t == 0 && kb == 3) PROF(2, 62);
      if (t + PF1 < n && t > 0 && ((ptile & 64) || ((ptile & 128) && ((kb ^ grp) & PFM) == 0))) tma2d_prefetch(pm, (ptile & 31) * 128 + c.rank * 64, kb < 0 ? 512 : kb * 64);
      if (++slot == 10) { slot = 0; par ^= 1; }
    }
  }
}

__device__ __forceinline__ void p1_storer(const Params& p, const Ctx& c) {
  const int n = p.s.r[c.cl].n1;
  const int type = p.s.r[c.cl].slab >> 3, grp = p.s.r[c.cl].slab & 7;
  for (int i = 0; i < 2 * n; i++) {
    const int t = i >> 1, w = i & 1, b = w * 2 + 1;
    const int tile = p.s.r[c.cl].tile[t] & 63;
    mbar_wait(c.bar + (B_SF + b) * 8, t & 1);
    const uint32_t src = c.sm + SM_BUF + b * 16384;
    int f = (type ? F_Q : F_KV) + (tile & 31) * 8 + grp;
    if (type == 0) {
      const int prev = p.s.prev[tile & 31][grp];
      if (prev != 255 && w == 0) {
        if (grp >= 2) flag_wait<false>(F_RD + prev * 8 + grp, 8 - grp);
        else flag_wait<false>(F_CTX + max(c.lane & 7, grp) * 64 + prev, 4);
      }
      uint8_t* dst = g_KV + (size_t)(((tile & 32) + p.s.slot[tile & 31][grp]) * 16 + grp * 2 + c.rank) * 32768 + w * 8192;
      bulk_store(dst, src, 8192);
      bulk_store(dst + 16384, src + 8192, 8192);
    } else if (tile < 32) {
      bulk_store(g_Q + (size_t)(tile * 32 + grp * 4 + c.rank * 2 + w) * 16384, src, 16384);
    } else {
      tma3d_store(&p.map_t[2], src, 8 + (grp * 4 + c.rank * 2 + w) * 32, 0, (tile - 32) * 64);
      f = F_QKVA + grp * 4 + ((0xE4390900u >> (2 * (tile - 30))) & 3);
    }
    BULK_COMMIT();
    BULK_WAIT(0);
    mbar_arrive_one(c.bar + (B_SE + b) * 8);
    flag_add_rx(f);
  }
}

__device__ __forceinline__ int p2_buf(int w, int i) { return w * 2 + (i & 1); }
__device__ __forceinline__ int p2_blk(int rank, int w, int i) { return ((i ^ w) & 1) == 0 ? 3 - rank : rank; }

template <int N>
__device__ __forceinline__ void row_max(const float (&s)[N], float& m0, float& m1) {
  float a0 = fmaxf(s[0], s[1]), a1 = fmaxf(s[2], s[3]);
#pragma unroll
  for (int i = 1; i < N / 4; i++) {
    m0 = fmaxf(m0, s[4 * i]); a0 = fmaxf(a0, s[4 * i + 1]);
    m1 = fmaxf(m1, s[4 * i + 2]); a1 = fmaxf(a1, s[4 * i + 3]);
  }
  m0 = fmaxf(m0, a0); m1 = fmaxf(m1, a1);
  m0 = fmaxf(m0, __shfl_xor_sync(0xffffffffu, m0, 1));
  m1 = fmaxf(m1, __shfl_xor_sync(0xffffffffu, m1, 1));
  m0 = fmaxf(m0, __shfl_xor_sync(0xffffffffu, m0, 2));
  m1 = fmaxf(m1, __shfl_xor_sync(0xffffffffu, m1, 2));
}
template <bool SUB, int N>
__device__ __forceinline__ void row_exp(const float (&s)[N], uint32_t (&P)[32], float m0, float m1, float& t0, float& t1) {
  float u0 = 0.f, u1 = 0.f;
  t0 = t1 = 0.f;
#pragma unroll
  for (int i = 0; i < N / 4; i++) {
    const float e0 = ex2(SUB ? s[4 * i] - m0 : s[4 * i]), e1 = ex2(SUB ? s[4 * i + 1] - m0 : s[4 * i + 1]);
    const float e2 = ex2(SUB ? s[4 * i + 2] - m1 : s[4 * i + 2]), e3 = ex2(SUB ? s[4 * i + 3] - m1 : s[4 * i + 3]);
    if (i == 0) { t0 = e0; u0 = e1; t1 = e2; u1 = e3; }
    else { t0 += e0; u0 += e1; t1 += e2; u1 += e3; }
    P[2 * i] = pack_bf16(e0, e1);
    P[2 * i + 1] = pack_bf16(e2, e3);
  }
#pragma unroll
  for (int i = N / 2; i < 32; i++) P[i] = 0;
  pin(P);
  t0 += u0; t1 += u1;
}
template <int N>
__device__ __forceinline__ void causal_mask(float (&s)[N], int thr) {
#pragma unroll
  for (int i = 0; i < 8; i++) {
    if (8 * i > thr) s[N - 32 + 4 * i] = -INFINITY;
    if (8 * i + 1 > thr) s[N - 32 + 4 * i + 1] = -INFINITY;
    if (8 * i - 8 > thr) s[N - 32 + 4 * i + 2] = -INFINITY;
    if (8 * i - 7 > thr) s[N - 32 + 4 * i + 3] = -INFINITY;
  }
}
__device__ __forceinline__ void issue_qk(float (&s)[32], uint32_t qd, uint32_t kd) {
  WG_FENCE();
#pragma unroll
  for (int kk = 0; kk < 8; kk++) wgmma_ss64<0>(s, qd + (kk >> 2) * 512 + (kk & 3) * 2, kd + (kk >> 2) * 1024 + (kk & 3) * 2, kk != 0);
  WG_COMMIT();
}
__device__ __forceinline__ void issue_qk(float (&s)[64], uint32_t qd, uint32_t kd) {
  WG_FENCE();
#pragma unroll
  for (int kk = 0; kk < 8; kk++) wgmma_ss128<0>(s, qd + (kk >> 2) * 512 + (kk & 3) * 2, kd + (kk >> 2) * 1024 + (kk & 3) * 2, kk != 0);
  WG_COMMIT();
}
template <int NK>
__device__ __forceinline__ void issue_pv(float (&o)[64], const uint32_t (&P)[32], uint32_t vd, int acc) {
  WG_FENCE();
#pragma unroll
  for (int kk = 0; kk < NK; kk++) wgmma_rs128<1>(o, P[4 * kk], P[4 * kk + 1], P[4 * kk + 2], P[4 * kk + 3], vd + kk * 128, kk != 0 ? 1 : acc);
  WG_COMMIT();
}
__device__ __forceinline__ void stage_done(const Ctx& c, int b) {
  FENCE_ASYNC_SMEM();
  __syncwarp();
  if (c.lane == 0) mbar_arrive(c.bar + (B_SF + b) * 8);
}
__device__ __forceinline__ void p2_epilogue(const float (&o)[64], float s0, float s1, const Ctx& c, int b) {
  stage_tile(o, c.sm + SM_BUF + b * 16384, c, s0, s1);
  stage_done(c, b);
}

struct P2State {
  float m0, m1, l0, l1;
  bool shift;
  float e0, e1;
  int ks;
  int wi, ai;
  uint32_t wb, ab;
  uint32_t qd;
};
#define PROFZ()
__device__ __forceinline__ int wrap5(int q) { return q >= 5 ? q - 5 : q; }
__device__ __forceinline__ void turn_wait(uint32_t ring, int i) { mbar_wait(ring + (i & 3) * 8, (i >> 2) & 1); }
__device__ __forceinline__ void turn_pass(const Ctx& c, uint32_t ring, int i) { if (c.lane == 0) mbar_arrive(ring + (i & 3) * 8); }
__device__ __forceinline__ void p2_scales(P2State& z) {
  float l0 = z.l0, l1 = z.l1;
  l0 += __shfl_xor_sync(0xffffffffu, l0, 1);
  l1 += __shfl_xor_sync(0xffffffffu, l1, 1);
  l0 += __shfl_xor_sync(0xffffffffu, l0, 2);
  l1 += __shfl_xor_sync(0xffffffffu, l1, 2);
  asm("rcp.approx.ftz.f32 %0, %1;" : "=f"(z.e0) : "f"(l0));
  asm("rcp.approx.ftz.f32 %0, %1;" : "=f"(z.e1) : "f"(l1));
}
template <int N>
__device__ __forceinline__ void p2_first(const Ctx& c, P2State& z, float (&o)[64], uint32_t (&Pc)[32], uint32_t (&Pn)[32],
                                         int ks, int vs, int cnt, int acc) {
  float s[N] = {};
  issue_qk(s, z.qd, desc_lo(c.sm + SM_RING, 16) + ks * 2048);
  if (vs >= 0) {
    p2_scales(z);
    issue_pv<8>(o, Pc, desc_lo(c.sm + SM_RING, 16384) + vs * 2048, acc);
  } else {
    WG_COMMIT();
  }
  mbar_expect(z.ab + (z.ai++ & 3) * 8, cnt == 1 ? 8192 : 0);
  PROFZ();
  WG_WAIT(1);
  PROFZ();
  pin(s);
  release(c, B_P2E + ks, cnt);
  causal_mask(s, c.warp * 16 + (c.lane >> 2) - 2 * (c.lane & 3));
  z.m0 = z.m1 = 0.f;
  row_exp<false>(s, Pn, 0.f, 0.f, z.l0, z.l1);
  z.shift = __any_sync(0xffffffffu, !(z.l0 + z.l1 <= SM_HI) || ((c.lane & 3) == 0 && !(fminf(z.l0, z.l1) >= SM_LO)));
  if (__builtin_expect(z.shift, 0)) {
    z.m0 = z.m1 = -INFINITY;
    row_max(s, z.m0, z.m1);
    row_exp<true>(s, Pn, z.m0, z.m1, z.l0, z.l1);
  }
  WG_WAIT(0);
  pin(o);
  if (vs >= 0) release(c, B_P2E + vs, 1);
}

template <bool SECOND>
__device__ __forceinline__ void p2_turn(const Ctx& c, P2State& z, float (&o)[64], uint32_t (&Pc)[32], uint32_t (&Pn)[32],
                                        int eb = -1, bool half = false, int vcnt = 1) {
  float s[64] = {};
  const int ks = z.ks, vs = wrap5(ks + 1);
  PROFZ();
  turn_wait(z.wb, z.wi++);
  PROFZ();
  issue_qk(s, z.qd, desc_lo(c.sm + SM_RING, 16) + ks * 2048);
  const uint32_t vd = desc_lo(c.sm + SM_RING, 16384) + vs * 2048;
  if (SECOND) {
    if (eb >= 0) stage_tile(o, c.sm + SM_BUF + eb * 16384, c, z.e0, z.e1);
    if (half) issue_pv<4>(o, Pc, vd, 0); else issue_pv<8>(o, Pc, vd, 0);
  } else {
    issue_pv<8>(o, Pc, vd, 1);
  }
  turn_pass(c, z.ab, z.ai++);
  if (SECOND) { if (eb >= 0) stage_done(c, eb); }
  PROFZ();
  z.ks = wrap5(ks + 2);
  WG_WAIT(1);
  PROFZ();
  pin(s);
  release(c, B_P2E + ks, 1);
  float t0, t1, a0 = 1.f, a1 = 1.f;
  row_exp<false>(s, Pn, 0.f, 0.f, t0, t1);
  z.shift = __any_sync(0xffffffffu, z.shift || !(t0 + t1 <= SM_HI));
  const bool redo = z.shift;
  if (__builtin_expect(redo, 0)) {
    float n0 = z.m0, n1 = z.m1;
    row_max(s, n0, n1);
    a0 = ex2(z.m0 - n0); a1 = ex2(z.m1 - n1);
    z.m0 = n0; z.m1 = n1;
    z.l0 *= a0; z.l1 *= a1;
    row_exp<true>(s, Pn, z.m0, z.m1, t0, t1);
  }
  WG_WAIT(0);
  pin(o);
  release(c, B_P2E + vs, vcnt);
  if (__builtin_expect(redo, 0)) {
#pragma unroll
    for (int i = 0; i < 16; i++) { o[4 * i] *= a0; o[4 * i + 1] *= a0; o[4 * i + 2] *= a1; o[4 * i + 3] *= a1; }
  }
  z.l0 += t0; z.l1 += t1;
}
__device__ __forceinline__ void copy_p(uint32_t (&d)[32], const uint32_t (&s)[32], int zero) {
#pragma unroll
  for (int i = 0; i < 32; i++) asm volatile("add.s32 %0, %1, %2;" : "=r"(d[i]) : "r"(s[i]), "r"(zero));
}

__device__ __forceinline__ void p2_consumer(const Params& p, const Ctx& c, int rot) {
  const int nit = p.s.r[c.cl].n2;
  const uint32_t fring = c.bar + B_P2F * 8, oring = c.bar + B_ORD * 8;
  float o[64] = {};
  uint32_t Pa[32] = {}, Pb[32] = {};
  P2State z;
  z.e0 = z.e1 = z.l0 = z.l1 = 0.f; z.ks = rot; z.shift = false;
  int acc = 0, n = 0;
  for (int it = 0; it < nit; it++) {
    const int j = p.s.r[c.cl].item[it] & 7, blk = p2_blk(c.rank, c.wg, it);
    const int lng = ((it ^ c.wg) & 1) ^ 1;
    z.qd = desc_lo(c.sm + SM_BUF, 16) + p2_buf(c.wg, it) * 1024;
    if (lng) { z.wb = oring; z.wi = n - it; z.ab = fring; z.ai = n + 1; }
    else { z.wb = fring; z.wi = n + 2; z.ab = oring; z.ai = n - it; }
    PROFZ();
    mbar_wait(c.bar + (B_QF + p2_buf(c.wg, it)) * 8, (it >> 1) & 1);
    turn_wait(fring, n + 1 - lng);
    PROFZ();
    const int vs = it ? wrap5(z.ks + 1) : -1, ks = lng ? z.ks : wrap5(z.ks + (it ? 2 : 1));
    if (blk & 1) p2_first<64>(c, z, o, Pa, Pb, ks, vs, 1 + lng, acc);
    else p2_first<32>(c, z, o, Pa, Pb, ks, vs, 1 + lng, acc);
    z.ks = wrap5(ks + (it == 0 && lng ? 1 : 2));
    PROF(c.wg, 24 + it);
    n += 2 * j + 2;
    int left = 2 * j + lng;
    acc = left != 0;
    if (left == 0) { copy_p(Pa, Pb, p.zero); continue; }
    p2_turn<true>(c, z, o, Pb, Pa, it > 0 ? p2_buf(c.wg, it - 1) : -1, !(blk & 1), 1 + lng);
    while (--left > 0) {
      p2_turn<false>(c, z, o, Pa, Pb);
      if (--left == 0) { copy_p(Pa, Pb, p.zero); break; }
      p2_turn<false>(c, z, o, Pb, Pa);
    }
  }
  {
    if (!acc && nit > 1) p2_epilogue(o, z.e0, z.e1, c, p2_buf(c.wg, nit));
    turn_wait(z.wb, z.wi);
    issue_pv<8>(o, Pa, desc_lo(c.sm + SM_RING, 16384) + z.ks * 2048, acc);
    if (((nit - 1) ^ c.wg) & 1) turn_pass(c, z.ab, z.ai);
    p2_scales(z);
    WG_WAIT(0);
    pin(o);
    release(c, B_P2E + z.ks);
    p2_epilogue(o, z.e0, z.e1, c, p2_buf(c.wg, nit - 1));
    PROF(c.wg, 24 + nit);
  }
}

__device__ __forceinline__ void p2_load_q(const Params& p, const Ctx& c, int it, int w) {
  const int item = p.s.r[c.cl].item[it], h = item >> 3, j = item & 7, b = p2_buf(w, it);
  mbar_expect(c.bar + (B_QF + b) * 8, 16384);
  bulk_load(c.sm + SM_BUF + b * 16384, g_Q + (size_t)(h * 32 + j * 4 + p2_blk(c.rank, w, it)) * 16384, 16384, c.bar + (B_QF + b) * 8, POL(4));
}
__device__ __forceinline__ void wait_p1_free(const Ctx& c, int u1, int s) {
  mbar_wait(c.bar + (B_P1E + 2 * s) * 8, ((u1 - 1 - 2 * s) / 10) & 1);
  mbar_wait(c.bar + (B_P1E + 2 * s + 1) * 8, ((u1 - 2 - 2 * s) / 10) & 1);
}
__device__ __forceinline__ void p2_producer(const Params& p, const Ctx& c, int u1, int rot) {
  const int nit = p.s.r[c.cl].n2;
  int slot = rot, cnt = 0, par = 1, n = 0;
  const uint8_t* pv = nullptr;
  bool pl = false;
  auto load = [&](const uint8_t* src, int expect, uint32_t fb, bool last) {
    if (cnt < 5) {
      if (u1) {
        wait_p1_free(c, u1, slot);
        if (cnt == 0) p2_load_q(p, c, 0, 1);
      }
      cnt++;
    } else {
      if (slot == rot) par ^= 1;
      mbar_wait(c.bar + (B_P2E + slot) * 8, par);
    }
    if (expect) mbar_expect(fb, expect);
    bulk_load_mc(c.sm + SM_RING + slot * 32768 + c.rank * 16384, src, 16384, fb, last ? POL(5) : L2_NORMAL);
    slot = wrap5(slot + 1);
  };
  for (int it = 0; it < nit; it++) {
    const int item = p.s.r[c.cl].item[it], h = item >> 3, j = item & 7;
    if (it == 1 && (c.phases & 16) && p.s.r[c.cl].n1 < 8) flag_wait<true>(F_GATE, 256);
    uint32_t ready = (c.phases & 16) ? 0u : 255u;
    if (it == 0) { if (c.phases & 16) flag_wait<false>(F_Q + item, 4); mbar_wait(c.bar + B_LAD * 8, 0); p2_load_q(p, c, 0, 0); if (!u1) p2_load_q(p, c, 0, 1); }
    for (int t = 2 * j + 1; t >= 0; t--) {
      mask_wait(ready, t >> 1, F_KV + h * 8 + (c.lane & 7), 8);
      const uint8_t* k = g_KV + (size_t)(p.s.slot[h][t >> 1] * 16 + t) * 32768 + c.rank * 16384;
      const uint32_t fb = c.bar + (B_P2F + (n & 3)) * 8;
      const bool last = (p.s.r[c.cl].last[it] >> (t >> 1)) & 1;
      load(k, pv && t != 2 * j ? 65536 : 32768, fb, last);
      if (!(t & 1) && t + 4 <= 2 * j && c.rank == 0) flag_add_rx(F_RD + h * 8 + (t >> 1) + 2);
      if (pv) load(pv, 0, t != 2 * j ? fb : c.bar + (B_ORD + ((n - 1 - it) & 3)) * 8, pl);
      pl = last;
      pv = k + (size_t)NH * 16 * 32768;
      n++;
    }
  }
  load(pv, 32768, c.bar + (B_P2F + (n & 3)) * 8, pl);
}

__device__ __forceinline__ void p2_storer(const Params& p, const Ctx& c, int sfpar) {
  const int nit = p.s.r[c.cl].n2;
  auto load_q = [&](int it, int w) {
    if (c.phases & 16) flag_wait<false>(F_Q + p.s.r[c.cl].item[it], 4);
    p2_load_q(p, c, it, w);
  };
  if (nit > 1) {
    load_q(1, 1); p2_load_q(p, c, 1, 0); }
  for (int i = 0; i < 2 * nit; i++) {
    const int it = i >> 1, w = (it ^ i ^ 1) & 1, b = p2_buf(w, it);
    const int item = p.s.r[c.cl].item[it], h = item >> 3, j = item & 7;
    mbar_wait(c.bar + (B_SF + b) * 8, (sfpar >> b) & 1);
    sfpar ^= 1 << b;
    bulk_store(g_Q + (size_t)(h * 32 + j * 4 + p2_blk(c.rank, w, it)) * 16384, c.sm + SM_BUF + b * 16384, 16384, POL(1));
    BULK_COMMIT();
    BULK_WAIT(0);
    flag_add_rx(F_CTX + j * 64 + h);
    if ((i & 1) && it + 2 < nit) { load_q(it + 2, w); p2_load_q(p, c, it + 2, w ^ 1); }
  }
  release(c, B_DONE);
}

__device__ __forceinline__ int p3_pos(int i, int x) { return i < 4 ? (i + x) & 3 : 4; }
__device__ __forceinline__ void p3_consumer(const Params& p, const Ctx& c, int x) {
  const bool first = p.s.r[c.cl].p3 >= 24;
  const int tile = p.s.r[c.cl].p3 - (first ? 24 : 0), j = tile / 3, nt = tile - 3 * j;
  const int na = first ? 9 : 0, nb = 2 * (p.s.task[c.cl][1] - p.s.task[c.cl][0]);
  const uint32_t ad = desc_lo(c.sm + SM_RING + c.wg * 8192, 16), bd = desc_lo(c.sm + SM_RING + 16384, 4096);
  float acc[96] = {};
  int slot = 0, par = 0, prev = 0;
  float g0 = 0.f, g1 = 0.f;
  const int hold = c.wg && LAG ? na + nb - LAG : -1, pass = c.wg || !LAG ? -1 : na + nb - 1;
#pragma unroll 1
  for (int kb = 0; kb < nb; kb++) {
    if (kb == hold) bar_sync(6, 256);
    mbar_wait(c.bar + (B_P3F + slot) * 8, par);
    if (kb == 0) PROF(c.wg, 39);
    WG_FENCE();
#pragma unroll
    for (int kk = 0; kk < 4; kk++) wgmma_ss192<1>(acc, ad + p3_pos(slot, x) * 2560 + kk * 2, bd + p3_pos(slot, x) * 2560 + (kk >> 1) * 768 + (kk & 1) * 128, kk != 0 ? 1 : kb != 0);
    WG_COMMIT();
    if (kb == pass) bar_arrive(6, 256);
    WG_WAIT(1);
    if (kb > 0) release(c, B_P3E + prev);
    else {
      const float* g = g_gate + j * 256 + c.rank * 128 + c.wg * 64 + c.warp * 16 + (c.lane >> 2);
      g0 = __ldcg(g); g1 = __ldcg(g + 8);
    }
    prev = slot;
    if (++slot == 5) { slot = 0; par ^= 1; }
  }
  WG_WAIT(0);
  pin(acc);
  g0 = 1.f - g0; g1 = 1.f - g1;
#pragma unroll
  for (int i = 0; i < 24; i++) { acc[4 * i] *= g0; acc[4 * i + 1] *= g0; acc[4 * i + 2] *= g1; acc[4 * i + 3] *= g1; }
#pragma unroll 1
  for (int kb = nb; kb < nb + na; kb++) {
    if (kb == hold) bar_sync(6, 256);
    mbar_wait(c.bar + (B_P3F + slot) * 8, par);
    if (kb == 0) PROF(c.wg, 39);
    WG_FENCE();
#pragma unroll
    for (int kk = 0; kk < 4; kk++) wgmma_ss192<1, 1>(acc, ad + p3_pos(slot, x) * 2560 + kk * 128, bd + p3_pos(slot, x) * 2560 + (kk >> 1) * 768 + (kk & 1) * 128, 1);
    WG_COMMIT();
    if (kb == pass) bar_arrive(6, 256);
    WG_WAIT(1);
    if (kb > 0) release(c, B_P3E + prev);
    prev = slot;
    if (++slot == 5) { slot = 0; par ^= 1; }
  }
  WG_WAIT(0);
  pin(acc);
  PROF(c.wg, 40);
  if (first) bar_sync(4 + c.wg, 128);
  mbar_wait(c.bar + B_OUT * 8, 0);
  const int row = (c.lane & 7) + ((c.lane >> 3) & 1) * 8;
  const uint32_t wbase = c.sm + SM_RING + c.wg * 8192 + c.warp * 2048;
  const uint32_t base = wbase + row * 128 + (((c.lane >> 4) ^ (row & 7)) << 4);
#pragma unroll
  for (int i = 0; i < 12; i++) {
    stsm4((base ^ ((i & 3) << 5)) + (i >> 2) * 40960, pack_bf16(acc[8 * i], acc[8 * i + 1]), pack_bf16(acc[8 * i + 2], acc[8 * i + 3]),
          pack_bf16(acc[8 * i + 4], acc[8 * i + 5]), pack_bf16(acc[8 * i + 6], acc[8 * i + 7]));
    if ((i & 3) == 3) {
      FENCE_ASYNC_SMEM();
      bar_sync(4 + c.wg, 128);
      if (c.warp == (i >> 2)) tma2d_add(&p.map_out, c.sm + SM_RING + c.wg * 8192 + c.warp * 40960, nt * 192 + c.warp * 64, j * 256 + c.rank * 128 + c.wg * 64);
    }
  }
  BULK_COMMIT();
  PROF(c.wg, 43);
  BULK_WAIT_READ(0);
  PROF(c.wg, 44);
}

__device__ __forceinline__ void p3_producer(const Params& p, const Ctx& c, int u1, int u2, int rot, int x) {
  const bool first = p.s.r[c.cl].p3 >= 24;
  const int tile = p.s.r[c.cl].p3 - (first ? 24 : 0), j = tile / 3, nt = tile - 3 * j;
  int slot = 0, par = 1, cnt = 0;
  auto wait_free = [&](int s) {
    const int f = wrap5(s + 5 - rot);
    if (f < u2) mbar_wait(c.bar + (B_P2E + s) * 8, ((u2 - 1 - f) / 5) & 1);
    else if (u1) wait_p1_free(c, u1, s);
  };
  asm volatile(ELECT("prefetch.tensormap [%0];") ::"l"(&p.map_o[0]) : "memory");
  asm volatile(ELECT("prefetch.tensormap [%0];") ::"l"(&p.map_out) : "memory");
  if ((c.phases & 16) && p.s.r[c.cl].n1 < 8 && p.s.r[c.cl].n2 < 2) flag_wait<true>(F_GATE, 256);
  uint32_t ready = (c.phases & 16) ? 0u : ~0u;
  const int q1 = p.s.task[c.cl][1] - !first;
  for (int q = p.s.task[c.cl][0]; q <= q1; q++) {
    const bool brA = first && q == q1;
    const int g = brA ? 32 : p.s.p3_order[j][q];
    if (brA) { if (c.phases & 16) flag_wait<false>(F_CTX + j * 64 + 32, 16); }
    else mask_wait(ready, g, F_CTX + j * 64 + c.lane, 4);
    const int nk = brA ? 9 : 2, k0 = (brA ? 0 : g * 128) + c.rank * 32;
    const uint8_t* a = brA ? g_oA + (j * 4 + c.rank * 2) * 73728 : g_Q + (size_t)(g * 32 + j * 4 + c.rank * 2) * 16384;
    const CUtensorMap* m = &p.map_o[brA];
    for (int i = 0; i < nk; i++) {
      const uint32_t st = c.sm + SM_RING + p3_pos(slot, x) * 40960, fb = c.bar + (B_P3F + slot) * 8;
      if (cnt < 4) { wait_free(p3_pos(cnt, x)); wait_free(p3_pos(cnt, x) + 1); }
      else if (cnt == 4) mbar_wait(c.bar + B_DONE * 8, 0);
      else mbar_wait(c.bar + (B_P3E + slot) * 8, par);
      cnt++;
      mbar_expect(fb, 40960);
      bulk_load(st, a + i * 8192, 8192, fb, POL(3));
      bulk_load(st + 8192, a + (nk + i) * 8192, 8192, fb, POL(3));
      tma3d_mc(st + 16384 + c.rank * 12288, m, 0, k0 + i * 64, nt * 3, fb);
      if (++slot == 5) { slot = 0; par ^= 1; }
    }
  }
}

__device__ __forceinline__ float bf_lo(uint32_t w) { return __uint_as_float(w << 16); }
__device__ __forceinline__ float bf_hi(uint32_t w) { return __uint_as_float(w & 0xffff0000u); }

__device__ __forceinline__ void gate_rows(const Params& p, int row0, int lane) {
  const uint4* x = reinterpret_cast<const uint4*>(p.x + (size_t)(row0 + (lane >> 2)) * DM) + (lane & 3);
  const uint4* w = reinterpret_cast<const uint4*>(p.gate_w) + (lane & 3);
  float a = 0.f;
#pragma unroll 1
  for (int b = 0; b < 3; b++) {
    uint4 u[6];
#pragma unroll
    for (int i = 0; i < 6; i++) u[i] = __ldg(x + (b * 6 + i) * 4);
#pragma unroll
    for (int i = 0; i < 6; i++) {
      const uint4 v = __ldg(w + (b * 6 + i) * 4);
      a = fmaf(bf_lo(u[i].x), bf_lo(v.x), a); a = fmaf(bf_hi(u[i].x), bf_hi(v.x), a);
      a = fmaf(bf_lo(u[i].y), bf_lo(v.y), a); a = fmaf(bf_hi(u[i].y), bf_hi(v.y), a);
      a = fmaf(bf_lo(u[i].z), bf_lo(v.z), a); a = fmaf(bf_hi(u[i].z), bf_hi(v.z), a);
      a = fmaf(bf_lo(u[i].w), bf_lo(v.w), a); a = fmaf(bf_hi(u[i].w), bf_hi(v.w), a);
    }
  }
  a += __shfl_xor_sync(0xffffffffu, a, 1);
  a += __shfl_xor_sync(0xffffffffu, a, 2);
  if ((lane & 3) == 0) g_gate[row0 + (lane >> 2)] = 1.f / (1.f + __expf(-a));
}

__device__ __forceinline__ void lds10(uint32_t (&k)[10], uint32_t a) {
  asm volatile("ld.shared.v2.u32 {%0, %1}, [%10];\nld.shared.v2.u32 {%2, %3}, [%10+8];\nld.shared.v2.u32 {%4, %5}, [%10+16];\n"
               "ld.shared.v2.u32 {%6, %7}, [%10+24];\nld.shared.v2.u32 {%8, %9}, [%10+32];"
               : "=r"(k[0]), "=r"(k[1]), "=r"(k[2]), "=r"(k[3]), "=r"(k[4]), "=r"(k[5]), "=r"(k[6]), "=r"(k[7]), "=r"(k[8]), "=r"(k[9]) : "r"(a));
}
__device__ __forceinline__ void local_attn(const Params& p, const Ctx& c, int rb, int hs) {
  const int lane = c.lane, grp = rb >> 2, par = lane >> 4, i0 = 2 * (lane & 15);
  const uint32_t buf = c.sm + SM_BUF + (c.warp - 2) * 8192, bqk = c.bar + (B_LA + (c.warp - 2) * 2) * 8, bv = bqk + 8;
  const uint32_t mine = buf + 2304 + par * 160 + i0 * 4;
  const bool flags = c.phases & 16;
  auto fetch_qk = [&](int i) {
    if (flags && !(i & 1)) {
      const int q = i >> 1;
      const int tgt = q == 0 ? 24 : q == 3 ? 8 : 12;
      flag_wait<false>(F_QKVA + (grp - (grp > 0 && (rb & 3) == 0 ? par : 0)) * 4 + q, tgt);
    }
    mbar_expect(bqk, 5184);
    tma3d(buf, &p.map_t[0], rb * 32 + 8, 0, 9 * (4 * i + hs), bqk, POL(2));
    tma3d(buf + 2304, &p.map_t[1], rb * 32, 0, 288 + 9 * (4 * i + hs), bqk, POL(2));
  };
  auto fetch_v = [&](int i) { mbar_expect(bv, 2880); tma3d(buf + 5248, &p.map_t[1], rb * 32, 0, 576 + 9 * (4 * i + hs), bv, POL(2)); };
  fetch_qk(0);
  if (flags) flag_wait<true>(F_GATE, 256);
#pragma unroll 1
  for (int q = 0; q < 8; q++) {
    fetch_v(q);
    float a[8], b[8];
#pragma unroll
    for (int w = 0; w < 8; w++) a[w] = b[w] = 0.f;
    mbar_wait(bqk, q & 1);
    PROFB(1 + 2 * q);
#pragma unroll 1
    for (int j = 0; j < 9; j++) {
      uint32_t x, y, k[10];
      asm volatile("ld.shared.v2.u32 {%0, %1}, [%2];" : "=r"(x), "=r"(y) : "r"(buf + lane * 8 + j * 256));
      lds10(k, mine + j * 320);
      const float xl = bf_lo(x), xh = bf_hi(x), yl = bf_lo(y), yh = bf_hi(y);
#pragma unroll
      for (int m = 1; m < 10; m++) {
        const float kl = bf_lo(k[m]), kh = bf_hi(k[m]);
        if (m < 9) a[8 - m] = fmaf(xl, kl, fmaf(xh, kh, a[8 - m]));
        if (m > 1) b[9 - m] = fmaf(yl, kl, fmaf(yh, kh, b[9 - m]));
      }
    }
    __syncwarp();
    if (q < 7) fetch_qk(q + 1);
    constexpr float SC = 0.23570226039551584f * 1.4426950408889634f;
    const float* gp = g_gate + rb * 64 + 2 * i0 + par;
    const float ga = __ldcg(gp), gb = __ldcg(gp + 2);
    float ma = a[0], mb = b[0];
#pragma unroll
    for (int w = 1; w < 8; w++) {
      if (rb == 0) {
        if (i0 < w) a[w] = -INFINITY;
        if (i0 + 1 < w) b[w] = -INFINITY;
      }
      ma = fmaxf(ma, a[w]); mb = fmaxf(mb, b[w]);
    }
    float la = 0.f, lb = 0.f;
#pragma unroll
    for (int w = 0; w < 8; w++) {
      a[w] = ex2((a[w] - ma) * SC); b[w] = ex2((b[w] - mb) * SC);
      la += a[w]; lb += b[w];
    }
    la = __fdividef(ga, la); lb = __fdividef(gb, lb);
#pragma unroll
    for (int w = 0; w < 8; w++) { a[w] *= la; b[w] *= lb; }
    uint8_t* dst = g_oA + rb * 73728 + ((i0 & 2) + par) * 4;
    mbar_wait(bv, q & 1);
#pragma unroll 1
    for (int j = 0; j < 9; j++) {
      uint32_t v[10];
      lds10(v, mine + 2944 + j * 320);
      float a0 = 0.f, a1 = 0.f, b0 = 0.f, b1 = 0.f;
#pragma unroll
      for (int m = 1; m < 10; m++) {
        const float vl = bf_lo(v[m]), vh = bf_hi(v[m]);
        if (m < 9) { a0 = fmaf(a[8 - m], vl, a0); a1 = fmaf(a[8 - m], vh, a1); }
        if (m > 1) { b0 = fmaf(b[9 - m], vl, b0); b1 = fmaf(b[9 - m], vh, b1); }
      }
      const uint32_t wa = pack_bf16(a0, a1), wb = pack_bf16(b0, b1);
      const uint32_t got = __shfl_xor_sync(0xffffffffu, par ? wa : wb, 16);
      const uint32_t r0 = par ? got : wa, r1 = par ? wb : got;
      const int col = 18 * (4 * q + hs) + 2 * j, o = col * 128 + ((((i0 >> 2) ^ col) & 7) << 4);
      *reinterpret_cast<uint32_t*>(dst + o) = __byte_perm(r0, r1, 0x5410);
      *reinterpret_cast<uint32_t*>(dst + ((o + 128) ^ 16)) = __byte_perm(r0, r1, 0x7632);
    }
    __syncwarp();
    PROFB(2 + 2 * q);
  }
  mbar_arrive_one(c.bar + B_LAD * 8);
  flag_add(F_CTX + grp * 64 + 32);
}

__global__ void __cluster_dims__(2, 1, 1) __launch_bounds__(384, 1) fused_kernel(const __grid_constant__ Params p) {
  extern __shared__ uint8_t smem_raw[];
  Ctx c;
  c.sm = ((uint32_t)__cvta_generic_to_shared(smem_raw) + 1023u) & ~1023u;
  c.bar = c.sm + SM_BAR;
  c.lane = threadIdx.x & 31;
  const int wid = __shfl_sync(0xffffffffu, threadIdx.x >> 5, 0);
  if (wid < 6) asm volatile("prefetch.tensormap [%0];" ::"l"(&p.map_a[0] + wid) : "memory");
  c.wg = wid >> 2;
  c.warp = wid & 3;
  PROF(c.wg, 0);
  PROFG(61);
  c.cl = (blockIdx.x + (wid >> 4)) >> 1;
  c.rank = blockIdx.x & 1;
  c.rbar = mapa(c.bar, c.lane & 1);
  {
    const int w = wid, cnt = (((int)(B_CNT >> (4 * w)) - 1) & 15) + 1;
    if (w < 11) {
#pragma unroll
      for (int i = 0; i < 8; i++) asm volatile("mbarrier.init.shared::cta.b64 [%0], %1;" ::"r"(c.bar + w * 64 + i * 8), "r"(cnt));
    }
    asm volatile("fence.mbarrier_init.release.cluster;" ::: "memory");
  }
  if (c.wg == 2) PROF(2, 56);
  asm volatile("barrier.cluster.arrive.relaxed;" ::: "memory");
  c.phases = p.s.r[c.cl].phases;
  const bool do1 = p.s.r[c.cl].n1 > 0, do2 = p.s.r[c.cl].n2 > 0, do3 = p.s.r[c.cl].p3 != 255;
  if (do1 && c.wg == 2 && c.warp == 0) {
    const int type = p.s.r[c.cl].slab >> 3;
    PROF(2, 57);
    FENCE_ASYNC_SMEM();
    mbar_expect(c.bar + B_P1F * 8, type ? 32768 : 16384);
    tma2d(type ? c.sm + SM_BUF + 32768 : c.sm + SM_RING, &p.map_a[type], type ? 512 : 0, (p.s.r[c.cl].slab & 7) * 256 + c.rank * 128, c.bar + B_P1F * 8);
    PROF(2, 58);
  }
  asm volatile("barrier.cluster.wait.acquire;" ::: "memory");
  if (c.wg == 2) PROF(2, 59);
  if (do1 && c.wg == 2 && c.warp == 0) {
    const int type = p.s.r[c.cl].slab >> 3, tile = p.s.r[c.cl].tile[0] & 63;
    const CUtensorMap* m = &p.map_w[type * 2 + (tile >> 5)];
#pragma unroll 1
    for (int s = 1 - type; s < NPRO; s++) {
      const int kb = (s - type) >> 1;
      const uint32_t fb = c.bar + (B_P1F + s) * 8;
      if (s) mbar_expect(fb, 16384);
      if ((s ^ type) & 1) tma2d_mc(c.sm + SM_RING + s * 16384 + c.rank * 8192, m, (tile & 31) * 128 + c.rank * 64, kb < 0 ? 512 : kb * 64, fb);
      else tma2d(c.sm + SM_RING + s * 16384, &p.map_a[type], kb * 64, (p.s.r[c.cl].slab & 7) * 256 + c.rank * 128, fb);
    }
  }

  if (c.wg < 2) {
    PROF(c.wg, 4);
    asm volatile("setmaxnreg.inc.sync.aligned.u32 224;");
    if (c.wg == 1) {
      if (do1) bar_arrive(ORDER, 256);
      if (c.lane == 0) mbar_arrive(c.bar + B_P2F * 8);
    }
    if (do1) p1_consumer(p, c);
    if (do2) p2_consumer(p, c, p.s.r[c.cl].rot);
    if (do3) p3_consumer(p, c, p.s.r[c.cl].x3);
    PROF(c.wg, 63);
    PROFG(62);
    if (c.lane == 0) mbar_arrive(c.bar + B_FIN * 8);
    __syncwarp();
    cluster_sync();
  } else {
    asm volatile("setmaxnreg.dec.sync.aligned.u32 56;");
    if (c.warp == 0) {
      PROF(2, 60);
      if (do1) p1_producer(p, c);
      if (do2) p2_producer(p, c, p.s.r[c.cl].u1, p.s.r[c.cl].rot);
      if (do3) p3_producer(p, c, p.s.r[c.cl].u1, p.s.r[c.cl].u2, p.s.r[c.cl].rot, p.s.r[c.cl].x3);
    } else if (c.warp == 1) {
      int sfpar = 0;
      if (do1) {
        p1_storer(p, c);
        sfpar = (p.s.r[c.cl].n1 & 1) * 10;
      }
      if (do2) p2_storer(p, c, sfpar);
      else { mbar_wait(c.bar + B_LAD * 8, 0); release(c, B_DONE); }
      if (do3) {
        const int tile = p.s.r[c.cl].p3 % 24;
        if (p.s.task[c.cl][1] == 32) {
          for (int r = 0; r < (2 * (32 - p.s.task[c.cl][0]) - ZLEAD) / 5; r++) mbar_wait(c.bar + B_P3F * 8, r & 1);
          const int j = tile / 3, nt = tile - 3 * j;
          uint4* o = reinterpret_cast<uint4*>(p.out + (size_t)(j * 256 + c.rank * 128 + (c.lane >> 3)) * DM + nt * 192) + (c.lane & 7);
#pragma unroll 4
          for (int r = 0; r < 32; r++) o[r * 288] = o[r * 288 + 8] = o[r * 288 + 16] = make_uint4(0u, 0u, 0u, 0u);
          __syncwarp();
          flag_add(F_OUT + tile * 2 + c.rank);
        } else if (c.phases & 16) {
          flag_wait<false, 256>(F_OUT + tile * 2 + c.rank, 1);
        }
        mbar_arrive_one(c.bar + B_OUT * 8);
      }
    } else {
      const int bw = blockIdx.x * 2 + (c.warp - 2);
      if ((c.phases & 1) && bw < 256) {
        gate_rows(p, bw * 8, c.lane);
        __syncwarp();
        flag_add(F_GATE);
      }
      if (p.s.r[c.cl].bg != 255) local_attn(p, c, p.s.r[c.cl].bg, bw & 3);
      else if (c.lane == 0) mbar_arrive(c.bar + B_LAD * 8);
    }
    __syncwarp();
    bar_sync(3, 128);
    if (c.warp == 0 && (c.phases & 32)) {
      int last = 0;
      if (c.lane == 0) { __threadfence(); last = atomicAdd(g_flags + F_DONE, 1) == 2 * NCL - 1; }
      if (__shfl_sync(0xffffffffu, last, 0)) for (int i = c.lane; i < F_NUM; i += 32) g_flags[i] = 0;
    }
    if (c.warp == 1) mbar_wait(c.bar + B_FIN * 8, 0);
    __syncwarp();
    cluster_sync();
  }
}

SCHED_DECL Sched k_sched = {
  {{0,29,2,32,0,{248,251,0,0,0,0,0,0,0,0,0},{0,0,0,0,0,0,0,0,0,0,0},{64,35,5,39,15,8,10,13,12,1,22,9,14,18,25,29,21,27,16,26,28,17,24,30,11,23,31,19,20,0}},
   {1,29,0,14,1,{0,0,0,0,0,0,0,0,0,0,0},{0,0,0,0,0,0,0,0,0,0,0},{64,35,6,39,15,8,10,13,12,1,22,9,14,18,25,29,21,27,16,26,28,17,24,30,23,11,31,19,20,0}},
   {2,29,1,27,2,{156,0,0,0,0,0,0,0,0,0,0},{0,0,0,0,0,0,0,0,0,0,0},{64,37,3,39,15,2,10,13,12,1,22,9,14,18,25,29,21,27,16,26,28,17,24,30,23,11,31,19,20,0}},
   {3,29,1,35,3,{250,0,0,0,0,0,0,0,0,0,0},{0,0,0,0,0,0,0,0,0,0,0},{69,38,0,39,15,2,10,13,12,1,22,9,14,18,25,29,21,27,26,16,28,17,24,30,11,23,31,19,20,0}},
   {4,28,1,46,4,{91,0,0,0,0,0,0,0,0,0,0},{0,0,0,0,0,0,0,0,0,0,0},{64,35,6,39,15,10,34,12,1,9,22,14,18,25,29,21,27,26,16,28,17,24,30,11,23,31,19,20,0,0}},
   {5,27,0,21,5,{0,0,0,0,0,0,0,0,0,0,0},{0,0,0,0,0,0,0,0,0,0,0},{69,32,6,39,15,2,42,12,33,22,14,18,25,29,21,27,16,26,28,17,24,30,11,23,31,19,20,0,0,0}},
   {6,26,2,34,6,{224,196,0,0,0,0,0,0,0,0,0},{0,0,0,0,0,0,0,0,0,0,0},{67,5,135,36,8,10,45,1,41,14,18,25,29,21,27,26,16,28,17,24,75,30,23,31,19,20,0,0,0,0}},
   {7,25,2,29,7,{208,159,0,0,0,0,0,0,0,0,0},{0,128,0,0,0,0,0,0,0,0,0},{69,6,135,79,66,77,108,73,118,82,89,93,85,91,90,80,92,81,88,94,75,87,95,83,84,0,0,0,0,0}},
   {0,29,0,0,8,{0,0,0,0,0,0,0,0,0,0,0},{0,0,0,0,0,0,0,0,0,0,0},{96,6,37,4,47,40,42,45,44,33,54,41,46,50,57,61,53,59,48,58,60,49,56,62,43,55,63,51,52,0}},
   {1,29,0,4,9,{0,0,0,0,0,0,0,0,0,0,0},{0,0,0,0,0,0,0,0,0,0,0},{96,5,38,4,47,40,42,45,44,33,54,41,46,50,57,61,53,59,48,58,60,49,56,62,55,43,63,51,52,0}},
   {2,29,2,4,10,{185,162,0,0,0,0,0,0,0,0,0},{0,0,0,0,0,0,0,0,0,0,0},{96,6,35,4,47,34,42,45,44,33,54,41,46,50,57,61,53,59,48,58,60,49,56,62,55,43,63,51,52,0}},
   {3,29,0,2,11,{0,0,0,0,0,0,0,0,0,0,0},{0,0,0,0,0,0,0,0,0,0,0},{101,3,32,4,47,34,42,45,44,33,54,41,46,50,57,61,53,59,58,48,60,49,56,62,43,55,63,51,52,0}},
   {4,28,2,43,12,{88,252,0,0,0,0,0,0,0,0,0},{0,0,0,0,0,0,0,0,0,0,0},{96,5,38,4,47,106,13,44,33,41,54,46,50,57,61,53,59,58,48,60,49,56,62,43,55,63,51,52,0,0}},
   {5,27,1,44,13,{254,0,0,0,0,0,0,0,0,0,0},{127,0,0,0,0,0,0,0,0,0,0},{101,3,38,4,47,34,13,44,9,54,46,50,57,61,53,59,48,58,60,49,56,62,43,55,63,51,52,0,0,0}},
   {6,26,1,14,14,{190,0,0,0,0,0,0,0,0,0,0},{64,0,0,0,0,0,0,0,0,0,0},{99,37,103,79,40,106,76,97,86,110,50,57,61,53,59,58,48,60,49,56,107,62,55,63,51,52,0,0,0,0}},
   {7,25,1,22,15,{191,0,0,0,0,0,0,0,0,0,0},{128,0,0,0,0,0,0,0,0,0,0},{101,38,103,111,98,109,65,105,78,114,121,125,117,123,122,112,124,113,120,126,107,119,127,115,116,0,0,0,0,0}},
   {0,6,5,41,255,{32,35,111,149,199,0,0,0,0,0,0},{0,0,0,0,255,0,0,0,0,0,0},{67,38,135,36,66,34,0,0,0,0,0,0,0,0,0,0,0,0,0,0,0,0,0,0,0,0,0,0,0,0}},
   {1,6,5,1,255,{56,38,106,150,171,0,0,0,0,0,0},{0,0,0,0,15,0,0,0,0,0,0},{67,37,135,36,66,34,0,0,0,0,0,0,0,0,0,0,0,0,0,0,0,0,0,0,0,0,0,0,0,0}},
   {2,6,8,28,255,{61,18,13,147,129,226,89,152,0,0,0},{0,0,0,0,0,0,0,0,0,0,0},{69,38,135,36,8,40,0,0,0,0,0,0,0,0,0,0,0,0,0,0,0,0,0,0,0,0,0,0,0,0}},
   {3,6,4,10,255,{127,14,134,158,0,0,0,0,0,0,0},{0,0,0,127,0,0,0,0,0,0,0},{70,35,135,36,8,40,0,0,0,0,0,0,0,0,0,0,0,0,0,0,0,0,0,0,0,0,0,0,0,0}},
   {4,8,6,9,255,{120,87,105,75,212,93,0,0,0,0,0},{0,0,0,0,0,63,0,0,0,0,0},{67,37,135,36,8,40,2,45,0,0,0,0,0,0,0,0,0,0,0,0,0,0,0,0,0,0,0,0,0,0}},
   {5,10,4,3,255,{16,124,151,168,0,0,0,0,0,0,0},{0,0,0,0,0,0,0,0,0,0,0},{64,35,135,36,8,40,10,45,1,41,0,0,0,0,0,0,0,0,0,0,0,0,0,0,0,0,0,0,0,0}},
   {6,10,7,20,255,{80,123,97,99,74,218,255,0,0,0,0},{0,0,0,0,3,0,128,0,0,0,0},{70,0,68,111,66,34,13,44,9,54,0,0,0,0,0,0,0,0,0,0,0,0,0,0,0,0,0,0,0,0}},
   {7,4,4,15,255,{44,36,102,237,0,0,0,0,0,0,0},{0,0,0,48,0,0,0,0,0,0,0},{67,0,68,72,0,0,0,0,0,0,0,0,0,0,0,0,0,0,0,0,0,0,0,0,0,0,0,0,0,0}},
   {8,17,2,5,16,{104,222,0,0,0,0,0,0,0,0,0},{0,0,0,0,0,0,0,0,0,0,0},{131,36,7,43,2,35,44,109,13,78,1,157,21,26,17,24,11,0,0,0,0,0,0,0,0,0,0,0,0,0}},
   {9,19,1,16,17,{221,0,0,0,0,0,0,0,0,0,0},{48,0,0,0,0,0,0,0,0,0,0},{128,41,162,7,39,2,10,40,1,13,14,25,21,16,28,24,11,83,31,0,0,0,0,0,0,0,0,0,0,0}},
   {10,17,3,5,18,{148,139,188,0,0,0,0,0,0,0,0},{4,0,0,0,0,0,0,0,0,0,0},{128,161,162,99,108,2,15,40,12,22,14,25,21,16,17,158,95,0,0,0,0,0,0,0,0,0,0,0,0,0}},
   {11,19,3,39,19,{213,193,194,0,0,0,0,0,0,0,0},{0,0,0,0,0,0,0,0,0,0,0},{133,36,7,15,2,39,10,40,1,22,14,25,21,26,16,24,11,83,20,0,0,0,0,0,0,0,0,0,0,0}},
   {12,19,2,17,20,{220,192,0,0,0,0,0,0,0,0,0},{0,0,0,0,0,0,0,0,0,0,0},{128,36,7,72,35,44,13,109,1,22,146,157,155,16,17,158,23,83,20,0,0,0,0,0,0,0,0,0,0,0}},
   {13,18,4,33,21,{72,235,138,157,0,0,0,0,0,0,0},{0,0,0,0,0,0,0,0,0,0,0},{133,41,7,15,77,35,44,65,45,78,146,157,80,26,17,158,23,83,0,0,0,0,0,0,0,0,0,0,0,0}},
   {14,18,3,24,22,{144,172,197,0,0,0,0,0,0,0,0},{0,0,0,0,0,0,0,0,0,0,0},{131,36,7,15,10,39,13,65,45,9,146,157,155,16,17,158,23,83,0,0,0,0,0,0,0,0,0,0,0,0}},
   {15,17,3,40,23,{96,236,198,0,0,0,0,0,0,0,0},{1,0,0,0,0,0,0,0,0,0,0},{133,32,42,43,2,13,39,12,73,45,14,25,21,26,28,24,11,0,0,0,0,0,0,0,0,0,0,0,0,0}},
   {8,20,2,12,24,{200,219,0,0,0,0,0,0,0,0,0},{0,12,0,0,0,0,0,0,0,0,0},{128,41,132,72,10,39,104,12,86,9,146,25,155,16,28,158,23,31,19,20,0,0,0,0,0,0,0,0,0,0}},
   {9,18,4,18,25,{112,146,209,94,0,0,0,0,0,0,0},{0,0,0,64,0,0,0,0,0,0,0},{131,161,166,99,108,8,76,109,86,9,146,157,155,26,17,158,23,84,0,0,0,0,0,0,0,0,0,0,0,0}},
   {10,20,4,0,26,{233,141,153,160,0,0,0,0,0,0,0},{0,0,0,0,0,0,0,0,0,0,0},{133,165,166,103,8,10,13,109,1,9,146,157,155,26,28,87,24,11,20,19,0,0,0,0,0,0,0,0,0,0}},
   {11,18,4,8,27,{176,133,242,90,0,0,0,0,0,0,0},{0,0,0,0,0,0,0,0,0,0,0},{70,41,132,72,35,44,13,109,12,9,146,157,155,81,28,158,23,31,0,0,0,0,0,0,0,0,0,0,0,0}},
   {12,17,1,19,28,{116,0,0,0,0,0,0,0,0,0,0},{24,0,0,0,0,0,0,0,0,0,0},{131,41,162,15,39,2,104,12,73,78,89,85,90,92,88,75,95,0,0,0,0,0,0,0,0,0,0,0,0,0}},
   {13,18,3,45,29,{214,243,154,0,0,0,0,0,0,0,0},{0,0,0,0,0,0,0,0,0,0,0},{128,161,132,72,10,39,76,40,86,9,89,85,155,92,88,75,95,84,0,0,0,0,0,0,0,0,0,0,0,0}},
   {14,18,2,23,30,{8,203,0,0,0,0,0,0,0,0,0},{0,0,0,0,0,0,0,0,0,0,0},{70,41,132,72,35,44,76,40,86,78,89,85,90,92,88,75,95,84,0,0,0,0,0,0,0,0,0,0,0,0}},
   {15,20,3,22,31,{232,140,184,0,0,0,0,0,0,0,0},{0,0,0,0,0,0,0,0,0,0,0},{131,36,132,72,10,35,44,65,40,22,146,157,155,16,17,158,23,31,19,20,0,0,0,0,0,0,0,0,0,0}},
   {8,3,6,47,255,{4,34,19,183,234,246,0,0,0,0,0},{0,0,0,32,0,127,0,0,0,0,0},{70,161,79,0,0,0,0,0,0,0,0,0,0,0,0,0,0,0,0,0,0,0,0,0,0,0,0,0,0,0}},
   {9,3,7,12,255,{5,22,118,169,210,186,163,0,0,0,0},{0,0,64,0,0,0,0,0,0,0,0},{133,165,107,0,0,0,0,0,0,0,0,0,0,0,0,0,0,0,0,0,0,0,0,0,0,0,0,0,0,0}},
   {10,3,6,8,255,{2,62,122,12,173,240,0,0,0,0,0},{0,0,0,0,0,0,0,0,0,0,0},{160,170,107,0,0,0,0,0,0,0,0,0,0,0,0,0,0,0,0,0,0,0,0,0,0,0,0,0,0,0}},
   {11,3,6,2,255,{24,29,69,117,230,187,0,0,0,0,0},{0,0,0,0,0,0,0,0,0,0,0},{131,161,162,0,0,0,0,0,0,0,0,0,0,0,0,0,0,0,0,0,0,0,0,0,0,0,0,0,0,0}},
   {12,3,6,31,255,{46,21,76,114,142,161,0,0,0,0,0},{0,0,0,0,127,0,0,0,0,0,0},{133,161,166,0,0,0,0,0,0,0,0,0,0,0,0,0,0,0,0,0,0,0,0,0,0,0,0,0,0,0}},
   {13,4,7,21,255,{40,53,85,206,217,137,253,0,0,0,0},{0,0,0,0,0,0,0,0,0,0,0},{131,165,162,66,0,0,0,0,0,0,0,0,0,0,0,0,0,0,0,0,0,0,0,0,0,0,0,0,0,0}},
   {14,3,6,38,255,{27,37,15,113,143,249,0,0,0,0,0},{0,0,128,0,255,0,0,0,0,0,0},{133,161,162,0,0,0,0,0,0,0,0,0,0,0,0,0,0,0,0,0,0,0,0,0,0,0,0,0,0,0}},
   {15,3,4,13,255,{31,110,175,136,0,0,0,0,0,0,0},{4,0,0,0,0,0,0,0,0,0,0},{70,41,79,0,0,0,0,0,0,0,0,0,0,0,0,0,0,0,0,0,0,0,0,0,0,0,0,0,0,0}},
   {8,3,6,17,255,{48,63,108,178,174,167,0,0,0,0,0},{0,0,0,0,0,128,0,0,0,0,0},{133,165,162,0,0,0,0,0,0,0,0,0,0,0,0,0,0,0,0,0,0,0,0,0,0,0,0,0,0,0}},
   {9,3,6,20,255,{0,52,70,78,170,128,0,0,0,0,0},{0,0,0,64,0,0,0,0,0,0,0},{160,170,132,0,0,0,0,0,0,0,0,0,0,0,0,0,0,0,0,0,0,0,0,0,0,0,0,0,0,0}},
   {10,3,5,1,255,{30,86,179,231,165,0,0,0,0,0,0},{0,0,0,3,63,0,0,0,0,0,0},{100,7,3,0,0,0,0,0,0,0,0,0,0,0,0,0,0,0,0,0,0,0,0,0,0,0,0,0,0,0}},
   {11,3,7,42,255,{42,49,26,109,77,132,189,0,0,0,0},{0,0,0,0,0,0,63,0,0,0,0},{128,165,166,0,0,0,0,0,0,0,0,0,0,0,0,0,0,0,0,0,0,0,0,0,0,0,0,0,0,0}},
   {12,4,5,13,255,{6,84,207,211,92,0,0,0,0,0,0},{0,0,0,0,0,0,0,0,0,0,0},{70,165,107,74,0,0,0,0,0,0,0,0,0,0,0,0,0,0,0,0,0,0,0,0,0,0,0,0,0,0}},
   {13,3,6,26,255,{43,50,125,181,229,244,0,0,0,0,0},{0,0,62,0,0,0,0,0,0,0,0},{160,170,166,0,0,0,0,0,0,0,0,0,0,0,0,0,0,0,0,0,0,0,0,0,0,0,0,0,0,0}},
   {14,3,7,36,255,{41,58,71,182,201,225,245,0,0,0,0},{0,0,0,0,0,0,0,0,0,0,0},{128,165,166,0,0,0,0,0,0,0,0,0,0,0,0,0,0,0,0,0,0,0,0,0,0,0,0,0,0,0}},
   {15,3,5,6,255,{55,20,177,238,227,0,0,0,0,0,0},{18,0,0,0,0,0,0,0,0,0,0},{128,161,162,0,0,0,0,0,0,0,0,0,0,0,0,0,0,0,0,0,0,0,0,0,0,0,0,0,0,0}},
   {8,3,6,37,255,{51,60,103,215,241,164,0,0,0,0,0},{0,0,0,3,0,0,0,0,0,0,0},{160,170,166,0,0,0,0,0,0,0,0,0,0,0,0,0,0,0,0,0,0,0,0,0,0,0,0,0,0,0}},
   {9,3,6,25,255,{7,17,83,73,205,95,0,0,0,0,0},{72,0,0,0,0,128,0,0,0,0,0},{100,6,79,0,0,0,0,0,0,0,0,0,0,0,0,0,0,0,0,0,0,0,0,0,0,0,0,0,0,0}},
   {10,3,7,10,255,{54,121,82,98,180,145,131,0,0,0,0},{0,0,0,0,0,3,7,0,0,0,0},{105,6,132,0,0,0,0,0,0,0,0,0,0,0,0,0,0,0,0,0,0,0,0,0,0,0,0,0,0,0}},
   {11,3,6,30,255,{25,59,68,79,202,247,0,0,0,0,0},{0,0,0,0,0,128,0,0,0,0,0},{160,170,107,0,0,0,0,0,0,0,0,0,0,0,0,0,0,0,0,0,0,0,0,0,0,0,0,0,0,0}},
   {12,3,6,6,255,{47,66,107,239,195,155,0,0,0,0,0},{1,0,0,0,0,0,0,0,0,0,0},{160,170,132,0,0,0,0,0,0,0,0,0,0,0,0,0,0,0,0,0,0,0,0,0,0,0,0,0,0,0}},
   {13,3,6,11,255,{45,33,67,100,115,130,0,0,0,0,0},{0,0,0,0,0,0,0,0,0,0,0},{100,6,107,0,0,0,0,0,0,0,0,0,0,0,0,0,0,0,0,0,0,0,0,0,0,0,0,0,0,0}},
   {14,4,5,16,255,{3,126,119,228,166,0,0,0,0,0,0},{0,0,128,0,64,0,0,0,0,0,0},{160,170,107,66,0,0,0,0,0,0,0,0,0,0,0,0,0,0,0,0,0,0,0,0,0,0,0,0,0,0}},
   {15,3,5,7,255,{28,23,11,204,216,0,0,0,0,0,0},{0,0,0,0,0,0,0,0,0,0,0},{71,165,166,0,0,0,0,0,0,0,0,0,0,0,0,0,0,0,0,0,0,0,0,0,0,0,0,0,0,0}},
   {6,2,6,9,255,{1,39,81,9,10,223,0,0,0,0,0},{0,0,0,0,0,192,0,0,0,0,0},{102,32,0,0,0,0,0,0,0,0,0,0,0,0,0,0,0,0,0,0,0,0,0,0,0,0,0,0,0,0}},
   {7,10,5,18,255,{64,57,65,101,135,0,0,0,0,0,0},{0,0,0,0,0,0,0,0,0,0,0},{99,32,100,104,74,106,76,97,86,110,0,0,0,0,0,0,0,0,0,0,0,0,0,0,0,0,0,0,0,0}}},
  {{0,1,0,0},{13,32,0,0},{0,1,0,0},{0,6,0,0},{0,6,0,0},{8,32,0,0},{0,6,0,0},{0,1,0,0},{13,32,0,0},{13,32,0,0},{7,13,0,0},
   {13,32,0,0},{0,1,0,0},{0,1,0,0},{5,13,0,0},{6,14,0,0},{0,5,0,0},{8,32,0,0},{0,7,0,0},{6,11,0,0},{1,9,0,0},{1,32,0,0},
   {1,7,0,0},{6,32,0,0},{9,32,0,0},{9,32,0,0},{1,9,0,0},{0,6,0,0},{9,32,0,0},{0,1,0,0},{0,5,0,0},{0,5,0,0},{10,32,0,0},
   {3,11,0,0},{5,13,0,0},{1,9,0,0},{1,32,0,0},{0,1,0,0},{5,32,0,0},{14,32,0,0},{0,5,0,0},{5,10,0,0},{9,32,0,0},{5,13,0,0},
   {0,5,0,0},{1,8,0,0},{0,5,0,0},{8,32,0,0},{5,9,0,0},{7,32,0,0},{5,8,0,0},{0,3,0,0},{0,8,0,0},{0,5,0,0},{0,5,0,0},
   {12,32,0,0},{0,0,0,0},{0,5,0,0},{11,32,0,0},{0,5,0,0},{5,12,0,0},{6,32,0,0},{5,9,0,0},{5,32,0,0},{9,32,0,0},{11,32,0,0}},
  {{0,3,6,5,4,7,15,2,8,10,12,13,1,9,14,18,22,21,25,29,27,16,26,17,24,30,28,23,11,31,19,20},
   {0,3,5,6,4,15,7,2,8,10,12,1,22,13,9,14,18,25,29,21,27,16,26,28,17,24,30,11,23,20,31,19},
   {0,5,7,6,3,4,8,2,10,15,13,12,1,22,9,14,18,25,29,16,21,27,26,17,28,30,23,31,24,11,20,19},
   {3,5,6,0,7,4,15,2,8,10,13,1,12,22,9,14,18,25,29,21,27,16,26,28,17,24,30,11,23,19,31,20},
   {0,3,5,6,7,4,8,15,10,2,13,12,1,9,22,14,18,25,29,21,27,26,16,28,17,24,30,11,23,31,19,20},
   {0,5,3,6,7,4,15,8,2,13,10,12,1,22,14,9,18,25,29,21,27,16,26,28,17,24,30,11,23,31,19,20},
   {3,5,6,0,7,4,15,8,2,10,13,12,1,22,9,14,18,25,29,27,21,26,16,28,17,24,30,11,23,31,19,20},
   {0,3,5,6,7,4,15,8,2,10,13,12,1,9,22,14,18,25,29,21,27,16,26,28,17,24,11,30,23,31,19,20}},
  {{0,0,0,3,0,1,3,3},{12,12,12,12,12,0,0,1},{7,7,8,8,9,8,8,8},{1,1,3,2,1,2,0,1},
   {5,5,5,5,5,5,5,5},{3,2,1,0,2,0,2,0},{2,3,2,1,3,3,1,2},{4,4,4,4,4,4,4,4},
   {8,8,7,7,7,7,7,7},{14,14,0,1,0,1,1,4},{9,9,9,9,8,9,9,9},{13,15,4,2,4,4,6,9},
   {11,11,11,11,11,11,11,0},{10,10,10,10,10,10,10,10},{15,15,1,5,5,5,5,5},{6,6,6,6,6,6,6,6},
   {7,7,10,11,11,7,11,0},{6,8,12,1,0,1,2,6},{0,0,5,4,4,4,4,2},{5,5,7,12,12,0,0,4},
   {2,2,11,11,11,7,11,0},{4,4,8,9,8,9,9,8},{13,13,13,0,1,2,2,6},{15,13,1,8,8,9,9,8},
   {10,11,13,0,1,5,4,2},{1,1,4,2,2,3,6,3},{9,9,7,7,7,11,7,7},{2,2,9,10,10,10,10,10},
   {8,10,11,12,12,0,0,4},{5,5,2,8,9,8,8,9},{12,12,0,4,2,3,8,3},{1,1,2,7,7,11,7,7}},
  {{255,255,255,255,255,255,255,255},{255,255,255,255,255,5,3,3},{255,255,255,255,255,255,255,255},{255,255,255,255,255,255,255,255},
   {255,255,255,255,255,255,255,255},{255,255,255,255,255,255,255,255},{255,255,255,255,255,255,255,255},{255,255,255,255,255,255,255,255},
   {255,255,255,255,255,255,255,255},{255,255,0,6,0,0,6,7},{255,255,255,255,255,255,255,255},{22,14,25,25,18,18,25,29},
   {255,255,255,255,255,255,255,5},{255,255,255,255,255,255,255,255},{255,255,5,4,4,4,4,4},{255,255,255,255,255,255,255,255},
   {2,2,13,12,12,8,12,12},{15,8,1,9,9,9,22,22},{0,0,4,7,7,7,7,6},{29,29,26,28,28,28,28,28},
   {27,27,28,16,16,16,16,16},{7,7,2,10,10,10,10,2},{255,255,255,5,3,3,5,15},{14,22,14,29,21,21,21,21},
   {13,12,22,22,22,14,18,18},{3,3,7,3,5,6,15,0},{10,10,8,8,8,12,8,8},{6,5,10,13,13,13,13,13},
   {8,13,12,1,1,1,1,9},{4,4,6,2,2,2,2,10},{1,1,9,18,25,25,29,25},{25,25,29,26,26,26,26,26}}};

typedef CUresult (*EncodeFn)(CUtensorMap*, CUtensorMapDataType, cuuint32_t, void*, const cuuint64_t*, const cuuint64_t*, const cuuint32_t*,
                             const cuuint32_t*, CUtensorMapInterleave, CUtensorMapSwizzle, CUtensorMapL2promotion, CUtensorMapFloatOOBfill);

void make_map2(EncodeFn enc, CUtensorMap* m, const void* ptr, int rows, int cols, int box_rows) {
  cuuint64_t dim[2] = {(cuuint64_t)cols, (cuuint64_t)rows}, str[1] = {(cuuint64_t)cols * 2};
  cuuint32_t box[2] = {64, (cuuint32_t)box_rows}, es[2] = {1, 1};
  enc(m, CU_TENSOR_MAP_DATA_TYPE_BFLOAT16, 2, const_cast<void*>(ptr), dim, str, box, es, CU_TENSOR_MAP_INTERLEAVE_NONE, CU_TENSOR_MAP_SWIZZLE_128B,
      CU_TENSOR_MAP_L2_PROMOTION_L2_128B, CU_TENSOR_MAP_FLOAT_OOB_FILL_NONE);
}
void make_map3(EncodeFn enc, CUtensorMap* m, const void* ptr, int rows) {
  cuuint64_t dim[3] = {64, (cuuint64_t)rows, 9}, str[2] = {DM * 2, 128};
  cuuint32_t box[3] = {64, 32, 3}, es[3] = {1, 1, 1};
  enc(m, CU_TENSOR_MAP_DATA_TYPE_BFLOAT16, 3, const_cast<void*>(ptr), dim, str, box, es, CU_TENSOR_MAP_INTERLEAVE_NONE, CU_TENSOR_MAP_SWIZZLE_128B,
      CU_TENSOR_MAP_L2_PROMOTION_L2_128B, CU_TENSOR_MAP_FLOAT_OOB_FILL_NONE);
}

void make_map_t(EncodeFn enc, CUtensorMap* m, void* ptr, int width, int cols) {
  cuuint64_t dim[3] = {TP / 2, 2, 864}, str[2] = {TP * 2, TP * 4};
  cuuint32_t box[3] = {(cuuint32_t)width, 2, (cuuint32_t)cols}, es[3] = {1, 1, 1};
  enc(m, CU_TENSOR_MAP_DATA_TYPE_UINT32, 3, ptr, dim, str, box, es, CU_TENSOR_MAP_INTERLEAVE_NONE, cols == 64 ? CU_TENSOR_MAP_SWIZZLE_128B : CU_TENSOR_MAP_SWIZZLE_NONE,
      CU_TENSOR_MAP_L2_PROMOTION_NONE, CU_TENSOR_MAP_FLOAT_OOB_FILL_NONE);
}

int g_mode = -1;

}

extern "C" void kernel_launch(void* const* d_in, const int* in_sizes, int n_in, void* d_out, int out_size) {
  static EncodeFn enc = nullptr;
  static void* t_ptr = nullptr;
  if (!enc) {
    void* fn = nullptr;
    cudaDriverEntryPointQueryResult st;
    cudaGetDriverEntryPoint("cuTensorMapEncodeTiled", &fn, cudaEnableDefault, &st);
    enc = (EncodeFn)fn;
    cudaGetSymbolAddress(&t_ptr, g_T);
    cudaFuncSetAttribute(fused_kernel, cudaFuncAttributeMaxDynamicSharedMemorySize, SMEM_BYTES);
    if (g_mode < 0) {
      cudaLaunchConfig_t cfg = {};
      cfg.gridDim = dim3(2 * NCL); cfg.blockDim = dim3(384); cfg.dynamicSmemBytes = SMEM_BYTES;
      cudaLaunchAttribute at; at.id = cudaLaunchAttributeClusterDimension;
      at.val.clusterDim.x = 2; at.val.clusterDim.y = 1; at.val.clusterDim.z = 1;
      cfg.attrs = &at; cfg.numAttrs = 1;
      int nc = 0;
      g_mode = (cudaOccupancyMaxActiveClusters(&nc, fused_kernel, &cfg) == cudaSuccess && nc >= NCL) ? 1 : 0;
      (void)cudaGetLastError();
    }
  }
  Params p;
  make_map2(enc, &p.map_a[0], d_in[4], SEQ, DC, 128);
  make_map2(enc, &p.map_a[1], d_in[0], SEQ, DM, 128);
  make_map2(enc, &p.map_w[0], d_in[6], DC, 4096, 64);
  make_map2(enc, &p.map_w[1], d_in[7], DC, 4096, 64);
  make_map2(enc, &p.map_w[2], d_in[5], DM, 4096, 64);
  make_map2(enc, &p.map_w[3], d_in[1], DM, 1728, 64);
  make_map3(enc, &p.map_o[0], d_in[8], 4096);
  make_map3(enc, &p.map_o[1], d_in[2], DM);
  make_map_t(enc, &p.map_t[0], t_ptr, 32, 9);
  make_map_t(enc, &p.map_t[1], t_ptr, 40, 9);
  make_map_t(enc, &p.map_t[2], t_ptr, 32, 64);
  p.x = (const __nv_bfloat16*)d_in[0];
  p.gate_w = (const __nv_bfloat16*)d_in[9];
  make_map2(enc, &p.map_out, d_out, SEQ, DM, 64);
  p.out = (__nv_bfloat16*)d_out;
  p.zero = 0;
  auto launch = [&](int phases) {
    p.s = k_sched;
    for (int i = 0; i < NCL; i++) {
      Rec& r = p.s.r[i];
      if (!(phases & 1)) r.n1 = 0;
      if (!(phases & 2)) r.n2 = 0;
      if (!(phases & (p.s.task[i][1] == 32 ? 4 : 32))) r.p3 = 255;
      if (!(phases & 8)) r.bg = 255;
      const int u1 = r.n1 ? 8 + r.n1 * (8 + (r.slab >> 3)) : 0;
      int u2 = 0;
      for (int k = 0; k < r.n2; k++) u2 += 4 * (r.item[k] & 7) + 4;
      r.u1 = (uint8_t)u1; r.u2 = (uint8_t)u2;
      r.rot = (uint8_t)(((u1 % 10 + 1) >> 1) % 5);
      r.x3 = (uint8_t)((r.rot + u2) % 5 & 3);
      r.phases = (uint8_t)phases;
    }
    if (!(phases & 16))
      for (int i = 0; i < 256; i++) { p.s.slot[i >> 3][i & 7] = (uint8_t)(i >> 3); p.s.prev[i >> 3][i & 7] = 255; }
    fused_kernel<<<2 * NCL, 384, SMEM_BYTES>>>(p);
  };
  if (g_mode == 1) launch(63);
  else { launch(1); launch(10); launch(4); launch(32); }
}
```

```cpp
#include <cuda_runtime.h>
#include <cuda_bf16.h>
#include <cuda.h>
#include <stdint.h>

namespace {

constexpr int SEQ = 2048, DM = 576, DC = 512, NH = 32;
constexpr int NCL = 66;
constexpr uint32_t DESC_HI = 0x40000040u;

constexpr int SM_RING = 0;
constexpr int SM_BUF = 163840;
constexpr int SM_BAR = 229376;
constexpr int B_P1E = 0, B_P2E = 10, B_P3E = 15, B_P2F = 24, B_SF = 32, B_ORD = 36, B_LAD = 40, B_DONE = 41, B_FIN = 48;
constexpr int B_P3F = 56, B_OUT = 61, B_P1F = 64, B_SE = 74, B_QF = 80, B_LA = 84, B_NUM = 88;
constexpr uint64_t B_CNT = 0x11118245000ull;
constexpr int SMEM_BYTES = SM_BAR + B_NUM * 8 + 1024;

constexpr int F_QKVA = 32;
constexpr int F_GATE = 64;
constexpr int F_DONE = 65;
constexpr int F_CTX = 96;
constexpr int F_OUT = 96 + 8 * 64;
constexpr int F_KV = F_OUT + 64;
constexpr int F_Q = F_KV + 256;
constexpr int F_RD = F_Q + 256;
constexpr int F_NUM = F_RD + 256;

struct Rec {
  uint8_t slab;
  uint8_t n1, n2;
  uint8_t p3;
  uint8_t bg;
  uint8_t item[11];
  uint8_t last[11];
  uint8_t tile[32];
  uint8_t u1, u2;
  uint8_t rot, x3;
  uint8_t phases;
};
struct Sched {
  Rec r[NCL];
  uint8_t task[NCL][4];
  uint8_t p3_order[24][32];
  uint8_t slot[32][8];
  uint8_t prev[32][8];
};

#define SCHED_DECL static const

struct Params {
  CUtensorMap map_a[2];
  CUtensorMap map_w[4];
  CUtensorMap map_o[2];
  CUtensorMap map_t[3];
  CUtensorMap map_out;
  const __nv_bfloat16* x;
  const __nv_bfloat16* gate_w;
  __nv_bfloat16* out;
  int zero;
  alignas(64) Sched s;
};

__device__ __align__(1024) uint8_t g_Q[NH * 32 * 16384];
__device__ __align__(1024) uint8_t g_KV[2 * NH * 16 * 32768];
__device__ __align__(1024) uint8_t g_oA[32 * 576 * 128];
constexpr int TP = SEQ + 16;
__device__ __align__(1024) uint32_t g_T[864 * TP];
__device__ float g_gate[SEQ];
__device__ int g_flags[F_NUM];

__device__ __forceinline__ void mbar_arrive(uint32_t b) { asm volatile("mbarrier.arrive.shared::cta.b64 _, [%0];" ::"r"(b) : "memory"); }
__device__ __forceinline__ void mbar_arrive_cl(uint32_t b, int cnt) {
  asm volatile("mbarrier.arrive.shared::cluster.b64 _, [%0], %1;" ::"r"(b), "r"(cnt) : "memory");
}
__device__ __forceinline__ void mbar_wait(uint32_t b, int par) {
  asm volatile(
      "{\n.reg .pred p;\n.reg .u32 c;\n"
      "mbarrier.try_wait.parity.shared::cta.b64 p, [%0], %1;\n@p bra DN;\nmov.u32 c, 0;\n"
      "LP:\nmbarrier.try_wait.parity.shared::cta.b64 p, [%0], %1;\n@p bra DN;\n"
      "add.u32 c, c, 1;\nsetp.lt.u32 p, c, 4000000;\n@p bra LP;\ntrap;\nDN:\n}" ::"r"(b), "r"(par) : "memory");
}
__device__ __forceinline__ uint32_t mapa(uint32_t a, uint32_t cta) {
  uint32_t r; asm("mapa.shared::cluster.u32 %0, %1, %2;" : "=r"(r) : "r"(a), "r"(cta)); return r;
}
#define ELECT(ins) "{\n.reg .pred e;\nelect.sync _|e, 0xffffffff;\n@e " ins "\n}"
__device__ __forceinline__ void mbar_expect(uint32_t b, int bytes) {
  asm volatile(ELECT("mbarrier.arrive.expect_tx.shared::cta.b64 _, [%0], %1;") ::"r"(b), "r"(bytes) : "memory");
}
__device__ __forceinline__ void mbar_arrive_one(uint32_t b) { asm volatile(ELECT("mbarrier.arrive.shared::cta.b64 _, [%0];") ::"r"(b) : "memory"); }
constexpr uint64_t L2_NORMAL = 0x1000000000000000ull, L2_FIRST = 0x12F0000000000000ull;
__device__ __forceinline__ void bulk_load(uint32_t dst, const void* src, int bytes, uint32_t bar, uint64_t pol = L2_NORMAL) {
  asm volatile(ELECT("cp.async.bulk.shared::cluster.global.mbarrier::complete_tx::bytes.L2::cache_hint [%0], [%1], %2, [%3], %4;") ::"r"(dst), "l"(src), "r"(bytes), "r"(bar), "l"(pol) : "memory");
}
__device__ __forceinline__ void bulk_load_mc(uint32_t dst, const void* src, int bytes, uint32_t bar, uint64_t pol = L2_NORMAL) {
  asm volatile(ELECT("cp.async.bulk.shared::cluster.global.mbarrier::complete_tx::bytes.multicast::cluster.L2::cache_hint [%0], [%1], %2, [%3], %4, %5;") ::"r"(dst), "l"(src), "r"(bytes), "r"(bar), "h"((uint16_t)3), "l"(pol) : "memory");
}
__device__ __forceinline__ void bulk_store(void* dst, uint32_t src, int bytes, uint64_t pol = L2_NORMAL) {
  asm volatile(ELECT("cp.async.bulk.global.shared::cta.bulk_group.L2::cache_hint [%0], [%1], %2, %3;") ::"l"(dst), "r"(src), "r"(bytes), "l"(pol) : "memory");
}
__device__ __forceinline__ void tma2d(uint32_t dst, const CUtensorMap* m, int c0, int c1, uint32_t bar, uint64_t pol = L2_NORMAL) {
  asm volatile(ELECT("cp.async.bulk.tensor.2d.shared::cluster.global.mbarrier::complete_tx::bytes.L2::cache_hint [%0], [%1, {%3, %4}], [%2], %5;") ::"r"(dst), "l"(m), "r"(bar), "r"(c0), "r"(c1), "l"(pol) : "memory");
}
__device__ __forceinline__ void tma2d_mc(uint32_t dst, const CUtensorMap* m, int c0, int c1, uint32_t bar, uint64_t pol = L2_NORMAL) {
  asm volatile(ELECT("cp.async.bulk.tensor.2d.shared::cluster.global.mbarrier::complete_tx::bytes.multicast::cluster.L2::cache_hint [%0], [%1, {%3, %4}], [%2], %5, %6;") ::"r"(dst), "l"(m), "r"(bar), "r"(c0), "r"(c1), "h"((uint16_t)3), "l"(pol) : "memory");
}
__device__ __forceinline__ void tma3d(uint32_t dst, const CUtensorMap* m, int c0, int c1, int c2, uint32_t bar, uint64_t pol = L2_NORMAL) {
  asm volatile(ELECT("cp.async.bulk.tensor.3d.shared::cluster.global.mbarrier::complete_tx::bytes.L2::cache_hint [%0], [%1, {%3, %4, %5}], [%2], %6;") ::"r"(dst), "l"(m), "r"(bar), "r"(c0), "r"(c1), "r"(c2), "l"(pol) : "memory");
}
__device__ __forceinline__ void tma3d_mc(uint32_t dst, const CUtensorMap* m, int c0, int c1, int c2, uint32_t bar, uint64_t pol = L2_NORMAL) {
  asm volatile(ELECT("cp.async.bulk.tensor.3d.shared::cluster.global.mbarrier::complete_tx::bytes.multicast::cluster.L2::cache_hint [%0], [%1, {%3, %4, %5}], [%2], %6, %7;") ::"r"(dst), "l"(m), "r"(bar), "r"(c0), "r"(c1), "r"(c2), "h"((uint16_t)3), "l"(pol) : "memory");
}
__device__ __forceinline__ void tma2d_add(const CUtensorMap* m, uint32_t src, int c0, int c1) {
  asm volatile(ELECT("cp.reduce.async.bulk.tensor.2d.global.shared::cta.add.bulk_group [%0, {%2, %3}], [%1];") ::"l"(m), "r"(src), "r"(c0), "r"(c1) : "memory");
}
__device__ __forceinline__ void tma3d_store(const CUtensorMap* m, uint32_t src, int c0, int c1, int c2, uint64_t pol = L2_NORMAL) {
  asm volatile(ELECT("cp.async.bulk.tensor.3d.global.shared::cta.bulk_group.L2::cache_hint [%0, {%2, %3, %4}], [%1], %5;") ::"l"(m), "r"(src), "r"(c0), "r"(c1), "r"(c2), "l"(pol) : "memory");
}
__device__ __forceinline__ void tma2d_prefetch(const CUtensorMap* m, int c0, int c1, uint64_t pol = L2_NORMAL) {
  asm volatile(ELECT("cp.async.bulk.prefetch.tensor.2d.L2.global.L2::cache_hint [%0, {%1, %2}], %3;") ::"l"(m), "r"(c0), "r"(c1), "l"(pol) : "memory");
}
#define LAG 3
#define HINT 62
#define POL(bit) ((HINT >> (bit)) & 1 ? L2_FIRST : L2_NORMAL)
#define BULK_COMMIT() asm volatile("cp.async.bulk.commit_group;" ::: "memory")
#define BULK_WAIT(n) asm volatile("cp.async.bulk.wait_group %0;" ::"n"(n) : "memory")
#define BULK_WAIT_READ(n) asm volatile("cp.async.bulk.wait_group.read %0;" ::"n"(n) : "memory")
#define FENCE_ASYNC_SMEM() asm volatile("fence.proxy.async.shared::cta;" ::: "memory")
#define FENCE_ASYNC_ALL() asm volatile("fence.proxy.async;" ::: "memory")
#define WG_FENCE() asm volatile("wgmma.fence.sync.aligned;" ::: "memory")
#define WG_COMMIT() asm volatile("wgmma.commit_group.sync.aligned;" ::: "memory")
#define WG_WAIT(n) asm volatile("wgmma.wait_group.sync.aligned %0;" ::"n"(n) : "memory")
__device__ __forceinline__ void bar_sync(int id, int n) { asm volatile("bar.sync %0, %1;" ::"r"(id), "r"(n) : "memory"); }
__device__ __forceinline__ void bar_arrive(int id, int n) { asm volatile("bar.arrive %0, %1;" ::"r"(id), "r"(n) : "memory"); }
__device__ __forceinline__ void cluster_sync() {
  asm volatile("barrier.cluster.arrive.relaxed;\nbarrier.cluster.wait.acquire;" ::: "memory");
}
template <int N> __device__ __forceinline__ void pin(float (&r)[N]) {
#pragma unroll
  for (int i = 0; i < N; i++) asm volatile("" : "+f"(r[i])::"memory");
}
template <int N> __device__ __forceinline__ void pin(uint32_t (&r)[N]) {
#pragma unroll
  for (int i = 0; i < N; i++) asm volatile("" : "+r"(r[i])::"memory");
}
__device__ __forceinline__ uint32_t pack_bf16(float lo, float hi) {
  uint32_t r; asm("cvt.rn.bf16x2.f32 %0, %1, %2;" : "=r"(r) : "f"(hi), "f"(lo)); return r;
}
__device__ __forceinline__ float ex2(float x) { float r; asm("ex2.approx.ftz.f32 %0, %1;" : "=f"(r) : "f"(x)); return r; }
__device__ __forceinline__ void ldsm4(uint32_t a, uint32_t& r0, uint32_t& r1, uint32_t& r2, uint32_t& r3) {
  asm volatile("ldmatrix.sync.aligned.m8n8.x4.shared.b16 {%0,%1,%2,%3}, [%4];" : "=r"(r0), "=r"(r1), "=r"(r2), "=r"(r3) : "r"(a) : "memory");
}
__device__ __forceinline__ void stsm4(uint32_t a, uint32_t r0, uint32_t r1, uint32_t r2, uint32_t r3) {
  asm volatile("stmatrix.sync.aligned.m8n8.x4.shared.b16 [%0], {%1,%2,%3,%4};" ::"r"(a), "r"(r0), "r"(r1), "r"(r2), "r"(r3) : "memory");
}
__device__ __forceinline__ void flag_add(int idx) {
  asm volatile(ELECT("red.release.gpu.global.add.s32 [%0], 1;") ::"l"(g_flags + idx) : "memory");
}
__device__ __forceinline__ void flag_add_rx(int idx) {
  asm volatile(ELECT("red.relaxed.gpu.global.add.s32 [%0], 1;") ::"l"(g_flags + idx) : "memory");
}
template <bool ACQ, int NS = 32> __device__ __forceinline__ void flag_wait(int idx, int target) {
  int n = 0;
  while (true) {
    int v;
    if (ACQ) asm volatile("ld.acquire.gpu.global.s32 %0, [%1];" : "=r"(v) : "l"(g_flags + idx) : "memory");
    else asm volatile("ld.relaxed.gpu.global.s32 %0, [%1];" : "=r"(v) : "l"(g_flags + idx) : "memory");
    if (__all_sync(0xffffffffu, v >= target)) break;
    if (++n > 20000000) __trap();
    __nanosleep(NS);
  }
}
__device__ __forceinline__ void mask_wait(uint32_t& ready, int bit, int idx, int target) {
  for (int n = 0; !((ready >> bit) & 1); n++) {
    int v;
    if (n) { __nanosleep(32); if (n > 20000000) __trap(); }
    asm volatile("ld.relaxed.gpu.global.s32 %0, [%1];" : "=r"(v) : "l"(g_flags + idx) : "memory");
    ready = __ballot_sync(0xffffffffu, v >= target);
  }
}
__device__ __forceinline__ uint32_t desc_lo(uint32_t addr, uint32_t lbo) { return ((addr & 0x3FFFFu) >> 4) | ((lbo >> 4) << 16); }
#define PROF(role, i)
#define PROFX(cond, i)
#define PROFB(i)
#define PROFG(i)

template <int TB, int TA = 0> __device__ __forceinline__ void wgmma_ss64(float (&d)[32], uint32_t alo, uint32_t blo, int sd) {
  asm volatile("{\n.reg .pred p;\n.reg .b64 da, db;\n"
    "setp.ne.b32 p, %34, 0;\nmov.b64 da, {%32, %36};\nmov.b64 db, {%33, %36};\n"
    "wgmma.mma_async.sync.aligned.m64n64k16.f32.bf16.bf16 "
    "{%0,%1,%2,%3,%4,%5,%6,%7,%8,%9,%10,%11,%12,%13,%14,%15,%16,%17,%18,%19,%20,%21,%22,%23,"
    "%24,%25,%26,%27,%28,%29,%30,%31}, "
    "da, db, p, 1, 1, %37, %35;\n}\n"
    : "+f"(d[0]),"+f"(d[1]),"+f"(d[2]),"+f"(d[3]),"+f"(d[4]),"+f"(d[5]),"+f"(d[6]),"+f"(d[7]),"+f"(d[8]),"+f"(d[9]),"+f"(d[10]),"+f"(d[11]),
      "+f"(d[12]),"+f"(d[13]),"+f"(d[14]),"+f"(d[15]),"+f"(d[16]),"+f"(d[17]),"+f"(d[18]),"+f"(d[19]),"+f"(d[20]),"+f"(d[21]),"+f"(d[22]),"+f"(d[23]),
      "+f"(d[24]),"+f"(d[25]),"+f"(d[26]),"+f"(d[27]),"+f"(d[28]),"+f"(d[29]),"+f"(d[30]),"+f"(d[31])
    : "r"(alo), "r"(blo), "r"(sd), "n"(TB), "r"(DESC_HI), "n"(TA));
}
template <int TB, int TA = 0> __device__ __forceinline__ void wgmma_ss128(float (&d)[64], uint32_t alo, uint32_t blo, int sd) {
  asm volatile("{\n.reg .pred p;\n.reg .b64 da, db;\n"
    "setp.ne.b32 p, %66, 0;\nmov.b64 da, {%64, %68};\nmov.b64 db, {%65, %68};\n"
    "wgmma.mma_async.sync.aligned.m64n128k16.f32.bf16.bf16 "
    "{%0,%1,%2,%3,%4,%5,%6,%7,%8,%9,%10,%11,%12,%13,%14,%15,%16,%17,%18,%19,%20,%21,%22,%23,"
    "%24,%25,%26,%27,%28,%29,%30,%31,%32,%33,%34,%35,%36,%37,%38,%39,%40,%41,%42,%43,%44,%45,%46,%47,"
    "%48,%49,%50,%51,%52,%53,%54,%55,%56,%57,%58,%59,%60,%61,%62,%63}, "
    "da, db, p, 1, 1, %69, %67;\n}\n"
    : "+f"(d[0]),"+f"(d[1]),"+f"(d[2]),"+f"(d[3]),"+f"(d[4]),"+f"(d[5]),"+f"(d[6]),"+f"(d[7]),"+f"(d[8]),"+f"(d[9]),"+f"(d[10]),"+f"(d[11]),
      "+f"(d[12]),"+f"(d[13]),"+f"(d[14]),"+f"(d[15]),"+f"(d[16]),"+f"(d[17]),"+f"(d[18]),"+f"(d[19]),"+f"(d[20]),"+f"(d[21]),"+f"(d[22]),"+f"(d[23]),
      "+f"(d[24]),"+f"(d[25]),"+f"(d[26]),"+f"(d[27]),"+f"(d[28]),"+f"(d[29]),"+f"(d[30]),"+f"(d[31]),"+f"(d[32]),"+f"(d[33]),"+f"(d[34]),"+f"(d[35]),
      "+f"(d[36]),"+f"(d[37]),"+f"(d[38]),"+f"(d[39]),"+f"(d[40]),"+f"(d[41]),"+f"(d[42]),"+f"(d[43]),"+f"(d[44]),"+f"(d[45]),"+f"(d[46]),"+f"(d[47]),
      "+f"(d[48]),"+f"(d[49]),"+f"(d[50]),"+f"(d[51]),"+f"(d[52]),"+f"(d[53]),"+f"(d[54]),"+f"(d[55]),"+f"(d[56]),"+f"(d[57]),"+f"(d[58]),"+f"(d[59]),
      "+f"(d[60]),"+f"(d[61]),"+f"(d[62]),"+f"(d[63])
    : "r"(alo), "r"(blo), "r"(sd), "n"(TB), "r"(DESC_HI), "n"(TA));
}
template <int TB> __device__ __forceinline__ void wgmma_rs128(float (&d)[64], uint32_t a0, uint32_t a1, uint32_t a2, uint32_t a3, uint32_t blo, int sd) {
  asm volatile("{\n.reg .pred p;\n.reg .b64 db;\n"
    "setp.ne.b32 p, %69, 0;\nmov.b64 db, {%68, %71};\n"
    "wgmma.mma_async.sync.aligned.m64n128k16.f32.bf16.bf16 "
    "{%0,%1,%2,%3,%4,%5,%6,%7,%8,%9,%10,%11,%12,%13,%14,%15,%16,%17,%18,%19,%20,%21,%22,%23,"
    "%24,%25,%26,%27,%28,%29,%30,%31,%32,%33,%34,%35,%36,%37,%38,%39,%40,%41,%42,%43,%44,%45,%46,%47,"
    "%48,%49,%50,%51,%52,%53,%54,%55,%56,%57,%58,%59,%60,%61,%62,%63}, "
    "{%64,%65,%66,%67}, db, p, 1, 1, %70;\n}\n"
    : "+f"(d[0]),"+f"(d[1]),"+f"(d[2]),"+f"(d[3]),"+f"(d[4]),"+f"(d[5]),"+f"(d[6]),"+f"(d[7]),"+f"(d[8]),"+f"(d[9]),"+f"(d[10]),"+f"(d[11]),
      "+f"(d[12]),"+f"(d[13]),"+f"(d[14]),"+f"(d[15]),"+f"(d[16]),"+f"(d[17]),"+f"(d[18]),"+f"(d[19]),"+f"(d[20]),"+f"(d[21]),"+f"(d[22]),"+f"(d[23]),
      "+f"(d[24]),"+f"(d[25]),"+f"(d[26]),"+f"(d[27]),"+f"(d[28]),"+f"(d[29]),"+f"(d[30]),"+f"(d[31]),"+f"(d[32]),"+f"(d[33]),"+f"(d[34]),"+f"(d[35]),
      "+f"(d[36]),"+f"(d[37]),"+f"(d[38]),"+f"(d[39]),"+f"(d[40]),"+f"(d[41]),"+f"(d[42]),"+f"(d[43]),"+f"(d[44]),"+f"(d[45]),"+f"(d[46]),"+f"(d[47]),
      "+f"(d[48]),"+f"(d[49]),"+f"(d[50]),"+f"(d[51]),"+f"(d[52]),"+f"(d[53]),"+f"(d[54]),"+f"(d[55]),"+f"(d[56]),"+f"(d[57]),"+f"(d[58]),"+f"(d[59]),
      "+f"(d[60]),"+f"(d[61]),"+f"(d[62]),"+f"(d[63])
    : "r"(a0), "r"(a1), "r"(a2), "r"(a3), "r"(blo), "r"(sd), "n"(TB), "r"(DESC_HI));
}
template <int TB, int TA = 0> __device__ __forceinline__ void wgmma_ss192(float (&d)[96], uint32_t alo, uint32_t blo, int sd) {
  asm volatile("{\n.reg .pred p;\n.reg .b64 da, db;\n"
    "setp.ne.b32 p, %98, 0;\nmov.b64 da, {%96, %100};\nmov.b64 db, {%97, %100};\n"
    "wgmma.mma_async.sync.aligned.m64n192k16.f32.bf16.bf16 "
    "{%0,%1,%2,%3,%4,%5,%6,%7,%8,%9,%10,%11,%12,%13,%14,%15,%16,%17,%18,%19,%20,%21,%22,%23,"
    "%24,%25,%26,%27,%28,%29,%30,%31,%32,%33,%34,%35,%36,%37,%38,%39,%40,%41,%42,%43,%44,%45,%46,%47,"
    "%48,%49,%50,%51,%52,%53,%54,%55,%56,%57,%58,%59,%60,%61,%62,%63,%64,%65,%66,%67,%68,%69,%70,%71,"
    "%72,%73,%74,%75,%76,%77,%78,%79,%80,%81,%82,%83,%84,%85,%86,%87,%88,%89,%90,%91,%92,%93,%94,%95}, "
    "da, db, p, 1, 1, %101, %99;\n}\n"
    : "+f"(d[0]),"+f"(d[1]),"+f"(d[2]),"+f"(d[3]),"+f"(d[4]),"+f"(d[5]),"+f"(d[6]),"+f"(d[7]),"+f"(d[8]),"+f"(d[9]),"+f"(d[10]),"+f"(d[11]),
      "+f"(d[12]),"+f"(d[13]),"+f"(d[14]),"+f"(d[15]),"+f"(d[16]),"+f"(d[17]),"+f"(d[18]),"+f"(d[19]),"+f"(d[20]),"+f"(d[21]),"+f"(d[22]),"+f"(d[23]),
      "+f"(d[24]),"+f"(d[25]),"+f"(d[26]),"+f"(d[27]),"+f"(d[28]),"+f"(d[29]),"+f"(d[30]),"+f"(d[31]),"+f"(d[32]),"+f"(d[33]),"+f"(d[34]),"+f"(d[35]),
      "+f"(d[36]),"+f"(d[37]),"+f"(d[38]),"+f"(d[39]),"+f"(d[40]),"+f"(d[41]),"+f"(d[42]),"+f"(d[43]),"+f"(d[44]),"+f"(d[45]),"+f"(d[46]),"+f"(d[47]),
      "+f"(d[48]),"+f"(d[49]),"+f"(d[50]),"+f"(d[51]),"+f"(d[52]),"+f"(d[53]),"+f"(d[54]),"+f"(d[55]),"+f"(d[56]),"+f"(d[57]),"+f"(d[58]),"+f"(d[59]),
      "+f"(d[60]),"+f"(d[61]),"+f"(d[62]),"+f"(d[63]),"+f"(d[64]),"+f"(d[65]),"+f"(d[66]),"+f"(d[67]),"+f"(d[68]),"+f"(d[69]),"+f"(d[70]),"+f"(d[71]),
      "+f"(d[72]),"+f"(d[73]),"+f"(d[74]),"+f"(d[75]),"+f"(d[76]),"+f"(d[77]),"+f"(d[78]),"+f"(d[79]),"+f"(d[80]),"+f"(d[81]),"+f"(d[82]),"+f"(d[83]),
      "+f"(d[84]),"+f"(d[85]),"+f"(d[86]),"+f"(d[87]),"+f"(d[88]),"+f"(d[89]),"+f"(d[90]),"+f"(d[91]),"+f"(d[92]),"+f"(d[93]),"+f"(d[94]),"+f"(d[95])
    : "r"(alo), "r"(blo), "r"(sd), "n"(TB), "r"(DESC_HI), "n"(TA));
}

struct Ctx {
  uint32_t sm;
  uint32_t bar;
  uint32_t rbar;
  int cl, rank, wg, warp, lane, phases;
};
__device__ __forceinline__ void release(const Ctx& c, int b, int cnt = 1) {
  if (c.lane < 2) mbar_arrive_cl(c.rbar + b * 8, cnt);
}
#define HK 5
#define NPRO 6
#define ZLEAD 14
#define PFM 7
#define PF1 1
constexpr float SM_SCALE = 0.08838834764831845f * 1.4426950408889634f;
constexpr float SM_HI = 1.8446744e19f, SM_LO = 5.4210109e-20f;
constexpr int ORDER = 1;

__device__ __forceinline__ void stage_tile(const float (&a)[64], uint32_t buf, const Ctx& c, float s0, float s1) {
  const int row = (c.lane & 7) + ((c.lane >> 3) & 1) * 8;
  const uint32_t base = buf + (c.warp * 16 + row) * 128 + (((c.lane >> 4) ^ (row & 7)) << 4);
#pragma unroll
  for (int i = 0; i < 8; i++)
    stsm4((base ^ ((i & 3) << 5)) + (i >> 2) * 8192, pack_bf16(a[8 * i] * s0, a[8 * i + 1] * s0), pack_bf16(a[8 * i + 2] * s1, a[8 * i + 3] * s1),
          pack_bf16(a[8 * i + 4] * s0, a[8 * i + 5] * s0), pack_bf16(a[8 * i + 6] * s1, a[8 * i + 7] * s1));
}

__device__ __forceinline__ void p1_epilogue(const Params& p, const Ctx& c, const float (&acc)[64], int t, int type) {
  const int tile = p.s.r[c.cl].tile[t] & 63, b = c.wg * 2 + 1;
  mbar_wait(c.bar + (B_SE + b) * 8, (t & 1) ^ 1);
  if (type && tile >= 32) {
    const int r = 2 * (c.lane & 3) + ((c.lane >> 2) & 1);
    const uint32_t dst = c.sm + SM_BUF + b * 16384 + r * 128 + (((c.warp * 2) ^ r) << 4) + (c.lane >> 3) * 4;
#pragma unroll
    for (int i = 0; i < 16; i++) {
      asm volatile("st.shared.u32 [%0], %1;" ::"r"(dst + i * 1024), "r"(pack_bf16(acc[4 * i], acc[4 * i + 1])) : "memory");
      asm volatile("st.shared.u32 [%0], %1;" ::"r"((dst ^ 16) + i * 1024), "r"(pack_bf16(acc[4 * i + 2], acc[4 * i + 3])) : "memory");
    }
  } else {
    if (type) stage_tile(acc, c.sm + SM_BUF + b * 16384, c, SM_SCALE, SM_SCALE);
    else stage_tile(acc, c.sm + SM_BUF + b * 16384, c, 1.f, 1.f);
  }
  FENCE_ASYNC_SMEM();
  __syncwarp();
  if (c.lane == 0) mbar_arrive(c.bar + (B_SF + b) * 8);
}

__device__ __forceinline__ void p1_consumer(const Params& p, const Ctx& c) {
  const int n = p.s.r[c.cl].n1;
  const int type = p.s.r[c.cl].slab >> 3;
  const uint32_t bdesc = desc_lo(c.sm + SM_RING, 8192), adesc = desc_lo(c.sm + SM_BUF + 32768 + c.wg * 8192, 16);
  uint32_t A[128];
  float acc[64] = {};
  int slot = 0, par = 0;
  auto next = [&]() { if (++slot == 10) { slot = 0; par ^= 1; } };
  {
    const int row = (c.lane & 7) + ((c.lane >> 3) & 1) * 8;
    const uint32_t base = c.sm + SM_RING + (c.wg * 64 + c.warp * 16 + row) * 128 + (((c.lane >> 4) ^ (row & 7)) << 4);
    if (c.wg == 1) bar_sync(ORDER + 1, 256);
    int pa = -1, pb = -1;
    if (type) {
      mbar_wait(c.bar + B_P1F * 8, 0);
      WG_FENCE();
#pragma unroll
      for (int kk = 0; kk < 4; kk++) wgmma_ss128<1>(acc, adesc + kk * 2, bdesc + kk * 128, kk != 0);
      WG_COMMIT();
      pb = 0; slot = 1;
    }
#pragma unroll
    for (int kb = 0; kb < 8; kb++) {
      const int sa = slot;
      mbar_wait(c.bar + (B_P1F + slot) * 8, par);
      if (kb == 0) PROF(c.wg, 5);
      next();
      mbar_wait(c.bar + (B_P1F + slot) * 8, par);
      PROF(c.wg, 6 + 2 * kb);
      WG_FENCE();
#pragma unroll
      for (int kk = 0; kk < 4; kk++)
        wgmma_ss128<1>(acc, desc_lo(c.sm + SM_RING + c.wg * 8192, 16) + sa * 1024 + kk * 2, bdesc + slot * 1024 + kk * 128, (kb | kk) != 0 ? 1 : type);
      WG_COMMIT();
      if (kb == 1 && c.wg == 0) bar_arrive(ORDER + 1, 256);
#pragma unroll
      for (int kk = 0; kk < 4; kk++) ldsm4((base ^ (kk << 5)) + sa * 16384, A[kb * 16 + kk * 4], A[kb * 16 + kk * 4 + 1], A[kb * 16 + kk * 4 + 2], A[kb * 16 + kk * 4 + 3]);
      WG_WAIT(1);
      if (kb > 0) release(c, B_P1E + pa);
      if (kb > 0 || pb >= 0) release(c, B_P1E + pb);
      pa = sa; pb = slot;
      next();
    }
    WG_WAIT(0);
    __syncwarp();
    release(c, B_P1E + pa);
    release(c, B_P1E + pb);
    pin(acc);
    PROF(c.wg, 1);
    p1_epilogue(p, c, acc, 0, type);
    PROF(c.wg, 2);
  }
  for (int t = 1; t < n; t++) {
    bar_sync(ORDER + c.wg, 256);
    int prev1 = -1, prev2 = -1;
    if (type) {
      mbar_wait(c.bar + (B_P1F + slot) * 8, par);
      WG_FENCE();
#pragma unroll
      for (int kk = 0; kk < 4; kk++) wgmma_ss128<1>(acc, adesc + kk * 2, bdesc + slot * 1024 + kk * 128, kk != 0);
      WG_COMMIT();
      prev1 = slot;
      next();
    }
#pragma unroll
    for (int kb = 0; kb < 8; kb++) {
      mbar_wait(c.bar + (B_P1F + slot) * 8, par);
      WG_FENCE();
      const uint32_t d = bdesc + slot * 1024;
#pragma unroll
      for (int kk = 0; kk < 4; kk++)
        wgmma_rs128<1>(acc, A[kb * 16 + kk * 4], A[kb * 16 + kk * 4 + 1], A[kb * 16 + kk * 4 + 2], A[kb * 16 + kk * 4 + 3], d + kk * 128, (kb | kk) != 0 ? 1 : type);
      WG_COMMIT();
      if (kb == HK) {
        if (t + 1 < n || c.wg == 0) bar_arrive(ORDER + (c.wg ^ 1), 256);
      }
      if (kb > 0) { WG_WAIT(2); if (kb > 1 || prev2 >= 0) release(c, B_P1E + prev2); }
      prev2 = prev1; prev1 = slot;
      next();
    }
    WG_WAIT(1);
    release(c, B_P1E + prev2);
    WG_WAIT(0);
    pin(acc);
    release(c, B_P1E + prev1);
    p1_epilogue(p, c, acc, t, type);
    PROF(c.wg, 3);
  }
}

__device__ __forceinline__ void p1_producer(const Params& p, const Ctx& c) {
  const int n = p.s.r[c.cl].n1;
  const int type = p.s.r[c.cl].slab >> 3, grp = p.s.r[c.cl].slab & 7;
  int slot = NPRO % 10, par = NPRO < 10;
#pragma unroll 1
  for (int t = 0; t < n; t++) {
    const int tile = p.s.r[c.cl].tile[t] & 63;
    const CUtensorMap* m = &p.map_w[type * 2 + (tile >> 5)];
    const int n0 = (tile & 31) * 128 + c.rank * 64;
    const int ptile = p.s.r[c.cl].tile[t + PF1 < n ? t + PF1 : t];
    const CUtensorMap* pm = &p.map_w[type * 2 + ((ptile >> 5) & 1)];
    if (t == 7 && (c.phases & 16)) flag_wait<true>(F_GATE, 256);
#pragma unroll 1
    for (int kb = t ? -type : (NPRO - type) >> 1; kb < 8; kb++) {
      if (t == 0 && 2 * kb + type >= NPRO) {
        mbar_wait(c.bar + (B_P1E + slot) * 8, par);
        mbar_expect(c.bar + (B_P1F + slot) * 8, 16384);
        tma2d(c.sm + SM_RING + slot * 16384, &p.map_a[type], kb * 64, grp * 256 + c.rank * 128, c.bar + (B_P1F + slot) * 8);
        if (++slot == 10) { slot = 0; par ^= 1; }
      }
      mbar_wait(c.bar + (B_P1E + slot) * 8, par);
      mbar_expect(c.bar + (B_P1F + slot) * 8, 16384);
      tma2d_mc(c.sm + SM_RING + slot * 16384 + c.rank * 8192, m, n0, kb < 0 ? 512 : kb * 64, c.bar + (B_P1F + slot) * 8);
      if (t == 0 && kb == 1) PROF(2, 61);
      if (t == 0 && kb == 3) PROF(2, 62);
      if (t + PF1 < n && t > 0 && ((ptile & 64) || ((ptile & 128) && ((kb ^ grp) & PFM) == 0))) tma2d_prefetch(pm, (ptile & 31) * 128 + c.rank * 64, kb < 0 ? 512 : kb * 64);
      if (++slot == 10) { slot = 0; par ^= 1; }
    }
  }
}

__device__ __forceinline__ void p1_storer(const Params& p, const Ctx& c) {
  const int n = p.s.r[c.cl].n1;
  const int type = p.s.r[c.cl].slab >> 3, grp = p.s.r[c.cl].slab & 7;
  for (int i = 0; i < 2 * n; i++) {
    const int t = i >> 1, w = i & 1, b = w * 2 + 1;
    const int tile = p.s.r[c.cl].tile[t] & 63;
    mbar_wait(c.bar + (B_SF + b) * 8, t & 1);
    const uint32_t src = c.sm + SM_BUF + b * 16384;
    int f = (type ? F_Q : F_KV) + (tile & 31) * 8 + grp;
    if (type == 0) {
      const int prev = p.s.prev[tile & 31][grp];
      if (prev != 255 && w == 0) {
        if (grp >= 2) flag_wait<false>(F_RD + prev * 8 + grp, 8 - grp);
        else flag_wait<false>(F_CTX + max(c.lane & 7, grp) * 64 + prev, 4);
      }
      uint8_t* dst = g_KV + (size_t)(((tile & 32) + p.s.slot[tile & 31][grp]) * 16 + grp * 2 + c.rank) * 32768 + w * 8192;
      bulk_store(dst, src, 8192);
      bulk_store(dst + 16384, src + 8192, 8192);
    } else if (tile < 32) {
      bulk_store(g_Q + (size_t)(tile * 32 + grp * 4 + c.rank * 2 + w) * 16384, src, 16384);
    } else {
      tma3d_store(&p.map_t[2], src, 8 + (grp * 4 + c.rank * 2 + w) * 32, 0, (tile - 32) * 64);
      f = F_QKVA + grp * 4 + ((0xE4390900u >> (2 * (tile - 30))) & 3);
    }
    BULK_COMMIT();
    BULK_WAIT(0);
    mbar_arrive_one(c.bar + (B_SE + b) * 8);
    flag_add_rx(f);
  }
}

__device__ __forceinline__ int p2_buf(int w, int i) { return w * 2 + (i & 1); }
__device__ __forceinline__ int p2_blk(int rank, int w, int i) { return ((i ^ w) & 1) == 0 ? 3 - rank : rank; }

template <int N>
__device__ __forceinline__ void row_max(const float (&s)[N], float& m0, float& m1) {
  float a0 = fmaxf(s[0], s[1]), a1 = fmaxf(s[2], s[3]);
#pragma unroll
  for (int i = 1; i < N / 4; i++) {
    m0 = fmaxf(m0, s[4 * i]); a0 = fmaxf(a0, s[4 * i + 1]);
    m1 = fmaxf(m1, s[4 * i + 2]); a1 = fmaxf(a1, s[4 * i + 3]);
  }
  m0 = fmaxf(m0, a0); m1 = fmaxf(m1, a1);
  m0 = fmaxf(m0, __shfl_xor_sync(0xffffffffu, m0, 1));
  m1 = fmaxf(m1, __shfl_xor_sync(0xffffffffu, m1, 1));
  m0 = fmaxf(m0, __shfl_xor_sync(0xffffffffu, m0, 2));
  m1 = fmaxf(m1, __shfl_xor_sync(0xffffffffu, m1, 2));
}
template <bool SUB, int N>
__device__ __forceinline__ void row_exp(const float (&s)[N], uint32_t (&P)[32], float m0, float m1, float& t0, float& t1) {
  float u0 = 0.f, u1 = 0.f;
  t0 = t1 = 0.f;
#pragma unroll
  for (int i = 0; i < N / 4; i++) {
    const float e0 = ex2(SUB ? s[4 * i] - m0 : s[4 * i]), e1 = ex2(SUB ? s[4 * i + 1] - m0 : s[4 * i + 1]);
    const float e2 = ex2(SUB ? s[4 * i + 2] - m1 : s[4 * i + 2]), e3 = ex2(SUB ? s[4 * i + 3] - m1 : s[4 * i + 3]);
    if (i == 0) { t0 = e0; u0 = e1; t1 = e2; u1 = e3; }
    else { t0 += e0; u0 += e1; t1 += e2; u1 += e3; }
    P[2 * i] = pack_bf16(e0, e1);
    P[2 * i + 1] = pack_bf16(e2, e3);
  }
#pragma unroll
  for (int i = N / 2; i < 32; i++) P[i] = 0;
  pin(P);
  t0 += u0; t1 += u1;
}
template <int N>
__device__ __forceinline__ void causal_mask(float (&s)[N], int thr) {
#pragma unroll
  for (int i = 0; i < 8; i++) {
    if (8 * i > thr) s[N - 32 + 4 * i] = -INFINITY;
    if (8 * i + 1 > thr) s[N - 32 + 4 * i + 1] = -INFINITY;
    if (8 * i - 8 > thr) s[N - 32 + 4 * i + 2] = -INFINITY;
    if (8 * i - 7 > thr) s[N - 32 + 4 * i + 3] = -INFINITY;
  }
}
__device__ __forceinline__ void issue_qk(float (&s)[32], uint32_t qd, uint32_t kd) {
  WG_FENCE();
#pragma unroll
  for (int kk = 0; kk < 8; kk++) wgmma_ss64<0>(s, qd + (kk >> 2) * 512 + (kk & 3) * 2, kd + (kk >> 2) * 1024 + (kk & 3) * 2, kk != 0);
  WG_COMMIT();
}
__device__ __forceinline__ void issue_qk(float (&s)[64], uint32_t qd, uint32_t kd) {
  WG_FENCE();
#pragma unroll
  for (int kk = 0; kk < 8; kk++) wgmma_ss128<0>(s, qd + (kk >> 2) * 512 + (kk & 3) * 2, kd + (kk >> 2) * 1024 + (kk & 3) * 2, kk != 0);
  WG_COMMIT();
}
template <int NK>
__device__ __forceinline__ void issue_pv(float (&o)[64], const uint32_t (&P)[32], uint32_t vd, int acc) {
  WG_FENCE();
#pragma unroll
  for (int kk = 0; kk < NK; kk++) wgmma_rs128<1>(o, P[4 * kk], P[4 * kk + 1], P[4 * kk + 2], P[4 * kk + 3], vd + kk * 128, kk != 0 ? 1 : acc);
  WG_COMMIT();
}
__device__ __forceinline__ void stage_done(const Ctx& c, int b) {
  FENCE_ASYNC_SMEM();
  __syncwarp();
  if (c.lane == 0) mbar_arrive(c.bar + (B_SF + b) * 8);
}
__device__ __forceinline__ void p2_epilogue(const float (&o)[64], float s0, float s1, const Ctx& c, int b) {
  stage_tile(o, c.sm + SM_BUF + b * 16384, c, s0, s1);
  stage_done(c, b);
}

struct P2State {
  float m0, m1, l0, l1;
  bool shift;
  float e0, e1;
  int ks;
  int wi, ai;
  uint32_t wb, ab;
  uint32_t qd;
};
#define PROFZ()
__device__ __forceinline__ int wrap5(int q) { return q >= 5 ? q - 5 : q; }
__device__ __forceinline__ void turn_wait(uint32_t ring, int i) { mbar_wait(ring + (i & 3) * 8, (i >> 2) & 1); }
__device__ __forceinline__ void turn_pass(const Ctx& c, uint32_t ring, int i) { if (c.lane == 0) mbar_arrive(ring + (i & 3) * 8); }
__device__ __forceinline__ void p2_scales(P2State& z) {
  float l0 = z.l0, l1 = z.l1;
  l0 += __shfl_xor_sync(0xffffffffu, l0, 1);
  l1 += __shfl_xor_sync(0xffffffffu, l1, 1);
  l0 += __shfl_xor_sync(0xffffffffu, l0, 2);
  l1 += __shfl_xor_sync(0xffffffffu, l1, 2);
  asm("rcp.approx.ftz.f32 %0, %1;" : "=f"(z.e0) : "f"(l0));
  asm("rcp.approx.ftz.f32 %0, %1;" : "=f"(z.e1) : "f"(l1));
}
template <int N>
__device__ __forceinline__ void p2_first(const Ctx& c, P2State& z, float (&o)[64], uint32_t (&Pc)[32], uint32_t (&Pn)[32],
                                         int ks, int vs, int cnt, int acc) {
  float s[N] = {};
  issue_qk(s, z.qd, desc_lo(c.sm + SM_RING, 16) + ks * 2048);
  if (vs >= 0) {
    p2_scales(z);
    issue_pv<8>(o, Pc, desc_lo(c.sm + SM_RING, 16384) + vs * 2048, acc);
  } else {
    WG_COMMIT();
  }
  mbar_expect(z.ab + (z.ai++ & 3) * 8, cnt == 1 ? 8192 : 0);
  PROFZ();
  WG_WAIT(1);
  PROFZ();
  pin(s);
  release(c, B_P2E + ks, cnt);
  causal_mask(s, c.warp * 16 + (c.lane >> 2) - 2 * (c.lane & 3));
  z.m0 = z.m1 = 0.f;
  row_exp<false>(s, Pn, 0.f, 0.f, z.l0, z.l1);
  z.shift = __any_sync(0xffffffffu, !(z.l0 + z.l1 <= SM_HI) || ((c.lane & 3) == 0 && !(fminf(z.l0, z.l1) >= SM_LO)));
  if (__builtin_expect(z.shift, 0)) {
    z.m0 = z.m1 = -INFINITY;
    row_max(s, z.m0, z.m1);
    row_exp<true>(s, Pn, z.m0, z.m1, z.l0, z.l1);
  }
  WG_WAIT(0);
  pin(o);
  if (vs >= 0) release(c, B_P2E + vs, 1);
}

template <bool SECOND>
__device__ __forceinline__ void p2_turn(const Ctx& c, P2State& z, float (&o)[64], uint32_t (&Pc)[32], uint32_t (&Pn)[32],
                                        int eb = -1, bool half = false, int vcnt = 1) {
  float s[64] = {};
  const int ks = z.ks, vs = wrap5(ks + 1);
  PROFZ();
  turn_wait(z.wb, z.wi++);
  PROFZ();
  issue_qk(s, z.qd, desc_lo(c.sm + SM_RING, 16) + ks * 2048);
  const uint32_t vd = desc_lo(c.sm + SM_RING, 16384) + vs * 2048;
  if (SECOND) {
    if (eb >= 0) stage_tile(o, c.sm + SM_BUF + eb * 16384, c, z.e0, z.e1);
    if (half) issue_pv<4>(o, Pc, vd, 0); else issue_pv<8>(o, Pc, vd, 0);
  } else {
    issue_pv<8>(o, Pc, vd, 1);
  }
  turn_pass(c, z.ab, z.ai++);
  if (SECOND) { if (eb >= 0) stage_done(c, eb); }
  PROFZ();
  z.ks = wrap5(ks + 2);
  WG_WAIT(1);
  PROFZ();
  pin(s);
  release(c, B_P2E + ks, 1);
  float t0, t1, a0 = 1.f, a1 = 1.f;
  row_exp<false>(s, Pn, 0.f, 0.f, t0, t1);
  z.shift = __any_sync(0xffffffffu, z.shift || !(t0 + t1 <= SM_HI));
  const bool redo = z.shift;
  if (__builtin_expect(redo, 0)) {
    float n0 = z.m0, n1 = z.m1;
    row_max(s, n0, n1);
    a0 = ex2(z.m0 - n0); a1 = ex2(z.m1 - n1);
    z.m0 = n0; z.m1 = n1;
    z.l0 *= a0; z.l1 *= a1;
    row_exp<true>(s, Pn, z.m0, z.m1, t0, t1);
  }
  WG_WAIT(0);
  pin(o);
  release(c, B_P2E + vs, vcnt);
  if (__builtin_expect(redo, 0)) {
#pragma unroll
    for (int i = 0; i < 16; i++) { o[4 * i] *= a0; o[4 * i + 1] *= a0; o[4 * i + 2] *= a1; o[4 * i + 3] *= a1; }
  }
  z.l0 += t0; z.l1 += t1;
}
__device__ __forceinline__ void copy_p(uint32_t (&d)[32], const uint32_t (&s)[32], int zero) {
#pragma unroll
  for (int i = 0; i < 32; i++) asm volatile("add.s32 %0, %1, %2;" : "=r"(d[i]) : "r"(s[i]), "r"(zero));
}

__device__ __forceinline__ void p2_consumer(const Params& p, const Ctx& c, int rot) {
  const int nit = p.s.r[c.cl].n2;
  const uint32_t fring = c.bar + B_P2F * 8, oring = c.bar + B_ORD * 8;
  float o[64] = {};
  uint32_t Pa[32] = {}, Pb[32] = {};
  P2State z;
  z.e0 = z.e1 = z.l0 = z.l1 = 0.f; z.ks = rot; z.shift = false;
  int acc = 0, n = 0;
  for (int it = 0; it < nit; it++) {
    const int j = p.s.r[c.cl].item[it] & 7, blk = p2_blk(c.rank, c.wg, it);
    const int lng = ((it ^ c.wg) & 1) ^ 1;
    z.qd = desc_lo(c.sm + SM_BUF, 16) + p2_buf(c.wg, it) * 1024;
    if (lng) { z.wb = oring; z.wi = n - it; z.ab = fring; z.ai = n + 1; }
    else { z.wb = fring; z.wi = n + 2; z.ab = oring; z.ai = n - it; }
    PROFZ();
    mbar_wait(c.bar + (B_QF + p2_buf(c.wg, it)) * 8, (it >> 1) & 1);
    turn_wait(fring, n + 1 - lng);
    PROFZ();
    const int vs = it ? wrap5(z.ks + 1) : -1, ks = lng ? z.ks : wrap5(z.ks + (it ? 2 : 1));
    if (blk & 1) p2_first<64>(c, z, o, Pa, Pb, ks, vs, 1 + lng, acc);
    else p2_first<32>(c, z, o, Pa, Pb, ks, vs, 1 + lng, acc);
    z.ks = wrap5(ks + (it == 0 && lng ? 1 : 2));
    PROF(c.wg, 24 + it);
    n += 2 * j + 2;
    int left = 2 * j + lng;
    acc = left != 0;
    if (left == 0) { copy_p(Pa, Pb, p.zero); continue; }
    p2_turn<true>(c, z, o, Pb, Pa, it > 0 ? p2_buf(c.wg, it - 1) : -1, !(blk & 1), 1 + lng);
    while (--left > 0) {
      p2_turn<false>(c, z, o, Pa, Pb);
      if (--left == 0) { copy_p(Pa, Pb, p.zero); break; }
      p2_turn<false>(c, z, o, Pb, Pa);
    }
  }
  {
    if (!acc && nit > 1) p2_epilogue(o, z.e0, z.e1, c, p2_buf(c.wg, nit));
    turn_wait(z.wb, z.wi);
    issue_pv<8>(o, Pa, desc_lo(c.sm + SM_RING, 16384) + z.ks * 2048, acc);
    if (((nit - 1) ^ c.wg) & 1) turn_pass(c, z.ab, z.ai);
    p2_scales(z);
    WG_WAIT(0);
    pin(o);
    release(c, B_P2E + z.ks);
    p2_epilogue(o, z.e0, z.e1, c, p2_buf(c.wg, nit - 1));
    PROF(c.wg, 24 + nit);
  }
}

__device__ __forceinline__ void p2_load_q(const Params& p, const Ctx& c, int it, int w) {
  const int item = p.s.r[c.cl].item[it], h = item >> 3, j = item & 7, b = p2_buf(w, it);
  mbar_expect(c.bar + (B_QF + b) * 8, 16384);
  bulk_load(c.sm + SM_BUF + b * 16384, g_Q + (size_t)(h * 32 + j * 4 + p2_blk(c.rank, w, it)) * 16384, 16384, c.bar + (B_QF + b) * 8, POL(4));
}
__device__ __forceinline__ void wait_p1_free(const Ctx& c, int u1, int s) {
  mbar_wait(c.bar + (B_P1E + 2 * s) * 8, ((u1 - 1 - 2 * s) / 10) & 1);
  mbar_wait(c.bar + (B_P1E + 2 * s + 1) * 8, ((u1 - 2 - 2 * s) / 10) & 1);
}
__device__ __forceinline__ void p2_producer(const Params& p, const Ctx& c, int u1, int rot) {
  const int nit = p.s.r[c.cl].n2;
  int slot = rot, cnt = 0, par = 1, n = 0;
  const uint8_t* pv = nullptr;
  bool pl = false;
  auto load = [&](const uint8_t* src, int expect, uint32_t fb, bool last) {
    if (cnt < 5) {
      if (u1) {
        wait_p1_free(c, u1, slot);
        if (cnt == 0) p2_load_q(p, c, 0, 1);
      }
      cnt++;
    } else {
      if (slot == rot) par ^= 1;
      mbar_wait(c.bar + (B_P2E + slot) * 8, par);
    }
    if (expect) mbar_expect(fb, expect);
    bulk_load_mc(c.sm + SM_RING + slot * 32768 + c.rank * 16384, src, 16384, fb, last ? POL(5) : L2_NORMAL);
    slot = wrap5(slot + 1);
  };
  for (int it = 0; it < nit; it++) {
    const int item = p.s.r[c.cl].item[it], h = item >> 3, j = item & 7;
    if (it == 1 && (c.phases & 16) && p.s.r[c.cl].n1 < 8) flag_wait<true>(F_GATE, 256);
    uint32_t ready = (c.phases & 16) ? 0u : 255u;
    if (it == 0) { if (c.phases & 16) flag_wait<false>(F_Q + item, 4); mbar_wait(c.bar + B_LAD * 8, 0); p2_load_q(p, c, 0, 0); if (!u1) p2_load_q(p, c, 0, 1); }
    for (int t = 2 * j + 1; t >= 0; t--) {
      mask_wait(ready, t >> 1, F_KV + h * 8 + (c.lane & 7), 8);
      const uint8_t* k = g_KV + (size_t)(p.s.slot[h][t >> 1] * 16 + t) * 32768 + c.rank * 16384;
      const uint32_t fb = c.bar + (B_P2F + (n & 3)) * 8;
      const bool last = (p.s.r[c.cl].last[it] >> (t >> 1)) & 1;
      load(k, pv && t != 2 * j ? 65536 : 32768, fb, last);
      if (!(t & 1) && t + 4 <= 2 * j && c.rank == 0) flag_add_rx(F_RD + h * 8 + (t >> 1) + 2);
      if (pv) load(pv, 0, t != 2 * j ? fb : c.bar + (B_ORD + ((n - 1 - it) & 3)) * 8, pl);
      pl = last;
      pv = k + (size_t)NH * 16 * 32768;
      n++;
    }
  }
  load(pv, 32768, c.bar + (B_P2F + (n & 3)) * 8, pl);
}

__device__ __forceinline__ void p2_storer(const Params& p, const Ctx& c, int sfpar) {
  const int nit = p.s.r[c.cl].n2;
  auto load_q = [&](int it, int w) {
    if (c.phases & 16) flag_wait<false>(F_Q + p.s.r[c.cl].item[it], 4);
    p2_load_q(p, c, it, w);
  };
  if (nit > 1) {
    load_q(1, 1); p2_load_q(p, c, 1, 0); }
  for (int i = 0; i < 2 * nit; i++) {
    const int it = i >> 1, w = (it ^ i ^ 1) & 1, b = p2_buf(w, it);
    const int item = p.s.r[c.cl].item[it], h = item >> 3, j = item & 7;
    mbar_wait(c.bar + (B_SF + b) * 8, (sfpar >> b) & 1);
    sfpar ^= 1 << b;
    bulk_store(g_Q + (size_t)(h * 32 + j * 4 + p2_blk(c.rank, w, it)) * 16384, c.sm + SM_BUF + b * 16384, 16384, POL(1));
    BULK_COMMIT();
    BULK_WAIT(0);
    flag_add_rx(F_CTX + j * 64 + h);
    if ((i & 1) && it + 2 < nit) { load_q(it + 2, w); p2_load_q(p, c, it + 2, w ^ 1); }
  }
  release(c, B_DONE);
}

__device__ __forceinline__ int p3_pos(int i, int x) { return i < 4 ? (i + x) & 3 : 4; }
__device__ __forceinline__ void p3_consumer(const Params& p, const Ctx& c, int x) {
  const bool first = p.s.r[c.cl].p3 >= 24;
  const int tile = p.s.r[c.cl].p3 - (first ? 24 : 0), j = tile / 3, nt = tile - 3 * j;
  const int na = first ? 9 : 0, nb = 2 * (p.s.task[c.cl][1] - p.s.task[c.cl][0]);
  const uint32_t ad = desc_lo(c.sm + SM_RING + c.wg * 8192, 16), bd = desc_lo(c.sm + SM_RING + 16384, 4096);
  float acc[96] = {};
  int slot = 0, par = 0, prev = 0;
  float g0 = 0.f, g1 = 0.f;
  const int hold = c.wg && LAG ? na + nb - LAG : -1, pass = c.wg || !LAG ? -1 : na + nb - 1;
#pragma unroll 1
  for (int kb = 0; kb < nb; kb++) {
    if (kb == hold) bar_sync(6, 256);
    mbar_wait(c.bar + (B_P3F + slot) * 8, par);
    if (kb == 0) PROF(c.wg, 39);
    WG_FENCE();
#pragma unroll
    for (int kk = 0; kk < 4; kk++) wgmma_ss192<1>(acc, ad + p3_pos(slot, x) * 2560 + kk * 2, bd + p3_pos(slot, x) * 2560 + (kk >> 1) * 768 + (kk & 1) * 128, kk != 0 ? 1 : kb != 0);
    WG_COMMIT();
    if (kb == pass) bar_arrive(6, 256);
    WG_WAIT(1);
    if (kb > 0) release(c, B_P3E + prev);
    else {
      const float* g = g_gate + j * 256 + c.rank * 128 + c.wg * 64 + c.warp * 16 + (c.lane >> 2);
      g0 = __ldcg(g); g1 = __ldcg(g + 8);
    }
    prev = slot;
    if (++slot == 5) { slot = 0; par ^= 1; }
  }
  WG_WAIT(0);
  pin(acc);
  g0 = 1.f - g0; g1 = 1.f - g1;
#pragma unroll
  for (int i = 0; i < 24; i++) { acc[4 * i] *= g0; acc[4 * i + 1] *= g0; acc[4 * i + 2] *= g1; acc[4 * i + 3] *= g1; }
#pragma unroll 1
  for (int kb = nb; kb < nb + na; kb++) {
    if (kb == hold) bar_sync(6, 256);
    mbar_wait(c.bar + (B_P3F + slot) * 8, par);
    if (kb == 0) PROF(c.wg, 39);
    WG_FENCE();
#pragma unroll
    for (int kk = 0; kk < 4; kk++) wgmma_ss192<1, 1>(acc, ad + p3_pos(slot, x) * 2560 + kk * 128, bd + p3_pos(slot, x) * 2560 + (kk >> 1) * 768 + (kk & 1) * 128, 1);
    WG_COMMIT();
    if (kb == pass) bar_arrive(6, 256);
    WG_WAIT(1);
    if (kb > 0) release(c, B_P3E + prev);
    prev = slot;
    if (++slot == 5) { slot = 0; par ^= 1; }
  }
  WG_WAIT(0);
  pin(acc);
  PROF(c.wg, 40);
  if (first) bar_sync(4 + c.wg, 128);
  mbar_wait(c.bar + B_OUT * 8, 0);
  const int row = (c.lane & 7) + ((c.lane >> 3) & 1) * 8;
  const uint32_t wbase = c.sm + SM_RING + c.wg * 8192 + c.warp * 2048;
  const uint32_t base = wbase + row * 128 + (((c.lane >> 4) ^ (row & 7)) << 4);
#pragma unroll
  for (int i = 0; i < 12; i++) {
    stsm4((base ^ ((i & 3) << 5)) + (i >> 2) * 40960, pack_bf16(acc[8 * i], acc[8 * i + 1]), pack_bf16(acc[8 * i + 2], acc[8 * i + 3]),
          pack_bf16(acc[8 * i + 4], acc[8 * i + 5]), pack_bf16(acc[8 * i + 6], acc[8 * i + 7]));
    if ((i & 3) == 3) {
      FENCE_ASYNC_SMEM();
      bar_sync(4 + c.wg, 128);
      if (c.warp == (i >> 2)) tma2d_add(&p.map_out, c.sm + SM_RING + c.wg * 8192 + c.warp * 40960, nt * 192 + c.warp * 64, j * 256 + c.rank * 128 + c.wg * 64);
    }
  }
  BULK_COMMIT();
  PROF(c.wg, 43);
  BULK_WAIT_READ(0);
  PROF(c.wg, 44);
}

__device__ __forceinline__ void p3_producer(const Params& p, const Ctx& c, int u1, int u2, int rot, int x) {
  const bool first = p.s.r[c.cl].p3 >= 24;
  const int tile = p.s.r[c.cl].p3 - (first ? 24 : 0), j = tile / 3, nt = tile - 3 * j;
  int slot = 0, par = 1, cnt = 0;
  auto wait_free = [&](int s) {
    const int f = wrap5(s + 5 - rot);
    if (f < u2) mbar_wait(c.bar + (B_P2E + s) * 8, ((u2 - 1 - f) / 5) & 1);
    else if (u1) wait_p1_free(c, u1, s);
  };
  asm volatile(ELECT("prefetch.tensormap [%0];") ::"l"(&p.map_o[0]) : "memory");
  asm volatile(ELECT("prefetch.tensormap [%0];") ::"l"(&p.map_out) : "memory");
  if ((c.phases & 16) && p.s.r[c.cl].n1 < 8 && p.s.r[c.cl].n2 < 2) flag_wait<true>(F_GATE, 256);
  uint32_t ready = (c.phases & 16) ? 0u : ~0u;
  const int q1 = p.s.task[c.cl][1] - !first;
  for (int q = p.s.task[c.cl][0]; q <= q1; q++) {
    const bool brA = first && q == q1;
    const int g = brA ? 32 : p.s.p3_order[tile][q];
    if (brA) { if (c.phases & 16) flag_wait<false>(F_CTX + j * 64 + 32, 16); }
    else mask_wait(ready, g, F_CTX + j * 64 + c.lane, 4);
    const int nk = brA ? 9 : 2, k0 = (brA ? 0 : g * 128) + c.rank * 32;
    const uint8_t* a = brA ? g_oA + (j * 4 + c.rank * 2) * 73728 : g_Q + (size_t)(g * 32 + j * 4 + c.rank * 2) * 16384;
    const CUtensorMap* m = &p.map_o[brA];
    for (int i = 0; i < nk; i++) {
      const uint32_t st = c.sm + SM_RING + p3_pos(slot, x) * 40960, fb = c.bar + (B_P3F + slot) * 8;
      if (cnt < 4) { wait_free(p3_pos(cnt, x)); wait_free(p3_pos(cnt, x) + 1); }
      else if (cnt == 4) mbar_wait(c.bar + B_DONE * 8, 0);
      else mbar_wait(c.bar + (B_P3E + slot) * 8, par);
      cnt++;
      mbar_expect(fb, 40960);
      bulk_load(st, a + i * 8192, 8192, fb, POL(3));
      bulk_load(st + 8192, a + (nk + i) * 8192, 8192, fb, POL(3));
      tma3d_mc(st + 16384 + c.rank * 12288, m, 0, k0 + i * 64, nt * 3, fb);
      if (++slot == 5) { slot = 0; par ^= 1; }
    }
  }
}

__device__ __forceinline__ float bf_lo(uint32_t w) { return __uint_as_float(w << 16); }
__device__ __forceinline__ float bf_hi(uint32_t w) { return __uint_as_float(w & 0xffff0000u); }

__device__ __forceinline__ void gate_rows(const Params& p, int row0, int lane) {
  const uint4* x = reinterpret_cast<const uint4*>(p.x + (size_t)(row0 + (lane >> 2)) * DM) + (lane & 3);
  const uint4* w = reinterpret_cast<const uint4*>(p.gate_w) + (lane & 3);
  float a = 0.f;
#pragma unroll 1
  for (int b = 0; b < 3; b++) {
    uint4 u[6];
#pragma unroll
    for (int i = 0; i < 6; i++) u[i] = __ldg(x + (b * 6 + i) * 4);
#pragma unroll
    for (int i = 0; i < 6; i++) {
      const uint4 v = __ldg(w + (b * 6 + i) * 4);
      a = fmaf(bf_lo(u[i].x), bf_lo(v.x), a); a = fmaf(bf_hi(u[i].x), bf_hi(v.x), a);
      a = fmaf(bf_lo(u[i].y), bf_lo(v.y), a); a = fmaf(bf_hi(u[i].y), bf_hi(v.y), a);
      a = fmaf(bf_lo(u[i].z), bf_lo(v.z), a); a = fmaf(bf_hi(u[i].z), bf_hi(v.z), a);
      a = fmaf(bf_lo(u[i].w), bf_lo(v.w), a); a = fmaf(bf_hi(u[i].w), bf_hi(v.w), a);
    }
  }
  a += __shfl_xor_sync(0xffffffffu, a, 1);
  a += __shfl_xor_sync(0xffffffffu, a, 2);
  if ((lane & 3) == 0) g_gate[row0 + (lane >> 2)] = 1.f / (1.f + __expf(-a));
}

__device__ __forceinline__ void lds10(uint32_t (&k)[10], uint32_t a) {
  asm volatile("ld.shared.v2.u32 {%0, %1}, [%10];\nld.shared.v2.u32 {%2, %3}, [%10+8];\nld.shared.v2.u32 {%4, %5}, [%10+16];\n"
               "ld.shared.v2.u32 {%6, %7}, [%10+24];\nld.shared.v2.u32 {%8, %9}, [%10+32];"
               : "=r"(k[0]), "=r"(k[1]), "=r"(k[2]), "=r"(k[3]), "=r"(k[4]), "=r"(k[5]), "=r"(k[6]), "=r"(k[7]), "=r"(k[8]), "=r"(k[9]) : "r"(a));
}
__device__ __forceinline__ void local_attn(const Params& p, const Ctx& c, int rb, int hs) {
  const int lane = c.lane, grp = rb >> 2, par = lane >> 4, i0 = 2 * (lane & 15);
  const uint32_t buf = c.sm + SM_BUF + (c.warp - 2) * 8192, bqk = c.bar + (B_LA + (c.warp - 2) * 2) * 8, bv = bqk + 8;
  const uint32_t mine = buf + 2304 + par * 160 + i0 * 4;
  const bool flags = c.phases & 16;
  auto fetch_qk = [&](int i) {
    if (flags && !(i & 1)) {
      const int q = i >> 1;
      const int tgt = q == 0 ? 24 : q == 3 ? 8 : 12;
      flag_wait<false>(F_QKVA + (grp - (grp > 0 && (rb & 3) == 0 ? par : 0)) * 4 + q, tgt);
    }
    mbar_expect(bqk, 5184);
    tma3d(buf, &p.map_t[0], rb * 32 + 8, 0, 9 * (4 * i + hs), bqk, POL(2));
    tma3d(buf + 2304, &p.map_t[1], rb * 32, 0, 288 + 9 * (4 * i + hs), bqk, POL(2));
  };
  auto fetch_v = [&](int i) { mbar_expect(bv, 2880); tma3d(buf + 5248, &p.map_t[1], rb * 32, 0, 576 + 9 * (4 * i + hs), bv, POL(2)); };
  fetch_qk(0);
  if (flags) flag_wait<true>(F_GATE, 256);
#pragma unroll 1
  for (int q = 0; q < 8; q++) {
    fetch_v(q);
    float a[8], b[8];
#pragma unroll
    for (int w = 0; w < 8; w++) a[w] = b[w] = 0.f;
    mbar_wait(bqk, q & 1);
    PROFB(1 + 2 * q);
#pragma unroll 1
    for (int j = 0; j < 9; j++) {
      uint32_t x, y, k[10];
      asm volatile("ld.shared.v2.u32 {%0, %1}, [%2];" : "=r"(x), "=r"(y) : "r"(buf + lane * 8 + j * 256));
      lds10(k, mine + j * 320);
      const float xl = bf_lo(x), xh = bf_hi(x), yl = bf_lo(y), yh = bf_hi(y);
#pragma unroll
      for (int m = 1; m < 10; m++) {
        const float kl = bf_lo(k[m]), kh = bf_hi(k[m]);
        if (m < 9) a[8 - m] = fmaf(xl, kl, fmaf(xh, kh, a[8 - m]));
        if (m > 1) b[9 - m] = fmaf(yl, kl, fmaf(yh, kh, b[9 - m]));
      }
    }
    __syncwarp();
    if (q < 7) fetch_qk(q + 1);
    constexpr float SC = 0.23570226039551584f * 1.4426950408889634f;
    const float* gp = g_gate + rb * 64 + 2 * i0 + par;
    const float ga = __ldcg(gp), gb = __ldcg(gp + 2);
    float ma = a[0], mb = b[0];
#pragma unroll
    for (int w = 1; w < 8; w++) {
      if (rb == 0) {
        if (i0 < w) a[w] = -INFINITY;
        if (i0 + 1 < w) b[w] = -INFINITY;
      }
      ma = fmaxf(ma, a[w]); mb = fmaxf(mb, b[w]);
    }
    float la = 0.f, lb = 0.f;
#pragma unroll
    for (int w = 0; w < 8; w++) {
      a[w] = ex2((a[w] - ma) * SC); b[w] = ex2((b[w] - mb) * SC);
      la += a[w]; lb += b[w];
    }
    la = __fdividef(ga, la); lb = __fdividef(gb, lb);
#pragma unroll
    for (int w = 0; w < 8; w++) { a[w] *= la; b[w] *= lb; }
    uint8_t* dst = g_oA + rb * 73728 + ((i0 & 2) + par) * 4;
    mbar_wait(bv, q & 1);
#pragma unroll 1
    for (int j = 0; j < 9; j++) {
      uint32_t v[10];
      lds10(v, mine + 2944 + j * 320);
      float a0 = 0.f, a1 = 0.f, b0 = 0.f, b1 = 0.f;
#pragma unroll
      for (int m = 1; m < 10; m++) {
        const float vl = bf_lo(v[m]), vh = bf_hi(v[m]);
        if (m < 9) { a0 = fmaf(a[8 - m], vl, a0); a1 = fmaf(a[8 - m], vh, a1); }
        if (m > 1) { b0 = fmaf(b[9 - m], vl, b0); b1 = fmaf(b[9 - m], vh, b1); }
      }
      const uint32_t wa = pack_bf16(a0, a1), wb = pack_bf16(b0, b1);
      const uint32_t got = __shfl_xor_sync(0xffffffffu, par ? wa : wb, 16);
      const uint32_t r0 = par ? got : wa, r1 = par ? wb : got;
      const int col = 18 * (4 * q + hs) + 2 * j, o = col * 128 + ((((i0 >> 2) ^ col) & 7) << 4);
      *reinterpret_cast<uint32_t*>(dst + o) = __byte_perm(r0, r1, 0x5410);
      *reinterpret_cast<uint32_t*>(dst + ((o + 128) ^ 16)) = __byte_perm(r0, r1, 0x7632);
    }
    __syncwarp();
    PROFB(2 + 2 * q);
  }
  mbar_arrive_one(c.bar + B_LAD * 8);
  flag_add(F_CTX + grp * 64 + 32);
}

__global__ void __cluster_dims__(2, 1, 1) __launch_bounds__(384, 1) fused_kernel(const __grid_constant__ Params p) {
  extern __shared__ uint8_t smem_raw[];
  Ctx c;
  c.sm = ((uint32_t)__cvta_generic_to_shared(smem_raw) + 1023u) & ~1023u;
  c.bar = c.sm + SM_BAR;
  c.lane = threadIdx.x & 31;
  const int wid = __shfl_sync(0xffffffffu, threadIdx.x >> 5, 0);
  if (wid < 6) asm volatile("prefetch.tensormap [%0];" ::"l"(&p.map_a[0] + wid) : "memory");
  c.wg = wid >> 2;
  c.warp = wid & 3;
  PROF(c.wg, 0);
  PROFG(61);
  c.cl = (blockIdx.x + (wid >> 4)) >> 1;
  c.rank = blockIdx.x & 1;
  c.rbar = mapa(c.bar, c.lane & 1);
  {
    const int w = wid, cnt = (((int)(B_CNT >> (4 * w)) - 1) & 15) + 1;
    if (w < 11) {
#pragma unroll
      for (int i = 0; i < 8; i++) asm volatile("mbarrier.init.shared::cta.b64 [%0], %1;" ::"r"(c.bar + w * 64 + i * 8), "r"(cnt));
    }
    asm volatile("fence.mbarrier_init.release.cluster;" ::: "memory");
  }
  if (c.wg == 2) PROF(2, 56);
  asm volatile("barrier.cluster.arrive.relaxed;" ::: "memory");
  c.phases = p.s.r[c.cl].phases;
  const bool do1 = p.s.r[c.cl].n1 > 0, do2 = p.s.r[c.cl].n2 > 0, do3 = p.s.r[c.cl].p3 != 255;
  if (do1 && c.wg == 2 && c.warp == 0) {
    const int type = p.s.r[c.cl].slab >> 3;
    PROF(2, 57);
    FENCE_ASYNC_SMEM();
    mbar_expect(c.bar + B_P1F * 8, type ? 32768 : 16384);
    tma2d(type ? c.sm + SM_BUF + 32768 : c.sm + SM_RING, &p.map_a[type], type ? 512 : 0, (p.s.r[c.cl].slab & 7) * 256 + c.rank * 128, c.bar + B_P1F * 8);
    PROF(2, 58);
  }
  asm volatile("barrier.cluster.wait.acquire;" ::: "memory");
  if (c.wg == 2) PROF(2, 59);
  if (do1 && c.wg == 2 && c.warp == 0) {
    const int type = p.s.r[c.cl].slab >> 3, tile = p.s.r[c.cl].tile[0] & 63;
    const CUtensorMap* m = &p.map_w[type * 2 + (tile >> 5)];
#pragma unroll 1
    for (int s = 1 - type; s < NPRO; s++) {
      const int kb = (s - type) >> 1;
      const uint32_t fb = c.bar + (B_P1F + s) * 8;
      if (s) mbar_expect(fb, 16384);
      if ((s ^ type) & 1) tma2d_mc(c.sm + SM_RING + s * 16384 + c.rank * 8192, m, (tile & 31) * 128 + c.rank * 64, kb < 0 ? 512 : kb * 64, fb);
      else tma2d(c.sm + SM_RING + s * 16384, &p.map_a[type], kb * 64, (p.s.r[c.cl].slab & 7) * 256 + c.rank * 128, fb);
    }
  }

  if (c.wg < 2) {
    PROF(c.wg, 4);
    asm volatile("setmaxnreg.inc.sync.aligned.u32 224;");
    if (c.wg == 1) {
      if (do1) bar_arrive(ORDER, 256);
      if (c.lane == 0) mbar_arrive(c.bar + B_P2F * 8);
    }
    if (do1) p1_consumer(p, c);
    if (do2) p2_consumer(p, c, p.s.r[c.cl].rot);
    if (do3) p3_consumer(p, c, p.s.r[c.cl].x3);
    PROF(c.wg, 63);
    PROFG(62);
    if (c.lane == 0) mbar_arrive(c.bar + B_FIN * 8);
    __syncwarp();
    cluster_sync();
  } else {
    asm volatile("setmaxnreg.dec.sync.aligned.u32 56;");
    if (c.warp == 0) {
      PROF(2, 60);
      if (do1) p1_producer(p, c);
      if (do2) p2_producer(p, c, p.s.r[c.cl].u1, p.s.r[c.cl].rot);
      if (do3) p3_producer(p, c, p.s.r[c.cl].u1, p.s.r[c.cl].u2, p.s.r[c.cl].rot, p.s.r[c.cl].x3);
    } else if (c.warp == 1) {
      int sfpar = 0;
      if (do1) {
        p1_storer(p, c);
        sfpar = (p.s.r[c.cl].n1 & 1) * 10;
      }
      if (do2) p2_storer(p, c, sfpar);
      else { mbar_wait(c.bar + B_LAD * 8, 0); release(c, B_DONE); }
      if (do3) {
        const int tile = p.s.r[c.cl].p3 % 24;
        if (p.s.task[c.cl][1] == 32) {
          for (int r = 0; r < (2 * (32 - p.s.task[c.cl][0]) - ZLEAD) / 5; r++) mbar_wait(c.bar + B_P3F * 8, r & 1);
          const int j = tile / 3, nt = tile - 3 * j;
          uint4* o = reinterpret_cast<uint4*>(p.out + (size_t)(j * 256 + c.rank * 128 + (c.lane >> 3)) * DM + nt * 192) + (c.lane & 7);
#pragma unroll 4
          for (int r = 0; r < 32; r++) o[r * 288] = o[r * 288 + 8] = o[r * 288 + 16] = make_uint4(0u, 0u, 0u, 0u);
          __syncwarp();
          flag_add(F_OUT + tile * 2 + c.rank);
        } else if (c.phases & 16) {
          flag_wait<false, 256>(F_OUT + tile * 2 + c.rank, 1);
        }
        mbar_arrive_one(c.bar + B_OUT * 8);
      }
    } else {
      const int bw = blockIdx.x * 2 + (c.warp - 2);
      if ((c.phases & 1) && bw < 256) {
        gate_rows(p, bw * 8, c.lane);
        __syncwarp();
        flag_add(F_GATE);
      }
      if (p.s.r[c.cl].bg != 255) local_attn(p, c, p.s.r[c.cl].bg, bw & 3);
      else if (c.lane == 0) mbar_arrive(c.bar + B_LAD * 8);
    }
    __syncwarp();
    bar_sync(3, 128);
    if (c.warp == 0 && (c.phases & 32)) {
      int last = 0;
      if (c.lane == 0) { __threadfence(); last = atomicAdd(g_flags + F_DONE, 1) == 2 * NCL - 1; }
      if (__shfl_sync(0xffffffffu, last, 0)) for (int i = c.lane; i < F_NUM; i += 32) g_flags[i] = 0;
    }
    if (c.warp == 1) mbar_wait(c.bar + B_FIN * 8, 0);
    __syncwarp();
    cluster_sync();
  }
}

SCHED_DECL Sched k_sched = {
  {{0,29,1,38,0,{155,0,0,0,0,0,0,0,0,0,0},{0,0,0,0,0,0,0,0,0,0,0},{64,39,1,46,16,18,3,12,9,5,27,31,13,25,21,28,20,4,2,11,24,15,29,23,26,19,8,17,30,0}},
   {1,29,2,21,1,{152,210,0,0,0,0,0,0,0,0,0},{0,0,0,0,0,0,0,0,0,0,0},{64,33,150,39,16,18,3,12,9,5,27,31,13,28,21,25,2,4,20,11,24,15,23,29,19,26,8,17,30,0}},
   {2,29,1,30,2,{68,0,0,0,0,0,0,0,0,0,0},{31,0,0,0,0,0,0,0,0,0,0},{70,33,150,39,16,10,3,12,5,9,27,31,13,21,25,28,2,4,20,11,24,15,23,19,26,29,8,17,30,0}},
   {3,29,0,22,3,{0,0,0,0,0,0,0,0,0,0,0},{0,0,0,0,0,0,0,0,0,0,0},{65,38,7,54,16,10,3,12,5,9,27,31,21,25,13,28,2,4,20,11,24,15,23,26,29,19,8,17,30,0}},
   {4,28,1,13,4,{212,0,0,0,0,0,0,0,0,0,0},{31,0,0,0,0,0,0,0,0,0,0},{65,32,150,39,16,10,35,5,9,27,31,21,13,25,28,2,4,20,11,24,15,23,26,29,19,8,17,30,0,0}},
   {5,27,1,0,5,{237,0,0,0,0,0,0,0,0,0,0},{0,0,0,0,0,0,0,0,0,0,0},{70,33,7,54,16,10,44,3,41,31,21,13,25,28,2,4,20,11,24,15,23,26,29,19,8,17,30,0,0,0}},
   {6,26,0,7,6,{0,0,0,0,0,0,0,0,0,0,0},{0,0,0,0,0,0,0,0,0,0,0},{64,6,150,46,18,12,35,9,59,21,13,25,28,2,20,4,11,24,15,26,23,29,8,19,17,30,0,0,0,0}},
   {7,25,4,39,7,{16,89,233,66,0,0,0,0,0,0,0},{0,3,0,0,0,0,0,0,0,0,0},{65,6,150,80,74,67,101,91,127,77,121,66,84,68,75,88,79,90,87,93,72,83,81,94,126,0,0,0,0,0}},
   {0,29,2,35,8,{64,139,0,0,0,0,0,0,0,0,0},{0,0,0,0,0,0,0,0,0,0,0},{96,6,33,22,48,50,35,44,41,37,59,63,45,57,53,60,52,36,34,43,56,47,61,55,58,51,40,49,62,0}},
   {1,29,1,41,9,{140,0,0,0,0,0,0,0,0,0,0},{0,0,0,0,0,0,0,0,0,0,0},{96,6,118,14,48,50,35,44,41,37,59,63,45,60,53,57,34,36,52,43,56,47,55,61,51,58,40,49,62,0}},
   {2,29,0,12,10,{0,0,0,0,0,0,0,0,0,0,0},{0,0,0,0,0,0,0,0,0,0,0},{102,0,118,14,48,42,35,44,37,41,59,63,45,53,57,60,34,36,52,43,56,47,55,51,58,61,40,49,62,0}},
   {3,29,1,22,11,{67,0,0,0,0,0,0,0,0,0,0},{0,0,0,0,0,0,0,0,0,0,0},{97,0,39,14,48,42,35,44,37,41,59,63,53,57,45,60,34,36,52,43,56,47,55,58,61,51,40,49,62,0}},
   {4,28,0,21,12,{0,0,0,0,0,0,0,0,0,0,0},{0,0,0,0,0,0,0,0,0,0,0},{97,6,118,14,48,42,12,37,41,59,63,53,45,57,60,34,36,52,43,56,47,55,58,61,51,40,49,62,0,0}},
   {5,27,1,17,13,{157,0,0,0,0,0,0,0,0,0,0},{0,0,0,0,0,0,0,0,0,0,0},{102,0,39,14,48,42,69,35,27,63,53,45,57,60,34,36,52,43,56,47,55,58,61,51,40,49,62,0,0,0}},
   {6,26,1,6,14,{238,0,0,0,0,0,0,0,0,0,0},{0,0,0,0,0,0,0,0,0,0,0},{96,38,118,80,50,108,69,105,95,117,45,57,60,34,52,36,43,56,47,58,55,61,40,51,49,62,0,0,0,0}},
   {7,23,4,46,15,{32,161,124,137,0,0,0,0,0,0,0},{0,0,31,0,0,0,0,0,0,0,0},{97,38,118,112,106,99,73,123,85,109,92,98,116,100,107,120,111,122,119,125,104,115,113,0,0,0,0,0,0,0}},
   {0,6,5,3,255,{2,49,149,220,228,0,0,0,0,0,0},{0,0,0,0,0,0,0,0,0,0,0},{71,38,78,54,74,42,0,0,0,0,0,0,0,0,0,0,0,0,0,0,0,0,0,0,0,0,0,0,0,0}},
   {1,6,4,14,255,{61,113,78,205,0,0,0,0,0,0,0},{0,0,0,0,0,0,0,0,0,0,0},{65,38,7,46,74,42,0,0,0,0,0,0,0,0,0,0,0,0,0,0,0,0,0,0,0,0,0,0,0,0}},
   {2,6,6,10,255,{176,57,132,26,25,23,0,0,0,0,0},{0,0,0,0,0,0,0,0,0,0,0},{65,32,7,46,18,50,0,0,0,0,0,0,0,0,0,0,0,0,0,0,0,0,0,0,0,0,0,0,0,0}},
   {3,6,6,4,255,{112,60,102,252,189,211,0,0,0,0,0},{0,0,0,0,0,0,0,0,0,0,0},{70,32,150,46,18,50,0,0,0,0,0,0,0,0,0,0,0,0,0,0,0,0,0,0,0,0,0,0,0,0}},
   {4,8,6,8,255,{128,103,97,105,166,247,0,0,0,0,0},{0,0,0,0,0,255,0,0,0,0,0},{64,38,7,46,18,50,3,44,0,0,0,0,0,0,0,0,0,0,0,0,0,0,0,0,0,0,0,0,0,0}},
   {5,10,5,9,255,{144,84,74,167,232,0,0,0,0,0,0},{0,0,0,128,0,0,0,0,0,0,0},{65,32,150,46,18,50,12,37,9,59,0,0,0,0,0,0,0,0,0,0,0,0,0,0,0,0,0,0,0,0}},
   {6,10,5,42,255,{80,101,253,226,71,0,0,0,0,0,0},{0,0,0,0,128,0,0,0,0,0,0},{71,1,78,112,74,42,3,37,27,63,0,0,0,0,0,0,0,0,0,0,0,0,0,0,0,0,0,0,0,0}},
   {7,4,6,5,255,{52,116,145,222,18,192,0,0,0,0,0},{0,0,0,0,0,0,0,0,0,0,0},{71,0,78,82,0,0,0,0,0,0,0,0,0,0,0,0,0,0,0,0,0,0,0,0,0,0,0,0,0,0}},
   {8,19,4,12,16,{104,19,194,234,0,0,0,0,0,0,0},{0,0,0,0,0,0,0,0,0,0,0},{71,41,78,16,18,39,104,12,27,5,13,31,4,11,2,29,26,8,17,0,0,0,0,0,0,0,0,0,0,0}},
   {9,17,2,8,17,{171,163,0,0,0,0,0,0,0,0,0},{0,0,0,0,0,0,0,0,0,0,0},{128,33,166,35,44,10,104,9,3,5,13,25,4,2,24,23,8,0,0,0,0,0,0,0,0,0,0,0,0,0}},
   {10,19,2,2,18,{248,164,0,0,0,0,0,0,0,0,0},{0,28,0,0,0,0,0,0,0,0,0},{70,33,34,103,14,18,3,45,12,27,13,25,28,4,15,83,29,26,30,0,0,0,0,0,0,0,0,0,0,0}},
   {11,18,2,2,19,{94,142,0,0,0,0,0,0,0,0,0},{0,0,0,0,0,0,0,0,0,0,0},{65,41,34,16,44,18,104,12,5,31,13,28,2,11,15,23,19,17,0,0,0,0,0,0,0,0,0,0,0,0}},
   {12,19,2,40,20,{93,246,0,0,0,0,0,0,0,0,0},{0,0,0,0,0,0,0,0,0,0,0},{65,41,7,14,35,44,18,40,9,31,13,28,20,11,15,26,19,8,30,0,0,0,0,0,0,0,0,0,0,0}},
   {13,18,3,9,21,{40,227,239,0,0,0,0,0,0,0,0},{1,0,255,0,0,0,0,0,0,0,0},{70,41,22,16,18,69,35,44,45,27,21,25,28,2,24,23,29,8,0,0,0,0,0,0,0,0,0,0,0,0}},
   {14,19,3,45,22,{200,35,158,0,0,0,0,0,0,0,0},{0,0,127,0,0,0,0,0,0,0,0},{128,165,22,43,35,44,12,9,45,31,13,28,20,4,15,23,19,17,30,0,0,0,0,0,0,0,0,0,0,0}},
   {15,18,1,6,23,{38,0,0,0,0,0,0,0,0,0,0},{0,0,0,0,0,0,0,0,0,0,0},{65,36,22,34,3,39,5,91,45,85,25,66,4,88,90,29,19,94,0,0,0,0,0,0,0,0,0,0,0,0}},
   {8,18,3,16,24,{216,198,236,0,0,0,0,0,0,0,0},{0,0,31,0,0,0,0,0,0,0,0},{128,33,22,10,35,44,109,3,9,89,21,84,28,88,15,23,19,94,0,0,0,0,0,0,0,0,0,0,0,0}},
   {9,20,3,27,25,{160,126,65,0,0,0,0,0,0,0,0},{0,0,0,0,0,0,0,0,0,0,0},{65,165,107,103,14,18,109,91,12,31,92,21,20,11,15,29,26,19,17,30,0,0,0,0,0,0,0,0,0,0}},
   {10,18,3,16,26,{72,202,34,0,0,0,0,0,0,0,0},{0,0,0,0,0,0,0,0,0,0,0},{65,165,166,108,16,10,104,9,5,31,21,66,20,11,24,23,8,17,0,0,0,0,0,0,0,0,0,0,0,0}},
   {11,18,2,44,27,{204,159,0,0,0,0,0,0,0,0,0},{0,128,0,0,0,0,0,0,0,0,0},{70,33,166,35,10,3,109,9,27,85,25,68,20,88,93,26,8,94,0,0,0,0,0,0,0,0,0,0,0,0}},
   {12,17,4,13,28,{96,229,193,208,0,0,0,0,0,0,0},{1,0,0,0,0,0,0,0,0,0,0},{128,33,34,10,39,12,5,45,27,85,25,66,4,88,87,29,81,0,0,0,0,0,0,0,0,0,0,0,0,0}},
   {13,19,3,1,29,{168,197,156,0,0,0,0,0,0,0,0},{0,0,31,0,0,0,0,0,0,0,0},{65,33,34,10,12,3,39,40,9,31,13,68,20,11,15,26,19,17,30,0,0,0,0,0,0,0,0,0,0,0}},
   {14,17,2,20,30,{230,120,0,0,0,0,0,0,0,0,0},{127,0,0,0,0,0,0,0,0,0,0},{160,170,78,18,39,3,5,40,27,85,25,66,75,88,90,29,8,0,0,0,0,0,0,0,0,0,0,0,0,0}},
   {15,17,4,18,31,{24,37,213,240,0,0,0,0,0,0,0},{0,0,0,0,0,0,0,0,0,0,0},{71,41,78,38,35,44,73,40,95,77,92,84,75,79,87,72,81,0,0,0,0,0,0,0,0,0,0,0,0,0}},
   {8,3,6,18,255,{12,177,31,249,106,36,0,0,0,0,0},{0,0,0,0,0,3,0,0,0,0,0},{70,165,34,0,0,0,0,0,0,0,0,0,0,0,0,0,0,0,0,0,0,0,0,0,0,0,0,0,0,0}},
   {9,3,7,20,255,{10,135,27,41,172,196,244,0,0,0,0},{0,0,0,0,31,7,0,0,0,0,0},{160,170,22,0,0,0,0,0,0,0,0,0,0,0,0,0,0,0,0,0,0,0,0,0,0,0,0,0,0,0}},
   {10,3,6,28,255,{51,151,76,22,123,209,0,0,0,0,0},{0,0,0,99,0,0,0,0,0,0,0},{160,170,107,0,0,0,0,0,0,0,0,0,0,0,0,0,0,0,0,0,0,0,0,0,0,0,0,0,0,0}},
   {11,3,5,47,255,{3,181,79,165,70,0,0,0,0,0,0},{0,0,0,0,96,0,0,0,0,0,0},{128,165,107,0,0,0,0,0,0,0,0,0,0,0,0,0,0,0,0,0,0,0,0,0,0,0,0,0,0,0}},
   {12,3,6,17,255,{4,58,28,175,162,184,0,0,0,0,0},{0,0,0,128,0,0,0,0,0,0,0},{70,165,166,0,0,0,0,0,0,0,0,0,0,0,0,0,0,0,0,0,0,0,0,0,0,0,0,0,0,0}},
   {13,3,6,19,255,{56,180,179,47,107,88,0,0,0,0,0},{0,0,0,192,0,0,0,0,0,0,0},{128,165,166,0,0,0,0,0,0,0,0,0,0,0,0,0,0,0,0,0,0,0,0,0,0,0,0,0,0,0}},
   {14,3,7,43,255,{48,54,129,146,98,173,215,0,0,0,0},{0,0,0,0,0,32,224,0,0,0,0},{164,7,80,0,0,0,0,0,0,0,0,0,0,0,0,0,0,0,0,0,0,0,0,0,0,0,0,0,0,0}},
   {15,4,4,23,255,{14,29,174,224,0,0,0,0,0,0,0},{0,0,0,0,0,0,0,0,0,0,0},{70,33,80,43,0,0,0,0,0,0,0,0,0,0,0,0,0,0,0,0,0,0,0,0,0,0,0,0,0,0}},
   {8,3,6,31,255,{50,134,82,217,110,191,0,0,0,0,0},{0,0,0,0,0,255,0,0,0,0,0},{160,170,166,0,0,0,0,0,0,0,0,0,0,0,0,0,0,0,0,0,0,0,0,0,0,0,0,0,0,0}},
   {9,3,6,24,255,{13,133,221,21,185,245,0,0,0,0,0},{0,0,0,35,0,0,0,0,0,0,0},{164,7,6,0,0,0,0,0,0,0,0,0,0,0,0,0,0,0,0,0,0,0,0,0,0,0,0,0,0,0}},
   {10,3,8,33,255,{7,100,43,170,125,186,241,136,0,0,0},{60,0,0,0,0,0,0,0,0,0,0},{164,86,7,0,0,0,0,0,0,0,0,0,0,0,0,0,0,0,0,0,0,0,0,0,0,0,0,0,0,0}},
   {11,3,7,25,255,{15,114,44,250,201,91,69,0,0,0,0},{70,0,0,0,0,0,0,0,0,0,0},{160,170,22,0,0,0,0,0,0,0,0,0,0,0,0,0,0,0,0,0,0,0,0,0,0,0,0,0,0,0}},
   {12,4,6,34,255,{182,45,251,203,190,242,0,0,0,0,0},{0,0,0,0,0,0,0,0,0,0,0},{160,170,107,67,0,0,0,0,0,0,0,0,0,0,0,0,0,0,0,0,0,0,0,0,0,0,0,0,0,0}},
   {13,3,5,4,255,{5,115,46,108,195,0,0,0,0,0,0},{0,0,0,0,0,0,0,0,0,0,0},{160,170,107,0,0,0,0,0,0,0,0,0,0,0,0,0,0,0,0,0,0,0,0,0,0,0,0,0,0,0}},
   {14,3,5,15,255,{9,119,81,99,206,0,0,0,0,0,0},{0,0,0,0,0,0,0,0,0,0,0},{105,6,34,0,0,0,0,0,0,0,0,0,0,0,0,0,0,0,0,0,0,0,0,0,0,0,0,0,0,0}},
   {15,4,6,37,255,{183,147,42,39,121,235,0,0,0,0,0},{0,0,0,0,0,0,0,0,0,0,0},{128,165,82,76,0,0,0,0,0,0,0,0,0,0,0,0,0,0,0,0,0,0,0,0,0,0,0,0,0,0}},
   {8,3,3,11,255,{55,148,111,0,0,0,0,0,0,0,0},{26,0,0,0,0,0,0,0,0,0,0},{164,1,107,0,0,0,0,0,0,0,0,0,0,0,0,0,0,0,0,0,0,0,0,0,0,0,0,0,0,0}},
   {9,3,7,10,255,{63,30,218,225,169,17,143,0,0,0,0},{0,0,0,0,3,0,255,0,0,0,0},{105,98,80,0,0,0,0,0,0,0,0,0,0,0,0,0,0,0,0,0,0,0,0,0,0,0,0,0,0,0}},
   {10,3,6,36,255,{53,86,207,33,122,187,0,0,0,0,0},{0,0,128,0,0,15,0,0,0,0,0},{105,0,99,0,0,0,0,0,0,0,0,0,0,0,0,0,0,0,0,0,0,0,0,0,0,0,0,0,0,0}},
   {11,4,6,32,255,{8,118,83,254,127,153,0,0,0,0,0},{0,0,0,0,224,0,0,0,0,0,0},{164,7,78,103,0,0,0,0,0,0,0,0,0,0,0,0,0,0,0,0,0,0,0,0,0,0,0,0,0,0}},
   {12,3,7,29,255,{0,62,131,255,92,154,243,0,0,0,0},{0,0,0,0,0,0,0,0,0,0,0},{164,86,80,0,0,0,0,0,0,0,0,0,0,0,0,0,0,0,0,0,0,0,0,0,0,0,0,0,0,0}},
   {13,3,6,26,255,{11,87,75,109,90,188,0,0,0,0,0},{0,0,0,0,0,31,0,0,0,0,0},{164,7,78,0,0,0,0,0,0,0,0,0,0,0,0,0,0,0,0,0,0,0,0,0,0,0,0,0,0,0}},
   {14,4,4,0,255,{59,117,223,20,0,0,0,0,0,0,0},{0,0,0,0,0,0,0,0,0,0,0},{97,1,166,10,0,0,0,0,0,0,0,0,0,0,0,0,0,0,0,0,0,0,0,0,0,0,0,0,0,0}},
   {15,3,4,1,255,{6,85,219,95,0,0,0,0,0,0,0},{0,0,0,0,0,0,0,0,0,0,0},{160,170,74,0,0,0,0,0,0,0,0,0,0,0,0,0,0,0,0,0,0,0,0,0,0,0,0,0,0,0}},
   {6,2,7,5,255,{1,178,150,73,231,214,138,0,0,0,0},{0,0,0,0,0,0,7,0,0,0,0},{103,33,0,0,0,0,0,0,0,0,0,0,0,0,0,0,0,0,0,0,0,0,0,0,0,0,0,0,0,0}},
   {7,12,4,14,255,{130,77,199,141,0,0,0,0,0,0,0},{0,0,0,0,0,0,0,0,0,0,0},{103,32,110,114,76,108,69,105,95,117,89,124,0,0,0,0,0,0,0,0,0,0,0,0,0,0,0,0,0,0}}},
  {{0,3,0,0},{3,11,0,0},{0,1,0,0},{13,32,0,0},{5,13,0,0},{0,8,0,0},{5,32,0,0},{0,5,0,0},{0,1,0,0},{0,1,0,0},{13,32,0,0},
   {5,13,0,0},{11,32,0,0},{1,9,0,0},{1,9,0,0},{0,5,0,0},{5,32,0,0},{6,32,0,0},{5,32,0,0},{5,13,0,0},{5,8,0,0},{9,32,0,0},
   {0,3,0,0},{5,32,0,0},{5,13,0,0},{8,32,0,0},{9,32,0,0},{5,9,0,0},{0,0,0,0},{1,9,0,0},{0,3,0,0},{9,32,0,0},{0,8,0,0},
   {0,5,0,0},{8,32,0,0},{0,3,0,0},{13,32,0,0},{3,10,0,0},{8,32,0,0},{3,11,0,0},{11,32,0,0},{3,8,0,0},{0,5,0,0},{0,2,0,0},
   {9,32,0,0},{4,32,0,0},{0,4,0,0},{2,32,0,0},{0,5,0,0},{0,0,0,0},{0,1,0,0},{0,3,0,0},{0,0,0,0},{13,32,0,0},{5,32,0,0},
   {0,5,0,0},{1,32,0,0},{0,5,0,0},{0,5,0,0},{0,5,0,0},{0,0,0,0},{0,5,0,0},{8,32,0,0},{10,32,0,0},{0,5,0,0},{3,6,0,0}},
  {{9,12,18,16,22,1,6,0,4,11,24,28,20,29,23,15,2,31,26,25,21,13,27,19,8,5,3,10,30,14,7,17},
   {27,12,10,13,5,18,16,14,7,17,24,11,29,23,15,2,4,26,28,20,31,25,19,8,21,9,3,30,22,1,6,0},
   {19,27,5,3,10,16,30,1,6,24,11,4,15,23,29,2,28,26,20,31,25,21,13,8,9,12,18,22,14,7,0,17},
   {9,10,16,7,8,25,28,13,21,31,5,20,4,2,12,3,11,24,23,15,27,29,18,14,6,22,26,17,19,1,0,30},
   {13,5,27,10,19,12,9,14,26,16,22,1,0,2,20,4,21,24,11,23,15,25,29,28,31,3,18,17,8,6,7,30},
   {19,8,22,30,0,28,25,13,21,31,5,12,20,2,4,3,27,24,11,23,15,9,29,18,10,14,16,17,26,6,7,1},
   {8,3,29,18,14,7,22,1,30,2,28,25,4,20,21,13,11,31,27,15,24,5,12,9,19,10,23,16,26,0,6,17},
   {16,14,0,23,8,21,13,25,2,28,31,27,4,20,5,12,11,9,15,3,24,10,18,19,7,29,22,6,26,1,17,30},
   {3,10,16,23,8,0,6,17,2,25,28,21,4,20,13,31,11,27,15,5,24,12,9,19,18,29,14,7,26,22,1,30},
   {22,15,16,29,7,19,6,0,30,25,28,13,21,4,2,20,11,24,31,27,5,9,12,3,18,10,14,23,26,8,1,17},
   {7,8,6,0,30,21,31,27,25,13,28,5,9,4,2,11,20,24,12,3,18,10,16,14,15,22,29,23,19,26,1,17},
   {26,31,27,5,9,21,12,3,18,25,28,13,10,4,2,20,11,24,16,14,22,7,6,1,0,15,29,23,8,19,17,30},
   {5,3,14,22,1,21,27,18,15,16,6,26,29,4,20,2,11,25,28,13,24,31,9,12,10,7,23,0,19,8,17,30},
   {27,5,12,14,23,18,10,7,6,29,1,8,30,2,4,20,11,25,28,13,21,24,31,9,15,3,16,22,26,19,0,17},
   {16,22,1,0,29,8,31,27,21,13,25,28,2,9,4,20,5,11,18,12,3,24,10,14,15,7,6,23,26,19,17,30},
   {16,22,6,0,19,31,27,9,21,13,5,25,3,28,20,2,11,4,12,15,23,24,18,10,14,7,1,26,29,8,17,30},
   {12,10,14,26,19,6,0,30,13,21,25,31,28,4,20,11,2,27,15,24,23,9,5,3,18,16,22,7,29,8,1,17},
   {22,3,18,16,26,29,8,1,17,13,25,21,28,4,20,11,2,31,15,23,24,27,9,5,12,10,14,7,19,6,0,30},
   {18,22,26,3,16,1,7,0,19,17,30,25,13,21,28,4,20,11,2,24,31,27,9,5,12,15,10,14,23,6,29,8},
   {14,15,7,0,31,27,21,9,25,13,5,12,28,4,20,11,2,24,3,10,18,16,22,1,6,26,23,29,19,8,17,30},
   {10,14,26,22,29,7,8,30,25,13,21,31,28,4,20,11,2,24,27,9,5,12,3,15,18,16,23,1,19,6,0,17},
   {12,16,23,3,10,22,7,29,8,0,30,2,28,20,4,11,25,21,24,13,31,27,9,5,15,18,14,26,6,19,1,17},
   {27,15,12,16,14,5,18,26,22,19,29,1,17,4,11,20,2,28,24,25,21,13,31,9,3,10,23,7,8,6,0,30},
   {0,23,27,31,13,9,25,21,28,2,5,3,20,4,11,12,18,10,24,16,14,22,7,6,15,1,26,29,19,8,17,30}},
  {{0,0,2,2,1,2,0,3},{3,1,1,0,0,1,3,0},{8,5,7,8,8,8,2,9},{9,9,9,9,9,11,10,10},
   {6,6,8,10,10,9,10,3},{12,12,11,11,11,10,11,0},{2,2,0,1,2,0,2,2},{1,4,4,3,4,3,1,1},
   {15,15,7,12,12,3,9,9},{11,11,12,12,12,3,0,1},{7,7,8,8,8,8,8,8},{7,7,9,12,12,3,0,11},
   {10,10,10,10,10,9,9,9},{15,15,0,6,5,5,6,6},{4,5,5,5,5,5,5,5},{3,9,13,11,11,1,1,4},
   {6,6,6,6,6,6,6,6},{1,3,9,10,10,0,4,11},{8,8,7,7,7,7,7,7},{14,13,4,8,8,11,0,3},
   {4,8,10,9,9,11,9,10},{0,0,3,4,3,4,5,2},{5,3,3,4,3,4,4,4},{11,11,11,0,0,10,6,6},
   {2,10,12,3,4,0,4,1},{1,3,5,5,6,6,7,7},{13,14,0,6,5,5,5,5},{13,13,13,3,4,0,4,4},
   {5,4,6,7,7,7,8,8},{9,12,5,5,6,6,7,8},{4,8,8,3,4,9,10,1},{14,14,4,0,0,1,1,5}},
  {{255,255,255,255,255,255,255,255},{255,255,255,255,255,255,255,255},{18,14,18,10,10,10,6,12},{255,255,255,255,255,255,255,255},
   {16,16,10,12,12,12,3,0},{255,255,255,255,255,255,255,1},{255,255,255,255,255,255,255,255},{255,255,255,255,255,255,255,255},
   {13,13,2,11,11,11,20,2},{255,255,255,255,255,7,0,7},{255,255,255,255,255,255,255,255},{10,10,3,9,9,9,9,255},
   {255,255,255,255,255,255,255,255},{255,255,6,16,14,14,16,16},{255,255,255,255,255,255,255,255},{1,3,27,5,5,31,31,27},
   {255,255,255,255,255,255,255,255},{25,25,11,4,4,24,24,11},{255,255,255,255,255,255,255,255},{31,27,31,2,2,20,11,4},
   {14,18,12,3,3,3,12,3},{0,0,22,22,22,22,14,6},{255,255,255,255,255,255,255,255},{9,9,5,31,31,5,13,13},
   {6,12,9,27,27,27,27,9},{7,22,14,14,16,16,18,18},{27,31,13,13,13,13,21,31},{255,255,255,7,7,6,22,22},
   {22,7,16,18,18,18,10,10},{3,5,25,25,25,25,25,28},{20,20,4,24,24,4,4,24},{255,255,7,1,1,1,7,14}}};

typedef CUresult (*EncodeFn)(CUtensorMap*, CUtensorMapDataType, cuuint32_t, void*, const cuuint64_t*, const cuuint64_t*, const cuuint32_t*,
                             const cuuint32_t*, CUtensorMapInterleave, CUtensorMapSwizzle, CUtensorMapL2promotion, CUtensorMapFloatOOBfill);

void make_map2(EncodeFn enc, CUtensorMap* m, const void* ptr, int rows, int cols, int box_rows) {
  cuuint64_t dim[2] = {(cuuint64_t)cols, (cuuint64_t)rows}, str[1] = {(cuuint64_t)cols * 2};
  cuuint32_t box[2] = {64, (cuuint32_t)box_rows}, es[2] = {1, 1};
  enc(m, CU_TENSOR_MAP_DATA_TYPE_BFLOAT16, 2, const_cast<void*>(ptr), dim, str, box, es, CU_TENSOR_MAP_INTERLEAVE_NONE, CU_TENSOR_MAP_SWIZZLE_128B,
      CU_TENSOR_MAP_L2_PROMOTION_L2_128B, CU_TENSOR_MAP_FLOAT_OOB_FILL_NONE);
}
void make_map3(EncodeFn enc, CUtensorMap* m, const void* ptr, int rows) {
  cuuint64_t dim[3] = {64, (cuuint64_t)rows, 9}, str[2] = {DM * 2, 128};
  cuuint32_t box[3] = {64, 32, 3}, es[3] = {1, 1, 1};
  enc(m, CU_TENSOR_MAP_DATA_TYPE_BFLOAT16, 3, const_cast<void*>(ptr), dim, str, box, es, CU_TENSOR_MAP_INTERLEAVE_NONE, CU_TENSOR_MAP_SWIZZLE_128B,
      CU_TENSOR_MAP_L2_PROMOTION_L2_128B, CU_TENSOR_MAP_FLOAT_OOB_FILL_NONE);
}

void make_map_t(EncodeFn enc, CUtensorMap* m, void* ptr, int width, int cols) {
  cuuint64_t dim[3] = {TP / 2, 2, 864}, str[2] = {TP * 2, TP * 4};
  cuuint32_t box[3] = {(cuuint32_t)width, 2, (cuuint32_t)cols}, es[3] = {1, 1, 1};
  enc(m, CU_TENSOR_MAP_DATA_TYPE_UINT32, 3, ptr, dim, str, box, es, CU_TENSOR_MAP_INTERLEAVE_NONE, cols == 64 ? CU_TENSOR_MAP_SWIZZLE_128B : CU_TENSOR_MAP_SWIZZLE_NONE,
      CU_TENSOR_MAP_L2_PROMOTION_NONE, CU_TENSOR_MAP_FLOAT_OOB_FILL_NONE);
}

int g_mode = -1;

}

extern "C" void kernel_launch(void* const* d_in, const int* in_sizes, int n_in, void* d_out, int out_size) {
  static EncodeFn enc = nullptr;
  static void* t_ptr = nullptr;
  if (!enc) {
    void* fn = nullptr;
    cudaDriverEntryPointQueryResult st;
    cudaGetDriverEntryPoint("cuTensorMapEncodeTiled", &fn, cudaEnableDefault, &st);
    enc = (EncodeFn)fn;
    cudaGetSymbolAddress(&t_ptr, g_T);
    cudaFuncSetAttribute(fused_kernel, cudaFuncAttributeMaxDynamicSharedMemorySize, SMEM_BYTES);
    if (g_mode < 0) {
      cudaLaunchConfig_t cfg = {};
      cfg.gridDim = dim3(2 * NCL); cfg.blockDim = dim3(384); cfg.dynamicSmemBytes = SMEM_BYTES;
      cudaLaunchAttribute at; at.id = cudaLaunchAttributeClusterDimension;
      at.val.clusterDim.x = 2; at.val.clusterDim.y = 1; at.val.clusterDim.z = 1;
      cfg.attrs = &at; cfg.numAttrs = 1;
      int nc = 0;
      g_mode = (cudaOccupancyMaxActiveClusters(&nc, fused_kernel, &cfg) == cudaSuccess && nc >= NCL) ? 1 : 0;
      (void)cudaGetLastError();
    }
  }
  Params p;
  make_map2(enc, &p.map_a[0], d_in[4], SEQ, DC, 128);
  make_map2(enc, &p.map_a[1], d_in[0], SEQ, DM, 128);
  make_map2(enc, &p.map_w[0], d_in[6], DC, 4096, 64);
  make_map2(enc, &p.map_w[1], d_in[7], DC, 4096, 64);
  make_map2(enc, &p.map_w[2], d_in[5], DM, 4096, 64);
  make_map2(enc, &p.map_w[3], d_in[1], DM, 1728, 64);
  make_map3(enc, &p.map_o[0], d_in[8], 4096);
  make_map3(enc, &p.map_o[1], d_in[2], DM);
  make_map_t(enc, &p.map_t[0], t_ptr, 32, 9);
  make_map_t(enc, &p.map_t[1], t_ptr, 40, 9);
  make_map_t(enc, &p.map_t[2], t_ptr, 32, 64);
  p.x = (const __nv_bfloat16*)d_in[0];
  p.gate_w = (const __nv_bfloat16*)d_in[9];
  make_map2(enc, &p.map_out, d_out, SEQ, DM, 64);
  p.out = (__nv_bfloat16*)d_out;
  p.zero = 0;
  auto launch = [&](int phases) {
    p.s = k_sched;
    for (int i = 0; i < NCL; i++) {
      Rec& r = p.s.r[i];
      if (!(phases & 1)) r.n1 = 0;
      if (!(phases & 2)) r.n2 = 0;
      if (!(phases & (p.s.task[i][1] == 32 ? 4 : 32))) r.p3 = 255;
      if (!(phases & 8)) r.bg = 255;
      const int u1 = r.n1 ? 8 + r.n1 * (8 + (r.slab >> 3)) : 0;
      int u2 = 0;
      for (int k = 0; k < r.n2; k++) u2 += 4 * (r.item[k] & 7) + 4;
      r.u1 = (uint8_t)u1; r.u2 = (uint8_t)u2;
      r.rot = (uint8_t)(((u1 % 10 + 1) >> 1) % 5);
      r.x3 = (uint8_t)((r.rot + u2) % 5 & 3);
      r.phases = (uint8_t)phases;
    }
    if (!(phases & 16))
      for (int i = 0; i < 256; i++) { p.s.slot[i >> 3][i & 7] = (uint8_t)(i >> 3); p.s.prev[i >> 3][i & 7] = 255; }
    fused_kernel<<<2 * NCL, 384, SMEM_BYTES>>>(p);
  };
  if (g_mode == 1) launch(63);
  else { launch(1); launch(10); launch(4); launch(32); }
}
```

```cpp
#include <cuda_runtime.h>
#include <cuda_bf16.h>
#include <cuda.h>
#include <stdint.h>

namespace {

constexpr int SEQ = 2048, DM = 576, DC = 512, NH = 32;
constexpr int NCL = 66;
constexpr uint32_t DESC_HI = 0x40000040u;

constexpr int SM_RING = 0;
constexpr int SM_BUF = 163840;
constexpr int SM_BAR = 229376;
constexpr int B_P1E = 0, B_P2E = 10, B_P3E = 15, B_P2F = 24, B_SF = 32, B_ORD = 36, B_LAD = 40, B_DONE = 41, B_FIN = 48;
constexpr int B_P3F = 56, B_OUT = 61, B_P1F = 64, B_SE = 74, B_QF = 80, B_LA = 84, B_NUM = 88;
constexpr uint64_t B_CNT = 0x11118245000ull;
constexpr int SMEM_BYTES = SM_BAR + B_NUM * 8 + 1024;

constexpr int F_QKVA = 32;
constexpr int F_GATE = 64;
constexpr int F_DONE = 65;
constexpr int F_CTX = 96;
constexpr int F_OUT = 96 + 8 * 64;
constexpr int F_KV = F_OUT + 64;
constexpr int F_Q = F_KV + 256;
constexpr int F_RD = F_Q + 256;
constexpr int F_NUM = F_RD + 256;

struct Rec {
  uint8_t slab;
  uint8_t n1, n2;
  uint8_t p3;
  uint8_t bg;
  uint8_t item[11];
  uint8_t last[11];
  uint8_t tile[32];
  uint8_t u1, u2;
  uint8_t rot, x3;
  uint8_t phases;
};
struct Sched {
  Rec r[NCL];
  uint8_t task[NCL][4];
  uint8_t p3_order[24][64];
  uint8_t slot[32][8];
  uint8_t prev[32][8];
};

#define SCHED_DECL static const

struct Params {
  CUtensorMap map_a[2];
  CUtensorMap map_w[4];
  CUtensorMap map_o[2];
  CUtensorMap map_t[3];
  CUtensorMap map_out;
  const __nv_bfloat16* x;
  const __nv_bfloat16* gate_w;
  __nv_bfloat16* out;
  int zero;
  alignas(64) Sched s;
};

__device__ __align__(1024) uint8_t g_Q[NH * 32 * 16384];
__device__ __align__(1024) uint8_t g_KV[2 * NH * 16 * 32768];
__device__ __align__(1024) uint8_t g_oA[32 * 576 * 128];
constexpr int TP = SEQ + 16;
__device__ __align__(1024) uint32_t g_T[864 * TP];
__device__ float g_gate[SEQ];
__device__ int g_flags[F_NUM];

__device__ __forceinline__ void mbar_arrive(uint32_t b) { asm volatile("mbarrier.arrive.shared::cta.b64 _, [%0];" ::"r"(b) : "memory"); }
__device__ __forceinline__ void mbar_arrive_cl(uint32_t b, int cnt) {
  asm volatile("mbarrier.arrive.shared::cluster.b64 _, [%0], %1;" ::"r"(b), "r"(cnt) : "memory");
}
__device__ __forceinline__ void mbar_wait(uint32_t b, int par) {
  asm volatile(
      "{\n.reg .pred p;\n.reg .u32 c;\n"
      "mbarrier.try_wait.parity.shared::cta.b64 p, [%0], %1;\n@p bra DN;\nmov.u32 c, 0;\n"
      "LP:\nmbarrier.try_wait.parity.shared::cta.b64 p, [%0], %1;\n@p bra DN;\n"
      "add.u32 c, c, 1;\nsetp.lt.u32 p, c, 4000000;\n@p bra LP;\ntrap;\nDN:\n}" ::"r"(b), "r"(par) : "memory");
}
__device__ __forceinline__ uint32_t mapa(uint32_t a, uint32_t cta) {
  uint32_t r; asm("mapa.shared::cluster.u32 %0, %1, %2;" : "=r"(r) : "r"(a), "r"(cta)); return r;
}
#define ELECT(ins) "{\n.reg .pred e;\nelect.sync _|e, 0xffffffff;\n@e " ins "\n}"
__device__ __forceinline__ void mbar_expect(uint32_t b, int bytes) {
  asm volatile(ELECT("mbarrier.arrive.expect_tx.shared::cta.b64 _, [%0], %1;") ::"r"(b), "r"(bytes) : "memory");
}
__device__ __forceinline__ void mbar_arrive_one(uint32_t b) { asm volatile(ELECT("mbarrier.arrive.shared::cta.b64 _, [%0];") ::"r"(b) : "memory"); }
constexpr uint64_t L2_NORMAL = 0x1000000000000000ull, L2_FIRST = 0x12F0000000000000ull;
__device__ __forceinline__ void bulk_load(uint32_t dst, const void* src, int bytes, uint32_t bar, uint64_t pol = L2_NORMAL) {
  asm volatile(ELECT("cp.async.bulk.shared::cluster.global.mbarrier::complete_tx::bytes.L2::cache_hint [%0], [%1], %2, [%3], %4;") ::"r"(dst), "l"(src), "r"(bytes), "r"(bar), "l"(pol) : "memory");
}
__device__ __forceinline__ void bulk_load_mc(uint32_t dst, const void* src, int bytes, uint32_t bar, uint64_t pol = L2_NORMAL) {
  asm volatile(ELECT("cp.async.bulk.shared::cluster.global.mbarrier::complete_tx::bytes.multicast::cluster.L2::cache_hint [%0], [%1], %2, [%3], %4, %5;") ::"r"(dst), "l"(src), "r"(bytes), "r"(bar), "h"((uint16_t)3), "l"(pol) : "memory");
}
__device__ __forceinline__ void bulk_store(void* dst, uint32_t src, int bytes, uint64_t pol = L2_NORMAL) {
  asm volatile(ELECT("cp.async.bulk.global.shared::cta.bulk_group.L2::cache_hint [%0], [%1], %2, %3;") ::"l"(dst), "r"(src), "r"(bytes), "l"(pol) : "memory");
}
__device__ __forceinline__ void tma2d(uint32_t dst, const CUtensorMap* m, int c0, int c1, uint32_t bar, uint64_t pol = L2_NORMAL) {
  asm volatile(ELECT("cp.async.bulk.tensor.2d.shared::cluster.global.mbarrier::complete_tx::bytes.L2::cache_hint [%0], [%1, {%3, %4}], [%2], %5;") ::"r"(dst), "l"(m), "r"(bar), "r"(c0), "r"(c1), "l"(pol) : "memory");
}
__device__ __forceinline__ void tma2d_mc(uint32_t dst, const CUtensorMap* m, int c0, int c1, uint32_t bar, uint64_t pol = L2_NORMAL) {
  asm volatile(ELECT("cp.async.bulk.tensor.2d.shared::cluster.global.mbarrier::complete_tx::bytes.multicast::cluster.L2::cache_hint [%0], [%1, {%3, %4}], [%2], %5, %6;") ::"r"(dst), "l"(m), "r"(bar), "r"(c0), "r"(c1), "h"((uint16_t)3), "l"(pol) : "memory");
}
__device__ __forceinline__ void tma3d(uint32_t dst, const CUtensorMap* m, int c0, int c1, int c2, uint32_t bar, uint64_t pol = L2_NORMAL) {
  asm volatile(ELECT("cp.async.bulk.tensor.3d.shared::cluster.global.mbarrier::complete_tx::bytes.L2::cache_hint [%0], [%1, {%3, %4, %5}], [%2], %6;") ::"r"(dst), "l"(m), "r"(bar), "r"(c0), "r"(c1), "r"(c2), "l"(pol) : "memory");
}
__device__ __forceinline__ void tma3d_mc(uint32_t dst, const CUtensorMap* m, int c0, int c1, int c2, uint32_t bar, uint64_t pol = L2_NORMAL) {
  asm volatile(ELECT("cp.async.bulk.tensor.3d.shared::cluster.global.mbarrier::complete_tx::bytes.multicast::cluster.L2::cache_hint [%0], [%1, {%3, %4, %5}], [%2], %6, %7;") ::"r"(dst), "l"(m), "r"(bar), "r"(c0), "r"(c1), "r"(c2), "h"((uint16_t)3), "l"(pol) : "memory");
}
__device__ __forceinline__ void tma2d_add(const CUtensorMap* m, uint32_t src, int c0, int c1) {
  asm volatile(ELECT("cp.reduce.async.bulk.tensor.2d.global.shared::cta.add.bulk_group [%0, {%2, %3}], [%1];") ::"l"(m), "r"(src), "r"(c0), "r"(c1) : "memory");
}
__device__ __forceinline__ void tma3d_store(const CUtensorMap* m, uint32_t src, int c0, int c1, int c2, uint64_t pol = L2_NORMAL) {
  asm volatile(ELECT("cp.async.bulk.tensor.3d.global.shared::cta.bulk_group.L2::cache_hint [%0, {%2, %3, %4}], [%1], %5;") ::"l"(m), "r"(src), "r"(c0), "r"(c1), "r"(c2), "l"(pol) : "memory");
}
__device__ __forceinline__ void tma2d_prefetch(const CUtensorMap* m, int c0, int c1, uint64_t pol = L2_NORMAL) {
  asm volatile(ELECT("cp.async.bulk.prefetch.tensor.2d.L2.global.L2::cache_hint [%0, {%1, %2}], %3;") ::"l"(m), "r"(c0), "r"(c1), "l"(pol) : "memory");
}
#define LAG 3
#define HINT 62
#define POL(bit) ((HINT >> (bit)) & 1 ? L2_FIRST : L2_NORMAL)
#define BULK_COMMIT() asm volatile("cp.async.bulk.commit_group;" ::: "memory")
#define BULK_WAIT(n) asm volatile("cp.async.bulk.wait_group %0;" ::"n"(n) : "memory")
#define BULK_WAIT_READ(n) asm volatile("cp.async.bulk.wait_group.read %0;" ::"n"(n) : "memory")
#define FENCE_ASYNC_SMEM() asm volatile("fence.proxy.async.shared::cta;" ::: "memory")
#define FENCE_ASYNC_ALL() asm volatile("fence.proxy.async;" ::: "memory")
#define WG_FENCE() asm volatile("wgmma.fence.sync.aligned;" ::: "memory")
#define WG_COMMIT() asm volatile("wgmma.commit_group.sync.aligned;" ::: "memory")
#define WG_WAIT(n) asm volatile("wgmma.wait_group.sync.aligned %0;" ::"n"(n) : "memory")
__device__ __forceinline__ void bar_sync(int id, int n) { asm volatile("bar.sync %0, %1;" ::"r"(id), "r"(n) : "memory"); }
__device__ __forceinline__ void bar_arrive(int id, int n) { asm volatile("bar.arrive %0, %1;" ::"r"(id), "r"(n) : "memory"); }
__device__ __forceinline__ void cluster_sync() {
  asm volatile("barrier.cluster.arrive.relaxed;\nbarrier.cluster.wait.acquire;" ::: "memory");
}
template <int N> __device__ __forceinline__ void pin(float (&r)[N]) {
#pragma unroll
  for (int i = 0; i < N; i++) asm volatile("" : "+f"(r[i])::"memory");
}
template <int N> __device__ __forceinline__ void pin(uint32_t (&r)[N]) {
#pragma unroll
  for (int i = 0; i < N; i++) asm volatile("" : "+r"(r[i])::"memory");
}
__device__ __forceinline__ uint32_t pack_bf16(float lo, float hi) {
  uint32_t r; asm("cvt.rn.bf16x2.f32 %0, %1, %2;" : "=r"(r) : "f"(hi), "f"(lo)); return r;
}
__device__ __forceinline__ float ex2(float x) { float r; asm("ex2.approx.ftz.f32 %0, %1;" : "=f"(r) : "f"(x)); return r; }
__device__ __forceinline__ void ldsm4(uint32_t a, uint32_t& r0, uint32_t& r1, uint32_t& r2, uint32_t& r3) {
  asm volatile("ldmatrix.sync.aligned.m8n8.x4.shared.b16 {%0,%1,%2,%3}, [%4];" : "=r"(r0), "=r"(r1), "=r"(r2), "=r"(r3) : "r"(a) : "memory");
}
__device__ __forceinline__ void stsm4(uint32_t a, uint32_t r0, uint32_t r1, uint32_t r2, uint32_t r3) {
  asm volatile("stmatrix.sync.aligned.m8n8.x4.shared.b16 [%0], {%1,%2,%3,%4};" ::"r"(a), "r"(r0), "r"(r1), "r"(r2), "r"(r3) : "memory");
}
__device__ __forceinline__ void flag_add(int idx) {
  asm volatile(ELECT("red.release.gpu.global.add.s32 [%0], 1;") ::"l"(g_flags + idx) : "memory");
}
__device__ __forceinline__ void flag_add_rx(int idx) {
  asm volatile(ELECT("red.relaxed.gpu.global.add.s32 [%0], 1;") ::"l"(g_flags + idx) : "memory");
}
template <bool ACQ, int NS = 32> __device__ __forceinline__ void flag_wait(int idx, int target) {
  int n = 0;
  while (true) {
    int v;
    if (ACQ) asm volatile("ld.acquire.gpu.global.s32 %0, [%1];" : "=r"(v) : "l"(g_flags + idx) : "memory");
    else asm volatile("ld.relaxed.gpu.global.s32 %0, [%1];" : "=r"(v) : "l"(g_flags + idx) : "memory");
    if (__all_sync(0xffffffffu, v >= target)) break;
    if (++n > 20000000) __trap();
    __nanosleep(NS);
  }
}
__device__ __forceinline__ void mask_wait(uint32_t& ready, int bit, int idx, int target) {
  for (int n = 0; !((ready >> bit) & 1); n++) {
    int v;
    if (n) { __nanosleep(32); if (n > 20000000) __trap(); }
    asm volatile("ld.relaxed.gpu.global.s32 %0, [%1];" : "=r"(v) : "l"(g_flags + idx) : "memory");
    ready = __ballot_sync(0xffffffffu, v >= target);
  }
}
__device__ __forceinline__ uint32_t desc_lo(uint32_t addr, uint32_t lbo) { return ((addr & 0x3FFFFu) >> 4) | ((lbo >> 4) << 16); }
#define PROF(role, i)
#define PROFX(cond, i)
#define PROFB(i)
#define PROFG(i)

template <int TB, int TA = 0> __device__ __forceinline__ void wgmma_ss64(float (&d)[32], uint32_t alo, uint32_t blo, int sd) {
  asm volatile("{\n.reg .pred p;\n.reg .b64 da, db;\n"
    "setp.ne.b32 p, %34, 0;\nmov.b64 da, {%32, %36};\nmov.b64 db, {%33, %36};\n"
    "wgmma.mma_async.sync.aligned.m64n64k16.f32.bf16.bf16 "
    "{%0,%1,%2,%3,%4,%5,%6,%7,%8,%9,%10,%11,%12,%13,%14,%15,%16,%17,%18,%19,%20,%21,%22,%23,"
    "%24,%25,%26,%27,%28,%29,%30,%31}, "
    "da, db, p, 1, 1, %37, %35;\n}\n"
    : "+f"(d[0]),"+f"(d[1]),"+f"(d[2]),"+f"(d[3]),"+f"(d[4]),"+f"(d[5]),"+f"(d[6]),"+f"(d[7]),"+f"(d[8]),"+f"(d[9]),"+f"(d[10]),"+f"(d[11]),
      "+f"(d[12]),"+f"(d[13]),"+f"(d[14]),"+f"(d[15]),"+f"(d[16]),"+f"(d[17]),"+f"(d[18]),"+f"(d[19]),"+f"(d[20]),"+f"(d[21]),"+f"(d[22]),"+f"(d[23]),
      "+f"(d[24]),"+f"(d[25]),"+f"(d[26]),"+f"(d[27]),"+f"(d[28]),"+f"(d[29]),"+f"(d[30]),"+f"(d[31])
    : "r"(alo), "r"(blo), "r"(sd), "n"(TB), "r"(DESC_HI), "n"(TA));
}
template <int TB, int TA = 0> __device__ __forceinline__ void wgmma_ss128(float (&d)[64], uint32_t alo, uint32_t blo, int sd) {
  asm volatile("{\n.reg .pred p;\n.reg .b64 da, db;\n"
    "setp.ne.b32 p, %66, 0;\nmov.b64 da, {%64, %68};\nmov.b64 db, {%65, %68};\n"
    "wgmma.mma_async.sync.aligned.m64n128k16.f32.bf16.bf16 "
    "{%0,%1,%2,%3,%4,%5,%6,%7,%8,%9,%10,%11,%12,%13,%14,%15,%16,%17,%18,%19,%20,%21,%22,%23,"
    "%24,%25,%26,%27,%28,%29,%30,%31,%32,%33,%34,%35,%36,%37,%38,%39,%40,%41,%42,%43,%44,%45,%46,%47,"
    "%48,%49,%50,%51,%52,%53,%54,%55,%56,%57,%58,%59,%60,%61,%62,%63}, "
    "da, db, p, 1, 1, %69, %67;\n}\n"
    : "+f"(d[0]),"+f"(d[1]),"+f"(d[2]),"+f"(d[3]),"+f"(d[4]),"+f"(d[5]),"+f"(d[6]),"+f"(d[7]),"+f"(d[8]),"+f"(d[9]),"+f"(d[10]),"+f"(d[11]),
      "+f"(d[12]),"+f"(d[13]),"+f"(d[14]),"+f"(d[15]),"+f"(d[16]),"+f"(d[17]),"+f"(d[18]),"+f"(d[19]),"+f"(d[20]),"+f"(d[21]),"+f"(d[22]),"+f"(d[23]),
      "+f"(d[24]),"+f"(d[25]),"+f"(d[26]),"+f"(d[27]),"+f"(d[28]),"+f"(d[29]),"+f"(d[30]),"+f"(d[31]),"+f"(d[32]),"+f"(d[33]),"+f"(d[34]),"+f"(d[35]),
      "+f"(d[36]),"+f"(d[37]),"+f"(d[38]),"+f"(d[39]),"+f"(d[40]),"+f"(d[41]),"+f"(d[42]),"+f"(d[43]),"+f"(d[44]),"+f"(d[45]),"+f"(d[46]),"+f"(d[47]),
      "+f"(d[48]),"+f"(d[49]),"+f"(d[50]),"+f"(d[51]),"+f"(d[52]),"+f"(d[53]),"+f"(d[54]),"+f"(d[55]),"+f"(d[56]),"+f"(d[57]),"+f"(d[58]),"+f"(d[59]),
      "+f"(d[60]),"+f"(d[61]),"+f"(d[62]),"+f"(d[63])
    : "r"(alo), "r"(blo), "r"(sd), "n"(TB), "r"(DESC_HI), "n"(TA));
}
template <int TB> __device__ __forceinline__ void wgmma_rs128(float (&d)[64], uint32_t a0, uint32_t a1, uint32_t a2, uint32_t a3, uint32_t blo, int sd) {
  asm volatile("{\n.reg .pred p;\n.reg .b64 db;\n"
    "setp.ne.b32 p, %69, 0;\nmov.b64 db, {%68, %71};\n"
    "wgmma.mma_async.sync.aligned.m64n128k16.f32.bf16.bf16 "
    "{%0,%1,%2,%3,%4,%5,%6,%7,%8,%9,%10,%11,%12,%13,%14,%15,%16,%17,%18,%19,%20,%21,%22,%23,"
    "%24,%25,%26,%27,%28,%29,%30,%31,%32,%33,%34,%35,%36,%37,%38,%39,%40,%41,%42,%43,%44,%45,%46,%47,"
    "%48,%49,%50,%51,%52,%53,%54,%55,%56,%57,%58,%59,%60,%61,%62,%63}, "
    "{%64,%65,%66,%67}, db, p, 1, 1, %70;\n}\n"
    : "+f"(d[0]),"+f"(d[1]),"+f"(d[2]),"+f"(d[3]),"+f"(d[4]),"+f"(d[5]),"+f"(d[6]),"+f"(d[7]),"+f"(d[8]),"+f"(d[9]),"+f"(d[10]),"+f"(d[11]),
      "+f"(d[12]),"+f"(d[13]),"+f"(d[14]),"+f"(d[15]),"+f"(d[16]),"+f"(d[17]),"+f"(d[18]),"+f"(d[19]),"+f"(d[20]),"+f"(d[21]),"+f"(d[22]),"+f"(d[23]),
      "+f"(d[24]),"+f"(d[25]),"+f"(d[26]),"+f"(d[27]),"+f"(d[28]),"+f"(d[29]),"+f"(d[30]),"+f"(d[31]),"+f"(d[32]),"+f"(d[33]),"+f"(d[34]),"+f"(d[35]),
      "+f"(d[36]),"+f"(d[37]),"+f"(d[38]),"+f"(d[39]),"+f"(d[40]),"+f"(d[41]),"+f"(d[42]),"+f"(d[43]),"+f"(d[44]),"+f"(d[45]),"+f"(d[46]),"+f"(d[47]),
      "+f"(d[48]),"+f"(d[49]),"+f"(d[50]),"+f"(d[51]),"+f"(d[52]),"+f"(d[53]),"+f"(d[54]),"+f"(d[55]),"+f"(d[56]),"+f"(d[57]),"+f"(d[58]),"+f"(d[59]),
      "+f"(d[60]),"+f"(d[61]),"+f"(d[62]),"+f"(d[63])
    : "r"(a0), "r"(a1), "r"(a2), "r"(a3), "r"(blo), "r"(sd), "n"(TB), "r"(DESC_HI));
}
template <int TB, int TA = 0> __device__ __forceinline__ void wgmma_ss192(float (&d)[96], uint32_t alo, uint32_t blo, int sd) {
  asm volatile("{\n.reg .pred p;\n.reg .b64 da, db;\n"
    "setp.ne.b32 p, %98, 0;\nmov.b64 da, {%96, %100};\nmov.b64 db, {%97, %100};\n"
    "wgmma.mma_async.sync.aligned.m64n192k16.f32.bf16.bf16 "
    "{%0,%1,%2,%3,%4,%5,%6,%7,%8,%9,%10,%11,%12,%13,%14,%15,%16,%17,%18,%19,%20,%21,%22,%23,"
    "%24,%25,%26,%27,%28,%29,%30,%31,%32,%33,%34,%35,%36,%37,%38,%39,%40,%41,%42,%43,%44,%45,%46,%47,"
    "%48,%49,%50,%51,%52,%53,%54,%55,%56,%57,%58,%59,%60,%61,%62,%63,%64,%65,%66,%67,%68,%69,%70,%71,"
    "%72,%73,%74,%75,%76,%77,%78,%79,%80,%81,%82,%83,%84,%85,%86,%87,%88,%89,%90,%91,%92,%93,%94,%95}, "
    "da, db, p, 1, 1, %101, %99;\n}\n"
    : "+f"(d[0]),"+f"(d[1]),"+f"(d[2]),"+f"(d[3]),"+f"(d[4]),"+f"(d[5]),"+f"(d[6]),"+f"(d[7]),"+f"(d[8]),"+f"(d[9]),"+f"(d[10]),"+f"(d[11]),
      "+f"(d[12]),"+f"(d[13]),"+f"(d[14]),"+f"(d[15]),"+f"(d[16]),"+f"(d[17]),"+f"(d[18]),"+f"(d[19]),"+f"(d[20]),"+f"(d[21]),"+f"(d[22]),"+f"(d[23]),
      "+f"(d[24]),"+f"(d[25]),"+f"(d[26]),"+f"(d[27]),"+f"(d[28]),"+f"(d[29]),"+f"(d[30]),"+f"(d[31]),"+f"(d[32]),"+f"(d[33]),"+f"(d[34]),"+f"(d[35]),
      "+f"(d[36]),"+f"(d[37]),"+f"(d[38]),"+f"(d[39]),"+f"(d[40]),"+f"(d[41]),"+f"(d[42]),"+f"(d[43]),"+f"(d[44]),"+f"(d[45]),"+f"(d[46]),"+f"(d[47]),
      "+f"(d[48]),"+f"(d[49]),"+f"(d[50]),"+f"(d[51]),"+f"(d[52]),"+f"(d[53]),"+f"(d[54]),"+f"(d[55]),"+f"(d[56]),"+f"(d[57]),"+f"(d[58]),"+f"(d[59]),
      "+f"(d[60]),"+f"(d[61]),"+f"(d[62]),"+f"(d[63]),"+f"(d[64]),"+f"(d[65]),"+f"(d[66]),"+f"(d[67]),"+f"(d[68]),"+f"(d[69]),"+f"(d[70]),"+f"(d[71]),
      "+f"(d[72]),"+f"(d[73]),"+f"(d[74]),"+f"(d[75]),"+f"(d[76]),"+f"(d[77]),"+f"(d[78]),"+f"(d[79]),"+f"(d[80]),"+f"(d[81]),"+f"(d[82]),"+f"(d[83]),
      "+f"(d[84]),"+f"(d[85]),"+f"(d[86]),"+f"(d[87]),"+f"(d[88]),"+f"(d[89]),"+f"(d[90]),"+f"(d[91]),"+f"(d[92]),"+f"(d[93]),"+f"(d[94]),"+f"(d[95])
    : "r"(alo), "r"(blo), "r"(sd), "n"(TB), "r"(DESC_HI), "n"(TA));
}

struct Ctx {
  uint32_t sm;
  uint32_t bar;
  uint32_t rbar;
  int cl, rank, wg, warp, lane, phases;
};
__device__ __forceinline__ void release(const Ctx& c, int b, int cnt = 1) {
  if (c.lane < 2) mbar_arrive_cl(c.rbar + b * 8, cnt);
}
#define HK 5
#define NPRO 6
#define ZLEAD 14
#define PFM 7
#define PF1 1
constexpr float SM_SCALE = 0.08838834764831845f * 1.4426950408889634f;
constexpr float SM_HI = 1.8446744e19f, SM_LO = 5.4210109e-20f;
constexpr int ORDER = 1;

__device__ __forceinline__ void stage_tile(const float (&a)[64], uint32_t buf, const Ctx& c, float s0, float s1) {
  const int row = (c.lane & 7) + ((c.lane >> 3) & 1) * 8;
  const uint32_t base = buf + (c.warp * 16 + row) * 128 + (((c.lane >> 4) ^ (row & 7)) << 4);
#pragma unroll
  for (int i = 0; i < 8; i++)
    stsm4((base ^ ((i & 3) << 5)) + (i >> 2) * 8192, pack_bf16(a[8 * i] * s0, a[8 * i + 1] * s0), pack_bf16(a[8 * i + 2] * s1, a[8 * i + 3] * s1),
          pack_bf16(a[8 * i + 4] * s0, a[8 * i + 5] * s0), pack_bf16(a[8 * i + 6] * s1, a[8 * i + 7] * s1));
}

__device__ __forceinline__ void p1_epilogue(const Params& p, const Ctx& c, const float (&acc)[64], int t, int type) {
  const int tile = p.s.r[c.cl].tile[t] & 63, b = c.wg * 2 + 1;
  mbar_wait(c.bar + (B_SE + b) * 8, (t & 1) ^ 1);
  if (type && tile >= 32) {
    const int r = 2 * (c.lane & 3) + ((c.lane >> 2) & 1);
    const uint32_t dst = c.sm + SM_BUF + b * 16384 + r * 128 + (((c.warp * 2) ^ r) << 4) + (c.lane >> 3) * 4;
#pragma unroll
    for (int i = 0; i < 16; i++) {
      asm volatile("st.shared.u32 [%0], %1;" ::"r"(dst + i * 1024), "r"(pack_bf16(acc[4 * i], acc[4 * i + 1])) : "memory");
      asm volatile("st.shared.u32 [%0], %1;" ::"r"((dst ^ 16) + i * 1024), "r"(pack_bf16(acc[4 * i + 2], acc[4 * i + 3])) : "memory");
    }
  } else {
    if (type) stage_tile(acc, c.sm + SM_BUF + b * 16384, c, SM_SCALE, SM_SCALE);
    else stage_tile(acc, c.sm + SM_BUF + b * 16384, c, 1.f, 1.f);
  }
  FENCE_ASYNC_SMEM();
  __syncwarp();
  if (c.lane == 0) mbar_arrive(c.bar + (B_SF + b) * 8);
}

__device__ __forceinline__ void p1_consumer(const Params& p, const Ctx& c) {
  const int n = p.s.r[c.cl].n1;
  const int type = p.s.r[c.cl].slab >> 3;
  const uint32_t bdesc = desc_lo(c.sm + SM_RING, 8192), adesc = desc_lo(c.sm + SM_BUF + 32768 + c.wg * 8192, 16);
  uint32_t A[128];
  float acc[64] = {};
  int slot = 0, par = 0;
  auto next = [&]() { if (++slot == 10) { slot = 0; par ^= 1; } };
  {
    const int row = (c.lane & 7) + ((c.lane >> 3) & 1) * 8;
    const uint32_t base = c.sm + SM_RING + (c.wg * 64 + c.warp * 16 + row) * 128 + (((c.lane >> 4) ^ (row & 7)) << 4);
    if (c.wg == 1) bar_sync(ORDER + 1, 256);
    int pa = -1, pb = -1;
    if (type) {
      mbar_wait(c.bar + B_P1F * 8, 0);
      WG_FENCE();
#pragma unroll
      for (int kk = 0; kk < 4; kk++) wgmma_ss128<1>(acc, adesc + kk * 2, bdesc + kk * 128, kk != 0);
      WG_COMMIT();
      pb = 0; slot = 1;
    }
#pragma unroll
    for (int kb = 0; kb < 8; kb++) {
      const int sa = slot;
      mbar_wait(c.bar + (B_P1F + slot) * 8, par);
      if (kb == 0) PROF(c.wg, 5);
      next();
      mbar_wait(c.bar + (B_P1F + slot) * 8, par);
      PROF(c.wg, 6 + 2 * kb);
      WG_FENCE();
#pragma unroll
      for (int kk = 0; kk < 4; kk++)
        wgmma_ss128<1>(acc, desc_lo(c.sm + SM_RING + c.wg * 8192, 16) + sa * 1024 + kk * 2, bdesc + slot * 1024 + kk * 128, (kb | kk) != 0 ? 1 : type);
      WG_COMMIT();
      if (kb == 1 && c.wg == 0) bar_arrive(ORDER + 1, 256);
#pragma unroll
      for (int kk = 0; kk < 4; kk++) ldsm4((base ^ (kk << 5)) + sa * 16384, A[kb * 16 + kk * 4], A[kb * 16 + kk * 4 + 1], A[kb * 16 + kk * 4 + 2], A[kb * 16 + kk * 4 + 3]);
      WG_WAIT(1);
      if (kb > 0) release(c, B_P1E + pa);
      if (kb > 0 || pb >= 0) release(c, B_P1E + pb);
      pa = sa; pb = slot;
      next();
    }
    WG_WAIT(0);
    __syncwarp();
    release(c, B_P1E + pa);
    release(c, B_P1E + pb);
    pin(acc);
    PROF(c.wg, 1);
    p1_epilogue(p, c, acc, 0, type);
    PROF(c.wg, 2);
  }
  for (int t = 1; t < n; t++) {
    bar_sync(ORDER + c.wg, 256);
    int prev1 = -1, prev2 = -1;
    if (type) {
      mbar_wait(c.bar + (B_P1F + slot) * 8, par);
      WG_FENCE();
#pragma unroll
      for (int kk = 0; kk < 4; kk++) wgmma_ss128<1>(acc, adesc + kk * 2, bdesc + slot * 1024 + kk * 128, kk != 0);
      WG_COMMIT();
      prev1 = slot;
      next();
    }
#pragma unroll
    for (int kb = 0; kb < 8; kb++) {
      mbar_wait(c.bar + (B_P1F + slot) * 8, par);
      WG_FENCE();
      const uint32_t d = bdesc + slot * 1024;
#pragma unroll
      for (int kk = 0; kk < 4; kk++)
        wgmma_rs128<1>(acc, A[kb * 16 + kk * 4], A[kb * 16 + kk * 4 + 1], A[kb * 16 + kk * 4 + 2], A[kb * 16 + kk * 4 + 3], d + kk * 128, (kb | kk) != 0 ? 1 : type);
      WG_COMMIT();
      if (kb == HK) {
        if (t + 1 < n || c.wg == 0) bar_arrive(ORDER + (c.wg ^ 1), 256);
      }
      if (kb > 0) { WG_WAIT(2); if (kb > 1 || prev2 >= 0) release(c, B_P1E + prev2); }
      prev2 = prev1; prev1 = slot;
      next();
    }
    WG_WAIT(1);
    release(c, B_P1E + prev2);
    WG_WAIT(0);
    pin(acc);
    release(c, B_P1E + prev1);
    p1_epilogue(p, c, acc, t, type);
    PROF(c.wg, 3);
  }
}

__device__ __forceinline__ void p1_producer(const Params& p, const Ctx& c) {
  const int n = p.s.r[c.cl].n1;
  const int type = p.s.r[c.cl].slab >> 3, grp = p.s.r[c.cl].slab & 7;
  int slot = NPRO % 10, par = NPRO < 10;
#pragma unroll 1
  for (int t = 0; t < n; t++) {
    const int tile = p.s.r[c.cl].tile[t] & 63;
    const CUtensorMap* m = &p.map_w[type * 2 + (tile >> 5)];
    const int n0 = (tile & 31) * 128 + c.rank * 64;
    const int ptile = p.s.r[c.cl].tile[t + PF1 < n ? t + PF1 : t];
    const CUtensorMap* pm = &p.map_w[type * 2 + ((ptile >> 5) & 1)];
    if (t == 7 && (c.phases & 16)) flag_wait<true>(F_GATE, 256);
#pragma unroll 1
    for (int kb = t ? -type : (NPRO - type) >> 1; kb < 8; kb++) {
      if (t == 0 && 2 * kb + type >= NPRO) {
        mbar_wait(c.bar + (B_P1E + slot) * 8, par);
        mbar_expect(c.bar + (B_P1F + slot) * 8, 16384);
        tma2d(c.sm + SM_RING + slot * 16384, &p.map_a[type], kb * 64, grp * 256 + c.rank * 128, c.bar + (B_P1F + slot) * 8);
        if (++slot == 10) { slot = 0; par ^= 1; }
      }
      mbar_wait(c.bar + (B_P1E + slot) * 8, par);
      mbar_expect(c.bar + (B_P1F + slot) * 8, 16384);
      tma2d_mc(c.sm + SM_RING + slot * 16384 + c.rank * 8192, m, n0, kb < 0 ? 512 : kb * 64, c.bar + (B_P1F + slot) * 8);
      if (t == 0 && kb == 1) PROF(2, 61);
      if (t == 0 && kb == 3) PROF(2, 62);
      if (t + PF1 < n && t > 0 && ((ptile & 64) || ((ptile & 128) && ((kb ^ grp) & PFM) == 0))) tma2d_prefetch(pm, (ptile & 31) * 128 + c.rank * 64, kb < 0 ? 512 : kb * 64);
      if (++slot == 10) { slot = 0; par ^= 1; }
    }
  }
}

__device__ __forceinline__ void p1_storer(const Params& p, const Ctx& c) {
  const int n = p.s.r[c.cl].n1;
  const int type = p.s.r[c.cl].slab >> 3, grp = p.s.r[c.cl].slab & 7;
  for (int i = 0; i < 2 * n; i++) {
    const int t = i >> 1, w = i & 1, b = w * 2 + 1;
    const int tile = p.s.r[c.cl].tile[t] & 63;
    mbar_wait(c.bar + (B_SF + b) * 8, t & 1);
    const uint32_t src = c.sm + SM_BUF + b * 16384;
    int f = (type ? F_Q : F_KV) + (tile & 31) * 8 + grp;
    if (type == 0) {
      const int prev = p.s.prev[tile & 31][grp];
      if (prev != 255 && w == 0) {
        if (grp >= 2) flag_wait<false>(F_RD + prev * 8 + grp, 8 - grp);
        else flag_wait<false>(F_CTX + max(c.lane & 7, grp) * 64 + prev, 4);
      }
      uint8_t* dst = g_KV + (size_t)(((tile & 32) + p.s.slot[tile & 31][grp]) * 16 + grp * 2 + c.rank) * 32768 + w * 8192;
      bulk_store(dst, src, 8192);
      bulk_store(dst + 16384, src + 8192, 8192);
    } else if (tile < 32) {
      bulk_store(g_Q + (size_t)(tile * 32 + grp * 4 + c.rank * 2 + w) * 16384, src, 16384);
    } else {
      tma3d_store(&p.map_t[2], src, 8 + (grp * 4 + c.rank * 2 + w) * 32, 0, (tile - 32) * 64);
      f = F_QKVA + grp * 4 + ((0xE4390900u >> (2 * (tile - 30))) & 3);
    }
    BULK_COMMIT();
    BULK_WAIT(0);
    mbar_arrive_one(c.bar + (B_SE + b) * 8);
    flag_add_rx(f);
  }
}

__device__ __forceinline__ int p2_buf(int w, int i) { return w * 2 + (i & 1); }
__device__ __forceinline__ int p2_blk(int rank, int w, int i) { return ((i ^ w) & 1) == 0 ? 3 - rank : rank; }

template <int N>
__device__ __forceinline__ void row_max(const float (&s)[N], float& m0, float& m1) {
  float a0 = fmaxf(s[0], s[1]), a1 = fmaxf(s[2], s[3]);
#pragma unroll
  for (int i = 1; i < N / 4; i++) {
    m0 = fmaxf(m0, s[4 * i]); a0 = fmaxf(a0, s[4 * i + 1]);
    m1 = fmaxf(m1, s[4 * i + 2]); a1 = fmaxf(a1, s[4 * i + 3]);
  }
  m0 = fmaxf(m0, a0); m1 = fmaxf(m1, a1);
  m0 = fmaxf(m0, __shfl_xor_sync(0xffffffffu, m0, 1));
  m1 = fmaxf(m1, __shfl_xor_sync(0xffffffffu, m1, 1));
  m0 = fmaxf(m0, __shfl_xor_sync(0xffffffffu, m0, 2));
  m1 = fmaxf(m1, __shfl_xor_sync(0xffffffffu, m1, 2));
}
template <bool SUB, int N>
__device__ __forceinline__ void row_exp(const float (&s)[N], uint32_t (&P)[32], float m0, float m1, float& t0, float& t1) {
  float u0 = 0.f, u1 = 0.f;
  t0 = t1 = 0.f;
#pragma unroll
  for (int i = 0; i < N / 4; i++) {
    const float e0 = ex2(SUB ? s[4 * i] - m0 : s[4 * i]), e1 = ex2(SUB ? s[4 * i + 1] - m0 : s[4 * i + 1]);
    const float e2 = ex2(SUB ? s[4 * i + 2] - m1 : s[4 * i + 2]), e3 = ex2(SUB ? s[4 * i + 3] - m1 : s[4 * i + 3]);
    if (i == 0) { t0 = e0; u0 = e1; t1 = e2; u1 = e3; }
    else { t0 += e0; u0 += e1; t1 += e2; u1 += e3; }
    P[2 * i] = pack_bf16(e0, e1);
    P[2 * i + 1] = pack_bf16(e2, e3);
  }
#pragma unroll
  for (int i = N / 2; i < 32; i++) P[i] = 0;
  pin(P);
  t0 += u0; t1 += u1;
}
template <int N>
__device__ __forceinline__ void causal_mask(float (&s)[N], int thr) {
#pragma unroll
  for (int i = 0; i < 8; i++) {
    if (8 * i > thr) s[N - 32 + 4 * i] = -INFINITY;
    if (8 * i + 1 > thr) s[N - 32 + 4 * i + 1] = -INFINITY;
    if (8 * i - 8 > thr) s[N - 32 + 4 * i + 2] = -INFINITY;
    if (8 * i - 7 > thr) s[N - 32 + 4 * i + 3] = -INFINITY;
  }
}
__device__ __forceinline__ void issue_qk(float (&s)[32], uint32_t qd, uint32_t kd) {
  WG_FENCE();
#pragma unroll
  for (int kk = 0; kk < 8; kk++) wgmma_ss64<0>(s, qd + (kk >> 2) * 512 + (kk & 3) * 2, kd + (kk >> 2) * 1024 + (kk & 3) * 2, kk != 0);
  WG_COMMIT();
}
__device__ __forceinline__ void issue_qk(float (&s)[64], uint32_t qd, uint32_t kd) {
  WG_FENCE();
#pragma unroll
  for (int kk = 0; kk < 8; kk++) wgmma_ss128<0>(s, qd + (kk >> 2) * 512 + (kk & 3) * 2, kd + (kk >> 2) * 1024 + (kk & 3) * 2, kk != 0);
  WG_COMMIT();
}
template <int NK>
__device__ __forceinline__ void issue_pv(float (&o)[64], const uint32_t (&P)[32], uint32_t vd, int acc) {
  WG_FENCE();
#pragma unroll
  for (int kk = 0; kk < NK; kk++) wgmma_rs128<1>(o, P[4 * kk], P[4 * kk + 1], P[4 * kk + 2], P[4 * kk + 3], vd + kk * 128, kk != 0 ? 1 : acc);
  WG_COMMIT();
}
__device__ __forceinline__ void stage_done(const Ctx& c, int b) {
  FENCE_ASYNC_SMEM();
  __syncwarp();
  if (c.lane == 0) mbar_arrive(c.bar + (B_SF + b) * 8);
}
__device__ __forceinline__ void p2_epilogue(const float (&o)[64], float s0, float s1, const Ctx& c, int b) {
  stage_tile(o, c.sm + SM_BUF + b * 16384, c, s0, s1);
  stage_done(c, b);
}

struct P2State {
  float m0, m1, l0, l1;
  bool shift;
  float e0, e1;
  int ks;
  int wi, ai;
  uint32_t wb, ab;
  uint32_t qd;
};
#define PROFZ()
__device__ __forceinline__ int wrap5(int q) { return q >= 5 ? q - 5 : q; }
__device__ __forceinline__ void turn_wait(uint32_t ring, int i) { mbar_wait(ring + (i & 3) * 8, (i >> 2) & 1); }
__device__ __forceinline__ void turn_pass(const Ctx& c, uint32_t ring, int i) { if (c.lane == 0) mbar_arrive(ring + (i & 3) * 8); }
__device__ __forceinline__ void p2_scales(P2State& z) {
  float l0 = z.l0, l1 = z.l1;
  l0 += __shfl_xor_sync(0xffffffffu, l0, 1);
  l1 += __shfl_xor_sync(0xffffffffu, l1, 1);
  l0 += __shfl_xor_sync(0xffffffffu, l0, 2);
  l1 += __shfl_xor_sync(0xffffffffu, l1, 2);
  asm("rcp.approx.ftz.f32 %0, %1;" : "=f"(z.e0) : "f"(l0));
  asm("rcp.approx.ftz.f32 %0, %1;" : "=f"(z.e1) : "f"(l1));
}
template <int N>
__device__ __forceinline__ void p2_first(const Ctx& c, P2State& z, float (&o)[64], uint32_t (&Pc)[32], uint32_t (&Pn)[32],
                                         int ks, int vs, int cnt, int acc) {
  float s[N] = {};
  issue_qk(s, z.qd, desc_lo(c.sm + SM_RING, 16) + ks * 2048);
  if (vs >= 0) {
    p2_scales(z);
    issue_pv<8>(o, Pc, desc_lo(c.sm + SM_RING, 16384) + vs * 2048, acc);
  } else {
    WG_COMMIT();
  }
  mbar_expect(z.ab + (z.ai++ & 3) * 8, cnt == 1 ? 8192 : 0);
  PROFZ();
  WG_WAIT(1);
  PROFZ();
  pin(s);
  release(c, B_P2E + ks, cnt);
  causal_mask(s, c.warp * 16 + (c.lane >> 2) - 2 * (c.lane & 3));
  z.m0 = z.m1 = 0.f;
  row_exp<false>(s, Pn, 0.f, 0.f, z.l0, z.l1);
  z.shift = __any_sync(0xffffffffu, !(z.l0 + z.l1 <= SM_HI) || ((c.lane & 3) == 0 && !(fminf(z.l0, z.l1) >= SM_LO)));
  if (__builtin_expect(z.shift, 0)) {
    z.m0 = z.m1 = -INFINITY;
    row_max(s, z.m0, z.m1);
    row_exp<true>(s, Pn, z.m0, z.m1, z.l0, z.l1);
  }
  WG_WAIT(0);
  pin(o);
  if (vs >= 0) release(c, B_P2E + vs, 1);
}

template <bool SECOND>
__device__ __forceinline__ void p2_turn(const Ctx& c, P2State& z, float (&o)[64], uint32_t (&Pc)[32], uint32_t (&Pn)[32],
                                        int eb = -1, bool half = false, int vcnt = 1) {
  float s[64] = {};
  const int ks = z.ks, vs = wrap5(ks + 1);
  PROFZ();
  turn_wait(z.wb, z.wi++);
  PROFZ();
  issue_qk(s, z.qd, desc_lo(c.sm + SM_RING, 16) + ks * 2048);
  const uint32_t vd = desc_lo(c.sm + SM_RING, 16384) + vs * 2048;
  if (SECOND) {
    if (eb >= 0) stage_tile(o, c.sm + SM_BUF + eb * 16384, c, z.e0, z.e1);
    if (half) issue_pv<4>(o, Pc, vd, 0); else issue_pv<8>(o, Pc, vd, 0);
  } else {
    issue_pv<8>(o, Pc, vd, 1);
  }
  turn_pass(c, z.ab, z.ai++);
  if (SECOND) { if (eb >= 0) stage_done(c, eb); }
  PROFZ();
  z.ks = wrap5(ks + 2);
  WG_WAIT(1);
  PROFZ();
  pin(s);
  release(c, B_P2E + ks, 1);
  float t0, t1, a0 = 1.f, a1 = 1.f;
  row_exp<false>(s, Pn, 0.f, 0.f, t0, t1);
  z.shift = __any_sync(0xffffffffu, z.shift || !(t0 + t1 <= SM_HI));
  const bool redo = z.shift;
  if (__builtin_expect(redo, 0)) {
    float n0 = z.m0, n1 = z.m1;
    row_max(s, n0, n1);
    a0 = ex2(z.m0 - n0); a1 = ex2(z.m1 - n1);
    z.m0 = n0; z.m1 = n1;
    z.l0 *= a0; z.l1 *= a1;
    row_exp<true>(s, Pn, z.m0, z.m1, t0, t1);
  }
  WG_WAIT(0);
  pin(o);
  release(c, B_P2E + vs, vcnt);
  if (__builtin_expect(redo, 0)) {
#pragma unroll
    for (int i = 0; i < 16; i++) { o[4 * i] *= a0; o[4 * i + 1] *= a0; o[4 * i + 2] *= a1; o[4 * i + 3] *= a1; }
  }
  z.l0 += t0; z.l1 += t1;
}
__device__ __forceinline__ void copy_p(uint32_t (&d)[32], const uint32_t (&s)[32], int zero) {
#pragma unroll
  for (int i = 0; i < 32; i++) asm volatile("add.s32 %0, %1, %2;" : "=r"(d[i]) : "r"(s[i]), "r"(zero));
}

__device__ __forceinline__ void p2_consumer(const Params& p, const Ctx& c, int rot) {
  const int nit = p.s.r[c.cl].n2;
  const uint32_t fring = c.bar + B_P2F * 8, oring = c.bar + B_ORD * 8;
  float o[64] = {};
  uint32_t Pa[32] = {}, Pb[32] = {};
  P2State z;
  z.e0 = z.e1 = z.l0 = z.l1 = 0.f; z.ks = rot; z.shift = false;
  int acc = 0, n = 0;
  for (int it = 0; it < nit; it++) {
    const int j = p.s.r[c.cl].item[it] & 7, blk = p2_blk(c.rank, c.wg, it);
    const int lng = ((it ^ c.wg) & 1) ^ 1;
    z.qd = desc_lo(c.sm + SM_BUF, 16) + p2_buf(c.wg, it) * 1024;
    if (lng) { z.wb = oring; z.wi = n - it; z.ab = fring; z.ai = n + 1; }
    else { z.wb = fring; z.wi = n + 2; z.ab = oring; z.ai = n - it; }
    PROFZ();
    mbar_wait(c.bar + (B_QF + p2_buf(c.wg, it)) * 8, (it >> 1) & 1);
    turn_wait(fring, n + 1 - lng);
    PROFZ();
    const int vs = it ? wrap5(z.ks + 1) : -1, ks = lng ? z.ks : wrap5(z.ks + (it ? 2 : 1));
    if (blk & 1) p2_first<64>(c, z, o, Pa, Pb, ks, vs, 1 + lng, acc);
    else p2_first<32>(c, z, o, Pa, Pb, ks, vs, 1 + lng, acc);
    z.ks = wrap5(ks + (it == 0 && lng ? 1 : 2));
    PROF(c.wg, 24 + it);
    n += 2 * j + 2;
    int left = 2 * j + lng;
    acc = left != 0;
    if (left == 0) { copy_p(Pa, Pb, p.zero); continue; }
    p2_turn<true>(c, z, o, Pb, Pa, it > 0 ? p2_buf(c.wg, it - 1) : -1, !(blk & 1), 1 + lng);
    while (--left > 0) {
      p2_turn<false>(c, z, o, Pa, Pb);
      if (--left == 0) { copy_p(Pa, Pb, p.zero); break; }
      p2_turn<false>(c, z, o, Pb, Pa);
    }
  }
  {
    if (!acc && nit > 1) p2_epilogue(o, z.e0, z.e1, c, p2_buf(c.wg, nit));
    turn_wait(z.wb, z.wi);
    issue_pv<8>(o, Pa, desc_lo(c.sm + SM_RING, 16384) + z.ks * 2048, acc);
    if (((nit - 1) ^ c.wg) & 1) turn_pass(c, z.ab, z.ai);
    p2_scales(z);
    WG_WAIT(0);
    pin(o);
    release(c, B_P2E + z.ks);
    p2_epilogue(o, z.e0, z.e1, c, p2_buf(c.wg, nit - 1));
    PROF(c.wg, 24 + nit);
  }
}

__device__ __forceinline__ void p2_load_q(const Params& p, const Ctx& c, int it, int w) {
  const int item = p.s.r[c.cl].item[it], h = item >> 3, j = item & 7, b = p2_buf(w, it);
  mbar_expect(c.bar + (B_QF + b) * 8, 16384);
  bulk_load(c.sm + SM_BUF + b * 16384, g_Q + (size_t)(h * 32 + j * 4 + p2_blk(c.rank, w, it)) * 16384, 16384, c.bar + (B_QF + b) * 8, POL(4));
}
__device__ __forceinline__ void wait_p1_free(const Ctx& c, int u1, int s) {
  mbar_wait(c.bar + (B_P1E + 2 * s) * 8, ((u1 - 1 - 2 * s) / 10) & 1);
  mbar_wait(c.bar + (B_P1E + 2 * s + 1) * 8, ((u1 - 2 - 2 * s) / 10) & 1);
}
__device__ __forceinline__ void p2_producer(const Params& p, const Ctx& c, int u1, int rot) {
  const int nit = p.s.r[c.cl].n2;
  int slot = rot, cnt = 0, par = 1, n = 0;
  const uint8_t* pv = nullptr;
  bool pl = false;
  auto load = [&](const uint8_t* src, int expect, uint32_t fb, bool last) {
    if (cnt < 5) {
      if (u1) {
        wait_p1_free(c, u1, slot);
        if (cnt == 0) p2_load_q(p, c, 0, 1);
      }
      cnt++;
    } else {
      if (slot == rot) par ^= 1;
      mbar_wait(c.bar + (B_P2E + slot) * 8, par);
    }
    if (expect) mbar_expect(fb, expect);
    bulk_load_mc(c.sm + SM_RING + slot * 32768 + c.rank * 16384, src, 16384, fb, last ? POL(5) : L2_NORMAL);
    slot = wrap5(slot + 1);
  };
  for (int it = 0; it < nit; it++) {
    const int item = p.s.r[c.cl].item[it], h = item >> 3, j = item & 7;
    if (it == 1 && (c.phases & 16) && p.s.r[c.cl].n1 < 8) flag_wait<true>(F_GATE, 256);
    uint32_t ready = (c.phases & 16) ? 0u : 255u;
    if (it == 0) { if (c.phases & 16) flag_wait<false>(F_Q + item, 4); mbar_wait(c.bar + B_LAD * 8, 0); p2_load_q(p, c, 0, 0); if (!u1) p2_load_q(p, c, 0, 1); }
    for (int t = 2 * j + 1; t >= 0; t--) {
      mask_wait(ready, t >> 1, F_KV + h * 8 + (c.lane & 7), 8);
      const uint8_t* k = g_KV + (size_t)(p.s.slot[h][t >> 1] * 16 + t) * 32768 + c.rank * 16384;
      const uint32_t fb = c.bar + (B_P2F + (n & 3)) * 8;
      const bool last = (p.s.r[c.cl].last[it] >> (t >> 1)) & 1;
      load(k, pv && t != 2 * j ? 65536 : 32768, fb, last);
      if (!(t & 1) && t + 4 <= 2 * j && c.rank == 0) flag_add_rx(F_RD + h * 8 + (t >> 1) + 2);
      if (pv) load(pv, 0, t != 2 * j ? fb : c.bar + (B_ORD + ((n - 1 - it) & 3)) * 8, pl);
      pl = last;
      pv = k + (size_t)NH * 16 * 32768;
      n++;
    }
  }
  load(pv, 32768, c.bar + (B_P2F + (n & 3)) * 8, pl);
}

__device__ __forceinline__ void p2_storer(const Params& p, const Ctx& c, int sfpar) {
  const int nit = p.s.r[c.cl].n2;
  auto load_q = [&](int it, int w) {
    if (c.phases & 16) flag_wait<false>(F_Q + p.s.r[c.cl].item[it], 4);
    p2_load_q(p, c, it, w);
  };
  if (nit > 1) {
    load_q(1, 1); p2_load_q(p, c, 1, 0); }
  for (int i = 0; i < 2 * nit; i++) {
    const int it = i >> 1, w = (it ^ i ^ 1) & 1, b = p2_buf(w, it);
    const int item = p.s.r[c.cl].item[it], h = item >> 3, j = item & 7;
    mbar_wait(c.bar + (B_SF + b) * 8, (sfpar >> b) & 1);
    sfpar ^= 1 << b;
    bulk_store(g_Q + (size_t)(h * 32 + j * 4 + p2_blk(c.rank, w, it)) * 16384, c.sm + SM_BUF + b * 16384, 16384, POL(1));
    BULK_COMMIT();
    BULK_WAIT(0);
    flag_add_rx(F_CTX + j * 64 + h);
    if ((i & 1) && it + 2 < nit) { load_q(it + 2, w); p2_load_q(p, c, it + 2, w ^ 1); }
  }
  release(c, B_DONE);
}

__device__ __forceinline__ int p3_pos(int i, int x) { return i < 4 ? (i + x) & 3 : 4; }
__device__ __forceinline__ void p3_consumer(const Params& p, const Ctx& c, int x) {
  const bool first = p.s.r[c.cl].p3 >= 24;
  const int tile = p.s.r[c.cl].p3 - (first ? 24 : 0), j = tile / 3, nt = tile - 3 * j;
  const int na = first ? 9 : 0, nb = p.s.task[c.cl][1] - p.s.task[c.cl][0];
  const uint32_t ad = desc_lo(c.sm + SM_RING + c.wg * 8192, 16), bd = desc_lo(c.sm + SM_RING + 16384, 4096);
  float acc[96] = {};
  int slot = 0, par = 0, prev = 0;
  float g0 = 0.f, g1 = 0.f;
  const int hold = c.wg && LAG ? na + nb - LAG : -1, pass = c.wg || !LAG ? -1 : na + nb - 1;
#pragma unroll 1
  for (int kb = 0; kb < nb; kb++) {
    if (kb == hold) bar_sync(6, 256);
    mbar_wait(c.bar + (B_P3F + slot) * 8, par);
    if (kb == 0) PROF(c.wg, 39);
    WG_FENCE();
#pragma unroll
    for (int kk = 0; kk < 4; kk++) wgmma_ss192<1>(acc, ad + p3_pos(slot, x) * 2560 + kk * 2, bd + p3_pos(slot, x) * 2560 + (kk >> 1) * 768 + (kk & 1) * 128, kk != 0 ? 1 : kb != 0);
    WG_COMMIT();
    if (kb == pass) bar_arrive(6, 256);
    WG_WAIT(1);
    if (kb > 0) release(c, B_P3E + prev);
    else {
      const float* g = g_gate + j * 256 + c.rank * 128 + c.wg * 64 + c.warp * 16 + (c.lane >> 2);
      g0 = __ldcg(g); g1 = __ldcg(g + 8);
    }
    prev = slot;
    if (++slot == 5) { slot = 0; par ^= 1; }
  }
  WG_WAIT(0);
  pin(acc);
  g0 = 1.f - g0; g1 = 1.f - g1;
#pragma unroll
  for (int i = 0; i < 24; i++) { acc[4 * i] *= g0; acc[4 * i + 1] *= g0; acc[4 * i + 2] *= g1; acc[4 * i + 3] *= g1; }
#pragma unroll 1
  for (int kb = nb; kb < nb + na; kb++) {
    if (kb == hold) bar_sync(6, 256);
    mbar_wait(c.bar + (B_P3F + slot) * 8, par);
    if (kb == 0) PROF(c.wg, 39);
    WG_FENCE();
#pragma unroll
    for (int kk = 0; kk < 4; kk++) wgmma_ss192<1, 1>(acc, ad + p3_pos(slot, x) * 2560 + kk * 128, bd + p3_pos(slot, x) * 2560 + (kk >> 1) * 768 + (kk & 1) * 128, 1);
    WG_COMMIT();
    if (kb == pass) bar_arrive(6, 256);
    WG_WAIT(1);
    if (kb > 0) release(c, B_P3E + prev);
    prev = slot;
    if (++slot == 5) { slot = 0; par ^= 1; }
  }
  WG_WAIT(0);
  pin(acc);
  PROF(c.wg, 40);
  if (first) bar_sync(4 + c.wg, 128);
  mbar_wait(c.bar + B_OUT * 8, 0);
  const int row = (c.lane & 7) + ((c.lane >> 3) & 1) * 8;
  const uint32_t wbase = c.sm + SM_RING + c.wg * 8192 + c.warp * 2048;
  const uint32_t base = wbase + row * 128 + (((c.lane >> 4) ^ (row & 7)) << 4);
#pragma unroll
  for (int i = 0; i < 12; i++) {
    stsm4((base ^ ((i & 3) << 5)) + (i >> 2) * 40960, pack_bf16(acc[8 * i], acc[8 * i + 1]), pack_bf16(acc[8 * i + 2], acc[8 * i + 3]),
          pack_bf16(acc[8 * i + 4], acc[8 * i + 5]), pack_bf16(acc[8 * i + 6], acc[8 * i + 7]));
    if ((i & 3) == 3) {
      FENCE_ASYNC_SMEM();
      bar_sync(4 + c.wg, 128);
      if (c.warp == (i >> 2)) tma2d_add(&p.map_out, c.sm + SM_RING + c.wg * 8192 + c.warp * 40960, nt * 192 + c.warp * 64, j * 256 + c.rank * 128 + c.wg * 64);
    }
  }
  BULK_COMMIT();
  PROF(c.wg, 43);
  BULK_WAIT_READ(0);
  PROF(c.wg, 44);
}

__device__ __forceinline__ void p3_producer(const Params& p, const Ctx& c, int u1, int u2, int rot, int x) {
  const bool first = p.s.r[c.cl].p3 >= 24;
  const int tile = p.s.r[c.cl].p3 - (first ? 24 : 0), j = tile / 3, nt = tile - 3 * j;
  int slot = 0, par = 1, cnt = 0;
  auto wait_free = [&](int s) {
    const int f = wrap5(s + 5 - rot);
    if (f < u2) mbar_wait(c.bar + (B_P2E + s) * 8, ((u2 - 1 - f) / 5) & 1);
    else if (u1) wait_p1_free(c, u1, s);
  };
  asm volatile(ELECT("prefetch.tensormap [%0];") ::"l"(&p.map_o[0]) : "memory");
  asm volatile(ELECT("prefetch.tensormap [%0];") ::"l"(&p.map_out) : "memory");
  if ((c.phases & 16) && p.s.r[c.cl].n1 < 8 && p.s.r[c.cl].n2 < 2) flag_wait<true>(F_GATE, 256);
  uint32_t ready = (c.phases & 16) ? 0u : ~0u;
  const int q1 = p.s.task[c.cl][1];
  for (int q = p.s.task[c.cl][0]; q < q1 + (first ? 9 : 0); q++) {
    const bool brA = q >= q1;
    const int kb = brA ? q - q1 : p.s.p3_order[tile][q];
    if (!brA) mask_wait(ready, kb >> 1, F_CTX + j * 64 + c.lane, 4);
    else if (kb == 0 && (c.phases & 16)) flag_wait<false>(F_CTX + j * 64 + 32, 16);
    const uint8_t* a = brA ? g_oA + (j * 4 + c.rank * 2) * 73728 + kb * 8192 : g_Q + (size_t)((kb >> 1) * 32 + j * 4 + c.rank * 2) * 16384 + (kb & 1) * 8192;
    const uint32_t st = c.sm + SM_RING + p3_pos(slot, x) * 40960, fb = c.bar + (B_P3F + slot) * 8;
    if (cnt < 4) { wait_free(p3_pos(cnt, x)); wait_free(p3_pos(cnt, x) + 1); }
    else if (cnt == 4) mbar_wait(c.bar + B_DONE * 8, 0);
    else mbar_wait(c.bar + (B_P3E + slot) * 8, par);
    cnt++;
    mbar_expect(fb, 40960);
    bulk_load(st, a, 8192, fb, POL(3));
    bulk_load(st + 8192, a + (brA ? 73728 : 16384), 8192, fb, POL(3));
    tma3d_mc(st + 16384 + c.rank * 12288, &p.map_o[brA], 0, kb * 64 + c.rank * 32, nt * 3, fb);
    if (++slot == 5) { slot = 0; par ^= 1; }
  }
}

__device__ __forceinline__ float bf_lo(uint32_t w) { return __uint_as_float(w << 16); }
__device__ __forceinline__ float bf_hi(uint32_t w) { return __uint_as_float(w & 0xffff0000u); }

__device__ __forceinline__ void gate_rows(const Params& p, int row0, int lane) {
  const uint4* x = reinterpret_cast<const uint4*>(p.x + (size_t)(row0 + (lane >> 2)) * DM) + (lane & 3);
  const uint4* w = reinterpret_cast<const uint4*>(p.gate_w) + (lane & 3);
  float a = 0.f;
#pragma unroll 1
  for (int b = 0; b < 3; b++) {
    uint4 u[6];
#pragma unroll
    for (int i = 0; i < 6; i++) u[i] = __ldg(x + (b * 6 + i) * 4);
#pragma unroll
    for (int i = 0; i < 6; i++) {
      const uint4 v = __ldg(w + (b * 6 + i) * 4);
      a = fmaf(bf_lo(u[i].x), bf_lo(v.x), a); a = fmaf(bf_hi(u[i].x), bf_hi(v.x), a);
      a = fmaf(bf_lo(u[i].y), bf_lo(v.y), a); a = fmaf(bf_hi(u[i].y), bf_hi(v.y), a);
      a = fmaf(bf_lo(u[i].z), bf_lo(v.z), a); a = fmaf(bf_hi(u[i].z), bf_hi(v.z), a);
      a = fmaf(bf_lo(u[i].w), bf_lo(v.w), a); a = fmaf(bf_hi(u[i].w), bf_hi(v.w), a);
    }
  }
  a += __shfl_xor_sync(0xffffffffu, a, 1);
  a += __shfl_xor_sync(0xffffffffu, a, 2);
  if ((lane & 3) == 0) g_gate[row0 + (lane >> 2)] = 1.f / (1.f + __expf(-a));
}

__device__ __forceinline__ void lds10(uint32_t (&k)[10], uint32_t a) {
  asm volatile("ld.shared.v2.u32 {%0, %1}, [%10];\nld.shared.v2.u32 {%2, %3}, [%10+8];\nld.shared.v2.u32 {%4, %5}, [%10+16];\n"
               "ld.shared.v2.u32 {%6, %7}, [%10+24];\nld.shared.v2.u32 {%8, %9}, [%10+32];"
               : "=r"(k[0]), "=r"(k[1]), "=r"(k[2]), "=r"(k[3]), "=r"(k[4]), "=r"(k[5]), "=r"(k[6]), "=r"(k[7]), "=r"(k[8]), "=r"(k[9]) : "r"(a));
}
__device__ __forceinline__ void local_attn(const Params& p, const Ctx& c, int rb, int hs) {
  const int lane = c.lane, grp = rb >> 2, par = lane >> 4, i0 = 2 * (lane & 15);
  const uint32_t buf = c.sm + SM_BUF + (c.warp - 2) * 8192, bqk = c.bar + (B_LA + (c.warp - 2) * 2) * 8, bv = bqk + 8;
  const uint32_t mine = buf + 2304 + par * 160 + i0 * 4;
  const bool flags = c.phases & 16;
  auto fetch_qk = [&](int i) {
    if (flags && !(i & 1)) {
      const int q = i >> 1;
      const int tgt = q == 0 ? 24 : q == 3 ? 8 : 12;
      flag_wait<false>(F_QKVA + (grp - (grp > 0 && (rb & 3) == 0 ? par : 0)) * 4 + q, tgt);
    }
    mbar_expect(bqk, 5184);
    tma3d(buf, &p.map_t[0], rb * 32 + 8, 0, 9 * (4 * i + hs), bqk, POL(2));
    tma3d(buf + 2304, &p.map_t[1], rb * 32, 0, 288 + 9 * (4 * i + hs), bqk, POL(2));
  };
  auto fetch_v = [&](int i) { mbar_expect(bv, 2880); tma3d(buf + 5248, &p.map_t[1], rb * 32, 0, 576 + 9 * (4 * i + hs), bv, POL(2)); };
  fetch_qk(0);
  if (flags) flag_wait<true>(F_GATE, 256);
#pragma unroll 1
  for (int q = 0; q < 8; q++) {
    fetch_v(q);
    float a[8], b[8];
#pragma unroll
    for (int w = 0; w < 8; w++) a[w] = b[w] = 0.f;
    mbar_wait(bqk, q & 1);
    PROFB(1 + 2 * q);
#pragma unroll 1
    for (int j = 0; j < 9; j++) {
      uint32_t x, y, k[10];
      asm volatile("ld.shared.v2.u32 {%0, %1}, [%2];" : "=r"(x), "=r"(y) : "r"(buf + lane * 8 + j * 256));
      lds10(k, mine + j * 320);
      const float xl = bf_lo(x), xh = bf_hi(x), yl = bf_lo(y), yh = bf_hi(y);
#pragma unroll
      for (int m = 1; m < 10; m++) {
        const float kl = bf_lo(k[m]), kh = bf_hi(k[m]);
        if (m < 9) a[8 - m] = fmaf(xl, kl, fmaf(xh, kh, a[8 - m]));
        if (m > 1) b[9 - m] = fmaf(yl, kl, fmaf(yh, kh, b[9 - m]));
      }
    }
    __syncwarp();
    if (q < 7) fetch_qk(q + 1);
    constexpr float SC = 0.23570226039551584f * 1.4426950408889634f;
    const float* gp = g_gate + rb * 64 + 2 * i0 + par;
    const float ga = __ldcg(gp), gb = __ldcg(gp + 2);
    float ma = a[0], mb = b[0];
#pragma unroll
    for (int w = 1; w < 8; w++) {
      if (rb == 0) {
        if (i0 < w) a[w] = -INFINITY;
        if (i0 + 1 < w) b[w] = -INFINITY;
      }
      ma = fmaxf(ma, a[w]); mb = fmaxf(mb, b[w]);
    }
    float la = 0.f, lb = 0.f;
#pragma unroll
    for (int w = 0; w < 8; w++) {
      a[w] = ex2((a[w] - ma) * SC); b[w] = ex2((b[w] - mb) * SC);
      la += a[w]; lb += b[w];
    }
    la = __fdividef(ga, la); lb = __fdividef(gb, lb);
#pragma unroll
    for (int w = 0; w < 8; w++) { a[w] *= la; b[w] *= lb; }
    uint8_t* dst = g_oA + rb * 73728 + ((i0 & 2) + par) * 4;
    mbar_wait(bv, q & 1);
#pragma unroll 1
    for (int j = 0; j < 9; j++) {
      uint32_t v[10];
      lds10(v, mine + 2944 + j * 320);
      float a0 = 0.f, a1 = 0.f, b0 = 0.f, b1 = 0.f;
#pragma unroll
      for (int m = 1; m < 10; m++) {
        const float vl = bf_lo(v[m]), vh = bf_hi(v[m]);
        if (m < 9) { a0 = fmaf(a[8 - m], vl, a0); a1 = fmaf(a[8 - m], vh, a1); }
        if (m > 1) { b0 = fmaf(b[9 - m], vl, b0); b1 = fmaf(b[9 - m], vh, b1); }
      }
      const uint32_t wa = pack_bf16(a0, a1), wb = pack_bf16(b0, b1);
      const uint32_t got = __shfl_xor_sync(0xffffffffu, par ? wa : wb, 16);
      const uint32_t r0 = par ? got : wa, r1 = par ? wb : got;
      const int col = 18 * (4 * q + hs) + 2 * j, o = col * 128 + ((((i0 >> 2) ^ col) & 7) << 4);
      *reinterpret_cast<uint32_t*>(dst + o) = __byte_perm(r0, r1, 0x5410);
      *reinterpret_cast<uint32_t*>(dst + ((o + 128) ^ 16)) = __byte_perm(r0, r1, 0x7632);
    }
    __syncwarp();
    PROFB(2 + 2 * q);
  }
  mbar_arrive_one(c.bar + B_LAD * 8);
  flag_add(F_CTX + grp * 64 + 32);
}

__global__ void __cluster_dims__(2, 1, 1) __launch_bounds__(384, 1) fused_kernel(const __grid_constant__ Params p) {
  extern __shared__ uint8_t smem_raw[];
  Ctx c;
  c.sm = ((uint32_t)__cvta_generic_to_shared(smem_raw) + 1023u) & ~1023u;
  c.bar = c.sm + SM_BAR;
  c.lane = threadIdx.x & 31;
  const int wid = __shfl_sync(0xffffffffu, threadIdx.x >> 5, 0);
  if (wid < 6) asm volatile("prefetch.tensormap [%0];" ::"l"(&p.map_a[0] + wid) : "memory");
  c.wg = wid >> 2;
  c.warp = wid & 3;
  PROF(c.wg, 0);
  PROFG(61);
  c.cl = (blockIdx.x + (wid >> 4)) >> 1;
  c.rank = blockIdx.x & 1;
  c.rbar = mapa(c.bar, c.lane & 1);
  {
    const int w = wid, cnt = (((int)(B_CNT >> (4 * w)) - 1) & 15) + 1;
    if (w < 11) {
#pragma unroll
      for (int i = 0; i < 8; i++) asm volatile("mbarrier.init.shared::cta.b64 [%0], %1;" ::"r"(c.bar + w * 64 + i * 8), "r"(cnt));
    }
    asm volatile("fence.mbarrier_init.release.cluster;" ::: "memory");
  }
  if (c.wg == 2) PROF(2, 56);
  asm volatile("barrier.cluster.arrive.relaxed;" ::: "memory");
  c.phases = p.s.r[c.cl].phases;
  const bool do1 = p.s.r[c.cl].n1 > 0, do2 = p.s.r[c.cl].n2 > 0, do3 = p.s.r[c.cl].p3 != 255;
  if (do1 && c.wg == 2 && c.warp == 0) {
    const int type = p.s.r[c.cl].slab >> 3;
    PROF(2, 57);
    FENCE_ASYNC_SMEM();
    mbar_expect(c.bar + B_P1F * 8, type ? 32768 : 16384);
    tma2d(type ? c.sm + SM_BUF + 32768 : c.sm + SM_RING, &p.map_a[type], type ? 512 : 0, (p.s.r[c.cl].slab & 7) * 256 + c.rank * 128, c.bar + B_P1F * 8);
    PROF(2, 58);
  }
  asm volatile("barrier.cluster.wait.acquire;" ::: "memory");
  if (c.wg == 2) PROF(2, 59);
  if (do1 && c.wg == 2 && c.warp == 0) {
    const int type = p.s.r[c.cl].slab >> 3, tile = p.s.r[c.cl].tile[0] & 63;
    const CUtensorMap* m = &p.map_w[type * 2 + (tile >> 5)];
#pragma unroll 1
    for (int s = 1 - type; s < NPRO; s++) {
      const int kb = (s - type) >> 1;
      const uint32_t fb = c.bar + (B_P1F + s) * 8;
      if (s) mbar_expect(fb, 16384);
      if ((s ^ type) & 1) tma2d_mc(c.sm + SM_RING + s * 16384 + c.rank * 8192, m, (tile & 31) * 128 + c.rank * 64, kb < 0 ? 512 : kb * 64, fb);
      else tma2d(c.sm + SM_RING + s * 16384, &p.map_a[type], kb * 64, (p.s.r[c.cl].slab & 7) * 256 + c.rank * 128, fb);
    }
  }

  if (c.wg < 2) {
    PROF(c.wg, 4);
    asm volatile("setmaxnreg.inc.sync.aligned.u32 224;");
    if (c.wg == 1) {
      if (do1) bar_arrive(ORDER, 256);
      if (c.lane == 0) mbar_arrive(c.bar + B_P2F * 8);
    }
    if (do1) p1_consumer(p, c);
    if (do2) p2_consumer(p, c, p.s.r[c.cl].rot);
    if (do3) p3_consumer(p, c, p.s.r[c.cl].x3);
    PROF(c.wg, 63);
    PROFG(62);
    if (c.lane == 0) mbar_arrive(c.bar + B_FIN * 8);
    __syncwarp();
    cluster_sync();
  } else {
    asm volatile("setmaxnreg.dec.sync.aligned.u32 56;");
    if (c.warp == 0) {
      PROF(2, 60);
      if (do1) p1_producer(p, c);
      if (do2) p2_producer(p, c, p.s.r[c.cl].u1, p.s.r[c.cl].rot);
      if (do3) p3_producer(p, c, p.s.r[c.cl].u1, p.s.r[c.cl].u2, p.s.r[c.cl].rot, p.s.r[c.cl].x3);
    } else if (c.warp == 1) {
      int sfpar = 0;
      if (do1) {
        p1_storer(p, c);
        sfpar = (p.s.r[c.cl].n1 & 1) * 10;
      }
      if (do2) p2_storer(p, c, sfpar);
      else { mbar_wait(c.bar + B_LAD * 8, 0); release(c, B_DONE); }
      if (do3) {
        const int tile = p.s.r[c.cl].p3 % 24;
        if (p.s.task[c.cl][1] == 64) {
          for (int r = 0; r < (64 - p.s.task[c.cl][0] - ZLEAD) / 5; r++) mbar_wait(c.bar + B_P3F * 8, r & 1);
          const int j = tile / 3, nt = tile - 3 * j;
          uint4* o = reinterpret_cast<uint4*>(p.out + (size_t)(j * 256 + c.rank * 128 + (c.lane >> 3)) * DM + nt * 192) + (c.lane & 7);
#pragma unroll 4
          for (int r = 0; r < 32; r++) o[r * 288] = o[r * 288 + 8] = o[r * 288 + 16] = make_uint4(0u, 0u, 0u, 0u);
          __syncwarp();
          flag_add(F_OUT + tile * 2 + c.rank);
        } else if (c.phases & 16) {
          flag_wait<false, 256>(F_OUT + tile * 2 + c.rank, 1);
        }
        mbar_arrive_one(c.bar + B_OUT * 8);
      }
    } else {
      const int bw = blockIdx.x * 2 + (c.warp - 2);
      if ((c.phases & 1) && bw < 256) {
        gate_rows(p, bw * 8, c.lane);
        __syncwarp();
        flag_add(F_GATE);
      }
      if (p.s.r[c.cl].bg != 255) local_attn(p, c, p.s.r[c.cl].bg, bw & 3);
      else if (c.lane == 0) mbar_arrive(c.bar + B_LAD * 8);
    }
    __syncwarp();
    bar_sync(3, 128);
    if (c.warp == 0 && (c.phases & 32)) {
      int last = 0;
      if (c.lane == 0) { __threadfence(); last = atomicAdd(g_flags + F_DONE, 1) == 2 * NCL - 1; }
      if (__shfl_sync(0xffffffffu, last, 0)) for (int i = c.lane; i < F_NUM; i += 32) g_flags[i] = 0;
    }
    if (c.warp == 1) mbar_wait(c.bar + B_FIN * 8, 0);
    __syncwarp();
    cluster_sync();
  }
}

SCHED_DECL Sched k_sched = {
  {{0,30,2,44,0,{250,248,0,0,0,0,0,0,0,0,0},{0,0,0,0,0,0,0,0,0,0,0},{65,41,136,34,69,3,0,10,11,17,12,26,21,20,27,15,28,19,13,14,25,18,22,7,29,30,24,31,16,23}},
   {1,30,2,8,1,{241,185,0,0,0,0,0,0,0,0,0},{0,0,0,0,0,0,0,0,0,0,0},{65,166,2,40,0,3,5,10,11,17,12,26,21,20,27,15,28,13,14,19,18,25,7,22,29,30,24,31,16,23}},
   {2,29,1,10,2,{244,0,0,0,0,0,0,0,0,0,0},{16,0,0,0,0,0,0,0,0,0,0},{73,166,2,40,3,0,5,11,17,12,21,26,27,20,15,28,13,14,19,18,25,22,7,29,30,24,31,16,23,0}},
   {3,29,2,2,3,{188,128,0,0,0,0,0,0,0,0,0},{0,0,0,0,0,0,0,0,0,0,0},{65,41,6,40,3,0,11,17,10,12,21,26,27,20,15,28,13,14,19,18,25,22,7,29,24,30,31,23,16,0}},
   {4,28,0,13,4,{0,0,0,0,0,0,0,0,0,0,0},{0,0,0,0,0,0,0,0,0,0,0},{66,33,9,40,3,5,42,17,12,21,26,27,20,15,28,13,14,19,18,25,22,7,29,24,30,31,23,16,0,0}},
   {5,27,0,1,5,{0,0,0,0,0,0,0,0,0,0,0},{0,0,0,0,0,0,0,0,0,0,0},{66,166,9,40,3,5,42,17,44,26,27,20,15,28,13,14,19,25,18,71,22,29,24,30,31,23,16,0,0,0}},
   {6,26,0,9,6,{0,0,0,0,0,0,0,0,0,0,0},{0,0,0,0,0,0,0,0,0,0,0},{73,6,68,40,0,10,43,12,53,27,20,15,28,13,14,19,18,25,22,29,7,24,30,31,23,16,0,0,0,0}},
   {7,25,0,23,7,{0,0,0,0,0,0,0,0,0,0,0},{0,0,0,0,0,0,0,0,0,0,0},{66,9,136,67,69,107,76,117,91,84,79,92,77,78,83,82,89,86,93,71,88,94,95,87,80,0,0,0,0,0}},
   {0,30,1,12,8,{187,0,0,0,0,0,0,0,0,0,0},{0,0,0,0,0,0,0,0,0,0,0},{97,6,104,4,101,35,32,42,43,49,44,58,53,52,59,47,60,51,45,46,57,50,54,39,61,62,56,63,48,55}},
   {1,30,1,9,9,{243,0,0,0,0,0,0,0,0,0,0},{15,0,0,0,0,0,0,0,0,0,0},{97,9,34,4,32,35,37,42,43,49,44,58,53,52,59,47,60,45,46,51,50,57,39,54,61,62,56,63,48,55}},
   {2,29,1,0,10,{252,0,0,0,0,0,0,0,0,0,0},{0,0,0,0,0,0,0,0,0,0,0},{105,1,34,4,35,32,37,43,49,44,53,58,59,52,47,60,45,46,51,50,57,54,39,61,62,56,63,48,55,0}},
   {3,29,1,45,11,{195,0,0,0,0,0,0,0,0,0,0},{0,0,0,0,0,0,0,0,0,0,0},{97,2,38,4,35,32,43,49,42,44,53,58,59,52,47,60,45,46,51,50,57,54,39,61,56,62,63,55,48,0}},
   {4,28,0,6,12,{0,0,0,0,0,0,0,0,0,0,0},{0,0,0,0,0,0,0,0,0,0,0},{98,6,41,4,35,37,11,49,44,53,58,59,52,47,60,45,46,51,50,57,54,39,61,56,62,63,55,48,0,0}},
   {5,27,0,10,13,{0,0,0,0,0,0,0,0,0,0,0},{0,0,0,0,0,0,0,0,0,0,0},{98,1,41,4,35,37,11,49,21,58,59,52,47,60,45,46,51,57,50,103,54,61,56,62,63,55,48,0,0,0}},
   {6,26,0,16,14,{0,0,0,0,0,0,0,0,0,0,0},{0,0,0,0,0,0,0,0,0,0,0},{105,166,100,67,32,42,17,44,26,59,52,47,60,45,46,51,50,57,54,61,39,56,62,63,55,48,0,0,0,0}},
   {7,25,0,5,15,{0,0,0,0,0,0,0,0,0,0,0},{0,0,0,0,0,0,0,0,0,0,0},{98,41,104,99,101,81,108,90,123,116,111,124,109,110,115,114,121,118,125,103,120,126,127,119,112,0,0,0,0,0}},
   {0,4,5,11,255,{8,71,44,222,224,0,0,0,0,0,0},{0,0,0,112,0,0,0,0,0,0,0},{73,166,2,36,0,0,0,0,0,0,0,0,0,0,0,0,0,0,0,0,0,0,0,0,0,0,0,0,0,0}},
   {1,4,6,38,255,{73,70,85,159,145,245,0,0,0,0,0},{0,0,0,0,0,32,0,0,0,0,0},{70,41,136,36,0,0,0,0,0,0,0,0,0,0,0,0,0,0,0,0,0,0,0,0,0,0,0,0,0,0}},
   {2,6,7,22,255,{32,68,45,99,162,115,134,0,0,0,0},{0,0,0,0,0,0,0,0,0,0,0},{70,33,136,36,74,42,0,0,0,0,0,0,0,0,0,0,0,0,0,0,0,0,0,0,0,0,0,0,0,0}},
   {3,6,6,6,255,{16,35,87,212,149,235,0,0,0,0,0},{0,0,128,0,0,0,0,0,0,0,0},{73,34,136,36,69,37,0,0,0,0,0,0,0,0,0,0,0,0,0,0,0,0,0,0,0,0,0,0,0,0}},
   {4,8,6,5,255,{40,36,83,166,204,133,0,0,0,0,0},{0,0,0,14,0,0,0,0,0,0,0},{65,166,136,36,0,32,10,43,0,0,0,0,0,0,0,0,0,0,0,0,0,0,0,0,0,0,0,0,0,0}},
   {5,10,5,33,255,{0,46,213,239,186,0,0,0,0,0,0},{0,0,0,128,6,0,0,0,0,0,0},{70,33,136,36,0,32,10,43,12,53,0,0,0,0,0,0,0,0,0,0,0,0,0,0,0,0,0,0,0,0}},
   {6,10,7,40,255,{80,2,84,163,114,247,192,0,0,0,0},{0,0,0,0,0,128,1,0,0,0,0},{66,1,136,99,69,37,11,49,21,58,0,0,0,0,0,0,0,0,0,0,0,0,0,0,0,0,0,0,0,0}},
   {7,5,4,3,255,{14,4,174,152,0,0,0,0,0,0,0},{0,0,127,0,0,0,0,0,0,0,0},{65,6,68,64,74,0,0,0,0,0,0,0,0,0,0,0,0,0,0,0,0,0,0,0,0,0,0,0,0,0}},
   {8,17,3,27,16,{136,207,253,0,0,0,0,0,0,0,0},{0,0,0,0,0,0,0,0,0,0,0},{73,161,2,69,10,35,44,109,17,27,26,77,28,25,18,7,30,0,0,0,0,0,0,0,0,0,0,0,0,0}},
   {9,18,3,4,17,{219,202,190,0,0,0,0,0,0,0,0},{0,0,64,0,0,0,0,0,0,0,0},{65,41,34,8,103,5,11,40,10,21,20,15,13,19,71,22,24,80,0,0,0,0,0,0,0,0,0,0,0,0}},
   {10,17,3,13,18,{161,108,191,0,0,0,0,0,0,0,0},{0,0,128,0,0,0,0,0,0,0,0},{73,161,166,4,0,39,11,5,45,21,20,27,13,19,18,22,30,0,0,0,0,0,0,0,0,0,0,0,0,0}},
   {11,17,3,18,19,{170,156,135,0,0,0,0,0,0,0,0},{0,0,255,0,0,0,0,0,0,0,0},{65,41,8,69,103,11,17,40,12,84,27,77,19,18,86,29,95,0,0,0,0,0,0,0,0,0,0,0,0,0}},
   {12,18,3,20,20,{216,148,56,0,0,0,0,0,0,0,0},{0,0,0,0,0,0,0,0,0,0,0},{66,41,8,3,103,0,10,17,40,21,20,15,13,19,86,7,24,31,0,0,0,0,0,0,0,0,0,0,0,0}},
   {13,18,3,25,21,{228,181,193,0,0,0,0,0,0,0,0},{0,0,0,0,0,0,0,0,0,0,0},{66,41,8,0,103,5,11,12,45,27,20,77,14,19,71,29,30,23,0,0,0,0,0,0,0,0,0,0,0,0}},
   {14,19,3,29,22,{208,116,254,0,0,0,0,0,0,0,0},{0,0,127,0,0,0,0,0,0,0,0},{73,41,132,38,10,81,39,12,45,26,20,15,14,25,86,88,30,31,16,0,0,0,0,0,0,0,0,0,0,0}},
   {15,18,3,17,23,{168,118,189,0,0,0,0,0,0,0,0},{0,123,56,0,0,0,0,0,0,0,0},{66,36,8,43,10,35,44,12,90,40,20,28,14,18,86,7,30,23,0,0,0,0,0,0,0,0,0,0,0,0}},
   {8,20,2,36,24,{206,242,0,0,0,0,0,0,0,0,0},{47,0,0,0,0,0,0,0,0,0,0},{65,165,132,3,0,39,104,11,12,21,83,20,15,14,86,29,24,31,23,16,0,0,0,0,0,0,0,0,0,0}},
   {9,19,3,35,25,{225,183,233,0,0,0,0,0,0,0,0},{0,128,0,0,0,0,0,0,0,0,0},{70,161,166,99,108,3,17,109,90,12,27,28,14,25,18,94,29,31,23,0,0,0,0,0,0,0,0,0,0,0}},
   {10,20,2,37,26,{150,234,0,0,0,0,0,0,0,0,0},{87,0,0,0,0,0,0,0,0,0,0},{70,165,107,74,35,44,17,40,12,26,79,78,28,25,71,29,95,24,16,23,0,0,0,0,0,0,0,0,0,0}},
   {11,19,2,22,27,{122,120,0,0,0,0,0,0,0,0,0},{0,0,0,0,0,0,0,0,0,0,0},{73,161,132,0,108,3,10,109,90,21,79,28,89,14,71,88,30,23,16,0,0,0,0,0,0,0,0,0,0,0}},
   {12,19,3,20,28,{121,203,237,0,0,0,0,0,0,0,0},{0,0,32,0,0,0,0,0,0,0,0},{65,161,34,99,108,5,76,11,45,26,27,28,82,14,25,29,30,23,16,0,0,0,0,0,0,0,0,0,0,0}},
   {13,18,3,47,29,{96,123,255,0,0,0,0,0,0,0,0},{0,4,128,0,0,0,0,0,0,0,0},{70,161,132,3,108,10,17,40,21,26,79,28,89,18,86,88,95,80,0,0,0,0,0,0,0,0,0,0,0,0}},
   {14,17,3,4,30,{88,117,176,0,0,0,0,0,0,0,0},{0,0,0,0,0,0,0,0,0,0,0},{66,161,8,43,75,35,44,40,21,27,92,77,19,18,71,29,87,0,0,0,0,0,0,0,0,0,0,0,0,0}},
   {15,18,2,24,31,{205,246,0,0,0,0,0,0,0,0,0},{0,64,0,0,0,0,0,0,0,0,0},{65,41,132,0,75,39,17,85,91,45,79,77,19,25,93,88,95,80,0,0,0,0,0,0,0,0,0,0,0,0}},
   {8,3,6,17,255,{22,34,89,98,231,112,0,0,0,0,0},{0,0,0,0,128,0,0,0,0,0,0},{160,170,34,0,0,0,0,0,0,0,0,0,0,0,0,0,0,0,0,0,0,0,0,0,0,0,0,0,0,0}},
   {9,3,6,41,255,{54,3,223,157,178,194,0,0,0,0,0},{0,0,0,0,0,0,0,0,0,0,0},{73,165,107,0,0,0,0,0,0,0,0,0,0,0,0,0,0,0,0,0,0,0,0,0,0,0,0,0,0,0}},
   {10,3,6,19,255,{13,66,27,81,165,104,0,0,0,0,0},{0,0,0,0,0,0,0,0,0,0,0},{160,170,2,0,0,0,0,0,0,0,0,0,0,0,0,0,0,0,0,0,0,0,0,0,0,0,0,0,0,0}},
   {11,3,7,39,255,{50,10,47,221,226,153,197,0,0,0,0},{0,0,0,0,0,0,32,0,0,0,0},{66,165,34,0,0,0,0,0,0,0,0,0,0,0,0,0,0,0,0,0,0,0,0,0,0,0,0,0,0,0}},
   {12,3,4,15,255,{15,143,220,160,0,0,0,0,0,0,0},{0,128,0,1,0,0,0,0,0,0,0},{70,165,166,0,0,0,0,0,0,0,0,0,0,0,0,0,0,0,0,0,0,0,0,0,0,0,0,0,0,0}},
   {13,4,7,30,255,{64,39,138,209,230,182,129,0,0,0,0},{0,0,0,0,0,127,0,0,0,0,0},{65,165,34,99,0,0,0,0,0,0,0,0,0,0,0,0,0,0,0,0,0,0,0,0,0,0,0,0,0,0}},
   {14,3,5,43,255,{12,5,215,158,196,0,0,0,0,0,0},{0,0,0,3,30,0,0,0,0,0,0},{70,165,64,0,0,0,0,0,0,0,0,0,0,0,0,0,0,0,0,0,0,0,0,0,0,0,0,0,0,0}},
   {15,4,7,1,255,{48,31,139,214,180,177,131,0,0,0,0},{0,0,0,0,0,0,0,0,0,0,0},{73,161,67,69,0,0,0,0,0,0,0,0,0,0,0,0,0,0,0,0,0,0,0,0,0,0,0,0,0,0}},
   {8,3,5,21,255,{21,33,95,109,146,0,0,0,0,0,0},{0,0,0,0,0,0,0,0,0,0,0},{164,6,166,0,0,0,0,0,0,0,0,0,0,0,0,0,0,0,0,0,0,0,0,0,0,0,0,0,0,0}},
   {9,3,7,46,255,{55,90,92,125,61,130,184,0,0,0,0},{136,0,0,0,0,0,1,0,0,0,0},{160,170,132,0,0,0,0,0,0,0,0,0,0,0,0,0,0,0,0,0,0,0,0,0,0,0,0,0,0,0}},
   {10,3,9,0,255,{72,17,67,26,25,42,97,229,113,0,0},{0,0,0,0,0,0,0,0,0,0,0},{164,1,8,0,0,0,0,0,0,0,0,0,0,0,0,0,0,0,0,0,0,0,0,0,0,0,0,0,0,0}},
   {11,4,6,21,255,{51,7,169,126,62,249,0,0,0,0,0},{0,0,0,0,0,0,0,0,0,0,0},{160,170,166,99,0,0,0,0,0,0,0,0,0,0,0,0,0,0,0,0,0,0,0,0,0,0,0,0,0,0}},
   {12,3,5,18,255,{53,1,94,111,144,0,0,0,0,0,0},{0,0,0,0,0,0,0,0,0,0,0},{160,170,107,0,0,0,0,0,0,0,0,0,0,0,0,0,0,0,0,0,0,0,0,0,0,0,0,0,0,0}},
   {13,3,6,16,255,{75,6,100,151,58,132,0,0,0,0,0},{0,0,0,0,0,0,0,0,0,0,0},{160,170,166,0,0,0,0,0,0,0,0,0,0,0,0,0,0,0,0,0,0,0,0,0,0,0,0,0,0,0}},
   {14,3,5,12,255,{19,37,175,210,147,0,0,0,0,0,0},{0,0,0,0,0,0,0,0,0,0,0},{160,170,67,0,0,0,0,0,0,0,0,0,0,0,0,0,0,0,0,0,0,0,0,0,0,0,0,0,0,0}},
   {15,3,6,42,255,{78,82,93,110,201,60,0,0,0,0,0},{0,0,0,0,0,31,0,0,0,0,0},{70,165,34,0,0,0,0,0,0,0,0,0,0,0,0,0,0,0,0,0,0,0,0,0,0,0,0,0,0,0}},
   {8,3,6,26,255,{74,76,28,127,63,232,0,0,0,0,0},{0,0,0,0,224,0,0,0,0,0,0},{105,72,107,0,0,0,0,0,0,0,0,0,0,0,0,0,0,0,0,0,0,0,0,0,0,0,0,0,0,0}},
   {9,3,6,31,255,{49,38,103,217,227,198,0,0,0,0,0},{0,0,0,0,0,0,0,0,0,0,0},{164,2,64,0,0,0,0,0,0,0,0,0,0,0,0,0,0,0,0,0,0,0,0,0,0,0,0,0,0,0}},
   {10,3,6,32,255,{79,41,141,171,106,238,0,0,0,0,0},{16,0,0,0,0,64,0,0,0,0,0},{105,98,67,0,0,0,0,0,0,0,0,0,0,0,0,0,0,0,0,0,0,0,0,0,0,0,0,0,0,0}},
   {11,3,7,28,255,{20,18,86,211,107,59,251,0,0,0,0},{0,0,0,0,0,0,0,0,0,0,0},{164,6,107,0,0,0,0,0,0,0,0,0,0,0,0,0,0,0,0,0,0,0,0,0,0,0,0,0,0,0}},
   {12,3,5,2,255,{11,30,140,164,154,0,0,0,0,0,0},{0,0,0,0,0,0,0,0,0,0,0},{164,9,132,0,0,0,0,0,0,0,0,0,0,0,0,0,0,0,0,0,0,0,0,0,0,0,0,0,0,0}},
   {13,3,5,7,255,{52,29,101,124,200,0,0,0,0,0,0},{0,0,0,0,0,0,0,0,0,0,0},{164,9,107,0,0,0,0,0,0,0,0,0,0,0,0,0,0,0,0,0,0,0,0,0,0,0,0,0,0,0}},
   {14,4,7,34,255,{77,43,137,173,218,179,236,0,0,0,0},{0,0,0,0,0,0,31,0,0,0,0},{164,1,34,69,0,0,0,0,0,0,0,0,0,0,0,0,0,0,0,0,0,0,0,0,0,0,0,0,0,0}},
   {15,3,4,14,255,{23,102,172,155,0,0,0,0,0,0,0},{7,0,0,0,0,0,0,0,0,0,0},{160,170,166,0,0,0,0,0,0,0,0,0,0,0,0,0,0,0,0,0,0,0,0,0,0,0,0,0,0,0}},
   {6,2,5,8,255,{9,69,142,119,57,0,0,0,0,0,0},{0,0,0,0,0,0,0,0,0,0,0},{98,33,0,0,0,0,0,0,0,0,0,0,0,0,0,0,0,0,0,0,0,0,0,0,0,0,0,0,0,0}},
   {7,9,7,14,255,{24,65,91,167,105,199,240,0,0,0,0},{0,0,0,0,0,192,0,0,0,0,0},{97,166,100,96,106,75,113,85,122,0,0,0,0,0,0,0,0,0,0,0,0,0,0,0,0,0,0,0,0,0}}},
  {{0,2,0,0},{9,20,0,0},{6,16,0,0},{9,15,0,0},{21,64,0,0},{16,64,0,0},{11,64,0,0},{6,64,0,0},{10,20,0,0},{1,11,0,0},{6,16,0,0},
   {0,6,0,0},{21,64,0,0},{16,64,0,0},{11,64,0,0},{6,64,0,0},{6,64,0,0},{0,3,0,0},{0,7,0,0},{5,21,0,0},{0,6,0,0},{0,1,0,0},
   {0,3,0,0},{1,64,0,0},{0,1,0,0},{5,16,0,0},{10,21,0,0},{9,15,0,0},{17,64,0,0},{0,7,0,0},{0,0,0,0},{4,14,0,0},{0,10,0,0},
   {0,6,0,0},{0,10,0,0},{7,64,0,0},{2,17,0,0},{0,6,0,0},{16,64,0,0},{0,6,0,0},{14,64,0,0},{0,4,0,0},{3,64,0,0},{0,5,0,0},
   {5,64,0,0},{0,5,0,0},{0,3,0,0},{7,16,0,0},{20,64,0,0},{0,0,0,0},{16,64,0,0},{6,20,0,0},{15,64,0,0},{3,11,0,0},{20,64,0,0},
   {0,9,0,0},{0,9,0,0},{0,9,0,0},{0,9,0,0},{0,5,0,0},{15,64,0,0},{9,64,0,0},{0,6,0,0},{15,64,0,0},{20,64,0,0},{3,15,0,0}},
  {{1,7,11,9,5,16,4,13,58,3,19,60,48,62,47,33,57,31,30,51,50,56,41,40,29,37,36,15,14,45,44,28,27,26,39,38,53,52,55,54,43,42,25,24,35,34,23,22,21,20,0,6,10,8,17,59,12,2,18,61,49,63,46,32},
   {21,1,7,11,9,5,17,59,13,3,19,60,48,62,46,32,57,31,30,51,50,56,41,29,37,36,15,14,45,44,28,40,27,26,39,38,53,52,55,54,43,42,25,24,35,34,23,22,20,0,6,10,8,4,16,58,12,2,18,61,49,63,47,33},
   {22,20,0,6,10,8,4,16,3,18,61,49,63,47,33,27,41,57,31,30,51,50,56,40,29,37,36,15,14,45,44,28,26,39,38,53,52,55,54,43,42,25,24,35,34,23,21,1,7,11,9,5,17,13,12,2,59,58,19,60,48,62,46,32},
   {61,41,40,55,54,25,24,43,42,53,52,57,56,31,30,21,20,35,34,23,27,26,22,7,6,11,29,28,10,15,14,17,39,51,50,37,36,38,16,9,8,1,0,5,4,19,18,13,45,44,12,3,2,60,48,49,58,59,32,33,63,62,47,46},
   {44,6,10,16,1,8,5,19,13,61,59,33,63,48,47,3,57,56,31,30,27,26,55,54,41,29,28,40,25,15,14,24,39,51,50,37,36,38,43,42,53,52,21,20,35,34,23,22,45,7,11,17,9,0,4,18,12,49,58,32,62,60,46,2},
   {59,33,62,48,47,2,55,54,41,40,25,24,57,56,31,30,43,42,53,52,21,27,26,20,35,34,29,28,23,22,15,14,7,39,51,37,36,50,38,6,11,10,17,16,9,8,1,0,5,45,44,4,19,18,13,12,3,61,49,58,63,32,60,46},
   {44,1,20,7,16,11,35,45,22,21,8,17,4,60,58,2,13,48,62,46,32,29,57,56,39,38,27,26,28,37,51,50,36,55,54,31,30,41,40,53,52,43,42,25,15,14,24,10,34,23,0,9,6,5,61,59,3,19,18,12,49,63,47,33},
   {14,7,17,5,45,3,19,12,59,43,42,25,24,53,41,40,52,55,54,31,29,28,30,57,39,38,56,27,26,37,36,51,50,11,10,35,34,23,22,1,0,21,20,9,15,8,6,16,4,44,2,18,13,58,60,61,48,49,62,63,46,47,32,33},
   {11,35,23,1,45,21,9,7,16,6,5,61,59,3,19,13,49,63,47,33,29,28,55,57,56,39,38,27,26,54,37,51,50,36,31,30,41,40,53,52,43,42,25,24,15,14,10,34,22,0,44,20,8,17,4,60,58,2,18,12,48,62,46,32},
   {12,16,19,5,3,58,63,48,46,61,33,43,42,41,40,53,55,54,52,25,24,31,30,57,56,27,39,38,26,21,37,36,51,50,20,29,28,45,44,35,34,7,6,15,14,23,22,1,0,11,10,9,8,17,13,18,4,59,49,62,2,47,60,32},
   {6,22,0,10,8,13,16,19,5,3,58,63,48,46,60,32,55,54,43,42,41,31,30,57,56,39,38,27,26,37,36,51,50,40,29,28,53,45,44,52,25,24,21,15,14,20,35,34,7,23,1,11,9,17,12,18,4,59,49,62,2,47,61,33},
   {16,12,18,4,2,59,41,40,43,42,53,52,25,24,21,20,55,54,35,34,7,31,30,57,56,39,38,27,26,6,37,36,51,50,23,29,28,45,44,22,1,0,11,15,14,10,9,8,17,13,19,5,3,58,48,49,62,63,46,47,60,61,32,33},
   {25,23,21,11,1,7,9,17,19,12,18,14,4,2,59,49,61,63,33,47,31,30,57,56,55,54,27,37,36,26,41,39,38,29,28,40,53,52,43,45,44,51,50,42,35,34,24,22,20,10,0,6,8,16,13,15,5,3,58,48,60,62,32,46},
   {35,25,23,21,11,1,7,9,16,13,17,18,14,5,3,58,48,60,62,32,46,57,56,31,30,27,37,36,26,55,39,38,29,28,54,41,40,53,52,45,44,51,50,43,42,34,24,22,20,10,0,6,8,19,15,12,4,2,59,49,61,63,33,47},
   {9,16,13,6,17,18,15,5,3,58,48,60,62,32,46,55,54,41,31,30,40,57,56,53,52,27,37,36,26,43,39,38,29,28,42,35,34,25,24,45,44,51,50,23,22,21,20,11,10,1,0,7,8,19,12,14,4,2,59,49,61,63,33,47},
   {14,4,2,44,59,43,42,25,55,54,24,35,41,40,53,52,34,23,22,31,57,56,30,27,26,21,29,51,50,28,20,11,10,7,6,39,38,1,0,9,8,37,36,17,16,19,18,13,12,15,5,3,45,58,48,49,60,61,62,63,46,47,32,33},
   {45,16,18,5,3,58,49,60,62,46,32,55,41,40,53,52,54,43,42,31,57,56,30,27,26,25,29,51,50,28,24,35,34,23,22,39,38,21,20,11,10,37,36,7,6,1,0,9,8,17,15,14,44,19,13,12,4,2,59,48,61,63,47,33},
   {14,17,44,19,18,12,4,2,59,49,61,63,47,33,41,40,53,52,55,31,30,57,56,27,26,54,43,51,50,29,28,42,25,24,35,39,38,34,23,22,21,20,37,36,11,10,7,6,1,0,15,9,8,45,16,13,5,3,58,48,60,62,46,32},
   {50,36,0,16,8,2,18,12,4,48,60,44,47,63,33,53,41,40,57,31,30,56,55,54,52,27,26,43,42,25,24,35,34,23,22,21,20,29,28,11,39,38,10,7,6,51,37,1,17,9,3,19,13,5,45,15,59,58,49,61,14,46,62,32},
   {45,15,49,25,24,35,34,23,22,21,20,43,42,11,53,52,41,40,57,31,30,56,55,54,27,26,10,7,6,1,0,17,16,9,8,3,2,29,28,19,39,38,18,13,51,50,37,36,12,5,4,44,14,48,58,59,60,61,46,47,62,63,32,33},
   {2,44,7,1,17,9,3,45,59,49,15,13,61,4,47,63,33,41,57,31,30,56,40,55,27,26,54,53,52,43,42,25,24,35,34,23,22,29,28,21,39,38,20,11,51,50,37,36,10,6,0,16,8,19,18,58,48,14,12,60,5,46,62,32},
   {20,10,9,6,45,44,0,7,16,58,18,14,12,4,63,2,49,61,47,33,31,30,41,57,29,28,39,38,27,26,37,36,56,40,55,54,53,51,50,52,43,42,25,24,35,34,23,22,21,11,1,8,17,59,19,15,13,5,3,62,48,60,46,32},
   {45,3,62,48,61,46,32,55,54,53,41,40,52,31,30,43,42,25,24,35,34,23,22,57,29,39,38,28,27,37,36,26,56,21,20,11,51,50,10,1,0,9,8,7,6,17,16,19,18,13,12,5,4,59,15,14,58,44,63,2,49,60,47,33},
   {12,4,2,45,59,62,55,54,53,52,43,41,40,42,31,30,25,24,35,34,23,22,21,57,56,29,39,38,28,27,37,36,26,20,11,10,1,51,50,0,9,8,7,6,17,16,19,18,13,5,3,44,58,14,15,63,48,49,60,61,46,47,32,33}},
  {{8,6,8,8,7,7,7,7},{0,0,2,0,1,2,3,1},{4,3,3,2,0,0,1,0},{7,7,6,6,6,6,6,6},
   {5,5,5,5,5,5,4,5},{6,8,9,7,8,8,8,8},{2,1,1,3,2,1,2,3},{12,9,1,4,4,3,1,6},
   {3,4,4,4,4,4,5,4},{1,2,0,1,3,3,0,2},{9,9,7,11,9,9,9,9},{10,10,10,9,10,10,10,10},
   {12,12,12,12,12,2,3,0},{8,2,8,7,8,8,8,7},{6,6,9,9,10,10,10,10},{5,5,0,6,6,1,1,2},
   {1,1,9,11,9,9,9,7},{11,11,11,10,11,11,11,11},{7,10,11,11,11,9,11,4},{2,8,10,10,12,2,3,0},
   {0,0,5,1,0,6,6,6},{14,14,13,0,1,0,5,4},{10,12,12,2,2,4,2,5},{5,5,10,10,12,2,3,10},
   {3,4,8,7,8,8,8,0},{9,11,7,12,9,11,9,1},{13,13,2,4,4,4,0,1},{3,4,4,5,5,5,4,5},
   {1,1,6,8,7,7,7,8},{11,7,2,5,6,1,0,2},{13,13,4,8,7,7,7,4},{8,2,6,6,0,6,6,1}},
  {{255,255,255,255,255,255,255,255},{255,255,255,255,255,255,255,255},{255,255,255,255,255,255,255,255},{255,255,255,255,255,255,255,255},
   {255,255,255,255,255,255,255,255},{255,255,255,255,255,255,255,255},{255,255,255,255,255,255,255,255},{12,10,6,26,26,9,15,20},
   {255,255,255,255,255,255,255,255},{255,255,255,255,255,255,255,255},{255,255,255,255,255,255,255,255},{255,255,255,255,255,255,255,255},
   {255,255,255,255,255,1,1,2},{0,9,0,5,5,5,5,0},{5,0,5,11,11,11,11,11},{4,4,9,3,3,6,2,9},
   {28,28,14,18,25,18,25,13},{255,255,255,255,255,255,255,255},{3,11,17,10,17,10,17,21},{6,5,11,17,12,12,12,12},
   {1,1,4,9,2,3,3,3},{255,255,255,1,1,2,8,8},{11,12,12,2,6,26,6,27},{15,15,19,19,19,19,19,14},
   {27,27,13,13,13,13,13,19},{10,17,10,12,10,17,10,26},{255,255,1,8,8,8,9,1},{8,8,8,4,4,4,4,4},
   {9,6,3,0,0,0,0,5},{17,3,26,27,15,15,26,15},{26,26,27,28,28,28,28,18},{13,13,28,15,20,20,20,25}}};

typedef CUresult (*EncodeFn)(CUtensorMap*, CUtensorMapDataType, cuuint32_t, void*, const cuuint64_t*, const cuuint64_t*, const cuuint32_t*,
                             const cuuint32_t*, CUtensorMapInterleave, CUtensorMapSwizzle, CUtensorMapL2promotion, CUtensorMapFloatOOBfill);

void make_map2(EncodeFn enc, CUtensorMap* m, const void* ptr, int rows, int cols, int box_rows) {
  cuuint64_t dim[2] = {(cuuint64_t)cols, (cuuint64_t)rows}, str[1] = {(cuuint64_t)cols * 2};
  cuuint32_t box[2] = {64, (cuuint32_t)box_rows}, es[2] = {1, 1};
  enc(m, CU_TENSOR_MAP_DATA_TYPE_BFLOAT16, 2, const_cast<void*>(ptr), dim, str, box, es, CU_TENSOR_MAP_INTERLEAVE_NONE, CU_TENSOR_MAP_SWIZZLE_128B,
      CU_TENSOR_MAP_L2_PROMOTION_L2_128B, CU_TENSOR_MAP_FLOAT_OOB_FILL_NONE);
}
void make_map3(EncodeFn enc, CUtensorMap* m, const void* ptr, int rows) {
  cuuint64_t dim[3] = {64, (cuuint64_t)rows, 9}, str[2] = {DM * 2, 128};
  cuuint32_t box[3] = {64, 32, 3}, es[3] = {1, 1, 1};
  enc(m, CU_TENSOR_MAP_DATA_TYPE_BFLOAT16, 3, const_cast<void*>(ptr), dim, str, box, es, CU_TENSOR_MAP_INTERLEAVE_NONE, CU_TENSOR_MAP_SWIZZLE_128B,
      CU_TENSOR_MAP_L2_PROMOTION_L2_128B, CU_TENSOR_MAP_FLOAT_OOB_FILL_NONE);
}

void make_map_t(EncodeFn enc, CUtensorMap* m, void* ptr, int width, int cols) {
  cuuint64_t dim[3] = {TP / 2, 2, 864}, str[2] = {TP * 2, TP * 4};
  cuuint32_t box[3] = {(cuuint32_t)width, 2, (cuuint32_t)cols}, es[3] = {1, 1, 1};
  enc(m, CU_TENSOR_MAP_DATA_TYPE_UINT32, 3, ptr, dim, str, box, es, CU_TENSOR_MAP_INTERLEAVE_NONE, cols == 64 ? CU_TENSOR_MAP_SWIZZLE_128B : CU_TENSOR_MAP_SWIZZLE_NONE,
      CU_TENSOR_MAP_L2_PROMOTION_NONE, CU_TENSOR_MAP_FLOAT_OOB_FILL_NONE);
}

int g_mode = -1;

}

extern "C" void kernel_launch(void* const* d_in, const int* in_sizes, int n_in, void* d_out, int out_size) {
  static EncodeFn enc = nullptr;
  static void* t_ptr = nullptr;
  if (!enc) {
    void* fn = nullptr;
    cudaDriverEntryPointQueryResult st;
    cudaGetDriverEntryPoint("cuTensorMapEncodeTiled", &fn, cudaEnableDefault, &st);
    enc = (EncodeFn)fn;
    cudaGetSymbolAddress(&t_ptr, g_T);
    cudaFuncSetAttribute(fused_kernel, cudaFuncAttributeMaxDynamicSharedMemorySize, SMEM_BYTES);
    if (g_mode < 0) {
      cudaLaunchConfig_t cfg = {};
      cfg.gridDim = dim3(2 * NCL); cfg.blockDim = dim3(384); cfg.dynamicSmemBytes = SMEM_BYTES;
      cudaLaunchAttribute at; at.id = cudaLaunchAttributeClusterDimension;
      at.val.clusterDim.x = 2; at.val.clusterDim.y = 1; at.val.clusterDim.z = 1;
      cfg.attrs = &at; cfg.numAttrs = 1;
      int nc = 0;
      g_mode = (cudaOccupancyMaxActiveClusters(&nc, fused_kernel, &cfg) == cudaSuccess && nc >= NCL) ? 1 : 0;
      (void)cudaGetLastError();
    }
  }
  Params p;
  make_map2(enc, &p.map_a[0], d_in[4], SEQ, DC, 128);
  make_map2(enc, &p.map_a[1], d_in[0], SEQ, DM, 128);
  make_map2(enc, &p.map_w[0], d_in[6], DC, 4096, 64);
  make_map2(enc, &p.map_w[1], d_in[7], DC, 4096, 64);
  make_map2(enc, &p.map_w[2], d_in[5], DM, 4096, 64);
  make_map2(enc, &p.map_w[3], d_in[1], DM, 1728, 64);
  make_map3(enc, &p.map_o[0], d_in[8], 4096);
  make_map3(enc, &p.map_o[1], d_in[2], DM);
  make_map_t(enc, &p.map_t[0], t_ptr, 32, 9);
  make_map_t(enc, &p.map_t[1], t_ptr, 40, 9);
  make_map_t(enc, &p.map_t[2], t_ptr, 32, 64);
  p.x = (const __nv_bfloat16*)d_in[0];
  p.gate_w = (const __nv_bfloat16*)d_in[9];
  make_map2(enc, &p.map_out, d_out, SEQ, DM, 64);
  p.out = (__nv_bfloat16*)d_out;
  p.zero = 0;
  auto launch = [&](int phases) {
    p.s = k_sched;
    for (int i = 0; i < NCL; i++) {
      Rec& r = p.s.r[i];
      if (!(phases & 1)) r.n1 = 0;
      if (!(phases & 2)) r.n2 = 0;
      if (!(phases & (p.s.task[i][1] == 64 ? 4 : 32))) r.p3 = 255;
      if (!(phases & 8)) r.bg = 255;
      const int u1 = r.n1 ? 8 + r.n1 * (8 + (r.slab >> 3)) : 0;
      int u2 = 0;
      for (int k = 0; k < r.n2; k++) u2 += 4 * (r.item[k] & 7) + 4;
      r.u1 = (uint8_t)u1; r.u2 = (uint8_t)u2;
      r.rot = (uint8_t)(((u1 % 10 + 1) >> 1) % 5);
      r.x3 = (uint8_t)((r.rot + u2) % 5 & 3);
      r.phases = (uint8_t)phases;
    }
    if (!(phases & 16))
      for (int i = 0; i < 256; i++) { p.s.slot[i >> 3][i & 7] = (uint8_t)(i >> 3); p.s.prev[i >> 3][i & 7] = 255; }
    fused_kernel<<<2 * NCL, 384, SMEM_BYTES>>>(p);
  };
  if (g_mode == 1) launch(63);
  else { launch(1); launch(10); launch(4); launch(32); }
}
```

```cpp
#include <cuda_runtime.h>
#include <cuda_bf16.h>
#include <cuda.h>
#include <stdint.h>

namespace {

constexpr int SEQ = 2048, DM = 576, DC = 512, NH = 32;
constexpr int NCL = 66;
constexpr uint32_t DESC_HI = 0x40000040u;

constexpr int SM_RING = 0;
constexpr int SM_BUF = 163840;
constexpr int SM_BAR = 229376;
constexpr int B_P1E = 0, B_P2E = 10, B_P3E = 15, B_P2F = 24, B_SF = 32, B_ORD = 36, B_LAD = 40, B_DONE = 41, B_FIN = 48;
constexpr int B_P3F = 56, B_OUT = 61, B_P1F = 64, B_SE = 74, B_QF = 80, B_LA = 84, B_NUM = 88;
constexpr uint64_t B_CNT = 0x11118245000ull;
constexpr int SMEM_BYTES = SM_BAR + B_NUM * 8 + 1024;

constexpr int F_QKVA = 32;
constexpr int F_GATE = 64;
constexpr int F_DONE = 65;
constexpr int F_CTX = 96;
constexpr int F_OUT = 96 + 8 * 64;
constexpr int F_KV = F_OUT + 64;
constexpr int F_Q = F_KV + 256;
constexpr int F_RD = F_Q + 256;
constexpr int F_NUM = F_RD + 256;

struct Rec {
  uint8_t slab;
  uint8_t n1, n2;
  uint8_t p3;
  uint8_t bg;
  uint8_t item[11];
  uint8_t last[11];
  uint8_t tile[32];
  uint8_t u1, u2;
  uint8_t rot, x3;
  uint8_t phases;
};
struct Sched {
  Rec r[NCL];
  uint8_t task[NCL][4];
  uint8_t p3_order[24][64];
  uint8_t slot[32][8];
  uint8_t prev[32][8];
};

#define SCHED_DECL static const

struct Params {
  CUtensorMap map_a[2];
  CUtensorMap map_w[4];
  CUtensorMap map_o[2];
  CUtensorMap map_t[3];
  CUtensorMap map_out;
  const __nv_bfloat16* x;
  const __nv_bfloat16* gate_w;
  __nv_bfloat16* out;
  int zero;
  alignas(64) Sched s;
};

__device__ __align__(1024) uint8_t g_Q[NH * 32 * 16384];
__device__ __align__(1024) uint8_t g_KV[2 * NH * 16 * 32768];
__device__ __align__(1024) uint8_t g_oA[32 * 576 * 128];
constexpr int TP = SEQ + 16;
__device__ __align__(1024) uint32_t g_T[864 * TP];
__device__ float g_gate[SEQ];
__device__ int g_flags[F_NUM];
#define PL(i)

__device__ __forceinline__ void mbar_arrive(uint32_t b) { asm volatile("mbarrier.arrive.shared::cta.b64 _, [%0];" ::"r"(b) : "memory"); }
__device__ __forceinline__ void mbar_arrive_cl(uint32_t b, int cnt) {
  asm volatile("mbarrier.arrive.shared::cluster.b64 _, [%0], %1;" ::"r"(b), "r"(cnt) : "memory");
}
__device__ __forceinline__ void mbar_wait(uint32_t b, int par) {
  asm volatile(
      "{\n.reg .pred p;\n.reg .u32 c;\n"
      "mbarrier.try_wait.parity.shared::cta.b64 p, [%0], %1;\n@p bra DN;\nmov.u32 c, 0;\n"
      "LP:\nmbarrier.try_wait.parity.shared::cta.b64 p, [%0], %1;\n@p bra DN;\n"
      "add.u32 c, c, 1;\nsetp.lt.u32 p, c, 4000000;\n@p bra LP;\ntrap;\nDN:\n}" ::"r"(b), "r"(par) : "memory");
}
__device__ __forceinline__ uint32_t mapa(uint32_t a, uint32_t cta) {
  uint32_t r; asm("mapa.shared::cluster.u32 %0, %1, %2;" : "=r"(r) : "r"(a), "r"(cta)); return r;
}
#define ELECT(ins) "{\n.reg .pred e;\nelect.sync _|e, 0xffffffff;\n@e " ins "\n}"
__device__ __forceinline__ void mbar_expect(uint32_t b, int bytes) {
  asm volatile(ELECT("mbarrier.arrive.expect_tx.shared::cta.b64 _, [%0], %1;") ::"r"(b), "r"(bytes) : "memory");
}
__device__ __forceinline__ void mbar_arrive_one(uint32_t b) { asm volatile(ELECT("mbarrier.arrive.shared::cta.b64 _, [%0];") ::"r"(b) : "memory"); }
constexpr uint64_t L2_NORMAL = 0x1000000000000000ull, L2_FIRST = 0x12F0000000000000ull;
__device__ __forceinline__ void bulk_load(uint32_t dst, const void* src, int bytes, uint32_t bar, uint64_t pol = L2_NORMAL) {
  asm volatile(ELECT("cp.async.bulk.shared::cluster.global.mbarrier::complete_tx::bytes.L2::cache_hint [%0], [%1], %2, [%3], %4;") ::"r"(dst), "l"(src), "r"(bytes), "r"(bar), "l"(pol) : "memory");
}
__device__ __forceinline__ void bulk_load_mc(uint32_t dst, const void* src, int bytes, uint32_t bar, uint64_t pol = L2_NORMAL) {
  asm volatile(ELECT("cp.async.bulk.shared::cluster.global.mbarrier::complete_tx::bytes.multicast::cluster.L2::cache_hint [%0], [%1], %2, [%3], %4, %5;") ::"r"(dst), "l"(src), "r"(bytes), "r"(bar), "h"((uint16_t)3), "l"(pol) : "memory");
}
__device__ __forceinline__ void bulk_store(void* dst, uint32_t src, int bytes, uint64_t pol = L2_NORMAL) {
  asm volatile(ELECT("cp.async.bulk.global.shared::cta.bulk_group.L2::cache_hint [%0], [%1], %2, %3;") ::"l"(dst), "r"(src), "r"(bytes), "l"(pol) : "memory");
}
__device__ __forceinline__ void tma2d(uint32_t dst, const CUtensorMap* m, int c0, int c1, uint32_t bar, uint64_t pol = L2_NORMAL) {
  asm volatile(ELECT("cp.async.bulk.tensor.2d.shared::cluster.global.mbarrier::complete_tx::bytes.L2::cache_hint [%0], [%1, {%3, %4}], [%2], %5;") ::"r"(dst), "l"(m), "r"(bar), "r"(c0), "r"(c1), "l"(pol) : "memory");
}
__device__ __forceinline__ void tma2d_mc(uint32_t dst, const CUtensorMap* m, int c0, int c1, uint32_t bar, uint64_t pol = L2_NORMAL) {
  asm volatile(ELECT("cp.async.bulk.tensor.2d.shared::cluster.global.mbarrier::complete_tx::bytes.multicast::cluster.L2::cache_hint [%0], [%1, {%3, %4}], [%2], %5, %6;") ::"r"(dst), "l"(m), "r"(bar), "r"(c0), "r"(c1), "h"((uint16_t)3), "l"(pol) : "memory");
}
__device__ __forceinline__ void tma3d(uint32_t dst, const CUtensorMap* m, int c0, int c1, int c2, uint32_t bar, uint64_t pol = L2_NORMAL) {
  asm volatile(ELECT("cp.async.bulk.tensor.3d.shared::cluster.global.mbarrier::complete_tx::bytes.L2::cache_hint [%0], [%1, {%3, %4, %5}], [%2], %6;") ::"r"(dst), "l"(m), "r"(bar), "r"(c0), "r"(c1), "r"(c2), "l"(pol) : "memory");
}
__device__ __forceinline__ void tma3d_mc(uint32_t dst, const CUtensorMap* m, int c0, int c1, int c2, uint32_t bar, uint64_t pol = L2_NORMAL) {
  asm volatile(ELECT("cp.async.bulk.tensor.3d.shared::cluster.global.mbarrier::complete_tx::bytes.multicast::cluster.L2::cache_hint [%0], [%1, {%3, %4, %5}], [%2], %6, %7;") ::"r"(dst), "l"(m), "r"(bar), "r"(c0), "r"(c1), "r"(c2), "h"((uint16_t)3), "l"(pol) : "memory");
}
__device__ __forceinline__ void tma2d_add(const CUtensorMap* m, uint32_t src, int c0, int c1) {
  asm volatile(ELECT("cp.reduce.async.bulk.tensor.2d.global.shared::cta.add.bulk_group [%0, {%2, %3}], [%1];") ::"l"(m), "r"(src), "r"(c0), "r"(c1) : "memory");
}
__device__ __forceinline__ void tma3d_store(const CUtensorMap* m, uint32_t src, int c0, int c1, int c2, uint64_t pol = L2_NORMAL) {
  asm volatile(ELECT("cp.async.bulk.tensor.3d.global.shared::cta.bulk_group.L2::cache_hint [%0, {%2, %3, %4}], [%1], %5;") ::"l"(m), "r"(src), "r"(c0), "r"(c1), "r"(c2), "l"(pol) : "memory");
}
__device__ __forceinline__ void tma2d_prefetch(const CUtensorMap* m, int c0, int c1, uint64_t pol = L2_NORMAL) {
  asm volatile(ELECT("cp.async.bulk.prefetch.tensor.2d.L2.global.L2::cache_hint [%0, {%1, %2}], %3;") ::"l"(m), "r"(c0), "r"(c1), "l"(pol) : "memory");
}
#define LAG 3
#define HINT 62
#define POL(bit) ((HINT >> (bit)) & 1 ? L2_FIRST : L2_NORMAL)
#define BULK_COMMIT() asm volatile("cp.async.bulk.commit_group;" ::: "memory")
#define BULK_WAIT(n) asm volatile("cp.async.bulk.wait_group %0;" ::"n"(n) : "memory")
#define BULK_WAIT_READ(n) asm volatile("cp.async.bulk.wait_group.read %0;" ::"n"(n) : "memory")
#define FENCE_ASYNC_SMEM() asm volatile("fence.proxy.async.shared::cta;" ::: "memory")
#define FENCE_ASYNC_ALL() asm volatile("fence.proxy.async;" ::: "memory")
#define WG_FENCE() asm volatile("wgmma.fence.sync.aligned;" ::: "memory")
#define WG_COMMIT() asm volatile("wgmma.commit_group.sync.aligned;" ::: "memory")
#define WG_WAIT(n) asm volatile("wgmma.wait_group.sync.aligned %0;" ::"n"(n) : "memory")
__device__ __forceinline__ void bar_sync(int id, int n) { asm volatile("bar.sync %0, %1;" ::"r"(id), "r"(n) : "memory"); }
__device__ __forceinline__ void bar_arrive(int id, int n) { asm volatile("bar.arrive %0, %1;" ::"r"(id), "r"(n) : "memory"); }
__device__ __forceinline__ void cluster_sync() {
  asm volatile("barrier.cluster.arrive.relaxed;\nbarrier.cluster.wait.acquire;" ::: "memory");
}
template <int N> __device__ __forceinline__ void pin(float (&r)[N]) {
#pragma unroll
  for (int i = 0; i < N; i++) asm volatile("" : "+f"(r[i])::"memory");
}
template <int N> __device__ __forceinline__ void pin(uint32_t (&r)[N]) {
#pragma unroll
  for (int i = 0; i < N; i++) asm volatile("" : "+r"(r[i])::"memory");
}
__device__ __forceinline__ uint32_t pack_bf16(float lo, float hi) {
  uint32_t r; asm("cvt.rn.bf16x2.f32 %0, %1, %2;" : "=r"(r) : "f"(hi), "f"(lo)); return r;
}
__device__ __forceinline__ float ex2(float x) { float r; asm("ex2.approx.ftz.f32 %0, %1;" : "=f"(r) : "f"(x)); return r; }
__device__ __forceinline__ void ldsm4(uint32_t a, uint32_t& r0, uint32_t& r1, uint32_t& r2, uint32_t& r3) {
  asm volatile("ldmatrix.sync.aligned.m8n8.x4.shared.b16 {%0,%1,%2,%3}, [%4];" : "=r"(r0), "=r"(r1), "=r"(r2), "=r"(r3) : "r"(a) : "memory");
}
__device__ __forceinline__ void stsm4(uint32_t a, uint32_t r0, uint32_t r1, uint32_t r2, uint32_t r3) {
  asm volatile("stmatrix.sync.aligned.m8n8.x4.shared.b16 [%0], {%1,%2,%3,%4};" ::"r"(a), "r"(r0), "r"(r1), "r"(r2), "r"(r3) : "memory");
}
__device__ __forceinline__ void flag_add(int idx, int v = 1) {
  asm volatile(ELECT("red.release.gpu.global.add.s32 [%0], %1;") ::"l"(g_flags + idx), "r"(v) : "memory");
}
__device__ __forceinline__ void flag_add_rx(int idx) {
  asm volatile(ELECT("red.relaxed.gpu.global.add.s32 [%0], 1;") ::"l"(g_flags + idx) : "memory");
}
template <bool ACQ, int NS = 32> __device__ __forceinline__ void flag_wait(int idx, int target) {
  int n = 0;
  while (true) {
    int v;
    if (ACQ) asm volatile("ld.acquire.gpu.global.s32 %0, [%1];" : "=r"(v) : "l"(g_flags + idx) : "memory");
    else asm volatile("ld.relaxed.gpu.global.s32 %0, [%1];" : "=r"(v) : "l"(g_flags + idx) : "memory");
    if (__all_sync(0xffffffffu, v >= target)) break;
    if (++n > 20000000) __trap();
    __nanosleep(NS);
  }
}
__device__ __forceinline__ void mask_wait(uint32_t& ready, int bit, int idx, int target) {
  for (int n = 0; !((ready >> bit) & 1); n++) {
    int v;
    if (n) { __nanosleep(32); if (n > 20000000) __trap(); }
    asm volatile("ld.relaxed.gpu.global.s32 %0, [%1];" : "=r"(v) : "l"(g_flags + idx) : "memory");
    ready = __ballot_sync(0xffffffffu, v >= target);
  }
}
__device__ __forceinline__ uint32_t desc_lo(uint32_t addr, uint32_t lbo) { return ((addr & 0x3FFFFu) >> 4) | ((lbo >> 4) << 16); }
#define PROF(role, i)
#define PROFX(cond, i)
#define PROFB(i)
#define PROFG(i)

template <int TB, int TA = 0> __device__ __forceinline__ void wgmma_ss64(float (&d)[32], uint32_t alo, uint32_t blo, int sd) {
  asm volatile("{\n.reg .pred p;\n.reg .b64 da, db;\n"
    "setp.ne.b32 p, %34, 0;\nmov.b64 da, {%32, %36};\nmov.b64 db, {%33, %36};\n"
    "wgmma.mma_async.sync.aligned.m64n64k16.f32.bf16.bf16 "
    "{%0,%1,%2,%3,%4,%5,%6,%7,%8,%9,%10,%11,%12,%13,%14,%15,%16,%17,%18,%19,%20,%21,%22,%23,"
    "%24,%25,%26,%27,%28,%29,%30,%31}, "
    "da, db, p, 1, 1, %37, %35;\n}\n"
    : "+f"(d[0]),"+f"(d[1]),"+f"(d[2]),"+f"(d[3]),"+f"(d[4]),"+f"(d[5]),"+f"(d[6]),"+f"(d[7]),"+f"(d[8]),"+f"(d[9]),"+f"(d[10]),"+f"(d[11]),
      "+f"(d[12]),"+f"(d[13]),"+f"(d[14]),"+f"(d[15]),"+f"(d[16]),"+f"(d[17]),"+f"(d[18]),"+f"(d[19]),"+f"(d[20]),"+f"(d[21]),"+f"(d[22]),"+f"(d[23]),
      "+f"(d[24]),"+f"(d[25]),"+f"(d[26]),"+f"(d[27]),"+f"(d[28]),"+f"(d[29]),"+f"(d[30]),"+f"(d[31])
    : "r"(alo), "r"(blo), "r"(sd), "n"(TB), "r"(DESC_HI), "n"(TA));
}
template <int TB, int TA = 0> __device__ __forceinline__ void wgmma_ss128(float (&d)[64], uint32_t alo, uint32_t blo, int sd) {
  asm volatile("{\n.reg .pred p;\n.reg .b64 da, db;\n"
    "setp.ne.b32 p, %66, 0;\nmov.b64 da, {%64, %68};\nmov.b64 db, {%65, %68};\n"
    "wgmma.mma_async.sync.aligned.m64n128k16.f32.bf16.bf16 "
    "{%0,%1,%2,%3,%4,%5,%6,%7,%8,%9,%10,%11,%12,%13,%14,%15,%16,%17,%18,%19,%20,%21,%22,%23,"
    "%24,%25,%26,%27,%28,%29,%30,%31,%32,%33,%34,%35,%36,%37,%38,%39,%40,%41,%42,%43,%44,%45,%46,%47,"
    "%48,%49,%50,%51,%52,%53,%54,%55,%56,%57,%58,%59,%60,%61,%62,%63}, "
    "da, db, p, 1, 1, %69, %67;\n}\n"
    : "+f"(d[0]),"+f"(d[1]),"+f"(d[2]),"+f"(d[3]),"+f"(d[4]),"+f"(d[5]),"+f"(d[6]),"+f"(d[7]),"+f"(d[8]),"+f"(d[9]),"+f"(d[10]),"+f"(d[11]),
      "+f"(d[12]),"+f"(d[13]),"+f"(d[14]),"+f"(d[15]),"+f"(d[16]),"+f"(d[17]),"+f"(d[18]),"+f"(d[19]),"+f"(d[20]),"+f"(d[21]),"+f"(d[22]),"+f"(d[23]),
      "+f"(d[24]),"+f"(d[25]),"+f"(d[26]),"+f"(d[27]),"+f"(d[28]),"+f"(d[29]),"+f"(d[30]),"+f"(d[31]),"+f"(d[32]),"+f"(d[33]),"+f"(d[34]),"+f"(d[35]),
      "+f"(d[36]),"+f"(d[37]),"+f"(d[38]),"+f"(d[39]),"+f"(d[40]),"+f"(d[41]),"+f"(d[42]),"+f"(d[43]),"+f"(d[44]),"+f"(d[45]),"+f"(d[46]),"+f"(d[47]),
      "+f"(d[48]),"+f"(d[49]),"+f"(d[50]),"+f"(d[51]),"+f"(d[52]),"+f"(d[53]),"+f"(d[54]),"+f"(d[55]),"+f"(d[56]),"+f"(d[57]),"+f"(d[58]),"+f"(d[59]),
      "+f"(d[60]),"+f"(d[61]),"+f"(d[62]),"+f"(d[63])
    : "r"(alo), "r"(blo), "r"(sd), "n"(TB), "r"(DESC_HI), "n"(TA));
}
template <int TB> __device__ __forceinline__ void wgmma_rs128(float (&d)[64], uint32_t a0, uint32_t a1, uint32_t a2, uint32_t a3, uint32_t blo, int sd) {
  asm volatile("{\n.reg .pred p;\n.reg .b64 db;\n"
    "setp.ne.b32 p, %69, 0;\nmov.b64 db, {%68, %71};\n"
    "wgmma.mma_async.sync.aligned.m64n128k16.f32.bf16.bf16 "
    "{%0,%1,%2,%3,%4,%5,%6,%7,%8,%9,%10,%11,%12,%13,%14,%15,%16,%17,%18,%19,%20,%21,%22,%23,"
    "%24,%25,%26,%27,%28,%29,%30,%31,%32,%33,%34,%35,%36,%37,%38,%39,%40,%41,%42,%43,%44,%45,%46,%47,"
    "%48,%49,%50,%51,%52,%53,%54,%55,%56,%57,%58,%59,%60,%61,%62,%63}, "
    "{%64,%65,%66,%67}, db, p, 1, 1, %70;\n}\n"
    : "+f"(d[0]),"+f"(d[1]),"+f"(d[2]),"+f"(d[3]),"+f"(d[4]),"+f"(d[5]),"+f"(d[6]),"+f"(d[7]),"+f"(d[8]),"+f"(d[9]),"+f"(d[10]),"+f"(d[11]),
      "+f"(d[12]),"+f"(d[13]),"+f"(d[14]),"+f"(d[15]),"+f"(d[16]),"+f"(d[17]),"+f"(d[18]),"+f"(d[19]),"+f"(d[20]),"+f"(d[21]),"+f"(d[22]),"+f"(d[23]),
      "+f"(d[24]),"+f"(d[25]),"+f"(d[26]),"+f"(d[27]),"+f"(d[28]),"+f"(d[29]),"+f"(d[30]),"+f"(d[31]),"+f"(d[32]),"+f"(d[33]),"+f"(d[34]),"+f"(d[35]),
      "+f"(d[36]),"+f"(d[37]),"+f"(d[38]),"+f"(d[39]),"+f"(d[40]),"+f"(d[41]),"+f"(d[42]),"+f"(d[43]),"+f"(d[44]),"+f"(d[45]),"+f"(d[46]),"+f"(d[47]),
      "+f"(d[48]),"+f"(d[49]),"+f"(d[50]),"+f"(d[51]),"+f"(d[52]),"+f"(d[53]),"+f"(d[54]),"+f"(d[55]),"+f"(d[56]),"+f"(d[57]),"+f"(d[58]),"+f"(d[59]),
      "+f"(d[60]),"+f"(d[61]),"+f"(d[62]),"+f"(d[63])
    : "r"(a0), "r"(a1), "r"(a2), "r"(a3), "r"(blo), "r"(sd), "n"(TB), "r"(DESC_HI));
}
template <int TB, int TA = 0> __device__ __forceinline__ void wgmma_ss192(float (&d)[96], uint32_t alo, uint32_t blo, int sd) {
  asm volatile("{\n.reg .pred p;\n.reg .b64 da, db;\n"
    "setp.ne.b32 p, %98, 0;\nmov.b64 da, {%96, %100};\nmov.b64 db, {%97, %100};\n"
    "wgmma.mma_async.sync.aligned.m64n192k16.f32.bf16.bf16 "
    "{%0,%1,%2,%3,%4,%5,%6,%7,%8,%9,%10,%11,%12,%13,%14,%15,%16,%17,%18,%19,%20,%21,%22,%23,"
    "%24,%25,%26,%27,%28,%29,%30,%31,%32,%33,%34,%35,%36,%37,%38,%39,%40,%41,%42,%43,%44,%45,%46,%47,"
    "%48,%49,%50,%51,%52,%53,%54,%55,%56,%57,%58,%59,%60,%61,%62,%63,%64,%65,%66,%67,%68,%69,%70,%71,"
    "%72,%73,%74,%75,%76,%77,%78,%79,%80,%81,%82,%83,%84,%85,%86,%87,%88,%89,%90,%91,%92,%93,%94,%95}, "
    "da, db, p, 1, 1, %101, %99;\n}\n"
    : "+f"(d[0]),"+f"(d[1]),"+f"(d[2]),"+f"(d[3]),"+f"(d[4]),"+f"(d[5]),"+f"(d[6]),"+f"(d[7]),"+f"(d[8]),"+f"(d[9]),"+f"(d[10]),"+f"(d[11]),
      "+f"(d[12]),"+f"(d[13]),"+f"(d[14]),"+f"(d[15]),"+f"(d[16]),"+f"(d[17]),"+f"(d[18]),"+f"(d[19]),"+f"(d[20]),"+f"(d[21]),"+f"(d[22]),"+f"(d[23]),
      "+f"(d[24]),"+f"(d[25]),"+f"(d[26]),"+f"(d[27]),"+f"(d[28]),"+f"(d[29]),"+f"(d[30]),"+f"(d[31]),"+f"(d[32]),"+f"(d[33]),"+f"(d[34]),"+f"(d[35]),
      "+f"(d[36]),"+f"(d[37]),"+f"(d[38]),"+f"(d[39]),"+f"(d[40]),"+f"(d[41]),"+f"(d[42]),"+f"(d[43]),"+f"(d[44]),"+f"(d[45]),"+f"(d[46]),"+f"(d[47]),
      "+f"(d[48]),"+f"(d[49]),"+f"(d[50]),"+f"(d[51]),"+f"(d[52]),"+f"(d[53]),"+f"(d[54]),"+f"(d[55]),"+f"(d[56]),"+f"(d[57]),"+f"(d[58]),"+f"(d[59]),
      "+f"(d[60]),"+f"(d[61]),"+f"(d[62]),"+f"(d[63]),"+f"(d[64]),"+f"(d[65]),"+f"(d[66]),"+f"(d[67]),"+f"(d[68]),"+f"(d[69]),"+f"(d[70]),"+f"(d[71]),
      "+f"(d[72]),"+f"(d[73]),"+f"(d[74]),"+f"(d[75]),"+f"(d[76]),"+f"(d[77]),"+f"(d[78]),"+f"(d[79]),"+f"(d[80]),"+f"(d[81]),"+f"(d[82]),"+f"(d[83]),
      "+f"(d[84]),"+f"(d[85]),"+f"(d[86]),"+f"(d[87]),"+f"(d[88]),"+f"(d[89]),"+f"(d[90]),"+f"(d[91]),"+f"(d[92]),"+f"(d[93]),"+f"(d[94]),"+f"(d[95])
    : "r"(alo), "r"(blo), "r"(sd), "n"(TB), "r"(DESC_HI), "n"(TA));
}

struct Ctx {
  uint32_t sm;
  uint32_t bar;
  uint32_t rbar;
  int cl, rank, wg, warp, lane, phases;
};
__device__ __forceinline__ void release(const Ctx& c, int b, int cnt = 1) {
  if (c.lane < 2) mbar_arrive_cl(c.rbar + b * 8, cnt);
}
#define HK 5
#define NPRO 6
#define ZLEAD 14
#define PFM 7
#define PF1 1
constexpr float SM_SCALE = 0.08838834764831845f * 1.4426950408889634f;
constexpr float SM_HI = 1.8446744e19f, SM_LO = 5.4210109e-20f;
constexpr int ORDER = 1;

__device__ __forceinline__ void stage_tile(const float (&a)[64], uint32_t buf, const Ctx& c, float s0, float s1) {
  const int row = (c.lane & 7) + ((c.lane >> 3) & 1) * 8;
  const uint32_t base = buf + (c.warp * 16 + row) * 128 + (((c.lane >> 4) ^ (row & 7)) << 4);
#pragma unroll
  for (int i = 0; i < 8; i++)
    stsm4((base ^ ((i & 3) << 5)) + (i >> 2) * 8192, pack_bf16(a[8 * i] * s0, a[8 * i + 1] * s0), pack_bf16(a[8 * i + 2] * s1, a[8 * i + 3] * s1),
          pack_bf16(a[8 * i + 4] * s0, a[8 * i + 5] * s0), pack_bf16(a[8 * i + 6] * s1, a[8 * i + 7] * s1));
}

__device__ __forceinline__ void p1_epilogue(const Params& p, const Ctx& c, const float (&acc)[64], int t, int type) {
  const int tile = p.s.r[c.cl].tile[t] & 63, b = c.wg * 2 + 1;
  mbar_wait(c.bar + (B_SE + b) * 8, (t & 1) ^ 1);
  if (type && tile >= 32) {
    const int r = 2 * (c.lane & 3) + ((c.lane >> 2) & 1);
    const uint32_t dst = c.sm + SM_BUF + b * 16384 + r * 128 + (((c.warp * 2) ^ r) << 4) + (c.lane >> 3) * 4;
#pragma unroll
    for (int i = 0; i < 16; i++) {
      asm volatile("st.shared.u32 [%0], %1;" ::"r"(dst + i * 1024), "r"(pack_bf16(acc[4 * i], acc[4 * i + 1])) : "memory");
      asm volatile("st.shared.u32 [%0], %1;" ::"r"((dst ^ 16) + i * 1024), "r"(pack_bf16(acc[4 * i + 2], acc[4 * i + 3])) : "memory");
    }
  } else {
    if (type) stage_tile(acc, c.sm + SM_BUF + b * 16384, c, SM_SCALE, SM_SCALE);
    else stage_tile(acc, c.sm + SM_BUF + b * 16384, c, 1.f, 1.f);
  }
  FENCE_ASYNC_SMEM();
  __syncwarp();
  if (c.lane == 0) mbar_arrive(c.bar + (B_SF + b) * 8);
}

__device__ __forceinline__ void p1_consumer(const Params& p, const Ctx& c) {
  const int n = p.s.r[c.cl].n1;
  const int type = p.s.r[c.cl].slab >> 3;
  const uint32_t bdesc = desc_lo(c.sm + SM_RING, 8192), adesc = desc_lo(c.sm + SM_BUF + 32768 + c.wg * 8192, 16);
  uint32_t A[128];
  float acc[64] = {};
  int slot = 0, par = 0;
  auto next = [&]() { if (++slot == 10) { slot = 0; par ^= 1; } };
  {
    const int row = (c.lane & 7) + ((c.lane >> 3) & 1) * 8;
    const uint32_t base = c.sm + SM_RING + (c.wg * 64 + c.warp * 16 + row) * 128 + (((c.lane >> 4) ^ (row & 7)) << 4);
    if (c.wg == 1) bar_sync(ORDER + 1, 256);
    int pa = -1, pb = -1;
    if (type) {
      mbar_wait(c.bar + B_P1F * 8, 0);
      WG_FENCE();
#pragma unroll
      for (int kk = 0; kk < 4; kk++) wgmma_ss128<1>(acc, adesc + kk * 2, bdesc + kk * 128, kk != 0);
      WG_COMMIT();
      pb = 0; slot = 1;
    }
#pragma unroll
    for (int kb = 0; kb < 8; kb++) {
      const int sa = slot;
      mbar_wait(c.bar + (B_P1F + slot) * 8, par);
      if (kb == 0) PROF(c.wg, 5);
      next();
      mbar_wait(c.bar + (B_P1F + slot) * 8, par);
      PROF(c.wg, 6 + 2 * kb);
      WG_FENCE();
#pragma unroll
      for (int kk = 0; kk < 4; kk++)
        wgmma_ss128<1>(acc, desc_lo(c.sm + SM_RING + c.wg * 8192, 16) + sa * 1024 + kk * 2, bdesc + slot * 1024 + kk * 128, (kb | kk) != 0 ? 1 : type);
      WG_COMMIT();
      if (kb == 1 && c.wg == 0) bar_arrive(ORDER + 1, 256);
#pragma unroll
      for (int kk = 0; kk < 4; kk++) ldsm4((base ^ (kk << 5)) + sa * 16384, A[kb * 16 + kk * 4], A[kb * 16 + kk * 4 + 1], A[kb * 16 + kk * 4 + 2], A[kb * 16 + kk * 4 + 3]);
      WG_WAIT(1);
      if (kb > 0) release(c, B_P1E + pa);
      if (kb > 0 || pb >= 0) release(c, B_P1E + pb);
      pa = sa; pb = slot;
      next();
    }
    WG_WAIT(0);
    __syncwarp();
    release(c, B_P1E + pa);
    release(c, B_P1E + pb);
    pin(acc);
    PROF(c.wg, 1);
    p1_epilogue(p, c, acc, 0, type);
    PROF(c.wg, 2);
  }
  for (int t = 1; t < n; t++) {
    bar_sync(ORDER + c.wg, 256);
    int prev1 = -1, prev2 = -1;
    if (type) {
      mbar_wait(c.bar + (B_P1F + slot) * 8, par);
      WG_FENCE();
#pragma unroll
      for (int kk = 0; kk < 4; kk++) wgmma_ss128<1>(acc, adesc + kk * 2, bdesc + slot * 1024 + kk * 128, kk != 0);
      WG_COMMIT();
      prev1 = slot;
      next();
    }
#pragma unroll
    for (int kb = 0; kb < 8; kb++) {
      mbar_wait(c.bar + (B_P1F + slot) * 8, par);
      WG_FENCE();
      const uint32_t d = bdesc + slot * 1024;
#pragma unroll
      for (int kk = 0; kk < 4; kk++)
        wgmma_rs128<1>(acc, A[kb * 16 + kk * 4], A[kb * 16 + kk * 4 + 1], A[kb * 16 + kk * 4 + 2], A[kb * 16 + kk * 4 + 3], d + kk * 128, (kb | kk) != 0 ? 1 : type);
      WG_COMMIT();
      if (kb == HK) {
        if (t + 1 < n || c.wg == 0) bar_arrive(ORDER + (c.wg ^ 1), 256);
      }
      if (kb > 0) { WG_WAIT(2); if (kb > 1 || prev2 >= 0) release(c, B_P1E + prev2); }
      prev2 = prev1; prev1 = slot;
      next();
    }
    WG_WAIT(1);
    release(c, B_P1E + prev2);
    WG_WAIT(0);
    pin(acc);
    release(c, B_P1E + prev1);
    p1_epilogue(p, c, acc, t, type);
    PROF(c.wg, 3);
  }
}

__device__ __forceinline__ void p1_producer(const Params& p, const Ctx& c) {
  const int n = p.s.r[c.cl].n1;
  const int type = p.s.r[c.cl].slab >> 3, grp = p.s.r[c.cl].slab & 7;
  int slot = NPRO % 10, par = NPRO < 10;
#pragma unroll 1
  for (int t = 0; t < n; t++) {
    const int tile = p.s.r[c.cl].tile[t] & 63;
    const CUtensorMap* m = &p.map_w[type * 2 + (tile >> 5)];
    const int n0 = (tile & 31) * 128 + c.rank * 64;
    const int ptile = p.s.r[c.cl].tile[t + PF1 < n ? t + PF1 : t];
    const CUtensorMap* pm = &p.map_w[type * 2 + ((ptile >> 5) & 1)];
    if (t == 7 && (c.phases & 16)) flag_wait<true>(F_GATE, 256);
#pragma unroll 1
    for (int kb = t ? -type : (NPRO - type) >> 1; kb < 8; kb++) {
      if (t == 0 && 2 * kb + type >= NPRO) {
        mbar_wait(c.bar + (B_P1E + slot) * 8, par);
        mbar_expect(c.bar + (B_P1F + slot) * 8, 16384);
        tma2d(c.sm + SM_RING + slot * 16384, &p.map_a[type], kb * 64, grp * 256 + c.rank * 128, c.bar + (B_P1F + slot) * 8);
        if (++slot == 10) { slot = 0; par ^= 1; }
      }
      mbar_wait(c.bar + (B_P1E + slot) * 8, par);
      mbar_expect(c.bar + (B_P1F + slot) * 8, 16384);
      tma2d_mc(c.sm + SM_RING + slot * 16384 + c.rank * 8192, m, n0, kb < 0 ? 512 : kb * 64, c.bar + (B_P1F + slot) * 8);
      if (t == 0 && kb == 1) PROF(2, 61);
      if (t == 0 && kb == 3) PROF(2, 62);
      if (t + PF1 < n && t > 0 && ((ptile & 64) || ((ptile & 128) && ((kb ^ grp) & PFM) == 0))) tma2d_prefetch(pm, (ptile & 31) * 128 + c.rank * 64, kb < 0 ? 512 : kb * 64);
      if (++slot == 10) { slot = 0; par ^= 1; }
    }
  }
}

__device__ __forceinline__ void p1_storer(const Params& p, const Ctx& c) {
  const int n = p.s.r[c.cl].n1;
  const int type = p.s.r[c.cl].slab >> 3, grp = p.s.r[c.cl].slab & 7;
  for (int i = 0; i < 2 * n; i++) {
    const int t = i >> 1, w = i & 1, b = w * 2 + 1;
    const int tile = p.s.r[c.cl].tile[t] & 63;
    mbar_wait(c.bar + (B_SF + b) * 8, t & 1);
    const uint32_t src = c.sm + SM_BUF + b * 16384;
    int f = (type ? F_Q : F_KV) + (tile & 31) * 8 + grp;
    if (type == 0) {
      const int prev = p.s.prev[tile & 31][grp];
      if (prev != 255 && w == 0) {
        if (grp >= 2) flag_wait<false>(F_RD + prev * 8 + grp, 8 - grp);
        else flag_wait<false>(F_CTX + max(c.lane & 7, grp) * 64 + prev, 4);
      }
      uint8_t* dst = g_KV + (size_t)(((tile & 32) + p.s.slot[tile & 31][grp]) * 16 + grp * 2 + c.rank) * 32768 + w * 8192;
      bulk_store(dst, src, 8192);
      bulk_store(dst + 16384, src + 8192, 8192);
    } else if (tile < 32) {
      bulk_store(g_Q + (size_t)(tile * 32 + grp * 4 + c.rank * 2 + w) * 16384, src, 16384);
    } else {
      tma3d_store(&p.map_t[2], src, 8 + (grp * 4 + c.rank * 2 + w) * 32, 0, (tile - 32) * 64);
      f = F_QKVA + grp * 4 + ((0xE4390900u >> (2 * (tile - 30))) & 3);
    }
    BULK_COMMIT();
    BULK_WAIT(0);
    mbar_arrive_one(c.bar + (B_SE + b) * 8);
    if (w) flag_add(f, 2);
  }
}

__device__ __forceinline__ int p2_buf(int w, int i) { return w * 2 + (i & 1); }
__device__ __forceinline__ int p2_blk(int rank, int w, int i) { return ((i ^ w) & 1) == 0 ? 3 - rank : rank; }

template <int N>
__device__ __forceinline__ void row_max(const float (&s)[N], float& m0, float& m1) {
  float a0 = fmaxf(s[0], s[1]), a1 = fmaxf(s[2], s[3]);
#pragma unroll
  for (int i = 1; i < N / 4; i++) {
    m0 = fmaxf(m0, s[4 * i]); a0 = fmaxf(a0, s[4 * i + 1]);
    m1 = fmaxf(m1, s[4 * i + 2]); a1 = fmaxf(a1, s[4 * i + 3]);
  }
  m0 = fmaxf(m0, a0); m1 = fmaxf(m1, a1);
  m0 = fmaxf(m0, __shfl_xor_sync(0xffffffffu, m0, 1));
  m1 = fmaxf(m1, __shfl_xor_sync(0xffffffffu, m1, 1));
  m0 = fmaxf(m0, __shfl_xor_sync(0xffffffffu, m0, 2));
  m1 = fmaxf(m1, __shfl_xor_sync(0xffffffffu, m1, 2));
}
template <bool SUB, int N>
__device__ __forceinline__ void row_exp(const float (&s)[N], uint32_t (&P)[32], float m0, float m1, float& t0, float& t1) {
  float u0 = 0.f, u1 = 0.f;
  t0 = t1 = 0.f;
#pragma unroll
  for (int i = 0; i < N / 4; i++) {
    const float e0 = ex2(SUB ? s[4 * i] - m0 : s[4 * i]), e1 = ex2(SUB ? s[4 * i + 1] - m0 : s[4 * i + 1]);
    const float e2 = ex2(SUB ? s[4 * i + 2] - m1 : s[4 * i + 2]), e3 = ex2(SUB ? s[4 * i + 3] - m1 : s[4 * i + 3]);
    if (i == 0) { t0 = e0; u0 = e1; t1 = e2; u1 = e3; }
    else { t0 += e0; u0 += e1; t1 += e2; u1 += e3; }
    P[2 * i] = pack_bf16(e0, e1);
    P[2 * i + 1] = pack_bf16(e2, e3);
  }
#pragma unroll
  for (int i = N / 2; i < 32; i++) P[i] = 0;
  pin(P);
  t0 += u0; t1 += u1;
}
template <int N>
__device__ __forceinline__ void causal_mask(float (&s)[N], int thr) {
#pragma unroll
  for (int i = 0; i < 8; i++) {
    if (8 * i > thr) s[N - 32 + 4 * i] = -INFINITY;
    if (8 * i + 1 > thr) s[N - 32 + 4 * i + 1] = -INFINITY;
    if (8 * i - 8 > thr) s[N - 32 + 4 * i + 2] = -INFINITY;
    if (8 * i - 7 > thr) s[N - 32 + 4 * i + 3] = -INFINITY;
  }
}
__device__ __forceinline__ void issue_qk(float (&s)[32], uint32_t qd, uint32_t kd) {
  WG_FENCE();
#pragma unroll
  for (int kk = 0; kk < 8; kk++) wgmma_ss64<0>(s, qd + (kk >> 2) * 512 + (kk & 3) * 2, kd + (kk >> 2) * 1024 + (kk & 3) * 2, kk != 0);
  WG_COMMIT();
}
__device__ __forceinline__ void issue_qk(float (&s)[64], uint32_t qd, uint32_t kd) {
  WG_FENCE();
#pragma unroll
  for (int kk = 0; kk < 8; kk++) wgmma_ss128<0>(s, qd + (kk >> 2) * 512 + (kk & 3) * 2, kd + (kk >> 2) * 1024 + (kk & 3) * 2, kk != 0);
  WG_COMMIT();
}
template <int NK>
__device__ __forceinline__ void issue_pv(float (&o)[64], const uint32_t (&P)[32], uint32_t vd, int acc) {
  WG_FENCE();
#pragma unroll
  for (int kk = 0; kk < NK; kk++) wgmma_rs128<1>(o, P[4 * kk], P[4 * kk + 1], P[4 * kk + 2], P[4 * kk + 3], vd + kk * 128, kk != 0 ? 1 : acc);
  WG_COMMIT();
}
__device__ __forceinline__ void stage_done(const Ctx& c, int b) {
  FENCE_ASYNC_SMEM();
  __syncwarp();
  if (c.lane == 0) mbar_arrive(c.bar + (B_SF + b) * 8);
}
__device__ __forceinline__ void p2_epilogue(const float (&o)[64], float s0, float s1, const Ctx& c, int b) {
  stage_tile(o, c.sm + SM_BUF + b * 16384, c, s0, s1);
  stage_done(c, b);
}

struct P2State {
  float m0, m1, l0, l1;
  bool shift;
  float e0, e1;
  int ks;
  int wi, ai;
  uint32_t wb, ab;
  uint32_t qd;
};
#define PROFZ()
__device__ __forceinline__ int wrap5(int q) { return q >= 5 ? q - 5 : q; }
__device__ __forceinline__ void turn_wait(uint32_t ring, int i) { mbar_wait(ring + (i & 3) * 8, (i >> 2) & 1); }
__device__ __forceinline__ void turn_pass(const Ctx& c, uint32_t ring, int i) { if (c.lane == 0) mbar_arrive(ring + (i & 3) * 8); }
__device__ __forceinline__ void p2_scales(P2State& z) {
  float l0 = z.l0, l1 = z.l1;
  l0 += __shfl_xor_sync(0xffffffffu, l0, 1);
  l1 += __shfl_xor_sync(0xffffffffu, l1, 1);
  l0 += __shfl_xor_sync(0xffffffffu, l0, 2);
  l1 += __shfl_xor_sync(0xffffffffu, l1, 2);
  asm("rcp.approx.ftz.f32 %0, %1;" : "=f"(z.e0) : "f"(l0));
  asm("rcp.approx.ftz.f32 %0, %1;" : "=f"(z.e1) : "f"(l1));
}
template <int N>
__device__ __forceinline__ void p2_first(const Ctx& c, P2State& z, float (&o)[64], uint32_t (&Pc)[32], uint32_t (&Pn)[32],
                                         int ks, int vs, int cnt, int acc) {
  float s[N] = {};
  issue_qk(s, z.qd, desc_lo(c.sm + SM_RING, 16) + ks * 2048);
  if (vs >= 0) {
    p2_scales(z);
    issue_pv<8>(o, Pc, desc_lo(c.sm + SM_RING, 16384) + vs * 2048, acc);
  } else {
    WG_COMMIT();
  }
  mbar_expect(z.ab + (z.ai++ & 3) * 8, cnt == 1 ? 8192 : 0);
  PROFZ();
  WG_WAIT(1);
  PROFZ();
  pin(s);
  release(c, B_P2E + ks, cnt);
  causal_mask(s, c.warp * 16 + (c.lane >> 2) - 2 * (c.lane & 3));
  z.m0 = z.m1 = 0.f;
  row_exp<false>(s, Pn, 0.f, 0.f, z.l0, z.l1);
  z.shift = __any_sync(0xffffffffu, !(z.l0 + z.l1 <= SM_HI) || ((c.lane & 3) == 0 && !(fminf(z.l0, z.l1) >= SM_LO)));
  if (__builtin_expect(z.shift, 0)) {
    z.m0 = z.m1 = -INFINITY;
    row_max(s, z.m0, z.m1);
    row_exp<true>(s, Pn, z.m0, z.m1, z.l0, z.l1);
  }
  WG_WAIT(0);
  pin(o);
  if (vs >= 0) release(c, B_P2E + vs, 1);
}

template <bool SECOND>
__device__ __forceinline__ void p2_turn(const Ctx& c, P2State& z, float (&o)[64], uint32_t (&Pc)[32], uint32_t (&Pn)[32],
                                        int eb = -1, bool half = false, int vcnt = 1) {
  float s[64] = {};
  const int ks = z.ks, vs = wrap5(ks + 1);
  PROFZ();
  turn_wait(z.wb, z.wi++);
  PROFZ();
  issue_qk(s, z.qd, desc_lo(c.sm + SM_RING, 16) + ks * 2048);
  const uint32_t vd = desc_lo(c.sm + SM_RING, 16384) + vs * 2048;
  if (SECOND) {
    if (eb >= 0) stage_tile(o, c.sm + SM_BUF + eb * 16384, c, z.e0, z.e1);
    if (half) issue_pv<4>(o, Pc, vd, 0); else issue_pv<8>(o, Pc, vd, 0);
  } else {
    issue_pv<8>(o, Pc, vd, 1);
  }
  turn_pass(c, z.ab, z.ai++);
  if (SECOND) { if (eb >= 0) stage_done(c, eb); }
  PROFZ();
  z.ks = wrap5(ks + 2);
  WG_WAIT(1);
  PROFZ();
  pin(s);
  release(c, B_P2E + ks, 1);
  float t0, t1, a0 = 1.f, a1 = 1.f;
  row_exp<false>(s, Pn, 0.f, 0.f, t0, t1);
  z.shift = __any_sync(0xffffffffu, z.shift || !(t0 + t1 <= SM_HI));
  const bool redo = z.shift;
  if (__builtin_expect(redo, 0)) {
    float n0 = z.m0, n1 = z.m1;
    row_max(s, n0, n1);
    a0 = ex2(z.m0 - n0); a1 = ex2(z.m1 - n1);
    z.m0 = n0; z.m1 = n1;
    z.l0 *= a0; z.l1 *= a1;
    row_exp<true>(s, Pn, z.m0, z.m1, t0, t1);
  }
  WG_WAIT(0);
  pin(o);
  release(c, B_P2E + vs, vcnt);
  if (__builtin_expect(redo, 0)) {
#pragma unroll
    for (int i = 0; i < 16; i++) { o[4 * i] *= a0; o[4 * i + 1] *= a0; o[4 * i + 2] *= a1; o[4 * i + 3] *= a1; }
  }
  z.l0 += t0; z.l1 += t1;
}
__device__ __forceinline__ void copy_p(uint32_t (&d)[32], const uint32_t (&s)[32], int zero) {
#pragma unroll
  for (int i = 0; i < 32; i++) asm volatile("add.s32 %0, %1, %2;" : "=r"(d[i]) : "r"(s[i]), "r"(zero));
}

__device__ __forceinline__ void p2_consumer(const Params& p, const Ctx& c, int rot) {
  const int nit = p.s.r[c.cl].n2;
  const uint32_t fring = c.bar + B_P2F * 8, oring = c.bar + B_ORD * 8;
  float o[64] = {};
  uint32_t Pa[32] = {}, Pb[32] = {};
  P2State z;
  z.e0 = z.e1 = z.l0 = z.l1 = 0.f; z.ks = rot; z.shift = false;
  int acc = 0, n = 0;
  for (int it = 0; it < nit; it++) {
    const int j = p.s.r[c.cl].item[it] & 7, blk = p2_blk(c.rank, c.wg, it);
    const int lng = ((it ^ c.wg) & 1) ^ 1;
    z.qd = desc_lo(c.sm + SM_BUF, 16) + p2_buf(c.wg, it) * 1024;
    if (lng) { z.wb = oring; z.wi = n - it; z.ab = fring; z.ai = n + 1; }
    else { z.wb = fring; z.wi = n + 2; z.ab = oring; z.ai = n - it; }
    PROFZ();
    mbar_wait(c.bar + (B_QF + p2_buf(c.wg, it)) * 8, (it >> 1) & 1);
    turn_wait(fring, n + 1 - lng);
    PROFZ();
    const int vs = it ? wrap5(z.ks + 1) : -1, ks = lng ? z.ks : wrap5(z.ks + (it ? 2 : 1));
    if (blk & 1) p2_first<64>(c, z, o, Pa, Pb, ks, vs, 1 + lng, acc);
    else p2_first<32>(c, z, o, Pa, Pb, ks, vs, 1 + lng, acc);
    z.ks = wrap5(ks + (it == 0 && lng ? 1 : 2));
    PROF(c.wg, 24 + it);
    n += 2 * j + 2;
    int left = 2 * j + lng;
    acc = left != 0;
    if (left == 0) { copy_p(Pa, Pb, p.zero); continue; }
    p2_turn<true>(c, z, o, Pb, Pa, it > 0 ? p2_buf(c.wg, it - 1) : -1, !(blk & 1), 1 + lng);
    while (--left > 0) {
      p2_turn<false>(c, z, o, Pa, Pb);
      if (--left == 0) { copy_p(Pa, Pb, p.zero); break; }
      p2_turn<false>(c, z, o, Pb, Pa);
    }
  }
  {
    if (!acc && nit > 1) p2_epilogue(o, z.e0, z.e1, c, p2_buf(c.wg, nit));
    turn_wait(z.wb, z.wi);
    issue_pv<8>(o, Pa, desc_lo(c.sm + SM_RING, 16384) + z.ks * 2048, acc);
    if (((nit - 1) ^ c.wg) & 1) turn_pass(c, z.ab, z.ai);
    p2_scales(z);
    WG_WAIT(0);
    pin(o);
    release(c, B_P2E + z.ks);
    p2_epilogue(o, z.e0, z.e1, c, p2_buf(c.wg, nit - 1));
    PROF(c.wg, 24 + nit);
  }
}

__device__ __forceinline__ void p2_load_q(const Params& p, const Ctx& c, int it, int w) {
  const int item = p.s.r[c.cl].item[it], h = item >> 3, j = item & 7, b = p2_buf(w, it);
  mbar_expect(c.bar + (B_QF + b) * 8, 16384);
  bulk_load(c.sm + SM_BUF + b * 16384, g_Q + (size_t)(h * 32 + j * 4 + p2_blk(c.rank, w, it)) * 16384, 16384, c.bar + (B_QF + b) * 8, POL(4));
}
__device__ __forceinline__ void wait_p1_free(const Ctx& c, int u1, int s) {
  mbar_wait(c.bar + (B_P1E + 2 * s) * 8, ((u1 - 1 - 2 * s) / 10) & 1);
  mbar_wait(c.bar + (B_P1E + 2 * s + 1) * 8, ((u1 - 2 - 2 * s) / 10) & 1);
}
__device__ __forceinline__ void p2_producer(const Params& p, const Ctx& c, int u1, int rot) {
  const int nit = p.s.r[c.cl].n2;
  int slot = rot, cnt = 0, par = 1, n = 0;
  const uint8_t* pv = nullptr;
  bool pl = false;
  auto load = [&](const uint8_t* src, int expect, uint32_t fb, bool last) {
    if (cnt < 5) {
      if (u1) {
        wait_p1_free(c, u1, slot);
        if (cnt == 0) p2_load_q(p, c, 0, 1);
      }
      cnt++;
    } else {
      if (slot == rot) par ^= 1;
      mbar_wait(c.bar + (B_P2E + slot) * 8, par);
    }
    if (expect) mbar_expect(fb, expect);
    bulk_load_mc(c.sm + SM_RING + slot * 32768 + c.rank * 16384, src, 16384, fb, last ? POL(5) : L2_NORMAL);
    slot = wrap5(slot + 1);
  };
  for (int it = 0; it < nit; it++) {
    const int item = p.s.r[c.cl].item[it], h = item >> 3, j = item & 7;
    if (it == 1 && (c.phases & 16) && p.s.r[c.cl].n1 < 8) flag_wait<true>(F_GATE, 256);
    uint32_t ready = (c.phases & 16) ? 0u : 255u;
    if (it == 0) { if (c.phases & 16) flag_wait<false>(F_Q + item, 4); mbar_wait(c.bar + B_LAD * 8, 0); p2_load_q(p, c, 0, 0); if (!u1) p2_load_q(p, c, 0, 1); }
    for (int t = 2 * j + 1; t >= 0; t--) {
      mask_wait(ready, t >> 1, F_KV + h * 8 + (c.lane & 7), 8);
      const uint8_t* k = g_KV + (size_t)(p.s.slot[h][t >> 1] * 16 + t) * 32768 + c.rank * 16384;
      const uint32_t fb = c.bar + (B_P2F + (n & 3)) * 8;
      const bool last = (p.s.r[c.cl].last[it] >> (t >> 1)) & 1;
      load(k, pv && t != 2 * j ? 65536 : 32768, fb, last);
      if (!(t & 1) && t + 4 <= 2 * j && c.rank == 0) flag_add_rx(F_RD + h * 8 + (t >> 1) + 2);
      if (pv) load(pv, 0, t != 2 * j ? fb : c.bar + (B_ORD + ((n - 1 - it) & 3)) * 8, pl);
      pl = last;
      pv = k + (size_t)NH * 16 * 32768;
      n++;
    }
  }
  load(pv, 32768, c.bar + (B_P2F + (n & 3)) * 8, pl);
}

__device__ __forceinline__ void p2_storer(const Params& p, const Ctx& c, int sfpar) {
  const int nit = p.s.r[c.cl].n2;
  auto load_q = [&](int it, int w) {
    if (c.phases & 16) flag_wait<false>(F_Q + p.s.r[c.cl].item[it], 4);
    p2_load_q(p, c, it, w);
  };
  if (nit > 1) {
    load_q(1, 1); p2_load_q(p, c, 1, 0); }
  for (int i = 0; i < 2 * nit; i++) {
    const int it = i >> 1, w = (it ^ i ^ 1) & 1, b = p2_buf(w, it);
    const int item = p.s.r[c.cl].item[it], h = item >> 3, j = item & 7;
    mbar_wait(c.bar + (B_SF + b) * 8, (sfpar >> b) & 1);
    sfpar ^= 1 << b;
    bulk_store(g_Q + (size_t)(h * 32 + j * 4 + p2_blk(c.rank, w, it)) * 16384, c.sm + SM_BUF + b * 16384, 16384, POL(1));
    BULK_COMMIT();
    if (i & 1) {
      BULK_WAIT(0);
      if (it + 1 == nit) release(c, B_DONE);
      flag_add(F_CTX + j * 64 + h, 2);
      if (it + 2 < nit) { load_q(it + 2, w); p2_load_q(p, c, it + 2, w ^ 1); }
    }
  }
}

__device__ __forceinline__ int p3_pos(int i, int x) { return i < 4 ? (i + x) & 3 : 4; }
__device__ __forceinline__ void p3_consumer(const Params& p, const Ctx& c, int x) {
  const bool first = p.s.r[c.cl].p3 >= 24;
  const int tile = p.s.r[c.cl].p3 - (first ? 24 : 0), j = tile / 3, nt = tile - 3 * j;
  const int na = first ? 9 : 0, nb = p.s.task[c.cl][1] - p.s.task[c.cl][0];
  const uint32_t ad = desc_lo(c.sm + SM_RING + c.wg * 8192, 16), bd = desc_lo(c.sm + SM_RING + 16384, 4096);
  float acc[96] = {};
  int slot = 0, par = 0, prev = 0;
  float g0 = 0.f, g1 = 0.f;
  const int hold = c.wg && LAG ? na + nb - LAG : -1, pass = c.wg || !LAG ? -1 : na + nb - 1;
#pragma unroll 1
  for (int kb = 0; kb < nb; kb++) {
    if (kb == hold) bar_sync(6, 256);
    mbar_wait(c.bar + (B_P3F + slot) * 8, par);
    if (kb == 0) PROF(c.wg, 39);
    WG_FENCE();
#pragma unroll
    for (int kk = 0; kk < 4; kk++) wgmma_ss192<1>(acc, ad + p3_pos(slot, x) * 2560 + kk * 2, bd + p3_pos(slot, x) * 2560 + (kk >> 1) * 768 + (kk & 1) * 128, kk != 0 ? 1 : kb != 0);
    WG_COMMIT();
    if (kb == pass) bar_arrive(6, 256);
    WG_WAIT(1);
    if (kb > 0) release(c, B_P3E + prev);
    else {
      const float* g = g_gate + j * 256 + c.rank * 128 + c.wg * 64 + c.warp * 16 + (c.lane >> 2);
      g0 = __ldcg(g); g1 = __ldcg(g + 8);
    }
    prev = slot;
    if (++slot == 5) { slot = 0; par ^= 1; }
  }
  WG_WAIT(0);
  pin(acc);
  g0 = 1.f - g0; g1 = 1.f - g1;
#pragma unroll
  for (int i = 0; i < 24; i++) { acc[4 * i] *= g0; acc[4 * i + 1] *= g0; acc[4 * i + 2] *= g1; acc[4 * i + 3] *= g1; }
#pragma unroll 1
  for (int kb = nb; kb < nb + na; kb++) {
    if (kb == hold) bar_sync(6, 256);
    mbar_wait(c.bar + (B_P3F + slot) * 8, par);
    if (kb == 0) PROF(c.wg, 39);
    WG_FENCE();
#pragma unroll
    for (int kk = 0; kk < 4; kk++) wgmma_ss192<1, 1>(acc, ad + p3_pos(slot, x) * 2560 + kk * 128, bd + p3_pos(slot, x) * 2560 + (kk >> 1) * 768 + (kk & 1) * 128, 1);
    WG_COMMIT();
    if (kb == pass) bar_arrive(6, 256);
    WG_WAIT(1);
    if (kb > 0) release(c, B_P3E + prev);
    prev = slot;
    if (++slot == 5) { slot = 0; par ^= 1; }
  }
  WG_WAIT(0);
  pin(acc);
  PROF(c.wg, 40);
  if (first) bar_sync(4 + c.wg, 128);
  mbar_wait(c.bar + B_OUT * 8, 0);
  const int row = (c.lane & 7) + ((c.lane >> 3) & 1) * 8;
  const uint32_t wbase = c.sm + SM_RING + c.wg * 8192 + c.warp * 2048;
  const uint32_t base = wbase + row * 128 + (((c.lane >> 4) ^ (row & 7)) << 4);
#pragma unroll
  for (int i = 0; i < 12; i++) {
    stsm4((base ^ ((i & 3) << 5)) + (i >> 2) * 40960, pack_bf16(acc[8 * i], acc[8 * i + 1]), pack_bf16(acc[8 * i + 2], acc[8 * i + 3]),
          pack_bf16(acc[8 * i + 4], acc[8 * i + 5]), pack_bf16(acc[8 * i + 6], acc[8 * i + 7]));
    if ((i & 3) == 3) {
      FENCE_ASYNC_SMEM();
      bar_sync(4 + c.wg, 128);
      if (c.warp == (i >> 2)) tma2d_add(&p.map_out, c.sm + SM_RING + c.wg * 8192 + c.warp * 40960, nt * 192 + c.warp * 64, j * 256 + c.rank * 128 + c.wg * 64);
    }
  }
  BULK_COMMIT();
  PROF(c.wg, 43);
  BULK_WAIT_READ(0);
  PROF(c.wg, 44);
}

__device__ __forceinline__ void p3_producer(const Params& p, const Ctx& c, int u1, int u2, int rot, int x) {
  const bool first = p.s.r[c.cl].p3 >= 24;
  const int tile = p.s.r[c.cl].p3 - (first ? 24 : 0), j = tile / 3, nt = tile - 3 * j;
  int slot = 0, par = 1, cnt = 0;
  auto wait_free = [&](int s) {
    const int f = wrap5(s + 5 - rot);
    if (f < u2) mbar_wait(c.bar + (B_P2E + s) * 8, ((u2 - 1 - f) / 5) & 1);
    else if (u1) wait_p1_free(c, u1, s);
  };
  asm volatile(ELECT("prefetch.tensormap [%0];") ::"l"(&p.map_o[0]) : "memory");
  asm volatile(ELECT("prefetch.tensormap [%0];") ::"l"(&p.map_out) : "memory");
  if ((c.phases & 16) && p.s.r[c.cl].n1 < 8 && p.s.r[c.cl].n2 < 2) flag_wait<true>(F_GATE, 256);
  uint32_t ready = (c.phases & 16) ? 0u : ~0u;
  const int q1 = p.s.task[c.cl][1];
  for (int q = p.s.task[c.cl][0]; q < q1 + (first ? 9 : 0); q++) {
    const bool brA = q >= q1;
    const int kb = brA ? q - q1 : p.s.p3_order[tile][q];
    if (!brA) mask_wait(ready, kb >> 1, F_CTX + j * 64 + c.lane, 4);
    else if (kb == 0 && (c.phases & 16)) flag_wait<false>(F_CTX + j * 64 + 32, 16);
    const uint8_t* a = brA ? g_oA + (j * 4 + c.rank * 2) * 73728 + kb * 8192 : g_Q + (size_t)((kb >> 1) * 32 + j * 4 + c.rank * 2) * 16384 + (kb & 1) * 8192;
    const uint32_t st = c.sm + SM_RING + p3_pos(slot, x) * 40960, fb = c.bar + (B_P3F + slot) * 8;
    if (cnt < 4) { wait_free(p3_pos(cnt, x)); wait_free(p3_pos(cnt, x) + 1); }
    else if (cnt == 4) mbar_wait(c.bar + B_DONE * 8, 0);
    else mbar_wait(c.bar + (B_P3E + slot) * 8, par);
    cnt++;
    mbar_expect(fb, 40960);
    bulk_load(st, a, 8192, fb, POL(3));
    bulk_load(st + 8192, a + (brA ? 73728 : 16384), 8192, fb, POL(3));
    tma3d_mc(st + 16384 + c.rank * 12288, &p.map_o[brA], 0, kb * 64 + c.rank * 32, nt * 3, fb);
    if (++slot == 5) { slot = 0; par ^= 1; }
  }
}

__device__ __forceinline__ float bf_lo(uint32_t w) { return __uint_as_float(w << 16); }
__device__ __forceinline__ float bf_hi(uint32_t w) { return __uint_as_float(w & 0xffff0000u); }

__device__ __forceinline__ void gate_rows(const Params& p, int row0, int lane) {
  const uint4* x = reinterpret_cast<const uint4*>(p.x + (size_t)(row0 + (lane >> 2)) * DM) + (lane & 3);
  const uint4* w = reinterpret_cast<const uint4*>(p.gate_w) + (lane & 3);
  float a = 0.f;
#pragma unroll 1
  for (int b = 0; b < 3; b++) {
    uint4 u[6];
#pragma unroll
    for (int i = 0; i < 6; i++) u[i] = __ldg(x + (b * 6 + i) * 4);
#pragma unroll
    for (int i = 0; i < 6; i++) {
      const uint4 v = __ldg(w + (b * 6 + i) * 4);
      a = fmaf(bf_lo(u[i].x), bf_lo(v.x), a); a = fmaf(bf_hi(u[i].x), bf_hi(v.x), a);
      a = fmaf(bf_lo(u[i].y), bf_lo(v.y), a); a = fmaf(bf_hi(u[i].y), bf_hi(v.y), a);
      a = fmaf(bf_lo(u[i].z), bf_lo(v.z), a); a = fmaf(bf_hi(u[i].z), bf_hi(v.z), a);
      a = fmaf(bf_lo(u[i].w), bf_lo(v.w), a); a = fmaf(bf_hi(u[i].w), bf_hi(v.w), a);
    }
  }
  a += __shfl_xor_sync(0xffffffffu, a, 1);
  a += __shfl_xor_sync(0xffffffffu, a, 2);
  if ((lane & 3) == 0) g_gate[row0 + (lane >> 2)] = 1.f / (1.f + __expf(-a));
}

__device__ __forceinline__ void lds10(uint32_t (&k)[10], uint32_t a) {
  asm volatile("ld.shared.v2.u32 {%0, %1}, [%10];\nld.shared.v2.u32 {%2, %3}, [%10+8];\nld.shared.v2.u32 {%4, %5}, [%10+16];\n"
               "ld.shared.v2.u32 {%6, %7}, [%10+24];\nld.shared.v2.u32 {%8, %9}, [%10+32];"
               : "=r"(k[0]), "=r"(k[1]), "=r"(k[2]), "=r"(k[3]), "=r"(k[4]), "=r"(k[5]), "=r"(k[6]), "=r"(k[7]), "=r"(k[8]), "=r"(k[9]) : "r"(a));
}
__device__ __forceinline__ void local_attn(const Params& p, const Ctx& c, int rb, int hs) {
  const int lane = c.lane, grp = rb >> 2, par = lane >> 4, i0 = 2 * (lane & 15);
  const uint32_t buf = c.sm + SM_BUF + (c.warp - 2) * 8192, bqk = c.bar + (B_LA + (c.warp - 2) * 2) * 8, bv = bqk + 8;
  const uint32_t mine = buf + 2304 + par * 160 + i0 * 4;
  const bool flags = c.phases & 16;
  auto fetch_qk = [&](int i) {
    if (flags && !(i & 1)) {
      const int q = i >> 1;
      const int tgt = q == 0 ? 24 : q == 3 ? 8 : 12;
      flag_wait<false>(F_QKVA + (grp - (grp > 0 && (rb & 3) == 0 ? par : 0)) * 4 + q, tgt);
    }
    mbar_expect(bqk, 5184);
    tma3d(buf, &p.map_t[0], rb * 32 + 8, 0, 9 * (4 * i + hs), bqk, POL(2));
    tma3d(buf + 2304, &p.map_t[1], rb * 32, 0, 288 + 9 * (4 * i + hs), bqk, POL(2));
  };
  auto fetch_v = [&](int i) { mbar_expect(bv, 2880); tma3d(buf + 5248, &p.map_t[1], rb * 32, 0, 576 + 9 * (4 * i + hs), bv, POL(2)); };
  fetch_qk(0);
  if (flags) flag_wait<true>(F_GATE, 256);
#pragma unroll 1
  for (int q = 0; q < 8; q++) {
    fetch_v(q);
    float a[8], b[8];
#pragma unroll
    for (int w = 0; w < 8; w++) a[w] = b[w] = 0.f;
    mbar_wait(bqk, q & 1);
    PROFB(1 + 2 * q);
#pragma unroll 1
    for (int j = 0; j < 9; j++) {
      uint32_t x, y, k[10];
      asm volatile("ld.shared.v2.u32 {%0, %1}, [%2];" : "=r"(x), "=r"(y) : "r"(buf + lane * 8 + j * 256));
      lds10(k, mine + j * 320);
      const float xl = bf_lo(x), xh = bf_hi(x), yl = bf_lo(y), yh = bf_hi(y);
#pragma unroll
      for (int m = 1; m < 10; m++) {
        const float kl = bf_lo(k[m]), kh = bf_hi(k[m]);
        if (m < 9) a[8 - m] = fmaf(xl, kl, fmaf(xh, kh, a[8 - m]));
        if (m > 1) b[9 - m] = fmaf(yl, kl, fmaf(yh, kh, b[9 - m]));
      }
    }
    __syncwarp();
    if (q < 7) fetch_qk(q + 1);
    constexpr float SC = 0.23570226039551584f * 1.4426950408889634f;
    const float* gp = g_gate + rb * 64 + 2 * i0 + par;
    const float ga = __ldcg(gp), gb = __ldcg(gp + 2);
    float ma = a[0], mb = b[0];
#pragma unroll
    for (int w = 1; w < 8; w++) {
      if (rb == 0) {
        if (i0 < w) a[w] = -INFINITY;
        if (i0 + 1 < w) b[w] = -INFINITY;
      }
      ma = fmaxf(ma, a[w]); mb = fmaxf(mb, b[w]);
    }
    float la = 0.f, lb = 0.f;
#pragma unroll
    for (int w = 0; w < 8; w++) {
      a[w] = ex2((a[w] - ma) * SC); b[w] = ex2((b[w] - mb) * SC);
      la += a[w]; lb += b[w];
    }
    la = __fdividef(ga, la); lb = __fdividef(gb, lb);
#pragma unroll
    for (int w = 0; w < 8; w++) { a[w] *= la; b[w] *= lb; }
    uint8_t* dst = g_oA + rb * 73728 + ((i0 & 2) + par) * 4;
    mbar_wait(bv, q & 1);
#pragma unroll 1
    for (int j = 0; j < 9; j++) {
      uint32_t v[10];
      lds10(v, mine + 2944 + j * 320);
      float a0 = 0.f, a1 = 0.f, b0 = 0.f, b1 = 0.f;
#pragma unroll
      for (int m = 1; m < 10; m++) {
        const float vl = bf_lo(v[m]), vh = bf_hi(v[m]);
        if (m < 9) { a0 = fmaf(a[8 - m], vl, a0); a1 = fmaf(a[8 - m], vh, a1); }
        if (m > 1) { b0 = fmaf(b[9 - m], vl, b0); b1 = fmaf(b[9 - m], vh, b1); }
      }
      const uint32_t wa = pack_bf16(a0, a1), wb = pack_bf16(b0, b1);
      const uint32_t got = __shfl_xor_sync(0xffffffffu, par ? wa : wb, 16);
      const uint32_t r0 = par ? got : wa, r1 = par ? wb : got;
      const int col = 18 * (4 * q + hs) + 2 * j, o = col * 128 + ((((i0 >> 2) ^ col) & 7) << 4);
      *reinterpret_cast<uint32_t*>(dst + o) = __byte_perm(r0, r1, 0x5410);
      *reinterpret_cast<uint32_t*>(dst + ((o + 128) ^ 16)) = __byte_perm(r0, r1, 0x7632);
    }
    __syncwarp();
    PROFB(2 + 2 * q);
  }
  mbar_arrive_one(c.bar + B_LAD * 8);
  flag_add(F_CTX + grp * 64 + 32);
}

__global__ void __cluster_dims__(2, 1, 1) __launch_bounds__(384, 1) fused_kernel(const __grid_constant__ Params p) {
  extern __shared__ uint8_t smem_raw[];
  Ctx c;
  c.sm = ((uint32_t)__cvta_generic_to_shared(smem_raw) + 1023u) & ~1023u;
  c.bar = c.sm + SM_BAR;
  c.lane = threadIdx.x & 31;
  const int wid = __shfl_sync(0xffffffffu, threadIdx.x >> 5, 0);
  if (wid < 6) asm volatile("prefetch.tensormap [%0];" ::"l"(&p.map_a[0] + wid) : "memory");
  c.wg = wid >> 2;
  c.warp = wid & 3;
  PROF(c.wg, 0);
  PROFG(61);
  c.cl = (blockIdx.x + (wid >> 4)) >> 1;
  c.rank = blockIdx.x & 1;
  c.rbar = mapa(c.bar, c.lane & 1);
  {
    const int w = wid, cnt = (((int)(B_CNT >> (4 * w)) - 1) & 15) + 1;
    if (w < 11) {
#pragma unroll
      for (int i = 0; i < 8; i++) asm volatile("mbarrier.init.shared::cta.b64 [%0], %1;" ::"r"(c.bar + w * 64 + i * 8), "r"(cnt));
    }
    asm volatile("fence.mbarrier_init.release.cluster;" ::: "memory");
  }
  if (c.wg == 2) PROF(2, 56);
  asm volatile("barrier.cluster.arrive.relaxed;" ::: "memory");
  c.phases = p.s.r[c.cl].phases;
  const bool do1 = p.s.r[c.cl].n1 > 0, do2 = p.s.r[c.cl].n2 > 0, do3 = p.s.r[c.cl].p3 != 255;
  if (do1 && c.wg == 2 && c.warp == 0) {
    const int type = p.s.r[c.cl].slab >> 3;
    PROF(2, 57);
    FENCE_ASYNC_SMEM();
    mbar_expect(c.bar + B_P1F * 8, type ? 32768 : 16384);
    tma2d(type ? c.sm + SM_BUF + 32768 : c.sm + SM_RING, &p.map_a[type], type ? 512 : 0, (p.s.r[c.cl].slab & 7) * 256 + c.rank * 128, c.bar + B_P1F * 8);
    PROF(2, 58);
  }
  asm volatile("barrier.cluster.wait.acquire;" ::: "memory");
  if (c.wg == 2) PROF(2, 59);
  if (do1 && c.wg == 2 && c.warp == 0) {
    const int type = p.s.r[c.cl].slab >> 3, tile = p.s.r[c.cl].tile[0] & 63;
    const CUtensorMap* m = &p.map_w[type * 2 + (tile >> 5)];
#pragma unroll 1
    for (int s = 1 - type; s < NPRO; s++) {
      const int kb = (s - type) >> 1;
      const uint32_t fb = c.bar + (B_P1F + s) * 8;
      if (s) mbar_expect(fb, 16384);
      if ((s ^ type) & 1) tma2d_mc(c.sm + SM_RING + s * 16384 + c.rank * 8192, m, (tile & 31) * 128 + c.rank * 64, kb < 0 ? 512 : kb * 64, fb);
      else tma2d(c.sm + SM_RING + s * 16384, &p.map_a[type], kb * 64, (p.s.r[c.cl].slab & 7) * 256 + c.rank * 128, fb);
    }
  }

  if (c.wg < 2) {
    PROF(c.wg, 4);
    asm volatile("setmaxnreg.inc.sync.aligned.u32 224;");
    if (c.wg == 1) {
      if (do1) bar_arrive(ORDER, 256);
      if (c.lane == 0) mbar_arrive(c.bar + B_P2F * 8);
    }
    PL(0);
    if (do1) p1_consumer(p, c);
    PL(1);
    if (do2) p2_consumer(p, c, p.s.r[c.cl].rot);
    PL(2);
    if (do3) p3_consumer(p, c, p.s.r[c.cl].x3);
    PL(3);
    PROF(c.wg, 63);
    PROFG(62);
    if (c.lane == 0) mbar_arrive(c.bar + B_FIN * 8);
    __syncwarp();
    cluster_sync();
  } else {
    asm volatile("setmaxnreg.dec.sync.aligned.u32 56;");
    if (c.warp == 0) {
      PROF(2, 60);
      if (do1) p1_producer(p, c);
      if (do2) p2_producer(p, c, p.s.r[c.cl].u1, p.s.r[c.cl].rot);
      if (do3) p3_producer(p, c, p.s.r[c.cl].u1, p.s.r[c.cl].u2, p.s.r[c.cl].rot, p.s.r[c.cl].x3);
    } else if (c.warp == 1) {
      int sfpar = 0;
      if (do1) {
        p1_storer(p, c);
        sfpar = (p.s.r[c.cl].n1 & 1) * 10;
      }
      if (do2) p2_storer(p, c, sfpar);
      else { mbar_wait(c.bar + B_LAD * 8, 0); release(c, B_DONE); }
      if (do3) {
        const int tile = p.s.r[c.cl].p3 % 24;
        if (p.s.task[c.cl][1] == 64) {
          for (int r = 0; r < (64 - p.s.task[c.cl][0] - ZLEAD) / 5; r++) mbar_wait(c.bar + B_P3F * 8, r & 1);
          const int j = tile / 3, nt = tile - 3 * j;
          uint4* o = reinterpret_cast<uint4*>(p.out + (size_t)(j * 256 + c.rank * 128 + (c.lane >> 3)) * DM + nt * 192) + (c.lane & 7);
#pragma unroll 4
          for (int r = 0; r < 32; r++) o[r * 288] = o[r * 288 + 8] = o[r * 288 + 16] = make_uint4(0u, 0u, 0u, 0u);
          __syncwarp();
          flag_add(F_OUT + tile * 2 + c.rank);
        } else if (c.phases & 16) {
          flag_wait<false, 256>(F_OUT + tile * 2 + c.rank, 1);
        }
        mbar_arrive_one(c.bar + B_OUT * 8);
      }
    } else {
      const int bw = blockIdx.x * 2 + (c.warp - 2);
      if ((c.phases & 1) && bw < 256) {
        gate_rows(p, bw * 8, c.lane);
        __syncwarp();
        flag_add(F_GATE);
      }
      if (p.s.r[c.cl].bg != 255) local_attn(p, c, p.s.r[c.cl].bg, bw & 3);
      else if (c.lane == 0) mbar_arrive(c.bar + B_LAD * 8);
    }
    __syncwarp();
    bar_sync(3, 128);
    if (c.warp == 0 && (c.phases & 32)) {
      int last = 0;
      if (c.lane == 0) { __threadfence(); last = atomicAdd(g_flags + F_DONE, 1) == 2 * NCL - 1; }
      if (__shfl_sync(0xffffffffu, last, 0)) for (int i = c.lane; i < F_NUM; i += 32) g_flags[i] = 0;
    }
    if (c.warp == 1) mbar_wait(c.bar + B_FIN * 8, 0);
    __syncwarp();
    cluster_sync();
  }
}

SCHED_DECL Sched k_sched = {
  {{0,30,2,44,0,{250,248,0,0,0,0,0,0,0,0,0},{0,0,0,0,0,0,0,0,0,0,0},{65,41,136,34,69,3,0,10,11,17,12,26,21,20,27,15,28,19,13,14,25,18,22,7,29,30,24,31,16,23}},
   {1,30,2,8,1,{241,185,0,0,0,0,0,0,0,0,0},{0,0,0,0,0,0,0,0,0,0,0},{65,166,2,40,0,3,5,10,11,17,12,26,21,20,27,15,28,13,14,19,18,25,7,22,29,30,24,31,16,23}},
   {2,29,1,10,2,{244,0,0,0,0,0,0,0,0,0,0},{16,0,0,0,0,0,0,0,0,0,0},{73,166,2,40,3,0,5,11,17,12,21,26,27,20,15,28,13,14,19,18,25,22,7,29,30,24,31,16,23,0}},
   {3,29,2,2,3,{188,128,0,0,0,0,0,0,0,0,0},{0,0,0,0,0,0,0,0,0,0,0},{65,41,6,40,3,0,11,17,10,12,21,26,27,20,15,28,13,14,19,18,25,22,7,29,24,30,31,23,16,0}},
   {4,28,0,13,4,{0,0,0,0,0,0,0,0,0,0,0},{0,0,0,0,0,0,0,0,0,0,0},{66,33,9,40,3,5,42,17,12,21,26,27,20,15,28,13,14,19,18,25,22,7,29,24,30,31,23,16,0,0}},
   {5,27,0,1,5,{0,0,0,0,0,0,0,0,0,0,0},{0,0,0,0,0,0,0,0,0,0,0},{66,166,9,40,3,5,42,17,44,26,27,20,15,28,13,14,19,25,18,71,22,29,24,30,31,23,16,0,0,0}},
   {6,26,0,9,6,{0,0,0,0,0,0,0,0,0,0,0},{0,0,0,0,0,0,0,0,0,0,0},{73,6,68,40,0,10,43,12,53,27,20,15,28,13,14,19,18,25,22,29,7,24,30,31,23,16,0,0,0,0}},
   {7,25,0,23,7,{0,0,0,0,0,0,0,0,0,0,0},{0,0,0,0,0,0,0,0,0,0,0},{66,9,136,67,69,107,76,117,91,84,79,92,77,78,83,82,89,86,93,71,88,94,95,87,80,0,0,0,0,0}},
   {0,30,1,12,8,{187,0,0,0,0,0,0,0,0,0,0},{0,0,0,0,0,0,0,0,0,0,0},{97,6,104,4,101,35,32,42,43,49,44,58,53,52,59,47,60,51,45,46,57,50,54,39,61,62,56,63,48,55}},
   {1,30,1,9,9,{243,0,0,0,0,0,0,0,0,0,0},{15,0,0,0,0,0,0,0,0,0,0},{97,9,34,4,32,35,37,42,43,49,44,58,53,52,59,47,60,45,46,51,50,57,39,54,61,62,56,63,48,55}},
   {2,29,1,0,10,{252,0,0,0,0,0,0,0,0,0,0},{0,0,0,0,0,0,0,0,0,0,0},{105,1,34,4,35,32,37,43,49,44,53,58,59,52,47,60,45,46,51,50,57,54,39,61,62,56,63,48,55,0}},
   {3,29,1,45,11,{195,0,0,0,0,0,0,0,0,0,0},{0,0,0,0,0,0,0,0,0,0,0},{97,2,38,4,35,32,43,49,42,44,53,58,59,52,47,60,45,46,51,50,57,54,39,61,56,62,63,55,48,0}},
   {4,28,0,6,12,{0,0,0,0,0,0,0,0,0,0,0},{0,0,0,0,0,0,0,0,0,0,0},{98,6,41,4,35,37,11,49,44,53,58,59,52,47,60,45,46,51,50,57,54,39,61,56,62,63,55,48,0,0}},
   {5,27,0,10,13,{0,0,0,0,0,0,0,0,0,0,0},{0,0,0,0,0,0,0,0,0,0,0},{98,1,41,4,35,37,11,49,21,58,59,52,47,60,45,46,51,57,50,103,54,61,56,62,63,55,48,0,0,0}},
   {6,26,0,16,14,{0,0,0,0,0,0,0,0,0,0,0},{0,0,0,0,0,0,0,0,0,0,0},{105,166,100,67,32,42,17,44,26,59,52,47,60,45,46,51,50,57,54,61,39,56,62,63,55,48,0,0,0,0}},
   {7,25,0,5,15,{0,0,0,0,0,0,0,0,0,0,0},{0,0,0,0,0,0,0,0,0,0,0},{98,41,104,99,101,81,108,90,123,116,111,124,109,110,115,114,121,118,125,103,120,126,127,119,112,0,0,0,0,0}},
   {0,4,5,11,255,{8,71,44,222,224,0,0,0,0,0,0},{0,0,0,112,0,0,0,0,0,0,0},{73,166,2,36,0,0,0,0,0,0,0,0,0,0,0,0,0,0,0,0,0,0,0,0,0,0,0,0,0,0}},
   {1,4,6,38,255,{73,70,85,159,145,245,0,0,0,0,0},{0,0,0,0,0,32,0,0,0,0,0},{70,41,136,36,0,0,0,0,0,0,0,0,0,0,0,0,0,0,0,0,0,0,0,0,0,0,0,0,0,0}},
   {2,6,7,22,255,{32,68,45,99,162,115,134,0,0,0,0},{0,0,0,0,0,0,0,0,0,0,0},{70,33,136,36,74,42,0,0,0,0,0,0,0,0,0,0,0,0,0,0,0,0,0,0,0,0,0,0,0,0}},
   {3,6,6,6,255,{16,35,87,212,149,235,0,0,0,0,0},{0,0,128,0,0,0,0,0,0,0,0},{73,34,136,36,69,37,0,0,0,0,0,0,0,0,0,0,0,0,0,0,0,0,0,0,0,0,0,0,0,0}},
   {4,8,6,5,255,{40,36,83,166,204,133,0,0,0,0,0},{0,0,0,14,0,0,0,0,0,0,0},{65,166,136,36,0,32,10,43,0,0,0,0,0,0,0,0,0,0,0,0,0,0,0,0,0,0,0,0,0,0}},
   {5,10,5,33,255,{0,46,213,239,186,0,0,0,0,0,0},{0,0,0,128,6,0,0,0,0,0,0},{70,33,136,36,0,32,10,43,12,53,0,0,0,0,0,0,0,0,0,0,0,0,0,0,0,0,0,0,0,0}},
   {6,10,7,40,255,{80,2,84,163,114,247,192,0,0,0,0},{0,0,0,0,0,128,1,0,0,0,0},{66,1,136,99,69,37,11,49,21,58,0,0,0,0,0,0,0,0,0,0,0,0,0,0,0,0,0,0,0,0}},
   {7,5,4,3,255,{14,4,174,152,0,0,0,0,0,0,0},{0,0,127,0,0,0,0,0,0,0,0},{65,6,68,64,74,0,0,0,0,0,0,0,0,0,0,0,0,0,0,0,0,0,0,0,0,0,0,0,0,0}},
   {8,17,3,27,16,{136,207,253,0,0,0,0,0,0,0,0},{0,0,0,0,0,0,0,0,0,0,0},{73,161,2,69,10,35,44,109,17,27,26,77,28,25,18,7,30,0,0,0,0,0,0,0,0,0,0,0,0,0}},
   {9,18,3,4,17,{219,202,190,0,0,0,0,0,0,0,0},{0,0,64,0,0,0,0,0,0,0,0},{65,41,34,8,103,5,11,40,10,21,20,15,13,19,71,22,24,80,0,0,0,0,0,0,0,0,0,0,0,0}},
   {10,17,3,13,18,{161,108,191,0,0,0,0,0,0,0,0},{0,0,128,0,0,0,0,0,0,0,0},{73,161,166,4,0,39,11,5,45,21,20,27,13,19,18,22,30,0,0,0,0,0,0,0,0,0,0,0,0,0}},
   {11,17,3,18,19,{170,156,135,0,0,0,0,0,0,0,0},{0,0,255,0,0,0,0,0,0,0,0},{65,41,8,69,103,11,17,40,12,84,27,77,19,18,86,29,95,0,0,0,0,0,0,0,0,0,0,0,0,0}},
   {12,18,3,20,20,{216,148,56,0,0,0,0,0,0,0,0},{0,0,0,0,0,0,0,0,0,0,0},{66,41,8,3,103,0,10,17,40,21,20,15,13,19,86,7,24,31,0,0,0,0,0,0,0,0,0,0,0,0}},
   {13,18,3,25,21,{228,181,193,0,0,0,0,0,0,0,0},{0,0,0,0,0,0,0,0,0,0,0},{66,41,8,0,103,5,11,12,45,27,20,77,14,19,71,29,30,23,0,0,0,0,0,0,0,0,0,0,0,0}},
   {14,19,3,29,22,{208,116,254,0,0,0,0,0,0,0,0},{0,0,127,0,0,0,0,0,0,0,0},{73,41,132,38,10,81,39,12,45,26,20,15,14,25,86,88,30,31,16,0,0,0,0,0,0,0,0,0,0,0}},
   {15,18,3,17,23,{168,118,189,0,0,0,0,0,0,0,0},{0,123,56,0,0,0,0,0,0,0,0},{66,36,8,43,10,35,44,12,90,40,20,28,14,18,86,7,30,23,0,0,0,0,0,0,0,0,0,0,0,0}},
   {8,20,2,36,24,{206,242,0,0,0,0,0,0,0,0,0},{47,0,0,0,0,0,0,0,0,0,0},{65,165,132,3,0,39,104,11,12,21,83,20,15,14,86,29,24,31,23,16,0,0,0,0,0,0,0,0,0,0}},
   {9,19,3,35,25,{225,183,233,0,0,0,0,0,0,0,0},{0,128,0,0,0,0,0,0,0,0,0},{70,161,166,99,108,3,17,109,90,12,27,28,14,25,18,94,29,31,23,0,0,0,0,0,0,0,0,0,0,0}},
   {10,20,2,37,26,{150,234,0,0,0,0,0,0,0,0,0},{87,0,0,0,0,0,0,0,0,0,0},{70,165,107,74,35,44,17,40,12,26,79,78,28,25,71,29,95,24,16,23,0,0,0,0,0,0,0,0,0,0}},
   {11,19,2,22,27,{122,120,0,0,0,0,0,0,0,0,0},{0,0,0,0,0,0,0,0,0,0,0},{73,161,132,0,108,3,10,109,90,21,79,28,89,14,71,88,30,23,16,0,0,0,0,0,0,0,0,0,0,0}},
   {12,19,3,20,28,{121,203,237,0,0,0,0,0,0,0,0},{0,0,32,0,0,0,0,0,0,0,0},{65,161,34,99,108,5,76,11,45,26,27,28,82,14,25,29,30,23,16,0,0,0,0,0,0,0,0,0,0,0}},
   {13,18,3,47,29,{96,123,255,0,0,0,0,0,0,0,0},{0,4,128,0,0,0,0,0,0,0,0},{70,161,132,3,108,10,17,40,21,26,79,28,89,18,86,88,95,80,0,0,0,0,0,0,0,0,0,0,0,0}},
   {14,17,3,4,30,{88,117,176,0,0,0,0,0,0,0,0},{0,0,0,0,0,0,0,0,0,0,0},{66,161,8,43,75,35,44,40,21,27,92,77,19,18,71,29,87,0,0,0,0,0,0,0,0,0,0,0,0,0}},
   {15,18,2,24,31,{205,246,0,0,0,0,0,0,0,0,0},{0,64,0,0,0,0,0,0,0,0,0},{65,41,132,0,75,39,17,85,91,45,79,77,19,25,93,88,95,80,0,0,0,0,0,0,0,0,0,0,0,0}},
   {8,3,6,17,255,{22,34,89,98,231,112,0,0,0,0,0},{0,0,0,0,128,0,0,0,0,0,0},{160,170,34,0,0,0,0,0,0,0,0,0,0,0,0,0,0,0,0,0,0,0,0,0,0,0,0,0,0,0}},
   {9,3,6,41,255,{54,3,223,157,178,194,0,0,0,0,0},{0,0,0,0,0,0,0,0,0,0,0},{73,165,107,0,0,0,0,0,0,0,0,0,0,0,0,0,0,0,0,0,0,0,0,0,0,0,0,0,0,0}},
   {10,3,6,19,255,{13,66,27,81,165,104,0,0,0,0,0},{0,0,0,0,0,0,0,0,0,0,0},{160,170,2,0,0,0,0,0,0,0,0,0,0,0,0,0,0,0,0,0,0,0,0,0,0,0,0,0,0,0}},
   {11,3,7,39,255,{50,10,47,221,226,153,197,0,0,0,0},{0,0,0,0,0,0,32,0,0,0,0},{66,165,34,0,0,0,0,0,0,0,0,0,0,0,0,0,0,0,0,0,0,0,0,0,0,0,0,0,0,0}},
   {12,3,4,15,255,{15,143,220,160,0,0,0,0,0,0,0},{0,128,0,1,0,0,0,0,0,0,0},{70,165,166,0,0,0,0,0,0,0,0,0,0,0,0,0,0,0,0,0,0,0,0,0,0,0,0,0,0,0}},
   {13,4,7,30,255,{64,39,138,209,230,182,129,0,0,0,0},{0,0,0,0,0,127,0,0,0,0,0},{65,165,34,99,0,0,0,0,0,0,0,0,0,0,0,0,0,0,0,0,0,0,0,0,0,0,0,0,0,0}},
   {14,3,5,43,255,{12,5,215,158,196,0,0,0,0,0,0},{0,0,0,3,30,0,0,0,0,0,0},{70,165,64,0,0,0,0,0,0,0,0,0,0,0,0,0,0,0,0,0,0,0,0,0,0,0,0,0,0,0}},
   {15,4,7,1,255,{48,31,139,214,180,177,131,0,0,0,0},{0,0,0,0,0,0,0,0,0,0,0},{73,161,67,69,0,0,0,0,0,0,0,0,0,0,0,0,0,0,0,0,0,0,0,0,0,0,0,0,0,0}},
   {8,3,5,21,255,{21,33,95,109,146,0,0,0,0,0,0},{0,0,0,0,0,0,0,0,0,0,0},{164,6,166,0,0,0,0,0,0,0,0,0,0,0,0,0,0,0,0,0,0,0,0,0,0,0,0,0,0,0}},
   {9,3,7,46,255,{55,90,92,125,61,130,184,0,0,0,0},{136,0,0,0,0,0,1,0,0,0,0},{160,170,132,0,0,0,0,0,0,0,0,0,0,0,0,0,0,0,0,0,0,0,0,0,0,0,0,0,0,0}},
   {10,3,9,0,255,{72,17,67,26,25,42,97,229,113,0,0},{0,0,0,0,0,0,0,0,0,0,0},{164,1,8,0,0,0,0,0,0,0,0,0,0,0,0,0,0,0,0,0,0,0,0,0,0,0,0,0,0,0}},
   {11,4,6,21,255,{51,7,169,126,62,249,0,0,0,0,0},{0,0,0,0,0,0,0,0,0,0,0},{160,170,166,99,0,0,0,0,0,0,0,0,0,0,0,0,0,0,0,0,0,0,0,0,0,0,0,0,0,0}},
   {12,3,5,18,255,{53,1,94,111,144,0,0,0,0,0,0},{0,0,0,0,0,0,0,0,0,0,0},{160,170,107,0,0,0,0,0,0,0,0,0,0,0,0,0,0,0,0,0,0,0,0,0,0,0,0,0,0,0}},
   {13,3,6,16,255,{75,6,100,151,58,132,0,0,0,0,0},{0,0,0,0,0,0,0,0,0,0,0},{160,170,166,0,0,0,0,0,0,0,0,0,0,0,0,0,0,0,0,0,0,0,0,0,0,0,0,0,0,0}},
   {14,3,5,12,255,{19,37,175,210,147,0,0,0,0,0,0},{0,0,0,0,0,0,0,0,0,0,0},{160,170,67,0,0,0,0,0,0,0,0,0,0,0,0,0,0,0,0,0,0,0,0,0,0,0,0,0,0,0}},
   {15,3,6,42,255,{78,82,93,110,201,60,0,0,0,0,0},{0,0,0,0,0,31,0,0,0,0,0},{70,165,34,0,0,0,0,0,0,0,0,0,0,0,0,0,0,0,0,0,0,0,0,0,0,0,0,0,0,0}},
   {8,3,6,26,255,{74,76,28,127,63,232,0,0,0,0,0},{0,0,0,0,224,0,0,0,0,0,0},{105,72,107,0,0,0,0,0,0,0,0,0,0,0,0,0,0,0,0,0,0,0,0,0,0,0,0,0,0,0}},
   {9,3,6,31,255,{49,38,103,217,227,198,0,0,0,0,0},{0,0,0,0,0,0,0,0,0,0,0},{164,2,64,0,0,0,0,0,0,0,0,0,0,0,0,0,0,0,0,0,0,0,0,0,0,0,0,0,0,0}},
   {10,3,6,32,255,{79,41,141,171,106,238,0,0,0,0,0},{16,0,0,0,0,64,0,0,0,0,0},{105,98,67,0,0,0,0,0,0,0,0,0,0,0,0,0,0,0,0,0,0,0,0,0,0,0,0,0,0,0}},
   {11,3,7,28,255,{20,18,86,211,107,59,251,0,0,0,0},{0,0,0,0,0,0,0,0,0,0,0},{164,6,107,0,0,0,0,0,0,0,0,0,0,0,0,0,0,0,0,0,0,0,0,0,0,0,0,0,0,0}},
   {12,3,5,2,255,{11,30,140,164,154,0,0,0,0,0,0},{0,0,0,0,0,0,0,0,0,0,0},{164,9,132,0,0,0,0,0,0,0,0,0,0,0,0,0,0,0,0,0,0,0,0,0,0,0,0,0,0,0}},
   {13,3,5,7,255,{52,29,101,124,200,0,0,0,0,0,0},{0,0,0,0,0,0,0,0,0,0,0},{164,9,107,0,0,0,0,0,0,0,0,0,0,0,0,0,0,0,0,0,0,0,0,0,0,0,0,0,0,0}},
   {14,4,7,34,255,{77,43,137,173,218,179,236,0,0,0,0},{0,0,0,0,0,0,31,0,0,0,0},{164,1,34,69,0,0,0,0,0,0,0,0,0,0,0,0,0,0,0,0,0,0,0,0,0,0,0,0,0,0}},
   {15,3,4,14,255,{23,102,172,155,0,0,0,0,0,0,0},{7,0,0,0,0,0,0,0,0,0,0},{160,170,166,0,0,0,0,0,0,0,0,0,0,0,0,0,0,0,0,0,0,0,0,0,0,0,0,0,0,0}},
   {6,2,5,8,255,{9,69,142,119,57,0,0,0,0,0,0},{0,0,0,0,0,0,0,0,0,0,0},{98,33,0,0,0,0,0,0,0,0,0,0,0,0,0,0,0,0,0,0,0,0,0,0,0,0,0,0,0,0}},
   {7,9,7,14,255,{24,65,91,167,105,199,240,0,0,0,0},{0,0,0,0,0,192,0,0,0,0,0},{97,166,100,96,106,75,113,85,122,0,0,0,0,0,0,0,0,0,0,0,0,0,0,0,0,0,0,0,0,0}}},
  {{0,2,0,0},{9,20,0,0},{6,16,0,0},{9,15,0,0},{21,64,0,0},{16,64,0,0},{11,64,0,0},{6,64,0,0},{10,20,0,0},{1,11,0,0},{6,16,0,0},
   {0,6,0,0},{21,64,0,0},{16,64,0,0},{11,64,0,0},{6,64,0,0},{6,64,0,0},{0,3,0,0},{0,7,0,0},{5,21,0,0},{0,6,0,0},{0,1,0,0},
   {0,3,0,0},{1,64,0,0},{0,1,0,0},{5,16,0,0},{10,21,0,0},{9,15,0,0},{17,64,0,0},{0,7,0,0},{0,0,0,0},{4,14,0,0},{0,10,0,0},
   {0,6,0,0},{0,10,0,0},{7,64,0,0},{2,17,0,0},{0,6,0,0},{16,64,0,0},{0,6,0,0},{14,64,0,0},{0,4,0,0},{3,64,0,0},{0,5,0,0},
   {5,64,0,0},{0,5,0,0},{0,3,0,0},{7,16,0,0},{20,64,0,0},{0,0,0,0},{16,64,0,0},{6,20,0,0},{15,64,0,0},{3,11,0,0},{20,64,0,0},
   {0,9,0,0},{0,9,0,0},{0,9,0,0},{0,9,0,0},{0,5,0,0},{15,64,0,0},{9,64,0,0},{0,6,0,0},{15,64,0,0},{20,64,0,0},{3,15,0,0}},
  {{1,7,11,9,5,16,4,13,58,3,19,60,48,62,47,33,57,31,30,51,50,56,41,40,29,37,36,15,14,45,44,28,27,26,39,38,53,52,55,54,43,42,25,24,35,34,23,22,21,20,0,6,10,8,17,59,12,2,18,61,49,63,46,32},
   {21,1,7,11,9,5,17,59,13,3,19,60,48,62,46,32,57,31,30,51,50,56,41,29,37,36,15,14,45,44,28,40,27,26,39,38,53,52,55,54,43,42,25,24,35,34,23,22,20,0,6,10,8,4,16,58,12,2,18,61,49,63,47,33},
   {22,20,0,6,10,8,4,16,3,18,61,49,63,47,33,27,41,57,31,30,51,50,56,40,29,37,36,15,14,45,44,28,26,39,38,53,52,55,54,43,42,25,24,35,34,23,21,1,7,11,9,5,17,13,12,2,59,58,19,60,48,62,46,32},
   {61,41,40,55,54,25,24,43,42,53,52,57,56,31,30,21,20,35,34,23,27,26,22,7,6,11,29,28,10,15,14,17,39,51,50,37,36,38,16,9,8,1,0,5,4,19,18,13,45,44,12,3,2,60,48,49,58,59,32,33,63,62,47,46},
   {44,6,10,16,1,8,5,19,13,61,59,33,63,48,47,3,57,56,31,30,27,26,55,54,41,29,28,40,25,15,14,24,39,51,50,37,36,38,43,42,53,52,21,20,35,34,23,22,45,7,11,17,9,0,4,18,12,49,58,32,62,60,46,2},
   {59,33,62,48,47,2,55,54,41,40,25,24,57,56,31,30,43,42,53,52,21,27,26,20,35,34,29,28,23,22,15,14,7,39,51,37,36,50,38,6,11,10,17,16,9,8,1,0,5,45,44,4,19,18,13,12,3,61,49,58,63,32,60,46},
   {44,1,20,7,16,11,35,45,22,21,8,17,4,60,58,2,13,48,62,46,32,29,57,56,39,38,27,26,28,37,51,50,36,55,54,31,30,41,40,53,52,43,42,25,15,14,24,10,34,23,0,9,6,5,61,59,3,19,18,12,49,63,47,33},
   {14,7,17,5,45,3,19,12,59,43,42,25,24,53,41,40,52,55,54,31,29,28,30,57,39,38,56,27,26,37,36,51,50,11,10,35,34,23,22,1,0,21,20,9,15,8,6,16,4,44,2,18,13,58,60,61,48,49,62,63,46,47,32,33},
   {11,35,23,1,45,21,9,7,16,6,5,61,59,3,19,13,49,63,47,33,29,28,55,57,56,39,38,27,26,54,37,51,50,36,31,30,41,40,53,52,43,42,25,24,15,14,10,34,22,0,44,20,8,17,4,60,58,2,18,12,48,62,46,32},
   {12,16,19,5,3,58,63,48,46,61,33,43,42,41,40,53,55,54,52,25,24,31,30,57,56,27,39,38,26,21,37,36,51,50,20,29,28,45,44,35,34,7,6,15,14,23,22,1,0,11,10,9,8,17,13,18,4,59,49,62,2,47,60,32},
   {6,22,0,10,8,13,16,19,5,3,58,63,48,46,60,32,55,54,43,42,41,31,30,57,56,39,38,27,26,37,36,51,50,40,29,28,53,45,44,52,25,24,21,15,14,20,35,34,7,23,1,11,9,17,12,18,4,59,49,62,2,47,61,33},
   {16,12,18,4,2,59,41,40,43,42,53,52,25,24,21,20,55,54,35,34,7,31,30,57,56,39,38,27,26,6,37,36,51,50,23,29,28,45,44,22,1,0,11,15,14,10,9,8,17,13,19,5,3,58,48,49,62,63,46,47,60,61,32,33},
   {25,23,21,11,1,7,9,17,19,12,18,14,4,2,59,49,61,63,33,47,31,30,57,56,55,54,27,37,36,26,41,39,38,29,28,40,53,52,43,45,44,51,50,42,35,34,24,22,20,10,0,6,8,16,13,15,5,3,58,48,60,62,32,46},
   {35,25,23,21,11,1,7,9,16,13,17,18,14,5,3,58,48,60,62,32,46,57,56,31,30,27,37,36,26,55,39,38,29,28,54,41,40,53,52,45,44,51,50,43,42,34,24,22,20,10,0,6,8,19,15,12,4,2,59,49,61,63,33,47},
   {9,16,13,6,17,18,15,5,3,58,48,60,62,32,46,55,54,41,31,30,40,57,56,53,52,27,37,36,26,43,39,38,29,28,42,35,34,25,24,45,44,51,50,23,22,21,20,11,10,1,0,7,8,19,12,14,4,2,59,49,61,63,33,47},
   {14,4,2,44,59,43,42,25,55,54,24,35,41,40,53,52,34,23,22,31,57,56,30,27,26,21,29,51,50,28,20,11,10,7,6,39,38,1,0,9,8,37,36,17,16,19,18,13,12,15,5,3,45,58,48,49,60,61,62,63,46,47,32,33},
   {45,16,18,5,3,58,49,60,62,46,32,55,41,40,53,52,54,43,42,31,57,56,30,27,26,25,29,51,50,28,24,35,34,23,22,39,38,21,20,11,10,37,36,7,6,1,0,9,8,17,15,14,44,19,13,12,4,2,59,48,61,63,47,33},
   {14,17,44,19,18,12,4,2,59,49,61,63,47,33,41,40,53,52,55,31,30,57,56,27,26,54,43,51,50,29,28,42,25,24,35,39,38,34,23,22,21,20,37,36,11,10,7,6,1,0,15,9,8,45,16,13,5,3,58,48,60,62,46,32},
   {50,36,0,16,8,2,18,12,4,48,60,44,47,63,33,53,41,40,57,31,30,56,55,54,52,27,26,43,42,25,24,35,34,23,22,21,20,29,28,11,39,38,10,7,6,51,37,1,17,9,3,19,13,5,45,15,59,58,49,61,14,46,62,32},
   {45,15,49,25,24,35,34,23,22,21,20,43,42,11,53,52,41,40,57,31,30,56,55,54,27,26,10,7,6,1,0,17,16,9,8,3,2,29,28,19,39,38,18,13,51,50,37,36,12,5,4,44,14,48,58,59,60,61,46,47,62,63,32,33},
   {2,44,7,1,17,9,3,45,59,49,15,13,61,4,47,63,33,41,57,31,30,56,40,55,27,26,54,53,52,43,42,25,24,35,34,23,22,29,28,21,39,38,20,11,51,50,37,36,10,6,0,16,8,19,18,58,48,14,12,60,5,46,62,32},
   {20,10,9,6,45,44,0,7,16,58,18,14,12,4,63,2,49,61,47,33,31,30,41,57,29,28,39,38,27,26,37,36,56,40,55,54,53,51,50,52,43,42,25,24,35,34,23,22,21,11,1,8,17,59,19,15,13,5,3,62,48,60,46,32},
   {45,3,62,48,61,46,32,55,54,53,41,40,52,31,30,43,42,25,24,35,34,23,22,57,29,39,38,28,27,37,36,26,56,21,20,11,51,50,10,1,0,9,8,7,6,17,16,19,18,13,12,5,4,59,15,14,58,44,63,2,49,60,47,33},
   {12,4,2,45,59,62,55,54,53,52,43,41,40,42,31,30,25,24,35,34,23,22,21,57,56,29,39,38,28,27,37,36,26,20,11,10,1,51,50,0,9,8,7,6,17,16,19,18,13,5,3,44,58,14,15,63,48,49,60,61,46,47,32,33}},
  {{8,6,8,8,7,7,7,7},{0,0,2,0,1,2,3,1},{4,3,3,2,0,0,1,0},{7,7,6,6,6,6,6,6},
   {5,5,5,5,5,5,4,5},{6,8,9,7,8,8,8,8},{2,1,1,3,2,1,2,3},{12,9,1,4,4,3,1,6},
   {3,4,4,4,4,4,5,4},{1,2,0,1,3,3,0,2},{9,9,7,11,9,9,9,9},{10,10,10,9,10,10,10,10},
   {12,12,12,12,12,2,3,0},{8,2,8,7,8,8,8,7},{6,6,9,9,10,10,10,10},{5,5,0,6,6,1,1,2},
   {1,1,9,11,9,9,9,7},{11,11,11,10,11,11,11,11},{7,10,11,11,11,9,11,4},{2,8,10,10,12,2,3,0},
   {0,0,5,1,0,6,6,6},{14,14,13,0,1,0,5,4},{10,12,12,2,2,4,2,5},{5,5,10,10,12,2,3,10},
   {3,4,8,7,8,8,8,0},{9,11,7,12,9,11,9,1},{13,13,2,4,4,4,0,1},{3,4,4,5,5,5,4,5},
   {1,1,6,8,7,7,7,8},{11,7,2,5,6,1,0,2},{13,13,4,8,7,7,7,4},{8,2,6,6,0,6,6,1}},
  {{255,255,255,255,255,255,255,255},{255,255,255,255,255,255,255,255},{255,255,255,255,255,255,255,255},{255,255,255,255,255,255,255,255},
   {255,255,255,255,255,255,255,255},{255,255,255,255,255,255,255,255},{255,255,255,255,255,255,255,255},{12,10,6,26,26,9,15,20},
   {255,255,255,255,255,255,255,255},{255,255,255,255,255,255,255,255},{255,255,255,255,255,255,255,255},{255,255,255,255,255,255,255,255},
   {255,255,255,255,255,1,1,2},{0,9,0,5,5,5,5,0},{5,0,5,11,11,11,11,11},{4,4,9,3,3,6,2,9},
   {28,28,14,18,25,18,25,13},{255,255,255,255,255,255,255,255},{3,11,17,10,17,10,17,21},{6,5,11,17,12,12,12,12},
   {1,1,4,9,2,3,3,3},{255,255,255,1,1,2,8,8},{11,12,12,2,6,26,6,27},{15,15,19,19,19,19,19,14},
   {27,27,13,13,13,13,13,19},{10,17,10,12,10,17,10,26},{255,255,1,8,8,8,9,1},{8,8,8,4,4,4,4,4},
   {9,6,3,0,0,0,0,5},{17,3,26,27,15,15,26,15},{26,26,27,28,28,28,28,18},{13,13,28,15,20,20,20,25}}};

typedef CUresult (*EncodeFn)(CUtensorMap*, CUtensorMapDataType, cuuint32_t, void*, const cuuint64_t*, const cuuint64_t*, const cuuint32_t*,
                             const cuuint32_t*, CUtensorMapInterleave, CUtensorMapSwizzle, CUtensorMapL2promotion, CUtensorMapFloatOOBfill);

void make_map2(EncodeFn enc, CUtensorMap* m, const void* ptr, int rows, int cols, int box_rows) {
  cuuint64_t dim[2] = {(cuuint64_t)cols, (cuuint64_t)rows}, str[1] = {(cuuint64_t)cols * 2};
  cuuint32_t box[2] = {64, (cuuint32_t)box_rows}, es[2] = {1, 1};
  enc(m, CU_TENSOR_MAP_DATA_TYPE_BFLOAT16, 2, const_cast<void*>(ptr), dim, str, box, es, CU_TENSOR_MAP_INTERLEAVE_NONE, CU_TENSOR_MAP_SWIZZLE_128B,
      CU_TENSOR_MAP_L2_PROMOTION_L2_128B, CU_TENSOR_MAP_FLOAT_OOB_FILL_NONE);
}
void make_map3(EncodeFn enc, CUtensorMap* m, const void* ptr, int rows) {
  cuuint64_t dim[3] = {64, (cuuint64_t)rows, 9}, str[2] = {DM * 2, 128};
  cuuint32_t box[3] = {64, 32, 3}, es[3] = {1, 1, 1};
  enc(m, CU_TENSOR_MAP_DATA_TYPE_BFLOAT16, 3, const_cast<void*>(ptr), dim, str, box, es, CU_TENSOR_MAP_INTERLEAVE_NONE, CU_TENSOR_MAP_SWIZZLE_128B,
      CU_TENSOR_MAP_L2_PROMOTION_L2_128B, CU_TENSOR_MAP_FLOAT_OOB_FILL_NONE);
}

void make_map_t(EncodeFn enc, CUtensorMap* m, void* ptr, int width, int cols) {
  cuuint64_t dim[3] = {TP / 2, 2, 864}, str[2] = {TP * 2, TP * 4};
  cuuint32_t box[3] = {(cuuint32_t)width, 2, (cuuint32_t)cols}, es[3] = {1, 1, 1};
  enc(m, CU_TENSOR_MAP_DATA_TYPE_UINT32, 3, ptr, dim, str, box, es, CU_TENSOR_MAP_INTERLEAVE_NONE, cols == 64 ? CU_TENSOR_MAP_SWIZZLE_128B : CU_TENSOR_MAP_SWIZZLE_NONE,
      CU_TENSOR_MAP_L2_PROMOTION_NONE, CU_TENSOR_MAP_FLOAT_OOB_FILL_NONE);
}

int g_mode = -1;

}

extern "C" void kernel_launch(void* const* d_in, const int* in_sizes, int n_in, void* d_out, int out_size) {
  static EncodeFn enc = nullptr;
  static void* t_ptr = nullptr;
  if (!enc) {
    void* fn = nullptr;
    cudaDriverEntryPointQueryResult st;
    cudaGetDriverEntryPoint("cuTensorMapEncodeTiled", &fn, cudaEnableDefault, &st);
    enc = (EncodeFn)fn;
    cudaGetSymbolAddress(&t_ptr, g_T);
    cudaFuncSetAttribute(fused_kernel, cudaFuncAttributeMaxDynamicSharedMemorySize, SMEM_BYTES);
    if (g_mode < 0) {
      cudaLaunchConfig_t cfg = {};
      cfg.gridDim = dim3(2 * NCL); cfg.blockDim = dim3(384); cfg.dynamicSmemBytes = SMEM_BYTES;
      cudaLaunchAttribute at; at.id = cudaLaunchAttributeClusterDimension;
      at.val.clusterDim.x = 2; at.val.clusterDim.y = 1; at.val.clusterDim.z = 1;
      cfg.attrs = &at; cfg.numAttrs = 1;
      int nc = 0;
      g_mode = (cudaOccupancyMaxActiveClusters(&nc, fused_kernel, &cfg) == cudaSuccess && nc >= NCL) ? 1 : 0;
      (void)cudaGetLastError();
    }
  }
  Params p;
  make_map2(enc, &p.map_a[0], d_in[4], SEQ, DC, 128);
  make_map2(enc, &p.map_a[1], d_in[0], SEQ, DM, 128);
  make_map2(enc, &p.map_w[0], d_in[6], DC, 4096, 64);
  make_map2(enc, &p.map_w[1], d_in[7], DC, 4096, 64);
  make_map2(enc, &p.map_w[2], d_in[5], DM, 4096, 64);
  make_map2(enc, &p.map_w[3], d_in[1], DM, 1728, 64);
  make_map3(enc, &p.map_o[0], d_in[8], 4096);
  make_map3(enc, &p.map_o[1], d_in[2], DM);
  make_map_t(enc, &p.map_t[0], t_ptr, 32, 9);
  make_map_t(enc, &p.map_t[1], t_ptr, 40, 9);
  make_map_t(enc, &p.map_t[2], t_ptr, 32, 64);
  p.x = (const __nv_bfloat16*)d_in[0];
  p.gate_w = (const __nv_bfloat16*)d_in[9];
  make_map2(enc, &p.map_out, d_out, SEQ, DM, 64);
  p.out = (__nv_bfloat16*)d_out;
  p.zero = 0;
  auto launch = [&](int phases) {
    p.s = k_sched;
    for (int i = 0; i < NCL; i++) {
      Rec& r = p.s.r[i];
      if (!(phases & 1)) r.n1 = 0;
      if (!(phases & 2)) r.n2 = 0;
      if (!(phases & (p.s.task[i][1] == 64 ? 4 : 32))) r.p3 = 255;
      if (!(phases & 8)) r.bg = 255;
      const int u1 = r.n1 ? 8 + r.n1 * (8 + (r.slab >> 3)) : 0;
      int u2 = 0;
      for (int k = 0; k < r.n2; k++) u2 += 4 * (r.item[k] & 7) + 4;
      r.u1 = (uint8_t)u1; r.u2 = (uint8_t)u2;
      r.rot = (uint8_t)(((u1 % 10 + 1) >> 1) % 5);
      r.x3 = (uint8_t)((r.rot + u2) % 5 & 3);
      r.phases = (uint8_t)phases;
    }
    if (!(phases & 16))
      for (int i = 0; i < 256; i++) { p.s.slot[i >> 3][i & 7] = (uint8_t)(i >> 3); p.s.prev[i >> 3][i & 7] = 255; }
    fused_kernel<<<2 * NCL, 384, SMEM_BYTES>>>(p);
  };
  if (g_mode == 1) launch(63);
  else { launch(1); launch(10); launch(4); launch(32); }
}
```

```cpp
#include <cuda_runtime.h>
#include <cuda_bf16.h>
#include <cuda.h>
#include <stdint.h>

namespace {

constexpr int SEQ = 2048, DM = 576, DC = 512, NH = 32;
constexpr int NCL = 66;
constexpr uint32_t DESC_HI = 0x40000040u;

constexpr int SM_RING = 0;
constexpr int SM_BUF = 163840;
constexpr int SM_BAR = 229376;
constexpr int B_P1E = 0, B_P2E = 10, B_P3E = 15, B_P2F = 24, B_SF = 32, B_ORD = 36, B_LAD = 40, B_DONE = 41, B_FIN = 48;
constexpr int B_P3F = 56, B_OUT = 61, B_P1F = 64, B_SE = 74, B_QF = 80, B_LA = 84, B_NUM = 88;
constexpr uint64_t B_CNT = 0x11118245000ull;
constexpr int SMEM_BYTES = SM_BAR + B_NUM * 8 + 1024;

constexpr int F_QKVA = 32;
constexpr int F_GATE = 64;
constexpr int F_DONE = 65;
constexpr int F_CTX = 96;
constexpr int F_OUT = 96 + 8 * 64;
constexpr int F_KV = F_OUT + 64;
constexpr int F_Q = F_KV + 256;
constexpr int F_RD = F_Q + 256;
constexpr int F_NUM = F_RD + 256;

struct Rec {
  uint8_t slab;
  uint8_t n1, n2;
  uint8_t p3;
  uint8_t bg;
  uint8_t item[11];
  uint8_t last[11];
  uint8_t tile[32];
  uint8_t u1, u2;
  uint8_t rot, x3;
  uint8_t phases;
};
struct Sched {
  Rec r[NCL];
  uint8_t task[NCL][4];
  uint8_t p3_order[24][64];
  uint8_t slot[32][8];
  uint8_t prev[32][8];
};

#define SCHED_DECL static const

struct Params {
  CUtensorMap map_a[2];
  CUtensorMap map_w[4];
  CUtensorMap map_o[2];
  CUtensorMap map_t[3];
  CUtensorMap map_out;
  const __nv_bfloat16* x;
  const __nv_bfloat16* gate_w;
  __nv_bfloat16* out;
  int zero;
  alignas(64) Sched s;
};

__device__ __align__(1024) uint8_t g_Q[NH * 32 * 16384];
__device__ __align__(1024) uint8_t g_KV[2 * NH * 16 * 32768];
__device__ __align__(1024) uint8_t g_oA[32 * 576 * 128];
constexpr int TP = SEQ + 16;
__device__ __align__(1024) uint32_t g_T[864 * TP];
__device__ float g_gate[SEQ];
__device__ int g_flags[F_NUM];
#define PL(i)

__device__ __forceinline__ void mbar_arrive(uint32_t b) { asm volatile("mbarrier.arrive.shared::cta.b64 _, [%0];" ::"r"(b) : "memory"); }
__device__ __forceinline__ void mbar_arrive_cl(uint32_t b, int cnt) {
  asm volatile("mbarrier.arrive.shared::cluster.b64 _, [%0], %1;" ::"r"(b), "r"(cnt) : "memory");
}
__device__ __forceinline__ void mbar_wait(uint32_t b, int par) {
  asm volatile(
      "{\n.reg .pred p;\n.reg .u32 c;\n"
      "mbarrier.try_wait.parity.shared::cta.b64 p, [%0], %1;\n@p bra DN;\nmov.u32 c, 0;\n"
      "LP:\nmbarrier.try_wait.parity.shared::cta.b64 p, [%0], %1;\n@p bra DN;\n"
      "add.u32 c, c, 1;\nsetp.lt.u32 p, c, 4000000;\n@p bra LP;\ntrap;\nDN:\n}" ::"r"(b), "r"(par) : "memory");
}
__device__ __forceinline__ uint32_t mapa(uint32_t a, uint32_t cta) {
  uint32_t r; asm("mapa.shared::cluster.u32 %0, %1, %2;" : "=r"(r) : "r"(a), "r"(cta)); return r;
}
#define ELECT(ins) "{\n.reg .pred e;\nelect.sync _|e, 0xffffffff;\n@e " ins "\n}"
__device__ __forceinline__ void mbar_expect(uint32_t b, int bytes) {
  asm volatile(ELECT("mbarrier.arrive.expect_tx.shared::cta.b64 _, [%0], %1;") ::"r"(b), "r"(bytes) : "memory");
}
__device__ __forceinline__ void mbar_arrive_one(uint32_t b) { asm volatile(ELECT("mbarrier.arrive.shared::cta.b64 _, [%0];") ::"r"(b) : "memory"); }
constexpr uint64_t L2_NORMAL = 0x1000000000000000ull, L2_FIRST = 0x12F0000000000000ull;
__device__ __forceinline__ void bulk_load(uint32_t dst, const void* src, int bytes, uint32_t bar, uint64_t pol = L2_NORMAL) {
  asm volatile(ELECT("cp.async.bulk.shared::cluster.global.mbarrier::complete_tx::bytes.L2::cache_hint [%0], [%1], %2, [%3], %4;") ::"r"(dst), "l"(src), "r"(bytes), "r"(bar), "l"(pol) : "memory");
}
__device__ __forceinline__ void bulk_load_mc(uint32_t dst, const void* src, int bytes, uint32_t bar, uint64_t pol = L2_NORMAL) {
  asm volatile(ELECT("cp.async.bulk.shared::cluster.global.mbarrier::complete_tx::bytes.multicast::cluster.L2::cache_hint [%0], [%1], %2, [%3], %4, %5;") ::"r"(dst), "l"(src), "r"(bytes), "r"(bar), "h"((uint16_t)3), "l"(pol) : "memory");
}
__device__ __forceinline__ void bulk_store(void* dst, uint32_t src, int bytes, uint64_t pol = L2_NORMAL) {
  asm volatile(ELECT("cp.async.bulk.global.shared::cta.bulk_group.L2::cache_hint [%0], [%1], %2, %3;") ::"l"(dst), "r"(src), "r"(bytes), "l"(pol) : "memory");
}
__device__ __forceinline__ void tma2d(uint32_t dst, const CUtensorMap* m, int c0, int c1, uint32_t bar, uint64_t pol = L2_NORMAL) {
  asm volatile(ELECT("cp.async.bulk.tensor.2d.shared::cluster.global.mbarrier::complete_tx::bytes.L2::cache_hint [%0], [%1, {%3, %4}], [%2], %5;") ::"r"(dst), "l"(m), "r"(bar), "r"(c0), "r"(c1), "l"(pol) : "memory");
}
__device__ __forceinline__ void tma2d_mc(uint32_t dst, const CUtensorMap* m, int c0, int c1, uint32_t bar, uint64_t pol = L2_NORMAL) {
  asm volatile(ELECT("cp.async.bulk.tensor.2d.shared::cluster.global.mbarrier::complete_tx::bytes.multicast::cluster.L2::cache_hint [%0], [%1, {%3, %4}], [%2], %5, %6;") ::"r"(dst), "l"(m), "r"(bar), "r"(c0), "r"(c1), "h"((uint16_t)3), "l"(pol) : "memory");
}
__device__ __forceinline__ void tma3d(uint32_t dst, const CUtensorMap* m, int c0, int c1, int c2, uint32_t bar, uint64_t pol = L2_NORMAL) {
  asm volatile(ELECT("cp.async.bulk.tensor.3d.shared::cluster.global.mbarrier::complete_tx::bytes.L2::cache_hint [%0], [%1, {%3, %4, %5}], [%2], %6;") ::"r"(dst), "l"(m), "r"(bar), "r"(c0), "r"(c1), "r"(c2), "l"(pol) : "memory");
}
__device__ __forceinline__ void tma3d_mc(uint32_t dst, const CUtensorMap* m, int c0, int c1, int c2, uint32_t bar, uint64_t pol = L2_NORMAL) {
  asm volatile(ELECT("cp.async.bulk.tensor.3d.shared::cluster.global.mbarrier::complete_tx::bytes.multicast::cluster.L2::cache_hint [%0], [%1, {%3, %4, %5}], [%2], %6, %7;") ::"r"(dst), "l"(m), "r"(bar), "r"(c0), "r"(c1), "r"(c2), "h"((uint16_t)3), "l"(pol) : "memory");
}
__device__ __forceinline__ void tma2d_add(const CUtensorMap* m, uint32_t src, int c0, int c1) {
  asm volatile(ELECT("cp.reduce.async.bulk.tensor.2d.global.shared::cta.add.bulk_group [%0, {%2, %3}], [%1];") ::"l"(m), "r"(src), "r"(c0), "r"(c1) : "memory");
}
__device__ __forceinline__ void tma3d_store(const CUtensorMap* m, uint32_t src, int c0, int c1, int c2, uint64_t pol = L2_NORMAL) {
  asm volatile(ELECT("cp.async.bulk.tensor.3d.global.shared::cta.bulk_group.L2::cache_hint [%0, {%2, %3, %4}], [%1], %5;") ::"l"(m), "r"(src), "r"(c0), "r"(c1), "r"(c2), "l"(pol) : "memory");
}
__device__ __forceinline__ void tma2d_prefetch(const CUtensorMap* m, int c0, int c1, uint64_t pol = L2_NORMAL) {
  asm volatile(ELECT("cp.async.bulk.prefetch.tensor.2d.L2.global.L2::cache_hint [%0, {%1, %2}], %3;") ::"l"(m), "r"(c0), "r"(c1), "l"(pol) : "memory");
}
#define LAG 3
#define HINT 62
#define POL(bit) ((HINT >> (bit)) & 1 ? L2_FIRST : L2_NORMAL)
#define BULK_COMMIT() asm volatile("cp.async.bulk.commit_group;" ::: "memory")
#define BULK_WAIT(n) asm volatile("cp.async.bulk.wait_group %0;" ::"n"(n) : "memory")
#define BULK_WAIT_READ(n) asm volatile("cp.async.bulk.wait_group.read %0;" ::"n"(n) : "memory")
#define FENCE_ASYNC_SMEM() asm volatile("fence.proxy.async.shared::cta;" ::: "memory")
#define FENCE_ASYNC_ALL() asm volatile("fence.proxy.async;" ::: "memory")
#define WG_FENCE() asm volatile("wgmma.fence.sync.aligned;" ::: "memory")
#define WG_COMMIT() asm volatile("wgmma.commit_group.sync.aligned;" ::: "memory")
#define WG_WAIT(n) asm volatile("wgmma.wait_group.sync.aligned %0;" ::"n"(n) : "memory")
__device__ __forceinline__ void bar_sync(int id, int n) { asm volatile("bar.sync %0, %1;" ::"r"(id), "r"(n) : "memory"); }
__device__ __forceinline__ void bar_arrive(int id, int n) { asm volatile("bar.arrive %0, %1;" ::"r"(id), "r"(n) : "memory"); }
__device__ __forceinline__ void cluster_sync() {
  asm volatile("barrier.cluster.arrive.relaxed;\nbarrier.cluster.wait.acquire;" ::: "memory");
}
template <int N> __device__ __forceinline__ void pin(float (&r)[N]) {
#pragma unroll
  for (int i = 0; i < N; i++) asm volatile("" : "+f"(r[i])::"memory");
}
template <int N> __device__ __forceinline__ void pin(uint32_t (&r)[N]) {
#pragma unroll
  for (int i = 0; i < N; i++) asm volatile("" : "+r"(r[i])::"memory");
}
__device__ __forceinline__ uint32_t pack_bf16(float lo, float hi) {
  uint32_t r; asm("cvt.rn.bf16x2.f32 %0, %1, %2;" : "=r"(r) : "f"(hi), "f"(lo)); return r;
}
__device__ __forceinline__ float ex2(float x) { float r; asm("ex2.approx.ftz.f32 %0, %1;" : "=f"(r) : "f"(x)); return r; }
__device__ __forceinline__ void ldsm4(uint32_t a, uint32_t& r0, uint32_t& r1, uint32_t& r2, uint32_t& r3) {
  asm volatile("ldmatrix.sync.aligned.m8n8.x4.shared.b16 {%0,%1,%2,%3}, [%4];" : "=r"(r0), "=r"(r1), "=r"(r2), "=r"(r3) : "r"(a) : "memory");
}
__device__ __forceinline__ void stsm4(uint32_t a, uint32_t r0, uint32_t r1, uint32_t r2, uint32_t r3) {
  asm volatile("stmatrix.sync.aligned.m8n8.x4.shared.b16 [%0], {%1,%2,%3,%4};" ::"r"(a), "r"(r0), "r"(r1), "r"(r2), "r"(r3) : "memory");
}
__device__ __forceinline__ void flag_add(int idx, int v = 1) {
  asm volatile(ELECT("red.release.gpu.global.add.s32 [%0], %1;") ::"l"(g_flags + idx), "r"(v) : "memory");
}
__device__ __forceinline__ void flag_add_rx(int idx) {
  asm volatile(ELECT("red.relaxed.gpu.global.add.s32 [%0], 1;") ::"l"(g_flags + idx) : "memory");
}
template <bool ACQ, int NS = 32> __device__ __forceinline__ void flag_wait(int idx, int target) {
  int n = 0;
  while (true) {
    int v;
    if (ACQ) asm volatile("ld.acquire.gpu.global.s32 %0, [%1];" : "=r"(v) : "l"(g_flags + idx) : "memory");
    else asm volatile("ld.relaxed.gpu.global.s32 %0, [%1];" : "=r"(v) : "l"(g_flags + idx) : "memory");
    if (__all_sync(0xffffffffu, v >= target)) break;
    if (++n > 20000000) __trap();
    __nanosleep(NS);
  }
}
__device__ __forceinline__ int flag_peek(int idx) {
  int v;
  asm volatile("ld.relaxed.gpu.global.s32 %0, [%1];" : "=r"(v) : "l"(g_flags + idx) : "memory");
  return v;
}
__device__ __forceinline__ void mask_wait(uint32_t& ready, int bit, int idx, int target) {
  for (int n = 0; !((ready >> bit) & 1); n++) {
    int v;
    if (n) { __nanosleep(32); if (n > 20000000) __trap(); }
    asm volatile("ld.relaxed.gpu.global.s32 %0, [%1];" : "=r"(v) : "l"(g_flags + idx) : "memory");
    ready = __ballot_sync(0xffffffffu, v >= target);
  }
}
__device__ __forceinline__ uint32_t desc_lo(uint32_t addr, uint32_t lbo) { return ((addr & 0x3FFFFu) >> 4) | ((lbo >> 4) << 16); }
#define PROF(role, i)
#define PROFX(cond, i)
#define PROFB(i)
#define PROFG(i)

template <int TB, int TA = 0> __device__ __forceinline__ void wgmma_ss64(float (&d)[32], uint32_t alo, uint32_t blo, int sd) {
  asm volatile("{\n.reg .pred p;\n.reg .b64 da, db;\n"
    "setp.ne.b32 p, %34, 0;\nmov.b64 da, {%32, %36};\nmov.b64 db, {%33, %36};\n"
    "wgmma.mma_async.sync.aligned.m64n64k16.f32.bf16.bf16 "
    "{%0,%1,%2,%3,%4,%5,%6,%7,%8,%9,%10,%11,%12,%13,%14,%15,%16,%17,%18,%19,%20,%21,%22,%23,"
    "%24,%25,%26,%27,%28,%29,%30,%31}, "
    "da, db, p, 1, 1, %37, %35;\n}\n"
    : "+f"(d[0]),"+f"(d[1]),"+f"(d[2]),"+f"(d[3]),"+f"(d[4]),"+f"(d[5]),"+f"(d[6]),"+f"(d[7]),"+f"(d[8]),"+f"(d[9]),"+f"(d[10]),"+f"(d[11]),
      "+f"(d[12]),"+f"(d[13]),"+f"(d[14]),"+f"(d[15]),"+f"(d[16]),"+f"(d[17]),"+f"(d[18]),"+f"(d[19]),"+f"(d[20]),"+f"(d[21]),"+f"(d[22]),"+f"(d[23]),
      "+f"(d[24]),"+f"(d[25]),"+f"(d[26]),"+f"(d[27]),"+f"(d[28]),"+f"(d[29]),"+f"(d[30]),"+f"(d[31])
    : "r"(alo), "r"(blo), "r"(sd), "n"(TB), "r"(DESC_HI), "n"(TA));
}
template <int TB, int TA = 0> __device__ __forceinline__ void wgmma_ss128(float (&d)[64], uint32_t alo, uint32_t blo, int sd) {
  asm volatile("{\n.reg .pred p;\n.reg .b64 da, db;\n"
    "setp.ne.b32 p, %66, 0;\nmov.b64 da, {%64, %68};\nmov.b64 db, {%65, %68};\n"
    "wgmma.mma_async.sync.aligned.m64n128k16.f32.bf16.bf16 "
    "{%0,%1,%2,%3,%4,%5,%6,%7,%8,%9,%10,%11,%12,%13,%14,%15,%16,%17,%18,%19,%20,%21,%22,%23,"
    "%24,%25,%26,%27,%28,%29,%30,%31,%32,%33,%34,%35,%36,%37,%38,%39,%40,%41,%42,%43,%44,%45,%46,%47,"
    "%48,%49,%50,%51,%52,%53,%54,%55,%56,%57,%58,%59,%60,%61,%62,%63}, "
    "da, db, p, 1, 1, %69, %67;\n}\n"
    : "+f"(d[0]),"+f"(d[1]),"+f"(d[2]),"+f"(d[3]),"+f"(d[4]),"+f"(d[5]),"+f"(d[6]),"+f"(d[7]),"+f"(d[8]),"+f"(d[9]),"+f"(d[10]),"+f"(d[11]),
      "+f"(d[12]),"+f"(d[13]),"+f"(d[14]),"+f"(d[15]),"+f"(d[16]),"+f"(d[17]),"+f"(d[18]),"+f"(d[19]),"+f"(d[20]),"+f"(d[21]),"+f"(d[22]),"+f"(d[23]),
      "+f"(d[24]),"+f"(d[25]),"+f"(d[26]),"+f"(d[27]),"+f"(d[28]),"+f"(d[29]),"+f"(d[30]),"+f"(d[31]),"+f"(d[32]),"+f"(d[33]),"+f"(d[34]),"+f"(d[35]),
      "+f"(d[36]),"+f"(d[37]),"+f"(d[38]),"+f"(d[39]),"+f"(d[40]),"+f"(d[41]),"+f"(d[42]),"+f"(d[43]),"+f"(d[44]),"+f"(d[45]),"+f"(d[46]),"+f"(d[47]),
      "+f"(d[48]),"+f"(d[49]),"+f"(d[50]),"+f"(d[51]),"+f"(d[52]),"+f"(d[53]),"+f"(d[54]),"+f"(d[55]),"+f"(d[56]),"+f"(d[57]),"+f"(d[58]),"+f"(d[59]),
      "+f"(d[60]),"+f"(d[61]),"+f"(d[62]),"+f"(d[63])
    : "r"(alo), "r"(blo), "r"(sd), "n"(TB), "r"(DESC_HI), "n"(TA));
}
template <int TB> __device__ __forceinline__ void wgmma_rs128(float (&d)[64], uint32_t a0, uint32_t a1, uint32_t a2, uint32_t a3, uint32_t blo, int sd) {
  asm volatile("{\n.reg .pred p;\n.reg .b64 db;\n"
    "setp.ne.b32 p, %69, 0;\nmov.b64 db, {%68, %71};\n"
    "wgmma.mma_async.sync.aligned.m64n128k16.f32.bf16.bf16 "
    "{%0,%1,%2,%3,%4,%5,%6,%7,%8,%9,%10,%11,%12,%13,%14,%15,%16,%17,%18,%19,%20,%21,%22,%23,"
    "%24,%25,%26,%27,%28,%29,%30,%31,%32,%33,%34,%35,%36,%37,%38,%39,%40,%41,%42,%43,%44,%45,%46,%47,"
    "%48,%49,%50,%51,%52,%53,%54,%55,%56,%57,%58,%59,%60,%61,%62,%63}, "
    "{%64,%65,%66,%67}, db, p, 1, 1, %70;\n}\n"
    : "+f"(d[0]),"+f"(d[1]),"+f"(d[2]),"+f"(d[3]),"+f"(d[4]),"+f"(d[5]),"+f"(d[6]),"+f"(d[7]),"+f"(d[8]),"+f"(d[9]),"+f"(d[10]),"+f"(d[11]),
      "+f"(d[12]),"+f"(d[13]),"+f"(d[14]),"+f"(d[15]),"+f"(d[16]),"+f"(d[17]),"+f"(d[18]),"+f"(d[19]),"+f"(d[20]),"+f"(d[21]),"+f"(d[22]),"+f"(d[23]),
      "+f"(d[24]),"+f"(d[25]),"+f"(d[26]),"+f"(d[27]),"+f"(d[28]),"+f"(d[29]),"+f"(d[30]),"+f"(d[31]),"+f"(d[32]),"+f"(d[33]),"+f"(d[34]),"+f"(d[35]),
      "+f"(d[36]),"+f"(d[37]),"+f"(d[38]),"+f"(d[39]),"+f"(d[40]),"+f"(d[41]),"+f"(d[42]),"+f"(d[43]),"+f"(d[44]),"+f"(d[45]),"+f"(d[46]),"+f"(d[47]),
      "+f"(d[48]),"+f"(d[49]),"+f"(d[50]),"+f"(d[51]),"+f"(d[52]),"+f"(d[53]),"+f"(d[54]),"+f"(d[55]),"+f"(d[56]),"+f"(d[57]),"+f"(d[58]),"+f"(d[59]),
      "+f"(d[60]),"+f"(d[61]),"+f"(d[62]),"+f"(d[63])
    : "r"(a0), "r"(a1), "r"(a2), "r"(a3), "r"(blo), "r"(sd), "n"(TB), "r"(DESC_HI));
}
template <int TB, int TA = 0> __device__ __forceinline__ void wgmma_ss192(float (&d)[96], uint32_t alo, uint32_t blo, int sd) {
  asm volatile("{\n.reg .pred p;\n.reg .b64 da, db;\n"
    "setp.ne.b32 p, %98, 0;\nmov.b64 da, {%96, %100};\nmov.b64 db, {%97, %100};\n"
    "wgmma.mma_async.sync.aligned.m64n192k16.f32.bf16.bf16 "
    "{%0,%1,%2,%3,%4,%5,%6,%7,%8,%9,%10,%11,%12,%13,%14,%15,%16,%17,%18,%19,%20,%21,%22,%23,"
    "%24,%25,%26,%27,%28,%29,%30,%31,%32,%33,%34,%35,%36,%37,%38,%39,%40,%41,%42,%43,%44,%45,%46,%47,"
    "%48,%49,%50,%51,%52,%53,%54,%55,%56,%57,%58,%59,%60,%61,%62,%63,%64,%65,%66,%67,%68,%69,%70,%71,"
    "%72,%73,%74,%75,%76,%77,%78,%79,%80,%81,%82,%83,%84,%85,%86,%87,%88,%89,%90,%91,%92,%93,%94,%95}, "
    "da, db, p, 1, 1, %101, %99;\n}\n"
    : "+f"(d[0]),"+f"(d[1]),"+f"(d[2]),"+f"(d[3]),"+f"(d[4]),"+f"(d[5]),"+f"(d[6]),"+f"(d[7]),"+f"(d[8]),"+f"(d[9]),"+f"(d[10]),"+f"(d[11]),
      "+f"(d[12]),"+f"(d[13]),"+f"(d[14]),"+f"(d[15]),"+f"(d[16]),"+f"(d[17]),"+f"(d[18]),"+f"(d[19]),"+f"(d[20]),"+f"(d[21]),"+f"(d[22]),"+f"(d[23]),
      "+f"(d[24]),"+f"(d[25]),"+f"(d[26]),"+f"(d[27]),"+f"(d[28]),"+f"(d[29]),"+f"(d[30]),"+f"(d[31]),"+f"(d[32]),"+f"(d[33]),"+f"(d[34]),"+f"(d[35]),
      "+f"(d[36]),"+f"(d[37]),"+f"(d[38]),"+f"(d[39]),"+f"(d[40]),"+f"(d[41]),"+f"(d[42]),"+f"(d[43]),"+f"(d[44]),"+f"(d[45]),"+f"(d[46]),"+f"(d[47]),
      "+f"(d[48]),"+f"(d[49]),"+f"(d[50]),"+f"(d[51]),"+f"(d[52]),"+f"(d[53]),"+f"(d[54]),"+f"(d[55]),"+f"(d[56]),"+f"(d[57]),"+f"(d[58]),"+f"(d[59]),
      "+f"(d[60]),"+f"(d[61]),"+f"(d[62]),"+f"(d[63]),"+f"(d[64]),"+f"(d[65]),"+f"(d[66]),"+f"(d[67]),"+f"(d[68]),"+f"(d[69]),"+f"(d[70]),"+f"(d[71]),
      "+f"(d[72]),"+f"(d[73]),"+f"(d[74]),"+f"(d[75]),"+f"(d[76]),"+f"(d[77]),"+f"(d[78]),"+f"(d[79]),"+f"(d[80]),"+f"(d[81]),"+f"(d[82]),"+f"(d[83]),
      "+f"(d[84]),"+f"(d[85]),"+f"(d[86]),"+f"(d[87]),"+f"(d[88]),"+f"(d[89]),"+f"(d[90]),"+f"(d[91]),"+f"(d[92]),"+f"(d[93]),"+f"(d[94]),"+f"(d[95])
    : "r"(alo), "r"(blo), "r"(sd), "n"(TB), "r"(DESC_HI), "n"(TA));
}

struct Ctx {
  uint32_t sm;
  uint32_t bar;
  uint32_t rbar;
  int cl, rank, wg, warp, lane, phases;
};
__device__ __forceinline__ void release(const Ctx& c, int b, int cnt = 1) {
  if (c.lane < 2) mbar_arrive_cl(c.rbar + b * 8, cnt);
}
#define HK 5
#define NPRO 6
#define ZLEAD 14
#define PFM 7
#define PF1 1
constexpr float SM_SCALE = 0.08838834764831845f * 1.4426950408889634f;
constexpr float SM_HI = 1.8446744e19f, SM_LO = 5.4210109e-20f;
constexpr int ORDER = 1;

__device__ __forceinline__ void stage_tile(const float (&a)[64], uint32_t buf, const Ctx& c, float s0, float s1) {
  const int row = (c.lane & 7) + ((c.lane >> 3) & 1) * 8;
  const uint32_t base = buf + (c.warp * 16 + row) * 128 + (((c.lane >> 4) ^ (row & 7)) << 4);
#pragma unroll
  for (int i = 0; i < 8; i++)
    stsm4((base ^ ((i & 3) << 5)) + (i >> 2) * 8192, pack_bf16(a[8 * i] * s0, a[8 * i + 1] * s0), pack_bf16(a[8 * i + 2] * s1, a[8 * i + 3] * s1),
          pack_bf16(a[8 * i + 4] * s0, a[8 * i + 5] * s0), pack_bf16(a[8 * i + 6] * s1, a[8 * i + 7] * s1));
}

__device__ __forceinline__ void p1_epilogue(const Params& p, const Ctx& c, const float (&acc)[64], int t, int type) {
  const int tile = p.s.r[c.cl].tile[t] & 63, b = c.wg * 2 + 1;
  mbar_wait(c.bar + (B_SE + b) * 8, (t & 1) ^ 1);
  if (type && tile >= 32) {
    const int r = 2 * (c.lane & 3) + ((c.lane >> 2) & 1);
    const uint32_t dst = c.sm + SM_BUF + b * 16384 + r * 128 + (((c.warp * 2) ^ r) << 4) + (c.lane >> 3) * 4;
#pragma unroll
    for (int i = 0; i < 16; i++) {
      asm volatile("st.shared.u32 [%0], %1;" ::"r"(dst + i * 1024), "r"(pack_bf16(acc[4 * i], acc[4 * i + 1])) : "memory");
      asm volatile("st.shared.u32 [%0], %1;" ::"r"((dst ^ 16) + i * 1024), "r"(pack_bf16(acc[4 * i + 2], acc[4 * i + 3])) : "memory");
    }
  } else {
    if (type) stage_tile(acc, c.sm + SM_BUF + b * 16384, c, SM_SCALE, SM_SCALE);
    else stage_tile(acc, c.sm + SM_BUF + b * 16384, c, 1.f, 1.f);
  }
  FENCE_ASYNC_SMEM();
  __syncwarp();
  if (c.lane == 0) mbar_arrive(c.bar + (B_SF + b) * 8);
}

__device__ __forceinline__ void p1_consumer(const Params& p, const Ctx& c) {
  const int n = p.s.r[c.cl].n1;
  const int type = p.s.r[c.cl].slab >> 3;
  const uint32_t bdesc = desc_lo(c.sm + SM_RING, 8192), adesc = desc_lo(c.sm + SM_BUF + 32768 + c.wg * 8192, 16);
  uint32_t A[128];
  float acc[64] = {};
  int slot = 0, par = 0;
  auto next = [&]() { if (++slot == 10) { slot = 0; par ^= 1; } };
  {
    const int row = (c.lane & 7) + ((c.lane >> 3) & 1) * 8;
    const uint32_t base = c.sm + SM_RING + (c.wg * 64 + c.warp * 16 + row) * 128 + (((c.lane >> 4) ^ (row & 7)) << 4);
    if (c.wg == 1) bar_sync(ORDER + 1, 256);
    int pa = -1, pb = -1;
    if (type) {
      mbar_wait(c.bar + B_P1F * 8, 0);
      WG_FENCE();
#pragma unroll
      for (int kk = 0; kk < 4; kk++) wgmma_ss128<1>(acc, adesc + kk * 2, bdesc + kk * 128, kk != 0);
      WG_COMMIT();
      pb = 0; slot = 1;
    }
#pragma unroll
    for (int kb = 0; kb < 8; kb++) {
      const int sa = slot;
      mbar_wait(c.bar + (B_P1F + slot) * 8, par);
      if (kb == 0) PROF(c.wg, 5);
      next();
      mbar_wait(c.bar + (B_P1F + slot) * 8, par);
      PROF(c.wg, 6 + 2 * kb);
      WG_FENCE();
#pragma unroll
      for (int kk = 0; kk < 4; kk++)
        wgmma_ss128<1>(acc, desc_lo(c.sm + SM_RING + c.wg * 8192, 16) + sa * 1024 + kk * 2, bdesc + slot * 1024 + kk * 128, (kb | kk) != 0 ? 1 : type);
      WG_COMMIT();
      if (kb == 1 && c.wg == 0) bar_arrive(ORDER + 1, 256);
#pragma unroll
      for (int kk = 0; kk < 4; kk++) ldsm4((base ^ (kk << 5)) + sa * 16384, A[kb * 16 + kk * 4], A[kb * 16 + kk * 4 + 1], A[kb * 16 + kk * 4 + 2], A[kb * 16 + kk * 4 + 3]);
      WG_WAIT(1);
      if (kb > 0) release(c, B_P1E + pa);
      if (kb > 0 || pb >= 0) release(c, B_P1E + pb);
      pa = sa; pb = slot;
      next();
    }
    WG_WAIT(0);
    __syncwarp();
    release(c, B_P1E + pa);
    release(c, B_P1E + pb);
    pin(acc);
    PROF(c.wg, 1);
    p1_epilogue(p, c, acc, 0, type);
    PROF(c.wg, 2);
  }
  for (int t = 1; t < n; t++) {
    bar_sync(ORDER + c.wg, 256);
    int prev1 = -1, prev2 = -1;
    if (type) {
      mbar_wait(c.bar + (B_P1F + slot) * 8, par);
      WG_FENCE();
#pragma unroll
      for (int kk = 0; kk < 4; kk++) wgmma_ss128<1>(acc, adesc + kk * 2, bdesc + slot * 1024 + kk * 128, kk != 0);
      WG_COMMIT();
      prev1 = slot;
      next();
    }
#pragma unroll
    for (int kb = 0; kb < 8; kb++) {
      mbar_wait(c.bar + (B_P1F + slot) * 8, par);
      WG_FENCE();
      const uint32_t d = bdesc + slot * 1024;
#pragma unroll
      for (int kk = 0; kk < 4; kk++)
        wgmma_rs128<1>(acc, A[kb * 16 + kk * 4], A[kb * 16 + kk * 4 + 1], A[kb * 16 + kk * 4 + 2], A[kb * 16 + kk * 4 + 3], d + kk * 128, (kb | kk) != 0 ? 1 : type);
      WG_COMMIT();
      if (kb == HK) {
        if (t + 1 < n || c.wg == 0) bar_arrive(ORDER + (c.wg ^ 1), 256);
      }
      if (kb > 0) { WG_WAIT(2); if (kb > 1 || prev2 >= 0) release(c, B_P1E + prev2); }
      prev2 = prev1; prev1 = slot;
      next();
    }
    WG_WAIT(1);
    release(c, B_P1E + prev2);
    WG_WAIT(0);
    pin(acc);
    release(c, B_P1E + prev1);
    p1_epilogue(p, c, acc, t, type);
    PROF(c.wg, 3);
  }
}

__device__ __forceinline__ void p1_producer(const Params& p, const Ctx& c) {
  const int n = p.s.r[c.cl].n1;
  const int type = p.s.r[c.cl].slab >> 3, grp = p.s.r[c.cl].slab & 7;
  int slot = NPRO % 10, par = NPRO < 10;
#pragma unroll 1
  for (int t = 0; t < n; t++) {
    const int tile = p.s.r[c.cl].tile[t] & 63;
    const CUtensorMap* m = &p.map_w[type * 2 + (tile >> 5)];
    const int n0 = (tile & 31) * 128 + c.rank * 64;
    const int ptile = p.s.r[c.cl].tile[t + PF1 < n ? t + PF1 : t];
    const CUtensorMap* pm = &p.map_w[type * 2 + ((ptile >> 5) & 1)];
    if (t == 7 && (c.phases & 16)) flag_wait<true>(F_GATE, 256);
#pragma unroll 1
    for (int kb = t ? -type : (NPRO - type) >> 1; kb < 8; kb++) {
      if (t == 0 && 2 * kb + type >= NPRO) {
        mbar_wait(c.bar + (B_P1E + slot) * 8, par);
        mbar_expect(c.bar + (B_P1F + slot) * 8, 16384);
        tma2d(c.sm + SM_RING + slot * 16384, &p.map_a[type], kb * 64, grp * 256 + c.rank * 128, c.bar + (B_P1F + slot) * 8);
        if (++slot == 10) { slot = 0; par ^= 1; }
      }
      mbar_wait(c.bar + (B_P1E + slot) * 8, par);
      mbar_expect(c.bar + (B_P1F + slot) * 8, 16384);
      tma2d_mc(c.sm + SM_RING + slot * 16384 + c.rank * 8192, m, n0, kb < 0 ? 512 : kb * 64, c.bar + (B_P1F + slot) * 8);
      if (t == 0 && kb == 1) PROF(2, 61);
      if (t == 0 && kb == 3) PROF(2, 62);
      if (t + PF1 < n && t > 0 && ((ptile & 64) || ((ptile & 128) && ((kb ^ grp) & PFM) == 0))) tma2d_prefetch(pm, (ptile & 31) * 128 + c.rank * 64, kb < 0 ? 512 : kb * 64);
      if (++slot == 10) { slot = 0; par ^= 1; }
    }
  }
}

__device__ __forceinline__ int p1_storer(const Params& p, const Ctx& c) {
  const int n = p.s.r[c.cl].n1;
  const int type = p.s.r[c.cl].slab >> 3, grp = p.s.r[c.cl].slab & 7;
  for (int i = 0; i < 2 * n; i++) {
    const int t = i >> 1, w = i & 1, b = w * 2 + 1;
    const int tile = p.s.r[c.cl].tile[t] & 63;
    mbar_wait(c.bar + (B_SF + b) * 8, t & 1);
    const uint32_t src = c.sm + SM_BUF + b * 16384;
    int f = (type ? F_Q : F_KV) + (tile & 31) * 8 + grp;
    if (type == 0) {
      const int prev = p.s.prev[tile & 31][grp];
      if (prev != 255 && w == 0) {
        if (grp >= 2) flag_wait<false>(F_RD + prev * 8 + grp, 8 - grp);
        else flag_wait<false>(F_CTX + max(c.lane & 7, grp) * 64 + prev, 4);
      }
      uint8_t* dst = g_KV + (size_t)(((tile & 32) + p.s.slot[tile & 31][grp]) * 16 + grp * 2 + c.rank) * 32768 + w * 8192;
      bulk_store(dst, src, 8192);
      bulk_store(dst + 16384, src + 8192, 8192);
    } else if (tile < 32) {
      bulk_store(g_Q + (size_t)(tile * 32 + grp * 4 + c.rank * 2 + w) * 16384, src, 16384);
    } else {
      tma3d_store(&p.map_t[2], src, 8 + (grp * 4 + c.rank * 2 + w) * 32, 0, (tile - 32) * 64);
      f = F_QKVA + grp * 4 + ((0xE4390900u >> (2 * (tile - 30))) & 3);
    }
    BULK_COMMIT();
    BULK_WAIT(0);
    mbar_arrive_one(c.bar + (B_SE + b) * 8);
    if (i == 2 * n - 1) return f;
    if (w) flag_add(f, 2);
  }
  return -1;
}

__device__ __forceinline__ int p2_buf(int w, int i) { return w * 2 + (i & 1); }
__device__ __forceinline__ int p2_blk(int rank, int w, int i) { return ((i ^ w) & 1) == 0 ? 3 - rank : rank; }

template <int N>
__device__ __forceinline__ void row_max(const float (&s)[N], float& m0, float& m1) {
  float a0 = fmaxf(s[0], s[1]), a1 = fmaxf(s[2], s[3]);
#pragma unroll
  for (int i = 1; i < N / 4; i++) {
    m0 = fmaxf(m0, s[4 * i]); a0 = fmaxf(a0, s[4 * i + 1]);
    m1 = fmaxf(m1, s[4 * i + 2]); a1 = fmaxf(a1, s[4 * i + 3]);
  }
  m0 = fmaxf(m0, a0); m1 = fmaxf(m1, a1);
  m0 = fmaxf(m0, __shfl_xor_sync(0xffffffffu, m0, 1));
  m1 = fmaxf(m1, __shfl_xor_sync(0xffffffffu, m1, 1));
  m0 = fmaxf(m0, __shfl_xor_sync(0xffffffffu, m0, 2));
  m1 = fmaxf(m1, __shfl_xor_sync(0xffffffffu, m1, 2));
}
template <bool SUB, int N>
__device__ __forceinline__ void row_exp(const float (&s)[N], uint32_t (&P)[32], float m0, float m1, float& t0, float& t1) {
  float u0 = 0.f, u1 = 0.f;
  t0 = t1 = 0.f;
#pragma unroll
  for (int i = 0; i < N / 4; i++) {
    const float e0 = ex2(SUB ? s[4 * i] - m0 : s[4 * i]), e1 = ex2(SUB ? s[4 * i + 1] - m0 : s[4 * i + 1]);
    const float e2 = ex2(SUB ? s[4 * i + 2] - m1 : s[4 * i + 2]), e3 = ex2(SUB ? s[4 * i + 3] - m1 : s[4 * i + 3]);
    if (i == 0) { t0 = e0; u0 = e1; t1 = e2; u1 = e3; }
    else { t0 += e0; u0 += e1; t1 += e2; u1 += e3; }
    P[2 * i] = pack_bf16(e0, e1);
    P[2 * i + 1] = pack_bf16(e2, e3);
  }
#pragma unroll
  for (int i = N / 2; i < 32; i++) P[i] = 0;
  pin(P);
  t0 += u0; t1 += u1;
}
template <int N>
__device__ __forceinline__ void causal_mask(float (&s)[N], int thr) {
#pragma unroll
  for (int i = 0; i < 8; i++) {
    if (8 * i > thr) s[N - 32 + 4 * i] = -INFINITY;
    if (8 * i + 1 > thr) s[N - 32 + 4 * i + 1] = -INFINITY;
    if (8 * i - 8 > thr) s[N - 32 + 4 * i + 2] = -INFINITY;
    if (8 * i - 7 > thr) s[N - 32 + 4 * i + 3] = -INFINITY;
  }
}
__device__ __forceinline__ void issue_qk(float (&s)[32], uint32_t qd, uint32_t kd) {
  WG_FENCE();
#pragma unroll
  for (int kk = 0; kk < 8; kk++) wgmma_ss64<0>(s, qd + (kk >> 2) * 512 + (kk & 3) * 2, kd + (kk >> 2) * 1024 + (kk & 3) * 2, kk != 0);
  WG_COMMIT();
}
__device__ __forceinline__ void issue_qk(float (&s)[64], uint32_t qd, uint32_t kd) {
  WG_FENCE();
#pragma unroll
  for (int kk = 0; kk < 8; kk++) wgmma_ss128<0>(s, qd + (kk >> 2) * 512 + (kk & 3) * 2, kd + (kk >> 2) * 1024 + (kk & 3) * 2, kk != 0);
  WG_COMMIT();
}
template <int NK>
__device__ __forceinline__ void issue_pv(float (&o)[64], const uint32_t (&P)[32], uint32_t vd, int acc) {
  WG_FENCE();
#pragma unroll
  for (int kk = 0; kk < NK; kk++) wgmma_rs128<1>(o, P[4 * kk], P[4 * kk + 1], P[4 * kk + 2], P[4 * kk + 3], vd + kk * 128, kk != 0 ? 1 : acc);
  WG_COMMIT();
}
__device__ __forceinline__ void stage_done(const Ctx& c, int b) {
  FENCE_ASYNC_SMEM();
  __syncwarp();
  if (c.lane == 0) mbar_arrive(c.bar + (B_SF + b) * 8);
}
__device__ __forceinline__ void p2_epilogue(const float (&o)[64], float s0, float s1, const Ctx& c, int b) {
  stage_tile(o, c.sm + SM_BUF + b * 16384, c, s0, s1);
  stage_done(c, b);
}

struct P2State {
  float m0, m1, l0, l1;
  bool shift;
  float e0, e1;
  int ks;
  int wi, ai;
  uint32_t wb, ab;
  uint32_t qd;
};
#define PROFZ()
__device__ __forceinline__ int wrap5(int q) { return q >= 5 ? q - 5 : q; }
__device__ __forceinline__ void turn_wait(uint32_t ring, int i) { mbar_wait(ring + (i & 3) * 8, (i >> 2) & 1); }
__device__ __forceinline__ void turn_pass(const Ctx& c, uint32_t ring, int i) { if (c.lane == 0) mbar_arrive(ring + (i & 3) * 8); }
__device__ __forceinline__ void p2_scales(P2State& z) {
  float l0 = z.l0, l1 = z.l1;
  l0 += __shfl_xor_sync(0xffffffffu, l0, 1);
  l1 += __shfl_xor_sync(0xffffffffu, l1, 1);
  l0 += __shfl_xor_sync(0xffffffffu, l0, 2);
  l1 += __shfl_xor_sync(0xffffffffu, l1, 2);
  asm("rcp.approx.ftz.f32 %0, %1;" : "=f"(z.e0) : "f"(l0));
  asm("rcp.approx.ftz.f32 %0, %1;" : "=f"(z.e1) : "f"(l1));
}
template <int N>
__device__ __forceinline__ void p2_first(const Ctx& c, P2State& z, float (&o)[64], uint32_t (&Pc)[32], uint32_t (&Pn)[32],
                                         int ks, int vs, int cnt, int acc) {
  float s[N] = {};
  issue_qk(s, z.qd, desc_lo(c.sm + SM_RING, 16) + ks * 2048);
  if (vs >= 0) {
    p2_scales(z);
    issue_pv<8>(o, Pc, desc_lo(c.sm + SM_RING, 16384) + vs * 2048, acc);
  } else {
    WG_COMMIT();
  }
  mbar_expect(z.ab + (z.ai++ & 3) * 8, cnt == 1 ? 8192 : 0);
  PROFZ();
  WG_WAIT(1);
  PROFZ();
  pin(s);
  release(c, B_P2E + ks, cnt);
  causal_mask(s, c.warp * 16 + (c.lane >> 2) - 2 * (c.lane & 3));
  z.m0 = z.m1 = 0.f;
  row_exp<false>(s, Pn, 0.f, 0.f, z.l0, z.l1);
  z.shift = __any_sync(0xffffffffu, !(z.l0 + z.l1 <= SM_HI) || ((c.lane & 3) == 0 && !(fminf(z.l0, z.l1) >= SM_LO)));
  if (__builtin_expect(z.shift, 0)) {
    z.m0 = z.m1 = -INFINITY;
    row_max(s, z.m0, z.m1);
    row_exp<true>(s, Pn, z.m0, z.m1, z.l0, z.l1);
  }
  WG_WAIT(0);
  pin(o);
  if (vs >= 0) release(c, B_P2E + vs, 1);
}

template <bool SECOND>
__device__ __forceinline__ void p2_turn(const Ctx& c, P2State& z, float (&o)[64], uint32_t (&Pc)[32], uint32_t (&Pn)[32],
                                        int eb = -1, bool half = false, int vcnt = 1) {
  float s[64] = {};
  const int ks = z.ks, vs = wrap5(ks + 1);
  PROFZ();
  turn_wait(z.wb, z.wi++);
  PROFZ();
  issue_qk(s, z.qd, desc_lo(c.sm + SM_RING, 16) + ks * 2048);
  const uint32_t vd = desc_lo(c.sm + SM_RING, 16384) + vs * 2048;
  if (SECOND) {
    if (eb >= 0) stage_tile(o, c.sm + SM_BUF + eb * 16384, c, z.e0, z.e1);
    if (half) issue_pv<4>(o, Pc, vd, 0); else issue_pv<8>(o, Pc, vd, 0);
  } else {
    issue_pv<8>(o, Pc, vd, 1);
  }
  turn_pass(c, z.ab, z.ai++);
  if (SECOND) { if (eb >= 0) stage_done(c, eb); }
  PROFZ();
  z.ks = wrap5(ks + 2);
  WG_WAIT(1);
  PROFZ();
  pin(s);
  release(c, B_P2E + ks, 1);
  float t0, t1, a0 = 1.f, a1 = 1.f;
  row_exp<false>(s, Pn, 0.f, 0.f, t0, t1);
  z.shift = __any_sync(0xffffffffu, z.shift || !(t0 + t1 <= SM_HI));
  const bool redo = z.shift;
  if (__builtin_expect(redo, 0)) {
    float n0 = z.m0, n1 = z.m1;
    row_max(s, n0, n1);
    a0 = ex2(z.m0 - n0); a1 = ex2(z.m1 - n1);
    z.m0 = n0; z.m1 = n1;
    z.l0 *= a0; z.l1 *= a1;
    row_exp<true>(s, Pn, z.m0, z.m1, t0, t1);
  }
  WG_WAIT(0);
  pin(o);
  release(c, B_P2E + vs, vcnt);
  if (__builtin_expect(redo, 0)) {
#pragma unroll
    for (int i = 0; i < 16; i++) { o[4 * i] *= a0; o[4 * i + 1] *= a0; o[4 * i + 2] *= a1; o[4 * i + 3] *= a1; }
  }
  z.l0 += t0; z.l1 += t1;
}
__device__ __forceinline__ void copy_p(uint32_t (&d)[32], const uint32_t (&s)[32], int zero) {
#pragma unroll
  for (int i = 0; i < 32; i++) asm volatile("add.s32 %0, %1, %2;" : "=r"(d[i]) : "r"(s[i]), "r"(zero));
}

__device__ __forceinline__ void p2_consumer(const Params& p, const Ctx& c, int rot) {
  const int nit = p.s.r[c.cl].n2;
  const uint32_t fring = c.bar + B_P2F * 8, oring = c.bar + B_ORD * 8;
  float o[64] = {};
  uint32_t Pa[32] = {}, Pb[32] = {};
  P2State z;
  z.e0 = z.e1 = z.l0 = z.l1 = 0.f; z.ks = rot; z.shift = false;
  int acc = 0, n = 0;
  for (int it = 0; it < nit; it++) {
    const int j = p.s.r[c.cl].item[it] & 7, blk = p2_blk(c.rank, c.wg, it);
    const int lng = ((it ^ c.wg) & 1) ^ 1;
    z.qd = desc_lo(c.sm + SM_BUF, 16) + p2_buf(c.wg, it) * 1024;
    if (lng) { z.wb = oring; z.wi = n - it; z.ab = fring; z.ai = n + 1; }
    else { z.wb = fring; z.wi = n + 2; z.ab = oring; z.ai = n - it; }
    PROFZ();
    mbar_wait(c.bar + (B_QF + p2_buf(c.wg, it)) * 8, (it >> 1) & 1);
    turn_wait(fring, n + 1 - lng);
    PROFZ();
    const int vs = it ? wrap5(z.ks + 1) : -1, ks = lng ? z.ks : wrap5(z.ks + (it ? 2 : 1));
    if (blk & 1) p2_first<64>(c, z, o, Pa, Pb, ks, vs, 1 + lng, acc);
    else p2_first<32>(c, z, o, Pa, Pb, ks, vs, 1 + lng, acc);
    z.ks = wrap5(ks + (it == 0 && lng ? 1 : 2));
    PROF(c.wg, 24 + it);
    n += 2 * j + 2;
    int left = 2 * j + lng;
    acc = left != 0;
    if (left == 0) { copy_p(Pa, Pb, p.zero); continue; }
    p2_turn<true>(c, z, o, Pb, Pa, it > 0 ? p2_buf(c.wg, it - 1) : -1, !(blk & 1), 1 + lng);
    while (--left > 0) {
      p2_turn<false>(c, z, o, Pa, Pb);
      if (--left == 0) { copy_p(Pa, Pb, p.zero); break; }
      p2_turn<false>(c, z, o, Pb, Pa);
    }
  }
  {
    if (!acc && nit > 1) p2_epilogue(o, z.e0, z.e1, c, p2_buf(c.wg, nit));
    turn_wait(z.wb, z.wi);
    issue_pv<8>(o, Pa, desc_lo(c.sm + SM_RING, 16384) + z.ks * 2048, acc);
    if (((nit - 1) ^ c.wg) & 1) turn_pass(c, z.ab, z.ai);
    p2_scales(z);
    WG_WAIT(0);
    pin(o);
    release(c, B_P2E + z.ks);
    p2_epilogue(o, z.e0, z.e1, c, p2_buf(c.wg, nit - 1));
    PROF(c.wg, 24 + nit);
  }
}

__device__ __forceinline__ void p2_load_q(const Params& p, const Ctx& c, int it, int w) {
  const int item = p.s.r[c.cl].item[it], h = item >> 3, j = item & 7, b = p2_buf(w, it);
  mbar_expect(c.bar + (B_QF + b) * 8, 16384);
  bulk_load(c.sm + SM_BUF + b * 16384, g_Q + (size_t)(h * 32 + j * 4 + p2_blk(c.rank, w, it)) * 16384, 16384, c.bar + (B_QF + b) * 8, POL(4));
}
__device__ __forceinline__ void wait_p1_free(const Ctx& c, int u1, int s) {
  mbar_wait(c.bar + (B_P1E + 2 * s) * 8, ((u1 - 1 - 2 * s) / 10) & 1);
  mbar_wait(c.bar + (B_P1E + 2 * s + 1) * 8, ((u1 - 2 - 2 * s) / 10) & 1);
}
__device__ __forceinline__ void p2_producer(const Params& p, const Ctx& c, int u1, int rot) {
  const int nit = p.s.r[c.cl].n2;
  int slot = rot, cnt = 0, par = 1, n = 0;
  const uint8_t* pv = nullptr;
  bool pl = false;
  auto load = [&](const uint8_t* src, int expect, uint32_t fb, bool last) {
    if (cnt < 5) {
      if (u1) {
        wait_p1_free(c, u1, slot);
        if (cnt == 0) p2_load_q(p, c, 0, 1);
      }
      cnt++;
    } else {
      if (slot == rot) par ^= 1;
      mbar_wait(c.bar + (B_P2E + slot) * 8, par);
    }
    if (expect) mbar_expect(fb, expect);
    bulk_load_mc(c.sm + SM_RING + slot * 32768 + c.rank * 16384, src, 16384, fb, last ? POL(5) : L2_NORMAL);
    slot = wrap5(slot + 1);
  };
  for (int it = 0; it < nit; it++) {
    const int item = p.s.r[c.cl].item[it], h = item >> 3, j = item & 7;
    if (it == 1 && (c.phases & 16) && p.s.r[c.cl].n1 < 8) flag_wait<true>(F_GATE, 256);
    uint32_t ready = (c.phases & 16) ? 0u : 255u;
    if (it == 0) { if (c.phases & 16) flag_wait<false>(F_Q + item, 4); mbar_wait(c.bar + B_LAD * 8, 0); p2_load_q(p, c, 0, 0); if (!u1) p2_load_q(p, c, 0, 1); }
    for (int t = 2 * j + 1; t >= 0; t--) {
      mask_wait(ready, t >> 1, F_KV + h * 8 + (c.lane & 7), 8);
      const uint8_t* k = g_KV + (size_t)(p.s.slot[h][t >> 1] * 16 + t) * 32768 + c.rank * 16384;
      const uint32_t fb = c.bar + (B_P2F + (n & 3)) * 8;
      const bool last = (p.s.r[c.cl].last[it] >> (t >> 1)) & 1;
      load(k, pv && t != 2 * j ? 65536 : 32768, fb, last);
      if (!(t & 1) && t + 4 <= 2 * j && c.rank == 0) flag_add_rx(F_RD + h * 8 + (t >> 1) + 2);
      if (pv) load(pv, 0, t != 2 * j ? fb : c.bar + (B_ORD + ((n - 1 - it) & 3)) * 8, pl);
      pl = last;
      pv = k + (size_t)NH * 16 * 32768;
      n++;
    }
  }
  load(pv, 32768, c.bar + (B_P2F + (n & 3)) * 8, pl);
}

__device__ __forceinline__ void publish_and_load_q(const Params& p, const Ctx& c, int f, int it, int seen) {
  const bool want = it < p.s.r[c.cl].n2, early = want && __all_sync(0xffffffffu, seen >= 4);
  if (early) { p2_load_q(p, c, it, it & 1); p2_load_q(p, c, it, (it & 1) ^ 1); }
  if (f >= 0) flag_add(f, 2);
  if (want && !early) {
    if (c.phases & 16) flag_wait<false>(F_Q + p.s.r[c.cl].item[it], 4);
    p2_load_q(p, c, it, it & 1); p2_load_q(p, c, it, (it & 1) ^ 1);
  }
}
__device__ __forceinline__ void p2_storer(const Params& p, const Ctx& c, int sfpar) {
  const int nit = p.s.r[c.cl].n2;
  for (int i = 0; i < 2 * nit; i++) {
    const int it = i >> 1, w = (it ^ i ^ 1) & 1, b = p2_buf(w, it);
    const int item = p.s.r[c.cl].item[it], h = item >> 3, j = item & 7;
    mbar_wait(c.bar + (B_SF + b) * 8, (sfpar >> b) & 1);
    sfpar ^= 1 << b;
    bulk_store(g_Q + (size_t)(h * 32 + j * 4 + p2_blk(c.rank, w, it)) * 16384, c.sm + SM_BUF + b * 16384, 16384, POL(1));
    BULK_COMMIT();
    if (i & 1) {
      const int seen = flag_peek(F_Q + p.s.r[c.cl].item[min(it + 2, nit - 1)]);
      BULK_WAIT(0);
      if (it + 1 == nit) release(c, B_DONE);
      publish_and_load_q(p, c, F_CTX + j * 64 + h, it + 2, seen);
    }
  }
}

__device__ __forceinline__ int p3_pos(int i, int x) { return i < 4 ? (i + x) & 3 : 4; }
__device__ __forceinline__ void p3_consumer(const Params& p, const Ctx& c, int x) {
  const bool first = p.s.r[c.cl].p3 >= 24;
  const int tile = p.s.r[c.cl].p3 - (first ? 24 : 0), j = tile / 3, nt = tile - 3 * j;
  const int na = first ? 9 : 0, nb = p.s.task[c.cl][1] - p.s.task[c.cl][0];
  const uint32_t ad = desc_lo(c.sm + SM_RING + c.wg * 8192, 16), bd = desc_lo(c.sm + SM_RING + 16384, 4096);
  float acc[96] = {};
  int slot = 0, par = 0, prev = 0;
  float g0 = 0.f, g1 = 0.f;
  const int hold = c.wg && LAG ? na + nb - LAG : -1, pass = c.wg || !LAG ? -1 : na + nb - 1;
#pragma unroll 1
  for (int kb = 0; kb < nb; kb++) {
    if (kb == hold) bar_sync(6, 256);
    mbar_wait(c.bar + (B_P3F + slot) * 8, par);
    if (kb == 0) PROF(c.wg, 39);
    WG_FENCE();
#pragma unroll
    for (int kk = 0; kk < 4; kk++) wgmma_ss192<1>(acc, ad + p3_pos(slot, x) * 2560 + kk * 2, bd + p3_pos(slot, x) * 2560 + (kk >> 1) * 768 + (kk & 1) * 128, kk != 0 ? 1 : kb != 0);
    WG_COMMIT();
    if (kb == pass) bar_arrive(6, 256);
    WG_WAIT(1);
    if (kb > 0) release(c, B_P3E + prev);
    else {
      const float* g = g_gate + j * 256 + c.rank * 128 + c.wg * 64 + c.warp * 16 + (c.lane >> 2);
      g0 = __ldcg(g); g1 = __ldcg(g + 8);
    }
    prev = slot;
    if (++slot == 5) { slot = 0; par ^= 1; }
  }
  WG_WAIT(0);
  pin(acc);
  g0 = 1.f - g0; g1 = 1.f - g1;
#pragma unroll
  for (int i = 0; i < 24; i++) { acc[4 * i] *= g0; acc[4 * i + 1] *= g0; acc[4 * i + 2] *= g1; acc[4 * i + 3] *= g1; }
#pragma unroll 1
  for (int kb = nb; kb < nb + na; kb++) {
    if (kb == hold) bar_sync(6, 256);
    mbar_wait(c.bar + (B_P3F + slot) * 8, par);
    if (kb == 0) PROF(c.wg, 39);
    WG_FENCE();
#pragma unroll
    for (int kk = 0; kk < 4; kk++) wgmma_ss192<1, 1>(acc, ad + p3_pos(slot, x) * 2560 + kk * 128, bd + p3_pos(slot, x) * 2560 + (kk >> 1) * 768 + (kk & 1) * 128, 1);
    WG_COMMIT();
    if (kb == pass) bar_arrive(6, 256);
    WG_WAIT(1);
    if (kb > 0) release(c, B_P3E + prev);
    prev = slot;
    if (++slot == 5) { slot = 0; par ^= 1; }
  }
  WG_WAIT(0);
  pin(acc);
  PROF(c.wg, 40);
  if (first) bar_sync(4 + c.wg, 128);
  mbar_wait(c.bar + B_OUT * 8, 0);
  const int row = (c.lane & 7) + ((c.lane >> 3) & 1) * 8;
  const uint32_t wbase = c.sm + SM_RING + c.wg * 8192 + c.warp * 2048;
  const uint32_t base = wbase + row * 128 + (((c.lane >> 4) ^ (row & 7)) << 4);
#pragma unroll
  for (int i = 0; i < 12; i++) {
    stsm4((base ^ ((i & 3) << 5)) + (i >> 2) * 40960, pack_bf16(acc[8 * i], acc[8 * i + 1]), pack_bf16(acc[8 * i + 2], acc[8 * i + 3]),
          pack_bf16(acc[8 * i + 4], acc[8 * i + 5]), pack_bf16(acc[8 * i + 6], acc[8 * i + 7]));
    if ((i & 3) == 3) {
      FENCE_ASYNC_SMEM();
      bar_sync(4 + c.wg, 128);
      if (c.warp == (i >> 2)) tma2d_add(&p.map_out, c.sm + SM_RING + c.wg * 8192 + c.warp * 40960, nt * 192 + c.warp * 64, j * 256 + c.rank * 128 + c.wg * 64);
    }
  }
  BULK_COMMIT();
  PROF(c.wg, 43);
  BULK_WAIT_READ(0);
  PROF(c.wg, 44);
}

__device__ __forceinline__ void p3_producer(const Params& p, const Ctx& c, int u1, int u2, int rot, int x) {
  const bool first = p.s.r[c.cl].p3 >= 24;
  const int tile = p.s.r[c.cl].p3 - (first ? 24 : 0), j = tile / 3, nt = tile - 3 * j;
  int slot = 0, par = 1, cnt = 0;
  auto wait_free = [&](int s) {
    const int f = wrap5(s + 5 - rot);
    if (f < u2) mbar_wait(c.bar + (B_P2E + s) * 8, ((u2 - 1 - f) / 5) & 1);
    else if (u1) wait_p1_free(c, u1, s);
  };
  asm volatile(ELECT("prefetch.tensormap [%0];") ::"l"(&p.map_o[0]) : "memory");
  asm volatile(ELECT("prefetch.tensormap [%0];") ::"l"(&p.map_out) : "memory");
  if ((c.phases & 16) && p.s.r[c.cl].n1 < 8 && p.s.r[c.cl].n2 < 2) flag_wait<true>(F_GATE, 256);
  uint32_t ready = (c.phases & 16) ? 0u : ~0u;
  const int q1 = p.s.task[c.cl][1];
  for (int q = p.s.task[c.cl][0]; q < q1 + (first ? 9 : 0); q++) {
    const bool brA = q >= q1;
    const int kb = brA ? q - q1 : p.s.p3_order[tile][q];
    if (!brA) mask_wait(ready, kb >> 1, F_CTX + j * 64 + c.lane, 4);
    else if (kb == 0 && (c.phases & 16)) flag_wait<false>(F_CTX + j * 64 + 32, 16);
    const uint8_t* a = brA ? g_oA + (j * 4 + c.rank * 2) * 73728 + kb * 8192 : g_Q + (size_t)((kb >> 1) * 32 + j * 4 + c.rank * 2) * 16384 + (kb & 1) * 8192;
    const uint32_t st = c.sm + SM_RING + p3_pos(slot, x) * 40960, fb = c.bar + (B_P3F + slot) * 8;
    if (cnt < 4) { wait_free(p3_pos(cnt, x)); wait_free(p3_pos(cnt, x) + 1); }
    else if (cnt == 4) mbar_wait(c.bar + B_DONE * 8, 0);
    else mbar_wait(c.bar + (B_P3E + slot) * 8, par);
    cnt++;
    mbar_expect(fb, 40960);
    bulk_load(st, a, 8192, fb, POL(3));
    bulk_load(st + 8192, a + (brA ? 73728 : 16384), 8192, fb, POL(3));
    tma3d_mc(st + 16384 + c.rank * 12288, &p.map_o[brA], 0, kb * 64 + c.rank * 32, nt * 3, fb);
    if (++slot == 5) { slot = 0; par ^= 1; }
  }
}

__device__ __forceinline__ float bf_lo(uint32_t w) { return __uint_as_float(w << 16); }
__device__ __forceinline__ float bf_hi(uint32_t w) { return __uint_as_float(w & 0xffff0000u); }

__device__ __forceinline__ void gate_rows(const Params& p, int row0, int lane) {
  const uint4* x = reinterpret_cast<const uint4*>(p.x + (size_t)(row0 + (lane >> 2)) * DM) + (lane & 3);
  const uint4* w = reinterpret_cast<const uint4*>(p.gate_w) + (lane & 3);
  float a = 0.f;
#pragma unroll 1
  for (int b = 0; b < 3; b++) {
    uint4 u[6];
#pragma unroll
    for (int i = 0; i < 6; i++) u[i] = __ldg(x + (b * 6 + i) * 4);
#pragma unroll
    for (int i = 0; i < 6; i++) {
      const uint4 v = __ldg(w + (b * 6 + i) * 4);
      a = fmaf(bf_lo(u[i].x), bf_lo(v.x), a); a = fmaf(bf_hi(u[i].x), bf_hi(v.x), a);
      a = fmaf(bf_lo(u[i].y), bf_lo(v.y), a); a = fmaf(bf_hi(u[i].y), bf_hi(v.y), a);
      a = fmaf(bf_lo(u[i].z), bf_lo(v.z), a); a = fmaf(bf_hi(u[i].z), bf_hi(v.z), a);
      a = fmaf(bf_lo(u[i].w), bf_lo(v.w), a); a = fmaf(bf_hi(u[i].w), bf_hi(v.w), a);
    }
  }
  a += __shfl_xor_sync(0xffffffffu, a, 1);
  a += __shfl_xor_sync(0xffffffffu, a, 2);
  if ((lane & 3) == 0) g_gate[row0 + (lane >> 2)] = 1.f / (1.f + __expf(-a));
}

__device__ __forceinline__ void lds10(uint32_t (&k)[10], uint32_t a) {
  asm volatile("ld.shared.v2.u32 {%0, %1}, [%10];\nld.shared.v2.u32 {%2, %3}, [%10+8];\nld.shared.v2.u32 {%4, %5}, [%10+16];\n"
               "ld.shared.v2.u32 {%6, %7}, [%10+24];\nld.shared.v2.u32 {%8, %9}, [%10+32];"
               : "=r"(k[0]), "=r"(k[1]), "=r"(k[2]), "=r"(k[3]), "=r"(k[4]), "=r"(k[5]), "=r"(k[6]), "=r"(k[7]), "=r"(k[8]), "=r"(k[9]) : "r"(a));
}
__device__ __forceinline__ void local_attn(const Params& p, const Ctx& c, int rb, int hs) {
  const int lane = c.lane, grp = rb >> 2, par = lane >> 4, i0 = 2 * (lane & 15);
  const uint32_t buf = c.sm + SM_BUF + (c.warp - 2) * 8192, bqk = c.bar + (B_LA + (c.warp - 2) * 2) * 8, bv = bqk + 8;
  const uint32_t mine = buf + 2304 + par * 160 + i0 * 4;
  const bool flags = c.phases & 16;
  auto fetch_qk = [&](int i) {
    if (flags && !(i & 1)) {
      const int q = i >> 1;
      const int tgt = q == 0 ? 24 : q == 3 ? 8 : 12;
      flag_wait<false>(F_QKVA + (grp - (grp > 0 && (rb & 3) == 0 ? par : 0)) * 4 + q, tgt);
    }
    mbar_expect(bqk, 5184);
    tma3d(buf, &p.map_t[0], rb * 32 + 8, 0, 9 * (4 * i + hs), bqk, POL(2));
    tma3d(buf + 2304, &p.map_t[1], rb * 32, 0, 288 + 9 * (4 * i + hs), bqk, POL(2));
  };
  auto fetch_v = [&](int i) { mbar_expect(bv, 2880); tma3d(buf + 5248, &p.map_t[1], rb * 32, 0, 576 + 9 * (4 * i + hs), bv, POL(2)); };
  fetch_qk(0);
  if (flags) flag_wait<true>(F_GATE, 256);
#pragma unroll 1
  for (int q = 0; q < 8; q++) {
    fetch_v(q);
    float a[8], b[8];
#pragma unroll
    for (int w = 0; w < 8; w++) a[w] = b[w] = 0.f;
    mbar_wait(bqk, q & 1);
    PROFB(1 + 2 * q);
#pragma unroll 1
    for (int j = 0; j < 9; j++) {
      uint32_t x, y, k[10];
      asm volatile("ld.shared.v2.u32 {%0, %1}, [%2];" : "=r"(x), "=r"(y) : "r"(buf + lane * 8 + j * 256));
      lds10(k, mine + j * 320);
      const float xl = bf_lo(x), xh = bf_hi(x), yl = bf_lo(y), yh = bf_hi(y);
#pragma unroll
      for (int m = 1; m < 10; m++) {
        const float kl = bf_lo(k[m]), kh = bf_hi(k[m]);
        if (m < 9) a[8 - m] = fmaf(xl, kl, fmaf(xh, kh, a[8 - m]));
        if (m > 1) b[9 - m] = fmaf(yl, kl, fmaf(yh, kh, b[9 - m]));
      }
    }
    __syncwarp();
    if (q < 7) fetch_qk(q + 1);
    constexpr float SC = 0.23570226039551584f * 1.4426950408889634f;
    const float* gp = g_gate + rb * 64 + 2 * i0 + par;
    const float ga = __ldcg(gp), gb = __ldcg(gp + 2);
    float ma = a[0], mb = b[0];
#pragma unroll
    for (int w = 1; w < 8; w++) {
      if (rb == 0) {
        if (i0 < w) a[w] = -INFINITY;
        if (i0 + 1 < w) b[w] = -INFINITY;
      }
      ma = fmaxf(ma, a[w]); mb = fmaxf(mb, b[w]);
    }
    float la = 0.f, lb = 0.f;
#pragma unroll
    for (int w = 0; w < 8; w++) {
      a[w] = ex2((a[w] - ma) * SC); b[w] = ex2((b[w] - mb) * SC);
      la += a[w]; lb += b[w];
    }
    la = __fdividef(ga, la); lb = __fdividef(gb, lb);
#pragma unroll
    for (int w = 0; w < 8; w++) { a[w] *= la; b[w] *= lb; }
    uint8_t* dst = g_oA + rb * 73728 + ((i0 & 2) + par) * 4;
    mbar_wait(bv, q & 1);
#pragma unroll 1
    for (int j = 0; j < 9; j++) {
      uint32_t v[10];
      lds10(v, mine + 2944 + j * 320);
      float a0 = 0.f, a1 = 0.f, b0 = 0.f, b1 = 0.f;
#pragma unroll
      for (int m = 1; m < 10; m++) {
        const float vl = bf_lo(v[m]), vh = bf_hi(v[m]);
        if (m < 9) { a0 = fmaf(a[8 - m], vl, a0); a1 = fmaf(a[8 - m], vh, a1); }
        if (m > 1) { b0 = fmaf(b[9 - m], vl, b0); b1 = fmaf(b[9 - m], vh, b1); }
      }
      const uint32_t wa = pack_bf16(a0, a1), wb = pack_bf16(b0, b1);
      const uint32_t got = __shfl_xor_sync(0xffffffffu, par ? wa : wb, 16);
      const uint32_t r0 = par ? got : wa, r1 = par ? wb : got;
      const int col = 18 * (4 * q + hs) + 2 * j, o = col * 128 + ((((i0 >> 2) ^ col) & 7) << 4);
      *reinterpret_cast<uint32_t*>(dst + o) = __byte_perm(r0, r1, 0x5410);
      *reinterpret_cast<uint32_t*>(dst + ((o + 128) ^ 16)) = __byte_perm(r0, r1, 0x7632);
    }
    __syncwarp();
    PROFB(2 + 2 * q);
  }
  mbar_arrive_one(c.bar + B_LAD * 8);
  flag_add(F_CTX + grp * 64 + 32);
}

__global__ void __cluster_dims__(2, 1, 1) __launch_bounds__(384, 1) fused_kernel(const __grid_constant__ Params p) {
  extern __shared__ uint8_t smem_raw[];
  Ctx c;
  c.sm = ((uint32_t)__cvta_generic_to_shared(smem_raw) + 1023u) & ~1023u;
  c.bar = c.sm + SM_BAR;
  c.lane = threadIdx.x & 31;
  const int wid = __shfl_sync(0xffffffffu, threadIdx.x >> 5, 0);
  if (wid < 6) asm volatile("prefetch.tensormap [%0];" ::"l"(&p.map_a[0] + wid) : "memory");
  c.wg = wid >> 2;
  c.warp = wid & 3;
  PROF(c.wg, 0);
  PROFG(61);
  c.cl = (blockIdx.x + (wid >> 4)) >> 1;
  c.rank = blockIdx.x & 1;
  c.rbar = mapa(c.bar, c.lane & 1);
  {
    const int w = wid, cnt = (((int)(B_CNT >> (4 * w)) - 1) & 15) + 1;
    if (w < 11) {
#pragma unroll
      for (int i = 0; i < 8; i++) asm volatile("mbarrier.init.shared::cta.b64 [%0], %1;" ::"r"(c.bar + w * 64 + i * 8), "r"(cnt));
    }
    asm volatile("fence.mbarrier_init.release.cluster;" ::: "memory");
  }
  if (c.wg == 2) PROF(2, 56);
  asm volatile("barrier.cluster.arrive.relaxed;" ::: "memory");
  c.phases = p.s.r[c.cl].phases;
  const bool do1 = p.s.r[c.cl].n1 > 0, do2 = p.s.r[c.cl].n2 > 0, do3 = p.s.r[c.cl].p3 != 255;
  if (do1 && c.wg == 2 && c.warp == 0) {
    const int type = p.s.r[c.cl].slab >> 3;
    PROF(2, 57);
    FENCE_ASYNC_SMEM();
    mbar_expect(c.bar + B_P1F * 8, type ? 32768 : 16384);
    tma2d(type ? c.sm + SM_BUF + 32768 : c.sm + SM_RING, &p.map_a[type], type ? 512 : 0, (p.s.r[c.cl].slab & 7) * 256 + c.rank * 128, c.bar + B_P1F * 8);
    PROF(2, 58);
  }
  asm volatile("barrier.cluster.wait.acquire;" ::: "memory");
  if (c.wg == 2) PROF(2, 59);
  if (do1 && c.wg == 2 && c.warp == 0) {
    const int type = p.s.r[c.cl].slab >> 3, tile = p.s.r[c.cl].tile[0] & 63;
    const CUtensorMap* m = &p.map_w[type * 2 + (tile >> 5)];
#pragma unroll 1
    for (int s = 1 - type; s < NPRO; s++) {
      const int kb = (s - type) >> 1;
      const uint32_t fb = c.bar + (B_P1F + s) * 8;
      if (s) mbar_expect(fb, 16384);
      if ((s ^ type) & 1) tma2d_mc(c.sm + SM_RING + s * 16384 + c.rank * 8192, m, (tile & 31) * 128 + c.rank * 64, kb < 0 ? 512 : kb * 64, fb);
      else tma2d(c.sm + SM_RING + s * 16384, &p.map_a[type], kb * 64, (p.s.r[c.cl].slab & 7) * 256 + c.rank * 128, fb);
    }
  }

  if (c.wg < 2) {
    PROF(c.wg, 4);
    asm volatile("setmaxnreg.inc.sync.aligned.u32 224;");
    if (c.wg == 1) {
      if (do1) bar_arrive(ORDER, 256);
      if (c.lane == 0) mbar_arrive(c.bar + B_P2F * 8);
    }
    PL(0);
    if (do1) p1_consumer(p, c);
    PL(1);
    if (do2) p2_consumer(p, c, p.s.r[c.cl].rot);
    PL(2);
    if (do3) p3_consumer(p, c, p.s.r[c.cl].x3);
    PL(3);
    PROF(c.wg, 63);
    PROFG(62);
    if (c.lane == 0) mbar_arrive(c.bar + B_FIN * 8);
    __syncwarp();
    cluster_sync();
  } else {
    asm volatile("setmaxnreg.dec.sync.aligned.u32 56;");
    if (c.warp == 0) {
      PROF(2, 60);
      if (do1) p1_producer(p, c);
      if (do2) p2_producer(p, c, p.s.r[c.cl].u1, p.s.r[c.cl].rot);
      if (do3) p3_producer(p, c, p.s.r[c.cl].u1, p.s.r[c.cl].u2, p.s.r[c.cl].rot, p.s.r[c.cl].x3);
    } else if (c.warp == 1) {
      const int f = do1 ? p1_storer(p, c) : -1;
      publish_and_load_q(p, c, f, 1, flag_peek(F_Q + p.s.r[c.cl].item[1]));
      if (do2) p2_storer(p, c, (p.s.r[c.cl].n1 & 1) * 10);
      else { mbar_wait(c.bar + B_LAD * 8, 0); release(c, B_DONE); }
      if (do3) {
        const int tile = p.s.r[c.cl].p3 % 24;
        if (p.s.task[c.cl][1] == 64) {
          for (int r = 0; r < (64 - p.s.task[c.cl][0] - ZLEAD) / 5; r++) mbar_wait(c.bar + B_P3F * 8, r & 1);
          const int j = tile / 3, nt = tile - 3 * j;
          uint4* o = reinterpret_cast<uint4*>(p.out + (size_t)(j * 256 + c.rank * 128 + (c.lane >> 3)) * DM + nt * 192) + (c.lane & 7);
#pragma unroll 4
          for (int r = 0; r < 32; r++) o[r * 288] = o[r * 288 + 8] = o[r * 288 + 16] = make_uint4(0u, 0u, 0u, 0u);
          __syncwarp();
          flag_add(F_OUT + tile * 2 + c.rank);
        } else if (c.phases & 16) {
          flag_wait<false, 256>(F_OUT + tile * 2 + c.rank, 1);
        }
        mbar_arrive_one(c.bar + B_OUT * 8);
      }
    } else {
      const int bw = blockIdx.x * 2 + (c.warp - 2);
      if ((c.phases & 1) && bw < 256) {
        gate_rows(p, bw * 8, c.lane);
        __syncwarp();
        flag_add(F_GATE);
      }
      if (p.s.r[c.cl].bg != 255) local_attn(p, c, p.s.r[c.cl].bg, bw & 3);
      else if (c.lane == 0) mbar_arrive(c.bar + B_LAD * 8);
    }
    __syncwarp();
    bar_sync(3, 128);
    if (c.warp == 0 && (c.phases & 32)) {
      int last = 0;
      if (c.lane == 0) { __threadfence(); last = atomicAdd(g_flags + F_DONE, 1) == 2 * NCL - 1; }
      if (__shfl_sync(0xffffffffu, last, 0)) for (int i = c.lane; i < F_NUM; i += 32) g_flags[i] = 0;
    }
    if (c.warp == 1) mbar_wait(c.bar + B_FIN * 8, 0);
    __syncwarp();
    cluster_sync();
  }
}

SCHED_DECL Sched k_sched = {
  {{0,30,1,22,0,{209,0,0,0,0,0,0,0,0,0,0},{0,0,0,0,0,0,0,0,0,0,0},{132,98,131,44,39,46,37,48,40,43,41,53,45,42,54,50,38,56,49,47,52,59,51,63,62,58,61,55,60,57}},
   {1,30,2,32,1,{185,200,0,0,0,0,0,0,0,0,0},{0,0,0,0,0,0,0,0,0,0,0},{132,98,131,44,39,46,37,48,40,43,41,53,45,42,54,38,50,56,49,47,52,59,51,63,62,58,61,55,60,57}},
   {2,29,0,1,2,{0,0,0,0,0,0,0,0,0,0,0},{0,0,0,0,0,0,0,0,0,0,0},{128,33,131,44,14,37,48,40,43,41,53,45,42,54,50,38,49,47,56,52,59,51,63,62,58,61,55,60,57,0}},
   {3,28,0,9,3,{0,0,0,0,0,0,0,0,0,0,0},{0,0,0,0,0,0,0,0,0,0,0},{132,33,131,44,14,37,8,43,41,53,45,42,54,50,38,49,47,56,52,59,51,63,62,58,61,55,60,57,0,0}},
   {4,28,0,10,4,{0,0,0,0,0,0,0,0,0,0,0},{0,0,0,0,0,0,0,0,0,0,0},{128,36,1,35,7,46,16,40,9,21,13,10,22,18,6,17,24,15,20,27,19,31,30,26,29,23,28,25,0,0}},
   {5,27,0,21,5,{0,0,0,0,0,0,0,0,0,0,0},{0,0,0,0,0,0,0,0,0,0,0},{128,36,1,35,7,46,16,40,11,53,10,22,18,6,17,24,15,20,27,19,31,30,26,29,23,28,25,0,0,0}},
   {6,26,0,23,6,{0,0,0,0,0,0,0,0,0,0,0},{0,0,0,0,0,0,0,0,0,0,0},{96,36,131,44,14,37,8,41,21,45,22,18,6,17,24,15,20,27,19,31,94,26,29,23,28,25,0,0,0,0}},
   {7,25,2,18,7,{192,231,0,0,0,0,0,0,0,0,0},{0,255,0,0,0,0,0,0,0,0,0},{132,0,131,71,69,72,105,85,109,86,82,70,81,88,79,84,91,83,95,90,94,93,87,92,89,0,0,0,0,0}},
   {0,30,1,14,8,{226,0,0,0,0,0,0,0,0,0,0},{0,0,0,0,0,0,0,0,0,0,0},{128,36,1,35,7,14,5,16,8,11,9,21,13,10,22,18,6,24,17,15,20,27,19,31,30,26,29,23,28,25}},
   {1,30,1,44,9,{233,0,0,0,0,0,0,0,0,0,0},{0,0,0,0,0,0,0,0,0,0,0},{128,36,1,35,7,14,5,16,8,11,9,21,13,10,22,6,18,24,17,15,20,27,19,31,30,26,29,23,28,25}},
   {2,29,0,20,10,{0,0,0,0,0,0,0,0,0,0,0},{0,0,0,0,0,0,0,0,0,0,0},{132,32,2,35,7,46,16,8,11,9,21,13,10,22,18,6,17,15,24,20,27,19,31,30,26,29,23,28,25,0}},
   {3,28,0,17,11,{0,0,0,0,0,0,0,0,0,0,0},{0,0,0,0,0,0,0,0,0,0,0},{128,36,2,35,7,46,16,40,9,21,13,10,22,18,6,17,15,24,20,27,19,31,30,26,29,23,28,25,0,0}},
   {4,28,0,5,12,{0,0,0,0,0,0,0,0,0,0,0},{0,0,0,0,0,0,0,0,0,0,0},{96,66,33,12,39,5,48,11,41,53,45,42,54,50,38,49,56,47,52,59,51,63,62,58,61,55,60,57,0,0}},
   {5,27,2,36,13,{251,202,0,0,0,0,0,0,0,0,0},{0,0,0,0,0,0,0,0,0,0,0},{96,66,33,12,39,5,48,9,43,13,42,54,50,38,49,56,47,52,59,51,63,62,58,61,55,60,57,0,0,0}},
   {6,26,0,3,14,{0,0,0,0,0,0,0,0,0,0,0},{0,0,0,0,0,0,0,0,0,0,0},{65,66,99,71,46,16,40,11,53,10,54,50,38,49,56,47,52,59,51,63,126,58,61,55,60,57,0,0,0,0}},
   {7,25,0,19,15,{0,0,0,0,0,0,0,0,0,0,0},{0,0,0,0,0,0,0,0,0,0,0},{100,32,99,103,101,104,75,117,74,118,114,102,113,120,111,116,123,115,127,122,126,125,119,124,121,0,0,0,0,0}},
   {0,4,8,41,255,{17,26,62,173,179,219,234,225,0,0,0},{0,0,0,0,0,0,0,0,0,0,0},{96,66,33,12,0,0,0,0,0,0,0,0,0,0,0,0,0,0,0,0,0,0,0,0,0,0,0,0,0,0}},
   {1,4,7,45,255,{21,46,73,182,121,217,205,0,0,0,0},{0,0,0,0,0,0,63,0,0,0,0},{96,66,33,12,0,0,0,0,0,0,0,0,0,0,0,0,0,0,0,0,0,0,0,0,0,0,0,0,0,0}},
   {2,6,7,13,255,{96,119,129,65,84,123,190,0,0,0,0},{0,0,0,0,0,0,96,0,0,0,0},{100,1,34,12,39,5,0,0,0,0,0,0,0,0,0,0,0,0,0,0,0,0,0,0,0,0,0,0,0,0}},
   {3,8,4,8,255,{56,118,76,142,0,0,0,0,0,0,0},{0,0,0,126,0,0,0,0,0,0,0},{96,1,34,12,39,5,48,11,0,0,0,0,0,0,0,0,0,0,0,0,0,0,0,0,0,0,0,0,0,0}},
   {4,8,5,43,255,{112,47,85,124,189,0,0,0,0,0,0},{0,0,0,0,0,0,0,0,0,0,0},{132,98,131,44,14,37,8,43,0,0,0,0,0,0,0,0,0,0,0,0,0,0,0,0,0,0,0,0,0,0}},
   {5,10,4,18,255,{134,108,125,248,0,0,0,0,0,0,0},{0,0,0,0,0,0,0,0,0,0,0},{132,98,131,44,14,37,8,41,21,45,0,0,0,0,0,0,0,0,0,0,0,0,0,0,0,0,0,0,0,0}},
   {6,10,7,20,255,{128,45,66,169,52,154,228,0,0,0,0},{0,0,0,0,1,0,0,0,0,0,0},{97,98,76,103,69,48,9,43,13,42,0,0,0,0,0,0,0,0,0,0,0,0,0,0,0,0,0,0,0,0}},
   {7,9,6,11,255,{40,97,113,94,148,136,0,0,0,0,0},{0,0,0,0,0,0,0,0,0,0,0},{65,66,76,78,80,73,107,77,106,0,0,0,0,0,0,0,0,0,0,0,0,0,0,0,0,0,0,0,0,0}},
   {8,18,4,10,16,{72,166,249,203,0,0,0,0,0,0,0},{1,0,0,0,0,0,0,0,0,0,0},{66,161,71,38,5,35,44,109,9,21,10,18,17,20,15,31,26,23,0,0,0,0,0,0,0,0,0,0,0,0}},
   {9,19,3,8,17,{122,163,229,0,0,0,0,0,0,0,0},{0,0,0,0,0,0,0,0,0,0,0},{132,41,102,7,99,44,16,109,9,21,13,18,84,17,27,30,29,26,25,0,0,0,0,0,0,0,0,0,0,0}},
   {10,18,4,14,18,{105,196,153,208,0,0,0,0,0,0,0},{0,0,0,0,0,0,0,0,0,0,0},{132,41,3,7,99,44,16,109,11,21,22,18,17,24,27,31,23,26,0,0,0,0,0,0,0,0,0,0,0,0}},
   {11,19,2,6,19,{222,188,0,0,0,0,0,0,0,0,0},{0,31,0,0,0,0,0,0,0,0,0},{96,106,107,7,99,44,16,40,9,21,10,6,15,24,27,31,30,26,25,0,0,0,0,0,0,0,0,0,0,0}},
   {12,19,3,25,20,{48,161,239,0,0,0,0,0,0,0,0},{0,0,128,0,0,0,0,0,0,0,0},{100,1,140,14,99,44,8,40,9,13,22,6,24,20,27,31,29,28,25,0,0,0,0,0,0,0,0,0,0,0}},
   {13,17,2,24,21,{149,253,0,0,0,0,0,0,0,0,0},{2,0,0,0,0,0,0,0,0,0,0},{100,1,107,80,108,75,104,85,74,82,81,79,91,94,90,87,89,0,0,0,0,0,0,0,0,0,0,0,0,0}},
   {14,18,3,47,22,{168,159,242,0,0,0,0,0,0,0,0},{0,0,7,0,0,0,0,0,0,0,0},{67,165,107,14,16,73,39,11,40,13,22,6,15,20,19,30,29,28,0,0,0,0,0,0,0,0,0,0,0,0}},
   {15,18,3,4,23,{167,235,201,0,0,0,0,0,0,0,0},{224,0,0,0,0,0,0,0,0,0,0},{128,41,71,43,16,73,39,11,77,45,22,6,24,20,19,26,29,28,0,0,0,0,0,0,0,0,0,0,0,0}},
   {8,19,2,0,24,{144,221,0,0,0,0,0,0,0,0,0},{0,0,0,0,0,0,0,0,0,0,0},{65,165,78,43,16,39,104,8,11,13,22,6,24,27,19,30,29,28,25,0,0,0,0,0,0,0,0,0,0,0}},
   {9,18,2,17,25,{53,238,0,0,0,0,0,0,0,0,0},{0,127,0,0,0,0,0,0,0,0,0},{66,161,107,14,103,5,104,8,11,10,70,88,22,15,19,31,23,28,0,0,0,0,0,0,0,0,0,0,0,0}},
   {10,19,2,30,26,{138,247,0,0,0,0,0,0,0,0,0},{0,240,0,0,0,0,0,0,0,0,0},{128,161,162,14,103,5,104,8,9,13,10,6,15,20,19,93,30,28,25,0,0,0,0,0,0,0,0,0,0,0}},
   {11,18,3,7,27,{80,147,160,0,0,0,0,0,0,0,0},{0,0,0,0,0,0,0,0,0,0,0},{100,1,3,14,103,5,8,109,11,13,22,18,17,20,19,93,23,28,0,0,0,0,0,0,0,0,0,0,0,0}},
   {12,18,4,31,28,{104,51,245,224,0,0,0,0,0,0,0},{0,0,0,0,0,0,0,0,0,0,0},{96,106,107,7,5,39,16,11,45,21,10,18,17,15,19,30,26,23,0,0,0,0,0,0,0,0,0,0,0,0}},
   {13,17,4,34,29,{64,82,164,243,0,0,0,0,0,0,0},{0,0,27,8,0,0,0,0,0,0,0},{96,106,102,69,103,8,9,109,77,86,70,88,84,83,95,93,92,0,0,0,0,0,0,0,0,0,0,0,0,0}},
   {14,19,3,2,30,{176,254,232,0,0,0,0,0,0,0,0},{0,0,0,0,0,0,0,0,0,0,0},{132,41,162,7,5,8,35,44,21,45,10,18,17,24,27,31,26,23,25,0,0,0,0,0,0,0,0,0,0,0}},
   {15,18,3,27,31,{88,50,215,0,0,0,0,0,0,0,0},{0,0,128,0,0,0,0,0,0,0,0},{66,161,78,69,72,35,44,85,40,10,18,17,15,27,95,30,23,25,0,0,0,0,0,0,0,0,0,0,0,0}},
   {8,3,5,15,255,{34,28,79,54,216,0,0,0,0,0,0},{0,0,0,0,0,0,0,0,0,0,0},{132,41,140,0,0,0,0,0,0,0,0,0,0,0,0,0,0,0,0,0,0,0,0,0,0,0,0,0,0,0}},
   {9,3,6,5,255,{2,12,59,77,126,206,0,0,0,0,0},{0,0,0,0,0,64,0,0,0,0,0},{128,36,162,0,0,0,0,0,0,0,0,0,0,0,0,0,0,0,0,0,0,0,0,0,0,0,0,0,0,0}},
   {10,3,6,16,255,{4,117,41,109,140,230,0,0,0,0,0},{0,0,0,0,0,0,0,0,0,0,0},{96,106,107,0,0,0,0,0,0,0,0,0,0,0,0,0,0,0,0,0,0,0,0,0,0,0,0,0,0,0}},
   {11,3,6,1,255,{35,19,115,75,199,237,0,0,0,0,0},{0,0,0,0,0,0,0,0,0,0,0},{105,2,140,0,0,0,0,0,0,0,0,0,0,0,0,0,0,0,0,0,0,0,0,0,0,0,0,0,0,0}},
   {12,3,5,13,255,{10,102,111,197,120,0,0,0,0,0,0},{0,0,0,0,0,0,0,0,0,0,0},{66,165,102,0,0,0,0,0,0,0,0,0,0,0,0,0,0,0,0,0,0,0,0,0,0,0,0,0,0,0}},
   {13,5,5,6,255,{24,29,43,172,223,0,0,0,0,0,0},{0,0,0,0,0,0,0,0,0,0,0},{132,161,140,7,99,0,0,0,0,0,0,0,0,0,0,0,0,0,0,0,0,0,0,0,0,0,0,0,0,0}},
   {14,3,7,40,255,{3,101,175,49,177,137,213,0,0,0,0},{0,0,0,0,0,0,48,0,0,0,0},{66,161,102,0,0,0,0,0,0,0,0,0,0,0,0,0,0,0,0,0,0,0,0,0,0,0,0,0,0,0}},
   {15,3,9,38,255,{32,30,133,90,81,193,194,252,184,0,0},{0,0,0,0,0,0,0,0,0,0,0},{65,36,140,0,0,0,0,0,0,0,0,0,0,0,0,0,0,0,0,0,0,0,0,0,0,0,0,0,0,0}},
   {8,3,6,46,255,{33,11,61,93,141,207,0,0,0,0,0},{0,0,0,22,0,128,0,0,0,0,0},{128,36,3,0,0,0,0,0,0,0,0,0,0,0,0,0,0,0,0,0,0,0,0,0,0,0,0,0,0,0}},
   {9,3,7,26,255,{0,20,135,74,178,157,250,0,0,0,0},{0,0,0,0,0,0,0,0,0,0,0},{65,165,3,0,0,0,0,0,0,0,0,0,0,0,0,0,0,0,0,0,0,0,0,0,0,0,0,0,0,0}},
   {10,3,6,22,255,{37,25,70,89,83,195,0,0,0,0,0},{0,0,0,0,0,0,0,0,0,0,0},{100,2,140,0,0,0,0,0,0,0,0,0,0,0,0,0,0,0,0,0,0,0,0,0,0,0,0,0,0,0}},
   {11,3,6,12,255,{39,78,106,146,220,211,0,0,0,0,0},{0,0,0,0,7,15,0,0,0,0,0},{132,165,102,0,0,0,0,0,0,0,0,0,0,0,0,0,0,0,0,0,0,0,0,0,0,0,0,0,0,0}},
   {12,3,6,2,255,{7,58,130,86,156,187,0,0,0,0,0},{255,0,0,0,0,0,0,0,0,0,0},{128,41,3,0,0,0,0,0,0,0,0,0,0,0,0,0,0,0,0,0,0,0,0,0,0,0,0,0,0,0}},
   {13,3,7,35,255,{22,60,91,181,162,241,210,0,0,0,0},{0,0,0,0,0,0,0,0,0,0,0},{66,165,162,0,0,0,0,0,0,0,0,0,0,0,0,0,0,0,0,0,0,0,0,0,0,0,0,0,0,0}},
   {14,3,5,12,255,{16,31,69,170,198,0,0,0,0,0,0},{0,0,0,0,3,0,0,0,0,0,0},{65,36,140,0,0,0,0,0,0,0,0,0,0,0,0,0,0,0,0,0,0,0,0,0,0,0,0,0,0,0}},
   {15,4,5,9,255,{9,63,67,55,214,0,0,0,0,0,0},{0,0,0,128,64,0,0,0,0,0,0},{132,32,42,38,0,0,0,0,0,0,0,0,0,0,0,0,0,0,0,0,0,0,0,0,0,0,0,0,0,0}},
   {8,3,5,42,255,{36,100,131,183,246,0,0,0,0,0,0},{0,0,0,237,0,0,0,0,0,0,0},{96,106,162,0,0,0,0,0,0,0,0,0,0,0,0,0,0,0,0,0,0,0,0,0,0,0,0,0,0,0}},
   {9,3,6,33,255,{14,57,132,151,244,227,0,0,0,0,0},{0,0,0,128,0,0,0,0,0,0,0},{96,106,140,0,0,0,0,0,0,0,0,0,0,0,0,0,0,0,0,0,0,0,0,0,0,0,0,0,0,0}},
   {10,3,5,21,255,{6,71,150,218,236,0,0,0,0,0,0},{0,0,0,0,0,0,0,0,0,0,0},{65,165,102,0,0,0,0,0,0,0,0,0,0,0,0,0,0,0,0,0,0,0,0,0,0,0,0,0,0,0}},
   {11,3,5,29,255,{5,99,42,87,255,0,0,0,0,0,0},{0,0,0,0,255,0,0,0,0,0,0},{128,161,162,0,0,0,0,0,0,0,0,0,0,0,0,0,0,0,0,0,0,0,0,0,0,0,0,0,0,0}},
   {12,3,6,39,255,{15,114,174,145,139,212,0,0,0,0,0},{24,0,0,0,0,0,0,0,0,0,0},{132,161,162,0,0,0,0,0,0,0,0,0,0,0,0,0,0,0,0,0,0,0,0,0,0,0,0,0,0,0}},
   {13,4,6,16,255,{8,103,68,107,165,152,0,0,0,0,0},{0,0,0,0,0,0,0,0,0,0,0},{128,41,3,14,0,0,0,0,0,0,0,0,0,0,0,0,0,0,0,0,0,0,0,0,0,0,0,0,0,0}},
   {14,3,6,0,255,{38,98,92,143,155,204,0,0,0,0,0},{0,0,0,0,15,0,0,0,0,0,0},{128,32,42,0,0,0,0,0,0,0,0,0,0,0,0,0,0,0,0,0,0,0,0,0,0,0,0,0,0,0}},
   {15,3,5,37,255,{23,44,171,180,191,0,0,0,0,0,0},{0,0,0,13,128,0,0,0,0,0,0},{67,165,162,0,0,0,0,0,0,0,0,0,0,0,0,0,0,0,0,0,0,0,0,0,0,0,0,0,0,0}},
   {6,2,6,4,255,{1,18,27,95,127,240,0,0,0,0,0},{0,0,0,0,124,0,0,0,0,0,0},{128,4,0,0,0,0,0,0,0,0,0,0,0,0,0,0,0,0,0,0,0,0,0,0,0,0,0,0,0,0}},
   {7,5,5,28,255,{13,116,110,158,186,0,0,0,0,0,0},{0,0,0,0,0,0,0,0,0,0,0},{97,98,108,110,112,0,0,0,0,0,0,0,0,0,0,0,0,0,0,0,0,0,0,0,0,0,0,0,0,0}}},
  {{0,20,0,0},{0,7,0,0},{28,64,0,0},{23,64,0,0},{23,64,0,0},{17,64,0,0},{11,64,0,0},{12,24,0,0},{13,29,0,0},{0,13,0,0},{25,64,0,0},
   {22,64,0,0},{23,64,0,0},{0,2,0,0},{11,64,0,0},{5,64,0,0},{0,5,0,0},{0,0,0,0},{7,21,0,0},{19,64,0,0},{0,5,0,0},{24,64,0,0},
   {13,25,0,0},{10,64,0,0},{11,23,0,0},{7,19,0,0},{29,64,0,0},{12,26,0,0},{0,10,0,0},{0,14,0,0},{0,11,0,0},{11,23,0,0},{24,64,0,0},
   {5,22,0,0},{0,12,0,0},{12,64,0,0},{0,12,0,0},{0,11,0,0},{33,64,0,0},{0,11,0,0},{14,64,0,0},{13,23,0,0},{10,23,0,0},{10,28,0,0},
   {21,64,0,0},{26,64,0,0},{0,10,0,0},{0,13,0,0},{0,0,0,0},{0,14,0,0},{20,64,0,0},{2,20,0,0},{14,33,0,0},{0,10,0,0},{20,64,0,0},
   {3,23,0,0},{0,12,0,0},{0,3,0,0},{0,17,0,0},{0,13,0,0},{0,14,0,0},{23,64,0,0},{14,24,0,0},{0,7,0,0},{23,64,0,0},{0,11,0,0}},
  {{12,52,36,44,26,58,20,42,22,18,16,32,10,47,57,15,25,7,3,50,1,9,5,4,41,40,55,49,48,54,35,34,13,31,30,39,61,60,63,62,38,53,37,45,27,59,21,43,23,19,17,33,11,29,46,56,28,14,24,6,51,2,0,8},
   {58,13,36,27,20,23,18,33,10,29,12,45,26,43,22,17,32,46,56,15,25,7,3,50,1,9,5,4,49,48,55,54,41,31,30,40,61,60,63,62,39,38,53,52,35,59,34,37,44,21,42,19,16,11,47,57,28,14,24,6,51,2,0,8},
   {49,52,55,41,59,34,37,44,21,42,19,16,10,29,35,12,45,26,43,22,17,32,47,57,28,25,7,3,50,1,9,5,4,31,30,39,61,60,63,62,38,53,48,54,40,58,13,36,27,20,23,18,33,11,46,56,15,14,24,6,51,2,0,8},
   {54,28,61,14,24,63,6,2,4,0,59,37,36,13,49,48,12,27,26,41,40,45,44,21,20,43,42,23,22,19,35,31,30,34,18,17,16,33,32,11,10,39,38,55,29,15,60,25,7,62,3,5,1,9,58,8,53,52,46,47,56,57,50,51},
   {20,42,60,22,18,62,16,32,10,15,14,28,58,24,52,6,2,4,46,0,57,8,51,45,44,41,40,49,48,35,34,31,30,37,36,13,12,27,26,21,55,39,38,54,43,61,23,19,63,17,33,11,29,59,25,53,7,3,5,47,1,9,56,50},
   {38,54,23,19,61,17,33,63,11,29,15,25,59,7,53,2,4,0,46,8,56,50,51,45,44,41,40,49,48,37,36,35,31,30,34,13,12,27,26,21,20,43,39,55,42,22,18,60,16,32,62,10,28,14,24,58,6,52,3,5,1,47,9,57},
   {38,27,43,19,23,17,33,11,28,63,24,5,10,15,62,7,4,47,53,59,61,2,57,8,0,51,31,30,49,48,35,34,13,12,37,36,21,41,55,54,40,20,45,39,44,26,42,18,22,16,32,29,14,25,6,3,46,52,58,60,9,56,1,50},
   {39,10,28,14,24,6,3,9,1,62,60,46,45,44,21,20,27,37,31,30,35,34,13,12,36,26,43,42,19,49,48,18,23,22,17,16,33,41,55,54,40,32,11,38,29,15,25,7,5,4,2,8,0,63,61,47,58,53,52,59,56,57,50,51},
   {33,11,29,15,63,24,5,62,7,4,47,53,59,61,2,57,1,50,51,31,30,35,34,13,12,37,36,21,20,49,48,45,44,27,26,43,42,41,55,54,40,19,18,39,38,23,22,17,16,32,10,28,14,25,6,3,46,52,58,60,9,56,8,0},
   {14,7,63,22,39,18,16,32,10,28,25,6,62,3,60,47,52,58,8,0,57,50,51,45,37,36,13,12,44,21,20,31,35,49,48,34,30,27,26,41,40,43,42,55,54,23,19,38,17,33,11,29,15,24,5,4,61,2,46,53,59,9,1,56},
   {23,19,39,17,33,11,29,15,25,6,62,7,63,3,61,9,53,59,46,0,57,50,51,45,44,37,36,13,12,21,20,27,35,49,48,34,31,30,26,41,40,43,42,55,54,22,18,38,16,32,10,28,14,24,5,4,2,60,8,52,58,47,1,56},
   {14,39,24,6,4,2,8,0,63,61,27,26,43,42,23,21,20,22,19,18,17,16,45,37,36,13,12,44,33,32,31,49,48,35,34,30,11,10,41,40,29,28,55,54,15,25,38,7,5,3,9,1,62,60,46,47,52,53,58,59,56,57,50,51},
   {52,14,23,61,17,32,10,28,53,62,24,6,2,4,8,58,0,47,57,51,21,20,37,36,45,44,27,26,13,12,43,35,49,48,34,31,30,42,19,41,40,39,55,54,38,18,22,60,16,33,11,29,15,63,25,7,3,5,9,59,1,46,56,50},
   {61,22,16,11,15,14,25,32,29,53,63,24,6,2,4,8,58,46,56,50,51,21,45,37,36,44,20,27,13,12,26,43,49,48,35,31,30,34,42,19,41,40,55,54,39,38,18,23,60,17,33,10,28,52,62,7,3,5,9,1,59,0,47,57},
   {55,38,44,20,26,42,60,23,16,11,28,63,14,18,17,32,29,52,15,24,6,2,4,8,58,0,47,57,51,13,12,35,49,48,34,31,30,37,36,41,40,39,54,45,21,27,43,61,19,22,33,10,53,62,25,7,3,5,9,59,1,46,56,50},
   {16,38,32,10,14,28,24,6,2,4,8,63,0,61,21,20,27,26,43,42,19,18,45,44,23,37,36,22,13,12,35,34,49,48,17,31,55,54,30,41,40,39,33,11,15,29,25,7,3,5,9,1,62,60,52,53,58,59,46,47,56,57,50,51},
   {43,19,23,17,33,11,15,63,25,61,29,28,7,6,2,53,4,58,8,0,47,57,51,45,44,37,36,21,13,12,35,34,49,48,20,31,55,54,30,41,40,39,38,27,26,42,18,22,16,32,10,14,62,24,60,3,5,52,59,9,1,46,56,50},
   {11,14,29,24,60,23,17,33,10,62,25,61,3,5,52,58,9,1,46,56,50,51,45,44,21,37,36,20,13,12,35,34,27,49,48,41,55,54,31,30,40,26,39,38,43,42,19,18,22,16,32,15,63,28,7,6,2,53,59,4,8,0,47,57},
   {40,42,39,62,22,18,16,11,29,15,24,3,25,6,60,1,52,5,9,58,46,56,50,51,37,36,45,13,12,44,21,35,34,49,48,20,31,30,27,26,41,55,54,43,23,63,38,19,17,33,32,10,28,14,7,61,2,53,0,4,59,8,47,57},
   {2,0,4,8,61,43,42,23,22,27,26,19,18,17,16,33,21,20,32,11,10,29,45,37,36,44,13,12,28,15,14,35,49,48,34,31,30,25,24,41,40,55,54,7,6,63,62,39,38,3,1,5,9,60,52,53,58,59,46,47,56,57,50,51},
   {54,26,42,62,38,22,18,16,32,10,28,25,61,15,24,60,3,53,0,4,58,8,47,57,51,37,13,12,36,45,44,35,49,48,34,31,30,21,20,41,40,55,27,43,63,39,23,19,17,33,11,29,14,7,6,2,52,1,5,59,9,46,56,50},
   {32,10,28,14,24,6,62,61,52,58,9,3,46,1,56,50,51,21,20,27,26,43,42,37,36,13,35,34,12,45,44,23,49,48,22,19,31,30,55,54,41,40,18,17,16,39,38,33,11,29,15,25,7,5,63,4,53,59,60,8,47,2,0,57},
   {18,38,16,32,10,28,14,24,6,63,4,53,59,60,8,47,2,56,50,51,21,20,37,36,45,13,35,34,12,44,27,26,49,48,43,42,31,30,55,54,41,40,23,22,19,39,17,33,11,29,15,25,7,5,62,61,52,58,9,3,46,1,0,57},
   {28,39,14,24,6,4,8,2,0,63,61,27,26,43,42,23,21,20,22,19,18,17,37,36,45,13,35,34,12,44,16,33,49,48,32,31,30,11,55,41,40,54,10,29,15,38,25,7,5,9,3,1,62,60,52,53,58,59,46,47,56,57,50,51}},
  {{0,0,1,0,0,0,0,2},{3,3,2,2,3,3,1,1},{2,2,3,3,2,2,3,3},{4,4,4,4,4,4,4,4},
   {1,1,0,1,1,1,2,0},{8,8,8,8,8,8,8,8},{1,5,6,7,8,8,8,8},{6,6,6,6,6,6,6,6},
   {10,10,10,10,10,10,10,10},{12,12,12,12,12,11,11,11},{2,2,4,4,5,5,5,5},{11,11,11,11,11,2,3,3},
   {5,5,5,5,5,5,5,5},{14,14,3,3,4,4,2,0},{7,7,7,7,7,7,7,7},{9,9,9,9,6,6,11,3},
   {9,9,9,9,9,9,9,9},{7,7,7,8,9,9,9,9},{5,1,0,1,7,7,7,6},{10,3,13,13,4,4,2,4},
   {8,8,10,6,12,11,3,11},{13,13,13,13,2,1,4,4},{4,4,5,5,1,3,1,7},{5,4,6,7,10,10,10,3},
   {6,6,8,10,10,10,10,10},{9,9,10,12,4,4,2,4},{11,12,4,11,7,7,8,5},{3,10,2,12,2,1,4,0},
   {7,5,8,10,2,1,4,0},{2,2,0,1,8,8,7,10},{14,14,12,4,1,2,6,9},{13,13,3,3,5,5,5,1}},
  {{255,255,255,255,255,255,255,255},{255,255,255,255,255,255,255,255},{255,255,255,255,255,255,255,255},{255,255,255,255,255,255,255,255},
   {255,255,255,255,255,255,255,255},{255,255,255,255,255,255,255,255},{4,12,7,14,5,5,5,5},{255,255,255,255,255,255,255,255},
   {255,255,255,255,255,255,255,255},{255,255,255,255,255,255,255,255},{2,2,3,3,12,12,12,12},{255,255,255,255,255,2,2,2},
   {255,255,255,255,255,255,255,255},{255,255,2,2,3,3,4,4},{255,255,255,255,255,255,255,255},{16,16,16,16,7,7,9,11},
   {255,255,255,255,255,255,255,255},{14,14,14,5,16,16,16,16},{12,4,4,4,14,14,14,7},{8,1,21,21,13,13,13,21},
   {5,5,8,7,9,9,11,9},{255,255,255,255,2,4,3,3},{3,3,12,12,4,1,1,14},{18,22,6,6,24,24,24,15},
   {7,7,5,8,8,8,8,8},{15,15,20,27,19,19,19,19},{11,9,10,11,18,18,6,10},{1,8,1,9,21,21,21,13},
   {17,6,24,24,27,27,27,27},{10,10,18,18,6,6,18,24},{13,13,9,10,22,11,7,17},{21,21,13,13,10,10,10,1}}};

typedef CUresult (*EncodeFn)(CUtensorMap*, CUtensorMapDataType, cuuint32_t, void*, const cuuint64_t*, const cuuint64_t*, const cuuint32_t*,
                             const cuuint32_t*, CUtensorMapInterleave, CUtensorMapSwizzle, CUtensorMapL2promotion, CUtensorMapFloatOOBfill);

void make_map2(EncodeFn enc, CUtensorMap* m, const void* ptr, int rows, int cols, int box_rows) {
  cuuint64_t dim[2] = {(cuuint64_t)cols, (cuuint64_t)rows}, str[1] = {(cuuint64_t)cols * 2};
  cuuint32_t box[2] = {64, (cuuint32_t)box_rows}, es[2] = {1, 1};
  enc(m, CU_TENSOR_MAP_DATA_TYPE_BFLOAT16, 2, const_cast<void*>(ptr), dim, str, box, es, CU_TENSOR_MAP_INTERLEAVE_NONE, CU_TENSOR_MAP_SWIZZLE_128B,
      CU_TENSOR_MAP_L2_PROMOTION_L2_128B, CU_TENSOR_MAP_FLOAT_OOB_FILL_NONE);
}
void make_map3(EncodeFn enc, CUtensorMap* m, const void* ptr, int rows) {
  cuuint64_t dim[3] = {64, (cuuint64_t)rows, 9}, str[2] = {DM * 2, 128};
  cuuint32_t box[3] = {64, 32, 3}, es[3] = {1, 1, 1};
  enc(m, CU_TENSOR_MAP_DATA_TYPE_BFLOAT16, 3, const_cast<void*>(ptr), dim, str, box, es, CU_TENSOR_MAP_INTERLEAVE_NONE, CU_TENSOR_MAP_SWIZZLE_128B,
      CU_TENSOR_MAP_L2_PROMOTION_L2_128B, CU_TENSOR_MAP_FLOAT_OOB_FILL_NONE);
}

void make_map_t(EncodeFn enc, CUtensorMap* m, void* ptr, int width, int cols) {
  cuuint64_t dim[3] = {TP / 2, 2, 864}, str[2] = {TP * 2, TP * 4};
  cuuint32_t box[3] = {(cuuint32_t)width, 2, (cuuint32_t)cols}, es[3] = {1, 1, 1};
  enc(m, CU_TENSOR_MAP_DATA_TYPE_UINT32, 3, ptr, dim, str, box, es, CU_TENSOR_MAP_INTERLEAVE_NONE, cols == 64 ? CU_TENSOR_MAP_SWIZZLE_128B : CU_TENSOR_MAP_SWIZZLE_NONE,
      CU_TENSOR_MAP_L2_PROMOTION_NONE, CU_TENSOR_MAP_FLOAT_OOB_FILL_NONE);
}

int g_mode = -1;

}

extern "C" void kernel_launch(void* const* d_in, const int* in_sizes, int n_in, void* d_out, int out_size) {
  static EncodeFn enc = nullptr;
  static void* t_ptr = nullptr;
  if (!enc) {
    void* fn = nullptr;
    cudaDriverEntryPointQueryResult st;
    cudaGetDriverEntryPoint("cuTensorMapEncodeTiled", &fn, cudaEnableDefault, &st);
    enc = (EncodeFn)fn;
    cudaGetSymbolAddress(&t_ptr, g_T);
    cudaFuncSetAttribute(fused_kernel, cudaFuncAttributeMaxDynamicSharedMemorySize, SMEM_BYTES);
    if (g_mode < 0) {
      cudaLaunchConfig_t cfg = {};
      cfg.gridDim = dim3(2 * NCL); cfg.blockDim = dim3(384); cfg.dynamicSmemBytes = SMEM_BYTES;
      cudaLaunchAttribute at; at.id = cudaLaunchAttributeClusterDimension;
      at.val.clusterDim.x = 2; at.val.clusterDim.y = 1; at.val.clusterDim.z = 1;
      cfg.attrs = &at; cfg.numAttrs = 1;
      int nc = 0;
      g_mode = (cudaOccupancyMaxActiveClusters(&nc, fused_kernel, &cfg) == cudaSuccess && nc >= NCL) ? 1 : 0;
      (void)cudaGetLastError();
    }
  }
  Params p;
  make_map2(enc, &p.map_a[0], d_in[4], SEQ, DC, 128);
  make_map2(enc, &p.map_a[1], d_in[0], SEQ, DM, 128);
  make_map2(enc, &p.map_w[0], d_in[6], DC, 4096, 64);
  make_map2(enc, &p.map_w[1], d_in[7], DC, 4096, 64);
  make_map2(enc, &p.map_w[2], d_in[5], DM, 4096, 64);
  make_map2(enc, &p.map_w[3], d_in[1], DM, 1728, 64);
  make_map3(enc, &p.map_o[0], d_in[8], 4096);
  make_map3(enc, &p.map_o[1], d_in[2], DM);
  make_map_t(enc, &p.map_t[0], t_ptr, 32, 9);
  make_map_t(enc, &p.map_t[1], t_ptr, 40, 9);
  make_map_t(enc, &p.map_t[2], t_ptr, 32, 64);
  p.x = (const __nv_bfloat16*)d_in[0];
  p.gate_w = (const __nv_bfloat16*)d_in[9];
  make_map2(enc, &p.map_out, d_out, SEQ, DM, 64);
  p.out = (__nv_bfloat16*)d_out;
  p.zero = 0;
  auto launch = [&](int phases) {
    p.s = k_sched;
    for (int i = 0; i < NCL; i++) {
      Rec& r = p.s.r[i];
      if (!(phases & 1)) r.n1 = 0;
      if (!(phases & 2)) r.n2 = 0;
      if (!(phases & (p.s.task[i][1] == 64 ? 4 : 32))) r.p3 = 255;
      if (!(phases & 8)) r.bg = 255;
      const int u1 = r.n1 ? 8 + r.n1 * (8 + (r.slab >> 3)) : 0;
      int u2 = 0;
      for (int k = 0; k < r.n2; k++) u2 += 4 * (r.item[k] & 7) + 4;
      r.u1 = (uint8_t)u1; r.u2 = (uint8_t)u2;
      r.rot = (uint8_t)(((u1 % 10 + 1) >> 1) % 5);
      r.x3 = (uint8_t)((r.rot + u2) % 5 & 3);
      r.phases = (uint8_t)phases;
    }
    if (!(phases & 16))
      for (int i = 0; i < 256; i++) { p.s.slot[i >> 3][i & 7] = (uint8_t)(i >> 3); p.s.prev[i >> 3][i & 7] = 255; }
    fused_kernel<<<2 * NCL, 384, SMEM_BYTES>>>(p);
  };
  if (g_mode == 1) launch(63);
  else { launch(1); launch(10); launch(4); launch(32); }
}
```

```cpp
#include <cuda_runtime.h>
#include <cuda_bf16.h>
#include <cuda.h>
#include <stdint.h>

namespace {

constexpr int SEQ = 2048, DM = 576, DC = 512, NH = 32;
constexpr int NCL = 66;
constexpr uint32_t DESC_HI = 0x40000040u;

constexpr int SM_RING = 0;
constexpr int SM_BUF = 163840;
constexpr int SM_BAR = 229376;
constexpr int B_P1E = 0, B_P2E = 10, B_P3E = 15, B_P2F = 24, B_SF = 32, B_ORD = 36, B_LAD = 40, B_DONE = 41, B_FIN = 48;
constexpr int B_P3F = 56, B_OUT = 61, B_P1F = 64, B_SE = 74, B_QF = 80, B_LA = 84, B_NUM = 88;
constexpr uint64_t B_CNT = 0x11118245000ull;
constexpr int SMEM_BYTES = SM_BAR + B_NUM * 8 + 1024;

constexpr int F_QKVA = 32;
constexpr int F_GATE = 64;
constexpr int F_TS = 68;
constexpr int F_DONE = 65;
constexpr int F_CTX = 96;
constexpr int F_OUT = 96 + 8 * 64;
constexpr int F_KV = F_OUT + 64;
constexpr int F_Q = F_KV + 256;
constexpr int F_RD = F_Q + 256;
constexpr int F_NUM = F_RD + 256;

struct Rec {
  uint8_t slab;
  uint8_t n1, n2;
  uint8_t p3;
  uint8_t bg;
  uint8_t item[11];
  uint8_t last[11];
  uint8_t tile[32];
  uint8_t u1, u2;
  uint8_t rot, x3;
  uint8_t phases;
};
struct Sched {
  Rec r[NCL];
  uint8_t task[NCL][4];
  uint8_t p3_order[24][64];
  uint8_t slot[32][8];
  uint8_t prev[32][8];
  uint16_t qblk[256];
  uint16_t qdep[256];
};

#define SCHED_DECL static const

struct Params {
  CUtensorMap map_a[2];
  CUtensorMap map_w[4];
  CUtensorMap map_o[2];
  CUtensorMap map_t[3];
  CUtensorMap map_out;
  const __nv_bfloat16* x;
  const __nv_bfloat16* gate_w;
  __nv_bfloat16* out;
  int zero;
  alignas(64) Sched s;
};

constexpr int S_T = 0, S_Q = 112, S_K = S_Q + 256, S_V = S_K + 256, S_NUM = S_V + 256;
__device__ __align__(1024) uint8_t g_S[(size_t)S_NUM * 65536];
__device__ __align__(1024) uint8_t g_oA[32 * 576 * 128];
__device__ float g_gate[SEQ];
__device__ int g_flags[F_NUM];
#define PL(i)

__device__ __forceinline__ void mbar_arrive(uint32_t b) { asm volatile("mbarrier.arrive.shared::cta.b64 _, [%0];" ::"r"(b) : "memory"); }
__device__ __forceinline__ void mbar_arrive_cl(uint32_t b, int cnt) {
  asm volatile("mbarrier.arrive.shared::cluster.b64 _, [%0], %1;" ::"r"(b), "r"(cnt) : "memory");
}
__device__ __forceinline__ void mbar_wait(uint32_t b, int par) {
  asm volatile(
      "{\n.reg .pred p;\n.reg .u32 c;\n"
      "mbarrier.try_wait.parity.shared::cta.b64 p, [%0], %1;\n@p bra DN;\nmov.u32 c, 0;\n"
      "LP:\nmbarrier.try_wait.parity.shared::cta.b64 p, [%0], %1;\n@p bra DN;\n"
      "add.u32 c, c, 1;\nsetp.lt.u32 p, c, 4000000;\n@p bra LP;\ntrap;\nDN:\n}" ::"r"(b), "r"(par) : "memory");
}
__device__ __forceinline__ uint32_t mapa(uint32_t a, uint32_t cta) {
  uint32_t r; asm("mapa.shared::cluster.u32 %0, %1, %2;" : "=r"(r) : "r"(a), "r"(cta)); return r;
}
#define ELECT(ins) "{\n.reg .pred e;\nelect.sync _|e, 0xffffffff;\n@e " ins "\n}"
__device__ __forceinline__ void mbar_expect(uint32_t b, int bytes) {
  asm volatile(ELECT("mbarrier.arrive.expect_tx.shared::cta.b64 _, [%0], %1;") ::"r"(b), "r"(bytes) : "memory");
}
__device__ __forceinline__ void mbar_arrive_one(uint32_t b) { asm volatile(ELECT("mbarrier.arrive.shared::cta.b64 _, [%0];") ::"r"(b) : "memory"); }
constexpr uint64_t L2_NORMAL = 0x1000000000000000ull, L2_FIRST = 0x12F0000000000000ull;
__device__ __forceinline__ void bulk_load(uint32_t dst, const void* src, int bytes, uint32_t bar, uint64_t pol = L2_NORMAL) {
  asm volatile(ELECT("cp.async.bulk.shared::cluster.global.mbarrier::complete_tx::bytes.L2::cache_hint [%0], [%1], %2, [%3], %4;") ::"r"(dst), "l"(src), "r"(bytes), "r"(bar), "l"(pol) : "memory");
}
__device__ __forceinline__ void bulk_load_mc(uint32_t dst, const void* src, int bytes, uint32_t bar, uint64_t pol = L2_NORMAL) {
  asm volatile(ELECT("cp.async.bulk.shared::cluster.global.mbarrier::complete_tx::bytes.multicast::cluster.L2::cache_hint [%0], [%1], %2, [%3], %4, %5;") ::"r"(dst), "l"(src), "r"(bytes), "r"(bar), "h"((uint16_t)3), "l"(pol) : "memory");
}
__device__ __forceinline__ void bulk_store(void* dst, uint32_t src, int bytes, uint64_t pol = L2_NORMAL) {
  asm volatile(ELECT("cp.async.bulk.global.shared::cta.bulk_group.L2::cache_hint [%0], [%1], %2, %3;") ::"l"(dst), "r"(src), "r"(bytes), "l"(pol) : "memory");
}
__device__ __forceinline__ void tma2d(uint32_t dst, const CUtensorMap* m, int c0, int c1, uint32_t bar, uint64_t pol = L2_NORMAL) {
  asm volatile(ELECT("cp.async.bulk.tensor.2d.shared::cluster.global.mbarrier::complete_tx::bytes.L2::cache_hint [%0], [%1, {%3, %4}], [%2], %5;") ::"r"(dst), "l"(m), "r"(bar), "r"(c0), "r"(c1), "l"(pol) : "memory");
}
__device__ __forceinline__ void tma2d_mc(uint32_t dst, const CUtensorMap* m, int c0, int c1, uint32_t bar, uint64_t pol = L2_NORMAL) {
  asm volatile(ELECT("cp.async.bulk.tensor.2d.shared::cluster.global.mbarrier::complete_tx::bytes.multicast::cluster.L2::cache_hint [%0], [%1, {%3, %4}], [%2], %5, %6;") ::"r"(dst), "l"(m), "r"(bar), "r"(c0), "r"(c1), "h"((uint16_t)3), "l"(pol) : "memory");
}
__device__ __forceinline__ void tma3d(uint32_t dst, const CUtensorMap* m, int c0, int c1, int c2, uint32_t bar, uint64_t pol = L2_NORMAL) {
  asm volatile(ELECT("cp.async.bulk.tensor.3d.shared::cluster.global.mbarrier::complete_tx::bytes.L2::cache_hint [%0], [%1, {%3, %4, %5}], [%2], %6;") ::"r"(dst), "l"(m), "r"(bar), "r"(c0), "r"(c1), "r"(c2), "l"(pol) : "memory");
}
__device__ __forceinline__ void tma3d_mc(uint32_t dst, const CUtensorMap* m, int c0, int c1, int c2, uint32_t bar, uint64_t pol = L2_NORMAL) {
  asm volatile(ELECT("cp.async.bulk.tensor.3d.shared::cluster.global.mbarrier::complete_tx::bytes.multicast::cluster.L2::cache_hint [%0], [%1, {%3, %4, %5}], [%2], %6, %7;") ::"r"(dst), "l"(m), "r"(bar), "r"(c0), "r"(c1), "r"(c2), "h"((uint16_t)3), "l"(pol) : "memory");
}
__device__ __forceinline__ void tma2d_add(const CUtensorMap* m, uint32_t src, int c0, int c1) {
  asm volatile(ELECT("cp.reduce.async.bulk.tensor.2d.global.shared::cta.add.bulk_group [%0, {%2, %3}], [%1];") ::"l"(m), "r"(src), "r"(c0), "r"(c1) : "memory");
}
__device__ __forceinline__ void tma3d_store(const CUtensorMap* m, uint32_t src, int c0, int c1, int c2, uint64_t pol = L2_NORMAL) {
  asm volatile(ELECT("cp.async.bulk.tensor.3d.global.shared::cta.bulk_group.L2::cache_hint [%0, {%2, %3, %4}], [%1], %5;") ::"l"(m), "r"(src), "r"(c0), "r"(c1), "r"(c2), "l"(pol) : "memory");
}
__device__ __forceinline__ void tma2d_prefetch(const CUtensorMap* m, int c0, int c1, uint64_t pol = L2_NORMAL) {
  asm volatile(ELECT("cp.async.bulk.prefetch.tensor.2d.L2.global.L2::cache_hint [%0, {%1, %2}], %3;") ::"l"(m), "r"(c0), "r"(c1), "l"(pol) : "memory");
}
#define LAG 3
#define HINT 62
#define POL(bit) ((HINT >> (bit)) & 1 ? L2_FIRST : L2_NORMAL)
#define BULK_COMMIT() asm volatile("cp.async.bulk.commit_group;" ::: "memory")
#define BULK_WAIT(n) asm volatile("cp.async.bulk.wait_group %0;" ::"n"(n) : "memory")
#define BULK_WAIT_READ(n) asm volatile("cp.async.bulk.wait_group.read %0;" ::"n"(n) : "memory")
#define FENCE_ASYNC_SMEM() asm volatile("fence.proxy.async.shared::cta;" ::: "memory")
#define FENCE_ASYNC_ALL() asm volatile("fence.proxy.async;" ::: "memory")
#define WG_FENCE() asm volatile("wgmma.fence.sync.aligned;" ::: "memory")
#define WG_COMMIT() asm volatile("wgmma.commit_group.sync.aligned;" ::: "memory")
#define WG_WAIT(n) asm volatile("wgmma.wait_group.sync.aligned %0;" ::"n"(n) : "memory")
__device__ __forceinline__ void bar_sync(int id, int n) { asm volatile("bar.sync %0, %1;" ::"r"(id), "r"(n) : "memory"); }
__device__ __forceinline__ void bar_arrive(int id, int n) { asm volatile("bar.arrive %0, %1;" ::"r"(id), "r"(n) : "memory"); }
__device__ __forceinline__ void cluster_sync() {
  asm volatile("barrier.cluster.arrive.relaxed;\nbarrier.cluster.wait.acquire;" ::: "memory");
}
template <int N> __device__ __forceinline__ void pin(float (&r)[N]) {
#pragma unroll
  for (int i = 0; i < N; i++) asm volatile("" : "+f"(r[i])::"memory");
}
template <int N> __device__ __forceinline__ void pin(uint32_t (&r)[N]) {
#pragma unroll
  for (int i = 0; i < N; i++) asm volatile("" : "+r"(r[i])::"memory");
}
__device__ __forceinline__ uint32_t pack_bf16(float lo, float hi) {
  uint32_t r; asm("cvt.rn.bf16x2.f32 %0, %1, %2;" : "=r"(r) : "f"(hi), "f"(lo)); return r;
}
__device__ __forceinline__ float ex2(float x) { float r; asm("ex2.approx.ftz.f32 %0, %1;" : "=f"(r) : "f"(x)); return r; }
__device__ __forceinline__ void ldsm4(uint32_t a, uint32_t& r0, uint32_t& r1, uint32_t& r2, uint32_t& r3) {
  asm volatile("ldmatrix.sync.aligned.m8n8.x4.shared.b16 {%0,%1,%2,%3}, [%4];" : "=r"(r0), "=r"(r1), "=r"(r2), "=r"(r3) : "r"(a) : "memory");
}
__device__ __forceinline__ void stsm4(uint32_t a, uint32_t r0, uint32_t r1, uint32_t r2, uint32_t r3) {
  asm volatile("stmatrix.sync.aligned.m8n8.x4.shared.b16 [%0], {%1,%2,%3,%4};" ::"r"(a), "r"(r0), "r"(r1), "r"(r2), "r"(r3) : "memory");
}
__device__ __forceinline__ void flag_add(int idx, int v = 1) {
  asm volatile(ELECT("red.release.gpu.global.add.s32 [%0], %1;") ::"l"(g_flags + idx), "r"(v) : "memory");
}
__device__ __forceinline__ void flag_add_rx(int idx) {
  asm volatile(ELECT("red.relaxed.gpu.global.add.s32 [%0], 1;") ::"l"(g_flags + idx) : "memory");
}
template <bool ACQ, int NS = 32> __device__ __forceinline__ void flag_wait(int idx, int target) {
  int n = 0;
  while (true) {
    int v;
    if (ACQ) asm volatile("ld.acquire.gpu.global.s32 %0, [%1];" : "=r"(v) : "l"(g_flags + idx) : "memory");
    else asm volatile("ld.relaxed.gpu.global.s32 %0, [%1];" : "=r"(v) : "l"(g_flags + idx) : "memory");
    if (__all_sync(0xffffffffu, v >= target)) break;
    if (++n > 20000000) __trap();
    __nanosleep(NS);
  }
}
__device__ __forceinline__ int flag_peek(int idx) {
  int v;
  asm volatile("ld.relaxed.gpu.global.s32 %0, [%1];" : "=r"(v) : "l"(g_flags + idx) : "memory");
  return v;
}
__device__ __forceinline__ void mask_wait(uint32_t& ready, int bit, int idx, int target) {
  for (int n = 0; !((ready >> bit) & 1); n++) {
    int v;
    if (n) { __nanosleep(32); if (n > 20000000) __trap(); }
    asm volatile("ld.relaxed.gpu.global.s32 %0, [%1];" : "=r"(v) : "l"(g_flags + idx) : "memory");
    ready = __ballot_sync(0xffffffffu, v >= target);
  }
}
__device__ __forceinline__ uint32_t desc_lo(uint32_t addr, uint32_t lbo) { return ((addr & 0x3FFFFu) >> 4) | ((lbo >> 4) << 16); }
#define PROF(role, i)
#define PROFX(cond, i)
#define PROFB(i)
#define PROFG(i)

template <int TB, int TA = 0> __device__ __forceinline__ void wgmma_ss64(float (&d)[32], uint32_t alo, uint32_t blo, int sd) {
  asm volatile("{\n.reg .pred p;\n.reg .b64 da, db;\n"
    "setp.ne.b32 p, %34, 0;\nmov.b64 da, {%32, %36};\nmov.b64 db, {%33, %36};\n"
    "wgmma.mma_async.sync.aligned.m64n64k16.f32.bf16.bf16 "
    "{%0,%1,%2,%3,%4,%5,%6,%7,%8,%9,%10,%11,%12,%13,%14,%15,%16,%17,%18,%19,%20,%21,%22,%23,"
    "%24,%25,%26,%27,%28,%29,%30,%31}, "
    "da, db, p, 1, 1, %37, %35;\n}\n"
    : "+f"(d[0]),"+f"(d[1]),"+f"(d[2]),"+f"(d[3]),"+f"(d[4]),"+f"(d[5]),"+f"(d[6]),"+f"(d[7]),"+f"(d[8]),"+f"(d[9]),"+f"(d[10]),"+f"(d[11]),
      "+f"(d[12]),"+f"(d[13]),"+f"(d[14]),"+f"(d[15]),"+f"(d[16]),"+f"(d[17]),"+f"(d[18]),"+f"(d[19]),"+f"(d[20]),"+f"(d[21]),"+f"(d[22]),"+f"(d[23]),
      "+f"(d[24]),"+f"(d[25]),"+f"(d[26]),"+f"(d[27]),"+f"(d[28]),"+f"(d[29]),"+f"(d[30]),"+f"(d[31])
    : "r"(alo), "r"(blo), "r"(sd), "n"(TB), "r"(DESC_HI), "n"(TA));
}
template <int TB, int TA = 0> __device__ __forceinline__ void wgmma_ss128(float (&d)[64], uint32_t alo, uint32_t blo, int sd) {
  asm volatile("{\n.reg .pred p;\n.reg .b64 da, db;\n"
    "setp.ne.b32 p, %66, 0;\nmov.b64 da, {%64, %68};\nmov.b64 db, {%65, %68};\n"
    "wgmma.mma_async.sync.aligned.m64n128k16.f32.bf16.bf16 "
    "{%0,%1,%2,%3,%4,%5,%6,%7,%8,%9,%10,%11,%12,%13,%14,%15,%16,%17,%18,%19,%20,%21,%22,%23,"
    "%24,%25,%26,%27,%28,%29,%30,%31,%32,%33,%34,%35,%36,%37,%38,%39,%40,%41,%42,%43,%44,%45,%46,%47,"
    "%48,%49,%50,%51,%52,%53,%54,%55,%56,%57,%58,%59,%60,%61,%62,%63}, "
    "da, db, p, 1, 1, %69, %67;\n}\n"
    : "+f"(d[0]),"+f"(d[1]),"+f"(d[2]),"+f"(d[3]),"+f"(d[4]),"+f"(d[5]),"+f"(d[6]),"+f"(d[7]),"+f"(d[8]),"+f"(d[9]),"+f"(d[10]),"+f"(d[11]),
      "+f"(d[12]),"+f"(d[13]),"+f"(d[14]),"+f"(d[15]),"+f"(d[16]),"+f"(d[17]),"+f"(d[18]),"+f"(d[19]),"+f"(d[20]),"+f"(d[21]),"+f"(d[22]),"+f"(d[23]),
      "+f"(d[24]),"+f"(d[25]),"+f"(d[26]),"+f"(d[27]),"+f"(d[28]),"+f"(d[29]),"+f"(d[30]),"+f"(d[31]),"+f"(d[32]),"+f"(d[33]),"+f"(d[34]),"+f"(d[35]),
      "+f"(d[36]),"+f"(d[37]),"+f"(d[38]),"+f"(d[39]),"+f"(d[40]),"+f"(d[41]),"+f"(d[42]),"+f"(d[43]),"+f"(d[44]),"+f"(d[45]),"+f"(d[46]),"+f"(d[47]),
      "+f"(d[48]),"+f"(d[49]),"+f"(d[50]),"+f"(d[51]),"+f"(d[52]),"+f"(d[53]),"+f"(d[54]),"+f"(d[55]),"+f"(d[56]),"+f"(d[57]),"+f"(d[58]),"+f"(d[59]),
      "+f"(d[60]),"+f"(d[61]),"+f"(d[62]),"+f"(d[63])
    : "r"(alo), "r"(blo), "r"(sd), "n"(TB), "r"(DESC_HI), "n"(TA));
}
template <int TB> __device__ __forceinline__ void wgmma_rs128(float (&d)[64], uint32_t a0, uint32_t a1, uint32_t a2, uint32_t a3, uint32_t blo, int sd) {
  asm volatile("{\n.reg .pred p;\n.reg .b64 db;\n"
    "setp.ne.b32 p, %69, 0;\nmov.b64 db, {%68, %71};\n"
    "wgmma.mma_async.sync.aligned.m64n128k16.f32.bf16.bf16 "
    "{%0,%1,%2,%3,%4,%5,%6,%7,%8,%9,%10,%11,%12,%13,%14,%15,%16,%17,%18,%19,%20,%21,%22,%23,"
    "%24,%25,%26,%27,%28,%29,%30,%31,%32,%33,%34,%35,%36,%37,%38,%39,%40,%41,%42,%43,%44,%45,%46,%47,"
    "%48,%49,%50,%51,%52,%53,%54,%55,%56,%57,%58,%59,%60,%61,%62,%63}, "
    "{%64,%65,%66,%67}, db, p, 1, 1, %70;\n}\n"
    : "+f"(d[0]),"+f"(d[1]),"+f"(d[2]),"+f"(d[3]),"+f"(d[4]),"+f"(d[5]),"+f"(d[6]),"+f"(d[7]),"+f"(d[8]),"+f"(d[9]),"+f"(d[10]),"+f"(d[11]),
      "+f"(d[12]),"+f"(d[13]),"+f"(d[14]),"+f"(d[15]),"+f"(d[16]),"+f"(d[17]),"+f"(d[18]),"+f"(d[19]),"+f"(d[20]),"+f"(d[21]),"+f"(d[22]),"+f"(d[23]),
      "+f"(d[24]),"+f"(d[25]),"+f"(d[26]),"+f"(d[27]),"+f"(d[28]),"+f"(d[29]),"+f"(d[30]),"+f"(d[31]),"+f"(d[32]),"+f"(d[33]),"+f"(d[34]),"+f"(d[35]),
      "+f"(d[36]),"+f"(d[37]),"+f"(d[38]),"+f"(d[39]),"+f"(d[40]),"+f"(d[41]),"+f"(d[42]),"+f"(d[43]),"+f"(d[44]),"+f"(d[45]),"+f"(d[46]),"+f"(d[47]),
      "+f"(d[48]),"+f"(d[49]),"+f"(d[50]),"+f"(d[51]),"+f"(d[52]),"+f"(d[53]),"+f"(d[54]),"+f"(d[55]),"+f"(d[56]),"+f"(d[57]),"+f"(d[58]),"+f"(d[59]),
      "+f"(d[60]),"+f"(d[61]),"+f"(d[62]),"+f"(d[63])
    : "r"(a0), "r"(a1), "r"(a2), "r"(a3), "r"(blo), "r"(sd), "n"(TB), "r"(DESC_HI));
}
template <int TB, int TA = 0> __device__ __forceinline__ void wgmma_ss192(float (&d)[96], uint32_t alo, uint32_t blo, int sd) {
  asm volatile("{\n.reg .pred p;\n.reg .b64 da, db;\n"
    "setp.ne.b32 p, %98, 0;\nmov.b64 da, {%96, %100};\nmov.b64 db, {%97, %100};\n"
    "wgmma.mma_async.sync.aligned.m64n192k16.f32.bf16.bf16 "
    "{%0,%1,%2,%3,%4,%5,%6,%7,%8,%9,%10,%11,%12,%13,%14,%15,%16,%17,%18,%19,%20,%21,%22,%23,"
    "%24,%25,%26,%27,%28,%29,%30,%31,%32,%33,%34,%35,%36,%37,%38,%39,%40,%41,%42,%43,%44,%45,%46,%47,"
    "%48,%49,%50,%51,%52,%53,%54,%55,%56,%57,%58,%59,%60,%61,%62,%63,%64,%65,%66,%67,%68,%69,%70,%71,"
    "%72,%73,%74,%75,%76,%77,%78,%79,%80,%81,%82,%83,%84,%85,%86,%87,%88,%89,%90,%91,%92,%93,%94,%95}, "
    "da, db, p, 1, 1, %101, %99;\n}\n"
    : "+f"(d[0]),"+f"(d[1]),"+f"(d[2]),"+f"(d[3]),"+f"(d[4]),"+f"(d[5]),"+f"(d[6]),"+f"(d[7]),"+f"(d[8]),"+f"(d[9]),"+f"(d[10]),"+f"(d[11]),
      "+f"(d[12]),"+f"(d[13]),"+f"(d[14]),"+f"(d[15]),"+f"(d[16]),"+f"(d[17]),"+f"(d[18]),"+f"(d[19]),"+f"(d[20]),"+f"(d[21]),"+f"(d[22]),"+f"(d[23]),
      "+f"(d[24]),"+f"(d[25]),"+f"(d[26]),"+f"(d[27]),"+f"(d[28]),"+f"(d[29]),"+f"(d[30]),"+f"(d[31]),"+f"(d[32]),"+f"(d[33]),"+f"(d[34]),"+f"(d[35]),
      "+f"(d[36]),"+f"(d[37]),"+f"(d[38]),"+f"(d[39]),"+f"(d[40]),"+f"(d[41]),"+f"(d[42]),"+f"(d[43]),"+f"(d[44]),"+f"(d[45]),"+f"(d[46]),"+f"(d[47]),
      "+f"(d[48]),"+f"(d[49]),"+f"(d[50]),"+f"(d[51]),"+f"(d[52]),"+f"(d[53]),"+f"(d[54]),"+f"(d[55]),"+f"(d[56]),"+f"(d[57]),"+f"(d[58]),"+f"(d[59]),
      "+f"(d[60]),"+f"(d[61]),"+f"(d[62]),"+f"(d[63]),"+f"(d[64]),"+f"(d[65]),"+f"(d[66]),"+f"(d[67]),"+f"(d[68]),"+f"(d[69]),"+f"(d[70]),"+f"(d[71]),
      "+f"(d[72]),"+f"(d[73]),"+f"(d[74]),"+f"(d[75]),"+f"(d[76]),"+f"(d[77]),"+f"(d[78]),"+f"(d[79]),"+f"(d[80]),"+f"(d[81]),"+f"(d[82]),"+f"(d[83]),
      "+f"(d[84]),"+f"(d[85]),"+f"(d[86]),"+f"(d[87]),"+f"(d[88]),"+f"(d[89]),"+f"(d[90]),"+f"(d[91]),"+f"(d[92]),"+f"(d[93]),"+f"(d[94]),"+f"(d[95])
    : "r"(alo), "r"(blo), "r"(sd), "n"(TB), "r"(DESC_HI), "n"(TA));
}

struct Ctx {
  uint32_t sm;
  uint32_t bar;
  uint32_t rbar;
  int cl, rank, wg, warp, lane, phases;
};
__device__ __forceinline__ void release(const Ctx& c, int b, int cnt = 1) {
  if (c.lane < 2) mbar_arrive_cl(c.rbar + b * 8, cnt);
}
#define HK 5
#define NPRO 6
#define ZLEAD 14
#define PFM 7
#define PF1 1
constexpr float SM_SCALE = 0.08838834764831845f * 1.4426950408889634f;
constexpr float SM_HI = 1.8446744e19f, SM_LO = 5.4210109e-20f;
constexpr int ORDER = 1;

__device__ __forceinline__ void stage_tile(const float (&a)[64], uint32_t buf, const Ctx& c, float s0, float s1) {
  const int row = (c.lane & 7) + ((c.lane >> 3) & 1) * 8;
  const uint32_t base = buf + (c.warp * 16 + row) * 128 + (((c.lane >> 4) ^ (row & 7)) << 4);
#pragma unroll
  for (int i = 0; i < 8; i++)
    stsm4((base ^ ((i & 3) << 5)) + (i >> 2) * 8192, pack_bf16(a[8 * i] * s0, a[8 * i + 1] * s0), pack_bf16(a[8 * i + 2] * s1, a[8 * i + 3] * s1),
          pack_bf16(a[8 * i + 4] * s0, a[8 * i + 5] * s0), pack_bf16(a[8 * i + 6] * s1, a[8 * i + 7] * s1));
}

__device__ __forceinline__ void p1_epilogue(const Params& p, const Ctx& c, const float (&acc)[64], int t, int type) {
  const int tile = p.s.r[c.cl].tile[t] & 63, b = c.wg * 2 + 1;
  mbar_wait(c.bar + (B_SE + b) * 8, (t & 1) ^ 1);
  if (type && tile >= 32) {
    const int r = 2 * (c.lane & 3) + ((c.lane >> 2) & 1);
    const uint32_t dst = c.sm + SM_BUF + b * 16384 + r * 128 + (((c.warp * 2) ^ r) << 4) + (c.lane >> 3) * 4;
#pragma unroll
    for (int i = 0; i < 16; i++) {
      asm volatile("st.shared.u32 [%0], %1;" ::"r"(dst + i * 1024), "r"(pack_bf16(acc[4 * i], acc[4 * i + 1])) : "memory");
      asm volatile("st.shared.u32 [%0], %1;" ::"r"((dst ^ 16) + i * 1024), "r"(pack_bf16(acc[4 * i + 2], acc[4 * i + 3])) : "memory");
    }
  } else {
    if (type) stage_tile(acc, c.sm + SM_BUF + b * 16384, c, SM_SCALE, SM_SCALE);
    else stage_tile(acc, c.sm + SM_BUF + b * 16384, c, 1.f, 1.f);
  }
  FENCE_ASYNC_SMEM();
  __syncwarp();
  if (c.lane == 0) mbar_arrive(c.bar + (B_SF + b) * 8);
}

__device__ __forceinline__ void p1_consumer(const Params& p, const Ctx& c) {
  const int n = p.s.r[c.cl].n1;
  const int type = p.s.r[c.cl].slab >> 3;
  const uint32_t bdesc = desc_lo(c.sm + SM_RING, 8192), adesc = desc_lo(c.sm + SM_BUF + 32768 + c.wg * 8192, 16);
  uint32_t A[128];
  float acc[64] = {};
  int slot = 0, par = 0;
  auto next = [&]() { if (++slot == 10) { slot = 0; par ^= 1; } };
  {
    const int row = (c.lane & 7) + ((c.lane >> 3) & 1) * 8;
    const uint32_t base = c.sm + SM_RING + (c.wg * 64 + c.warp * 16 + row) * 128 + (((c.lane >> 4) ^ (row & 7)) << 4);
    if (c.wg == 1) bar_sync(ORDER + 1, 256);
    int pa = -1, pb = -1;
    if (type) {
      mbar_wait(c.bar + B_P1F * 8, 0);
      WG_FENCE();
#pragma unroll
      for (int kk = 0; kk < 4; kk++) wgmma_ss128<1>(acc, adesc + kk * 2, bdesc + kk * 128, kk != 0);
      WG_COMMIT();
      pb = 0; slot = 1;
    }
#pragma unroll
    for (int kb = 0; kb < 8; kb++) {
      const int sa = slot;
      mbar_wait(c.bar + (B_P1F + slot) * 8, par);
      if (kb == 0) PROF(c.wg, 5);
      next();
      mbar_wait(c.bar + (B_P1F + slot) * 8, par);
      PROF(c.wg, 6 + 2 * kb);
      WG_FENCE();
#pragma unroll
      for (int kk = 0; kk < 4; kk++)
        wgmma_ss128<1>(acc, desc_lo(c.sm + SM_RING + c.wg * 8192, 16) + sa * 1024 + kk * 2, bdesc + slot * 1024 + kk * 128, (kb | kk) != 0 ? 1 : type);
      WG_COMMIT();
      if (kb == 1 && c.wg == 0) bar_arrive(ORDER + 1, 256);
#pragma unroll
      for (int kk = 0; kk < 4; kk++) ldsm4((base ^ (kk << 5)) + sa * 16384, A[kb * 16 + kk * 4], A[kb * 16 + kk * 4 + 1], A[kb * 16 + kk * 4 + 2], A[kb * 16 + kk * 4 + 3]);
      WG_WAIT(1);
      if (kb > 0) release(c, B_P1E + pa);
      if (kb > 0 || pb >= 0) release(c, B_P1E + pb);
      pa = sa; pb = slot;
      next();
    }
    WG_WAIT(0);
    __syncwarp();
    release(c, B_P1E + pa);
    release(c, B_P1E + pb);
    pin(acc);
    PROF(c.wg, 1);
    p1_epilogue(p, c, acc, 0, type);
    PROF(c.wg, 2);
  }
  for (int t = 1; t < n; t++) {
    bar_sync(ORDER + c.wg, 256);
    int prev1 = -1, prev2 = -1;
    if (type) {
      mbar_wait(c.bar + (B_P1F + slot) * 8, par);
      WG_FENCE();
#pragma unroll
      for (int kk = 0; kk < 4; kk++) wgmma_ss128<1>(acc, adesc + kk * 2, bdesc + slot * 1024 + kk * 128, kk != 0);
      WG_COMMIT();
      prev1 = slot;
      next();
    }
#pragma unroll
    for (int kb = 0; kb < 8; kb++) {
      mbar_wait(c.bar + (B_P1F + slot) * 8, par);
      WG_FENCE();
      const uint32_t d = bdesc + slot * 1024;
#pragma unroll
      for (int kk = 0; kk < 4; kk++)
        wgmma_rs128<1>(acc, A[kb * 16 + kk * 4], A[kb * 16 + kk * 4 + 1], A[kb * 16 + kk * 4 + 2], A[kb * 16 + kk * 4 + 3], d + kk * 128, (kb | kk) != 0 ? 1 : type);
      WG_COMMIT();
      if (kb == HK) {
        if (t + 1 < n || c.wg == 0) bar_arrive(ORDER + (c.wg ^ 1), 256);
      }
      if (kb > 0) { WG_WAIT(2); if (kb > 1 || prev2 >= 0) release(c, B_P1E + prev2); }
      prev2 = prev1; prev1 = slot;
      next();
    }
    WG_WAIT(1);
    release(c, B_P1E + prev2);
    WG_WAIT(0);
    pin(acc);
    release(c, B_P1E + prev1);
    p1_epilogue(p, c, acc, t, type);
    PROF(c.wg, 3);
  }
}

__device__ __forceinline__ void p1_producer(const Params& p, const Ctx& c) {
  const int n = p.s.r[c.cl].n1;
  const int type = p.s.r[c.cl].slab >> 3, grp = p.s.r[c.cl].slab & 7;
  int slot = NPRO % 10, par = NPRO < 10;
#pragma unroll 1
  for (int t = 0; t < n; t++) {
    const int tile = p.s.r[c.cl].tile[t] & 63;
    const CUtensorMap* m = &p.map_w[type * 2 + (tile >> 5)];
    const int n0 = (tile & 31) * 128 + c.rank * 64;
    const int ptile = p.s.r[c.cl].tile[t + PF1 < n ? t + PF1 : t];
    const CUtensorMap* pm = &p.map_w[type * 2 + ((ptile >> 5) & 1)];
    if (t == 7 && (c.phases & 16)) flag_wait<true>(F_GATE, 256);
#pragma unroll 1
    for (int kb = t ? -type : (NPRO - type) >> 1; kb < 8; kb++) {
      if (t == 0 && 2 * kb + type >= NPRO) {
        mbar_wait(c.bar + (B_P1E + slot) * 8, par);
        mbar_expect(c.bar + (B_P1F + slot) * 8, 16384);
        tma2d(c.sm + SM_RING + slot * 16384, &p.map_a[type], kb * 64, grp * 256 + c.rank * 128, c.bar + (B_P1F + slot) * 8);
        if (++slot == 10) { slot = 0; par ^= 1; }
      }
      mbar_wait(c.bar + (B_P1E + slot) * 8, par);
      mbar_expect(c.bar + (B_P1F + slot) * 8, 16384);
      tma2d_mc(c.sm + SM_RING + slot * 16384 + c.rank * 8192, m, n0, kb < 0 ? 512 : kb * 64, c.bar + (B_P1F + slot) * 8);
      if (t == 0 && kb == 1) PROF(2, 61);
      if (t == 0 && kb == 3) PROF(2, 62);
      if (t + PF1 < n && t > 0 && ((ptile & 64) || ((ptile & 128) && ((kb ^ grp) & PFM) == 0))) tma2d_prefetch(pm, (ptile & 31) * 128 + c.rank * 64, kb < 0 ? 512 : kb * 64);
      if (++slot == 10) { slot = 0; par ^= 1; }
    }
  }
}

__device__ __forceinline__ void wait_kv_dead(const Ctx& c, int h, int g) {
  if (g >= 2) flag_wait<false>(F_RD + h * 8 + g, 8 - g);
  else flag_wait<false>(F_CTX + max(c.lane & 7, g) * 64 + h, 4);
}
__device__ __forceinline__ int p1_storer(const Params& p, const Ctx& c) {
  const int n = p.s.r[c.cl].n1;
  const int type = p.s.r[c.cl].slab >> 3, grp = p.s.r[c.cl].slab & 7;
  for (int i = 0; i < 2 * n; i++) {
    const int t = i >> 1, w = i & 1, b = w * 2 + 1;
    const int tile = p.s.r[c.cl].tile[t] & 63;
    mbar_wait(c.bar + (B_SF + b) * 8, t & 1);
    const uint32_t src = c.sm + SM_BUF + b * 16384;
    int f = (type ? F_Q : F_KV) + (tile & 31) * 8 + grp;
    if (type == 0) {
      const int prev = p.s.prev[tile & 31][grp];
      if (prev != 255 && w == 0) wait_kv_dead(c, prev, grp);
      uint8_t* dst = g_S + (size_t)(S_K + ((tile & 32) + p.s.slot[tile & 31][grp]) * 8 + grp) * 65536 + c.rank * 32768 + w * 8192;
      bulk_store(dst, src, 8192);
      bulk_store(dst + 16384, src + 8192, 8192);
    } else if (tile < 32) {
      const int dep = p.s.qdep[tile * 8 + grp];
      if (dep != 511 && w == 0) {
        if (dep < 256) wait_kv_dead(c, dep >> 3, dep & 7);
        else flag_wait<false>(F_TS + dep - 256, 128);
      }
      bulk_store(g_S + (size_t)p.s.qblk[tile * 8 + grp] * 65536 + (c.rank * 2 + w) * 16384, src, 16384);
    } else {
      tma3d_store(&p.map_t[2], src, (grp * 4 + c.rank * 2 + w) * 32, 0, (tile - 32) * 64);
      f = F_QKVA + grp * 4 + ((0xE4390900u >> (2 * (tile - 30))) & 3);
    }
    BULK_COMMIT();
    BULK_WAIT(0);
    mbar_arrive_one(c.bar + (B_SE + b) * 8);
    if (i == 2 * n - 1) return f;
    if (w) flag_add(f, 2);
  }
  return -1;
}

__device__ __forceinline__ int p2_buf(int w, int i) { return w * 2 + (i & 1); }
__device__ __forceinline__ int p2_blk(int rank, int w, int i) { return ((i ^ w) & 1) == 0 ? 3 - rank : rank; }

template <int N>
__device__ __forceinline__ void row_max(const float (&s)[N], float& m0, float& m1) {
  float a0 = fmaxf(s[0], s[1]), a1 = fmaxf(s[2], s[3]);
#pragma unroll
  for (int i = 1; i < N / 4; i++) {
    m0 = fmaxf(m0, s[4 * i]); a0 = fmaxf(a0, s[4 * i + 1]);
    m1 = fmaxf(m1, s[4 * i + 2]); a1 = fmaxf(a1, s[4 * i + 3]);
  }
  m0 = fmaxf(m0, a0); m1 = fmaxf(m1, a1);
  m0 = fmaxf(m0, __shfl_xor_sync(0xffffffffu, m0, 1));
  m1 = fmaxf(m1, __shfl_xor_sync(0xffffffffu, m1, 1));
  m0 = fmaxf(m0, __shfl_xor_sync(0xffffffffu, m0, 2));
  m1 = fmaxf(m1, __shfl_xor_sync(0xffffffffu, m1, 2));
}
template <bool SUB, int N>
__device__ __forceinline__ void row_exp(const float (&s)[N], uint32_t (&P)[32], float m0, float m1, float& t0, float& t1) {
  float u0 = 0.f, u1 = 0.f;
  t0 = t1 = 0.f;
#pragma unroll
  for (int i = 0; i < N / 4; i++) {
    const float e0 = ex2(SUB ? s[4 * i] - m0 : s[4 * i]), e1 = ex2(SUB ? s[4 * i + 1] - m0 : s[4 * i + 1]);
    const float e2 = ex2(SUB ? s[4 * i + 2] - m1 : s[4 * i + 2]), e3 = ex2(SUB ? s[4 * i + 3] - m1 : s[4 * i + 3]);
    if (i == 0) { t0 = e0; u0 = e1; t1 = e2; u1 = e3; }
    else { t0 += e0; u0 += e1; t1 += e2; u1 += e3; }
    P[2 * i] = pack_bf16(e0, e1);
    P[2 * i + 1] = pack_bf16(e2, e3);
  }
#pragma unroll
  for (int i = N / 2; i < 32; i++) P[i] = 0;
  pin(P);
  t0 += u0; t1 += u1;
}
template <int N>
__device__ __forceinline__ void causal_mask(float (&s)[N], int thr) {
#pragma unroll
  for (int i = 0; i < 8; i++) {
    if (8 * i > thr) s[N - 32 + 4 * i] = -INFINITY;
    if (8 * i + 1 > thr) s[N - 32 + 4 * i + 1] = -INFINITY;
    if (8 * i - 8 > thr) s[N - 32 + 4 * i + 2] = -INFINITY;
    if (8 * i - 7 > thr) s[N - 32 + 4 * i + 3] = -INFINITY;
  }
}
__device__ __forceinline__ void issue_qk(float (&s)[32], uint32_t qd, uint32_t kd) {
  WG_FENCE();
#pragma unroll
  for (int kk = 0; kk < 8; kk++) wgmma_ss64<0>(s, qd + (kk >> 2) * 512 + (kk & 3) * 2, kd + (kk >> 2) * 1024 + (kk & 3) * 2, kk != 0);
  WG_COMMIT();
}
__device__ __forceinline__ void issue_qk(float (&s)[64], uint32_t qd, uint32_t kd) {
  WG_FENCE();
#pragma unroll
  for (int kk = 0; kk < 8; kk++) wgmma_ss128<0>(s, qd + (kk >> 2) * 512 + (kk & 3) * 2, kd + (kk >> 2) * 1024 + (kk & 3) * 2, kk != 0);
  WG_COMMIT();
}
template <int NK>
__device__ __forceinline__ void issue_pv(float (&o)[64], const uint32_t (&P)[32], uint32_t vd, int acc) {
  WG_FENCE();
#pragma unroll
  for (int kk = 0; kk < NK; kk++) wgmma_rs128<1>(o, P[4 * kk], P[4 * kk + 1], P[4 * kk + 2], P[4 * kk + 3], vd + kk * 128, kk != 0 ? 1 : acc);
  WG_COMMIT();
}
__device__ __forceinline__ void stage_done(const Ctx& c, int b) {
  FENCE_ASYNC_SMEM();
  __syncwarp();
  if (c.lane == 0) mbar_arrive(c.bar + (B_SF + b) * 8);
}
__device__ __forceinline__ void p2_epilogue(const float (&o)[64], float s0, float s1, const Ctx& c, int b) {
  stage_tile(o, c.sm + SM_BUF + b * 16384, c, s0, s1);
  stage_done(c, b);
}

struct P2State {
  float m0, m1, l0, l1;
  bool shift;
  float e0, e1;
  int ks;
  int wi, ai;
  uint32_t wb, ab;
  uint32_t qd;
};
#define PROFZ()
__device__ __forceinline__ int wrap5(int q) { return q >= 5 ? q - 5 : q; }
__device__ __forceinline__ void turn_wait(uint32_t ring, int i) { mbar_wait(ring + (i & 3) * 8, (i >> 2) & 1); }
__device__ __forceinline__ void turn_pass(const Ctx& c, uint32_t ring, int i) { if (c.lane == 0) mbar_arrive(ring + (i & 3) * 8); }
__device__ __forceinline__ void p2_scales(P2State& z) {
  float l0 = z.l0, l1 = z.l1;
  l0 += __shfl_xor_sync(0xffffffffu, l0, 1);
  l1 += __shfl_xor_sync(0xffffffffu, l1, 1);
  l0 += __shfl_xor_sync(0xffffffffu, l0, 2);
  l1 += __shfl_xor_sync(0xffffffffu, l1, 2);
  asm("rcp.approx.ftz.f32 %0, %1;" : "=f"(z.e0) : "f"(l0));
  asm("rcp.approx.ftz.f32 %0, %1;" : "=f"(z.e1) : "f"(l1));
}
template <int N>
__device__ __forceinline__ void p2_first(const Ctx& c, P2State& z, float (&o)[64], uint32_t (&Pc)[32], uint32_t (&Pn)[32],
                                         int ks, int vs, int cnt, int acc) {
  float s[N] = {};
  issue_qk(s, z.qd, desc_lo(c.sm + SM_RING, 16) + ks * 2048);
  if (vs >= 0) {
    p2_scales(z);
    issue_pv<8>(o, Pc, desc_lo(c.sm + SM_RING, 16384) + vs * 2048, acc);
  } else {
    WG_COMMIT();
  }
  mbar_expect(z.ab + (z.ai++ & 3) * 8, cnt == 1 ? 8192 : 0);
  PROFZ();
  WG_WAIT(1);
  PROFZ();
  pin(s);
  release(c, B_P2E + ks, cnt);
  causal_mask(s, c.warp * 16 + (c.lane >> 2) - 2 * (c.lane & 3));
  z.m0 = z.m1 = 0.f;
  row_exp<false>(s, Pn, 0.f, 0.f, z.l0, z.l1);
  z.shift = __any_sync(0xffffffffu, !(z.l0 + z.l1 <= SM_HI) || ((c.lane & 3) == 0 && !(fminf(z.l0, z.l1) >= SM_LO)));
  if (__builtin_expect(z.shift, 0)) {
    z.m0 = z.m1 = -INFINITY;
    row_max(s, z.m0, z.m1);
    row_exp<true>(s, Pn, z.m0, z.m1, z.l0, z.l1);
  }
  WG_WAIT(0);
  pin(o);
  if (vs >= 0) release(c, B_P2E + vs, 1);
}

template <bool SECOND>
__device__ __forceinline__ void p2_turn(const Ctx& c, P2State& z, float (&o)[64], uint32_t (&Pc)[32], uint32_t (&Pn)[32],
                                        int eb = -1, bool half = false, int vcnt = 1) {
  float s[64] = {};
  const int ks = z.ks, vs = wrap5(ks + 1);
  PROFZ();
  turn_wait(z.wb, z.wi++);
  PROFZ();
  issue_qk(s, z.qd, desc_lo(c.sm + SM_RING, 16) + ks * 2048);
  const uint32_t vd = desc_lo(c.sm + SM_RING, 16384) + vs * 2048;
  if (SECOND) {
    if (eb >= 0) stage_tile(o, c.sm + SM_BUF + eb * 16384, c, z.e0, z.e1);
    if (half) issue_pv<4>(o, Pc, vd, 0); else issue_pv<8>(o, Pc, vd, 0);
  } else {
    issue_pv<8>(o, Pc, vd, 1);
  }
  turn_pass(c, z.ab, z.ai++);
  if (SECOND) { if (eb >= 0) stage_done(c, eb); }
  PROFZ();
  z.ks = wrap5(ks + 2);
  WG_WAIT(1);
  PROFZ();
  pin(s);
  release(c, B_P2E + ks, 1);
  float t0, t1, a0 = 1.f, a1 = 1.f;
  row_exp<false>(s, Pn, 0.f, 0.f, t0, t1);
  z.shift = __any_sync(0xffffffffu, z.shift || !(t0 + t1 <= SM_HI));
  const bool redo = z.shift;
  if (__builtin_expect(redo, 0)) {
    float n0 = z.m0, n1 = z.m1;
    row_max(s, n0, n1);
    a0 = ex2(z.m0 - n0); a1 = ex2(z.m1 - n1);
    z.m0 = n0; z.m1 = n1;
    z.l0 *= a0; z.l1 *= a1;
    row_exp<true>(s, Pn, z.m0, z.m1, t0, t1);
  }
  WG_WAIT(0);
  pin(o);
  release(c, B_P2E + vs, vcnt);
  if (__builtin_expect(redo, 0)) {
#pragma unroll
    for (int i = 0; i < 16; i++) { o[4 * i] *= a0; o[4 * i + 1] *= a0; o[4 * i + 2] *= a1; o[4 * i + 3] *= a1; }
  }
  z.l0 += t0; z.l1 += t1;
}
__device__ __forceinline__ void copy_p(uint32_t (&d)[32], const uint32_t (&s)[32], int zero) {
#pragma unroll
  for (int i = 0; i < 32; i++) asm volatile("add.s32 %0, %1, %2;" : "=r"(d[i]) : "r"(s[i]), "r"(zero));
}

__device__ __forceinline__ void p2_consumer(const Params& p, const Ctx& c, int rot) {
  const int nit = p.s.r[c.cl].n2;
  const uint32_t fring = c.bar + B_P2F * 8, oring = c.bar + B_ORD * 8;
  float o[64] = {};
  uint32_t Pa[32] = {}, Pb[32] = {};
  P2State z;
  z.e0 = z.e1 = z.l0 = z.l1 = 0.f; z.ks = rot; z.shift = false;
  int acc = 0, n = 0;
  for (int it = 0; it < nit; it++) {
    const int j = p.s.r[c.cl].item[it] & 7, blk = p2_blk(c.rank, c.wg, it);
    const int lng = ((it ^ c.wg) & 1) ^ 1;
    z.qd = desc_lo(c.sm + SM_BUF, 16) + p2_buf(c.wg, it) * 1024;
    if (lng) { z.wb = oring; z.wi = n - it; z.ab = fring; z.ai = n + 1; }
    else { z.wb = fring; z.wi = n + 2; z.ab = oring; z.ai = n - it; }
    PROFZ();
    mbar_wait(c.bar + (B_QF + p2_buf(c.wg, it)) * 8, (it >> 1) & 1);
    turn_wait(fring, n + 1 - lng);
    PROFZ();
    const int vs = it ? wrap5(z.ks + 1) : -1, ks = lng ? z.ks : wrap5(z.ks + (it ? 2 : 1));
    if (blk & 1) p2_first<64>(c, z, o, Pa, Pb, ks, vs, 1 + lng, acc);
    else p2_first<32>(c, z, o, Pa, Pb, ks, vs, 1 + lng, acc);
    z.ks = wrap5(ks + (it == 0 && lng ? 1 : 2));
    PROF(c.wg, 24 + it);
    n += 2 * j + 2;
    int left = 2 * j + lng;
    acc = left != 0;
    if (left == 0) { copy_p(Pa, Pb, p.zero); continue; }
    p2_turn<true>(c, z, o, Pb, Pa, it > 0 ? p2_buf(c.wg, it - 1) : -1, !(blk & 1), 1 + lng);
    while (--left > 0) {
      p2_turn<false>(c, z, o, Pa, Pb);
      if (--left == 0) { copy_p(Pa, Pb, p.zero); break; }
      p2_turn<false>(c, z, o, Pb, Pa);
    }
  }
  {
    if (!acc && nit > 1) p2_epilogue(o, z.e0, z.e1, c, p2_buf(c.wg, nit));
    turn_wait(z.wb, z.wi);
    issue_pv<8>(o, Pa, desc_lo(c.sm + SM_RING, 16384) + z.ks * 2048, acc);
    if (((nit - 1) ^ c.wg) & 1) turn_pass(c, z.ab, z.ai);
    p2_scales(z);
    WG_WAIT(0);
    pin(o);
    release(c, B_P2E + z.ks);
    p2_epilogue(o, z.e0, z.e1, c, p2_buf(c.wg, nit - 1));
    PROF(c.wg, 24 + nit);
  }
}

__device__ __forceinline__ void p2_load_q(const Params& p, const Ctx& c, int it, int w) {
  const int item = p.s.r[c.cl].item[it], b = p2_buf(w, it);
  mbar_expect(c.bar + (B_QF + b) * 8, 16384);
  bulk_load(c.sm + SM_BUF + b * 16384, g_S + (size_t)p.s.qblk[item] * 65536 + p2_blk(c.rank, w, it) * 16384, 16384, c.bar + (B_QF + b) * 8, POL(4));
}
__device__ __forceinline__ void wait_p1_free(const Ctx& c, int u1, int s) {
  mbar_wait(c.bar + (B_P1E + 2 * s) * 8, ((u1 - 1 - 2 * s) / 10) & 1);
  mbar_wait(c.bar + (B_P1E + 2 * s + 1) * 8, ((u1 - 2 - 2 * s) / 10) & 1);
}
__device__ __forceinline__ void p2_producer(const Params& p, const Ctx& c, int u1, int rot) {
  const int nit = p.s.r[c.cl].n2;
  int slot = rot, cnt = 0, par = 1, n = 0;
  const uint8_t* pv = nullptr;
  bool pl = false;
  auto load = [&](const uint8_t* src, int expect, uint32_t fb, bool last) {
    if (cnt < 5) {
      if (u1) {
        wait_p1_free(c, u1, slot);
        if (cnt == 0) p2_load_q(p, c, 0, 1);
      }
      cnt++;
    } else {
      if (slot == rot) par ^= 1;
      mbar_wait(c.bar + (B_P2E + slot) * 8, par);
    }
    if (expect) mbar_expect(fb, expect);
    bulk_load_mc(c.sm + SM_RING + slot * 32768 + c.rank * 16384, src, 16384, fb, last ? POL(5) : L2_NORMAL);
    slot = wrap5(slot + 1);
  };
  for (int it = 0; it < nit; it++) {
    const int item = p.s.r[c.cl].item[it], h = item >> 3, j = item & 7;
    if (it == 1 && (c.phases & 16) && p.s.r[c.cl].n1 < 8) flag_wait<true>(F_GATE, 256);
    uint32_t ready = (c.phases & 16) ? 0u : 255u;
    if (it == 0) { if (c.phases & 16) flag_wait<false>(F_Q + item, 4); mbar_wait(c.bar + B_LAD * 8, 0); p2_load_q(p, c, 0, 0); if (!u1) p2_load_q(p, c, 0, 1); }
    for (int t = 2 * j + 1; t >= 0; t--) {
      mask_wait(ready, t >> 1, F_KV + h * 8 + (c.lane & 7), 8);
      const uint8_t* k = g_S + (size_t)(2 * S_K + p.s.slot[h][t >> 1] * 16 + t) * 32768 + c.rank * 16384;
      const uint32_t fb = c.bar + (B_P2F + (n & 3)) * 8;
      const bool last = (p.s.r[c.cl].last[it] >> (t >> 1)) & 1;
      load(k, pv && t != 2 * j ? 65536 : 32768, fb, last);
      if (!(t & 1) && t + 4 <= 2 * j && c.rank == 0) flag_add_rx(F_RD + h * 8 + (t >> 1) + 2);
      if (pv) load(pv, 0, t != 2 * j ? fb : c.bar + (B_ORD + ((n - 1 - it) & 3)) * 8, pl);
      pl = last;
      pv = k + (size_t)NH * 16 * 32768;
      n++;
    }
  }
  load(pv, 32768, c.bar + (B_P2F + (n & 3)) * 8, pl);
}

__device__ __forceinline__ void publish_and_load_q(const Params& p, const Ctx& c, int f, int it, int seen) {
  const bool want = it < p.s.r[c.cl].n2, early = want && __all_sync(0xffffffffu, seen >= 4);
  if (early) { p2_load_q(p, c, it, it & 1); p2_load_q(p, c, it, (it & 1) ^ 1); }
  if (f >= 0) flag_add(f, 2);
  if (want && !early) {
    if (c.phases & 16) flag_wait<false>(F_Q + p.s.r[c.cl].item[it], 4);
    p2_load_q(p, c, it, it & 1); p2_load_q(p, c, it, (it & 1) ^ 1);
  }
}
__device__ __forceinline__ void p2_storer(const Params& p, const Ctx& c, int sfpar) {
  const int nit = p.s.r[c.cl].n2;
  for (int i = 0; i < 2 * nit; i++) {
    const int it = i >> 1, w = (it ^ i ^ 1) & 1, b = p2_buf(w, it);
    const int item = p.s.r[c.cl].item[it], h = item >> 3, j = item & 7;
    mbar_wait(c.bar + (B_SF + b) * 8, (sfpar >> b) & 1);
    sfpar ^= 1 << b;
    bulk_store(g_S + (size_t)p.s.qblk[item] * 65536 + p2_blk(c.rank, w, it) * 16384, c.sm + SM_BUF + b * 16384, 16384, POL(1));
    BULK_COMMIT();
    if (i & 1) {
      const int seen = flag_peek(F_Q + p.s.r[c.cl].item[min(it + 2, nit - 1)]);
      BULK_WAIT(0);
      if (it + 1 == nit) release(c, B_DONE);
      publish_and_load_q(p, c, F_CTX + j * 64 + h, it + 2, seen);
    }
  }
}

__device__ __forceinline__ int p3_pos(int i, int x) { return i < 4 ? (i + x) & 3 : 4; }
__device__ __forceinline__ void p3_consumer(const Params& p, const Ctx& c, int x) {
  const bool first = p.s.r[c.cl].p3 >= 24;
  const int tile = p.s.r[c.cl].p3 - (first ? 24 : 0), j = tile / 3, nt = tile - 3 * j;
  const int na = first ? 9 : 0, nb = p.s.task[c.cl][1] - p.s.task[c.cl][0];
  const uint32_t ad = desc_lo(c.sm + SM_RING + c.wg * 8192, 16), bd = desc_lo(c.sm + SM_RING + 16384, 4096);
  float acc[96] = {};
  int slot = 0, par = 0, prev = 0;
  float g0 = 0.f, g1 = 0.f;
  const int hold = c.wg && LAG ? na + nb - LAG : -1, pass = c.wg || !LAG ? -1 : na + nb - 1;
#pragma unroll 1
  for (int kb = 0; kb < nb; kb++) {
    if (kb == hold) bar_sync(6, 256);
    mbar_wait(c.bar + (B_P3F + slot) * 8, par);
    if (kb == 0) PROF(c.wg, 39);
    WG_FENCE();
#pragma unroll
    for (int kk = 0; kk < 4; kk++) wgmma_ss192<1>(acc, ad + p3_pos(slot, x) * 2560 + kk * 2, bd + p3_pos(slot, x) * 2560 + (kk >> 1) * 768 + (kk & 1) * 128, kk != 0 ? 1 : kb != 0);
    WG_COMMIT();
    if (kb == pass) bar_arrive(6, 256);
    WG_WAIT(1);
    if (kb > 0) release(c, B_P3E + prev);
    else {
      const float* g = g_gate + j * 256 + c.rank * 128 + c.wg * 64 + c.warp * 16 + (c.lane >> 2);
      g0 = __ldcg(g); g1 = __ldcg(g + 8);
    }
    prev = slot;
    if (++slot == 5) { slot = 0; par ^= 1; }
  }
  WG_WAIT(0);
  pin(acc);
  g0 = 1.f - g0; g1 = 1.f - g1;
#pragma unroll
  for (int i = 0; i < 24; i++) { acc[4 * i] *= g0; acc[4 * i + 1] *= g0; acc[4 * i + 2] *= g1; acc[4 * i + 3] *= g1; }
#pragma unroll 1
  for (int kb = nb; kb < nb + na; kb++) {
    if (kb == hold) bar_sync(6, 256);
    mbar_wait(c.bar + (B_P3F + slot) * 8, par);
    if (kb == 0) PROF(c.wg, 39);
    WG_FENCE();
#pragma unroll
    for (int kk = 0; kk < 4; kk++) wgmma_ss192<1, 1>(acc, ad + p3_pos(slot, x) * 2560 + kk * 128, bd + p3_pos(slot, x) * 2560 + (kk >> 1) * 768 + (kk & 1) * 128, 1);
    WG_COMMIT();
    if (kb == pass) bar_arrive(6, 256);
    WG_WAIT(1);
    if (kb > 0) release(c, B_P3E + prev);
    prev = slot;
    if (++slot == 5) { slot = 0; par ^= 1; }
  }
  WG_WAIT(0);
  pin(acc);
  PROF(c.wg, 40);
  if (first) bar_sync(4 + c.wg, 128);
  mbar_wait(c.bar + B_OUT * 8, 0);
  const int row = (c.lane & 7) + ((c.lane >> 3) & 1) * 8;
  const uint32_t wbase = c.sm + SM_RING + c.wg * 8192 + c.warp * 2048;
  const uint32_t base = wbase + row * 128 + (((c.lane >> 4) ^ (row & 7)) << 4);
#pragma unroll
  for (int i = 0; i < 12; i++) {
    stsm4((base ^ ((i & 3) << 5)) + (i >> 2) * 40960, pack_bf16(acc[8 * i], acc[8 * i + 1]), pack_bf16(acc[8 * i + 2], acc[8 * i + 3]),
          pack_bf16(acc[8 * i + 4], acc[8 * i + 5]), pack_bf16(acc[8 * i + 6], acc[8 * i + 7]));
    if ((i & 3) == 3) {
      FENCE_ASYNC_SMEM();
      bar_sync(4 + c.wg, 128);
      if (c.warp == (i >> 2)) tma2d_add(&p.map_out, c.sm + SM_RING + c.wg * 8192 + c.warp * 40960, nt * 192 + c.warp * 64, j * 256 + c.rank * 128 + c.wg * 64);
    }
  }
  BULK_COMMIT();
  PROF(c.wg, 43);
  BULK_WAIT_READ(0);
  PROF(c.wg, 44);
}

__device__ __forceinline__ void p3_producer(const Params& p, const Ctx& c, int u1, int u2, int rot, int x) {
  const bool first = p.s.r[c.cl].p3 >= 24;
  const int tile = p.s.r[c.cl].p3 - (first ? 24 : 0), j = tile / 3, nt = tile - 3 * j;
  int slot = 0, par = 1, cnt = 0;
  auto wait_free = [&](int s) {
    const int f = wrap5(s + 5 - rot);
    if (f < u2) mbar_wait(c.bar + (B_P2E + s) * 8, ((u2 - 1 - f) / 5) & 1);
    else if (u1) wait_p1_free(c, u1, s);
  };
  asm volatile(ELECT("prefetch.tensormap [%0];") ::"l"(&p.map_o[0]) : "memory");
  asm volatile(ELECT("prefetch.tensormap [%0];") ::"l"(&p.map_out) : "memory");
  if ((c.phases & 16) && p.s.r[c.cl].n1 < 8 && p.s.r[c.cl].n2 < 2) flag_wait<true>(F_GATE, 256);
  uint32_t ready = (c.phases & 16) ? 0u : ~0u;
  const int q1 = p.s.task[c.cl][1];
  for (int q = p.s.task[c.cl][0]; q < q1 + (first ? 9 : 0); q++) {
    const bool brA = q >= q1;
    const int kb = brA ? q - q1 : p.s.p3_order[tile][q];
    if (!brA) mask_wait(ready, kb >> 1, F_CTX + j * 64 + c.lane, 4);
    else if (kb == 0 && (c.phases & 16)) flag_wait<false>(F_CTX + j * 64 + 32, 16);
    const uint8_t* a = brA ? g_oA + (j * 4 + c.rank * 2) * 73728 + kb * 8192 : g_S + (size_t)p.s.qblk[(kb >> 1) * 8 + j] * 65536 + c.rank * 32768 + (kb & 1) * 8192;
    const uint32_t st = c.sm + SM_RING + p3_pos(slot, x) * 40960, fb = c.bar + (B_P3F + slot) * 8;
    if (cnt < 4) { wait_free(p3_pos(cnt, x)); wait_free(p3_pos(cnt, x) + 1); }
    else if (cnt == 4) mbar_wait(c.bar + B_DONE * 8, 0);
    else mbar_wait(c.bar + (B_P3E + slot) * 8, par);
    cnt++;
    mbar_expect(fb, 40960);
    bulk_load(st, a, 8192, fb, POL(3));
    bulk_load(st + 8192, a + (brA ? 73728 : 16384), 8192, fb, POL(3));
    tma3d_mc(st + 16384 + c.rank * 12288, &p.map_o[brA], 0, kb * 64 + c.rank * 32, nt * 3, fb);
    if (++slot == 5) { slot = 0; par ^= 1; }
  }
}

__device__ __forceinline__ float bf_lo(uint32_t w) { return __uint_as_float(w << 16); }
__device__ __forceinline__ float bf_hi(uint32_t w) { return __uint_as_float(w & 0xffff0000u); }

__device__ __forceinline__ void gate_rows(const Params& p, int row0, int lane) {
  const uint4* x = reinterpret_cast<const uint4*>(p.x + (size_t)(row0 + (lane >> 2)) * DM) + (lane & 3);
  const uint4* w = reinterpret_cast<const uint4*>(p.gate_w) + (lane & 3);
  float a = 0.f;
#pragma unroll 1
  for (int b = 0; b < 3; b++) {
    uint4 u[6];
#pragma unroll
    for (int i = 0; i < 6; i++) u[i] = __ldg(x + (b * 6 + i) * 4);
#pragma unroll
    for (int i = 0; i < 6; i++) {
      const uint4 v = __ldg(w + (b * 6 + i) * 4);
      a = fmaf(bf_lo(u[i].x), bf_lo(v.x), a); a = fmaf(bf_hi(u[i].x), bf_hi(v.x), a);
      a = fmaf(bf_lo(u[i].y), bf_lo(v.y), a); a = fmaf(bf_hi(u[i].y), bf_hi(v.y), a);
      a = fmaf(bf_lo(u[i].z), bf_lo(v.z), a); a = fmaf(bf_hi(u[i].z), bf_hi(v.z), a);
      a = fmaf(bf_lo(u[i].w), bf_lo(v.w), a); a = fmaf(bf_hi(u[i].w), bf_hi(v.w), a);
    }
  }
  a += __shfl_xor_sync(0xffffffffu, a, 1);
  a += __shfl_xor_sync(0xffffffffu, a, 2);
  if ((lane & 3) == 0) g_gate[row0 + (lane >> 2)] = 1.f / (1.f + __expf(-a));
}

__device__ __forceinline__ void lds10(uint32_t (&k)[10], uint32_t a) {
  asm volatile("ld.shared.v2.u32 {%0, %1}, [%10];\nld.shared.v2.u32 {%2, %3}, [%10+8];\nld.shared.v2.u32 {%4, %5}, [%10+16];\n"
               "ld.shared.v2.u32 {%6, %7}, [%10+24];\nld.shared.v2.u32 {%8, %9}, [%10+32];"
               : "=r"(k[0]), "=r"(k[1]), "=r"(k[2]), "=r"(k[3]), "=r"(k[4]), "=r"(k[5]), "=r"(k[6]), "=r"(k[7]), "=r"(k[8]), "=r"(k[9]) : "r"(a));
}
__device__ __forceinline__ void local_attn(const Params& p, const Ctx& c, int rb, int hs) {
  const int lane = c.lane, grp = rb >> 2, par = lane >> 4, i0 = 2 * (lane & 15);
  const uint32_t buf = c.sm + SM_BUF + (c.warp - 2) * 8192, bqk = c.bar + (B_LA + (c.warp - 2) * 2) * 8, bv = bqk + 8;
  const uint32_t mine = buf + 2304 + par * 160 + i0 * 4;
  const bool flags = c.phases & 16;
  auto fetch_qk = [&](int i) {
    if (flags && !(i & 1)) {
      const int q = i >> 1;
      const int tgt = q == 0 ? 24 : q == 3 ? 8 : 12;
      flag_wait<false>(F_QKVA + (grp - (grp > 0 && (rb & 3) == 0 ? par : 0)) * 4 + q, tgt);
    }
    mbar_expect(bqk, 5184);
    tma3d(buf, &p.map_t[0], rb * 32, 0, 9 * (4 * i + hs), bqk, POL(2));
    tma3d(buf + 2304, &p.map_t[1], rb * 32 - 8, 0, 288 + 9 * (4 * i + hs), bqk, POL(2));
  };
  auto fetch_v = [&](int i) { mbar_expect(bv, 2880); tma3d(buf + 5248, &p.map_t[1], rb * 32 - 8, 0, 576 + 9 * (4 * i + hs), bv, POL(2)); };
  fetch_qk(0);
  if (flags) flag_wait<true>(F_GATE, 256);
#pragma unroll 1
  for (int q = 0; q < 8; q++) {
    fetch_v(q);
    float a[8], b[8];
#pragma unroll
    for (int w = 0; w < 8; w++) a[w] = b[w] = 0.f;
    mbar_wait(bqk, q & 1);
    PROFB(1 + 2 * q);
#pragma unroll 1
    for (int j = 0; j < 9; j++) {
      uint32_t x, y, k[10];
      asm volatile("ld.shared.v2.u32 {%0, %1}, [%2];" : "=r"(x), "=r"(y) : "r"(buf + lane * 8 + j * 256));
      lds10(k, mine + j * 320);
      const float xl = bf_lo(x), xh = bf_hi(x), yl = bf_lo(y), yh = bf_hi(y);
#pragma unroll
      for (int m = 1; m < 10; m++) {
        const float kl = bf_lo(k[m]), kh = bf_hi(k[m]);
        if (m < 9) a[8 - m] = fmaf(xl, kl, fmaf(xh, kh, a[8 - m]));
        if (m > 1) b[9 - m] = fmaf(yl, kl, fmaf(yh, kh, b[9 - m]));
      }
    }
    __syncwarp();
    mbar_wait(bv, q & 1);
    if (q & 1) flag_add_rx(F_TS + (q >> 1));
    if (q < 7) fetch_qk(q + 1);
    constexpr float SC = 0.23570226039551584f * 1.4426950408889634f;
    const float* gp = g_gate + rb * 64 + 2 * i0 + par;
    const float ga = __ldcg(gp), gb = __ldcg(gp + 2);
    float ma = a[0], mb = b[0];
#pragma unroll
    for (int w = 1; w < 8; w++) {
      if (rb == 0) {
        if (i0 < w) a[w] = -INFINITY;
        if (i0 + 1 < w) b[w] = -INFINITY;
      }
      ma = fmaxf(ma, a[w]); mb = fmaxf(mb, b[w]);
    }
    float la = 0.f, lb = 0.f;
#pragma unroll
    for (int w = 0; w < 8; w++) {
      a[w] = ex2((a[w] - ma) * SC); b[w] = ex2((b[w] - mb) * SC);
      la += a[w]; lb += b[w];
    }
    la = __fdividef(ga, la); lb = __fdividef(gb, lb);
#pragma unroll
    for (int w = 0; w < 8; w++) { a[w] *= la; b[w] *= lb; }
    uint8_t* dst = g_oA + rb * 73728 + ((i0 & 2) + par) * 4;
#pragma unroll 1
    for (int j = 0; j < 9; j++) {
      uint32_t v[10];
      lds10(v, mine + 2944 + j * 320);
      float a0 = 0.f, a1 = 0.f, b0 = 0.f, b1 = 0.f;
#pragma unroll
      for (int m = 1; m < 10; m++) {
        const float vl = bf_lo(v[m]), vh = bf_hi(v[m]);
        if (m < 9) { a0 = fmaf(a[8 - m], vl, a0); a1 = fmaf(a[8 - m], vh, a1); }
        if (m > 1) { b0 = fmaf(b[9 - m], vl, b0); b1 = fmaf(b[9 - m], vh, b1); }
      }
      const uint32_t wa = pack_bf16(a0, a1), wb = pack_bf16(b0, b1);
      const uint32_t got = __shfl_xor_sync(0xffffffffu, par ? wa : wb, 16);
      const uint32_t r0 = par ? got : wa, r1 = par ? wb : got;
      const int col = 18 * (4 * q + hs) + 2 * j, o = col * 128 + ((((i0 >> 2) ^ col) & 7) << 4);
      *reinterpret_cast<uint32_t*>(dst + o) = __byte_perm(r0, r1, 0x5410);
      *reinterpret_cast<uint32_t*>(dst + ((o + 128) ^ 16)) = __byte_perm(r0, r1, 0x7632);
    }
    __syncwarp();
    PROFB(2 + 2 * q);
  }
  mbar_arrive_one(c.bar + B_LAD * 8);
  flag_add(F_CTX + grp * 64 + 32);
}

__global__ void __cluster_dims__(2, 1, 1) __launch_bounds__(384, 1) fused_kernel(const __grid_constant__ Params p) {
  extern __shared__ uint8_t smem_raw[];
  Ctx c;
  c.sm = ((uint32_t)__cvta_generic_to_shared(smem_raw) + 1023u) & ~1023u;
  c.bar = c.sm + SM_BAR;
  c.lane = threadIdx.x & 31;
  const int wid = __shfl_sync(0xffffffffu, threadIdx.x >> 5, 0);
  if (wid < 6) asm volatile("prefetch.tensormap [%0];" ::"l"(&p.map_a[0] + wid) : "memory");
  c.wg = wid >> 2;
  c.warp = wid & 3;
  PROF(c.wg, 0);
  PROFG(61);
  c.cl = (blockIdx.x + (wid >> 4)) >> 1;
  c.rank = blockIdx.x & 1;
  c.rbar = mapa(c.bar, c.lane & 1);
  {
    const int w = wid, cnt = (((int)(B_CNT >> (4 * w)) - 1) & 15) + 1;
    if (w < 11) {
#pragma unroll
      for (int i = 0; i < 8; i++) asm volatile("mbarrier.init.shared::cta.b64 [%0], %1;" ::"r"(c.bar + w * 64 + i * 8), "r"(cnt));
    }
    asm volatile("fence.mbarrier_init.release.cluster;" ::: "memory");
  }
  if (c.wg == 2) PROF(2, 56);
  asm volatile("barrier.cluster.arrive.relaxed;" ::: "memory");
  c.phases = p.s.r[c.cl].phases;
  const bool do1 = p.s.r[c.cl].n1 > 0, do2 = p.s.r[c.cl].n2 > 0, do3 = p.s.r[c.cl].p3 != 255;
  if (do1 && c.wg == 2 && c.warp == 0) {
    const int type = p.s.r[c.cl].slab >> 3;
    PROF(2, 57);
    FENCE_ASYNC_SMEM();
    mbar_expect(c.bar + B_P1F * 8, type ? 32768 : 16384);
    tma2d(type ? c.sm + SM_BUF + 32768 : c.sm + SM_RING, &p.map_a[type], type ? 512 : 0, (p.s.r[c.cl].slab & 7) * 256 + c.rank * 128, c.bar + B_P1F * 8);
    PROF(2, 58);
  }
  asm volatile("barrier.cluster.wait.acquire;" ::: "memory");
  if (c.wg == 2) PROF(2, 59);
  if (do1 && c.wg == 2 && c.warp == 0) {
    const int type = p.s.r[c.cl].slab >> 3, tile = p.s.r[c.cl].tile[0] & 63;
    const CUtensorMap* m = &p.map_w[type * 2 + (tile >> 5)];
#pragma unroll 1
    for (int s = 1 - type; s < NPRO; s++) {
      const int kb = (s - type) >> 1;
      const uint32_t fb = c.bar + (B_P1F + s) * 8;
      if (s) mbar_expect(fb, 16384);
      if ((s ^ type) & 1) tma2d_mc(c.sm + SM_RING + s * 16384 + c.rank * 8192, m, (tile & 31) * 128 + c.rank * 64, kb < 0 ? 512 : kb * 64, fb);
      else tma2d(c.sm + SM_RING + s * 16384, &p.map_a[type], kb * 64, (p.s.r[c.cl].slab & 7) * 256 + c.rank * 128, fb);
    }
  }

  if (c.wg < 2) {
    PROF(c.wg, 4);
    asm volatile("setmaxnreg.inc.sync.aligned.u32 224;");
    if (c.wg == 1) {
      if (do1) bar_arrive(ORDER, 256);
      if (c.lane == 0) mbar_arrive(c.bar + B_P2F * 8);
    }
    PL(0);
    if (do1) p1_consumer(p, c);
    PL(1);
    if (do2) p2_consumer(p, c, p.s.r[c.cl].rot);
    PL(2);
    if (do3) p3_consumer(p, c, p.s.r[c.cl].x3);
    PL(3);
    PROF(c.wg, 63);
    PROFG(62);
    if (c.lane == 0) mbar_arrive(c.bar + B_FIN * 8);
    __syncwarp();
    cluster_sync();
  } else {
    asm volatile("setmaxnreg.dec.sync.aligned.u32 56;");
    if (c.warp == 0) {
      PROF(2, 60);
      if (do1) p1_producer(p, c);
      if (do2) p2_producer(p, c, p.s.r[c.cl].u1, p.s.r[c.cl].rot);
      if (do3) p3_producer(p, c, p.s.r[c.cl].u1, p.s.r[c.cl].u2, p.s.r[c.cl].rot, p.s.r[c.cl].x3);
    } else if (c.warp == 1) {
      const int f = do1 ? p1_storer(p, c) : -1;
      publish_and_load_q(p, c, f, 1, flag_peek(F_Q + p.s.r[c.cl].item[1]));
      if (do2) p2_storer(p, c, (p.s.r[c.cl].n1 & 1) * 10);
      else { mbar_wait(c.bar + B_LAD * 8, 0); release(c, B_DONE); }
      if (do3) {
        const int tile = p.s.r[c.cl].p3 % 24;
        if (p.s.task[c.cl][1] == 64) {
          for (int r = 0; r < (64 - p.s.task[c.cl][0] - ZLEAD) / 5; r++) mbar_wait(c.bar + B_P3F * 8, r & 1);
          const int j = tile / 3, nt = tile - 3 * j;
          uint4* o = reinterpret_cast<uint4*>(p.out + (size_t)(j * 256 + c.rank * 128 + (c.lane >> 3)) * DM + nt * 192) + (c.lane & 7);
#pragma unroll 4
          for (int r = 0; r < 32; r++) o[r * 288] = o[r * 288 + 8] = o[r * 288 + 16] = make_uint4(0u, 0u, 0u, 0u);
          __syncwarp();
          flag_add(F_OUT + tile * 2 + c.rank);
        } else if (c.phases & 16) {
          flag_wait<false, 256>(F_OUT + tile * 2 + c.rank, 1);
        }
        mbar_arrive_one(c.bar + B_OUT * 8);
      }
    } else {
      const int bw = blockIdx.x * 2 + (c.warp - 2);
      if ((c.phases & 1) && bw < 256) {
        gate_rows(p, bw * 8, c.lane);
        __syncwarp();
        flag_add(F_GATE);
      }
      if (p.s.r[c.cl].bg != 255) local_attn(p, c, p.s.r[c.cl].bg, bw & 3);
      else if (c.lane == 0) mbar_arrive(c.bar + B_LAD * 8);
    }
    __syncwarp();
    bar_sync(3, 128);
    if (c.warp == 0 && (c.phases & 32)) {
      int last = 0;
      if (c.lane == 0) { __threadfence(); last = atomicAdd(g_flags + F_DONE, 1) == 2 * NCL - 1; }
      if (__shfl_sync(0xffffffffu, last, 0)) for (int i = c.lane; i < F_NUM; i += 32) g_flags[i] = 0;
    }
    if (c.warp == 1) mbar_wait(c.bar + B_FIN * 8, 0);
    __syncwarp();
    cluster_sync();
  }
}

SCHED_DECL Sched k_sched = {
  {{0,30,1,22,0,{209,0,0,0,0,0,0,0,0,0,0},{0,0,0,0,0,0,0,0,0,0,0},{66,164,131,44,39,46,37,48,40,43,41,53,45,42,54,50,38,56,49,47,52,59,51,63,62,58,61,55,60,57}},
   {1,30,2,32,1,{185,200,0,0,0,0,0,0,0,0,0},{0,0,0,0,0,0,0,0,0,0,0},{68,98,131,44,39,46,37,48,40,43,41,53,45,42,54,38,50,56,49,47,52,59,51,63,62,58,61,55,60,57}},
   {2,29,0,1,2,{0,0,0,0,0,0,0,0,0,0,0},{0,0,0,0,0,0,0,0,0,0,0},{65,164,131,44,14,37,48,40,43,41,53,45,42,54,50,38,49,47,56,52,59,51,63,62,58,61,55,60,57,0}},
   {3,28,0,9,3,{0,0,0,0,0,0,0,0,0,0,0},{0,0,0,0,0,0,0,0,0,0,0},{68,33,131,44,14,37,8,43,41,53,45,42,54,50,38,49,47,56,52,59,51,63,62,58,61,55,60,57,0,0}},
   {4,28,0,10,4,{0,0,0,0,0,0,0,0,0,0,0},{0,0,0,0,0,0,0,0,0,0,0},{128,164,1,35,7,46,16,40,9,21,13,10,22,18,6,17,24,15,20,27,19,31,30,26,29,23,28,25,0,0}},
   {5,27,0,21,5,{0,0,0,0,0,0,0,0,0,0,0},{0,0,0,0,0,0,0,0,0,0,0},{128,164,1,35,7,46,16,40,11,53,10,22,18,6,17,24,15,20,27,19,31,30,26,29,23,28,25,0,0,0}},
   {6,26,0,23,6,{0,0,0,0,0,0,0,0,0,0,0},{0,0,0,0,0,0,0,0,0,0,0},{160,98,131,44,14,37,8,41,21,45,22,18,6,17,24,15,20,27,19,31,94,26,29,23,28,25,0,0,0,0}},
   {7,25,2,18,7,{192,231,0,0,0,0,0,0,0,0,0},{0,255,0,0,0,0,0,0,0,0,0},{128,2,131,71,69,72,105,85,109,86,82,70,81,88,79,84,91,83,95,90,94,93,87,92,89,0,0,0,0,0}},
   {0,30,1,14,8,{226,0,0,0,0,0,0,0,0,0,0},{0,0,0,0,0,0,0,0,0,0,0},{128,98,1,35,7,14,5,16,8,11,9,21,13,10,22,18,6,24,17,15,20,27,19,31,30,26,29,23,28,25}},
   {1,30,1,44,9,{233,0,0,0,0,0,0,0,0,0,0},{0,0,0,0,0,0,0,0,0,0,0},{128,164,1,35,7,14,5,16,8,11,9,21,13,10,22,6,18,24,17,15,20,27,19,31,30,26,29,23,28,25}},
   {2,29,0,20,10,{0,0,0,0,0,0,0,0,0,0,0},{0,0,0,0,0,0,0,0,0,0,0},{128,33,2,35,7,46,16,8,11,9,21,13,10,22,18,6,17,15,24,20,27,19,31,30,26,29,23,28,25,0}},
   {3,28,0,17,11,{0,0,0,0,0,0,0,0,0,0,0},{0,0,0,0,0,0,0,0,0,0,0},{128,164,2,35,7,46,16,40,9,21,13,10,22,18,6,17,15,24,20,27,19,31,30,26,29,23,28,25,0,0}},
   {4,28,0,5,12,{0,0,0,0,0,0,0,0,0,0,0},{0,0,0,0,0,0,0,0,0,0,0},{160,2,33,12,39,5,48,11,41,53,45,42,54,50,38,49,56,47,52,59,51,63,62,58,61,55,60,57,0,0}},
   {5,27,2,36,13,{251,202,0,0,0,0,0,0,0,0,0},{0,0,0,0,0,0,0,0,0,0,0},{160,2,33,12,39,5,48,9,43,13,42,54,50,38,49,56,47,52,59,51,63,62,58,61,55,60,57,0,0,0}},
   {6,26,0,3,14,{0,0,0,0,0,0,0,0,0,0,0},{0,0,0,0,0,0,0,0,0,0,0},{65,4,99,71,46,16,40,11,53,10,54,50,38,49,56,47,52,59,51,63,126,58,61,55,60,57,0,0,0,0}},
   {7,25,0,19,15,{0,0,0,0,0,0,0,0,0,0,0},{0,0,0,0,0,0,0,0,0,0,0},{160,98,99,103,101,104,75,117,74,118,114,102,113,120,111,116,123,115,127,122,126,125,119,124,121,0,0,0,0,0}},
   {0,4,8,41,255,{17,26,62,173,179,219,234,225,0,0,0},{0,0,0,0,0,0,0,0,0,0,0},{160,4,33,12,0,0,0,0,0,0,0,0,0,0,0,0,0,0,0,0,0,0,0,0,0,0,0,0,0,0}},
   {1,4,7,45,255,{21,46,73,182,121,217,205,0,0,0,0},{0,0,0,0,0,0,63,0,0,0,0},{160,2,33,12,0,0,0,0,0,0,0,0,0,0,0,0,0,0,0,0,0,0,0,0,0,0,0,0,0,0}},
   {2,6,7,13,255,{96,119,129,65,84,123,190,0,0,0,0},{0,0,0,0,0,0,96,0,0,0,0},{160,4,34,12,39,5,0,0,0,0,0,0,0,0,0,0,0,0,0,0,0,0,0,0,0,0,0,0,0,0}},
   {3,8,4,8,255,{56,118,76,142,0,0,0,0,0,0,0},{0,0,0,126,0,0,0,0,0,0,0},{160,1,34,12,39,5,48,11,0,0,0,0,0,0,0,0,0,0,0,0,0,0,0,0,0,0,0,0,0,0}},
   {4,8,5,43,255,{112,47,85,124,189,0,0,0,0,0,0},{0,0,0,0,0,0,0,0,0,0,0},{68,98,131,44,14,37,8,43,0,0,0,0,0,0,0,0,0,0,0,0,0,0,0,0,0,0,0,0,0,0}},
   {5,10,4,18,255,{134,108,125,248,0,0,0,0,0,0,0},{0,0,0,0,0,0,0,0,0,0,0},{68,98,131,44,14,37,8,41,21,45,0,0,0,0,0,0,0,0,0,0,0,0,0,0,0,0,0,0,0,0}},
   {6,10,7,20,255,{128,45,66,169,52,154,228,0,0,0,0},{0,0,0,0,1,0,0,0,0,0,0},{97,164,76,103,69,48,9,43,13,42,0,0,0,0,0,0,0,0,0,0,0,0,0,0,0,0,0,0,0,0}},
   {7,9,6,11,255,{40,97,113,94,148,136,0,0,0,0,0},{0,0,0,0,0,0,0,0,0,0,0},{65,4,76,78,80,73,107,77,106,0,0,0,0,0,0,0,0,0,0,0,0,0,0,0,0,0,0,0,0,0}},
   {8,18,4,10,16,{72,166,249,203,0,0,0,0,0,0,0},{1,0,0,0,0,0,0,0,0,0,0},{132,161,71,38,5,35,44,109,9,21,13,18,17,20,15,31,26,23,0,0,0,0,0,0,0,0,0,0,0,0}},
   {9,19,3,8,17,{122,163,229,0,0,0,0,0,0,0,0},{0,0,0,0,0,0,0,0,0,0,0},{132,41,102,7,99,44,16,109,9,21,13,18,84,17,27,30,29,26,25,0,0,0,0,0,0,0,0,0,0,0}},
   {10,18,4,14,18,{105,196,153,208,0,0,0,0,0,0,0},{0,0,0,0,0,0,0,0,0,0,0},{128,41,3,7,99,44,16,109,11,21,22,18,17,24,27,31,23,26,0,0,0,0,0,0,0,0,0,0,0,0}},
   {11,19,2,6,19,{222,188,0,0,0,0,0,0,0,0,0},{0,31,0,0,0,0,0,0,0,0,0},{96,106,107,7,99,44,16,40,9,21,10,6,15,24,27,31,30,26,25,0,0,0,0,0,0,0,0,0,0,0}},
   {12,19,3,25,20,{48,161,239,0,0,0,0,0,0,0,0},{0,0,128,0,0,0,0,0,0,0,0},{100,1,140,14,99,44,8,40,9,13,22,6,24,20,27,31,29,28,25,0,0,0,0,0,0,0,0,0,0,0}},
   {13,17,2,24,21,{149,253,0,0,0,0,0,0,0,0,0},{2,0,0,0,0,0,0,0,0,0,0},{100,1,107,80,108,75,104,85,74,82,81,79,91,94,90,87,89,0,0,0,0,0,0,0,0,0,0,0,0,0}},
   {14,18,3,47,22,{168,159,242,0,0,0,0,0,0,0,0},{0,0,7,0,0,0,0,0,0,0,0},{67,165,107,14,16,73,39,11,40,13,22,6,15,20,19,30,29,28,0,0,0,0,0,0,0,0,0,0,0,0}},
   {15,18,3,4,23,{167,235,201,0,0,0,0,0,0,0,0},{224,0,0,0,0,0,0,0,0,0,0},{66,41,71,43,16,73,39,11,77,45,22,6,24,20,19,26,29,28,0,0,0,0,0,0,0,0,0,0,0,0}},
   {8,19,2,0,24,{144,221,0,0,0,0,0,0,0,0,0},{0,0,0,0,0,0,0,0,0,0,0},{65,165,78,43,16,39,104,8,11,10,22,6,24,27,19,30,29,28,25,0,0,0,0,0,0,0,0,0,0,0}},
   {9,18,2,17,25,{53,238,0,0,0,0,0,0,0,0,0},{0,127,0,0,0,0,0,0,0,0,0},{66,161,107,14,103,5,104,8,11,10,70,88,22,15,19,31,23,28,0,0,0,0,0,0,0,0,0,0,0,0}},
   {10,19,2,30,26,{138,247,0,0,0,0,0,0,0,0,0},{0,240,0,0,0,0,0,0,0,0,0},{65,161,162,14,103,5,104,8,9,13,10,6,15,20,19,93,30,28,25,0,0,0,0,0,0,0,0,0,0,0}},
   {11,18,3,7,27,{80,147,160,0,0,0,0,0,0,0,0},{0,0,0,0,0,0,0,0,0,0,0},{100,1,3,14,103,5,8,109,11,13,22,18,17,20,19,93,23,28,0,0,0,0,0,0,0,0,0,0,0,0}},
   {12,18,4,31,28,{104,51,245,224,0,0,0,0,0,0,0},{0,0,0,0,0,0,0,0,0,0,0},{96,106,107,7,5,39,16,11,45,21,10,18,17,15,19,30,26,23,0,0,0,0,0,0,0,0,0,0,0,0}},
   {13,17,4,34,29,{64,82,164,243,0,0,0,0,0,0,0},{0,0,27,8,0,0,0,0,0,0,0},{96,106,102,69,103,8,9,109,77,86,70,88,84,83,95,93,92,0,0,0,0,0,0,0,0,0,0,0,0,0}},
   {14,19,3,2,30,{176,254,232,0,0,0,0,0,0,0,0},{0,0,0,0,0,0,0,0,0,0,0},{66,41,162,7,5,8,35,44,21,45,10,18,17,24,27,31,26,23,25,0,0,0,0,0,0,0,0,0,0,0}},
   {15,18,3,27,31,{88,50,215,0,0,0,0,0,0,0,0},{0,0,128,0,0,0,0,0,0,0,0},{132,161,78,69,72,35,44,85,40,10,18,17,15,27,95,30,23,25,0,0,0,0,0,0,0,0,0,0,0,0}},
   {8,3,5,15,255,{34,28,79,54,216,0,0,0,0,0,0},{0,0,0,0,0,0,0,0,0,0,0},{66,41,140,0,0,0,0,0,0,0,0,0,0,0,0,0,0,0,0,0,0,0,0,0,0,0,0,0,0,0}},
   {9,3,6,5,255,{2,12,59,77,126,206,0,0,0,0,0},{0,0,0,0,0,64,0,0,0,0,0},{128,36,162,0,0,0,0,0,0,0,0,0,0,0,0,0,0,0,0,0,0,0,0,0,0,0,0,0,0,0}},
   {10,3,6,16,255,{4,117,41,109,140,230,0,0,0,0,0},{0,0,0,0,0,0,0,0,0,0,0},{96,106,107,0,0,0,0,0,0,0,0,0,0,0,0,0,0,0,0,0,0,0,0,0,0,0,0,0,0,0}},
   {11,3,6,1,255,{35,19,115,75,199,237,0,0,0,0,0},{0,0,0,0,0,0,0,0,0,0,0},{105,2,140,0,0,0,0,0,0,0,0,0,0,0,0,0,0,0,0,0,0,0,0,0,0,0,0,0,0,0}},
   {12,3,5,13,255,{10,102,111,197,120,0,0,0,0,0,0},{0,0,0,0,0,0,0,0,0,0,0},{66,165,102,0,0,0,0,0,0,0,0,0,0,0,0,0,0,0,0,0,0,0,0,0,0,0,0,0,0,0}},
   {13,5,5,6,255,{24,29,43,172,223,0,0,0,0,0,0},{0,0,0,0,0,0,0,0,0,0,0},{132,161,140,7,99,0,0,0,0,0,0,0,0,0,0,0,0,0,0,0,0,0,0,0,0,0,0,0,0,0}},
   {14,3,7,40,255,{3,101,175,49,177,137,213,0,0,0,0},{0,0,0,0,0,0,48,0,0,0,0},{132,161,102,0,0,0,0,0,0,0,0,0,0,0,0,0,0,0,0,0,0,0,0,0,0,0,0,0,0,0}},
   {15,3,9,38,255,{32,30,133,90,81,193,194,252,184,0,0},{0,0,0,0,0,0,0,0,0,0,0},{65,36,140,0,0,0,0,0,0,0,0,0,0,0,0,0,0,0,0,0,0,0,0,0,0,0,0,0,0,0}},
   {8,3,6,46,255,{33,11,61,93,141,207,0,0,0,0,0},{0,0,0,6,0,128,0,0,0,0,0},{128,36,3,0,0,0,0,0,0,0,0,0,0,0,0,0,0,0,0,0,0,0,0,0,0,0,0,0,0,0}},
   {9,3,7,26,255,{0,20,135,74,178,157,250,0,0,0,0},{0,0,0,0,0,0,0,0,0,0,0},{65,165,3,0,0,0,0,0,0,0,0,0,0,0,0,0,0,0,0,0,0,0,0,0,0,0,0,0,0,0}},
   {10,3,6,22,255,{37,25,70,89,83,195,0,0,0,0,0},{0,0,0,0,0,0,0,0,0,0,0},{100,2,140,0,0,0,0,0,0,0,0,0,0,0,0,0,0,0,0,0,0,0,0,0,0,0,0,0,0,0}},
   {11,3,6,12,255,{39,78,106,146,220,211,0,0,0,0,0},{0,0,0,0,7,15,0,0,0,0,0},{132,165,102,0,0,0,0,0,0,0,0,0,0,0,0,0,0,0,0,0,0,0,0,0,0,0,0,0,0,0}},
   {12,3,6,2,255,{7,58,130,86,156,187,0,0,0,0,0},{0,0,0,0,0,0,0,0,0,0,0},{128,41,3,0,0,0,0,0,0,0,0,0,0,0,0,0,0,0,0,0,0,0,0,0,0,0,0,0,0,0}},
   {13,3,7,35,255,{22,60,91,181,162,241,210,0,0,0,0},{0,0,0,0,0,0,0,0,0,0,0},{66,165,162,0,0,0,0,0,0,0,0,0,0,0,0,0,0,0,0,0,0,0,0,0,0,0,0,0,0,0}},
   {14,3,5,12,255,{16,31,69,170,198,0,0,0,0,0,0},{0,0,0,0,3,0,0,0,0,0,0},{65,36,140,0,0,0,0,0,0,0,0,0,0,0,0,0,0,0,0,0,0,0,0,0,0,0,0,0,0,0}},
   {15,4,5,9,255,{9,63,67,55,214,0,0,0,0,0,0},{0,0,0,128,64,0,0,0,0,0,0},{128,32,42,38,0,0,0,0,0,0,0,0,0,0,0,0,0,0,0,0,0,0,0,0,0,0,0,0,0,0}},
   {8,3,5,42,255,{36,100,131,183,246,0,0,0,0,0,0},{0,0,0,109,0,0,0,0,0,0,0},{96,106,162,0,0,0,0,0,0,0,0,0,0,0,0,0,0,0,0,0,0,0,0,0,0,0,0,0,0,0}},
   {9,3,6,33,255,{14,57,132,151,244,227,0,0,0,0,0},{0,0,0,0,0,0,0,0,0,0,0},{96,106,140,0,0,0,0,0,0,0,0,0,0,0,0,0,0,0,0,0,0,0,0,0,0,0,0,0,0,0}},
   {10,3,5,21,255,{6,71,150,218,236,0,0,0,0,0,0},{0,0,0,0,0,0,0,0,0,0,0},{132,165,102,0,0,0,0,0,0,0,0,0,0,0,0,0,0,0,0,0,0,0,0,0,0,0,0,0,0,0}},
   {11,3,5,29,255,{5,99,42,87,255,0,0,0,0,0,0},{0,0,0,0,255,0,0,0,0,0,0},{128,161,162,0,0,0,0,0,0,0,0,0,0,0,0,0,0,0,0,0,0,0,0,0,0,0,0,0,0,0}},
   {12,3,6,39,255,{15,114,174,145,139,212,0,0,0,0,0},{0,0,0,0,0,0,0,0,0,0,0},{132,161,162,0,0,0,0,0,0,0,0,0,0,0,0,0,0,0,0,0,0,0,0,0,0,0,0,0,0,0}},
   {13,4,6,16,255,{8,103,68,107,165,152,0,0,0,0,0},{0,0,0,0,0,0,0,0,0,0,0},{128,41,3,14,0,0,0,0,0,0,0,0,0,0,0,0,0,0,0,0,0,0,0,0,0,0,0,0,0,0}},
   {14,3,6,0,255,{38,98,92,143,155,204,0,0,0,0,0},{0,0,0,0,15,0,0,0,0,0,0},{128,32,42,0,0,0,0,0,0,0,0,0,0,0,0,0,0,0,0,0,0,0,0,0,0,0,0,0,0,0}},
   {15,3,5,37,255,{23,44,171,180,191,0,0,0,0,0,0},{0,0,0,13,128,0,0,0,0,0,0},{67,165,162,0,0,0,0,0,0,0,0,0,0,0,0,0,0,0,0,0,0,0,0,0,0,0,0,0,0,0}},
   {6,2,6,4,255,{1,18,27,95,127,240,0,0,0,0,0},{0,0,0,0,124,0,0,0,0,0,0},{128,2,0,0,0,0,0,0,0,0,0,0,0,0,0,0,0,0,0,0,0,0,0,0,0,0,0,0,0,0}},
   {7,5,5,28,255,{13,116,110,158,186,0,0,0,0,0,0},{0,0,0,0,0,0,0,0,0,0,0},{97,164,108,110,112,0,0,0,0,0,0,0,0,0,0,0,0,0,0,0,0,0,0,0,0,0,0,0,0,0}}},
  {{0,20,0,0},{0,7,0,0},{28,64,0,0},{23,64,0,0},{23,64,0,0},{17,64,0,0},{11,64,0,0},{12,24,0,0},{13,29,0,0},{0,13,0,0},{25,64,0,0},
   {22,64,0,0},{23,64,0,0},{0,2,0,0},{11,64,0,0},{5,64,0,0},{0,5,0,0},{0,0,0,0},{7,21,0,0},{19,64,0,0},{0,5,0,0},{24,64,0,0},
   {13,25,0,0},{10,64,0,0},{11,23,0,0},{7,19,0,0},{29,64,0,0},{12,26,0,0},{0,10,0,0},{0,14,0,0},{0,11,0,0},{11,23,0,0},{24,64,0,0},
   {5,22,0,0},{0,12,0,0},{12,64,0,0},{0,12,0,0},{0,11,0,0},{33,64,0,0},{0,11,0,0},{14,64,0,0},{13,23,0,0},{10,23,0,0},{10,28,0,0},
   {21,64,0,0},{26,64,0,0},{0,10,0,0},{0,13,0,0},{0,0,0,0},{0,14,0,0},{20,64,0,0},{2,20,0,0},{14,33,0,0},{0,10,0,0},{20,64,0,0},
   {3,23,0,0},{0,12,0,0},{0,3,0,0},{0,17,0,0},{0,13,0,0},{0,14,0,0},{23,64,0,0},{14,24,0,0},{0,7,0,0},{23,64,0,0},{0,11,0,0}},
  {{12,52,36,44,26,58,20,42,22,18,16,32,10,47,57,15,25,7,3,50,1,9,5,4,41,40,55,49,48,54,35,34,13,31,30,39,61,60,63,62,38,53,37,45,27,59,21,43,23,19,17,33,11,29,46,56,28,14,24,6,51,2,0,8},
   {58,13,36,27,20,23,18,33,10,29,12,45,26,43,22,17,32,46,56,15,25,7,3,50,1,9,5,4,49,48,55,54,41,31,30,40,61,60,63,62,39,38,53,52,35,59,34,37,44,21,42,19,16,11,47,57,28,14,24,6,51,2,0,8},
   {49,52,55,41,59,34,37,44,21,42,19,16,10,29,35,12,45,26,43,22,17,32,47,57,28,25,7,3,50,1,9,5,4,31,30,39,61,60,63,62,38,53,48,54,40,58,13,36,27,20,23,18,33,11,46,56,15,14,24,6,51,2,0,8},
   {54,28,61,14,24,63,6,2,4,0,59,37,36,13,49,48,12,27,26,41,40,45,44,21,20,43,42,23,22,19,35,31,30,34,18,17,16,33,32,11,10,39,38,55,29,15,60,25,7,62,3,5,1,9,58,8,53,52,46,47,56,57,50,51},
   {20,42,60,22,18,62,16,32,10,15,14,28,58,24,52,6,2,4,46,0,57,8,51,45,44,41,40,49,48,35,34,31,30,37,36,13,12,27,26,21,55,39,38,54,43,61,23,19,63,17,33,11,29,59,25,53,7,3,5,47,1,9,56,50},
   {38,54,23,19,61,17,33,63,11,29,15,25,59,7,53,2,4,0,46,8,56,50,51,45,44,41,40,49,48,37,36,35,31,30,34,13,12,27,26,21,20,43,39,55,42,22,18,60,16,32,62,10,28,14,24,58,6,52,3,5,1,47,9,57},
   {38,27,43,19,23,17,33,11,28,63,24,5,10,15,62,7,4,47,53,59,61,2,57,8,0,51,31,30,49,48,35,34,13,12,37,36,21,41,55,54,40,20,45,39,44,26,42,18,22,16,32,29,14,25,6,3,46,52,58,60,9,56,1,50},
   {39,10,28,14,24,6,3,9,1,62,60,46,45,44,21,20,27,37,31,30,35,34,13,12,36,26,43,42,19,49,48,18,23,22,17,16,33,41,55,54,40,32,11,38,29,15,25,7,5,4,2,8,0,63,61,47,58,53,52,59,56,57,50,51},
   {33,11,29,15,63,24,5,62,7,4,47,53,59,61,2,57,1,50,51,31,30,35,34,13,12,37,36,21,20,49,48,45,44,27,26,43,42,41,55,54,40,19,18,39,38,23,22,17,16,32,10,28,14,25,6,3,46,52,58,60,9,56,8,0},
   {14,7,63,22,39,18,16,32,10,28,25,6,62,3,60,47,52,58,8,0,57,50,51,45,37,36,13,12,44,21,20,31,35,49,48,34,30,27,26,41,40,43,42,55,54,23,19,38,17,33,11,29,15,24,5,4,61,2,46,53,59,9,1,56},
   {23,19,39,17,33,11,29,15,25,6,62,7,63,3,61,9,53,59,46,0,57,50,51,45,44,37,36,13,12,21,20,27,35,49,48,34,31,30,26,41,40,43,42,55,54,22,18,38,16,32,10,28,14,24,5,4,2,60,8,52,58,47,1,56},
   {14,39,24,6,4,2,8,0,63,61,27,26,43,42,23,21,20,22,19,18,17,16,45,37,36,13,12,44,33,32,31,49,48,35,34,30,11,10,41,40,29,28,55,54,15,25,38,7,5,3,9,1,62,60,46,47,52,53,58,59,56,57,50,51},
   {52,14,23,61,17,32,10,28,53,62,24,6,2,4,8,58,0,47,57,51,21,20,37,36,45,44,27,26,13,12,43,35,49,48,34,31,30,42,19,41,40,39,55,54,38,18,22,60,16,33,11,29,15,63,25,7,3,5,9,59,1,46,56,50},
   {61,22,16,11,15,14,25,32,29,53,63,24,6,2,4,8,58,46,56,50,51,21,45,37,36,44,20,27,13,12,26,43,49,48,35,31,30,34,42,19,41,40,55,54,39,38,18,23,60,17,33,10,28,52,62,7,3,5,9,1,59,0,47,57},
   {55,38,44,20,26,42,60,23,16,11,28,63,14,18,17,32,29,52,15,24,6,2,4,8,58,0,47,57,51,13,12,35,49,48,34,31,30,37,36,41,40,39,54,45,21,27,43,61,19,22,33,10,53,62,25,7,3,5,9,59,1,46,56,50},
   {16,38,32,10,14,28,24,6,2,4,8,63,0,61,21,20,27,26,43,42,19,18,45,44,23,37,36,22,13,12,35,34,49,48,17,31,55,54,30,41,40,39,33,11,15,29,25,7,3,5,9,1,62,60,52,53,58,59,46,47,56,57,50,51},
   {43,19,23,17,33,11,15,63,25,61,29,28,7,6,2,53,4,58,8,0,47,57,51,45,44,37,36,21,13,12,35,34,49,48,20,31,55,54,30,41,40,39,38,27,26,42,18,22,16,32,10,14,62,24,60,3,5,52,59,9,1,46,56,50},
   {11,14,29,24,60,23,17,33,10,62,25,61,3,5,52,58,9,1,46,56,50,51,45,44,21,37,36,20,13,12,35,34,27,49,48,41,55,54,31,30,40,26,39,38,43,42,19,18,22,16,32,15,63,28,7,6,2,53,59,4,8,0,47,57},
   {40,42,39,62,22,18,16,11,29,15,24,3,25,6,60,1,52,5,9,58,46,56,50,51,37,36,45,13,12,44,21,35,34,49,48,20,31,30,27,26,41,55,54,43,23,63,38,19,17,33,32,10,28,14,7,61,2,53,0,4,59,8,47,57},
   {2,0,4,8,61,43,42,23,22,27,26,19,18,17,16,33,21,20,32,11,10,29,45,37,36,44,13,12,28,15,14,35,49,48,34,31,30,25,24,41,40,55,54,7,6,63,62,39,38,3,1,5,9,60,52,53,58,59,46,47,56,57,50,51},
   {54,26,42,62,38,22,18,16,32,10,28,25,61,15,24,60,3,53,0,4,58,8,47,57,51,37,13,12,36,45,44,35,49,48,34,31,30,21,20,41,40,55,27,43,63,39,23,19,17,33,11,29,14,7,6,2,52,1,5,59,9,46,56,50},
   {32,10,28,14,24,6,62,61,52,58,9,3,46,1,56,50,51,21,20,27,26,43,42,37,36,13,35,34,12,45,44,23,49,48,22,19,31,30,55,54,41,40,18,17,16,39,38,33,11,29,15,25,7,5,63,4,53,59,60,8,47,2,0,57},
   {18,38,16,32,10,28,14,24,6,63,4,53,59,60,8,47,2,56,50,51,21,20,37,36,45,13,35,34,12,44,27,26,49,48,43,42,31,30,55,54,41,40,23,22,19,39,17,33,11,29,15,25,7,5,62,61,52,58,9,3,46,1,0,57},
   {28,39,14,24,6,4,8,2,0,63,61,27,26,43,42,23,21,20,22,19,18,17,37,36,45,13,35,34,12,44,16,33,49,48,32,31,30,11,55,41,40,54,10,29,15,38,25,7,5,9,3,1,62,60,52,53,58,59,46,47,56,57,50,51}},
  {{0,0,0,0,0,0,0,0},{3,3,1,2,3,3,1,1},{1,2,3,3,2,2,2,2},{4,4,4,4,4,4,4,4},
   {2,1,2,1,1,1,3,3},{8,8,8,8,8,8,8,8},{2,5,6,7,8,8,8,8},{6,6,6,6,6,6,6,6},
   {10,10,10,10,10,10,10,10},{12,12,12,12,12,11,11,11},{1,2,4,4,5,5,5,5},{11,11,11,11,11,2,2,2},
   {5,5,5,5,5,5,5,5},{14,14,3,3,4,4,3,3},{7,7,7,7,7,7,7,7},{9,9,9,9,6,6,11,2},
   {9,9,9,9,9,9,9,9},{7,7,7,8,9,9,9,9},{5,1,2,1,7,7,7,6},{10,3,13,13,4,4,3,4},
   {8,8,10,6,12,11,2,11},{13,13,13,13,2,1,4,4},{4,4,5,5,1,3,1,7},{5,4,6,7,10,10,10,2},
   {6,6,8,10,10,10,10,10},{9,9,10,12,4,4,3,4},{11,12,4,11,7,7,8,5},{3,10,1,12,2,1,4,3},
   {7,5,8,10,2,1,4,3},{1,2,2,1,8,8,7,10},{14,14,12,4,1,2,6,9},{13,13,3,3,5,5,5,1}},
  {{255,255,255,255,255,255,255,255},{255,255,255,255,255,255,255,255},{255,255,255,255,255,255,255,255},{255,255,255,255,255,255,255,255},
   {255,255,255,255,255,255,255,255},{255,255,255,255,255,255,255,255},{4,12,7,14,5,5,5,5},{255,255,255,255,255,255,255,255},
   {255,255,255,255,255,255,255,255},{255,255,255,255,255,255,255,255},{2,2,3,3,12,12,12,12},{255,255,255,255,255,2,2,2},
   {255,255,255,255,255,255,255,255},{255,255,2,2,3,3,4,4},{255,255,255,255,255,255,255,255},{16,16,16,16,7,7,9,11},
   {255,255,255,255,255,255,255,255},{14,14,14,5,16,16,16,16},{12,4,4,4,14,14,14,7},{8,1,21,21,13,13,13,21},
   {5,5,8,7,9,9,11,9},{255,255,255,255,2,4,3,3},{3,3,12,12,4,1,1,14},{18,22,6,6,24,24,24,15},
   {7,7,5,8,8,8,8,8},{15,15,20,27,19,19,19,19},{11,9,10,11,18,18,6,10},{1,8,1,9,21,21,21,13},
   {17,6,24,24,27,27,27,27},{10,10,18,18,6,6,18,24},{13,13,9,10,22,11,7,17},{21,21,13,13,10,10,10,1}},
  {112,113,114,115,116,117,118,119,120,121,122,123,124,125,126,127,128,129,130,131,132,133,134,135,136,137,138,139,140,141,142,143,144,145,146,147,148,149,150,151,152,153,154,155,156,157,158,159,15,370,9,47,51,165,45,13,168,169,170,171,172,173,174,175,1,629,373,179,180,181,375,183,39,8,6,42,72,189,190,631,77,75,387,195,196,43,198,78,40,36,7,44,4,205,3,0,208,209,210,211,212,213,214,215,216,626,73,628,627,41,80,37,224,225,226,227,228,229,230,231,24,233,52,368,236,48,88,85,240,630,374,243,244,245,246,247,86,249,53,624,369,253,83,16,17,11,10,49,50,396,14,263,25,20,18,56,57,269,54,22,272,81,274,275,276,89,278,279,79,76,74,652,371,5,38,2,288,82,643,291,292,372,294,295,29,297,460,299,33,301,27,303,87,12,306,307,308,46,310,84,67,65,64,68,69,317,66,30,320,423,431,34,324,58,326,92,328,21,19,59,60,625,23,335,31,679,687,35,63,341,32,28,344,345,61,347,348,97,350,351,94,90,716,355,356,357,98,95,96,91,62,363,364,55,93,26},
  {511,511,511,511,511,511,511,511,511,511,511,511,511,511,511,511,511,511,511,511,511,511,511,511,511,511,511,511,511,511,511,511,511,511,511,511,511,511,511,511,511,511,511,511,511,511,511,511,257,2,257,257,257,511,257,257,511,511,511,511,511,511,511,511,256,5,5,511,511,511,7,511,256,256,256,256,256,511,511,7,256,256,11,511,511,256,511,256,256,256,256,256,256,511,256,256,511,511,511,511,511,511,511,511,511,2,256,4,3,256,256,256,511,511,511,511,511,511,511,511,258,511,257,0,511,257,257,257,511,6,6,511,511,511,511,511,257,511,257,0,1,511,257,257,257,257,257,257,257,12,257,511,258,258,258,258,258,511,258,258,511,257,511,511,511,257,511,511,256,256,256,12,3,256,256,256,511,257,11,511,511,4,511,511,259,511,92,511,259,511,259,511,257,257,511,511,511,257,511,257,259,259,259,259,259,511,259,259,511,151,183,259,511,258,511,258,511,258,258,258,258,1,258,511,259,151,183,259,259,511,259,259,511,511,258,511,511,258,511,511,258,258,92,511,511,511,258,258,258,258,258,511,511,258,258,258}};

typedef CUresult (*EncodeFn)(CUtensorMap*, CUtensorMapDataType, cuuint32_t, void*, const cuuint64_t*, const cuuint64_t*, const cuuint32_t*,
                             const cuuint32_t*, CUtensorMapInterleave, CUtensorMapSwizzle, CUtensorMapL2promotion, CUtensorMapFloatOOBfill);

void make_map2(EncodeFn enc, CUtensorMap* m, const void* ptr, int rows, int cols, int box_rows) {
  cuuint64_t dim[2] = {(cuuint64_t)cols, (cuuint64_t)rows}, str[1] = {(cuuint64_t)cols * 2};
  cuuint32_t box[2] = {64, (cuuint32_t)box_rows}, es[2] = {1, 1};
  enc(m, CU_TENSOR_MAP_DATA_TYPE_BFLOAT16, 2, const_cast<void*>(ptr), dim, str, box, es, CU_TENSOR_MAP_INTERLEAVE_NONE, CU_TENSOR_MAP_SWIZZLE_128B,
      CU_TENSOR_MAP_L2_PROMOTION_L2_128B, CU_TENSOR_MAP_FLOAT_OOB_FILL_NONE);
}
void make_map3(EncodeFn enc, CUtensorMap* m, const void* ptr, int rows) {
  cuuint64_t dim[3] = {64, (cuuint64_t)rows, 9}, str[2] = {DM * 2, 128};
  cuuint32_t box[3] = {64, 32, 3}, es[3] = {1, 1, 1};
  enc(m, CU_TENSOR_MAP_DATA_TYPE_BFLOAT16, 3, const_cast<void*>(ptr), dim, str, box, es, CU_TENSOR_MAP_INTERLEAVE_NONE, CU_TENSOR_MAP_SWIZZLE_128B,
      CU_TENSOR_MAP_L2_PROMOTION_L2_128B, CU_TENSOR_MAP_FLOAT_OOB_FILL_NONE);
}

void make_map_t(EncodeFn enc, CUtensorMap* m, void* ptr, int width, int cols) {
  cuuint64_t dim[3] = {SEQ / 2, 2, 864}, str[2] = {SEQ * 2, SEQ * 4};
  cuuint32_t box[3] = {(cuuint32_t)width, 2, (cuuint32_t)cols}, es[3] = {1, 1, 1};
  enc(m, CU_TENSOR_MAP_DATA_TYPE_UINT32, 3, ptr, dim, str, box, es, CU_TENSOR_MAP_INTERLEAVE_NONE, cols == 64 ? CU_TENSOR_MAP_SWIZZLE_128B : CU_TENSOR_MAP_SWIZZLE_NONE,
      CU_TENSOR_MAP_L2_PROMOTION_NONE, CU_TENSOR_MAP_FLOAT_OOB_FILL_NONE);
}

int g_mode = -1;

}

extern "C" void kernel_launch(void* const* d_in, const int* in_sizes, int n_in, void* d_out, int out_size) {
  static EncodeFn enc = nullptr;
  static void* t_ptr = nullptr;
  if (!enc) {
    void* fn = nullptr;
    cudaDriverEntryPointQueryResult st;
    cudaGetDriverEntryPoint("cuTensorMapEncodeTiled", &fn, cudaEnableDefault, &st);
    enc = (EncodeFn)fn;
    cudaGetSymbolAddress(&t_ptr, g_S);
    cudaFuncSetAttribute(fused_kernel, cudaFuncAttributeMaxDynamicSharedMemorySize, SMEM_BYTES);
    if (g_mode < 0) {
      cudaLaunchConfig_t cfg = {};
      cfg.gridDim = dim3(2 * NCL); cfg.blockDim = dim3(384); cfg.dynamicSmemBytes = SMEM_BYTES;
      cudaLaunchAttribute at; at.id = cudaLaunchAttributeClusterDimension;
      at.val.clusterDim.x = 2; at.val.clusterDim.y = 1; at.val.clusterDim.z = 1;
      cfg.attrs = &at; cfg.numAttrs = 1;
      int nc = 0;
      g_mode = (cudaOccupancyMaxActiveClusters(&nc, fused_kernel, &cfg) == cudaSuccess && nc >= NCL) ? 1 : 0;
      (void)cudaGetLastError();
    }
  }
  Params p;
  make_map2(enc, &p.map_a[0], d_in[4], SEQ, DC, 128);
  make_map2(enc, &p.map_a[1], d_in[0], SEQ, DM, 128);
  make_map2(enc, &p.map_w[0], d_in[6], DC, 4096, 64);
  make_map2(enc, &p.map_w[1], d_in[7], DC, 4096, 64);
  make_map2(enc, &p.map_w[2], d_in[5], DM, 4096, 64);
  make_map2(enc, &p.map_w[3], d_in[1], DM, 1728, 64);
  make_map3(enc, &p.map_o[0], d_in[8], 4096);
  make_map3(enc, &p.map_o[1], d_in[2], DM);
  make_map_t(enc, &p.map_t[0], t_ptr, 32, 9);
  make_map_t(enc, &p.map_t[1], t_ptr, 40, 9);
  make_map_t(enc, &p.map_t[2], t_ptr, 32, 64);
  p.x = (const __nv_bfloat16*)d_in[0];
  p.gate_w = (const __nv_bfloat16*)d_in[9];
  make_map2(enc, &p.map_out, d_out, SEQ, DM, 64);
  p.out = (__nv_bfloat16*)d_out;
  p.zero = 0;
  auto launch = [&](int phases) {
    p.s = k_sched;
    for (int i = 0; i < NCL; i++) {
      Rec& r = p.s.r[i];
      if (!(phases & 1)) r.n1 = 0;
      if (!(phases & 2)) r.n2 = 0;
      if (!(phases & (p.s.task[i][1] == 64 ? 4 : 32))) r.p3 = 255;
      if (!(phases & 8)) r.bg = 255;
      const int u1 = r.n1 ? 8 + r.n1 * (8 + (r.slab >> 3)) : 0;
      int u2 = 0;
      for (int k = 0; k < r.n2; k++) u2 += 4 * (r.item[k] & 7) + 4;
      r.u1 = (uint8_t)u1; r.u2 = (uint8_t)u2;
      r.rot = (uint8_t)(((u1 % 10 + 1) >> 1) % 5);
      r.x3 = (uint8_t)((r.rot + u2) % 5 & 3);
      r.phases = (uint8_t)phases;
    }
    if (!(phases & 16))
      for (int i = 0; i < 256; i++) { p.s.slot[i >> 3][i & 7] = (uint8_t)(i >> 3); p.s.prev[i >> 3][i & 7] = 255; p.s.qblk[i] = (uint16_t)(S_Q + i); p.s.qdep[i] = 511; }
    fused_kernel<<<2 * NCL, 384, SMEM_BYTES>>>(p);
  };
  if (g_mode == 1) launch(63);
  else { launch(1); launch(10); launch(4); launch(32); }
}
```

```cpp
#include <cuda_runtime.h>
#include <cuda_bf16.h>
#include <cuda.h>
#include <stdint.h>

namespace {

constexpr int SEQ = 2048, DM = 576, DC = 512, NH = 32;
constexpr int NCL = 66;
constexpr uint32_t DESC_HI = 0x40000040u;

constexpr int SM_RING = 0;
constexpr int SM_BUF = 163840;
constexpr int SM_BAR = 229376;
constexpr int B_P1E = 0, B_P2E = 10, B_P3E = 15, B_P2F = 24, B_SF = 32, B_ORD = 36, B_LAD = 40, B_DONE = 41, B_FIN = 48;
constexpr int B_P3F = 56, B_OUT = 61, B_P1F = 64, B_SE = 74, B_QF = 80, B_LA = 84, B_NUM = 88;
constexpr uint64_t B_CNT = 0x11118245000ull;
constexpr int SMEM_BYTES = SM_BAR + B_NUM * 8 + 1024;

constexpr int F_QKVA = 32;
constexpr int F_GATE = 64;
constexpr int F_TS = 68;
constexpr int F_DONE = 65;
constexpr int F_CTX = 96;
constexpr int F_OUT = 96 + 8 * 64;
constexpr int F_KV = F_OUT + 64;
constexpr int F_Q = F_KV + 256;
constexpr int F_RD = F_Q + 256;
constexpr int F_NUM = F_RD + 256;

struct Rec {
  uint8_t slab;
  uint8_t n1, n2;
  uint8_t p3;
  uint8_t bg;
  uint8_t item[11];
  uint8_t last[11];
  uint8_t tile[32];
  uint8_t u1, u2;
  uint8_t rot, x3;
  uint8_t phases;
};
struct Sched {
  Rec r[NCL];
  uint8_t task[NCL][4];
  uint8_t p3_order[24][64];
  uint8_t slot[32][8];
  uint8_t prev[32][8];
  uint16_t qblk[256];
  uint16_t qdep[256];
};

#define SCHED_DECL static const

struct Params {
  CUtensorMap map_a[2];
  CUtensorMap map_w[4];
  CUtensorMap map_o[2];
  CUtensorMap map_t[3];
  CUtensorMap map_out;
  const __nv_bfloat16* x;
  const __nv_bfloat16* gate_w;
  __nv_bfloat16* out;
  int zero;
  alignas(64) Sched s;
};

constexpr int S_T = 0, S_Q = 112, S_K = S_Q + 256, S_V = S_K + 256, S_NUM = S_V + 256;
__device__ __align__(1024) uint8_t g_S[(size_t)S_NUM * 65536];
__device__ __align__(1024) uint8_t g_oA[32 * 576 * 128];
__device__ float g_gate[SEQ];
__device__ int g_flags[F_NUM];
#define PL(i)

__device__ __forceinline__ void mbar_arrive(uint32_t b) { asm volatile("mbarrier.arrive.shared::cta.b64 _, [%0];" ::"r"(b) : "memory"); }
__device__ __forceinline__ void mbar_arrive_cl(uint32_t b, int cnt) {
  asm volatile("mbarrier.arrive.shared::cluster.b64 _, [%0], %1;" ::"r"(b), "r"(cnt) : "memory");
}
__device__ __forceinline__ void mbar_wait(uint32_t b, int par) {
  asm volatile(
      "{\n.reg .pred p;\n.reg .u32 c;\n"
      "mbarrier.try_wait.parity.shared::cta.b64 p, [%0], %1;\n@p bra DN;\nmov.u32 c, 0;\n"
      "LP:\nmbarrier.try_wait.parity.shared::cta.b64 p, [%0], %1;\n@p bra DN;\n"
      "add.u32 c, c, 1;\nsetp.lt.u32 p, c, 4000000;\n@p bra LP;\ntrap;\nDN:\n}" ::"r"(b), "r"(par) : "memory");
}
__device__ __forceinline__ uint32_t mapa(uint32_t a, uint32_t cta) {
  uint32_t r; asm("mapa.shared::cluster.u32 %0, %1, %2;" : "=r"(r) : "r"(a), "r"(cta)); return r;
}
#define ELECT(ins) "{\n.reg .pred e;\nelect.sync _|e, 0xffffffff;\n@e " ins "\n}"
__device__ __forceinline__ void mbar_expect(uint32_t b, int bytes) {
  asm volatile(ELECT("mbarrier.arrive.expect_tx.shared::cta.b64 _, [%0], %1;") ::"r"(b), "r"(bytes) : "memory");
}
__device__ __forceinline__ void mbar_arrive_one(uint32_t b) { asm volatile(ELECT("mbarrier.arrive.shared::cta.b64 _, [%0];") ::"r"(b) : "memory"); }
constexpr uint64_t L2_NORMAL = 0x1000000000000000ull, L2_FIRST = 0x12F0000000000000ull;
__device__ __forceinline__ void bulk_load(uint32_t dst, const void* src, int bytes, uint32_t bar, uint64_t pol = L2_NORMAL) {
  asm volatile(ELECT("cp.async.bulk.shared::cluster.global.mbarrier::complete_tx::bytes.L2::cache_hint [%0], [%1], %2, [%3], %4;") ::"r"(dst), "l"(src), "r"(bytes), "r"(bar), "l"(pol) : "memory");
}
__device__ __forceinline__ void bulk_load_mc(uint32_t dst, const void* src, int bytes, uint32_t bar, uint64_t pol = L2_NORMAL) {
  asm volatile(ELECT("cp.async.bulk.shared::cluster.global.mbarrier::complete_tx::bytes.multicast::cluster.L2::cache_hint [%0], [%1], %2, [%3], %4, %5;") ::"r"(dst), "l"(src), "r"(bytes), "r"(bar), "h"((uint16_t)3), "l"(pol) : "memory");
}
__device__ __forceinline__ void bulk_store(void* dst, uint32_t src, int bytes, uint64_t pol = L2_NORMAL) {
  asm volatile(ELECT("cp.async.bulk.global.shared::cta.bulk_group.L2::cache_hint [%0], [%1], %2, %3;") ::"l"(dst), "r"(src), "r"(bytes), "l"(pol) : "memory");
}
__device__ __forceinline__ void tma2d(uint32_t dst, const CUtensorMap* m, int c0, int c1, uint32_t bar, uint64_t pol = L2_NORMAL) {
  asm volatile(ELECT("cp.async.bulk.tensor.2d.shared::cluster.global.mbarrier::complete_tx::bytes.L2::cache_hint [%0], [%1, {%3, %4}], [%2], %5;") ::"r"(dst), "l"(m), "r"(bar), "r"(c0), "r"(c1), "l"(pol) : "memory");
}
__device__ __forceinline__ void tma2d_mc(uint32_t dst, const CUtensorMap* m, int c0, int c1, uint32_t bar, uint64_t pol = L2_NORMAL) {
  asm volatile(ELECT("cp.async.bulk.tensor.2d.shared::cluster.global.mbarrier::complete_tx::bytes.multicast::cluster.L2::cache_hint [%0], [%1, {%3, %4}], [%2], %5, %6;") ::"r"(dst), "l"(m), "r"(bar), "r"(c0), "r"(c1), "h"((uint16_t)3), "l"(pol) : "memory");
}
__device__ __forceinline__ void tma3d(uint32_t dst, const CUtensorMap* m, int c0, int c1, int c2, uint32_t bar, uint64_t pol = L2_NORMAL) {
  asm volatile(ELECT("cp.async.bulk.tensor.3d.shared::cluster.global.mbarrier::complete_tx::bytes.L2::cache_hint [%0], [%1, {%3, %4, %5}], [%2], %6;") ::"r"(dst), "l"(m), "r"(bar), "r"(c0), "r"(c1), "r"(c2), "l"(pol) : "memory");
}
__device__ __forceinline__ void tma3d_mc(uint32_t dst, const CUtensorMap* m, int c0, int c1, int c2, uint32_t bar, uint64_t pol = L2_NORMAL) {
  asm volatile(ELECT("cp.async.bulk.tensor.3d.shared::cluster.global.mbarrier::complete_tx::bytes.multicast::cluster.L2::cache_hint [%0], [%1, {%3, %4, %5}], [%2], %6, %7;") ::"r"(dst), "l"(m), "r"(bar), "r"(c0), "r"(c1), "r"(c2), "h"((uint16_t)3), "l"(pol) : "memory");
}
__device__ __forceinline__ void tma2d_add(const CUtensorMap* m, uint32_t src, int c0, int c1) {
  asm volatile(ELECT("cp.reduce.async.bulk.tensor.2d.global.shared::cta.add.bulk_group [%0, {%2, %3}], [%1];") ::"l"(m), "r"(src), "r"(c0), "r"(c1) : "memory");
}
__device__ __forceinline__ void tma3d_store(const CUtensorMap* m, uint32_t src, int c0, int c1, int c2, uint64_t pol = L2_NORMAL) {
  asm volatile(ELECT("cp.async.bulk.tensor.3d.global.shared::cta.bulk_group.L2::cache_hint [%0, {%2, %3, %4}], [%1], %5;") ::"l"(m), "r"(src), "r"(c0), "r"(c1), "r"(c2), "l"(pol) : "memory");
}
__device__ __forceinline__ void tma2d_prefetch(const CUtensorMap* m, int c0, int c1, uint64_t pol = L2_NORMAL) {
  asm volatile(ELECT("cp.async.bulk.prefetch.tensor.2d.L2.global.L2::cache_hint [%0, {%1, %2}], %3;") ::"l"(m), "r"(c0), "r"(c1), "l"(pol) : "memory");
}
#define LAG 3
#define HINT 62
#define POL(bit) ((HINT >> (bit)) & 1 ? L2_FIRST : L2_NORMAL)
#define BULK_COMMIT() asm volatile("cp.async.bulk.commit_group;" ::: "memory")
#define BULK_WAIT(n) asm volatile("cp.async.bulk.wait_group %0;" ::"n"(n) : "memory")
#define BULK_WAIT_READ(n) asm volatile("cp.async.bulk.wait_group.read %0;" ::"n"(n) : "memory")
#define FENCE_ASYNC_SMEM() asm volatile("fence.proxy.async.shared::cta;" ::: "memory")
#define FENCE_ASYNC_ALL() asm volatile("fence.proxy.async;" ::: "memory")
#define WG_FENCE() asm volatile("wgmma.fence.sync.aligned;" ::: "memory")
#define WG_COMMIT() asm volatile("wgmma.commit_group.sync.aligned;" ::: "memory")
#define WG_WAIT(n) asm volatile("wgmma.wait_group.sync.aligned %0;" ::"n"(n) : "memory")
__device__ __forceinline__ void bar_sync(int id, int n) { asm volatile("bar.sync %0, %1;" ::"r"(id), "r"(n) : "memory"); }
__device__ __forceinline__ void bar_arrive(int id, int n) { asm volatile("bar.arrive %0, %1;" ::"r"(id), "r"(n) : "memory"); }
__device__ __forceinline__ void cluster_sync() {
  asm volatile("barrier.cluster.arrive.relaxed;\nbarrier.cluster.wait.acquire;" ::: "memory");
}
template <int N> __device__ __forceinline__ void pin(float (&r)[N]) {
#pragma unroll
  for (int i = 0; i < N; i++) asm volatile("" : "+f"(r[i])::"memory");
}
template <int N> __device__ __forceinline__ void pin(uint32_t (&r)[N]) {
#pragma unroll
  for (int i = 0; i < N; i++) asm volatile("" : "+r"(r[i])::"memory");
}
__device__ __forceinline__ uint32_t pack_bf16(float lo, float hi) {
  uint32_t r; asm("cvt.rn.bf16x2.f32 %0, %1, %2;" : "=r"(r) : "f"(hi), "f"(lo)); return r;
}
__device__ __forceinline__ float ex2(float x) { float r; asm("ex2.approx.ftz.f32 %0, %1;" : "=f"(r) : "f"(x)); return r; }
__device__ __forceinline__ void ldsm4(uint32_t a, uint32_t& r0, uint32_t& r1, uint32_t& r2, uint32_t& r3) {
  asm volatile("ldmatrix.sync.aligned.m8n8.x4.shared.b16 {%0,%1,%2,%3}, [%4];" : "=r"(r0), "=r"(r1), "=r"(r2), "=r"(r3) : "r"(a) : "memory");
}
__device__ __forceinline__ void stsm4(uint32_t a, uint32_t r0, uint32_t r1, uint32_t r2, uint32_t r3) {
  asm volatile("stmatrix.sync.aligned.m8n8.x4.shared.b16 [%0], {%1,%2,%3,%4};" ::"r"(a), "r"(r0), "r"(r1), "r"(r2), "r"(r3) : "memory");
}
__device__ __forceinline__ void flag_add(int idx, int v = 1) {
  asm volatile(ELECT("red.release.gpu.global.add.s32 [%0], %1;") ::"l"(g_flags + idx), "r"(v) : "memory");
}
__device__ __forceinline__ void flag_add_rx(int idx) {
  asm volatile(ELECT("red.relaxed.gpu.global.add.s32 [%0], 1;") ::"l"(g_flags + idx) : "memory");
}
template <bool ACQ, int NS = 32> __device__ __forceinline__ void flag_wait(int idx, int target) {
  int n = 0;
  while (true) {
    int v;
    if (ACQ) asm volatile("ld.acquire.gpu.global.s32 %0, [%1];" : "=r"(v) : "l"(g_flags + idx) : "memory");
    else asm volatile("ld.relaxed.gpu.global.s32 %0, [%1];" : "=r"(v) : "l"(g_flags + idx) : "memory");
    if (__all_sync(0xffffffffu, v >= target)) break;
    if (++n > 20000000) __trap();
    __nanosleep(NS);
  }
}
__device__ __forceinline__ int flag_peek(int idx) {
  int v;
  asm volatile("ld.relaxed.gpu.global.s32 %0, [%1];" : "=r"(v) : "l"(g_flags + idx) : "memory");
  return v;
}
__device__ __forceinline__ void mask_wait(uint32_t& ready, int bit, int idx, int target) {
  for (int n = 0; !((ready >> bit) & 1); n++) {
    int v;
    if (n) { __nanosleep(32); if (n > 20000000) __trap(); }
    asm volatile("ld.relaxed.gpu.global.s32 %0, [%1];" : "=r"(v) : "l"(g_flags + idx) : "memory");
    ready = __ballot_sync(0xffffffffu, v >= target);
  }
}
__device__ __forceinline__ uint32_t desc_lo(uint32_t addr, uint32_t lbo) { return ((addr & 0x3FFFFu) >> 4) | ((lbo >> 4) << 16); }
#define PROF(role, i)
#define PROFX(cond, i)
#define PROFB(i)
#define PROFG(i)

template <int TB, int TA = 0> __device__ __forceinline__ void wgmma_ss64(float (&d)[32], uint32_t alo, uint32_t blo, int sd) {
  asm volatile("{\n.reg .pred p;\n.reg .b64 da, db;\n"
    "setp.ne.b32 p, %34, 0;\nmov.b64 da, {%32, %36};\nmov.b64 db, {%33, %36};\n"
    "wgmma.mma_async.sync.aligned.m64n64k16.f32.bf16.bf16 "
    "{%0,%1,%2,%3,%4,%5,%6,%7,%8,%9,%10,%11,%12,%13,%14,%15,%16,%17,%18,%19,%20,%21,%22,%23,"
    "%24,%25,%26,%27,%28,%29,%30,%31}, "
    "da, db, p, 1, 1, %37, %35;\n}\n"
    : "+f"(d[0]),"+f"(d[1]),"+f"(d[2]),"+f"(d[3]),"+f"(d[4]),"+f"(d[5]),"+f"(d[6]),"+f"(d[7]),"+f"(d[8]),"+f"(d[9]),"+f"(d[10]),"+f"(d[11]),
      "+f"(d[12]),"+f"(d[13]),"+f"(d[14]),"+f"(d[15]),"+f"(d[16]),"+f"(d[17]),"+f"(d[18]),"+f"(d[19]),"+f"(d[20]),"+f"(d[21]),"+f"(d[22]),"+f"(d[23]),
      "+f"(d[24]),"+f"(d[25]),"+f"(d[26]),"+f"(d[27]),"+f"(d[28]),"+f"(d[29]),"+f"(d[30]),"+f"(d[31])
    : "r"(alo), "r"(blo), "r"(sd), "n"(TB), "r"(DESC_HI), "n"(TA));
}
template <int TB, int TA = 0> __device__ __forceinline__ void wgmma_ss128(float (&d)[64], uint32_t alo, uint32_t blo, int sd) {
  asm volatile("{\n.reg .pred p;\n.reg .b64 da, db;\n"
    "setp.ne.b32 p, %66, 0;\nmov.b64 da, {%64, %68};\nmov.b64 db, {%65, %68};\n"
    "wgmma.mma_async.sync.aligned.m64n128k16.f32.bf16.bf16 "
    "{%0,%1,%2,%3,%4,%5,%6,%7,%8,%9,%10,%11,%12,%13,%14,%15,%16,%17,%18,%19,%20,%21,%22,%23,"
    "%24,%25,%26,%27,%28,%29,%30,%31,%32,%33,%34,%35,%36,%37,%38,%39,%40,%41,%42,%43,%44,%45,%46,%47,"
    "%48,%49,%50,%51,%52,%53,%54,%55,%56,%57,%58,%59,%60,%61,%62,%63}, "
    "da, db, p, 1, 1, %69, %67;\n}\n"
    : "+f"(d[0]),"+f"(d[1]),"+f"(d[2]),"+f"(d[3]),"+f"(d[4]),"+f"(d[5]),"+f"(d[6]),"+f"(d[7]),"+f"(d[8]),"+f"(d[9]),"+f"(d[10]),"+f"(d[11]),
      "+f"(d[12]),"+f"(d[13]),"+f"(d[14]),"+f"(d[15]),"+f"(d[16]),"+f"(d[17]),"+f"(d[18]),"+f"(d[19]),"+f"(d[20]),"+f"(d[21]),"+f"(d[22]),"+f"(d[23]),
      "+f"(d[24]),"+f"(d[25]),"+f"(d[26]),"+f"(d[27]),"+f"(d[28]),"+f"(d[29]),"+f"(d[30]),"+f"(d[31]),"+f"(d[32]),"+f"(d[33]),"+f"(d[34]),"+f"(d[35]),
      "+f"(d[36]),"+f"(d[37]),"+f"(d[38]),"+f"(d[39]),"+f"(d[40]),"+f"(d[41]),"+f"(d[42]),"+f"(d[43]),"+f"(d[44]),"+f"(d[45]),"+f"(d[46]),"+f"(d[47]),
      "+f"(d[48]),"+f"(d[49]),"+f"(d[50]),"+f"(d[51]),"+f"(d[52]),"+f"(d[53]),"+f"(d[54]),"+f"(d[55]),"+f"(d[56]),"+f"(d[57]),"+f"(d[58]),"+f"(d[59]),
      "+f"(d[60]),"+f"(d[61]),"+f"(d[62]),"+f"(d[63])
    : "r"(alo), "r"(blo), "r"(sd), "n"(TB), "r"(DESC_HI), "n"(TA));
}
template <int TB> __device__ __forceinline__ void wgmma_rs128(float (&d)[64], uint32_t a0, uint32_t a1, uint32_t a2, uint32_t a3, uint32_t blo, int sd) {
  asm volatile("{\n.reg .pred p;\n.reg .b64 db;\n"
    "setp.ne.b32 p, %69, 0;\nmov.b64 db, {%68, %71};\n"
    "wgmma.mma_async.sync.aligned.m64n128k16.f32.bf16.bf16 "
    "{%0,%1,%2,%3,%4,%5,%6,%7,%8,%9,%10,%11,%12,%13,%14,%15,%16,%17,%18,%19,%20,%21,%22,%23,"
    "%24,%25,%26,%27,%28,%29,%30,%31,%32,%33,%34,%35,%36,%37,%38,%39,%40,%41,%42,%43,%44,%45,%46,%47,"
    "%48,%49,%50,%51,%52,%53,%54,%55,%56,%57,%58,%59,%60,%61,%62,%63}, "
    "{%64,%65,%66,%67}, db, p, 1, 1, %70;\n}\n"
    : "+f"(d[0]),"+f"(d[1]),"+f"(d[2]),"+f"(d[3]),"+f"(d[4]),"+f"(d[5]),"+f"(d[6]),"+f"(d[7]),"+f"(d[8]),"+f"(d[9]),"+f"(d[10]),"+f"(d[11]),
      "+f"(d[12]),"+f"(d[13]),"+f"(d[14]),"+f"(d[15]),"+f"(d[16]),"+f"(d[17]),"+f"(d[18]),"+f"(d[19]),"+f"(d[20]),"+f"(d[21]),"+f"(d[22]),"+f"(d[23]),
      "+f"(d[24]),"+f"(d[25]),"+f"(d[26]),"+f"(d[27]),"+f"(d[28]),"+f"(d[29]),"+f"(d[30]),"+f"(d[31]),"+f"(d[32]),"+f"(d[33]),"+f"(d[34]),"+f"(d[35]),
      "+f"(d[36]),"+f"(d[37]),"+f"(d[38]),"+f"(d[39]),"+f"(d[40]),"+f"(d[41]),"+f"(d[42]),"+f"(d[43]),"+f"(d[44]),"+f"(d[45]),"+f"(d[46]),"+f"(d[47]),
      "+f"(d[48]),"+f"(d[49]),"+f"(d[50]),"+f"(d[51]),"+f"(d[52]),"+f"(d[53]),"+f"(d[54]),"+f"(d[55]),"+f"(d[56]),"+f"(d[57]),"+f"(d[58]),"+f"(d[59]),
      "+f"(d[60]),"+f"(d[61]),"+f"(d[62]),"+f"(d[63])
    : "r"(a0), "r"(a1), "r"(a2), "r"(a3), "r"(blo), "r"(sd), "n"(TB), "r"(DESC_HI));
}
template <int TB, int TA = 0> __device__ __forceinline__ void wgmma_ss192(float (&d)[96], uint32_t alo, uint32_t blo, int sd) {
  asm volatile("{\n.reg .pred p;\n.reg .b64 da, db;\n"
    "setp.ne.b32 p, %98, 0;\nmov.b64 da, {%96, %100};\nmov.b64 db, {%97, %100};\n"
    "wgmma.mma_async.sync.aligned.m64n192k16.f32.bf16.bf16 "
    "{%0,%1,%2,%3,%4,%5,%6,%7,%8,%9,%10,%11,%12,%13,%14,%15,%16,%17,%18,%19,%20,%21,%22,%23,"
    "%24,%25,%26,%27,%28,%29,%30,%31,%32,%33,%34,%35,%36,%37,%38,%39,%40,%41,%42,%43,%44,%45,%46,%47,"
    "%48,%49,%50,%51,%52,%53,%54,%55,%56,%57,%58,%59,%60,%61,%62,%63,%64,%65,%66,%67,%68,%69,%70,%71,"
    "%72,%73,%74,%75,%76,%77,%78,%79,%80,%81,%82,%83,%84,%85,%86,%87,%88,%89,%90,%91,%92,%93,%94,%95}, "
    "da, db, p, 1, 1, %101, %99;\n}\n"
    : "+f"(d[0]),"+f"(d[1]),"+f"(d[2]),"+f"(d[3]),"+f"(d[4]),"+f"(d[5]),"+f"(d[6]),"+f"(d[7]),"+f"(d[8]),"+f"(d[9]),"+f"(d[10]),"+f"(d[11]),
      "+f"(d[12]),"+f"(d[13]),"+f"(d[14]),"+f"(d[15]),"+f"(d[16]),"+f"(d[17]),"+f"(d[18]),"+f"(d[19]),"+f"(d[20]),"+f"(d[21]),"+f"(d[22]),"+f"(d[23]),
      "+f"(d[24]),"+f"(d[25]),"+f"(d[26]),"+f"(d[27]),"+f"(d[28]),"+f"(d[29]),"+f"(d[30]),"+f"(d[31]),"+f"(d[32]),"+f"(d[33]),"+f"(d[34]),"+f"(d[35]),
      "+f"(d[36]),"+f"(d[37]),"+f"(d[38]),"+f"(d[39]),"+f"(d[40]),"+f"(d[41]),"+f"(d[42]),"+f"(d[43]),"+f"(d[44]),"+f"(d[45]),"+f"(d[46]),"+f"(d[47]),
      "+f"(d[48]),"+f"(d[49]),"+f"(d[50]),"+f"(d[51]),"+f"(d[52]),"+f"(d[53]),"+f"(d[54]),"+f"(d[55]),"+f"(d[56]),"+f"(d[57]),"+f"(d[58]),"+f"(d[59]),
      "+f"(d[60]),"+f"(d[61]),"+f"(d[62]),"+f"(d[63]),"+f"(d[64]),"+f"(d[65]),"+f"(d[66]),"+f"(d[67]),"+f"(d[68]),"+f"(d[69]),"+f"(d[70]),"+f"(d[71]),
      "+f"(d[72]),"+f"(d[73]),"+f"(d[74]),"+f"(d[75]),"+f"(d[76]),"+f"(d[77]),"+f"(d[78]),"+f"(d[79]),"+f"(d[80]),"+f"(d[81]),"+f"(d[82]),"+f"(d[83]),
      "+f"(d[84]),"+f"(d[85]),"+f"(d[86]),"+f"(d[87]),"+f"(d[88]),"+f"(d[89]),"+f"(d[90]),"+f"(d[91]),"+f"(d[92]),"+f"(d[93]),"+f"(d[94]),"+f"(d[95])
    : "r"(alo), "r"(blo), "r"(sd), "n"(TB), "r"(DESC_HI), "n"(TA));
}

struct Ctx {
  uint32_t sm;
  uint32_t bar;
  uint32_t rbar;
  int cl, rank, wg, warp, lane, phases;
};
__device__ __forceinline__ void release(const Ctx& c, int b, int cnt = 1) {
  if (c.lane < 2) mbar_arrive_cl(c.rbar + b * 8, cnt);
}
#define HK 5
#define NPRO 6
#define ZLEAD 14
#define PFM 7
#define PF1 1
constexpr float SM_SCALE = 0.08838834764831845f * 1.4426950408889634f;
constexpr float SM_HI = 1.8446744e19f, SM_LO = 5.4210109e-20f;
constexpr int ORDER = 1;

__device__ __forceinline__ void stage_tile(const float (&a)[64], uint32_t buf, const Ctx& c, float s0, float s1) {
  const int row = (c.lane & 7) + ((c.lane >> 3) & 1) * 8;
  const uint32_t base = buf + (c.warp * 16 + row) * 128 + (((c.lane >> 4) ^ (row & 7)) << 4);
#pragma unroll
  for (int i = 0; i < 8; i++)
    stsm4((base ^ ((i & 3) << 5)) + (i >> 2) * 8192, pack_bf16(a[8 * i] * s0, a[8 * i + 1] * s0), pack_bf16(a[8 * i + 2] * s1, a[8 * i + 3] * s1),
          pack_bf16(a[8 * i + 4] * s0, a[8 * i + 5] * s0), pack_bf16(a[8 * i + 6] * s1, a[8 * i + 7] * s1));
}

__device__ __forceinline__ void p1_epilogue(const Params& p, const Ctx& c, const float (&acc)[64], int t, int type) {
  const int tile = p.s.r[c.cl].tile[t] & 63, b = c.wg * 2 + 1;
  mbar_wait(c.bar + (B_SE + b) * 8, (t & 1) ^ 1);
  if (type && tile >= 32) {
    const int r = 2 * (c.lane & 3) + ((c.lane >> 2) & 1);
    const uint32_t dst = c.sm + SM_BUF + b * 16384 + r * 128 + (((c.warp * 2) ^ r) << 4) + (c.lane >> 3) * 4;
#pragma unroll
    for (int i = 0; i < 16; i++) {
      asm volatile("st.shared.u32 [%0], %1;" ::"r"(dst + i * 1024), "r"(pack_bf16(acc[4 * i], acc[4 * i + 1])) : "memory");
      asm volatile("st.shared.u32 [%0], %1;" ::"r"((dst ^ 16) + i * 1024), "r"(pack_bf16(acc[4 * i + 2], acc[4 * i + 3])) : "memory");
    }
  } else {
    if (type) stage_tile(acc, c.sm + SM_BUF + b * 16384, c, SM_SCALE, SM_SCALE);
    else stage_tile(acc, c.sm + SM_BUF + b * 16384, c, 1.f, 1.f);
  }
  FENCE_ASYNC_SMEM();
  __syncwarp();
  if (c.lane == 0) mbar_arrive(c.bar + (B_SF + b) * 8);
}

__device__ __forceinline__ void p1_consumer(const Params& p, const Ctx& c) {
  const int n = p.s.r[c.cl].n1;
  const int type = p.s.r[c.cl].slab >> 3;
  const uint32_t bdesc = desc_lo(c.sm + SM_RING, 8192), adesc = desc_lo(c.sm + SM_BUF + 32768 + c.wg * 8192, 16);
  uint32_t A[128];
  float acc[64] = {};
  int slot = 0, par = 0;
  auto next = [&]() { if (++slot == 10) { slot = 0; par ^= 1; } };
  {
    const int row = (c.lane & 7) + ((c.lane >> 3) & 1) * 8;
    const uint32_t base = c.sm + SM_RING + (c.wg * 64 + c.warp * 16 + row) * 128 + (((c.lane >> 4) ^ (row & 7)) << 4);
    if (c.wg == 1) bar_sync(ORDER + 1, 256);
    int pa = -1, pb = -1;
    if (type) {
      mbar_wait(c.bar + B_P1F * 8, 0);
      WG_FENCE();
#pragma unroll
      for (int kk = 0; kk < 4; kk++) wgmma_ss128<1>(acc, adesc + kk * 2, bdesc + kk * 128, kk != 0);
      WG_COMMIT();
      pb = 0; slot = 1;
    }
#pragma unroll
    for (int kb = 0; kb < 8; kb++) {
      const int sa = slot;
      mbar_wait(c.bar + (B_P1F + slot) * 8, par);
      if (kb == 0) PROF(c.wg, 5);
      next();
      mbar_wait(c.bar + (B_P1F + slot) * 8, par);
      PROF(c.wg, 6 + 2 * kb);
      WG_FENCE();
#pragma unroll
      for (int kk = 0; kk < 4; kk++)
        wgmma_ss128<1>(acc, desc_lo(c.sm + SM_RING + c.wg * 8192, 16) + sa * 1024 + kk * 2, bdesc + slot * 1024 + kk * 128, (kb | kk) != 0 ? 1 : type);
      WG_COMMIT();
      if (kb == 1 && c.wg == 0) bar_arrive(ORDER + 1, 256);
#pragma unroll
      for (int kk = 0; kk < 4; kk++) ldsm4((base ^ (kk << 5)) + sa * 16384, A[kb * 16 + kk * 4], A[kb * 16 + kk * 4 + 1], A[kb * 16 + kk * 4 + 2], A[kb * 16 + kk * 4 + 3]);
      WG_WAIT(1);
      if (kb > 0) release(c, B_P1E + pa);
      if (kb > 0 || pb >= 0) release(c, B_P1E + pb);
      pa = sa; pb = slot;
      next();
    }
    WG_WAIT(0);
    __syncwarp();
    release(c, B_P1E + pa);
    release(c, B_P1E + pb);
    pin(acc);
    PROF(c.wg, 1);
    p1_epilogue(p, c, acc, 0, type);
    PROF(c.wg, 2);
  }
  for (int t = 1; t < n; t++) {
    bar_sync(ORDER + c.wg, 256);
    int prev1 = -1, prev2 = -1;
    if (type) {
      mbar_wait(c.bar + (B_P1F + slot) * 8, par);
      WG_FENCE();
#pragma unroll
      for (int kk = 0; kk < 4; kk++) wgmma_ss128<1>(acc, adesc + kk * 2, bdesc + slot * 1024 + kk * 128, kk != 0);
      WG_COMMIT();
      prev1 = slot;
      next();
    }
#pragma unroll
    for (int kb = 0; kb < 8; kb++) {
      mbar_wait(c.bar + (B_P1F + slot) * 8, par);
      WG_FENCE();
      const uint32_t d = bdesc + slot * 1024;
#pragma unroll
      for (int kk = 0; kk < 4; kk++)
        wgmma_rs128<1>(acc, A[kb * 16 + kk * 4], A[kb * 16 + kk * 4 + 1], A[kb * 16 + kk * 4 + 2], A[kb * 16 + kk * 4 + 3], d + kk * 128, (kb | kk) != 0 ? 1 : type);
      WG_COMMIT();
      if (kb == HK) {
        if (t + 1 < n || c.wg == 0) bar_arrive(ORDER + (c.wg ^ 1), 256);
      }
      if (kb > 0) { WG_WAIT(2); if (kb > 1 || prev2 >= 0) release(c, B_P1E + prev2); }
      prev2 = prev1; prev1 = slot;
      next();
    }
    WG_WAIT(1);
    release(c, B_P1E + prev2);
    WG_WAIT(0);
    pin(acc);
    release(c, B_P1E + prev1);
    p1_epilogue(p, c, acc, t, type);
    PROF(c.wg, 3);
  }
}

__device__ __forceinline__ void p1_producer(const Params& p, const Ctx& c) {
  const int n = p.s.r[c.cl].n1;
  const int type = p.s.r[c.cl].slab >> 3, grp = p.s.r[c.cl].slab & 7;
  int slot = NPRO % 10, par = NPRO < 10;
#pragma unroll 1
  for (int t = 0; t < n; t++) {
    const int tile = p.s.r[c.cl].tile[t] & 63;
    const CUtensorMap* m = &p.map_w[type * 2 + (tile >> 5)];
    const int n0 = (tile & 31) * 128 + c.rank * 64;
    const int ptile = p.s.r[c.cl].tile[t + PF1 < n ? t + PF1 : t];
    const CUtensorMap* pm = &p.map_w[type * 2 + ((ptile >> 5) & 1)];
    if (t == 7 && (c.phases & 16)) flag_wait<true>(F_GATE, 256);
#pragma unroll 1
    for (int kb = t ? -type : (NPRO - type) >> 1; kb < 8; kb++) {
      if (t == 0 && 2 * kb + type >= NPRO) {
        mbar_wait(c.bar + (B_P1E + slot) * 8, par);
        mbar_expect(c.bar + (B_P1F + slot) * 8, 16384);
        tma2d(c.sm + SM_RING + slot * 16384, &p.map_a[type], kb * 64, grp * 256 + c.rank * 128, c.bar + (B_P1F + slot) * 8);
        if (++slot == 10) { slot = 0; par ^= 1; }
      }
      mbar_wait(c.bar + (B_P1E + slot) * 8, par);
      mbar_expect(c.bar + (B_P1F + slot) * 8, 16384);
      tma2d_mc(c.sm + SM_RING + slot * 16384 + c.rank * 8192, m, n0, kb < 0 ? 512 : kb * 64, c.bar + (B_P1F + slot) * 8);
      if (t == 0 && kb == 1) PROF(2, 61);
      if (t == 0 && kb == 3) PROF(2, 62);
      if (t + PF1 < n && t > 0 && ((ptile & 64) || ((ptile & 128) && ((kb ^ grp) & PFM) == 0))) tma2d_prefetch(pm, (ptile & 31) * 128 + c.rank * 64, kb < 0 ? 512 : kb * 64);
      if (++slot == 10) { slot = 0; par ^= 1; }
    }
  }
}

__device__ __forceinline__ void wait_kv_dead(const Ctx& c, int h, int g) {
  if (g >= 2) flag_wait<false>(F_RD + h * 8 + g, 8 - g);
  else flag_wait<false>(F_CTX + max(c.lane & 7, g) * 64 + h, 4);
}
__device__ __forceinline__ int p1_storer(const Params& p, const Ctx& c) {
  const int n = p.s.r[c.cl].n1;
  const int type = p.s.r[c.cl].slab >> 3, grp = p.s.r[c.cl].slab & 7;
  for (int i = 0; i < 2 * n; i++) {
    const int t = i >> 1, w = i & 1, b = w * 2 + 1;
    const int tile = p.s.r[c.cl].tile[t] & 63;
    mbar_wait(c.bar + (B_SF + b) * 8, t & 1);
    const uint32_t src = c.sm + SM_BUF + b * 16384;
    int f = (type ? F_Q : F_KV) + (tile & 31) * 8 + grp;
    if (type == 0) {
      const int prev = p.s.prev[tile & 31][grp];
      if (prev != 255 && w == 0) wait_kv_dead(c, prev, grp);
      uint8_t* dst = g_S + (size_t)(S_K + ((tile & 32) + p.s.slot[tile & 31][grp]) * 8 + grp) * 65536 + c.rank * 32768 + w * 8192;
      bulk_store(dst, src, 8192);
      bulk_store(dst + 16384, src + 8192, 8192);
    } else if (tile < 32) {
      const int dep = p.s.qdep[tile * 8 + grp];
      if (dep != 511 && w == 0) {
        if (dep < 256) wait_kv_dead(c, dep >> 3, dep & 7);
        else flag_wait<false>(F_TS + dep - 256, 128);
      }
      bulk_store(g_S + (size_t)p.s.qblk[tile * 8 + grp] * 65536 + (c.rank * 2 + w) * 16384, src, 16384);
    } else {
      tma3d_store(&p.map_t[2], src, (grp * 4 + c.rank * 2 + w) * 32, 0, (tile - 32) * 64);
      f = F_QKVA + grp * 4 + ((0xE4390900u >> (2 * (tile - 30))) & 3);
    }
    BULK_COMMIT();
    BULK_WAIT(0);
    mbar_arrive_one(c.bar + (B_SE + b) * 8);
    if (i == 2 * n - 1) return f;
    if (w) flag_add(f, 2);
  }
  return -1;
}

__device__ __forceinline__ int p2_buf(int w, int i) { return w * 2 + (i & 1); }
__device__ __forceinline__ int p2_blk(int rank, int w, int i) { return ((i ^ w) & 1) == 0 ? 3 - rank : rank; }

template <int N>
__device__ __forceinline__ void row_max(const float (&s)[N], float& m0, float& m1) {
  float a0 = fmaxf(s[0], s[1]), a1 = fmaxf(s[2], s[3]);
#pragma unroll
  for (int i = 1; i < N / 4; i++) {
    m0 = fmaxf(m0, s[4 * i]); a0 = fmaxf(a0, s[4 * i + 1]);
    m1 = fmaxf(m1, s[4 * i + 2]); a1 = fmaxf(a1, s[4 * i + 3]);
  }
  m0 = fmaxf(m0, a0); m1 = fmaxf(m1, a1);
  m0 = fmaxf(m0, __shfl_xor_sync(0xffffffffu, m0, 1));
  m1 = fmaxf(m1, __shfl_xor_sync(0xffffffffu, m1, 1));
  m0 = fmaxf(m0, __shfl_xor_sync(0xffffffffu, m0, 2));
  m1 = fmaxf(m1, __shfl_xor_sync(0xffffffffu, m1, 2));
}
template <bool SUB, int N>
__device__ __forceinline__ void row_exp(const float (&s)[N], uint32_t (&P)[32], float m0, float m1, float& t0, float& t1) {
  float u0 = 0.f, u1 = 0.f;
  t0 = t1 = 0.f;
#pragma unroll
  for (int i = 0; i < N / 4; i++) {
    const float e0 = ex2(SUB ? s[4 * i] - m0 : s[4 * i]), e1 = ex2(SUB ? s[4 * i + 1] - m0 : s[4 * i + 1]);
    const float e2 = ex2(SUB ? s[4 * i + 2] - m1 : s[4 * i + 2]), e3 = ex2(SUB ? s[4 * i + 3] - m1 : s[4 * i + 3]);
    if (i == 0) { t0 = e0; u0 = e1; t1 = e2; u1 = e3; }
    else { t0 += e0; u0 += e1; t1 += e2; u1 += e3; }
    P[2 * i] = pack_bf16(e0, e1);
    P[2 * i + 1] = pack_bf16(e2, e3);
  }
#pragma unroll
  for (int i = N / 2; i < 32; i++) P[i] = 0;
  pin(P);
  t0 += u0; t1 += u1;
}
template <int N>
__device__ __forceinline__ void causal_mask(float (&s)[N], int thr) {
#pragma unroll
  for (int i = 0; i < 8; i++) {
    if (8 * i > thr) s[N - 32 + 4 * i] = -INFINITY;
    if (8 * i + 1 > thr) s[N - 32 + 4 * i + 1] = -INFINITY;
    if (8 * i - 8 > thr) s[N - 32 + 4 * i + 2] = -INFINITY;
    if (8 * i - 7 > thr) s[N - 32 + 4 * i + 3] = -INFINITY;
  }
}
__device__ __forceinline__ void issue_qk(float (&s)[32], uint32_t qd, uint32_t kd) {
  WG_FENCE();
#pragma unroll
  for (int kk = 0; kk < 8; kk++) wgmma_ss64<0>(s, qd + (kk >> 2) * 512 + (kk & 3) * 2, kd + (kk >> 2) * 1024 + (kk & 3) * 2, kk != 0);
  WG_COMMIT();
}
__device__ __forceinline__ void issue_qk(float (&s)[64], uint32_t qd, uint32_t kd) {
  WG_FENCE();
#pragma unroll
  for (int kk = 0; kk < 8; kk++) wgmma_ss128<0>(s, qd + (kk >> 2) * 512 + (kk & 3) * 2, kd + (kk >> 2) * 1024 + (kk & 3) * 2, kk != 0);
  WG_COMMIT();
}
template <int NK>
__device__ __forceinline__ void issue_pv(float (&o)[64], const uint32_t (&P)[32], uint32_t vd, int acc) {
  WG_FENCE();
#pragma unroll
  for (int kk = 0; kk < NK; kk++) wgmma_rs128<1>(o, P[4 * kk], P[4 * kk + 1], P[4 * kk + 2], P[4 * kk + 3], vd + kk * 128, kk != 0 ? 1 : acc);
  WG_COMMIT();
}
__device__ __forceinline__ void stage_done(const Ctx& c, int b) {
  FENCE_ASYNC_SMEM();
  __syncwarp();
  if (c.lane == 0) mbar_arrive(c.bar + (B_SF + b) * 8);
}
__device__ __forceinline__ void p2_epilogue(const float (&o)[64], float s0, float s1, const Ctx& c, int b) {
  stage_tile(o, c.sm + SM_BUF + b * 16384, c, s0, s1);
  stage_done(c, b);
}

struct P2State {
  float m0, m1, l0, l1;
  bool shift;
  float e0, e1;
  int ks;
  int wi, ai;
  uint32_t wb, ab;
  uint32_t qd;
};
#define PROFZ()
__device__ __forceinline__ int wrap5(int q) { return q >= 5 ? q - 5 : q; }
__device__ __forceinline__ void turn_wait(uint32_t ring, int i) { mbar_wait(ring + (i & 3) * 8, (i >> 2) & 1); }
__device__ __forceinline__ void turn_pass(const Ctx& c, uint32_t ring, int i) { if (c.lane == 0) mbar_arrive(ring + (i & 3) * 8); }
__device__ __forceinline__ void p2_scales(P2State& z) {
  float l0 = z.l0, l1 = z.l1;
  l0 += __shfl_xor_sync(0xffffffffu, l0, 1);
  l1 += __shfl_xor_sync(0xffffffffu, l1, 1);
  l0 += __shfl_xor_sync(0xffffffffu, l0, 2);
  l1 += __shfl_xor_sync(0xffffffffu, l1, 2);
  asm("rcp.approx.ftz.f32 %0, %1;" : "=f"(z.e0) : "f"(l0));
  asm("rcp.approx.ftz.f32 %0, %1;" : "=f"(z.e1) : "f"(l1));
}
template <int N>
__device__ __forceinline__ void p2_first(const Ctx& c, P2State& z, float (&o)[64], uint32_t (&Pc)[32], uint32_t (&Pn)[32],
                                         int ks, int vs, int cnt, int acc) {
  float s[N] = {};
  issue_qk(s, z.qd, desc_lo(c.sm + SM_RING, 16) + ks * 2048);
  if (vs >= 0) {
    p2_scales(z);
    issue_pv<8>(o, Pc, desc_lo(c.sm + SM_RING, 16384) + vs * 2048, acc);
  } else {
    WG_COMMIT();
  }
  mbar_expect(z.ab + (z.ai++ & 3) * 8, cnt == 1 ? 8192 : 0);
  PROFZ();
  WG_WAIT(1);
  PROFZ();
  pin(s);
  release(c, B_P2E + ks, cnt);
  causal_mask(s, c.warp * 16 + (c.lane >> 2) - 2 * (c.lane & 3));
  z.m0 = z.m1 = 0.f;
  row_exp<false>(s, Pn, 0.f, 0.f, z.l0, z.l1);
  z.shift = __any_sync(0xffffffffu, !(z.l0 + z.l1 <= SM_HI) || ((c.lane & 3) == 0 && !(fminf(z.l0, z.l1) >= SM_LO)));
  if (__builtin_expect(z.shift, 0)) {
    z.m0 = z.m1 = -INFINITY;
    row_max(s, z.m0, z.m1);
    row_exp<true>(s, Pn, z.m0, z.m1, z.l0, z.l1);
  }
  WG_WAIT(0);
  pin(o);
  if (vs >= 0) release(c, B_P2E + vs, 1);
}

template <bool SECOND>
__device__ __forceinline__ void p2_turn(const Ctx& c, P2State& z, float (&o)[64], uint32_t (&Pc)[32], uint32_t (&Pn)[32],
                                        int eb = -1, bool half = false, int vcnt = 1) {
  float s[64] = {};
  const int ks = z.ks, vs = wrap5(ks + 1);
  PROFZ();
  turn_wait(z.wb, z.wi++);
  PROFZ();
  issue_qk(s, z.qd, desc_lo(c.sm + SM_RING, 16) + ks * 2048);
  const uint32_t vd = desc_lo(c.sm + SM_RING, 16384) + vs * 2048;
  if (SECOND) {
    if (eb >= 0) stage_tile(o, c.sm + SM_BUF + eb * 16384, c, z.e0, z.e1);
    if (half) issue_pv<4>(o, Pc, vd, 0); else issue_pv<8>(o, Pc, vd, 0);
  } else {
    issue_pv<8>(o, Pc, vd, 1);
  }
  turn_pass(c, z.ab, z.ai++);
  if (SECOND) { if (eb >= 0) stage_done(c, eb); }
  PROFZ();
  z.ks = wrap5(ks + 2);
  WG_WAIT(1);
  PROFZ();
  pin(s);
  release(c, B_P2E + ks, 1);
  float t0, t1, a0 = 1.f, a1 = 1.f;
  row_exp<false>(s, Pn, 0.f, 0.f, t0, t1);
  z.shift = __any_sync(0xffffffffu, z.shift || !(t0 + t1 <= SM_HI));
  const bool redo = z.shift;
  if (__builtin_expect(redo, 0)) {
    float n0 = z.m0, n1 = z.m1;
    row_max(s, n0, n1);
    a0 = ex2(z.m0 - n0); a1 = ex2(z.m1 - n1);
    z.m0 = n0; z.m1 = n1;
    z.l0 *= a0; z.l1 *= a1;
    row_exp<true>(s, Pn, z.m0, z.m1, t0, t1);
  }
  WG_WAIT(0);
  pin(o);
  release(c, B_P2E + vs, vcnt);
  if (__builtin_expect(redo, 0)) {
#pragma unroll
    for (int i = 0; i < 16; i++) { o[4 * i] *= a0; o[4 * i + 1] *= a0; o[4 * i + 2] *= a1; o[4 * i + 3] *= a1; }
  }
  z.l0 += t0; z.l1 += t1;
}
__device__ __forceinline__ void copy_p(uint32_t (&d)[32], const uint32_t (&s)[32], int zero) {
#pragma unroll
  for (int i = 0; i < 32; i++) asm volatile("add.s32 %0, %1, %2;" : "=r"(d[i]) : "r"(s[i]), "r"(zero));
}

__device__ __forceinline__ void p2_consumer(const Params& p, const Ctx& c, int rot) {
  const int nit = p.s.r[c.cl].n2;
  const uint32_t fring = c.bar + B_P2F * 8, oring = c.bar + B_ORD * 8;
  float o[64] = {};
  uint32_t Pa[32] = {}, Pb[32] = {};
  P2State z;
  z.e0 = z.e1 = z.l0 = z.l1 = 0.f; z.ks = rot; z.shift = false;
  int acc = 0, n = 0;
  for (int it = 0; it < nit; it++) {
    const int j = p.s.r[c.cl].item[it] & 7, blk = p2_blk(c.rank, c.wg, it);
    const int lng = ((it ^ c.wg) & 1) ^ 1;
    z.qd = desc_lo(c.sm + SM_BUF, 16) + p2_buf(c.wg, it) * 1024;
    if (lng) { z.wb = oring; z.wi = n - it; z.ab = fring; z.ai = n + 1; }
    else { z.wb = fring; z.wi = n + 2; z.ab = oring; z.ai = n - it; }
    PROFZ();
    mbar_wait(c.bar + (B_QF + p2_buf(c.wg, it)) * 8, (it >> 1) & 1);
    turn_wait(fring, n + 1 - lng);
    PROFZ();
    const int vs = it ? wrap5(z.ks + 1) : -1, ks = lng ? z.ks : wrap5(z.ks + (it ? 2 : 1));
    if (blk & 1) p2_first<64>(c, z, o, Pa, Pb, ks, vs, 1 + lng, acc);
    else p2_first<32>(c, z, o, Pa, Pb, ks, vs, 1 + lng, acc);
    z.ks = wrap5(ks + (it == 0 && lng ? 1 : 2));
    PROF(c.wg, 24 + it);
    n += 2 * j + 2;
    int left = 2 * j + lng;
    acc = left != 0;
    if (left == 0) { copy_p(Pa, Pb, p.zero); continue; }
    p2_turn<true>(c, z, o, Pb, Pa, it > 0 ? p2_buf(c.wg, it - 1) : -1, !(blk & 1), 1 + lng);
    while (--left > 0) {
      p2_turn<false>(c, z, o, Pa, Pb);
      if (--left == 0) { copy_p(Pa, Pb, p.zero); break; }
      p2_turn<false>(c, z, o, Pb, Pa);
    }
  }
  {
    if (!acc && nit > 1) p2_epilogue(o, z.e0, z.e1, c, p2_buf(c.wg, nit));
    turn_wait(z.wb, z.wi);
    issue_pv<8>(o, Pa, desc_lo(c.sm + SM_RING, 16384) + z.ks * 2048, acc);
    if (((nit - 1) ^ c.wg) & 1) turn_pass(c, z.ab, z.ai);
    p2_scales(z);
    WG_WAIT(0);
    pin(o);
    release(c, B_P2E + z.ks);
    p2_epilogue(o, z.e0, z.e1, c, p2_buf(c.wg, nit - 1));
    PROF(c.wg, 24 + nit);
  }
}

__device__ __forceinline__ void p2_load_q(const Params& p, const Ctx& c, int it, int w) {
  const int item = p.s.r[c.cl].item[it], b = p2_buf(w, it);
  mbar_expect(c.bar + (B_QF + b) * 8, 16384);
  bulk_load(c.sm + SM_BUF + b * 16384, g_S + (size_t)p.s.qblk[item] * 65536 + p2_blk(c.rank, w, it) * 16384, 16384, c.bar + (B_QF + b) * 8, POL(4));
}
__device__ __forceinline__ void wait_p1_free(const Ctx& c, int u1, int s) {
  mbar_wait(c.bar + (B_P1E + 2 * s) * 8, ((u1 - 1 - 2 * s) / 10) & 1);
  mbar_wait(c.bar + (B_P1E + 2 * s + 1) * 8, ((u1 - 2 - 2 * s) / 10) & 1);
}
__device__ __forceinline__ void p2_producer(const Params& p, const Ctx& c, int u1, int rot) {
  const int nit = p.s.r[c.cl].n2;
  int slot = rot, cnt = 0, par = 1, n = 0;
  const uint8_t* pv = nullptr;
  bool pl = false;
  auto load = [&](const uint8_t* src, int expect, uint32_t fb, bool last) {
    if (cnt < 5) {
      if (u1) {
        wait_p1_free(c, u1, slot);
        if (cnt == 0) p2_load_q(p, c, 0, 1);
      }
      cnt++;
    } else {
      if (slot == rot) par ^= 1;
      mbar_wait(c.bar + (B_P2E + slot) * 8, par);
    }
    if (expect) mbar_expect(fb, expect);
    bulk_load_mc(c.sm + SM_RING + slot * 32768 + c.rank * 16384, src, 16384, fb, last ? POL(5) : L2_NORMAL);
    slot = wrap5(slot + 1);
  };
  for (int it = 0; it < nit; it++) {
    const int item = p.s.r[c.cl].item[it], h = item >> 3, j = item & 7;
    if (it == 1 && (c.phases & 16) && p.s.r[c.cl].n1 < 8) flag_wait<true>(F_GATE, 256);
    uint32_t ready = (c.phases & 16) ? 0u : 255u;
    if (it == 0) { if (c.phases & 16) flag_wait<false>(F_Q + item, 4); mbar_wait(c.bar + B_LAD * 8, 0); p2_load_q(p, c, 0, 0); if (!u1) p2_load_q(p, c, 0, 1); }
    for (int t = 2 * j + 1; t >= 0; t--) {
      mask_wait(ready, t >> 1, F_KV + h * 8 + (c.lane & 7), 8);
      const uint8_t* k = g_S + (size_t)(2 * S_K + p.s.slot[h][t >> 1] * 16 + t) * 32768 + c.rank * 16384;
      const uint32_t fb = c.bar + (B_P2F + (n & 3)) * 8;
      const bool last = (p.s.r[c.cl].last[it] >> (t >> 1)) & 1;
      load(k, pv && t != 2 * j ? 65536 : 32768, fb, last);
      if (!(t & 1) && t + 4 <= 2 * j && c.rank == 0) flag_add_rx(F_RD + h * 8 + (t >> 1) + 2);
      if (pv) load(pv, 0, t != 2 * j ? fb : c.bar + (B_ORD + ((n - 1 - it) & 3)) * 8, pl);
      pl = last;
      pv = k + (size_t)NH * 16 * 32768;
      n++;
    }
  }
  load(pv, 32768, c.bar + (B_P2F + (n & 3)) * 8, pl);
}

__device__ __forceinline__ void publish_and_load_q(const Params& p, const Ctx& c, int f, int it, int seen) {
  const bool want = it < p.s.r[c.cl].n2, early = want && __all_sync(0xffffffffu, seen >= 4);
  if (early) { p2_load_q(p, c, it, it & 1); p2_load_q(p, c, it, (it & 1) ^ 1); }
  if (f >= 0) flag_add(f, 2);
  if (want && !early) {
    if (c.phases & 16) flag_wait<false>(F_Q + p.s.r[c.cl].item[it], 4);
    p2_load_q(p, c, it, it & 1); p2_load_q(p, c, it, (it & 1) ^ 1);
  }
}
__device__ __forceinline__ void p2_storer(const Params& p, const Ctx& c, int sfpar) {
  const int nit = p.s.r[c.cl].n2;
  for (int i = 0; i < 2 * nit; i++) {
    const int it = i >> 1, w = (it ^ i ^ 1) & 1, b = p2_buf(w, it);
    const int item = p.s.r[c.cl].item[it], h = item >> 3, j = item & 7;
    mbar_wait(c.bar + (B_SF + b) * 8, (sfpar >> b) & 1);
    sfpar ^= 1 << b;
    bulk_store(g_S + (size_t)p.s.qblk[item] * 65536 + p2_blk(c.rank, w, it) * 16384, c.sm + SM_BUF + b * 16384, 16384, POL(1));
    BULK_COMMIT();
    if (i & 1) {
      const int seen = flag_peek(F_Q + p.s.r[c.cl].item[min(it + 2, nit - 1)]);
      BULK_WAIT(0);
      if (it + 1 == nit) release(c, B_DONE);
      publish_and_load_q(p, c, F_CTX + j * 64 + h, it + 2, seen);
    }
  }
}

__device__ __forceinline__ int p3_pos(int i, int x) { return i < 4 ? (i + x) & 3 : 4; }
__device__ __forceinline__ void p3_consumer(const Params& p, const Ctx& c, int x) {
  const bool first = p.s.r[c.cl].p3 >= 24;
  const int tile = p.s.r[c.cl].p3 - (first ? 24 : 0), j = tile / 3, nt = tile - 3 * j;
  const int na = first ? 9 : 0, nb = p.s.task[c.cl][1] - p.s.task[c.cl][0];
  const uint32_t ad = desc_lo(c.sm + SM_RING + c.wg * 8192, 16), bd = desc_lo(c.sm + SM_RING + 16384, 4096);
  float acc[96] = {};
  int slot = 0, par = 0, prev = 0;
  float g0 = 0.f, g1 = 0.f;
  const int hold = c.wg && LAG ? na + nb - LAG : -1, pass = c.wg || !LAG ? -1 : na + nb - 1;
#pragma unroll 1
  for (int kb = 0; kb < nb; kb++) {
    if (kb == hold) bar_sync(6, 256);
    mbar_wait(c.bar + (B_P3F + slot) * 8, par);
    if (kb == 0) PROF(c.wg, 39);
    WG_FENCE();
#pragma unroll
    for (int kk = 0; kk < 4; kk++) wgmma_ss192<1>(acc, ad + p3_pos(slot, x) * 2560 + kk * 2, bd + p3_pos(slot, x) * 2560 + (kk >> 1) * 768 + (kk & 1) * 128, kk != 0 ? 1 : kb != 0);
    WG_COMMIT();
    if (kb == pass) bar_arrive(6, 256);
    WG_WAIT(1);
    if (kb > 0) release(c, B_P3E + prev);
    else {
      const float* g = g_gate + j * 256 + c.rank * 128 + c.wg * 64 + c.warp * 16 + (c.lane >> 2);
      g0 = __ldcg(g); g1 = __ldcg(g + 8);
    }
    prev = slot;
    if (++slot == 5) { slot = 0; par ^= 1; }
  }
  WG_WAIT(0);
  pin(acc);
  g0 = 1.f - g0; g1 = 1.f - g1;
#pragma unroll
  for (int i = 0; i < 24; i++) { acc[4 * i] *= g0; acc[4 * i + 1] *= g0; acc[4 * i + 2] *= g1; acc[4 * i + 3] *= g1; }
#pragma unroll 1
  for (int kb = nb; kb < nb + na; kb++) {
    if (kb == hold) bar_sync(6, 256);
    mbar_wait(c.bar + (B_P3F + slot) * 8, par);
    if (kb == 0) PROF(c.wg, 39);
    WG_FENCE();
#pragma unroll
    for (int kk = 0; kk < 4; kk++) wgmma_ss192<1, 1>(acc, ad + p3_pos(slot, x) * 2560 + kk * 128, bd + p3_pos(slot, x) * 2560 + (kk >> 1) * 768 + (kk & 1) * 128, 1);
    WG_COMMIT();
    if (kb == pass) bar_arrive(6, 256);
    WG_WAIT(1);
    if (kb > 0) release(c, B_P3E + prev);
    prev = slot;
    if (++slot == 5) { slot = 0; par ^= 1; }
  }
  WG_WAIT(0);
  pin(acc);
  PROF(c.wg, 40);
  if (first) bar_sync(4 + c.wg, 128);
  mbar_wait(c.bar + B_OUT * 8, 0);
  const int row = (c.lane & 7) + ((c.lane >> 3) & 1) * 8;
  const uint32_t wbase = c.sm + SM_RING + c.wg * 8192 + c.warp * 2048;
  const uint32_t base = wbase + row * 128 + (((c.lane >> 4) ^ (row & 7)) << 4);
#pragma unroll
  for (int i = 0; i < 12; i++) {
    stsm4((base ^ ((i & 3) << 5)) + (i >> 2) * 40960, pack_bf16(acc[8 * i], acc[8 * i + 1]), pack_bf16(acc[8 * i + 2], acc[8 * i + 3]),
          pack_bf16(acc[8 * i + 4], acc[8 * i + 5]), pack_bf16(acc[8 * i + 6], acc[8 * i + 7]));
    if ((i & 3) == 3) {
      FENCE_ASYNC_SMEM();
      bar_sync(4 + c.wg, 128);
      if (c.warp == (i >> 2)) tma2d_add(&p.map_out, c.sm + SM_RING + c.wg * 8192 + c.warp * 40960, nt * 192 + c.warp * 64, j * 256 + c.rank * 128 + c.wg * 64);
    }
  }
  BULK_COMMIT();
  PROF(c.wg, 43);
  BULK_WAIT_READ(0);
  PROF(c.wg, 44);
}

__device__ __forceinline__ void p3_producer(const Params& p, const Ctx& c, int u1, int u2, int rot, int x) {
  const bool first = p.s.r[c.cl].p3 >= 24;
  const int tile = p.s.r[c.cl].p3 - (first ? 24 : 0), j = tile / 3, nt = tile - 3 * j;
  int slot = 0, par = 1, cnt = 0;
  auto wait_free = [&](int s) {
    const int f = wrap5(s + 5 - rot);
    if (f < u2) mbar_wait(c.bar + (B_P2E + s) * 8, ((u2 - 1 - f) / 5) & 1);
    else if (u1) wait_p1_free(c, u1, s);
  };
  asm volatile(ELECT("prefetch.tensormap [%0];") ::"l"(&p.map_o[0]) : "memory");
  asm volatile(ELECT("prefetch.tensormap [%0];") ::"l"(&p.map_out) : "memory");
  if ((c.phases & 16) && p.s.r[c.cl].n1 < 8 && p.s.r[c.cl].n2 < 2) flag_wait<true>(F_GATE, 256);
  uint32_t ready = (c.phases & 16) ? 0u : ~0u;
  const int q1 = p.s.task[c.cl][1];
  for (int q = p.s.task[c.cl][0]; q < q1 + (first ? 9 : 0); q++) {
    const bool brA = q >= q1;
    const int kb = brA ? q - q1 : p.s.p3_order[tile][q];
    if (!brA) mask_wait(ready, kb >> 1, F_CTX + j * 64 + c.lane, 4);
    else if (kb == 0 && (c.phases & 16)) flag_wait<false>(F_CTX + j * 64 + 32, 16);
    const uint8_t* a = brA ? g_oA + (j * 4 + c.rank * 2) * 73728 + kb * 8192 : g_S + (size_t)p.s.qblk[(kb >> 1) * 8 + j] * 65536 + c.rank * 32768 + (kb & 1) * 8192;
    const uint32_t st = c.sm + SM_RING + p3_pos(slot, x) * 40960, fb = c.bar + (B_P3F + slot) * 8;
    if (cnt < 4) { wait_free(p3_pos(cnt, x)); wait_free(p3_pos(cnt, x) + 1); }
    else if (cnt == 4) mbar_wait(c.bar + B_DONE * 8, 0);
    else mbar_wait(c.bar + (B_P3E + slot) * 8, par);
    cnt++;
    mbar_expect(fb, 40960);
    bulk_load(st, a, 8192, fb, POL(3));
    bulk_load(st + 8192, a + (brA ? 73728 : 16384), 8192, fb, POL(3));
    tma3d_mc(st + 16384 + c.rank * 12288, &p.map_o[brA], 0, kb * 64 + c.rank * 32, nt * 3, fb);
    if (++slot == 5) { slot = 0; par ^= 1; }
  }
}

__device__ __forceinline__ float bf_lo(uint32_t w) { return __uint_as_float(w << 16); }
__device__ __forceinline__ float bf_hi(uint32_t w) { return __uint_as_float(w & 0xffff0000u); }

__device__ __forceinline__ void gate_rows(const Params& p, int row0, int lane) {
  const uint4* x = reinterpret_cast<const uint4*>(p.x + (size_t)(row0 + (lane >> 2)) * DM) + (lane & 3);
  const uint4* w = reinterpret_cast<const uint4*>(p.gate_w) + (lane & 3);
  float a = 0.f;
#pragma unroll 1
  for (int b = 0; b < 3; b++) {
    uint4 u[6];
#pragma unroll
    for (int i = 0; i < 6; i++) u[i] = __ldg(x + (b * 6 + i) * 4);
#pragma unroll
    for (int i = 0; i < 6; i++) {
      const uint4 v = __ldg(w + (b * 6 + i) * 4);
      a = fmaf(bf_lo(u[i].x), bf_lo(v.x), a); a = fmaf(bf_hi(u[i].x), bf_hi(v.x), a);
      a = fmaf(bf_lo(u[i].y), bf_lo(v.y), a); a = fmaf(bf_hi(u[i].y), bf_hi(v.y), a);
      a = fmaf(bf_lo(u[i].z), bf_lo(v.z), a); a = fmaf(bf_hi(u[i].z), bf_hi(v.z), a);
      a = fmaf(bf_lo(u[i].w), bf_lo(v.w), a); a = fmaf(bf_hi(u[i].w), bf_hi(v.w), a);
    }
  }
  a += __shfl_xor_sync(0xffffffffu, a, 1);
  a += __shfl_xor_sync(0xffffffffu, a, 2);
  if ((lane & 3) == 0) g_gate[row0 + (lane >> 2)] = 1.f / (1.f + __expf(-a));
}

__device__ __forceinline__ void lds10(uint32_t (&k)[10], uint32_t a) {
  asm volatile("ld.shared.v2.u32 {%0, %1}, [%10];\nld.shared.v2.u32 {%2, %3}, [%10+8];\nld.shared.v2.u32 {%4, %5}, [%10+16];\n"
               "ld.shared.v2.u32 {%6, %7}, [%10+24];\nld.shared.v2.u32 {%8, %9}, [%10+32];"
               : "=r"(k[0]), "=r"(k[1]), "=r"(k[2]), "=r"(k[3]), "=r"(k[4]), "=r"(k[5]), "=r"(k[6]), "=r"(k[7]), "=r"(k[8]), "=r"(k[9]) : "r"(a));
}
__device__ __forceinline__ void local_attn(const Params& p, const Ctx& c, int rb, int hs) {
  const int lane = c.lane, grp = rb >> 2, par = lane >> 4, i0 = 2 * (lane & 15);
  const uint32_t buf = c.sm + SM_BUF + (c.warp - 2) * 8192, bqk = c.bar + (B_LA + (c.warp - 2) * 2) * 8, bv = bqk + 8;
  const uint32_t mine = buf + 2304 + par * 160 + i0 * 4;
  const bool flags = c.phases & 16;
  auto fetch_qk = [&](int i) {
    if (flags && !(i & 1)) {
      const int q = i >> 1;
      const int tgt = q == 0 ? 24 : q == 3 ? 8 : 12;
      flag_wait<false>(F_QKVA + (grp - (grp > 0 && (rb & 3) == 0 ? par : 0)) * 4 + q, tgt);
    }
    mbar_expect(bqk, 5184);
    tma3d(buf, &p.map_t[0], rb * 32, 0, 9 * (4 * i + hs), bqk, POL(2));
    tma3d(buf + 2304, &p.map_t[1], rb * 32 - 8, 0, 288 + 9 * (4 * i + hs), bqk, POL(2));
  };
  auto fetch_v = [&](int i) { mbar_expect(bv, 2880); tma3d(buf + 5248, &p.map_t[1], rb * 32 - 8, 0, 576 + 9 * (4 * i + hs), bv, POL(2)); };
  fetch_qk(0);
  if (flags) flag_wait<true>(F_GATE, 256);
#pragma unroll 1
  for (int q = 0; q < 8; q++) {
    fetch_v(q);
    float a[8], b[8];
#pragma unroll
    for (int w = 0; w < 8; w++) a[w] = b[w] = 0.f;
    mbar_wait(bqk, q & 1);
    PROFB(1 + 2 * q);
#pragma unroll 1
    for (int j = 0; j < 9; j++) {
      uint32_t x, y, k[10];
      asm volatile("ld.shared.v2.u32 {%0, %1}, [%2];" : "=r"(x), "=r"(y) : "r"(buf + lane * 8 + j * 256));
      lds10(k, mine + j * 320);
      const float xl = bf_lo(x), xh = bf_hi(x), yl = bf_lo(y), yh = bf_hi(y);
#pragma unroll
      for (int m = 1; m < 10; m++) {
        const float kl = bf_lo(k[m]), kh = bf_hi(k[m]);
        if (m < 9) a[8 - m] = fmaf(xl, kl, fmaf(xh, kh, a[8 - m]));
        if (m > 1) b[9 - m] = fmaf(yl, kl, fmaf(yh, kh, b[9 - m]));
      }
    }
    __syncwarp();
    mbar_wait(bv, q & 1);
    if (q & 1) flag_add_rx(F_TS + (q >> 1));
    if (q < 7) fetch_qk(q + 1);
    constexpr float SC = 0.23570226039551584f * 1.4426950408889634f;
    const float* gp = g_gate + rb * 64 + 2 * i0 + par;
    const float ga = __ldcg(gp), gb = __ldcg(gp + 2);
    float ma = a[0], mb = b[0];
#pragma unroll
    for (int w = 1; w < 8; w++) {
      if (rb == 0) {
        if (i0 < w) a[w] = -INFINITY;
        if (i0 + 1 < w) b[w] = -INFINITY;
      }
      ma = fmaxf(ma, a[w]); mb = fmaxf(mb, b[w]);
    }
    float la = 0.f, lb = 0.f;
#pragma unroll
    for (int w = 0; w < 8; w++) {
      a[w] = ex2((a[w] - ma) * SC); b[w] = ex2((b[w] - mb) * SC);
      la += a[w]; lb += b[w];
    }
    la = __fdividef(ga, la); lb = __fdividef(gb, lb);
#pragma unroll
    for (int w = 0; w < 8; w++) { a[w] *= la; b[w] *= lb; }
    uint8_t* dst = g_oA + rb * 73728 + ((i0 & 2) + par) * 4;
#pragma unroll 1
    for (int j = 0; j < 9; j++) {
      uint32_t v[10];
      lds10(v, mine + 2944 + j * 320);
      float a0 = 0.f, a1 = 0.f, b0 = 0.f, b1 = 0.f;
#pragma unroll
      for (int m = 1; m < 10; m++) {
        const float vl = bf_lo(v[m]), vh = bf_hi(v[m]);
        if (m < 9) { a0 = fmaf(a[8 - m], vl, a0); a1 = fmaf(a[8 - m], vh, a1); }
        if (m > 1) { b0 = fmaf(b[9 - m], vl, b0); b1 = fmaf(b[9 - m], vh, b1); }
      }
      const uint32_t wa = pack_bf16(a0, a1), wb = pack_bf16(b0, b1);
      const uint32_t got = __shfl_xor_sync(0xffffffffu, par ? wa : wb, 16);
      const uint32_t r0 = par ? got : wa, r1 = par ? wb : got;
      const int col = 18 * (4 * q + hs) + 2 * j, o = col * 128 + ((((i0 >> 2) ^ col) & 7) << 4);
      *reinterpret_cast<uint32_t*>(dst + o) = __byte_perm(r0, r1, 0x5410);
      *reinterpret_cast<uint32_t*>(dst + ((o + 128) ^ 16)) = __byte_perm(r0, r1, 0x7632);
    }
    __syncwarp();
    PROFB(2 + 2 * q);
  }
  mbar_arrive_one(c.bar + B_LAD * 8);
  flag_add(F_CTX + grp * 64 + 32);
}

__global__ void __cluster_dims__(2, 1, 1) __launch_bounds__(384, 1) fused_kernel(const __grid_constant__ Params p) {
  extern __shared__ uint8_t smem_raw[];
  Ctx c;
  c.sm = ((uint32_t)__cvta_generic_to_shared(smem_raw) + 1023u) & ~1023u;
  c.bar = c.sm + SM_BAR;
  c.lane = threadIdx.x & 31;
  const int wid = __shfl_sync(0xffffffffu, threadIdx.x >> 5, 0);
  if (wid < 6) asm volatile("prefetch.tensormap [%0];" ::"l"(&p.map_a[0] + wid) : "memory");
  c.wg = wid >> 2;
  c.warp = wid & 3;
  PROF(c.wg, 0);
  PROFG(61);
  c.cl = (blockIdx.x + (wid >> 4)) >> 1;
  c.rank = blockIdx.x & 1;
  c.rbar = mapa(c.bar, c.lane & 1);
  {
    const int w = wid, cnt = (((int)(B_CNT >> (4 * w)) - 1) & 15) + 1;
    if (w < 11) {
#pragma unroll
      for (int i = 0; i < 8; i++) asm volatile("mbarrier.init.shared::cta.b64 [%0], %1;" ::"r"(c.bar + w * 64 + i * 8), "r"(cnt));
    }
    asm volatile("fence.mbarrier_init.release.cluster;" ::: "memory");
  }
  if (c.wg == 2) PROF(2, 56);
  asm volatile("barrier.cluster.arrive.relaxed;" ::: "memory");
  c.phases = p.s.r[c.cl].phases;
  const bool do1 = p.s.r[c.cl].n1 > 0, do2 = p.s.r[c.cl].n2 > 0, do3 = p.s.r[c.cl].p3 != 255;
  if (do1 && c.wg == 2 && c.warp == 0) {
    const int type = p.s.r[c.cl].slab >> 3;
    PROF(2, 57);
    FENCE_ASYNC_SMEM();
    mbar_expect(c.bar + B_P1F * 8, type ? 32768 : 16384);
    tma2d(type ? c.sm + SM_BUF + 32768 : c.sm + SM_RING, &p.map_a[type], type ? 512 : 0, (p.s.r[c.cl].slab & 7) * 256 + c.rank * 128, c.bar + B_P1F * 8);
    PROF(2, 58);
  }
  asm volatile("barrier.cluster.wait.acquire;" ::: "memory");
  if (c.wg == 2) PROF(2, 59);
  if (do1 && c.wg == 2 && c.warp == 0) {
    const int type = p.s.r[c.cl].slab >> 3, tile = p.s.r[c.cl].tile[0] & 63;
    const CUtensorMap* m = &p.map_w[type * 2 + (tile >> 5)];
#pragma unroll 1
    for (int s = 1 - type; s < NPRO; s++) {
      const int kb = (s - type) >> 1;
      const uint32_t fb = c.bar + (B_P1F + s) * 8;
      if (s) mbar_expect(fb, 16384);
      if ((s ^ type) & 1) tma2d_mc(c.sm + SM_RING + s * 16384 + c.rank * 8192, m, (tile & 31) * 128 + c.rank * 64, kb < 0 ? 512 : kb * 64, fb);
      else tma2d(c.sm + SM_RING + s * 16384, &p.map_a[type], kb * 64, (p.s.r[c.cl].slab & 7) * 256 + c.rank * 128, fb);
    }
  }

  if (c.wg < 2) {
    PROF(c.wg, 4);
    asm volatile("setmaxnreg.inc.sync.aligned.u32 224;");
    if (c.wg == 1) {
      if (do1) bar_arrive(ORDER, 256);
      if (c.lane == 0) mbar_arrive(c.bar + B_P2F * 8);
    }
    PL(0);
    if (do1) p1_consumer(p, c);
    PL(1);
    if (do2) p2_consumer(p, c, p.s.r[c.cl].rot);
    PL(2);
    if (do3) p3_consumer(p, c, p.s.r[c.cl].x3);
    PL(3);
    PROF(c.wg, 63);
    PROFG(62);
    if (c.lane == 0) mbar_arrive(c.bar + B_FIN * 8);
    __syncwarp();
    cluster_sync();
  } else {
    asm volatile("setmaxnreg.dec.sync.aligned.u32 56;");
    if (c.warp == 0) {
      PROF(2, 60);
      if (do1) p1_producer(p, c);
      if (do2) p2_producer(p, c, p.s.r[c.cl].u1, p.s.r[c.cl].rot);
      if (do3) p3_producer(p, c, p.s.r[c.cl].u1, p.s.r[c.cl].u2, p.s.r[c.cl].rot, p.s.r[c.cl].x3);
    } else if (c.warp == 1) {
      const int f = do1 ? p1_storer(p, c) : -1;
      publish_and_load_q(p, c, f, 1, flag_peek(F_Q + p.s.r[c.cl].item[1]));
      if (do2) p2_storer(p, c, (p.s.r[c.cl].n1 & 1) * 10);
      else { mbar_wait(c.bar + B_LAD * 8, 0); release(c, B_DONE); }
      if (do3) {
        const int tile = p.s.r[c.cl].p3 % 24;
        if (p.s.task[c.cl][1] == 64) {
          for (int r = 0; r < (64 - p.s.task[c.cl][0] - ZLEAD) / 5; r++) mbar_wait(c.bar + B_P3F * 8, r & 1);
          const int j = tile / 3, nt = tile - 3 * j;
          uint4* o = reinterpret_cast<uint4*>(p.out + (size_t)(j * 256 + c.rank * 128 + (c.lane >> 3)) * DM + nt * 192) + (c.lane & 7);
#pragma unroll 4
          for (int r = 0; r < 32; r++) o[r * 288] = o[r * 288 + 8] = o[r * 288 + 16] = make_uint4(0u, 0u, 0u, 0u);
          __syncwarp();
          flag_add(F_OUT + tile * 2 + c.rank);
        } else if (c.phases & 16) {
          flag_wait<false, 256>(F_OUT + tile * 2 + c.rank, 1);
        }
        mbar_arrive_one(c.bar + B_OUT * 8);
      }
    } else {
      const int bw = blockIdx.x * 2 + (c.warp - 2);
      if ((c.phases & 1) && bw < 256) {
        gate_rows(p, bw * 8, c.lane);
        __syncwarp();
        flag_add(F_GATE);
      }
      if (p.s.r[c.cl].bg != 255) local_attn(p, c, p.s.r[c.cl].bg, bw & 3);
      else if (c.lane == 0) mbar_arrive(c.bar + B_LAD * 8);
    }
    __syncwarp();
    bar_sync(3, 128);
    if (c.warp == 0 && (c.phases & 32)) {
      int last = 0;
      if (c.lane == 0) { __threadfence(); last = atomicAdd(g_flags + F_DONE, 1) == 2 * NCL - 1; }
      if (__shfl_sync(0xffffffffu, last, 0)) for (int i = c.lane; i < F_NUM; i += 32) g_flags[i] = 0;
    }
    if (c.warp == 1) mbar_wait(c.bar + B_FIN * 8, 0);
    __syncwarp();
    cluster_sync();
  }
}

SCHED_DECL Sched k_sched = {
  {{0,30,2,0,0,{217,184,0,0,0,0,0,0,0,0,0},{0,0,0,0,0,0,0,0,0,0,0},{66,40,5,33,35,38,43,36,42,51,47,41,48,49,57,56,45,44,52,54,63,46,53,58,50,61,59,55,62,60}},
   {1,30,2,8,1,{185,216,0,0,0,0,0,0,0,0,0},{0,0,0,0,0,0,0,0,0,0,0},{66,40,128,33,35,43,38,36,42,51,47,41,48,49,57,56,45,44,52,54,63,46,53,58,50,61,59,55,62,60}},
   {2,30,1,39,2,{218,0,0,0,0,0,0,0,0,0,0},{0,0,0,0,0,0,0,0,0,0,0},{72,101,128,33,35,43,38,36,42,51,47,41,48,49,57,56,45,44,52,54,63,46,53,58,50,61,59,55,62,60}},
   {3,29,0,2,3,{0,0,0,0,0,0,0,0,0,0,0},{0,0,0,0,0,0,0,0,0,0,0},{72,162,128,33,3,38,36,42,51,47,41,48,49,57,56,45,44,52,54,63,46,53,58,61,50,59,55,62,60,0}},
   {4,28,0,1,4,{0,0,0,0,0,0,0,0,0,0,0},{0,0,0,0,0,0,0,0,0,0,0},{135,40,5,32,11,35,4,42,15,9,16,17,25,24,13,12,20,22,31,14,21,26,18,29,27,23,30,28,0,0}},
   {5,27,0,4,5,{0,0,0,0,0,0,0,0,0,0,0},{0,0,0,0,0,0,0,0,0,0,0},{72,39,5,32,11,35,4,42,15,41,17,25,24,13,12,20,22,31,14,21,26,18,29,27,23,30,28,0,0,0}},
   {6,26,2,38,6,{113,236,0,0,0,0,0,0,0,0,0},{0,31,0,0,0,0,0,0,0,0,0},{167,162,128,33,3,38,10,51,9,48,25,24,13,12,20,22,31,14,21,90,18,29,27,23,30,28,0,0,0,0}},
   {7,25,0,23,7,{0,0,0,0,0,0,0,0,0,0,0},{0,0,0,0,0,0,0,0,0,0,0},{72,69,128,75,70,74,79,105,81,89,88,77,76,84,86,95,78,85,82,90,93,91,87,94,92,0,0,0,0,0}},
   {0,30,1,34,8,{243,0,0,0,0,0,0,0,0,0,0},{0,0,0,0,0,0,0,0,0,0,0},{135,162,128,37,3,6,11,4,10,19,15,9,16,17,25,24,13,12,20,22,31,14,21,26,18,29,27,23,30,28}},
   {1,30,1,28,9,{234,0,0,0,0,0,0,0,0,0,0},{0,0,0,0,0,0,0,0,0,0,0},{135,162,5,32,3,11,6,4,10,19,15,9,16,17,25,24,13,12,20,22,31,14,21,26,18,29,27,23,30,28}},
   {2,30,1,43,10,{186,0,0,0,0,0,0,0,0,0,0},{0,0,0,0,0,0,0,0,0,0,0},{135,40,2,32,3,11,6,4,10,19,15,9,16,17,25,24,13,12,20,22,31,14,21,26,18,29,27,23,30,28}},
   {3,29,0,12,11,{0,0,0,0,0,0,0,0,0,0,0},{0,0,0,0,0,0,0,0,0,0,0},{135,40,5,32,11,35,4,10,19,15,9,16,17,25,24,13,12,20,22,31,14,21,26,29,18,27,23,30,28,0}},
   {4,28,0,5,12,{0,0,0,0,0,0,0,0,0,0,0},{0,0,0,0,0,0,0,0,0,0,0},{167,2,37,1,43,6,36,19,47,41,48,49,57,56,45,44,52,54,63,46,53,58,50,61,59,55,62,60,0,0}},
   {5,27,0,14,13,{0,0,0,0,0,0,0,0,0,0,0},{0,0,0,0,0,0,0,0,0,0,0},{104,2,37,1,43,6,36,19,47,16,49,57,56,45,44,52,54,63,46,53,58,50,61,59,55,62,60,0,0,0}},
   {6,26,0,10,14,{0,0,0,0,0,0,0,0,0,0,0},{0,0,0,0,0,0,0,0,0,0,0},{72,69,96,75,35,4,42,15,41,17,57,56,45,44,52,54,63,46,53,122,50,61,59,55,62,60,0,0,0,0}},
   {7,25,0,7,15,{0,0,0,0,0,0,0,0,0,0,0},{0,0,0,0,0,0,0,0,0,0,0},{104,101,96,107,102,106,111,80,113,121,120,109,108,116,118,127,110,117,114,122,125,123,119,126,124,0,0,0,0,0}},
   {0,4,7,9,255,{22,90,34,121,74,175,219,0,0,0,0},{0,0,0,0,0,0,0,0,0,0,0},{167,8,96,1,0,0,0,0,0,0,0,0,0,0,0,0,0,0,0,0,0,0,0,0,0,0,0,0,0,0}},
   {1,4,7,35,255,{20,11,50,83,140,116,211,0,0,0,0},{0,0,0,0,0,0,15,0,0,0,0},{167,8,37,1,0,0,0,0,0,0,0,0,0,0,0,0,0,0,0,0,0,0,0,0,0,0,0,0,0,0}},
   {2,4,6,42,255,{42,43,26,157,110,238,0,0,0,0,0},{0,0,0,0,0,96,0,0,0,0,0},{167,69,34,1,0,0,0,0,0,0,0,0,0,0,0,0,0,0,0,0,0,0,0,0,0,0,0,0,0,0}},
   {3,6,8,18,255,{95,89,153,122,193,97,179,144,0,0,0},{0,0,0,0,0,0,0,0,0,0,0},{167,2,37,1,43,6,0,0,0,0,0,0,0,0,0,0,0,0,0,0,0,0,0,0,0,0,0,0,0,0}},
   {4,8,4,47,255,{55,82,103,190,0,0,0,0,0,0,0},{0,0,0,0,0,0,0,0,0,0,0},{72,162,128,33,3,38,10,51,0,0,0,0,0,0,0,0,0,0,0,0,0,0,0,0,0,0,0,0,0,0}},
   {5,10,5,13,255,{88,25,85,205,151,0,0,0,0,0,0},{0,0,0,0,224,0,0,0,0,0,0},{135,162,128,33,3,38,10,51,9,48,0,0,0,0,0,0,0,0,0,0,0,0,0,0,0,0,0,0,0,0}},
   {6,10,5,18,255,{48,53,75,182,221,0,0,0,0,0,0},{0,0,0,0,63,0,0,0,0,0,0},{104,101,65,107,70,36,19,47,16,49,0,0,0,0,0,0,0,0,0,0,0,0,0,0,0,0,0,0,0,0}},
   {7,8,5,16,255,{24,29,84,167,208,0,0,0,0,0,0},{0,0,0,252,0,0,0,0,0,0,0},{135,2,65,67,68,83,73,112,0,0,0,0,0,0,0,0,0,0,0,0,0,0,0,0,0,0,0,0,0,0}},
   {8,18,1,19,16,{100,0,0,0,0,0,0,0,0,0,0},{0,0,0,0,0,0,0,0,0,0,0},{136,33,67,43,35,44,109,10,9,17,77,24,78,85,90,18,27,30,0,0,0,0,0,0,0,0,0,0,0,0}},
   {9,17,3,0,17,{32,254,248,0,0,0,0,0,0,0,0},{0,0,1,0,0,0,0,0,0,0,0},{66,41,162,3,108,11,40,19,9,89,16,76,95,14,90,93,27,0,0,0,0,0,0,0,0,0,0,0,0,0}},
   {10,18,4,41,18,{80,105,162,191,0,0,0,0,0,0,0},{1,0,0,255,0,0,0,0,0,0,0},{135,41,162,11,39,6,40,10,15,16,17,13,12,31,21,26,29,30,0,0,0,0,0,0,0,0,0,0,0,0}},
   {11,19,3,12,19,{200,99,213,0,0,0,0,0,0,0,0},{0,0,0,0,0,0,0,0,0,0,0},{100,2,107,3,35,44,4,45,19,15,17,25,20,31,14,93,18,23,28,0,0,0,0,0,0,0,0,0,0,0}},
   {12,19,2,5,20,{106,239,0,0,0,0,0,0,0,0,0},{0,128,0,0,0,0,0,0,0,0,0},{100,5,1,6,35,44,10,40,9,16,25,13,20,31,21,18,27,30,28,0,0,0,0,0,0,0,0,0,0,0}},
   {13,18,2,21,21,{101,96,0,0,0,0,0,0,0,0,0},{0,0,0,0,0,0,0,0,0,0,0},{96,106,107,6,39,4,19,40,9,17,24,76,20,31,82,26,23,92,0,0,0,0,0,0,0,0,0,0,0,0}},
   {14,17,3,30,22,{201,194,215,0,0,0,0,0,0,0,0},{0,0,224,0,0,0,0,0,0,0,0},{64,165,107,6,74,35,44,73,45,17,24,76,22,14,90,91,23,0,0,0,0,0,0,0,0,0,0,0,0,0}},
   {15,18,3,45,23,{152,165,246,0,0,0,0,0,0,0,0},{1,0,0,0,0,0,0,0,0,0,0},{69,36,75,38,68,83,35,44,80,45,25,13,20,31,21,26,27,30,0,0,0,0,0,0,0,0,0,0,0,0}},
   {8,18,3,15,24,{72,138,192,0,0,0,0,0,0,0,0},{0,0,0,0,0,0,0,0,0,0,0},{64,165,162,6,39,104,4,19,15,16,25,86,12,20,31,93,23,92,0,0,0,0,0,0,0,0,0,0,0,0}},
   {9,18,2,36,25,{108,223,0,0,0,0,0,0,0,0,0},{0,192,0,0,0,0,0,0,0,0,0},{136,33,166,99,6,10,109,15,81,88,77,84,22,85,82,87,94,92,0,0,0,0,0,0,0,0,0,0,0,0}},
   {10,18,4,4,26,{196,171,233,227,0,0,0,0,0,0,0},{0,0,0,15,0,0,0,0,0,0,0},{136,33,166,1,108,4,109,19,9,89,24,84,22,14,82,87,27,92,0,0,0,0,0,0,0,0,0,0,0,0}},
   {11,18,3,24,27,{128,174,188,0,0,0,0,0,0,0,0},{0,0,0,0,0,0,0,0,0,0,0},{105,5,0,6,39,11,40,10,9,16,24,13,12,22,21,26,27,30,0,0,0,0,0,0,0,0,0,0,0,0}},
   {12,18,4,40,28,{119,146,241,224,0,0,0,0,0,0,0},{0,0,0,0,0,0,0,0,0,0,0},{96,106,107,3,11,39,4,19,45,15,17,24,12,22,14,26,29,23,0,0,0,0,0,0,0,0,0,0,0,0}},
   {13,18,3,22,29,{136,107,249,0,0,0,0,0,0,0,0},{0,0,0,0,0,0,0,0,0,0,0},{69,165,166,11,35,44,10,15,45,16,25,13,22,14,21,93,27,30,0,0,0,0,0,0,0,0,0,0,0,0}},
   {14,19,3,9,30,{104,163,170,0,0,0,0,0,0,0,0},{0,0,0,0,0,0,0,0,0,0,0},{66,41,162,11,68,83,39,15,40,16,25,13,20,31,21,18,29,30,28,0,0,0,0,0,0,0,0,0,0,0}},
   {15,18,3,21,31,{120,118,220,0,0,0,0,0,0,0,0},{0,0,0,0,0,0,0,0,0,0,0},{66,41,67,43,74,79,39,73,40,17,24,76,22,14,82,93,23,92,0,0,0,0,0,0,0,0,0,0,0,0}},
   {8,3,4,20,255,{63,159,102,112,0,0,0,0,0,0,0},{0,0,0,0,0,0,0,0,0,0,0},{135,41,1,0,0,0,0,0,0,0,0,0,0,0,0,0,0,0,0,0,0,0,0,0,0,0,0,0,0,0}},
   {9,3,6,6,255,{60,30,77,202,178,168,0,0,0,0,0},{0,0,0,0,0,0,0,0,0,0,0},{135,36,0,0,0,0,0,0,0,0,0,0,0,0,0,0,0,0,0,0,0,0,0,0,0,0,0,0,0,0}},
   {10,4,7,20,255,{0,1,67,86,199,177,189,0,0,0,0},{0,0,0,0,64,0,0,0,0,0,0},{96,106,0,99,0,0,0,0,0,0,0,0,0,0,0,0,0,0,0,0,0,0,0,0,0,0,0,0,0,0}},
   {11,3,6,29,255,{61,2,135,204,150,225,0,0,0,0,0},{0,0,0,0,0,0,0,0,0,0,0},{97,8,1,0,0,0,0,0,0,0,0,0,0,0,0,0,0,0,0,0,0,0,0,0,0,0,0,0,0,0}},
   {12,3,5,44,255,{62,38,142,214,242,0,0,0,0,0,0},{0,0,0,0,0,0,0,0,0,0,0},{66,165,166,0,0,0,0,0,0,0,0,0,0,0,0,0,0,0,0,0,0,0,0,0,0,0,0,0,0,0}},
   {13,4,6,16,255,{7,91,133,117,209,210,0,0,0,0,0},{0,0,0,0,0,0,0,0,0,0,0},{135,41,1,3,0,0,0,0,0,0,0,0,0,0,0,0,0,0,0,0,0,0,0,0,0,0,0,0,0,0}},
   {14,3,7,10,255,{66,19,52,76,255,145,228,0,0,0,0},{0,0,0,0,0,0,16,0,0,0,0},{69,33,166,0,0,0,0,0,0,0,0,0,0,0,0,0,0,0,0,0,0,0,0,0,0,0,0,0,0,0}},
   {15,4,7,17,255,{59,3,36,123,195,172,244,0,0,0,0},{0,0,0,0,0,3,31,0,0,0,0},{135,32,42,34,0,0,0,0,0,0,0,0,0,0,0,0,0,0,0,0,0,0,0,0,0,0,0,0,0,0}},
   {8,3,6,6,255,{71,158,206,250,235,226,0,0,0,0,0},{0,0,121,6,0,0,0,0,0,0,0},{66,36,5,0,0,0,0,0,0,0,0,0,0,0,0,0,0,0,0,0,0,0,0,0,0,0,0,0,0,0}},
   {9,5,6,11,255,{40,18,12,81,154,198,0,0,0,0,0},{0,0,0,0,0,0,0,0,0,0,0},{69,165,107,103,68,0,0,0,0,0,0,0,0,0,0,0,0,0,0,0,0,0,0,0,0,0,0,0,0,0}},
   {10,3,8,31,255,{56,41,13,49,125,197,222,240,0,0,0},{0,0,0,0,0,62,0,0,0,0,0},{100,2,67,0,0,0,0,0,0,0,0,0,0,0,0,0,0,0,0,0,0,0,0,0,0,0,0,0,0,0}},
   {11,3,6,26,255,{21,28,35,132,252,148,0,0,0,0,0},{0,0,0,0,0,31,0,0,0,0,0},{96,106,166,0,0,0,0,0,0,0,0,0,0,0,0,0,0,0,0,0,0,0,0,0,0,0,0,0,0,0}},
   {12,3,6,32,255,{23,127,139,98,149,232,0,0,0,0,0},{0,0,0,0,0,0,0,0,0,0,0},{135,41,0,0,0,0,0,0,0,0,0,0,0,0,0,0,0,0,0,0,0,0,0,0,0,0,0,0,0,0}},
   {13,3,6,13,255,{47,51,124,130,251,160,0,0,0,0,0},{0,0,0,0,0,1,0,0,0,0,0},{66,33,162,0,0,0,0,0,0,0,0,0,0,0,0,0,0,0,0,0,0,0,0,0,0,0,0,0,0,0}},
   {14,3,5,46,255,{68,94,143,173,187,0,0,0,0,0,0},{0,0,0,0,0,0,0,0,0,0,0},{136,36,1,0,0,0,0,0,0,0,0,0,0,0,0,0,0,0,0,0,0,0,0,0,0,0,0,0,0,0}},
   {15,3,6,14,255,{58,4,10,126,181,231,0,0,0,0,0},{0,0,0,0,0,192,0,0,0,0,0},{136,65,37,0,0,0,0,0,0,0,0,0,0,0,0,0,0,0,0,0,0,0,0,0,0,0,0,0,0,0}},
   {8,4,5,8,255,{46,92,155,109,114,0,0,0,0,0,0},{0,0,0,0,3,0,0,0,0,0,0},{96,106,166,11,0,0,0,0,0,0,0,0,0,0,0,0,0,0,0,0,0,0,0,0,0,0,0,0,0,0}},
   {9,3,5,27,255,{70,93,207,161,247,0,0,0,0,0,0},{0,0,0,0,224,0,0,0,0,0,0},{96,106,1,0,0,0,0,0,0,0,0,0,0,0,0,0,0,0,0,0,0,0,0,0,0,0,0,0,0,0}},
   {10,3,7,25,255,{64,6,27,134,164,169,147,0,0,0,0},{0,0,0,0,0,0,0,0,0,0,0},{69,165,107,0,0,0,0,0,0,0,0,0,0,0,0,0,0,0,0,0,0,0,0,0,0,0,0,0,0,0}},
   {11,3,6,1,255,{65,14,37,131,253,245,0,0,0,0,0},{0,0,0,0,0,0,0,0,0,0,0},{135,165,162,0,0,0,0,0,0,0,0,0,0,0,0,0,0,0,0,0,0,0,0,0,0,0,0,0,0,0}},
   {12,3,7,22,255,{17,5,87,137,203,115,229,0,0,0,0},{0,0,0,0,0,0,48,0,0,0,0},{136,33,162,0,0,0,0,0,0,0,0,0,0,0,0,0,0,0,0,0,0,0,0,0,0,0,0,0,0,0}},
   {13,3,7,33,255,{16,15,33,78,129,180,212,0,0,0,0},{0,0,0,0,0,0,16,0,0,0,0},{136,36,0,0,0,0,0,0,0,0,0,0,0,0,0,0,0,0,0,0,0,0,0,0,0,0,0,0,0,0}},
   {14,4,5,37,255,{45,9,79,183,230,0,0,0,0,0,0},{0,0,0,250,0,0,0,0,0,0,0},{135,32,42,3,0,0,0,0,0,0,0,0,0,0,0,0,0,0,0,0,0,0,0,0,0,0,0,0,0,0}},
   {15,3,4,3,255,{69,54,73,141,0,0,0,0,0,0,0},{0,0,0,0,0,0,0,0,0,0,0},{64,33,70,0,0,0,0,0,0,0,0,0,0,0,0,0,0,0,0,0,0,0,0,0,0,0,0,0,0,0}},
   {6,2,5,17,255,{57,44,39,111,176,0,0,0,0,0,0},{0,0,0,135,0,0,0,0,0,0,0},{135,2,0,0,0,0,0,0,0,0,0,0,0,0,0,0,0,0,0,0,0,0,0,0,0,0,0,0,0,0}},
   {7,6,5,2,255,{8,31,156,166,237,0,0,0,0,0,0},{0,0,0,0,0,0,0,0,0,0,0},{167,162,97,99,100,115,0,0,0,0,0,0,0,0,0,0,0,0,0,0,0,0,0,0,0,0,0,0,0,0}}},
  {{6,23,0,0},{9,26,0,0},{0,6,0,0},{28,64,0,0},{22,64,0,0},{17,64,0,0},{0,8,0,0},{5,64,0,0},{0,2,0,0},{0,8,0,0},{0,8,0,0},
   {27,64,0,0},{22,64,0,0},{17,64,0,0},{11,64,0,0},{5,64,0,0},{10,28,0,0},{0,10,0,0},{0,9,0,0},{24,64,0,0},{0,5,0,0},{0,20,0,0},
   {9,24,0,0},{22,64,0,0},{8,64,0,0},{23,64,0,0},{0,4,0,0},{7,27,0,0},{3,22,0,0},{18,64,0,0},{0,10,0,0},{0,2,0,0},{6,64,0,0},
   {0,7,0,0},{8,17,0,0},{0,6,0,0},{0,3,0,0},{17,64,0,0},{28,64,0,0},{2,18,0,0},{16,64,0,0},{19,64,0,0},{2,16,0,0},{0,3,0,0},
   {0,2,0,0},{3,22,0,0},{2,11,0,0},{4,15,0,0},{10,19,0,0},{10,64,0,0},{0,5,0,0},{0,8,0,0},{0,9,0,0},{20,64,0,0},{0,8,0,0},
   {8,17,0,0},{26,64,0,0},{0,2,0,0},{0,9,0,0},{9,22,0,0},{8,17,0,0},{0,10,0,0},{0,0,0,0},{2,64,0,0},{15,64,0,0},{8,28,0,0}},
  {{19,38,9,22,6,11,34,30,39,20,23,12,3,10,0,14,58,55,47,60,5,57,56,49,48,51,45,29,28,25,43,41,40,53,63,37,36,62,52,42,24,44,50,27,26,33,32,35,31,18,21,8,13,7,2,1,15,59,17,54,46,61,16,4},
   {34,30,18,38,20,8,13,6,11,23,12,3,10,0,14,58,54,46,61,5,57,56,49,48,51,50,45,44,29,25,43,41,40,53,52,37,36,63,62,42,24,28,27,26,33,32,35,31,19,39,21,9,22,7,2,1,15,17,59,55,47,16,60,4},
   {32,31,18,21,8,13,6,11,48,50,26,35,30,39,9,22,7,2,1,15,17,58,54,46,61,5,56,57,29,28,25,43,41,40,53,63,37,36,62,52,42,24,45,44,49,51,27,33,34,19,38,20,23,12,3,10,0,14,59,55,47,16,60,4},
   {17,14,35,34,51,50,49,48,19,18,33,32,27,26,31,30,25,24,39,38,21,20,23,22,9,8,13,12,41,63,62,40,7,6,3,45,44,2,29,28,1,0,43,42,11,10,53,37,36,52,5,4,59,58,16,15,46,47,54,55,56,57,60,61},
   {36,20,22,8,59,12,6,2,11,5,17,54,46,15,57,61,60,25,24,27,26,33,32,49,48,51,50,35,41,63,62,40,34,19,18,45,44,31,29,28,30,39,43,42,38,21,53,37,52,23,9,13,58,7,3,1,0,10,4,55,47,16,14,56},
   {9,12,3,31,36,52,39,21,23,59,8,7,2,0,10,4,54,46,15,56,60,61,25,24,27,26,33,32,63,62,41,40,49,48,51,45,44,29,28,50,35,43,42,34,19,18,37,53,30,38,20,22,58,13,6,1,11,5,17,55,47,16,14,57},
   {39,21,9,13,3,23,7,0,4,36,53,17,58,46,54,15,60,56,57,27,26,49,48,35,34,51,41,25,24,40,50,45,44,33,32,19,18,29,28,43,42,63,62,31,30,38,20,8,12,2,22,6,1,5,37,11,10,52,59,47,55,16,14,61},
   {10,16,14,52,46,19,18,31,30,39,38,33,32,21,20,9,51,35,49,27,26,48,34,50,8,41,40,25,24,13,45,44,12,3,2,23,22,29,28,43,42,63,62,7,6,1,0,5,4,11,17,15,36,37,53,47,58,59,54,55,60,61,56,57},
   {32,18,39,20,13,2,7,0,37,31,38,9,12,23,6,4,11,17,52,59,47,55,15,60,56,57,41,25,24,40,27,45,44,26,49,48,35,29,28,43,42,63,62,34,51,50,33,19,30,21,8,3,22,1,5,36,10,53,16,58,46,54,14,61},
   {35,33,30,39,20,23,12,3,0,11,32,19,38,9,22,7,2,17,5,15,58,47,54,36,52,60,56,57,27,25,24,41,63,62,40,26,45,44,51,50,49,29,28,43,42,48,34,31,18,21,8,13,6,1,16,10,4,59,55,46,37,53,14,61},
   {16,10,52,37,46,54,58,15,60,56,57,33,35,34,32,31,30,19,18,49,48,51,50,27,26,39,38,21,41,25,24,63,62,40,20,45,44,9,8,23,22,29,43,42,28,13,12,7,6,3,2,1,0,17,11,5,53,59,47,55,36,4,14,61},
   {7,3,1,17,11,5,15,52,58,36,33,32,31,35,34,30,19,18,39,49,48,51,50,27,26,38,21,20,9,25,24,41,63,62,40,8,45,44,23,22,13,29,28,43,42,12,6,2,0,16,10,4,14,53,59,37,54,55,46,47,60,61,56,57},
   {18,20,23,12,3,0,5,42,33,31,19,38,9,22,7,2,11,4,53,16,59,36,46,54,60,56,57,27,26,49,48,51,41,40,50,45,44,63,62,25,29,28,24,35,43,34,32,30,39,21,8,13,6,1,10,17,52,15,58,37,47,55,14,61},
   {42,38,20,8,22,12,6,2,0,10,4,16,52,36,58,46,54,60,56,57,25,24,49,27,26,48,51,50,35,34,33,32,41,40,31,45,44,63,62,30,19,29,28,18,43,39,21,9,23,13,7,3,1,11,5,17,53,15,37,59,47,55,14,61},
   {8,22,12,6,2,0,10,17,53,15,59,37,47,55,60,56,57,35,34,33,25,24,32,27,26,49,48,51,50,31,30,19,41,40,18,39,45,63,62,44,38,29,28,21,43,42,20,9,23,13,7,3,1,11,5,4,16,52,14,58,36,46,54,61},
   {10,16,5,58,52,36,33,32,19,18,31,30,39,35,34,38,21,20,51,50,9,8,13,12,23,22,27,26,49,25,24,45,44,41,40,48,29,63,62,28,7,6,43,42,3,2,1,0,11,17,15,14,4,59,53,37,54,55,46,47,60,61,56,57},
   {3,0,17,31,39,21,9,13,23,7,2,11,16,53,59,37,14,4,46,60,56,57,51,50,35,34,27,26,49,25,24,45,44,41,40,48,63,62,29,28,33,32,43,42,19,18,30,38,20,8,12,22,6,1,10,15,52,58,36,5,54,55,47,61},
   {6,2,0,17,11,16,53,59,37,14,54,46,60,56,57,35,34,33,51,50,32,19,18,31,30,39,27,26,49,25,24,45,44,41,40,48,63,62,29,28,38,21,43,42,20,9,8,13,12,23,22,7,3,1,10,15,52,58,36,5,4,55,47,61},
   {18,30,38,9,12,7,2,52,10,20,13,22,3,53,11,4,16,37,59,14,46,60,56,57,51,50,27,26,25,41,40,24,49,48,45,63,62,44,35,43,42,29,28,34,33,32,19,31,39,21,8,23,6,1,0,5,17,15,36,58,54,55,47,61},
   {2,0,10,4,15,52,58,36,33,32,19,18,31,30,39,38,21,20,35,34,9,49,51,50,48,8,27,26,25,41,40,24,13,12,45,63,62,44,23,43,42,29,28,22,7,6,3,1,11,5,17,16,14,53,59,37,54,55,46,47,60,61,56,57},
   {0,11,22,6,2,53,10,4,16,37,58,14,55,47,61,57,33,32,35,34,19,49,51,50,48,18,27,26,25,41,40,24,31,30,45,63,62,44,29,43,42,28,39,38,21,20,9,8,13,12,23,7,3,1,52,5,17,59,36,15,54,46,60,56},
   {0,4,13,7,23,3,1,10,15,52,58,36,55,17,46,60,56,57,35,51,50,34,33,32,19,18,49,27,26,48,25,24,31,30,41,40,45,63,62,44,29,28,43,42,39,38,21,20,9,8,12,6,22,2,11,5,53,59,37,14,54,16,47,61},
   {9,12,6,22,2,0,10,4,52,58,36,55,17,46,60,56,57,35,51,50,34,33,32,19,18,31,49,27,26,48,25,24,30,39,41,40,45,63,62,44,29,28,43,42,38,21,20,8,13,7,23,3,1,11,5,15,53,59,37,14,54,16,47,61},
   {4,17,36,52,58,33,32,19,18,31,30,39,35,34,38,21,20,9,51,50,8,13,12,7,6,49,27,26,48,25,24,23,22,41,40,45,63,62,44,29,28,43,42,3,2,1,0,11,10,5,15,14,16,37,53,59,54,55,46,47,60,61,56,57}},
  {{3,4,4,4,4,4,4,4},{5,5,5,5,5,5,5,5},{1,1,3,2,2,2,2,3},{6,6,6,7,7,7,7,7},
   {9,9,9,9,9,9,9,9},{4,3,2,3,3,3,3,2},{7,8,8,8,8,8,8,8},{0,0,0,0,0,1,0,1},
   {2,2,1,1,1,0,1,0},{13,13,2,3,3,2,5,3},{10,10,10,10,10,10,10,10},{8,7,7,6,6,6,6,6},
   {6,6,7,6,6,6,7,1},{5,5,8,8,8,8,8,8},{2,10,2,3,3,2,5,3},{12,12,12,12,12,3,3,2},
   {14,14,4,4,4,5,4,5},{4,0,3,2,2,4,2,4},{13,12,3,8,2,4,2,4},{11,11,11,11,11,11,11,11},
   {7,7,9,9,9,9,9,9},{9,11,12,11,10,5,4,11},{8,8,10,10,11,11,11,2},{1,4,10,12,12,3,10,5},
   {1,3,6,7,7,7,6,6},{3,4,5,5,5,1,0,7},{12,13,4,4,4,10,3,7},{4,0,7,6,6,6,7,1},
   {8,7,12,11,10,2,5,3},{14,14,5,2,8,8,8,6},{6,6,2,3,3,5,4,11},{0,9,11,12,12,3,10,5}},
  {{255,255,255,255,255,255,255,255},{255,255,255,255,255,255,255,255},{255,255,255,255,255,255,255,255},{255,255,255,255,255,255,255,255},
   {255,255,255,255,255,255,255,255},{255,255,255,255,255,255,255,255},{255,255,255,255,255,255,255,255},{255,255,255,255,255,255,255,255},
   {255,255,255,255,255,255,255,255},{255,255,5,5,5,2,1,2},{255,255,255,255,255,255,255,255},{255,255,255,255,255,255,255,255},
   {3,3,11,11,11,11,3,7},{1,1,6,6,6,6,6,6},{8,10,9,9,9,9,9,9},{255,255,255,255,255,5,5,5},
   {255,255,0,0,0,1,0,1},{5,7,2,2,2,0,2,0},{9,15,17,13,17,17,17,17},{255,255,255,255,255,255,255,255},
   {6,11,4,4,4,4,4,4},{4,19,15,19,10,16,16,19},{11,6,10,10,19,19,19,15},{24,25,22,31,31,31,31,31},
   {2,5,3,3,3,3,11,11},{0,0,1,1,1,7,7,3},{15,9,16,16,16,10,15,25},{17,17,12,12,12,12,12,12},
   {22,20,21,21,21,14,14,14},{16,16,25,17,13,13,13,24},{12,12,14,14,14,21,21,21},{7,4,19,15,15,15,10,16}},
  {112,113,114,115,116,117,118,119,120,121,122,123,124,125,126,127,128,129,130,131,132,133,134,135,136,137,138,139,140,141,142,143,375,145,146,382,638,149,150,151,152,153,154,155,156,157,158,159,160,161,162,163,164,165,166,167,168,169,170,171,172,173,174,175,176,177,178,179,180,181,182,183,42,39,37,44,74,72,6,3,4,193,373,8,196,631,198,199,200,201,202,203,204,205,206,207,85,11,52,385,641,47,45,15,216,370,9,48,51,46,13,14,86,225,711,56,57,229,230,231,43,0,38,379,635,7,2,239,80,626,75,371,244,372,79,41,380,40,378,251,252,627,628,636,94,20,18,259,260,58,92,24,5,1,629,73,36,269,270,271,272,12,10,377,455,633,83,84,280,281,19,59,60,54,22,23,16,81,53,291,292,88,89,87,296,90,61,34,35,301,302,303,17,77,634,307,49,309,310,311,312,78,76,50,316,317,318,319,25,21,62,323,324,325,55,93,328,329,330,331,332,333,97,335,30,27,338,67,68,63,66,31,95,91,346,347,348,98,350,96,32,353,354,64,65,33,28,29,26,82,362,363,364,365,366,367},
  {511,511,511,511,511,511,511,511,511,511,511,511,511,511,511,511,511,511,511,511,511,511,511,511,511,511,511,511,511,511,511,511,71,511,511,70,70,511,511,511,511,511,511,511,511,511,511,511,511,511,511,511,511,511,511,511,511,511,511,511,511,511,511,511,511,511,511,511,511,511,511,511,256,256,256,256,256,256,256,256,256,511,69,256,511,71,511,511,511,511,511,511,511,511,511,511,257,257,257,65,65,257,257,257,511,58,257,257,257,257,257,257,257,511,87,258,258,511,511,511,256,256,256,67,67,256,256,511,256,58,256,59,511,60,256,256,68,256,66,511,511,59,60,68,258,258,258,511,511,258,258,258,256,256,69,256,256,511,511,511,511,257,257,17,87,17,257,257,511,511,258,258,258,258,258,258,257,257,257,511,511,257,257,257,511,258,258,259,259,511,511,511,257,256,66,511,257,511,511,511,511,256,256,257,511,511,511,511,258,258,258,511,511,511,258,258,511,511,511,511,511,511,258,511,259,259,511,259,259,259,259,259,258,258,511,511,511,258,511,258,259,511,511,259,259,259,259,259,258,257,511,511,511,511,511,511}};

typedef CUresult (*EncodeFn)(CUtensorMap*, CUtensorMapDataType, cuuint32_t, void*, const cuuint64_t*, const cuuint64_t*, const cuuint32_t*,
                             const cuuint32_t*, CUtensorMapInterleave, CUtensorMapSwizzle, CUtensorMapL2promotion, CUtensorMapFloatOOBfill);

void make_map2(EncodeFn enc, CUtensorMap* m, const void* ptr, int rows, int cols, int box_rows) {
  cuuint64_t dim[2] = {(cuuint64_t)cols, (cuuint64_t)rows}, str[1] = {(cuuint64_t)cols * 2};
  cuuint32_t box[2] = {64, (cuuint32_t)box_rows}, es[2] = {1, 1};
  enc(m, CU_TENSOR_MAP_DATA_TYPE_BFLOAT16, 2, const_cast<void*>(ptr), dim, str, box, es, CU_TENSOR_MAP_INTERLEAVE_NONE, CU_TENSOR_MAP_SWIZZLE_128B,
      CU_TENSOR_MAP_L2_PROMOTION_L2_128B, CU_TENSOR_MAP_FLOAT_OOB_FILL_NONE);
}
void make_map3(EncodeFn enc, CUtensorMap* m, const void* ptr, int rows) {
  cuuint64_t dim[3] = {64, (cuuint64_t)rows, 9}, str[2] = {DM * 2, 128};
  cuuint32_t box[3] = {64, 32, 3}, es[3] = {1, 1, 1};
  enc(m, CU_TENSOR_MAP_DATA_TYPE_BFLOAT16, 3, const_cast<void*>(ptr), dim, str, box, es, CU_TENSOR_MAP_INTERLEAVE_NONE, CU_TENSOR_MAP_SWIZZLE_128B,
      CU_TENSOR_MAP_L2_PROMOTION_L2_128B, CU_TENSOR_MAP_FLOAT_OOB_FILL_NONE);
}

void make_map_t(EncodeFn enc, CUtensorMap* m, void* ptr, int width, int cols) {
  cuuint64_t dim[3] = {SEQ / 2, 2, 864}, str[2] = {SEQ * 2, SEQ * 4};
  cuuint32_t box[3] = {(cuuint32_t)width, 2, (cuuint32_t)cols}, es[3] = {1, 1, 1};
  enc(m, CU_TENSOR_MAP_DATA_TYPE_UINT32, 3, ptr, dim, str, box, es, CU_TENSOR_MAP_INTERLEAVE_NONE, cols == 64 ? CU_TENSOR_MAP_SWIZZLE_128B : CU_TENSOR_MAP_SWIZZLE_NONE,
      CU_TENSOR_MAP_L2_PROMOTION_NONE, CU_TENSOR_MAP_FLOAT_OOB_FILL_NONE);
}

int g_mode = -1;

}

extern "C" void kernel_launch(void* const* d_in, const int* in_sizes, int n_in, void* d_out, int out_size) {
  static EncodeFn enc = nullptr;
  static void* t_ptr = nullptr;
  if (!enc) {
    void* fn = nullptr;
    cudaDriverEntryPointQueryResult st;
    cudaGetDriverEntryPoint("cuTensorMapEncodeTiled", &fn, cudaEnableDefault, &st);
    enc = (EncodeFn)fn;
    cudaGetSymbolAddress(&t_ptr, g_S);
    cudaFuncSetAttribute(fused_kernel, cudaFuncAttributeMaxDynamicSharedMemorySize, SMEM_BYTES);
    if (g_mode < 0) {
      cudaLaunchConfig_t cfg = {};
      cfg.gridDim = dim3(2 * NCL); cfg.blockDim = dim3(384); cfg.dynamicSmemBytes = SMEM_BYTES;
      cudaLaunchAttribute at; at.id = cudaLaunchAttributeClusterDimension;
      at.val.clusterDim.x = 2; at.val.clusterDim.y = 1; at.val.clusterDim.z = 1;
      cfg.attrs = &at; cfg.numAttrs = 1;
      int nc = 0;
      g_mode = (cudaOccupancyMaxActiveClusters(&nc, fused_kernel, &cfg) == cudaSuccess && nc >= NCL) ? 1 : 0;
      (void)cudaGetLastError();
    }
  }
  Params p;
  make_map2(enc, &p.map_a[0], d_in[4], SEQ, DC, 128);
  make_map2(enc, &p.map_a[1], d_in[0], SEQ, DM, 128);
  make_map2(enc, &p.map_w[0], d_in[6], DC, 4096, 64);
  make_map2(enc, &p.map_w[1], d_in[7], DC, 4096, 64);
  make_map2(enc, &p.map_w[2], d_in[5], DM, 4096, 64);
  make_map2(enc, &p.map_w[3], d_in[1], DM, 1728, 64);
  make_map3(enc, &p.map_o[0], d_in[8], 4096);
  make_map3(enc, &p.map_o[1], d_in[2], DM);
  make_map_t(enc, &p.map_t[0], t_ptr, 32, 9);
  make_map_t(enc, &p.map_t[1], t_ptr, 40, 9);
  make_map_t(enc, &p.map_t[2], t_ptr, 32, 64);
  p.x = (const __nv_bfloat16*)d_in[0];
  p.gate_w = (const __nv_bfloat16*)d_in[9];
  make_map2(enc, &p.map_out, d_out, SEQ, DM, 64);
  p.out = (__nv_bfloat16*)d_out;
  p.zero = 0;
  auto launch = [&](int phases) {
    p.s = k_sched;
    for (int i = 0; i < NCL; i++) {
      Rec& r = p.s.r[i];
      if (!(phases & 1)) r.n1 = 0;
      if (!(phases & 2)) r.n2 = 0;
      if (!(phases & (p.s.task[i][1] == 64 ? 4 : 32))) r.p3 = 255;
      if (!(phases & 8)) r.bg = 255;
      const int u1 = r.n1 ? 8 + r.n1 * (8 + (r.slab >> 3)) : 0;
      int u2 = 0;
      for (int k = 0; k < r.n2; k++) u2 += 4 * (r.item[k] & 7) + 4;
      r.u1 = (uint8_t)u1; r.u2 = (uint8_t)u2;
      r.rot = (uint8_t)(((u1 % 10 + 1) >> 1) % 5);
      r.x3 = (uint8_t)((r.rot + u2) % 5 & 3);
      r.phases = (uint8_t)phases;
    }
    if (!(phases & 16))
      for (int i = 0; i < 256; i++) { p.s.slot[i >> 3][i & 7] = (uint8_t)(i >> 3); p.s.prev[i >> 3][i & 7] = 255; p.s.qblk[i] = (uint16_t)(S_Q + i); p.s.qdep[i] = 511; }
    fused_kernel<<<2 * NCL, 384, SMEM_BYTES>>>(p);
  };
  if (g_mode == 1) launch(63);
  else { launch(1); launch(10); launch(4); launch(32); }
}
```

```cpp
#include <cuda_runtime.h>
#include <cuda_bf16.h>
#include <cuda.h>
#include <stdint.h>

namespace {

constexpr int SEQ = 2048, DM = 576, DC = 512, NH = 32;
constexpr int NCL = 66;
constexpr uint32_t DESC_HI = 0x40000040u;

constexpr int SM_RING = 0;
constexpr int SM_BUF = 163840;
constexpr int SM_BAR = 229376;
constexpr int B_P1E = 0, B_P2E = 10, B_P3E = 15, B_P2F = 24, B_SF = 32, B_ORD = 36, B_LAD = 40, B_DONE = 41, B_FIN = 48;
constexpr int B_P3F = 56, B_OUT = 61, B_P1F = 64, B_SE = 74, B_QF = 80, B_LA = 84, B_NUM = 88;
constexpr uint64_t B_CNT = 0x11118245000ull;
constexpr int SMEM_BYTES = SM_BAR + B_NUM * 8 + 1024;

constexpr int F_QKVA = 32;
constexpr int F_GATE = 64;
constexpr int F_TS = 68;
constexpr int F_DONE = 65;
constexpr int F_CTX = 96;
constexpr int F_OUT = 96 + 8 * 64;
constexpr int F_KV = F_OUT + 64;
constexpr int F_Q = F_KV + 256;
constexpr int F_RD = F_Q + 256;
constexpr int F_NUM = F_RD + 256;

struct Rec {
  uint8_t slab;
  uint8_t n1, n2;
  uint8_t p3;
  uint8_t bg;
  uint8_t item[11];
  uint8_t last[11];
  uint8_t tile[32];
  uint8_t u1, u2;
  uint8_t rot, x3;
  uint8_t phases;
};
struct Sched {
  Rec r[NCL];
  uint8_t task[NCL][4];
  uint8_t p3_order[24][64];
  uint8_t slot[32][8];
  uint8_t prev[32][8];
  uint16_t qblk[256];
  uint16_t qdep[256];
};

#define SCHED_DECL static const

struct Params {
  CUtensorMap map_a[2];
  CUtensorMap map_w[4];
  CUtensorMap map_o[2];
  CUtensorMap map_t[3];
  CUtensorMap map_out;
  const __nv_bfloat16* x;
  const __nv_bfloat16* gate_w;
  __nv_bfloat16* out;
  int zero;
  alignas(64) Sched s;
};

constexpr int S_T = 0, S_Q = 112, S_K = S_Q + 256, S_V = S_K + 256, S_NUM = S_V + 256;
__device__ __align__(1024) uint8_t g_S[(size_t)S_NUM * 65536];
__device__ __align__(1024) uint8_t g_oA[32 * 576 * 128];
__device__ float g_gate[SEQ];
__device__ int g_flags[F_NUM];
#define PL(i)

__device__ __forceinline__ void mbar_arrive(uint32_t b) { asm volatile("mbarrier.arrive.shared::cta.b64 _, [%0];" ::"r"(b) : "memory"); }
__device__ __forceinline__ void mbar_arrive_cl(uint32_t b, int cnt) {
  asm volatile("mbarrier.arrive.shared::cluster.b64 _, [%0], %1;" ::"r"(b), "r"(cnt) : "memory");
}
__device__ __forceinline__ void mbar_wait(uint32_t b, int par) {
  asm volatile(
      "{\n.reg .pred p;\n.reg .u32 c;\n"
      "mbarrier.try_wait.parity.shared::cta.b64 p, [%0], %1;\n@p bra DN;\nmov.u32 c, 0;\n"
      "LP:\nmbarrier.try_wait.parity.shared::cta.b64 p, [%0], %1;\n@p bra DN;\n"
      "add.u32 c, c, 1;\nsetp.lt.u32 p, c, 4000000;\n@p bra LP;\ntrap;\nDN:\n}" ::"r"(b), "r"(par) : "memory");
}
__device__ __forceinline__ uint32_t mapa(uint32_t a, uint32_t cta) {
  uint32_t r; asm("mapa.shared::cluster.u32 %0, %1, %2;" : "=r"(r) : "r"(a), "r"(cta)); return r;
}
#define ELECT(ins) "{\n.reg .pred e;\nelect.sync _|e, 0xffffffff;\n@e " ins "\n}"
__device__ __forceinline__ void mbar_expect(uint32_t b, int bytes) {
  asm volatile(ELECT("mbarrier.arrive.expect_tx.shared::cta.b64 _, [%0], %1;") ::"r"(b), "r"(bytes) : "memory");
}
__device__ __forceinline__ void mbar_arrive_one(uint32_t b) { asm volatile(ELECT("mbarrier.arrive.shared::cta.b64 _, [%0];") ::"r"(b) : "memory"); }
constexpr uint64_t L2_NORMAL = 0x1000000000000000ull, L2_FIRST = 0x12F0000000000000ull;
__device__ __forceinline__ void bulk_load(uint32_t dst, const void* src, int bytes, uint32_t bar, uint64_t pol = L2_NORMAL) {
  asm volatile(ELECT("cp.async.bulk.shared::cluster.global.mbarrier::complete_tx::bytes.L2::cache_hint [%0], [%1], %2, [%3], %4;") ::"r"(dst), "l"(src), "r"(bytes), "r"(bar), "l"(pol) : "memory");
}
__device__ __forceinline__ void bulk_load_mc(uint32_t dst, const void* src, int bytes, uint32_t bar, uint64_t pol = L2_NORMAL) {
  asm volatile(ELECT("cp.async.bulk.shared::cluster.global.mbarrier::complete_tx::bytes.multicast::cluster.L2::cache_hint [%0], [%1], %2, [%3], %4, %5;") ::"r"(dst), "l"(src), "r"(bytes), "r"(bar), "h"((uint16_t)3), "l"(pol) : "memory");
}
__device__ __forceinline__ void bulk_store(void* dst, uint32_t src, int bytes, uint64_t pol = L2_NORMAL) {
  asm volatile(ELECT("cp.async.bulk.global.shared::cta.bulk_group.L2::cache_hint [%0], [%1], %2, %3;") ::"l"(dst), "r"(src), "r"(bytes), "l"(pol) : "memory");
}
__device__ __forceinline__ void tma2d(uint32_t dst, const CUtensorMap* m, int c0, int c1, uint32_t bar, uint64_t pol = L2_NORMAL) {
  asm volatile(ELECT("cp.async.bulk.tensor.2d.shared::cluster.global.mbarrier::complete_tx::bytes.L2::cache_hint [%0], [%1, {%3, %4}], [%2], %5;") ::"r"(dst), "l"(m), "r"(bar), "r"(c0), "r"(c1), "l"(pol) : "memory");
}
__device__ __forceinline__ void tma2d_mc(uint32_t dst, const CUtensorMap* m, int c0, int c1, uint32_t bar, uint64_t pol = L2_NORMAL) {
  asm volatile(ELECT("cp.async.bulk.tensor.2d.shared::cluster.global.mbarrier::complete_tx::bytes.multicast::cluster.L2::cache_hint [%0], [%1, {%3, %4}], [%2], %5, %6;") ::"r"(dst), "l"(m), "r"(bar), "r"(c0), "r"(c1), "h"((uint16_t)3), "l"(pol) : "memory");
}
__device__ __forceinline__ void tma3d(uint32_t dst, const CUtensorMap* m, int c0, int c1, int c2, uint32_t bar, uint64_t pol = L2_NORMAL) {
  asm volatile(ELECT("cp.async.bulk.tensor.3d.shared::cluster.global.mbarrier::complete_tx::bytes.L2::cache_hint [%0], [%1, {%3, %4, %5}], [%2], %6;") ::"r"(dst), "l"(m), "r"(bar), "r"(c0), "r"(c1), "r"(c2), "l"(pol) : "memory");
}
__device__ __forceinline__ void tma3d_mc(uint32_t dst, const CUtensorMap* m, int c0, int c1, int c2, uint32_t bar, uint64_t pol = L2_NORMAL) {
  asm volatile(ELECT("cp.async.bulk.tensor.3d.shared::cluster.global.mbarrier::complete_tx::bytes.multicast::cluster.L2::cache_hint [%0], [%1, {%3, %4, %5}], [%2], %6, %7;") ::"r"(dst), "l"(m), "r"(bar), "r"(c0), "r"(c1), "r"(c2), "h"((uint16_t)3), "l"(pol) : "memory");
}
__device__ __forceinline__ void tma2d_add(const CUtensorMap* m, uint32_t src, int c0, int c1) {
  asm volatile(ELECT("cp.reduce.async.bulk.tensor.2d.global.shared::cta.add.bulk_group [%0, {%2, %3}], [%1];") ::"l"(m), "r"(src), "r"(c0), "r"(c1) : "memory");
}
__device__ __forceinline__ void tma3d_store(const CUtensorMap* m, uint32_t src, int c0, int c1, int c2, uint64_t pol = L2_NORMAL) {
  asm volatile(ELECT("cp.async.bulk.tensor.3d.global.shared::cta.bulk_group.L2::cache_hint [%0, {%2, %3, %4}], [%1], %5;") ::"l"(m), "r"(src), "r"(c0), "r"(c1), "r"(c2), "l"(pol) : "memory");
}
__device__ __forceinline__ void tma2d_prefetch(const CUtensorMap* m, int c0, int c1, uint64_t pol = L2_NORMAL) {
  asm volatile(ELECT("cp.async.bulk.prefetch.tensor.2d.L2.global.L2::cache_hint [%0, {%1, %2}], %3;") ::"l"(m), "r"(c0), "r"(c1), "l"(pol) : "memory");
}
#define LAG 3
#define HINT 62
#define POL(bit) ((HINT >> (bit)) & 1 ? L2_FIRST : L2_NORMAL)
#define BULK_COMMIT() asm volatile("cp.async.bulk.commit_group;" ::: "memory")
#define BULK_WAIT(n) asm volatile("cp.async.bulk.wait_group %0;" ::"n"(n) : "memory")
#define BULK_WAIT_READ(n) asm volatile("cp.async.bulk.wait_group.read %0;" ::"n"(n) : "memory")
#define FENCE_ASYNC_SMEM() asm volatile("fence.proxy.async.shared::cta;" ::: "memory")
#define FENCE_ASYNC_ALL() asm volatile("fence.proxy.async;" ::: "memory")
#define WG_FENCE() asm volatile("wgmma.fence.sync.aligned;" ::: "memory")
#define WG_COMMIT() asm volatile("wgmma.commit_group.sync.aligned;" ::: "memory")
#define WG_WAIT(n) asm volatile("wgmma.wait_group.sync.aligned %0;" ::"n"(n) : "memory")
__device__ __forceinline__ void bar_sync(int id, int n) { asm volatile("bar.sync %0, %1;" ::"r"(id), "r"(n) : "memory"); }
__device__ __forceinline__ void bar_arrive(int id, int n) { asm volatile("bar.arrive %0, %1;" ::"r"(id), "r"(n) : "memory"); }
__device__ __forceinline__ void cluster_sync() {
  asm volatile("barrier.cluster.arrive.relaxed;\nbarrier.cluster.wait.acquire;" ::: "memory");
}
template <int N> __device__ __forceinline__ void pin(float (&r)[N]) {
#pragma unroll
  for (int i = 0; i < N; i++) asm volatile("" : "+f"(r[i])::"memory");
}
template <int N> __device__ __forceinline__ void pin(uint32_t (&r)[N]) {
#pragma unroll
  for (int i = 0; i < N; i++) asm volatile("" : "+r"(r[i])::"memory");
}
__device__ __forceinline__ uint32_t pack_bf16(float lo, float hi) {
  uint32_t r; asm("cvt.rn.bf16x2.f32 %0, %1, %2;" : "=r"(r) : "f"(hi), "f"(lo)); return r;
}
__device__ __forceinline__ float ex2(float x) { float r; asm("ex2.approx.ftz.f32 %0, %1;" : "=f"(r) : "f"(x)); return r; }
__device__ __forceinline__ void ldsm4(uint32_t a, uint32_t& r0, uint32_t& r1, uint32_t& r2, uint32_t& r3) {
  asm volatile("ldmatrix.sync.aligned.m8n8.x4.shared.b16 {%0,%1,%2,%3}, [%4];" : "=r"(r0), "=r"(r1), "=r"(r2), "=r"(r3) : "r"(a) : "memory");
}
__device__ __forceinline__ void stsm4(uint32_t a, uint32_t r0, uint32_t r1, uint32_t r2, uint32_t r3) {
  asm volatile("stmatrix.sync.aligned.m8n8.x4.shared.b16 [%0], {%1,%2,%3,%4};" ::"r"(a), "r"(r0), "r"(r1), "r"(r2), "r"(r3) : "memory");
}
__device__ __forceinline__ void flag_add(int idx, int v = 1) {
  asm volatile(ELECT("red.release.gpu.global.add.s32 [%0], %1;") ::"l"(g_flags + idx), "r"(v) : "memory");
}
__device__ __forceinline__ void flag_add_rx(int idx) {
  asm volatile(ELECT("red.relaxed.gpu.global.add.s32 [%0], 1;") ::"l"(g_flags + idx) : "memory");
}
template <bool ACQ, int NS = 32> __device__ __forceinline__ void flag_wait(int idx, int target) {
  int n = 0;
  while (true) {
    int v;
    if (ACQ) asm volatile("ld.acquire.gpu.global.s32 %0, [%1];" : "=r"(v) : "l"(g_flags + idx) : "memory");
    else asm volatile("ld.relaxed.gpu.global.s32 %0, [%1];" : "=r"(v) : "l"(g_flags + idx) : "memory");
    if (__all_sync(0xffffffffu, v >= target)) break;
    if (++n > 20000000) __trap();
    __nanosleep(NS);
  }
}
__device__ __forceinline__ int flag_peek(int idx) {
  int v;
  asm volatile("ld.relaxed.gpu.global.s32 %0, [%1];" : "=r"(v) : "l"(g_flags + idx) : "memory");
  return v;
}
__device__ __forceinline__ void mask_wait(uint32_t& ready, int bit, int idx, int target) {
  for (int n = 0; !((ready >> bit) & 1); n++) {
    int v;
    if (n) { __nanosleep(32); if (n > 20000000) __trap(); }
    asm volatile("ld.relaxed.gpu.global.s32 %0, [%1];" : "=r"(v) : "l"(g_flags + idx) : "memory");
    ready = __ballot_sync(0xffffffffu, v >= target);
  }
}
__device__ __forceinline__ uint32_t desc_lo(uint32_t addr, uint32_t lbo) { return ((addr & 0x3FFFFu) >> 4) | ((lbo >> 4) << 16); }
#define PROF(role, i)
#define PROFX(cond, i)
#define PROFB(i)
#define PROFG(i)

template <int TB, int TA = 0> __device__ __forceinline__ void wgmma_ss64(float (&d)[32], uint32_t alo, uint32_t blo, int sd) {
  asm volatile("{\n.reg .pred p;\n.reg .b64 da, db;\n"
    "setp.ne.b32 p, %34, 0;\nmov.b64 da, {%32, %36};\nmov.b64 db, {%33, %36};\n"
    "wgmma.mma_async.sync.aligned.m64n64k16.f32.bf16.bf16 "
    "{%0,%1,%2,%3,%4,%5,%6,%7,%8,%9,%10,%11,%12,%13,%14,%15,%16,%17,%18,%19,%20,%21,%22,%23,"
    "%24,%25,%26,%27,%28,%29,%30,%31}, "
    "da, db, p, 1, 1, %37, %35;\n}\n"
    : "+f"(d[0]),"+f"(d[1]),"+f"(d[2]),"+f"(d[3]),"+f"(d[4]),"+f"(d[5]),"+f"(d[6]),"+f"(d[7]),"+f"(d[8]),"+f"(d[9]),"+f"(d[10]),"+f"(d[11]),
      "+f"(d[12]),"+f"(d[13]),"+f"(d[14]),"+f"(d[15]),"+f"(d[16]),"+f"(d[17]),"+f"(d[18]),"+f"(d[19]),"+f"(d[20]),"+f"(d[21]),"+f"(d[22]),"+f"(d[23]),
      "+f"(d[24]),"+f"(d[25]),"+f"(d[26]),"+f"(d[27]),"+f"(d[28]),"+f"(d[29]),"+f"(d[30]),"+f"(d[31])
    : "r"(alo), "r"(blo), "r"(sd), "n"(TB), "r"(DESC_HI), "n"(TA));
}
template <int TB, int TA = 0> __device__ __forceinline__ void wgmma_ss128(float (&d)[64], uint32_t alo, uint32_t blo, int sd) {
  asm volatile("{\n.reg .pred p;\n.reg .b64 da, db;\n"
    "setp.ne.b32 p, %66, 0;\nmov.b64 da, {%64, %68};\nmov.b64 db, {%65, %68};\n"
    "wgmma.mma_async.sync.aligned.m64n128k16.f32.bf16.bf16 "
    "{%0,%1,%2,%3,%4,%5,%6,%7,%8,%9,%10,%11,%12,%13,%14,%15,%16,%17,%18,%19,%20,%21,%22,%23,"
    "%24,%25,%26,%27,%28,%29,%30,%31,%32,%33,%34,%35,%36,%37,%38,%39,%40,%41,%42,%43,%44,%45,%46,%47,"
    "%48,%49,%50,%51,%52,%53,%54,%55,%56,%57,%58,%59,%60,%61,%62,%63}, "
    "da, db, p, 1, 1, %69, %67;\n}\n"
    : "+f"(d[0]),"+f"(d[1]),"+f"(d[2]),"+f"(d[3]),"+f"(d[4]),"+f"(d[5]),"+f"(d[6]),"+f"(d[7]),"+f"(d[8]),"+f"(d[9]),"+f"(d[10]),"+f"(d[11]),
      "+f"(d[12]),"+f"(d[13]),"+f"(d[14]),"+f"(d[15]),"+f"(d[16]),"+f"(d[17]),"+f"(d[18]),"+f"(d[19]),"+f"(d[20]),"+f"(d[21]),"+f"(d[22]),"+f"(d[23]),
      "+f"(d[24]),"+f"(d[25]),"+f"(d[26]),"+f"(d[27]),"+f"(d[28]),"+f"(d[29]),"+f"(d[30]),"+f"(d[31]),"+f"(d[32]),"+f"(d[33]),"+f"(d[34]),"+f"(d[35]),
      "+f"(d[36]),"+f"(d[37]),"+f"(d[38]),"+f"(d[39]),"+f"(d[40]),"+f"(d[41]),"+f"(d[42]),"+f"(d[43]),"+f"(d[44]),"+f"(d[45]),"+f"(d[46]),"+f"(d[47]),
      "+f"(d[48]),"+f"(d[49]),"+f"(d[50]),"+f"(d[51]),"+f"(d[52]),"+f"(d[53]),"+f"(d[54]),"+f"(d[55]),"+f"(d[56]),"+f"(d[57]),"+f"(d[58]),"+f"(d[59]),
      "+f"(d[60]),"+f"(d[61]),"+f"(d[62]),"+f"(d[63])
    : "r"(alo), "r"(blo), "r"(sd), "n"(TB), "r"(DESC_HI), "n"(TA));
}
template <int TB> __device__ __forceinline__ void wgmma_rs128(float (&d)[64], uint32_t a0, uint32_t a1, uint32_t a2, uint32_t a3, uint32_t blo, int sd) {
  asm volatile("{\n.reg .pred p;\n.reg .b64 db;\n"
    "setp.ne.b32 p, %69, 0;\nmov.b64 db, {%68, %71};\n"
    "wgmma.mma_async.sync.aligned.m64n128k16.f32.bf16.bf16 "
    "{%0,%1,%2,%3,%4,%5,%6,%7,%8,%9,%10,%11,%12,%13,%14,%15,%16,%17,%18,%19,%20,%21,%22,%23,"
    "%24,%25,%26,%27,%28,%29,%30,%31,%32,%33,%34,%35,%36,%37,%38,%39,%40,%41,%42,%43,%44,%45,%46,%47,"
    "%48,%49,%50,%51,%52,%53,%54,%55,%56,%57,%58,%59,%60,%61,%62,%63}, "
    "{%64,%65,%66,%67}, db, p, 1, 1, %70;\n}\n"
    : "+f"(d[0]),"+f"(d[1]),"+f"(d[2]),"+f"(d[3]),"+f"(d[4]),"+f"(d[5]),"+f"(d[6]),"+f"(d[7]),"+f"(d[8]),"+f"(d[9]),"+f"(d[10]),"+f"(d[11]),
      "+f"(d[12]),"+f"(d[13]),"+f"(d[14]),"+f"(d[15]),"+f"(d[16]),"+f"(d[17]),"+f"(d[18]),"+f"(d[19]),"+f"(d[20]),"+f"(d[21]),"+f"(d[22]),"+f"(d[23]),
      "+f"(d[24]),"+f"(d[25]),"+f"(d[26]),"+f"(d[27]),"+f"(d[28]),"+f"(d[29]),"+f"(d[30]),"+f"(d[31]),"+f"(d[32]),"+f"(d[33]),"+f"(d[34]),"+f"(d[35]),
      "+f"(d[36]),"+f"(d[37]),"+f"(d[38]),"+f"(d[39]),"+f"(d[40]),"+f"(d[41]),"+f"(d[42]),"+f"(d[43]),"+f"(d[44]),"+f"(d[45]),"+f"(d[46]),"+f"(d[47]),
      "+f"(d[48]),"+f"(d[49]),"+f"(d[50]),"+f"(d[51]),"+f"(d[52]),"+f"(d[53]),"+f"(d[54]),"+f"(d[55]),"+f"(d[56]),"+f"(d[57]),"+f"(d[58]),"+f"(d[59]),
      "+f"(d[60]),"+f"(d[61]),"+f"(d[62]),"+f"(d[63])
    : "r"(a0), "r"(a1), "r"(a2), "r"(a3), "r"(blo), "r"(sd), "n"(TB), "r"(DESC_HI));
}
template <int TB, int TA = 0> __device__ __forceinline__ void wgmma_ss192(float (&d)[96], uint32_t alo, uint32_t blo, int sd) {
  asm volatile("{\n.reg .pred p;\n.reg .b64 da, db;\n"
    "setp.ne.b32 p, %98, 0;\nmov.b64 da, {%96, %100};\nmov.b64 db, {%97, %100};\n"
    "wgmma.mma_async.sync.aligned.m64n192k16.f32.bf16.bf16 "
    "{%0,%1,%2,%3,%4,%5,%6,%7,%8,%9,%10,%11,%12,%13,%14,%15,%16,%17,%18,%19,%20,%21,%22,%23,"
    "%24,%25,%26,%27,%28,%29,%30,%31,%32,%33,%34,%35,%36,%37,%38,%39,%40,%41,%42,%43,%44,%45,%46,%47,"
    "%48,%49,%50,%51,%52,%53,%54,%55,%56,%57,%58,%59,%60,%61,%62,%63,%64,%65,%66,%67,%68,%69,%70,%71,"
    "%72,%73,%74,%75,%76,%77,%78,%79,%80,%81,%82,%83,%84,%85,%86,%87,%88,%89,%90,%91,%92,%93,%94,%95}, "
    "da, db, p, 1, 1, %101, %99;\n}\n"
    : "+f"(d[0]),"+f"(d[1]),"+f"(d[2]),"+f"(d[3]),"+f"(d[4]),"+f"(d[5]),"+f"(d[6]),"+f"(d[7]),"+f"(d[8]),"+f"(d[9]),"+f"(d[10]),"+f"(d[11]),
      "+f"(d[12]),"+f"(d[13]),"+f"(d[14]),"+f"(d[15]),"+f"(d[16]),"+f"(d[17]),"+f"(d[18]),"+f"(d[19]),"+f"(d[20]),"+f"(d[21]),"+f"(d[22]),"+f"(d[23]),
      "+f"(d[24]),"+f"(d[25]),"+f"(d[26]),"+f"(d[27]),"+f"(d[28]),"+f"(d[29]),"+f"(d[30]),"+f"(d[31]),"+f"(d[32]),"+f"(d[33]),"+f"(d[34]),"+f"(d[35]),
      "+f"(d[36]),"+f"(d[37]),"+f"(d[38]),"+f"(d[39]),"+f"(d[40]),"+f"(d[41]),"+f"(d[42]),"+f"(d[43]),"+f"(d[44]),"+f"(d[45]),"+f"(d[46]),"+f"(d[47]),
      "+f"(d[48]),"+f"(d[49]),"+f"(d[50]),"+f"(d[51]),"+f"(d[52]),"+f"(d[53]),"+f"(d[54]),"+f"(d[55]),"+f"(d[56]),"+f"(d[57]),"+f"(d[58]),"+f"(d[59]),
      "+f"(d[60]),"+f"(d[61]),"+f"(d[62]),"+f"(d[63]),"+f"(d[64]),"+f"(d[65]),"+f"(d[66]),"+f"(d[67]),"+f"(d[68]),"+f"(d[69]),"+f"(d[70]),"+f"(d[71]),
      "+f"(d[72]),"+f"(d[73]),"+f"(d[74]),"+f"(d[75]),"+f"(d[76]),"+f"(d[77]),"+f"(d[78]),"+f"(d[79]),"+f"(d[80]),"+f"(d[81]),"+f"(d[82]),"+f"(d[83]),
      "+f"(d[84]),"+f"(d[85]),"+f"(d[86]),"+f"(d[87]),"+f"(d[88]),"+f"(d[89]),"+f"(d[90]),"+f"(d[91]),"+f"(d[92]),"+f"(d[93]),"+f"(d[94]),"+f"(d[95])
    : "r"(alo), "r"(blo), "r"(sd), "n"(TB), "r"(DESC_HI), "n"(TA));
}

struct Ctx {
  uint32_t sm;
  uint32_t bar;
  uint32_t rbar;
  int cl, rank, wg, warp, lane, phases;
};
__device__ __forceinline__ void release(const Ctx& c, int b, int cnt = 1) {
  if (c.lane < 2) mbar_arrive_cl(c.rbar + b * 8, cnt);
}
#define HK 5
#define NPRO 6
#define ZLEAD 14
#define PFM 7
#define PF1 1
constexpr float SM_SCALE = 0.08838834764831845f * 1.4426950408889634f;
constexpr float SM_HI = 1.8446744e19f, SM_LO = 5.4210109e-20f;
constexpr int ORDER = 1;

__device__ __forceinline__ void stage_tile(const float (&a)[64], uint32_t buf, const Ctx& c, float s0, float s1) {
  const int row = (c.lane & 7) + ((c.lane >> 3) & 1) * 8;
  const uint32_t base = buf + (c.warp * 16 + row) * 128 + (((c.lane >> 4) ^ (row & 7)) << 4);
#pragma unroll
  for (int i = 0; i < 8; i++)
    stsm4((base ^ ((i & 3) << 5)) + (i >> 2) * 8192, pack_bf16(a[8 * i] * s0, a[8 * i + 1] * s0), pack_bf16(a[8 * i + 2] * s1, a[8 * i + 3] * s1),
          pack_bf16(a[8 * i + 4] * s0, a[8 * i + 5] * s0), pack_bf16(a[8 * i + 6] * s1, a[8 * i + 7] * s1));
}

__device__ __forceinline__ void p1_epilogue(const Params& p, const Ctx& c, const float (&acc)[64], int t, int type) {
  const int tile = p.s.r[c.cl].tile[t] & 63, b = c.wg * 2 + 1;
  mbar_wait(c.bar + (B_SE + b) * 8, (t & 1) ^ 1);
  if (type && tile >= 32) {
    const int r = 2 * (c.lane & 3) + ((c.lane >> 2) & 1);
    const uint32_t dst = c.sm + SM_BUF + b * 16384 + r * 128 + (((c.warp * 2) ^ r) << 4) + (c.lane >> 3) * 4;
#pragma unroll
    for (int i = 0; i < 16; i++) {
      asm volatile("st.shared.u32 [%0], %1;" ::"r"(dst + i * 1024), "r"(pack_bf16(acc[4 * i], acc[4 * i + 1])) : "memory");
      asm volatile("st.shared.u32 [%0], %1;" ::"r"((dst ^ 16) + i * 1024), "r"(pack_bf16(acc[4 * i + 2], acc[4 * i + 3])) : "memory");
    }
  } else {
    if (type) stage_tile(acc, c.sm + SM_BUF + b * 16384, c, SM_SCALE, SM_SCALE);
    else stage_tile(acc, c.sm + SM_BUF + b * 16384, c, 1.f, 1.f);
  }
  FENCE_ASYNC_SMEM();
  __syncwarp();
  if (c.lane == 0) mbar_arrive(c.bar + (B_SF + b) * 8);
}

__device__ __forceinline__ void p1_consumer(const Params& p, const Ctx& c) {
  const int n = p.s.r[c.cl].n1;
  const int type = p.s.r[c.cl].slab >> 3;
  const uint32_t bdesc = desc_lo(c.sm + SM_RING, 8192), adesc = desc_lo(c.sm + SM_BUF + 32768 + c.wg * 8192, 16);
  uint32_t A[128];
  float acc[64] = {};
  int slot = 0, par = 0;
  auto next = [&]() { if (++slot == 10) { slot = 0; par ^= 1; } };
  {
    const int row = (c.lane & 7) + ((c.lane >> 3) & 1) * 8;
    const uint32_t base = c.sm + SM_RING + (c.wg * 64 + c.warp * 16 + row) * 128 + (((c.lane >> 4) ^ (row & 7)) << 4);
    if (c.wg == 1) bar_sync(ORDER + 1, 256);
    int pa = -1, pb = -1;
    if (type) {
      mbar_wait(c.bar + B_P1F * 8, 0);
      WG_FENCE();
#pragma unroll
      for (int kk = 0; kk < 4; kk++) wgmma_ss128<1>(acc, adesc + kk * 2, bdesc + kk * 128, kk != 0);
      WG_COMMIT();
      pb = 0; slot = 1;
    }
#pragma unroll
    for (int kb = 0; kb < 8; kb++) {
      const int sa = slot;
      mbar_wait(c.bar + (B_P1F + slot) * 8, par);
      if (kb == 0) PROF(c.wg, 5);
      next();
      mbar_wait(c.bar + (B_P1F + slot) * 8, par);
      PROF(c.wg, 6 + 2 * kb);
      WG_FENCE();
#pragma unroll
      for (int kk = 0; kk < 4; kk++)
        wgmma_ss128<1>(acc, desc_lo(c.sm + SM_RING + c.wg * 8192, 16) + sa * 1024 + kk * 2, bdesc + slot * 1024 + kk * 128, (kb | kk) != 0 ? 1 : type);
      WG_COMMIT();
      if (kb == 1 && c.wg == 0) bar_arrive(ORDER + 1, 256);
#pragma unroll
      for (int kk = 0; kk < 4; kk++) ldsm4((base ^ (kk << 5)) + sa * 16384, A[kb * 16 + kk * 4], A[kb * 16 + kk * 4 + 1], A[kb * 16 + kk * 4 + 2], A[kb * 16 + kk * 4 + 3]);
      WG_WAIT(1);
      if (kb > 0) release(c, B_P1E + pa);
      if (kb > 0 || pb >= 0) release(c, B_P1E + pb);
      pa = sa; pb = slot;
      next();
    }
    WG_WAIT(0);
    __syncwarp();
    release(c, B_P1E + pa);
    release(c, B_P1E + pb);
    pin(acc);
    PROF(c.wg, 1);
    p1_epilogue(p, c, acc, 0, type);
    PROF(c.wg, 2);
  }
  for (int t = 1; t < n; t++) {
    bar_sync(ORDER + c.wg, 256);
    int prev1 = -1, prev2 = -1;
    if (type) {
      mbar_wait(c.bar + (B_P1F + slot) * 8, par);
      WG_FENCE();
#pragma unroll
      for (int kk = 0; kk < 4; kk++) wgmma_ss128<1>(acc, adesc + kk * 2, bdesc + slot * 1024 + kk * 128, kk != 0);
      WG_COMMIT();
      prev1 = slot;
      next();
    }
#pragma unroll
    for (int kb = 0; kb < 8; kb++) {
      mbar_wait(c.bar + (B_P1F + slot) * 8, par);
      WG_FENCE();
      const uint32_t d = bdesc + slot * 1024;
#pragma unroll
      for (int kk = 0; kk < 4; kk++)
        wgmma_rs128<1>(acc, A[kb * 16 + kk * 4], A[kb * 16 + kk * 4 + 1], A[kb * 16 + kk * 4 + 2], A[kb * 16 + kk * 4 + 3], d + kk * 128, (kb | kk) != 0 ? 1 : type);
      WG_COMMIT();
      if (kb == HK) {
        if (t + 1 < n || c.wg == 0) bar_arrive(ORDER + (c.wg ^ 1), 256);
      }
      if (kb > 0) { WG_WAIT(2); if (kb > 1 || prev2 >= 0) release(c, B_P1E + prev2); }
      prev2 = prev1; prev1 = slot;
      next();
    }
    WG_WAIT(1);
    release(c, B_P1E + prev2);
    WG_WAIT(0);
    pin(acc);
    release(c, B_P1E + prev1);
    p1_epilogue(p, c, acc, t, type);
    PROF(c.wg, 3);
  }
}

__device__ __forceinline__ void p1_producer(const Params& p, const Ctx& c) {
  const int n = p.s.r[c.cl].n1;
  const int type = p.s.r[c.cl].slab >> 3, grp = p.s.r[c.cl].slab & 7;
  int slot = NPRO % 10, par = NPRO < 10;
#pragma unroll 1
  for (int t = 0; t < n; t++) {
    const int tile = p.s.r[c.cl].tile[t] & 63;
    const CUtensorMap* m = &p.map_w[type * 2 + (tile >> 5)];
    const int n0 = (tile & 31) * 128 + c.rank * 64;
    const int ptile = p.s.r[c.cl].tile[t + PF1 < n ? t + PF1 : t];
    const CUtensorMap* pm = &p.map_w[type * 2 + ((ptile >> 5) & 1)];
    if (t == 7 && (c.phases & 16)) flag_wait<true>(F_GATE, 256);
#pragma unroll 1
    for (int kb = t ? -type : (NPRO - type) >> 1; kb < 8; kb++) {
      if (t == 0 && 2 * kb + type >= NPRO) {
        mbar_wait(c.bar + (B_P1E + slot) * 8, par);
        mbar_expect(c.bar + (B_P1F + slot) * 8, 16384);
        tma2d(c.sm + SM_RING + slot * 16384, &p.map_a[type], kb * 64, grp * 256 + c.rank * 128, c.bar + (B_P1F + slot) * 8);
        if (++slot == 10) { slot = 0; par ^= 1; }
      }
      mbar_wait(c.bar + (B_P1E + slot) * 8, par);
      mbar_expect(c.bar + (B_P1F + slot) * 8, 16384);
      tma2d_mc(c.sm + SM_RING + slot * 16384 + c.rank * 8192, m, n0, kb < 0 ? 512 : kb * 64, c.bar + (B_P1F + slot) * 8);
      if (t == 0 && kb == 1) PROF(2, 61);
      if (t == 0 && kb == 3) PROF(2, 62);
      if (t + PF1 < n && t > 0 && ((ptile & 64) || ((ptile & 128) && ((kb ^ grp) & PFM) == 0))) tma2d_prefetch(pm, (ptile & 31) * 128 + c.rank * 64, kb < 0 ? 512 : kb * 64);
      if (++slot == 10) { slot = 0; par ^= 1; }
    }
  }
}

__device__ __forceinline__ void wait_kv_dead(const Ctx& c, int h, int g) {
  if (g >= 2) flag_wait<false>(F_RD + h * 8 + g, 8 - g);
  else flag_wait<false>(F_CTX + max(c.lane & 7, g) * 64 + h, 4);
}
__device__ __forceinline__ int p1_storer(const Params& p, const Ctx& c) {
  const int n = p.s.r[c.cl].n1;
  const int type = p.s.r[c.cl].slab >> 3, grp = p.s.r[c.cl].slab & 7;
  for (int i = 0; i < 2 * n; i++) {
    const int t = i >> 1, w = i & 1, b = w * 2 + 1;
    const int tile = p.s.r[c.cl].tile[t] & 63;
    mbar_wait(c.bar + (B_SF + b) * 8, t & 1);
    const uint32_t src = c.sm + SM_BUF + b * 16384;
    int f = (type ? F_Q : F_KV) + (tile & 31) * 8 + grp;
    if (type == 0) {
      const int prev = p.s.prev[tile & 31][grp];
      if (prev != 255 && w == 0) wait_kv_dead(c, prev, grp);
      uint8_t* dst = g_S + (size_t)(S_K + ((tile & 32) + p.s.slot[tile & 31][grp]) * 8 + grp) * 65536 + c.rank * 32768 + w * 8192;
      bulk_store(dst, src, 8192);
      bulk_store(dst + 16384, src + 8192, 8192);
    } else if (tile < 32) {
      const int dep = p.s.qdep[tile * 8 + grp];
      if (dep != 511 && w == 0) {
        if (dep < 256) wait_kv_dead(c, dep >> 3, dep & 7);
        else flag_wait<false>(F_TS + dep - 256, 128);
      }
      bulk_store(g_S + (size_t)p.s.qblk[tile * 8 + grp] * 65536 + (c.rank * 2 + w) * 16384, src, 16384);
    } else {
      tma3d_store(&p.map_t[2], src, (grp * 4 + c.rank * 2 + w) * 32, 0, (tile - 32) * 64);
      f = F_QKVA + grp * 4 + ((0xE4390900u >> (2 * (tile - 30))) & 3);
    }
    BULK_COMMIT();
    BULK_WAIT(0);
    mbar_arrive_one(c.bar + (B_SE + b) * 8);
    if (i == 2 * n - 1) return f;
    if (w) flag_add(f, 2);
  }
  return -1;
}

__device__ __forceinline__ int p2_buf(int w, int i) { return w * 2 + (i & 1); }
__device__ __forceinline__ int p2_blk(int rank, int w, int i) { return ((i ^ w) & 1) == 0 ? 3 - rank : rank; }

template <int N>
__device__ __forceinline__ void row_max(const float (&s)[N], float& m0, float& m1) {
  float a0 = fmaxf(s[0], s[1]), a1 = fmaxf(s[2], s[3]);
#pragma unroll
  for (int i = 1; i < N / 4; i++) {
    m0 = fmaxf(m0, s[4 * i]); a0 = fmaxf(a0, s[4 * i + 1]);
    m1 = fmaxf(m1, s[4 * i + 2]); a1 = fmaxf(a1, s[4 * i + 3]);
  }
  m0 = fmaxf(m0, a0); m1 = fmaxf(m1, a1);
  m0 = fmaxf(m0, __shfl_xor_sync(0xffffffffu, m0, 1));
  m1 = fmaxf(m1, __shfl_xor_sync(0xffffffffu, m1, 1));
  m0 = fmaxf(m0, __shfl_xor_sync(0xffffffffu, m0, 2));
  m1 = fmaxf(m1, __shfl_xor_sync(0xffffffffu, m1, 2));
}
template <bool SUB, int N>
__device__ __forceinline__ void row_exp(const float (&s)[N], uint32_t (&P)[32], float m0, float m1, float& t0, float& t1) {
  float u0 = 0.f, u1 = 0.f;
  t0 = t1 = 0.f;
#pragma unroll
  for (int i = 0; i < N / 4; i++) {
    const float e0 = ex2(SUB ? s[4 * i] - m0 : s[4 * i]), e1 = ex2(SUB ? s[4 * i + 1] - m0 : s[4 * i + 1]);
    const float e2 = ex2(SUB ? s[4 * i + 2] - m1 : s[4 * i + 2]), e3 = ex2(SUB ? s[4 * i + 3] - m1 : s[4 * i + 3]);
    if (i == 0) { t0 = e0; u0 = e1; t1 = e2; u1 = e3; }
    else { t0 += e0; u0 += e1; t1 += e2; u1 += e3; }
    P[2 * i] = pack_bf16(e0, e1);
    P[2 * i + 1] = pack_bf16(e2, e3);
  }
#pragma unroll
  for (int i = N / 2; i < 32; i++) P[i] = 0;
  pin(P);
  t0 += u0; t1 += u1;
}
template <int N>
__device__ __forceinline__ void causal_mask(float (&s)[N], int thr) {
#pragma unroll
  for (int i = 0; i < 8; i++) {
    if (8 * i > thr) s[N - 32 + 4 * i] = -INFINITY;
    if (8 * i + 1 > thr) s[N - 32 + 4 * i + 1] = -INFINITY;
    if (8 * i - 8 > thr) s[N - 32 + 4 * i + 2] = -INFINITY;
    if (8 * i - 7 > thr) s[N - 32 + 4 * i + 3] = -INFINITY;
  }
}
__device__ __forceinline__ void issue_qk(float (&s)[32], uint32_t qd, uint32_t kd) {
  WG_FENCE();
#pragma unroll
  for (int kk = 0; kk < 8; kk++) wgmma_ss64<0>(s, qd + (kk >> 2) * 512 + (kk & 3) * 2, kd + (kk >> 2) * 1024 + (kk & 3) * 2, kk != 0);
  WG_COMMIT();
}
__device__ __forceinline__ void issue_qk(float (&s)[64], uint32_t qd, uint32_t kd) {
  WG_FENCE();
#pragma unroll
  for (int kk = 0; kk < 8; kk++) wgmma_ss128<0>(s, qd + (kk >> 2) * 512 + (kk & 3) * 2, kd + (kk >> 2) * 1024 + (kk & 3) * 2, kk != 0);
  WG_COMMIT();
}
template <int NK>
__device__ __forceinline__ void issue_pv(float (&o)[64], const uint32_t (&P)[32], uint32_t vd, int acc) {
  WG_FENCE();
#pragma unroll
  for (int kk = 0; kk < NK; kk++) wgmma_rs128<1>(o, P[4 * kk], P[4 * kk + 1], P[4 * kk + 2], P[4 * kk + 3], vd + kk * 128, kk != 0 ? 1 : acc);
  WG_COMMIT();
}
__device__ __forceinline__ void stage_done(const Ctx& c, int b) {
  FENCE_ASYNC_SMEM();
  __syncwarp();
  if (c.lane == 0) mbar_arrive(c.bar + (B_SF + b) * 8);
}
__device__ __forceinline__ void p2_epilogue(const float (&o)[64], float s0, float s1, const Ctx& c, int b) {
  stage_tile(o, c.sm + SM_BUF + b * 16384, c, s0, s1);
  stage_done(c, b);
}

struct P2State {
  float m0, m1, l0, l1;
  bool shift;
  float e0, e1;
  int ks;
  int wi, ai;
  uint32_t wb, ab;
  uint32_t qd;
};
#define PROFZ()
__device__ __forceinline__ int wrap5(int q) { return q >= 5 ? q - 5 : q; }
__device__ __forceinline__ void turn_wait(uint32_t ring, int i) { mbar_wait(ring + (i & 3) * 8, (i >> 2) & 1); }
__device__ __forceinline__ void turn_pass(const Ctx& c, uint32_t ring, int i) { if (c.lane == 0) mbar_arrive(ring + (i & 3) * 8); }
__device__ __forceinline__ void p2_scales(P2State& z) {
  float l0 = z.l0, l1 = z.l1;
  l0 += __shfl_xor_sync(0xffffffffu, l0, 1);
  l1 += __shfl_xor_sync(0xffffffffu, l1, 1);
  l0 += __shfl_xor_sync(0xffffffffu, l0, 2);
  l1 += __shfl_xor_sync(0xffffffffu, l1, 2);
  asm("rcp.approx.ftz.f32 %0, %1;" : "=f"(z.e0) : "f"(l0));
  asm("rcp.approx.ftz.f32 %0, %1;" : "=f"(z.e1) : "f"(l1));
}
template <int N>
__device__ __forceinline__ void p2_first(const Ctx& c, P2State& z, float (&o)[64], uint32_t (&Pc)[32], uint32_t (&Pn)[32],
                                         int ks, int vs, int cnt, int acc) {
  float s[N] = {};
  issue_qk(s, z.qd, desc_lo(c.sm + SM_RING, 16) + ks * 2048);
  if (vs >= 0) {
    p2_scales(z);
    issue_pv<8>(o, Pc, desc_lo(c.sm + SM_RING, 16384) + vs * 2048, acc);
  } else {
    WG_COMMIT();
  }
  mbar_expect(z.ab + (z.ai++ & 3) * 8, cnt == 1 ? 8192 : 0);
  PROFZ();
  WG_WAIT(1);
  PROFZ();
  pin(s);
  release(c, B_P2E + ks, cnt);
  causal_mask(s, c.warp * 16 + (c.lane >> 2) - 2 * (c.lane & 3));
  z.m0 = z.m1 = 0.f;
  row_exp<false>(s, Pn, 0.f, 0.f, z.l0, z.l1);
  z.shift = __any_sync(0xffffffffu, !(z.l0 + z.l1 <= SM_HI) || ((c.lane & 3) == 0 && !(fminf(z.l0, z.l1) >= SM_LO)));
  if (__builtin_expect(z.shift, 0)) {
    z.m0 = z.m1 = -INFINITY;
    row_max(s, z.m0, z.m1);
    row_exp<true>(s, Pn, z.m0, z.m1, z.l0, z.l1);
  }
  WG_WAIT(0);
  pin(o);
  if (vs >= 0) release(c, B_P2E + vs, 1);
}

template <bool SECOND>
__device__ __forceinline__ void p2_turn(const Ctx& c, P2State& z, float (&o)[64], uint32_t (&Pc)[32], uint32_t (&Pn)[32],
                                        int eb = -1, bool half = false, int vcnt = 1) {
  float s[64] = {};
  const int ks = z.ks, vs = wrap5(ks + 1);
  PROFZ();
  turn_wait(z.wb, z.wi++);
  PROFZ();
  issue_qk(s, z.qd, desc_lo(c.sm + SM_RING, 16) + ks * 2048);
  const uint32_t vd = desc_lo(c.sm + SM_RING, 16384) + vs * 2048;
  if (SECOND) {
    if (eb >= 0) stage_tile(o, c.sm + SM_BUF + eb * 16384, c, z.e0, z.e1);
    if (half) issue_pv<4>(o, Pc, vd, 0); else issue_pv<8>(o, Pc, vd, 0);
  } else {
    issue_pv<8>(o, Pc, vd, 1);
  }
  turn_pass(c, z.ab, z.ai++);
  if (SECOND) { if (eb >= 0) stage_done(c, eb); }
  PROFZ();
  z.ks = wrap5(ks + 2);
  WG_WAIT(1);
  PROFZ();
  pin(s);
  release(c, B_P2E + ks, 1);
  float t0, t1, a0 = 1.f, a1 = 1.f;
  row_exp<false>(s, Pn, 0.f, 0.f, t0, t1);
  z.shift = __any_sync(0xffffffffu, z.shift || !(t0 + t1 <= SM_HI));
  const bool redo = z.shift;
  if (__builtin_expect(redo, 0)) {
    float n0 = z.m0, n1 = z.m1;
    row_max(s, n0, n1);
    a0 = ex2(z.m0 - n0); a1 = ex2(z.m1 - n1);
    z.m0 = n0; z.m1 = n1;
    z.l0 *= a0; z.l1 *= a1;
    row_exp<true>(s, Pn, z.m0, z.m1, t0, t1);
  }
  WG_WAIT(0);
  pin(o);
  release(c, B_P2E + vs, vcnt);
  if (__builtin_expect(redo, 0)) {
#pragma unroll
    for (int i = 0; i < 16; i++) { o[4 * i] *= a0; o[4 * i + 1] *= a0; o[4 * i + 2] *= a1; o[4 * i + 3] *= a1; }
  }
  z.l0 += t0; z.l1 += t1;
}
__device__ __forceinline__ void copy_p(uint32_t (&d)[32], const uint32_t (&s)[32], int zero) {
#pragma unroll
  for (int i = 0; i < 32; i++) asm volatile("add.s32 %0, %1, %2;" : "=r"(d[i]) : "r"(s[i]), "r"(zero));
}

__device__ __forceinline__ void p2_consumer(const Params& p, const Ctx& c, int rot) {
  const int nit = p.s.r[c.cl].n2;
  const uint32_t fring = c.bar + B_P2F * 8, oring = c.bar + B_ORD * 8;
  float o[64] = {};
  uint32_t Pa[32] = {}, Pb[32] = {};
  P2State z;
  z.e0 = z.e1 = z.l0 = z.l1 = 0.f; z.ks = rot; z.shift = false;
  int acc = 0, n = 0;
  for (int it = 0; it < nit; it++) {
    const int j = p.s.r[c.cl].item[it] & 7, blk = p2_blk(c.rank, c.wg, it);
    const int lng = ((it ^ c.wg) & 1) ^ 1;
    z.qd = desc_lo(c.sm + SM_BUF, 16) + p2_buf(c.wg, it) * 1024;
    if (lng) { z.wb = oring; z.wi = n - it; z.ab = fring; z.ai = n + 1; }
    else { z.wb = fring; z.wi = n + 2; z.ab = oring; z.ai = n - it; }
    PROFZ();
    mbar_wait(c.bar + (B_QF + p2_buf(c.wg, it)) * 8, (it >> 1) & 1);
    turn_wait(fring, n + 1 - lng);
    PROFZ();
    const int vs = it ? wrap5(z.ks + 1) : -1, ks = lng ? z.ks : wrap5(z.ks + (it ? 2 : 1));
    if (blk & 1) p2_first<64>(c, z, o, Pa, Pb, ks, vs, 1 + lng, acc);
    else p2_first<32>(c, z, o, Pa, Pb, ks, vs, 1 + lng, acc);
    z.ks = wrap5(ks + (it == 0 && lng ? 1 : 2));
    PROF(c.wg, 24 + it);
    n += 2 * j + 2;
    int left = 2 * j + lng;
    acc = left != 0;
    if (left == 0) { copy_p(Pa, Pb, p.zero); continue; }
    p2_turn<true>(c, z, o, Pb, Pa, it > 0 ? p2_buf(c.wg, it - 1) : -1, !(blk & 1), 1 + lng);
    while (--left > 0) {
      p2_turn<false>(c, z, o, Pa, Pb);
      if (--left == 0) { copy_p(Pa, Pb, p.zero); break; }
      p2_turn<false>(c, z, o, Pb, Pa);
    }
  }
  {
    if (!acc && nit > 1) p2_epilogue(o, z.e0, z.e1, c, p2_buf(c.wg, nit));
    turn_wait(z.wb, z.wi);
    issue_pv<8>(o, Pa, desc_lo(c.sm + SM_RING, 16384) + z.ks * 2048, acc);
    if (((nit - 1) ^ c.wg) & 1) turn_pass(c, z.ab, z.ai);
    p2_scales(z);
    WG_WAIT(0);
    pin(o);
    release(c, B_P2E + z.ks);
    p2_epilogue(o, z.e0, z.e1, c, p2_buf(c.wg, nit - 1));
    PROF(c.wg, 24 + nit);
  }
}

__device__ __forceinline__ void p2_load_q(const Params& p, const Ctx& c, int it, int w) {
  const int item = p.s.r[c.cl].item[it], b = p2_buf(w, it);
  mbar_expect(c.bar + (B_QF + b) * 8, 16384);
  bulk_load(c.sm + SM_BUF + b * 16384, g_S + (size_t)p.s.qblk[item] * 65536 + p2_blk(c.rank, w, it) * 16384, 16384, c.bar + (B_QF + b) * 8, POL(4));
}
__device__ __forceinline__ void wait_p1_free(const Ctx& c, int u1, int s) {
  mbar_wait(c.bar + (B_P1E + 2 * s) * 8, ((u1 - 1 - 2 * s) / 10) & 1);
  mbar_wait(c.bar + (B_P1E + 2 * s + 1) * 8, ((u1 - 2 - 2 * s) / 10) & 1);
}
__device__ __forceinline__ void p2_producer(const Params& p, const Ctx& c, int u1, int rot) {
  const int nit = p.s.r[c.cl].n2;
  int slot = rot, cnt = 0, par = 1, n = 0;
  const uint8_t* pv = nullptr;
  bool pl = false;
  auto load = [&](const uint8_t* src, int expect, uint32_t fb, bool last) {
    if (cnt < 5) {
      if (u1) {
        wait_p1_free(c, u1, slot);
        if (cnt == 0) p2_load_q(p, c, 0, 1);
      }
      cnt++;
    } else {
      if (slot == rot) par ^= 1;
      mbar_wait(c.bar + (B_P2E + slot) * 8, par);
    }
    if (expect) mbar_expect(fb, expect);
    bulk_load_mc(c.sm + SM_RING + slot * 32768 + c.rank * 16384, src, 16384, fb, last ? POL(5) : L2_NORMAL);
    slot = wrap5(slot + 1);
  };
  for (int it = 0; it < nit; it++) {
    const int item = p.s.r[c.cl].item[it], h = item >> 3, j = item & 7;
    if (it == 1 && (c.phases & 16) && p.s.r[c.cl].n1 < 8) flag_wait<true>(F_GATE, 256);
    uint32_t ready = (c.phases & 16) ? 0u : 255u;
    if (it == 0) { if (c.phases & 16) flag_wait<false>(F_Q + item, 4); mbar_wait(c.bar + B_LAD * 8, 0); p2_load_q(p, c, 0, 0); if (!u1) p2_load_q(p, c, 0, 1); }
    for (int t = 2 * j + 1; t >= 0; t--) {
      mask_wait(ready, t >> 1, F_KV + h * 8 + (c.lane & 7), 8);
      const uint8_t* k = g_S + (size_t)(2 * S_K + p.s.slot[h][t >> 1] * 16 + t) * 32768 + c.rank * 16384;
      const uint32_t fb = c.bar + (B_P2F + (n & 3)) * 8;
      const bool last = (p.s.r[c.cl].last[it] >> (t >> 1)) & 1;
      load(k, pv && t != 2 * j ? 65536 : 32768, fb, last);
      if (!(t & 1) && t + 4 <= 2 * j && c.rank == 0) flag_add_rx(F_RD + h * 8 + (t >> 1) + 2);
      if (pv) load(pv, 0, t != 2 * j ? fb : c.bar + (B_ORD + ((n - 1 - it) & 3)) * 8, pl);
      pl = last;
      pv = k + (size_t)NH * 16 * 32768;
      n++;
    }
  }
  load(pv, 32768, c.bar + (B_P2F + (n & 3)) * 8, pl);
}

__device__ __forceinline__ void publish_and_load_q(const Params& p, const Ctx& c, int f, int it, int seen) {
  const bool want = it < p.s.r[c.cl].n2, early = want && __all_sync(0xffffffffu, seen >= 4);
  if (early) { p2_load_q(p, c, it, it & 1); p2_load_q(p, c, it, (it & 1) ^ 1); }
  if (f >= 0) flag_add(f, 2);
  if (want && !early) {
    if (c.phases & 16) flag_wait<false>(F_Q + p.s.r[c.cl].item[it], 4);
    p2_load_q(p, c, it, it & 1); p2_load_q(p, c, it, (it & 1) ^ 1);
  }
}
__device__ __forceinline__ void p2_storer(const Params& p, const Ctx& c, int sfpar) {
  const int nit = p.s.r[c.cl].n2;
  for (int i = 0; i < 2 * nit; i++) {
    const int it = i >> 1, w = (it ^ i ^ 1) & 1, b = p2_buf(w, it);
    const int item = p.s.r[c.cl].item[it], h = item >> 3, j = item & 7;
    mbar_wait(c.bar + (B_SF + b) * 8, (sfpar >> b) & 1);
    sfpar ^= 1 << b;
    bulk_store(g_S + (size_t)p.s.qblk[item] * 65536 + p2_blk(c.rank, w, it) * 16384, c.sm + SM_BUF + b * 16384, 16384, POL(1));
    BULK_COMMIT();
    if (i & 1) {
      const int seen = flag_peek(F_Q + p.s.r[c.cl].item[min(it + 2, nit - 1)]);
      BULK_WAIT(0);
      if (it + 1 == nit) release(c, B_DONE);
      publish_and_load_q(p, c, F_CTX + j * 64 + h, it + 2, seen);
    }
  }
}

__device__ __forceinline__ int p3_pos(int i, int x) { return i < 4 ? (i + x) & 3 : 4; }
__device__ __forceinline__ void p3_consumer(const Params& p, const Ctx& c, int x) {
  const bool first = p.s.r[c.cl].p3 >= 24;
  const int tile = p.s.r[c.cl].p3 - (first ? 24 : 0), j = tile / 3, nt = tile - 3 * j;
  const int na = first ? 9 : 0, nb = p.s.task[c.cl][1] - p.s.task[c.cl][0];
  const uint32_t ad = desc_lo(c.sm + SM_RING + c.wg * 8192, 16), bd = desc_lo(c.sm + SM_RING + 16384, 4096);
  float acc[96] = {};
  int slot = 0, par = 0, prev = 0;
  float g0 = 0.f, g1 = 0.f;
  const int hold = c.wg && LAG ? na + nb - LAG : -1, pass = c.wg || !LAG ? -1 : na + nb - 1;
  const float* gp = g_gate + j * 256 + c.rank * 128 + c.wg * 64 + c.warp * 16 + (c.lane >> 2);
#pragma unroll 1
  for (int kb = 0; kb < na; kb++) {
    if (kb == hold) bar_sync(6, 256);
    mbar_wait(c.bar + (B_P3F + slot) * 8, par);
    if (kb == 0) PROF(c.wg, 39);
    WG_FENCE();
#pragma unroll
    for (int kk = 0; kk < 4; kk++) wgmma_ss192<1, 1>(acc, ad + p3_pos(slot, x) * 2560 + kk * 128, bd + p3_pos(slot, x) * 2560 + (kk >> 1) * 768 + (kk & 1) * 128, kk != 0 ? 1 : kb != 0);
    WG_COMMIT();
    if (kb == pass) bar_arrive(6, 256);
    WG_WAIT(1);
    if (kb > 0) release(c, B_P3E + prev);
    else { g0 = __ldcg(gp); g1 = __ldcg(gp + 8); }
    prev = slot;
    if (++slot == 5) { slot = 0; par ^= 1; }
  }
#pragma unroll 1
  for (int kb = na; kb < na + nb; kb++) {
    if (kb == hold) bar_sync(6, 256);
    mbar_wait(c.bar + (B_P3F + slot) * 8, par);
    if (kb == 0) PROF(c.wg, 39);
    WG_FENCE();
#pragma unroll
    for (int kk = 0; kk < 4; kk++) wgmma_ss192<1>(acc, ad + p3_pos(slot, x) * 2560 + kk * 2, bd + p3_pos(slot, x) * 2560 + (kk >> 1) * 768 + (kk & 1) * 128, kk != 0 ? 1 : kb != 0);
    WG_COMMIT();
    if (kb == pass) bar_arrive(6, 256);
    WG_WAIT(1);
    if (kb > 0) release(c, B_P3E + prev);
    else { g0 = __ldcg(gp); g1 = __ldcg(gp + 8); }
    prev = slot;
    if (++slot == 5) { slot = 0; par ^= 1; }
  }
  g0 = __fdividef(1.f, 1.f + g0); g1 = __fdividef(1.f, 1.f + g1);
  WG_WAIT(0);
  pin(acc);
  PROF(c.wg, 40);
  if (first) bar_sync(4 + c.wg, 128);
  mbar_wait(c.bar + B_OUT * 8, 0);
  const int row = (c.lane & 7) + ((c.lane >> 3) & 1) * 8;
  const uint32_t wbase = c.sm + SM_RING + c.wg * 8192 + c.warp * 2048;
  const uint32_t base = wbase + row * 128 + (((c.lane >> 4) ^ (row & 7)) << 4);
#pragma unroll
  for (int i = 0; i < 12; i++) {
    stsm4((base ^ ((i & 3) << 5)) + (i >> 2) * 40960, pack_bf16(acc[8 * i] * g0, acc[8 * i + 1] * g0), pack_bf16(acc[8 * i + 2] * g1, acc[8 * i + 3] * g1),
          pack_bf16(acc[8 * i + 4] * g0, acc[8 * i + 5] * g0), pack_bf16(acc[8 * i + 6] * g1, acc[8 * i + 7] * g1));
    if ((i & 3) == 3) {
      FENCE_ASYNC_SMEM();
      bar_sync(4 + c.wg, 128);
      if (c.warp == (i >> 2)) tma2d_add(&p.map_out, c.sm + SM_RING + c.wg * 8192 + c.warp * 40960, nt * 192 + c.warp * 64, j * 256 + c.rank * 128 + c.wg * 64);
    }
  }
  BULK_COMMIT();
  PROF(c.wg, 43);
  BULK_WAIT_READ(0);
  PROF(c.wg, 44);
}

__device__ __forceinline__ void p3_producer(const Params& p, const Ctx& c, int u1, int u2, int rot, int x) {
  const bool first = p.s.r[c.cl].p3 >= 24;
  const int tile = p.s.r[c.cl].p3 - (first ? 24 : 0), j = tile / 3, nt = tile - 3 * j;
  int slot = 0, par = 1, cnt = 0;
  auto wait_free = [&](int s) {
    const int f = wrap5(s + 5 - rot);
    if (f < u2) mbar_wait(c.bar + (B_P2E + s) * 8, ((u2 - 1 - f) / 5) & 1);
    else if (u1) wait_p1_free(c, u1, s);
  };
  asm volatile(ELECT("prefetch.tensormap [%0];") ::"l"(&p.map_o[0]) : "memory");
  asm volatile(ELECT("prefetch.tensormap [%0];") ::"l"(&p.map_out) : "memory");
  if ((c.phases & 16) && p.s.r[c.cl].n1 < 8 && p.s.r[c.cl].n2 < 2) flag_wait<true>(F_GATE, 256);
  uint32_t ready = (c.phases & 16) ? 0u : ~0u;
  const int q0 = p.s.task[c.cl][0], q1 = p.s.task[c.cl][1];
  for (int q = q0 - (first ? 9 : 0); q < q1; q++) {
    const bool brA = q < q0;
    const int kb = brA ? q - q0 + 9 : p.s.p3_order[tile][q];
    if (!brA) mask_wait(ready, kb >> 1, F_CTX + j * 64 + c.lane, 4);
    else if (kb == 0 && (c.phases & 16)) flag_wait<false>(F_CTX + j * 64 + 32, 16);
    const uint8_t* a = brA ? g_oA + (j * 4 + c.rank * 2) * 73728 + kb * 8192 : g_S + (size_t)p.s.qblk[(kb >> 1) * 8 + j] * 65536 + c.rank * 32768 + (kb & 1) * 8192;
    const uint32_t st = c.sm + SM_RING + p3_pos(slot, x) * 40960, fb = c.bar + (B_P3F + slot) * 8;
    if (cnt < 4) { wait_free(p3_pos(cnt, x)); wait_free(p3_pos(cnt, x) + 1); }
    else if (cnt == 4) mbar_wait(c.bar + B_DONE * 8, 0);
    else mbar_wait(c.bar + (B_P3E + slot) * 8, par);
    cnt++;
    mbar_expect(fb, 40960);
    bulk_load(st, a, 8192, fb, POL(3));
    bulk_load(st + 8192, a + (brA ? 73728 : 16384), 8192, fb, POL(3));
    tma3d_mc(st + 16384 + c.rank * 12288, &p.map_o[brA], 0, kb * 64 + c.rank * 32, nt * 3, fb);
    if (++slot == 5) { slot = 0; par ^= 1; }
  }
}

__device__ __forceinline__ float bf_lo(uint32_t w) { return __uint_as_float(w << 16); }
__device__ __forceinline__ float bf_hi(uint32_t w) { return __uint_as_float(w & 0xffff0000u); }

__device__ __forceinline__ void gate_rows(const Params& p, int row0, int lane) {
  const uint4* x = reinterpret_cast<const uint4*>(p.x + (size_t)(row0 + (lane >> 2)) * DM) + (lane & 3);
  const uint4* w = reinterpret_cast<const uint4*>(p.gate_w) + (lane & 3);
  float a = 0.f;
#pragma unroll 1
  for (int b = 0; b < 3; b++) {
    uint4 u[6];
#pragma unroll
    for (int i = 0; i < 6; i++) u[i] = __ldg(x + (b * 6 + i) * 4);
#pragma unroll
    for (int i = 0; i < 6; i++) {
      const uint4 v = __ldg(w + (b * 6 + i) * 4);
      a = fmaf(bf_lo(u[i].x), bf_lo(v.x), a); a = fmaf(bf_hi(u[i].x), bf_hi(v.x), a);
      a = fmaf(bf_lo(u[i].y), bf_lo(v.y), a); a = fmaf(bf_hi(u[i].y), bf_hi(v.y), a);
      a = fmaf(bf_lo(u[i].z), bf_lo(v.z), a); a = fmaf(bf_hi(u[i].z), bf_hi(v.z), a);
      a = fmaf(bf_lo(u[i].w), bf_lo(v.w), a); a = fmaf(bf_hi(u[i].w), bf_hi(v.w), a);
    }
  }
  a += __shfl_xor_sync(0xffffffffu, a, 1);
  a += __shfl_xor_sync(0xffffffffu, a, 2);
  if ((lane & 3) == 0) g_gate[row0 + (lane >> 2)] = __expf(fminf(a, 60.f));
}

__device__ __forceinline__ void lds10(uint32_t (&k)[10], uint32_t a) {
  asm volatile("ld.shared.v2.u32 {%0, %1}, [%10];\nld.shared.v2.u32 {%2, %3}, [%10+8];\nld.shared.v2.u32 {%4, %5}, [%10+16];\n"
               "ld.shared.v2.u32 {%6, %7}, [%10+24];\nld.shared.v2.u32 {%8, %9}, [%10+32];"
               : "=r"(k[0]), "=r"(k[1]), "=r"(k[2]), "=r"(k[3]), "=r"(k[4]), "=r"(k[5]), "=r"(k[6]), "=r"(k[7]), "=r"(k[8]), "=r"(k[9]) : "r"(a));
}
__device__ __forceinline__ void local_attn(const Params& p, const Ctx& c, int rb, int hs) {
  const int lane = c.lane, grp = rb >> 2, par = lane >> 4, i0 = 2 * (lane & 15);
  const uint32_t buf = c.sm + SM_BUF + (c.warp - 2) * 8192, bqk = c.bar + (B_LA + (c.warp - 2) * 2) * 8, bv = bqk + 8;
  const uint32_t mine = buf + 2304 + par * 160 + i0 * 4;
  const bool flags = c.phases & 16;
  auto fetch_qk = [&](int i) {
    if (flags && !(i & 1)) {
      const int q = i >> 1;
      const int tgt = q == 0 ? 24 : q == 3 ? 8 : 12;
      flag_wait<false>(F_QKVA + (grp - (grp > 0 && (rb & 3) == 0 ? par : 0)) * 4 + q, tgt);
    }
    mbar_expect(bqk, 5184);
    tma3d(buf, &p.map_t[0], rb * 32, 0, 9 * (4 * i + hs), bqk, POL(2));
    tma3d(buf + 2304, &p.map_t[1], rb * 32 - 8, 0, 288 + 9 * (4 * i + hs), bqk, POL(2));
  };
  auto fetch_v = [&](int i) { mbar_expect(bv, 2880); tma3d(buf + 5248, &p.map_t[1], rb * 32 - 8, 0, 576 + 9 * (4 * i + hs), bv, POL(2)); };
  fetch_qk(0);
  if (flags) flag_wait<true>(F_GATE, 256);
#pragma unroll 1
  for (int q = 0; q < 8; q++) {
    fetch_v(q);
    float a[8], b[8];
#pragma unroll
    for (int w = 0; w < 8; w++) a[w] = b[w] = 0.f;
    mbar_wait(bqk, q & 1);
    PROFB(1 + 2 * q);
#pragma unroll 1
    for (int j = 0; j < 9; j++) {
      uint32_t x, y, k[10];
      asm volatile("ld.shared.v2.u32 {%0, %1}, [%2];" : "=r"(x), "=r"(y) : "r"(buf + lane * 8 + j * 256));
      lds10(k, mine + j * 320);
      const float xl = bf_lo(x), xh = bf_hi(x), yl = bf_lo(y), yh = bf_hi(y);
#pragma unroll
      for (int m = 1; m < 10; m++) {
        const float kl = bf_lo(k[m]), kh = bf_hi(k[m]);
        if (m < 9) a[8 - m] = fmaf(xl, kl, fmaf(xh, kh, a[8 - m]));
        if (m > 1) b[9 - m] = fmaf(yl, kl, fmaf(yh, kh, b[9 - m]));
      }
    }
    __syncwarp();
    mbar_wait(bv, q & 1);
    if (q & 1) flag_add_rx(F_TS + (q >> 1));
    if (q < 7) fetch_qk(q + 1);
    constexpr float SC = 0.23570226039551584f * 1.4426950408889634f;
    const float* gp = g_gate + rb * 64 + 2 * i0 + par;
    const float ga = __ldcg(gp), gb = __ldcg(gp + 2);
    float ma = a[0], mb = b[0];
#pragma unroll
    for (int w = 1; w < 8; w++) {
      if (rb == 0) {
        if (i0 < w) a[w] = -INFINITY;
        if (i0 + 1 < w) b[w] = -INFINITY;
      }
      ma = fmaxf(ma, a[w]); mb = fmaxf(mb, b[w]);
    }
    float la = 0.f, lb = 0.f;
#pragma unroll
    for (int w = 0; w < 8; w++) {
      a[w] = ex2((a[w] - ma) * SC); b[w] = ex2((b[w] - mb) * SC);
      la += a[w]; lb += b[w];
    }
    la = __fdividef(ga, la); lb = __fdividef(gb, lb);
#pragma unroll
    for (int w = 0; w < 8; w++) { a[w] *= la; b[w] *= lb; }
    uint8_t* dst = g_oA + rb * 73728 + ((i0 & 2) + par) * 4;
#pragma unroll 1
    for (int j = 0; j < 9; j++) {
      uint32_t v[10];
      lds10(v, mine + 2944 + j * 320);
      float a0 = 0.f, a1 = 0.f, b0 = 0.f, b1 = 0.f;
#pragma unroll
      for (int m = 1; m < 10; m++) {
        const float vl = bf_lo(v[m]), vh = bf_hi(v[m]);
        if (m < 9) { a0 = fmaf(a[8 - m], vl, a0); a1 = fmaf(a[8 - m], vh, a1); }
        if (m > 1) { b0 = fmaf(b[9 - m], vl, b0); b1 = fmaf(b[9 - m], vh, b1); }
      }
      const uint32_t wa = pack_bf16(a0, a1), wb = pack_bf16(b0, b1);
      const uint32_t got = __shfl_xor_sync(0xffffffffu, par ? wa : wb, 16);
      const uint32_t r0 = par ? got : wa, r1 = par ? wb : got;
      const int col = 18 * (4 * q + hs) + 2 * j, o = col * 128 + ((((i0 >> 2) ^ col) & 7) << 4);
      *reinterpret_cast<uint32_t*>(dst + o) = __byte_perm(r0, r1, 0x5410);
      *reinterpret_cast<uint32_t*>(dst + ((o + 128) ^ 16)) = __byte_perm(r0, r1, 0x7632);
    }
    __syncwarp();
    PROFB(2 + 2 * q);
  }
  mbar_arrive_one(c.bar + B_LAD * 8);
  flag_add(F_CTX + grp * 64 + 32);
}

__global__ void __cluster_dims__(2, 1, 1) __launch_bounds__(384, 1) fused_kernel(const __grid_constant__ Params p) {
  extern __shared__ uint8_t smem_raw[];
  Ctx c;
  c.sm = ((uint32_t)__cvta_generic_to_shared(smem_raw) + 1023u) & ~1023u;
  c.bar = c.sm + SM_BAR;
  c.lane = threadIdx.x & 31;
  const int wid = __shfl_sync(0xffffffffu, threadIdx.x >> 5, 0);
  if (wid < 6) asm volatile("prefetch.tensormap [%0];" ::"l"(&p.map_a[0] + wid) : "memory");
  c.wg = wid >> 2;
  c.warp = wid & 3;
  PROF(c.wg, 0);
  PROFG(61);
  c.cl = (blockIdx.x + (wid >> 4)) >> 1;
  c.rank = blockIdx.x & 1;
  c.rbar = mapa(c.bar, c.lane & 1);
  {
    const int w = wid, cnt = (((int)(B_CNT >> (4 * w)) - 1) & 15) + 1;
    if (w < 11) {
#pragma unroll
      for (int i = 0; i < 8; i++) asm volatile("mbarrier.init.shared::cta.b64 [%0], %1;" ::"r"(c.bar + w * 64 + i * 8), "r"(cnt));
    }
    asm volatile("fence.mbarrier_init.release.cluster;" ::: "memory");
  }
  if (c.wg == 2) PROF(2, 56);
  asm volatile("barrier.cluster.arrive.relaxed;" ::: "memory");
  c.phases = p.s.r[c.cl].phases;
  const bool do1 = p.s.r[c.cl].n1 > 0, do2 = p.s.r[c.cl].n2 > 0, do3 = p.s.r[c.cl].p3 != 255;
  if (do1 && c.wg == 2 && c.warp == 0) {
    const int type = p.s.r[c.cl].slab >> 3;
    PROF(2, 57);
    FENCE_ASYNC_SMEM();
    mbar_expect(c.bar + B_P1F * 8, type ? 32768 : 16384);
    tma2d(type ? c.sm + SM_BUF + 32768 : c.sm + SM_RING, &p.map_a[type], type ? 512 : 0, (p.s.r[c.cl].slab & 7) * 256 + c.rank * 128, c.bar + B_P1F * 8);
    PROF(2, 58);
  }
  asm volatile("barrier.cluster.wait.acquire;" ::: "memory");
  if (c.wg == 2) PROF(2, 59);
  if (do1 && c.wg == 2 && c.warp == 0) {
    const int type = p.s.r[c.cl].slab >> 3, tile = p.s.r[c.cl].tile[0] & 63;
    const CUtensorMap* m = &p.map_w[type * 2 + (tile >> 5)];
#pragma unroll 1
    for (int s = 1 - type; s < NPRO; s++) {
      const int kb = (s - type) >> 1;
      const uint32_t fb = c.bar + (B_P1F + s) * 8;
      if (s) mbar_expect(fb, 16384);
      if ((s ^ type) & 1) tma2d_mc(c.sm + SM_RING + s * 16384 + c.rank * 8192, m, (tile & 31) * 128 + c.rank * 64, kb < 0 ? 512 : kb * 64, fb);
      else tma2d(c.sm + SM_RING + s * 16384, &p.map_a[type], kb * 64, (p.s.r[c.cl].slab & 7) * 256 + c.rank * 128, fb);
    }
  }

  if (c.wg < 2) {
    PROF(c.wg, 4);
    asm volatile("setmaxnreg.inc.sync.aligned.u32 224;");
    if (c.wg == 1) {
      if (do1) bar_arrive(ORDER, 256);
      if (c.lane == 0) mbar_arrive(c.bar + B_P2F * 8);
    }
    PL(0);
    if (do1) p1_consumer(p, c);
    PL(1);
    if (do2) p2_consumer(p, c, p.s.r[c.cl].rot);
    PL(2);
    if (do3) p3_consumer(p, c, p.s.r[c.cl].x3);
    PL(3);
    PROF(c.wg, 63);
    PROFG(62);
    if (c.lane == 0) mbar_arrive(c.bar + B_FIN * 8);
    __syncwarp();
    cluster_sync();
  } else {
    asm volatile("setmaxnreg.dec.sync.aligned.u32 56;");
    if (c.warp == 0) {
      PROF(2, 60);
      if (do1) p1_producer(p, c);
      if (do2) p2_producer(p, c, p.s.r[c.cl].u1, p.s.r[c.cl].rot);
      if (do3) p3_producer(p, c, p.s.r[c.cl].u1, p.s.r[c.cl].u2, p.s.r[c.cl].rot, p.s.r[c.cl].x3);
    } else if (c.warp == 1) {
      const int f = do1 ? p1_storer(p, c) : -1;
      publish_and_load_q(p, c, f, 1, flag_peek(F_Q + p.s.r[c.cl].item[1]));
      if (do2) p2_storer(p, c, (p.s.r[c.cl].n1 & 1) * 10);
      else { mbar_wait(c.bar + B_LAD * 8, 0); release(c, B_DONE); }
      if (do3) {
        const int tile = p.s.r[c.cl].p3 % 24;
        if (p.s.task[c.cl][1] == 64) {
          for (int r = 0; r < (64 - p.s.task[c.cl][0] - ZLEAD) / 5; r++) mbar_wait(c.bar + B_P3F * 8, r & 1);
          const int j = tile / 3, nt = tile - 3 * j;
          uint4* o = reinterpret_cast<uint4*>(p.out + (size_t)(j * 256 + c.rank * 128 + (c.lane >> 3)) * DM + nt * 192) + (c.lane & 7);
#pragma unroll 4
          for (int r = 0; r < 32; r++) o[r * 288] = o[r * 288 + 8] = o[r * 288 + 16] = make_uint4(0u, 0u, 0u, 0u);
          __syncwarp();
          flag_add(F_OUT + tile * 2 + c.rank);
        } else if (c.phases & 16) {
          flag_wait<false, 256>(F_OUT + tile * 2 + c.rank, 1);
        }
        mbar_arrive_one(c.bar + B_OUT * 8);
      }
    } else {
      const int bw = blockIdx.x * 2 + (c.warp - 2);
      if ((c.phases & 1) && bw < 256) {
        gate_rows(p, bw * 8, c.lane);
        __syncwarp();
        flag_add(F_GATE);
      }
      if (p.s.r[c.cl].bg != 255) local_attn(p, c, p.s.r[c.cl].bg, bw & 3);
      else if (c.lane == 0) mbar_arrive(c.bar + B_LAD * 8);
    }
    __syncwarp();
    bar_sync(3, 128);
    if (c.warp == 0 && (c.phases & 32)) {
      int last = 0;
      if (c.lane == 0) { __threadfence(); last = atomicAdd(g_flags + F_DONE, 1) == 2 * NCL - 1; }
      if (__shfl_sync(0xffffffffu, last, 0)) for (int i = c.lane; i < F_NUM; i += 32) g_flags[i] = 0;
    }
    if (c.warp == 1) mbar_wait(c.bar + B_FIN * 8, 0);
    __syncwarp();
    cluster_sync();
  }
}

SCHED_DECL Sched k_sched = {
  {{0,30,2,36,0,{177,224,0,0,0,0,0,0,0,0,0},{0,0,0,0,0,0,0,0,0,0,0},{135,32,133,41,36,43,35,38,59,49,44,45,48,46,53,50,42,52,55,51,63,40,62,58,54,47,56,57,60,61}},
   {1,30,2,37,1,{201,120,0,0,0,0,0,0,0,0,0},{0,0,0,0,0,0,0,0,0,0,0},{135,32,1,41,36,43,35,38,59,49,44,45,48,46,53,50,42,52,55,51,63,40,62,58,54,47,56,57,60,61}},
   {2,30,2,10,2,{176,194,0,0,0,0,0,0,0,0,0},{0,7,0,0,0,0,0,0,0,0,0},{64,34,1,41,36,43,35,38,59,49,44,45,48,46,53,50,52,42,51,55,63,40,62,58,54,47,56,57,60,61}},
   {3,29,1,25,3,{195,0,0,0,0,0,0,0,0,0,0},{0,0,0,0,0,0,0,0,0,0,0},{66,39,133,41,11,35,38,59,49,44,45,48,46,53,50,52,42,51,55,63,40,62,58,54,47,56,57,60,61,0}},
   {4,28,1,42,4,{205,0,0,0,0,0,0,0,0,0,0},{63,0,0,0,0,0,0,0,0,0,0},{135,34,1,37,4,43,6,59,12,13,16,14,21,18,20,10,19,23,31,8,30,26,22,24,15,25,28,29,0,0}},
   {5,27,0,1,5,{0,0,0,0,0,0,0,0,0,0,0},{0,0,0,0,0,0,0,0,0,0,0},{66,39,0,37,4,43,6,59,12,45,14,21,18,20,10,19,23,31,8,30,26,22,15,24,25,28,29,0,0,0}},
   {6,26,0,20,6,{0,0,0,0,0,0,0,0,0,0,0},{0,0,0,0,0,0,0,0,0,0,0},{98,33,133,41,11,35,27,49,13,48,21,18,20,10,19,23,31,8,30,26,22,15,24,25,28,29,0,0,0,0}},
   {7,25,3,4,7,{214,233,232,0,0,0,0,0,0,0,0},{0,0,0,0,0,0,0,0,0,0,0},{65,0,73,68,67,91,76,109,78,85,82,84,74,83,87,95,72,94,90,86,79,88,89,92,93,0,0,0,0,0}},
   {0,30,1,34,8,{227,0,0,0,0,0,0,0,0,0,0},{0,0,0,0,0,0,0,0,0,0,0},{66,39,1,37,4,11,3,6,27,17,12,13,16,14,21,18,10,20,23,19,31,8,30,26,22,15,24,25,28,29}},
   {1,30,1,21,9,{203,0,0,0,0,0,0,0,0,0,0},{0,0,0,0,0,0,0,0,0,0,0},{66,39,133,33,4,11,3,6,27,17,12,13,16,14,21,18,10,20,23,19,31,8,30,26,22,15,24,25,28,29}},
   {2,30,2,16,10,{121,234,0,0,0,0,0,0,0,0,0},{0,0,0,0,0,0,0,0,0,0,0},{135,32,133,33,4,11,3,6,27,17,12,13,16,14,21,18,20,10,19,23,31,8,30,26,22,15,24,25,28,29}},
   {3,29,2,31,11,{178,192,0,0,0,0,0,0,0,0,0},{0,0,0,0,0,0,0,0,0,0,0},{64,34,1,37,4,43,6,27,17,12,13,16,14,21,18,20,10,19,23,31,8,30,26,22,15,24,25,28,29,0}},
   {4,28,0,21,12,{0,0,0,0,0,0,0,0,0,0,0},{0,0,0,0,0,0,0,0,0,0,0},{103,0,33,9,36,3,38,17,44,45,48,46,53,50,52,42,51,55,63,40,62,58,54,56,47,57,60,61,0,0}},
   {5,27,0,6,13,{0,0,0,0,0,0,0,0,0,0,0},{0,0,0,0,0,0,0,0,0,0,0},{98,1,32,9,36,3,38,17,44,16,46,53,50,52,42,51,55,63,40,62,58,54,47,56,57,60,61,0,0,0}},
   {6,26,0,4,14,{0,0,0,0,0,0,0,0,0,0,0},{0,0,0,0,0,0,0,0,0,0,0},{135,0,101,68,43,6,59,12,45,14,53,50,52,42,51,55,63,40,62,58,54,47,56,57,60,61,0,0,0,0}},
   {7,25,0,19,15,{0,0,0,0,0,0,0,0,0,0,0},{0,0,0,0,0,0,0,0,0,0,0},{97,32,105,100,99,123,108,80,110,117,114,116,106,115,119,127,104,126,122,118,111,120,121,124,125,0,0,0,0,0}},
   {0,4,6,12,255,{0,11,31,117,83,152,0,0,0,0,0},{0,0,0,0,0,0,0,0,0,0,0},{98,0,33,9,0,0,0,0,0,0,0,0,0,0,0,0,0,0,0,0,0,0,0,0,0,0,0,0,0,0}},
   {1,4,3,10,255,{14,223,87,0,0,0,0,0,0,0,0},{0,0,0,0,0,0,0,0,0,0,0},{98,0,101,9,0,0,0,0,0,0,0,0,0,0,0,0,0,0,0,0,0,0,0,0,0,0,0,0,0,0}},
   {2,4,6,38,255,{19,73,54,108,71,124,0,0,0,0,0},{0,0,0,0,0,0,0,0,0,0,0},{103,2,101,9,0,0,0,0,0,0,0,0,0,0,0,0,0,0,0,0,0,0,0,0,0,0,0,0,0,0}},
   {3,6,6,2,255,{72,44,28,118,67,206,0,0,0,0,0},{0,0,0,0,0,64,0,0,0,0,0},{96,7,33,9,36,3,0,0,0,0,0,0,0,0,0,0,0,0,0,0,0,0,0,0,0,0,0,0,0,0}},
   {4,8,6,1,255,{32,76,221,114,246,228,0,0,0,0,0},{0,0,0,0,0,0,0,0,0,0,0},{66,32,133,41,11,35,27,49,0,0,0,0,0,0,0,0,0,0,0,0,0,0,0,0,0,0,0,0,0,0}},
   {5,10,6,13,255,{24,91,101,157,212,202,0,0,0,0,0},{0,0,0,0,0,0,0,0,0,0,0},{135,33,133,41,11,35,27,49,13,48,0,0,0,0,0,0,0,0,0,0,0,0,0,0,0,0,0,0,0,0}},
   {6,10,6,35,255,{88,29,174,186,241,180,0,0,0,0,0},{0,0,0,0,0,31,0,0,0,0,0},{103,32,73,100,67,38,17,44,16,46,0,0,0,0,0,0,0,0,0,0,0,0,0,0,0,0,0,0,0,0}},
   {7,8,6,46,255,{18,222,173,154,242,123,0,0,0,0,0},{0,0,0,0,0,0,0,0,0,0,0},{135,2,133,75,70,81,77,112,0,0,0,0,0,0,0,0,0,0,0,0,0,0,0,0,0,0,0,0,0,0}},
   {8,18,2,9,16,{255,229,0,0,0,0,0,0,0,0,0},{0,0,0,0,0,0,0,0,0,0,0},{128,161,68,11,35,44,109,27,17,142,21,18,23,19,30,22,153,28,0,0,0,0,0,0,0,0,0,0,0,0}},
   {9,17,1,22,17,{191,0,0,0,0,0,0,0,0,0,0},{3,0,0,0,0,0,0,0,0,0,0},{135,161,166,11,108,27,109,17,13,16,82,87,147,8,90,88,153,0,0,0,0,0,0,0,0,0,0,0,0,0}},
   {10,18,3,26,18,{96,84,182,0,0,0,0,0,0,0,0},{1,0,96,0,0,0,0,0,0,0,0},{135,161,2,4,108,11,40,6,12,16,21,20,147,31,30,26,24,28,0,0,0,0,0,0,0,0,0,0,0,0}},
   {11,19,3,40,19,{168,253,196,0,0,0,0,0,0,0,0},{0,3,0,0,0,0,0,0,0,0,0},{135,161,107,11,39,6,27,45,12,16,21,18,147,31,30,26,24,28,29,0,0,0,0,0,0,0,0,0,0,0}},
   {12,18,2,13,20,{104,189,0,0,0,0,0,0,0,0,0},{0,0,0,0,0,0,0,0,0,0,0},{96,106,9,67,39,6,40,17,13,142,84,10,23,8,90,88,153,93,0,0,0,0,0,0,0,0,0,0,0,0}},
   {13,20,2,2,21,{155,208,0,0,0,0,0,0,0,0,0},{0,0,0,0,0,0,0,0,0,0,0},{105,0,107,11,70,39,27,12,45,142,21,20,147,31,30,22,24,25,28,29,0,0,0,0,0,0,0,0,0,0}},
   {14,18,5,17,22,{169,81,249,65,238,0,0,0,0,0,0},{0,0,0,0,127,0,0,0,0,0,0},{69,165,107,67,91,39,17,77,45,142,82,10,23,8,90,15,153,93,0,0,0,0,0,0,0,0,0,0,0,0}},
   {15,18,4,32,23,{136,113,251,198,0,0,0,0,0,0,0},{0,0,0,0,0,0,0,0,0,0,0},{128,36,68,43,70,81,35,44,80,45,21,20,147,31,30,22,24,28,0,0,0,0,0,0,0,0,0,0,0,0}},
   {8,18,2,18,24,{148,64,0,0,0,0,0,0,0,0,0},{0,0,0,0,0,0,0,0,0,0,0},{65,165,162,67,39,104,6,12,80,13,74,72,20,31,90,88,15,93,0,0,0,0,0,0,0,0,0,0,0,0}},
   {9,18,1,11,25,{172,0,0,0,0,0,0,0,0,0,0},{28,0,0,0,0,0,0,0,0,0,0},{128,165,107,99,3,104,6,12,85,142,74,20,95,94,79,22,92,93,0,0,0,0,0,0,0,0,0,0,0,0}},
   {10,18,3,24,26,{216,147,183,0,0,0,0,0,0,0,0},{1,0,224,0,0,0,0,0,0,0,0},{128,165,162,99,3,27,109,17,13,142,82,10,23,8,86,15,153,93,0,0,0,0,0,0,0,0,0,0,0,0}},
   {11,17,5,30,27,{105,170,213,193,200,0,0,0,0,0,0},{0,0,0,0,0,0,0,0,0,0,0},{65,165,5,4,108,3,40,77,17,142,84,10,23,8,86,15,153,0,0,0,0,0,0,0,0,0,0,0,0,0}},
   {12,18,3,0,28,{112,188,240,0,0,0,0,0,0,0,0},{0,0,0,0,0,0,0,0,0,0,0},{65,165,107,11,35,44,27,45,12,16,21,18,147,31,30,22,15,28,0,0,0,0,0,0,0,0,0,0,0,0}},
   {13,17,3,39,29,{48,163,215,0,0,0,0,0,0,0,0},{0,0,248,0,0,0,0,0,0,0,0},{100,1,166,4,3,35,44,17,40,13,16,18,10,23,8,26,15,0,0,0,0,0,0,0,0,0,0,0,0,0}},
   {14,18,3,28,30,{128,156,207,0,0,0,0,0,0,0,0},{0,0,128,0,0,0,0,0,0,0,0},{65,41,162,11,70,35,44,12,40,16,21,20,147,31,30,22,24,28,0,0,0,0,0,0,0,0,0,0,0,0}},
   {15,18,2,8,31,{164,144,0,0,0,0,0,0,0,0,0},{0,0,0,0,0,0,0,0,0,0,0},{130,41,75,67,91,76,39,77,40,142,82,10,23,8,90,15,153,93,0,0,0,0,0,0,0,0,0,0,0,0}},
   {8,3,7,29,255,{61,74,26,109,129,162,127,0,0,0,0},{0,0,0,0,0,0,128,0,0,0,0},{135,41,9,0,0,0,0,0,0,0,0,0,0,0,0,0,0,0,0,0,0,0,0,0,0,0,0,0,0,0}},
   {9,5,6,41,255,{40,39,135,145,245,210,0,0,0,0,0},{0,0,0,0,0,7,0,0,0,0,0},{130,41,162,4,39,0,0,0,0,0,0,0,0,0,0,0,0,0,0,0,0,0,0,0,0,0,0,0,0,0}},
   {10,3,4,17,255,{3,95,100,190,0,0,0,0,0,0,0},{0,0,0,0,0,0,0,0,0,0,0},{100,5,107,0,0,0,0,0,0,0,0,0,0,0,0,0,0,0,0,0,0,0,0,0,0,0,0,0,0,0}},
   {11,4,3,3,255,{46,143,116,0,0,0,0,0,0,0,0},{0,0,3,0,0,0,0,0,0,0,0},{96,106,9,99,0,0,0,0,0,0,0,0,0,0,0,0,0,0,0,0,0,0,0,0,0,0,0,0,0,0}},
   {12,3,5,27,255,{4,55,134,69,204,0,0,0,0,0,0},{0,0,32,3,0,0,0,0,0,0,0},{128,161,166,0,0,0,0,0,0,0,0,0,0,0,0,0,0,0,0,0,0,0,0,0,0,0,0,0,0,0}},
   {13,3,7,5,255,{7,34,220,130,146,250,230,0,0,0,0},{0,0,0,0,0,0,127,0,0,0,0},{135,165,9,0,0,0,0,0,0,0,0,0,0,0,0,0,0,0,0,0,0,0,0,0,0,0,0,0,0,0}},
   {14,3,5,14,255,{20,94,175,82,248,0,0,0,0,0,0},{0,0,0,0,0,0,0,0,0,0,0},{128,161,166,0,0,0,0,0,0,0,0,0,0,0,0,0,0,0,0,0,0,0,0,0,0,0,0,0,0,0}},
   {15,3,6,20,255,{62,75,141,85,244,235,0,0,0,0,0},{0,0,0,0,0,0,0,0,0,0,0},{135,32,42,0,0,0,0,0,0,0,0,0,0,0,0,0,0,0,0,0,0,0,0,0,0,0,0,0,0,0}},
   {8,4,5,7,255,{6,35,217,137,150,0,0,0,0,0,0},{0,0,0,0,56,0,0,0,0,0,0},{130,36,5,43,0,0,0,0,0,0,0,0,0,0,0,0,0,0,0,0,0,0,0,0,0,0,0,0,0,0}},
   {9,3,6,14,255,{21,36,218,133,247,122,0,0,0,0,0},{0,0,0,0,255,7,0,0,0,0,0},{96,106,1,0,0,0,0,0,0,0,0,0,0,0,0,0,0,0,0,0,0,0,0,0,0,0,0,0,0,0}},
   {10,3,6,33,255,{15,89,25,140,158,126,0,0,0,0,0},{0,0,0,0,4,127,0,0,0,0,0},{105,1,9,0,0,0,0,0,0,0,0,0,0,0,0,0,0,0,0,0,0,0,0,0,0,0,0,0,0,0}},
   {11,3,6,5,255,{23,53,98,171,161,160,0,0,0,0,0},{0,0,0,0,0,1,0,0,0,0,0},{130,41,166,0,0,0,0,0,0,0,0,0,0,0,0,0,0,0,0,0,0,0,0,0,0,0,0,0,0,0}},
   {12,4,6,6,255,{47,27,138,106,252,231,0,0,0,0,0},{0,0,0,0,0,128,0,0,0,0,0},{135,36,5,4,0,0,0,0,0,0,0,0,0,0,0,0,0,0,0,0,0,0,0,0,0,0,0,0,0,0}},
   {13,3,7,16,255,{16,2,77,90,139,165,184,0,0,0,0},{0,0,0,0,0,0,0,0,0,0,0},{96,106,162,0,0,0,0,0,0,0,0,0,0,0,0,0,0,0,0,0,0,0,0,0,0,0,0,0,0,0}},
   {14,4,5,0,255,{79,142,159,209,237,0,0,0,0,0,0},{0,0,128,0,0,0,0,0,0,0,0},{135,36,9,4,0,0,0,0,0,0,0,0,0,0,0,0,0,0,0,0,0,0,0,0,0,0,0,0,0,0}},
   {15,4,6,18,255,{12,43,111,254,179,226,0,0,0,0,0},{0,0,0,0,0,0,0,0,0,0,0},{65,5,37,38,0,0,0,0,0,0,0,0,0,0,0,0,0,0,0,0,0,0,0,0,0,0,0,0,0,0}},
   {8,3,7,12,255,{22,41,219,151,153,243,236,0,0,0,0},{0,0,0,0,0,0,0,0,0,0,0},{96,106,166,0,0,0,0,0,0,0,0,0,0,0,0,0,0,0,0,0,0,0,0,0,0,0,0,0,0,0}},
   {9,3,6,44,255,{1,5,103,97,70,125,0,0,0,0,0},{0,0,0,0,0,63,0,0,0,0,0},{100,9,5,0,0,0,0,0,0,0,0,0,0,0,0,0,0,0,0,0,0,0,0,0,0,0,0,0,0,0}},
   {10,4,7,45,255,{8,13,92,99,131,68,211,0,0,0,0},{0,0,0,0,2,0,0,0,0,0,0},{96,106,166,103,0,0,0,0,0,0,0,0,0,0,0,0,0,0,0,0,0,0,0,0,0,0,0,0,0,0}},
   {11,3,7,43,255,{63,33,110,115,185,181,225,0,0,0,0},{0,0,0,0,0,0,0,0,0,0,0},{128,36,162,0,0,0,0,0,0,0,0,0,0,0,0,0,0,0,0,0,0,0,0,0,0,0,0,0,0,0}},
   {12,3,6,22,255,{56,59,37,52,166,199,0,0,0,0,0},{0,0,0,0,70,248,0,0,0,0,0},{130,41,162,0,0,0,0,0,0,0,0,0,0,0,0,0,0,0,0,0,0,0,0,0,0,0,0,0,0,0}},
   {13,3,5,15,255,{60,9,93,49,167,0,0,0,0,0,0},{0,0,0,0,0,0,0,0,0,0,0},{130,161,5,0,0,0,0,0,0,0,0,0,0,0,0,0,0,0,0,0,0,0,0,0,0,0,0,0,0,0}},
   {14,3,6,8,255,{57,42,38,119,187,239,0,0,0,0,0},{0,0,0,0,0,128,0,0,0,0,0},{130,32,42,0,0,0,0,0,0,0,0,0,0,0,0,0,0,0,0,0,0,0,0,0,0,0,0,0,0,0}},
   {15,3,6,47,255,{58,45,102,149,66,197,0,0,0,0,0},{0,0,0,0,0,0,0,0,0,0,0},{73,161,162,0,0,0,0,0,0,0,0,0,0,0,0,0,0,0,0,0,0,0,0,0,0,0,0,0,0,0}},
   {6,2,6,23,255,{17,78,51,50,132,80,0,0,0,0,0},{0,0,0,0,0,0,0,0,0,0,0},{66,1,0,0,0,0,0,0,0,0,0,0,0,0,0,0,0,0,0,0,0,0,0,0,0,0,0,0,0,0}},
   {7,6,4,9,255,{10,30,107,86,0,0,0,0,0,0,0},{0,0,0,120,0,0,0,0,0,0,0},{103,34,101,107,102,113,0,0,0,0,0,0,0,0,0,0,0,0,0,0,0,0,0,0,0,0,0,0,0,0}}},
  {{0,8,0,0},{0,8,0,0},{2,13,0,0},{0,6,0,0},{0,2,0,0},{17,64,0,0},{11,64,0,0},{2,11,0,0},{0,2,0,0},{10,22,0,0},{6,14,0,0},
   {0,8,0,0},{22,64,0,0},{17,64,0,0},{11,64,0,0},{5,64,0,0},{16,64,0,0},{13,64,0,0},{0,4,0,0},{8,19,0,0},{6,17,0,0},{8,19,0,0},
   {0,7,0,0},{0,8,0,0},{3,13,0,0},{20,64,0,0},{0,8,0,0},{0,6,0,0},{19,64,0,0},{19,64,0,0},{10,18,0,0},{0,3,0,0},{12,64,0,0},
   {7,64,0,0},{0,8,0,0},{0,8,0,0},{17,64,0,0},{0,10,0,0},{0,2,0,0},{12,64,0,0},{0,6,0,0},{0,10,0,0},{18,64,0,0},{2,64,0,0},
   {0,2,0,0},{6,15,0,0},{16,64,0,0},{3,11,0,0},{8,64,0,0},{4,16,0,0},{0,3,0,0},{15,64,0,0},{8,17,0,0},{14,64,0,0},{8,17,0,0},
   {2,12,0,0},{8,16,0,0},{0,3,0,0},{0,10,0,0},{0,5,0,0},{8,20,0,0},{10,64,0,0},{3,12,0,0},{0,3,0,0},{3,64,0,0},{13,64,0,0}},
  {{40,39,60,53,48,51,56,58,46,41,62,61,44,49,30,57,59,4,5,14,15,0,1,2,3,10,11,18,19,8,9,22,23,6,7,12,13,24,25,54,55,32,33,34,35,28,29,26,27,42,43,20,21,16,17,36,37,47,38,63,52,45,50,31},
   {63,52,45,51,56,58,36,46,40,38,62,61,44,49,30,57,59,4,5,14,15,0,1,2,3,10,11,18,19,8,9,22,23,6,7,12,13,24,25,54,55,32,33,34,35,28,29,26,27,42,43,20,21,16,17,37,47,41,39,60,53,48,50,31},
   {40,62,61,44,49,30,57,59,21,17,37,47,38,63,53,48,51,56,58,4,5,14,15,0,1,2,3,10,11,18,19,8,9,22,23,6,7,12,13,24,25,54,55,32,33,34,35,28,29,26,27,42,43,20,16,36,46,41,39,60,52,45,50,31},
   {58,59,14,15,4,5,0,1,18,19,2,3,10,11,8,9,22,23,6,7,54,55,12,13,34,35,24,25,26,27,42,43,32,33,28,29,36,37,20,21,46,47,40,41,38,39,62,63,16,17,60,61,52,53,30,31,48,49,44,45,50,51,56,57},
   {51,58,63,17,61,53,31,49,50,57,59,14,15,4,5,0,1,18,19,2,3,10,11,8,9,22,23,6,7,54,55,12,13,34,35,24,25,26,27,42,43,32,33,28,29,36,37,20,21,46,47,40,41,38,39,62,16,60,52,30,48,44,45,56},
   {61,30,49,50,57,59,38,62,16,60,53,48,45,56,58,14,15,4,5,0,1,18,19,2,3,10,11,8,9,22,23,6,7,54,55,12,13,34,35,24,25,26,27,42,43,32,33,28,29,36,37,20,21,46,47,40,41,39,63,17,52,31,44,51},
   {47,16,61,44,31,50,57,59,38,46,63,60,53,30,49,56,58,14,15,0,1,10,11,2,3,4,5,18,19,8,9,6,7,22,23,54,55,12,13,34,35,24,25,26,27,32,33,28,29,42,43,36,37,40,41,20,21,39,62,17,52,45,48,51},
   {61,53,45,31,49,51,57,59,14,15,0,1,10,11,2,3,4,5,18,19,8,9,6,7,22,23,54,55,12,13,34,35,24,25,26,27,32,33,28,29,42,43,36,37,40,41,20,21,38,39,46,47,62,63,16,17,60,52,44,30,48,50,56,58},
   {48,51,58,63,17,61,53,45,31,50,57,59,14,15,0,1,10,11,2,3,4,5,18,19,8,9,6,7,22,23,54,55,12,13,34,35,24,25,26,27,32,33,28,29,42,43,36,37,40,41,20,21,38,39,46,47,62,16,60,52,44,30,49,56},
   {48,56,58,46,62,16,60,44,52,31,50,57,59,0,1,4,5,14,15,2,3,10,11,18,19,22,23,8,9,12,13,6,7,54,55,26,27,34,35,24,25,32,33,28,29,42,43,40,41,36,37,20,21,38,39,47,63,17,61,45,53,30,49,51},
   {57,59,39,47,63,17,61,45,53,31,50,56,58,0,1,4,5,14,15,2,3,10,11,18,19,22,23,8,9,12,13,6,7,54,55,26,27,34,35,24,25,32,33,28,29,42,43,40,41,36,37,20,21,38,46,62,16,60,44,52,30,48,49,51},
   {45,53,31,49,51,57,59,0,1,4,5,14,15,2,3,10,11,18,19,22,23,8,9,12,13,6,7,54,55,26,27,34,35,24,25,32,33,28,29,42,43,40,41,36,37,20,21,38,39,46,47,62,63,16,17,60,61,44,52,30,48,50,56,58},
   {47,16,61,44,49,50,57,59,39,62,17,52,45,30,56,58,14,15,4,5,0,1,2,3,10,11,18,19,8,9,22,23,6,7,12,13,54,55,34,35,24,25,26,27,28,29,32,33,42,43,36,37,40,41,20,21,38,46,63,60,53,48,31,51},
   {47,16,61,44,49,50,57,59,40,20,38,46,63,60,53,48,31,56,58,14,15,4,5,0,1,2,3,10,11,18,19,8,9,22,23,6,7,12,13,54,55,34,35,24,25,26,27,28,29,32,33,42,43,36,37,41,21,39,62,17,52,45,30,51},
   {49,50,57,59,41,21,39,47,63,17,61,53,48,31,56,58,14,15,4,5,0,1,2,3,10,11,18,19,8,9,22,23,6,7,12,13,54,55,34,35,24,25,26,27,28,29,32,33,42,43,36,37,40,20,38,46,62,16,60,52,44,45,30,51},
   {63,17,61,53,45,31,49,56,58,59,14,15,4,5,2,3,0,1,10,11,18,19,8,9,22,23,6,7,12,13,54,55,34,35,24,25,26,27,28,29,32,33,42,43,36,37,40,41,20,21,38,39,46,47,62,16,60,52,44,30,48,50,51,57},
   {61,44,31,50,57,59,47,63,17,52,45,48,51,58,14,15,4,5,2,3,0,1,10,11,18,19,8,9,22,23,6,7,12,13,54,55,34,35,24,25,26,27,28,29,32,33,42,43,36,37,40,41,20,21,38,39,46,62,16,60,53,30,49,56},
   {20,38,47,16,61,44,31,50,57,59,46,63,60,53,30,49,56,58,14,15,4,5,2,3,0,1,10,11,18,19,8,9,22,23,6,7,12,13,54,55,34,35,24,25,26,27,28,29,32,33,42,43,36,37,40,41,21,39,62,17,52,45,48,51},
   {57,59,39,63,17,61,44,48,30,50,56,58,14,15,4,5,2,3,0,1,10,11,18,19,8,9,22,23,6,7,12,13,54,55,34,35,24,25,26,27,32,33,28,29,42,43,36,37,20,21,40,41,46,47,38,62,16,60,52,53,45,49,31,51},
   {49,31,51,57,59,14,15,4,5,2,3,0,1,10,11,18,19,8,9,22,23,6,7,12,13,54,55,34,35,24,25,26,27,32,33,28,29,42,43,36,37,20,21,40,41,46,47,38,39,62,63,16,17,60,61,52,53,44,45,48,30,50,56,58},
   {31,56,59,16,60,52,44,48,30,51,58,14,15,4,5,2,3,0,1,10,11,18,19,8,9,22,23,6,7,12,13,54,55,34,35,24,25,26,27,32,33,28,29,42,43,36,37,20,21,40,41,46,47,38,39,62,63,17,61,53,45,49,50,57},
   {40,21,38,63,60,53,30,49,56,59,29,43,37,20,47,62,17,52,45,48,51,58,0,1,14,15,4,5,2,3,18,19,10,11,8,9,22,23,6,7,12,13,54,55,34,35,24,25,26,27,32,33,28,42,36,41,46,39,16,61,44,31,50,57},
   {47,62,17,52,45,48,51,58,43,37,41,21,38,63,60,53,30,49,57,59,0,1,14,15,4,5,2,3,18,19,10,11,8,9,22,23,6,7,12,13,54,55,34,35,24,25,26,27,32,33,28,29,42,36,40,20,46,39,16,61,44,31,50,56},
   {51,57,59,0,1,14,15,4,5,2,3,18,19,10,11,8,9,22,23,6,7,12,13,54,55,34,35,24,25,26,27,32,33,28,29,42,43,36,37,40,41,20,21,46,47,38,39,62,63,16,17,60,61,52,53,44,45,30,31,48,49,50,56,58}},
  {{2,2,1,0,2,3,3,2},{3,4,4,3,3,2,2,0},{0,0,2,1,1,0,0,3},{8,8,8,8,8,8,8,8},
   {6,6,6,6,6,6,6,6},{4,3,3,4,4,4,4,5},{9,9,9,9,9,9,9,9},{1,1,0,2,0,1,1,1},
   {2,10,11,3,3,0,11,3},{5,5,5,5,5,5,5,4},{5,5,7,7,7,9,8,8},{7,7,7,7,7,7,7,7},
   {12,12,12,12,12,2,2,0},{13,13,4,3,3,0,4,3},{3,15,3,4,5,5,0,4},{14,9,6,8,0,8,7,9},
   {14,14,2,1,4,4,5,5},{11,11,11,11,11,11,11,11},{4,3,6,6,6,6,7,7},{7,8,0,0,0,7,10,10},
   {6,6,8,8,8,8,9,9},{0,4,5,5,1,1,1,6},{11,13,3,4,5,5,0,7},{8,7,10,10,10,10,2,0},
   {0,4,7,0,8,7,10,8},{4,3,10,10,10,10,2,0},{13,12,2,1,4,1,1,6},{10,10,10,10,10,10,10,10},
   {5,5,12,12,12,2,11,3},{7,8,11,3,3,0,4,11},{9,11,4,11,11,11,6,5},{1,0,12,12,12,2,4,11}},
  {{255,255,255,255,255,255,255,255},{255,255,255,255,255,255,255,255},{255,255,255,255,255,255,255,255},{255,255,255,255,255,255,255,255},
   {255,255,255,255,255,255,255,255},{255,255,255,255,255,255,255,255},{255,255,255,255,255,255,255,255},{255,255,255,255,255,255,255,255},
   {0,27,17,13,13,13,17,13},{255,255,255,255,255,255,255,255},{9,9,11,11,11,6,3,3},{255,255,255,255,255,255,255,255},
   {255,255,255,255,255,1,1,1},{255,255,1,1,1,2,5,2},{1,255,5,5,9,9,2,9},{16,6,18,20,19,20,18,20},
   {255,255,2,2,5,5,9,5},{255,255,255,255,255,255,255,255},{5,5,4,4,4,4,11,11},{11,3,7,0,7,11,27,27},
   {4,4,3,3,3,3,6,6},{2,1,9,9,2,7,7,4},{17,13,14,14,14,14,14,18},{3,11,27,27,27,27,12,12},
   {21,21,10,19,20,19,19,10},{18,18,23,23,23,23,23,23},{13,12,16,16,16,21,21,21},{255,255,255,255,255,255,255,255},
   {10,10,31,31,31,31,8,8},{19,19,8,8,8,8,31,31},{6,17,13,17,17,17,4,16},{7,2,12,12,12,12,13,17}},
  {112,113,114,115,116,117,118,119,120,121,122,123,124,125,126,127,128,129,130,131,132,133,134,135,136,137,138,139,140,141,142,143,144,145,146,147,148,149,150,151,152,153,154,155,156,157,158,159,647,391,397,163,164,165,166,167,168,169,170,171,172,173,174,175,15,177,178,179,180,54,182,183,184,185,186,187,188,189,190,191,192,193,9,47,51,88,45,16,200,201,202,203,204,205,206,207,3,0,38,72,73,8,2,215,388,40,39,36,75,643,6,4,644,78,76,227,228,229,230,387,232,20,61,444,236,237,97,94,43,79,77,243,244,245,80,42,44,1,653,74,37,7,383,255,17,257,378,48,49,46,262,263,264,81,52,385,641,377,83,84,85,11,10,275,276,50,13,14,280,41,634,283,284,285,286,287,95,90,18,56,700,407,92,93,86,12,53,633,300,301,89,87,96,91,443,307,308,309,310,311,312,313,699,315,316,32,318,319,24,21,62,663,60,98,55,25,5,329,330,639,398,654,334,335,28,337,442,33,34,63,670,27,29,414,698,64,35,65,31,30,26,353,19,57,58,59,22,23,360,82,362,363,364,365,366,367},
  {511,511,511,511,511,511,511,511,511,511,511,511,511,511,511,511,511,511,511,511,511,511,511,511,511,511,511,511,511,511,511,511,511,511,511,511,511,511,511,511,511,511,511,511,511,511,511,511,7,7,5,511,511,511,511,511,511,511,511,511,511,511,511,511,257,511,511,511,511,258,511,511,511,511,511,511,511,511,511,511,511,511,257,257,257,257,257,257,511,511,511,511,511,511,511,511,256,256,256,256,256,256,256,511,4,256,256,256,256,59,256,256,4,256,256,511,511,511,511,59,511,258,258,52,511,511,258,258,256,256,256,511,511,511,256,256,256,256,5,256,256,256,63,511,257,511,2,257,257,257,511,511,511,257,257,1,1,57,257,257,257,257,257,511,511,257,257,257,511,256,2,511,511,511,511,511,258,258,258,258,52,119,258,258,257,257,257,57,511,511,257,257,258,258,51,511,511,511,511,511,511,511,51,511,511,259,511,511,258,258,258,119,258,258,258,258,256,511,511,63,6,6,511,511,259,511,50,259,259,259,134,259,259,134,50,259,259,259,259,259,258,511,258,258,258,258,258,258,511,257,511,511,511,511,511,511}};

typedef CUresult (*EncodeFn)(CUtensorMap*, CUtensorMapDataType, cuuint32_t, void*, const cuuint64_t*, const cuuint64_t*, const cuuint32_t*,
                             const cuuint32_t*, CUtensorMapInterleave, CUtensorMapSwizzle, CUtensorMapL2promotion, CUtensorMapFloatOOBfill);

void make_map2(EncodeFn enc, CUtensorMap* m, const void* ptr, int rows, int cols, int box_rows) {
  cuuint64_t dim[2] = {(cuuint64_t)cols, (cuuint64_t)rows}, str[1] = {(cuuint64_t)cols * 2};
  cuuint32_t box[2] = {64, (cuuint32_t)box_rows}, es[2] = {1, 1};
  enc(m, CU_TENSOR_MAP_DATA_TYPE_BFLOAT16, 2, const_cast<void*>(ptr), dim, str, box, es, CU_TENSOR_MAP_INTERLEAVE_NONE, CU_TENSOR_MAP_SWIZZLE_128B,
      CU_TENSOR_MAP_L2_PROMOTION_L2_128B, CU_TENSOR_MAP_FLOAT_OOB_FILL_NONE);
}
void make_map3(EncodeFn enc, CUtensorMap* m, const void* ptr, int rows) {
  cuuint64_t dim[3] = {64, (cuuint64_t)rows, 9}, str[2] = {DM * 2, 128};
  cuuint32_t box[3] = {64, 32, 3}, es[3] = {1, 1, 1};
  enc(m, CU_TENSOR_MAP_DATA_TYPE_BFLOAT16, 3, const_cast<void*>(ptr), dim, str, box, es, CU_TENSOR_MAP_INTERLEAVE_NONE, CU_TENSOR_MAP_SWIZZLE_128B,
      CU_TENSOR_MAP_L2_PROMOTION_L2_128B, CU_TENSOR_MAP_FLOAT_OOB_FILL_NONE);
}

void make_map_t(EncodeFn enc, CUtensorMap* m, void* ptr, int width, int cols) {
  cuuint64_t dim[3] = {SEQ / 2, 2, 864}, str[2] = {SEQ * 2, SEQ * 4};
  cuuint32_t box[3] = {(cuuint32_t)width, 2, (cuuint32_t)cols}, es[3] = {1, 1, 1};
  enc(m, CU_TENSOR_MAP_DATA_TYPE_UINT32, 3, ptr, dim, str, box, es, CU_TENSOR_MAP_INTERLEAVE_NONE, cols == 64 ? CU_TENSOR_MAP_SWIZZLE_128B : CU_TENSOR_MAP_SWIZZLE_NONE,
      CU_TENSOR_MAP_L2_PROMOTION_NONE, CU_TENSOR_MAP_FLOAT_OOB_FILL_NONE);
}

int g_mode = -1;

}

extern "C" void kernel_launch(void* const* d_in, const int* in_sizes, int n_in, void* d_out, int out_size) {
  static EncodeFn enc = nullptr;
  static void* t_ptr = nullptr;
  if (!enc) {
    void* fn = nullptr;
    cudaDriverEntryPointQueryResult st;
    cudaGetDriverEntryPoint("cuTensorMapEncodeTiled", &fn, cudaEnableDefault, &st);
    enc = (EncodeFn)fn;
    cudaGetSymbolAddress(&t_ptr, g_S);
    cudaFuncSetAttribute(fused_kernel, cudaFuncAttributeMaxDynamicSharedMemorySize, SMEM_BYTES);
    if (g_mode < 0) {
      cudaLaunchConfig_t cfg = {};
      cfg.gridDim = dim3(2 * NCL); cfg.blockDim = dim3(384); cfg.dynamicSmemBytes = SMEM_BYTES;
      cudaLaunchAttribute at; at.id = cudaLaunchAttributeClusterDimension;
      at.val.clusterDim.x = 2; at.val.clusterDim.y = 1; at.val.clusterDim.z = 1;
      cfg.attrs = &at; cfg.numAttrs = 1;
      int nc = 0;
      g_mode = (cudaOccupancyMaxActiveClusters(&nc, fused_kernel, &cfg) == cudaSuccess && nc >= NCL) ? 1 : 0;
      (void)cudaGetLastError();
    }
  }
  Params p;
  make_map2(enc, &p.map_a[0], d_in[4], SEQ, DC, 128);
  make_map2(enc, &p.map_a[1], d_in[0], SEQ, DM, 128);
  make_map2(enc, &p.map_w[0], d_in[6], DC, 4096, 64);
  make_map2(enc, &p.map_w[1], d_in[7], DC, 4096, 64);
  make_map2(enc, &p.map_w[2], d_in[5], DM, 4096, 64);
  make_map2(enc, &p.map_w[3], d_in[1], DM, 1728, 64);
  make_map3(enc, &p.map_o[0], d_in[8], 4096);
  make_map3(enc, &p.map_o[1], d_in[2], DM);
  make_map_t(enc, &p.map_t[0], t_ptr, 32, 9);
  make_map_t(enc, &p.map_t[1], t_ptr, 40, 9);
  make_map_t(enc, &p.map_t[2], t_ptr, 32, 64);
  p.x = (const __nv_bfloat16*)d_in[0];
  p.gate_w = (const __nv_bfloat16*)d_in[9];
  make_map2(enc, &p.map_out, d_out, SEQ, DM, 64);
  p.out = (__nv_bfloat16*)d_out;
  p.zero = 0;
  auto launch = [&](int phases) {
    p.s = k_sched;
    for (int i = 0; i < NCL; i++) {
      Rec& r = p.s.r[i];
      if (!(phases & 1)) r.n1 = 0;
      if (!(phases & 2)) r.n2 = 0;
      if (!(phases & (p.s.task[i][1] == 64 ? 4 : 32))) r.p3 = 255;
      if (!(phases & 8)) r.bg = 255;
      const int u1 = r.n1 ? 8 + r.n1 * (8 + (r.slab >> 3)) : 0;
      int u2 = 0;
      for (int k = 0; k < r.n2; k++) u2 += 4 * (r.item[k] & 7) + 4;
      r.u1 = (uint8_t)u1; r.u2 = (uint8_t)u2;
      r.rot = (uint8_t)(((u1 % 10 + 1) >> 1) % 5);
      r.x3 = (uint8_t)((r.rot + u2) % 5 & 3);
      r.phases = (uint8_t)phases;
    }
    if (!(phases & 16))
      for (int i = 0; i < 256; i++) { p.s.slot[i >> 3][i & 7] = (uint8_t)(i >> 3); p.s.prev[i >> 3][i & 7] = 255; p.s.qblk[i] = (uint16_t)(S_Q + i); p.s.qdep[i] = 511; }
    fused_kernel<<<2 * NCL, 384, SMEM_BYTES>>>(p);
  };
  if (g_mode == 1) launch(63);
  else { launch(1); launch(10); launch(4); launch(32); }
}
```

```cpp
#include <cuda_runtime.h>
#include <cuda_bf16.h>
#include <cuda.h>
#include <stdint.h>

namespace {

constexpr int SEQ = 2048, DM = 576, DC = 512, NH = 32;
constexpr int NCL = 66;
constexpr uint32_t DESC_HI = 0x40000040u;

constexpr int SM_RING = 0;
constexpr int SM_BUF = 163840;
constexpr int SM_BAR = 229376;
constexpr int B_P1E = 0, B_P2E = 10, B_P3E = 15, B_P2F = 24, B_SF = 32, B_ORD = 36, B_LAD = 40, B_DONE = 41, B_FIN = 48;
constexpr int B_P3F = 56, B_OUT = 61, B_P1F = 64, B_SE = 74, B_QF = 80, B_LA = 84, B_NUM = 88;
constexpr uint64_t B_CNT = 0x11118245000ull;
constexpr int SMEM_BYTES = SM_BAR + B_NUM * 8 + 1024;

constexpr int F_QKVA = 32;
constexpr int F_GATE = 64;
constexpr int F_TS = 68;
constexpr int F_DONE = 65;
constexpr int F_CTX = 96;
constexpr int F_OUT = 96 + 8 * 64;
constexpr int F_KV = F_OUT + 64;
constexpr int F_Q = F_KV + 256;
constexpr int F_RD = F_Q + 256;
constexpr int F_NUM = F_RD + 256;

struct Rec {
  uint8_t slab;
  uint8_t n1, n2;
  uint8_t p3;
  uint8_t bg;
  uint8_t item[11];
  uint8_t last[11];
  uint8_t tile[32];
  uint8_t u1, u2;
  uint8_t rot, x3;
  uint8_t phases;
};
struct Sched {
  Rec r[NCL];
  uint8_t task[NCL][4];
  uint8_t p3_order[24][64];
  uint8_t slot[32][8];
  uint8_t prev[32][8];
  uint16_t qblk[256];
  uint16_t qdep[256];
};

#define SCHED_DECL static const

struct Params {
  CUtensorMap map_a[2];
  CUtensorMap map_w[4];
  CUtensorMap map_o[2];
  CUtensorMap map_t[3];
  CUtensorMap map_out;
  const __nv_bfloat16* x;
  const __nv_bfloat16* gate_w;
  __nv_bfloat16* out;
  int zero;
  alignas(64) Sched s;
};

constexpr int S_T = 0, S_Q = 112, S_K = S_Q + 256, S_V = S_K + 256, S_NUM = S_V + 256;
__device__ __align__(1024) uint8_t g_S[(size_t)S_NUM * 65536];
__device__ __align__(1024) uint8_t g_oA[32 * 576 * 128];
__device__ float g_gate[SEQ];
__device__ int g_flags[F_NUM];
#define PL(i)

__device__ __forceinline__ void mbar_arrive(uint32_t b) { asm volatile("mbarrier.arrive.shared::cta.b64 _, [%0];" ::"r"(b) : "memory"); }
__device__ __forceinline__ void mbar_arrive_cl(uint32_t b, int cnt) {
  asm volatile("mbarrier.arrive.shared::cluster.b64 _, [%0], %1;" ::"r"(b), "r"(cnt) : "memory");
}
__device__ __forceinline__ void mbar_wait(uint32_t b, int par) {
  asm volatile(
      "{\n.reg .pred p;\n.reg .u32 c;\n"
      "mbarrier.try_wait.parity.shared::cta.b64 p, [%0], %1;\n@p bra DN;\nmov.u32 c, 0;\n"
      "LP:\nmbarrier.try_wait.parity.shared::cta.b64 p, [%0], %1;\n@p bra DN;\n"
      "add.u32 c, c, 1;\nsetp.lt.u32 p, c, 4000000;\n@p bra LP;\ntrap;\nDN:\n}" ::"r"(b), "r"(par) : "memory");
}
__device__ __forceinline__ bool mbar_test(uint32_t b, int par) {
  uint32_t ok;
  asm volatile("{\n.reg .pred p;\nmbarrier.test_wait.parity.shared::cta.b64 p, [%1], %2;\nselp.u32 %0, 1, 0, p;\n}" : "=r"(ok) : "r"(b), "r"(par) : "memory");
  return __all_sync(0xffffffffu, ok);
}
__device__ __forceinline__ uint32_t mapa(uint32_t a, uint32_t cta) {
  uint32_t r; asm("mapa.shared::cluster.u32 %0, %1, %2;" : "=r"(r) : "r"(a), "r"(cta)); return r;
}
#define ELECT(ins) "{\n.reg .pred e;\nelect.sync _|e, 0xffffffff;\n@e " ins "\n}"
__device__ __forceinline__ void mbar_expect(uint32_t b, int bytes) {
  asm volatile(ELECT("mbarrier.arrive.expect_tx.shared::cta.b64 _, [%0], %1;") ::"r"(b), "r"(bytes) : "memory");
}
__device__ __forceinline__ void mbar_arrive_one(uint32_t b) { asm volatile(ELECT("mbarrier.arrive.shared::cta.b64 _, [%0];") ::"r"(b) : "memory"); }
constexpr uint64_t L2_NORMAL = 0x1000000000000000ull, L2_FIRST = 0x12F0000000000000ull;
__device__ __forceinline__ void bulk_load(uint32_t dst, const void* src, int bytes, uint32_t bar, uint64_t pol = L2_NORMAL) {
  asm volatile(ELECT("cp.async.bulk.shared::cluster.global.mbarrier::complete_tx::bytes.L2::cache_hint [%0], [%1], %2, [%3], %4;") ::"r"(dst), "l"(src), "r"(bytes), "r"(bar), "l"(pol) : "memory");
}
__device__ __forceinline__ void bulk_load_mc(uint32_t dst, const void* src, int bytes, uint32_t bar, uint64_t pol = L2_NORMAL) {
  asm volatile(ELECT("cp.async.bulk.shared::cluster.global.mbarrier::complete_tx::bytes.multicast::cluster.L2::cache_hint [%0], [%1], %2, [%3], %4, %5;") ::"r"(dst), "l"(src), "r"(bytes), "r"(bar), "h"((uint16_t)3), "l"(pol) : "memory");
}
__device__ __forceinline__ void bulk_store(void* dst, uint32_t src, int bytes, uint64_t pol = L2_NORMAL) {
  asm volatile(ELECT("cp.async.bulk.global.shared::cta.bulk_group.L2::cache_hint [%0], [%1], %2, %3;") ::"l"(dst), "r"(src), "r"(bytes), "l"(pol) : "memory");
}
__device__ __forceinline__ void tma2d(uint32_t dst, const CUtensorMap* m, int c0, int c1, uint32_t bar, uint64_t pol = L2_NORMAL) {
  asm volatile(ELECT("cp.async.bulk.tensor.2d.shared::cluster.global.mbarrier::complete_tx::bytes.L2::cache_hint [%0], [%1, {%3, %4}], [%2], %5;") ::"r"(dst), "l"(m), "r"(bar), "r"(c0), "r"(c1), "l"(pol) : "memory");
}
__device__ __forceinline__ void tma2d_mc(uint32_t dst, const CUtensorMap* m, int c0, int c1, uint32_t bar, uint64_t pol = L2_NORMAL) {
  asm volatile(ELECT("cp.async.bulk.tensor.2d.shared::cluster.global.mbarrier::complete_tx::bytes.multicast::cluster.L2::cache_hint [%0], [%1, {%3, %4}], [%2], %5, %6;") ::"r"(dst), "l"(m), "r"(bar), "r"(c0), "r"(c1), "h"((uint16_t)3), "l"(pol) : "memory");
}
__device__ __forceinline__ void tma3d(uint32_t dst, const CUtensorMap* m, int c0, int c1, int c2, uint32_t bar, uint64_t pol = L2_NORMAL) {
  asm volatile(ELECT("cp.async.bulk.tensor.3d.shared::cluster.global.mbarrier::complete_tx::bytes.L2::cache_hint [%0], [%1, {%3, %4, %5}], [%2], %6;") ::"r"(dst), "l"(m), "r"(bar), "r"(c0), "r"(c1), "r"(c2), "l"(pol) : "memory");
}
__device__ __forceinline__ void tma3d_mc(uint32_t dst, const CUtensorMap* m, int c0, int c1, int c2, uint32_t bar, uint64_t pol = L2_NORMAL) {
  asm volatile(ELECT("cp.async.bulk.tensor.3d.shared::cluster.global.mbarrier::complete_tx::bytes.multicast::cluster.L2::cache_hint [%0], [%1, {%3, %4, %5}], [%2], %6, %7;") ::"r"(dst), "l"(m), "r"(bar), "r"(c0), "r"(c1), "r"(c2), "h"((uint16_t)3), "l"(pol) : "memory");
}
__device__ __forceinline__ void tma2d_add(const CUtensorMap* m, uint32_t src, int c0, int c1) {
  asm volatile(ELECT("cp.reduce.async.bulk.tensor.2d.global.shared::cta.add.bulk_group [%0, {%2, %3}], [%1];") ::"l"(m), "r"(src), "r"(c0), "r"(c1) : "memory");
}
__device__ __forceinline__ void tma3d_store(const CUtensorMap* m, uint32_t src, int c0, int c1, int c2, uint64_t pol = L2_NORMAL) {
  asm volatile(ELECT("cp.async.bulk.tensor.3d.global.shared::cta.bulk_group.L2::cache_hint [%0, {%2, %3, %4}], [%1], %5;") ::"l"(m), "r"(src), "r"(c0), "r"(c1), "r"(c2), "l"(pol) : "memory");
}
__device__ __forceinline__ void tma2d_prefetch(const CUtensorMap* m, int c0, int c1, uint64_t pol = L2_NORMAL) {
  asm volatile(ELECT("cp.async.bulk.prefetch.tensor.2d.L2.global.L2::cache_hint [%0, {%1, %2}], %3;") ::"l"(m), "r"(c0), "r"(c1), "l"(pol) : "memory");
}
#define LAG 3
#define HINT 62
#define POL(bit) ((HINT >> (bit)) & 1 ? L2_FIRST : L2_NORMAL)
#define BULK_COMMIT() asm volatile("cp.async.bulk.commit_group;" ::: "memory")
#define BULK_WAIT(n) asm volatile("cp.async.bulk.wait_group %0;" ::"n"(n) : "memory")
#define BULK_WAIT_READ(n) asm volatile("cp.async.bulk.wait_group.read %0;" ::"n"(n) : "memory")
#define FENCE_ASYNC_SMEM() asm volatile("fence.proxy.async.shared::cta;" ::: "memory")
#define FENCE_ASYNC_ALL() asm volatile("fence.proxy.async;" ::: "memory")
#define WG_FENCE() asm volatile("wgmma.fence.sync.aligned;" ::: "memory")
#define WG_COMMIT() asm volatile("wgmma.commit_group.sync.aligned;" ::: "memory")
#define WG_WAIT(n) asm volatile("wgmma.wait_group.sync.aligned %0;" ::"n"(n) : "memory")
__device__ __forceinline__ void bar_sync(int id, int n) { asm volatile("bar.sync %0, %1;" ::"r"(id), "r"(n) : "memory"); }
__device__ __forceinline__ void bar_arrive(int id, int n) { asm volatile("bar.arrive %0, %1;" ::"r"(id), "r"(n) : "memory"); }
__device__ __forceinline__ void cluster_sync() {
  asm volatile("barrier.cluster.arrive.relaxed;\nbarrier.cluster.wait.acquire;" ::: "memory");
}
template <int N> __device__ __forceinline__ void pin(float (&r)[N]) {
#pragma unroll
  for (int i = 0; i < N; i++) asm volatile("" : "+f"(r[i])::"memory");
}
template <int N> __device__ __forceinline__ void pin(uint32_t (&r)[N]) {
#pragma unroll
  for (int i = 0; i < N; i++) asm volatile("" : "+r"(r[i])::"memory");
}
__device__ __forceinline__ uint32_t pack_bf16(float lo, float hi) {
  uint32_t r; asm("cvt.rn.bf16x2.f32 %0, %1, %2;" : "=r"(r) : "f"(hi), "f"(lo)); return r;
}
__device__ __forceinline__ float ex2(float x) { float r; asm("ex2.approx.ftz.f32 %0, %1;" : "=f"(r) : "f"(x)); return r; }
__device__ __forceinline__ void ldsm4(uint32_t a, uint32_t& r0, uint32_t& r1, uint32_t& r2, uint32_t& r3) {
  asm volatile("ldmatrix.sync.aligned.m8n8.x4.shared.b16 {%0,%1,%2,%3}, [%4];" : "=r"(r0), "=r"(r1), "=r"(r2), "=r"(r3) : "r"(a) : "memory");
}
__device__ __forceinline__ void stsm4(uint32_t a, uint32_t r0, uint32_t r1, uint32_t r2, uint32_t r3) {
  asm volatile("stmatrix.sync.aligned.m8n8.x4.shared.b16 [%0], {%1,%2,%3,%4};" ::"r"(a), "r"(r0), "r"(r1), "r"(r2), "r"(r3) : "memory");
}
__device__ __forceinline__ void flag_add(int idx, int v = 1) {
  asm volatile(ELECT("red.release.gpu.global.add.s32 [%0], %1;") ::"l"(g_flags + idx), "r"(v) : "memory");
}
__device__ __forceinline__ void flag_add_rx(int idx, int v = 1) {
  asm volatile(ELECT("red.relaxed.gpu.global.add.s32 [%0], %1;") ::"l"(g_flags + idx), "r"(v) : "memory");
}
template <bool ACQ, int NS = 32> __device__ __forceinline__ void flag_wait(int idx, int target) {
  int n = 0;
  while (true) {
    int v;
    if (ACQ) asm volatile("ld.acquire.gpu.global.s32 %0, [%1];" : "=r"(v) : "l"(g_flags + idx) : "memory");
    else asm volatile("ld.relaxed.gpu.global.s32 %0, [%1];" : "=r"(v) : "l"(g_flags + idx) : "memory");
    if (__all_sync(0xffffffffu, v >= target)) break;
    if (++n > 20000000) __trap();
    __nanosleep(NS);
  }
}
__device__ __forceinline__ int flag_peek(int idx) {
  int v;
  asm volatile("ld.relaxed.gpu.global.s32 %0, [%1];" : "=r"(v) : "l"(g_flags + idx) : "memory");
  return v;
}
__device__ __forceinline__ void mask_wait(uint32_t& ready, int bit, int idx, int target) {
  for (int n = 0; !((ready >> bit) & 1); n++) {
    int v;
    if (n) { __nanosleep(32); if (n > 20000000) __trap(); }
    asm volatile("ld.relaxed.gpu.global.s32 %0, [%1];" : "=r"(v) : "l"(g_flags + idx) : "memory");
    ready = __ballot_sync(0xffffffffu, v >= target);
  }
}
__device__ __forceinline__ uint32_t desc_lo(uint32_t addr, uint32_t lbo) { return ((addr & 0x3FFFFu) >> 4) | ((lbo >> 4) << 16); }
#define PROF(role, i)
#define PROFX(cond, i)
#define PROFB(i)
#define PROFG(i)

template <int TB, int TA = 0> __device__ __forceinline__ void wgmma_ss64(float (&d)[32], uint32_t alo, uint32_t blo, int sd) {
  asm volatile("{\n.reg .pred p;\n.reg .b64 da, db;\n"
    "setp.ne.b32 p, %34, 0;\nmov.b64 da, {%32, %36};\nmov.b64 db, {%33, %36};\n"
    "wgmma.mma_async.sync.aligned.m64n64k16.f32.bf16.bf16 "
    "{%0,%1,%2,%3,%4,%5,%6,%7,%8,%9,%10,%11,%12,%13,%14,%15,%16,%17,%18,%19,%20,%21,%22,%23,"
    "%24,%25,%26,%27,%28,%29,%30,%31}, "
    "da, db, p, 1, 1, %37, %35;\n}\n"
    : "+f"(d[0]),"+f"(d[1]),"+f"(d[2]),"+f"(d[3]),"+f"(d[4]),"+f"(d[5]),"+f"(d[6]),"+f"(d[7]),"+f"(d[8]),"+f"(d[9]),"+f"(d[10]),"+f"(d[11]),
      "+f"(d[12]),"+f"(d[13]),"+f"(d[14]),"+f"(d[15]),"+f"(d[16]),"+f"(d[17]),"+f"(d[18]),"+f"(d[19]),"+f"(d[20]),"+f"(d[21]),"+f"(d[22]),"+f"(d[23]),
      "+f"(d[24]),"+f"(d[25]),"+f"(d[26]),"+f"(d[27]),"+f"(d[28]),"+f"(d[29]),"+f"(d[30]),"+f"(d[31])
    : "r"(alo), "r"(blo), "r"(sd), "n"(TB), "r"(DESC_HI), "n"(TA));
}
template <int TB, int TA = 0> __device__ __forceinline__ void wgmma_ss128(float (&d)[64], uint32_t alo, uint32_t blo, int sd) {
  asm volatile("{\n.reg .pred p;\n.reg .b64 da, db;\n"
    "setp.ne.b32 p, %66, 0;\nmov.b64 da, {%64, %68};\nmov.b64 db, {%65, %68};\n"
    "wgmma.mma_async.sync.aligned.m64n128k16.f32.bf16.bf16 "
    "{%0,%1,%2,%3,%4,%5,%6,%7,%8,%9,%10,%11,%12,%13,%14,%15,%16,%17,%18,%19,%20,%21,%22,%23,"
    "%24,%25,%26,%27,%28,%29,%30,%31,%32,%33,%34,%35,%36,%37,%38,%39,%40,%41,%42,%43,%44,%45,%46,%47,"
    "%48,%49,%50,%51,%52,%53,%54,%55,%56,%57,%58,%59,%60,%61,%62,%63}, "
    "da, db, p, 1, 1, %69, %67;\n}\n"
    : "+f"(d[0]),"+f"(d[1]),"+f"(d[2]),"+f"(d[3]),"+f"(d[4]),"+f"(d[5]),"+f"(d[6]),"+f"(d[7]),"+f"(d[8]),"+f"(d[9]),"+f"(d[10]),"+f"(d[11]),
      "+f"(d[12]),"+f"(d[13]),"+f"(d[14]),"+f"(d[15]),"+f"(d[16]),"+f"(d[17]),"+f"(d[18]),"+f"(d[19]),"+f"(d[20]),"+f"(d[21]),"+f"(d[22]),"+f"(d[23]),
      "+f"(d[24]),"+f"(d[25]),"+f"(d[26]),"+f"(d[27]),"+f"(d[28]),"+f"(d[29]),"+f"(d[30]),"+f"(d[31]),"+f"(d[32]),"+f"(d[33]),"+f"(d[34]),"+f"(d[35]),
      "+f"(d[36]),"+f"(d[37]),"+f"(d[38]),"+f"(d[39]),"+f"(d[40]),"+f"(d[41]),"+f"(d[42]),"+f"(d[43]),"+f"(d[44]),"+f"(d[45]),"+f"(d[46]),"+f"(d[47]),
      "+f"(d[48]),"+f"(d[49]),"+f"(d[50]),"+f"(d[51]),"+f"(d[52]),"+f"(d[53]),"+f"(d[54]),"+f"(d[55]),"+f"(d[56]),"+f"(d[57]),"+f"(d[58]),"+f"(d[59]),
      "+f"(d[60]),"+f"(d[61]),"+f"(d[62]),"+f"(d[63])
    : "r"(alo), "r"(blo), "r"(sd), "n"(TB), "r"(DESC_HI), "n"(TA));
}
template <int TB> __device__ __forceinline__ void wgmma_rs128(float (&d)[64], uint32_t a0, uint32_t a1, uint32_t a2, uint32_t a3, uint32_t blo, int sd) {
  asm volatile("{\n.reg .pred p;\n.reg .b64 db;\n"
    "setp.ne.b32 p, %69, 0;\nmov.b64 db, {%68, %71};\n"
    "wgmma.mma_async.sync.aligned.m64n128k16.f32.bf16.bf16 "
    "{%0,%1,%2,%3,%4,%5,%6,%7,%8,%9,%10,%11,%12,%13,%14,%15,%16,%17,%18,%19,%20,%21,%22,%23,"
    "%24,%25,%26,%27,%28,%29,%30,%31,%32,%33,%34,%35,%36,%37,%38,%39,%40,%41,%42,%43,%44,%45,%46,%47,"
    "%48,%49,%50,%51,%52,%53,%54,%55,%56,%57,%58,%59,%60,%61,%62,%63}, "
    "{%64,%65,%66,%67}, db, p, 1, 1, %70;\n}\n"
    : "+f"(d[0]),"+f"(d[1]),"+f"(d[2]),"+f"(d[3]),"+f"(d[4]),"+f"(d[5]),"+f"(d[6]),"+f"(d[7]),"+f"(d[8]),"+f"(d[9]),"+f"(d[10]),"+f"(d[11]),
      "+f"(d[12]),"+f"(d[13]),"+f"(d[14]),"+f"(d[15]),"+f"(d[16]),"+f"(d[17]),"+f"(d[18]),"+f"(d[19]),"+f"(d[20]),"+f"(d[21]),"+f"(d[22]),"+f"(d[23]),
      "+f"(d[24]),"+f"(d[25]),"+f"(d[26]),"+f"(d[27]),"+f"(d[28]),"+f"(d[29]),"+f"(d[30]),"+f"(d[31]),"+f"(d[32]),"+f"(d[33]),"+f"(d[34]),"+f"(d[35]),
      "+f"(d[36]),"+f"(d[37]),"+f"(d[38]),"+f"(d[39]),"+f"(d[40]),"+f"(d[41]),"+f"(d[42]),"+f"(d[43]),"+f"(d[44]),"+f"(d[45]),"+f"(d[46]),"+f"(d[47]),
      "+f"(d[48]),"+f"(d[49]),"+f"(d[50]),"+f"(d[51]),"+f"(d[52]),"+f"(d[53]),"+f"(d[54]),"+f"(d[55]),"+f"(d[56]),"+f"(d[57]),"+f"(d[58]),"+f"(d[59]),
      "+f"(d[60]),"+f"(d[61]),"+f"(d[62]),"+f"(d[63])
    : "r"(a0), "r"(a1), "r"(a2), "r"(a3), "r"(blo), "r"(sd), "n"(TB), "r"(DESC_HI));
}
template <int TB, int TA = 0> __device__ __forceinline__ void wgmma_ss192(float (&d)[96], uint32_t alo, uint32_t blo, int sd) {
  asm volatile("{\n.reg .pred p;\n.reg .b64 da, db;\n"
    "setp.ne.b32 p, %98, 0;\nmov.b64 da, {%96, %100};\nmov.b64 db, {%97, %100};\n"
    "wgmma.mma_async.sync.aligned.m64n192k16.f32.bf16.bf16 "
    "{%0,%1,%2,%3,%4,%5,%6,%7,%8,%9,%10,%11,%12,%13,%14,%15,%16,%17,%18,%19,%20,%21,%22,%23,"
    "%24,%25,%26,%27,%28,%29,%30,%31,%32,%33,%34,%35,%36,%37,%38,%39,%40,%41,%42,%43,%44,%45,%46,%47,"
    "%48,%49,%50,%51,%52,%53,%54,%55,%56,%57,%58,%59,%60,%61,%62,%63,%64,%65,%66,%67,%68,%69,%70,%71,"
    "%72,%73,%74,%75,%76,%77,%78,%79,%80,%81,%82,%83,%84,%85,%86,%87,%88,%89,%90,%91,%92,%93,%94,%95}, "
    "da, db, p, 1, 1, %101, %99;\n}\n"
    : "+f"(d[0]),"+f"(d[1]),"+f"(d[2]),"+f"(d[3]),"+f"(d[4]),"+f"(d[5]),"+f"(d[6]),"+f"(d[7]),"+f"(d[8]),"+f"(d[9]),"+f"(d[10]),"+f"(d[11]),
      "+f"(d[12]),"+f"(d[13]),"+f"(d[14]),"+f"(d[15]),"+f"(d[16]),"+f"(d[17]),"+f"(d[18]),"+f"(d[19]),"+f"(d[20]),"+f"(d[21]),"+f"(d[22]),"+f"(d[23]),
      "+f"(d[24]),"+f"(d[25]),"+f"(d[26]),"+f"(d[27]),"+f"(d[28]),"+f"(d[29]),"+f"(d[30]),"+f"(d[31]),"+f"(d[32]),"+f"(d[33]),"+f"(d[34]),"+f"(d[35]),
      "+f"(d[36]),"+f"(d[37]),"+f"(d[38]),"+f"(d[39]),"+f"(d[40]),"+f"(d[41]),"+f"(d[42]),"+f"(d[43]),"+f"(d[44]),"+f"(d[45]),"+f"(d[46]),"+f"(d[47]),
      "+f"(d[48]),"+f"(d[49]),"+f"(d[50]),"+f"(d[51]),"+f"(d[52]),"+f"(d[53]),"+f"(d[54]),"+f"(d[55]),"+f"(d[56]),"+f"(d[57]),"+f"(d[58]),"+f"(d[59]),
      "+f"(d[60]),"+f"(d[61]),"+f"(d[62]),"+f"(d[63]),"+f"(d[64]),"+f"(d[65]),"+f"(d[66]),"+f"(d[67]),"+f"(d[68]),"+f"(d[69]),"+f"(d[70]),"+f"(d[71]),
      "+f"(d[72]),"+f"(d[73]),"+f"(d[74]),"+f"(d[75]),"+f"(d[76]),"+f"(d[77]),"+f"(d[78]),"+f"(d[79]),"+f"(d[80]),"+f"(d[81]),"+f"(d[82]),"+f"(d[83]),
      "+f"(d[84]),"+f"(d[85]),"+f"(d[86]),"+f"(d[87]),"+f"(d[88]),"+f"(d[89]),"+f"(d[90]),"+f"(d[91]),"+f"(d[92]),"+f"(d[93]),"+f"(d[94]),"+f"(d[95])
    : "r"(alo), "r"(blo), "r"(sd), "n"(TB), "r"(DESC_HI), "n"(TA));
}

struct Ctx {
  uint32_t sm;
  uint32_t bar;
  uint32_t rbar;
  int cl, rank, wg, warp, lane, phases;
};
__device__ __forceinline__ void release(const Ctx& c, int b, int cnt = 1) {
  if (c.lane < 2) mbar_arrive_cl(c.rbar + b * 8, cnt);
}
#define HK 5
#define NPRO 6
#define ZLEAD 14
#define PFM 7
#define PF1 1
constexpr float SM_SCALE = 0.08838834764831845f * 1.4426950408889634f;
constexpr float SM_HI = 1.8446744e19f, SM_LO = 5.4210109e-20f;
constexpr int ORDER = 1;

__device__ __forceinline__ void stage_tile(const float (&a)[64], uint32_t buf, const Ctx& c, float s0, float s1) {
  const int row = (c.lane & 7) + ((c.lane >> 3) & 1) * 8;
  const uint32_t base = buf + (c.warp * 16 + row) * 128 + (((c.lane >> 4) ^ (row & 7)) << 4);
#pragma unroll
  for (int i = 0; i < 8; i++)
    stsm4((base ^ ((i & 3) << 5)) + (i >> 2) * 8192, pack_bf16(a[8 * i] * s0, a[8 * i + 1] * s0), pack_bf16(a[8 * i + 2] * s1, a[8 * i + 3] * s1),
          pack_bf16(a[8 * i + 4] * s0, a[8 * i + 5] * s0), pack_bf16(a[8 * i + 6] * s1, a[8 * i + 7] * s1));
}

__device__ __forceinline__ void p1_epilogue(const Params& p, const Ctx& c, const float (&acc)[64], int t, int type) {
  const int tile = p.s.r[c.cl].tile[t] & 63, b = c.wg * 2 + 1;
  mbar_wait(c.bar + (B_SE + b) * 8, (t & 1) ^ 1);
  if (type && tile >= 32) {
    const int r = 2 * (c.lane & 3) + ((c.lane >> 2) & 1);
    const uint32_t dst = c.sm + SM_BUF + b * 16384 + r * 128 + (((c.warp * 2) ^ r) << 4) + (c.lane >> 3) * 4;
#pragma unroll
    for (int i = 0; i < 16; i++) {
      asm volatile("st.shared.u32 [%0], %1;" ::"r"(dst + i * 1024), "r"(pack_bf16(acc[4 * i], acc[4 * i + 1])) : "memory");
      asm volatile("st.shared.u32 [%0], %1;" ::"r"((dst ^ 16) + i * 1024), "r"(pack_bf16(acc[4 * i + 2], acc[4 * i + 3])) : "memory");
    }
  } else {
    if (type) stage_tile(acc, c.sm + SM_BUF + b * 16384, c, SM_SCALE, SM_SCALE);
    else stage_tile(acc, c.sm + SM_BUF + b * 16384, c, 1.f, 1.f);
  }
  FENCE_ASYNC_SMEM();
  __syncwarp();
  if (c.lane == 0) mbar_arrive(c.bar + (B_SF + b) * 8);
}

__device__ __forceinline__ void p1_consumer(const Params& p, const Ctx& c) {
  const int n = p.s.r[c.cl].n1;
  const int type = p.s.r[c.cl].slab >> 3;
  const uint32_t bdesc = desc_lo(c.sm + SM_RING, 8192), adesc = desc_lo(c.sm + SM_BUF + 32768 + c.wg * 8192, 16);
  uint32_t A[128];
  float acc[64] = {};
  int slot = 0, par = 0;
  auto next = [&]() { if (++slot == 10) { slot = 0; par ^= 1; } };
  {
    const int row = (c.lane & 7) + ((c.lane >> 3) & 1) * 8;
    const uint32_t base = c.sm + SM_RING + (c.wg * 64 + c.warp * 16 + row) * 128 + (((c.lane >> 4) ^ (row & 7)) << 4);
    if (c.wg == 1) bar_sync(ORDER + 1, 256);
    int pa = -1, pb = -1;
    if (type) {
      mbar_wait(c.bar + B_P1F * 8, 0);
      WG_FENCE();
#pragma unroll
      for (int kk = 0; kk < 4; kk++) wgmma_ss128<1>(acc, adesc + kk * 2, bdesc + kk * 128, kk != 0);
      WG_COMMIT();
      pb = 0; slot = 1;
    }
#pragma unroll
    for (int kb = 0; kb < 8; kb++) {
      const int sa = slot;
      mbar_wait(c.bar + (B_P1F + slot) * 8, par);
      if (kb == 0) PROF(c.wg, 5);
      next();
      mbar_wait(c.bar + (B_P1F + slot) * 8, par);
      PROF(c.wg, 6 + 2 * kb);
      WG_FENCE();
#pragma unroll
      for (int kk = 0; kk < 4; kk++)
        wgmma_ss128<1>(acc, desc_lo(c.sm + SM_RING + c.wg * 8192, 16) + sa * 1024 + kk * 2, bdesc + slot * 1024 + kk * 128, (kb | kk) != 0 ? 1 : type);
      WG_COMMIT();
      if (kb == 1 && c.wg == 0) bar_arrive(ORDER + 1, 256);
#pragma unroll
      for (int kk = 0; kk < 4; kk++) ldsm4((base ^ (kk << 5)) + sa * 16384, A[kb * 16 + kk * 4], A[kb * 16 + kk * 4 + 1], A[kb * 16 + kk * 4 + 2], A[kb * 16 + kk * 4 + 3]);
      WG_WAIT(1);
      if (kb > 0) release(c, B_P1E + pa);
      if (kb > 0 || pb >= 0) release(c, B_P1E + pb);
      pa = sa; pb = slot;
      next();
    }
    WG_WAIT(0);
    __syncwarp();
    release(c, B_P1E + pa);
    release(c, B_P1E + pb);
    pin(acc);
    PROF(c.wg, 1);
    p1_epilogue(p, c, acc, 0, type);
    PROF(c.wg, 2);
  }
  for (int t = 1; t < n; t++) {
    bar_sync(ORDER + c.wg, 256);
    int prev1 = -1, prev2 = -1;
    if (type) {
      mbar_wait(c.bar + (B_P1F + slot) * 8, par);
      WG_FENCE();
#pragma unroll
      for (int kk = 0; kk < 4; kk++) wgmma_ss128<1>(acc, adesc + kk * 2, bdesc + slot * 1024 + kk * 128, kk != 0);
      WG_COMMIT();
      prev1 = slot;
      next();
    }
#pragma unroll
    for (int kb = 0; kb < 8; kb++) {
      mbar_wait(c.bar + (B_P1F + slot) * 8, par);
      WG_FENCE();
      const uint32_t d = bdesc + slot * 1024;
#pragma unroll
      for (int kk = 0; kk < 4; kk++)
        wgmma_rs128<1>(acc, A[kb * 16 + kk * 4], A[kb * 16 + kk * 4 + 1], A[kb * 16 + kk * 4 + 2], A[kb * 16 + kk * 4 + 3], d + kk * 128, (kb | kk) != 0 ? 1 : type);
      WG_COMMIT();
      if (kb == HK) {
        if (t + 1 < n || c.wg == 0) bar_arrive(ORDER + (c.wg ^ 1), 256);
      }
      if (kb > 0) { WG_WAIT(2); if (kb > 1 || prev2 >= 0) release(c, B_P1E + prev2); }
      prev2 = prev1; prev1 = slot;
      next();
    }
    WG_WAIT(1);
    release(c, B_P1E + prev2);
    WG_WAIT(0);
    pin(acc);
    release(c, B_P1E + prev1);
    p1_epilogue(p, c, acc, t, type);
    PROF(c.wg, 3);
  }
}

__device__ __forceinline__ void p1_producer(const Params& p, const Ctx& c) {
  const int n = p.s.r[c.cl].n1;
  const int type = p.s.r[c.cl].slab >> 3, grp = p.s.r[c.cl].slab & 7;
  int slot = NPRO % 10, par = NPRO < 10;
#pragma unroll 1
  for (int t = 0; t < n; t++) {
    const int tile = p.s.r[c.cl].tile[t] & 63;
    const CUtensorMap* m = &p.map_w[type * 2 + (tile >> 5)];
    const int n0 = (tile & 31) * 128 + c.rank * 64;
    const int ptile = p.s.r[c.cl].tile[t + PF1 < n ? t + PF1 : t];
    const CUtensorMap* pm = &p.map_w[type * 2 + ((ptile >> 5) & 1)];
    if (t == 7 && (c.phases & 16)) flag_wait<true>(F_GATE, 256);
#pragma unroll 1
    for (int kb = t ? -type : (NPRO - type) >> 1; kb < 8; kb++) {
      if (t == 0 && 2 * kb + type >= NPRO) {
        mbar_wait(c.bar + (B_P1E + slot) * 8, par);
        mbar_expect(c.bar + (B_P1F + slot) * 8, 16384);
        tma2d(c.sm + SM_RING + slot * 16384, &p.map_a[type], kb * 64, grp * 256 + c.rank * 128, c.bar + (B_P1F + slot) * 8);
        if (++slot == 10) { slot = 0; par ^= 1; }
      }
      mbar_wait(c.bar + (B_P1E + slot) * 8, par);
      mbar_expect(c.bar + (B_P1F + slot) * 8, 16384);
      tma2d_mc(c.sm + SM_RING + slot * 16384 + c.rank * 8192, m, n0, kb < 0 ? 512 : kb * 64, c.bar + (B_P1F + slot) * 8);
      if (t == 0 && kb == 1) PROF(2, 61);
      if (t == 0 && kb == 3) PROF(2, 62);
      if (t + PF1 < n && t > 0 && ((ptile & 64) || ((ptile & 128) && ((kb ^ grp) & PFM) == 0))) tma2d_prefetch(pm, (ptile & 31) * 128 + c.rank * 64, kb < 0 ? 512 : kb * 64);
      if (++slot == 10) { slot = 0; par ^= 1; }
    }
  }
}

__device__ __forceinline__ void wait_kv_dead(const Ctx& c, int h, int g) {
  if (g >= 2) flag_wait<false>(F_RD + h * 8 + g, 8 - g);
  else flag_wait<false>(F_CTX + max(c.lane & 7, g) * 64 + h, 4);
}
__device__ __forceinline__ int p1_storer(const Params& p, const Ctx& c) {
  const int n = p.s.r[c.cl].n1;
  const int type = p.s.r[c.cl].slab >> 3, grp = p.s.r[c.cl].slab & 7;
  for (int i = 0; i < 2 * n; i++) {
    const int t = i >> 1, w = i & 1, b = w * 2 + 1;
    const int tile = p.s.r[c.cl].tile[t] & 63;
    mbar_wait(c.bar + (B_SF + b) * 8, t & 1);
    const uint32_t src = c.sm + SM_BUF + b * 16384;
    int f = (type ? F_Q : F_KV) + (tile & 31) * 8 + grp;
    if (type == 0) {
      const int prev = p.s.prev[tile & 31][grp];
      if (prev != 255 && w == 0) wait_kv_dead(c, prev, grp);
      uint8_t* dst = g_S + (size_t)(S_K + ((tile & 32) + p.s.slot[tile & 31][grp]) * 8 + grp) * 65536 + c.rank * 32768 + w * 8192;
      bulk_store(dst, src, 8192);
      bulk_store(dst + 16384, src + 8192, 8192);
    } else if (tile < 32) {
      const int dep = p.s.qdep[tile * 8 + grp];
      if (dep != 511 && w == 0) {
        if (dep < 256) wait_kv_dead(c, dep >> 3, dep & 7);
        else flag_wait<false>(F_TS + dep - 256, 128);
      }
      bulk_store(g_S + (size_t)p.s.qblk[tile * 8 + grp] * 65536 + (c.rank * 2 + w) * 16384, src, 16384);
    } else {
      tma3d_store(&p.map_t[2], src, (grp * 4 + c.rank * 2 + w) * 32, 0, (tile - 32) * 64);
      f = F_QKVA + grp * 4 + ((0xE4390900u >> (2 * (tile - 30))) & 3);
    }
    BULK_COMMIT();
    BULK_WAIT(0);
    mbar_arrive_one(c.bar + (B_SE + b) * 8);
    if (i == 2 * n - 1) return f;
    if (w) flag_add(f, 2);
  }
  return -1;
}

__device__ __forceinline__ int p2_buf(int w, int i) { return w * 2 + (i & 1); }
__device__ __forceinline__ int p2_blk(int rank, int w, int i) { return ((i ^ w) & 1) == 0 ? 3 - rank : rank; }

template <int N>
__device__ __forceinline__ void row_max(const float (&s)[N], float& m0, float& m1) {
  float a0 = fmaxf(s[0], s[1]), a1 = fmaxf(s[2], s[3]);
#pragma unroll
  for (int i = 1; i < N / 4; i++) {
    m0 = fmaxf(m0, s[4 * i]); a0 = fmaxf(a0, s[4 * i + 1]);
    m1 = fmaxf(m1, s[4 * i + 2]); a1 = fmaxf(a1, s[4 * i + 3]);
  }
  m0 = fmaxf(m0, a0); m1 = fmaxf(m1, a1);
  m0 = fmaxf(m0, __shfl_xor_sync(0xffffffffu, m0, 1));
  m1 = fmaxf(m1, __shfl_xor_sync(0xffffffffu, m1, 1));
  m0 = fmaxf(m0, __shfl_xor_sync(0xffffffffu, m0, 2));
  m1 = fmaxf(m1, __shfl_xor_sync(0xffffffffu, m1, 2));
}
template <bool SUB, int N>
__device__ __forceinline__ void row_exp(const float (&s)[N], uint32_t (&P)[32], float m0, float m1, float& t0, float& t1) {
  float u0 = 0.f, u1 = 0.f;
  t0 = t1 = 0.f;
#pragma unroll
  for (int i = 0; i < N / 4; i++) {
    const float e0 = ex2(SUB ? s[4 * i] - m0 : s[4 * i]), e1 = ex2(SUB ? s[4 * i + 1] - m0 : s[4 * i + 1]);
    const float e2 = ex2(SUB ? s[4 * i + 2] - m1 : s[4 * i + 2]), e3 = ex2(SUB ? s[4 * i + 3] - m1 : s[4 * i + 3]);
    if (i == 0) { t0 = e0; u0 = e1; t1 = e2; u1 = e3; }
    else { t0 += e0; u0 += e1; t1 += e2; u1 += e3; }
    P[2 * i] = pack_bf16(e0, e1);
    P[2 * i + 1] = pack_bf16(e2, e3);
  }
#pragma unroll
  for (int i = N / 2; i < 32; i++) P[i] = 0;
  pin(P);
  t0 += u0; t1 += u1;
}
template <int N>
__device__ __forceinline__ void causal_mask(float (&s)[N], int thr) {
#pragma unroll
  for (int i = 0; i < 8; i++) {
    if (8 * i > thr) s[N - 32 + 4 * i] = -INFINITY;
    if (8 * i + 1 > thr) s[N - 32 + 4 * i + 1] = -INFINITY;
    if (8 * i - 8 > thr) s[N - 32 + 4 * i + 2] = -INFINITY;
    if (8 * i - 7 > thr) s[N - 32 + 4 * i + 3] = -INFINITY;
  }
}
__device__ __forceinline__ void issue_qk(float (&s)[32], uint32_t qd, uint32_t kd) {
  WG_FENCE();
#pragma unroll
  for (int kk = 0; kk < 8; kk++) wgmma_ss64<0>(s, qd + (kk >> 2) * 512 + (kk & 3) * 2, kd + (kk >> 2) * 1024 + (kk & 3) * 2, kk != 0);
  WG_COMMIT();
}
__device__ __forceinline__ void issue_qk(float (&s)[64], uint32_t qd, uint32_t kd) {
  WG_FENCE();
#pragma unroll
  for (int kk = 0; kk < 8; kk++) wgmma_ss128<0>(s, qd + (kk >> 2) * 512 + (kk & 3) * 2, kd + (kk >> 2) * 1024 + (kk & 3) * 2, kk != 0);
  WG_COMMIT();
}
template <int NK>
__device__ __forceinline__ void issue_pv(float (&o)[64], const uint32_t (&P)[32], uint32_t vd, int acc) {
  WG_FENCE();
#pragma unroll
  for (int kk = 0; kk < NK; kk++) wgmma_rs128<1>(o, P[4 * kk], P[4 * kk + 1], P[4 * kk + 2], P[4 * kk + 3], vd + kk * 128, kk != 0 ? 1 : acc);
  WG_COMMIT();
}
__device__ __forceinline__ void stage_done(const Ctx& c, int b) {
  FENCE_ASYNC_SMEM();
  __syncwarp();
  if (c.lane == 0) mbar_arrive(c.bar + (B_SF + b) * 8);
}
__device__ __forceinline__ void p2_epilogue(const float (&o)[64], float s0, float s1, const Ctx& c, int b) {
  stage_tile(o, c.sm + SM_BUF + b * 16384, c, s0, s1);
  stage_done(c, b);
}

struct P2State {
  float m0, m1, l0, l1;
  bool shift;
  float e0, e1;
  int ks;
  int wi, ai;
  uint32_t wb, ab;
  uint32_t qd;
};
#define PROFZ()
__device__ __forceinline__ int wrap5(int q) { return q >= 5 ? q - 5 : q; }
__device__ __forceinline__ void turn_wait(uint32_t ring, int i) { mbar_wait(ring + (i & 3) * 8, (i >> 2) & 1); }
__device__ __forceinline__ void turn_pass(const Ctx& c, uint32_t ring, int i) { if (c.lane == 0) mbar_arrive(ring + (i & 3) * 8); }
__device__ __forceinline__ void p2_scales(P2State& z) {
  float l0 = z.l0, l1 = z.l1;
  l0 += __shfl_xor_sync(0xffffffffu, l0, 1);
  l1 += __shfl_xor_sync(0xffffffffu, l1, 1);
  l0 += __shfl_xor_sync(0xffffffffu, l0, 2);
  l1 += __shfl_xor_sync(0xffffffffu, l1, 2);
  asm("rcp.approx.ftz.f32 %0, %1;" : "=f"(z.e0) : "f"(l0));
  asm("rcp.approx.ftz.f32 %0, %1;" : "=f"(z.e1) : "f"(l1));
}
template <int N>
__device__ __forceinline__ void p2_first(const Ctx& c, P2State& z, float (&o)[64], uint32_t (&Pc)[32], uint32_t (&Pn)[32],
                                         int ks, int vs, int cnt, int acc) {
  float s[N] = {};
  issue_qk(s, z.qd, desc_lo(c.sm + SM_RING, 16) + ks * 2048);
  if (vs >= 0) {
    p2_scales(z);
    issue_pv<8>(o, Pc, desc_lo(c.sm + SM_RING, 16384) + vs * 2048, acc);
  } else {
    WG_COMMIT();
  }
  mbar_expect(z.ab + (z.ai++ & 3) * 8, cnt == 1 ? 8192 : 0);
  PROFZ();
  WG_WAIT(1);
  PROFZ();
  pin(s);
  release(c, B_P2E + ks, cnt);
  causal_mask(s, c.warp * 16 + (c.lane >> 2) - 2 * (c.lane & 3));
  z.m0 = z.m1 = 0.f;
  row_exp<false>(s, Pn, 0.f, 0.f, z.l0, z.l1);
  z.shift = __any_sync(0xffffffffu, !(z.l0 + z.l1 <= SM_HI) || ((c.lane & 3) == 0 && !(fminf(z.l0, z.l1) >= SM_LO)));
  if (__builtin_expect(z.shift, 0)) {
    z.m0 = z.m1 = -INFINITY;
    row_max(s, z.m0, z.m1);
    row_exp<true>(s, Pn, z.m0, z.m1, z.l0, z.l1);
  }
  WG_WAIT(0);
  pin(o);
  if (vs >= 0) release(c, B_P2E + vs, 1);
}

template <bool SECOND>
__device__ __forceinline__ void p2_turn(const Ctx& c, P2State& z, float (&o)[64], uint32_t (&Pc)[32], uint32_t (&Pn)[32],
                                        int eb = -1, bool half = false, int vcnt = 1) {
  float s[64] = {};
  const int ks = z.ks, vs = wrap5(ks + 1);
  PROFZ();
  turn_wait(z.wb, z.wi++);
  PROFZ();
  issue_qk(s, z.qd, desc_lo(c.sm + SM_RING, 16) + ks * 2048);
  const uint32_t vd = desc_lo(c.sm + SM_RING, 16384) + vs * 2048;
  if (SECOND) {
    if (eb >= 0) stage_tile(o, c.sm + SM_BUF + eb * 16384, c, z.e0, z.e1);
    if (half) issue_pv<4>(o, Pc, vd, 0); else issue_pv<8>(o, Pc, vd, 0);
  } else {
    issue_pv<8>(o, Pc, vd, 1);
  }
  turn_pass(c, z.ab, z.ai++);
  if (SECOND) { if (eb >= 0) stage_done(c, eb); }
  PROFZ();
  z.ks = wrap5(ks + 2);
  WG_WAIT(1);
  PROFZ();
  pin(s);
  release(c, B_P2E + ks, 1);
  float t0, t1, a0 = 1.f, a1 = 1.f;
  row_exp<false>(s, Pn, 0.f, 0.f, t0, t1);
  z.shift = __any_sync(0xffffffffu, z.shift || !(t0 + t1 <= SM_HI));
  const bool redo = z.shift;
  if (__builtin_expect(redo, 0)) {
    float n0 = z.m0, n1 = z.m1;
    row_max(s, n0, n1);
    a0 = ex2(z.m0 - n0); a1 = ex2(z.m1 - n1);
    z.m0 = n0; z.m1 = n1;
    z.l0 *= a0; z.l1 *= a1;
    row_exp<true>(s, Pn, z.m0, z.m1, t0, t1);
  }
  WG_WAIT(0);
  pin(o);
  release(c, B_P2E + vs, vcnt);
  if (__builtin_expect(redo, 0)) {
#pragma unroll
    for (int i = 0; i < 16; i++) { o[4 * i] *= a0; o[4 * i + 1] *= a0; o[4 * i + 2] *= a1; o[4 * i + 3] *= a1; }
  }
  z.l0 += t0; z.l1 += t1;
}
__device__ __forceinline__ void copy_p(uint32_t (&d)[32], const uint32_t (&s)[32], int zero) {
#pragma unroll
  for (int i = 0; i < 32; i++) asm volatile("add.s32 %0, %1, %2;" : "=r"(d[i]) : "r"(s[i]), "r"(zero));
}

__device__ __forceinline__ void p2_consumer(const Params& p, const Ctx& c, int rot) {
  const int nit = p.s.r[c.cl].n2;
  const uint32_t fring = c.bar + B_P2F * 8, oring = c.bar + B_ORD * 8;
  float o[64] = {};
  uint32_t Pa[32] = {}, Pb[32] = {};
  P2State z;
  z.e0 = z.e1 = z.l0 = z.l1 = 0.f; z.ks = rot; z.shift = false;
  int acc = 0, n = 0;
  for (int it = 0; it < nit; it++) {
    const int j = p.s.r[c.cl].item[it] & 7, blk = p2_blk(c.rank, c.wg, it);
    const int lng = ((it ^ c.wg) & 1) ^ 1;
    z.qd = desc_lo(c.sm + SM_BUF, 16) + p2_buf(c.wg, it) * 1024;
    if (lng) { z.wb = oring; z.wi = n - it; z.ab = fring; z.ai = n + 1; }
    else { z.wb = fring; z.wi = n + 2; z.ab = oring; z.ai = n - it; }
    PROFZ();
    mbar_wait(c.bar + (B_QF + p2_buf(c.wg, it)) * 8, (it >> 1) & 1);
    turn_wait(fring, n + 1 - lng);
    PROFZ();
    const int vs = it ? wrap5(z.ks + 1) : -1, ks = lng ? z.ks : wrap5(z.ks + (it ? 2 : 1));
    if (blk & 1) p2_first<64>(c, z, o, Pa, Pb, ks, vs, 1 + lng, acc);
    else p2_first<32>(c, z, o, Pa, Pb, ks, vs, 1 + lng, acc);
    z.ks = wrap5(ks + (it == 0 && lng ? 1 : 2));
    PROF(c.wg, 24 + it);
    n += 2 * j + 2;
    int left = 2 * j + lng;
    acc = left != 0;
    if (left == 0) { copy_p(Pa, Pb, p.zero); continue; }
    p2_turn<true>(c, z, o, Pb, Pa, it > 0 ? p2_buf(c.wg, it - 1) : -1, !(blk & 1), 1 + lng);
    while (--left > 0) {
      p2_turn<false>(c, z, o, Pa, Pb);
      if (--left == 0) { copy_p(Pa, Pb, p.zero); break; }
      p2_turn<false>(c, z, o, Pb, Pa);
    }
  }
  {
    if (!acc && nit > 1) p2_epilogue(o, z.e0, z.e1, c, p2_buf(c.wg, nit));
    turn_wait(z.wb, z.wi);
    issue_pv<8>(o, Pa, desc_lo(c.sm + SM_RING, 16384) + z.ks * 2048, acc);
    if (((nit - 1) ^ c.wg) & 1) turn_pass(c, z.ab, z.ai);
    p2_scales(z);
    WG_WAIT(0);
    pin(o);
    release(c, B_P2E + z.ks);
    p2_epilogue(o, z.e0, z.e1, c, p2_buf(c.wg, nit - 1));
    PROF(c.wg, 24 + nit);
  }
}

__device__ __forceinline__ void p2_load_q(const Params& p, const Ctx& c, int it, int w) {
  const int item = p.s.r[c.cl].item[it], b = p2_buf(w, it);
  mbar_expect(c.bar + (B_QF + b) * 8, 16384);
  bulk_load(c.sm + SM_BUF + b * 16384, g_S + (size_t)p.s.qblk[item] * 65536 + p2_blk(c.rank, w, it) * 16384, 16384, c.bar + (B_QF + b) * 8, POL(4));
}
__device__ __forceinline__ void wait_p1_free(const Ctx& c, int u1, int s) {
  mbar_wait(c.bar + (B_P1E + 2 * s) * 8, ((u1 - 1 - 2 * s) / 10) & 1);
  mbar_wait(c.bar + (B_P1E + 2 * s + 1) * 8, ((u1 - 2 - 2 * s) / 10) & 1);
}
__device__ __forceinline__ void p2_producer(const Params& p, const Ctx& c, int u1, int rot) {
  const int nit = p.s.r[c.cl].n2;
  int slot = rot, cnt = 0, par = 1, n = 0;
  const uint8_t* pv = nullptr;
  bool pl = false;
  auto load = [&](const uint8_t* src, int expect, uint32_t fb, bool last) {
    if (cnt < 5) {
      if (u1) {
        wait_p1_free(c, u1, slot);
        if (cnt == 0) p2_load_q(p, c, 0, 1);
      }
      cnt++;
    } else {
      if (slot == rot) par ^= 1;
      mbar_wait(c.bar + (B_P2E + slot) * 8, par);
    }
    if (expect) mbar_expect(fb, expect);
    bulk_load_mc(c.sm + SM_RING + slot * 32768 + c.rank * 16384, src, 16384, fb, last ? POL(5) : L2_NORMAL);
    slot = wrap5(slot + 1);
  };
  for (int it = 0; it < nit; it++) {
    const int item = p.s.r[c.cl].item[it], h = item >> 3, j = item & 7;
    if (it == 1 && (c.phases & 16) && p.s.r[c.cl].n1 < 8) flag_wait<true>(F_GATE, 256);
    uint32_t ready = (c.phases & 16) ? 0u : 255u;
    if (it == 0) { if (c.phases & 16) flag_wait<false>(F_Q + item, 4); mbar_wait(c.bar + B_LAD * 8, 0); p2_load_q(p, c, 0, 0); if (!u1) p2_load_q(p, c, 0, 1); }
    for (int t = 2 * j + 1; t >= 0; t--) {
      mask_wait(ready, t >> 1, F_KV + h * 8 + (c.lane & 7), 8);
      const uint8_t* k = g_S + (size_t)(2 * S_K + p.s.slot[h][t >> 1] * 16 + t) * 32768 + c.rank * 16384;
      const uint32_t fb = c.bar + (B_P2F + (n & 3)) * 8;
      const bool last = (p.s.r[c.cl].last[it] >> (t >> 1)) & 1;
      load(k, pv && t != 2 * j ? 65536 : 32768, fb, last);
      if (!(t & 1) && t + 4 <= 2 * j && c.rank == 0) flag_add_rx(F_RD + h * 8 + (t >> 1) + 2);
      if (pv) load(pv, 0, t != 2 * j ? fb : c.bar + (B_ORD + ((n - 1 - it) & 3)) * 8, pl);
      pl = last;
      pv = k + (size_t)NH * 16 * 32768;
      n++;
    }
  }
  load(pv, 32768, c.bar + (B_P2F + (n & 3)) * 8, pl);
}

__device__ __forceinline__ void publish_and_load_q(const Params& p, const Ctx& c, int f, int it, int seen) {
  const bool want = it < p.s.r[c.cl].n2, early = want && __all_sync(0xffffffffu, seen >= 4);
  if (early) { p2_load_q(p, c, it, it & 1); p2_load_q(p, c, it, (it & 1) ^ 1); }
  if (f >= 0) flag_add(f, 2);
  if (want && !early) {
    if (c.phases & 16) flag_wait<false>(F_Q + p.s.r[c.cl].item[it], 4);
    p2_load_q(p, c, it, it & 1); p2_load_q(p, c, it, (it & 1) ^ 1);
  }
}
__device__ __forceinline__ void p2_storer(const Params& p, const Ctx& c, int sfpar) {
  const int nit = p.s.r[c.cl].n2;
  int held = -1;
  for (int i = 0; i < 2 * nit; i++) {
    const int it = i >> 1, w = (it ^ i ^ 1) & 1, b = p2_buf(w, it);
    const int item = p.s.r[c.cl].item[it], h = item >> 3, j = item & 7;
    mbar_wait(c.bar + (B_SF + b) * 8, (sfpar >> b) & 1);
    sfpar ^= 1 << b;
    bulk_store(g_S + (size_t)p.s.qblk[item] * 65536 + p2_blk(c.rank, w, it) * 16384, c.sm + SM_BUF + b * 16384, 16384, POL(1));
    BULK_COMMIT();
    if (i & 1) {
      if (it + 2 == nit && (p.s.r[c.cl].item[it + 1] & 7) == 0) { held = F_CTX + j * 64 + h; continue; }
      const int seen = flag_peek(F_Q + p.s.r[c.cl].item[min(it + 2, nit - 1)]);
      BULK_WAIT(0);
      if (it + 1 == nit) release(c, B_DONE);
      publish_and_load_q(p, c, F_CTX + j * 64 + h, it + 2, seen);
    }
  }
  if (held >= 0) flag_add_rx(held, 2);
}

__device__ __forceinline__ int p3_pos(int i, int x) { return i < 4 ? (i + x) & 3 : 4; }
__device__ __forceinline__ void p3_consumer(const Params& p, const Ctx& c, int x) {
  const bool first = p.s.r[c.cl].p3 >= 24;
  const int tile = p.s.r[c.cl].p3 - (first ? 24 : 0), j = tile / 3, nt = tile - 3 * j;
  const int na = first ? 9 : 0, nb = p.s.task[c.cl][1] - p.s.task[c.cl][0];
  const uint32_t ad = desc_lo(c.sm + SM_RING + c.wg * 8192, 16), bd = desc_lo(c.sm + SM_RING + 16384, 4096);
  float acc[96] = {};
  int slot = 0, par = 0, prev = 0;
  float g0 = 0.f, g1 = 0.f;
  const int hold = c.wg && LAG ? na + nb - LAG : -1, pass = c.wg || !LAG ? -1 : na + nb - 1;
  const float* gp = g_gate + j * 256 + c.rank * 128 + c.wg * 64 + c.warp * 16 + (c.lane >> 2);
#pragma unroll 1
  for (int kb = 0; kb < na; kb++) {
    if (kb == hold) bar_sync(6, 256);
    mbar_wait(c.bar + (B_P3F + slot) * 8, par);
    if (kb == 0) PROF(c.wg, 39);
    WG_FENCE();
#pragma unroll
    for (int kk = 0; kk < 4; kk++) wgmma_ss192<1, 1>(acc, ad + p3_pos(slot, x) * 2560 + kk * 128, bd + p3_pos(slot, x) * 2560 + (kk >> 1) * 768 + (kk & 1) * 128, kk != 0 ? 1 : kb != 0);
    WG_COMMIT();
    if (kb == pass) bar_arrive(6, 256);
    WG_WAIT(1);
    if (kb > 0) release(c, B_P3E + prev);
    else { g0 = __ldcg(gp); g1 = __ldcg(gp + 8); }
    prev = slot;
    if (++slot == 5) { slot = 0; par ^= 1; }
  }
#pragma unroll 1
  for (int kb = na; kb < na + nb; kb++) {
    if (kb == hold) bar_sync(6, 256);
    mbar_wait(c.bar + (B_P3F + slot) * 8, par);
    if (kb == 0) PROF(c.wg, 39);
    WG_FENCE();
#pragma unroll
    for (int kk = 0; kk < 4; kk++) wgmma_ss192<1>(acc, ad + p3_pos(slot, x) * 2560 + kk * 2, bd + p3_pos(slot, x) * 2560 + (kk >> 1) * 768 + (kk & 1) * 128, kk != 0 ? 1 : kb != 0);
    WG_COMMIT();
    if (kb == pass) bar_arrive(6, 256);
    WG_WAIT(1);
    if (kb > 0) release(c, B_P3E + prev);
    else { g0 = __ldcg(gp); g1 = __ldcg(gp + 8); }
    prev = slot;
    if (++slot == 5) { slot = 0; par ^= 1; }
  }
  g0 = __fdividef(1.f, 1.f + g0); g1 = __fdividef(1.f, 1.f + g1);
  WG_WAIT(0);
  pin(acc);
  PROF(c.wg, 40);
  if (first) bar_sync(4 + c.wg, 128);
  mbar_wait(c.bar + B_OUT * 8, 0);
  const int row = (c.lane & 7) + ((c.lane >> 3) & 1) * 8;
  const uint32_t wbase = c.sm + SM_RING + c.wg * 8192 + c.warp * 2048;
  const uint32_t base = wbase + row * 128 + (((c.lane >> 4) ^ (row & 7)) << 4);
#pragma unroll
  for (int i = 0; i < 12; i++) {
    stsm4((base ^ ((i & 3) << 5)) + (i >> 2) * 40960, pack_bf16(acc[8 * i] * g0, acc[8 * i + 1] * g0), pack_bf16(acc[8 * i + 2] * g1, acc[8 * i + 3] * g1),
          pack_bf16(acc[8 * i + 4] * g0, acc[8 * i + 5] * g0), pack_bf16(acc[8 * i + 6] * g1, acc[8 * i + 7] * g1));
    if ((i & 3) == 3) {
      FENCE_ASYNC_SMEM();
      bar_sync(4 + c.wg, 128);
      if (c.warp == (i >> 2)) tma2d_add(&p.map_out, c.sm + SM_RING + c.wg * 8192 + c.warp * 40960, nt * 192 + c.warp * 64, j * 256 + c.rank * 128 + c.wg * 64);
    }
  }
  BULK_COMMIT();
  PROF(c.wg, 43);
  BULK_WAIT_READ(0);
  PROF(c.wg, 44);
}

__device__ __forceinline__ void p3_producer(const Params& p, const Ctx& c, int u1, int u2, int rot, int x) {
  const bool first = p.s.r[c.cl].p3 >= 24;
  const int tile = p.s.r[c.cl].p3 - (first ? 24 : 0), j = tile / 3, nt = tile - 3 * j;
  int slot = 0, par = 1, cnt = 0;
  auto wait_free = [&](int s) {
    const int f = wrap5(s + 5 - rot);
    if (f < u2) mbar_wait(c.bar + (B_P2E + s) * 8, ((u2 - 1 - f) / 5) & 1);
    else if (u1) wait_p1_free(c, u1, s);
  };
  asm volatile(ELECT("prefetch.tensormap [%0];") ::"l"(&p.map_o[0]) : "memory");
  asm volatile(ELECT("prefetch.tensormap [%0];") ::"l"(&p.map_out) : "memory");
  if ((c.phases & 16) && p.s.r[c.cl].n1 < 8 && p.s.r[c.cl].n2 < 2) flag_wait<true>(F_GATE, 256);
  uint32_t ready = (c.phases & 16) ? 0u : ~0u;
  const int q0 = p.s.task[c.cl][0], q1 = p.s.task[c.cl][1];
  for (int q = q0 - (first ? 9 : 0); q < q1; q++) {
    const bool brA = q < q0;
    const int kb = brA ? q - q0 + 9 : p.s.p3_order[tile][q];
    if (!brA) mask_wait(ready, kb >> 1, F_CTX + j * 64 + c.lane, 4);
    else if (kb == 0 && (c.phases & 16)) flag_wait<false>(F_CTX + j * 64 + 32, 16);
    const uint8_t* a = brA ? g_oA + (j * 4 + c.rank * 2) * 73728 + kb * 8192 : g_S + (size_t)p.s.qblk[(kb >> 1) * 8 + j] * 65536 + c.rank * 32768 + (kb & 1) * 8192;
    const uint32_t st = c.sm + SM_RING + p3_pos(slot, x) * 40960, fb = c.bar + (B_P3F + slot) * 8;
    if (cnt < 4) { wait_free(p3_pos(cnt, x)); wait_free(p3_pos(cnt, x) + 1); }
    else if (cnt == 4) mbar_wait(c.bar + B_DONE * 8, 0);
    else mbar_wait(c.bar + (B_P3E + slot) * 8, par);
    cnt++;
    mbar_expect(fb, 40960);
    bulk_load(st, a, 8192, fb, POL(3));
    bulk_load(st + 8192, a + (brA ? 73728 : 16384), 8192, fb, POL(3));
    tma3d_mc(st + 16384 + c.rank * 12288, &p.map_o[brA], 0, kb * 64 + c.rank * 32, nt * 3, fb);
    if (++slot == 5) { slot = 0; par ^= 1; }
  }
}

__device__ __forceinline__ float bf_lo(uint32_t w) { return __uint_as_float(w << 16); }
__device__ __forceinline__ float bf_hi(uint32_t w) { return __uint_as_float(w & 0xffff0000u); }

__device__ __forceinline__ void gate_rows(const Params& p, int row0, int lane) {
  const uint4* x = reinterpret_cast<const uint4*>(p.x + (size_t)(row0 + (lane >> 2)) * DM) + (lane & 3);
  const uint4* w = reinterpret_cast<const uint4*>(p.gate_w) + (lane & 3);
  float a = 0.f;
#pragma unroll 1
  for (int b = 0; b < 3; b++) {
    uint4 u[6];
#pragma unroll
    for (int i = 0; i < 6; i++) u[i] = __ldg(x + (b * 6 + i) * 4);
#pragma unroll
    for (int i = 0; i < 6; i++) {
      const uint4 v = __ldg(w + (b * 6 + i) * 4);
      a = fmaf(bf_lo(u[i].x), bf_lo(v.x), a); a = fmaf(bf_hi(u[i].x), bf_hi(v.x), a);
      a = fmaf(bf_lo(u[i].y), bf_lo(v.y), a); a = fmaf(bf_hi(u[i].y), bf_hi(v.y), a);
      a = fmaf(bf_lo(u[i].z), bf_lo(v.z), a); a = fmaf(bf_hi(u[i].z), bf_hi(v.z), a);
      a = fmaf(bf_lo(u[i].w), bf_lo(v.w), a); a = fmaf(bf_hi(u[i].w), bf_hi(v.w), a);
    }
  }
  a += __shfl_xor_sync(0xffffffffu, a, 1);
  a += __shfl_xor_sync(0xffffffffu, a, 2);
  if ((lane & 3) == 0) g_gate[row0 + (lane >> 2)] = __expf(fminf(a, 60.f));
}

__device__ __forceinline__ void lds10(uint32_t (&k)[10], uint32_t a) {
  asm volatile("ld.shared.v2.u32 {%0, %1}, [%10];\nld.shared.v2.u32 {%2, %3}, [%10+8];\nld.shared.v2.u32 {%4, %5}, [%10+16];\n"
               "ld.shared.v2.u32 {%6, %7}, [%10+24];\nld.shared.v2.u32 {%8, %9}, [%10+32];"
               : "=r"(k[0]), "=r"(k[1]), "=r"(k[2]), "=r"(k[3]), "=r"(k[4]), "=r"(k[5]), "=r"(k[6]), "=r"(k[7]), "=r"(k[8]), "=r"(k[9]) : "r"(a));
}
__device__ __forceinline__ void local_attn(const Params& p, const Ctx& c, int rb, int hs) {
  const int lane = c.lane, grp = rb >> 2, par = lane >> 4, i0 = 2 * (lane & 15);
  const uint32_t buf = c.sm + SM_BUF + (c.warp - 2) * 8192, bqk = c.bar + (B_LA + (c.warp - 2) * 2) * 8, bv = bqk + 8;
  const uint32_t mine = buf + 2304 + par * 160 + i0 * 4;
  const bool flags = c.phases & 16;
  auto fetch_qk = [&](int i) {
    if (flags && !(i & 1)) {
      const int q = i >> 1;
      const int tgt = q == 0 ? 24 : q == 3 ? 8 : 12;
      flag_wait<false>(F_QKVA + (grp - (grp > 0 && (rb & 3) == 0 ? par : 0)) * 4 + q, tgt);
    }
    mbar_expect(bqk, 5184);
    tma3d(buf, &p.map_t[0], rb * 32, 0, 9 * (4 * i + hs), bqk, POL(2));
    tma3d(buf + 2304, &p.map_t[1], rb * 32 - 8, 0, 288 + 9 * (4 * i + hs), bqk, POL(2));
  };
  auto fetch_v = [&](int i) { mbar_expect(bv, 2880); tma3d(buf + 5248, &p.map_t[1], rb * 32 - 8, 0, 576 + 9 * (4 * i + hs), bv, POL(2)); };
  fetch_qk(0);
  if (flags) flag_wait<true>(F_GATE, 256);
#pragma unroll 1
  for (int q = 0; q < 8; q++) {
    fetch_v(q);
    float a[8], b[8];
#pragma unroll
    for (int w = 0; w < 8; w++) a[w] = b[w] = 0.f;
    mbar_wait(bqk, q & 1);
    PROFB(1 + 2 * q);
#pragma unroll 1
    for (int j = 0; j < 9; j++) {
      uint32_t x, y, k[10];
      asm volatile("ld.shared.v2.u32 {%0, %1}, [%2];" : "=r"(x), "=r"(y) : "r"(buf + lane * 8 + j * 256));
      lds10(k, mine + j * 320);
      const float xl = bf_lo(x), xh = bf_hi(x), yl = bf_lo(y), yh = bf_hi(y);
#pragma unroll
      for (int m = 1; m < 10; m++) {
        const float kl = bf_lo(k[m]), kh = bf_hi(k[m]);
        if (m < 9) a[8 - m] = fmaf(xl, kl, fmaf(xh, kh, a[8 - m]));
        if (m > 1) b[9 - m] = fmaf(yl, kl, fmaf(yh, kh, b[9 - m]));
      }
    }
    __syncwarp();
    mbar_wait(bv, q & 1);
    if (q & 1) flag_add_rx(F_TS + (q >> 1));
    if (q < 7) fetch_qk(q + 1);
    constexpr float SC = 0.23570226039551584f * 1.4426950408889634f;
    const float* gp = g_gate + rb * 64 + 2 * i0 + par;
    const float ga = __ldcg(gp), gb = __ldcg(gp + 2);
    float ma = a[0], mb = b[0];
#pragma unroll
    for (int w = 1; w < 8; w++) {
      if (rb == 0) {
        if (i0 < w) a[w] = -INFINITY;
        if (i0 + 1 < w) b[w] = -INFINITY;
      }
      ma = fmaxf(ma, a[w]); mb = fmaxf(mb, b[w]);
    }
    float la = 0.f, lb = 0.f;
#pragma unroll
    for (int w = 0; w < 8; w++) {
      a[w] = ex2((a[w] - ma) * SC); b[w] = ex2((b[w] - mb) * SC);
      la += a[w]; lb += b[w];
    }
    la = __fdividef(ga, la); lb = __fdividef(gb, lb);
#pragma unroll
    for (int w = 0; w < 8; w++) { a[w] *= la; b[w] *= lb; }
    uint8_t* dst = g_oA + rb * 73728 + ((i0 & 2) + par) * 4;
#pragma unroll 1
    for (int j = 0; j < 9; j++) {
      uint32_t v[10];
      lds10(v, mine + 2944 + j * 320);
      float a0 = 0.f, a1 = 0.f, b0 = 0.f, b1 = 0.f;
#pragma unroll
      for (int m = 1; m < 10; m++) {
        const float vl = bf_lo(v[m]), vh = bf_hi(v[m]);
        if (m < 9) { a0 = fmaf(a[8 - m], vl, a0); a1 = fmaf(a[8 - m], vh, a1); }
        if (m > 1) { b0 = fmaf(b[9 - m], vl, b0); b1 = fmaf(b[9 - m], vh, b1); }
      }
      const uint32_t wa = pack_bf16(a0, a1), wb = pack_bf16(b0, b1);
      const uint32_t got = __shfl_xor_sync(0xffffffffu, par ? wa : wb, 16);
      const uint32_t r0 = par ? got : wa, r1 = par ? wb : got;
      const int col = 18 * (4 * q + hs) + 2 * j, o = col * 128 + ((((i0 >> 2) ^ col) & 7) << 4);
      *reinterpret_cast<uint32_t*>(dst + o) = __byte_perm(r0, r1, 0x5410);
      *reinterpret_cast<uint32_t*>(dst + ((o + 128) ^ 16)) = __byte_perm(r0, r1, 0x7632);
    }
    __syncwarp();
    PROFB(2 + 2 * q);
  }
  mbar_arrive_one(c.bar + B_LAD * 8);
  flag_add(F_CTX + grp * 64 + 32);
}

__global__ void __cluster_dims__(2, 1, 1) __launch_bounds__(384, 1) fused_kernel(const __grid_constant__ Params p) {
  extern __shared__ uint8_t smem_raw[];
  Ctx c;
  c.sm = ((uint32_t)__cvta_generic_to_shared(smem_raw) + 1023u) & ~1023u;
  c.bar = c.sm + SM_BAR;
  c.lane = threadIdx.x & 31;
  const int wid = __shfl_sync(0xffffffffu, threadIdx.x >> 5, 0);
  if (wid < 6) asm volatile("prefetch.tensormap [%0];" ::"l"(&p.map_a[0] + wid) : "memory");
  c.wg = wid >> 2;
  c.warp = wid & 3;
  PROF(c.wg, 0);
  PROFG(61);
  c.cl = (blockIdx.x + (wid >> 4)) >> 1;
  c.rank = blockIdx.x & 1;
  c.rbar = mapa(c.bar, c.lane & 1);
  {
    const int w = wid, cnt = (((int)(B_CNT >> (4 * w)) - 1) & 15) + 1;
    if (w < 11) {
#pragma unroll
      for (int i = 0; i < 8; i++) asm volatile("mbarrier.init.shared::cta.b64 [%0], %1;" ::"r"(c.bar + w * 64 + i * 8), "r"(cnt));
    }
    asm volatile("fence.mbarrier_init.release.cluster;" ::: "memory");
  }
  if (c.wg == 2) PROF(2, 56);
  asm volatile("barrier.cluster.arrive.relaxed;" ::: "memory");
  c.phases = p.s.r[c.cl].phases;
  const bool do1 = p.s.r[c.cl].n1 > 0, do2 = p.s.r[c.cl].n2 > 0, do3 = p.s.r[c.cl].p3 != 255;
  if (do1 && c.wg == 2 && c.warp == 0) {
    const int type = p.s.r[c.cl].slab >> 3;
    PROF(2, 57);
    FENCE_ASYNC_SMEM();
    mbar_expect(c.bar + B_P1F * 8, type ? 32768 : 16384);
    tma2d(type ? c.sm + SM_BUF + 32768 : c.sm + SM_RING, &p.map_a[type], type ? 512 : 0, (p.s.r[c.cl].slab & 7) * 256 + c.rank * 128, c.bar + B_P1F * 8);
    PROF(2, 58);
  }
  asm volatile("barrier.cluster.wait.acquire;" ::: "memory");
  if (c.wg == 2) PROF(2, 59);
  if (do1 && c.wg == 2 && c.warp == 0) {
    const int type = p.s.r[c.cl].slab >> 3, tile = p.s.r[c.cl].tile[0] & 63;
    const CUtensorMap* m = &p.map_w[type * 2 + (tile >> 5)];
#pragma unroll 1
    for (int s = 1 - type; s < NPRO; s++) {
      const int kb = (s - type) >> 1;
      const uint32_t fb = c.bar + (B_P1F + s) * 8;
      if (s) mbar_expect(fb, 16384);
      if ((s ^ type) & 1) tma2d_mc(c.sm + SM_RING + s * 16384 + c.rank * 8192, m, (tile & 31) * 128 + c.rank * 64, kb < 0 ? 512 : kb * 64, fb);
      else tma2d(c.sm + SM_RING + s * 16384, &p.map_a[type], kb * 64, (p.s.r[c.cl].slab & 7) * 256 + c.rank * 128, fb);
    }
  }

  if (c.wg < 2) {
    PROF(c.wg, 4);
    asm volatile("setmaxnreg.inc.sync.aligned.u32 224;");
    if (c.wg == 1) {
      if (do1) bar_arrive(ORDER, 256);
      if (c.lane == 0) mbar_arrive(c.bar + B_P2F * 8);
    }
    PL(0);
    if (do1) p1_consumer(p, c);
    PL(1);
    if (do2) p2_consumer(p, c, p.s.r[c.cl].rot);
    PL(2);
    if (do3) p3_consumer(p, c, p.s.r[c.cl].x3);
    PL(3);
    PROF(c.wg, 63);
    PROFG(62);
    if (c.lane == 0) mbar_arrive(c.bar + B_FIN * 8);
    __syncwarp();
    cluster_sync();
  } else {
    asm volatile("setmaxnreg.dec.sync.aligned.u32 56;");
    if (c.warp == 0) {
      PROF(2, 60);
      if (do1) p1_producer(p, c);
      if (do2) p2_producer(p, c, p.s.r[c.cl].u1, p.s.r[c.cl].rot);
      if (do3) p3_producer(p, c, p.s.r[c.cl].u1, p.s.r[c.cl].u2, p.s.r[c.cl].rot, p.s.r[c.cl].x3);
    } else if (c.warp == 1) {
      const int f = do1 ? p1_storer(p, c) : -1;
      if (do2) {
        publish_and_load_q(p, c, f, 1, flag_peek(F_Q + p.s.r[c.cl].item[1]));
        p2_storer(p, c, (p.s.r[c.cl].n1 & 1) * 10);
      } else {
        const bool idle = mbar_test(c.bar + B_LAD * 8, 0);
        if (idle) release(c, B_DONE);
        if (f >= 0) flag_add(f, 2);
        if (!idle) { mbar_wait(c.bar + B_LAD * 8, 0); release(c, B_DONE); }
      }
      if (do3) {
        const int tile = p.s.r[c.cl].p3 % 24;
        if (p.s.task[c.cl][1] == 64) {
          for (int r = 0; r < (64 - p.s.task[c.cl][0] - ZLEAD) / 5; r++) mbar_wait(c.bar + B_P3F * 8, r & 1);
          const int j = tile / 3, nt = tile - 3 * j;
          uint4* o = reinterpret_cast<uint4*>(p.out + (size_t)(j * 256 + c.rank * 128 + (c.lane >> 3)) * DM + nt * 192) + (c.lane & 7);
#pragma unroll 4
          for (int r = 0; r < 32; r++) o[r * 288] = o[r * 288 + 8] = o[r * 288 + 16] = make_uint4(0u, 0u, 0u, 0u);
          __syncwarp();
          flag_add(F_OUT + tile * 2 + c.rank);
        } else if (c.phases & 16) {
          flag_wait<false, 256>(F_OUT + tile * 2 + c.rank, 1);
        }
        mbar_arrive_one(c.bar + B_OUT * 8);
      }
    } else {
      const int bw = blockIdx.x * 2 + (c.warp - 2);
      if ((c.phases & 1) && bw < 256) {
        gate_rows(p, bw * 8, c.lane);
        __syncwarp();
        flag_add(F_GATE);
      }
      if (p.s.r[c.cl].bg != 255) local_attn(p, c, p.s.r[c.cl].bg, bw & 3);
      else if (c.lane == 0) mbar_arrive(c.bar + B_LAD * 8);
    }
    __syncwarp();
    bar_sync(3, 128);
    if (c.warp == 0 && (c.phases & 32)) {
      int last = 0;
      if (c.lane == 0) { __threadfence(); last = atomicAdd(g_flags + F_DONE, 1) == 2 * NCL - 1; }
      if (__shfl_sync(0xffffffffu, last, 0)) for (int i = c.lane; i < F_NUM; i += 32) g_flags[i] = 0;
    }
    if (c.warp == 1) mbar_wait(c.bar + B_FIN * 8, 0);
    __syncwarp();
    cluster_sync();
  }
}

SCHED_DECL Sched k_sched = {
  {{0,30,2,36,0,{177,224,0,0,0,0,0,0,0,0,0},{0,0,0,0,0,0,0,0,0,0,0},{135,32,133,41,36,43,35,38,59,49,44,45,48,46,53,50,42,52,55,51,63,40,62,58,54,47,56,57,60,61}},
   {1,30,2,37,1,{201,120,0,0,0,0,0,0,0,0,0},{0,0,0,0,0,0,0,0,0,0,0},{135,32,1,41,36,43,35,38,59,49,44,45,48,46,53,50,42,52,55,51,63,40,62,58,54,47,56,57,60,61}},
   {2,30,2,10,2,{176,194,0,0,0,0,0,0,0,0,0},{0,7,0,0,0,0,0,0,0,0,0},{64,34,1,41,36,43,35,38,59,49,44,45,48,46,53,50,52,42,51,55,63,40,62,58,54,47,56,57,60,61}},
   {3,29,1,25,3,{195,0,0,0,0,0,0,0,0,0,0},{0,0,0,0,0,0,0,0,0,0,0},{66,39,133,41,11,35,38,59,49,44,45,48,46,53,50,52,42,51,55,63,40,62,58,54,47,56,57,60,61,0}},
   {4,28,1,42,4,{205,0,0,0,0,0,0,0,0,0,0},{63,0,0,0,0,0,0,0,0,0,0},{135,34,1,37,4,43,6,59,12,13,16,14,21,18,20,10,19,23,31,8,30,26,22,24,15,25,28,29,0,0}},
   {5,27,0,1,5,{0,0,0,0,0,0,0,0,0,0,0},{0,0,0,0,0,0,0,0,0,0,0},{66,39,0,37,4,43,6,59,12,45,14,21,18,20,10,19,23,31,8,30,26,22,15,24,25,28,29,0,0,0}},
   {6,26,0,20,6,{0,0,0,0,0,0,0,0,0,0,0},{0,0,0,0,0,0,0,0,0,0,0},{98,33,133,41,11,35,27,49,13,48,21,18,20,10,19,23,31,8,30,26,22,15,24,25,28,29,0,0,0,0}},
   {7,25,3,4,7,{214,233,232,0,0,0,0,0,0,0,0},{0,0,0,0,0,0,0,0,0,0,0},{65,0,73,68,67,91,76,109,78,85,82,84,74,83,87,95,72,94,90,86,79,88,89,92,93,0,0,0,0,0}},
   {0,30,1,34,8,{227,0,0,0,0,0,0,0,0,0,0},{0,0,0,0,0,0,0,0,0,0,0},{66,39,1,37,4,11,3,6,27,17,12,13,16,14,21,18,10,20,23,19,31,8,30,26,22,15,24,25,28,29}},
   {1,30,1,21,9,{203,0,0,0,0,0,0,0,0,0,0},{0,0,0,0,0,0,0,0,0,0,0},{66,39,133,33,4,11,3,6,27,17,12,13,16,14,21,18,10,20,23,19,31,8,30,26,22,15,24,25,28,29}},
   {2,30,2,16,10,{121,234,0,0,0,0,0,0,0,0,0},{0,0,0,0,0,0,0,0,0,0,0},{135,32,133,33,4,11,3,6,27,17,12,13,16,14,21,18,20,10,19,23,31,8,30,26,22,15,24,25,28,29}},
   {3,29,2,31,11,{178,192,0,0,0,0,0,0,0,0,0},{0,0,0,0,0,0,0,0,0,0,0},{64,34,1,37,4,43,6,27,17,12,13,16,14,21,18,20,10,19,23,31,8,30,26,22,15,24,25,28,29,0}},
   {4,28,0,21,12,{0,0,0,0,0,0,0,0,0,0,0},{0,0,0,0,0,0,0,0,0,0,0},{103,0,33,9,36,3,38,17,44,45,48,46,53,50,52,42,51,55,63,40,62,58,54,56,47,57,60,61,0,0}},
   {5,27,0,6,13,{0,0,0,0,0,0,0,0,0,0,0},{0,0,0,0,0,0,0,0,0,0,0},{98,1,32,9,36,3,38,17,44,16,46,53,50,52,42,51,55,63,40,62,58,54,47,56,57,60,61,0,0,0}},
   {6,26,0,4,14,{0,0,0,0,0,0,0,0,0,0,0},{0,0,0,0,0,0,0,0,0,0,0},{135,0,101,68,43,6,59,12,45,14,53,50,52,42,51,55,63,40,62,58,54,47,56,57,60,61,0,0,0,0}},
   {7,25,0,19,15,{0,0,0,0,0,0,0,0,0,0,0},{0,0,0,0,0,0,0,0,0,0,0},{97,32,105,100,99,123,108,80,110,117,114,116,106,115,119,127,104,126,122,118,111,120,121,124,125,0,0,0,0,0}},
   {0,4,6,12,255,{0,11,31,117,83,152,0,0,0,0,0},{0,0,0,0,0,0,0,0,0,0,0},{98,0,33,9,0,0,0,0,0,0,0,0,0,0,0,0,0,0,0,0,0,0,0,0,0,0,0,0,0,0}},
   {1,4,3,10,255,{14,223,87,0,0,0,0,0,0,0,0},{0,0,0,0,0,0,0,0,0,0,0},{98,0,101,9,0,0,0,0,0,0,0,0,0,0,0,0,0,0,0,0,0,0,0,0,0,0,0,0,0,0}},
   {2,4,6,38,255,{19,73,54,108,71,124,0,0,0,0,0},{0,0,0,0,0,0,0,0,0,0,0},{103,2,101,9,0,0,0,0,0,0,0,0,0,0,0,0,0,0,0,0,0,0,0,0,0,0,0,0,0,0}},
   {3,6,6,2,255,{72,44,28,118,67,206,0,0,0,0,0},{0,0,0,0,0,64,0,0,0,0,0},{96,7,33,9,36,3,0,0,0,0,0,0,0,0,0,0,0,0,0,0,0,0,0,0,0,0,0,0,0,0}},
   {4,8,6,1,255,{32,76,221,114,246,228,0,0,0,0,0},{0,0,0,0,0,0,0,0,0,0,0},{66,32,133,41,11,35,27,49,0,0,0,0,0,0,0,0,0,0,0,0,0,0,0,0,0,0,0,0,0,0}},
   {5,10,6,13,255,{24,91,101,157,212,202,0,0,0,0,0},{0,0,0,0,0,0,0,0,0,0,0},{135,33,133,41,11,35,27,49,13,48,0,0,0,0,0,0,0,0,0,0,0,0,0,0,0,0,0,0,0,0}},
   {6,10,6,35,255,{88,29,174,186,241,180,0,0,0,0,0},{0,0,0,0,0,31,0,0,0,0,0},{103,32,73,100,67,38,17,44,16,46,0,0,0,0,0,0,0,0,0,0,0,0,0,0,0,0,0,0,0,0}},
   {7,8,6,46,255,{18,222,173,154,242,123,0,0,0,0,0},{0,0,0,0,0,0,0,0,0,0,0},{135,2,133,75,70,81,77,112,0,0,0,0,0,0,0,0,0,0,0,0,0,0,0,0,0,0,0,0,0,0}},
   {8,18,2,9,16,{255,229,0,0,0,0,0,0,0,0,0},{0,0,0,0,0,0,0,0,0,0,0},{128,161,68,11,35,44,109,27,17,142,21,18,23,19,30,22,153,28,0,0,0,0,0,0,0,0,0,0,0,0}},
   {9,17,1,22,17,{191,0,0,0,0,0,0,0,0,0,0},{3,0,0,0,0,0,0,0,0,0,0},{135,161,166,11,108,27,109,17,13,16,82,87,147,8,90,88,153,0,0,0,0,0,0,0,0,0,0,0,0,0}},
   {10,18,3,26,18,{96,84,182,0,0,0,0,0,0,0,0},{1,0,96,0,0,0,0,0,0,0,0},{135,161,2,4,108,11,40,6,12,16,21,20,147,31,30,26,24,28,0,0,0,0,0,0,0,0,0,0,0,0}},
   {11,19,3,40,19,{168,253,196,0,0,0,0,0,0,0,0},{0,3,0,0,0,0,0,0,0,0,0},{135,161,107,11,39,6,27,45,12,16,21,18,147,31,30,26,24,28,29,0,0,0,0,0,0,0,0,0,0,0}},
   {12,18,2,13,20,{104,189,0,0,0,0,0,0,0,0,0},{0,0,0,0,0,0,0,0,0,0,0},{96,106,9,67,39,6,40,17,13,142,84,10,23,8,90,88,153,93,0,0,0,0,0,0,0,0,0,0,0,0}},
   {13,20,2,2,21,{155,208,0,0,0,0,0,0,0,0,0},{0,0,0,0,0,0,0,0,0,0,0},{105,0,107,11,70,39,27,12,45,142,21,20,147,31,30,22,24,25,28,29,0,0,0,0,0,0,0,0,0,0}},
   {14,18,5,17,22,{169,81,249,65,238,0,0,0,0,0,0},{0,0,0,0,127,0,0,0,0,0,0},{69,165,107,67,91,39,17,77,45,142,82,10,23,8,90,15,153,93,0,0,0,0,0,0,0,0,0,0,0,0}},
   {15,18,4,32,23,{136,113,251,198,0,0,0,0,0,0,0},{0,0,0,0,0,0,0,0,0,0,0},{128,36,68,43,70,81,35,44,80,45,21,20,147,31,30,22,24,28,0,0,0,0,0,0,0,0,0,0,0,0}},
   {8,18,2,18,24,{148,64,0,0,0,0,0,0,0,0,0},{0,0,0,0,0,0,0,0,0,0,0},{65,165,162,67,39,104,6,12,80,13,74,72,20,31,90,88,15,93,0,0,0,0,0,0,0,0,0,0,0,0}},
   {9,18,1,11,25,{172,0,0,0,0,0,0,0,0,0,0},{28,0,0,0,0,0,0,0,0,0,0},{128,165,107,99,3,104,6,12,85,142,74,20,95,94,79,22,92,93,0,0,0,0,0,0,0,0,0,0,0,0}},
   {10,18,3,24,26,{216,147,183,0,0,0,0,0,0,0,0},{1,0,224,0,0,0,0,0,0,0,0},{128,165,162,99,3,27,109,17,13,142,82,10,23,8,86,15,153,93,0,0,0,0,0,0,0,0,0,0,0,0}},
   {11,17,5,30,27,{105,170,213,193,200,0,0,0,0,0,0},{0,0,0,0,0,0,0,0,0,0,0},{65,165,5,4,108,3,40,77,17,142,84,10,23,8,86,15,153,0,0,0,0,0,0,0,0,0,0,0,0,0}},
   {12,18,3,0,28,{112,188,240,0,0,0,0,0,0,0,0},{0,0,0,0,0,0,0,0,0,0,0},{65,165,107,11,35,44,27,45,12,16,21,18,147,31,30,22,15,28,0,0,0,0,0,0,0,0,0,0,0,0}},
   {13,17,3,39,29,{48,163,215,0,0,0,0,0,0,0,0},{0,0,248,0,0,0,0,0,0,0,0},{100,1,166,4,3,35,44,17,40,13,16,18,10,23,8,26,15,0,0,0,0,0,0,0,0,0,0,0,0,0}},
   {14,18,3,28,30,{128,156,207,0,0,0,0,0,0,0,0},{0,0,128,0,0,0,0,0,0,0,0},{65,41,162,11,70,35,44,12,40,16,21,20,147,31,30,22,24,28,0,0,0,0,0,0,0,0,0,0,0,0}},
   {15,18,2,8,31,{164,144,0,0,0,0,0,0,0,0,0},{0,0,0,0,0,0,0,0,0,0,0},{130,41,75,67,91,76,39,77,40,142,82,10,23,8,90,15,153,93,0,0,0,0,0,0,0,0,0,0,0,0}},
   {8,3,7,29,255,{61,74,26,109,129,162,127,0,0,0,0},{0,0,0,0,0,0,128,0,0,0,0},{135,41,9,0,0,0,0,0,0,0,0,0,0,0,0,0,0,0,0,0,0,0,0,0,0,0,0,0,0,0}},
   {9,5,6,41,255,{40,39,135,145,245,210,0,0,0,0,0},{0,0,0,0,0,7,0,0,0,0,0},{130,41,162,4,39,0,0,0,0,0,0,0,0,0,0,0,0,0,0,0,0,0,0,0,0,0,0,0,0,0}},
   {10,3,4,17,255,{3,95,100,190,0,0,0,0,0,0,0},{0,0,0,0,0,0,0,0,0,0,0},{100,5,107,0,0,0,0,0,0,0,0,0,0,0,0,0,0,0,0,0,0,0,0,0,0,0,0,0,0,0}},
   {11,4,3,3,255,{46,143,116,0,0,0,0,0,0,0,0},{0,0,3,0,0,0,0,0,0,0,0},{96,106,9,99,0,0,0,0,0,0,0,0,0,0,0,0,0,0,0,0,0,0,0,0,0,0,0,0,0,0}},
   {12,3,5,27,255,{4,55,134,69,204,0,0,0,0,0,0},{0,0,32,3,0,0,0,0,0,0,0},{128,161,166,0,0,0,0,0,0,0,0,0,0,0,0,0,0,0,0,0,0,0,0,0,0,0,0,0,0,0}},
   {13,3,7,5,255,{7,34,220,130,146,250,230,0,0,0,0},{0,0,0,0,0,0,127,0,0,0,0},{135,165,9,0,0,0,0,0,0,0,0,0,0,0,0,0,0,0,0,0,0,0,0,0,0,0,0,0,0,0}},
   {14,3,5,14,255,{20,94,175,82,248,0,0,0,0,0,0},{0,0,0,0,0,0,0,0,0,0,0},{128,161,166,0,0,0,0,0,0,0,0,0,0,0,0,0,0,0,0,0,0,0,0,0,0,0,0,0,0,0}},
   {15,3,6,20,255,{62,75,141,85,244,235,0,0,0,0,0},{0,0,0,0,0,0,0,0,0,0,0},{135,32,42,0,0,0,0,0,0,0,0,0,0,0,0,0,0,0,0,0,0,0,0,0,0,0,0,0,0,0}},
   {8,4,5,7,255,{6,35,217,137,150,0,0,0,0,0,0},{0,0,0,0,56,0,0,0,0,0,0},{130,36,5,43,0,0,0,0,0,0,0,0,0,0,0,0,0,0,0,0,0,0,0,0,0,0,0,0,0,0}},
   {9,3,6,14,255,{21,36,218,133,247,122,0,0,0,0,0},{0,0,0,0,255,7,0,0,0,0,0},{96,106,1,0,0,0,0,0,0,0,0,0,0,0,0,0,0,0,0,0,0,0,0,0,0,0,0,0,0,0}},
   {10,3,6,33,255,{15,89,25,140,158,126,0,0,0,0,0},{0,0,0,0,4,127,0,0,0,0,0},{105,1,9,0,0,0,0,0,0,0,0,0,0,0,0,0,0,0,0,0,0,0,0,0,0,0,0,0,0,0}},
   {11,3,6,5,255,{23,53,98,171,161,160,0,0,0,0,0},{0,0,0,0,0,1,0,0,0,0,0},{130,41,166,0,0,0,0,0,0,0,0,0,0,0,0,0,0,0,0,0,0,0,0,0,0,0,0,0,0,0}},
   {12,4,6,6,255,{47,27,138,106,252,231,0,0,0,0,0},{0,0,0,0,0,128,0,0,0,0,0},{135,36,5,4,0,0,0,0,0,0,0,0,0,0,0,0,0,0,0,0,0,0,0,0,0,0,0,0,0,0}},
   {13,3,7,16,255,{16,2,77,90,139,165,184,0,0,0,0},{0,0,0,0,0,0,0,0,0,0,0},{96,106,162,0,0,0,0,0,0,0,0,0,0,0,0,0,0,0,0,0,0,0,0,0,0,0,0,0,0,0}},
   {14,4,5,0,255,{79,142,159,209,237,0,0,0,0,0,0},{0,0,128,0,0,0,0,0,0,0,0},{135,36,9,4,0,0,0,0,0,0,0,0,0,0,0,0,0,0,0,0,0,0,0,0,0,0,0,0,0,0}},
   {15,4,6,18,255,{12,43,111,254,179,226,0,0,0,0,0},{0,0,0,0,0,0,0,0,0,0,0},{65,5,37,38,0,0,0,0,0,0,0,0,0,0,0,0,0,0,0,0,0,0,0,0,0,0,0,0,0,0}},
   {8,3,7,12,255,{22,41,219,151,153,243,236,0,0,0,0},{0,0,0,0,0,0,0,0,0,0,0},{96,106,166,0,0,0,0,0,0,0,0,0,0,0,0,0,0,0,0,0,0,0,0,0,0,0,0,0,0,0}},
   {9,3,6,44,255,{1,5,103,97,70,125,0,0,0,0,0},{0,0,0,0,0,63,0,0,0,0,0},{100,9,5,0,0,0,0,0,0,0,0,0,0,0,0,0,0,0,0,0,0,0,0,0,0,0,0,0,0,0}},
   {10,4,7,45,255,{8,13,92,99,131,68,211,0,0,0,0},{0,0,0,0,2,0,0,0,0,0,0},{96,106,166,103,0,0,0,0,0,0,0,0,0,0,0,0,0,0,0,0,0,0,0,0,0,0,0,0,0,0}},
   {11,3,7,43,255,{63,33,110,115,185,181,225,0,0,0,0},{0,0,0,0,0,0,0,0,0,0,0},{128,36,162,0,0,0,0,0,0,0,0,0,0,0,0,0,0,0,0,0,0,0,0,0,0,0,0,0,0,0}},
   {12,3,6,22,255,{56,59,37,52,166,199,0,0,0,0,0},{0,0,0,0,70,248,0,0,0,0,0},{130,41,162,0,0,0,0,0,0,0,0,0,0,0,0,0,0,0,0,0,0,0,0,0,0,0,0,0,0,0}},
   {13,3,5,15,255,{60,9,93,49,167,0,0,0,0,0,0},{0,0,0,0,0,0,0,0,0,0,0},{130,161,5,0,0,0,0,0,0,0,0,0,0,0,0,0,0,0,0,0,0,0,0,0,0,0,0,0,0,0}},
   {14,3,6,8,255,{57,42,38,119,187,239,0,0,0,0,0},{0,0,0,0,0,128,0,0,0,0,0},{130,32,42,0,0,0,0,0,0,0,0,0,0,0,0,0,0,0,0,0,0,0,0,0,0,0,0,0,0,0}},
   {15,3,6,47,255,{58,45,102,149,66,197,0,0,0,0,0},{0,0,0,0,0,0,0,0,0,0,0},{73,161,162,0,0,0,0,0,0,0,0,0,0,0,0,0,0,0,0,0,0,0,0,0,0,0,0,0,0,0}},
   {6,2,6,23,255,{17,78,51,50,132,80,0,0,0,0,0},{0,0,0,0,0,0,0,0,0,0,0},{66,1,0,0,0,0,0,0,0,0,0,0,0,0,0,0,0,0,0,0,0,0,0,0,0,0,0,0,0,0}},
   {7,6,4,9,255,{10,30,107,86,0,0,0,0,0,0,0},{0,0,0,120,0,0,0,0,0,0,0},{103,34,101,107,102,113,0,0,0,0,0,0,0,0,0,0,0,0,0,0,0,0,0,0,0,0,0,0,0,0}}},
  {{0,8,0,0},{0,8,0,0},{2,13,0,0},{0,6,0,0},{0,2,0,0},{17,64,0,0},{11,64,0,0},{2,11,0,0},{0,2,0,0},{10,22,0,0},{6,14,0,0},
   {0,8,0,0},{22,64,0,0},{17,64,0,0},{11,64,0,0},{5,64,0,0},{16,64,0,0},{13,64,0,0},{0,4,0,0},{8,19,0,0},{6,17,0,0},{8,19,0,0},
   {0,7,0,0},{0,8,0,0},{3,13,0,0},{20,64,0,0},{0,8,0,0},{0,6,0,0},{19,64,0,0},{19,64,0,0},{10,18,0,0},{0,3,0,0},{12,64,0,0},
   {7,64,0,0},{0,8,0,0},{0,8,0,0},{17,64,0,0},{0,10,0,0},{0,2,0,0},{12,64,0,0},{0,6,0,0},{0,10,0,0},{18,64,0,0},{2,64,0,0},
   {0,2,0,0},{6,15,0,0},{16,64,0,0},{3,11,0,0},{8,64,0,0},{4,16,0,0},{0,3,0,0},{15,64,0,0},{8,17,0,0},{14,64,0,0},{8,17,0,0},
   {2,12,0,0},{8,16,0,0},{0,3,0,0},{0,10,0,0},{0,5,0,0},{8,20,0,0},{10,64,0,0},{3,12,0,0},{0,3,0,0},{3,64,0,0},{13,64,0,0}},
  {{40,39,60,53,48,51,56,58,46,41,62,61,44,49,30,57,59,4,5,14,15,0,1,2,3,10,11,18,19,8,9,22,23,6,7,12,13,24,25,54,55,32,33,34,35,28,29,26,27,42,43,20,21,16,17,36,37,47,38,63,52,45,50,31},
   {63,52,45,51,56,58,36,46,40,38,62,61,44,49,30,57,59,4,5,14,15,0,1,2,3,10,11,18,19,8,9,22,23,6,7,12,13,24,25,54,55,32,33,34,35,28,29,26,27,42,43,20,21,16,17,37,47,41,39,60,53,48,50,31},
   {40,62,61,44,49,30,57,59,21,17,37,47,38,63,53,48,51,56,58,4,5,14,15,0,1,2,3,10,11,18,19,8,9,22,23,6,7,12,13,24,25,54,55,32,33,34,35,28,29,26,27,42,43,20,16,36,46,41,39,60,52,45,50,31},
   {58,59,14,15,4,5,0,1,18,19,2,3,10,11,8,9,22,23,6,7,54,55,12,13,34,35,24,25,26,27,42,43,32,33,28,29,36,37,20,21,46,47,40,41,38,39,62,63,16,17,60,61,52,53,30,31,48,49,44,45,50,51,56,57},
   {51,58,63,17,61,53,31,49,50,57,59,14,15,4,5,0,1,18,19,2,3,10,11,8,9,22,23,6,7,54,55,12,13,34,35,24,25,26,27,42,43,32,33,28,29,36,37,20,21,46,47,40,41,38,39,62,16,60,52,30,48,44,45,56},
   {61,30,49,50,57,59,38,62,16,60,53,48,45,56,58,14,15,4,5,0,1,18,19,2,3,10,11,8,9,22,23,6,7,54,55,12,13,34,35,24,25,26,27,42,43,32,33,28,29,36,37,20,21,46,47,40,41,39,63,17,52,31,44,51},
   {47,16,61,44,31,50,57,59,38,46,63,60,53,30,49,56,58,14,15,0,1,10,11,2,3,4,5,18,19,8,9,6,7,22,23,54,55,12,13,34,35,24,25,26,27,32,33,28,29,42,43,36,37,40,41,20,21,39,62,17,52,45,48,51},
   {61,53,45,31,49,51,57,59,14,15,0,1,10,11,2,3,4,5,18,19,8,9,6,7,22,23,54,55,12,13,34,35,24,25,26,27,32,33,28,29,42,43,36,37,40,41,20,21,38,39,46,47,62,63,16,17,60,52,44,30,48,50,56,58},
   {48,51,58,63,17,61,53,45,31,50,57,59,14,15,0,1,10,11,2,3,4,5,18,19,8,9,6,7,22,23,54,55,12,13,34,35,24,25,26,27,32,33,28,29,42,43,36,37,40,41,20,21,38,39,46,47,62,16,60,52,44,30,49,56},
   {48,56,58,46,62,16,60,44,52,31,50,57,59,0,1,4,5,14,15,2,3,10,11,18,19,22,23,8,9,12,13,6,7,54,55,26,27,34,35,24,25,32,33,28,29,42,43,40,41,36,37,20,21,38,39,47,63,17,61,45,53,30,49,51},
   {57,59,39,47,63,17,61,45,53,31,50,56,58,0,1,4,5,14,15,2,3,10,11,18,19,22,23,8,9,12,13,6,7,54,55,26,27,34,35,24,25,32,33,28,29,42,43,40,41,36,37,20,21,38,46,62,16,60,44,52,30,48,49,51},
   {45,53,31,49,51,57,59,0,1,4,5,14,15,2,3,10,11,18,19,22,23,8,9,12,13,6,7,54,55,26,27,34,35,24,25,32,33,28,29,42,43,40,41,36,37,20,21,38,39,46,47,62,63,16,17,60,61,44,52,30,48,50,56,58},
   {47,16,61,44,49,50,57,59,39,62,17,52,45,30,56,58,14,15,4,5,0,1,2,3,10,11,18,19,8,9,22,23,6,7,12,13,54,55,34,35,24,25,26,27,28,29,32,33,42,43,36,37,40,41,20,21,38,46,63,60,53,48,31,51},
   {47,16,61,44,49,50,57,59,40,20,38,46,63,60,53,48,31,56,58,14,15,4,5,0,1,2,3,10,11,18,19,8,9,22,23,6,7,12,13,54,55,34,35,24,25,26,27,28,29,32,33,42,43,36,37,41,21,39,62,17,52,45,30,51},
   {49,50,57,59,41,21,39,47,63,17,61,53,48,31,56,58,14,15,4,5,0,1,2,3,10,11,18,19,8,9,22,23,6,7,12,13,54,55,34,35,24,25,26,27,28,29,32,33,42,43,36,37,40,20,38,46,62,16,60,52,44,45,30,51},
   {63,17,61,53,45,31,49,56,58,59,14,15,4,5,2,3,0,1,10,11,18,19,8,9,22,23,6,7,12,13,54,55,34,35,24,25,26,27,28,29,32,33,42,43,36,37,40,41,20,21,38,39,46,47,62,16,60,52,44,30,48,50,51,57},
   {61,44,31,50,57,59,47,63,17,52,45,48,51,58,14,15,4,5,2,3,0,1,10,11,18,19,8,9,22,23,6,7,12,13,54,55,34,35,24,25,26,27,28,29,32,33,42,43,36,37,40,41,20,21,38,39,46,62,16,60,53,30,49,56},
   {20,38,47,16,61,44,31,50,57,59,46,63,60,53,30,49,56,58,14,15,4,5,2,3,0,1,10,11,18,19,8,9,22,23,6,7,12,13,54,55,34,35,24,25,26,27,28,29,32,33,42,43,36,37,40,41,21,39,62,17,52,45,48,51},
   {57,59,39,63,17,61,44,48,30,50,56,58,14,15,4,5,2,3,0,1,10,11,18,19,8,9,22,23,6,7,12,13,54,55,34,35,24,25,26,27,32,33,28,29,42,43,36,37,20,21,40,41,46,47,38,62,16,60,52,53,45,49,31,51},
   {49,31,51,57,59,14,15,4,5,2,3,0,1,10,11,18,19,8,9,22,23,6,7,12,13,54,55,34,35,24,25,26,27,32,33,28,29,42,43,36,37,20,21,40,41,46,47,38,39,62,63,16,17,60,61,52,53,44,45,48,30,50,56,58},
   {31,56,59,16,60,52,44,48,30,51,58,14,15,4,5,2,3,0,1,10,11,18,19,8,9,22,23,6,7,12,13,54,55,34,35,24,25,26,27,32,33,28,29,42,43,36,37,20,21,40,41,46,47,38,39,62,63,17,61,53,45,49,50,57},
   {40,21,38,63,60,53,30,49,56,59,29,43,37,20,47,62,17,52,45,48,51,58,0,1,14,15,4,5,2,3,18,19,10,11,8,9,22,23,6,7,12,13,54,55,34,35,24,25,26,27,32,33,28,42,36,41,46,39,16,61,44,31,50,57},
   {47,62,17,52,45,48,51,58,43,37,41,21,38,63,60,53,30,49,57,59,0,1,14,15,4,5,2,3,18,19,10,11,8,9,22,23,6,7,12,13,54,55,34,35,24,25,26,27,32,33,28,29,42,36,40,20,46,39,16,61,44,31,50,56},
   {51,57,59,0,1,14,15,4,5,2,3,18,19,10,11,8,9,22,23,6,7,12,13,54,55,34,35,24,25,26,27,32,33,28,29,42,43,36,37,40,41,20,21,46,47,38,39,62,63,16,17,60,61,52,53,44,45,30,31,48,49,50,56,58}},
  {{2,2,1,0,2,3,3,2},{3,4,4,3,3,2,2,0},{0,0,2,1,1,0,0,3},{8,8,8,8,8,8,8,8},
   {6,6,6,6,6,6,6,6},{4,3,3,4,4,4,4,5},{9,9,9,9,9,9,9,9},{1,1,0,2,0,1,1,1},
   {2,10,11,3,3,0,11,3},{5,5,5,5,5,5,5,4},{5,5,7,7,7,9,8,8},{7,7,7,7,7,7,7,7},
   {12,12,12,12,12,2,2,0},{13,13,4,3,3,0,4,3},{3,15,3,4,5,5,0,4},{14,9,6,8,0,8,7,9},
   {14,14,2,1,4,4,5,5},{11,11,11,11,11,11,11,11},{4,3,6,6,6,6,7,7},{7,8,0,0,0,7,10,10},
   {6,6,8,8,8,8,9,9},{0,4,5,5,1,1,1,6},{11,13,3,4,5,5,0,7},{8,7,10,10,10,10,2,0},
   {0,4,7,0,8,7,10,8},{4,3,10,10,10,10,2,0},{13,12,2,1,4,1,1,6},{10,10,10,10,10,10,10,10},
   {5,5,12,12,12,2,11,3},{7,8,11,3,3,0,4,11},{9,11,4,11,11,11,6,5},{1,0,12,12,12,2,4,11}},
  {{255,255,255,255,255,255,255,255},{255,255,255,255,255,255,255,255},{255,255,255,255,255,255,255,255},{255,255,255,255,255,255,255,255},
   {255,255,255,255,255,255,255,255},{255,255,255,255,255,255,255,255},{255,255,255,255,255,255,255,255},{255,255,255,255,255,255,255,255},
   {0,27,17,13,13,13,17,13},{255,255,255,255,255,255,255,255},{9,9,11,11,11,6,3,3},{255,255,255,255,255,255,255,255},
   {255,255,255,255,255,1,1,1},{255,255,1,1,1,2,5,2},{1,255,5,5,9,9,2,9},{16,6,18,20,19,20,18,20},
   {255,255,2,2,5,5,9,5},{255,255,255,255,255,255,255,255},{5,5,4,4,4,4,11,11},{11,3,7,0,7,11,27,27},
   {4,4,3,3,3,3,6,6},{2,1,9,9,2,7,7,4},{17,13,14,14,14,14,14,18},{3,11,27,27,27,27,12,12},
   {21,21,10,19,20,19,19,10},{18,18,23,23,23,23,23,23},{13,12,16,16,16,21,21,21},{255,255,255,255,255,255,255,255},
   {10,10,31,31,31,31,8,8},{19,19,8,8,8,8,31,31},{6,17,13,17,17,17,4,16},{7,2,12,12,12,12,13,17}},
  {112,113,114,115,116,117,118,119,120,121,122,123,124,125,126,127,128,129,130,131,132,133,134,135,136,137,138,139,140,141,142,143,144,145,146,147,148,149,150,151,152,153,154,155,156,157,158,159,647,391,397,163,164,165,166,167,168,169,170,171,172,173,174,175,15,177,178,179,180,54,182,183,184,185,186,187,188,189,190,191,192,193,9,47,51,88,45,16,200,201,202,203,204,205,206,207,3,0,38,72,73,8,2,215,388,40,39,36,75,643,6,4,644,78,76,227,228,229,230,387,232,20,61,444,236,237,97,94,43,79,77,243,244,245,80,42,44,1,653,74,37,7,383,255,17,257,378,48,49,46,262,263,264,81,52,385,641,377,83,84,85,11,10,275,276,50,13,14,280,41,634,283,284,285,286,287,95,90,18,56,700,407,92,93,86,12,53,633,300,301,89,87,96,91,443,307,308,309,310,311,312,313,699,315,316,32,318,319,24,21,62,663,60,98,55,25,5,329,330,639,398,654,334,335,28,337,442,33,34,63,670,27,29,414,698,64,35,65,31,30,26,353,19,57,58,59,22,23,360,82,362,363,364,365,366,367},
  {511,511,511,511,511,511,511,511,511,511,511,511,511,511,511,511,511,511,511,511,511,511,511,511,511,511,511,511,511,511,511,511,511,511,511,511,511,511,511,511,511,511,511,511,511,511,511,511,7,7,5,511,511,511,511,511,511,511,511,511,511,511,511,511,257,511,511,511,511,258,511,511,511,511,511,511,511,511,511,511,511,511,257,257,257,257,257,257,511,511,511,511,511,511,511,511,256,256,256,256,256,256,256,511,4,256,256,256,256,59,256,256,4,256,256,511,511,511,511,59,511,258,258,52,511,511,258,258,256,256,256,511,511,511,256,256,256,256,5,256,256,256,63,511,257,511,2,257,257,257,511,511,511,257,257,1,1,57,257,257,257,257,257,511,511,257,257,257,511,256,2,511,511,511,511,511,258,258,258,258,52,119,258,258,257,257,257,57,511,511,257,257,258,258,51,511,511,511,511,511,511,511,51,511,511,259,511,511,258,258,258,119,258,258,258,258,256,511,511,63,6,6,511,511,259,511,50,259,259,259,134,259,259,134,50,259,259,259,259,259,258,511,258,258,258,258,258,258,511,257,511,511,511,511,511,511}};

typedef CUresult (*EncodeFn)(CUtensorMap*, CUtensorMapDataType, cuuint32_t, void*, const cuuint64_t*, const cuuint64_t*, const cuuint32_t*,
                             const cuuint32_t*, CUtensorMapInterleave, CUtensorMapSwizzle, CUtensorMapL2promotion, CUtensorMapFloatOOBfill);

void make_map2(EncodeFn enc, CUtensorMap* m, const void* ptr, int rows, int cols, int box_rows) {
  cuuint64_t dim[2] = {(cuuint64_t)cols, (cuuint64_t)rows}, str[1] = {(cuuint64_t)cols * 2};
  cuuint32_t box[2] = {64, (cuuint32_t)box_rows}, es[2] = {1, 1};
  enc(m, CU_TENSOR_MAP_DATA_TYPE_BFLOAT16, 2, const_cast<void*>(ptr), dim, str, box, es, CU_TENSOR_MAP_INTERLEAVE_NONE, CU_TENSOR_MAP_SWIZZLE_128B,
      CU_TENSOR_MAP_L2_PROMOTION_L2_128B, CU_TENSOR_MAP_FLOAT_OOB_FILL_NONE);
}
void make_map3(EncodeFn enc, CUtensorMap* m, const void* ptr, int rows) {
  cuuint64_t dim[3] = {64, (cuuint64_t)rows, 9}, str[2] = {DM * 2, 128};
  cuuint32_t box[3] = {64, 32, 3}, es[3] = {1, 1, 1};
  enc(m, CU_TENSOR_MAP_DATA_TYPE_BFLOAT16, 3, const_cast<void*>(ptr), dim, str, box, es, CU_TENSOR_MAP_INTERLEAVE_NONE, CU_TENSOR_MAP_SWIZZLE_128B,
      CU_TENSOR_MAP_L2_PROMOTION_L2_128B, CU_TENSOR_MAP_FLOAT_OOB_FILL_NONE);
}

void make_map_t(EncodeFn enc, CUtensorMap* m, void* ptr, int width, int cols) {
  cuuint64_t dim[3] = {SEQ / 2, 2, 864}, str[2] = {SEQ * 2, SEQ * 4};
  cuuint32_t box[3] = {(cuuint32_t)width, 2, (cuuint32_t)cols}, es[3] = {1, 1, 1};
  enc(m, CU_TENSOR_MAP_DATA_TYPE_UINT32, 3, ptr, dim, str, box, es, CU_TENSOR_MAP_INTERLEAVE_NONE, cols == 64 ? CU_TENSOR_MAP_SWIZZLE_128B : CU_TENSOR_MAP_SWIZZLE_NONE,
      CU_TENSOR_MAP_L2_PROMOTION_NONE, CU_TENSOR_MAP_FLOAT_OOB_FILL_NONE);
}

int g_mode = -1;

}

extern "C" void kernel_launch(void* const* d_in, const int* in_sizes, int n_in, void* d_out, int out_size) {
  static EncodeFn enc = nullptr;
  static void* t_ptr = nullptr;
  if (!enc) {
    void* fn = nullptr;
    cudaDriverEntryPointQueryResult st;
    cudaGetDriverEntryPoint("cuTensorMapEncodeTiled", &fn, cudaEnableDefault, &st);
    enc = (EncodeFn)fn;
    cudaGetSymbolAddress(&t_ptr, g_S);
    cudaFuncSetAttribute(fused_kernel, cudaFuncAttributeMaxDynamicSharedMemorySize, SMEM_BYTES);
    if (g_mode < 0) {
      cudaLaunchConfig_t cfg = {};
      cfg.gridDim = dim3(2 * NCL); cfg.blockDim = dim3(384); cfg.dynamicSmemBytes = SMEM_BYTES;
      cudaLaunchAttribute at; at.id = cudaLaunchAttributeClusterDimension;
      at.val.clusterDim.x = 2; at.val.clusterDim.y = 1; at.val.clusterDim.z = 1;
      cfg.attrs = &at; cfg.numAttrs = 1;
      int nc = 0;
      g_mode = (cudaOccupancyMaxActiveClusters(&nc, fused_kernel, &cfg) == cudaSuccess && nc >= NCL) ? 1 : 0;
      (void)cudaGetLastError();
    }
  }
  Params p;
  make_map2(enc, &p.map_a[0], d_in[4], SEQ, DC, 128);
  make_map2(enc, &p.map_a[1], d_in[0], SEQ, DM, 128);
  make_map2(enc, &p.map_w[0], d_in[6], DC, 4096, 64);
  make_map2(enc, &p.map_w[1], d_in[7], DC, 4096, 64);
  make_map2(enc, &p.map_w[2], d_in[5], DM, 4096, 64);
  make_map2(enc, &p.map_w[3], d_in[1], DM, 1728, 64);
  make_map3(enc, &p.map_o[0], d_in[8], 4096);
  make_map3(enc, &p.map_o[1], d_in[2], DM);
  make_map_t(enc, &p.map_t[0], t_ptr, 32, 9);
  make_map_t(enc, &p.map_t[1], t_ptr, 40, 9);
  make_map_t(enc, &p.map_t[2], t_ptr, 32, 64);
  p.x = (const __nv_bfloat16*)d_in[0];
  p.gate_w = (const __nv_bfloat16*)d_in[9];
  make_map2(enc, &p.map_out, d_out, SEQ, DM, 64);
  p.out = (__nv_bfloat16*)d_out;
  p.zero = 0;
  auto launch = [&](int phases) {
    p.s = k_sched;
    for (int i = 0; i < NCL; i++) {
      Rec& r = p.s.r[i];
      if (!(phases & 1)) r.n1 = 0;
      if (!(phases & 2)) r.n2 = 0;
      if (!(phases & (p.s.task[i][1] == 64 ? 4 : 32))) r.p3 = 255;
      if (!(phases & 8)) r.bg = 255;
      const int u1 = r.n1 ? 8 + r.n1 * (8 + (r.slab >> 3)) : 0;
      int u2 = 0;
      for (int k = 0; k < r.n2; k++) u2 += 4 * (r.item[k] & 7) + 4;
      r.u1 = (uint8_t)u1; r.u2 = (uint8_t)u2;
      r.rot = (uint8_t)(((u1 % 10 + 1) >> 1) % 5);
      r.x3 = (uint8_t)((r.rot + u2) % 5 & 3);
      r.phases = (uint8_t)phases;
    }
    if (!(phases & 16))
      for (int i = 0; i < 256; i++) { p.s.slot[i >> 3][i & 7] = (uint8_t)(i >> 3); p.s.prev[i >> 3][i & 7] = 255; p.s.qblk[i] = (uint16_t)(S_Q + i); p.s.qdep[i] = 511; }
    fused_kernel<<<2 * NCL, 384, SMEM_BYTES>>>(p);
  };
  if (g_mode == 1) launch(63);
  else { launch(1); launch(10); launch(4); launch(32); }
}
```

```cpp
#include <cuda_runtime.h>
#include <cuda_bf16.h>
#include <cuda.h>
#include <stdint.h>

namespace {

constexpr int SEQ = 2048, DM = 576, DC = 512, NH = 32;
constexpr int NCL = 66;
constexpr uint32_t DESC_HI = 0x40000040u;

constexpr int SM_RING = 0;
constexpr int SM_BUF = 163840;
constexpr int SM_BAR = 229376;
constexpr int B_P1E = 0, B_P2E = 10, B_P3E = 15, B_P2F = 24, B_SF = 32, B_ORD = 36, B_LAD = 40, B_DONE = 41, B_FIN = 48;
constexpr int B_P3F = 56, B_OUT = 61, B_P1F = 64, B_SE = 74, B_QF = 80, B_LA = 84, B_NUM = 88;
constexpr uint64_t B_CNT = 0x11118245000ull;
constexpr int SMEM_BYTES = SM_BAR + B_NUM * 8 + 1024;

constexpr int F_QKVA = 32;
constexpr int F_GATE = 64;
constexpr int F_TS = 68;
constexpr int F_DONE = 65;
constexpr int F_CTX = 96;
constexpr int F_OUT = 96 + 8 * 64;
constexpr int F_KV = F_OUT + 64;
constexpr int F_Q = F_KV + 256;
constexpr int F_RD = F_Q + 256;
constexpr int F_NUM = F_RD + 256;

struct Rec {
  uint8_t slab;
  uint8_t n1, n2;
  uint8_t p3;
  uint8_t bg;
  uint8_t item[11];
  uint8_t last[11];
  uint8_t tile[32];
  uint8_t u1, u2;
  uint8_t rot, x3;
  uint8_t phases;
};
struct Sched {
  Rec r[NCL];
  uint8_t task[NCL][4];
  uint8_t p3_order[24][64];
  uint8_t slot[32][8];
  uint8_t prev[32][8];
  uint16_t qblk[256];
  uint16_t qdep[256];
};

#define SCHED_DECL static const

struct Params {
  CUtensorMap map_a[2];
  CUtensorMap map_w[4];
  CUtensorMap map_o[2];
  CUtensorMap map_t[3];
  CUtensorMap map_out;
  const __nv_bfloat16* x;
  const __nv_bfloat16* gate_w;
  __nv_bfloat16* out;
  int zero;
  alignas(64) Sched s;
};

constexpr int S_T = 0, S_Q = 112, S_K = S_Q + 256, S_V = S_K + 256, S_NUM = S_V + 256;
__device__ __align__(1024) uint8_t g_S[(size_t)S_NUM * 65536];
__device__ __align__(1024) uint8_t g_oA[32 * 576 * 128];
__device__ float g_gate[SEQ];
__device__ int g_flags[F_NUM];
#define PL(i)

__device__ __forceinline__ void mbar_arrive(uint32_t b) { asm volatile("mbarrier.arrive.shared::cta.b64 _, [%0];" ::"r"(b) : "memory"); }
__device__ __forceinline__ void mbar_arrive_cl(uint32_t b, int cnt) {
  asm volatile("mbarrier.arrive.shared::cluster.b64 _, [%0], %1;" ::"r"(b), "r"(cnt) : "memory");
}
__device__ __forceinline__ void mbar_wait(uint32_t b, int par) {
  asm volatile(
      "{\n.reg .pred p;\n.reg .u32 c;\n"
      "mbarrier.try_wait.parity.shared::cta.b64 p, [%0], %1;\n@p bra DN;\nmov.u32 c, 0;\n"
      "LP:\nmbarrier.try_wait.parity.shared::cta.b64 p, [%0], %1;\n@p bra DN;\n"
      "add.u32 c, c, 1;\nsetp.lt.u32 p, c, 4000000;\n@p bra LP;\ntrap;\nDN:\n}" ::"r"(b), "r"(par) : "memory");
}
__device__ __forceinline__ bool mbar_test(uint32_t b, int par) {
  uint32_t ok;
  asm volatile("{\n.reg .pred p;\nmbarrier.test_wait.parity.shared::cta.b64 p, [%1], %2;\nselp.u32 %0, 1, 0, p;\n}" : "=r"(ok) : "r"(b), "r"(par) : "memory");
  return __all_sync(0xffffffffu, ok);
}
__device__ __forceinline__ uint32_t mapa(uint32_t a, uint32_t cta) {
  uint32_t r; asm("mapa.shared::cluster.u32 %0, %1, %2;" : "=r"(r) : "r"(a), "r"(cta)); return r;
}
#define ELECT(ins) "{\n.reg .pred e;\nelect.sync _|e, 0xffffffff;\n@e " ins "\n}"
__device__ __forceinline__ void mbar_expect(uint32_t b, int bytes) {
  asm volatile(ELECT("mbarrier.arrive.expect_tx.shared::cta.b64 _, [%0], %1;") ::"r"(b), "r"(bytes) : "memory");
}
__device__ __forceinline__ void mbar_arrive_one(uint32_t b) { asm volatile(ELECT("mbarrier.arrive.shared::cta.b64 _, [%0];") ::"r"(b) : "memory"); }
constexpr uint64_t L2_NORMAL = 0x1000000000000000ull, L2_FIRST = 0x12F0000000000000ull;
__device__ __forceinline__ void bulk_load(uint32_t dst, const void* src, int bytes, uint32_t bar, uint64_t pol = L2_NORMAL) {
  asm volatile(ELECT("cp.async.bulk.shared::cluster.global.mbarrier::complete_tx::bytes.L2::cache_hint [%0], [%1], %2, [%3], %4;") ::"r"(dst), "l"(src), "r"(bytes), "r"(bar), "l"(pol) : "memory");
}
__device__ __forceinline__ void bulk_load_mc(uint32_t dst, const void* src, int bytes, uint32_t bar, uint64_t pol = L2_NORMAL) {
  asm volatile(ELECT("cp.async.bulk.shared::cluster.global.mbarrier::complete_tx::bytes.multicast::cluster.L2::cache_hint [%0], [%1], %2, [%3], %4, %5;") ::"r"(dst), "l"(src), "r"(bytes), "r"(bar), "h"((uint16_t)3), "l"(pol) : "memory");
}
__device__ __forceinline__ void bulk_store(void* dst, uint32_t src, int bytes, uint64_t pol = L2_NORMAL) {
  asm volatile(ELECT("cp.async.bulk.global.shared::cta.bulk_group.L2::cache_hint [%0], [%1], %2, %3;") ::"l"(dst), "r"(src), "r"(bytes), "l"(pol) : "memory");
}
__device__ __forceinline__ void tma2d(uint32_t dst, const CUtensorMap* m, int c0, int c1, uint32_t bar, uint64_t pol = L2_NORMAL) {
  asm volatile(ELECT("cp.async.bulk.tensor.2d.shared::cluster.global.mbarrier::complete_tx::bytes.L2::cache_hint [%0], [%1, {%3, %4}], [%2], %5;") ::"r"(dst), "l"(m), "r"(bar), "r"(c0), "r"(c1), "l"(pol) : "memory");
}
__device__ __forceinline__ void tma2d_mc(uint32_t dst, const CUtensorMap* m, int c0, int c1, uint32_t bar, uint64_t pol = L2_NORMAL) {
  asm volatile(ELECT("cp.async.bulk.tensor.2d.shared::cluster.global.mbarrier::complete_tx::bytes.multicast::cluster.L2::cache_hint [%0], [%1, {%3, %4}], [%2], %5, %6;") ::"r"(dst), "l"(m), "r"(bar), "r"(c0), "r"(c1), "h"((uint16_t)3), "l"(pol) : "memory");
}
__device__ __forceinline__ void tma3d(uint32_t dst, const CUtensorMap* m, int c0, int c1, int c2, uint32_t bar, uint64_t pol = L2_NORMAL) {
  asm volatile(ELECT("cp.async.bulk.tensor.3d.shared::cluster.global.mbarrier::complete_tx::bytes.L2::cache_hint [%0], [%1, {%3, %4, %5}], [%2], %6;") ::"r"(dst), "l"(m), "r"(bar), "r"(c0), "r"(c1), "r"(c2), "l"(pol) : "memory");
}
__device__ __forceinline__ void tma3d_mc(uint32_t dst, const CUtensorMap* m, int c0, int c1, int c2, uint32_t bar, uint64_t pol = L2_NORMAL) {
  asm volatile(ELECT("cp.async.bulk.tensor.3d.shared::cluster.global.mbarrier::complete_tx::bytes.multicast::cluster.L2::cache_hint [%0], [%1, {%3, %4, %5}], [%2], %6, %7;") ::"r"(dst), "l"(m), "r"(bar), "r"(c0), "r"(c1), "r"(c2), "h"((uint16_t)3), "l"(pol) : "memory");
}
__device__ __forceinline__ void tma2d_add(const CUtensorMap* m, uint32_t src, int c0, int c1) {
  asm volatile(ELECT("cp.reduce.async.bulk.tensor.2d.global.shared::cta.add.bulk_group [%0, {%2, %3}], [%1];") ::"l"(m), "r"(src), "r"(c0), "r"(c1) : "memory");
}
__device__ __forceinline__ void tma3d_store(const CUtensorMap* m, uint32_t src, int c0, int c1, int c2, uint64_t pol = L2_NORMAL) {
  asm volatile(ELECT("cp.async.bulk.tensor.3d.global.shared::cta.bulk_group.L2::cache_hint [%0, {%2, %3, %4}], [%1], %5;") ::"l"(m), "r"(src), "r"(c0), "r"(c1), "r"(c2), "l"(pol) : "memory");
}
__device__ __forceinline__ void tma2d_prefetch(const CUtensorMap* m, int c0, int c1, uint64_t pol = L2_NORMAL) {
  asm volatile(ELECT("cp.async.bulk.prefetch.tensor.2d.L2.global.L2::cache_hint [%0, {%1, %2}], %3;") ::"l"(m), "r"(c0), "r"(c1), "l"(pol) : "memory");
}
#define LAG 3
#define HINT 62
#define POL(bit) ((HINT >> (bit)) & 1 ? L2_FIRST : L2_NORMAL)
#define BULK_COMMIT() asm volatile("cp.async.bulk.commit_group;" ::: "memory")
#define BULK_WAIT(n) asm volatile("cp.async.bulk.wait_group %0;" ::"n"(n) : "memory")
#define BULK_WAIT_READ(n) asm volatile("cp.async.bulk.wait_group.read %0;" ::"n"(n) : "memory")
#define FENCE_ASYNC_SMEM() asm volatile("fence.proxy.async.shared::cta;" ::: "memory")
#define FENCE_ASYNC_ALL() asm volatile("fence.proxy.async;" ::: "memory")
#define WG_FENCE() asm volatile("wgmma.fence.sync.aligned;" ::: "memory")
#define WG_COMMIT() asm volatile("wgmma.commit_group.sync.aligned;" ::: "memory")
#define WG_WAIT(n) asm volatile("wgmma.wait_group.sync.aligned %0;" ::"n"(n) : "memory")
__device__ __forceinline__ void bar_sync(int id, int n) { asm volatile("bar.sync %0, %1;" ::"r"(id), "r"(n) : "memory"); }
__device__ __forceinline__ void bar_arrive(int id, int n) { asm volatile("bar.arrive %0, %1;" ::"r"(id), "r"(n) : "memory"); }
__device__ __forceinline__ void cluster_sync() {
  asm volatile("barrier.cluster.arrive.relaxed;\nbarrier.cluster.wait.acquire;" ::: "memory");
}
template <int N> __device__ __forceinline__ void pin(float (&r)[N]) {
#pragma unroll
  for (int i = 0; i < N; i++) asm volatile("" : "+f"(r[i])::"memory");
}
template <int N> __device__ __forceinline__ void pin(uint32_t (&r)[N]) {
#pragma unroll
  for (int i = 0; i < N; i++) asm volatile("" : "+r"(r[i])::"memory");
}
__device__ __forceinline__ uint32_t pack_bf16(float lo, float hi) {
  uint32_t r; asm("cvt.rn.bf16x2.f32 %0, %1, %2;" : "=r"(r) : "f"(hi), "f"(lo)); return r;
}
__device__ __forceinline__ float ex2(float x) { float r; asm("ex2.approx.ftz.f32 %0, %1;" : "=f"(r) : "f"(x)); return r; }
__device__ __forceinline__ void ldsm4(uint32_t a, uint32_t& r0, uint32_t& r1, uint32_t& r2, uint32_t& r3) {
  asm volatile("ldmatrix.sync.aligned.m8n8.x4.shared.b16 {%0,%1,%2,%3}, [%4];" : "=r"(r0), "=r"(r1), "=r"(r2), "=r"(r3) : "r"(a) : "memory");
}
__device__ __forceinline__ void stsm4(uint32_t a, uint32_t r0, uint32_t r1, uint32_t r2, uint32_t r3) {
  asm volatile("stmatrix.sync.aligned.m8n8.x4.shared.b16 [%0], {%1,%2,%3,%4};" ::"r"(a), "r"(r0), "r"(r1), "r"(r2), "r"(r3) : "memory");
}
__device__ __forceinline__ void flag_add(int idx, int v = 1) {
  asm volatile(ELECT("red.release.gpu.global.add.s32 [%0], %1;") ::"l"(g_flags + idx), "r"(v) : "memory");
}
__device__ __forceinline__ void flag_add_rx(int idx, int v = 1) {
  asm volatile(ELECT("red.relaxed.gpu.global.add.s32 [%0], %1;") ::"l"(g_flags + idx), "r"(v) : "memory");
}
template <bool ACQ, int NS = 32> __device__ __forceinline__ void flag_wait(int idx, int target) {
  int n = 0;
  while (true) {
    int v;
    if (ACQ) asm volatile("ld.acquire.gpu.global.s32 %0, [%1];" : "=r"(v) : "l"(g_flags + idx) : "memory");
    else asm volatile("ld.relaxed.gpu.global.s32 %0, [%1];" : "=r"(v) : "l"(g_flags + idx) : "memory");
    if (__all_sync(0xffffffffu, v >= target)) break;
    if (++n > 20000000) __trap();
    __nanosleep(NS);
  }
}
__device__ __forceinline__ int flag_peek(int idx) {
  int v;
  asm volatile("ld.relaxed.gpu.global.s32 %0, [%1];" : "=r"(v) : "l"(g_flags + idx) : "memory");
  return v;
}
__device__ __forceinline__ void mask_wait(uint32_t& ready, int bit, int idx, int target) {
  for (int n = 0; !((ready >> bit) & 1); n++) {
    int v;
    if (n) { __nanosleep(32); if (n > 20000000) __trap(); }
    asm volatile("ld.relaxed.gpu.global.s32 %0, [%1];" : "=r"(v) : "l"(g_flags + idx) : "memory");
    ready = __ballot_sync(0xffffffffu, v >= target);
  }
}
__device__ __forceinline__ uint32_t desc_lo(uint32_t addr, uint32_t lbo) { return ((addr & 0x3FFFFu) >> 4) | ((lbo >> 4) << 16); }
#define PROF(role, i)
#define PROFX(cond, i)
#define PROFB(i)
#define PROFG(i)

template <int TB, int TA = 0> __device__ __forceinline__ void wgmma_ss64(float (&d)[32], uint32_t alo, uint32_t blo, int sd) {
  asm volatile("{\n.reg .pred p;\n.reg .b64 da, db;\n"
    "setp.ne.b32 p, %34, 0;\nmov.b64 da, {%32, %36};\nmov.b64 db, {%33, %36};\n"
    "wgmma.mma_async.sync.aligned.m64n64k16.f32.bf16.bf16 "
    "{%0,%1,%2,%3,%4,%5,%6,%7,%8,%9,%10,%11,%12,%13,%14,%15,%16,%17,%18,%19,%20,%21,%22,%23,"
    "%24,%25,%26,%27,%28,%29,%30,%31}, "
    "da, db, p, 1, 1, %37, %35;\n}\n"
    : "+f"(d[0]),"+f"(d[1]),"+f"(d[2]),"+f"(d[3]),"+f"(d[4]),"+f"(d[5]),"+f"(d[6]),"+f"(d[7]),"+f"(d[8]),"+f"(d[9]),"+f"(d[10]),"+f"(d[11]),
      "+f"(d[12]),"+f"(d[13]),"+f"(d[14]),"+f"(d[15]),"+f"(d[16]),"+f"(d[17]),"+f"(d[18]),"+f"(d[19]),"+f"(d[20]),"+f"(d[21]),"+f"(d[22]),"+f"(d[23]),
      "+f"(d[24]),"+f"(d[25]),"+f"(d[26]),"+f"(d[27]),"+f"(d[28]),"+f"(d[29]),"+f"(d[30]),"+f"(d[31])
    : "r"(alo), "r"(blo), "r"(sd), "n"(TB), "r"(DESC_HI), "n"(TA));
}
template <int TB, int TA = 0> __device__ __forceinline__ void wgmma_ss128(float (&d)[64], uint32_t alo, uint32_t blo, int sd) {
  asm volatile("{\n.reg .pred p;\n.reg .b64 da, db;\n"
    "setp.ne.b32 p, %66, 0;\nmov.b64 da, {%64, %68};\nmov.b64 db, {%65, %68};\n"
    "wgmma.mma_async.sync.aligned.m64n128k16.f32.bf16.bf16 "
    "{%0,%1,%2,%3,%4,%5,%6,%7,%8,%9,%10,%11,%12,%13,%14,%15,%16,%17,%18,%19,%20,%21,%22,%23,"
    "%24,%25,%26,%27,%28,%29,%30,%31,%32,%33,%34,%35,%36,%37,%38,%39,%40,%41,%42,%43,%44,%45,%46,%47,"
    "%48,%49,%50,%51,%52,%53,%54,%55,%56,%57,%58,%59,%60,%61,%62,%63}, "
    "da, db, p, 1, 1, %69, %67;\n}\n"
    : "+f"(d[0]),"+f"(d[1]),"+f"(d[2]),"+f"(d[3]),"+f"(d[4]),"+f"(d[5]),"+f"(d[6]),"+f"(d[7]),"+f"(d[8]),"+f"(d[9]),"+f"(d[10]),"+f"(d[11]),
      "+f"(d[12]),"+f"(d[13]),"+f"(d[14]),"+f"(d[15]),"+f"(d[16]),"+f"(d[17]),"+f"(d[18]),"+f"(d[19]),"+f"(d[20]),"+f"(d[21]),"+f"(d[22]),"+f"(d[23]),
      "+f"(d[24]),"+f"(d[25]),"+f"(d[26]),"+f"(d[27]),"+f"(d[28]),"+f"(d[29]),"+f"(d[30]),"+f"(d[31]),"+f"(d[32]),"+f"(d[33]),"+f"(d[34]),"+f"(d[35]),
      "+f"(d[36]),"+f"(d[37]),"+f"(d[38]),"+f"(d[39]),"+f"(d[40]),"+f"(d[41]),"+f"(d[42]),"+f"(d[43]),"+f"(d[44]),"+f"(d[45]),"+f"(d[46]),"+f"(d[47]),
      "+f"(d[48]),"+f"(d[49]),"+f"(d[50]),"+f"(d[51]),"+f"(d[52]),"+f"(d[53]),"+f"(d[54]),"+f"(d[55]),"+f"(d[56]),"+f"(d[57]),"+f"(d[58]),"+f"(d[59]),
      "+f"(d[60]),"+f"(d[61]),"+f"(d[62]),"+f"(d[63])
    : "r"(alo), "r"(blo), "r"(sd), "n"(TB), "r"(DESC_HI), "n"(TA));
}
template <int TB> __device__ __forceinline__ void wgmma_rs128(float (&d)[64], uint32_t a0, uint32_t a1, uint32_t a2, uint32_t a3, uint32_t blo, int sd) {
  asm volatile("{\n.reg .pred p;\n.reg .b64 db;\n"
    "setp.ne.b32 p, %69, 0;\nmov.b64 db, {%68, %71};\n"
    "wgmma.mma_async.sync.aligned.m64n128k16.f32.bf16.bf16 "
    "{%0,%1,%2,%3,%4,%5,%6,%7,%8,%9,%10,%11,%12,%13,%14,%15,%16,%17,%18,%19,%20,%21,%22,%23,"
    "%24,%25,%26,%27,%28,%29,%30,%31,%32,%33,%34,%35,%36,%37,%38,%39,%40,%41,%42,%43,%44,%45,%46,%47,"
    "%48,%49,%50,%51,%52,%53,%54,%55,%56,%57,%58,%59,%60,%61,%62,%63}, "
    "{%64,%65,%66,%67}, db, p, 1, 1, %70;\n}\n"
    : "+f"(d[0]),"+f"(d[1]),"+f"(d[2]),"+f"(d[3]),"+f"(d[4]),"+f"(d[5]),"+f"(d[6]),"+f"(d[7]),"+f"(d[8]),"+f"(d[9]),"+f"(d[10]),"+f"(d[11]),
      "+f"(d[12]),"+f"(d[13]),"+f"(d[14]),"+f"(d[15]),"+f"(d[16]),"+f"(d[17]),"+f"(d[18]),"+f"(d[19]),"+f"(d[20]),"+f"(d[21]),"+f"(d[22]),"+f"(d[23]),
      "+f"(d[24]),"+f"(d[25]),"+f"(d[26]),"+f"(d[27]),"+f"(d[28]),"+f"(d[29]),"+f"(d[30]),"+f"(d[31]),"+f"(d[32]),"+f"(d[33]),"+f"(d[34]),"+f"(d[35]),
      "+f"(d[36]),"+f"(d[37]),"+f"(d[38]),"+f"(d[39]),"+f"(d[40]),"+f"(d[41]),"+f"(d[42]),"+f"(d[43]),"+f"(d[44]),"+f"(d[45]),"+f"(d[46]),"+f"(d[47]),
      "+f"(d[48]),"+f"(d[49]),"+f"(d[50]),"+f"(d[51]),"+f"(d[52]),"+f"(d[53]),"+f"(d[54]),"+f"(d[55]),"+f"(d[56]),"+f"(d[57]),"+f"(d[58]),"+f"(d[59]),
      "+f"(d[60]),"+f"(d[61]),"+f"(d[62]),"+f"(d[63])
    : "r"(a0), "r"(a1), "r"(a2), "r"(a3), "r"(blo), "r"(sd), "n"(TB), "r"(DESC_HI));
}
template <int TB, int TA = 0> __device__ __forceinline__ void wgmma_ss192(float (&d)[96], uint32_t alo, uint32_t blo, int sd) {
  asm volatile("{\n.reg .pred p;\n.reg .b64 da, db;\n"
    "setp.ne.b32 p, %98, 0;\nmov.b64 da, {%96, %100};\nmov.b64 db, {%97, %100};\n"
    "wgmma.mma_async.sync.aligned.m64n192k16.f32.bf16.bf16 "
    "{%0,%1,%2,%3,%4,%5,%6,%7,%8,%9,%10,%11,%12,%13,%14,%15,%16,%17,%18,%19,%20,%21,%22,%23,"
    "%24,%25,%26,%27,%28,%29,%30,%31,%32,%33,%34,%35,%36,%37,%38,%39,%40,%41,%42,%43,%44,%45,%46,%47,"
    "%48,%49,%50,%51,%52,%53,%54,%55,%56,%57,%58,%59,%60,%61,%62,%63,%64,%65,%66,%67,%68,%69,%70,%71,"
    "%72,%73,%74,%75,%76,%77,%78,%79,%80,%81,%82,%83,%84,%85,%86,%87,%88,%89,%90,%91,%92,%93,%94,%95}, "
    "da, db, p, 1, 1, %101, %99;\n}\n"
    : "+f"(d[0]),"+f"(d[1]),"+f"(d[2]),"+f"(d[3]),"+f"(d[4]),"+f"(d[5]),"+f"(d[6]),"+f"(d[7]),"+f"(d[8]),"+f"(d[9]),"+f"(d[10]),"+f"(d[11]),
      "+f"(d[12]),"+f"(d[13]),"+f"(d[14]),"+f"(d[15]),"+f"(d[16]),"+f"(d[17]),"+f"(d[18]),"+f"(d[19]),"+f"(d[20]),"+f"(d[21]),"+f"(d[22]),"+f"(d[23]),
      "+f"(d[24]),"+f"(d[25]),"+f"(d[26]),"+f"(d[27]),"+f"(d[28]),"+f"(d[29]),"+f"(d[30]),"+f"(d[31]),"+f"(d[32]),"+f"(d[33]),"+f"(d[34]),"+f"(d[35]),
      "+f"(d[36]),"+f"(d[37]),"+f"(d[38]),"+f"(d[39]),"+f"(d[40]),"+f"(d[41]),"+f"(d[42]),"+f"(d[43]),"+f"(d[44]),"+f"(d[45]),"+f"(d[46]),"+f"(d[47]),
      "+f"(d[48]),"+f"(d[49]),"+f"(d[50]),"+f"(d[51]),"+f"(d[52]),"+f"(d[53]),"+f"(d[54]),"+f"(d[55]),"+f"(d[56]),"+f"(d[57]),"+f"(d[58]),"+f"(d[59]),
      "+f"(d[60]),"+f"(d[61]),"+f"(d[62]),"+f"(d[63]),"+f"(d[64]),"+f"(d[65]),"+f"(d[66]),"+f"(d[67]),"+f"(d[68]),"+f"(d[69]),"+f"(d[70]),"+f"(d[71]),
      "+f"(d[72]),"+f"(d[73]),"+f"(d[74]),"+f"(d[75]),"+f"(d[76]),"+f"(d[77]),"+f"(d[78]),"+f"(d[79]),"+f"(d[80]),"+f"(d[81]),"+f"(d[82]),"+f"(d[83]),
      "+f"(d[84]),"+f"(d[85]),"+f"(d[86]),"+f"(d[87]),"+f"(d[88]),"+f"(d[89]),"+f"(d[90]),"+f"(d[91]),"+f"(d[92]),"+f"(d[93]),"+f"(d[94]),"+f"(d[95])
    : "r"(alo), "r"(blo), "r"(sd), "n"(TB), "r"(DESC_HI), "n"(TA));
}

struct Ctx {
  uint32_t sm;
  uint32_t bar;
  uint32_t rbar;
  int cl, rank, wg, warp, lane, phases;
};
__device__ __forceinline__ void release(const Ctx& c, int b, int cnt = 1) {
  if (c.lane < 2) mbar_arrive_cl(c.rbar + b * 8, cnt);
}
#define HK 5
#define NPRO 6
#define ZLEAD 14
#define PFM 7
#define PF1 1
constexpr float SM_SCALE = 0.08838834764831845f * 1.4426950408889634f;
constexpr float SM_HI = 1.8446744e19f, SM_LO = 5.4210109e-20f;
constexpr int ORDER = 1;

__device__ __forceinline__ void stage_tile(const float (&a)[64], uint32_t buf, const Ctx& c, float s0, float s1) {
  const int row = (c.lane & 7) + ((c.lane >> 3) & 1) * 8;
  const uint32_t base = buf + (c.warp * 16 + row) * 128 + (((c.lane >> 4) ^ (row & 7)) << 4);
#pragma unroll
  for (int i = 0; i < 8; i++)
    stsm4((base ^ ((i & 3) << 5)) + (i >> 2) * 8192, pack_bf16(a[8 * i] * s0, a[8 * i + 1] * s0), pack_bf16(a[8 * i + 2] * s1, a[8 * i + 3] * s1),
          pack_bf16(a[8 * i + 4] * s0, a[8 * i + 5] * s0), pack_bf16(a[8 * i + 6] * s1, a[8 * i + 7] * s1));
}

__device__ __forceinline__ void p1_epilogue(const Params& p, const Ctx& c, const float (&acc)[64], int t, int type) {
  const int tile = p.s.r[c.cl].tile[t] & 63, b = c.wg * 2 + 1;
  mbar_wait(c.bar + (B_SE + b) * 8, (t & 1) ^ 1);
  if (type && tile >= 32) {
    const int r = 2 * (c.lane & 3) + ((c.lane >> 2) & 1);
    const uint32_t dst = c.sm + SM_BUF + b * 16384 + r * 128 + (((c.warp * 2) ^ r) << 4) + (c.lane >> 3) * 4;
#pragma unroll
    for (int i = 0; i < 16; i++) {
      asm volatile("st.shared.u32 [%0], %1;" ::"r"(dst + i * 1024), "r"(pack_bf16(acc[4 * i], acc[4 * i + 1])) : "memory");
      asm volatile("st.shared.u32 [%0], %1;" ::"r"((dst ^ 16) + i * 1024), "r"(pack_bf16(acc[4 * i + 2], acc[4 * i + 3])) : "memory");
    }
  } else {
    if (type) stage_tile(acc, c.sm + SM_BUF + b * 16384, c, SM_SCALE, SM_SCALE);
    else stage_tile(acc, c.sm + SM_BUF + b * 16384, c, 1.f, 1.f);
  }
  FENCE_ASYNC_SMEM();
  __syncwarp();
  if (c.lane == 0) mbar_arrive(c.bar + (B_SF + b) * 8);
}

__device__ __forceinline__ void p1_consumer(const Params& p, const Ctx& c) {
  const int n = p.s.r[c.cl].n1;
  const int type = p.s.r[c.cl].slab >> 3;
  const uint32_t bdesc = desc_lo(c.sm + SM_RING, 8192), adesc = desc_lo(c.sm + SM_BUF + 32768 + c.wg * 8192, 16);
  uint32_t A[128];
  float acc[64] = {};
  int slot = 0, par = 0;
  auto next = [&]() { if (++slot == 10) { slot = 0; par ^= 1; } };
  {
    const int row = (c.lane & 7) + ((c.lane >> 3) & 1) * 8;
    const uint32_t base = c.sm + SM_RING + (c.wg * 64 + c.warp * 16 + row) * 128 + (((c.lane >> 4) ^ (row & 7)) << 4);
    if (c.wg == 1) bar_sync(ORDER + 1, 256);
    int pa = -1, pb = -1;
    if (type) {
      mbar_wait(c.bar + B_P1F * 8, 0);
      WG_FENCE();
#pragma unroll
      for (int kk = 0; kk < 4; kk++) wgmma_ss128<1>(acc, adesc + kk * 2, bdesc + kk * 128, kk != 0);
      WG_COMMIT();
      pb = 0; slot = 1;
    }
#pragma unroll
    for (int kb = 0; kb < 8; kb++) {
      const int sa = slot;
      mbar_wait(c.bar + (B_P1F + slot) * 8, par);
      if (kb == 0) PROF(c.wg, 5);
      next();
      mbar_wait(c.bar + (B_P1F + slot) * 8, par);
      PROF(c.wg, 6 + 2 * kb);
      WG_FENCE();
#pragma unroll
      for (int kk = 0; kk < 4; kk++)
        wgmma_ss128<1>(acc, desc_lo(c.sm + SM_RING + c.wg * 8192, 16) + sa * 1024 + kk * 2, bdesc + slot * 1024 + kk * 128, (kb | kk) != 0 ? 1 : type);
      WG_COMMIT();
      if (kb == 1 && c.wg == 0) bar_arrive(ORDER + 1, 256);
#pragma unroll
      for (int kk = 0; kk < 4; kk++) ldsm4((base ^ (kk << 5)) + sa * 16384, A[kb * 16 + kk * 4], A[kb * 16 + kk * 4 + 1], A[kb * 16 + kk * 4 + 2], A[kb * 16 + kk * 4 + 3]);
      WG_WAIT(1);
      if (kb > 0) release(c, B_P1E + pa);
      if (kb > 0 || pb >= 0) release(c, B_P1E + pb);
      pa = sa; pb = slot;
      next();
    }
    WG_WAIT(0);
    __syncwarp();
    release(c, B_P1E + pa);
    release(c, B_P1E + pb);
    pin(acc);
    PROF(c.wg, 1);
    p1_epilogue(p, c, acc, 0, type);
    PROF(c.wg, 2);
  }
  for (int t = 1; t < n; t++) {
    bar_sync(ORDER + c.wg, 256);
    int prev1 = -1, prev2 = -1;
    if (type) {
      mbar_wait(c.bar + (B_P1F + slot) * 8, par);
      WG_FENCE();
#pragma unroll
      for (int kk = 0; kk < 4; kk++) wgmma_ss128<1>(acc, adesc + kk * 2, bdesc + slot * 1024 + kk * 128, kk != 0);
      WG_COMMIT();
      prev1 = slot;
      next();
    }
#pragma unroll
    for (int kb = 0; kb < 8; kb++) {
      mbar_wait(c.bar + (B_P1F + slot) * 8, par);
      WG_FENCE();
      const uint32_t d = bdesc + slot * 1024;
#pragma unroll
      for (int kk = 0; kk < 4; kk++)
        wgmma_rs128<1>(acc, A[kb * 16 + kk * 4], A[kb * 16 + kk * 4 + 1], A[kb * 16 + kk * 4 + 2], A[kb * 16 + kk * 4 + 3], d + kk * 128, (kb | kk) != 0 ? 1 : type);
      WG_COMMIT();
      if (kb == HK) {
        if (t + 1 < n || c.wg == 0) bar_arrive(ORDER + (c.wg ^ 1), 256);
      }
      if (kb > 0) { WG_WAIT(2); if (kb > 1 || prev2 >= 0) release(c, B_P1E + prev2); }
      prev2 = prev1; prev1 = slot;
      next();
    }
    WG_WAIT(1);
    release(c, B_P1E + prev2);
    WG_WAIT(0);
    pin(acc);
    release(c, B_P1E + prev1);
    p1_epilogue(p, c, acc, t, type);
    PROF(c.wg, 3);
  }
}

__device__ __forceinline__ void p1_producer(const Params& p, const Ctx& c) {
  const int n = p.s.r[c.cl].n1;
  const int type = p.s.r[c.cl].slab >> 3, grp = p.s.r[c.cl].slab & 7;
  int slot = NPRO % 10, par = NPRO < 10;
#pragma unroll 1
  for (int t = 0; t < n; t++) {
    const int tile = p.s.r[c.cl].tile[t] & 63;
    const CUtensorMap* m = &p.map_w[type * 2 + (tile >> 5)];
    const int n0 = (tile & 31) * 128 + c.rank * 64;
    const int ptile = p.s.r[c.cl].tile[t + PF1 < n ? t + PF1 : t];
    const CUtensorMap* pm = &p.map_w[type * 2 + ((ptile >> 5) & 1)];
    if (t == 7 && (c.phases & 16)) flag_wait<true>(F_GATE, 256);
#pragma unroll 1
    for (int kb = t ? -type : (NPRO - type) >> 1; kb < 8; kb++) {
      if (t == 0 && 2 * kb + type >= NPRO) {
        mbar_wait(c.bar + (B_P1E + slot) * 8, par);
        mbar_expect(c.bar + (B_P1F + slot) * 8, 16384);
        tma2d(c.sm + SM_RING + slot * 16384, &p.map_a[type], kb * 64, grp * 256 + c.rank * 128, c.bar + (B_P1F + slot) * 8);
        if (++slot == 10) { slot = 0; par ^= 1; }
      }
      mbar_wait(c.bar + (B_P1E + slot) * 8, par);
      mbar_expect(c.bar + (B_P1F + slot) * 8, 16384);
      tma2d_mc(c.sm + SM_RING + slot * 16384 + c.rank * 8192, m, n0, kb < 0 ? 512 : kb * 64, c.bar + (B_P1F + slot) * 8);
      if (t == 0 && kb == 1) PROF(2, 61);
      if (t == 0 && kb == 3) PROF(2, 62);
      if (t + PF1 < n && t > 0 && ((ptile & 64) || ((ptile & 128) && ((kb ^ grp) & PFM) == 0))) tma2d_prefetch(pm, (ptile & 31) * 128 + c.rank * 64, kb < 0 ? 512 : kb * 64);
      if (++slot == 10) { slot = 0; par ^= 1; }
    }
  }
}

__device__ __forceinline__ void wait_kv_dead(const Ctx& c, int h, int g) {
  if (g >= 2) flag_wait<false>(F_RD + h * 8 + g, 8 - g);
  else flag_wait<false>(F_CTX + max(c.lane & 7, g) * 64 + h, 4);
}
__device__ __forceinline__ int p1_storer(const Params& p, const Ctx& c) {
  const int n = p.s.r[c.cl].n1;
  const int type = p.s.r[c.cl].slab >> 3, grp = p.s.r[c.cl].slab & 7;
  for (int i = 0; i < 2 * n; i++) {
    const int t = i >> 1, w = i & 1, b = w * 2 + 1;
    const int tile = p.s.r[c.cl].tile[t] & 63;
    mbar_wait(c.bar + (B_SF + b) * 8, t & 1);
    const uint32_t src = c.sm + SM_BUF + b * 16384;
    int f = (type ? F_Q : F_KV) + (tile & 31) * 8 + grp;
    if (type == 0) {
      const int prev = p.s.prev[tile & 31][grp];
      if (prev != 255 && w == 0) wait_kv_dead(c, prev, grp);
      uint8_t* dst = g_S + (size_t)(S_K + ((tile & 32) + p.s.slot[tile & 31][grp]) * 8 + grp) * 65536 + c.rank * 32768 + w * 8192;
      bulk_store(dst, src, 8192);
      bulk_store(dst + 16384, src + 8192, 8192);
    } else if (tile < 32) {
      const int dep = p.s.qdep[tile * 8 + grp];
      if (dep != 511 && w == 0) {
        if (dep < 256) wait_kv_dead(c, dep >> 3, dep & 7);
        else flag_wait<false>(F_TS + dep - 256, 128);
      }
      bulk_store(g_S + (size_t)p.s.qblk[tile * 8 + grp] * 65536 + (c.rank * 2 + w) * 16384, src, 16384);
    } else {
      tma3d_store(&p.map_t[2], src, (grp * 4 + c.rank * 2 + w) * 32, 0, (tile - 32) * 64);
      f = F_QKVA + grp * 4 + ((0xE4390900u >> (2 * (tile - 30))) & 3);
    }
    BULK_COMMIT();
    BULK_WAIT(0);
    mbar_arrive_one(c.bar + (B_SE + b) * 8);
    if (i == 2 * n - 1) return f;
    if (w) flag_add(f, 2);
  }
  return -1;
}

__device__ __forceinline__ int p2_buf(int w, int i) { return w * 2 + (i & 1); }
__device__ __forceinline__ int p2_blk(int rank, int w, int i) { return ((i ^ w) & 1) == 0 ? 3 - rank : rank; }

template <int N>
__device__ __forceinline__ void row_max(const float (&s)[N], float& m0, float& m1) {
  float a0 = fmaxf(s[0], s[1]), a1 = fmaxf(s[2], s[3]);
#pragma unroll
  for (int i = 1; i < N / 4; i++) {
    m0 = fmaxf(m0, s[4 * i]); a0 = fmaxf(a0, s[4 * i + 1]);
    m1 = fmaxf(m1, s[4 * i + 2]); a1 = fmaxf(a1, s[4 * i + 3]);
  }
  m0 = fmaxf(m0, a0); m1 = fmaxf(m1, a1);
  m0 = fmaxf(m0, __shfl_xor_sync(0xffffffffu, m0, 1));
  m1 = fmaxf(m1, __shfl_xor_sync(0xffffffffu, m1, 1));
  m0 = fmaxf(m0, __shfl_xor_sync(0xffffffffu, m0, 2));
  m1 = fmaxf(m1, __shfl_xor_sync(0xffffffffu, m1, 2));
}
template <bool SUB, int N>
__device__ __forceinline__ void row_exp(const float (&s)[N], uint32_t (&P)[32], float m0, float m1, float& t0, float& t1) {
  float u0 = 0.f, u1 = 0.f;
  t0 = t1 = 0.f;
#pragma unroll
  for (int i = 0; i < N / 4; i++) {
    const float e0 = ex2(SUB ? s[4 * i] - m0 : s[4 * i]), e1 = ex2(SUB ? s[4 * i + 1] - m0 : s[4 * i + 1]);
    const float e2 = ex2(SUB ? s[4 * i + 2] - m1 : s[4 * i + 2]), e3 = ex2(SUB ? s[4 * i + 3] - m1 : s[4 * i + 3]);
    if (i == 0) { t0 = e0; u0 = e1; t1 = e2; u1 = e3; }
    else { t0 += e0; u0 += e1; t1 += e2; u1 += e3; }
    P[2 * i] = pack_bf16(e0, e1);
    P[2 * i + 1] = pack_bf16(e2, e3);
  }
#pragma unroll
  for (int i = N / 2; i < 32; i++) P[i] = 0;
  pin(P);
  t0 += u0; t1 += u1;
}
template <int N>
__device__ __forceinline__ void causal_mask(float (&s)[N], int thr) {
#pragma unroll
  for (int i = 0; i < 8; i++) {
    if (8 * i > thr) s[N - 32 + 4 * i] = -INFINITY;
    if (8 * i + 1 > thr) s[N - 32 + 4 * i + 1] = -INFINITY;
    if (8 * i - 8 > thr) s[N - 32 + 4 * i + 2] = -INFINITY;
    if (8 * i - 7 > thr) s[N - 32 + 4 * i + 3] = -INFINITY;
  }
}
__device__ __forceinline__ void issue_qk(float (&s)[32], uint32_t qd, uint32_t kd) {
  WG_FENCE();
#pragma unroll
  for (int kk = 0; kk < 8; kk++) wgmma_ss64<0>(s, qd + (kk >> 2) * 512 + (kk & 3) * 2, kd + (kk >> 2) * 1024 + (kk & 3) * 2, kk != 0);
  WG_COMMIT();
}
__device__ __forceinline__ void issue_qk(float (&s)[64], uint32_t qd, uint32_t kd) {
  WG_FENCE();
#pragma unroll
  for (int kk = 0; kk < 8; kk++) wgmma_ss128<0>(s, qd + (kk >> 2) * 512 + (kk & 3) * 2, kd + (kk >> 2) * 1024 + (kk & 3) * 2, kk != 0);
  WG_COMMIT();
}
template <int NK>
__device__ __forceinline__ void issue_pv(float (&o)[64], const uint32_t (&P)[32], uint32_t vd, int acc) {
  WG_FENCE();
#pragma unroll
  for (int kk = 0; kk < NK; kk++) wgmma_rs128<1>(o, P[4 * kk], P[4 * kk + 1], P[4 * kk + 2], P[4 * kk + 3], vd + kk * 128, kk != 0 ? 1 : acc);
  WG_COMMIT();
}
__device__ __forceinline__ void stage_done(const Ctx& c, int b) {
  FENCE_ASYNC_SMEM();
  __syncwarp();
  if (c.lane == 0) mbar_arrive(c.bar + (B_SF + b) * 8);
}
__device__ __forceinline__ void p2_epilogue(const float (&o)[64], float s0, float s1, const Ctx& c, int b) {
  stage_tile(o, c.sm + SM_BUF + b * 16384, c, s0, s1);
  stage_done(c, b);
}

struct P2State {
  float m0, m1, l0, l1;
  bool shift;
  float e0, e1;
  int ks;
  int wi, ai;
  uint32_t wb, ab;
  uint32_t qd;
};
#define PROFZ()
__device__ __forceinline__ int wrap5(int q) { return q >= 5 ? q - 5 : q; }
__device__ __forceinline__ void turn_wait(uint32_t ring, int i) { mbar_wait(ring + (i & 3) * 8, (i >> 2) & 1); }
__device__ __forceinline__ void turn_pass(const Ctx& c, uint32_t ring, int i) { if (c.lane == 0) mbar_arrive(ring + (i & 3) * 8); }
__device__ __forceinline__ void p2_scales(P2State& z) {
  float l0 = z.l0, l1 = z.l1;
  l0 += __shfl_xor_sync(0xffffffffu, l0, 1);
  l1 += __shfl_xor_sync(0xffffffffu, l1, 1);
  l0 += __shfl_xor_sync(0xffffffffu, l0, 2);
  l1 += __shfl_xor_sync(0xffffffffu, l1, 2);
  asm("rcp.approx.ftz.f32 %0, %1;" : "=f"(z.e0) : "f"(l0));
  asm("rcp.approx.ftz.f32 %0, %1;" : "=f"(z.e1) : "f"(l1));
}
template <int N>
__device__ __forceinline__ void p2_first(const Ctx& c, P2State& z, float (&o)[64], uint32_t (&Pc)[32], uint32_t (&Pn)[32],
                                         int ks, int vs, int cnt, int acc) {
  float s[N] = {};
  issue_qk(s, z.qd, desc_lo(c.sm + SM_RING, 16) + ks * 2048);
  if (vs >= 0) {
    p2_scales(z);
    issue_pv<8>(o, Pc, desc_lo(c.sm + SM_RING, 16384) + vs * 2048, acc);
  } else {
    WG_COMMIT();
  }
  mbar_expect(z.ab + (z.ai++ & 3) * 8, cnt == 1 ? 8192 : 0);
  PROFZ();
  WG_WAIT(1);
  PROFZ();
  pin(s);
  release(c, B_P2E + ks, cnt);
  causal_mask(s, c.warp * 16 + (c.lane >> 2) - 2 * (c.lane & 3));
  z.m0 = z.m1 = 0.f;
  row_exp<false>(s, Pn, 0.f, 0.f, z.l0, z.l1);
  z.shift = __any_sync(0xffffffffu, !(z.l0 + z.l1 <= SM_HI) || ((c.lane & 3) == 0 && !(fminf(z.l0, z.l1) >= SM_LO)));
  if (__builtin_expect(z.shift, 0)) {
    z.m0 = z.m1 = -INFINITY;
    row_max(s, z.m0, z.m1);
    row_exp<true>(s, Pn, z.m0, z.m1, z.l0, z.l1);
  }
  WG_WAIT(0);
  pin(o);
  if (vs >= 0) release(c, B_P2E + vs, 1);
}

template <bool SECOND>
__device__ __forceinline__ void p2_turn(const Ctx& c, P2State& z, float (&o)[64], uint32_t (&Pc)[32], uint32_t (&Pn)[32],
                                        int eb = -1, bool half = false, int vcnt = 1) {
  float s[64] = {};
  const int ks = z.ks, vs = wrap5(ks + 1);
  PROFZ();
  turn_wait(z.wb, z.wi++);
  PROFZ();
  issue_qk(s, z.qd, desc_lo(c.sm + SM_RING, 16) + ks * 2048);
  const uint32_t vd = desc_lo(c.sm + SM_RING, 16384) + vs * 2048;
  if (SECOND) {
    if (eb >= 0) stage_tile(o, c.sm + SM_BUF + eb * 16384, c, z.e0, z.e1);
    if (half) issue_pv<4>(o, Pc, vd, 0); else issue_pv<8>(o, Pc, vd, 0);
  } else {
    issue_pv<8>(o, Pc, vd, 1);
  }
  turn_pass(c, z.ab, z.ai++);
  if (SECOND) { if (eb >= 0) stage_done(c, eb); }
  PROFZ();
  z.ks = wrap5(ks + 2);
  WG_WAIT(1);
  PROFZ();
  pin(s);
  release(c, B_P2E + ks, 1);
  float t0, t1, a0 = 1.f, a1 = 1.f;
  row_exp<false>(s, Pn, 0.f, 0.f, t0, t1);
  z.shift = __any_sync(0xffffffffu, z.shift || !(t0 + t1 <= SM_HI));
  const bool redo = z.shift;
  if (__builtin_expect(redo, 0)) {
    float n0 = z.m0, n1 = z.m1;
    row_max(s, n0, n1);
    a0 = ex2(z.m0 - n0); a1 = ex2(z.m1 - n1);
    z.m0 = n0; z.m1 = n1;
    z.l0 *= a0; z.l1 *= a1;
    row_exp<true>(s, Pn, z.m0, z.m1, t0, t1);
  }
  WG_WAIT(0);
  pin(o);
  release(c, B_P2E + vs, vcnt);
  if (__builtin_expect(redo, 0)) {
#pragma unroll
    for (int i = 0; i < 16; i++) { o[4 * i] *= a0; o[4 * i + 1] *= a0; o[4 * i + 2] *= a1; o[4 * i + 3] *= a1; }
  }
  z.l0 += t0; z.l1 += t1;
}
__device__ __forceinline__ void copy_p(uint32_t (&d)[32], const uint32_t (&s)[32], int zero) {
#pragma unroll
  for (int i = 0; i < 32; i++) asm volatile("add.s32 %0, %1, %2;" : "=r"(d[i]) : "r"(s[i]), "r"(zero));
}

__device__ __forceinline__ void p2_consumer(const Params& p, const Ctx& c, int rot) {
  const int nit = p.s.r[c.cl].n2;
  const uint32_t fring = c.bar + B_P2F * 8, oring = c.bar + B_ORD * 8;
  float o[64] = {};
  uint32_t Pa[32] = {}, Pb[32] = {};
  P2State z;
  z.e0 = z.e1 = z.l0 = z.l1 = 0.f; z.ks = rot; z.shift = false;
  int acc = 0, n = 0;
  for (int it = 0; it < nit; it++) {
    const int j = p.s.r[c.cl].item[it] & 7, blk = p2_blk(c.rank, c.wg, it);
    const int lng = ((it ^ c.wg) & 1) ^ 1;
    z.qd = desc_lo(c.sm + SM_BUF, 16) + p2_buf(c.wg, it) * 1024;
    if (lng) { z.wb = oring; z.wi = n - it; z.ab = fring; z.ai = n + 1; }
    else { z.wb = fring; z.wi = n + 2; z.ab = oring; z.ai = n - it; }
    PROFZ();
    mbar_wait(c.bar + (B_QF + p2_buf(c.wg, it)) * 8, (it >> 1) & 1);
    turn_wait(fring, n + 1 - lng);
    PROFZ();
    const int vs = it ? wrap5(z.ks + 1) : -1, ks = lng ? z.ks : wrap5(z.ks + (it ? 2 : 1));
    if (blk & 1) p2_first<64>(c, z, o, Pa, Pb, ks, vs, 1 + lng, acc);
    else p2_first<32>(c, z, o, Pa, Pb, ks, vs, 1 + lng, acc);
    z.ks = wrap5(ks + (it == 0 && lng ? 1 : 2));
    PROF(c.wg, 24 + it);
    n += 2 * j + 2;
    int left = 2 * j + lng;
    acc = left != 0;
    if (left == 0) { copy_p(Pa, Pb, p.zero); continue; }
    p2_turn<true>(c, z, o, Pb, Pa, it > 0 ? p2_buf(c.wg, it - 1) : -1, !(blk & 1), 1 + lng);
    while (--left > 0) {
      p2_turn<false>(c, z, o, Pa, Pb);
      if (--left == 0) { copy_p(Pa, Pb, p.zero); break; }
      p2_turn<false>(c, z, o, Pb, Pa);
    }
  }
  {
    if (!acc && nit > 1) p2_epilogue(o, z.e0, z.e1, c, p2_buf(c.wg, nit));
    turn_wait(z.wb, z.wi);
    issue_pv<8>(o, Pa, desc_lo(c.sm + SM_RING, 16384) + z.ks * 2048, acc);
    if (((nit - 1) ^ c.wg) & 1) turn_pass(c, z.ab, z.ai);
    p2_scales(z);
    WG_WAIT(0);
    pin(o);
    release(c, B_P2E + z.ks);
    p2_epilogue(o, z.e0, z.e1, c, p2_buf(c.wg, nit - 1));
    PROF(c.wg, 24 + nit);
  }
}

__device__ __forceinline__ void p2_load_q(const Params& p, const Ctx& c, int it, int w) {
  const int item = p.s.r[c.cl].item[it], b = p2_buf(w, it);
  mbar_expect(c.bar + (B_QF + b) * 8, 16384);
  bulk_load(c.sm + SM_BUF + b * 16384, g_S + (size_t)p.s.qblk[item] * 65536 + p2_blk(c.rank, w, it) * 16384, 16384, c.bar + (B_QF + b) * 8, POL(4));
}
__device__ __forceinline__ void wait_p1_free(const Ctx& c, int u1, int s) {
  mbar_wait(c.bar + (B_P1E + 2 * s) * 8, ((u1 - 1 - 2 * s) / 10) & 1);
  mbar_wait(c.bar + (B_P1E + 2 * s + 1) * 8, ((u1 - 2 - 2 * s) / 10) & 1);
}
__device__ __forceinline__ void p2_producer(const Params& p, const Ctx& c, int u1, int rot) {
  const int nit = p.s.r[c.cl].n2;
  int slot = rot, cnt = 0, par = 1, n = 0;
  const uint8_t* pv = nullptr;
  bool pl = false;
  auto load = [&](const uint8_t* src, int expect, uint32_t fb, bool last) {
    if (cnt < 5) {
      if (u1) {
        wait_p1_free(c, u1, slot);
        if (cnt == 0) p2_load_q(p, c, 0, 1);
      }
      cnt++;
    } else {
      if (slot == rot) par ^= 1;
      mbar_wait(c.bar + (B_P2E + slot) * 8, par);
    }
    if (expect) mbar_expect(fb, expect);
    bulk_load_mc(c.sm + SM_RING + slot * 32768 + c.rank * 16384, src, 16384, fb, last ? POL(5) : L2_NORMAL);
    slot = wrap5(slot + 1);
  };
  for (int it = 0; it < nit; it++) {
    const int item = p.s.r[c.cl].item[it], h = item >> 3, j = item & 7;
    if (it == 1 && (c.phases & 16) && p.s.r[c.cl].n1 < 8) flag_wait<true>(F_GATE, 256);
    uint32_t ready = (c.phases & 16) ? 0u : 255u;
    if (it == 0) { if (c.phases & 16) flag_wait<false>(F_Q + item, 4); mbar_wait(c.bar + B_LAD * 8, 0); p2_load_q(p, c, 0, 0); if (!u1) p2_load_q(p, c, 0, 1); }
    for (int t = 2 * j + 1; t >= 0; t--) {
      mask_wait(ready, t >> 1, F_KV + h * 8 + (c.lane & 7), 8);
      const uint8_t* k = g_S + (size_t)(2 * S_K + p.s.slot[h][t >> 1] * 16 + t) * 32768 + c.rank * 16384;
      const uint32_t fb = c.bar + (B_P2F + (n & 3)) * 8;
      const bool last = (p.s.r[c.cl].last[it] >> (t >> 1)) & 1;
      load(k, pv && t != 2 * j ? 65536 : 32768, fb, last);
      if (!(t & 1) && t + 4 <= 2 * j && c.rank == 0) flag_add_rx(F_RD + h * 8 + (t >> 1) + 2);
      if (pv) load(pv, 0, t != 2 * j ? fb : c.bar + (B_ORD + ((n - 1 - it) & 3)) * 8, pl);
      pl = last;
      pv = k + (size_t)NH * 16 * 32768;
      n++;
    }
  }
  load(pv, 32768, c.bar + (B_P2F + (n & 3)) * 8, pl);
}

__device__ __forceinline__ void publish_and_load_q(const Params& p, const Ctx& c, int f, int it, int seen) {
  const bool want = it < p.s.r[c.cl].n2, early = want && __all_sync(0xffffffffu, seen >= 4);
  if (early) { p2_load_q(p, c, it, it & 1); p2_load_q(p, c, it, (it & 1) ^ 1); }
  if (f >= 0) flag_add(f, 2);
  if (want && !early) {
    if (c.phases & 16) flag_wait<false>(F_Q + p.s.r[c.cl].item[it], 4);
    p2_load_q(p, c, it, it & 1); p2_load_q(p, c, it, (it & 1) ^ 1);
  }
}
__device__ __forceinline__ void p2_storer(const Params& p, const Ctx& c, int sfpar) {
  const int nit = p.s.r[c.cl].n2;
  int held = -1;
  for (int i = 0; i < 2 * nit; i++) {
    const int it = i >> 1, w = (it ^ i ^ 1) & 1, b = p2_buf(w, it);
    const int item = p.s.r[c.cl].item[it], h = item >> 3, j = item & 7;
    mbar_wait(c.bar + (B_SF + b) * 8, (sfpar >> b) & 1);
    sfpar ^= 1 << b;
    bulk_store(g_S + (size_t)p.s.qblk[item] * 65536 + p2_blk(c.rank, w, it) * 16384, c.sm + SM_BUF + b * 16384, 16384, POL(1));
    BULK_COMMIT();
    if (i & 1) {
      if (it + 2 == nit && (p.s.r[c.cl].item[it + 1] & 7) == 0) { held = F_CTX + j * 64 + h; continue; }
      const int seen = flag_peek(F_Q + p.s.r[c.cl].item[min(it + 2, nit - 1)]);
      BULK_WAIT(0);
      if (it + 1 == nit) release(c, B_DONE);
      publish_and_load_q(p, c, F_CTX + j * 64 + h, it + 2, seen);
    }
  }
  if (held >= 0) flag_add_rx(held, 2);
}

__device__ __forceinline__ int p3_pos(int i, int x) { return i < 4 ? (i + x) & 3 : 4; }
__device__ __forceinline__ void p3_consumer(const Params& p, const Ctx& c, int x) {
  const bool first = p.s.r[c.cl].p3 >= 24;
  const int tile = p.s.r[c.cl].p3 - (first ? 24 : 0), j = tile / 3, nt = tile - 3 * j;
  const int na = first ? 9 : 0, nb = p.s.task[c.cl][1] - p.s.task[c.cl][0];
  const uint32_t ad = desc_lo(c.sm + SM_RING + c.wg * 8192, 16), bd = desc_lo(c.sm + SM_RING + 16384, 4096);
  float acc[96] = {};
  int slot = 0, par = 0, prev = 0;
  float g0 = 0.f, g1 = 0.f;
  const int hold = c.wg && LAG ? na + nb - LAG : -1, pass = c.wg || !LAG ? -1 : na + nb - 1;
  const float* gp = g_gate + j * 256 + c.rank * 128 + c.wg * 64 + c.warp * 16 + (c.lane >> 2);
#pragma unroll 1
  for (int kb = 0; kb < na; kb++) {
    if (kb == hold) bar_sync(6, 256);
    mbar_wait(c.bar + (B_P3F + slot) * 8, par);
    if (kb == 0) PROF(c.wg, 39);
    WG_FENCE();
#pragma unroll
    for (int kk = 0; kk < 4; kk++) wgmma_ss192<1, 1>(acc, ad + p3_pos(slot, x) * 2560 + kk * 128, bd + p3_pos(slot, x) * 2560 + (kk >> 1) * 768 + (kk & 1) * 128, kk != 0 ? 1 : kb != 0);
    WG_COMMIT();
    if (kb == pass) bar_arrive(6, 256);
    WG_WAIT(1);
    if (kb > 0) release(c, B_P3E + prev);
    else { g0 = __ldcg(gp); g1 = __ldcg(gp + 8); }
    prev = slot;
    if (++slot == 5) { slot = 0; par ^= 1; }
  }
#pragma unroll 1
  for (int kb = na; kb < na + nb; kb++) {
    if (kb == hold) bar_sync(6, 256);
    mbar_wait(c.bar + (B_P3F + slot) * 8, par);
    if (kb == 0) PROF(c.wg, 39);
    WG_FENCE();
#pragma unroll
    for (int kk = 0; kk < 4; kk++) wgmma_ss192<1>(acc, ad + p3_pos(slot, x) * 2560 + kk * 2, bd + p3_pos(slot, x) * 2560 + (kk >> 1) * 768 + (kk & 1) * 128, kk != 0 ? 1 : kb != 0);
    WG_COMMIT();
    if (kb == pass) bar_arrive(6, 256);
    WG_WAIT(1);
    if (kb > 0) release(c, B_P3E + prev);
    else { g0 = __ldcg(gp); g1 = __ldcg(gp + 8); }
    prev = slot;
    if (++slot == 5) { slot = 0; par ^= 1; }
  }
  g0 = __fdividef(1.f, 1.f + g0); g1 = __fdividef(1.f, 1.f + g1);
  WG_WAIT(0);
  pin(acc);
  PROF(c.wg, 40);
  if (first) bar_sync(4 + c.wg, 128);
  mbar_wait(c.bar + B_OUT * 8, 0);
  const int row = (c.lane & 7) + ((c.lane >> 3) & 1) * 8;
  const uint32_t wbase = c.sm + SM_RING + c.wg * 8192 + c.warp * 2048;
  const uint32_t base = wbase + row * 128 + (((c.lane >> 4) ^ (row & 7)) << 4);
#pragma unroll
  for (int i = 0; i < 12; i++) {
    stsm4((base ^ ((i & 3) << 5)) + (i >> 2) * 40960, pack_bf16(acc[8 * i] * g0, acc[8 * i + 1] * g0), pack_bf16(acc[8 * i + 2] * g1, acc[8 * i + 3] * g1),
          pack_bf16(acc[8 * i + 4] * g0, acc[8 * i + 5] * g0), pack_bf16(acc[8 * i + 6] * g1, acc[8 * i + 7] * g1));
    if ((i & 3) == 3) {
      FENCE_ASYNC_SMEM();
      bar_sync(4 + c.wg, 128);
      if (c.warp == (i >> 2)) tma2d_add(&p.map_out, c.sm + SM_RING + c.wg * 8192 + c.warp * 40960, nt * 192 + c.warp * 64, j * 256 + c.rank * 128 + c.wg * 64);
    }
  }
  BULK_COMMIT();
  PROF(c.wg, 43);
  BULK_WAIT_READ(0);
  PROF(c.wg, 44);
}

__device__ __forceinline__ void p3_producer(const Params& p, const Ctx& c, int u1, int u2, int rot, int x) {
  const bool first = p.s.r[c.cl].p3 >= 24;
  const int tile = p.s.r[c.cl].p3 - (first ? 24 : 0), j = tile / 3, nt = tile - 3 * j;
  int slot = 0, par = 1, cnt = 0;
  auto wait_free = [&](int s) {
    const int f = wrap5(s + 5 - rot);
    if (f < u2) mbar_wait(c.bar + (B_P2E + s) * 8, ((u2 - 1 - f) / 5) & 1);
    else if (u1) wait_p1_free(c, u1, s);
  };
  asm volatile(ELECT("prefetch.tensormap [%0];") ::"l"(&p.map_o[0]) : "memory");
  asm volatile(ELECT("prefetch.tensormap [%0];") ::"l"(&p.map_out) : "memory");
  if ((c.phases & 16) && p.s.r[c.cl].n1 < 8 && p.s.r[c.cl].n2 < 2) flag_wait<true>(F_GATE, 256);
  uint32_t ready = (c.phases & 16) ? 0u : ~0u;
  const int q0 = p.s.task[c.cl][0], q1 = p.s.task[c.cl][1];
  for (int q = q0 - (first ? 9 : 0); q < q1; q++) {
    const bool brA = q < q0;
    const int kb = brA ? q - q0 + 9 : p.s.p3_order[tile][q];
    if (!brA) mask_wait(ready, kb >> 1, F_CTX + j * 64 + c.lane, 4);
    else if (kb == 0 && (c.phases & 16)) flag_wait<false>(F_CTX + j * 64 + 32, 16);
    const uint8_t* a = brA ? g_oA + (j * 4 + c.rank * 2) * 73728 + kb * 8192 : g_S + (size_t)p.s.qblk[(kb >> 1) * 8 + j] * 65536 + c.rank * 32768 + (kb & 1) * 8192;
    const uint32_t st = c.sm + SM_RING + p3_pos(slot, x) * 40960, fb = c.bar + (B_P3F + slot) * 8;
    if (cnt < 4) { wait_free(p3_pos(cnt, x)); wait_free(p3_pos(cnt, x) + 1); }
    else if (cnt == 4) mbar_wait(c.bar + B_DONE * 8, 0);
    else mbar_wait(c.bar + (B_P3E + slot) * 8, par);
    cnt++;
    mbar_expect(fb, 40960);
    bulk_load(st, a, 8192, fb, POL(3));
    bulk_load(st + 8192, a + (brA ? 73728 : 16384), 8192, fb, POL(3));
    tma3d_mc(st + 16384 + c.rank * 12288, &p.map_o[brA], 0, kb * 64 + c.rank * 32, nt * 3, fb);
    if (++slot == 5) { slot = 0; par ^= 1; }
  }
}

__device__ __forceinline__ float bf_lo(uint32_t w) { return __uint_as_float(w << 16); }
__device__ __forceinline__ float bf_hi(uint32_t w) { return __uint_as_float(w & 0xffff0000u); }

__device__ __forceinline__ void gate_rows(const Params& p, int row0, int lane) {
  const uint4* x = reinterpret_cast<const uint4*>(p.x + (size_t)(row0 + (lane >> 2)) * DM) + (lane & 3);
  const uint4* w = reinterpret_cast<const uint4*>(p.gate_w) + (lane & 3);
  float a = 0.f;
#pragma unroll 1
  for (int b = 0; b < 3; b++) {
    uint4 u[6];
#pragma unroll
    for (int i = 0; i < 6; i++) u[i] = __ldg(x + (b * 6 + i) * 4);
#pragma unroll
    for (int i = 0; i < 6; i++) {
      const uint4 v = __ldg(w + (b * 6 + i) * 4);
      a = fmaf(bf_lo(u[i].x), bf_lo(v.x), a); a = fmaf(bf_hi(u[i].x), bf_hi(v.x), a);
      a = fmaf(bf_lo(u[i].y), bf_lo(v.y), a); a = fmaf(bf_hi(u[i].y), bf_hi(v.y), a);
      a = fmaf(bf_lo(u[i].z), bf_lo(v.z), a); a = fmaf(bf_hi(u[i].z), bf_hi(v.z), a);
      a = fmaf(bf_lo(u[i].w), bf_lo(v.w), a); a = fmaf(bf_hi(u[i].w), bf_hi(v.w), a);
    }
  }
  a += __shfl_xor_sync(0xffffffffu, a, 1);
  a += __shfl_xor_sync(0xffffffffu, a, 2);
  if ((lane & 3) == 0) g_gate[row0 + (lane >> 2)] = __expf(fminf(a, 60.f));
}

__device__ __forceinline__ void lds10(uint32_t (&k)[10], uint32_t a) {
  asm volatile("ld.shared.v2.u32 {%0, %1}, [%10];\nld.shared.v2.u32 {%2, %3}, [%10+8];\nld.shared.v2.u32 {%4, %5}, [%10+16];\n"
               "ld.shared.v2.u32 {%6, %7}, [%10+24];\nld.shared.v2.u32 {%8, %9}, [%10+32];"
               : "=r"(k[0]), "=r"(k[1]), "=r"(k[2]), "=r"(k[3]), "=r"(k[4]), "=r"(k[5]), "=r"(k[6]), "=r"(k[7]), "=r"(k[8]), "=r"(k[9]) : "r"(a));
}
__device__ __forceinline__ void local_attn(const Params& p, const Ctx& c, int rb, int hs) {
  const int lane = c.lane, grp = rb >> 2, par = lane >> 4, i0 = 2 * (lane & 15);
  const uint32_t buf = c.sm + SM_BUF + (c.warp - 2) * 8192, bqk = c.bar + (B_LA + (c.warp - 2) * 2) * 8, bv = bqk + 8;
  const uint32_t mine = buf + 2304 + par * 160 + i0 * 4;
  const bool flags = c.phases & 16;
  auto fetch_qk = [&](int i) {
    if (flags && !(i & 1)) {
      const int q = i >> 1;
      const int tgt = q == 0 ? 24 : q == 3 ? 8 : 12;
      flag_wait<false>(F_QKVA + (grp - (grp > 0 && (rb & 3) == 0 ? par : 0)) * 4 + q, tgt);
    }
    mbar_expect(bqk, 5184);
    tma3d(buf, &p.map_t[0], rb * 32, 0, 9 * (4 * i + hs), bqk, POL(2));
    tma3d(buf + 2304, &p.map_t[1], rb * 32 - 8, 0, 288 + 9 * (4 * i + hs), bqk, POL(2));
  };
  auto fetch_v = [&](int i) { mbar_expect(bv, 2880); tma3d(buf + 5248, &p.map_t[1], rb * 32 - 8, 0, 576 + 9 * (4 * i + hs), bv, POL(2)); };
  fetch_qk(0);
  if (flags) flag_wait<true>(F_GATE, 256);
#pragma unroll 1
  for (int q = 0; q < 8; q++) {
    fetch_v(q);
    float a[8], b[8];
#pragma unroll
    for (int w = 0; w < 8; w++) a[w] = b[w] = 0.f;
    mbar_wait(bqk, q & 1);
    PROFB(1 + 2 * q);
#pragma unroll 1
    for (int j = 0; j < 9; j++) {
      uint32_t x, y, k[10];
      asm volatile("ld.shared.v2.u32 {%0, %1}, [%2];" : "=r"(x), "=r"(y) : "r"(buf + lane * 8 + j * 256));
      lds10(k, mine + j * 320);
      const float xl = bf_lo(x), xh = bf_hi(x), yl = bf_lo(y), yh = bf_hi(y);
#pragma unroll
      for (int m = 1; m < 10; m++) {
        const float kl = bf_lo(k[m]), kh = bf_hi(k[m]);
        if (m < 9) a[8 - m] = fmaf(xl, kl, fmaf(xh, kh, a[8 - m]));
        if (m > 1) b[9 - m] = fmaf(yl, kl, fmaf(yh, kh, b[9 - m]));
      }
    }
    __syncwarp();
    mbar_wait(bv, q & 1);
    if (q & 1) flag_add_rx(F_TS + (q >> 1));
    if (q < 7) fetch_qk(q + 1);
    constexpr float SC = 0.23570226039551584f * 1.4426950408889634f;
    const float* gp = g_gate + rb * 64 + 2 * i0 + par;
    const float ga = __ldcg(gp), gb = __ldcg(gp + 2);
    float ma = a[0], mb = b[0];
#pragma unroll
    for (int w = 1; w < 8; w++) {
      if (rb == 0) {
        if (i0 < w) a[w] = -INFINITY;
        if (i0 + 1 < w) b[w] = -INFINITY;
      }
      ma = fmaxf(ma, a[w]); mb = fmaxf(mb, b[w]);
    }
    float la = 0.f, lb = 0.f;
#pragma unroll
    for (int w = 0; w < 8; w++) {
      a[w] = ex2((a[w] - ma) * SC); b[w] = ex2((b[w] - mb) * SC);
      la += a[w]; lb += b[w];
    }
    la = __fdividef(ga, la); lb = __fdividef(gb, lb);
#pragma unroll
    for (int w = 0; w < 8; w++) { a[w] *= la; b[w] *= lb; }
    uint8_t* dst = g_oA + rb * 73728 + ((i0 & 2) + par) * 4;
#pragma unroll 1
    for (int j = 0; j < 9; j++) {
      uint32_t v[10];
      lds10(v, mine + 2944 + j * 320);
      float a0 = 0.f, a1 = 0.f, b0 = 0.f, b1 = 0.f;
#pragma unroll
      for (int m = 1; m < 10; m++) {
        const float vl = bf_lo(v[m]), vh = bf_hi(v[m]);
        if (m < 9) { a0 = fmaf(a[8 - m], vl, a0); a1 = fmaf(a[8 - m], vh, a1); }
        if (m > 1) { b0 = fmaf(b[9 - m], vl, b0); b1 = fmaf(b[9 - m], vh, b1); }
      }
      const uint32_t wa = pack_bf16(a0, a1), wb = pack_bf16(b0, b1);
      const uint32_t got = __shfl_xor_sync(0xffffffffu, par ? wa : wb, 16);
      const uint32_t r0 = par ? got : wa, r1 = par ? wb : got;
      const int col = 18 * (4 * q + hs) + 2 * j, o = col * 128 + ((((i0 >> 2) ^ col) & 7) << 4);
      *reinterpret_cast<uint32_t*>(dst + o) = __byte_perm(r0, r1, 0x5410);
      *reinterpret_cast<uint32_t*>(dst + ((o + 128) ^ 16)) = __byte_perm(r0, r1, 0x7632);
    }
    __syncwarp();
    PROFB(2 + 2 * q);
  }
  mbar_arrive_one(c.bar + B_LAD * 8);
  flag_add(F_CTX + grp * 64 + 32);
}

__global__ void __cluster_dims__(2, 1, 1) __launch_bounds__(384, 1) fused_kernel(const __grid_constant__ Params p) {
  extern __shared__ uint8_t smem_raw[];
  Ctx c;
  c.sm = ((uint32_t)__cvta_generic_to_shared(smem_raw) + 1023u) & ~1023u;
  c.bar = c.sm + SM_BAR;
  c.lane = threadIdx.x & 31;
  const int wid = __shfl_sync(0xffffffffu, threadIdx.x >> 5, 0);
  if (wid < 6) asm volatile("prefetch.tensormap [%0];" ::"l"(&p.map_a[0] + wid) : "memory");
  c.wg = wid >> 2;
  c.warp = wid & 3;
  PROF(c.wg, 0);
  PROFG(61);
  c.cl = (blockIdx.x + (wid >> 4)) >> 1;
  c.rank = blockIdx.x & 1;
  c.rbar = mapa(c.bar, c.lane & 1);
  {
    const int w = wid, cnt = (((int)(B_CNT >> (4 * w)) - 1) & 15) + 1;
    if (w < 11) {
#pragma unroll
      for (int i = 0; i < 8; i++) asm volatile("mbarrier.init.shared::cta.b64 [%0], %1;" ::"r"(c.bar + w * 64 + i * 8), "r"(cnt));
    }
    asm volatile("fence.mbarrier_init.release.cluster;" ::: "memory");
  }
  if (c.wg == 2) PROF(2, 56);
  asm volatile("barrier.cluster.arrive.relaxed;" ::: "memory");
  c.phases = p.s.r[c.cl].phases;
  const bool do1 = p.s.r[c.cl].n1 > 0, do2 = p.s.r[c.cl].n2 > 0, do3 = p.s.r[c.cl].p3 != 255;
  if (do1 && c.wg == 2 && c.warp == 0) {
    const int type = p.s.r[c.cl].slab >> 3;
    PROF(2, 57);
    FENCE_ASYNC_SMEM();
    mbar_expect(c.bar + B_P1F * 8, type ? 32768 : 16384);
    tma2d(type ? c.sm + SM_BUF + 32768 : c.sm + SM_RING, &p.map_a[type], type ? 512 : 0, (p.s.r[c.cl].slab & 7) * 256 + c.rank * 128, c.bar + B_P1F * 8);
    PROF(2, 58);
  }
  asm volatile("barrier.cluster.wait.acquire;" ::: "memory");
  if (c.wg == 2) PROF(2, 59);
  if (do1 && c.wg == 2 && c.warp == 0) {
    const int type = p.s.r[c.cl].slab >> 3, tile = p.s.r[c.cl].tile[0] & 63;
    const CUtensorMap* m = &p.map_w[type * 2 + (tile >> 5)];
#pragma unroll 1
    for (int s = 1 - type; s < NPRO; s++) {
      const int kb = (s - type) >> 1;
      const uint32_t fb = c.bar + (B_P1F + s) * 8;
      if (s) mbar_expect(fb, 16384);
      if ((s ^ type) & 1) tma2d_mc(c.sm + SM_RING + s * 16384 + c.rank * 8192, m, (tile & 31) * 128 + c.rank * 64, kb < 0 ? 512 : kb * 64, fb);
      else tma2d(c.sm + SM_RING + s * 16384, &p.map_a[type], kb * 64, (p.s.r[c.cl].slab & 7) * 256 + c.rank * 128, fb);
    }
  }

  if (c.wg < 2) {
    PROF(c.wg, 4);
    asm volatile("setmaxnreg.inc.sync.aligned.u32 224;");
    if (c.wg == 1) {
      if (do1) bar_arrive(ORDER, 256);
      if (c.lane == 0) mbar_arrive(c.bar + B_P2F * 8);
    }
    PL(0);
    if (do1) p1_consumer(p, c);
    PL(1);
    if (do2) p2_consumer(p, c, p.s.r[c.cl].rot);
    PL(2);
    if (do3) p3_consumer(p, c, p.s.r[c.cl].x3);
    PL(3);
    PROF(c.wg, 63);
    PROFG(62);
    if (c.lane == 0) mbar_arrive(c.bar + B_FIN * 8);
    __syncwarp();
    cluster_sync();
  } else {
    asm volatile("setmaxnreg.dec.sync.aligned.u32 56;");
    if (c.warp == 0) {
      PROF(2, 60);
      if (do1) p1_producer(p, c);
      if (do2) p2_producer(p, c, p.s.r[c.cl].u1, p.s.r[c.cl].rot);
      if (do3) p3_producer(p, c, p.s.r[c.cl].u1, p.s.r[c.cl].u2, p.s.r[c.cl].rot, p.s.r[c.cl].x3);
    } else if (c.warp == 1) {
      const int f = do1 ? p1_storer(p, c) : -1;
      if (do2) {
        publish_and_load_q(p, c, f, 1, flag_peek(F_Q + p.s.r[c.cl].item[1]));
        p2_storer(p, c, (p.s.r[c.cl].n1 & 1) * 10);
      } else {
        const bool idle = mbar_test(c.bar + B_LAD * 8, 0);
        if (idle) release(c, B_DONE);
        if (f >= 0) flag_add(f, 2);
        if (!idle) { mbar_wait(c.bar + B_LAD * 8, 0); release(c, B_DONE); }
      }
      if (do3) {
        const int tile = p.s.r[c.cl].p3 % 24;
        if (p.s.task[c.cl][1] == 64) {
          for (int r = 0; r < (64 - p.s.task[c.cl][0] - ZLEAD) / 5; r++) mbar_wait(c.bar + B_P3F * 8, r & 1);
          const int j = tile / 3, nt = tile - 3 * j;
          uint4* o = reinterpret_cast<uint4*>(p.out + (size_t)(j * 256 + c.rank * 128 + (c.lane >> 3)) * DM + nt * 192) + (c.lane & 7);
#pragma unroll 4
          for (int r = 0; r < 32; r++) o[r * 288] = o[r * 288 + 8] = o[r * 288 + 16] = make_uint4(0u, 0u, 0u, 0u);
          __syncwarp();
          flag_add(F_OUT + tile * 2 + c.rank);
        } else if (c.phases & 16) {
          flag_wait<false, 256>(F_OUT + tile * 2 + c.rank, 1);
        }
        mbar_arrive_one(c.bar + B_OUT * 8);
      }
    } else {
      const int bw = blockIdx.x * 2 + (c.warp - 2);
      if ((c.phases & 1) && bw < 256) {
        gate_rows(p, bw * 8, c.lane);
        __syncwarp();
        flag_add(F_GATE);
      }
      if (p.s.r[c.cl].bg != 255) local_attn(p, c, p.s.r[c.cl].bg, bw & 3);
      else if (c.lane == 0) mbar_arrive(c.bar + B_LAD * 8);
    }
    __syncwarp();
    bar_sync(3, 128);
    if (c.warp == 0 && (c.phases & 32)) {
      int last = 0;
      if (c.lane == 0) { __threadfence(); last = atomicAdd(g_flags + F_DONE, 1) == 2 * NCL - 1; }
      if (__shfl_sync(0xffffffffu, last, 0)) for (int i = c.lane; i < F_NUM; i += 32) g_flags[i] = 0;
    }
    if (c.warp == 1) mbar_wait(c.bar + B_FIN * 8, 0);
    __syncwarp();
    cluster_sync();
  }
}

SCHED_DECL Sched k_sched = {
  {{0,29,1,34,0,{243,0,0,0,0,0,0,0,0,0,0},{15,0,0,0,0,0,0,0,0,0,0},{68,105,128,38,11,37,46,39,42,52,35,59,58,54,53,49,45,48,44,56,51,60,55,47,62,61,63,50,57,0}},
   {1,29,2,28,1,{248,242,0,0,0,0,0,0,0,0,0},{0,0,0,0,0,0,0,0,0,0,0},{68,40,128,38,11,37,46,39,42,52,35,59,58,54,53,49,45,48,44,56,51,60,55,47,62,61,63,50,57,0}},
   {2,29,1,40,2,{252,0,0,0,0,0,0,0,0,0,0},{31,0,0,0,0,0,0,0,0,0,0},{129,105,128,38,11,37,46,39,42,52,35,59,58,54,53,49,45,48,44,56,51,60,55,47,62,61,63,50,57,0}},
   {3,29,1,35,3,{235,0,0,0,0,0,0,0,0,0,0},{0,0,0,0,0,0,0,0,0,0,0},{129,40,9,38,11,37,46,39,42,52,35,59,58,54,53,49,45,48,44,56,51,60,47,62,55,61,63,50,57,0}},
   {4,28,0,6,4,{0,0,0,0,0,0,0,0,0,0,0},{0,0,0,0,0,0,0,0,0,0,0},{129,40,128,41,2,43,14,39,20,3,27,26,22,21,17,13,16,12,24,19,28,30,15,23,29,31,18,25,0,0}},
   {5,27,0,16,5,{0,0,0,0,0,0,0,0,0,0,0},{0,0,0,0,0,0,0,0,0,0,0},{68,40,9,32,2,43,14,39,20,35,26,22,21,17,13,16,12,24,19,28,30,15,23,29,31,18,25,0,0,0}},
   {6,26,0,13,6,{0,0,0,0,0,0,0,0,0,0,0},{0,0,0,0,0,0,0,0,0,0,0},{97,40,128,38,11,37,7,42,3,59,22,21,17,13,12,16,24,19,28,30,15,23,29,31,18,25,0,0,0,0}},
   {7,25,0,11,7,{0,0,0,0,0,0,0,0,0,0,0},{0,0,0,0,0,0,0,0,0,0,0},{129,73,128,66,69,71,84,99,90,86,85,81,77,76,80,88,83,92,94,79,87,93,95,82,89,0,0,0,0,0}},
   {0,29,1,10,8,{187,0,0,0,0,0,0,0,0,0,0},{0,0,0,0,0,0,0,0,0,0,0},{129,36,8,32,2,43,14,7,10,20,3,27,26,22,21,17,13,16,12,24,19,28,23,15,30,29,31,18,25,0}},
   {1,29,2,27,9,{232,147,0,0,0,0,0,0,0,0,0},{0,0,0,0,0,0,0,0,0,0,0},{129,36,9,32,2,43,14,7,10,20,3,27,26,22,21,17,13,16,12,24,19,28,23,15,30,29,31,18,25,0}},
   {2,29,2,1,10,{240,204,0,0,0,0,0,0,0,0,0},{0,0,0,0,0,0,0,0,0,0,0},{68,33,8,32,2,43,14,7,10,20,3,27,26,22,21,17,13,16,12,24,19,28,23,15,30,29,31,18,25,0}},
   {3,29,2,14,11,{233,146,0,0,0,0,0,0,0,0,0},{0,0,0,0,0,0,0,0,0,0,0},{68,33,128,41,2,43,14,7,10,20,3,27,26,22,21,17,13,16,12,24,19,28,15,30,23,29,31,18,25,0}},
   {4,28,0,10,12,{0,0,0,0,0,0,0,0,0,0,0},{0,0,0,0,0,0,0,0,0,0,0},{97,4,96,6,34,5,46,10,52,35,59,58,54,53,49,45,48,44,56,51,60,62,47,55,61,63,50,57,0,0}},
   {5,27,0,4,13,{0,0,0,0,0,0,0,0,0,0,0},{0,0,0,0,0,0,0,0,0,0,0},{100,1,41,6,34,5,46,10,52,27,58,54,53,49,45,48,44,56,51,60,62,47,55,61,63,50,57,0,0,0}},
   {6,26,0,12,14,{0,0,0,0,0,0,0,0,0,0,0},{0,0,0,0,0,0,0,0,0,0,0},{68,73,96,66,43,14,39,20,35,26,54,53,49,45,44,48,56,51,60,62,47,55,61,63,50,57,0,0,0,0}},
   {7,25,0,7,15,{0,0,0,0,0,0,0,0,0,0,0},{0,0,0,0,0,0,0,0,0,0,0},{97,105,96,98,101,103,116,91,122,118,117,113,109,108,112,120,115,124,126,111,119,125,127,114,121,0,0,0,0,0}},
   {0,6,7,39,255,{73,95,215,154,227,234,200,0,0,0,0},{0,0,0,0,0,0,0,0,0,0,0},{97,73,40,6,34,5,0,0,0,0,0,0,0,0,0,0,0,0,0,0,0,0,0,0,0,0,0,0,0,0}},
   {1,6,7,37,255,{0,1,52,85,174,226,205,0,0,0,0},{0,0,0,0,7,0,0,0,0,0,0},{97,8,41,6,34,5,0,0,0,0,0,0,0,0,0,0,0,0,0,0,0,0,0,0,0,0,0,0,0,0}},
   {2,6,5,5,255,{5,167,180,130,254,0,0,0,0,0,0},{0,0,0,0,0,0,0,0,0,0,0},{100,73,40,6,34,5,0,0,0,0,0,0,0,0,0,0,0,0,0,0,0,0,0,0,0,0,0,0,0,0}},
   {3,6,7,25,255,{48,53,61,26,139,129,125,0,0,0,0},{0,0,0,0,0,0,0,0,0,0,0},{100,8,96,6,34,5,0,0,0,0,0,0,0,0,0,0,0,0,0,0,0,0,0,0,0,0,0,0,0,0}},
   {4,8,6,33,255,{88,46,82,173,155,253,0,0,0,0,0},{0,0,0,0,0,32,0,0,0,0,0},{72,36,9,38,11,37,7,42,0,0,0,0,0,0,0,0,0,0,0,0,0,0,0,0,0,0,0,0,0,0}},
   {5,10,6,20,255,{20,57,161,27,99,184,0,0,0,0,0},{0,0,0,0,0,0,0,0,0,0,0},{72,33,128,38,11,37,7,42,3,59,0,0,0,0,0,0,0,0,0,0,0,0,0,0,0,0,0,0,0,0}},
   {6,10,6,43,255,{40,50,41,221,140,246,0,0,0,0,0},{0,0,0,0,27,96,0,0,0,0,0},{100,105,70,98,69,46,10,52,27,58,0,0,0,0,0,0,0,0,0,0,0,0,0,0,0,0,0,0,0,0}},
   {7,8,4,9,255,{16,94,83,135,0,0,0,0,0,0,0},{0,0,0,0,0,0,0,0,0,0,0},{72,4,70,75,78,74,67,123,0,0,0,0,0,0,0,0,0,0,0,0,0,0,0,0,0,0,0,0,0,0}},
   {8,18,2,8,16,{134,150,0,0,0,0,0,0,0,0,0},{127,64,0,0,0,0,0,0,0,0,0},{129,161,66,38,35,44,109,14,10,86,27,21,17,92,12,15,29,146,0,0,0,0,0,0,0,0,0,0,0,0}},
   {9,19,3,24,17,{216,106,191,0,0,0,0,0,0,0,0},{0,0,128,0,0,0,0,0,0,0,0},{132,161,34,2,39,11,14,40,10,3,22,17,13,12,28,23,30,31,25,0,0,0,0,0,0,0,0,0,0,0}},
   {10,18,4,2,18,{217,131,225,120,0,0,0,0,0,0,0},{0,0,0,0,0,0,0,0,0,0,0},{132,41,102,11,108,5,40,7,20,3,22,21,76,83,28,15,30,146,0,0,0,0,0,0,0,0,0,0,0,0}},
   {11,18,1,17,19,{109,0,0,0,0,0,0,0,0,0,0},{0,0,0,0,0,0,0,0,0,0,0},{136,165,102,11,39,5,40,7,20,27,22,13,16,24,28,23,29,146,0,0,0,0,0,0,0,0,0,0,0,0}},
   {12,18,4,13,20,{24,132,228,202,0,0,0,0,0,0,0},{0,0,31,0,0,0,0,0,0,0,0},{105,9,134,69,39,14,40,10,3,26,85,13,76,83,79,30,95,89,0,0,0,0,0,0,0,0,0,0,0,0}},
   {13,19,3,4,21,{138,193,151,0,0,0,0,0,0,0,0},{0,0,128,0,0,0,0,0,0,0,0},{100,9,107,11,78,39,7,20,45,27,22,17,16,24,28,30,29,146,25,0,0,0,0,0,0,0,0,0,0,0}},
   {14,18,2,0,22,{102,152,0,0,0,0,0,0,0,0,0},{2,0,0,0,0,0,0,0,0,0,0},{160,170,102,69,71,35,44,40,3,26,85,13,76,83,79,23,95,89,0,0,0,0,0,0,0,0,0,0,0,0}},
   {15,18,3,17,23,{80,108,255,0,0,0,0,0,0,0,0},{0,0,192,0,0,0,0,0,0,0,0},{73,41,66,43,78,74,35,44,40,27,22,17,76,24,28,15,29,146,0,0,0,0,0,0,0,0,0,0,0,0}},
   {8,18,2,8,24,{172,192,0,0,0,0,0,0,0,0,0},{0,0,0,0,0,0,0,0,0,0,0},{136,165,75,43,39,104,7,20,90,3,77,80,88,87,19,30,95,89,0,0,0,0,0,0,0,0,0,0,0,0}},
   {9,18,4,12,25,{112,169,231,203,0,0,0,0,0,0,0},{1,0,128,0,0,0,0,0,0,0,0},{136,165,102,99,108,5,7,45,20,27,85,26,88,16,19,15,29,146,0,0,0,0,0,0,0,0,0,0,0,0}},
   {10,18,3,38,26,{56,198,124,0,0,0,0,0,0,0,0},{1,0,0,0,0,0,0,0,0,0,0},{129,161,107,99,2,14,109,10,91,26,81,13,88,16,23,93,95,89,0,0,0,0,0,0,0,0,0,0,0,0}},
   {11,18,3,18,27,{176,107,128,0,0,0,0,0,0,0,0},{0,0,0,0,0,0,0,0,0,0,0},{160,170,107,99,108,14,109,10,3,26,81,21,76,83,79,30,95,89,0,0,0,0,0,0,0,0,0,0,0,0}},
   {12,18,4,47,28,{210,194,185,237,0,0,0,0,0,0,0},{0,0,0,32,0,0,0,0,0,0,0},{100,0,107,11,35,44,7,45,20,27,22,17,16,24,28,23,29,146,0,0,0,0,0,0,0,0,0,0,0,0}},
   {13,18,4,26,29,{177,170,229,145,0,0,0,0,0,0,0},{0,0,32,0,0,0,0,0,0,0,0},{160,170,102,2,5,35,44,10,40,3,26,21,13,12,19,15,23,31,0,0,0,0,0,0,0,0,0,0,0,0}},
   {14,18,3,16,30,{160,158,188,0,0,0,0,0,0,0,0},{1,0,0,0,0,0,0,0,0,0,0},{136,161,66,11,78,74,39,20,45,27,22,17,16,24,28,30,29,146,0,0,0,0,0,0,0,0,0,0,0,0}},
   {15,18,5,42,31,{208,137,156,241,251,0,0,0,0,0,0},{0,0,0,0,0,0,0,0,0,0,0},{132,161,75,69,71,84,39,67,45,26,85,13,16,83,94,23,95,89,0,0,0,0,0,0,0,0,0,0,0,0}},
   {8,3,3,19,255,{39,117,183,0,0,0,0,0,0,0,0},{0,0,120,0,0,0,0,0,0,0,0},{73,41,134,0,0,0,0,0,0,0,0,0,0,0,0,0,0,0,0,0,0,0,0,0,0,0,0,0,0,0}},
   {9,3,5,3,255,{12,47,28,178,168,0,0,0,0,0,0},{0,0,0,0,0,0,0,0,0,0,0},{129,41,0,0,0,0,0,0,0,0,0,0,0,0,0,0,0,0,0,0,0,0,0,0,0,0,0,0,0,0}},
   {10,3,6,36,255,{38,17,89,115,175,239,0,0,0,0,0},{0,0,0,0,128,192,0,0,0,0,0},{160,170,0,0,0,0,0,0,0,0,0,0,0,0,0,0,0,0,0,0,0,0,0,0,0,0,0,0,0,0}},
   {11,3,5,2,255,{79,86,220,195,189,0,0,0,0,0,0},{0,0,0,0,63,0,0,0,0,0,0},{100,9,134,0,0,0,0,0,0,0,0,0,0,0,0,0,0,0,0,0,0,0,0,0,0,0,0,0,0,0}},
   {12,3,5,9,255,{70,49,31,141,126,0,0,0,0,0,0},{0,0,0,32,127,0,0,0,0,0,0},{160,170,102,0,0,0,0,0,0,0,0,0,0,0,0,0,0,0,0,0,0,0,0,0,0,0,0,0,0,0}},
   {13,3,7,29,255,{33,76,2,116,218,159,149,0,0,0,0},{0,0,0,0,0,0,32,0,0,0,0},{136,161,134,0,0,0,0,0,0,0,0,0,0,0,0,0,0,0,0,0,0,0,0,0,0,0,0,0,0,0}},
   {14,3,7,18,255,{37,93,81,162,211,157,148,0,0,0,0},{0,0,0,0,0,7,31,0,0,0,0},{73,165,34,0,0,0,0,0,0,0,0,0,0,0,0,0,0,0,0,0,0,0,0,0,0,0,0,0,0,0}},
   {15,4,7,5,255,{8,55,42,163,25,171,136,0,0,0,0},{0,0,0,0,0,0,0,0,0,0,0},{136,36,134,38,0,0,0,0,0,0,0,0,0,0,0,0,0,0,0,0,0,0,0,0,0,0,0,0,0,0}},
   {8,3,8,0,255,{11,3,19,58,182,97,121,244,0,0,0},{0,0,0,0,0,0,0,16,0,0,0},{132,36,0,0,0,0,0,0,0,0,0,0,0,0,0,0,0,0,0,0,0,0,0,0,0,0,0,0,0,0}},
   {9,3,6,30,255,{74,54,114,164,179,127,0,0,0,0,0},{0,0,0,0,0,128,0,0,0,0,0},{160,170,107,0,0,0,0,0,0,0,0,0,0,0,0,0,0,0,0,0,0,0,0,0,0,0,0,0,0,0}},
   {10,4,6,21,255,{64,4,51,166,133,207,0,0,0,0,0},{0,0,0,0,0,255,0,0,0,0,0},{100,98,134,103,0,0,0,0,0,0,0,0,0,0,0,0,0,0,0,0,0,0,0,0,0,0,0,0,0,0}},
   {11,3,4,22,255,{35,22,165,199,0,0,0,0,0,0,0},{0,0,0,3,0,0,0,0,0,0,0},{129,161,34,0,0,0,0,0,0,0,0,0,0,0,0,0,0,0,0,0,0,0,0,0,0,0,0,0,0,0}},
   {12,4,4,1,255,{68,21,84,110,0,0,0,0,0,0,0},{0,0,0,4,0,0,0,0,0,0,0},{129,161,4,2,0,0,0,0,0,0,0,0,0,0,0,0,0,0,0,0,0,0,0,0,0,0,0,0,0,0}},
   {13,3,8,22,255,{34,36,90,60,219,105,247,144,0,0,0},{0,0,0,0,0,0,128,0,0,0,0},{129,165,34,0,0,0,0,0,0,0,0,0,0,0,0,0,0,0,0,0,0,0,0,0,0,0,0,0,0,0}},
   {14,3,7,6,255,{32,78,118,143,153,123,201,0,0,0,0},{0,0,0,192,0,0,0,0,0,0,0},{132,41,134,0,0,0,0,0,0,0,0,0,0,0,0,0,0,0,0,0,0,0,0,0,0,0,0,0,0,0}},
   {15,3,5,14,255,{15,91,29,101,96,0,0,0,0,0,0},{0,0,0,0,1,0,0,0,0,0,0},{129,32,42,0,0,0,0,0,0,0,0,0,0,0,0,0,0,0,0,0,0,0,0,0,0,0,0,0,0,0}},
   {8,4,5,46,255,{69,119,181,230,249,0,0,0,0,0,0},{0,0,0,64,0,0,0,0,0,0,0},{160,170,34,69,0,0,0,0,0,0,0,0,0,0,0,0,0,0,0,0,0,0,0,0,0,0,0,0,0,0}},
   {9,3,6,41,255,{10,75,92,59,103,238,0,0,0,0,0},{0,0,0,0,128,64,0,0,0,0,0},{100,9,134,0,0,0,0,0,0,0,0,0,0,0,0,0,0,0,0,0,0,0,0,0,0,0,0,0,0,0}},
   {10,3,5,32,255,{71,62,111,186,236,0,0,0,0,0,0},{0,0,0,0,31,0,0,0,0,0,0},{73,165,8,0,0,0,0,0,0,0,0,0,0,0,0,0,0,0,0,0,0,0,0,0,0,0,0,0,0,0}},
   {11,4,5,15,255,{67,66,63,212,104,0,0,0,0,0,0},{0,0,0,0,0,0,0,0,0,0,0},{132,41,0,2,0,0,0,0,0,0,0,0,0,0,0,0,0,0,0,0,0,0,0,0,0,0,0,0,0,0}},
   {12,3,6,44,255,{72,13,45,213,100,245,0,0,0,0,0},{0,0,0,0,0,0,0,0,0,0,0},{136,165,34,0,0,0,0,0,0,0,0,0,0,0,0,0,0,0,0,0,0,0,0,0,0,0,0,0,0,0}},
   {13,3,6,20,255,{65,6,18,30,197,206,0,0,0,0,0},{0,0,0,0,0,0,0,0,0,0,0},{132,41,0,0,0,0,0,0,0,0,0,0,0,0,0,0,0,0,0,0,0,0,0,0,0,0,0,0,0,0}},
   {14,4,6,31,255,{7,43,214,196,122,250,0,0,0,0,0},{0,0,0,0,0,0,0,0,0,0,0},{129,36,0,43,0,0,0,0,0,0,0,0,0,0,0,0,0,0,0,0,0,0,0,0,0,0,0,0,0,0}},
   {15,3,5,45,255,{14,44,223,98,190,0,0,0,0,0,0},{0,0,0,0,127,0,0,0,0,0,0},{64,165,34,0,0,0,0,0,0,0,0,0,0,0,0,0,0,0,0,0,0,0,0,0,0,0,0,0,0,0}},
   {6,2,5,21,255,{9,77,87,142,224,0,0,0,0,0,0},{0,0,0,0,0,0,0,0,0,0,0},{129,8,0,0,0,0,0,0,0,0,0,0,0,0,0,0,0,0,0,0,0,0,0,0,0,0,0,0,0,0}},
   {7,6,4,23,255,{23,113,222,209,0,0,0,0,0,0,0},{0,0,0,0,0,0,0,0,0,0,0},{104,36,102,107,110,106,0,0,0,0,0,0,0,0,0,0,0,0,0,0,0,0,0,0,0,0,0,0,0,0}}},
  {{0,6,0,0},{0,7,0,0},{0,1,0,0},{0,6,0,0},{22,64,0,0},{17,64,0,0},{11,64,0,0},{6,64,0,0},{6,22,0,0},{0,4,0,0},{8,16,0,0},
   {8,20,0,0},{22,64,0,0},{17,64,0,0},{11,64,0,0},{6,64,0,0},{0,4,0,0},{0,0,0,0},{0,12,0,0},{0,8,0,0},{0,2,0,0},{16,64,0,0},
   {0,7,0,0},{18,64,0,0},{2,12,0,0},{0,7,0,0},{24,64,0,0},{14,64,0,0},{0,11,0,0},{7,17,0,0},{23,64,0,0},{3,14,0,0},{12,64,0,0},
   {3,11,0,0},{0,8,0,0},{12,64,0,0},{0,3,0,0},{0,8,0,0},{1,17,0,0},{0,4,0,0},{7,64,0,0},{4,64,0,0},{0,3,0,0},{8,24,0,0},
   {2,18,0,0},{0,0,0,0},{4,12,0,0},{12,64,0,0},{7,23,0,0},{0,8,0,0},{7,15,0,0},{23,64,0,0},{16,64,0,0},{8,23,0,0},{8,22,0,0},
   {20,64,0,0},{0,8,0,0},{0,3,0,0},{0,2,0,0},{4,64,0,0},{0,8,0,0},{8,16,0,0},{0,6,0,0},{0,7,0,0},{15,64,0,0},{3,64,0,0}},
  {{57,24,39,60,59,36,50,52,44,6,55,27,43,33,35,49,46,25,30,61,62,37,51,8,9,18,19,2,3,16,17,0,1,12,13,4,5,22,23,10,11,14,15,28,29,20,21,40,41,53,45,7,54,26,42,32,34,48,56,47,38,31,58,63},
   {35,57,24,39,60,59,36,50,49,46,25,30,61,62,37,51,8,9,18,19,2,3,16,17,0,1,12,13,4,5,22,23,10,11,14,15,28,29,20,21,40,41,52,53,44,45,6,7,54,55,26,27,42,43,32,33,34,48,56,47,38,31,58,63},
   {35,56,47,38,31,58,63,50,40,52,44,7,55,27,43,33,48,57,24,39,60,59,36,51,8,9,18,19,2,3,16,17,0,1,12,13,4,5,22,23,10,11,14,15,28,29,20,21,41,53,45,6,54,26,42,32,34,49,46,25,30,61,62,37},
   {59,63,37,51,2,3,16,17,8,9,18,19,0,1,12,13,4,5,22,23,10,11,28,29,14,15,20,21,40,41,6,7,54,55,44,45,42,43,34,35,52,53,26,27,48,49,24,25,32,33,56,57,38,39,46,47,30,31,60,61,58,62,36,50},
   {33,38,47,60,59,36,50,26,49,25,56,39,30,61,62,37,51,2,3,16,17,8,9,18,19,0,1,12,13,4,5,22,23,10,11,28,29,14,15,20,21,40,41,6,7,54,55,44,45,42,43,34,35,52,53,27,48,24,32,57,46,31,58,63},
   {49,25,33,38,46,30,60,58,62,36,50,51,2,3,16,17,8,9,18,19,0,1,12,13,4,5,22,23,10,11,28,29,14,15,20,21,40,41,6,7,54,55,44,45,42,43,34,35,52,53,26,27,48,24,32,56,57,39,47,31,61,59,63,37},
   {25,38,33,46,31,62,36,50,7,53,45,35,43,27,48,39,56,47,60,63,37,51,8,9,2,3,18,19,16,17,0,1,12,13,22,23,4,5,10,11,28,29,14,15,20,21,40,41,54,55,6,52,44,34,42,26,24,49,32,57,30,61,58,59},
   {60,62,58,36,50,51,8,9,2,3,18,19,16,17,0,1,12,13,22,23,4,5,10,11,28,29,14,15,20,21,40,41,54,55,6,7,52,53,44,45,34,35,42,43,26,27,24,25,48,49,38,39,32,33,56,57,46,47,30,31,61,63,59,37},
   {59,50,49,39,33,57,47,60,62,58,37,51,8,9,2,3,18,19,16,17,0,1,12,13,22,23,4,5,10,11,28,29,14,15,20,21,40,41,54,55,6,7,52,53,44,45,34,35,42,43,26,27,24,25,48,38,32,56,46,30,31,61,63,36},
   {37,51,52,44,35,27,43,33,25,49,39,57,31,47,59,61,63,50,2,3,8,9,16,17,18,19,0,1,12,13,4,5,22,23,10,11,28,29,14,15,20,21,40,41,6,7,54,55,53,45,34,26,42,32,24,48,38,56,30,46,58,60,62,36},
   {39,30,47,60,63,50,7,55,53,45,35,27,43,33,25,49,56,31,58,62,37,51,2,3,8,9,16,17,18,19,0,1,12,13,4,5,22,23,10,11,28,29,14,15,20,21,40,41,6,54,52,44,34,26,42,32,24,48,38,57,46,59,61,36},
   {58,60,62,36,50,51,2,3,8,9,16,17,18,19,0,1,12,13,4,5,22,23,10,11,28,29,14,15,20,21,40,41,6,7,54,55,52,53,44,45,34,35,26,27,42,43,32,33,24,25,48,49,38,39,56,57,30,31,46,47,59,61,63,37},
   {58,63,50,38,56,30,46,60,62,37,51,2,3,16,17,0,1,18,19,8,9,12,13,4,5,22,23,10,11,28,29,14,15,20,21,40,41,6,7,54,55,52,53,44,45,42,43,34,35,26,27,32,33,24,25,48,49,39,57,31,47,61,59,36},
   {25,49,39,57,31,47,61,59,63,37,51,2,3,16,17,0,1,18,19,8,9,12,13,4,5,22,23,10,11,28,29,14,15,20,21,40,41,6,7,54,55,52,53,44,45,42,43,34,35,26,27,32,33,24,48,38,56,30,46,60,58,62,36,50},
   {33,48,39,30,47,59,36,50,45,43,35,27,24,49,56,31,61,62,37,51,2,3,16,17,0,1,18,19,8,9,12,13,4,5,22,23,10,11,28,29,14,15,20,21,40,41,6,7,54,55,52,53,44,42,34,26,32,25,38,57,46,60,58,63},
   {62,36,50,51,8,9,16,17,2,3,18,19,0,1,12,13,4,5,22,23,10,11,28,29,14,15,20,21,40,41,6,7,54,55,52,53,44,45,42,43,26,27,34,35,32,33,24,25,48,49,38,39,56,57,30,31,60,61,46,47,58,59,63,37},
   {50,44,42,26,34,32,24,49,39,57,31,61,47,59,63,37,51,8,9,16,17,2,3,18,19,0,1,12,13,4,5,22,23,10,11,28,29,14,15,20,21,40,41,6,7,54,55,52,53,45,43,27,35,33,25,48,38,56,30,60,46,58,62,36},
   {59,36,50,32,24,48,39,57,31,61,47,62,37,51,8,9,16,17,2,3,18,19,0,1,12,13,4,5,22,23,10,11,28,29,14,15,20,21,40,41,6,7,54,55,52,53,44,45,42,43,26,27,34,35,33,25,49,38,56,30,60,46,58,63},
   {47,62,37,51,49,39,57,31,61,58,36,50,16,17,2,3,8,9,18,19,0,1,12,13,4,5,22,23,10,11,28,29,14,15,20,21,40,41,6,7,54,55,52,53,44,45,42,43,34,35,26,27,32,33,24,25,48,38,56,30,60,46,59,63},
   {31,61,47,59,63,37,51,16,17,2,3,8,9,18,19,0,1,12,13,4,5,22,23,10,11,28,29,14,15,20,21,40,41,6,7,54,55,52,53,44,45,42,43,34,35,26,27,32,33,24,25,48,49,38,39,56,57,30,60,46,58,62,36,50},
   {25,38,57,60,47,62,37,51,33,48,39,30,61,58,63,50,16,17,2,3,8,9,18,19,0,1,12,13,4,5,22,23,10,11,28,29,14,15,20,21,40,41,6,7,54,55,52,53,44,45,42,43,34,35,26,27,32,24,49,56,31,46,59,36},
   {48,39,30,47,59,36,50,24,49,57,46,61,62,37,51,2,3,8,9,16,17,18,19,0,1,12,13,4,5,22,23,10,11,28,29,14,15,20,21,40,41,6,7,54,55,52,53,44,45,42,43,34,35,26,27,32,33,25,38,56,31,60,58,63},
   {33,48,56,31,60,59,36,50,7,55,53,45,43,26,32,25,38,57,46,61,62,37,51,2,3,8,9,16,17,18,19,0,1,12,13,4,5,22,23,10,11,28,29,14,15,20,21,40,41,6,54,52,44,42,34,35,27,24,49,39,30,47,58,63},
   {36,50,51,2,3,8,9,16,17,18,19,0,1,12,13,4,5,22,23,10,11,28,29,14,15,20,21,40,41,6,7,54,55,52,53,44,45,42,43,34,35,26,27,32,33,24,25,48,49,38,39,56,57,30,31,46,47,60,61,58,59,62,63,37}},
  {{4,4,4,3,3,4,4,4},{0,0,1,1,0,2,0,0},{6,6,6,6,6,6,6,6},{13,13,13,4,4,1,4,1},
   {1,1,0,0,2,0,1,3},{8,8,8,8,8,8,8,8},{5,5,5,5,5,5,5,5},{10,10,10,10,10,10,10,10},
   {3,2,3,2,1,1,2,1},{2,3,2,4,4,3,3,2},{11,11,11,11,11,11,11,11},{7,7,7,7,7,7,7,7},
   {8,8,9,10,10,11,9,9},{5,5,8,6,6,6,1,3},{9,9,9,9,9,9,9,9},{11,12,2,2,3,4,2,4},
   {7,6,6,9,9,9,11,2},{4,4,7,8,8,8,8,8},{2,1,9,11,11,10,3,11},{1,9,11,12,4,3,3,11},
   {12,12,12,12,12,3,3,2},{3,3,5,7,7,7,7,7},{2,1,4,5,1,0,6,6},{16,11,13,7,7,7,7,6},
   {6,7,10,11,11,10,10,1},{5,5,10,12,4,3,10,1},{15,15,3,2,5,5,5,5},{14,14,2,3,3,4,2,4},
   {0,10,12,4,12,1,4,10},{14,14,4,6,6,6,1,3},{13,13,3,3,5,5,5,5},{15,15,7,10,10,11,9,2}},
  {{255,255,255,255,255,255,255,255},{255,255,255,255,255,255,255,255},{255,255,255,255,255,255,255,255},{255,255,255,9,9,8,0,8},
   {255,255,255,255,255,255,255,255},{255,255,255,255,255,255,255,255},{255,255,255,255,255,255,255,255},{255,255,255,255,255,255,255,255},
   {255,255,255,255,255,255,255,255},{255,255,255,255,255,255,255,255},{255,255,255,255,255,255,255,255},{255,255,255,255,255,255,255,255},
   {5,5,14,7,7,10,14,14},{6,6,5,2,2,2,4,4},{255,255,255,255,255,255,255,255},{10,20,27,26,27,27,27,27},
   {11,2,2,14,14,14,10,20},{0,0,11,5,5,5,5,5},{22,22,12,24,24,24,19,19},{4,14,10,20,3,20,20,10},
   {255,255,255,255,255,9,9,9},{8,9,6,11,11,11,11,11},{9,4,0,6,8,4,2,2},{255,10,3,21,21,21,21,22},
   {2,11,7,10,10,7,7,3},{13,13,24,19,19,19,24,24},{255,255,8,8,6,6,6,6},{255,255,9,0,0,0,8,0},
   {1,7,20,3,20,3,3,7},{27,27,22,13,13,13,13,13},{3,3,26,27,26,26,26,26},{26,26,17,12,12,12,12,16}},
  {112,113,114,115,116,117,118,119,120,121,122,123,124,125,126,127,128,129,130,131,132,133,134,135,80,76,74,43,73,388,42,1,144,145,146,147,148,149,150,151,152,153,154,155,156,157,158,159,160,161,162,163,164,165,166,167,374,375,389,5,630,173,174,175,176,177,178,179,180,181,182,183,184,185,186,187,188,189,190,191,40,38,645,6,8,4,198,199,200,201,202,203,204,205,206,207,24,209,52,369,212,213,88,83,216,81,9,47,51,89,45,15,2,631,226,227,228,229,230,231,94,90,61,56,60,97,54,92,16,241,242,625,385,641,84,85,86,11,378,251,48,49,13,14,31,27,258,63,64,65,29,30,25,20,266,267,268,55,270,271,3,39,36,44,72,7,0,279,17,370,10,50,284,46,286,287,372,626,634,291,292,293,294,295,296,91,18,299,300,301,98,95,87,82,53,307,308,309,310,311,32,68,314,66,67,69,34,33,41,12,75,379,324,325,644,628,328,77,37,635,371,627,78,79,336,21,19,57,58,59,22,23,344,345,62,347,348,349,350,351,96,353,354,355,356,357,93,26,360,28,362,363,364,35,366,367},
  {511,511,511,511,511,511,511,511,511,511,511,511,511,511,511,511,511,511,511,511,511,511,511,511,256,256,256,256,256,36,256,256,511,511,511,511,511,511,511,511,511,511,511,511,511,511,511,511,511,511,511,511,511,511,511,511,14,15,13,256,14,511,511,511,511,511,511,511,511,511,511,511,511,511,511,511,511,511,511,511,256,256,13,256,256,256,511,511,511,511,511,511,511,511,511,511,258,511,257,9,511,511,257,257,511,257,257,257,257,257,257,257,256,15,511,511,511,511,511,511,258,258,258,258,258,258,258,258,257,511,511,9,65,65,257,257,257,257,10,511,257,257,257,257,259,259,511,259,259,259,259,259,258,258,511,511,511,258,511,511,256,256,256,256,256,256,256,511,257,34,257,257,511,257,511,511,12,34,10,511,511,511,511,511,511,258,258,511,511,511,258,258,257,257,257,511,511,511,511,511,259,259,511,259,259,259,259,259,256,257,256,11,511,511,36,12,511,256,256,11,35,35,256,256,511,258,258,258,258,258,258,258,511,511,258,511,511,511,511,511,258,511,511,511,511,511,258,258,511,259,511,511,511,259,511,511}};

typedef CUresult (*EncodeFn)(CUtensorMap*, CUtensorMapDataType, cuuint32_t, void*, const cuuint64_t*, const cuuint64_t*, const cuuint32_t*,
                             const cuuint32_t*, CUtensorMapInterleave, CUtensorMapSwizzle, CUtensorMapL2promotion, CUtensorMapFloatOOBfill);

void make_map2(EncodeFn enc, CUtensorMap* m, const void* ptr, int rows, int cols, int box_rows) {
  cuuint64_t dim[2] = {(cuuint64_t)cols, (cuuint64_t)rows}, str[1] = {(cuuint64_t)cols * 2};
  cuuint32_t box[2] = {64, (cuuint32_t)box_rows}, es[2] = {1, 1};
  enc(m, CU_TENSOR_MAP_DATA_TYPE_BFLOAT16, 2, const_cast<void*>(ptr), dim, str, box, es, CU_TENSOR_MAP_INTERLEAVE_NONE, CU_TENSOR_MAP_SWIZZLE_128B,
      CU_TENSOR_MAP_L2_PROMOTION_L2_128B, CU_TENSOR_MAP_FLOAT_OOB_FILL_NONE);
}
void make_map3(EncodeFn enc, CUtensorMap* m, const void* ptr, int rows) {
  cuuint64_t dim[3] = {64, (cuuint64_t)rows, 9}, str[2] = {DM * 2, 128};
  cuuint32_t box[3] = {64, 32, 3}, es[3] = {1, 1, 1};
  enc(m, CU_TENSOR_MAP_DATA_TYPE_BFLOAT16, 3, const_cast<void*>(ptr), dim, str, box, es, CU_TENSOR_MAP_INTERLEAVE_NONE, CU_TENSOR_MAP_SWIZZLE_128B,
      CU_TENSOR_MAP_L2_PROMOTION_L2_128B, CU_TENSOR_MAP_FLOAT_OOB_FILL_NONE);
}

void make_map_t(EncodeFn enc, CUtensorMap* m, void* ptr, int width, int cols) {
  cuuint64_t dim[3] = {SEQ / 2, 2, 864}, str[2] = {SEQ * 2, SEQ * 4};
  cuuint32_t box[3] = {(cuuint32_t)width, 2, (cuuint32_t)cols}, es[3] = {1, 1, 1};
  enc(m, CU_TENSOR_MAP_DATA_TYPE_UINT32, 3, ptr, dim, str, box, es, CU_TENSOR_MAP_INTERLEAVE_NONE, cols == 64 ? CU_TENSOR_MAP_SWIZZLE_128B : CU_TENSOR_MAP_SWIZZLE_NONE,
      CU_TENSOR_MAP_L2_PROMOTION_NONE, CU_TENSOR_MAP_FLOAT_OOB_FILL_NONE);
}

int g_mode = -1;

}

extern "C" void kernel_launch(void* const* d_in, const int* in_sizes, int n_in, void* d_out, int out_size) {
  static EncodeFn enc = nullptr;
  static void* t_ptr = nullptr;
  if (!enc) {
    void* fn = nullptr;
    cudaDriverEntryPointQueryResult st;
    cudaGetDriverEntryPoint("cuTensorMapEncodeTiled", &fn, cudaEnableDefault, &st);
    enc = (EncodeFn)fn;
    cudaGetSymbolAddress(&t_ptr, g_S);
    cudaFuncSetAttribute(fused_kernel, cudaFuncAttributeMaxDynamicSharedMemorySize, SMEM_BYTES);
    if (g_mode < 0) {
      cudaLaunchConfig_t cfg = {};
      cfg.gridDim = dim3(2 * NCL); cfg.blockDim = dim3(384); cfg.dynamicSmemBytes = SMEM_BYTES;
      cudaLaunchAttribute at; at.id = cudaLaunchAttributeClusterDimension;
      at.val.clusterDim.x = 2; at.val.clusterDim.y = 1; at.val.clusterDim.z = 1;
      cfg.attrs = &at; cfg.numAttrs = 1;
      int nc = 0;
      g_mode = (cudaOccupancyMaxActiveClusters(&nc, fused_kernel, &cfg) == cudaSuccess && nc >= NCL) ? 1 : 0;
      (void)cudaGetLastError();
    }
  }
  Params p;
  make_map2(enc, &p.map_a[0], d_in[4], SEQ, DC, 128);
  make_map2(enc, &p.map_a[1], d_in[0], SEQ, DM, 128);
  make_map2(enc, &p.map_w[0], d_in[6], DC, 4096, 64);
  make_map2(enc, &p.map_w[1], d_in[7], DC, 4096, 64);
  make_map2(enc, &p.map_w[2], d_in[5], DM, 4096, 64);
  make_map2(enc, &p.map_w[3], d_in[1], DM, 1728, 64);
  make_map3(enc, &p.map_o[0], d_in[8], 4096);
  make_map3(enc, &p.map_o[1], d_in[2], DM);
  make_map_t(enc, &p.map_t[0], t_ptr, 32, 9);
  make_map_t(enc, &p.map_t[1], t_ptr, 40, 9);
  make_map_t(enc, &p.map_t[2], t_ptr, 32, 64);
  p.x = (const __nv_bfloat16*)d_in[0];
  p.gate_w = (const __nv_bfloat16*)d_in[9];
  make_map2(enc, &p.map_out, d_out, SEQ, DM, 64);
  p.out = (__nv_bfloat16*)d_out;
  p.zero = 0;
  auto launch = [&](int phases) {
    p.s = k_sched;
    for (int i = 0; i < NCL; i++) {
      Rec& r = p.s.r[i];
      if (!(phases & 1)) r.n1 = 0;
      if (!(phases & 2)) r.n2 = 0;
      if (!(phases & (p.s.task[i][1] == 64 ? 4 : 32))) r.p3 = 255;
      if (!(phases & 8)) r.bg = 255;
      const int u1 = r.n1 ? 8 + r.n1 * (8 + (r.slab >> 3)) : 0;
      int u2 = 0;
      for (int k = 0; k < r.n2; k++) u2 += 4 * (r.item[k] & 7) + 4;
      r.u1 = (uint8_t)u1; r.u2 = (uint8_t)u2;
      r.rot = (uint8_t)(((u1 % 10 + 1) >> 1) % 5);
      r.x3 = (uint8_t)((r.rot + u2) % 5 & 3);
      r.phases = (uint8_t)phases;
    }
    if (!(phases & 16))
      for (int i = 0; i < 256; i++) { p.s.slot[i >> 3][i & 7] = (uint8_t)(i >> 3); p.s.prev[i >> 3][i & 7] = 255; p.s.qblk[i] = (uint16_t)(S_Q + i); p.s.qdep[i] = 511; }
    fused_kernel<<<2 * NCL, 384, SMEM_BYTES>>>(p);
  };
  if (g_mode == 1) launch(63);
  else { launch(1); launch(10); launch(4); launch(32); }
}
```

```cpp
#include <cuda_runtime.h>
#include <cuda_bf16.h>
#include <cuda.h>
#include <stdint.h>

namespace {

constexpr int SEQ = 2048, DM = 576, DC = 512, NH = 32;
constexpr int NCL = 66;
constexpr uint32_t DESC_HI = 0x40000040u;

constexpr int SM_RING = 0;
constexpr int SM_BUF = 163840;
constexpr int SM_BAR = 229376;
constexpr int B_P1E = 0, B_P2E = 10, B_P3E = 15, B_P2F = 24, B_SF = 32, B_ORD = 36, B_LAD = 40, B_DONE = 41, B_FIN = 48;
constexpr int B_P3F = 56, B_OUT = 61, B_P1F = 64, B_SE = 74, B_QF = 80, B_LA = 84, B_NUM = 88;
constexpr uint64_t B_CNT = 0x11118245000ull;
constexpr int SMEM_BYTES = SM_BAR + B_NUM * 8 + 1024;

constexpr int F_QKVA = 32;
constexpr int F_GATE = 64;
constexpr int F_TS = 68;
constexpr int F_DONE = 65;
constexpr int F_CTX = 96;
constexpr int F_OUT = 96 + 8 * 64;
constexpr int F_KV = F_OUT + 64;
constexpr int F_Q = F_KV + 256;
constexpr int F_RD = F_Q + 256;
constexpr int F_NUM = F_RD + 256;

struct Rec {
  uint8_t slab;
  uint8_t n1, n2;
  uint8_t p3;
  uint8_t bg;
  uint8_t item[11];
  uint8_t last[11];
  uint8_t tile[32];
  uint8_t u1, u2;
  uint8_t rot, x3;
  uint8_t phases;
};
struct Sched {
  Rec r[NCL];
  uint8_t task[NCL][4];
  uint8_t p3_order[24][64];
  uint8_t slot[32][8];
  uint8_t prev[32][8];
  uint16_t qblk[256];
  uint16_t qdep[256];
};

#define SCHED_DECL static const

struct Params {
  CUtensorMap map_a[2];
  CUtensorMap map_w[4];
  CUtensorMap map_o[2];
  CUtensorMap map_t[3];
  CUtensorMap map_out;
  const __nv_bfloat16* x;
  const __nv_bfloat16* gate_w;
  __nv_bfloat16* out;
  int zero;
  alignas(64) Sched s;
};

constexpr int S_T = 0, S_Q = 112, S_K = S_Q + 256, S_V = S_K + 256, S_NUM = S_V + 256;
__device__ __align__(1024) uint8_t g_S[(size_t)S_NUM * 65536];
__device__ __align__(1024) uint8_t g_oA[32 * 576 * 128];
__device__ float g_gate[SEQ];
__device__ int g_flags[F_NUM];
#define PL(i)

__device__ __forceinline__ void mbar_arrive(uint32_t b) { asm volatile("mbarrier.arrive.shared::cta.b64 _, [%0];" ::"r"(b) : "memory"); }
__device__ __forceinline__ void mbar_arrive_cl(uint32_t b, int cnt) {
  asm volatile("mbarrier.arrive.shared::cluster.b64 _, [%0], %1;" ::"r"(b), "r"(cnt) : "memory");
}
__device__ __forceinline__ void mbar_wait(uint32_t b, int par) {
  asm volatile(
      "{\n.reg .pred p;\n.reg .u32 c;\n"
      "mbarrier.try_wait.parity.shared::cta.b64 p, [%0], %1;\n@p bra DN;\nmov.u32 c, 0;\n"
      "LP:\nmbarrier.try_wait.parity.shared::cta.b64 p, [%0], %1;\n@p bra DN;\n"
      "add.u32 c, c, 1;\nsetp.lt.u32 p, c, 4000000;\n@p bra LP;\ntrap;\nDN:\n}" ::"r"(b), "r"(par) : "memory");
}
__device__ __forceinline__ bool mbar_test(uint32_t b, int par) {
  uint32_t ok;
  asm volatile("{\n.reg .pred p;\nmbarrier.test_wait.parity.shared::cta.b64 p, [%1], %2;\nselp.u32 %0, 1, 0, p;\n}" : "=r"(ok) : "r"(b), "r"(par) : "memory");
  return __all_sync(0xffffffffu, ok);
}
__device__ __forceinline__ uint32_t mapa(uint32_t a, uint32_t cta) {
  uint32_t r; asm("mapa.shared::cluster.u32 %0, %1, %2;" : "=r"(r) : "r"(a), "r"(cta)); return r;
}
#define ELECT(ins) "{\n.reg .pred e;\nelect.sync _|e, 0xffffffff;\n@e " ins "\n}"
__device__ __forceinline__ void mbar_expect(uint32_t b, int bytes) {
  asm volatile(ELECT("mbarrier.arrive.expect_tx.shared::cta.b64 _, [%0], %1;") ::"r"(b), "r"(bytes) : "memory");
}
__device__ __forceinline__ void mbar_arrive_one(uint32_t b) { asm volatile(ELECT("mbarrier.arrive.shared::cta.b64 _, [%0];") ::"r"(b) : "memory"); }
constexpr uint64_t L2_NORMAL = 0x1000000000000000ull, L2_FIRST = 0x12F0000000000000ull;
__device__ __forceinline__ void bulk_load(uint32_t dst, const void* src, int bytes, uint32_t bar, uint64_t pol = L2_NORMAL) {
  asm volatile(ELECT("cp.async.bulk.shared::cluster.global.mbarrier::complete_tx::bytes.L2::cache_hint [%0], [%1], %2, [%3], %4;") ::"r"(dst), "l"(src), "r"(bytes), "r"(bar), "l"(pol) : "memory");
}
__device__ __forceinline__ void bulk_load_mc(uint32_t dst, const void* src, int bytes, uint32_t bar, uint64_t pol = L2_NORMAL) {
  asm volatile(ELECT("cp.async.bulk.shared::cluster.global.mbarrier::complete_tx::bytes.multicast::cluster.L2::cache_hint [%0], [%1], %2, [%3], %4, %5;") ::"r"(dst), "l"(src), "r"(bytes), "r"(bar), "h"((uint16_t)3), "l"(pol) : "memory");
}
__device__ __forceinline__ void bulk_store(void* dst, uint32_t src, int bytes, uint64_t pol = L2_NORMAL) {
  asm volatile(ELECT("cp.async.bulk.global.shared::cta.bulk_group.L2::cache_hint [%0], [%1], %2, %3;") ::"l"(dst), "r"(src), "r"(bytes), "l"(pol) : "memory");
}
__device__ __forceinline__ void tma2d(uint32_t dst, const CUtensorMap* m, int c0, int c1, uint32_t bar, uint64_t pol = L2_NORMAL) {
  asm volatile(ELECT("cp.async.bulk.tensor.2d.shared::cluster.global.mbarrier::complete_tx::bytes.L2::cache_hint [%0], [%1, {%3, %4}], [%2], %5;") ::"r"(dst), "l"(m), "r"(bar), "r"(c0), "r"(c1), "l"(pol) : "memory");
}
__device__ __forceinline__ void tma2d_mc(uint32_t dst, const CUtensorMap* m, int c0, int c1, uint32_t bar, uint64_t pol = L2_NORMAL) {
  asm volatile(ELECT("cp.async.bulk.tensor.2d.shared::cluster.global.mbarrier::complete_tx::bytes.multicast::cluster.L2::cache_hint [%0], [%1, {%3, %4}], [%2], %5, %6;") ::"r"(dst), "l"(m), "r"(bar), "r"(c0), "r"(c1), "h"((uint16_t)3), "l"(pol) : "memory");
}
__device__ __forceinline__ void tma3d(uint32_t dst, const CUtensorMap* m, int c0, int c1, int c2, uint32_t bar, uint64_t pol = L2_NORMAL) {
  asm volatile(ELECT("cp.async.bulk.tensor.3d.shared::cluster.global.mbarrier::complete_tx::bytes.L2::cache_hint [%0], [%1, {%3, %4, %5}], [%2], %6;") ::"r"(dst), "l"(m), "r"(bar), "r"(c0), "r"(c1), "r"(c2), "l"(pol) : "memory");
}
__device__ __forceinline__ void tma3d_mc(uint32_t dst, const CUtensorMap* m, int c0, int c1, int c2, uint32_t bar, uint64_t pol = L2_NORMAL) {
  asm volatile(ELECT("cp.async.bulk.tensor.3d.shared::cluster.global.mbarrier::complete_tx::bytes.multicast::cluster.L2::cache_hint [%0], [%1, {%3, %4, %5}], [%2], %6, %7;") ::"r"(dst), "l"(m), "r"(bar), "r"(c0), "r"(c1), "r"(c2), "h"((uint16_t)3), "l"(pol) : "memory");
}
__device__ __forceinline__ void tma2d_add(const CUtensorMap* m, uint32_t src, int c0, int c1) {
  asm volatile(ELECT("cp.reduce.async.bulk.tensor.2d.global.shared::cta.add.bulk_group [%0, {%2, %3}], [%1];") ::"l"(m), "r"(src), "r"(c0), "r"(c1) : "memory");
}
__device__ __forceinline__ void tma3d_store(const CUtensorMap* m, uint32_t src, int c0, int c1, int c2, uint64_t pol = L2_NORMAL) {
  asm volatile(ELECT("cp.async.bulk.tensor.3d.global.shared::cta.bulk_group.L2::cache_hint [%0, {%2, %3, %4}], [%1], %5;") ::"l"(m), "r"(src), "r"(c0), "r"(c1), "r"(c2), "l"(pol) : "memory");
}
__device__ __forceinline__ void tma2d_prefetch(const CUtensorMap* m, int c0, int c1, uint64_t pol = L2_NORMAL) {
  asm volatile(ELECT("cp.async.bulk.prefetch.tensor.2d.L2.global.L2::cache_hint [%0, {%1, %2}], %3;") ::"l"(m), "r"(c0), "r"(c1), "l"(pol) : "memory");
}
#define LAG 3
#define HINT 63
#define POL(bit) ((HINT >> (bit)) & 1 ? L2_FIRST : L2_NORMAL)
#define BULK_COMMIT() asm volatile("cp.async.bulk.commit_group;" ::: "memory")
#define BULK_WAIT(n) asm volatile("cp.async.bulk.wait_group %0;" ::"n"(n) : "memory")
#define BULK_WAIT_READ(n) asm volatile("cp.async.bulk.wait_group.read %0;" ::"n"(n) : "memory")
#define FENCE_ASYNC_SMEM() asm volatile("fence.proxy.async.shared::cta;" ::: "memory")
#define FENCE_ASYNC_ALL() asm volatile("fence.proxy.async;" ::: "memory")
#define WG_FENCE() asm volatile("wgmma.fence.sync.aligned;" ::: "memory")
#define WG_COMMIT() asm volatile("wgmma.commit_group.sync.aligned;" ::: "memory")
#define WG_WAIT(n) asm volatile("wgmma.wait_group.sync.aligned %0;" ::"n"(n) : "memory")
__device__ __forceinline__ void bar_sync(int id, int n) { asm volatile("bar.sync %0, %1;" ::"r"(id), "r"(n) : "memory"); }
__device__ __forceinline__ void bar_arrive(int id, int n) { asm volatile("bar.arrive %0, %1;" ::"r"(id), "r"(n) : "memory"); }
__device__ __forceinline__ void cluster_sync() {
  asm volatile("barrier.cluster.arrive.relaxed;\nbarrier.cluster.wait.acquire;" ::: "memory");
}
template <int N> __device__ __forceinline__ void pin(float (&r)[N]) {
#pragma unroll
  for (int i = 0; i < N; i++) asm volatile("" : "+f"(r[i])::"memory");
}
template <int N> __device__ __forceinline__ void pin(uint32_t (&r)[N]) {
#pragma unroll
  for (int i = 0; i < N; i++) asm volatile("" : "+r"(r[i])::"memory");
}
__device__ __forceinline__ uint32_t pack_bf16(float lo, float hi) {
  uint32_t r; asm("cvt.rn.bf16x2.f32 %0, %1, %2;" : "=r"(r) : "f"(hi), "f"(lo)); return r;
}
__device__ __forceinline__ float ex2(float x) { float r; asm("ex2.approx.ftz.f32 %0, %1;" : "=f"(r) : "f"(x)); return r; }
__device__ __forceinline__ void ldsm4(uint32_t a, uint32_t& r0, uint32_t& r1, uint32_t& r2, uint32_t& r3) {
  asm volatile("ldmatrix.sync.aligned.m8n8.x4.shared.b16 {%0,%1,%2,%3}, [%4];" : "=r"(r0), "=r"(r1), "=r"(r2), "=r"(r3) : "r"(a) : "memory");
}
__device__ __forceinline__ void stsm4(uint32_t a, uint32_t r0, uint32_t r1, uint32_t r2, uint32_t r3) {
  asm volatile("stmatrix.sync.aligned.m8n8.x4.shared.b16 [%0], {%1,%2,%3,%4};" ::"r"(a), "r"(r0), "r"(r1), "r"(r2), "r"(r3) : "memory");
}
__device__ __forceinline__ void flag_add(int idx, int v = 1) {
  asm volatile(ELECT("red.release.gpu.global.add.s32 [%0], %1;") ::"l"(g_flags + idx), "r"(v) : "memory");
}
__device__ __forceinline__ void flag_add_rx(int idx, int v = 1) {
  asm volatile(ELECT("red.relaxed.gpu.global.add.s32 [%0], %1;") ::"l"(g_flags + idx), "r"(v) : "memory");
}
template <bool ACQ, int NS = 32> __device__ __forceinline__ void flag_wait(int idx, int target) {
  int n = 0;
  while (true) {
    int v;
    if (ACQ) asm volatile("ld.acquire.gpu.global.s32 %0, [%1];" : "=r"(v) : "l"(g_flags + idx) : "memory");
    else asm volatile("ld.relaxed.gpu.global.s32 %0, [%1];" : "=r"(v) : "l"(g_flags + idx) : "memory");
    if (__all_sync(0xffffffffu, v >= target)) break;
    if (++n > 20000000) __trap();
    __nanosleep(NS);
  }
}
__device__ __forceinline__ int flag_peek(int idx) {
  int v;
  asm volatile("ld.relaxed.gpu.global.s32 %0, [%1];" : "=r"(v) : "l"(g_flags + idx) : "memory");
  return v;
}
__device__ __forceinline__ void mask_wait(uint32_t& ready, int bit, int idx, int target) {
  for (int n = 0; !((ready >> bit) & 1); n++) {
    int v;
    if (n) { __nanosleep(32); if (n > 20000000) __trap(); }
    asm volatile("ld.relaxed.gpu.global.s32 %0, [%1];" : "=r"(v) : "l"(g_flags + idx) : "memory");
    ready = __ballot_sync(0xffffffffu, v >= target);
  }
}
__device__ __forceinline__ uint32_t desc_lo(uint32_t addr, uint32_t lbo) { return ((addr & 0x3FFFFu) >> 4) | ((lbo >> 4) << 16); }
#define PROF(role, i)
#define PROFX(cond, i)
#define PROFB(i)
#define PROFG(i)

template <int TB, int TA = 0> __device__ __forceinline__ void wgmma_ss64(float (&d)[32], uint32_t alo, uint32_t blo, int sd) {
  asm volatile("{\n.reg .pred p;\n.reg .b64 da, db;\n"
    "setp.ne.b32 p, %34, 0;\nmov.b64 da, {%32, %36};\nmov.b64 db, {%33, %36};\n"
    "wgmma.mma_async.sync.aligned.m64n64k16.f32.bf16.bf16 "
    "{%0,%1,%2,%3,%4,%5,%6,%7,%8,%9,%10,%11,%12,%13,%14,%15,%16,%17,%18,%19,%20,%21,%22,%23,"
    "%24,%25,%26,%27,%28,%29,%30,%31}, "
    "da, db, p, 1, 1, %37, %35;\n}\n"
    : "+f"(d[0]),"+f"(d[1]),"+f"(d[2]),"+f"(d[3]),"+f"(d[4]),"+f"(d[5]),"+f"(d[6]),"+f"(d[7]),"+f"(d[8]),"+f"(d[9]),"+f"(d[10]),"+f"(d[11]),
      "+f"(d[12]),"+f"(d[13]),"+f"(d[14]),"+f"(d[15]),"+f"(d[16]),"+f"(d[17]),"+f"(d[18]),"+f"(d[19]),"+f"(d[20]),"+f"(d[21]),"+f"(d[22]),"+f"(d[23]),
      "+f"(d[24]),"+f"(d[25]),"+f"(d[26]),"+f"(d[27]),"+f"(d[28]),"+f"(d[29]),"+f"(d[30]),"+f"(d[31])
    : "r"(alo), "r"(blo), "r"(sd), "n"(TB), "r"(DESC_HI), "n"(TA));
}
template <int TB, int TA = 0> __device__ __forceinline__ void wgmma_ss128(float (&d)[64], uint32_t alo, uint32_t blo, int sd) {
  asm volatile("{\n.reg .pred p;\n.reg .b64 da, db;\n"
    "setp.ne.b32 p, %66, 0;\nmov.b64 da, {%64, %68};\nmov.b64 db, {%65, %68};\n"
    "wgmma.mma_async.sync.aligned.m64n128k16.f32.bf16.bf16 "
    "{%0,%1,%2,%3,%4,%5,%6,%7,%8,%9,%10,%11,%12,%13,%14,%15,%16,%17,%18,%19,%20,%21,%22,%23,"
    "%24,%25,%26,%27,%28,%29,%30,%31,%32,%33,%34,%35,%36,%37,%38,%39,%40,%41,%42,%43,%44,%45,%46,%47,"
    "%48,%49,%50,%51,%52,%53,%54,%55,%56,%57,%58,%59,%60,%61,%62,%63}, "
    "da, db, p, 1, 1, %69, %67;\n}\n"
    : "+f"(d[0]),"+f"(d[1]),"+f"(d[2]),"+f"(d[3]),"+f"(d[4]),"+f"(d[5]),"+f"(d[6]),"+f"(d[7]),"+f"(d[8]),"+f"(d[9]),"+f"(d[10]),"+f"(d[11]),
      "+f"(d[12]),"+f"(d[13]),"+f"(d[14]),"+f"(d[15]),"+f"(d[16]),"+f"(d[17]),"+f"(d[18]),"+f"(d[19]),"+f"(d[20]),"+f"(d[21]),"+f"(d[22]),"+f"(d[23]),
      "+f"(d[24]),"+f"(d[25]),"+f"(d[26]),"+f"(d[27]),"+f"(d[28]),"+f"(d[29]),"+f"(d[30]),"+f"(d[31]),"+f"(d[32]),"+f"(d[33]),"+f"(d[34]),"+f"(d[35]),
      "+f"(d[36]),"+f"(d[37]),"+f"(d[38]),"+f"(d[39]),"+f"(d[40]),"+f"(d[41]),"+f"(d[42]),"+f"(d[43]),"+f"(d[44]),"+f"(d[45]),"+f"(d[46]),"+f"(d[47]),
      "+f"(d[48]),"+f"(d[49]),"+f"(d[50]),"+f"(d[51]),"+f"(d[52]),"+f"(d[53]),"+f"(d[54]),"+f"(d[55]),"+f"(d[56]),"+f"(d[57]),"+f"(d[58]),"+f"(d[59]),
      "+f"(d[60]),"+f"(d[61]),"+f"(d[62]),"+f"(d[63])
    : "r"(alo), "r"(blo), "r"(sd), "n"(TB), "r"(DESC_HI), "n"(TA));
}
template <int TB> __device__ __forceinline__ void wgmma_rs128(float (&d)[64], uint32_t a0, uint32_t a1, uint32_t a2, uint32_t a3, uint32_t blo, int sd) {
  asm volatile("{\n.reg .pred p;\n.reg .b64 db;\n"
    "setp.ne.b32 p, %69, 0;\nmov.b64 db, {%68, %71};\n"
    "wgmma.mma_async.sync.aligned.m64n128k16.f32.bf16.bf16 "
    "{%0,%1,%2,%3,%4,%5,%6,%7,%8,%9,%10,%11,%12,%13,%14,%15,%16,%17,%18,%19,%20,%21,%22,%23,"
    "%24,%25,%26,%27,%28,%29,%30,%31,%32,%33,%34,%35,%36,%37,%38,%39,%40,%41,%42,%43,%44,%45,%46,%47,"
    "%48,%49,%50,%51,%52,%53,%54,%55,%56,%57,%58,%59,%60,%61,%62,%63}, "
    "{%64,%65,%66,%67}, db, p, 1, 1, %70;\n}\n"
    : "+f"(d[0]),"+f"(d[1]),"+f"(d[2]),"+f"(d[3]),"+f"(d[4]),"+f"(d[5]),"+f"(d[6]),"+f"(d[7]),"+f"(d[8]),"+f"(d[9]),"+f"(d[10]),"+f"(d[11]),
      "+f"(d[12]),"+f"(d[13]),"+f"(d[14]),"+f"(d[15]),"+f"(d[16]),"+f"(d[17]),"+f"(d[18]),"+f"(d[19]),"+f"(d[20]),"+f"(d[21]),"+f"(d[22]),"+f"(d[23]),
      "+f"(d[24]),"+f"(d[25]),"+f"(d[26]),"+f"(d[27]),"+f"(d[28]),"+f"(d[29]),"+f"(d[30]),"+f"(d[31]),"+f"(d[32]),"+f"(d[33]),"+f"(d[34]),"+f"(d[35]),
      "+f"(d[36]),"+f"(d[37]),"+f"(d[38]),"+f"(d[39]),"+f"(d[40]),"+f"(d[41]),"+f"(d[42]),"+f"(d[43]),"+f"(d[44]),"+f"(d[45]),"+f"(d[46]),"+f"(d[47]),
      "+f"(d[48]),"+f"(d[49]),"+f"(d[50]),"+f"(d[51]),"+f"(d[52]),"+f"(d[53]),"+f"(d[54]),"+f"(d[55]),"+f"(d[56]),"+f"(d[57]),"+f"(d[58]),"+f"(d[59]),
      "+f"(d[60]),"+f"(d[61]),"+f"(d[62]),"+f"(d[63])
    : "r"(a0), "r"(a1), "r"(a2), "r"(a3), "r"(blo), "r"(sd), "n"(TB), "r"(DESC_HI));
}
template <int TB, int TA = 0> __device__ __forceinline__ void wgmma_ss192(float (&d)[96], uint32_t alo, uint32_t blo, int sd) {
  asm volatile("{\n.reg .pred p;\n.reg .b64 da, db;\n"
    "setp.ne.b32 p, %98, 0;\nmov.b64 da, {%96, %100};\nmov.b64 db, {%97, %100};\n"
    "wgmma.mma_async.sync.aligned.m64n192k16.f32.bf16.bf16 "
    "{%0,%1,%2,%3,%4,%5,%6,%7,%8,%9,%10,%11,%12,%13,%14,%15,%16,%17,%18,%19,%20,%21,%22,%23,"
    "%24,%25,%26,%27,%28,%29,%30,%31,%32,%33,%34,%35,%36,%37,%38,%39,%40,%41,%42,%43,%44,%45,%46,%47,"
    "%48,%49,%50,%51,%52,%53,%54,%55,%56,%57,%58,%59,%60,%61,%62,%63,%64,%65,%66,%67,%68,%69,%70,%71,"
    "%72,%73,%74,%75,%76,%77,%78,%79,%80,%81,%82,%83,%84,%85,%86,%87,%88,%89,%90,%91,%92,%93,%94,%95}, "
    "da, db, p, 1, 1, %101, %99;\n}\n"
    : "+f"(d[0]),"+f"(d[1]),"+f"(d[2]),"+f"(d[3]),"+f"(d[4]),"+f"(d[5]),"+f"(d[6]),"+f"(d[7]),"+f"(d[8]),"+f"(d[9]),"+f"(d[10]),"+f"(d[11]),
      "+f"(d[12]),"+f"(d[13]),"+f"(d[14]),"+f"(d[15]),"+f"(d[16]),"+f"(d[17]),"+f"(d[18]),"+f"(d[19]),"+f"(d[20]),"+f"(d[21]),"+f"(d[22]),"+f"(d[23]),
      "+f"(d[24]),"+f"(d[25]),"+f"(d[26]),"+f"(d[27]),"+f"(d[28]),"+f"(d[29]),"+f"(d[30]),"+f"(d[31]),"+f"(d[32]),"+f"(d[33]),"+f"(d[34]),"+f"(d[35]),
      "+f"(d[36]),"+f"(d[37]),"+f"(d[38]),"+f"(d[39]),"+f"(d[40]),"+f"(d[41]),"+f"(d[42]),"+f"(d[43]),"+f"(d[44]),"+f"(d[45]),"+f"(d[46]),"+f"(d[47]),
      "+f"(d[48]),"+f"(d[49]),"+f"(d[50]),"+f"(d[51]),"+f"(d[52]),"+f"(d[53]),"+f"(d[54]),"+f"(d[55]),"+f"(d[56]),"+f"(d[57]),"+f"(d[58]),"+f"(d[59]),
      "+f"(d[60]),"+f"(d[61]),"+f"(d[62]),"+f"(d[63]),"+f"(d[64]),"+f"(d[65]),"+f"(d[66]),"+f"(d[67]),"+f"(d[68]),"+f"(d[69]),"+f"(d[70]),"+f"(d[71]),
      "+f"(d[72]),"+f"(d[73]),"+f"(d[74]),"+f"(d[75]),"+f"(d[76]),"+f"(d[77]),"+f"(d[78]),"+f"(d[79]),"+f"(d[80]),"+f"(d[81]),"+f"(d[82]),"+f"(d[83]),
      "+f"(d[84]),"+f"(d[85]),"+f"(d[86]),"+f"(d[87]),"+f"(d[88]),"+f"(d[89]),"+f"(d[90]),"+f"(d[91]),"+f"(d[92]),"+f"(d[93]),"+f"(d[94]),"+f"(d[95])
    : "r"(alo), "r"(blo), "r"(sd), "n"(TB), "r"(DESC_HI), "n"(TA));
}

struct Ctx {
  uint32_t sm;
  uint32_t bar;
  uint32_t rbar;
  int cl, rank, wg, warp, lane, phases;
};
__device__ __forceinline__ void release(const Ctx& c, int b, int cnt = 1) {
  if (c.lane < 2) mbar_arrive_cl(c.rbar + b * 8, cnt);
}
#define HK 5
#define NPRO 6
#define ZLEAD 14
#define PFM 7
#define PF1 1
constexpr float SM_SCALE = 0.08838834764831845f * 1.4426950408889634f;
constexpr float SM_HI = 1.8446744e19f, SM_LO = 5.4210109e-20f;
constexpr int ORDER = 1;

__device__ __forceinline__ void stage_tile(const float (&a)[64], uint32_t buf, const Ctx& c, float s0, float s1) {
  const int row = (c.lane & 7) + ((c.lane >> 3) & 1) * 8;
  const uint32_t base = buf + (c.warp * 16 + row) * 128 + (((c.lane >> 4) ^ (row & 7)) << 4);
#pragma unroll
  for (int i = 0; i < 8; i++)
    stsm4((base ^ ((i & 3) << 5)) + (i >> 2) * 8192, pack_bf16(a[8 * i] * s0, a[8 * i + 1] * s0), pack_bf16(a[8 * i + 2] * s1, a[8 * i + 3] * s1),
          pack_bf16(a[8 * i + 4] * s0, a[8 * i + 5] * s0), pack_bf16(a[8 * i + 6] * s1, a[8 * i + 7] * s1));
}

__device__ __forceinline__ void p1_epilogue(const Params& p, const Ctx& c, const float (&acc)[64], int t, int type) {
  const int tile = p.s.r[c.cl].tile[t] & 63, b = c.wg * 2 + 1;
  mbar_wait(c.bar + (B_SE + b) * 8, (t & 1) ^ 1);
  if (type && tile >= 32) {
    const int r = 2 * (c.lane & 3) + ((c.lane >> 2) & 1);
    const uint32_t dst = c.sm + SM_BUF + b * 16384 + r * 128 + (((c.warp * 2) ^ r) << 4) + (c.lane >> 3) * 4;
#pragma unroll
    for (int i = 0; i < 16; i++) {
      asm volatile("st.shared.u32 [%0], %1;" ::"r"(dst + i * 1024), "r"(pack_bf16(acc[4 * i], acc[4 * i + 1])) : "memory");
      asm volatile("st.shared.u32 [%0], %1;" ::"r"((dst ^ 16) + i * 1024), "r"(pack_bf16(acc[4 * i + 2], acc[4 * i + 3])) : "memory");
    }
  } else {
    if (type) stage_tile(acc, c.sm + SM_BUF + b * 16384, c, SM_SCALE, SM_SCALE);
    else stage_tile(acc, c.sm + SM_BUF + b * 16384, c, 1.f, 1.f);
  }
  FENCE_ASYNC_SMEM();
  __syncwarp();
  if (c.lane == 0) mbar_arrive(c.bar + (B_SF + b) * 8);
}

__device__ __forceinline__ void p1_consumer(const Params& p, const Ctx& c) {
  const int n = p.s.r[c.cl].n1;
  const int type = p.s.r[c.cl].slab >> 3;
  const uint32_t bdesc = desc_lo(c.sm + SM_RING, 8192), adesc = desc_lo(c.sm + SM_BUF + 32768 + c.wg * 8192, 16);
  uint32_t A[128];
  float acc[64] = {};
  int slot = 0, par = 0;
  auto next = [&]() { if (++slot == 10) { slot = 0; par ^= 1; } };
  {
    const int row = (c.lane & 7) + ((c.lane >> 3) & 1) * 8;
    const uint32_t base = c.sm + SM_RING + (c.wg * 64 + c.warp * 16 + row) * 128 + (((c.lane >> 4) ^ (row & 7)) << 4);
    if (c.wg == 1) bar_sync(ORDER + 1, 256);
    int pa = -1, pb = -1;
    if (type) {
      mbar_wait(c.bar + B_P1F * 8, 0);
      WG_FENCE();
#pragma unroll
      for (int kk = 0; kk < 4; kk++) wgmma_ss128<1>(acc, adesc + kk * 2, bdesc + kk * 128, kk != 0);
      WG_COMMIT();
      pb = 0; slot = 1;
    }
#pragma unroll
    for (int kb = 0; kb < 8; kb++) {
      const int sa = slot;
      mbar_wait(c.bar + (B_P1F + slot) * 8, par);
      if (kb == 0) PROF(c.wg, 5);
      next();
      mbar_wait(c.bar + (B_P1F + slot) * 8, par);
      PROF(c.wg, 6 + 2 * kb);
      WG_FENCE();
#pragma unroll
      for (int kk = 0; kk < 4; kk++)
        wgmma_ss128<1>(acc, desc_lo(c.sm + SM_RING + c.wg * 8192, 16) + sa * 1024 + kk * 2, bdesc + slot * 1024 + kk * 128, (kb | kk) != 0 ? 1 : type);
      WG_COMMIT();
      if (kb == 1 && c.wg == 0) bar_arrive(ORDER + 1, 256);
#pragma unroll
      for (int kk = 0; kk < 4; kk++) ldsm4((base ^ (kk << 5)) + sa * 16384, A[kb * 16 + kk * 4], A[kb * 16 + kk * 4 + 1], A[kb * 16 + kk * 4 + 2], A[kb * 16 + kk * 4 + 3]);
      WG_WAIT(1);
      if (kb > 0) release(c, B_P1E + pa);
      if (kb > 0 || pb >= 0) release(c, B_P1E + pb);
      pa = sa; pb = slot;
      next();
    }
    WG_WAIT(0);
    __syncwarp();
    release(c, B_P1E + pa);
    release(c, B_P1E + pb);
    pin(acc);
    PROF(c.wg, 1);
    p1_epilogue(p, c, acc, 0, type);
    PROF(c.wg, 2);
  }
  for (int t = 1; t < n; t++) {
    bar_sync(ORDER + c.wg, 256);
    int prev1 = -1, prev2 = -1;
    if (type) {
      mbar_wait(c.bar + (B_P1F + slot) * 8, par);
      WG_FENCE();
#pragma unroll
      for (int kk = 0; kk < 4; kk++) wgmma_ss128<1>(acc, adesc + kk * 2, bdesc + slot * 1024 + kk * 128, kk != 0);
      WG_COMMIT();
      prev1 = slot;
      next();
    }
#pragma unroll
    for (int kb = 0; kb < 8; kb++) {
      mbar_wait(c.bar + (B_P1F + slot) * 8, par);
      WG_FENCE();
      const uint32_t d = bdesc + slot * 1024;
#pragma unroll
      for (int kk = 0; kk < 4; kk++)
        wgmma_rs128<1>(acc, A[kb * 16 + kk * 4], A[kb * 16 + kk * 4 + 1], A[kb * 16 + kk * 4 + 2], A[kb * 16 + kk * 4 + 3], d + kk * 128, (kb | kk) != 0 ? 1 : type);
      WG_COMMIT();
      if (kb == HK) {
        if (t + 1 < n || c.wg == 0) bar_arrive(ORDER + (c.wg ^ 1), 256);
      }
      if (kb > 0) { WG_WAIT(2); if (kb > 1 || prev2 >= 0) release(c, B_P1E + prev2); }
      prev2 = prev1; prev1 = slot;
      next();
    }
    WG_WAIT(1);
    release(c, B_P1E + prev2);
    WG_WAIT(0);
    pin(acc);
    release(c, B_P1E + prev1);
    p1_epilogue(p, c, acc, t, type);
    PROF(c.wg, 3);
  }
}

__device__ __forceinline__ void p1_producer(const Params& p, const Ctx& c) {
  const int n = p.s.r[c.cl].n1;
  const int type = p.s.r[c.cl].slab >> 3, grp = p.s.r[c.cl].slab & 7;
  int slot = NPRO % 10, par = NPRO < 10;
#pragma unroll 1
  for (int t = 0; t < n; t++) {
    const int tile = p.s.r[c.cl].tile[t] & 63;
    const CUtensorMap* m = &p.map_w[type * 2 + (tile >> 5)];
    const int n0 = (tile & 31) * 128 + c.rank * 64;
    const uint64_t pol = p.s.r[c.cl].tile[t] >= 192 ? POL(0) : L2_NORMAL;
    const int ptile = p.s.r[c.cl].tile[t + PF1 < n ? t + PF1 : t];
    const CUtensorMap* pm = &p.map_w[type * 2 + ((ptile >> 5) & 1)];
    if (t == 7 && (c.phases & 16)) flag_wait<true>(F_GATE, 256);
#pragma unroll 1
    for (int kb = t ? -type : (NPRO - type) >> 1; kb < 8; kb++) {
      if (t == 0 && 2 * kb + type >= NPRO) {
        mbar_wait(c.bar + (B_P1E + slot) * 8, par);
        mbar_expect(c.bar + (B_P1F + slot) * 8, 16384);
        tma2d(c.sm + SM_RING + slot * 16384, &p.map_a[type], kb * 64, grp * 256 + c.rank * 128, c.bar + (B_P1F + slot) * 8);
        if (++slot == 10) { slot = 0; par ^= 1; }
      }
      mbar_wait(c.bar + (B_P1E + slot) * 8, par);
      mbar_expect(c.bar + (B_P1F + slot) * 8, 16384);
      tma2d_mc(c.sm + SM_RING + slot * 16384 + c.rank * 8192, m, n0, kb < 0 ? 512 : kb * 64, c.bar + (B_P1F + slot) * 8, pol);
      if (t == 0 && kb == 1) PROF(2, 61);
      if (t == 0 && kb == 3) PROF(2, 62);
      if (t + PF1 < n && t > 0 && ((ptile >> 6) == 1 || ((ptile >> 6) == 2 && ((kb ^ grp) & PFM) == 0))) tma2d_prefetch(pm, (ptile & 31) * 128 + c.rank * 64, kb < 0 ? 512 : kb * 64);
      if (++slot == 10) { slot = 0; par ^= 1; }
    }
  }
}

__device__ __forceinline__ void wait_kv_dead(const Ctx& c, int h, int g) {
  if (g >= 2) flag_wait<false>(F_RD + h * 8 + g, 8 - g);
  else flag_wait<false>(F_CTX + max(c.lane & 7, g) * 64 + h, 4);
}
__device__ __forceinline__ int p1_storer(const Params& p, const Ctx& c) {
  const int n = p.s.r[c.cl].n1;
  const int type = p.s.r[c.cl].slab >> 3, grp = p.s.r[c.cl].slab & 7;
  for (int i = 0; i < 2 * n; i++) {
    const int t = i >> 1, w = i & 1, b = w * 2 + 1;
    const int tile = p.s.r[c.cl].tile[t] & 63;
    mbar_wait(c.bar + (B_SF + b) * 8, t & 1);
    const uint32_t src = c.sm + SM_BUF + b * 16384;
    int f = (type ? F_Q : F_KV) + (tile & 31) * 8 + grp;
    if (type == 0) {
      const int prev = p.s.prev[tile & 31][grp];
      if (prev != 255 && w == 0) wait_kv_dead(c, prev, grp);
      uint8_t* dst = g_S + (size_t)(S_K + ((tile & 32) + p.s.slot[tile & 31][grp]) * 8 + grp) * 65536 + c.rank * 32768 + w * 8192;
      bulk_store(dst, src, 8192);
      bulk_store(dst + 16384, src + 8192, 8192);
    } else if (tile < 32) {
      const int dep = p.s.qdep[tile * 8 + grp];
      if (dep != 511 && w == 0) {
        if (dep < 256) wait_kv_dead(c, dep >> 3, dep & 7);
        else flag_wait<false>(F_TS + dep - 256, 128);
      }
      bulk_store(g_S + (size_t)p.s.qblk[tile * 8 + grp] * 65536 + (c.rank * 2 + w) * 16384, src, 16384);
    } else {
      tma3d_store(&p.map_t[2], src, (grp * 4 + c.rank * 2 + w) * 32, 0, (tile - 32) * 64);
      f = F_QKVA + grp * 4 + ((0xE4390900u >> (2 * (tile - 30))) & 3);
    }
    BULK_COMMIT();
    BULK_WAIT(0);
    mbar_arrive_one(c.bar + (B_SE + b) * 8);
    if (i == 2 * n - 1) return f;
    if (w) flag_add(f, 2);
  }
  return -1;
}

__device__ __forceinline__ int p2_buf(int w, int i) { return w * 2 + (i & 1); }
__device__ __forceinline__ int p2_blk(int rank, int w, int i) { return ((i ^ w) & 1) == 0 ? 3 - rank : rank; }

template <int N>
__device__ __forceinline__ void row_max(const float (&s)[N], float& m0, float& m1) {
  float a0 = fmaxf(s[0], s[1]), a1 = fmaxf(s[2], s[3]);
#pragma unroll
  for (int i = 1; i < N / 4; i++) {
    m0 = fmaxf(m0, s[4 * i]); a0 = fmaxf(a0, s[4 * i + 1]);
    m1 = fmaxf(m1, s[4 * i + 2]); a1 = fmaxf(a1, s[4 * i + 3]);
  }
  m0 = fmaxf(m0, a0); m1 = fmaxf(m1, a1);
  m0 = fmaxf(m0, __shfl_xor_sync(0xffffffffu, m0, 1));
  m1 = fmaxf(m1, __shfl_xor_sync(0xffffffffu, m1, 1));
  m0 = fmaxf(m0, __shfl_xor_sync(0xffffffffu, m0, 2));
  m1 = fmaxf(m1, __shfl_xor_sync(0xffffffffu, m1, 2));
}
template <bool SUB, int N>
__device__ __forceinline__ void row_exp(const float (&s)[N], uint32_t (&P)[32], float m0, float m1, float& t0, float& t1) {
  float u0 = 0.f, u1 = 0.f;
  t0 = t1 = 0.f;
#pragma unroll
  for (int i = 0; i < N / 4; i++) {
    const float e0 = ex2(SUB ? s[4 * i] - m0 : s[4 * i]), e1 = ex2(SUB ? s[4 * i + 1] - m0 : s[4 * i + 1]);
    const float e2 = ex2(SUB ? s[4 * i + 2] - m1 : s[4 * i + 2]), e3 = ex2(SUB ? s[4 * i + 3] - m1 : s[4 * i + 3]);
    if (i == 0) { t0 = e0; u0 = e1; t1 = e2; u1 = e3; }
    else { t0 += e0; u0 += e1; t1 += e2; u1 += e3; }
    P[2 * i] = pack_bf16(e0, e1);
    P[2 * i + 1] = pack_bf16(e2, e3);
  }
#pragma unroll
  for (int i = N / 2; i < 32; i++) P[i] = 0;
  pin(P);
  t0 += u0; t1 += u1;
}
template <int N>
__device__ __forceinline__ void causal_mask(float (&s)[N], int thr) {
#pragma unroll
  for (int i = 0; i < 8; i++) {
    if (8 * i > thr) s[N - 32 + 4 * i] = -INFINITY;
    if (8 * i + 1 > thr) s[N - 32 + 4 * i + 1] = -INFINITY;
    if (8 * i - 8 > thr) s[N - 32 + 4 * i + 2] = -INFINITY;
    if (8 * i - 7 > thr) s[N - 32 + 4 * i + 3] = -INFINITY;
  }
}
__device__ __forceinline__ void issue_qk(float (&s)[32], uint32_t qd, uint32_t kd) {
  WG_FENCE();
#pragma unroll
  for (int kk = 0; kk < 8; kk++) wgmma_ss64<0>(s, qd + (kk >> 2) * 512 + (kk & 3) * 2, kd + (kk >> 2) * 1024 + (kk & 3) * 2, kk != 0);
  WG_COMMIT();
}
__device__ __forceinline__ void issue_qk(float (&s)[64], uint32_t qd, uint32_t kd) {
  WG_FENCE();
#pragma unroll
  for (int kk = 0; kk < 8; kk++) wgmma_ss128<0>(s, qd + (kk >> 2) * 512 + (kk & 3) * 2, kd + (kk >> 2) * 1024 + (kk & 3) * 2, kk != 0);
  WG_COMMIT();
}
template <int NK>
__device__ __forceinline__ void issue_pv(float (&o)[64], const uint32_t (&P)[32], uint32_t vd, int acc) {
  WG_FENCE();
#pragma unroll
  for (int kk = 0; kk < NK; kk++) wgmma_rs128<1>(o, P[4 * kk], P[4 * kk + 1], P[4 * kk + 2], P[4 * kk + 3], vd + kk * 128, kk != 0 ? 1 : acc);
  WG_COMMIT();
}
__device__ __forceinline__ void stage_done(const Ctx& c, int b) {
  FENCE_ASYNC_SMEM();
  __syncwarp();
  if (c.lane == 0) mbar_arrive(c.bar + (B_SF + b) * 8);
}
__device__ __forceinline__ void p2_epilogue(const float (&o)[64], float s0, float s1, const Ctx& c, int b) {
  stage_tile(o, c.sm + SM_BUF + b * 16384, c, s0, s1);
  stage_done(c, b);
}

struct P2State {
  float m0, m1, l0, l1;
  bool shift;
  float e0, e1;
  int ks;
  int wi, ai;
  uint32_t wb, ab;
  uint32_t qd;
};
#define PROFZ()
__device__ __forceinline__ int wrap5(int q) { return q >= 5 ? q - 5 : q; }
__device__ __forceinline__ void turn_wait(uint32_t ring, int i) { mbar_wait(ring + (i & 3) * 8, (i >> 2) & 1); }
__device__ __forceinline__ void turn_pass(const Ctx& c, uint32_t ring, int i) { if (c.lane == 0) mbar_arrive(ring + (i & 3) * 8); }
__device__ __forceinline__ void p2_scales(P2State& z) {
  float l0 = z.l0, l1 = z.l1;
  l0 += __shfl_xor_sync(0xffffffffu, l0, 1);
  l1 += __shfl_xor_sync(0xffffffffu, l1, 1);
  l0 += __shfl_xor_sync(0xffffffffu, l0, 2);
  l1 += __shfl_xor_sync(0xffffffffu, l1, 2);
  asm("rcp.approx.ftz.f32 %0, %1;" : "=f"(z.e0) : "f"(l0));
  asm("rcp.approx.ftz.f32 %0, %1;" : "=f"(z.e1) : "f"(l1));
}
template <int N>
__device__ __forceinline__ void p2_first(const Ctx& c, P2State& z, float (&o)[64], uint32_t (&Pc)[32], uint32_t (&Pn)[32],
                                         int ks, int vs, int cnt, int acc) {
  float s[N] = {};
  issue_qk(s, z.qd, desc_lo(c.sm + SM_RING, 16) + ks * 2048);
  if (vs >= 0) {
    p2_scales(z);
    issue_pv<8>(o, Pc, desc_lo(c.sm + SM_RING, 16384) + vs * 2048, acc);
  } else {
    WG_COMMIT();
  }
  mbar_expect(z.ab + (z.ai++ & 3) * 8, cnt == 1 ? 8192 : 0);
  PROFZ();
  WG_WAIT(1);
  PROFZ();
  pin(s);
  release(c, B_P2E + ks, cnt);
  causal_mask(s, c.warp * 16 + (c.lane >> 2) - 2 * (c.lane & 3));
  z.m0 = z.m1 = 0.f;
  row_exp<false>(s, Pn, 0.f, 0.f, z.l0, z.l1);
  z.shift = __any_sync(0xffffffffu, !(z.l0 + z.l1 <= SM_HI) || ((c.lane & 3) == 0 && !(fminf(z.l0, z.l1) >= SM_LO)));
  if (__builtin_expect(z.shift, 0)) {
    z.m0 = z.m1 = -INFINITY;
    row_max(s, z.m0, z.m1);
    row_exp<true>(s, Pn, z.m0, z.m1, z.l0, z.l1);
  }
  WG_WAIT(0);
  pin(o);
  if (vs >= 0) release(c, B_P2E + vs, 1);
}

template <bool SECOND>
__device__ __forceinline__ void p2_turn(const Ctx& c, P2State& z, float (&o)[64], uint32_t (&Pc)[32], uint32_t (&Pn)[32],
                                        int eb = -1, bool half = false, int vcnt = 1) {
  float s[64] = {};
  const int ks = z.ks, vs = wrap5(ks + 1);
  PROFZ();
  turn_wait(z.wb, z.wi++);
  PROFZ();
  issue_qk(s, z.qd, desc_lo(c.sm + SM_RING, 16) + ks * 2048);
  const uint32_t vd = desc_lo(c.sm + SM_RING, 16384) + vs * 2048;
  if (SECOND) {
    if (eb >= 0) stage_tile(o, c.sm + SM_BUF + eb * 16384, c, z.e0, z.e1);
    if (half) issue_pv<4>(o, Pc, vd, 0); else issue_pv<8>(o, Pc, vd, 0);
  } else {
    issue_pv<8>(o, Pc, vd, 1);
  }
  turn_pass(c, z.ab, z.ai++);
  if (SECOND) { if (eb >= 0) stage_done(c, eb); }
  PROFZ();
  z.ks = wrap5(ks + 2);
  WG_WAIT(1);
  PROFZ();
  pin(s);
  release(c, B_P2E + ks, 1);
  float t0, t1, a0 = 1.f, a1 = 1.f;
  row_exp<false>(s, Pn, 0.f, 0.f, t0, t1);
  z.shift = __any_sync(0xffffffffu, z.shift || !(t0 + t1 <= SM_HI));
  const bool redo = z.shift;
  if (__builtin_expect(redo, 0)) {
    float n0 = z.m0, n1 = z.m1;
    row_max(s, n0, n1);
    a0 = ex2(z.m0 - n0); a1 = ex2(z.m1 - n1);
    z.m0 = n0; z.m1 = n1;
    z.l0 *= a0; z.l1 *= a1;
    row_exp<true>(s, Pn, z.m0, z.m1, t0, t1);
  }
  WG_WAIT(0);
  pin(o);
  release(c, B_P2E + vs, vcnt);
  if (__builtin_expect(redo, 0)) {
#pragma unroll
    for (int i = 0; i < 16; i++) { o[4 * i] *= a0; o[4 * i + 1] *= a0; o[4 * i + 2] *= a1; o[4 * i + 3] *= a1; }
  }
  z.l0 += t0; z.l1 += t1;
}
__device__ __forceinline__ void copy_p(uint32_t (&d)[32], const uint32_t (&s)[32], int zero) {
#pragma unroll
  for (int i = 0; i < 32; i++) asm volatile("add.s32 %0, %1, %2;" : "=r"(d[i]) : "r"(s[i]), "r"(zero));
}

__device__ __forceinline__ void p2_consumer(const Params& p, const Ctx& c, int rot) {
  const int nit = p.s.r[c.cl].n2;
  const uint32_t fring = c.bar + B_P2F * 8, oring = c.bar + B_ORD * 8;
  float o[64] = {};
  uint32_t Pa[32] = {}, Pb[32] = {};
  P2State z;
  z.e0 = z.e1 = z.l0 = z.l1 = 0.f; z.ks = rot; z.shift = false;
  int acc = 0, n = 0;
  for (int it = 0; it < nit; it++) {
    const int j = p.s.r[c.cl].item[it] & 7, blk = p2_blk(c.rank, c.wg, it);
    const int lng = ((it ^ c.wg) & 1) ^ 1;
    z.qd = desc_lo(c.sm + SM_BUF, 16) + p2_buf(c.wg, it) * 1024;
    if (lng) { z.wb = oring; z.wi = n - it; z.ab = fring; z.ai = n + 1; }
    else { z.wb = fring; z.wi = n + 2; z.ab = oring; z.ai = n - it; }
    PROFZ();
    mbar_wait(c.bar + (B_QF + p2_buf(c.wg, it)) * 8, (it >> 1) & 1);
    turn_wait(fring, n + 1 - lng);
    PROFZ();
    const int vs = it ? wrap5(z.ks + 1) : -1, ks = lng ? z.ks : wrap5(z.ks + (it ? 2 : 1));
    if (blk & 1) p2_first<64>(c, z, o, Pa, Pb, ks, vs, 1 + lng, acc);
    else p2_first<32>(c, z, o, Pa, Pb, ks, vs, 1 + lng, acc);
    z.ks = wrap5(ks + (it == 0 && lng ? 1 : 2));
    PROF(c.wg, 24 + it);
    n += 2 * j + 2;
    int left = 2 * j + lng;
    acc = left != 0;
    if (left == 0) { copy_p(Pa, Pb, p.zero); continue; }
    p2_turn<true>(c, z, o, Pb, Pa, it > 0 ? p2_buf(c.wg, it - 1) : -1, !(blk & 1), 1 + lng);
    while (--left > 0) {
      p2_turn<false>(c, z, o, Pa, Pb);
      if (--left == 0) { copy_p(Pa, Pb, p.zero); break; }
      p2_turn<false>(c, z, o, Pb, Pa);
    }
  }
  {
    if (!acc && nit > 1) p2_epilogue(o, z.e0, z.e1, c, p2_buf(c.wg, nit));
    turn_wait(z.wb, z.wi);
    issue_pv<8>(o, Pa, desc_lo(c.sm + SM_RING, 16384) + z.ks * 2048, acc);
    if (((nit - 1) ^ c.wg) & 1) turn_pass(c, z.ab, z.ai);
    p2_scales(z);
    WG_WAIT(0);
    pin(o);
    release(c, B_P2E + z.ks);
    p2_epilogue(o, z.e0, z.e1, c, p2_buf(c.wg, nit - 1));
    PROF(c.wg, 24 + nit);
  }
}

__device__ __forceinline__ void p2_load_q(const Params& p, const Ctx& c, int it, int w) {
  const int item = p.s.r[c.cl].item[it], b = p2_buf(w, it);
  mbar_expect(c.bar + (B_QF + b) * 8, 16384);
  bulk_load(c.sm + SM_BUF + b * 16384, g_S + (size_t)p.s.qblk[item] * 65536 + p2_blk(c.rank, w, it) * 16384, 16384, c.bar + (B_QF + b) * 8, POL(4));
}
__device__ __forceinline__ void wait_p1_free(const Ctx& c, int u1, int s) {
  mbar_wait(c.bar + (B_P1E + 2 * s) * 8, ((u1 - 1 - 2 * s) / 10) & 1);
  mbar_wait(c.bar + (B_P1E + 2 * s + 1) * 8, ((u1 - 2 - 2 * s) / 10) & 1);
}
__device__ __forceinline__ void p2_producer(const Params& p, const Ctx& c, int u1, int rot) {
  const int nit = p.s.r[c.cl].n2;
  int slot = rot, cnt = 0, par = 1, n = 0;
  const uint8_t* pv = nullptr;
  bool pl = false;
  auto load = [&](const uint8_t* src, int expect, uint32_t fb, bool last) {
    if (cnt < 5) {
      if (u1) {
        wait_p1_free(c, u1, slot);
        if (cnt == 0) p2_load_q(p, c, 0, 1);
      }
      cnt++;
    } else {
      if (slot == rot) par ^= 1;
      mbar_wait(c.bar + (B_P2E + slot) * 8, par);
    }
    if (expect) mbar_expect(fb, expect);
    bulk_load_mc(c.sm + SM_RING + slot * 32768 + c.rank * 16384, src, 16384, fb, last ? POL(5) : L2_NORMAL);
    slot = wrap5(slot + 1);
  };
  for (int it = 0; it < nit; it++) {
    const int item = p.s.r[c.cl].item[it], h = item >> 3, j = item & 7;
    if (it == 1 && (c.phases & 16) && p.s.r[c.cl].n1 < 8) flag_wait<true>(F_GATE, 256);
    uint32_t ready = (c.phases & 16) ? 0u : 255u;
    if (it == 0) { if (c.phases & 16) flag_wait<false>(F_Q + item, 4); mbar_wait(c.bar + B_LAD * 8, 0); p2_load_q(p, c, 0, 0); if (!u1) p2_load_q(p, c, 0, 1); }
    for (int t = 2 * j + 1; t >= 0; t--) {
      mask_wait(ready, t >> 1, F_KV + h * 8 + (c.lane & 7), 8);
      const uint8_t* k = g_S + (size_t)(2 * S_K + p.s.slot[h][t >> 1] * 16 + t) * 32768 + c.rank * 16384;
      const uint32_t fb = c.bar + (B_P2F + (n & 3)) * 8;
      const bool last = (p.s.r[c.cl].last[it] >> (t >> 1)) & 1;
      load(k, pv && t != 2 * j ? 65536 : 32768, fb, last);
      if (!(t & 1) && t + 4 <= 2 * j && c.rank == 0) flag_add_rx(F_RD + h * 8 + (t >> 1) + 2);
      if (pv) load(pv, 0, t != 2 * j ? fb : c.bar + (B_ORD + ((n - 1 - it) & 3)) * 8, pl);
      pl = last;
      pv = k + (size_t)NH * 16 * 32768;
      n++;
    }
  }
  load(pv, 32768, c.bar + (B_P2F + (n & 3)) * 8, pl);
}

__device__ __forceinline__ void publish_and_load_q(const Params& p, const Ctx& c, int f, int it, int seen) {
  const bool want = it < p.s.r[c.cl].n2, early = want && __all_sync(0xffffffffu, seen >= 4);
  if (early) { p2_load_q(p, c, it, it & 1); p2_load_q(p, c, it, (it & 1) ^ 1); }
  if (f >= 0) flag_add(f, 2);
  if (want && !early) {
    if (c.phases & 16) flag_wait<false>(F_Q + p.s.r[c.cl].item[it], 4);
    p2_load_q(p, c, it, it & 1); p2_load_q(p, c, it, (it & 1) ^ 1);
  }
}
__device__ __forceinline__ void p2_storer(const Params& p, const Ctx& c, int sfpar) {
  const int nit = p.s.r[c.cl].n2;
  int held = -1;
  for (int i = 0; i < 2 * nit; i++) {
    const int it = i >> 1, w = (it ^ i ^ 1) & 1, b = p2_buf(w, it);
    const int item = p.s.r[c.cl].item[it], h = item >> 3, j = item & 7;
    mbar_wait(c.bar + (B_SF + b) * 8, (sfpar >> b) & 1);
    sfpar ^= 1 << b;
    bulk_store(g_S + (size_t)p.s.qblk[item] * 65536 + p2_blk(c.rank, w, it) * 16384, c.sm + SM_BUF + b * 16384, 16384, POL(1));
    BULK_COMMIT();
    if (i & 1) {
      if (it + 2 == nit && (p.s.r[c.cl].item[it + 1] & 7) == 0) { held = F_CTX + j * 64 + h; continue; }
      const int seen = flag_peek(F_Q + p.s.r[c.cl].item[min(it + 2, nit - 1)]);
      BULK_WAIT(0);
      if (it + 1 == nit) release(c, B_DONE);
      publish_and_load_q(p, c, F_CTX + j * 64 + h, it + 2, seen);
    }
  }
  if (held >= 0) flag_add_rx(held, 2);
}

__device__ __forceinline__ int p3_pos(int i, int x) { return i < 4 ? (i + x) & 3 : 4; }
__device__ __forceinline__ void p3_consumer(const Params& p, const Ctx& c, int x) {
  const bool first = p.s.r[c.cl].p3 >= 24;
  const int tile = p.s.r[c.cl].p3 - (first ? 24 : 0), j = tile / 3, nt = tile - 3 * j;
  const int na = first ? 9 : 0, nb = p.s.task[c.cl][1] - p.s.task[c.cl][0];
  const uint32_t ad = desc_lo(c.sm + SM_RING + c.wg * 8192, 16), bd = desc_lo(c.sm + SM_RING + 16384, 4096);
  float acc[96] = {};
  int slot = 0, par = 0, prev = 0;
  float g0 = 0.f, g1 = 0.f;
  const int hold = c.wg && LAG ? na + nb - LAG : -1, pass = c.wg || !LAG ? -1 : na + nb - 1;
  const float* gp = g_gate + j * 256 + c.rank * 128 + c.wg * 64 + c.warp * 16 + (c.lane >> 2);
#pragma unroll 1
  for (int kb = 0; kb < na; kb++) {
    if (kb == hold) bar_sync(6, 256);
    mbar_wait(c.bar + (B_P3F + slot) * 8, par);
    if (kb == 0) PROF(c.wg, 39);
    WG_FENCE();
#pragma unroll
    for (int kk = 0; kk < 4; kk++) wgmma_ss192<1, 1>(acc, ad + p3_pos(slot, x) * 2560 + kk * 128, bd + p3_pos(slot, x) * 2560 + (kk >> 1) * 768 + (kk & 1) * 128, kk != 0 ? 1 : kb != 0);
    WG_COMMIT();
    if (kb == pass) bar_arrive(6, 256);
    WG_WAIT(1);
    if (kb > 0) release(c, B_P3E + prev);
    else { g0 = __ldcg(gp); g1 = __ldcg(gp + 8); }
    prev = slot;
    if (++slot == 5) { slot = 0; par ^= 1; }
  }
#pragma unroll 1
  for (int kb = na; kb < na + nb; kb++) {
    if (kb == hold) bar_sync(6, 256);
    mbar_wait(c.bar + (B_P3F + slot) * 8, par);
    if (kb == 0) PROF(c.wg, 39);
    WG_FENCE();
#pragma unroll
    for (int kk = 0; kk < 4; kk++) wgmma_ss192<1>(acc, ad + p3_pos(slot, x) * 2560 + kk * 2, bd + p3_pos(slot, x) * 2560 + (kk >> 1) * 768 + (kk & 1) * 128, kk != 0 ? 1 : kb != 0);
    WG_COMMIT();
    if (kb == pass) bar_arrive(6, 256);
    WG_WAIT(1);
    if (kb > 0) release(c, B_P3E + prev);
    else { g0 = __ldcg(gp); g1 = __ldcg(gp + 8); }
    prev = slot;
    if (++slot == 5) { slot = 0; par ^= 1; }
  }
  g0 = __fdividef(1.f, 1.f + g0); g1 = __fdividef(1.f, 1.f + g1);
  WG_WAIT(0);
  pin(acc);
  PROF(c.wg, 40);
  if (first) bar_sync(4 + c.wg, 128);
  mbar_wait(c.bar + B_OUT * 8, 0);
  const int row = (c.lane & 7) + ((c.lane >> 3) & 1) * 8;
  const uint32_t wbase = c.sm + SM_RING + c.wg * 8192 + c.warp * 2048;
  const uint32_t base = wbase + row * 128 + (((c.lane >> 4) ^ (row & 7)) << 4);
#pragma unroll
  for (int i = 0; i < 12; i++) {
    stsm4((base ^ ((i & 3) << 5)) + (i >> 2) * 40960, pack_bf16(acc[8 * i] * g0, acc[8 * i + 1] * g0), pack_bf16(acc[8 * i + 2] * g1, acc[8 * i + 3] * g1),
          pack_bf16(acc[8 * i + 4] * g0, acc[8 * i + 5] * g0), pack_bf16(acc[8 * i + 6] * g1, acc[8 * i + 7] * g1));
    if ((i & 3) == 3) {
      FENCE_ASYNC_SMEM();
      bar_sync(4 + c.wg, 128);
      if (c.warp == (i >> 2)) tma2d_add(&p.map_out, c.sm + SM_RING + c.wg * 8192 + c.warp * 40960, nt * 192 + c.warp * 64, j * 256 + c.rank * 128 + c.wg * 64);
    }
  }
  BULK_COMMIT();
  PROF(c.wg, 43);
  BULK_WAIT_READ(0);
  PROF(c.wg, 44);
}

__device__ __forceinline__ void p3_producer(const Params& p, const Ctx& c, int u1, int u2, int rot, int x) {
  const bool first = p.s.r[c.cl].p3 >= 24;
  const int tile = p.s.r[c.cl].p3 - (first ? 24 : 0), j = tile / 3, nt = tile - 3 * j;
  int slot = 0, par = 1, cnt = 0;
  auto wait_free = [&](int s) {
    const int f = wrap5(s + 5 - rot);
    if (f < u2) mbar_wait(c.bar + (B_P2E + s) * 8, ((u2 - 1 - f) / 5) & 1);
    else if (u1) wait_p1_free(c, u1, s);
  };
  asm volatile(ELECT("prefetch.tensormap [%0];") ::"l"(&p.map_o[0]) : "memory");
  asm volatile(ELECT("prefetch.tensormap [%0];") ::"l"(&p.map_out) : "memory");
  if ((c.phases & 16) && p.s.r[c.cl].n1 < 8 && p.s.r[c.cl].n2 < 2) flag_wait<true>(F_GATE, 256);
  uint32_t ready = (c.phases & 16) ? 0u : ~0u;
  const int q0 = p.s.task[c.cl][0], q1 = p.s.task[c.cl][1];
  for (int q = q0 - (first ? 9 : 0); q < q1; q++) {
    const bool brA = q < q0;
    const int kb = brA ? q - q0 + 9 : p.s.p3_order[tile][q];
    if (!brA) mask_wait(ready, kb >> 1, F_CTX + j * 64 + c.lane, 4);
    else if (kb == 0 && (c.phases & 16)) flag_wait<false>(F_CTX + j * 64 + 32, 16);
    const uint8_t* a = brA ? g_oA + (j * 4 + c.rank * 2) * 73728 + kb * 8192 : g_S + (size_t)p.s.qblk[(kb >> 1) * 8 + j] * 65536 + c.rank * 32768 + (kb & 1) * 8192;
    const uint32_t st = c.sm + SM_RING + p3_pos(slot, x) * 40960, fb = c.bar + (B_P3F + slot) * 8;
    if (cnt < 4) { wait_free(p3_pos(cnt, x)); wait_free(p3_pos(cnt, x) + 1); }
    else if (cnt == 4) mbar_wait(c.bar + B_DONE * 8, 0);
    else mbar_wait(c.bar + (B_P3E + slot) * 8, par);
    cnt++;
    mbar_expect(fb, 40960);
    bulk_load(st, a, 8192, fb, POL(3));
    bulk_load(st + 8192, a + (brA ? 73728 : 16384), 8192, fb, POL(3));
    tma3d_mc(st + 16384 + c.rank * 12288, &p.map_o[brA], 0, kb * 64 + c.rank * 32, nt * 3, fb);
    if (++slot == 5) { slot = 0; par ^= 1; }
  }
}

__device__ __forceinline__ float bf_lo(uint32_t w) { return __uint_as_float(w << 16); }
__device__ __forceinline__ float bf_hi(uint32_t w) { return __uint_as_float(w & 0xffff0000u); }

__device__ __forceinline__ void gate_rows(const Params& p, int row0, int lane) {
  const uint4* x = reinterpret_cast<const uint4*>(p.x + (size_t)(row0 + (lane >> 2)) * DM) + (lane & 3);
  const uint4* w = reinterpret_cast<const uint4*>(p.gate_w) + (lane & 3);
  float a = 0.f;
#pragma unroll 1
  for (int b = 0; b < 3; b++) {
    uint4 u[6];
#pragma unroll
    for (int i = 0; i < 6; i++) u[i] = __ldg(x + (b * 6 + i) * 4);
#pragma unroll
    for (int i = 0; i < 6; i++) {
      const uint4 v = __ldg(w + (b * 6 + i) * 4);
      a = fmaf(bf_lo(u[i].x), bf_lo(v.x), a); a = fmaf(bf_hi(u[i].x), bf_hi(v.x), a);
      a = fmaf(bf_lo(u[i].y), bf_lo(v.y), a); a = fmaf(bf_hi(u[i].y), bf_hi(v.y), a);
      a = fmaf(bf_lo(u[i].z), bf_lo(v.z), a); a = fmaf(bf_hi(u[i].z), bf_hi(v.z), a);
      a = fmaf(bf_lo(u[i].w), bf_lo(v.w), a); a = fmaf(bf_hi(u[i].w), bf_hi(v.w), a);
    }
  }
  a += __shfl_xor_sync(0xffffffffu, a, 1);
  a += __shfl_xor_sync(0xffffffffu, a, 2);
  if ((lane & 3) == 0) g_gate[row0 + (lane >> 2)] = __expf(fminf(a, 60.f));
}

__device__ __forceinline__ void lds10(uint32_t (&k)[10], uint32_t a) {
  asm volatile("ld.shared.v2.u32 {%0, %1}, [%10];\nld.shared.v2.u32 {%2, %3}, [%10+8];\nld.shared.v2.u32 {%4, %5}, [%10+16];\n"
               "ld.shared.v2.u32 {%6, %7}, [%10+24];\nld.shared.v2.u32 {%8, %9}, [%10+32];"
               : "=r"(k[0]), "=r"(k[1]), "=r"(k[2]), "=r"(k[3]), "=r"(k[4]), "=r"(k[5]), "=r"(k[6]), "=r"(k[7]), "=r"(k[8]), "=r"(k[9]) : "r"(a));
}
__device__ __forceinline__ void local_attn(const Params& p, const Ctx& c, int rb, int hs) {
  const int lane = c.lane, grp = rb >> 2, par = lane >> 4, i0 = 2 * (lane & 15);
  const uint32_t buf = c.sm + SM_BUF + (c.warp - 2) * 8192, bqk = c.bar + (B_LA + (c.warp - 2) * 2) * 8, bv = bqk + 8;
  const uint32_t mine = buf + 2304 + par * 160 + i0 * 4;
  const bool flags = c.phases & 16;
  auto fetch_qk = [&](int i) {
    if (flags && !(i & 1)) {
      const int q = i >> 1;
      const int tgt = q == 0 ? 24 : q == 3 ? 8 : 12;
      flag_wait<false>(F_QKVA + (grp - (grp > 0 && (rb & 3) == 0 ? par : 0)) * 4 + q, tgt);
    }
    mbar_expect(bqk, 5184);
    tma3d(buf, &p.map_t[0], rb * 32, 0, 9 * (4 * i + hs), bqk, POL(2));
    tma3d(buf + 2304, &p.map_t[1], rb * 32 - 8, 0, 288 + 9 * (4 * i + hs), bqk, POL(2));
  };
  auto fetch_v = [&](int i) { mbar_expect(bv, 2880); tma3d(buf + 5248, &p.map_t[1], rb * 32 - 8, 0, 576 + 9 * (4 * i + hs), bv, POL(2)); };
  fetch_qk(0);
  if (flags) flag_wait<true>(F_GATE, 256);
#pragma unroll 1
  for (int q = 0; q < 8; q++) {
    fetch_v(q);
    float a[8], b[8];
#pragma unroll
    for (int w = 0; w < 8; w++) a[w] = b[w] = 0.f;
    mbar_wait(bqk, q & 1);
    PROFB(1 + 2 * q);
#pragma unroll 1
    for (int j = 0; j < 9; j++) {
      uint32_t x, y, k[10];
      asm volatile("ld.shared.v2.u32 {%0, %1}, [%2];" : "=r"(x), "=r"(y) : "r"(buf + lane * 8 + j * 256));
      lds10(k, mine + j * 320);
      const float xl = bf_lo(x), xh = bf_hi(x), yl = bf_lo(y), yh = bf_hi(y);
#pragma unroll
      for (int m = 1; m < 10; m++) {
        const float kl = bf_lo(k[m]), kh = bf_hi(k[m]);
        if (m < 9) a[8 - m] = fmaf(xl, kl, fmaf(xh, kh, a[8 - m]));
        if (m > 1) b[9 - m] = fmaf(yl, kl, fmaf(yh, kh, b[9 - m]));
      }
    }
    __syncwarp();
    mbar_wait(bv, q & 1);
    if (q & 1) flag_add_rx(F_TS + (q >> 1));
    if (q < 7) fetch_qk(q + 1);
    constexpr float SC = 0.23570226039551584f * 1.4426950408889634f;
    const float* gp = g_gate + rb * 64 + 2 * i0 + par;
    const float ga = __ldcg(gp), gb = __ldcg(gp + 2);
    float ma = a[0], mb = b[0];
#pragma unroll
    for (int w = 1; w < 8; w++) {
      if (rb == 0) {
        if (i0 < w) a[w] = -INFINITY;
        if (i0 + 1 < w) b[w] = -INFINITY;
      }
      ma = fmaxf(ma, a[w]); mb = fmaxf(mb, b[w]);
    }
    float la = 0.f, lb = 0.f;
#pragma unroll
    for (int w = 0; w < 8; w++) {
      a[w] = ex2((a[w] - ma) * SC); b[w] = ex2((b[w] - mb) * SC);
      la += a[w]; lb += b[w];
    }
    la = __fdividef(ga, la); lb = __fdividef(gb, lb);
#pragma unroll
    for (int w = 0; w < 8; w++) { a[w] *= la; b[w] *= lb; }
    uint8_t* dst = g_oA + rb * 73728 + ((i0 & 2) + par) * 4;
#pragma unroll 1
    for (int j = 0; j < 9; j++) {
      uint32_t v[10];
      lds10(v, mine + 2944 + j * 320);
      float a0 = 0.f, a1 = 0.f, b0 = 0.f, b1 = 0.f;
#pragma unroll
      for (int m = 1; m < 10; m++) {
        const float vl = bf_lo(v[m]), vh = bf_hi(v[m]);
        if (m < 9) { a0 = fmaf(a[8 - m], vl, a0); a1 = fmaf(a[8 - m], vh, a1); }
        if (m > 1) { b0 = fmaf(b[9 - m], vl, b0); b1 = fmaf(b[9 - m], vh, b1); }
      }
      const uint32_t wa = pack_bf16(a0, a1), wb = pack_bf16(b0, b1);
      const uint32_t got = __shfl_xor_sync(0xffffffffu, par ? wa : wb, 16);
      const uint32_t r0 = par ? got : wa, r1 = par ? wb : got;
      const int col = 18 * (4 * q + hs) + 2 * j, o = col * 128 + ((((i0 >> 2) ^ col) & 7) << 4);
      *reinterpret_cast<uint32_t*>(dst + o) = __byte_perm(r0, r1, 0x5410);
      *reinterpret_cast<uint32_t*>(dst + ((o + 128) ^ 16)) = __byte_perm(r0, r1, 0x7632);
    }
    __syncwarp();
    PROFB(2 + 2 * q);
  }
  mbar_arrive_one(c.bar + B_LAD * 8);
  flag_add(F_CTX + grp * 64 + 32);
}

__global__ void __cluster_dims__(2, 1, 1) __launch_bounds__(384, 1) fused_kernel(const __grid_constant__ Params p) {
  extern __shared__ uint8_t smem_raw[];
  Ctx c;
  c.sm = ((uint32_t)__cvta_generic_to_shared(smem_raw) + 1023u) & ~1023u;
  c.bar = c.sm + SM_BAR;
  c.lane = threadIdx.x & 31;
  const int wid = __shfl_sync(0xffffffffu, threadIdx.x >> 5, 0);
  if (wid < 6) asm volatile("prefetch.tensormap [%0];" ::"l"(&p.map_a[0] + wid) : "memory");
  c.wg = wid >> 2;
  c.warp = wid & 3;
  PROF(c.wg, 0);
  PROFG(61);
  c.cl = (blockIdx.x + (wid >> 4)) >> 1;
  c.rank = blockIdx.x & 1;
  c.rbar = mapa(c.bar, c.lane & 1);
  {
    const int w = wid, cnt = (((int)(B_CNT >> (4 * w)) - 1) & 15) + 1;
    if (w < 11) {
#pragma unroll
      for (int i = 0; i < 8; i++) asm volatile("mbarrier.init.shared::cta.b64 [%0], %1;" ::"r"(c.bar + w * 64 + i * 8), "r"(cnt));
    }
    asm volatile("fence.mbarrier_init.release.cluster;" ::: "memory");
  }
  if (c.wg == 2) PROF(2, 56);
  asm volatile("barrier.cluster.arrive.relaxed;" ::: "memory");
  c.phases = p.s.r[c.cl].phases;
  const bool do1 = p.s.r[c.cl].n1 > 0, do2 = p.s.r[c.cl].n2 > 0, do3 = p.s.r[c.cl].p3 != 255;
  if (do1 && c.wg == 2 && c.warp == 0) {
    const int type = p.s.r[c.cl].slab >> 3;
    PROF(2, 57);
    FENCE_ASYNC_SMEM();
    mbar_expect(c.bar + B_P1F * 8, type ? 32768 : 16384);
    tma2d(type ? c.sm + SM_BUF + 32768 : c.sm + SM_RING, &p.map_a[type], type ? 512 : 0, (p.s.r[c.cl].slab & 7) * 256 + c.rank * 128, c.bar + B_P1F * 8);
    PROF(2, 58);
  }
  asm volatile("barrier.cluster.wait.acquire;" ::: "memory");
  if (c.wg == 2) PROF(2, 59);
  if (do1 && c.wg == 2 && c.warp == 0) {
    const int type = p.s.r[c.cl].slab >> 3, tile = p.s.r[c.cl].tile[0] & 63;
    const CUtensorMap* m = &p.map_w[type * 2 + (tile >> 5)];
#pragma unroll 1
    for (int s = 1 - type; s < NPRO; s++) {
      const int kb = (s - type) >> 1;
      const uint32_t fb = c.bar + (B_P1F + s) * 8;
      if (s) mbar_expect(fb, 16384);
      if ((s ^ type) & 1) tma2d_mc(c.sm + SM_RING + s * 16384 + c.rank * 8192, m, (tile & 31) * 128 + c.rank * 64, kb < 0 ? 512 : kb * 64, fb);
      else tma2d(c.sm + SM_RING + s * 16384, &p.map_a[type], kb * 64, (p.s.r[c.cl].slab & 7) * 256 + c.rank * 128, fb);
    }
  }

  if (c.wg < 2) {
    PROF(c.wg, 4);
    asm volatile("setmaxnreg.inc.sync.aligned.u32 224;");
    if (c.wg == 1) {
      if (do1) bar_arrive(ORDER, 256);
      if (c.lane == 0) mbar_arrive(c.bar + B_P2F * 8);
    }
    PL(0);
    if (do1) p1_consumer(p, c);
    PL(1);
    if (do2) p2_consumer(p, c, p.s.r[c.cl].rot);
    PL(2);
    if (do3) p3_consumer(p, c, p.s.r[c.cl].x3);
    PL(3);
    PROF(c.wg, 63);
    PROFG(62);
    if (c.lane == 0) mbar_arrive(c.bar + B_FIN * 8);
    __syncwarp();
    cluster_sync();
  } else {
    asm volatile("setmaxnreg.dec.sync.aligned.u32 56;");
    if (c.warp == 0) {
      PROF(2, 60);
      if (do1) p1_producer(p, c);
      if (do2) p2_producer(p, c, p.s.r[c.cl].u1, p.s.r[c.cl].rot);
      if (do3) p3_producer(p, c, p.s.r[c.cl].u1, p.s.r[c.cl].u2, p.s.r[c.cl].rot, p.s.r[c.cl].x3);
    } else if (c.warp == 1) {
      const int f = do1 ? p1_storer(p, c) : -1;
      if (do2) {
        publish_and_load_q(p, c, f, 1, flag_peek(F_Q + p.s.r[c.cl].item[1]));
        p2_storer(p, c, (p.s.r[c.cl].n1 & 1) * 10);
      } else {
        const bool idle = mbar_test(c.bar + B_LAD * 8, 0);
        if (idle) release(c, B_DONE);
        if (f >= 0) flag_add(f, 2);
        if (!idle) { mbar_wait(c.bar + B_LAD * 8, 0); release(c, B_DONE); }
      }
      if (do3) {
        const int tile = p.s.r[c.cl].p3 % 24;
        if (p.s.task[c.cl][1] == 64) {
          for (int r = 0; r < (64 - p.s.task[c.cl][0] - ZLEAD) / 5; r++) mbar_wait(c.bar + B_P3F * 8, r & 1);
          const int j = tile / 3, nt = tile - 3 * j;
          uint4* o = reinterpret_cast<uint4*>(p.out + (size_t)(j * 256 + c.rank * 128 + (c.lane >> 3)) * DM + nt * 192) + (c.lane & 7);
#pragma unroll 4
          for (int r = 0; r < 32; r++) o[r * 288] = o[r * 288 + 8] = o[r * 288 + 16] = make_uint4(0u, 0u, 0u, 0u);
          __syncwarp();
          flag_add(F_OUT + tile * 2 + c.rank);
        } else if (c.phases & 16) {
          flag_wait<false, 256>(F_OUT + tile * 2 + c.rank, 1);
        }
        mbar_arrive_one(c.bar + B_OUT * 8);
      }
    } else {
      const int bw = blockIdx.x * 2 + (c.warp - 2);
      if ((c.phases & 1) && bw < 256) {
        gate_rows(p, bw * 8, c.lane);
        __syncwarp();
        flag_add(F_GATE);
      }
      if (p.s.r[c.cl].bg != 255) local_attn(p, c, p.s.r[c.cl].bg, bw & 3);
      else if (c.lane == 0) mbar_arrive(c.bar + B_LAD * 8);
    }
    __syncwarp();
    bar_sync(3, 128);
    if (c.warp == 0 && (c.phases & 32)) {
      int last = 0;
      if (c.lane == 0) { __threadfence(); last = atomicAdd(g_flags + F_DONE, 1) == 2 * NCL - 1; }
      if (__shfl_sync(0xffffffffu, last, 0)) for (int i = c.lane; i < F_NUM; i += 32) g_flags[i] = 0;
    }
    if (c.warp == 1) mbar_wait(c.bar + B_FIN * 8, 0);
    __syncwarp();
    cluster_sync();
  }
}

SCHED_DECL Sched k_sched = {
  {{0,29,2,35,0,{200,242,0,0,0,0,0,0,0,0,0},{0,0,0,0,0,0,0,0,0,0,0},{70,105,8,226,192,49,44,231,225,234,54,235,53,242,240,51,47,46,244,237,248,250,60,62,249,63,253,247,251,0}},
   {1,29,1,20,1,{236,0,0,0,0,0,0,0,0,0,0},{31,0,0,0,0,0,0,0,0,0,0},{68,105,66,232,192,108,241,231,225,234,54,235,53,242,240,46,243,239,244,237,248,250,60,62,249,61,63,247,251,0}},
   {2,29,1,12,2,{188,0,0,0,0,0,0,0,0,0,0},{0,0,0,0,0,0,0,0,0,0,0},{68,227,201,226,192,49,39,33,236,234,43,246,50,245,240,51,47,52,46,237,248,250,57,252,254,55,253,255,251,0}},
   {3,29,2,14,3,{248,187,0,0,0,0,0,0,0,0,0},{0,0,0,0,0,0,0,0,0,0,0},{70,104,201,226,192,49,33,231,236,234,43,246,50,245,240,51,47,52,45,238,248,250,57,252,254,61,63,247,251,0}},
   {4,28,1,24,4,{228,0,0,0,0,0,0,0,0,0,0},{0,0,0,0,0,0,0,0,0,0,0},{70,35,9,40,197,224,1,39,10,11,22,21,16,210,19,15,20,13,14,24,26,25,28,30,29,31,23,27,0,0}},
   {5,27,0,17,5,{0,0,0,0,0,0,0,0,0,0,0},{0,0,0,0,0,0,0,0,0,0,0},{131,36,9,40,5,32,7,33,10,43,21,18,16,19,15,14,20,13,24,26,25,28,30,29,31,23,27,0,0,0}},
   {6,26,0,9,6,{0,0,0,0,0,0,0,0,0,0,0},{0,0,0,0,0,0,0,0,0,0,0},{99,105,8,34,0,49,7,44,11,54,18,16,19,15,20,14,13,24,26,25,28,30,29,31,23,27,0,0,0,0}},
   {7,25,0,7,7,{0,0,0,0,0,0,0,0,0,0,0},{0,0,0,0,0,0,0,0,0,0,0},{131,6,8,69,81,71,44,75,118,82,80,83,79,84,78,77,88,90,89,92,94,93,95,87,91,0,0,0,0,0}},
   {0,29,1,37,8,{227,0,0,0,0,0,0,0,0,0,0},{0,0,0,0,0,0,0,0,0,0,0},{131,38,4,40,5,32,12,7,193,10,22,203,21,18,16,19,15,14,212,205,24,26,28,30,217,31,221,23,27,0}},
   {1,29,2,22,9,{233,218,0,0,0,0,0,0,0,0,0},{0,0,0,0,0,0,0,0,0,0,0},{131,36,198,34,5,32,209,7,1,10,22,11,21,18,16,14,211,207,20,13,24,26,28,30,25,29,31,23,27,0}},
   {2,29,2,32,10,{201,250,0,0,0,0,0,0,0,0,0},{0,0,0,0,0,0,0,0,0,0,0},{70,36,8,41,5,32,7,1,12,10,11,22,18,21,16,19,15,20,14,13,24,26,25,28,30,23,29,223,27,0}},
   {3,29,1,28,11,{243,0,0,0,0,0,0,0,0,0,0},{0,0,0,0,0,0,0,0,0,0,0},{131,38,196,233,5,32,1,199,204,202,11,214,18,213,208,19,15,20,13,206,216,218,25,220,222,29,31,215,219,0}},
   {4,28,0,16,12,{0,0,0,0,0,0,0,0,0,0,0},{0,0,0,0,0,0,0,0,0,0,0},{102,4,41,194,229,17,33,12,42,43,54,53,48,50,51,47,52,45,46,56,58,57,60,62,61,63,55,59,0,0}},
   {5,27,0,20,13,{0,0,0,0,0,0,0,0,0,0,0},{0,0,0,0,0,0,0,0,0,0,0},{99,6,41,2,37,17,39,12,42,22,53,50,48,51,47,46,52,45,56,58,57,60,62,61,63,55,59,0,0,0}},
   {6,26,0,18,14,{0,0,0,0,0,0,0,0,0,0,0},{0,0,0,0,0,0,0,0,0,0,0},{68,6,40,69,32,1,39,10,43,21,50,48,51,47,52,46,45,56,58,57,60,62,61,63,55,59,0,0,0,0}},
   {7,25,0,19,15,{0,0,0,0,0,0,0,0,0,0,0},{0,0,0,0,0,0,0,0,0,0,0},{99,38,40,101,113,103,74,107,85,114,112,115,111,116,110,109,120,122,121,124,126,125,127,119,123,0,0,0,0,0}},
   {0,6,6,4,255,{32,47,138,181,163,240,0,0,0,0,0},{0,0,0,0,0,0,0,0,0,0,0},{99,73,36,2,37,17,0,0,0,0,0,0,0,0,0,0,0,0,0,0,0,0,0,0,0,0,0,0,0,0}},
   {1,6,6,10,255,{64,46,13,145,164,208,0,0,0,0,0},{0,0,0,0,0,0,0,0,0,0,0},{99,73,230,200,37,76,0,0,0,0,0,0,0,0,0,0,0,0,0,0,0,0,0,0,0,0,0,0,0,0}},
   {2,6,7,43,255,{76,41,60,82,148,214,185,0,0,0,0},{0,0,0,0,0,127,0,0,0,0,0},{102,195,40,2,37,17,0,0,0,0,0,0,0,0,0,0,0,0,0,0,0,0,0,0,0,0,0,0,0,0}},
   {3,6,5,36,255,{16,69,95,166,190,0,0,0,0,0,0},{0,0,0,127,0,0,0,0,0,0,0},{99,72,228,2,37,17,0,0,0,0,0,0,0,0,0,0,0,0,0,0,0,0,0,0,0,0,0,0,0,0}},
   {4,8,5,14,255,{40,6,99,129,165,0,0,0,0,0,0},{0,0,0,0,0,0,0,0,0,0,0},{131,36,8,34,0,49,7,44,0,0,0,0,0,0,0,0,0,0,0,0,0,0,0,0,0,0,0,0,0,0}},
   {5,10,5,45,255,{136,43,85,157,191,0,0,0,0,0,0},{0,0,0,48,255,0,0,0,0,0,0},{68,38,8,34,0,49,1,44,11,54,0,0,0,0,0,0,0,0,0,0,0,0,0,0,0,0,0,0,0,0}},
   {6,10,5,38,255,{0,4,98,134,247,0,0,0,0,0,0},{0,0,0,0,128,0,0,0,0,0,0},{100,38,66,101,81,33,12,42,22,53,0,0,0,0,0,0,0,0,0,0,0,0,0,0,0,0,0,0,0,0}},
   {7,9,6,27,255,{19,86,147,161,206,184,0,0,0,0,0},{0,0,0,0,0,0,0,0,0,0,0},{68,73,66,64,65,76,106,86,117,0,0,0,0,0,0,0,0,0,0,0,0,0,0,0,0,0,0,0,0,0}},
   {8,18,3,25,16,{125,105,237,0,0,0,0,0,0,0,0},{0,0,32,0,0,0,0,0,0,0,0},{160,170,69,235,35,44,109,12,10,85,79,208,77,152,206,158,159,29,0,0,0,0,0,0,0,0,0,0,0,0}},
   {9,18,3,29,17,{8,109,229,0,0,0,0,0,0,0,0},{0,0,0,0,0,0,0,0,0,0,0},{68,161,166,5,44,76,40,209,199,85,16,78,207,152,92,158,29,23,0,0,0,0,0,0,0,0,0,0,0,0}},
   {10,17,3,34,18,{172,193,246,0,0,0,0,0,0,0,0},{0,0,64,0,0,0,0,0,0,0,0},{134,161,162,99,71,17,109,12,86,85,16,78,15,152,89,158,159,0,0,0,0,0,0,0,0,0,0,0,0,0}},
   {11,17,2,5,19,{56,118,0,0,0,0,0,0,0,0,0},{0,0,0,0,0,0,0,0,0,0,0},{72,165,107,197,227,236,40,193,202,22,213,211,212,13,89,220,29,0,0,0,0,0,0,0,0,0,0,0,0,0}},
   {12,18,3,11,20,{176,146,144,0,0,0,0,0,0,0,0},{0,0,0,0,0,0,0,0,0,0,0},{105,9,194,81,39,1,12,45,11,80,18,15,77,152,89,158,23,27,0,0,0,0,0,0,0,0,0,0,0,0}},
   {13,18,3,31,21,{88,131,231,0,0,0,0,0,0,0,0},{0,0,255,0,0,0,0,0,0,0,0},{160,170,107,81,39,7,1,75,237,85,16,15,212,152,89,158,29,27,0,0,0,0,0,0,0,0,0,0,0,0}},
   {14,17,2,1,22,{111,222,0,0,0,0,0,0,0,0,0},{0,64,0,0,0,0,0,0,0,0,0},{160,170,166,99,44,1,74,40,86,80,19,84,14,90,92,93,23,0,0,0,0,0,0,0,0,0,0,0,0,0}},
   {15,18,3,30,23,{152,108,230,0,0,0,0,0,0,0,0},{0,0,0,0,0,0,0,0,0,0,0},{134,233,69,43,71,231,12,75,45,85,16,15,14,152,89,158,159,27,0,0,0,0,0,0,0,0,0,0,0,0}},
   {8,18,3,2,24,{168,116,112,0,0,0,0,0,0,0,0},{0,0,0,0,0,0,0,0,0,0,0},{100,9,162,0,39,104,7,1,83,11,214,210,20,90,92,217,23,27,0,0,0,0,0,0,0,0,0,0,0,0}},
   {9,18,3,42,25,{80,215,252,0,0,0,0,0,0,0,0},{1,0,31,0,0,0,0,0,0,0,0},{73,165,107,99,192,1,109,10,86,82,203,19,20,90,205,25,159,27,0,0,0,0,0,0,0,0,0,0,0,0}},
   {10,18,3,5,26,{156,210,253,0,0,0,0,0,0,0,0},{0,0,32,0,0,0,0,0,0,0,0},{68,165,166,103,0,104,1,10,11,82,19,84,77,90,92,87,91,29,0,0,0,0,0,0,0,0,0,0,0,0}},
   {11,19,4,39,27,{128,155,212,249,0,0,0,0,0,0,0},{0,15,0,0,0,0,0,0,0,0,0},{160,170,201,81,39,7,109,204,11,82,16,15,14,152,218,158,159,215,219,0,0,0,0,0,0,0,0,0,0,0}},
   {12,18,3,6,28,{120,113,115,0,0,0,0,0,0,0,0},{0,0,0,0,0,0,0,0,0,0,0},{100,4,107,0,227,236,7,40,202,22,213,211,212,14,218,220,159,221,0,0,0,0,0,0,0,0,0,0,0,0}},
   {13,18,1,3,29,{124,0,0,0,0,0,0,0,0,0,0},{0,0,0,0,0,0,0,0,0,0,0},{73,165,166,0,35,44,12,10,232,22,18,19,14,13,26,28,159,23,0,0,0,0,0,0,0,0,0,0,0,0}},
   {14,18,2,46,30,{110,245,0,0,0,0,0,0,0,0,0},{0,32,0,0,0,0,0,0,0,0,0},{73,161,69,0,39,7,12,75,45,85,18,15,77,152,89,158,159,27,0,0,0,0,0,0,0,0,0,0,0,0}},
   {15,17,5,33,31,{96,89,130,196,251,0,0,0,0,0,0},{1,0,0,7,0,0,0,0,0,0,0},{73,161,64,81,35,44,74,40,86,82,19,84,77,90,92,93,23,0,0,0,0,0,0,0,0,0,0,0,0,0}},
   {8,3,3,0,255,{31,103,119,0,0,0,0,0,0,0,0},{0,0,128,0,0,0,0,0,0,0,0},{134,165,2,0,0,0,0,0,0,0,0,0,0,0,0,0,0,0,0,0,0,0,0,0,0,0,0,0,0,0}},
   {9,3,5,17,255,{38,142,135,213,234,0,0,0,0,0,0},{0,0,252,0,0,0,0,0,0,0,0},{131,41,162,0,0,0,0,0,0,0,0,0,0,0,0,0,0,0,0,0,0,0,0,0,0,0,0,0,0,0}},
   {10,4,6,23,255,{34,26,44,9,151,104,0,0,0,0,0},{0,0,0,0,0,0,0,0,0,0,0},{100,9,200,197,0,0,0,0,0,0,0,0,0,0,0,0,0,0,0,0,0,0,0,0,0,0,0,0,0,0}},
   {11,4,6,21,255,{77,18,94,90,154,239,0,0,0,0,0},{0,0,0,0,0,192,0,0,0,0,0},{100,4,2,0,0,0,0,0,0,0,0,0,0,0,0,0,0,0,0,0,0,0,0,0,0,0,0,0,0,0}},
   {12,3,5,1,255,{27,35,3,183,114,0,0,0,0,0,0},{0,0,0,0,0,0,0,0,0,0,0},{160,170,166,0,0,0,0,0,0,0,0,0,0,0,0,0,0,0,0,0,0,0,0,0,0,0,0,0,0,0}},
   {13,3,8,9,255,{24,36,5,81,83,170,122,223,0,0,0},{0,0,0,0,0,0,0,128,0,0,0},{68,233,2,0,0,0,0,0,0,0,0,0,0,0,0,0,0,0,0,0,0,0,0,0,0,0,0,0,0,0}},
   {14,4,6,10,255,{28,49,63,91,198,220,0,0,0,0,0},{0,0,0,0,0,0,0,0,0,0,0},{134,165,162,81,0,0,0,0,0,0,0,0,0,0,0,0,0,0,0,0,0,0,0,0,0,0,0,0,0,0}},
   {15,3,6,21,255,{73,74,75,62,158,192,0,0,0,0,0},{0,0,0,2,0,0,0,0,0,0,0},{68,228,2,0,0,0,0,0,0,0,0,0,0,0,0,0,0,0,0,0,0,0,0,0,0,0,0,0,0,0}},
   {8,3,6,2,255,{55,12,182,197,226,217,0,0,0,0,0},{0,0,0,0,0,0,0,0,0,0,0},{131,161,196,0,0,0,0,0,0,0,0,0,0,0,0,0,0,0,0,0,0,0,0,0,0,0,0,0,0,0}},
   {9,3,8,18,255,{33,17,21,101,169,117,211,219,0,0,0},{0,0,0,0,0,0,0,0,0,0,0},{160,170,198,0,0,0,0,0,0,0,0,0,0,0,0,0,0,0,0,0,0,0,0,0,0,0,0,0,0,0}},
   {10,3,6,47,255,{29,65,140,175,194,205,0,0,0,0,0},{0,0,0,0,0,63,0,0,0,0,0},{105,195,2,0,0,0,0,0,0,0,0,0,0,0,0,0,0,0,0,0,0,0,0,0,0,0,0,0,0,0}},
   {11,3,8,4,255,{53,66,2,11,132,106,202,235,0,0,0},{0,0,0,0,0,0,0,0,0,0,0},{134,161,166,0,0,0,0,0,0,0,0,0,0,0,0,0,0,0,0,0,0,0,0,0,0,0,0,0,0,0}},
   {12,4,7,6,255,{67,20,1,59,127,238,216,0,0,0,0},{0,0,0,0,0,0,0,0,0,0,0},{134,161,8,5,0,0,0,0,0,0,0,0,0,0,0,0,0,0,0,0,0,0,0,0,0,0,0,0,0,0}},
   {13,4,4,40,255,{79,87,199,204,0,0,0,0,0,0,0},{0,0,0,0,0,0,0,0,0,0,0},{134,161,162,5,0,0,0,0,0,0,0,0,0,0,0,0,0,0,0,0,0,0,0,0,0,0,0,0,0,0}},
   {14,4,7,0,255,{50,7,137,174,162,241,189,0,0,0,0},{0,0,0,0,0,0,0,0,0,0,0},{68,41,2,43,0,0,0,0,0,0,0,0,0,0,0,0,0,0,0,0,0,0,0,0,0,0,0,0,0,0}},
   {15,4,5,22,255,{52,45,84,126,224,0,0,0,0,0,0},{0,0,0,3,0,0,0,0,0,0,0},{131,224,234,230,0,0,0,0,0,0,0,0,0,0,0,0,0,0,0,0,0,0,0,0,0,0,0,0,0,0}},
   {8,4,7,44,255,{71,58,92,178,123,203,186,0,0,0,0},{0,0,0,0,0,0,0,0,0,0,0},{105,8,166,81,0,0,0,0,0,0,0,0,0,0,0,0,0,0,0,0,0,0,0,0,0,0,0,0,0,0}},
   {9,4,7,41,255,{48,23,97,93,171,207,232,0,0,0,0},{0,0,0,0,0,192,0,0,0,0,0},{100,66,200,103,0,0,0,0,0,0,0,0,0,0,0,0,0,0,0,0,0,0,0,0,0,0,0,0,0,0}},
   {10,4,6,13,255,{78,141,57,173,107,221,0,0,0,0,0},{0,0,0,0,3,63,0,0,0,0,0},{160,170,107,108,0,0,0,0,0,0,0,0,0,0,0,0,0,0,0,0,0,0,0,0,0,0,0,0,0,0}},
   {11,3,4,8,255,{51,68,14,167,0,0,0,0,0,0,0},{0,0,0,128,0,0,0,0,0,0,0},{131,233,162,0,0,0,0,0,0,0,0,0,0,0,0,0,0,0,0,0,0,0,0,0,0,0,0,0,0,0}},
   {12,3,7,26,255,{39,42,100,179,121,209,254,0,0,0,0},{0,0,0,0,0,0,0,0,0,0,0},{131,165,162,0,0,0,0,0,0,0,0,0,0,0,0,0,0,0,0,0,0,0,0,0,0,0,0,0,0,0}},
   {13,3,5,13,255,{37,143,177,149,225,0,0,0,0,0,0},{0,0,0,0,0,0,0,0,0,0,0},{131,228,8,0,0,0,0,0,0,0,0,0,0,0,0,0,0,0,0,0,0,0,0,0,0,0,0,0,0,0}},
   {14,3,3,15,255,{30,15,150,0,0,0,0,0,0,0,0},{0,0,67,0,0,0,0,0,0,0,0},{131,36,8,0,0,0,0,0,0,0,0,0,0,0,0,0,0,0,0,0,0,0,0,0,0,0,0,0,0,0}},
   {15,4,5,8,255,{54,139,10,159,255,0,0,0,0,0,0},{0,0,0,0,192,0,0,0,0,0,0},{72,165,162,65,0,0,0,0,0,0,0,0,0,0,0,0,0,0,0,0,0,0,0,0,0,0,0,0,0,0}},
   {6,2,7,16,255,{25,70,61,180,153,195,244,0,0,0,0},{0,0,0,0,0,0,31,0,0,0,0},{131,73,0,0,0,0,0,0,0,0,0,0,0,0,0,0,0,0,0,0,0,0,0,0,0,0,0,0,0,0}},
   {7,5,5,12,255,{72,22,102,133,160,0,0,0,0,0,0},{0,0,0,0,0,0,0,0,0,0,0},{100,105,98,96,97,0,0,0,0,0,0,0,0,0,0,0,0,0,0,0,0,0,0,0,0,0,0,0,0,0}}},
  {{0,7,0,0},{6,17,0,0},{1,12,0,0},{6,17,0,0},{0,7,0,0},{17,64,0,0},{11,64,0,0},{6,64,0,0},{0,7,0,0},{6,19,0,0},{0,4,0,0},
   {0,7,0,0},{22,64,0,0},{17,64,0,0},{11,64,0,0},{5,64,0,0},{21,64,0,0},{15,64,0,0},{0,5,0,0},{0,1,0,0},{17,64,0,0},{0,1,0,0},
   {0,6,0,0},{0,8,0,0},{0,2,0,0},{0,7,0,0},{0,6,0,0},{19,64,0,0},{7,64,0,0},{0,6,0,0},{2,11,0,0},{0,7,0,0},{17,64,0,0},
   {0,2,0,0},{7,19,0,0},{0,7,0,0},{17,64,0,0},{8,64,0,0},{0,6,0,0},{0,2,0,0},{18,64,0,0},{5,17,0,0},{8,64,0,0},{1,15,0,0},
   {11,64,0,0},{2,11,0,0},{6,15,0,0},{15,64,0,0},{4,17,0,0},{2,11,0,0},{0,8,0,0},{7,21,0,0},{7,17,0,0},{0,8,0,0},{7,18,0,0},
   {19,64,0,0},{0,6,0,0},{0,5,0,0},{7,16,0,0},{17,64,0,0},{0,4,0,0},{16,64,0,0},{7,64,0,0},{4,17,0,0},{8,22,0,0},{12,64,0,0}},
  {{48,53,56,61,62,47,54,32,36,26,40,49,28,57,50,63,58,55,6,7,12,13,18,19,16,17,8,9,4,5,10,11,0,1,34,35,24,25,14,15,2,3,20,21,38,39,42,43,22,23,30,31,44,45,33,37,27,41,52,29,60,51,46,59},
   {47,54,49,53,29,57,61,51,63,58,55,6,7,12,13,18,19,16,17,8,9,4,5,10,11,0,1,34,35,24,25,14,15,2,3,20,21,38,39,42,43,22,23,30,31,44,45,32,33,36,37,26,27,40,41,48,52,28,56,60,50,62,46,59},
   {61,62,47,54,45,33,37,27,41,49,53,29,57,50,63,59,55,6,7,12,13,18,19,16,17,8,9,4,5,10,11,0,1,34,35,24,25,14,15,2,3,20,21,38,39,42,43,22,23,30,31,44,32,36,26,40,48,52,28,56,60,51,46,58},
   {53,27,61,51,59,63,47,55,6,7,18,19,8,9,4,5,12,13,16,17,10,11,0,1,24,25,2,3,34,35,20,21,14,15,44,45,42,43,36,37,32,33,22,23,28,29,38,39,30,31,40,41,56,57,48,49,52,26,60,50,58,62,46,54},
   {57,52,27,50,59,46,55,43,37,22,28,38,30,40,56,49,26,61,58,63,54,6,7,18,19,8,9,4,5,12,13,16,17,10,11,0,1,24,25,2,3,34,35,20,21,14,15,44,45,42,36,32,33,23,29,39,31,41,48,53,60,51,62,47},
   {56,49,26,61,58,63,54,22,28,38,30,40,57,52,27,50,59,46,55,6,7,18,19,8,9,4,5,12,13,16,17,10,11,0,1,24,25,2,3,34,35,20,21,14,15,44,45,42,43,36,37,32,33,23,29,39,31,41,48,53,60,51,62,47},
   {27,52,51,60,47,54,59,38,40,30,26,49,50,57,46,63,58,12,13,8,9,18,19,6,7,16,17,4,5,10,11,14,15,0,1,34,35,2,3,24,25,20,21,44,45,22,23,42,43,36,37,28,29,32,33,39,41,31,48,53,56,61,62,55},
   {57,61,47,63,55,59,12,13,8,9,18,19,6,7,16,17,4,5,10,11,14,15,0,1,34,35,2,3,24,25,20,21,44,45,22,23,42,43,36,37,28,29,32,33,38,39,40,41,30,31,26,27,48,49,52,53,50,51,56,60,46,62,54,58},
   {57,46,63,58,29,33,39,41,31,27,49,53,51,60,47,54,59,12,13,8,9,18,19,6,7,16,17,4,5,10,11,14,15,0,1,34,35,2,3,24,25,20,21,44,45,22,23,42,43,36,37,28,32,38,40,30,26,48,52,50,56,61,62,55},
   {62,47,27,49,51,53,57,61,59,46,55,12,13,6,7,16,17,8,9,18,19,4,5,10,11,34,35,0,1,14,15,2,3,24,25,20,21,22,23,44,45,36,37,42,43,32,33,28,29,38,39,30,31,40,41,26,48,50,52,56,60,58,63,54},
   {48,51,57,58,63,54,31,41,27,50,53,60,59,46,55,12,13,6,7,16,17,8,9,18,19,4,5,10,11,34,35,0,1,14,15,2,3,24,25,20,21,22,23,44,45,36,37,42,43,32,33,28,29,38,39,30,40,26,49,52,56,61,62,47},
   {53,57,61,59,63,47,55,12,13,6,7,16,17,8,9,18,19,4,5,10,11,34,35,0,1,14,15,2,3,24,25,20,21,22,23,44,45,36,37,42,43,32,33,28,29,38,39,30,31,40,41,26,27,48,49,50,51,52,56,60,58,62,46,54},
   {54,26,28,48,52,50,56,61,63,47,59,55,12,13,6,7,8,9,18,19,16,17,4,5,10,11,0,1,34,35,2,3,14,15,24,25,20,21,22,23,44,45,32,33,42,43,30,31,36,37,38,39,40,41,27,29,49,53,51,57,60,62,46,58},
   {28,49,50,57,62,47,54,40,26,29,52,51,60,63,59,55,12,13,6,7,8,9,18,19,16,17,4,5,10,11,0,1,34,35,2,3,14,15,24,25,20,21,22,23,44,45,32,33,42,43,30,31,36,37,38,39,41,27,48,53,56,61,46,58},
   {49,50,57,62,47,54,36,38,40,26,29,52,51,60,63,58,55,12,13,6,7,8,9,18,19,16,17,4,5,10,11,0,1,34,35,2,3,14,15,24,25,20,21,22,23,44,45,32,33,42,43,30,31,37,39,41,27,28,48,53,56,61,46,59},
   {51,57,61,63,59,47,55,8,9,12,13,6,7,18,19,16,17,4,5,10,11,0,1,34,35,14,15,24,25,2,3,20,21,22,23,44,45,42,43,36,37,32,33,38,39,40,41,30,31,28,29,26,27,48,49,52,53,50,56,60,62,58,46,54},
   {31,26,49,50,57,62,59,54,45,43,37,33,39,41,28,27,52,51,60,58,47,55,8,9,12,13,6,7,18,19,16,17,4,5,10,11,0,1,34,35,14,15,24,25,2,3,20,21,22,23,44,42,36,32,38,40,30,29,48,53,56,61,63,46},
   {50,57,62,59,54,39,41,31,29,27,49,53,56,61,58,47,55,8,9,12,13,6,7,18,19,16,17,4,5,10,11,0,1,34,35,14,15,24,25,2,3,20,21,22,23,44,45,42,43,36,37,32,33,38,40,30,28,26,48,52,51,60,63,46},
   {59,54,27,49,53,51,57,61,63,46,55,6,7,8,9,18,19,12,13,16,17,4,5,10,11,0,1,34,35,14,15,2,3,24,25,20,21,22,23,44,45,42,43,36,37,32,33,38,39,30,31,28,29,40,41,26,48,52,50,56,60,62,58,47},
   {61,63,59,47,55,6,7,8,9,18,19,12,13,16,17,4,5,10,11,0,1,34,35,14,15,2,3,24,25,20,21,22,23,44,45,42,43,36,37,32,33,38,39,30,31,28,29,40,41,26,27,48,49,52,53,50,51,56,57,60,62,58,46,54},
   {52,51,60,63,46,54,30,28,40,26,48,53,56,61,58,47,55,6,7,8,9,18,19,12,13,16,17,4,5,10,11,0,1,34,35,14,15,2,3,24,25,20,21,22,23,44,45,42,43,36,37,32,33,38,39,31,29,41,27,49,50,57,62,59},
   {54,38,40,30,28,26,48,52,56,60,50,58,62,46,55,12,13,6,7,8,9,18,19,16,17,4,5,10,11,0,1,34,35,2,3,14,15,24,25,20,21,22,23,44,45,42,43,36,37,32,33,39,41,31,29,27,49,53,57,61,51,59,63,47},
   {49,56,61,58,63,54,37,33,39,41,31,29,27,52,57,50,59,46,55,12,13,6,7,8,9,18,19,16,17,4,5,10,11,0,1,34,35,2,3,14,15,24,25,20,21,22,23,44,45,42,43,36,32,38,40,30,28,26,48,53,60,51,62,47},
   {53,57,61,51,59,63,47,55,12,13,6,7,8,9,18,19,16,17,4,5,10,11,0,1,34,35,2,3,14,15,24,25,20,21,22,23,44,45,42,43,36,37,32,33,38,39,40,41,30,31,28,29,26,27,48,49,52,56,60,50,58,62,46,54}},
  {{7,7,7,7,7,7,7,7},{11,11,10,9,9,10,9,9},{5,4,5,5,5,5,5,5},{0,0,2,0,1,0,0,0},
   {3,1,1,3,2,1,1,1},{6,6,6,6,6,6,6,6},{1,3,0,1,0,2,3,2},{10,10,9,10,10,9,10,10},
   {4,5,3,2,4,4,4,4},{2,2,4,4,3,3,2,3},{12,12,12,12,12,1,1,1},{14,14,13,3,2,0,4,4},
   {9,8,11,11,11,11,11,11},{8,9,11,11,11,0,4,4},{7,4,2,12,2,2,11,11},{2,7,6,8,8,8,8,8},
   {4,5,4,7,3,7,7,7},{8,9,8,8,8,8,8,8},{3,1,3,5,7,3,6,6},{5,2,7,6,6,6,0,0},
   {6,6,8,0,1,11,3,10},{15,15,5,4,5,5,5,5},{13,13,1,2,4,4,2,3},{4,5,3,11,2,2,11,4},
   {0,0,10,9,12,1,1,1},{14,14,13,2,4,4,2,3},{1,8,12,3,9,10,9,9},{7,4,11,9,12,1,1,9},
   {10,11,1,4,5,5,5,6},{15,13,6,8,8,8,8,8},{11,12,5,5,7,3,0,0},{13,15,2,12,11,0,4,1}},
  {{255,255,255,255,255,255,255,255},{255,255,255,255,255,255,255,255},{255,255,255,255,255,255,255,255},{255,255,255,255,255,255,255,255},
   {255,255,255,255,255,255,255,255},{255,255,255,255,255,255,255,255},{255,255,255,255,255,255,255,255},{255,255,255,255,255,255,255,255},
   {255,255,255,255,255,255,255,255},{255,255,255,255,255,255,255,255},{255,255,255,255,255,4,4,4},{255,255,255,4,4,3,8,8},
   {255,255,255,255,255,255,255,255},{17,17,12,12,12,11,11,11},{0,2,3,10,11,6,12,12},{9,0,5,17,17,17,17,17},
   {8,8,9,0,9,0,0,0},{255,255,255,255,255,255,255,255},{4,4,8,2,0,9,5,5},{2,9,0,5,5,5,3,3},
   {5,5,17,3,3,12,6,7},{255,255,2,9,2,2,2,2},{255,255,4,8,8,8,9,9},{16,16,18,13,14,14,14,13},
   {3,3,1,1,10,10,10,10},{11,11,11,22,22,22,22,22},{6,12,10,11,1,1,1,1},{14,14,13,24,24,24,24,26},
   {7,1,22,21,21,21,21,18},{21,22,15,15,15,15,15,15},{1,10,21,18,18,18,19,19},{22,21,14,14,13,13,13,24}},
  {112,113,114,115,116,117,118,119,6,121,122,36,124,125,126,127,128,129,130,131,132,133,134,135,136,137,138,139,140,141,142,143,144,145,146,147,148,149,150,151,152,153,154,155,156,157,158,159,160,161,162,163,164,165,166,167,168,41,170,391,172,647,174,175,176,177,178,179,180,181,182,183,184,185,186,187,188,189,190,191,43,2,0,74,75,8,198,199,635,201,39,76,77,37,4,5,7,209,1,38,212,213,214,215,216,18,393,219,220,221,222,223,22,50,48,227,228,229,230,231,11,233,649,86,236,87,52,53,81,241,370,16,244,17,246,9,248,3,250,251,252,253,254,255,82,80,78,259,47,14,10,263,44,51,626,88,89,84,15,12,272,273,49,275,276,277,85,83,280,372,79,45,46,285,628,379,13,42,40,291,292,293,73,72,296,28,59,35,300,34,302,303,304,305,454,307,308,309,310,311,92,61,445,54,58,55,20,21,320,321,710,56,57,25,326,327,32,29,707,66,65,63,30,31,23,19,701,97,98,95,26,24,33,698,27,347,64,349,96,93,94,62,60,452,451,708,90,91,360,415,442,363,364,365,671,367},
  {511,511,511,511,511,511,511,511,256,511,511,256,511,511,511,511,511,511,511,511,511,511,511,511,511,511,511,511,511,511,511,511,511,511,511,511,511,511,511,511,511,511,511,511,511,511,511,511,511,511,511,511,511,511,511,511,511,256,511,55,511,55,511,511,511,511,511,511,511,511,511,511,511,511,511,511,511,511,511,511,256,256,256,256,256,256,511,511,51,511,256,256,256,256,256,256,256,511,256,256,511,511,511,511,511,258,49,511,511,511,511,511,258,257,257,511,511,511,511,511,257,511,49,257,511,257,257,257,257,511,50,257,511,257,511,257,511,256,511,511,511,511,511,511,257,256,256,511,257,257,257,511,256,257,50,257,257,257,257,257,511,511,257,511,511,511,257,257,511,52,256,257,257,511,52,51,257,256,256,511,511,511,256,256,511,259,258,259,511,259,511,511,511,511,62,511,511,511,511,511,258,258,61,258,258,258,258,258,511,511,62,258,258,258,511,511,259,259,59,259,259,259,259,259,258,258,61,258,258,258,258,258,259,58,259,511,259,511,258,258,258,258,258,60,59,60,258,258,511,175,58,511,511,511,175,511}};

typedef CUresult (*EncodeFn)(CUtensorMap*, CUtensorMapDataType, cuuint32_t, void*, const cuuint64_t*, const cuuint64_t*, const cuuint32_t*,
                             const cuuint32_t*, CUtensorMapInterleave, CUtensorMapSwizzle, CUtensorMapL2promotion, CUtensorMapFloatOOBfill);

void make_map2(EncodeFn enc, CUtensorMap* m, const void* ptr, int rows, int cols, int box_rows) {
  cuuint64_t dim[2] = {(cuuint64_t)cols, (cuuint64_t)rows}, str[1] = {(cuuint64_t)cols * 2};
  cuuint32_t box[2] = {64, (cuuint32_t)box_rows}, es[2] = {1, 1};
  enc(m, CU_TENSOR_MAP_DATA_TYPE_BFLOAT16, 2, const_cast<void*>(ptr), dim, str, box, es, CU_TENSOR_MAP_INTERLEAVE_NONE, CU_TENSOR_MAP_SWIZZLE_128B,
      CU_TENSOR_MAP_L2_PROMOTION_L2_128B, CU_TENSOR_MAP_FLOAT_OOB_FILL_NONE);
}
void make_map3(EncodeFn enc, CUtensorMap* m, const void* ptr, int rows) {
  cuuint64_t dim[3] = {64, (cuuint64_t)rows, 9}, str[2] = {DM * 2, 128};
  cuuint32_t box[3] = {64, 32, 3}, es[3] = {1, 1, 1};
  enc(m, CU_TENSOR_MAP_DATA_TYPE_BFLOAT16, 3, const_cast<void*>(ptr), dim, str, box, es, CU_TENSOR_MAP_INTERLEAVE_NONE, CU_TENSOR_MAP_SWIZZLE_128B,
      CU_TENSOR_MAP_L2_PROMOTION_L2_128B, CU_TENSOR_MAP_FLOAT_OOB_FILL_NONE);
}

void make_map_t(EncodeFn enc, CUtensorMap* m, void* ptr, int width, int cols) {
  cuuint64_t dim[3] = {SEQ / 2, 2, 864}, str[2] = {SEQ * 2, SEQ * 4};
  cuuint32_t box[3] = {(cuuint32_t)width, 2, (cuuint32_t)cols}, es[3] = {1, 1, 1};
  enc(m, CU_TENSOR_MAP_DATA_TYPE_UINT32, 3, ptr, dim, str, box, es, CU_TENSOR_MAP_INTERLEAVE_NONE, cols == 64 ? CU_TENSOR_MAP_SWIZZLE_128B : CU_TENSOR_MAP_SWIZZLE_NONE,
      CU_TENSOR_MAP_L2_PROMOTION_NONE, CU_TENSOR_MAP_FLOAT_OOB_FILL_NONE);
}

int g_mode = -1;

}

extern "C" void kernel_launch(void* const* d_in, const int* in_sizes, int n_in, void* d_out, int out_size) {
  static EncodeFn enc = nullptr;
  static void* t_ptr = nullptr;
  if (!enc) {
    void* fn = nullptr;
    cudaDriverEntryPointQueryResult st;
    cudaGetDriverEntryPoint("cuTensorMapEncodeTiled", &fn, cudaEnableDefault, &st);
    enc = (EncodeFn)fn;
    cudaGetSymbolAddress(&t_ptr, g_S);
    cudaFuncSetAttribute(fused_kernel, cudaFuncAttributeMaxDynamicSharedMemorySize, SMEM_BYTES);
    if (g_mode < 0) {
      cudaLaunchConfig_t cfg = {};
      cfg.gridDim = dim3(2 * NCL); cfg.blockDim = dim3(384); cfg.dynamicSmemBytes = SMEM_BYTES;
      cudaLaunchAttribute at; at.id = cudaLaunchAttributeClusterDimension;
      at.val.clusterDim.x = 2; at.val.clusterDim.y = 1; at.val.clusterDim.z = 1;
      cfg.attrs = &at; cfg.numAttrs = 1;
      int nc = 0;
      g_mode = (cudaOccupancyMaxActiveClusters(&nc, fused_kernel, &cfg) == cudaSuccess && nc >= NCL) ? 1 : 0;
      (void)cudaGetLastError();
    }
  }
  Params p;
  make_map2(enc, &p.map_a[0], d_in[4], SEQ, DC, 128);
  make_map2(enc, &p.map_a[1], d_in[0], SEQ, DM, 128);
  make_map2(enc, &p.map_w[0], d_in[6], DC, 4096, 64);
  make_map2(enc, &p.map_w[1], d_in[7], DC, 4096, 64);
  make_map2(enc, &p.map_w[2], d_in[5], DM, 4096, 64);
  make_map2(enc, &p.map_w[3], d_in[1], DM, 1728, 64);
  make_map3(enc, &p.map_o[0], d_in[8], 4096);
  make_map3(enc, &p.map_o[1], d_in[2], DM);
  make_map_t(enc, &p.map_t[0], t_ptr, 32, 9);
  make_map_t(enc, &p.map_t[1], t_ptr, 40, 9);
  make_map_t(enc, &p.map_t[2], t_ptr, 32, 64);
  p.x = (const __nv_bfloat16*)d_in[0];
  p.gate_w = (const __nv_bfloat16*)d_in[9];
  make_map2(enc, &p.map_out, d_out, SEQ, DM, 64);
  p.out = (__nv_bfloat16*)d_out;
  p.zero = 0;
  auto launch = [&](int phases) {
    p.s = k_sched;
    for (int i = 0; i < NCL; i++) {
      Rec& r = p.s.r[i];
      if (!(phases & 1)) r.n1 = 0;
      if (!(phases & 2)) r.n2 = 0;
      if (!(phases & (p.s.task[i][1] == 64 ? 4 : 32))) r.p3 = 255;
      if (!(phases & 8)) r.bg = 255;
      const int u1 = r.n1 ? 8 + r.n1 * (8 + (r.slab >> 3)) : 0;
      int u2 = 0;
      for (int k = 0; k < r.n2; k++) u2 += 4 * (r.item[k] & 7) + 4;
      r.u1 = (uint8_t)u1; r.u2 = (uint8_t)u2;
      r.rot = (uint8_t)(((u1 % 10 + 1) >> 1) % 5);
      r.x3 = (uint8_t)((r.rot + u2) % 5 & 3);
      r.phases = (uint8_t)phases;
    }
    if (!(phases & 16))
      for (int i = 0; i < 256; i++) { p.s.slot[i >> 3][i & 7] = (uint8_t)(i >> 3); p.s.prev[i >> 3][i & 7] = 255; p.s.qblk[i] = (uint16_t)(S_Q + i); p.s.qdep[i] = 511; }
    fused_kernel<<<2 * NCL, 384, SMEM_BYTES>>>(p);
  };
  if (g_mode == 1) launch(63);
  else { launch(1); launch(10); launch(4); launch(32); }
}
```

```cpp
#include <cuda_runtime.h>
#include <cuda_bf16.h>
#include <cuda.h>
#include <stdint.h>

namespace {

constexpr int SEQ = 2048, DM = 576, DC = 512, NH = 32;
constexpr int NCL = 66;
constexpr uint32_t DESC_HI = 0x40000040u;

constexpr int SM_RING = 0;
constexpr int SM_BUF = 163840;
constexpr int SM_BAR = 229376;
constexpr int B_P1E = 0, B_P2E = 10, B_P3E = 15, B_P2F = 24, B_SF = 32, B_ORD = 36, B_LAD = 40, B_DONE = 41, B_FIN = 48;
constexpr int B_P3F = 56, B_OUT = 61, B_ZF = 62, B_P1F = 64, B_SE = 74, B_QF = 80, B_LA = 84, B_NUM = 88;
constexpr uint64_t B_CNT = 0x11118245000ull;
constexpr int SMEM_BYTES = SM_BAR + B_NUM * 8 + 1024;

constexpr int F_QKVA = 32;
constexpr int F_GATE = 64;
constexpr int F_TS = 68;
constexpr int F_DONE = 65;
constexpr int F_CTX = 96;
constexpr int F_OUT = 96 + 8 * 64;
constexpr int F_KV = F_OUT + 64;
constexpr int F_Q = F_KV + 256;
constexpr int F_RD = F_Q + 256;
constexpr int F_NUM = F_RD + 256;

struct Rec {
  uint8_t slab;
  uint8_t n1, n2;
  uint8_t p3;
  uint8_t bg;
  uint8_t item[11];
  uint8_t last[11];
  uint8_t tile[32];
  uint8_t u1, u2;
  uint8_t rot, x3;
  uint8_t phases;
};
struct Sched {
  Rec r[NCL];
  uint8_t task[NCL][4];
  uint8_t p3_order[24][64];
  uint8_t slot[32][8];
  uint8_t prev[32][8];
  uint16_t qblk[256];
  uint16_t qdep[256];
};


struct Params {
  CUtensorMap map_a[2];
  CUtensorMap map_w[4];
  CUtensorMap map_o[2];
  CUtensorMap map_t[3];
  CUtensorMap map_out;
  const __nv_bfloat16* x;
  const __nv_bfloat16* gate_w;
  __nv_bfloat16* out;
  int zero;
  alignas(64) Sched s;
};

constexpr int S_T = 0, S_Q = 112, S_K = S_Q + 256, S_V = S_K + 256, S_NUM = S_V + 256;
__device__ __align__(1024) uint8_t g_S[(size_t)S_NUM * 65536];
__device__ __align__(1024) uint8_t g_oA[32 * 576 * 128];
__device__ float g_gate[SEQ];
__device__ int g_flags[F_NUM];

__device__ __forceinline__ void mbar_arrive(uint32_t b) { asm volatile("mbarrier.arrive.shared::cta.b64 _, [%0];" ::"r"(b) : "memory"); }
__device__ __forceinline__ void mbar_arrive_cl(uint32_t b, int cnt) {
  asm volatile("mbarrier.arrive.shared::cluster.b64 _, [%0], %1;" ::"r"(b), "r"(cnt) : "memory");
}
__device__ __forceinline__ void mbar_wait(uint32_t b, int par) {
  asm volatile(
      "{\n.reg .pred p;\n.reg .u32 c;\n"
      "mbarrier.try_wait.parity.shared::cta.b64 p, [%0], %1;\n@p bra DN;\nmov.u32 c, 0;\n"
      "LP:\nmbarrier.try_wait.parity.shared::cta.b64 p, [%0], %1;\n@p bra DN;\n"
      "add.u32 c, c, 1;\nsetp.lt.u32 p, c, 4000000;\n@p bra LP;\ntrap;\nDN:\n}" ::"r"(b), "r"(par) : "memory");
}
__device__ __forceinline__ bool mbar_test(uint32_t b, int par) {
  uint32_t ok;
  asm volatile("{\n.reg .pred p;\nmbarrier.test_wait.parity.shared::cta.b64 p, [%1], %2;\nselp.u32 %0, 1, 0, p;\n}" : "=r"(ok) : "r"(b), "r"(par) : "memory");
  return __all_sync(0xffffffffu, ok);
}
__device__ __forceinline__ uint32_t mapa(uint32_t a, uint32_t cta) {
  uint32_t r; asm("mapa.shared::cluster.u32 %0, %1, %2;" : "=r"(r) : "r"(a), "r"(cta)); return r;
}
#define ELECT(ins) "{\n.reg .pred e;\nelect.sync _|e, 0xffffffff;\n@e " ins "\n}"
__device__ __forceinline__ void mbar_expect(uint32_t b, int bytes) {
  asm volatile(ELECT("mbarrier.arrive.expect_tx.shared::cta.b64 _, [%0], %1;") ::"r"(b), "r"(bytes) : "memory");
}
__device__ __forceinline__ void mbar_arrive_one(uint32_t b) { asm volatile(ELECT("mbarrier.arrive.shared::cta.b64 _, [%0];") ::"r"(b) : "memory"); }
constexpr uint64_t L2_NORMAL = 0x1000000000000000ull, L2_FIRST = 0x12F0000000000000ull;
__device__ __forceinline__ void bulk_load(uint32_t dst, const void* src, int bytes, uint32_t bar, uint64_t pol = L2_NORMAL) {
  asm volatile(ELECT("cp.async.bulk.shared::cluster.global.mbarrier::complete_tx::bytes.L2::cache_hint [%0], [%1], %2, [%3], %4;") ::"r"(dst), "l"(src), "r"(bytes), "r"(bar), "l"(pol) : "memory");
}
__device__ __forceinline__ void bulk_load_mc(uint32_t dst, const void* src, int bytes, uint32_t bar, uint64_t pol = L2_NORMAL) {
  asm volatile(ELECT("cp.async.bulk.shared::cluster.global.mbarrier::complete_tx::bytes.multicast::cluster.L2::cache_hint [%0], [%1], %2, [%3], %4, %5;") ::"r"(dst), "l"(src), "r"(bytes), "r"(bar), "h"((uint16_t)3), "l"(pol) : "memory");
}
__device__ __forceinline__ void bulk_store(void* dst, uint32_t src, int bytes, uint64_t pol = L2_NORMAL) {
  asm volatile(ELECT("cp.async.bulk.global.shared::cta.bulk_group.L2::cache_hint [%0], [%1], %2, %3;") ::"l"(dst), "r"(src), "r"(bytes), "l"(pol) : "memory");
}
__device__ __forceinline__ void tma2d(uint32_t dst, const CUtensorMap* m, int c0, int c1, uint32_t bar, uint64_t pol = L2_NORMAL) {
  asm volatile(ELECT("cp.async.bulk.tensor.2d.shared::cluster.global.mbarrier::complete_tx::bytes.L2::cache_hint [%0], [%1, {%3, %4}], [%2], %5;") ::"r"(dst), "l"(m), "r"(bar), "r"(c0), "r"(c1), "l"(pol) : "memory");
}
__device__ __forceinline__ void tma2d_mc(uint32_t dst, const CUtensorMap* m, int c0, int c1, uint32_t bar, uint64_t pol = L2_NORMAL) {
  asm volatile(ELECT("cp.async.bulk.tensor.2d.shared::cluster.global.mbarrier::complete_tx::bytes.multicast::cluster.L2::cache_hint [%0], [%1, {%3, %4}], [%2], %5, %6;") ::"r"(dst), "l"(m), "r"(bar), "r"(c0), "r"(c1), "h"((uint16_t)3), "l"(pol) : "memory");
}
__device__ __forceinline__ void tma3d(uint32_t dst, const CUtensorMap* m, int c0, int c1, int c2, uint32_t bar, uint64_t pol = L2_NORMAL) {
  asm volatile(ELECT("cp.async.bulk.tensor.3d.shared::cluster.global.mbarrier::complete_tx::bytes.L2::cache_hint [%0], [%1, {%3, %4, %5}], [%2], %6;") ::"r"(dst), "l"(m), "r"(bar), "r"(c0), "r"(c1), "r"(c2), "l"(pol) : "memory");
}
__device__ __forceinline__ void tma3d_mc(uint32_t dst, const CUtensorMap* m, int c0, int c1, int c2, uint32_t bar, uint64_t pol = L2_NORMAL) {
  asm volatile(ELECT("cp.async.bulk.tensor.3d.shared::cluster.global.mbarrier::complete_tx::bytes.multicast::cluster.L2::cache_hint [%0], [%1, {%3, %4, %5}], [%2], %6, %7;") ::"r"(dst), "l"(m), "r"(bar), "r"(c0), "r"(c1), "r"(c2), "h"((uint16_t)3), "l"(pol) : "memory");
}
__device__ __forceinline__ void tma2d_add(const CUtensorMap* m, uint32_t src, int c0, int c1) {
  asm volatile(ELECT("cp.reduce.async.bulk.tensor.2d.global.shared::cta.add.bulk_group [%0, {%2, %3}], [%1];") ::"l"(m), "r"(src), "r"(c0), "r"(c1) : "memory");
}
__device__ __forceinline__ void tma3d_store(const CUtensorMap* m, uint32_t src, int c0, int c1, int c2, uint64_t pol = L2_NORMAL) {
  asm volatile(ELECT("cp.async.bulk.tensor.3d.global.shared::cta.bulk_group.L2::cache_hint [%0, {%2, %3, %4}], [%1], %5;") ::"l"(m), "r"(src), "r"(c0), "r"(c1), "r"(c2), "l"(pol) : "memory");
}
__device__ __forceinline__ void tma2d_prefetch(const CUtensorMap* m, int c0, int c1, uint64_t pol = L2_NORMAL) {
  asm volatile(ELECT("cp.async.bulk.prefetch.tensor.2d.L2.global.L2::cache_hint [%0, {%1, %2}], %3;") ::"l"(m), "r"(c0), "r"(c1), "l"(pol) : "memory");
}
#define LAG 3
#define HINT 63
#define POL(bit) ((HINT >> (bit)) & 1 ? L2_FIRST : L2_NORMAL)
#define BULK_COMMIT() asm volatile("cp.async.bulk.commit_group;" ::: "memory")
#define BULK_WAIT(n) asm volatile("cp.async.bulk.wait_group %0;" ::"n"(n) : "memory")
#define BULK_WAIT_READ(n) asm volatile("cp.async.bulk.wait_group.read %0;" ::"n"(n) : "memory")
#define FENCE_ASYNC_SMEM() asm volatile("fence.proxy.async.shared::cta;" ::: "memory")
#define WG_FENCE() asm volatile("wgmma.fence.sync.aligned;" ::: "memory")
#define WG_COMMIT() asm volatile("wgmma.commit_group.sync.aligned;" ::: "memory")
#define WG_WAIT(n) asm volatile("wgmma.wait_group.sync.aligned %0;" ::"n"(n) : "memory")
__device__ __forceinline__ void bar_sync(int id, int n) { asm volatile("bar.sync %0, %1;" ::"r"(id), "r"(n) : "memory"); }
__device__ __forceinline__ void bar_arrive(int id, int n) { asm volatile("bar.arrive %0, %1;" ::"r"(id), "r"(n) : "memory"); }
__device__ __forceinline__ void cluster_sync() {
  asm volatile("barrier.cluster.arrive.relaxed;\nbarrier.cluster.wait.acquire;" ::: "memory");
}
template <int N> __device__ __forceinline__ void pin(float (&r)[N]) {
#pragma unroll
  for (int i = 0; i < N; i++) asm volatile("" : "+f"(r[i])::"memory");
}
template <int N> __device__ __forceinline__ void pin(uint32_t (&r)[N]) {
#pragma unroll
  for (int i = 0; i < N; i++) asm volatile("" : "+r"(r[i])::"memory");
}
__device__ __forceinline__ uint32_t pack_bf16(float lo, float hi) {
  uint32_t r; asm("cvt.rn.bf16x2.f32 %0, %1, %2;" : "=r"(r) : "f"(hi), "f"(lo)); return r;
}
__device__ __forceinline__ float ex2(float x) { float r; asm("ex2.approx.ftz.f32 %0, %1;" : "=f"(r) : "f"(x)); return r; }
__device__ __forceinline__ void ldsm4(uint32_t a, uint32_t& r0, uint32_t& r1, uint32_t& r2, uint32_t& r3) {
  asm volatile("ldmatrix.sync.aligned.m8n8.x4.shared.b16 {%0,%1,%2,%3}, [%4];" : "=r"(r0), "=r"(r1), "=r"(r2), "=r"(r3) : "r"(a) : "memory");
}
__device__ __forceinline__ void stsm4(uint32_t a, uint32_t r0, uint32_t r1, uint32_t r2, uint32_t r3) {
  asm volatile("stmatrix.sync.aligned.m8n8.x4.shared.b16 [%0], {%1,%2,%3,%4};" ::"r"(a), "r"(r0), "r"(r1), "r"(r2), "r"(r3) : "memory");
}
__device__ __forceinline__ void flag_add(int idx, int v = 1) {
  asm volatile(ELECT("red.release.gpu.global.add.s32 [%0], %1;") ::"l"(g_flags + idx), "r"(v) : "memory");
}
__device__ __forceinline__ void flag_add_rx(int idx, int v = 1) {
  asm volatile(ELECT("red.relaxed.gpu.global.add.s32 [%0], %1;") ::"l"(g_flags + idx), "r"(v) : "memory");
}
template <bool ACQ, int NS = 32> __device__ __forceinline__ void flag_wait(int idx, int target) {
  int n = 0;
  while (true) {
    int v;
    if (ACQ) asm volatile("ld.acquire.gpu.global.s32 %0, [%1];" : "=r"(v) : "l"(g_flags + idx) : "memory");
    else asm volatile("ld.relaxed.gpu.global.s32 %0, [%1];" : "=r"(v) : "l"(g_flags + idx) : "memory");
    if (__all_sync(0xffffffffu, v >= target)) break;
    if (++n > 20000000) __trap();
    __nanosleep(NS);
  }
}
__device__ __forceinline__ int flag_peek(int idx) {
  int v;
  asm volatile("ld.relaxed.gpu.global.s32 %0, [%1];" : "=r"(v) : "l"(g_flags + idx) : "memory");
  return v;
}
__device__ __forceinline__ void mask_wait(uint32_t& ready, int bit, int idx, int target) {
  for (int n = 0; !((ready >> bit) & 1); n++) {
    int v;
    if (n) { __nanosleep(32); if (n > 20000000) __trap(); }
    asm volatile("ld.relaxed.gpu.global.s32 %0, [%1];" : "=r"(v) : "l"(g_flags + idx) : "memory");
    ready = __ballot_sync(0xffffffffu, v >= target);
  }
}
__device__ __forceinline__ uint32_t desc_lo(uint32_t addr, uint32_t lbo) { return ((addr & 0x3FFFFu) >> 4) | ((lbo >> 4) << 16); }

template <int TB, int TA = 0> __device__ __forceinline__ void wgmma_ss64(float (&d)[32], uint32_t alo, uint32_t blo, int sd) {
  asm volatile("{\n.reg .pred p;\n.reg .b64 da, db;\n"
    "setp.ne.b32 p, %34, 0;\nmov.b64 da, {%32, %36};\nmov.b64 db, {%33, %36};\n"
    "wgmma.mma_async.sync.aligned.m64n64k16.f32.bf16.bf16 "
    "{%0,%1,%2,%3,%4,%5,%6,%7,%8,%9,%10,%11,%12,%13,%14,%15,%16,%17,%18,%19,%20,%21,%22,%23,"
    "%24,%25,%26,%27,%28,%29,%30,%31}, "
    "da, db, p, 1, 1, %37, %35;\n}\n"
    : "+f"(d[0]),"+f"(d[1]),"+f"(d[2]),"+f"(d[3]),"+f"(d[4]),"+f"(d[5]),"+f"(d[6]),"+f"(d[7]),"+f"(d[8]),"+f"(d[9]),"+f"(d[10]),"+f"(d[11]),
      "+f"(d[12]),"+f"(d[13]),"+f"(d[14]),"+f"(d[15]),"+f"(d[16]),"+f"(d[17]),"+f"(d[18]),"+f"(d[19]),"+f"(d[20]),"+f"(d[21]),"+f"(d[22]),"+f"(d[23]),
      "+f"(d[24]),"+f"(d[25]),"+f"(d[26]),"+f"(d[27]),"+f"(d[28]),"+f"(d[29]),"+f"(d[30]),"+f"(d[31])
    : "r"(alo), "r"(blo), "r"(sd), "n"(TB), "r"(DESC_HI), "n"(TA));
}
template <int TB, int TA = 0> __device__ __forceinline__ void wgmma_ss128(float (&d)[64], uint32_t alo, uint32_t blo, int sd) {
  asm volatile("{\n.reg .pred p;\n.reg .b64 da, db;\n"
    "setp.ne.b32 p, %66, 0;\nmov.b64 da, {%64, %68};\nmov.b64 db, {%65, %68};\n"
    "wgmma.mma_async.sync.aligned.m64n128k16.f32.bf16.bf16 "
    "{%0,%1,%2,%3,%4,%5,%6,%7,%8,%9,%10,%11,%12,%13,%14,%15,%16,%17,%18,%19,%20,%21,%22,%23,"
    "%24,%25,%26,%27,%28,%29,%30,%31,%32,%33,%34,%35,%36,%37,%38,%39,%40,%41,%42,%43,%44,%45,%46,%47,"
    "%48,%49,%50,%51,%52,%53,%54,%55,%56,%57,%58,%59,%60,%61,%62,%63}, "
    "da, db, p, 1, 1, %69, %67;\n}\n"
    : "+f"(d[0]),"+f"(d[1]),"+f"(d[2]),"+f"(d[3]),"+f"(d[4]),"+f"(d[5]),"+f"(d[6]),"+f"(d[7]),"+f"(d[8]),"+f"(d[9]),"+f"(d[10]),"+f"(d[11]),
      "+f"(d[12]),"+f"(d[13]),"+f"(d[14]),"+f"(d[15]),"+f"(d[16]),"+f"(d[17]),"+f"(d[18]),"+f"(d[19]),"+f"(d[20]),"+f"(d[21]),"+f"(d[22]),"+f"(d[23]),
      "+f"(d[24]),"+f"(d[25]),"+f"(d[26]),"+f"(d[27]),"+f"(d[28]),"+f"(d[29]),"+f"(d[30]),"+f"(d[31]),"+f"(d[32]),"+f"(d[33]),"+f"(d[34]),"+f"(d[35]),
      "+f"(d[36]),"+f"(d[37]),"+f"(d[38]),"+f"(d[39]),"+f"(d[40]),"+f"(d[41]),"+f"(d[42]),"+f"(d[43]),"+f"(d[44]),"+f"(d[45]),"+f"(d[46]),"+f"(d[47]),
      "+f"(d[48]),"+f"(d[49]),"+f"(d[50]),"+f"(d[51]),"+f"(d[52]),"+f"(d[53]),"+f"(d[54]),"+f"(d[55]),"+f"(d[56]),"+f"(d[57]),"+f"(d[58]),"+f"(d[59]),
      "+f"(d[60]),"+f"(d[61]),"+f"(d[62]),"+f"(d[63])
    : "r"(alo), "r"(blo), "r"(sd), "n"(TB), "r"(DESC_HI), "n"(TA));
}
template <int TB> __device__ __forceinline__ void wgmma_rs128(float (&d)[64], uint32_t a0, uint32_t a1, uint32_t a2, uint32_t a3, uint32_t blo, int sd) {
  asm volatile("{\n.reg .pred p;\n.reg .b64 db;\n"
    "setp.ne.b32 p, %69, 0;\nmov.b64 db, {%68, %71};\n"
    "wgmma.mma_async.sync.aligned.m64n128k16.f32.bf16.bf16 "
    "{%0,%1,%2,%3,%4,%5,%6,%7,%8,%9,%10,%11,%12,%13,%14,%15,%16,%17,%18,%19,%20,%21,%22,%23,"
    "%24,%25,%26,%27,%28,%29,%30,%31,%32,%33,%34,%35,%36,%37,%38,%39,%40,%41,%42,%43,%44,%45,%46,%47,"
    "%48,%49,%50,%51,%52,%53,%54,%55,%56,%57,%58,%59,%60,%61,%62,%63}, "
    "{%64,%65,%66,%67}, db, p, 1, 1, %70;\n}\n"
    : "+f"(d[0]),"+f"(d[1]),"+f"(d[2]),"+f"(d[3]),"+f"(d[4]),"+f"(d[5]),"+f"(d[6]),"+f"(d[7]),"+f"(d[8]),"+f"(d[9]),"+f"(d[10]),"+f"(d[11]),
      "+f"(d[12]),"+f"(d[13]),"+f"(d[14]),"+f"(d[15]),"+f"(d[16]),"+f"(d[17]),"+f"(d[18]),"+f"(d[19]),"+f"(d[20]),"+f"(d[21]),"+f"(d[22]),"+f"(d[23]),
      "+f"(d[24]),"+f"(d[25]),"+f"(d[26]),"+f"(d[27]),"+f"(d[28]),"+f"(d[29]),"+f"(d[30]),"+f"(d[31]),"+f"(d[32]),"+f"(d[33]),"+f"(d[34]),"+f"(d[35]),
      "+f"(d[36]),"+f"(d[37]),"+f"(d[38]),"+f"(d[39]),"+f"(d[40]),"+f"(d[41]),"+f"(d[42]),"+f"(d[43]),"+f"(d[44]),"+f"(d[45]),"+f"(d[46]),"+f"(d[47]),
      "+f"(d[48]),"+f"(d[49]),"+f"(d[50]),"+f"(d[51]),"+f"(d[52]),"+f"(d[53]),"+f"(d[54]),"+f"(d[55]),"+f"(d[56]),"+f"(d[57]),"+f"(d[58]),"+f"(d[59]),
      "+f"(d[60]),"+f"(d[61]),"+f"(d[62]),"+f"(d[63])
    : "r"(a0), "r"(a1), "r"(a2), "r"(a3), "r"(blo), "r"(sd), "n"(TB), "r"(DESC_HI));
}
template <int TB, int TA = 0> __device__ __forceinline__ void wgmma_ss192(float (&d)[96], uint32_t alo, uint32_t blo, int sd) {
  asm volatile("{\n.reg .pred p;\n.reg .b64 da, db;\n"
    "setp.ne.b32 p, %98, 0;\nmov.b64 da, {%96, %100};\nmov.b64 db, {%97, %100};\n"
    "wgmma.mma_async.sync.aligned.m64n192k16.f32.bf16.bf16 "
    "{%0,%1,%2,%3,%4,%5,%6,%7,%8,%9,%10,%11,%12,%13,%14,%15,%16,%17,%18,%19,%20,%21,%22,%23,"
    "%24,%25,%26,%27,%28,%29,%30,%31,%32,%33,%34,%35,%36,%37,%38,%39,%40,%41,%42,%43,%44,%45,%46,%47,"
    "%48,%49,%50,%51,%52,%53,%54,%55,%56,%57,%58,%59,%60,%61,%62,%63,%64,%65,%66,%67,%68,%69,%70,%71,"
    "%72,%73,%74,%75,%76,%77,%78,%79,%80,%81,%82,%83,%84,%85,%86,%87,%88,%89,%90,%91,%92,%93,%94,%95}, "
    "da, db, p, 1, 1, %101, %99;\n}\n"
    : "+f"(d[0]),"+f"(d[1]),"+f"(d[2]),"+f"(d[3]),"+f"(d[4]),"+f"(d[5]),"+f"(d[6]),"+f"(d[7]),"+f"(d[8]),"+f"(d[9]),"+f"(d[10]),"+f"(d[11]),
      "+f"(d[12]),"+f"(d[13]),"+f"(d[14]),"+f"(d[15]),"+f"(d[16]),"+f"(d[17]),"+f"(d[18]),"+f"(d[19]),"+f"(d[20]),"+f"(d[21]),"+f"(d[22]),"+f"(d[23]),
      "+f"(d[24]),"+f"(d[25]),"+f"(d[26]),"+f"(d[27]),"+f"(d[28]),"+f"(d[29]),"+f"(d[30]),"+f"(d[31]),"+f"(d[32]),"+f"(d[33]),"+f"(d[34]),"+f"(d[35]),
      "+f"(d[36]),"+f"(d[37]),"+f"(d[38]),"+f"(d[39]),"+f"(d[40]),"+f"(d[41]),"+f"(d[42]),"+f"(d[43]),"+f"(d[44]),"+f"(d[45]),"+f"(d[46]),"+f"(d[47]),
      "+f"(d[48]),"+f"(d[49]),"+f"(d[50]),"+f"(d[51]),"+f"(d[52]),"+f"(d[53]),"+f"(d[54]),"+f"(d[55]),"+f"(d[56]),"+f"(d[57]),"+f"(d[58]),"+f"(d[59]),
      "+f"(d[60]),"+f"(d[61]),"+f"(d[62]),"+f"(d[63]),"+f"(d[64]),"+f"(d[65]),"+f"(d[66]),"+f"(d[67]),"+f"(d[68]),"+f"(d[69]),"+f"(d[70]),"+f"(d[71]),
      "+f"(d[72]),"+f"(d[73]),"+f"(d[74]),"+f"(d[75]),"+f"(d[76]),"+f"(d[77]),"+f"(d[78]),"+f"(d[79]),"+f"(d[80]),"+f"(d[81]),"+f"(d[82]),"+f"(d[83]),
      "+f"(d[84]),"+f"(d[85]),"+f"(d[86]),"+f"(d[87]),"+f"(d[88]),"+f"(d[89]),"+f"(d[90]),"+f"(d[91]),"+f"(d[92]),"+f"(d[93]),"+f"(d[94]),"+f"(d[95])
    : "r"(alo), "r"(blo), "r"(sd), "n"(TB), "r"(DESC_HI), "n"(TA));
}

struct Ctx {
  uint32_t sm;
  uint32_t bar;
  uint32_t rbar;
  int cl, rank, wg, warp, lane, phases;
};
__device__ __forceinline__ void release(const Ctx& c, int b, int cnt = 1) {
  if (c.lane < 2) mbar_arrive_cl(c.rbar + b * 8, cnt);
}
#define HK 5
#define NPRO 6
#define ZLEAD 16
#define PFM 7
#define PF1 1
constexpr float SM_SCALE = 0.08838834764831845f * 1.4426950408889634f;
constexpr float SM_HI = 1.8446744e19f, SM_LO = 5.4210109e-20f;
constexpr int ORDER = 1;

__device__ __forceinline__ void stage_tile(const float (&a)[64], uint32_t buf, const Ctx& c, float s0, float s1) {
  const int row = (c.lane & 7) + ((c.lane >> 3) & 1) * 8;
  const uint32_t base = buf + (c.warp * 16 + row) * 128 + (((c.lane >> 4) ^ (row & 7)) << 4);
#pragma unroll
  for (int i = 0; i < 8; i++)
    stsm4((base ^ ((i & 3) << 5)) + (i >> 2) * 8192, pack_bf16(a[8 * i] * s0, a[8 * i + 1] * s0), pack_bf16(a[8 * i + 2] * s1, a[8 * i + 3] * s1),
          pack_bf16(a[8 * i + 4] * s0, a[8 * i + 5] * s0), pack_bf16(a[8 * i + 6] * s1, a[8 * i + 7] * s1));
}

__device__ __forceinline__ void p1_epilogue(const Params& p, const Ctx& c, const float (&acc)[64], int t, int type) {
  const int tile = p.s.r[c.cl].tile[t] & 63, b = c.wg * 2 + 1;
  mbar_wait(c.bar + (B_SE + b) * 8, (t & 1) ^ 1);
  if (type && tile >= 32) {
    const int r = 2 * (c.lane & 3) + ((c.lane >> 2) & 1);
    const uint32_t dst = c.sm + SM_BUF + b * 16384 + r * 128 + (((c.warp * 2) ^ r) << 4) + (c.lane >> 3) * 4;
#pragma unroll
    for (int i = 0; i < 16; i++) {
      asm volatile("st.shared.u32 [%0], %1;" ::"r"(dst + i * 1024), "r"(pack_bf16(acc[4 * i], acc[4 * i + 1])) : "memory");
      asm volatile("st.shared.u32 [%0], %1;" ::"r"((dst ^ 16) + i * 1024), "r"(pack_bf16(acc[4 * i + 2], acc[4 * i + 3])) : "memory");
    }
  } else {
    if (type) stage_tile(acc, c.sm + SM_BUF + b * 16384, c, SM_SCALE, SM_SCALE);
    else stage_tile(acc, c.sm + SM_BUF + b * 16384, c, 1.f, 1.f);
  }
  FENCE_ASYNC_SMEM();
  __syncwarp();
  if (c.lane == 0) mbar_arrive(c.bar + (B_SF + b) * 8);
}

__device__ __forceinline__ void p1_consumer(const Params& p, const Ctx& c) {
  const int n = p.s.r[c.cl].n1;
  const int type = p.s.r[c.cl].slab >> 3;
  const uint32_t bdesc = desc_lo(c.sm + SM_RING, 8192), adesc = desc_lo(c.sm + SM_BUF + 32768 + c.wg * 8192, 16);
  uint32_t A[128];
  float acc[64] = {};
  int slot = 0, par = 0;
  auto next = [&]() { if (++slot == 10) { slot = 0; par ^= 1; } };
  {
    const int row = (c.lane & 7) + ((c.lane >> 3) & 1) * 8;
    const uint32_t base = c.sm + SM_RING + (c.wg * 64 + c.warp * 16 + row) * 128 + (((c.lane >> 4) ^ (row & 7)) << 4);
    if (c.wg == 1) bar_sync(ORDER + 1, 256);
    int pa = -1, pb = -1;
    if (type) {
      mbar_wait(c.bar + B_P1F * 8, 0);
      WG_FENCE();
#pragma unroll
      for (int kk = 0; kk < 4; kk++) wgmma_ss128<1>(acc, adesc + kk * 2, bdesc + kk * 128, kk != 0);
      WG_COMMIT();
      pb = 0; slot = 1;
    }
#pragma unroll
    for (int kb = 0; kb < 8; kb++) {
      const int sa = slot;
      mbar_wait(c.bar + (B_P1F + slot) * 8, par);
      next();
      mbar_wait(c.bar + (B_P1F + slot) * 8, par);
      WG_FENCE();
#pragma unroll
      for (int kk = 0; kk < 4; kk++)
        wgmma_ss128<1>(acc, desc_lo(c.sm + SM_RING + c.wg * 8192, 16) + sa * 1024 + kk * 2, bdesc + slot * 1024 + kk * 128, (kb | kk) != 0 ? 1 : type);
      WG_COMMIT();
      if (kb == 1 && c.wg == 0) bar_arrive(ORDER + 1, 256);
#pragma unroll
      for (int kk = 0; kk < 4; kk++) ldsm4((base ^ (kk << 5)) + sa * 16384, A[kb * 16 + kk * 4], A[kb * 16 + kk * 4 + 1], A[kb * 16 + kk * 4 + 2], A[kb * 16 + kk * 4 + 3]);
      WG_WAIT(1);
      if (kb > 0) release(c, B_P1E + pa);
      if (kb > 0 || pb >= 0) release(c, B_P1E + pb);
      pa = sa; pb = slot;
      next();
    }
    WG_WAIT(0);
    __syncwarp();
    release(c, B_P1E + pa);
    release(c, B_P1E + pb);
    pin(acc);
    p1_epilogue(p, c, acc, 0, type);
  }
  for (int t = 1; t < n; t++) {
    bar_sync(ORDER + c.wg, 256);
    int prev1 = -1, prev2 = -1;
    if (type) {
      mbar_wait(c.bar + (B_P1F + slot) * 8, par);
      WG_FENCE();
#pragma unroll
      for (int kk = 0; kk < 4; kk++) wgmma_ss128<1>(acc, adesc + kk * 2, bdesc + slot * 1024 + kk * 128, kk != 0);
      WG_COMMIT();
      prev1 = slot;
      next();
    }
#pragma unroll
    for (int kb = 0; kb < 8; kb++) {
      mbar_wait(c.bar + (B_P1F + slot) * 8, par);
      WG_FENCE();
      const uint32_t d = bdesc + slot * 1024;
#pragma unroll
      for (int kk = 0; kk < 4; kk++)
        wgmma_rs128<1>(acc, A[kb * 16 + kk * 4], A[kb * 16 + kk * 4 + 1], A[kb * 16 + kk * 4 + 2], A[kb * 16 + kk * 4 + 3], d + kk * 128, (kb | kk) != 0 ? 1 : type);
      WG_COMMIT();
      if (kb == HK) {
        if (t + 1 < n || c.wg == 0) bar_arrive(ORDER + (c.wg ^ 1), 256);
      }
      if (kb > 0) { WG_WAIT(2); if (kb > 1 || prev2 >= 0) release(c, B_P1E + prev2); }
      prev2 = prev1; prev1 = slot;
      next();
    }
    WG_WAIT(1);
    release(c, B_P1E + prev2);
    WG_WAIT(0);
    pin(acc);
    release(c, B_P1E + prev1);
    p1_epilogue(p, c, acc, t, type);
  }
}

__device__ __forceinline__ void p1_producer(const Params& p, const Ctx& c) {
  const int n = p.s.r[c.cl].n1;
  const int type = p.s.r[c.cl].slab >> 3, grp = p.s.r[c.cl].slab & 7;
  int slot = NPRO % 10, par = NPRO < 10;
#pragma unroll 1
  for (int t = 0; t < n; t++) {
    const int tile = p.s.r[c.cl].tile[t] & 63;
    const CUtensorMap* m = &p.map_w[type * 2 + (tile >> 5)];
    const int n0 = (tile & 31) * 128 + c.rank * 64;
    const uint64_t pol = p.s.r[c.cl].tile[t] >= 192 ? POL(0) : L2_NORMAL;
    const int ptile = p.s.r[c.cl].tile[t + PF1 < n ? t + PF1 : t];
    const CUtensorMap* pm = &p.map_w[type * 2 + ((ptile >> 5) & 1)];
    if (t == 7 && (c.phases & 16)) flag_wait<true>(F_GATE, 256);
#pragma unroll 1
    for (int kb = t ? -type : (NPRO - type) >> 1; kb < 8; kb++) {
      if (t == 0 && 2 * kb + type >= NPRO) {
        mbar_wait(c.bar + (B_P1E + slot) * 8, par);
        mbar_expect(c.bar + (B_P1F + slot) * 8, 16384);
        tma2d(c.sm + SM_RING + slot * 16384, &p.map_a[type], kb * 64, grp * 256 + c.rank * 128, c.bar + (B_P1F + slot) * 8);
        if (++slot == 10) { slot = 0; par ^= 1; }
      }
      mbar_wait(c.bar + (B_P1E + slot) * 8, par);
      mbar_expect(c.bar + (B_P1F + slot) * 8, 16384);
      tma2d_mc(c.sm + SM_RING + slot * 16384 + c.rank * 8192, m, n0, kb < 0 ? 512 : kb * 64, c.bar + (B_P1F + slot) * 8, pol);
      if (t + PF1 < n && t > 0 && ((ptile >> 6) == 1 || ((ptile >> 6) == 2 && ((kb ^ grp) & PFM) == 0))) tma2d_prefetch(pm, (ptile & 31) * 128 + c.rank * 64, kb < 0 ? 512 : kb * 64);
      if (++slot == 10) { slot = 0; par ^= 1; }
    }
  }
}

__device__ __forceinline__ void wait_kv_dead(const Ctx& c, int h, int g) {
  if (g >= 2) flag_wait<false>(F_RD + h * 8 + g, 8 - g);
  else flag_wait<false>(F_CTX + max(c.lane & 7, g) * 64 + h, 4);
}
__device__ __forceinline__ int p1_storer(const Params& p, const Ctx& c) {
  const int n = p.s.r[c.cl].n1;
  const int type = p.s.r[c.cl].slab >> 3, grp = p.s.r[c.cl].slab & 7;
  for (int i = 0; i < 2 * n; i++) {
    const int t = i >> 1, w = i & 1, b = w * 2 + 1;
    const int tile = p.s.r[c.cl].tile[t] & 63;
    mbar_wait(c.bar + (B_SF + b) * 8, t & 1);
    const uint32_t src = c.sm + SM_BUF + b * 16384;
    int f = (type ? F_Q : F_KV) + (tile & 31) * 8 + grp;
    if (type == 0) {
      const int prev = p.s.prev[tile & 31][grp];
      if (prev != 255 && w == 0) wait_kv_dead(c, prev, grp);
      uint8_t* dst = g_S + (size_t)(S_K + ((tile & 32) + p.s.slot[tile & 31][grp]) * 8 + grp) * 65536 + c.rank * 32768 + w * 8192;
      bulk_store(dst, src, 8192);
      bulk_store(dst + 16384, src + 8192, 8192);
    } else if (tile < 32) {
      const int dep = p.s.qdep[tile * 8 + grp];
      if (dep != 511 && w == 0) {
        if (dep < 256) wait_kv_dead(c, dep >> 3, dep & 7);
        else flag_wait<false>(F_TS + dep - 256, 128);
      }
      bulk_store(g_S + (size_t)p.s.qblk[tile * 8 + grp] * 65536 + (c.rank * 2 + w) * 16384, src, 16384);
    } else {
      tma3d_store(&p.map_t[2], src, (grp * 4 + c.rank * 2 + w) * 32, 0, (tile - 32) * 64);
      f = F_QKVA + grp * 4 + ((0xE4390900u >> (2 * (tile - 30))) & 3);
    }
    BULK_COMMIT();
    BULK_WAIT(0);
    mbar_arrive_one(c.bar + (B_SE + b) * 8);
    if (i == 2 * n - 1) return f;
    if (w) flag_add(f, 2);
  }
  return -1;
}

__device__ __forceinline__ int p2_buf(int w, int i) { return w * 2 + (i & 1); }
__device__ __forceinline__ int p2_blk(int rank, int w, int i) { return ((i ^ w) & 1) == 0 ? 3 - rank : rank; }


template <int N>
__device__ __forceinline__ void row_max(const float (&s)[N], float& m0, float& m1) {
  float a0 = fmaxf(s[0], s[1]), a1 = fmaxf(s[2], s[3]);
#pragma unroll
  for (int i = 1; i < N / 4; i++) {
    m0 = fmaxf(m0, s[4 * i]); a0 = fmaxf(a0, s[4 * i + 1]);
    m1 = fmaxf(m1, s[4 * i + 2]); a1 = fmaxf(a1, s[4 * i + 3]);
  }
  m0 = fmaxf(m0, a0); m1 = fmaxf(m1, a1);
  m0 = fmaxf(m0, __shfl_xor_sync(0xffffffffu, m0, 1));
  m1 = fmaxf(m1, __shfl_xor_sync(0xffffffffu, m1, 1));
  m0 = fmaxf(m0, __shfl_xor_sync(0xffffffffu, m0, 2));
  m1 = fmaxf(m1, __shfl_xor_sync(0xffffffffu, m1, 2));
}
template <bool SUB, int N>
__device__ __forceinline__ void row_exp(const float (&s)[N], uint32_t (&P)[32], float m0, float m1, float& t0, float& t1) {
  float u0 = 0.f, u1 = 0.f;
  t0 = t1 = 0.f;
#pragma unroll
  for (int i = 0; i < N / 4; i++) {
    const float e0 = ex2(SUB ? s[4 * i] - m0 : s[4 * i]), e1 = ex2(SUB ? s[4 * i + 1] - m0 : s[4 * i + 1]);
    const float e2 = ex2(SUB ? s[4 * i + 2] - m1 : s[4 * i + 2]), e3 = ex2(SUB ? s[4 * i + 3] - m1 : s[4 * i + 3]);
    if (i == 0) { t0 = e0; u0 = e1; t1 = e2; u1 = e3; }
    else { t0 += e0; u0 += e1; t1 += e2; u1 += e3; }
    P[2 * i] = pack_bf16(e0, e1);
    P[2 * i + 1] = pack_bf16(e2, e3);
  }
#pragma unroll
  for (int i = N / 2; i < 32; i++) P[i] = 0;
  pin(P);
  t0 += u0; t1 += u1;
}
template <int N>
__device__ __forceinline__ void causal_mask(float (&s)[N], int thr) {
#pragma unroll
  for (int i = 0; i < 8; i++) {
    if (8 * i > thr) s[N - 32 + 4 * i] = -INFINITY;
    if (8 * i + 1 > thr) s[N - 32 + 4 * i + 1] = -INFINITY;
    if (8 * i - 8 > thr) s[N - 32 + 4 * i + 2] = -INFINITY;
    if (8 * i - 7 > thr) s[N - 32 + 4 * i + 3] = -INFINITY;
  }
}
__device__ __forceinline__ void issue_qk(float (&s)[32], uint32_t qd, uint32_t kd) {
  WG_FENCE();
#pragma unroll
  for (int kk = 0; kk < 8; kk++) wgmma_ss64<0>(s, qd + (kk >> 2) * 512 + (kk & 3) * 2, kd + (kk >> 2) * 1024 + (kk & 3) * 2, kk != 0);
  WG_COMMIT();
}
__device__ __forceinline__ void issue_qk(float (&s)[64], uint32_t qd, uint32_t kd) {
  WG_FENCE();
#pragma unroll
  for (int kk = 0; kk < 8; kk++) wgmma_ss128<0>(s, qd + (kk >> 2) * 512 + (kk & 3) * 2, kd + (kk >> 2) * 1024 + (kk & 3) * 2, kk != 0);
  WG_COMMIT();
}
template <int NK>
__device__ __forceinline__ void issue_pv(float (&o)[64], const uint32_t (&P)[32], uint32_t vd, int acc) {
  WG_FENCE();
#pragma unroll
  for (int kk = 0; kk < NK; kk++) wgmma_rs128<1>(o, P[4 * kk], P[4 * kk + 1], P[4 * kk + 2], P[4 * kk + 3], vd + kk * 128, kk != 0 ? 1 : acc);
  WG_COMMIT();
}
__device__ __forceinline__ void stage_done(const Ctx& c, int b) {
  FENCE_ASYNC_SMEM();
  __syncwarp();
  if (c.lane == 0) mbar_arrive(c.bar + (B_SF + b) * 8);
}
__device__ __forceinline__ void p2_epilogue(const float (&o)[64], float s0, float s1, const Ctx& c, int b) {
  stage_tile(o, c.sm + SM_BUF + b * 16384, c, s0, s1);
  stage_done(c, b);
}

struct P2State {
  float m0, m1, l0, l1;
  bool shift;
  float e0, e1;
  int ks;
  int wi, ai;
  uint32_t wb, ab;
  uint32_t qd;
};
__device__ __forceinline__ int wrap5(int q) { return q >= 5 ? q - 5 : q; }
__device__ __forceinline__ void turn_wait(uint32_t ring, int i) { mbar_wait(ring + (i & 3) * 8, (i >> 2) & 1); }
__device__ __forceinline__ void turn_pass(const Ctx& c, uint32_t ring, int i) { if (c.lane == 0) mbar_arrive(ring + (i & 3) * 8); }
__device__ __forceinline__ void p2_scales(P2State& z) {
  float l0 = z.l0, l1 = z.l1;
  l0 += __shfl_xor_sync(0xffffffffu, l0, 1);
  l1 += __shfl_xor_sync(0xffffffffu, l1, 1);
  l0 += __shfl_xor_sync(0xffffffffu, l0, 2);
  l1 += __shfl_xor_sync(0xffffffffu, l1, 2);
  asm("rcp.approx.ftz.f32 %0, %1;" : "=f"(z.e0) : "f"(l0));
  asm("rcp.approx.ftz.f32 %0, %1;" : "=f"(z.e1) : "f"(l1));
}
template <int N>
__device__ __forceinline__ void p2_first(const Ctx& c, P2State& z, float (&o)[64], uint32_t (&Pc)[32], uint32_t (&Pn)[32],
                                         int ks, int vs, int cnt, int acc) {
  float s[N] = {};
  issue_qk(s, z.qd, desc_lo(c.sm + SM_RING, 16) + ks * 2048);
  if (vs >= 0) {
    p2_scales(z);
    issue_pv<8>(o, Pc, desc_lo(c.sm + SM_RING, 16384) + vs * 2048, acc);
  } else {
    WG_COMMIT();
  }
  mbar_expect(z.ab + (z.ai++ & 3) * 8, cnt == 1 ? 8192 : 0);
  WG_WAIT(1);
  pin(s);
  release(c, B_P2E + ks, cnt);
  causal_mask(s, c.warp * 16 + (c.lane >> 2) - 2 * (c.lane & 3));
  z.m0 = z.m1 = 0.f;
  row_exp<false>(s, Pn, 0.f, 0.f, z.l0, z.l1);
  z.shift = __any_sync(0xffffffffu, !(z.l0 + z.l1 <= SM_HI) || ((c.lane & 3) == 0 && !(fminf(z.l0, z.l1) >= SM_LO)));
  if (__builtin_expect(z.shift, 0)) {
    z.m0 = z.m1 = -INFINITY;
    row_max(s, z.m0, z.m1);
    row_exp<true>(s, Pn, z.m0, z.m1, z.l0, z.l1);
  }
  WG_WAIT(0);
  pin(o);
  if (vs >= 0) release(c, B_P2E + vs, 1);
}

template <bool SECOND>
__device__ __forceinline__ void p2_turn(const Ctx& c, P2State& z, float (&o)[64], uint32_t (&Pc)[32], uint32_t (&Pn)[32],
                                        int eb = -1, bool half = false, int vcnt = 1) {
  float s[64] = {};
  const int ks = z.ks, vs = wrap5(ks + 1);
  turn_wait(z.wb, z.wi++);
  issue_qk(s, z.qd, desc_lo(c.sm + SM_RING, 16) + ks * 2048);
  const uint32_t vd = desc_lo(c.sm + SM_RING, 16384) + vs * 2048;
  if (SECOND) {
    if (eb >= 0) stage_tile(o, c.sm + SM_BUF + eb * 16384, c, z.e0, z.e1);
    if (half) issue_pv<4>(o, Pc, vd, 0); else issue_pv<8>(o, Pc, vd, 0);
  } else {
    issue_pv<8>(o, Pc, vd, 1);
  }
  turn_pass(c, z.ab, z.ai++);
  if (SECOND) { if (eb >= 0) stage_done(c, eb); }
  z.ks = wrap5(ks + 2);
  WG_WAIT(1);
  pin(s);
  release(c, B_P2E + ks, 1);
  float t0, t1, a0 = 1.f, a1 = 1.f;
  row_exp<false>(s, Pn, 0.f, 0.f, t0, t1);
  z.shift = __any_sync(0xffffffffu, z.shift || !(t0 + t1 <= SM_HI));
  const bool redo = z.shift;
  if (__builtin_expect(redo, 0)) {
    float n0 = z.m0, n1 = z.m1;
    row_max(s, n0, n1);
    a0 = ex2(z.m0 - n0); a1 = ex2(z.m1 - n1);
    z.m0 = n0; z.m1 = n1;
    z.l0 *= a0; z.l1 *= a1;
    row_exp<true>(s, Pn, z.m0, z.m1, t0, t1);
  }
  WG_WAIT(0);
  pin(o);
  release(c, B_P2E + vs, vcnt);
  if (__builtin_expect(redo, 0)) {
#pragma unroll
    for (int i = 0; i < 16; i++) { o[4 * i] *= a0; o[4 * i + 1] *= a0; o[4 * i + 2] *= a1; o[4 * i + 3] *= a1; }
  }
  z.l0 += t0; z.l1 += t1;
}
__device__ __forceinline__ void copy_p(uint32_t (&d)[32], const uint32_t (&s)[32], int zero) {
#pragma unroll
  for (int i = 0; i < 32; i++) asm volatile("add.s32 %0, %1, %2;" : "=r"(d[i]) : "r"(s[i]), "r"(zero));
}

__device__ __forceinline__ void p2_consumer(const Params& p, const Ctx& c, int rot) {
  const int nit = p.s.r[c.cl].n2;
  const uint32_t fring = c.bar + B_P2F * 8, oring = c.bar + B_ORD * 8;
  float o[64] = {};
  uint32_t Pa[32] = {}, Pb[32] = {};
  P2State z;
  z.e0 = z.e1 = z.l0 = z.l1 = 0.f; z.ks = rot; z.shift = false;
  int acc = 0, n = 0;
  for (int it = 0; it < nit; it++) {
    const int j = p.s.r[c.cl].item[it] & 7, blk = p2_blk(c.rank, c.wg, it);
    const int lng = ((it ^ c.wg) & 1) ^ 1;
    z.qd = desc_lo(c.sm + SM_BUF, 16) + p2_buf(c.wg, it) * 1024;
    if (lng) { z.wb = oring; z.wi = n - it; z.ab = fring; z.ai = n + 1; }
    else { z.wb = fring; z.wi = n + 2; z.ab = oring; z.ai = n - it; }
    mbar_wait(c.bar + (B_QF + p2_buf(c.wg, it)) * 8, (it >> 1) & 1);
    turn_wait(fring, n + 1 - lng);
    const int vs = it ? wrap5(z.ks + 1) : -1, ks = lng ? z.ks : wrap5(z.ks + (it ? 2 : 1));
    if (blk & 1) p2_first<64>(c, z, o, Pa, Pb, ks, vs, 1 + lng, acc);
    else p2_first<32>(c, z, o, Pa, Pb, ks, vs, 1 + lng, acc);
    z.ks = wrap5(ks + (it == 0 && lng ? 1 : 2));
    n += 2 * j + 2;
    int left = 2 * j + lng;
    acc = left != 0;
    if (left == 0) { copy_p(Pa, Pb, p.zero); continue; }
    p2_turn<true>(c, z, o, Pb, Pa, it > 0 ? p2_buf(c.wg, it - 1) : -1, !(blk & 1), 1 + lng);
    while (--left > 0) {
      p2_turn<false>(c, z, o, Pa, Pb);
      if (--left == 0) { copy_p(Pa, Pb, p.zero); break; }
      p2_turn<false>(c, z, o, Pb, Pa);
    }
  }
  {
    if (!acc && nit > 1) p2_epilogue(o, z.e0, z.e1, c, p2_buf(c.wg, nit));
    turn_wait(z.wb, z.wi);
    issue_pv<8>(o, Pa, desc_lo(c.sm + SM_RING, 16384) + z.ks * 2048, acc);
    if (((nit - 1) ^ c.wg) & 1) turn_pass(c, z.ab, z.ai);
    p2_scales(z);
    WG_WAIT(0);
    pin(o);
    release(c, B_P2E + z.ks);
    p2_epilogue(o, z.e0, z.e1, c, p2_buf(c.wg, nit - 1));
  }
}

__device__ __forceinline__ void p2_load_q(const Params& p, const Ctx& c, int it, int w) {
  const int item = p.s.r[c.cl].item[it], b = p2_buf(w, it);
  mbar_expect(c.bar + (B_QF + b) * 8, 16384);
  bulk_load(c.sm + SM_BUF + b * 16384, g_S + (size_t)p.s.qblk[item] * 65536 + p2_blk(c.rank, w, it) * 16384, 16384, c.bar + (B_QF + b) * 8, POL(4));
}
__device__ __forceinline__ void wait_p1_free(const Ctx& c, int u1, int s) {
  mbar_wait(c.bar + (B_P1E + 2 * s) * 8, ((u1 - 1 - 2 * s) / 10) & 1);
  mbar_wait(c.bar + (B_P1E + 2 * s + 1) * 8, ((u1 - 2 - 2 * s) / 10) & 1);
}
__device__ __forceinline__ void p2_producer(const Params& p, const Ctx& c, int u1, int rot) {
  const int nit = p.s.r[c.cl].n2;
  int slot = rot, cnt = 0, par = 1, n = 0;
  const uint8_t* pv = nullptr;
  bool pl = false;
  auto load = [&](const uint8_t* src, int expect, uint32_t fb, bool last) {
    if (cnt < 5) {
      if (u1) {
        wait_p1_free(c, u1, slot);
        if (cnt == 0) p2_load_q(p, c, 0, 1);
      }
      cnt++;
    } else {
      if (slot == rot) par ^= 1;
      mbar_wait(c.bar + (B_P2E + slot) * 8, par);
    }
    if (expect) mbar_expect(fb, expect);
    bulk_load_mc(c.sm + SM_RING + slot * 32768 + c.rank * 16384, src, 16384, fb, last ? POL(5) : L2_NORMAL);
    slot = wrap5(slot + 1);
  };
  for (int it = 0; it < nit; it++) {
    const int item = p.s.r[c.cl].item[it], h = item >> 3, j = item & 7;
    if (it == 1 && (c.phases & 16) && p.s.r[c.cl].n1 < 8) flag_wait<true>(F_GATE, 256);
    uint32_t ready = (c.phases & 16) ? 0u : 255u;
    if (it == 0) { if (c.phases & 16) flag_wait<false>(F_Q + item, 4); mbar_wait(c.bar + B_LAD * 8, 0); p2_load_q(p, c, 0, 0); if (!u1) p2_load_q(p, c, 0, 1); }
    for (int t = 2 * j + 1; t >= 0; t--) {
      mask_wait(ready, t >> 1, F_KV + h * 8 + (c.lane & 7), 8);
      const uint8_t* k = g_S + (size_t)(2 * S_K + p.s.slot[h][t >> 1] * 16 + t) * 32768 + c.rank * 16384;
      const uint32_t fb = c.bar + (B_P2F + (n & 3)) * 8;
      const bool last = (p.s.r[c.cl].last[it] >> (t >> 1)) & 1;
      load(k, pv && t != 2 * j ? 65536 : 32768, fb, last);
      if (!(t & 1) && t + 4 <= 2 * j && c.rank == 0) flag_add_rx(F_RD + h * 8 + (t >> 1) + 2);
      if (pv) load(pv, 0, t != 2 * j ? fb : c.bar + (B_ORD + ((n - 1 - it) & 3)) * 8, pl);
      pl = last;
      pv = k + (size_t)NH * 16 * 32768;
      n++;
    }
  }
  load(pv, 32768, c.bar + (B_P2F + (n & 3)) * 8, pl);
}

__device__ __forceinline__ void publish_and_load_q(const Params& p, const Ctx& c, int f, int it, int seen) {
  const bool want = it < p.s.r[c.cl].n2, early = want && __all_sync(0xffffffffu, seen >= 4);
  if (early) { p2_load_q(p, c, it, it & 1); p2_load_q(p, c, it, (it & 1) ^ 1); }
  if (f >= 0) flag_add(f, 2);
  if (want && !early) {
    if (c.phases & 16) flag_wait<false>(F_Q + p.s.r[c.cl].item[it], 4);
    p2_load_q(p, c, it, it & 1); p2_load_q(p, c, it, (it & 1) ^ 1);
  }
}
__device__ __forceinline__ void p2_storer(const Params& p, const Ctx& c, int sfpar) {
  const int nit = p.s.r[c.cl].n2;
  int held = -1;
  for (int i = 0; i < 2 * nit; i++) {
    const int it = i >> 1, w = (it ^ i ^ 1) & 1, b = p2_buf(w, it);
    const int item = p.s.r[c.cl].item[it], h = item >> 3, j = item & 7;
    mbar_wait(c.bar + (B_SF + b) * 8, (sfpar >> b) & 1);
    sfpar ^= 1 << b;
    bulk_store(g_S + (size_t)p.s.qblk[item] * 65536 + p2_blk(c.rank, w, it) * 16384, c.sm + SM_BUF + b * 16384, 16384, POL(1));
    BULK_COMMIT();
    if (i & 1) {
      if (it + 2 == nit && (p.s.r[c.cl].item[it + 1] & 7) == 0) { held = F_CTX + j * 64 + h; continue; }
      const int seen = flag_peek(F_Q + p.s.r[c.cl].item[min(it + 2, nit - 1)]);
      BULK_WAIT(0);
      if (it + 1 == nit) release(c, B_DONE);
      publish_and_load_q(p, c, F_CTX + j * 64 + h, it + 2, seen);
    }
  }
  if (held >= 0) flag_add_rx(held, 2);
}

__device__ __forceinline__ int p3_pos(int i, int x) { return i < 4 ? (i + x) & 3 : 4; }
__device__ __forceinline__ void p3_consumer(const Params& p, const Ctx& c, int x) {
  const bool first = p.s.r[c.cl].p3 >= 24;
  const int tile = p.s.r[c.cl].p3 - (first ? 24 : 0), j = tile / 3, nt = tile - 3 * j;
  const int na = first ? 9 : 0, nb = p.s.task[c.cl][1] - p.s.task[c.cl][0];
  const uint32_t ad = desc_lo(c.sm + SM_RING + c.wg * 8192, 16), bd = desc_lo(c.sm + SM_RING + 16384, 4096);
  float acc[96] = {};
  int slot = 0, par = 0, prev = 0;
  float g0 = 0.f, g1 = 0.f;
  const int hold = c.wg && LAG ? na + nb - LAG : -1, pass = c.wg || !LAG ? -1 : na + nb - 1;
  const float* gp = g_gate + j * 256 + c.rank * 128 + c.wg * 64 + c.warp * 16 + (c.lane >> 2);
#pragma unroll 1
  for (int kb = 0; kb < na; kb++) {
    if (kb == hold) bar_sync(6, 256);
    mbar_wait(c.bar + (B_P3F + slot) * 8, par);
    WG_FENCE();
#pragma unroll
    for (int kk = 0; kk < 4; kk++) wgmma_ss192<1, 1>(acc, ad + p3_pos(slot, x) * 2560 + kk * 128, bd + p3_pos(slot, x) * 2560 + (kk >> 1) * 768 + (kk & 1) * 128, kk != 0 ? 1 : kb != 0);
    WG_COMMIT();
    if (kb == pass) bar_arrive(6, 256);
    WG_WAIT(1);
    if (kb > 0) release(c, B_P3E + prev);
    else { g0 = __ldcg(gp); g1 = __ldcg(gp + 8); }
    prev = slot;
    if (++slot == 5) { slot = 0; par ^= 1; }
  }
#pragma unroll 1
  for (int kb = na; kb < na + nb; kb++) {
    if (kb == hold) bar_sync(6, 256);
    mbar_wait(c.bar + (B_P3F + slot) * 8, par);
    WG_FENCE();
#pragma unroll
    for (int kk = 0; kk < 4; kk++) wgmma_ss192<1>(acc, ad + p3_pos(slot, x) * 2560 + kk * 2, bd + p3_pos(slot, x) * 2560 + (kk >> 1) * 768 + (kk & 1) * 128, kk != 0 ? 1 : kb != 0);
    WG_COMMIT();
    if (kb == pass) bar_arrive(6, 256);
    WG_WAIT(1);
    if (kb > 0) release(c, B_P3E + prev);
    else { g0 = __ldcg(gp); g1 = __ldcg(gp + 8); }
    prev = slot;
    if (++slot == 5) { slot = 0; par ^= 1; }
  }
  g0 = __fdividef(1.f, 1.f + g0); g1 = __fdividef(1.f, 1.f + g1);
  WG_WAIT(0);
  pin(acc);
  if (first) bar_sync(4 + c.wg, 128);
  mbar_wait(c.bar + B_OUT * 8, 0);
  const int row = (c.lane & 7) + ((c.lane >> 3) & 1) * 8;
  const uint32_t wbase = c.sm + SM_RING + c.wg * 8192 + c.warp * 2048;
  const uint32_t base = wbase + row * 128 + (((c.lane >> 4) ^ (row & 7)) << 4);
#pragma unroll
  for (int i = 0; i < 12; i++) {
    stsm4((base ^ ((i & 3) << 5)) + (i >> 2) * 40960, pack_bf16(acc[8 * i] * g0, acc[8 * i + 1] * g0), pack_bf16(acc[8 * i + 2] * g1, acc[8 * i + 3] * g1),
          pack_bf16(acc[8 * i + 4] * g0, acc[8 * i + 5] * g0), pack_bf16(acc[8 * i + 6] * g1, acc[8 * i + 7] * g1));
    if ((i & 3) == 3) {
      FENCE_ASYNC_SMEM();
      bar_sync(4 + c.wg, 128);
      if (c.warp == (i >> 2)) tma2d_add(&p.map_out, c.sm + SM_RING + c.wg * 8192 + c.warp * 40960, nt * 192 + c.warp * 64, j * 256 + c.rank * 128 + c.wg * 64);
    }
  }
  BULK_COMMIT();
  BULK_WAIT_READ(0);
}

__device__ __forceinline__ void p3_producer(const Params& p, const Ctx& c, int u1, int u2, int rot, int x) {
  const bool first = p.s.r[c.cl].p3 >= 24;
  const int tile = p.s.r[c.cl].p3 - (first ? 24 : 0), j = tile / 3, nt = tile - 3 * j;
  int slot = 0, par = 1, cnt = 0;
  auto wait_free = [&](int s) {
    const int f = wrap5(s + 5 - rot);
    if (f < u2) mbar_wait(c.bar + (B_P2E + s) * 8, ((u2 - 1 - f) / 5) & 1);
    else if (u1) wait_p1_free(c, u1, s);
  };
  asm volatile(ELECT("prefetch.tensormap [%0];") ::"l"(&p.map_o[0]) : "memory");
  asm volatile(ELECT("prefetch.tensormap [%0];") ::"l"(&p.map_out) : "memory");
  if ((c.phases & 16) && p.s.r[c.cl].n1 < 8 && p.s.r[c.cl].n2 < 2) flag_wait<true>(F_GATE, 256);
  uint32_t ready = (c.phases & 16) ? 0u : ~0u;
  const int q0 = p.s.task[c.cl][0], q1 = p.s.task[c.cl][1];
  for (int q = q0 - (first ? 9 : 0); q < q1; q++) {
    if (q == max(q0, 64 - ZLEAD)) mbar_arrive_one(c.bar + B_ZF * 8);
    const bool brA = q < q0;
    const int kb = brA ? q - q0 + 9 : p.s.p3_order[tile][q];
    if (!brA) mask_wait(ready, kb >> 1, F_CTX + j * 64 + c.lane, 4);
    else if (kb == 0 && (c.phases & 16)) flag_wait<false>(F_CTX + j * 64 + 32, 16);
    const uint8_t* a = brA ? g_oA + (j * 4 + c.rank * 2) * 73728 + kb * 8192 : g_S + (size_t)p.s.qblk[(kb >> 1) * 8 + j] * 65536 + c.rank * 32768 + (kb & 1) * 8192;
    const uint32_t st = c.sm + SM_RING + p3_pos(slot, x) * 40960, fb = c.bar + (B_P3F + slot) * 8;
    if (cnt < 4) { wait_free(p3_pos(cnt, x)); wait_free(p3_pos(cnt, x) + 1); }
    else if (cnt == 4) mbar_wait(c.bar + B_DONE * 8, 0);
    else mbar_wait(c.bar + (B_P3E + slot) * 8, par);
    cnt++;
    mbar_expect(fb, 40960);
    bulk_load(st, a, 8192, fb, POL(3));
    bulk_load(st + 8192, a + (brA ? 73728 : 16384), 8192, fb, POL(3));
    tma3d_mc(st + 16384 + c.rank * 12288, &p.map_o[brA], 0, kb * 64 + c.rank * 32, nt * 3, fb);
    if (++slot == 5) { slot = 0; par ^= 1; }
  }
}

__device__ __forceinline__ float bf_lo(uint32_t w) { return __uint_as_float(w << 16); }
__device__ __forceinline__ float bf_hi(uint32_t w) { return __uint_as_float(w & 0xffff0000u); }

__device__ __forceinline__ void gate_rows(const Params& p, int row0, int lane) {
  const uint4* x = reinterpret_cast<const uint4*>(p.x + (size_t)(row0 + (lane >> 2)) * DM) + (lane & 3);
  const uint4* w = reinterpret_cast<const uint4*>(p.gate_w) + (lane & 3);
  float a = 0.f;
#pragma unroll 1
  for (int b = 0; b < 3; b++) {
    uint4 u[6];
#pragma unroll
    for (int i = 0; i < 6; i++) u[i] = __ldg(x + (b * 6 + i) * 4);
#pragma unroll
    for (int i = 0; i < 6; i++) {
      const uint4 v = __ldg(w + (b * 6 + i) * 4);
      a = fmaf(bf_lo(u[i].x), bf_lo(v.x), a); a = fmaf(bf_hi(u[i].x), bf_hi(v.x), a);
      a = fmaf(bf_lo(u[i].y), bf_lo(v.y), a); a = fmaf(bf_hi(u[i].y), bf_hi(v.y), a);
      a = fmaf(bf_lo(u[i].z), bf_lo(v.z), a); a = fmaf(bf_hi(u[i].z), bf_hi(v.z), a);
      a = fmaf(bf_lo(u[i].w), bf_lo(v.w), a); a = fmaf(bf_hi(u[i].w), bf_hi(v.w), a);
    }
  }
  a += __shfl_xor_sync(0xffffffffu, a, 1);
  a += __shfl_xor_sync(0xffffffffu, a, 2);
  if ((lane & 3) == 0) g_gate[row0 + (lane >> 2)] = __expf(fminf(a, 60.f));
}

__device__ __forceinline__ void lds10(uint32_t (&k)[10], uint32_t a) {
  asm volatile("ld.shared.v2.u32 {%0, %1}, [%10];\nld.shared.v2.u32 {%2, %3}, [%10+8];\nld.shared.v2.u32 {%4, %5}, [%10+16];\n"
               "ld.shared.v2.u32 {%6, %7}, [%10+24];\nld.shared.v2.u32 {%8, %9}, [%10+32];"
               : "=r"(k[0]), "=r"(k[1]), "=r"(k[2]), "=r"(k[3]), "=r"(k[4]), "=r"(k[5]), "=r"(k[6]), "=r"(k[7]), "=r"(k[8]), "=r"(k[9]) : "r"(a));
}
__device__ __forceinline__ void local_attn(const Params& p, const Ctx& c, int rb, int hs) {
  const int lane = c.lane, grp = rb >> 2, par = lane >> 4, i0 = 2 * (lane & 15);
  const uint32_t buf = c.sm + SM_BUF + (c.warp - 2) * 8192, bqk = c.bar + (B_LA + (c.warp - 2) * 2) * 8, bv = bqk + 8;
  const uint32_t mine = buf + 2304 + par * 160 + i0 * 4;
  const bool flags = c.phases & 16;
  auto fetch_qk = [&](int i) {
    if (flags && !(i & 1)) {
      const int q = i >> 1;
      const int tgt = q == 0 ? 24 : q == 3 ? 8 : 12;
      flag_wait<false>(F_QKVA + (grp - (grp > 0 && (rb & 3) == 0 ? par : 0)) * 4 + q, tgt);
    }
    mbar_expect(bqk, 5184);
    tma3d(buf, &p.map_t[0], rb * 32, 0, 9 * (4 * i + hs), bqk, POL(2));
    tma3d(buf + 2304, &p.map_t[1], rb * 32 - 8, 0, 288 + 9 * (4 * i + hs), bqk, POL(2));
  };
  auto fetch_v = [&](int i) { mbar_expect(bv, 2880); tma3d(buf + 5248, &p.map_t[1], rb * 32 - 8, 0, 576 + 9 * (4 * i + hs), bv, POL(2)); };
  fetch_qk(0);
  if (flags) flag_wait<true>(F_GATE, 256);
#pragma unroll 1
  for (int q = 0; q < 8; q++) {
    fetch_v(q);
    float a[8], b[8];
#pragma unroll
    for (int w = 0; w < 8; w++) a[w] = b[w] = 0.f;
    mbar_wait(bqk, q & 1);
#pragma unroll 1
    for (int j = 0; j < 9; j++) {
      uint32_t x, y, k[10];
      asm volatile("ld.shared.v2.u32 {%0, %1}, [%2];" : "=r"(x), "=r"(y) : "r"(buf + lane * 8 + j * 256));
      lds10(k, mine + j * 320);
      const float xl = bf_lo(x), xh = bf_hi(x), yl = bf_lo(y), yh = bf_hi(y);
#pragma unroll
      for (int m = 1; m < 10; m++) {
        const float kl = bf_lo(k[m]), kh = bf_hi(k[m]);
        if (m < 9) a[8 - m] = fmaf(xl, kl, fmaf(xh, kh, a[8 - m]));
        if (m > 1) b[9 - m] = fmaf(yl, kl, fmaf(yh, kh, b[9 - m]));
      }
    }
    __syncwarp();
    mbar_wait(bv, q & 1);
    if (q & 1) flag_add_rx(F_TS + (q >> 1));
    if (q < 7) fetch_qk(q + 1);
    constexpr float SC = 0.23570226039551584f * 1.4426950408889634f;
    const float* gp = g_gate + rb * 64 + 2 * i0 + par;
    const float ga = __ldcg(gp), gb = __ldcg(gp + 2);
    float ma = a[0], mb = b[0];
#pragma unroll
    for (int w = 1; w < 8; w++) {
      if (rb == 0) {
        if (i0 < w) a[w] = -INFINITY;
        if (i0 + 1 < w) b[w] = -INFINITY;
      }
      ma = fmaxf(ma, a[w]); mb = fmaxf(mb, b[w]);
    }
    float la = 0.f, lb = 0.f;
#pragma unroll
    for (int w = 0; w < 8; w++) {
      a[w] = ex2((a[w] - ma) * SC); b[w] = ex2((b[w] - mb) * SC);
      la += a[w]; lb += b[w];
    }
    la = __fdividef(ga, la); lb = __fdividef(gb, lb);
#pragma unroll
    for (int w = 0; w < 8; w++) { a[w] *= la; b[w] *= lb; }
    uint8_t* dst = g_oA + rb * 73728 + ((i0 & 2) + par) * 4;
#pragma unroll 1
    for (int j = 0; j < 9; j++) {
      uint32_t v[10];
      lds10(v, mine + 2944 + j * 320);
      float a0 = 0.f, a1 = 0.f, b0 = 0.f, b1 = 0.f;
#pragma unroll
      for (int m = 1; m < 10; m++) {
        const float vl = bf_lo(v[m]), vh = bf_hi(v[m]);
        if (m < 9) { a0 = fmaf(a[8 - m], vl, a0); a1 = fmaf(a[8 - m], vh, a1); }
        if (m > 1) { b0 = fmaf(b[9 - m], vl, b0); b1 = fmaf(b[9 - m], vh, b1); }
      }
      const uint32_t wa = pack_bf16(a0, a1), wb = pack_bf16(b0, b1);
      const uint32_t got = __shfl_xor_sync(0xffffffffu, par ? wa : wb, 16);
      const uint32_t r0 = par ? got : wa, r1 = par ? wb : got;
      const int col = 18 * (4 * q + hs) + 2 * j, o = col * 128 + ((((i0 >> 2) ^ col) & 7) << 4);
      *reinterpret_cast<uint32_t*>(dst + o) = __byte_perm(r0, r1, 0x5410);
      *reinterpret_cast<uint32_t*>(dst + ((o + 128) ^ 16)) = __byte_perm(r0, r1, 0x7632);
    }
    __syncwarp();
  }
  mbar_arrive_one(c.bar + B_LAD * 8);
  flag_add(F_CTX + grp * 64 + 32);
}

__global__ void __cluster_dims__(2, 1, 1) __launch_bounds__(384, 1) fused_kernel(const __grid_constant__ Params p) {
  extern __shared__ uint8_t smem_raw[];
  Ctx c;
  c.sm = ((uint32_t)__cvta_generic_to_shared(smem_raw) + 1023u) & ~1023u;
  c.bar = c.sm + SM_BAR;
  c.lane = threadIdx.x & 31;
  const int wid = __shfl_sync(0xffffffffu, threadIdx.x >> 5, 0);
  if (wid < 6) asm volatile("prefetch.tensormap [%0];" ::"l"(&p.map_a[0] + wid) : "memory");
  c.wg = wid >> 2;
  c.warp = wid & 3;
  c.cl = (blockIdx.x + (wid >> 4)) >> 1;
  c.rank = blockIdx.x & 1;
  c.rbar = mapa(c.bar, c.lane & 1);
  {
    const int w = wid, cnt = (((int)(B_CNT >> (4 * w)) - 1) & 15) + 1;
    if (w < 11) {
#pragma unroll
      for (int i = 0; i < 8; i++) asm volatile("mbarrier.init.shared::cta.b64 [%0], %1;" ::"r"(c.bar + w * 64 + i * 8), "r"(cnt));
    }
    asm volatile("fence.mbarrier_init.release.cluster;" ::: "memory");
  }
  asm volatile("barrier.cluster.arrive.relaxed;" ::: "memory");
  c.phases = p.s.r[c.cl].phases;
  const bool do1 = p.s.r[c.cl].n1 > 0, do2 = p.s.r[c.cl].n2 > 0, do3 = p.s.r[c.cl].p3 != 255;
  if (do1 && c.wg == 2 && c.warp == 0) {
    const int type = p.s.r[c.cl].slab >> 3;
    FENCE_ASYNC_SMEM();
    mbar_expect(c.bar + B_P1F * 8, type ? 32768 : 16384);
    tma2d(type ? c.sm + SM_BUF + 32768 : c.sm + SM_RING, &p.map_a[type], type ? 512 : 0, (p.s.r[c.cl].slab & 7) * 256 + c.rank * 128, c.bar + B_P1F * 8);
  }
  asm volatile("barrier.cluster.wait.acquire;" ::: "memory");
  if (do1 && c.wg == 2 && c.warp == 0) {
    const int type = p.s.r[c.cl].slab >> 3, tile = p.s.r[c.cl].tile[0] & 63;
    const CUtensorMap* m = &p.map_w[type * 2 + (tile >> 5)];
#pragma unroll 1
    for (int s = 1 - type; s < NPRO; s++) {
      const int kb = (s - type) >> 1;
      const uint32_t fb = c.bar + (B_P1F + s) * 8;
      if (s) mbar_expect(fb, 16384);
      if ((s ^ type) & 1) tma2d_mc(c.sm + SM_RING + s * 16384 + c.rank * 8192, m, (tile & 31) * 128 + c.rank * 64, kb < 0 ? 512 : kb * 64, fb);
      else tma2d(c.sm + SM_RING + s * 16384, &p.map_a[type], kb * 64, (p.s.r[c.cl].slab & 7) * 256 + c.rank * 128, fb);
    }
  }

  if (c.wg < 2) {
    asm volatile("setmaxnreg.inc.sync.aligned.u32 224;");
    if (c.wg == 1) {
      if (do1) bar_arrive(ORDER, 256);
      if (c.lane == 0) mbar_arrive(c.bar + B_P2F * 8);
    }
    if (do1) p1_consumer(p, c);
    if (do2) p2_consumer(p, c, p.s.r[c.cl].rot);
    if (do3) p3_consumer(p, c, p.s.r[c.cl].x3);
    if (c.lane == 0) mbar_arrive(c.bar + B_FIN * 8);
    __syncwarp();
    cluster_sync();
  } else {
    asm volatile("setmaxnreg.dec.sync.aligned.u32 56;");
    if (c.warp == 0) {
      if (do1) p1_producer(p, c);
      if (do2) p2_producer(p, c, p.s.r[c.cl].u1, p.s.r[c.cl].rot);
      if (do3) p3_producer(p, c, p.s.r[c.cl].u1, p.s.r[c.cl].u2, p.s.r[c.cl].rot, p.s.r[c.cl].x3);
    } else if (c.warp == 1) {
      const int f = do1 ? p1_storer(p, c) : -1;
      if (do2) {
        publish_and_load_q(p, c, f, 1, flag_peek(F_Q + p.s.r[c.cl].item[1]));
        p2_storer(p, c, (p.s.r[c.cl].n1 & 1) * 10);
      } else {
        const bool idle = mbar_test(c.bar + B_LAD * 8, 0);
        if (idle) release(c, B_DONE);
        if (f >= 0) flag_add(f, 2);
        if (!idle) { mbar_wait(c.bar + B_LAD * 8, 0); release(c, B_DONE); }
      }
      if (do3) {
        const int tile = p.s.r[c.cl].p3 % 24;
        if (p.s.task[c.cl][1] == 64) {
          mbar_wait(c.bar + B_ZF * 8, 0);
          const int j = tile / 3, nt = tile - 3 * j;
          uint4* o = reinterpret_cast<uint4*>(p.out + (size_t)(j * 256 + c.rank * 128 + (c.lane >> 3)) * DM + nt * 192) + (c.lane & 7);
#pragma unroll 4
          for (int r = 0; r < 32; r++) o[r * 288] = o[r * 288 + 8] = o[r * 288 + 16] = make_uint4(0u, 0u, 0u, 0u);
          __syncwarp();
          flag_add(F_OUT + tile * 2 + c.rank);
        } else if (c.phases & 16) {
          flag_wait<false, 256>(F_OUT + tile * 2 + c.rank, 1);
        }
        mbar_arrive_one(c.bar + B_OUT * 8);
      }
    } else {
      const int bw = blockIdx.x * 2 + (c.warp - 2);
      if ((c.phases & 1) && bw < 256) {
        gate_rows(p, bw * 8, c.lane);
        __syncwarp();
        flag_add(F_GATE);
      }
      if (p.s.r[c.cl].bg != 255) local_attn(p, c, p.s.r[c.cl].bg, bw & 3);
      else if (c.lane == 0) mbar_arrive(c.bar + B_LAD * 8);
    }
    __syncwarp();
    bar_sync(3, 128);
    if (c.warp == 0 && (c.phases & 32)) {
      int last = 0;
      if (c.lane == 0) { __threadfence(); last = atomicAdd(g_flags + F_DONE, 1) == 2 * NCL - 1; }
      if (__shfl_sync(0xffffffffu, last, 0)) for (int i = c.lane; i < F_NUM; i += 32) g_flags[i] = 0;
    }
    if (c.warp == 1) mbar_wait(c.bar + B_FIN * 8, 0);
    __syncwarp();
    cluster_sync();
  }
}

static const Sched k_sched = {
  {{0,29,2,35,0,{200,242,0,0,0,0,0,0,0,0,0},{0,0,0,0,0,0,0,0,0,0,0},{70,105,8,226,192,49,44,231,225,234,54,235,53,242,240,51,47,46,244,237,248,250,60,62,249,63,253,247,251,0}},
   {1,29,1,20,1,{236,0,0,0,0,0,0,0,0,0,0},{31,0,0,0,0,0,0,0,0,0,0},{68,105,66,232,192,108,241,231,225,234,54,235,53,242,240,46,243,239,244,237,248,250,60,62,249,61,63,247,251,0}},
   {2,29,1,12,2,{188,0,0,0,0,0,0,0,0,0,0},{0,0,0,0,0,0,0,0,0,0,0},{68,227,201,226,192,49,39,33,236,234,43,246,50,245,240,51,47,52,46,237,248,250,57,252,254,55,253,255,251,0}},
   {3,29,2,14,3,{248,187,0,0,0,0,0,0,0,0,0},{0,0,0,0,0,0,0,0,0,0,0},{70,104,201,226,192,49,33,231,236,234,43,246,50,245,240,51,47,52,45,238,248,250,57,252,254,61,63,247,251,0}},
   {4,28,1,24,4,{228,0,0,0,0,0,0,0,0,0,0},{0,0,0,0,0,0,0,0,0,0,0},{70,35,9,40,197,224,1,39,10,11,22,21,16,210,19,15,20,13,14,24,26,25,28,30,29,31,23,27,0,0}},
   {5,27,0,17,5,{0,0,0,0,0,0,0,0,0,0,0},{0,0,0,0,0,0,0,0,0,0,0},{131,36,9,40,5,32,7,33,10,43,21,18,16,19,15,14,20,13,24,26,25,28,30,29,31,23,27,0,0,0}},
   {6,26,0,9,6,{0,0,0,0,0,0,0,0,0,0,0},{0,0,0,0,0,0,0,0,0,0,0},{99,105,8,34,0,49,7,44,11,54,18,16,19,15,20,14,13,24,26,25,28,30,29,31,23,27,0,0,0,0}},
   {7,25,0,7,7,{0,0,0,0,0,0,0,0,0,0,0},{0,0,0,0,0,0,0,0,0,0,0},{131,6,8,69,81,71,44,75,118,82,80,83,79,84,78,77,88,90,89,92,94,93,95,87,91,0,0,0,0,0}},
   {0,29,1,37,8,{227,0,0,0,0,0,0,0,0,0,0},{0,0,0,0,0,0,0,0,0,0,0},{131,38,4,40,5,32,12,7,193,10,22,203,21,18,16,19,15,14,212,205,24,26,28,30,217,31,221,23,27,0}},
   {1,29,2,22,9,{233,218,0,0,0,0,0,0,0,0,0},{0,0,0,0,0,0,0,0,0,0,0},{131,36,198,34,5,32,209,7,1,10,22,11,21,18,16,14,211,207,20,13,24,26,28,30,25,29,31,23,27,0}},
   {2,29,2,32,10,{201,250,0,0,0,0,0,0,0,0,0},{0,0,0,0,0,0,0,0,0,0,0},{70,36,8,41,5,32,7,1,12,10,11,22,18,21,16,19,15,20,14,13,24,26,25,28,30,23,29,223,27,0}},
   {3,29,1,28,11,{243,0,0,0,0,0,0,0,0,0,0},{0,0,0,0,0,0,0,0,0,0,0},{131,38,196,233,5,32,1,199,204,202,11,214,18,213,208,19,15,20,13,206,216,218,25,220,222,29,31,215,219,0}},
   {4,28,0,16,12,{0,0,0,0,0,0,0,0,0,0,0},{0,0,0,0,0,0,0,0,0,0,0},{102,4,41,194,229,17,33,12,42,43,54,53,48,50,51,47,52,45,46,56,58,57,60,62,61,63,55,59,0,0}},
   {5,27,0,20,13,{0,0,0,0,0,0,0,0,0,0,0},{0,0,0,0,0,0,0,0,0,0,0},{99,6,41,2,37,17,39,12,42,22,53,50,48,51,47,46,52,45,56,58,57,60,62,61,63,55,59,0,0,0}},
   {6,26,0,18,14,{0,0,0,0,0,0,0,0,0,0,0},{0,0,0,0,0,0,0,0,0,0,0},{68,6,40,69,32,1,39,10,43,21,50,48,51,47,52,46,45,56,58,57,60,62,61,63,55,59,0,0,0,0}},
   {7,25,0,19,15,{0,0,0,0,0,0,0,0,0,0,0},{0,0,0,0,0,0,0,0,0,0,0},{99,38,40,101,113,103,74,107,85,114,112,115,111,116,110,109,120,122,121,124,126,125,127,119,123,0,0,0,0,0}},
   {0,6,6,4,255,{32,47,138,181,163,240,0,0,0,0,0},{0,0,0,0,0,0,0,0,0,0,0},{99,73,36,2,37,17,0,0,0,0,0,0,0,0,0,0,0,0,0,0,0,0,0,0,0,0,0,0,0,0}},
   {1,6,6,10,255,{64,46,13,145,164,208,0,0,0,0,0},{0,0,0,0,0,0,0,0,0,0,0},{99,73,230,200,37,76,0,0,0,0,0,0,0,0,0,0,0,0,0,0,0,0,0,0,0,0,0,0,0,0}},
   {2,6,7,43,255,{76,41,60,82,148,214,185,0,0,0,0},{0,0,0,0,0,127,0,0,0,0,0},{102,195,40,2,37,17,0,0,0,0,0,0,0,0,0,0,0,0,0,0,0,0,0,0,0,0,0,0,0,0}},
   {3,6,5,36,255,{16,69,95,166,190,0,0,0,0,0,0},{0,0,0,127,0,0,0,0,0,0,0},{99,72,228,2,37,17,0,0,0,0,0,0,0,0,0,0,0,0,0,0,0,0,0,0,0,0,0,0,0,0}},
   {4,8,5,14,255,{40,6,99,129,165,0,0,0,0,0,0},{0,0,0,0,0,0,0,0,0,0,0},{131,36,8,34,0,49,7,44,0,0,0,0,0,0,0,0,0,0,0,0,0,0,0,0,0,0,0,0,0,0}},
   {5,10,5,45,255,{136,43,85,157,191,0,0,0,0,0,0},{0,0,0,48,255,0,0,0,0,0,0},{68,38,8,34,0,49,1,44,11,54,0,0,0,0,0,0,0,0,0,0,0,0,0,0,0,0,0,0,0,0}},
   {6,10,5,38,255,{0,4,98,134,247,0,0,0,0,0,0},{0,0,0,0,128,0,0,0,0,0,0},{100,38,66,101,81,33,12,42,22,53,0,0,0,0,0,0,0,0,0,0,0,0,0,0,0,0,0,0,0,0}},
   {7,9,6,27,255,{19,86,147,161,206,184,0,0,0,0,0},{0,0,0,0,0,0,0,0,0,0,0},{68,73,66,64,65,76,106,86,117,0,0,0,0,0,0,0,0,0,0,0,0,0,0,0,0,0,0,0,0,0}},
   {8,18,3,25,16,{125,105,237,0,0,0,0,0,0,0,0},{0,0,32,0,0,0,0,0,0,0,0},{160,170,69,235,35,44,109,12,10,85,79,208,77,152,206,158,159,29,0,0,0,0,0,0,0,0,0,0,0,0}},
   {9,18,3,29,17,{8,109,229,0,0,0,0,0,0,0,0},{0,0,0,0,0,0,0,0,0,0,0},{68,161,166,5,44,76,40,209,199,85,16,78,207,152,92,158,29,23,0,0,0,0,0,0,0,0,0,0,0,0}},
   {10,17,3,34,18,{172,193,246,0,0,0,0,0,0,0,0},{0,0,64,0,0,0,0,0,0,0,0},{134,161,162,99,71,17,109,12,86,85,16,78,15,152,89,158,159,0,0,0,0,0,0,0,0,0,0,0,0,0}},
   {11,17,2,5,19,{56,118,0,0,0,0,0,0,0,0,0},{0,0,0,0,0,0,0,0,0,0,0},{72,165,107,197,227,236,40,193,202,22,213,211,212,13,89,220,29,0,0,0,0,0,0,0,0,0,0,0,0,0}},
   {12,18,3,11,20,{176,146,144,0,0,0,0,0,0,0,0},{0,0,0,0,0,0,0,0,0,0,0},{105,9,194,81,39,1,12,45,11,80,18,15,77,152,89,158,23,27,0,0,0,0,0,0,0,0,0,0,0,0}},
   {13,18,3,31,21,{88,131,231,0,0,0,0,0,0,0,0},{0,0,255,0,0,0,0,0,0,0,0},{160,170,107,81,39,7,1,75,237,85,16,15,212,152,89,158,29,27,0,0,0,0,0,0,0,0,0,0,0,0}},
   {14,17,2,1,22,{111,222,0,0,0,0,0,0,0,0,0},{0,64,0,0,0,0,0,0,0,0,0},{160,170,166,99,44,1,74,40,86,80,19,84,14,90,92,93,23,0,0,0,0,0,0,0,0,0,0,0,0,0}},
   {15,18,3,30,23,{152,108,230,0,0,0,0,0,0,0,0},{0,0,0,0,0,0,0,0,0,0,0},{134,233,69,43,71,231,12,75,45,85,16,15,14,152,89,158,159,27,0,0,0,0,0,0,0,0,0,0,0,0}},
   {8,18,3,2,24,{168,116,112,0,0,0,0,0,0,0,0},{0,0,0,0,0,0,0,0,0,0,0},{100,9,162,0,39,104,7,1,83,11,214,210,20,90,92,217,23,27,0,0,0,0,0,0,0,0,0,0,0,0}},
   {9,18,3,42,25,{80,215,252,0,0,0,0,0,0,0,0},{1,0,31,0,0,0,0,0,0,0,0},{73,165,107,99,192,1,109,10,86,82,203,19,20,90,205,25,159,27,0,0,0,0,0,0,0,0,0,0,0,0}},
   {10,18,3,5,26,{156,210,253,0,0,0,0,0,0,0,0},{0,0,32,0,0,0,0,0,0,0,0},{68,165,166,103,0,104,1,10,11,82,19,84,77,90,92,87,91,29,0,0,0,0,0,0,0,0,0,0,0,0}},
   {11,19,4,39,27,{128,155,212,249,0,0,0,0,0,0,0},{0,15,0,0,0,0,0,0,0,0,0},{160,170,201,81,39,7,109,204,11,82,16,15,14,152,218,158,159,215,219,0,0,0,0,0,0,0,0,0,0,0}},
   {12,18,3,6,28,{120,113,115,0,0,0,0,0,0,0,0},{0,0,0,0,0,0,0,0,0,0,0},{100,4,107,0,227,236,7,40,202,22,213,211,212,14,218,220,159,221,0,0,0,0,0,0,0,0,0,0,0,0}},
   {13,18,1,3,29,{124,0,0,0,0,0,0,0,0,0,0},{0,0,0,0,0,0,0,0,0,0,0},{73,165,166,0,35,44,12,10,232,22,18,19,14,13,26,28,159,23,0,0,0,0,0,0,0,0,0,0,0,0}},
   {14,18,2,46,30,{110,245,0,0,0,0,0,0,0,0,0},{0,32,0,0,0,0,0,0,0,0,0},{73,161,69,0,39,7,12,75,45,85,18,15,77,152,89,158,159,27,0,0,0,0,0,0,0,0,0,0,0,0}},
   {15,17,5,33,31,{96,89,130,196,251,0,0,0,0,0,0},{1,0,0,7,0,0,0,0,0,0,0},{73,161,64,81,35,44,74,40,86,82,19,84,77,90,92,93,23,0,0,0,0,0,0,0,0,0,0,0,0,0}},
   {8,3,3,0,255,{31,103,119,0,0,0,0,0,0,0,0},{0,0,128,0,0,0,0,0,0,0,0},{134,165,2,0,0,0,0,0,0,0,0,0,0,0,0,0,0,0,0,0,0,0,0,0,0,0,0,0,0,0}},
   {9,3,5,17,255,{38,142,135,213,234,0,0,0,0,0,0},{0,0,252,0,0,0,0,0,0,0,0},{131,41,162,0,0,0,0,0,0,0,0,0,0,0,0,0,0,0,0,0,0,0,0,0,0,0,0,0,0,0}},
   {10,4,6,23,255,{34,26,44,9,151,104,0,0,0,0,0},{0,0,0,0,0,0,0,0,0,0,0},{100,9,200,197,0,0,0,0,0,0,0,0,0,0,0,0,0,0,0,0,0,0,0,0,0,0,0,0,0,0}},
   {11,4,6,21,255,{77,18,94,90,154,239,0,0,0,0,0},{0,0,0,0,0,192,0,0,0,0,0},{100,4,2,0,0,0,0,0,0,0,0,0,0,0,0,0,0,0,0,0,0,0,0,0,0,0,0,0,0,0}},
   {12,3,5,1,255,{27,35,3,183,114,0,0,0,0,0,0},{0,0,0,0,0,0,0,0,0,0,0},{160,170,166,0,0,0,0,0,0,0,0,0,0,0,0,0,0,0,0,0,0,0,0,0,0,0,0,0,0,0}},
   {13,3,8,9,255,{24,36,5,81,83,170,122,223,0,0,0},{0,0,0,0,0,0,0,128,0,0,0},{68,233,2,0,0,0,0,0,0,0,0,0,0,0,0,0,0,0,0,0,0,0,0,0,0,0,0,0,0,0}},
   {14,4,6,10,255,{28,49,63,91,198,220,0,0,0,0,0},{0,0,0,0,0,0,0,0,0,0,0},{134,165,162,81,0,0,0,0,0,0,0,0,0,0,0,0,0,0,0,0,0,0,0,0,0,0,0,0,0,0}},
   {15,3,6,21,255,{73,74,75,62,158,192,0,0,0,0,0},{0,0,0,2,0,0,0,0,0,0,0},{68,228,2,0,0,0,0,0,0,0,0,0,0,0,0,0,0,0,0,0,0,0,0,0,0,0,0,0,0,0}},
   {8,3,6,2,255,{55,12,182,197,226,217,0,0,0,0,0},{0,0,0,0,0,0,0,0,0,0,0},{131,161,196,0,0,0,0,0,0,0,0,0,0,0,0,0,0,0,0,0,0,0,0,0,0,0,0,0,0,0}},
   {9,3,8,18,255,{33,17,21,101,169,117,211,219,0,0,0},{0,0,0,0,0,0,0,0,0,0,0},{160,170,198,0,0,0,0,0,0,0,0,0,0,0,0,0,0,0,0,0,0,0,0,0,0,0,0,0,0,0}},
   {10,3,6,47,255,{29,65,140,175,194,205,0,0,0,0,0},{0,0,0,0,0,63,0,0,0,0,0},{105,195,2,0,0,0,0,0,0,0,0,0,0,0,0,0,0,0,0,0,0,0,0,0,0,0,0,0,0,0}},
   {11,3,8,4,255,{53,66,2,11,132,106,202,235,0,0,0},{0,0,0,0,0,0,0,0,0,0,0},{134,161,166,0,0,0,0,0,0,0,0,0,0,0,0,0,0,0,0,0,0,0,0,0,0,0,0,0,0,0}},
   {12,4,7,6,255,{67,20,1,59,127,238,216,0,0,0,0},{0,0,0,0,0,0,0,0,0,0,0},{134,161,8,5,0,0,0,0,0,0,0,0,0,0,0,0,0,0,0,0,0,0,0,0,0,0,0,0,0,0}},
   {13,4,4,40,255,{79,87,199,204,0,0,0,0,0,0,0},{0,0,0,0,0,0,0,0,0,0,0},{134,161,162,5,0,0,0,0,0,0,0,0,0,0,0,0,0,0,0,0,0,0,0,0,0,0,0,0,0,0}},
   {14,4,7,0,255,{50,7,137,174,162,241,189,0,0,0,0},{0,0,0,0,0,0,0,0,0,0,0},{68,41,2,43,0,0,0,0,0,0,0,0,0,0,0,0,0,0,0,0,0,0,0,0,0,0,0,0,0,0}},
   {15,4,5,22,255,{52,45,84,126,224,0,0,0,0,0,0},{0,0,0,3,0,0,0,0,0,0,0},{131,224,234,230,0,0,0,0,0,0,0,0,0,0,0,0,0,0,0,0,0,0,0,0,0,0,0,0,0,0}},
   {8,4,7,44,255,{71,58,92,178,123,203,186,0,0,0,0},{0,0,0,0,0,0,0,0,0,0,0},{105,8,166,81,0,0,0,0,0,0,0,0,0,0,0,0,0,0,0,0,0,0,0,0,0,0,0,0,0,0}},
   {9,4,7,41,255,{48,23,97,93,171,207,232,0,0,0,0},{0,0,0,0,0,192,0,0,0,0,0},{100,66,200,103,0,0,0,0,0,0,0,0,0,0,0,0,0,0,0,0,0,0,0,0,0,0,0,0,0,0}},
   {10,4,6,13,255,{78,141,57,173,107,221,0,0,0,0,0},{0,0,0,0,3,63,0,0,0,0,0},{160,170,107,108,0,0,0,0,0,0,0,0,0,0,0,0,0,0,0,0,0,0,0,0,0,0,0,0,0,0}},
   {11,3,4,8,255,{51,68,14,167,0,0,0,0,0,0,0},{0,0,0,128,0,0,0,0,0,0,0},{131,233,162,0,0,0,0,0,0,0,0,0,0,0,0,0,0,0,0,0,0,0,0,0,0,0,0,0,0,0}},
   {12,3,7,26,255,{39,42,100,179,121,209,254,0,0,0,0},{0,0,0,0,0,0,0,0,0,0,0},{131,165,162,0,0,0,0,0,0,0,0,0,0,0,0,0,0,0,0,0,0,0,0,0,0,0,0,0,0,0}},
   {13,3,5,13,255,{37,143,177,149,225,0,0,0,0,0,0},{0,0,0,0,0,0,0,0,0,0,0},{131,228,8,0,0,0,0,0,0,0,0,0,0,0,0,0,0,0,0,0,0,0,0,0,0,0,0,0,0,0}},
   {14,3,3,15,255,{30,15,150,0,0,0,0,0,0,0,0},{0,0,67,0,0,0,0,0,0,0,0},{131,36,8,0,0,0,0,0,0,0,0,0,0,0,0,0,0,0,0,0,0,0,0,0,0,0,0,0,0,0}},
   {15,4,5,8,255,{54,139,10,159,255,0,0,0,0,0,0},{0,0,0,0,192,0,0,0,0,0,0},{72,165,162,65,0,0,0,0,0,0,0,0,0,0,0,0,0,0,0,0,0,0,0,0,0,0,0,0,0,0}},
   {6,2,7,16,255,{25,70,61,180,153,195,244,0,0,0,0},{0,0,0,0,0,0,31,0,0,0,0},{131,73,0,0,0,0,0,0,0,0,0,0,0,0,0,0,0,0,0,0,0,0,0,0,0,0,0,0,0,0}},
   {7,5,5,12,255,{72,22,102,133,160,0,0,0,0,0,0},{0,0,0,0,0,0,0,0,0,0,0},{100,105,98,96,97,0,0,0,0,0,0,0,0,0,0,0,0,0,0,0,0,0,0,0,0,0,0,0,0,0}}},
  {{0,7,0,0},{6,17,0,0},{1,12,0,0},{6,17,0,0},{0,7,0,0},{17,64,0,0},{11,64,0,0},{6,64,0,0},{0,7,0,0},{6,19,0,0},{0,4,0,0},
   {0,7,0,0},{22,64,0,0},{17,64,0,0},{11,64,0,0},{5,64,0,0},{21,64,0,0},{15,64,0,0},{0,5,0,0},{0,1,0,0},{17,64,0,0},{0,1,0,0},
   {0,6,0,0},{0,8,0,0},{0,2,0,0},{0,7,0,0},{0,6,0,0},{19,64,0,0},{7,64,0,0},{0,6,0,0},{2,11,0,0},{0,7,0,0},{17,64,0,0},
   {0,2,0,0},{7,19,0,0},{0,7,0,0},{17,64,0,0},{8,64,0,0},{0,6,0,0},{0,2,0,0},{18,64,0,0},{5,17,0,0},{8,64,0,0},{1,15,0,0},
   {11,64,0,0},{2,11,0,0},{6,15,0,0},{15,64,0,0},{4,17,0,0},{2,11,0,0},{0,8,0,0},{7,21,0,0},{7,17,0,0},{0,8,0,0},{7,18,0,0},
   {19,64,0,0},{0,6,0,0},{0,5,0,0},{7,16,0,0},{17,64,0,0},{0,4,0,0},{16,64,0,0},{7,64,0,0},{4,17,0,0},{8,22,0,0},{12,64,0,0}},
  {{48,53,56,61,62,47,54,32,36,26,40,49,28,57,50,63,58,55,6,7,12,13,18,19,16,17,8,9,4,5,10,11,0,1,34,35,24,25,14,15,2,3,20,21,38,39,42,43,22,23,30,31,44,45,33,37,27,41,52,29,60,51,46,59},
   {47,54,49,53,29,57,61,51,63,58,55,6,7,12,13,18,19,16,17,8,9,4,5,10,11,0,1,34,35,24,25,14,15,2,3,20,21,38,39,42,43,22,23,30,31,44,45,32,33,36,37,26,27,40,41,48,52,28,56,60,50,62,46,59},
   {61,62,47,54,45,33,37,27,41,49,53,29,57,50,63,59,55,6,7,12,13,18,19,16,17,8,9,4,5,10,11,0,1,34,35,24,25,14,15,2,3,20,21,38,39,42,43,22,23,30,31,44,32,36,26,40,48,52,28,56,60,51,46,58},
   {53,27,61,51,59,63,47,55,6,7,18,19,8,9,4,5,12,13,16,17,10,11,0,1,24,25,2,3,34,35,20,21,14,15,44,45,42,43,36,37,32,33,22,23,28,29,38,39,30,31,40,41,56,57,48,49,52,26,60,50,58,62,46,54},
   {57,52,27,50,59,46,55,43,37,22,28,38,30,40,56,49,26,61,58,63,54,6,7,18,19,8,9,4,5,12,13,16,17,10,11,0,1,24,25,2,3,34,35,20,21,14,15,44,45,42,36,32,33,23,29,39,31,41,48,53,60,51,62,47},
   {56,49,26,61,58,63,54,22,28,38,30,40,57,52,27,50,59,46,55,6,7,18,19,8,9,4,5,12,13,16,17,10,11,0,1,24,25,2,3,34,35,20,21,14,15,44,45,42,43,36,37,32,33,23,29,39,31,41,48,53,60,51,62,47},
   {27,52,51,60,47,54,59,38,40,30,26,49,50,57,46,63,58,12,13,8,9,18,19,6,7,16,17,4,5,10,11,14,15,0,1,34,35,2,3,24,25,20,21,44,45,22,23,42,43,36,37,28,29,32,33,39,41,31,48,53,56,61,62,55},
   {57,61,47,63,55,59,12,13,8,9,18,19,6,7,16,17,4,5,10,11,14,15,0,1,34,35,2,3,24,25,20,21,44,45,22,23,42,43,36,37,28,29,32,33,38,39,40,41,30,31,26,27,48,49,52,53,50,51,56,60,46,62,54,58},
   {57,46,63,58,29,33,39,41,31,27,49,53,51,60,47,54,59,12,13,8,9,18,19,6,7,16,17,4,5,10,11,14,15,0,1,34,35,2,3,24,25,20,21,44,45,22,23,42,43,36,37,28,32,38,40,30,26,48,52,50,56,61,62,55},
   {62,47,27,49,51,53,57,61,59,46,55,12,13,6,7,16,17,8,9,18,19,4,5,10,11,34,35,0,1,14,15,2,3,24,25,20,21,22,23,44,45,36,37,42,43,32,33,28,29,38,39,30,31,40,41,26,48,50,52,56,60,58,63,54},
   {48,51,57,58,63,54,31,41,27,50,53,60,59,46,55,12,13,6,7,16,17,8,9,18,19,4,5,10,11,34,35,0,1,14,15,2,3,24,25,20,21,22,23,44,45,36,37,42,43,32,33,28,29,38,39,30,40,26,49,52,56,61,62,47},
   {53,57,61,59,63,47,55,12,13,6,7,16,17,8,9,18,19,4,5,10,11,34,35,0,1,14,15,2,3,24,25,20,21,22,23,44,45,36,37,42,43,32,33,28,29,38,39,30,31,40,41,26,27,48,49,50,51,52,56,60,58,62,46,54},
   {54,26,28,48,52,50,56,61,63,47,59,55,12,13,6,7,8,9,18,19,16,17,4,5,10,11,0,1,34,35,2,3,14,15,24,25,20,21,22,23,44,45,32,33,42,43,30,31,36,37,38,39,40,41,27,29,49,53,51,57,60,62,46,58},
   {28,49,50,57,62,47,54,40,26,29,52,51,60,63,59,55,12,13,6,7,8,9,18,19,16,17,4,5,10,11,0,1,34,35,2,3,14,15,24,25,20,21,22,23,44,45,32,33,42,43,30,31,36,37,38,39,41,27,48,53,56,61,46,58},
   {49,50,57,62,47,54,36,38,40,26,29,52,51,60,63,58,55,12,13,6,7,8,9,18,19,16,17,4,5,10,11,0,1,34,35,2,3,14,15,24,25,20,21,22,23,44,45,32,33,42,43,30,31,37,39,41,27,28,48,53,56,61,46,59},
   {51,57,61,63,59,47,55,8,9,12,13,6,7,18,19,16,17,4,5,10,11,0,1,34,35,14,15,24,25,2,3,20,21,22,23,44,45,42,43,36,37,32,33,38,39,40,41,30,31,28,29,26,27,48,49,52,53,50,56,60,62,58,46,54},
   {31,26,49,50,57,62,59,54,45,43,37,33,39,41,28,27,52,51,60,58,47,55,8,9,12,13,6,7,18,19,16,17,4,5,10,11,0,1,34,35,14,15,24,25,2,3,20,21,22,23,44,42,36,32,38,40,30,29,48,53,56,61,63,46},
   {50,57,62,59,54,39,41,31,29,27,49,53,56,61,58,47,55,8,9,12,13,6,7,18,19,16,17,4,5,10,11,0,1,34,35,14,15,24,25,2,3,20,21,22,23,44,45,42,43,36,37,32,33,38,40,30,28,26,48,52,51,60,63,46},
   {59,54,27,49,53,51,57,61,63,46,55,6,7,8,9,18,19,12,13,16,17,4,5,10,11,0,1,34,35,14,15,2,3,24,25,20,21,22,23,44,45,42,43,36,37,32,33,38,39,30,31,28,29,40,41,26,48,52,50,56,60,62,58,47},
   {61,63,59,47,55,6,7,8,9,18,19,12,13,16,17,4,5,10,11,0,1,34,35,14,15,2,3,24,25,20,21,22,23,44,45,42,43,36,37,32,33,38,39,30,31,28,29,40,41,26,27,48,49,52,53,50,51,56,57,60,62,58,46,54},
   {52,51,60,63,46,54,30,28,40,26,48,53,56,61,58,47,55,6,7,8,9,18,19,12,13,16,17,4,5,10,11,0,1,34,35,14,15,2,3,24,25,20,21,22,23,44,45,42,43,36,37,32,33,38,39,31,29,41,27,49,50,57,62,59},
   {54,38,40,30,28,26,48,52,56,60,50,58,62,46,55,12,13,6,7,8,9,18,19,16,17,4,5,10,11,0,1,34,35,2,3,14,15,24,25,20,21,22,23,44,45,42,43,36,37,32,33,39,41,31,29,27,49,53,57,61,51,59,63,47},
   {49,56,61,58,63,54,37,33,39,41,31,29,27,52,57,50,59,46,55,12,13,6,7,8,9,18,19,16,17,4,5,10,11,0,1,34,35,2,3,14,15,24,25,20,21,22,23,44,45,42,43,36,32,38,40,30,28,26,48,53,60,51,62,47},
   {53,57,61,51,59,63,47,55,12,13,6,7,8,9,18,19,16,17,4,5,10,11,0,1,34,35,2,3,14,15,24,25,20,21,22,23,44,45,42,43,36,37,32,33,38,39,40,41,30,31,28,29,26,27,48,49,52,56,60,50,58,62,46,54}},
  {{7,7,7,7,7,7,7,7},{11,11,10,9,9,10,9,9},{5,4,5,5,5,5,5,5},{0,0,2,0,1,0,0,0},
   {3,1,1,3,2,1,1,1},{6,6,6,6,6,6,6,6},{1,3,0,1,0,2,3,2},{10,10,9,10,10,9,10,10},
   {4,5,3,2,4,4,4,4},{2,2,4,4,3,3,2,3},{12,12,12,12,12,1,1,1},{14,14,13,3,2,0,4,4},
   {9,8,11,11,11,11,11,11},{8,9,11,11,11,0,4,4},{7,4,2,12,2,2,11,11},{2,7,6,8,8,8,8,8},
   {4,5,4,7,3,7,7,7},{8,9,8,8,8,8,8,8},{3,1,3,5,7,3,6,6},{5,2,7,6,6,6,0,0},
   {6,6,8,0,1,11,3,10},{15,15,5,4,5,5,5,5},{13,13,1,2,4,4,2,3},{4,5,3,11,2,2,11,4},
   {0,0,10,9,12,1,1,1},{14,14,13,2,4,4,2,3},{1,8,12,3,9,10,9,9},{7,4,11,9,12,1,1,9},
   {10,11,1,4,5,5,5,6},{15,13,6,8,8,8,8,8},{11,12,5,5,7,3,0,0},{13,15,2,12,11,0,4,1}},
  {{255,255,255,255,255,255,255,255},{255,255,255,255,255,255,255,255},{255,255,255,255,255,255,255,255},{255,255,255,255,255,255,255,255},
   {255,255,255,255,255,255,255,255},{255,255,255,255,255,255,255,255},{255,255,255,255,255,255,255,255},{255,255,255,255,255,255,255,255},
   {255,255,255,255,255,255,255,255},{255,255,255,255,255,255,255,255},{255,255,255,255,255,4,4,4},{255,255,255,4,4,3,8,8},
   {255,255,255,255,255,255,255,255},{17,17,12,12,12,11,11,11},{0,2,3,10,11,6,12,12},{9,0,5,17,17,17,17,17},
   {8,8,9,0,9,0,0,0},{255,255,255,255,255,255,255,255},{4,4,8,2,0,9,5,5},{2,9,0,5,5,5,3,3},
   {5,5,17,3,3,12,6,7},{255,255,2,9,2,2,2,2},{255,255,4,8,8,8,9,9},{16,16,18,13,14,14,14,13},
   {3,3,1,1,10,10,10,10},{11,11,11,22,22,22,22,22},{6,12,10,11,1,1,1,1},{14,14,13,24,24,24,24,26},
   {7,1,22,21,21,21,21,18},{21,22,15,15,15,15,15,15},{1,10,21,18,18,18,19,19},{22,21,14,14,13,13,13,24}},
  {112,113,114,115,116,117,118,119,6,121,122,36,124,125,126,127,128,129,130,131,132,133,134,135,136,137,138,139,140,141,142,143,144,145,146,147,148,149,150,151,152,153,154,155,156,157,158,159,160,161,162,163,164,165,166,167,168,41,170,391,172,647,174,175,176,177,178,179,180,181,182,183,184,185,186,187,188,189,190,191,43,2,0,74,75,8,198,199,635,201,39,76,77,37,4,5,7,209,1,38,212,213,214,215,216,18,393,219,220,221,222,223,22,50,48,227,228,229,230,231,11,233,649,86,236,87,52,53,81,241,370,16,244,17,246,9,248,3,250,251,252,253,254,255,82,80,78,259,47,14,10,263,44,51,626,88,89,84,15,12,272,273,49,275,276,277,85,83,280,372,79,45,46,285,628,379,13,42,40,291,292,293,73,72,296,28,59,35,300,34,302,303,304,305,454,307,308,309,310,311,92,61,445,54,58,55,20,21,320,321,710,56,57,25,326,327,32,29,707,66,65,63,30,31,23,19,701,97,98,95,26,24,33,698,27,347,64,349,96,93,94,62,60,452,451,708,90,91,360,415,442,363,364,365,671,367},
  {511,511,511,511,511,511,511,511,256,511,511,256,511,511,511,511,511,511,511,511,511,511,511,511,511,511,511,511,511,511,511,511,511,511,511,511,511,511,511,511,511,511,511,511,511,511,511,511,511,511,511,511,511,511,511,511,511,256,511,55,511,55,511,511,511,511,511,511,511,511,511,511,511,511,511,511,511,511,511,511,256,256,256,256,256,256,511,511,51,511,256,256,256,256,256,256,256,511,256,256,511,511,511,511,511,258,49,511,511,511,511,511,258,257,257,511,511,511,511,511,257,511,49,257,511,257,257,257,257,511,50,257,511,257,511,257,511,256,511,511,511,511,511,511,257,256,256,511,257,257,257,511,256,257,50,257,257,257,257,257,511,511,257,511,511,511,257,257,511,52,256,257,257,511,52,51,257,256,256,511,511,511,256,256,511,259,258,259,511,259,511,511,511,511,62,511,511,511,511,511,258,258,61,258,258,258,258,258,511,511,62,258,258,258,511,511,259,259,59,259,259,259,259,259,258,258,61,258,258,258,258,258,259,58,259,511,259,511,258,258,258,258,258,60,59,60,258,258,511,175,58,511,511,511,175,511}};

typedef CUresult (*EncodeFn)(CUtensorMap*, CUtensorMapDataType, cuuint32_t, void*, const cuuint64_t*, const cuuint64_t*, const cuuint32_t*,
                             const cuuint32_t*, CUtensorMapInterleave, CUtensorMapSwizzle, CUtensorMapL2promotion, CUtensorMapFloatOOBfill);

void make_map2(EncodeFn enc, CUtensorMap* m, const void* ptr, int rows, int cols, int box_rows) {
  cuuint64_t dim[2] = {(cuuint64_t)cols, (cuuint64_t)rows}, str[1] = {(cuuint64_t)cols * 2};
  cuuint32_t box[2] = {64, (cuuint32_t)box_rows}, es[2] = {1, 1};
  enc(m, CU_TENSOR_MAP_DATA_TYPE_BFLOAT16, 2, const_cast<void*>(ptr), dim, str, box, es, CU_TENSOR_MAP_INTERLEAVE_NONE, CU_TENSOR_MAP_SWIZZLE_128B,
      CU_TENSOR_MAP_L2_PROMOTION_L2_128B, CU_TENSOR_MAP_FLOAT_OOB_FILL_NONE);
}
void make_map3(EncodeFn enc, CUtensorMap* m, const void* ptr, int rows) {
  cuuint64_t dim[3] = {64, (cuuint64_t)rows, 9}, str[2] = {DM * 2, 128};
  cuuint32_t box[3] = {64, 32, 3}, es[3] = {1, 1, 1};
  enc(m, CU_TENSOR_MAP_DATA_TYPE_BFLOAT16, 3, const_cast<void*>(ptr), dim, str, box, es, CU_TENSOR_MAP_INTERLEAVE_NONE, CU_TENSOR_MAP_SWIZZLE_128B,
      CU_TENSOR_MAP_L2_PROMOTION_L2_128B, CU_TENSOR_MAP_FLOAT_OOB_FILL_NONE);
}

void make_map_t(EncodeFn enc, CUtensorMap* m, void* ptr, int width, int cols) {
  cuuint64_t dim[3] = {SEQ / 2, 2, 864}, str[2] = {SEQ * 2, SEQ * 4};
  cuuint32_t box[3] = {(cuuint32_t)width, 2, (cuuint32_t)cols}, es[3] = {1, 1, 1};
  enc(m, CU_TENSOR_MAP_DATA_TYPE_UINT32, 3, ptr, dim, str, box, es, CU_TENSOR_MAP_INTERLEAVE_NONE, cols == 64 ? CU_TENSOR_MAP_SWIZZLE_128B : CU_TENSOR_MAP_SWIZZLE_NONE,
      CU_TENSOR_MAP_L2_PROMOTION_NONE, CU_TENSOR_MAP_FLOAT_OOB_FILL_NONE);
}

int g_mode = -1;

}

extern "C" void kernel_launch(void* const* d_in, const int* in_sizes, int n_in, void* d_out, int out_size) {
  static EncodeFn enc = nullptr;
  static void* t_ptr = nullptr;
  if (!enc) {
    void* fn = nullptr;
    cudaDriverEntryPointQueryResult st;
    cudaGetDriverEntryPoint("cuTensorMapEncodeTiled", &fn, cudaEnableDefault, &st);
    enc = (EncodeFn)fn;
    cudaGetSymbolAddress(&t_ptr, g_S);
    cudaFuncSetAttribute(fused_kernel, cudaFuncAttributeMaxDynamicSharedMemorySize, SMEM_BYTES);
    if (g_mode < 0) {
      cudaLaunchConfig_t cfg = {};
      cfg.gridDim = dim3(2 * NCL); cfg.blockDim = dim3(384); cfg.dynamicSmemBytes = SMEM_BYTES;
      cudaLaunchAttribute at; at.id = cudaLaunchAttributeClusterDimension;
      at.val.clusterDim.x = 2; at.val.clusterDim.y = 1; at.val.clusterDim.z = 1;
      cfg.attrs = &at; cfg.numAttrs = 1;
      int nc = 0;
      g_mode = (cudaOccupancyMaxActiveClusters(&nc, fused_kernel, &cfg) == cudaSuccess && nc >= NCL) ? 1 : 0;
      (void)cudaGetLastError();
    }
  }
  Params p;
  make_map2(enc, &p.map_a[0], d_in[4], SEQ, DC, 128);
  make_map2(enc, &p.map_a[1], d_in[0], SEQ, DM, 128);
  make_map2(enc, &p.map_w[0], d_in[6], DC, 4096, 64);
  make_map2(enc, &p.map_w[1], d_in[7], DC, 4096, 64);
  make_map2(enc, &p.map_w[2], d_in[5], DM, 4096, 64);
  make_map2(enc, &p.map_w[3], d_in[1], DM, 1728, 64);
  make_map3(enc, &p.map_o[0], d_in[8], 4096);
  make_map3(enc, &p.map_o[1], d_in[2], DM);
  make_map_t(enc, &p.map_t[0], t_ptr, 32, 9);
  make_map_t(enc, &p.map_t[1], t_ptr, 40, 9);
  make_map_t(enc, &p.map_t[2], t_ptr, 32, 64);
  p.x = (const __nv_bfloat16*)d_in[0];
  p.gate_w = (const __nv_bfloat16*)d_in[9];
  make_map2(enc, &p.map_out, d_out, SEQ, DM, 64);
  p.out = (__nv_bfloat16*)d_out;
  p.zero = 0;
  auto launch = [&](int phases) {
    p.s = k_sched;
    for (int i = 0; i < NCL; i++) {
      Rec& r = p.s.r[i];
      if (!(phases & 1)) r.n1 = 0;
      if (!(phases & 2)) r.n2 = 0;
      if (!(phases & (p.s.task[i][1] == 64 ? 4 : 32))) r.p3 = 255;
      if (!(phases & 8)) r.bg = 255;
      const int u1 = r.n1 ? 8 + r.n1 * (8 + (r.slab >> 3)) : 0;
      int u2 = 0;
      for (int k = 0; k < r.n2; k++) u2 += 4 * (r.item[k] & 7) + 4;
      r.u1 = (uint8_t)u1; r.u2 = (uint8_t)u2;
      r.rot = (uint8_t)(((u1 % 10 + 1) >> 1) % 5);
      r.x3 = (uint8_t)((r.rot + u2) % 5 & 3);
      r.phases = (uint8_t)phases;
    }
    if (!(phases & 16))
      for (int i = 0; i < 256; i++) { p.s.slot[i >> 3][i & 7] = (uint8_t)(i >> 3); p.s.prev[i >> 3][i & 7] = 255; p.s.qblk[i] = (uint16_t)(S_Q + i); p.s.qdep[i] = 511; }
    fused_kernel<<<2 * NCL, 384, SMEM_BYTES>>>(p);
  };
  if (g_mode == 1) launch(63);
  else { launch(1); launch(10); launch(4); launch(32); }
}
```

```cpp
#include <cuda_runtime.h>
#include <cuda_bf16.h>
#include <cuda.h>
#include <stdint.h>

namespace {

constexpr int SEQ = 2048, DM = 576, DC = 512, NH = 32;
constexpr int NCL = 66;
constexpr uint32_t DESC_HI = 0x40000040u;

constexpr int SM_RING = 0;
constexpr int SM_BUF = 163840;
constexpr int SM_BAR = 229376;
constexpr int B_P1E = 0, B_P2E = 10, B_P3E = 15, B_P2F = 24, B_SF = 32, B_ORD = 36, B_LAD = 40, B_DONE = 41, B_FIN = 48;
constexpr int B_P3F = 56, B_OUT = 61, B_ZF = 62, B_P1F = 64, B_SE = 74, B_QF = 80, B_LA = 84, B_NUM = 88;
constexpr uint64_t B_CNT = 0x11118245000ull;
constexpr int SMEM_BYTES = SM_BAR + B_NUM * 8 + 1024;

constexpr int F_QKVA = 32;
constexpr int F_GATE = 64;
constexpr int F_TS = 68;
constexpr int F_DONE = 65;
constexpr int F_CTX = 96;
constexpr int F_OUT = 96 + 8 * 64;
constexpr int F_KV = F_OUT + 64;
constexpr int F_Q = F_KV + 256;
constexpr int F_RD = F_Q + 256;
constexpr int F_NUM = F_RD + 256;

struct Rec {
  uint8_t slab;
  uint8_t n1, n2;
  uint8_t p3;
  uint8_t bg;
  uint8_t item[11];
  uint8_t last[11];
  uint8_t tile[32];
  uint8_t u1, u2;
  uint8_t rot, x3;
  uint8_t phases;
};
struct Sched {
  Rec r[NCL];
  uint8_t task[NCL][4];
  uint8_t p3_order[24][64];
  uint8_t slot[32][8];
  uint8_t prev[32][8];
  uint16_t qblk[256];
  uint16_t qdep[256];
};


struct Params {
  CUtensorMap map_a[2];
  CUtensorMap map_w[4];
  CUtensorMap map_o[2];
  CUtensorMap map_t[3];
  CUtensorMap map_out;
  const __nv_bfloat16* x;
  const __nv_bfloat16* gate_w;
  __nv_bfloat16* out;
  int zero;
  alignas(64) Sched s;
};

constexpr int S_Q = 112, S_K = S_Q + 256, S_V = S_K + 256, S_NUM = S_V + 256;
__device__ __align__(1024) uint8_t g_S[(size_t)S_NUM * 65536];
__device__ __align__(1024) uint8_t g_oA[32 * 576 * 128];
__device__ float g_gate[SEQ];
__device__ int g_flags[F_NUM];

__device__ __forceinline__ void mbar_arrive(uint32_t b) { asm volatile("mbarrier.arrive.shared::cta.b64 _, [%0];" ::"r"(b) : "memory"); }
__device__ __forceinline__ void mbar_arrive_cl(uint32_t b, int cnt) {
  asm volatile("mbarrier.arrive.shared::cluster.b64 _, [%0], %1;" ::"r"(b), "r"(cnt) : "memory");
}
__device__ __forceinline__ void mbar_wait(uint32_t b, int par) {
  asm volatile(
      "{\n.reg .pred p;\n.reg .u32 c;\n"
      "mbarrier.try_wait.parity.shared::cta.b64 p, [%0], %1;\n@p bra DN;\nmov.u32 c, 0;\n"
      "LP:\nmbarrier.try_wait.parity.shared::cta.b64 p, [%0], %1;\n@p bra DN;\n"
      "add.u32 c, c, 1;\nsetp.lt.u32 p, c, 4000000;\n@p bra LP;\ntrap;\nDN:\n}" ::"r"(b), "r"(par) : "memory");
}
__device__ __forceinline__ bool mbar_test(uint32_t b, int par) {
  uint32_t ok;
  asm volatile("{\n.reg .pred p;\nmbarrier.test_wait.parity.shared::cta.b64 p, [%1], %2;\nselp.u32 %0, 1, 0, p;\n}" : "=r"(ok) : "r"(b), "r"(par) : "memory");
  return __all_sync(0xffffffffu, ok);
}
__device__ __forceinline__ uint32_t mapa(uint32_t a, uint32_t cta) {
  uint32_t r; asm("mapa.shared::cluster.u32 %0, %1, %2;" : "=r"(r) : "r"(a), "r"(cta)); return r;
}
#define ELECT(ins) "{\n.reg .pred e;\nelect.sync _|e, 0xffffffff;\n@e " ins "\n}"
__device__ __forceinline__ void mbar_expect(uint32_t b, int bytes) {
  asm volatile(ELECT("mbarrier.arrive.expect_tx.shared::cta.b64 _, [%0], %1;") ::"r"(b), "r"(bytes) : "memory");
}
__device__ __forceinline__ void mbar_arrive_one(uint32_t b) { asm volatile(ELECT("mbarrier.arrive.shared::cta.b64 _, [%0];") ::"r"(b) : "memory"); }
constexpr uint64_t L2_NORMAL = 0x1000000000000000ull, L2_FIRST = 0x12F0000000000000ull;
__device__ __forceinline__ void bulk_load(uint32_t dst, const void* src, int bytes, uint32_t bar, uint64_t pol = L2_NORMAL) {
  asm volatile(ELECT("cp.async.bulk.shared::cluster.global.mbarrier::complete_tx::bytes.L2::cache_hint [%0], [%1], %2, [%3], %4;") ::"r"(dst), "l"(src), "r"(bytes), "r"(bar), "l"(pol) : "memory");
}
__device__ __forceinline__ void bulk_load_mc(uint32_t dst, const void* src, int bytes, uint32_t bar, uint64_t pol = L2_NORMAL) {
  asm volatile(ELECT("cp.async.bulk.shared::cluster.global.mbarrier::complete_tx::bytes.multicast::cluster.L2::cache_hint [%0], [%1], %2, [%3], %4, %5;") ::"r"(dst), "l"(src), "r"(bytes), "r"(bar), "h"((uint16_t)3), "l"(pol) : "memory");
}
__device__ __forceinline__ void bulk_store(void* dst, uint32_t src, int bytes, uint64_t pol = L2_NORMAL) {
  asm volatile(ELECT("cp.async.bulk.global.shared::cta.bulk_group.L2::cache_hint [%0], [%1], %2, %3;") ::"l"(dst), "r"(src), "r"(bytes), "l"(pol) : "memory");
}
__device__ __forceinline__ void tma2d(uint32_t dst, const CUtensorMap* m, int c0, int c1, uint32_t bar, uint64_t pol = L2_NORMAL) {
  asm volatile(ELECT("cp.async.bulk.tensor.2d.shared::cluster.global.mbarrier::complete_tx::bytes.L2::cache_hint [%0], [%1, {%3, %4}], [%2], %5;") ::"r"(dst), "l"(m), "r"(bar), "r"(c0), "r"(c1), "l"(pol) : "memory");
}
__device__ __forceinline__ void tma2d_mc(uint32_t dst, const CUtensorMap* m, int c0, int c1, uint32_t bar, uint64_t pol = L2_NORMAL) {
  asm volatile(ELECT("cp.async.bulk.tensor.2d.shared::cluster.global.mbarrier::complete_tx::bytes.multicast::cluster.L2::cache_hint [%0], [%1, {%3, %4}], [%2], %5, %6;") ::"r"(dst), "l"(m), "r"(bar), "r"(c0), "r"(c1), "h"((uint16_t)3), "l"(pol) : "memory");
}
__device__ __forceinline__ void tma3d(uint32_t dst, const CUtensorMap* m, int c0, int c1, int c2, uint32_t bar, uint64_t pol = L2_NORMAL) {
  asm volatile(ELECT("cp.async.bulk.tensor.3d.shared::cluster.global.mbarrier::complete_tx::bytes.L2::cache_hint [%0], [%1, {%3, %4, %5}], [%2], %6;") ::"r"(dst), "l"(m), "r"(bar), "r"(c0), "r"(c1), "r"(c2), "l"(pol) : "memory");
}
__device__ __forceinline__ void tma3d_mc(uint32_t dst, const CUtensorMap* m, int c0, int c1, int c2, uint32_t bar, uint64_t pol = L2_NORMAL) {
  asm volatile(ELECT("cp.async.bulk.tensor.3d.shared::cluster.global.mbarrier::complete_tx::bytes.multicast::cluster.L2::cache_hint [%0], [%1, {%3, %4, %5}], [%2], %6, %7;") ::"r"(dst), "l"(m), "r"(bar), "r"(c0), "r"(c1), "r"(c2), "h"((uint16_t)3), "l"(pol) : "memory");
}
__device__ __forceinline__ void tma2d_add(const CUtensorMap* m, uint32_t src, int c0, int c1) {
  asm volatile(ELECT("cp.reduce.async.bulk.tensor.2d.global.shared::cta.add.bulk_group [%0, {%2, %3}], [%1];") ::"l"(m), "r"(src), "r"(c0), "r"(c1) : "memory");
}
__device__ __forceinline__ void tma3d_store(const CUtensorMap* m, uint32_t src, int c0, int c1, int c2, uint64_t pol = L2_NORMAL) {
  asm volatile(ELECT("cp.async.bulk.tensor.3d.global.shared::cta.bulk_group.L2::cache_hint [%0, {%2, %3, %4}], [%1], %5;") ::"l"(m), "r"(src), "r"(c0), "r"(c1), "r"(c2), "l"(pol) : "memory");
}
__device__ __forceinline__ void tma2d_prefetch(const CUtensorMap* m, int c0, int c1, uint64_t pol = L2_NORMAL) {
  asm volatile(ELECT("cp.async.bulk.prefetch.tensor.2d.L2.global.L2::cache_hint [%0, {%1, %2}], %3;") ::"l"(m), "r"(c0), "r"(c1), "l"(pol) : "memory");
}
#define LAG 3
#define HINT 63
#define POL(bit) ((HINT >> (bit)) & 1 ? L2_FIRST : L2_NORMAL)
#define BULK_COMMIT() asm volatile("cp.async.bulk.commit_group;" ::: "memory")
#define BULK_WAIT(n) asm volatile("cp.async.bulk.wait_group %0;" ::"n"(n) : "memory")
#define BULK_WAIT_READ(n) asm volatile("cp.async.bulk.wait_group.read %0;" ::"n"(n) : "memory")
#define FENCE_ASYNC_SMEM() asm volatile("fence.proxy.async.shared::cta;" ::: "memory")
#define WG_FENCE() asm volatile("wgmma.fence.sync.aligned;" ::: "memory")
#define WG_COMMIT() asm volatile("wgmma.commit_group.sync.aligned;" ::: "memory")
#define WG_WAIT(n) asm volatile("wgmma.wait_group.sync.aligned %0;" ::"n"(n) : "memory")
__device__ __forceinline__ void bar_sync(int id, int n) { asm volatile("bar.sync %0, %1;" ::"r"(id), "r"(n) : "memory"); }
__device__ __forceinline__ void bar_arrive(int id, int n) { asm volatile("bar.arrive %0, %1;" ::"r"(id), "r"(n) : "memory"); }
__device__ __forceinline__ void cluster_sync() {
  asm volatile("barrier.cluster.arrive.relaxed;\nbarrier.cluster.wait.acquire;" ::: "memory");
}
template <int N> __device__ __forceinline__ void pin(float (&r)[N]) {
#pragma unroll
  for (int i = 0; i < N; i++) asm volatile("" : "+f"(r[i])::"memory");
}
template <int N> __device__ __forceinline__ void pin(uint32_t (&r)[N]) {
#pragma unroll
  for (int i = 0; i < N; i++) asm volatile("" : "+r"(r[i])::"memory");
}
__device__ __forceinline__ uint32_t pack_bf16(float lo, float hi) {
  uint32_t r; asm("cvt.rn.bf16x2.f32 %0, %1, %2;" : "=r"(r) : "f"(hi), "f"(lo)); return r;
}
__device__ __forceinline__ float ex2(float x) { float r; asm("ex2.approx.ftz.f32 %0, %1;" : "=f"(r) : "f"(x)); return r; }
__device__ __forceinline__ void ldsm4(uint32_t a, uint32_t& r0, uint32_t& r1, uint32_t& r2, uint32_t& r3) {
  asm volatile("ldmatrix.sync.aligned.m8n8.x4.shared.b16 {%0,%1,%2,%3}, [%4];" : "=r"(r0), "=r"(r1), "=r"(r2), "=r"(r3) : "r"(a) : "memory");
}
__device__ __forceinline__ void stsm4(uint32_t a, uint32_t r0, uint32_t r1, uint32_t r2, uint32_t r3) {
  asm volatile("stmatrix.sync.aligned.m8n8.x4.shared.b16 [%0], {%1,%2,%3,%4};" ::"r"(a), "r"(r0), "r"(r1), "r"(r2), "r"(r3) : "memory");
}
__device__ __forceinline__ void flag_add(int idx, int v = 1) {
  asm volatile(ELECT("red.release.gpu.global.add.s32 [%0], %1;") ::"l"(g_flags + idx), "r"(v) : "memory");
}
__device__ __forceinline__ void flag_add_rx(int idx, int v = 1) {
  asm volatile(ELECT("red.relaxed.gpu.global.add.s32 [%0], %1;") ::"l"(g_flags + idx), "r"(v) : "memory");
}
template <bool ACQ, int NS = 32> __device__ __forceinline__ void flag_wait(int idx, int target) {
  int n = 0;
  while (true) {
    int v;
    if (ACQ) asm volatile("ld.acquire.gpu.global.s32 %0, [%1];" : "=r"(v) : "l"(g_flags + idx) : "memory");
    else asm volatile("ld.relaxed.gpu.global.s32 %0, [%1];" : "=r"(v) : "l"(g_flags + idx) : "memory");
    if (__all_sync(0xffffffffu, v >= target)) break;
    if (++n > 20000000) __trap();
    __nanosleep(NS);
  }
}
__device__ __forceinline__ int flag_peek(int idx) {
  int v;
  asm volatile("ld.relaxed.gpu.global.s32 %0, [%1];" : "=r"(v) : "l"(g_flags + idx) : "memory");
  return v;
}
__device__ __forceinline__ void mask_wait(uint32_t& ready, int bit, int idx, int target) {
  for (int n = 0; !((ready >> bit) & 1); n++) {
    int v;
    if (n) { __nanosleep(32); if (n > 20000000) __trap(); }
    asm volatile("ld.relaxed.gpu.global.s32 %0, [%1];" : "=r"(v) : "l"(g_flags + idx) : "memory");
    ready = __ballot_sync(0xffffffffu, v >= target);
  }
}
__device__ __forceinline__ uint32_t desc_lo(uint32_t addr, uint32_t lbo) { return ((addr & 0x3FFFFu) >> 4) | ((lbo >> 4) << 16); }

template <int TB, int TA = 0> __device__ __forceinline__ void wgmma_ss64(float (&d)[32], uint32_t alo, uint32_t blo, int sd) {
  asm volatile("{\n.reg .pred p;\n.reg .b64 da, db;\n"
    "setp.ne.b32 p, %34, 0;\nmov.b64 da, {%32, %36};\nmov.b64 db, {%33, %36};\n"
    "wgmma.mma_async.sync.aligned.m64n64k16.f32.bf16.bf16 "
    "{%0,%1,%2,%3,%4,%5,%6,%7,%8,%9,%10,%11,%12,%13,%14,%15,%16,%17,%18,%19,%20,%21,%22,%23,"
    "%24,%25,%26,%27,%28,%29,%30,%31}, "
    "da, db, p, 1, 1, %37, %35;\n}\n"
    : "+f"(d[0]),"+f"(d[1]),"+f"(d[2]),"+f"(d[3]),"+f"(d[4]),"+f"(d[5]),"+f"(d[6]),"+f"(d[7]),"+f"(d[8]),"+f"(d[9]),"+f"(d[10]),"+f"(d[11]),
      "+f"(d[12]),"+f"(d[13]),"+f"(d[14]),"+f"(d[15]),"+f"(d[16]),"+f"(d[17]),"+f"(d[18]),"+f"(d[19]),"+f"(d[20]),"+f"(d[21]),"+f"(d[22]),"+f"(d[23]),
      "+f"(d[24]),"+f"(d[25]),"+f"(d[26]),"+f"(d[27]),"+f"(d[28]),"+f"(d[29]),"+f"(d[30]),"+f"(d[31])
    : "r"(alo), "r"(blo), "r"(sd), "n"(TB), "r"(DESC_HI), "n"(TA));
}
template <int TB, int TA = 0> __device__ __forceinline__ void wgmma_ss128(float (&d)[64], uint32_t alo, uint32_t blo, int sd) {
  asm volatile("{\n.reg .pred p;\n.reg .b64 da, db;\n"
    "setp.ne.b32 p, %66, 0;\nmov.b64 da, {%64, %68};\nmov.b64 db, {%65, %68};\n"
    "wgmma.mma_async.sync.aligned.m64n128k16.f32.bf16.bf16 "
    "{%0,%1,%2,%3,%4,%5,%6,%7,%8,%9,%10,%11,%12,%13,%14,%15,%16,%17,%18,%19,%20,%21,%22,%23,"
    "%24,%25,%26,%27,%28,%29,%30,%31,%32,%33,%34,%35,%36,%37,%38,%39,%40,%41,%42,%43,%44,%45,%46,%47,"
    "%48,%49,%50,%51,%52,%53,%54,%55,%56,%57,%58,%59,%60,%61,%62,%63}, "
    "da, db, p, 1, 1, %69, %67;\n}\n"
    : "+f"(d[0]),"+f"(d[1]),"+f"(d[2]),"+f"(d[3]),"+f"(d[4]),"+f"(d[5]),"+f"(d[6]),"+f"(d[7]),"+f"(d[8]),"+f"(d[9]),"+f"(d[10]),"+f"(d[11]),
      "+f"(d[12]),"+f"(d[13]),"+f"(d[14]),"+f"(d[15]),"+f"(d[16]),"+f"(d[17]),"+f"(d[18]),"+f"(d[19]),"+f"(d[20]),"+f"(d[21]),"+f"(d[22]),"+f"(d[23]),
      "+f"(d[24]),"+f"(d[25]),"+f"(d[26]),"+f"(d[27]),"+f"(d[28]),"+f"(d[29]),"+f"(d[30]),"+f"(d[31]),"+f"(d[32]),"+f"(d[33]),"+f"(d[34]),"+f"(d[35]),
      "+f"(d[36]),"+f"(d[37]),"+f"(d[38]),"+f"(d[39]),"+f"(d[40]),"+f"(d[41]),"+f"(d[42]),"+f"(d[43]),"+f"(d[44]),"+f"(d[45]),"+f"(d[46]),"+f"(d[47]),
      "+f"(d[48]),"+f"(d[49]),"+f"(d[50]),"+f"(d[51]),"+f"(d[52]),"+f"(d[53]),"+f"(d[54]),"+f"(d[55]),"+f"(d[56]),"+f"(d[57]),"+f"(d[58]),"+f"(d[59]),
      "+f"(d[60]),"+f"(d[61]),"+f"(d[62]),"+f"(d[63])
    : "r"(alo), "r"(blo), "r"(sd), "n"(TB), "r"(DESC_HI), "n"(TA));
}
template <int TB> __device__ __forceinline__ void wgmma_rs128(float (&d)[64], uint32_t a0, uint32_t a1, uint32_t a2, uint32_t a3, uint32_t blo, int sd) {
  asm volatile("{\n.reg .pred p;\n.reg .b64 db;\n"
    "setp.ne.b32 p, %69, 0;\nmov.b64 db, {%68, %71};\n"
    "wgmma.mma_async.sync.aligned.m64n128k16.f32.bf16.bf16 "
    "{%0,%1,%2,%3,%4,%5,%6,%7,%8,%9,%10,%11,%12,%13,%14,%15,%16,%17,%18,%19,%20,%21,%22,%23,"
    "%24,%25,%26,%27,%28,%29,%30,%31,%32,%33,%34,%35,%36,%37,%38,%39,%40,%41,%42,%43,%44,%45,%46,%47,"
    "%48,%49,%50,%51,%52,%53,%54,%55,%56,%57,%58,%59,%60,%61,%62,%63}, "
    "{%64,%65,%66,%67}, db, p, 1, 1, %70;\n}\n"
    : "+f"(d[0]),"+f"(d[1]),"+f"(d[2]),"+f"(d[3]),"+f"(d[4]),"+f"(d[5]),"+f"(d[6]),"+f"(d[7]),"+f"(d[8]),"+f"(d[9]),"+f"(d[10]),"+f"(d[11]),
      "+f"(d[12]),"+f"(d[13]),"+f"(d[14]),"+f"(d[15]),"+f"(d[16]),"+f"(d[17]),"+f"(d[18]),"+f"(d[19]),"+f"(d[20]),"+f"(d[21]),"+f"(d[22]),"+f"(d[23]),
      "+f"(d[24]),"+f"(d[25]),"+f"(d[26]),"+f"(d[27]),"+f"(d[28]),"+f"(d[29]),"+f"(d[30]),"+f"(d[31]),"+f"(d[32]),"+f"(d[33]),"+f"(d[34]),"+f"(d[35]),
      "+f"(d[36]),"+f"(d[37]),"+f"(d[38]),"+f"(d[39]),"+f"(d[40]),"+f"(d[41]),"+f"(d[42]),"+f"(d[43]),"+f"(d[44]),"+f"(d[45]),"+f"(d[46]),"+f"(d[47]),
      "+f"(d[48]),"+f"(d[49]),"+f"(d[50]),"+f"(d[51]),"+f"(d[52]),"+f"(d[53]),"+f"(d[54]),"+f"(d[55]),"+f"(d[56]),"+f"(d[57]),"+f"(d[58]),"+f"(d[59]),
      "+f"(d[60]),"+f"(d[61]),"+f"(d[62]),"+f"(d[63])
    : "r"(a0), "r"(a1), "r"(a2), "r"(a3), "r"(blo), "r"(sd), "n"(TB), "r"(DESC_HI));
}
template <int TB, int TA = 0> __device__ __forceinline__ void wgmma_ss192(float (&d)[96], uint32_t alo, uint32_t blo, int sd) {
  asm volatile("{\n.reg .pred p;\n.reg .b64 da, db;\n"
    "setp.ne.b32 p, %98, 0;\nmov.b64 da, {%96, %100};\nmov.b64 db, {%97, %100};\n"
    "wgmma.mma_async.sync.aligned.m64n192k16.f32.bf16.bf16 "
    "{%0,%1,%2,%3,%4,%5,%6,%7,%8,%9,%10,%11,%12,%13,%14,%15,%16,%17,%18,%19,%20,%21,%22,%23,"
    "%24,%25,%26,%27,%28,%29,%30,%31,%32,%33,%34,%35,%36,%37,%38,%39,%40,%41,%42,%43,%44,%45,%46,%47,"
    "%48,%49,%50,%51,%52,%53,%54,%55,%56,%57,%58,%59,%60,%61,%62,%63,%64,%65,%66,%67,%68,%69,%70,%71,"
    "%72,%73,%74,%75,%76,%77,%78,%79,%80,%81,%82,%83,%84,%85,%86,%87,%88,%89,%90,%91,%92,%93,%94,%95}, "
    "da, db, p, 1, 1, %101, %99;\n}\n"
    : "+f"(d[0]),"+f"(d[1]),"+f"(d[2]),"+f"(d[3]),"+f"(d[4]),"+f"(d[5]),"+f"(d[6]),"+f"(d[7]),"+f"(d[8]),"+f"(d[9]),"+f"(d[10]),"+f"(d[11]),
      "+f"(d[12]),"+f"(d[13]),"+f"(d[14]),"+f"(d[15]),"+f"(d[16]),"+f"(d[17]),"+f"(d[18]),"+f"(d[19]),"+f"(d[20]),"+f"(d[21]),"+f"(d[22]),"+f"(d[23]),
      "+f"(d[24]),"+f"(d[25]),"+f"(d[26]),"+f"(d[27]),"+f"(d[28]),"+f"(d[29]),"+f"(d[30]),"+f"(d[31]),"+f"(d[32]),"+f"(d[33]),"+f"(d[34]),"+f"(d[35]),
      "+f"(d[36]),"+f"(d[37]),"+f"(d[38]),"+f"(d[39]),"+f"(d[40]),"+f"(d[41]),"+f"(d[42]),"+f"(d[43]),"+f"(d[44]),"+f"(d[45]),"+f"(d[46]),"+f"(d[47]),
      "+f"(d[48]),"+f"(d[49]),"+f"(d[50]),"+f"(d[51]),"+f"(d[52]),"+f"(d[53]),"+f"(d[54]),"+f"(d[55]),"+f"(d[56]),"+f"(d[57]),"+f"(d[58]),"+f"(d[59]),
      "+f"(d[60]),"+f"(d[61]),"+f"(d[62]),"+f"(d[63]),"+f"(d[64]),"+f"(d[65]),"+f"(d[66]),"+f"(d[67]),"+f"(d[68]),"+f"(d[69]),"+f"(d[70]),"+f"(d[71]),
      "+f"(d[72]),"+f"(d[73]),"+f"(d[74]),"+f"(d[75]),"+f"(d[76]),"+f"(d[77]),"+f"(d[78]),"+f"(d[79]),"+f"(d[80]),"+f"(d[81]),"+f"(d[82]),"+f"(d[83]),
      "+f"(d[84]),"+f"(d[85]),"+f"(d[86]),"+f"(d[87]),"+f"(d[88]),"+f"(d[89]),"+f"(d[90]),"+f"(d[91]),"+f"(d[92]),"+f"(d[93]),"+f"(d[94]),"+f"(d[95])
    : "r"(alo), "r"(blo), "r"(sd), "n"(TB), "r"(DESC_HI), "n"(TA));
}

struct Ctx {
  uint32_t sm;
  uint32_t bar;
  uint32_t rbar;
  int cl, rank, wg, warp, lane, phases;
};
__device__ __forceinline__ void release(const Ctx& c, int b, int cnt = 1) {
  if (c.lane < 2) mbar_arrive_cl(c.rbar + b * 8, cnt);
}
#define HK 5
#define NPRO 6
#define ZLEAD 16
#define PFM 7
#define PF1 1
constexpr float SM_SCALE = 0.08838834764831845f * 1.4426950408889634f;
constexpr float SM_HI = 1.8446744e19f, SM_LO = 5.4210109e-20f;
constexpr int ORDER = 1;

__device__ __forceinline__ void stage_tile(const float (&a)[64], uint32_t buf, const Ctx& c, float s0, float s1) {
  const int row = (c.lane & 7) + ((c.lane >> 3) & 1) * 8;
  const uint32_t base = buf + (c.warp * 16 + row) * 128 + (((c.lane >> 4) ^ (row & 7)) << 4);
#pragma unroll
  for (int i = 0; i < 8; i++)
    stsm4((base ^ ((i & 3) << 5)) + (i >> 2) * 8192, pack_bf16(a[8 * i] * s0, a[8 * i + 1] * s0), pack_bf16(a[8 * i + 2] * s1, a[8 * i + 3] * s1),
          pack_bf16(a[8 * i + 4] * s0, a[8 * i + 5] * s0), pack_bf16(a[8 * i + 6] * s1, a[8 * i + 7] * s1));
}

__device__ __forceinline__ void p1_epilogue(const Params& p, const Ctx& c, const float (&acc)[64], int t, int type) {
  const int tile = p.s.r[c.cl].tile[t] & 63, b = c.wg * 2 + 1;
  mbar_wait(c.bar + (B_SE + b) * 8, (t & 1) ^ 1);
  if (type && tile >= 32) {
    const int r = 2 * (c.lane & 3) + ((c.lane >> 2) & 1);
    const uint32_t dst = c.sm + SM_BUF + b * 16384 + r * 128 + (((c.warp * 2) ^ r) << 4) + (c.lane >> 3) * 4;
#pragma unroll
    for (int i = 0; i < 16; i++) {
      asm volatile("st.shared.u32 [%0], %1;" ::"r"(dst + i * 1024), "r"(pack_bf16(acc[4 * i], acc[4 * i + 1])) : "memory");
      asm volatile("st.shared.u32 [%0], %1;" ::"r"((dst ^ 16) + i * 1024), "r"(pack_bf16(acc[4 * i + 2], acc[4 * i + 3])) : "memory");
    }
  } else {
    if (type) stage_tile(acc, c.sm + SM_BUF + b * 16384, c, SM_SCALE, SM_SCALE);
    else stage_tile(acc, c.sm + SM_BUF + b * 16384, c, 1.f, 1.f);
  }
  FENCE_ASYNC_SMEM();
  __syncwarp();
  if (c.lane == 0) mbar_arrive(c.bar + (B_SF + b) * 8);
}

__device__ __forceinline__ void p1_consumer(const Params& p, const Ctx& c) {
  const int n = p.s.r[c.cl].n1;
  const int type = p.s.r[c.cl].slab >> 3;
  const uint32_t bdesc = desc_lo(c.sm + SM_RING, 8192), adesc = desc_lo(c.sm + SM_BUF + 32768 + c.wg * 8192, 16);
  uint32_t A[128];
  float acc[64] = {};
  int slot = 0, par = 0;
  auto next = [&]() { if (++slot == 10) { slot = 0; par ^= 1; } };
  {
    const int row = (c.lane & 7) + ((c.lane >> 3) & 1) * 8;
    const uint32_t base = c.sm + SM_RING + (c.wg * 64 + c.warp * 16 + row) * 128 + (((c.lane >> 4) ^ (row & 7)) << 4);
    if (c.wg == 1) bar_sync(ORDER + 1, 256);
    int pa = -1, pb = -1;
    if (type) {
      mbar_wait(c.bar + B_P1F * 8, 0);
      WG_FENCE();
#pragma unroll
      for (int kk = 0; kk < 4; kk++) wgmma_ss128<1>(acc, adesc + kk * 2, bdesc + kk * 128, kk != 0);
      WG_COMMIT();
      pb = 0; slot = 1;
    }
#pragma unroll
    for (int kb = 0; kb < 8; kb++) {
      const int sa = slot;
      mbar_wait(c.bar + (B_P1F + slot) * 8, par);
      next();
      mbar_wait(c.bar + (B_P1F + slot) * 8, par);
      WG_FENCE();
#pragma unroll
      for (int kk = 0; kk < 4; kk++)
        wgmma_ss128<1>(acc, desc_lo(c.sm + SM_RING + c.wg * 8192, 16) + sa * 1024 + kk * 2, bdesc + slot * 1024 + kk * 128, (kb | kk) != 0 ? 1 : type);
      WG_COMMIT();
      if (kb == 1 && c.wg == 0) bar_arrive(ORDER + 1, 256);
#pragma unroll
      for (int kk = 0; kk < 4; kk++) ldsm4((base ^ (kk << 5)) + sa * 16384, A[kb * 16 + kk * 4], A[kb * 16 + kk * 4 + 1], A[kb * 16 + kk * 4 + 2], A[kb * 16 + kk * 4 + 3]);
      WG_WAIT(1);
      if (kb > 0) release(c, B_P1E + pa);
      if (kb > 0 || pb >= 0) release(c, B_P1E + pb);
      pa = sa; pb = slot;
      next();
    }
    WG_WAIT(0);
    __syncwarp();
    release(c, B_P1E + pa);
    release(c, B_P1E + pb);
    pin(acc);
    p1_epilogue(p, c, acc, 0, type);
  }
  for (int t = 1; t < n; t++) {
    bar_sync(ORDER + c.wg, 256);
    int prev1 = -1, prev2 = -1;
    if (type) {
      mbar_wait(c.bar + (B_P1F + slot) * 8, par);
      WG_FENCE();
#pragma unroll
      for (int kk = 0; kk < 4; kk++) wgmma_ss128<1>(acc, adesc + kk * 2, bdesc + slot * 1024 + kk * 128, kk != 0);
      WG_COMMIT();
      prev1 = slot;
      next();
    }
#pragma unroll
    for (int kb = 0; kb < 8; kb++) {
      mbar_wait(c.bar + (B_P1F + slot) * 8, par);
      WG_FENCE();
      const uint32_t d = bdesc + slot * 1024;
#pragma unroll
      for (int kk = 0; kk < 4; kk++)
        wgmma_rs128<1>(acc, A[kb * 16 + kk * 4], A[kb * 16 + kk * 4 + 1], A[kb * 16 + kk * 4 + 2], A[kb * 16 + kk * 4 + 3], d + kk * 128, (kb | kk) != 0 ? 1 : type);
      WG_COMMIT();
      if (kb == HK) {
        if (t + 1 < n || c.wg == 0) bar_arrive(ORDER + (c.wg ^ 1), 256);
      }
      if (kb > 0) { WG_WAIT(2); if (kb > 1 || prev2 >= 0) release(c, B_P1E + prev2); }
      prev2 = prev1; prev1 = slot;
      next();
    }
    WG_WAIT(1);
    release(c, B_P1E + prev2);
    WG_WAIT(0);
    pin(acc);
    release(c, B_P1E + prev1);
    p1_epilogue(p, c, acc, t, type);
  }
}

__device__ __forceinline__ void p1_producer(const Params& p, const Ctx& c) {
  const int n = p.s.r[c.cl].n1;
  const int type = p.s.r[c.cl].slab >> 3, grp = p.s.r[c.cl].slab & 7;
  int slot = NPRO % 10, par = NPRO < 10;
#pragma unroll 1
  for (int t = 0; t < n; t++) {
    const int tile = p.s.r[c.cl].tile[t] & 63;
    const CUtensorMap* m = &p.map_w[type * 2 + (tile >> 5)];
    const int n0 = (tile & 31) * 128 + c.rank * 64;
    const uint64_t pol = p.s.r[c.cl].tile[t] >= 192 ? POL(0) : L2_NORMAL;
    const int ptile = p.s.r[c.cl].tile[t + PF1 < n ? t + PF1 : t];
    const CUtensorMap* pm = &p.map_w[type * 2 + ((ptile >> 5) & 1)];
    if (t == 7 && (c.phases & 16)) flag_wait<true>(F_GATE, 256);
#pragma unroll 1
    for (int kb = t ? -type : (NPRO - type) >> 1; kb < 8; kb++) {
      if (t == 0 && 2 * kb + type >= NPRO) {
        mbar_wait(c.bar + (B_P1E + slot) * 8, par);
        mbar_expect(c.bar + (B_P1F + slot) * 8, 16384);
        tma2d(c.sm + SM_RING + slot * 16384, &p.map_a[type], kb * 64, grp * 256 + c.rank * 128, c.bar + (B_P1F + slot) * 8);
        if (++slot == 10) { slot = 0; par ^= 1; }
      }
      mbar_wait(c.bar + (B_P1E + slot) * 8, par);
      mbar_expect(c.bar + (B_P1F + slot) * 8, 16384);
      tma2d_mc(c.sm + SM_RING + slot * 16384 + c.rank * 8192, m, n0, kb < 0 ? 512 : kb * 64, c.bar + (B_P1F + slot) * 8, pol);
      if (t + PF1 < n && t > 0 && ((ptile >> 6) == 1 || ((ptile >> 6) == 2 && ((kb ^ grp) & PFM) == 0))) tma2d_prefetch(pm, (ptile & 31) * 128 + c.rank * 64, kb < 0 ? 512 : kb * 64);
      if (++slot == 10) { slot = 0; par ^= 1; }
    }
  }
}

__device__ __forceinline__ void wait_kv_dead(const Ctx& c, int h, int g) {
  if (g >= 2) flag_wait<false>(F_RD + h * 8 + g, 8 - g);
  else flag_wait<false>(F_CTX + max(c.lane & 7, g) * 64 + h, 4);
}
__device__ __forceinline__ int p1_storer(const Params& p, const Ctx& c) {
  const int n = p.s.r[c.cl].n1;
  const int type = p.s.r[c.cl].slab >> 3, grp = p.s.r[c.cl].slab & 7;
  for (int i = 0; i < 2 * n; i++) {
    const int t = i >> 1, w = i & 1, b = w * 2 + 1;
    const int tile = p.s.r[c.cl].tile[t] & 63;
    mbar_wait(c.bar + (B_SF + b) * 8, t & 1);
    const uint32_t src = c.sm + SM_BUF + b * 16384;
    int f = (type ? F_Q : F_KV) + (tile & 31) * 8 + grp;
    if (type == 0) {
      const int prev = p.s.prev[tile & 31][grp];
      if (prev != 255 && w == 0) wait_kv_dead(c, prev, grp);
      uint8_t* dst = g_S + (size_t)(S_K + ((tile & 32) + p.s.slot[tile & 31][grp]) * 8 + grp) * 65536 + c.rank * 32768 + w * 8192;
      bulk_store(dst, src, 8192);
      bulk_store(dst + 16384, src + 8192, 8192);
    } else if (tile < 32) {
      const int dep = p.s.qdep[tile * 8 + grp];
      if (dep != 511 && w == 0) {
        if (dep < 256) wait_kv_dead(c, dep >> 3, dep & 7);
        else flag_wait<false>(F_TS + dep - 256, 128);
      }
      bulk_store(g_S + (size_t)p.s.qblk[tile * 8 + grp] * 65536 + (c.rank * 2 + w) * 16384, src, 16384);
    } else {
      tma3d_store(&p.map_t[2], src, (grp * 4 + c.rank * 2 + w) * 32, 0, (tile - 32) * 64);
      f = F_QKVA + grp * 4 + ((0xE4390900u >> (2 * (tile - 30))) & 3);
    }
    BULK_COMMIT();
    BULK_WAIT(0);
    mbar_arrive_one(c.bar + (B_SE + b) * 8);
    if (i == 2 * n - 1) return f;
    if (w) flag_add(f, 2);
  }
  return -1;
}

__device__ __forceinline__ int p2_buf(int w, int i) { return w * 2 + (i & 1); }
__device__ __forceinline__ int p2_blk(int rank, int w, int i) { return ((i ^ w) & 1) == 0 ? 3 - rank : rank; }


template <int N>
__device__ __forceinline__ void row_max(const float (&s)[N], float& m0, float& m1) {
  float a0 = fmaxf(s[0], s[1]), a1 = fmaxf(s[2], s[3]);
#pragma unroll
  for (int i = 1; i < N / 4; i++) {
    m0 = fmaxf(m0, s[4 * i]); a0 = fmaxf(a0, s[4 * i + 1]);
    m1 = fmaxf(m1, s[4 * i + 2]); a1 = fmaxf(a1, s[4 * i + 3]);
  }
  m0 = fmaxf(m0, a0); m1 = fmaxf(m1, a1);
  m0 = fmaxf(m0, __shfl_xor_sync(0xffffffffu, m0, 1));
  m1 = fmaxf(m1, __shfl_xor_sync(0xffffffffu, m1, 1));
  m0 = fmaxf(m0, __shfl_xor_sync(0xffffffffu, m0, 2));
  m1 = fmaxf(m1, __shfl_xor_sync(0xffffffffu, m1, 2));
}
template <bool SUB, int N>
__device__ __forceinline__ void row_exp(const float (&s)[N], uint32_t (&P)[32], float m0, float m1, float& t0, float& t1) {
  float u0 = 0.f, u1 = 0.f;
  t0 = t1 = 0.f;
#pragma unroll
  for (int i = 0; i < N / 4; i++) {
    const float e0 = ex2(SUB ? s[4 * i] - m0 : s[4 * i]), e1 = ex2(SUB ? s[4 * i + 1] - m0 : s[4 * i + 1]);
    const float e2 = ex2(SUB ? s[4 * i + 2] - m1 : s[4 * i + 2]), e3 = ex2(SUB ? s[4 * i + 3] - m1 : s[4 * i + 3]);
    if (i == 0) { t0 = e0; u0 = e1; t1 = e2; u1 = e3; }
    else { t0 += e0; u0 += e1; t1 += e2; u1 += e3; }
    P[2 * i] = pack_bf16(e0, e1);
    P[2 * i + 1] = pack_bf16(e2, e3);
  }
#pragma unroll
  for (int i = N / 2; i < 32; i++) P[i] = 0;
  pin(P);
  t0 += u0; t1 += u1;
}
template <int N>
__device__ __forceinline__ void causal_mask(float (&s)[N], int thr) {
#pragma unroll
  for (int i = 0; i < 8; i++) {
    if (8 * i > thr) s[N - 32 + 4 * i] = -INFINITY;
    if (8 * i + 1 > thr) s[N - 32 + 4 * i + 1] = -INFINITY;
    if (8 * i - 8 > thr) s[N - 32 + 4 * i + 2] = -INFINITY;
    if (8 * i - 7 > thr) s[N - 32 + 4 * i + 3] = -INFINITY;
  }
}
__device__ __forceinline__ void issue_qk(float (&s)[32], uint32_t qd, uint32_t kd) {
  WG_FENCE();
#pragma unroll
  for (int kk = 0; kk < 8; kk++) wgmma_ss64<0>(s, qd + (kk >> 2) * 512 + (kk & 3) * 2, kd + (kk >> 2) * 1024 + (kk & 3) * 2, kk != 0);
  WG_COMMIT();
}
__device__ __forceinline__ void issue_qk(float (&s)[64], uint32_t qd, uint32_t kd) {
  WG_FENCE();
#pragma unroll
  for (int kk = 0; kk < 8; kk++) wgmma_ss128<0>(s, qd + (kk >> 2) * 512 + (kk & 3) * 2, kd + (kk >> 2) * 1024 + (kk & 3) * 2, kk != 0);
  WG_COMMIT();
}
template <int NK>
__device__ __forceinline__ void issue_pv(float (&o)[64], const uint32_t (&P)[32], uint32_t vd, int acc) {
  WG_FENCE();
#pragma unroll
  for (int kk = 0; kk < NK; kk++) wgmma_rs128<1>(o, P[4 * kk], P[4 * kk + 1], P[4 * kk + 2], P[4 * kk + 3], vd + kk * 128, kk != 0 ? 1 : acc);
  WG_COMMIT();
}
__device__ __forceinline__ void stage_done(const Ctx& c, int b) {
  FENCE_ASYNC_SMEM();
  __syncwarp();
  if (c.lane == 0) mbar_arrive(c.bar + (B_SF + b) * 8);
}
__device__ __forceinline__ void p2_epilogue(const float (&o)[64], float s0, float s1, const Ctx& c, int b) {
  stage_tile(o, c.sm + SM_BUF + b * 16384, c, s0, s1);
  stage_done(c, b);
}

struct P2State {
  float m0, m1, l0, l1;
  bool shift;
  float e0, e1;
  int ks;
  int wi, ai;
  uint32_t wb, ab;
  uint32_t qd;
};
__device__ __forceinline__ int wrap5(int q) { return q >= 5 ? q - 5 : q; }
__device__ __forceinline__ void turn_wait(uint32_t ring, int i) { mbar_wait(ring + (i & 3) * 8, (i >> 2) & 1); }
__device__ __forceinline__ void turn_pass(const Ctx& c, uint32_t ring, int i) { if (c.lane == 0) mbar_arrive(ring + (i & 3) * 8); }
__device__ __forceinline__ void p2_scales(P2State& z) {
  float l0 = z.l0, l1 = z.l1;
  l0 += __shfl_xor_sync(0xffffffffu, l0, 1);
  l1 += __shfl_xor_sync(0xffffffffu, l1, 1);
  l0 += __shfl_xor_sync(0xffffffffu, l0, 2);
  l1 += __shfl_xor_sync(0xffffffffu, l1, 2);
  asm("rcp.approx.ftz.f32 %0, %1;" : "=f"(z.e0) : "f"(l0));
  asm("rcp.approx.ftz.f32 %0, %1;" : "=f"(z.e1) : "f"(l1));
}
template <int N>
__device__ __forceinline__ void p2_first(const Ctx& c, P2State& z, float (&o)[64], uint32_t (&Pc)[32], uint32_t (&Pn)[32],
                                         int ks, int vs, int cnt, int acc) {
  float s[N] = {};
  issue_qk(s, z.qd, desc_lo(c.sm + SM_RING, 16) + ks * 2048);
  if (vs >= 0) {
    p2_scales(z);
    issue_pv<8>(o, Pc, desc_lo(c.sm + SM_RING, 16384) + vs * 2048, acc);
  } else {
    WG_COMMIT();
  }
  mbar_expect(z.ab + (z.ai++ & 3) * 8, cnt == 1 ? 8192 : 0);
  WG_WAIT(1);
  pin(s);
  release(c, B_P2E + ks, cnt);
  causal_mask(s, c.warp * 16 + (c.lane >> 2) - 2 * (c.lane & 3));
  z.m0 = z.m1 = 0.f;
  row_exp<false>(s, Pn, 0.f, 0.f, z.l0, z.l1);
  z.shift = __any_sync(0xffffffffu, !(z.l0 + z.l1 <= SM_HI) || ((c.lane & 3) == 0 && !(fminf(z.l0, z.l1) >= SM_LO)));
  if (__builtin_expect(z.shift, 0)) {
    z.m0 = z.m1 = -INFINITY;
    row_max(s, z.m0, z.m1);
    row_exp<true>(s, Pn, z.m0, z.m1, z.l0, z.l1);
  }
  WG_WAIT(0);
  pin(o);
  if (vs >= 0) release(c, B_P2E + vs, 1);
}

template <bool SECOND>
__device__ __forceinline__ void p2_turn(const Ctx& c, P2State& z, float (&o)[64], uint32_t (&Pc)[32], uint32_t (&Pn)[32],
                                        int eb = -1, bool half = false, int vcnt = 1) {
  float s[64] = {};
  const int ks = z.ks, vs = wrap5(ks + 1);
  turn_wait(z.wb, z.wi++);
  issue_qk(s, z.qd, desc_lo(c.sm + SM_RING, 16) + ks * 2048);
  const uint32_t vd = desc_lo(c.sm + SM_RING, 16384) + vs * 2048;
  if (SECOND) {
    if (eb >= 0) stage_tile(o, c.sm + SM_BUF + eb * 16384, c, z.e0, z.e1);
    if (half) issue_pv<4>(o, Pc, vd, 0); else issue_pv<8>(o, Pc, vd, 0);
  } else {
    issue_pv<8>(o, Pc, vd, 1);
  }
  turn_pass(c, z.ab, z.ai++);
  if (SECOND) { if (eb >= 0) stage_done(c, eb); }
  z.ks = wrap5(ks + 2);
  WG_WAIT(1);
  pin(s);
  release(c, B_P2E + ks, 1);
  float t0, t1, a0 = 1.f, a1 = 1.f;
  row_exp<false>(s, Pn, 0.f, 0.f, t0, t1);
  const bool redo = __any_sync(0xffffffffu, z.shift || !(t0 + t1 <= SM_HI));
  if (__builtin_expect(redo, 0)) {
    float n0 = z.m0, n1 = z.m1;
    if (!z.shift) { n0 = __log2f(z.l0); n1 = __log2f(z.l1); }
    z.shift = true;
    row_max(s, n0, n1);
    a0 = ex2(z.m0 - n0); a1 = ex2(z.m1 - n1);
    z.m0 = n0; z.m1 = n1;
    z.l0 *= a0; z.l1 *= a1;
    row_exp<true>(s, Pn, z.m0, z.m1, t0, t1);
  }
  WG_WAIT(0);
  pin(o);
  release(c, B_P2E + vs, vcnt);
  if (__builtin_expect(redo, 0)) {
#pragma unroll
    for (int i = 0; i < 16; i++) { o[4 * i] *= a0; o[4 * i + 1] *= a0; o[4 * i + 2] *= a1; o[4 * i + 3] *= a1; }
  }
  z.l0 += t0; z.l1 += t1;
}
__device__ __forceinline__ void copy_p(uint32_t (&d)[32], const uint32_t (&s)[32], int zero) {
#pragma unroll
  for (int i = 0; i < 32; i++) asm volatile("add.s32 %0, %1, %2;" : "=r"(d[i]) : "r"(s[i]), "r"(zero));
}

__device__ __forceinline__ void p2_consumer(const Params& p, const Ctx& c, int rot) {
  const int nit = p.s.r[c.cl].n2;
  const uint32_t fring = c.bar + B_P2F * 8, oring = c.bar + B_ORD * 8;
  float o[64] = {};
  uint32_t Pa[32] = {}, Pb[32] = {};
  P2State z;
  z.e0 = z.e1 = z.l0 = z.l1 = 0.f; z.ks = rot; z.shift = false;
  int acc = 0, n = 0;
  for (int it = 0; it < nit; it++) {
    const int j = p.s.r[c.cl].item[it] & 7, blk = p2_blk(c.rank, c.wg, it);
    const int lng = ((it ^ c.wg) & 1) ^ 1;
    z.qd = desc_lo(c.sm + SM_BUF, 16) + p2_buf(c.wg, it) * 1024;
    if (lng) { z.wb = oring; z.wi = n - it; z.ab = fring; z.ai = n + 1; }
    else { z.wb = fring; z.wi = n + 2; z.ab = oring; z.ai = n - it; }
    mbar_wait(c.bar + (B_QF + p2_buf(c.wg, it)) * 8, (it >> 1) & 1);
    turn_wait(fring, n + 1 - lng);
    const int vs = it ? wrap5(z.ks + 1) : -1, ks = lng ? z.ks : wrap5(z.ks + (it ? 2 : 1));
    if (blk & 1) p2_first<64>(c, z, o, Pa, Pb, ks, vs, 1 + lng, acc);
    else p2_first<32>(c, z, o, Pa, Pb, ks, vs, 1 + lng, acc);
    z.ks = wrap5(ks + (it == 0 && lng ? 1 : 2));
    n += 2 * j + 2;
    int left = 2 * j + lng;
    acc = left != 0;
    if (left == 0) { copy_p(Pa, Pb, p.zero); continue; }
    p2_turn<true>(c, z, o, Pb, Pa, it > 0 ? p2_buf(c.wg, it - 1) : -1, !(blk & 1), 1 + lng);
    while (--left > 0) {
      p2_turn<false>(c, z, o, Pa, Pb);
      if (--left == 0) { copy_p(Pa, Pb, p.zero); break; }
      p2_turn<false>(c, z, o, Pb, Pa);
    }
  }
  {
    if (!acc && nit > 1) p2_epilogue(o, z.e0, z.e1, c, p2_buf(c.wg, nit));
    turn_wait(z.wb, z.wi);
    issue_pv<8>(o, Pa, desc_lo(c.sm + SM_RING, 16384) + z.ks * 2048, acc);
    if (((nit - 1) ^ c.wg) & 1) turn_pass(c, z.ab, z.ai);
    p2_scales(z);
    WG_WAIT(0);
    pin(o);
    release(c, B_P2E + z.ks);
    p2_epilogue(o, z.e0, z.e1, c, p2_buf(c.wg, nit - 1));
  }
}

__device__ __forceinline__ void p2_load_q(const Params& p, const Ctx& c, int it, int w) {
  const int item = p.s.r[c.cl].item[it], b = p2_buf(w, it);
  mbar_expect(c.bar + (B_QF + b) * 8, 16384);
  bulk_load(c.sm + SM_BUF + b * 16384, g_S + (size_t)p.s.qblk[item] * 65536 + p2_blk(c.rank, w, it) * 16384, 16384, c.bar + (B_QF + b) * 8, POL(4));
}
__device__ __forceinline__ void wait_p1_free(const Ctx& c, int u1, int s) {
  mbar_wait(c.bar + (B_P1E + 2 * s) * 8, ((u1 - 1 - 2 * s) / 10) & 1);
  mbar_wait(c.bar + (B_P1E + 2 * s + 1) * 8, ((u1 - 2 - 2 * s) / 10) & 1);
}
__device__ __forceinline__ void p2_producer(const Params& p, const Ctx& c, int u1, int rot) {
  const int nit = p.s.r[c.cl].n2;
  int slot = rot, cnt = 0, par = 1, n = 0;
  const uint8_t* pv = nullptr;
  bool pl = false;
  auto load = [&](const uint8_t* src, int expect, uint32_t fb, bool last) {
    if (cnt < 5) {
      if (u1) {
        wait_p1_free(c, u1, slot);
        if (cnt == 0) p2_load_q(p, c, 0, 1);
      }
      cnt++;
    } else {
      if (slot == rot) par ^= 1;
      mbar_wait(c.bar + (B_P2E + slot) * 8, par);
    }
    if (expect) mbar_expect(fb, expect);
    bulk_load_mc(c.sm + SM_RING + slot * 32768 + c.rank * 16384, src, 16384, fb, last ? POL(5) : L2_NORMAL);
    slot = wrap5(slot + 1);
  };
  for (int it = 0; it < nit; it++) {
    const int item = p.s.r[c.cl].item[it], h = item >> 3, j = item & 7;
    if (it == 1 && (c.phases & 16) && p.s.r[c.cl].n1 < 8) flag_wait<true>(F_GATE, 256);
    uint32_t ready = (c.phases & 16) ? 0u : 255u;
    if (it == 0) { if (c.phases & 16) flag_wait<false>(F_Q + item, 4); mbar_wait(c.bar + B_LAD * 8, 0); p2_load_q(p, c, 0, 0); if (!u1) p2_load_q(p, c, 0, 1); }
    for (int t = 2 * j + 1; t >= 0; t--) {
      mask_wait(ready, t >> 1, F_KV + h * 8 + (c.lane & 7), 8);
      const uint8_t* k = g_S + (size_t)(2 * S_K + p.s.slot[h][t >> 1] * 16 + t) * 32768 + c.rank * 16384;
      const uint32_t fb = c.bar + (B_P2F + (n & 3)) * 8;
      const bool last = (p.s.r[c.cl].last[it] >> (t >> 1)) & 1;
      load(k, pv && t != 2 * j ? 65536 : 32768, fb, last);
      if (!(t & 1) && t + 4 <= 2 * j && c.rank == 0) flag_add_rx(F_RD + h * 8 + (t >> 1) + 2);
      if (pv) load(pv, 0, t != 2 * j ? fb : c.bar + (B_ORD + ((n - 1 - it) & 3)) * 8, pl);
      pl = last;
      pv = k + (size_t)NH * 16 * 32768;
      n++;
    }
  }
  load(pv, 32768, c.bar + (B_P2F + (n & 3)) * 8, pl);
}

__device__ __forceinline__ void publish_and_load_q(const Params& p, const Ctx& c, int f, int it, int seen) {
  const bool want = it < p.s.r[c.cl].n2, early = want && __all_sync(0xffffffffu, seen >= 4);
  if (early) { p2_load_q(p, c, it, it & 1); p2_load_q(p, c, it, (it & 1) ^ 1); }
  if (f >= 0) flag_add(f, 2);
  if (want && !early) {
    if (c.phases & 16) flag_wait<false>(F_Q + p.s.r[c.cl].item[it], 4);
    p2_load_q(p, c, it, it & 1); p2_load_q(p, c, it, (it & 1) ^ 1);
  }
}
__device__ __forceinline__ void p2_storer(const Params& p, const Ctx& c, int sfpar) {
  const int nit = p.s.r[c.cl].n2;
  int held = -1;
  for (int i = 0; i < 2 * nit; i++) {
    const int it = i >> 1, w = (it ^ i ^ 1) & 1, b = p2_buf(w, it);
    const int item = p.s.r[c.cl].item[it], h = item >> 3, j = item & 7;
    mbar_wait(c.bar + (B_SF + b) * 8, (sfpar >> b) & 1);
    sfpar ^= 1 << b;
    bulk_store(g_S + (size_t)p.s.qblk[item] * 65536 + p2_blk(c.rank, w, it) * 16384, c.sm + SM_BUF + b * 16384, 16384, POL(1));
    BULK_COMMIT();
    if (i & 1) {
      if (it + 2 == nit && (p.s.r[c.cl].item[it + 1] & 7) == 0) { held = F_CTX + j * 64 + h; continue; }
      const int seen = flag_peek(F_Q + p.s.r[c.cl].item[min(it + 2, nit - 1)]);
      BULK_WAIT(0);
      if (it + 1 == nit) release(c, B_DONE);
      publish_and_load_q(p, c, F_CTX + j * 64 + h, it + 2, seen);
    }
  }
  if (held >= 0) flag_add_rx(held, 2);
}

__device__ __forceinline__ int p3_pos(int i, int x) { return i < 4 ? (i + x) & 3 : 4; }
__device__ __forceinline__ void p3_consumer(const Params& p, const Ctx& c, int x) {
  const bool first = p.s.r[c.cl].p3 >= 24;
  const int tile = p.s.r[c.cl].p3 - (first ? 24 : 0), j = tile / 3, nt = tile - 3 * j;
  const int na = first ? 9 : 0, nb = p.s.task[c.cl][1] - p.s.task[c.cl][0];
  const uint32_t ad = desc_lo(c.sm + SM_RING + c.wg * 8192, 16), bd = desc_lo(c.sm + SM_RING + 16384, 4096);
  float acc[96] = {};
  int slot = 0, par = 0, prev = 0;
  float g0 = 0.f, g1 = 0.f;
  const int hold = c.wg && LAG ? na + nb - LAG : -1, pass = c.wg || !LAG ? -1 : na + nb - 1;
  const float* gp = g_gate + j * 256 + c.rank * 128 + c.wg * 64 + c.warp * 16 + (c.lane >> 2);
#pragma unroll 1
  for (int kb = 0; kb < na; kb++) {
    if (kb == hold) bar_sync(6, 256);
    mbar_wait(c.bar + (B_P3F + slot) * 8, par);
    WG_FENCE();
#pragma unroll
    for (int kk = 0; kk < 4; kk++) wgmma_ss192<1, 1>(acc, ad + p3_pos(slot, x) * 2560 + kk * 128, bd + p3_pos(slot, x) * 2560 + (kk >> 1) * 768 + (kk & 1) * 128, kk != 0 ? 1 : kb != 0);
    WG_COMMIT();
    if (kb == pass) bar_arrive(6, 256);
    WG_WAIT(1);
    if (kb > 0) release(c, B_P3E + prev);
    else { g0 = __ldcg(gp); g1 = __ldcg(gp + 8); }
    prev = slot;
    if (++slot == 5) { slot = 0; par ^= 1; }
  }
#pragma unroll 1
  for (int kb = na; kb < na + nb; kb++) {
    if (kb == hold) bar_sync(6, 256);
    mbar_wait(c.bar + (B_P3F + slot) * 8, par);
    WG_FENCE();
#pragma unroll
    for (int kk = 0; kk < 4; kk++) wgmma_ss192<1>(acc, ad + p3_pos(slot, x) * 2560 + kk * 2, bd + p3_pos(slot, x) * 2560 + (kk >> 1) * 768 + (kk & 1) * 128, kk != 0 ? 1 : kb != 0);
    WG_COMMIT();
    if (kb == pass) bar_arrive(6, 256);
    WG_WAIT(1);
    if (kb > 0) release(c, B_P3E + prev);
    else { g0 = __ldcg(gp); g1 = __ldcg(gp + 8); }
    prev = slot;
    if (++slot == 5) { slot = 0; par ^= 1; }
  }
  g0 = __fdividef(1.f, 1.f + g0); g1 = __fdividef(1.f, 1.f + g1);
  WG_WAIT(0);
  pin(acc);
  if (first) bar_sync(4 + c.wg, 128);
  mbar_wait(c.bar + B_OUT * 8, 0);
  const int row = (c.lane & 7) + ((c.lane >> 3) & 1) * 8;
  const uint32_t wbase = c.sm + SM_RING + c.wg * 8192 + c.warp * 2048;
  const uint32_t base = wbase + row * 128 + (((c.lane >> 4) ^ (row & 7)) << 4);
#pragma unroll
  for (int i = 0; i < 12; i++) {
    stsm4((base ^ ((i & 3) << 5)) + (i >> 2) * 40960, pack_bf16(acc[8 * i] * g0, acc[8 * i + 1] * g0), pack_bf16(acc[8 * i + 2] * g1, acc[8 * i + 3] * g1),
          pack_bf16(acc[8 * i + 4] * g0, acc[8 * i + 5] * g0), pack_bf16(acc[8 * i + 6] * g1, acc[8 * i + 7] * g1));
    if ((i & 3) == 3) {
      FENCE_ASYNC_SMEM();
      bar_sync(4 + c.wg, 128);
      if (c.warp == (i >> 2)) tma2d_add(&p.map_out, c.sm + SM_RING + c.wg * 8192 + c.warp * 40960, nt * 192 + c.warp * 64, j * 256 + c.rank * 128 + c.wg * 64);
    }
  }
  BULK_COMMIT();
  BULK_WAIT_READ(0);
}

__device__ __forceinline__ void p3_producer(const Params& p, const Ctx& c, int u1, int u2, int rot, int x) {
  const bool first = p.s.r[c.cl].p3 >= 24;
  const int tile = p.s.r[c.cl].p3 - (first ? 24 : 0), j = tile / 3, nt = tile - 3 * j;
  int slot = 0, par = 1, cnt = 0;
  auto wait_free = [&](int s) {
    const int f = wrap5(s + 5 - rot);
    if (f < u2) mbar_wait(c.bar + (B_P2E + s) * 8, ((u2 - 1 - f) / 5) & 1);
    else if (u1) wait_p1_free(c, u1, s);
  };
  asm volatile(ELECT("prefetch.tensormap [%0];") ::"l"(&p.map_o[0]) : "memory");
  asm volatile(ELECT("prefetch.tensormap [%0];") ::"l"(&p.map_out) : "memory");
  if ((c.phases & 16) && p.s.r[c.cl].n1 < 8 && p.s.r[c.cl].n2 < 2) flag_wait<true>(F_GATE, 256);
  uint32_t ready = (c.phases & 16) ? 0u : ~0u;
  const int q0 = p.s.task[c.cl][0], q1 = p.s.task[c.cl][1];
  for (int q = q0 - (first ? 9 : 0); q < q1; q++) {
    if (q == max(q0, 64 - ZLEAD)) mbar_arrive_one(c.bar + B_ZF * 8);
    const bool brA = q < q0;
    const int kb = brA ? q - q0 + 9 : p.s.p3_order[tile][q];
    if (!brA) mask_wait(ready, kb >> 1, F_CTX + j * 64 + c.lane, 4);
    else if (kb == 0 && (c.phases & 16)) flag_wait<false>(F_CTX + j * 64 + 32, 16);
    const uint8_t* a = brA ? g_oA + (j * 4 + c.rank * 2) * 73728 + kb * 8192 : g_S + (size_t)p.s.qblk[(kb >> 1) * 8 + j] * 65536 + c.rank * 32768 + (kb & 1) * 8192;
    const uint32_t st = c.sm + SM_RING + p3_pos(slot, x) * 40960, fb = c.bar + (B_P3F + slot) * 8;
    if (cnt < 4) { wait_free(p3_pos(cnt, x)); wait_free(p3_pos(cnt, x) + 1); }
    else if (cnt == 4) mbar_wait(c.bar + B_DONE * 8, 0);
    else mbar_wait(c.bar + (B_P3E + slot) * 8, par);
    cnt++;
    mbar_expect(fb, 40960);
    bulk_load(st, a, 8192, fb, POL(3));
    bulk_load(st + 8192, a + (brA ? 73728 : 16384), 8192, fb, POL(3));
    tma3d_mc(st + 16384 + c.rank * 12288, &p.map_o[brA], 0, kb * 64 + c.rank * 32, nt * 3, fb);
    if (++slot == 5) { slot = 0; par ^= 1; }
  }
}

__device__ __forceinline__ float bf_lo(uint32_t w) { return __uint_as_float(w << 16); }
__device__ __forceinline__ float bf_hi(uint32_t w) { return __uint_as_float(w & 0xffff0000u); }

__device__ __forceinline__ void gate_rows(const Params& p, int row0, int lane) {
  const uint4* x = reinterpret_cast<const uint4*>(p.x + (size_t)(row0 + (lane >> 2)) * DM) + (lane & 3);
  const uint4* w = reinterpret_cast<const uint4*>(p.gate_w) + (lane & 3);
  float a = 0.f;
#pragma unroll 1
  for (int b = 0; b < 3; b++) {
    uint4 u[6];
#pragma unroll
    for (int i = 0; i < 6; i++) u[i] = __ldg(x + (b * 6 + i) * 4);
#pragma unroll
    for (int i = 0; i < 6; i++) {
      const uint4 v = __ldg(w + (b * 6 + i) * 4);
      a = fmaf(bf_lo(u[i].x), bf_lo(v.x), a); a = fmaf(bf_hi(u[i].x), bf_hi(v.x), a);
      a = fmaf(bf_lo(u[i].y), bf_lo(v.y), a); a = fmaf(bf_hi(u[i].y), bf_hi(v.y), a);
      a = fmaf(bf_lo(u[i].z), bf_lo(v.z), a); a = fmaf(bf_hi(u[i].z), bf_hi(v.z), a);
      a = fmaf(bf_lo(u[i].w), bf_lo(v.w), a); a = fmaf(bf_hi(u[i].w), bf_hi(v.w), a);
    }
  }
  a += __shfl_xor_sync(0xffffffffu, a, 1);
  a += __shfl_xor_sync(0xffffffffu, a, 2);
  if ((lane & 3) == 0) g_gate[row0 + (lane >> 2)] = __expf(fminf(a, 60.f));
}

__device__ __forceinline__ void lds10(uint32_t (&k)[10], uint32_t a) {
  asm volatile("ld.shared.v2.u32 {%0, %1}, [%10];\nld.shared.v2.u32 {%2, %3}, [%10+8];\nld.shared.v2.u32 {%4, %5}, [%10+16];\n"
               "ld.shared.v2.u32 {%6, %7}, [%10+24];\nld.shared.v2.u32 {%8, %9}, [%10+32];"
               : "=r"(k[0]), "=r"(k[1]), "=r"(k[2]), "=r"(k[3]), "=r"(k[4]), "=r"(k[5]), "=r"(k[6]), "=r"(k[7]), "=r"(k[8]), "=r"(k[9]) : "r"(a));
}
__device__ __forceinline__ void local_attn(const Params& p, const Ctx& c, int rb, int hs) {
  const int lane = c.lane, grp = rb >> 2, par = lane >> 4, i0 = 2 * (lane & 15);
  const uint32_t buf = c.sm + SM_BUF + (c.warp - 2) * 8192, bqk = c.bar + (B_LA + (c.warp - 2) * 2) * 8, bv = bqk + 8;
  const uint32_t mine = buf + 2304 + par * 160 + i0 * 4;
  const bool flags = c.phases & 16;
  auto fetch_qk = [&](int i) {
    if (flags && !(i & 1)) {
      const int q = i >> 1;
      const int tgt = q == 0 ? 24 : q == 3 ? 8 : 12;
      flag_wait<false>(F_QKVA + (grp - (grp > 0 && (rb & 3) == 0 ? par : 0)) * 4 + q, tgt);
    }
    mbar_expect(bqk, 5184);
    tma3d(buf, &p.map_t[0], rb * 32, 0, 9 * (4 * i + hs), bqk, POL(2));
    tma3d(buf + 2304, &p.map_t[1], rb * 32 - 8, 0, 288 + 9 * (4 * i + hs), bqk, POL(2));
  };
  auto fetch_v = [&](int i) { mbar_expect(bv, 2880); tma3d(buf + 5248, &p.map_t[1], rb * 32 - 8, 0, 576 + 9 * (4 * i + hs), bv, POL(2)); };
  fetch_qk(0);
  if (flags) flag_wait<true>(F_GATE, 256);
#pragma unroll 1
  for (int q = 0; q < 8; q++) {
    fetch_v(q);
    float a[8], b[8];
#pragma unroll
    for (int w = 0; w < 8; w++) a[w] = b[w] = 0.f;
    mbar_wait(bqk, q & 1);
#pragma unroll 1
    for (int j = 0; j < 9; j++) {
      uint32_t x, y, k[10];
      asm volatile("ld.shared.v2.u32 {%0, %1}, [%2];" : "=r"(x), "=r"(y) : "r"(buf + lane * 8 + j * 256));
      lds10(k, mine + j * 320);
      const float xl = bf_lo(x), xh = bf_hi(x), yl = bf_lo(y), yh = bf_hi(y);
#pragma unroll
      for (int m = 1; m < 10; m++) {
        const float kl = bf_lo(k[m]), kh = bf_hi(k[m]);
        if (m < 9) a[8 - m] = fmaf(xl, kl, fmaf(xh, kh, a[8 - m]));
        if (m > 1) b[9 - m] = fmaf(yl, kl, fmaf(yh, kh, b[9 - m]));
      }
    }
    __syncwarp();
    mbar_wait(bv, q & 1);
    if (q & 1) flag_add_rx(F_TS + (q >> 1));
    if (q < 7) fetch_qk(q + 1);
    constexpr float SC = 0.23570226039551584f * 1.4426950408889634f;
    const float* gp = g_gate + rb * 64 + 2 * i0 + par;
    const float ga = __ldcg(gp), gb = __ldcg(gp + 2);
    float ma = a[0], mb = b[0];
#pragma unroll
    for (int w = 1; w < 8; w++) {
      if (rb == 0) {
        if (i0 < w) a[w] = -INFINITY;
        if (i0 + 1 < w) b[w] = -INFINITY;
      }
      ma = fmaxf(ma, a[w]); mb = fmaxf(mb, b[w]);
    }
    float la = 0.f, lb = 0.f;
#pragma unroll
    for (int w = 0; w < 8; w++) {
      a[w] = ex2((a[w] - ma) * SC); b[w] = ex2((b[w] - mb) * SC);
      la += a[w]; lb += b[w];
    }
    la = __fdividef(ga, la); lb = __fdividef(gb, lb);
#pragma unroll
    for (int w = 0; w < 8; w++) { a[w] *= la; b[w] *= lb; }
    uint8_t* dst = g_oA + rb * 73728 + ((i0 & 2) + par) * 4;
#pragma unroll 1
    for (int j = 0; j < 9; j++) {
      uint32_t v[10];
      lds10(v, mine + 2944 + j * 320);
      float a0 = 0.f, a1 = 0.f, b0 = 0.f, b1 = 0.f;
#pragma unroll
      for (int m = 1; m < 10; m++) {
        const float vl = bf_lo(v[m]), vh = bf_hi(v[m]);
        if (m < 9) { a0 = fmaf(a[8 - m], vl, a0); a1 = fmaf(a[8 - m], vh, a1); }
        if (m > 1) { b0 = fmaf(b[9 - m], vl, b0); b1 = fmaf(b[9 - m], vh, b1); }
      }
      const uint32_t wa = pack_bf16(a0, a1), wb = pack_bf16(b0, b1);
      const uint32_t got = __shfl_xor_sync(0xffffffffu, par ? wa : wb, 16);
      const uint32_t r0 = par ? got : wa, r1 = par ? wb : got;
      const int col = 18 * (4 * q + hs) + 2 * j, o = col * 128 + ((((i0 >> 2) ^ col) & 7) << 4);
      *reinterpret_cast<uint32_t*>(dst + o) = __byte_perm(r0, r1, 0x5410);
      *reinterpret_cast<uint32_t*>(dst + ((o + 128) ^ 16)) = __byte_perm(r0, r1, 0x7632);
    }
    __syncwarp();
  }
  mbar_arrive_one(c.bar + B_LAD * 8);
  flag_add(F_CTX + grp * 64 + 32);
}

__global__ void __cluster_dims__(2, 1, 1) __launch_bounds__(384, 1) fused_kernel(const __grid_constant__ Params p) {
  extern __shared__ uint8_t smem_raw[];
  Ctx c;
  c.sm = ((uint32_t)__cvta_generic_to_shared(smem_raw) + 1023u) & ~1023u;
  c.bar = c.sm + SM_BAR;
  c.lane = threadIdx.x & 31;
  const int wid = __shfl_sync(0xffffffffu, threadIdx.x >> 5, 0);
  if (wid < 6) asm volatile("prefetch.tensormap [%0];" ::"l"(&p.map_a[0] + wid) : "memory");
  c.wg = wid >> 2;
  c.warp = wid & 3;
  c.cl = (blockIdx.x + (wid >> 4)) >> 1;
  c.rank = blockIdx.x & 1;
  c.rbar = mapa(c.bar, c.lane & 1);
  {
    const int w = wid, cnt = (((int)(B_CNT >> (4 * w)) - 1) & 15) + 1;
    if (w < 11) {
#pragma unroll
      for (int i = 0; i < 8; i++) asm volatile("mbarrier.init.shared::cta.b64 [%0], %1;" ::"r"(c.bar + w * 64 + i * 8), "r"(cnt));
    }
    asm volatile("fence.mbarrier_init.release.cluster;" ::: "memory");
  }
  asm volatile("barrier.cluster.arrive.relaxed;" ::: "memory");
  c.phases = p.s.r[c.cl].phases;
  const bool do1 = p.s.r[c.cl].n1 > 0, do2 = p.s.r[c.cl].n2 > 0, do3 = p.s.r[c.cl].p3 != 255;
  if (do1 && c.wg == 2 && c.warp == 0) {
    const int type = p.s.r[c.cl].slab >> 3;
    FENCE_ASYNC_SMEM();
    mbar_expect(c.bar + B_P1F * 8, type ? 32768 : 16384);
    tma2d(type ? c.sm + SM_BUF + 32768 : c.sm + SM_RING, &p.map_a[type], type ? 512 : 0, (p.s.r[c.cl].slab & 7) * 256 + c.rank * 128, c.bar + B_P1F * 8);
  }
  asm volatile("barrier.cluster.wait.acquire;" ::: "memory");
  if (do1 && c.wg == 2 && c.warp == 0) {
    const int type = p.s.r[c.cl].slab >> 3, tile = p.s.r[c.cl].tile[0] & 63;
    const CUtensorMap* m = &p.map_w[type * 2 + (tile >> 5)];
#pragma unroll 1
    for (int s = 1 - type; s < NPRO; s++) {
      const int kb = (s - type) >> 1;
      const uint32_t fb = c.bar + (B_P1F + s) * 8;
      if (s) mbar_expect(fb, 16384);
      if ((s ^ type) & 1) tma2d_mc(c.sm + SM_RING + s * 16384 + c.rank * 8192, m, (tile & 31) * 128 + c.rank * 64, kb < 0 ? 512 : kb * 64, fb);
      else tma2d(c.sm + SM_RING + s * 16384, &p.map_a[type], kb * 64, (p.s.r[c.cl].slab & 7) * 256 + c.rank * 128, fb);
    }
  }

  if (c.wg < 2) {
    asm volatile("setmaxnreg.inc.sync.aligned.u32 224;");
    if (c.wg == 1) {
      if (do1) bar_arrive(ORDER, 256);
      if (c.lane == 0) mbar_arrive(c.bar + B_P2F * 8);
    }
    if (do1) p1_consumer(p, c);
    if (do2) p2_consumer(p, c, p.s.r[c.cl].rot);
    if (do3) p3_consumer(p, c, p.s.r[c.cl].x3);
    if (c.lane == 0) mbar_arrive(c.bar + B_FIN * 8);
    __syncwarp();
    cluster_sync();
  } else {
    asm volatile("setmaxnreg.dec.sync.aligned.u32 56;");
    if (c.warp == 0) {
      if (do1) p1_producer(p, c);
      if (do2) p2_producer(p, c, p.s.r[c.cl].u1, p.s.r[c.cl].rot);
      if (do3) p3_producer(p, c, p.s.r[c.cl].u1, p.s.r[c.cl].u2, p.s.r[c.cl].rot, p.s.r[c.cl].x3);
    } else if (c.warp == 1) {
      const int f = do1 ? p1_storer(p, c) : -1;
      if (do2) {
        publish_and_load_q(p, c, f, 1, flag_peek(F_Q + p.s.r[c.cl].item[1]));
        p2_storer(p, c, (p.s.r[c.cl].n1 & 1) * 10);
      } else {
        const bool idle = mbar_test(c.bar + B_LAD * 8, 0);
        if (idle) release(c, B_DONE);
        if (f >= 0) flag_add(f, 2);
        if (!idle) { mbar_wait(c.bar + B_LAD * 8, 0); release(c, B_DONE); }
      }
      if (do3) {
        const int tile = p.s.r[c.cl].p3 % 24;
        if (p.s.task[c.cl][1] == 64) {
          mbar_wait(c.bar + B_ZF * 8, 0);
          const int j = tile / 3, nt = tile - 3 * j;
          uint4* o = reinterpret_cast<uint4*>(p.out + (size_t)(j * 256 + c.rank * 128 + (c.lane >> 3)) * DM + nt * 192) + (c.lane & 7);
#pragma unroll 4
          for (int r = 0; r < 32; r++) o[r * 288] = o[r * 288 + 8] = o[r * 288 + 16] = make_uint4(0u, 0u, 0u, 0u);
          __syncwarp();
          flag_add(F_OUT + tile * 2 + c.rank);
        } else if (c.phases & 16) {
          flag_wait<false, 256>(F_OUT + tile * 2 + c.rank, 1);
        }
        mbar_arrive_one(c.bar + B_OUT * 8);
      }
    } else {
      const int bw = blockIdx.x * 2 + (c.warp - 2);
      if ((c.phases & 1) && bw < 256) {
        gate_rows(p, bw * 8, c.lane);
        __syncwarp();
        flag_add(F_GATE);
      }
      if (p.s.r[c.cl].bg != 255) local_attn(p, c, p.s.r[c.cl].bg, bw & 3);
      else if (c.lane == 0) mbar_arrive(c.bar + B_LAD * 8);
    }
    __syncwarp();
    bar_sync(3, 128);
    if (c.warp == 0 && (c.phases & 32)) {
      int last = 0;
      if (c.lane == 0) { __threadfence(); last = atomicAdd(g_flags + F_DONE, 1) == 2 * NCL - 1; }
      if (__shfl_sync(0xffffffffu, last, 0)) for (int i = c.lane; i < F_NUM; i += 32) g_flags[i] = 0;
    }
    if (c.warp == 1) mbar_wait(c.bar + B_FIN * 8, 0);
    __syncwarp();
    cluster_sync();
  }
}

static const Sched k_sched = {
  {{0,29,2,35,0,{200,242,0,0,0,0,0,0,0,0,0},{0,0,0,0,0,0,0,0,0,0,0},{70,105,8,226,192,49,44,231,225,234,54,235,53,242,240,51,47,46,244,237,248,250,60,62,249,63,253,247,251,0}},
   {1,29,1,20,1,{236,0,0,0,0,0,0,0,0,0,0},{31,0,0,0,0,0,0,0,0,0,0},{68,105,66,232,192,108,241,231,225,234,54,235,53,242,240,46,243,239,244,237,248,250,60,62,249,61,63,247,251,0}},
   {2,29,1,12,2,{188,0,0,0,0,0,0,0,0,0,0},{0,0,0,0,0,0,0,0,0,0,0},{68,227,201,226,192,49,39,33,236,234,43,246,50,245,240,51,47,52,46,237,248,250,57,252,254,55,253,255,251,0}},
   {3,29,2,14,3,{248,187,0,0,0,0,0,0,0,0,0},{0,0,0,0,0,0,0,0,0,0,0},{70,104,201,226,192,49,33,231,236,234,43,246,50,245,240,51,47,52,45,238,248,250,57,252,254,61,63,247,251,0}},
   {4,28,1,24,4,{228,0,0,0,0,0,0,0,0,0,0},{0,0,0,0,0,0,0,0,0,0,0},{70,35,9,40,197,224,1,39,10,11,22,21,16,210,19,15,20,13,14,24,26,25,28,30,29,31,23,27,0,0}},
   {5,27,0,17,5,{0,0,0,0,0,0,0,0,0,0,0},{0,0,0,0,0,0,0,0,0,0,0},{131,36,9,40,5,32,7,33,10,43,21,18,16,19,15,14,20,13,24,26,25,28,30,29,31,23,27,0,0,0}},
   {6,26,0,9,6,{0,0,0,0,0,0,0,0,0,0,0},{0,0,0,0,0,0,0,0,0,0,0},{99,105,8,34,0,49,7,44,11,54,18,16,19,15,20,14,13,24,26,25,28,30,29,31,23,27,0,0,0,0}},
   {7,25,0,7,7,{0,0,0,0,0,0,0,0,0,0,0},{0,0,0,0,0,0,0,0,0,0,0},{131,6,8,69,81,71,44,75,118,82,80,83,79,84,78,77,88,90,89,92,94,93,95,87,91,0,0,0,0,0}},
   {0,29,1,37,8,{227,0,0,0,0,0,0,0,0,0,0},{0,0,0,0,0,0,0,0,0,0,0},{131,38,4,40,5,32,12,7,193,10,22,203,21,18,16,19,15,14,212,205,24,26,28,30,217,31,221,23,27,0}},
   {1,29,2,22,9,{233,218,0,0,0,0,0,0,0,0,0},{0,0,0,0,0,0,0,0,0,0,0},{131,36,198,34,5,32,209,7,1,10,22,11,21,18,16,14,211,207,20,13,24,26,28,30,25,29,31,23,27,0}},
   {2,29,2,32,10,{201,250,0,0,0,0,0,0,0,0,0},{0,0,0,0,0,0,0,0,0,0,0},{70,36,8,41,5,32,7,1,12,10,11,22,18,21,16,19,15,20,14,13,24,26,25,28,30,23,29,223,27,0}},
   {3,29,1,28,11,{243,0,0,0,0,0,0,0,0,0,0},{0,0,0,0,0,0,0,0,0,0,0},{131,38,196,233,5,32,1,199,204,202,11,214,18,213,208,19,15,20,13,206,216,218,25,220,222,29,31,215,219,0}},
   {4,28,0,16,12,{0,0,0,0,0,0,0,0,0,0,0},{0,0,0,0,0,0,0,0,0,0,0},{102,4,41,194,229,17,33,12,42,43,54,53,48,50,51,47,52,45,46,56,58,57,60,62,61,63,55,59,0,0}},
   {5,27,0,20,13,{0,0,0,0,0,0,0,0,0,0,0},{0,0,0,0,0,0,0,0,0,0,0},{99,6,41,2,37,17,39,12,42,22,53,50,48,51,47,46,52,45,56,58,57,60,62,61,63,55,59,0,0,0}},
   {6,26,0,18,14,{0,0,0,0,0,0,0,0,0,0,0},{0,0,0,0,0,0,0,0,0,0,0},{68,6,40,69,32,1,39,10,43,21,50,48,51,47,52,46,45,56,58,57,60,62,61,63,55,59,0,0,0,0}},
   {7,25,0,19,15,{0,0,0,0,0,0,0,0,0,0,0},{0,0,0,0,0,0,0,0,0,0,0},{99,38,40,101,113,103,74,107,85,114,112,115,111,116,110,109,120,122,121,124,126,125,127,119,123,0,0,0,0,0}},
   {0,6,6,4,255,{32,47,138,181,163,240,0,0,0,0,0},{0,0,0,0,0,0,0,0,0,0,0},{99,73,36,2,37,17,0,0,0,0,0,0,0,0,0,0,0,0,0,0,0,0,0,0,0,0,0,0,0,0}},
   {1,6,6,10,255,{64,46,13,145,164,208,0,0,0,0,0},{0,0,0,0,0,0,0,0,0,0,0},{99,73,230,200,37,76,0,0,0,0,0,0,0,0,0,0,0,0,0,0,0,0,0,0,0,0,0,0,0,0}},
   {2,6,7,43,255,{76,41,60,82,148,214,185,0,0,0,0},{0,0,0,0,0,127,0,0,0,0,0},{102,195,40,2,37,17,0,0,0,0,0,0,0,0,0,0,0,0,0,0,0,0,0,0,0,0,0,0,0,0}},
   {3,6,5,36,255,{16,69,95,166,190,0,0,0,0,0,0},{0,0,0,127,0,0,0,0,0,0,0},{99,72,228,2,37,17,0,0,0,0,0,0,0,0,0,0,0,0,0,0,0,0,0,0,0,0,0,0,0,0}},
   {4,8,5,14,255,{40,6,99,129,165,0,0,0,0,0,0},{0,0,0,0,0,0,0,0,0,0,0},{131,36,8,34,0,49,7,44,0,0,0,0,0,0,0,0,0,0,0,0,0,0,0,0,0,0,0,0,0,0}},
   {5,10,5,45,255,{136,43,85,157,191,0,0,0,0,0,0},{0,0,0,48,255,0,0,0,0,0,0},{68,38,8,34,0,49,1,44,11,54,0,0,0,0,0,0,0,0,0,0,0,0,0,0,0,0,0,0,0,0}},
   {6,10,5,38,255,{0,4,98,134,247,0,0,0,0,0,0},{0,0,0,0,128,0,0,0,0,0,0},{100,38,66,101,81,33,12,42,22,53,0,0,0,0,0,0,0,0,0,0,0,0,0,0,0,0,0,0,0,0}},
   {7,9,6,27,255,{19,86,147,161,206,184,0,0,0,0,0},{0,0,0,0,0,0,0,0,0,0,0},{68,73,66,64,65,76,106,86,117,0,0,0,0,0,0,0,0,0,0,0,0,0,0,0,0,0,0,0,0,0}},
   {8,18,3,25,16,{125,105,237,0,0,0,0,0,0,0,0},{0,0,32,0,0,0,0,0,0,0,0},{160,170,69,235,35,44,109,12,10,85,79,208,77,152,206,158,159,29,0,0,0,0,0,0,0,0,0,0,0,0}},
   {9,18,3,29,17,{8,109,229,0,0,0,0,0,0,0,0},{0,0,0,0,0,0,0,0,0,0,0},{68,161,166,5,44,76,40,209,199,85,16,78,207,152,92,158,29,23,0,0,0,0,0,0,0,0,0,0,0,0}},
   {10,17,3,34,18,{172,193,246,0,0,0,0,0,0,0,0},{0,0,64,0,0,0,0,0,0,0,0},{134,161,162,99,71,17,109,12,86,85,16,78,15,152,89,158,159,0,0,0,0,0,0,0,0,0,0,0,0,0}},
   {11,17,2,5,19,{56,118,0,0,0,0,0,0,0,0,0},{0,0,0,0,0,0,0,0,0,0,0},{72,165,107,197,227,236,40,193,202,22,213,211,212,13,89,220,29,0,0,0,0,0,0,0,0,0,0,0,0,0}},
   {12,18,3,11,20,{176,146,144,0,0,0,0,0,0,0,0},{0,0,0,0,0,0,0,0,0,0,0},{105,9,194,81,39,1,12,45,11,80,18,15,77,152,89,158,23,27,0,0,0,0,0,0,0,0,0,0,0,0}},
   {13,18,3,31,21,{88,131,231,0,0,0,0,0,0,0,0},{0,0,255,0,0,0,0,0,0,0,0},{160,170,107,81,39,7,1,75,237,85,16,15,212,152,89,158,29,27,0,0,0,0,0,0,0,0,0,0,0,0}},
   {14,17,2,1,22,{111,222,0,0,0,0,0,0,0,0,0},{0,64,0,0,0,0,0,0,0,0,0},{160,170,166,99,44,1,74,40,86,80,19,84,14,90,92,93,23,0,0,0,0,0,0,0,0,0,0,0,0,0}},
   {15,18,3,30,23,{152,108,230,0,0,0,0,0,0,0,0},{0,0,0,0,0,0,0,0,0,0,0},{134,233,69,43,71,231,12,75,45,85,16,15,14,152,89,158,159,27,0,0,0,0,0,0,0,0,0,0,0,0}},
   {8,18,3,2,24,{168,116,112,0,0,0,0,0,0,0,0},{0,0,0,0,0,0,0,0,0,0,0},{100,9,162,0,39,104,7,1,83,11,214,210,20,90,92,217,23,27,0,0,0,0,0,0,0,0,0,0,0,0}},
   {9,18,3,42,25,{80,215,252,0,0,0,0,0,0,0,0},{1,0,31,0,0,0,0,0,0,0,0},{73,165,107,99,192,1,109,10,86,82,203,19,20,90,205,25,159,27,0,0,0,0,0,0,0,0,0,0,0,0}},
   {10,18,3,5,26,{156,210,253,0,0,0,0,0,0,0,0},{0,0,32,0,0,0,0,0,0,0,0},{68,165,166,103,0,104,1,10,11,82,19,84,77,90,92,87,91,29,0,0,0,0,0,0,0,0,0,0,0,0}},
   {11,19,4,39,27,{128,155,212,249,0,0,0,0,0,0,0},{0,15,0,0,0,0,0,0,0,0,0},{160,170,201,81,39,7,109,204,11,82,16,15,14,152,218,158,159,215,219,0,0,0,0,0,0,0,0,0,0,0}},
   {12,18,3,6,28,{120,113,115,0,0,0,0,0,0,0,0},{0,0,0,0,0,0,0,0,0,0,0},{100,4,107,0,227,236,7,40,202,22,213,211,212,14,218,220,159,221,0,0,0,0,0,0,0,0,0,0,0,0}},
   {13,18,1,3,29,{124,0,0,0,0,0,0,0,0,0,0},{0,0,0,0,0,0,0,0,0,0,0},{73,165,166,0,35,44,12,10,232,22,18,19,14,13,26,28,159,23,0,0,0,0,0,0,0,0,0,0,0,0}},
   {14,18,2,46,30,{110,245,0,0,0,0,0,0,0,0,0},{0,32,0,0,0,0,0,0,0,0,0},{73,161,69,0,39,7,12,75,45,85,18,15,77,152,89,158,159,27,0,0,0,0,0,0,0,0,0,0,0,0}},
   {15,17,5,33,31,{96,89,130,196,251,0,0,0,0,0,0},{1,0,0,7,0,0,0,0,0,0,0},{73,161,64,81,35,44,74,40,86,82,19,84,77,90,92,93,23,0,0,0,0,0,0,0,0,0,0,0,0,0}},
   {8,3,3,0,255,{31,103,119,0,0,0,0,0,0,0,0},{0,0,128,0,0,0,0,0,0,0,0},{134,165,2,0,0,0,0,0,0,0,0,0,0,0,0,0,0,0,0,0,0,0,0,0,0,0,0,0,0,0}},
   {9,3,5,17,255,{38,142,135,213,234,0,0,0,0,0,0},{0,0,252,0,0,0,0,0,0,0,0},{131,41,162,0,0,0,0,0,0,0,0,0,0,0,0,0,0,0,0,0,0,0,0,0,0,0,0,0,0,0}},
   {10,4,6,23,255,{34,26,44,9,151,104,0,0,0,0,0},{0,0,0,0,0,0,0,0,0,0,0},{100,9,200,197,0,0,0,0,0,0,0,0,0,0,0,0,0,0,0,0,0,0,0,0,0,0,0,0,0,0}},
   {11,4,6,21,255,{77,18,94,90,154,239,0,0,0,0,0},{0,0,0,0,0,192,0,0,0,0,0},{100,4,2,0,0,0,0,0,0,0,0,0,0,0,0,0,0,0,0,0,0,0,0,0,0,0,0,0,0,0}},
   {12,3,5,1,255,{27,35,3,183,114,0,0,0,0,0,0},{0,0,0,0,0,0,0,0,0,0,0},{160,170,166,0,0,0,0,0,0,0,0,0,0,0,0,0,0,0,0,0,0,0,0,0,0,0,0,0,0,0}},
   {13,3,8,9,255,{24,36,5,81,83,170,122,223,0,0,0},{0,0,0,0,0,0,0,128,0,0,0},{68,233,2,0,0,0,0,0,0,0,0,0,0,0,0,0,0,0,0,0,0,0,0,0,0,0,0,0,0,0}},
   {14,4,6,10,255,{28,49,63,91,198,220,0,0,0,0,0},{0,0,0,0,0,0,0,0,0,0,0},{134,165,162,81,0,0,0,0,0,0,0,0,0,0,0,0,0,0,0,0,0,0,0,0,0,0,0,0,0,0}},
   {15,3,6,21,255,{73,74,75,62,158,192,0,0,0,0,0},{0,0,0,2,0,0,0,0,0,0,0},{68,228,2,0,0,0,0,0,0,0,0,0,0,0,0,0,0,0,0,0,0,0,0,0,0,0,0,0,0,0}},
   {8,3,6,2,255,{55,12,182,197,226,217,0,0,0,0,0},{0,0,0,0,0,0,0,0,0,0,0},{131,161,196,0,0,0,0,0,0,0,0,0,0,0,0,0,0,0,0,0,0,0,0,0,0,0,0,0,0,0}},
   {9,3,8,18,255,{33,17,21,101,169,117,211,219,0,0,0},{0,0,0,0,0,0,0,0,0,0,0},{160,170,198,0,0,0,0,0,0,0,0,0,0,0,0,0,0,0,0,0,0,0,0,0,0,0,0,0,0,0}},
   {10,3,6,47,255,{29,65,140,175,194,205,0,0,0,0,0},{0,0,0,0,0,63,0,0,0,0,0},{105,195,2,0,0,0,0,0,0,0,0,0,0,0,0,0,0,0,0,0,0,0,0,0,0,0,0,0,0,0}},
   {11,3,8,4,255,{53,66,2,11,132,106,202,235,0,0,0},{0,0,0,0,0,0,0,0,0,0,0},{134,161,166,0,0,0,0,0,0,0,0,0,0,0,0,0,0,0,0,0,0,0,0,0,0,0,0,0,0,0}},
   {12,4,7,6,255,{67,20,1,59,127,238,216,0,0,0,0},{0,0,0,0,0,0,0,0,0,0,0},{134,161,8,5,0,0,0,0,0,0,0,0,0,0,0,0,0,0,0,0,0,0,0,0,0,0,0,0,0,0}},
   {13,4,4,40,255,{79,87,199,204,0,0,0,0,0,0,0},{0,0,0,0,0,0,0,0,0,0,0},{134,161,162,5,0,0,0,0,0,0,0,0,0,0,0,0,0,0,0,0,0,0,0,0,0,0,0,0,0,0}},
   {14,4,7,0,255,{50,7,137,174,162,241,189,0,0,0,0},{0,0,0,0,0,0,0,0,0,0,0},{68,41,2,43,0,0,0,0,0,0,0,0,0,0,0,0,0,0,0,0,0,0,0,0,0,0,0,0,0,0}},
   {15,4,5,22,255,{52,45,84,126,224,0,0,0,0,0,0},{0,0,0,3,0,0,0,0,0,0,0},{131,224,234,230,0,0,0,0,0,0,0,0,0,0,0,0,0,0,0,0,0,0,0,0,0,0,0,0,0,0}},
   {8,4,7,44,255,{71,58,92,178,123,203,186,0,0,0,0},{0,0,0,0,0,0,0,0,0,0,0},{105,8,166,81,0,0,0,0,0,0,0,0,0,0,0,0,0,0,0,0,0,0,0,0,0,0,0,0,0,0}},
   {9,4,7,41,255,{48,23,97,93,171,207,232,0,0,0,0},{0,0,0,0,0,192,0,0,0,0,0},{100,66,200,103,0,0,0,0,0,0,0,0,0,0,0,0,0,0,0,0,0,0,0,0,0,0,0,0,0,0}},
   {10,4,6,13,255,{78,141,57,173,107,221,0,0,0,0,0},{0,0,0,0,3,63,0,0,0,0,0},{160,170,107,108,0,0,0,0,0,0,0,0,0,0,0,0,0,0,0,0,0,0,0,0,0,0,0,0,0,0}},
   {11,3,4,8,255,{51,68,14,167,0,0,0,0,0,0,0},{0,0,0,128,0,0,0,0,0,0,0},{131,233,162,0,0,0,0,0,0,0,0,0,0,0,0,0,0,0,0,0,0,0,0,0,0,0,0,0,0,0}},
   {12,3,7,26,255,{39,42,100,179,121,209,254,0,0,0,0},{0,0,0,0,0,0,0,0,0,0,0},{131,165,162,0,0,0,0,0,0,0,0,0,0,0,0,0,0,0,0,0,0,0,0,0,0,0,0,0,0,0}},
   {13,3,5,13,255,{37,143,177,149,225,0,0,0,0,0,0},{0,0,0,0,0,0,0,0,0,0,0},{131,228,8,0,0,0,0,0,0,0,0,0,0,0,0,0,0,0,0,0,0,0,0,0,0,0,0,0,0,0}},
   {14,3,3,15,255,{30,15,150,0,0,0,0,0,0,0,0},{0,0,67,0,0,0,0,0,0,0,0},{131,36,8,0,0,0,0,0,0,0,0,0,0,0,0,0,0,0,0,0,0,0,0,0,0,0,0,0,0,0}},
   {15,4,5,8,255,{54,139,10,159,255,0,0,0,0,0,0},{0,0,0,0,192,0,0,0,0,0,0},{72,165,162,65,0,0,0,0,0,0,0,0,0,0,0,0,0,0,0,0,0,0,0,0,0,0,0,0,0,0}},
   {6,2,7,16,255,{25,70,61,180,153,195,244,0,0,0,0},{0,0,0,0,0,0,31,0,0,0,0},{131,73,0,0,0,0,0,0,0,0,0,0,0,0,0,0,0,0,0,0,0,0,0,0,0,0,0,0,0,0}},
   {7,5,5,12,255,{72,22,102,133,160,0,0,0,0,0,0},{0,0,0,0,0,0,0,0,0,0,0},{100,105,98,96,97,0,0,0,0,0,0,0,0,0,0,0,0,0,0,0,0,0,0,0,0,0,0,0,0,0}}},
  {{0,7,0,0},{6,17,0,0},{1,12,0,0},{6,17,0,0},{0,7,0,0},{17,64,0,0},{11,64,0,0},{6,64,0,0},{0,7,0,0},{6,19,0,0},{0,4,0,0},
   {0,7,0,0},{22,64,0,0},{17,64,0,0},{11,64,0,0},{5,64,0,0},{21,64,0,0},{15,64,0,0},{0,5,0,0},{0,1,0,0},{17,64,0,0},{0,1,0,0},
   {0,6,0,0},{0,8,0,0},{0,2,0,0},{0,7,0,0},{0,6,0,0},{19,64,0,0},{7,64,0,0},{0,6,0,0},{2,11,0,0},{0,7,0,0},{17,64,0,0},
   {0,2,0,0},{7,19,0,0},{0,7,0,0},{17,64,0,0},{8,64,0,0},{0,6,0,0},{0,2,0,0},{18,64,0,0},{5,17,0,0},{8,64,0,0},{1,15,0,0},
   {11,64,0,0},{2,11,0,0},{6,15,0,0},{15,64,0,0},{4,17,0,0},{2,11,0,0},{0,8,0,0},{7,21,0,0},{7,17,0,0},{0,8,0,0},{7,18,0,0},
   {19,64,0,0},{0,6,0,0},{0,5,0,0},{7,16,0,0},{17,64,0,0},{0,4,0,0},{16,64,0,0},{7,64,0,0},{4,17,0,0},{8,22,0,0},{12,64,0,0}},
  {{48,53,56,61,62,47,54,32,36,26,40,49,28,57,50,63,58,55,6,7,12,13,18,19,16,17,8,9,4,5,10,11,0,1,34,35,24,25,14,15,2,3,20,21,38,39,42,43,22,23,30,31,44,45,33,37,27,41,52,29,60,51,46,59},
   {47,54,49,53,29,57,61,51,63,58,55,6,7,12,13,18,19,16,17,8,9,4,5,10,11,0,1,34,35,24,25,14,15,2,3,20,21,38,39,42,43,22,23,30,31,44,45,32,33,36,37,26,27,40,41,48,52,28,56,60,50,62,46,59},
   {61,62,47,54,45,33,37,27,41,49,53,29,57,50,63,59,55,6,7,12,13,18,19,16,17,8,9,4,5,10,11,0,1,34,35,24,25,14,15,2,3,20,21,38,39,42,43,22,23,30,31,44,32,36,26,40,48,52,28,56,60,51,46,58},
   {53,27,61,51,59,63,47,55,6,7,18,19,8,9,4,5,12,13,16,17,10,11,0,1,24,25,2,3,34,35,20,21,14,15,44,45,42,43,36,37,32,33,22,23,28,29,38,39,30,31,40,41,56,57,48,49,52,26,60,50,58,62,46,54},
   {57,52,27,50,59,46,55,43,37,22,28,38,30,40,56,49,26,61,58,63,54,6,7,18,19,8,9,4,5,12,13,16,17,10,11,0,1,24,25,2,3,34,35,20,21,14,15,44,45,42,36,32,33,23,29,39,31,41,48,53,60,51,62,47},
   {56,49,26,61,58,63,54,22,28,38,30,40,57,52,27,50,59,46,55,6,7,18,19,8,9,4,5,12,13,16,17,10,11,0,1,24,25,2,3,34,35,20,21,14,15,44,45,42,43,36,37,32,33,23,29,39,31,41,48,53,60,51,62,47},
   {27,52,51,60,47,54,59,38,40,30,26,49,50,57,46,63,58,12,13,8,9,18,19,6,7,16,17,4,5,10,11,14,15,0,1,34,35,2,3,24,25,20,21,44,45,22,23,42,43,36,37,28,29,32,33,39,41,31,48,53,56,61,62,55},
   {57,61,47,63,55,59,12,13,8,9,18,19,6,7,16,17,4,5,10,11,14,15,0,1,34,35,2,3,24,25,20,21,44,45,22,23,42,43,36,37,28,29,32,33,38,39,40,41,30,31,26,27,48,49,52,53,50,51,56,60,46,62,54,58},
   {57,46,63,58,29,33,39,41,31,27,49,53,51,60,47,54,59,12,13,8,9,18,19,6,7,16,17,4,5,10,11,14,15,0,1,34,35,2,3,24,25,20,21,44,45,22,23,42,43,36,37,28,32,38,40,30,26,48,52,50,56,61,62,55},
   {62,47,27,49,51,53,57,61,59,46,55,12,13,6,7,16,17,8,9,18,19,4,5,10,11,34,35,0,1,14,15,2,3,24,25,20,21,22,23,44,45,36,37,42,43,32,33,28,29,38,39,30,31,40,41,26,48,50,52,56,60,58,63,54},
   {48,51,57,58,63,54,31,41,27,50,53,60,59,46,55,12,13,6,7,16,17,8,9,18,19,4,5,10,11,34,35,0,1,14,15,2,3,24,25,20,21,22,23,44,45,36,37,42,43,32,33,28,29,38,39,30,40,26,49,52,56,61,62,47},
   {53,57,61,59,63,47,55,12,13,6,7,16,17,8,9,18,19,4,5,10,11,34,35,0,1,14,15,2,3,24,25,20,21,22,23,44,45,36,37,42,43,32,33,28,29,38,39,30,31,40,41,26,27,48,49,50,51,52,56,60,58,62,46,54},
   {54,26,28,48,52,50,56,61,63,47,59,55,12,13,6,7,8,9,18,19,16,17,4,5,10,11,0,1,34,35,2,3,14,15,24,25,20,21,22,23,44,45,32,33,42,43,30,31,36,37,38,39,40,41,27,29,49,53,51,57,60,62,46,58},
   {28,49,50,57,62,47,54,40,26,29,52,51,60,63,59,55,12,13,6,7,8,9,18,19,16,17,4,5,10,11,0,1,34,35,2,3,14,15,24,25,20,21,22,23,44,45,32,33,42,43,30,31,36,37,38,39,41,27,48,53,56,61,46,58},
   {49,50,57,62,47,54,36,38,40,26,29,52,51,60,63,58,55,12,13,6,7,8,9,18,19,16,17,4,5,10,11,0,1,34,35,2,3,14,15,24,25,20,21,22,23,44,45,32,33,42,43,30,31,37,39,41,27,28,48,53,56,61,46,59},
   {51,57,61,63,59,47,55,8,9,12,13,6,7,18,19,16,17,4,5,10,11,0,1,34,35,14,15,24,25,2,3,20,21,22,23,44,45,42,43,36,37,32,33,38,39,40,41,30,31,28,29,26,27,48,49,52,53,50,56,60,62,58,46,54},
   {31,26,49,50,57,62,59,54,45,43,37,33,39,41,28,27,52,51,60,58,47,55,8,9,12,13,6,7,18,19,16,17,4,5,10,11,0,1,34,35,14,15,24,25,2,3,20,21,22,23,44,42,36,32,38,40,30,29,48,53,56,61,63,46},
   {50,57,62,59,54,39,41,31,29,27,49,53,56,61,58,47,55,8,9,12,13,6,7,18,19,16,17,4,5,10,11,0,1,34,35,14,15,24,25,2,3,20,21,22,23,44,45,42,43,36,37,32,33,38,40,30,28,26,48,52,51,60,63,46},
   {59,54,27,49,53,51,57,61,63,46,55,6,7,8,9,18,19,12,13,16,17,4,5,10,11,0,1,34,35,14,15,2,3,24,25,20,21,22,23,44,45,42,43,36,37,32,33,38,39,30,31,28,29,40,41,26,48,52,50,56,60,62,58,47},
   {61,63,59,47,55,6,7,8,9,18,19,12,13,16,17,4,5,10,11,0,1,34,35,14,15,2,3,24,25,20,21,22,23,44,45,42,43,36,37,32,33,38,39,30,31,28,29,40,41,26,27,48,49,52,53,50,51,56,57,60,62,58,46,54},
   {52,51,60,63,46,54,30,28,40,26,48,53,56,61,58,47,55,6,7,8,9,18,19,12,13,16,17,4,5,10,11,0,1,34,35,14,15,2,3,24,25,20,21,22,23,44,45,42,43,36,37,32,33,38,39,31,29,41,27,49,50,57,62,59},
   {54,38,40,30,28,26,48,52,56,60,50,58,62,46,55,12,13,6,7,8,9,18,19,16,17,4,5,10,11,0,1,34,35,2,3,14,15,24,25,20,21,22,23,44,45,42,43,36,37,32,33,39,41,31,29,27,49,53,57,61,51,59,63,47},
   {49,56,61,58,63,54,37,33,39,41,31,29,27,52,57,50,59,46,55,12,13,6,7,8,9,18,19,16,17,4,5,10,11,0,1,34,35,2,3,14,15,24,25,20,21,22,23,44,45,42,43,36,32,38,40,30,28,26,48,53,60,51,62,47},
   {53,57,61,51,59,63,47,55,12,13,6,7,8,9,18,19,16,17,4,5,10,11,0,1,34,35,2,3,14,15,24,25,20,21,22,23,44,45,42,43,36,37,32,33,38,39,40,41,30,31,28,29,26,27,48,49,52,56,60,50,58,62,46,54}},
  {{7,7,7,7,7,7,7,7},{11,11,10,9,9,10,9,9},{5,4,5,5,5,5,5,5},{0,0,2,0,1,0,0,0},
   {3,1,1,3,2,1,1,1},{6,6,6,6,6,6,6,6},{1,3,0,1,0,2,3,2},{10,10,9,10,10,9,10,10},
   {4,5,3,2,4,4,4,4},{2,2,4,4,3,3,2,3},{12,12,12,12,12,1,1,1},{14,14,13,3,2,0,4,4},
   {9,8,11,11,11,11,11,11},{8,9,11,11,11,0,4,4},{7,4,2,12,2,2,11,11},{2,7,6,8,8,8,8,8},
   {4,5,4,7,3,7,7,7},{8,9,8,8,8,8,8,8},{3,1,3,5,7,3,6,6},{5,2,7,6,6,6,0,0},
   {6,6,8,0,1,11,3,10},{15,15,5,4,5,5,5,5},{13,13,1,2,4,4,2,3},{4,5,3,11,2,2,11,4},
   {0,0,10,9,12,1,1,1},{14,14,13,2,4,4,2,3},{1,8,12,3,9,10,9,9},{7,4,11,9,12,1,1,9},
   {10,11,1,4,5,5,5,6},{15,13,6,8,8,8,8,8},{11,12,5,5,7,3,0,0},{13,15,2,12,11,0,4,1}},
  {{255,255,255,255,255,255,255,255},{255,255,255,255,255,255,255,255},{255,255,255,255,255,255,255,255},{255,255,255,255,255,255,255,255},
   {255,255,255,255,255,255,255,255},{255,255,255,255,255,255,255,255},{255,255,255,255,255,255,255,255},{255,255,255,255,255,255,255,255},
   {255,255,255,255,255,255,255,255},{255,255,255,255,255,255,255,255},{255,255,255,255,255,4,4,4},{255,255,255,4,4,3,8,8},
   {255,255,255,255,255,255,255,255},{17,17,12,12,12,11,11,11},{0,2,3,10,11,6,12,12},{9,0,5,17,17,17,17,17},
   {8,8,9,0,9,0,0,0},{255,255,255,255,255,255,255,255},{4,4,8,2,0,9,5,5},{2,9,0,5,5,5,3,3},
   {5,5,17,3,3,12,6,7},{255,255,2,9,2,2,2,2},{255,255,4,8,8,8,9,9},{16,16,18,13,14,14,14,13},
   {3,3,1,1,10,10,10,10},{11,11,11,22,22,22,22,22},{6,12,10,11,1,1,1,1},{14,14,13,24,24,24,24,26},
   {7,1,22,21,21,21,21,18},{21,22,15,15,15,15,15,15},{1,10,21,18,18,18,19,19},{22,21,14,14,13,13,13,24}},
  {112,113,114,115,116,117,118,119,6,121,122,36,124,125,126,127,128,129,130,131,132,133,134,135,136,137,138,139,140,141,142,143,144,145,146,147,148,149,150,151,152,153,154,155,156,157,158,159,160,161,162,163,164,165,166,167,168,41,170,391,172,647,174,175,176,177,178,179,180,181,182,183,184,185,186,187,188,189,190,191,43,2,0,74,75,8,198,199,635,201,39,76,77,37,4,5,7,209,1,38,212,213,214,215,216,18,393,219,220,221,222,223,22,50,48,227,228,229,230,231,11,233,649,86,236,87,52,53,81,241,370,16,244,17,246,9,248,3,250,251,252,253,254,255,82,80,78,259,47,14,10,263,44,51,626,88,89,84,15,12,272,273,49,275,276,277,85,83,280,372,79,45,46,285,628,379,13,42,40,291,292,293,73,72,296,28,59,35,300,34,302,303,304,305,454,307,308,309,310,311,92,61,445,54,58,55,20,21,320,321,710,56,57,25,326,327,32,29,707,66,65,63,30,31,23,19,701,97,98,95,26,24,33,698,27,347,64,349,96,93,94,62,60,452,451,708,90,91,360,415,442,363,364,365,671,367},
  {511,511,511,511,511,511,511,511,256,511,511,256,511,511,511,511,511,511,511,511,511,511,511,511,511,511,511,511,511,511,511,511,511,511,511,511,511,511,511,511,511,511,511,511,511,511,511,511,511,511,511,511,511,511,511,511,511,256,511,55,511,55,511,511,511,511,511,511,511,511,511,511,511,511,511,511,511,511,511,511,256,256,256,256,256,256,511,511,51,511,256,256,256,256,256,256,256,511,256,256,511,511,511,511,511,258,49,511,511,511,511,511,258,257,257,511,511,511,511,511,257,511,49,257,511,257,257,257,257,511,50,257,511,257,511,257,511,256,511,511,511,511,511,511,257,256,256,511,257,257,257,511,256,257,50,257,257,257,257,257,511,511,257,511,511,511,257,257,511,52,256,257,257,511,52,51,257,256,256,511,511,511,256,256,511,259,258,259,511,259,511,511,511,511,62,511,511,511,511,511,258,258,61,258,258,258,258,258,511,511,62,258,258,258,511,511,259,259,59,259,259,259,259,259,258,258,61,258,258,258,258,258,259,58,259,511,259,511,258,258,258,258,258,60,59,60,258,258,511,175,58,511,511,511,175,511}};

typedef CUresult (*EncodeFn)(CUtensorMap*, CUtensorMapDataType, cuuint32_t, void*, const cuuint64_t*, const cuuint64_t*, const cuuint32_t*,
                             const cuuint32_t*, CUtensorMapInterleave, CUtensorMapSwizzle, CUtensorMapL2promotion, CUtensorMapFloatOOBfill);

void make_map2(EncodeFn enc, CUtensorMap* m, const void* ptr, int rows, int cols, int box_rows) {
  cuuint64_t dim[2] = {(cuuint64_t)cols, (cuuint64_t)rows}, str[1] = {(cuuint64_t)cols * 2};
  cuuint32_t box[2] = {64, (cuuint32_t)box_rows}, es[2] = {1, 1};
  enc(m, CU_TENSOR_MAP_DATA_TYPE_BFLOAT16, 2, const_cast<void*>(ptr), dim, str, box, es, CU_TENSOR_MAP_INTERLEAVE_NONE, CU_TENSOR_MAP_SWIZZLE_128B,
      CU_TENSOR_MAP_L2_PROMOTION_L2_128B, CU_TENSOR_MAP_FLOAT_OOB_FILL_NONE);
}
void make_map3(EncodeFn enc, CUtensorMap* m, const void* ptr, int rows) {
  cuuint64_t dim[3] = {64, (cuuint64_t)rows, 9}, str[2] = {DM * 2, 128};
  cuuint32_t box[3] = {64, 32, 3}, es[3] = {1, 1, 1};
  enc(m, CU_TENSOR_MAP_DATA_TYPE_BFLOAT16, 3, const_cast<void*>(ptr), dim, str, box, es, CU_TENSOR_MAP_INTERLEAVE_NONE, CU_TENSOR_MAP_SWIZZLE_128B,
      CU_TENSOR_MAP_L2_PROMOTION_L2_128B, CU_TENSOR_MAP_FLOAT_OOB_FILL_NONE);
}

void make_map_t(EncodeFn enc, CUtensorMap* m, void* ptr, int width, int cols) {
  cuuint64_t dim[3] = {SEQ / 2, 2, 864}, str[2] = {SEQ * 2, SEQ * 4};
  cuuint32_t box[3] = {(cuuint32_t)width, 2, (cuuint32_t)cols}, es[3] = {1, 1, 1};
  enc(m, CU_TENSOR_MAP_DATA_TYPE_UINT32, 3, ptr, dim, str, box, es, CU_TENSOR_MAP_INTERLEAVE_NONE, cols == 64 ? CU_TENSOR_MAP_SWIZZLE_128B : CU_TENSOR_MAP_SWIZZLE_NONE,
      CU_TENSOR_MAP_L2_PROMOTION_NONE, CU_TENSOR_MAP_FLOAT_OOB_FILL_NONE);
}

int g_mode = -1;

}

extern "C" void kernel_launch(void* const* d_in, const int* in_sizes, int n_in, void* d_out, int out_size) {
  static EncodeFn enc = nullptr;
  static void* t_ptr = nullptr;
  if (!enc) {
    void* fn = nullptr;
    cudaDriverEntryPointQueryResult st;
    cudaGetDriverEntryPoint("cuTensorMapEncodeTiled", &fn, cudaEnableDefault, &st);
    enc = (EncodeFn)fn;
    cudaGetSymbolAddress(&t_ptr, g_S);
    cudaFuncSetAttribute(fused_kernel, cudaFuncAttributeMaxDynamicSharedMemorySize, SMEM_BYTES);
    if (g_mode < 0) {
      cudaLaunchConfig_t cfg = {};
      cfg.gridDim = dim3(2 * NCL); cfg.blockDim = dim3(384); cfg.dynamicSmemBytes = SMEM_BYTES;
      cudaLaunchAttribute at; at.id = cudaLaunchAttributeClusterDimension;
      at.val.clusterDim.x = 2; at.val.clusterDim.y = 1; at.val.clusterDim.z = 1;
      cfg.attrs = &at; cfg.numAttrs = 1;
      int nc = 0;
      g_mode = (cudaOccupancyMaxActiveClusters(&nc, fused_kernel, &cfg) == cudaSuccess && nc >= NCL) ? 1 : 0;
      (void)cudaGetLastError();
    }
  }
  Params p;
  make_map2(enc, &p.map_a[0], d_in[4], SEQ, DC, 128);
  make_map2(enc, &p.map_a[1], d_in[0], SEQ, DM, 128);
  make_map2(enc, &p.map_w[0], d_in[6], DC, 4096, 64);
  make_map2(enc, &p.map_w[1], d_in[7], DC, 4096, 64);
  make_map2(enc, &p.map_w[2], d_in[5], DM, 4096, 64);
  make_map2(enc, &p.map_w[3], d_in[1], DM, 1728, 64);
  make_map3(enc, &p.map_o[0], d_in[8], 4096);
  make_map3(enc, &p.map_o[1], d_in[2], DM);
  make_map_t(enc, &p.map_t[0], t_ptr, 32, 9);
  make_map_t(enc, &p.map_t[1], t_ptr, 40, 9);
  make_map_t(enc, &p.map_t[2], t_ptr, 32, 64);
  p.x = (const __nv_bfloat16*)d_in[0];
  p.gate_w = (const __nv_bfloat16*)d_in[9];
  make_map2(enc, &p.map_out, d_out, SEQ, DM, 64);
  p.out = (__nv_bfloat16*)d_out;
  p.zero = 0;
  auto launch = [&](int phases) {
    p.s = k_sched;
    for (int i = 0; i < NCL; i++) {
      Rec& r = p.s.r[i];
      if (!(phases & 1)) r.n1 = 0;
      if (!(phases & 2)) r.n2 = 0;
      if (!(phases & (p.s.task[i][1] == 64 ? 4 : 32))) r.p3 = 255;
      if (!(phases & 8)) r.bg = 255;
      const int u1 = r.n1 ? 8 + r.n1 * (8 + (r.slab >> 3)) : 0;
      int u2 = 0;
      for (int k = 0; k < r.n2; k++) u2 += 4 * (r.item[k] & 7) + 4;
      r.u1 = (uint8_t)u1; r.u2 = (uint8_t)u2;
      r.rot = (uint8_t)(((u1 % 10 + 1) >> 1) % 5);
      r.x3 = (uint8_t)((r.rot + u2) % 5 & 3);
      r.phases = (uint8_t)phases;
    }
    if (!(phases & 16))
      for (int i = 0; i < 256; i++) { p.s.slot[i >> 3][i & 7] = (uint8_t)(i >> 3); p.s.prev[i >> 3][i & 7] = 255; p.s.qblk[i] = (uint16_t)(S_Q + i); p.s.qdep[i] = 511; }
    fused_kernel<<<2 * NCL, 384, SMEM_BYTES>>>(p);
  };
  if (g_mode == 1) launch(63);
  else { launch(1); launch(10); launch(4); launch(32); }
}
```

```cpp
#include <cuda_runtime.h>
#include <cuda_bf16.h>
#include <cuda.h>
#include <stdint.h>

namespace {

constexpr int SEQ = 2048, DM = 576, DC = 512, NH = 32;
constexpr int NCL = 66;
constexpr uint32_t DESC_HI = 0x40000040u;

constexpr int SM_RING = 0;
constexpr int SM_BUF = 163840;
constexpr int SM_BAR = 229376;
constexpr int B_P1E = 0, B_P2E = 10, B_P3E = 15, B_P2F = 24, B_SF = 32, B_ORD = 36, B_LAD = 40, B_DONE = 41, B_FIN = 48;
constexpr int B_P3F = 56, B_OUT = 61, B_ZF = 62, B_P1F = 64, B_SE = 74, B_QF = 80, B_LA = 84, B_NUM = 88;
constexpr uint64_t B_CNT = 0x11118245000ull;
constexpr int SMEM_BYTES = SM_BAR + B_NUM * 8 + 1024;

constexpr int F_QKVA = 32;
constexpr int F_GATE = 64;
constexpr int F_TS = 68;
constexpr int F_DONE = 65;
constexpr int F_CTX = 96;
constexpr int F_OUT = 96 + 8 * 64;
constexpr int F_KV = F_OUT + 64;
constexpr int F_Q = F_KV + 256;
constexpr int F_RD = F_Q + 256;
constexpr int F_NUM = F_RD + 256;

struct Rec {
  uint8_t slab;
  uint8_t n1, n2;
  uint8_t p3;
  uint8_t bg;
  uint8_t item[11];
  uint8_t last[11];
  uint8_t tile[32];
  uint8_t u1, u2;
  uint8_t rot, x3;
  uint8_t phases;
};
struct Sched {
  Rec r[NCL];
  uint8_t task[NCL][4];
  uint8_t p3_order[24][64];
  uint8_t slot[32][8];
  uint8_t prev[32][8];
  uint16_t qblk[256];
  uint16_t qdep[256];
};


struct Params {
  CUtensorMap map_a[2];
  CUtensorMap map_w[4];
  CUtensorMap map_o[2];
  CUtensorMap map_t[3];
  CUtensorMap map_out;
  const __nv_bfloat16* x;
  const __nv_bfloat16* gate_w;
  __nv_bfloat16* out;
  int zero;
  alignas(64) Sched s;
};

constexpr int S_Q = 112, S_K = S_Q + 256, S_V = S_K + 256, S_NUM = S_V + 256;
__device__ __align__(1024) uint8_t g_S[(size_t)S_NUM * 65536];
__device__ __align__(1024) uint8_t g_oA[32 * 576 * 128];
__device__ float g_gate[SEQ];
__device__ int g_flags[F_NUM];

__device__ __forceinline__ void mbar_arrive(uint32_t b) { asm volatile("mbarrier.arrive.shared::cta.b64 _, [%0];" ::"r"(b) : "memory"); }
__device__ __forceinline__ void mbar_arrive_cl(uint32_t b, int cnt) {
  asm volatile("mbarrier.arrive.shared::cluster.b64 _, [%0], %1;" ::"r"(b), "r"(cnt) : "memory");
}
__device__ __forceinline__ void mbar_wait(uint32_t b, int par) {
  asm volatile(
      "{\n.reg .pred p;\n.reg .u32 c;\n"
      "mbarrier.try_wait.parity.shared::cta.b64 p, [%0], %1;\n@p bra DN;\nmov.u32 c, 0;\n"
      "LP:\nmbarrier.try_wait.parity.shared::cta.b64 p, [%0], %1;\n@p bra DN;\n"
      "add.u32 c, c, 1;\nsetp.lt.u32 p, c, 4000000;\n@p bra LP;\ntrap;\nDN:\n}" ::"r"(b), "r"(par) : "memory");
}
__device__ __forceinline__ bool mbar_test(uint32_t b, int par) {
  uint32_t ok;
  asm volatile("{\n.reg .pred p;\nmbarrier.test_wait.parity.shared::cta.b64 p, [%1], %2;\nselp.u32 %0, 1, 0, p;\n}" : "=r"(ok) : "r"(b), "r"(par) : "memory");
  return __all_sync(0xffffffffu, ok);
}
__device__ __forceinline__ uint32_t mapa(uint32_t a, uint32_t cta) {
  uint32_t r; asm("mapa.shared::cluster.u32 %0, %1, %2;" : "=r"(r) : "r"(a), "r"(cta)); return r;
}
#define ELECT(ins) "{\n.reg .pred e;\nelect.sync _|e, 0xffffffff;\n@e " ins "\n}"
__device__ __forceinline__ void mbar_expect(uint32_t b, int bytes) {
  asm volatile(ELECT("mbarrier.arrive.expect_tx.shared::cta.b64 _, [%0], %1;") ::"r"(b), "r"(bytes) : "memory");
}
__device__ __forceinline__ void mbar_arrive_one(uint32_t b) { asm volatile(ELECT("mbarrier.arrive.shared::cta.b64 _, [%0];") ::"r"(b) : "memory"); }
constexpr uint64_t L2_NORMAL = 0x1000000000000000ull, L2_FIRST = 0x12F0000000000000ull;
__device__ __forceinline__ void bulk_load(uint32_t dst, const void* src, int bytes, uint32_t bar, uint64_t pol = L2_NORMAL) {
  asm volatile(ELECT("cp.async.bulk.shared::cluster.global.mbarrier::complete_tx::bytes.L2::cache_hint [%0], [%1], %2, [%3], %4;") ::"r"(dst), "l"(src), "r"(bytes), "r"(bar), "l"(pol) : "memory");
}
__device__ __forceinline__ void bulk_load_mc(uint32_t dst, const void* src, int bytes, uint32_t bar, uint64_t pol = L2_NORMAL) {
  asm volatile(ELECT("cp.async.bulk.shared::cluster.global.mbarrier::complete_tx::bytes.multicast::cluster.L2::cache_hint [%0], [%1], %2, [%3], %4, %5;") ::"r"(dst), "l"(src), "r"(bytes), "r"(bar), "h"((uint16_t)3), "l"(pol) : "memory");
}
__device__ __forceinline__ void bulk_store(void* dst, uint32_t src, int bytes, uint64_t pol = L2_NORMAL) {
  asm volatile(ELECT("cp.async.bulk.global.shared::cta.bulk_group.L2::cache_hint [%0], [%1], %2, %3;") ::"l"(dst), "r"(src), "r"(bytes), "l"(pol) : "memory");
}
__device__ __forceinline__ void tma2d(uint32_t dst, const CUtensorMap* m, int c0, int c1, uint32_t bar, uint64_t pol = L2_NORMAL) {
  asm volatile(ELECT("cp.async.bulk.tensor.2d.shared::cluster.global.mbarrier::complete_tx::bytes.L2::cache_hint [%0], [%1, {%3, %4}], [%2], %5;") ::"r"(dst), "l"(m), "r"(bar), "r"(c0), "r"(c1), "l"(pol) : "memory");
}
__device__ __forceinline__ void tma2d_mc(uint32_t dst, const CUtensorMap* m, int c0, int c1, uint32_t bar, uint64_t pol = L2_NORMAL) {
  asm volatile(ELECT("cp.async.bulk.tensor.2d.shared::cluster.global.mbarrier::complete_tx::bytes.multicast::cluster.L2::cache_hint [%0], [%1, {%3, %4}], [%2], %5, %6;") ::"r"(dst), "l"(m), "r"(bar), "r"(c0), "r"(c1), "h"((uint16_t)3), "l"(pol) : "memory");
}
__device__ __forceinline__ void tma3d(uint32_t dst, const CUtensorMap* m, int c0, int c1, int c2, uint32_t bar, uint64_t pol = L2_NORMAL) {
  asm volatile(ELECT("cp.async.bulk.tensor.3d.shared::cluster.global.mbarrier::complete_tx::bytes.L2::cache_hint [%0], [%1, {%3, %4, %5}], [%2], %6;") ::"r"(dst), "l"(m), "r"(bar), "r"(c0), "r"(c1), "r"(c2), "l"(pol) : "memory");
}
__device__ __forceinline__ void tma3d_mc(uint32_t dst, const CUtensorMap* m, int c0, int c1, int c2, uint32_t bar, uint64_t pol = L2_NORMAL) {
  asm volatile(ELECT("cp.async.bulk.tensor.3d.shared::cluster.global.mbarrier::complete_tx::bytes.multicast::cluster.L2::cache_hint [%0], [%1, {%3, %4, %5}], [%2], %6, %7;") ::"r"(dst), "l"(m), "r"(bar), "r"(c0), "r"(c1), "r"(c2), "h"((uint16_t)3), "l"(pol) : "memory");
}
__device__ __forceinline__ void tma2d_add(const CUtensorMap* m, uint32_t src, int c0, int c1) {
  asm volatile(ELECT("cp.reduce.async.bulk.tensor.2d.global.shared::cta.add.bulk_group [%0, {%2, %3}], [%1];") ::"l"(m), "r"(src), "r"(c0), "r"(c1) : "memory");
}
__device__ __forceinline__ void tma3d_store(const CUtensorMap* m, uint32_t src, int c0, int c1, int c2, uint64_t pol = L2_NORMAL) {
  asm volatile(ELECT("cp.async.bulk.tensor.3d.global.shared::cta.bulk_group.L2::cache_hint [%0, {%2, %3, %4}], [%1], %5;") ::"l"(m), "r"(src), "r"(c0), "r"(c1), "r"(c2), "l"(pol) : "memory");
}
__device__ __forceinline__ void tma2d_prefetch(const CUtensorMap* m, int c0, int c1, uint64_t pol = L2_NORMAL) {
  asm volatile(ELECT("cp.async.bulk.prefetch.tensor.2d.L2.global.L2::cache_hint [%0, {%1, %2}], %3;") ::"l"(m), "r"(c0), "r"(c1), "l"(pol) : "memory");
}
#define LAG 3
#define HINT 63
#define POL(bit) ((HINT >> (bit)) & 1 ? L2_FIRST : L2_NORMAL)
#define BULK_COMMIT() asm volatile("cp.async.bulk.commit_group;" ::: "memory")
#define BULK_WAIT(n) asm volatile("cp.async.bulk.wait_group %0;" ::"n"(n) : "memory")
#define BULK_WAIT_READ(n) asm volatile("cp.async.bulk.wait_group.read %0;" ::"n"(n) : "memory")
#define FENCE_ASYNC_SMEM() asm volatile("fence.proxy.async.shared::cta;" ::: "memory")
#define WG_FENCE() asm volatile("wgmma.fence.sync.aligned;" ::: "memory")
#define WG_COMMIT() asm volatile("wgmma.commit_group.sync.aligned;" ::: "memory")
#define WG_WAIT(n) asm volatile("wgmma.wait_group.sync.aligned %0;" ::"n"(n) : "memory")
__device__ __forceinline__ void bar_sync(int id, int n) { asm volatile("bar.sync %0, %1;" ::"r"(id), "r"(n) : "memory"); }
__device__ __forceinline__ void bar_arrive(int id, int n) { asm volatile("bar.arrive %0, %1;" ::"r"(id), "r"(n) : "memory"); }
__device__ __forceinline__ void cluster_sync() {
  asm volatile("barrier.cluster.arrive.relaxed;\nbarrier.cluster.wait.acquire;" ::: "memory");
}
template <int N> __device__ __forceinline__ void pin(float (&r)[N]) {
#pragma unroll
  for (int i = 0; i < N; i++) asm volatile("" : "+f"(r[i])::"memory");
}
template <int N> __device__ __forceinline__ void pin(uint32_t (&r)[N]) {
#pragma unroll
  for (int i = 0; i < N; i++) asm volatile("" : "+r"(r[i])::"memory");
}
__device__ __forceinline__ uint32_t pack_bf16(float lo, float hi) {
  uint32_t r; asm("cvt.rn.bf16x2.f32 %0, %1, %2;" : "=r"(r) : "f"(hi), "f"(lo)); return r;
}
__device__ __forceinline__ float ex2(float x) { float r; asm("ex2.approx.ftz.f32 %0, %1;" : "=f"(r) : "f"(x)); return r; }
__device__ __forceinline__ void ldsm4(uint32_t a, uint32_t& r0, uint32_t& r1, uint32_t& r2, uint32_t& r3) {
  asm volatile("ldmatrix.sync.aligned.m8n8.x4.shared.b16 {%0,%1,%2,%3}, [%4];" : "=r"(r0), "=r"(r1), "=r"(r2), "=r"(r3) : "r"(a) : "memory");
}
__device__ __forceinline__ void stsm4(uint32_t a, uint32_t r0, uint32_t r1, uint32_t r2, uint32_t r3) {
  asm volatile("stmatrix.sync.aligned.m8n8.x4.shared.b16 [%0], {%1,%2,%3,%4};" ::"r"(a), "r"(r0), "r"(r1), "r"(r2), "r"(r3) : "memory");
}
__device__ __forceinline__ void flag_add(int idx, int v = 1) {
  asm volatile(ELECT("red.release.gpu.global.add.s32 [%0], %1;") ::"l"(g_flags + idx), "r"(v) : "memory");
}
__device__ __forceinline__ void flag_add_rx(int idx, int v = 1) {
  asm volatile(ELECT("red.relaxed.gpu.global.add.s32 [%0], %1;") ::"l"(g_flags + idx), "r"(v) : "memory");
}
template <bool ACQ, int NS = 32> __device__ __forceinline__ void flag_wait(int idx, int target) {
  int n = 0;
  while (true) {
    int v;
    if (ACQ) asm volatile("ld.acquire.gpu.global.s32 %0, [%1];" : "=r"(v) : "l"(g_flags + idx) : "memory");
    else asm volatile("ld.relaxed.gpu.global.s32 %0, [%1];" : "=r"(v) : "l"(g_flags + idx) : "memory");
    if (__all_sync(0xffffffffu, v >= target)) break;
    if (++n > 20000000) __trap();
    __nanosleep(NS);
  }
}
__device__ __forceinline__ int flag_peek(int idx) {
  int v;
  asm volatile("ld.relaxed.gpu.global.s32 %0, [%1];" : "=r"(v) : "l"(g_flags + idx) : "memory");
  return v;
}
__device__ __forceinline__ void mask_wait(uint32_t& ready, int bit, int idx, int target) {
  for (int n = 0; !((ready >> bit) & 1); n++) {
    int v;
    if (n) { __nanosleep(32); if (n > 20000000) __trap(); }
    asm volatile("ld.relaxed.gpu.global.s32 %0, [%1];" : "=r"(v) : "l"(g_flags + idx) : "memory");
    ready = __ballot_sync(0xffffffffu, v >= target);
  }
}
__device__ __forceinline__ uint32_t desc_lo(uint32_t addr, uint32_t lbo) { return ((addr & 0x3FFFFu) >> 4) | ((lbo >> 4) << 16); }

template <int TB, int TA = 0> __device__ __forceinline__ void wgmma_ss64(float (&d)[32], uint32_t alo, uint32_t blo, int sd) {
  asm volatile("{\n.reg .pred p;\n.reg .b64 da, db;\n"
    "setp.ne.b32 p, %34, 0;\nmov.b64 da, {%32, %36};\nmov.b64 db, {%33, %36};\n"
    "wgmma.mma_async.sync.aligned.m64n64k16.f32.bf16.bf16 "
    "{%0,%1,%2,%3,%4,%5,%6,%7,%8,%9,%10,%11,%12,%13,%14,%15,%16,%17,%18,%19,%20,%21,%22,%23,"
    "%24,%25,%26,%27,%28,%29,%30,%31}, "
    "da, db, p, 1, 1, %37, %35;\n}\n"
    : "+f"(d[0]),"+f"(d[1]),"+f"(d[2]),"+f"(d[3]),"+f"(d[4]),"+f"(d[5]),"+f"(d[6]),"+f"(d[7]),"+f"(d[8]),"+f"(d[9]),"+f"(d[10]),"+f"(d[11]),
      "+f"(d[12]),"+f"(d[13]),"+f"(d[14]),"+f"(d[15]),"+f"(d[16]),"+f"(d[17]),"+f"(d[18]),"+f"(d[19]),"+f"(d[20]),"+f"(d[21]),"+f"(d[22]),"+f"(d[23]),
      "+f"(d[24]),"+f"(d[25]),"+f"(d[26]),"+f"(d[27]),"+f"(d[28]),"+f"(d[29]),"+f"(d[30]),"+f"(d[31])
    : "r"(alo), "r"(blo), "r"(sd), "n"(TB), "r"(DESC_HI), "n"(TA));
}
template <int TB, int TA = 0> __device__ __forceinline__ void wgmma_ss128(float (&d)[64], uint32_t alo, uint32_t blo, int sd) {
  asm volatile("{\n.reg .pred p;\n.reg .b64 da, db;\n"
    "setp.ne.b32 p, %66, 0;\nmov.b64 da, {%64, %68};\nmov.b64 db, {%65, %68};\n"
    "wgmma.mma_async.sync.aligned.m64n128k16.f32.bf16.bf16 "
    "{%0,%1,%2,%3,%4,%5,%6,%7,%8,%9,%10,%11,%12,%13,%14,%15,%16,%17,%18,%19,%20,%21,%22,%23,"
    "%24,%25,%26,%27,%28,%29,%30,%31,%32,%33,%34,%35,%36,%37,%38,%39,%40,%41,%42,%43,%44,%45,%46,%47,"
    "%48,%49,%50,%51,%52,%53,%54,%55,%56,%57,%58,%59,%60,%61,%62,%63}, "
    "da, db, p, 1, 1, %69, %67;\n}\n"
    : "+f"(d[0]),"+f"(d[1]),"+f"(d[2]),"+f"(d[3]),"+f"(d[4]),"+f"(d[5]),"+f"(d[6]),"+f"(d[7]),"+f"(d[8]),"+f"(d[9]),"+f"(d[10]),"+f"(d[11]),
      "+f"(d[12]),"+f"(d[13]),"+f"(d[14]),"+f"(d[15]),"+f"(d[16]),"+f"(d[17]),"+f"(d[18]),"+f"(d[19]),"+f"(d[20]),"+f"(d[21]),"+f"(d[22]),"+f"(d[23]),
      "+f"(d[24]),"+f"(d[25]),"+f"(d[26]),"+f"(d[27]),"+f"(d[28]),"+f"(d[29]),"+f"(d[30]),"+f"(d[31]),"+f"(d[32]),"+f"(d[33]),"+f"(d[34]),"+f"(d[35]),
      "+f"(d[36]),"+f"(d[37]),"+f"(d[38]),"+f"(d[39]),"+f"(d[40]),"+f"(d[41]),"+f"(d[42]),"+f"(d[43]),"+f"(d[44]),"+f"(d[45]),"+f"(d[46]),"+f"(d[47]),
      "+f"(d[48]),"+f"(d[49]),"+f"(d[50]),"+f"(d[51]),"+f"(d[52]),"+f"(d[53]),"+f"(d[54]),"+f"(d[55]),"+f"(d[56]),"+f"(d[57]),"+f"(d[58]),"+f"(d[59]),
      "+f"(d[60]),"+f"(d[61]),"+f"(d[62]),"+f"(d[63])
    : "r"(alo), "r"(blo), "r"(sd), "n"(TB), "r"(DESC_HI), "n"(TA));
}
template <int TB> __device__ __forceinline__ void wgmma_rs128(float (&d)[64], uint32_t a0, uint32_t a1, uint32_t a2, uint32_t a3, uint32_t blo, int sd) {
  asm volatile("{\n.reg .pred p;\n.reg .b64 db;\n"
    "setp.ne.b32 p, %69, 0;\nmov.b64 db, {%68, %71};\n"
    "wgmma.mma_async.sync.aligned.m64n128k16.f32.bf16.bf16 "
    "{%0,%1,%2,%3,%4,%5,%6,%7,%8,%9,%10,%11,%12,%13,%14,%15,%16,%17,%18,%19,%20,%21,%22,%23,"
    "%24,%25,%26,%27,%28,%29,%30,%31,%32,%33,%34,%35,%36,%37,%38,%39,%40,%41,%42,%43,%44,%45,%46,%47,"
    "%48,%49,%50,%51,%52,%53,%54,%55,%56,%57,%58,%59,%60,%61,%62,%63}, "
    "{%64,%65,%66,%67}, db, p, 1, 1, %70;\n}\n"
    : "+f"(d[0]),"+f"(d[1]),"+f"(d[2]),"+f"(d[3]),"+f"(d[4]),"+f"(d[5]),"+f"(d[6]),"+f"(d[7]),"+f"(d[8]),"+f"(d[9]),"+f"(d[10]),"+f"(d[11]),
      "+f"(d[12]),"+f"(d[13]),"+f"(d[14]),"+f"(d[15]),"+f"(d[16]),"+f"(d[17]),"+f"(d[18]),"+f"(d[19]),"+f"(d[20]),"+f"(d[21]),"+f"(d[22]),"+f"(d[23]),
      "+f"(d[24]),"+f"(d[25]),"+f"(d[26]),"+f"(d[27]),"+f"(d[28]),"+f"(d[29]),"+f"(d[30]),"+f"(d[31]),"+f"(d[32]),"+f"(d[33]),"+f"(d[34]),"+f"(d[35]),
      "+f"(d[36]),"+f"(d[37]),"+f"(d[38]),"+f"(d[39]),"+f"(d[40]),"+f"(d[41]),"+f"(d[42]),"+f"(d[43]),"+f"(d[44]),"+f"(d[45]),"+f"(d[46]),"+f"(d[47]),
      "+f"(d[48]),"+f"(d[49]),"+f"(d[50]),"+f"(d[51]),"+f"(d[52]),"+f"(d[53]),"+f"(d[54]),"+f"(d[55]),"+f"(d[56]),"+f"(d[57]),"+f"(d[58]),"+f"(d[59]),
      "+f"(d[60]),"+f"(d[61]),"+f"(d[62]),"+f"(d[63])
    : "r"(a0), "r"(a1), "r"(a2), "r"(a3), "r"(blo), "r"(sd), "n"(TB), "r"(DESC_HI));
}
template <int TB, int TA = 0> __device__ __forceinline__ void wgmma_ss192(float (&d)[96], uint32_t alo, uint32_t blo, int sd) {
  asm volatile("{\n.reg .pred p;\n.reg .b64 da, db;\n"
    "setp.ne.b32 p, %98, 0;\nmov.b64 da, {%96, %100};\nmov.b64 db, {%97, %100};\n"
    "wgmma.mma_async.sync.aligned.m64n192k16.f32.bf16.bf16 "
    "{%0,%1,%2,%3,%4,%5,%6,%7,%8,%9,%10,%11,%12,%13,%14,%15,%16,%17,%18,%19,%20,%21,%22,%23,"
    "%24,%25,%26,%27,%28,%29,%30,%31,%32,%33,%34,%35,%36,%37,%38,%39,%40,%41,%42,%43,%44,%45,%46,%47,"
    "%48,%49,%50,%51,%52,%53,%54,%55,%56,%57,%58,%59,%60,%61,%62,%63,%64,%65,%66,%67,%68,%69,%70,%71,"
    "%72,%73,%74,%75,%76,%77,%78,%79,%80,%81,%82,%83,%84,%85,%86,%87,%88,%89,%90,%91,%92,%93,%94,%95}, "
    "da, db, p, 1, 1, %101, %99;\n}\n"
    : "+f"(d[0]),"+f"(d[1]),"+f"(d[2]),"+f"(d[3]),"+f"(d[4]),"+f"(d[5]),"+f"(d[6]),"+f"(d[7]),"+f"(d[8]),"+f"(d[9]),"+f"(d[10]),"+f"(d[11]),
      "+f"(d[12]),"+f"(d[13]),"+f"(d[14]),"+f"(d[15]),"+f"(d[16]),"+f"(d[17]),"+f"(d[18]),"+f"(d[19]),"+f"(d[20]),"+f"(d[21]),"+f"(d[22]),"+f"(d[23]),
      "+f"(d[24]),"+f"(d[25]),"+f"(d[26]),"+f"(d[27]),"+f"(d[28]),"+f"(d[29]),"+f"(d[30]),"+f"(d[31]),"+f"(d[32]),"+f"(d[33]),"+f"(d[34]),"+f"(d[35]),
      "+f"(d[36]),"+f"(d[37]),"+f"(d[38]),"+f"(d[39]),"+f"(d[40]),"+f"(d[41]),"+f"(d[42]),"+f"(d[43]),"+f"(d[44]),"+f"(d[45]),"+f"(d[46]),"+f"(d[47]),
      "+f"(d[48]),"+f"(d[49]),"+f"(d[50]),"+f"(d[51]),"+f"(d[52]),"+f"(d[53]),"+f"(d[54]),"+f"(d[55]),"+f"(d[56]),"+f"(d[57]),"+f"(d[58]),"+f"(d[59]),
      "+f"(d[60]),"+f"(d[61]),"+f"(d[62]),"+f"(d[63]),"+f"(d[64]),"+f"(d[65]),"+f"(d[66]),"+f"(d[67]),"+f"(d[68]),"+f"(d[69]),"+f"(d[70]),"+f"(d[71]),
      "+f"(d[72]),"+f"(d[73]),"+f"(d[74]),"+f"(d[75]),"+f"(d[76]),"+f"(d[77]),"+f"(d[78]),"+f"(d[79]),"+f"(d[80]),"+f"(d[81]),"+f"(d[82]),"+f"(d[83]),
      "+f"(d[84]),"+f"(d[85]),"+f"(d[86]),"+f"(d[87]),"+f"(d[88]),"+f"(d[89]),"+f"(d[90]),"+f"(d[91]),"+f"(d[92]),"+f"(d[93]),"+f"(d[94]),"+f"(d[95])
    : "r"(alo), "r"(blo), "r"(sd), "n"(TB), "r"(DESC_HI), "n"(TA));
}

struct Ctx {
  uint32_t sm;
  uint32_t bar;
  uint32_t rbar;
  int cl, rank, wg, warp, lane, phases;
};
__device__ __forceinline__ void release(const Ctx& c, int b, int cnt = 1) {
  if (c.lane < 2) mbar_arrive_cl(c.rbar + b * 8, cnt);
}
#define HK 5
#define NPRO 6
#define ZLEAD 16
#define PFM 7
#define PF1 1
constexpr float SM_SCALE = 0.08838834764831845f * 1.4426950408889634f;
constexpr float SM_HI = 1.8446744e19f, SM_LO = 5.4210109e-20f;
constexpr int ORDER = 1;

__device__ __forceinline__ void stage_tile(const float (&a)[64], uint32_t buf, const Ctx& c, float s0, float s1) {
  const int row = (c.lane & 7) + ((c.lane >> 3) & 1) * 8;
  const uint32_t base = buf + (c.warp * 16 + row) * 128 + (((c.lane >> 4) ^ (row & 7)) << 4);
#pragma unroll
  for (int i = 0; i < 8; i++)
    stsm4((base ^ ((i & 3) << 5)) + (i >> 2) * 8192, pack_bf16(a[8 * i] * s0, a[8 * i + 1] * s0), pack_bf16(a[8 * i + 2] * s1, a[8 * i + 3] * s1),
          pack_bf16(a[8 * i + 4] * s0, a[8 * i + 5] * s0), pack_bf16(a[8 * i + 6] * s1, a[8 * i + 7] * s1));
}

__device__ __forceinline__ void p1_epilogue(const Params& p, const Ctx& c, const float (&acc)[64], int t, int type) {
  const int tile = p.s.r[c.cl].tile[t] & 63, b = c.wg * 2 + 1;
  mbar_wait(c.bar + (B_SE + b) * 8, (t & 1) ^ 1);
  if (type && tile >= 32) {
    const int r = 2 * (c.lane & 3) + ((c.lane >> 2) & 1);
    const uint32_t dst = c.sm + SM_BUF + b * 16384 + r * 128 + (((c.warp * 2) ^ r) << 4) + (c.lane >> 3) * 4;
#pragma unroll
    for (int i = 0; i < 16; i++) {
      asm volatile("st.shared.u32 [%0], %1;" ::"r"(dst + i * 1024), "r"(pack_bf16(acc[4 * i], acc[4 * i + 1])) : "memory");
      asm volatile("st.shared.u32 [%0], %1;" ::"r"((dst ^ 16) + i * 1024), "r"(pack_bf16(acc[4 * i + 2], acc[4 * i + 3])) : "memory");
    }
  } else {
    if (type) stage_tile(acc, c.sm + SM_BUF + b * 16384, c, SM_SCALE, SM_SCALE);
    else stage_tile(acc, c.sm + SM_BUF + b * 16384, c, 1.f, 1.f);
  }
  FENCE_ASYNC_SMEM();
  __syncwarp();
  if (c.lane == 0) mbar_arrive(c.bar + (B_SF + b) * 8);
}

__device__ __forceinline__ void p1_consumer(const Params& p, const Ctx& c) {
  const int n = p.s.r[c.cl].n1;
  const int type = p.s.r[c.cl].slab >> 3;
  const uint32_t bdesc = desc_lo(c.sm + SM_RING, 8192), adesc = desc_lo(c.sm + SM_BUF + 32768 + c.wg * 8192, 16);
  uint32_t A[128];
  float acc[64] = {};
  int slot = 0, par = 0;
  auto next = [&]() { if (++slot == 10) { slot = 0; par ^= 1; } };
  {
    const int row = (c.lane & 7) + ((c.lane >> 3) & 1) * 8;
    const uint32_t base = c.sm + SM_RING + (c.wg * 64 + c.warp * 16 + row) * 128 + (((c.lane >> 4) ^ (row & 7)) << 4);
    if (c.wg == 1) bar_sync(ORDER + 1, 256);
    int pa = -1, pb = -1;
    if (type) {
      mbar_wait(c.bar + B_P1F * 8, 0);
      WG_FENCE();
#pragma unroll
      for (int kk = 0; kk < 4; kk++) wgmma_ss128<1>(acc, adesc + kk * 2, bdesc + kk * 128, kk != 0);
      WG_COMMIT();
      pb = 0; slot = 1;
    }
#pragma unroll
    for (int kb = 0; kb < 8; kb++) {
      const int sa = slot;
      mbar_wait(c.bar + (B_P1F + slot) * 8, par);
      next();
      mbar_wait(c.bar + (B_P1F + slot) * 8, par);
      WG_FENCE();
#pragma unroll
      for (int kk = 0; kk < 4; kk++)
        wgmma_ss128<1>(acc, desc_lo(c.sm + SM_RING + c.wg * 8192, 16) + sa * 1024 + kk * 2, bdesc + slot * 1024 + kk * 128, (kb | kk) != 0 ? 1 : type);
      WG_COMMIT();
      if (kb == 1 && c.wg == 0) bar_arrive(ORDER + 1, 256);
#pragma unroll
      for (int kk = 0; kk < 4; kk++) ldsm4((base ^ (kk << 5)) + sa * 16384, A[kb * 16 + kk * 4], A[kb * 16 + kk * 4 + 1], A[kb * 16 + kk * 4 + 2], A[kb * 16 + kk * 4 + 3]);
      WG_WAIT(1);
      if (kb > 0) release(c, B_P1E + pa);
      if (kb > 0 || pb >= 0) release(c, B_P1E + pb);
      pa = sa; pb = slot;
      next();
    }
    WG_WAIT(0);
    __syncwarp();
    release(c, B_P1E + pa);
    release(c, B_P1E + pb);
    pin(acc);
    p1_epilogue(p, c, acc, 0, type);
  }
  for (int t = 1; t < n; t++) {
    bar_sync(ORDER + c.wg, 256);
    int prev1 = -1, prev2 = -1;
    if (type) {
      mbar_wait(c.bar + (B_P1F + slot) * 8, par);
      WG_FENCE();
#pragma unroll
      for (int kk = 0; kk < 4; kk++) wgmma_ss128<1>(acc, adesc + kk * 2, bdesc + slot * 1024 + kk * 128, kk != 0);
      WG_COMMIT();
      prev1 = slot;
      next();
    }
#pragma unroll
    for (int kb = 0; kb < 8; kb++) {
      mbar_wait(c.bar + (B_P1F + slot) * 8, par);
      WG_FENCE();
      const uint32_t d = bdesc + slot * 1024;
#pragma unroll
      for (int kk = 0; kk < 4; kk++)
        wgmma_rs128<1>(acc, A[kb * 16 + kk * 4], A[kb * 16 + kk * 4 + 1], A[kb * 16 + kk * 4 + 2], A[kb * 16 + kk * 4 + 3], d + kk * 128, (kb | kk) != 0 ? 1 : type);
      WG_COMMIT();
      if (kb == HK) {
        if (t + 1 < n || c.wg == 0) bar_arrive(ORDER + (c.wg ^ 1), 256);
      }
      if (kb > 0) { WG_WAIT(2); if (kb > 1 || prev2 >= 0) release(c, B_P1E + prev2); }
      prev2 = prev1; prev1 = slot;
      next();
    }
    WG_WAIT(1);
    release(c, B_P1E + prev2);
    WG_WAIT(0);
    pin(acc);
    release(c, B_P1E + prev1);
    p1_epilogue(p, c, acc, t, type);
  }
}

__device__ __forceinline__ void p1_producer(const Params& p, const Ctx& c) {
  const int n = p.s.r[c.cl].n1;
  const int type = p.s.r[c.cl].slab >> 3, grp = p.s.r[c.cl].slab & 7;
  int slot = NPRO % 10, par = NPRO < 10;
#pragma unroll 1
  for (int t = 0; t < n; t++) {
    const int tile = p.s.r[c.cl].tile[t] & 63;
    const CUtensorMap* m = &p.map_w[type * 2 + (tile >> 5)];
    const int n0 = (tile & 31) * 128 + c.rank * 64;
    const uint64_t pol = p.s.r[c.cl].tile[t] >= 192 ? POL(0) : L2_NORMAL;
    const int ptile = p.s.r[c.cl].tile[t + PF1 < n ? t + PF1 : t];
    const CUtensorMap* pm = &p.map_w[type * 2 + ((ptile >> 5) & 1)];
    if (t == 7 && (c.phases & 16)) flag_wait<true>(F_GATE, 256);
#pragma unroll 1
    for (int kb = t ? -type : (NPRO - type) >> 1; kb < 8; kb++) {
      if (t == 0 && 2 * kb + type >= NPRO) {
        mbar_wait(c.bar + (B_P1E + slot) * 8, par);
        mbar_expect(c.bar + (B_P1F + slot) * 8, 16384);
        tma2d(c.sm + SM_RING + slot * 16384, &p.map_a[type], kb * 64, grp * 256 + c.rank * 128, c.bar + (B_P1F + slot) * 8);
        if (++slot == 10) { slot = 0; par ^= 1; }
      }
      mbar_wait(c.bar + (B_P1E + slot) * 8, par);
      mbar_expect(c.bar + (B_P1F + slot) * 8, 16384);
      tma2d_mc(c.sm + SM_RING + slot * 16384 + c.rank * 8192, m, n0, kb < 0 ? 512 : kb * 64, c.bar + (B_P1F + slot) * 8, pol);
      if (t + PF1 < n && t > 0 && ((ptile >> 6) == 1 || ((ptile >> 6) == 2 && ((kb ^ grp) & PFM) == 0))) tma2d_prefetch(pm, (ptile & 31) * 128 + c.rank * 64, kb < 0 ? 512 : kb * 64);
      if (++slot == 10) { slot = 0; par ^= 1; }
    }
  }
}

__device__ __forceinline__ void wait_kv_dead(const Ctx& c, int h, int g) {
  if (g >= 2) flag_wait<false>(F_RD + h * 8 + g, 8 - g);
  else flag_wait<false>(F_CTX + max(c.lane & 7, g) * 64 + h, 4);
}
__device__ __forceinline__ int p1_storer(const Params& p, const Ctx& c) {
  const int n = p.s.r[c.cl].n1;
  const int type = p.s.r[c.cl].slab >> 3, grp = p.s.r[c.cl].slab & 7;
  for (int i = 0; i < 2 * n; i++) {
    const int t = i >> 1, w = i & 1, b = w * 2 + 1;
    const int tile = p.s.r[c.cl].tile[t] & 63;
    mbar_wait(c.bar + (B_SF + b) * 8, t & 1);
    const uint32_t src = c.sm + SM_BUF + b * 16384;
    int f = (type ? F_Q : F_KV) + (tile & 31) * 8 + grp;
    if (type == 0) {
      const int prev = p.s.prev[tile & 31][grp];
      if (prev != 255 && w == 0) wait_kv_dead(c, prev, grp);
      uint8_t* dst = g_S + (size_t)(S_K + ((tile & 32) + p.s.slot[tile & 31][grp]) * 8 + grp) * 65536 + c.rank * 32768 + w * 8192;
      bulk_store(dst, src, 8192);
      bulk_store(dst + 16384, src + 8192, 8192);
    } else if (tile < 32) {
      const int dep = p.s.qdep[tile * 8 + grp];
      if (dep != 511 && w == 0) {
        if (dep < 256) wait_kv_dead(c, dep >> 3, dep & 7);
        else flag_wait<false>(F_TS + dep - 256, 128);
      }
      bulk_store(g_S + (size_t)p.s.qblk[tile * 8 + grp] * 65536 + (c.rank * 2 + w) * 16384, src, 16384);
    } else {
      tma3d_store(&p.map_t[2], src, (grp * 4 + c.rank * 2 + w) * 32, 0, (tile - 32) * 64);
      f = F_QKVA + grp * 4 + ((0xE4390900u >> (2 * (tile - 30))) & 3);
    }
    BULK_COMMIT();
    BULK_WAIT(0);
    mbar_arrive_one(c.bar + (B_SE + b) * 8);
    if (i == 2 * n - 1) return f;
    if (w) flag_add(f, 2);
  }
  return -1;
}

__device__ __forceinline__ int p2_buf(int w, int i) { return w * 2 + (i & 1); }
__device__ __forceinline__ int p2_blk(int rank, int w, int i) { return ((i ^ w) & 1) == 0 ? 3 - rank : rank; }


template <int N>
__device__ __forceinline__ void row_max(const float (&s)[N], float& m0, float& m1) {
  float a0 = fmaxf(s[0], s[1]), a1 = fmaxf(s[2], s[3]);
#pragma unroll
  for (int i = 1; i < N / 4; i++) {
    m0 = fmaxf(m0, s[4 * i]); a0 = fmaxf(a0, s[4 * i + 1]);
    m1 = fmaxf(m1, s[4 * i + 2]); a1 = fmaxf(a1, s[4 * i + 3]);
  }
  m0 = fmaxf(m0, a0); m1 = fmaxf(m1, a1);
  m0 = fmaxf(m0, __shfl_xor_sync(0xffffffffu, m0, 1));
  m1 = fmaxf(m1, __shfl_xor_sync(0xffffffffu, m1, 1));
  m0 = fmaxf(m0, __shfl_xor_sync(0xffffffffu, m0, 2));
  m1 = fmaxf(m1, __shfl_xor_sync(0xffffffffu, m1, 2));
}
template <bool SUB, int N>
__device__ __forceinline__ void row_exp(const float (&s)[N], uint32_t (&P)[32], float m0, float m1, float& t0, float& t1) {
  float u0 = 0.f, u1 = 0.f;
  t0 = t1 = 0.f;
#pragma unroll
  for (int i = 0; i < N / 4; i++) {
    const float e0 = ex2(SUB ? s[4 * i] - m0 : s[4 * i]), e1 = ex2(SUB ? s[4 * i + 1] - m0 : s[4 * i + 1]);
    const float e2 = ex2(SUB ? s[4 * i + 2] - m1 : s[4 * i + 2]), e3 = ex2(SUB ? s[4 * i + 3] - m1 : s[4 * i + 3]);
    if (i == 0) { t0 = e0; u0 = e1; t1 = e2; u1 = e3; }
    else { t0 += e0; u0 += e1; t1 += e2; u1 += e3; }
    P[2 * i] = pack_bf16(e0, e1);
    P[2 * i + 1] = pack_bf16(e2, e3);
  }
#pragma unroll
  for (int i = N / 2; i < 32; i++) P[i] = 0;
  pin(P);
  t0 += u0; t1 += u1;
}
template <int N>
__device__ __forceinline__ void causal_mask(float (&s)[N], int thr) {
#pragma unroll
  for (int i = 0; i < 8; i++) {
    if (8 * i > thr) s[N - 32 + 4 * i] = -INFINITY;
    if (8 * i + 1 > thr) s[N - 32 + 4 * i + 1] = -INFINITY;
    if (8 * i - 8 > thr) s[N - 32 + 4 * i + 2] = -INFINITY;
    if (8 * i - 7 > thr) s[N - 32 + 4 * i + 3] = -INFINITY;
  }
}
__device__ __forceinline__ void issue_qk(float (&s)[32], uint32_t qd, uint32_t kd) {
  WG_FENCE();
#pragma unroll
  for (int kk = 0; kk < 8; kk++) wgmma_ss64<0>(s, qd + (kk >> 2) * 512 + (kk & 3) * 2, kd + (kk >> 2) * 1024 + (kk & 3) * 2, kk != 0);
  WG_COMMIT();
}
__device__ __forceinline__ void issue_qk(float (&s)[64], uint32_t qd, uint32_t kd) {
  WG_FENCE();
#pragma unroll
  for (int kk = 0; kk < 8; kk++) wgmma_ss128<0>(s, qd + (kk >> 2) * 512 + (kk & 3) * 2, kd + (kk >> 2) * 1024 + (kk & 3) * 2, kk != 0);
  WG_COMMIT();
}
template <int NK>
__device__ __forceinline__ void issue_pv(float (&o)[64], const uint32_t (&P)[32], uint32_t vd, int acc) {
  WG_FENCE();
#pragma unroll
  for (int kk = 0; kk < NK; kk++) wgmma_rs128<1>(o, P[4 * kk], P[4 * kk + 1], P[4 * kk + 2], P[4 * kk + 3], vd + kk * 128, kk != 0 ? 1 : acc);
  WG_COMMIT();
}
__device__ __forceinline__ void stage_done(const Ctx& c, int b) {
  FENCE_ASYNC_SMEM();
  __syncwarp();
  if (c.lane == 0) mbar_arrive(c.bar + (B_SF + b) * 8);
}
__device__ __forceinline__ void p2_epilogue(const float (&o)[64], float s0, float s1, const Ctx& c, int b) {
  stage_tile(o, c.sm + SM_BUF + b * 16384, c, s0, s1);
  stage_done(c, b);
}

struct P2State {
  float m0, m1, l0, l1;
  bool shift;
  float e0, e1;
  int ks;
  int wi, ai;
  uint32_t wb, ab;
  uint32_t qd;
};
__device__ __forceinline__ int wrap5(int q) { return q >= 5 ? q - 5 : q; }
__device__ __forceinline__ void turn_wait(uint32_t ring, int i) { mbar_wait(ring + (i & 3) * 8, (i >> 2) & 1); }
__device__ __forceinline__ void turn_pass(const Ctx& c, uint32_t ring, int i) { if (c.lane == 0) mbar_arrive(ring + (i & 3) * 8); }
__device__ __forceinline__ void p2_scales(P2State& z) {
  float l0 = z.l0, l1 = z.l1;
  l0 += __shfl_xor_sync(0xffffffffu, l0, 1);
  l1 += __shfl_xor_sync(0xffffffffu, l1, 1);
  l0 += __shfl_xor_sync(0xffffffffu, l0, 2);
  l1 += __shfl_xor_sync(0xffffffffu, l1, 2);
  asm("rcp.approx.ftz.f32 %0, %1;" : "=f"(z.e0) : "f"(l0));
  asm("rcp.approx.ftz.f32 %0, %1;" : "=f"(z.e1) : "f"(l1));
}
template <int N>
__device__ __forceinline__ void p2_first(const Ctx& c, P2State& z, float (&o)[64], uint32_t (&Pc)[32], uint32_t (&Pn)[32],
                                         int ks, int vs, int cnt, int acc) {
  float s[N] = {};
  issue_qk(s, z.qd, desc_lo(c.sm + SM_RING, 16) + ks * 2048);
  if (vs >= 0) {
    p2_scales(z);
    issue_pv<8>(o, Pc, desc_lo(c.sm + SM_RING, 16384) + vs * 2048, acc);
  } else {
    WG_COMMIT();
  }
  mbar_expect(z.ab + (z.ai++ & 3) * 8, cnt == 1 ? 8192 : 0);
  WG_WAIT(1);
  pin(s);
  release(c, B_P2E + ks, cnt);
  causal_mask(s, c.warp * 16 + (c.lane >> 2) - 2 * (c.lane & 3));
  z.m0 = z.m1 = 0.f;
  row_exp<false>(s, Pn, 0.f, 0.f, z.l0, z.l1);
  z.shift = __any_sync(0xffffffffu, !(z.l0 + z.l1 <= SM_HI) || ((c.lane & 3) == 0 && !(fminf(z.l0, z.l1) >= SM_LO)));
  if (__builtin_expect(z.shift, 0)) {
    z.m0 = z.m1 = -INFINITY;
    row_max(s, z.m0, z.m1);
    row_exp<true>(s, Pn, z.m0, z.m1, z.l0, z.l1);
  }
  WG_WAIT(0);
  pin(o);
  if (vs >= 0) release(c, B_P2E + vs, 1);
}

template <bool SECOND>
__device__ __forceinline__ void p2_turn(const Ctx& c, P2State& z, float (&o)[64], uint32_t (&Pc)[32], uint32_t (&Pn)[32],
                                        int eb = -1, bool half = false, int vcnt = 1) {
  float s[64] = {};
  const int ks = z.ks, vs = wrap5(ks + 1);
  turn_wait(z.wb, z.wi++);
  issue_qk(s, z.qd, desc_lo(c.sm + SM_RING, 16) + ks * 2048);
  const uint32_t vd = desc_lo(c.sm + SM_RING, 16384) + vs * 2048;
  if (SECOND) {
    if (eb >= 0) stage_tile(o, c.sm + SM_BUF + eb * 16384, c, z.e0, z.e1);
    if (half) issue_pv<4>(o, Pc, vd, 0); else issue_pv<8>(o, Pc, vd, 0);
  } else {
    issue_pv<8>(o, Pc, vd, 1);
  }
  turn_pass(c, z.ab, z.ai++);
  if (SECOND) { if (eb >= 0) stage_done(c, eb); }
  z.ks = wrap5(ks + 2);
  WG_WAIT(1);
  pin(s);
  release(c, B_P2E + ks, 1);
  float t0, t1, a0 = 1.f, a1 = 1.f;
  row_exp<false>(s, Pn, 0.f, 0.f, t0, t1);
  const bool redo = __any_sync(0xffffffffu, z.shift || !(t0 + t1 <= SM_HI));
  if (__builtin_expect(redo, 0)) {
    float n0 = z.m0, n1 = z.m1;
    if (!z.shift) { n0 = __log2f(z.l0); n1 = __log2f(z.l1); }
    z.shift = true;
    row_max(s, n0, n1);
    a0 = ex2(z.m0 - n0); a1 = ex2(z.m1 - n1);
    z.m0 = n0; z.m1 = n1;
    z.l0 *= a0; z.l1 *= a1;
    row_exp<true>(s, Pn, z.m0, z.m1, t0, t1);
  }
  WG_WAIT(0);
  pin(o);
  release(c, B_P2E + vs, vcnt);
  if (__builtin_expect(redo, 0)) {
#pragma unroll
    for (int i = 0; i < 16; i++) { o[4 * i] *= a0; o[4 * i + 1] *= a0; o[4 * i + 2] *= a1; o[4 * i + 3] *= a1; }
  }
  z.l0 += t0; z.l1 += t1;
}
__device__ __forceinline__ void copy_p(uint32_t (&d)[32], const uint32_t (&s)[32], int zero) {
#pragma unroll
  for (int i = 0; i < 32; i++) asm volatile("add.s32 %0, %1, %2;" : "=r"(d[i]) : "r"(s[i]), "r"(zero));
}

__device__ __forceinline__ void p2_consumer(const Params& p, const Ctx& c, int rot) {
  const int nit = p.s.r[c.cl].n2;
  const uint32_t fring = c.bar + B_P2F * 8, oring = c.bar + B_ORD * 8;
  float o[64] = {};
  uint32_t Pa[32] = {}, Pb[32] = {};
  P2State z;
  z.e0 = z.e1 = z.l0 = z.l1 = 0.f; z.ks = rot; z.shift = false;
  int acc = 0, n = 0;
  for (int it = 0; it < nit; it++) {
    const int j = p.s.r[c.cl].item[it] & 7, blk = p2_blk(c.rank, c.wg, it);
    const int lng = ((it ^ c.wg) & 1) ^ 1;
    z.qd = desc_lo(c.sm + SM_BUF, 16) + p2_buf(c.wg, it) * 1024;
    if (lng) { z.wb = oring; z.wi = n - it; z.ab = fring; z.ai = n + 1; }
    else { z.wb = fring; z.wi = n + 2; z.ab = oring; z.ai = n - it; }
    mbar_wait(c.bar + (B_QF + p2_buf(c.wg, it)) * 8, (it >> 1) & 1);
    turn_wait(fring, n + 1 - lng);
    const int vs = it ? wrap5(z.ks + 1) : -1, ks = lng ? z.ks : wrap5(z.ks + (it ? 2 : 1));
    if (blk & 1) p2_first<64>(c, z, o, Pa, Pb, ks, vs, 1 + lng, acc);
    else p2_first<32>(c, z, o, Pa, Pb, ks, vs, 1 + lng, acc);
    z.ks = wrap5(ks + (it == 0 && lng ? 1 : 2));
    n += 2 * j + 2;
    int left = 2 * j + lng;
    acc = left != 0;
    if (left == 0) { copy_p(Pa, Pb, p.zero); continue; }
    p2_turn<true>(c, z, o, Pb, Pa, it > 0 ? p2_buf(c.wg, it - 1) : -1, !(blk & 1), 1 + lng);
    while (--left > 0) {
      p2_turn<false>(c, z, o, Pa, Pb);
      if (--left == 0) { copy_p(Pa, Pb, p.zero); break; }
      p2_turn<false>(c, z, o, Pb, Pa);
    }
  }
  {
    if (!acc && nit > 1) p2_epilogue(o, z.e0, z.e1, c, p2_buf(c.wg, nit));
    turn_wait(z.wb, z.wi);
    issue_pv<8>(o, Pa, desc_lo(c.sm + SM_RING, 16384) + z.ks * 2048, acc);
    if (((nit - 1) ^ c.wg) & 1) turn_pass(c, z.ab, z.ai);
    p2_scales(z);
    WG_WAIT(0);
    pin(o);
    release(c, B_P2E + z.ks);
    p2_epilogue(o, z.e0, z.e1, c, p2_buf(c.wg, nit - 1));
  }
}

__device__ __forceinline__ void p2_load_q(const Params& p, const Ctx& c, int it, int w) {
  const int item = p.s.r[c.cl].item[it], b = p2_buf(w, it);
  mbar_expect(c.bar + (B_QF + b) * 8, 16384);
  bulk_load(c.sm + SM_BUF + b * 16384, g_S + (size_t)p.s.qblk[item] * 65536 + p2_blk(c.rank, w, it) * 16384, 16384, c.bar + (B_QF + b) * 8, POL(4));
}
__device__ __forceinline__ void wait_p1_free(const Ctx& c, int u1, int s) {
  mbar_wait(c.bar + (B_P1E + 2 * s) * 8, ((u1 - 1 - 2 * s) / 10) & 1);
  mbar_wait(c.bar + (B_P1E + 2 * s + 1) * 8, ((u1 - 2 - 2 * s) / 10) & 1);
}
__device__ __forceinline__ void p2_producer(const Params& p, const Ctx& c, int u1, int rot) {
  const int nit = p.s.r[c.cl].n2;
  int slot = rot, cnt = 0, par = 1, n = 0;
  const uint8_t* pv = nullptr;
  bool pl = false;
  auto load = [&](const uint8_t* src, int expect, uint32_t fb, bool last) {
    if (cnt < 5) {
      if (u1) {
        wait_p1_free(c, u1, slot);
        if (cnt == 0) p2_load_q(p, c, 0, 1);
      }
      cnt++;
    } else {
      if (slot == rot) par ^= 1;
      mbar_wait(c.bar + (B_P2E + slot) * 8, par);
    }
    if (expect) mbar_expect(fb, expect);
    bulk_load_mc(c.sm + SM_RING + slot * 32768 + c.rank * 16384, src, 16384, fb, last ? POL(5) : L2_NORMAL);
    slot = wrap5(slot + 1);
  };
  for (int it = 0; it < nit; it++) {
    const int item = p.s.r[c.cl].item[it], h = item >> 3, j = item & 7;
    if (it == 1 && (c.phases & 16) && p.s.r[c.cl].n1 < 8) flag_wait<true>(F_GATE, 256);
    uint32_t ready = (c.phases & 16) ? 0u : 255u;
    if (it == 0) { if (c.phases & 16) flag_wait<false>(F_Q + item, 4); mbar_wait(c.bar + B_LAD * 8, 0); p2_load_q(p, c, 0, 0); if (!u1) p2_load_q(p, c, 0, 1); }
    for (int t = 2 * j + 1; t >= 0; t--) {
      mask_wait(ready, t >> 1, F_KV + h * 8 + (c.lane & 7), 8);
      const uint8_t* k = g_S + (size_t)(2 * S_K + p.s.slot[h][t >> 1] * 16 + t) * 32768 + c.rank * 16384;
      const uint32_t fb = c.bar + (B_P2F + (n & 3)) * 8;
      const bool last = (p.s.r[c.cl].last[it] >> (t >> 1)) & 1;
      load(k, pv && t != 2 * j ? 65536 : 32768, fb, last);
      if (!(t & 1) && t + 4 <= 2 * j && c.rank == 0) flag_add_rx(F_RD + h * 8 + (t >> 1) + 2);
      if (pv) load(pv, 0, t != 2 * j ? fb : c.bar + (B_ORD + ((n - 1 - it) & 3)) * 8, pl);
      pl = last;
      pv = k + (size_t)NH * 16 * 32768;
      n++;
    }
  }
  load(pv, 32768, c.bar + (B_P2F + (n & 3)) * 8, pl);
}

__device__ __forceinline__ void publish_and_load_q(const Params& p, const Ctx& c, int f, int it, int seen) {
  const bool want = it < p.s.r[c.cl].n2, early = want && __all_sync(0xffffffffu, seen >= 4);
  if (early) { p2_load_q(p, c, it, it & 1); p2_load_q(p, c, it, (it & 1) ^ 1); }
  if (f >= 0) flag_add(f, 2);
  if (want && !early) {
    if (c.phases & 16) flag_wait<false>(F_Q + p.s.r[c.cl].item[it], 4);
    p2_load_q(p, c, it, it & 1); p2_load_q(p, c, it, (it & 1) ^ 1);
  }
}
__device__ __forceinline__ void p2_storer(const Params& p, const Ctx& c, int sfpar) {
  const int nit = p.s.r[c.cl].n2;
  int held = -1;
  for (int i = 0; i < 2 * nit; i++) {
    const int it = i >> 1, w = (it ^ i ^ 1) & 1, b = p2_buf(w, it);
    const int item = p.s.r[c.cl].item[it], h = item >> 3, j = item & 7;
    mbar_wait(c.bar + (B_SF + b) * 8, (sfpar >> b) & 1);
    sfpar ^= 1 << b;
    bulk_store(g_S + (size_t)p.s.qblk[item] * 65536 + p2_blk(c.rank, w, it) * 16384, c.sm + SM_BUF + b * 16384, 16384, POL(1));
    BULK_COMMIT();
    if (i & 1) {
      if (it + 2 == nit && (p.s.r[c.cl].item[it + 1] & 7) == 0) { held = F_CTX + j * 64 + h; continue; }
      const int seen = flag_peek(F_Q + p.s.r[c.cl].item[min(it + 2, nit - 1)]);
      BULK_WAIT(0);
      if (it + 1 == nit) release(c, B_DONE);
      publish_and_load_q(p, c, F_CTX + j * 64 + h, it + 2, seen);
    }
  }
  if (held >= 0) flag_add_rx(held, 2);
}

__device__ __forceinline__ int p3_pos(int i, int x) { return i < 4 ? (i + x) & 3 : 4; }
__device__ __forceinline__ void p3_consumer(const Params& p, const Ctx& c, int x) {
  const bool first = p.s.r[c.cl].p3 >= 24;
  const int tile = p.s.r[c.cl].p3 - (first ? 24 : 0), j = tile / 3, nt = tile - 3 * j;
  const int na = first ? 9 : 0, nb = p.s.task[c.cl][1] - p.s.task[c.cl][0];
  const uint32_t ad = desc_lo(c.sm + SM_RING + c.wg * 8192, 16), bd = desc_lo(c.sm + SM_RING + 16384, 4096);
  float acc[96] = {};
  int slot = 0, par = 0, prev = 0;
  float g0 = 0.f, g1 = 0.f;
  const int hold = c.wg && LAG ? na + nb - LAG : -1, pass = c.wg || !LAG ? -1 : na + nb - 1;
  const float* gp = g_gate + j * 256 + c.rank * 128 + c.wg * 64 + c.warp * 16 + (c.lane >> 2);
#pragma unroll 1
  for (int kb = 0; kb < na; kb++) {
    if (kb == hold) bar_sync(6, 256);
    mbar_wait(c.bar + (B_P3F + slot) * 8, par);
    WG_FENCE();
#pragma unroll
    for (int kk = 0; kk < 4; kk++) wgmma_ss192<1, 1>(acc, ad + p3_pos(slot, x) * 2560 + kk * 128, bd + p3_pos(slot, x) * 2560 + (kk >> 1) * 768 + (kk & 1) * 128, kk != 0 ? 1 : kb != 0);
    WG_COMMIT();
    if (kb == pass) bar_arrive(6, 256);
    WG_WAIT(1);
    if (kb > 0) release(c, B_P3E + prev);
    else { g0 = __ldcg(gp); g1 = __ldcg(gp + 8); }
    prev = slot;
    if (++slot == 5) { slot = 0; par ^= 1; }
  }
#pragma unroll 1
  for (int kb = na; kb < na + nb; kb++) {
    if (kb == hold) bar_sync(6, 256);
    mbar_wait(c.bar + (B_P3F + slot) * 8, par);
    WG_FENCE();
#pragma unroll
    for (int kk = 0; kk < 4; kk++) wgmma_ss192<1>(acc, ad + p3_pos(slot, x) * 2560 + kk * 2, bd + p3_pos(slot, x) * 2560 + (kk >> 1) * 768 + (kk & 1) * 128, kk != 0 ? 1 : kb != 0);
    WG_COMMIT();
    if (kb == pass) bar_arrive(6, 256);
    WG_WAIT(1);
    if (kb > 0) release(c, B_P3E + prev);
    else { g0 = __ldcg(gp); g1 = __ldcg(gp + 8); }
    prev = slot;
    if (++slot == 5) { slot = 0; par ^= 1; }
  }
  g0 = __fdividef(1.f, 1.f + g0); g1 = __fdividef(1.f, 1.f + g1);
  WG_WAIT(0);
  pin(acc);
  if (first) bar_sync(4 + c.wg, 128);
  mbar_wait(c.bar + B_OUT * 8, 0);
  const int row = (c.lane & 7) + ((c.lane >> 3) & 1) * 8;
  const uint32_t wbase = c.sm + SM_RING + c.wg * 8192 + c.warp * 2048;
  const uint32_t base = wbase + row * 128 + (((c.lane >> 4) ^ (row & 7)) << 4);
#pragma unroll
  for (int i = 0; i < 12; i++) {
    stsm4((base ^ ((i & 3) << 5)) + (i >> 2) * 40960, pack_bf16(acc[8 * i] * g0, acc[8 * i + 1] * g0), pack_bf16(acc[8 * i + 2] * g1, acc[8 * i + 3] * g1),
          pack_bf16(acc[8 * i + 4] * g0, acc[8 * i + 5] * g0), pack_bf16(acc[8 * i + 6] * g1, acc[8 * i + 7] * g1));
    if ((i & 3) == 3) {
      FENCE_ASYNC_SMEM();
      bar_sync(4 + c.wg, 128);
      if (c.warp == (i >> 2)) tma2d_add(&p.map_out, c.sm + SM_RING + c.wg * 8192 + c.warp * 40960, nt * 192 + c.warp * 64, j * 256 + c.rank * 128 + c.wg * 64);
    }
  }
  BULK_COMMIT();
  BULK_WAIT_READ(0);
}

__device__ __forceinline__ void p3_producer(const Params& p, const Ctx& c, int u1, int u2, int rot, int x) {
  const bool first = p.s.r[c.cl].p3 >= 24;
  const int tile = p.s.r[c.cl].p3 - (first ? 24 : 0), j = tile / 3, nt = tile - 3 * j;
  int slot = 0, par = 1, cnt = 0;
  auto wait_free = [&](int s) {
    const int f = wrap5(s + 5 - rot);
    if (f < u2) mbar_wait(c.bar + (B_P2E + s) * 8, ((u2 - 1 - f) / 5) & 1);
    else if (u1) wait_p1_free(c, u1, s);
  };
  asm volatile(ELECT("prefetch.tensormap [%0];") ::"l"(&p.map_o[0]) : "memory");
  asm volatile(ELECT("prefetch.tensormap [%0];") ::"l"(&p.map_out) : "memory");
  if ((c.phases & 16) && p.s.r[c.cl].n1 < 8 && p.s.r[c.cl].n2 < 2) flag_wait<true>(F_GATE, 256);
  uint32_t ready = (c.phases & 16) ? 0u : ~0u;
  const int q0 = p.s.task[c.cl][0], q1 = p.s.task[c.cl][1];
  for (int q = q0 - (first ? 9 : 0); q < q1; q++) {
    if (q == max(q0, 64 - ZLEAD)) mbar_arrive_one(c.bar + B_ZF * 8);
    const bool brA = q < q0;
    const int kb = brA ? q - q0 + 9 : p.s.p3_order[tile][q];
    if (!brA) mask_wait(ready, kb >> 1, F_CTX + j * 64 + c.lane, 4);
    else if (kb == 0 && (c.phases & 16)) flag_wait<false>(F_CTX + j * 64 + 32, 16);
    const uint8_t* a = brA ? g_oA + (j * 4 + c.rank * 2) * 73728 + kb * 8192 : g_S + (size_t)p.s.qblk[(kb >> 1) * 8 + j] * 65536 + c.rank * 32768 + (kb & 1) * 8192;
    const uint32_t st = c.sm + SM_RING + p3_pos(slot, x) * 40960, fb = c.bar + (B_P3F + slot) * 8;
    if (cnt < 4) { wait_free(p3_pos(cnt, x)); wait_free(p3_pos(cnt, x) + 1); }
    else if (cnt == 4) mbar_wait(c.bar + B_DONE * 8, 0);
    else mbar_wait(c.bar + (B_P3E + slot) * 8, par);
    cnt++;
    mbar_expect(fb, 40960);
    bulk_load(st, a, 8192, fb, POL(3));
    bulk_load(st + 8192, a + (brA ? 73728 : 16384), 8192, fb, POL(3));
    tma3d_mc(st + 16384 + c.rank * 12288, &p.map_o[brA], 0, kb * 64 + c.rank * 32, nt * 3, fb);
    if (++slot == 5) { slot = 0; par ^= 1; }
  }
}

__device__ __forceinline__ float bf_lo(uint32_t w) { return __uint_as_float(w << 16); }
__device__ __forceinline__ float bf_hi(uint32_t w) { return __uint_as_float(w & 0xffff0000u); }

__device__ __forceinline__ void gate_rows(const Params& p, int row0, int lane) {
  const uint4* x = reinterpret_cast<const uint4*>(p.x + (size_t)(row0 + (lane >> 2)) * DM) + (lane & 3);
  const uint4* w = reinterpret_cast<const uint4*>(p.gate_w) + (lane & 3);
  float a = 0.f;
#pragma unroll 1
  for (int b = 0; b < 3; b++) {
    uint4 u[6];
#pragma unroll
    for (int i = 0; i < 6; i++) u[i] = __ldg(x + (b * 6 + i) * 4);
#pragma unroll
    for (int i = 0; i < 6; i++) {
      const uint4 v = __ldg(w + (b * 6 + i) * 4);
      a = fmaf(bf_lo(u[i].x), bf_lo(v.x), a); a = fmaf(bf_hi(u[i].x), bf_hi(v.x), a);
      a = fmaf(bf_lo(u[i].y), bf_lo(v.y), a); a = fmaf(bf_hi(u[i].y), bf_hi(v.y), a);
      a = fmaf(bf_lo(u[i].z), bf_lo(v.z), a); a = fmaf(bf_hi(u[i].z), bf_hi(v.z), a);
      a = fmaf(bf_lo(u[i].w), bf_lo(v.w), a); a = fmaf(bf_hi(u[i].w), bf_hi(v.w), a);
    }
  }
  a += __shfl_xor_sync(0xffffffffu, a, 1);
  a += __shfl_xor_sync(0xffffffffu, a, 2);
  if ((lane & 3) == 0) g_gate[row0 + (lane >> 2)] = __expf(fminf(a, 60.f));
}

__device__ __forceinline__ void lds10(uint32_t (&k)[10], uint32_t a) {
  asm volatile("ld.shared.v2.u32 {%0, %1}, [%10];\nld.shared.v2.u32 {%2, %3}, [%10+8];\nld.shared.v2.u32 {%4, %5}, [%10+16];\n"
               "ld.shared.v2.u32 {%6, %7}, [%10+24];\nld.shared.v2.u32 {%8, %9}, [%10+32];"
               : "=r"(k[0]), "=r"(k[1]), "=r"(k[2]), "=r"(k[3]), "=r"(k[4]), "=r"(k[5]), "=r"(k[6]), "=r"(k[7]), "=r"(k[8]), "=r"(k[9]) : "r"(a));
}
__device__ __forceinline__ void local_attn(const Params& p, const Ctx& c, int rb, int hs) {
  const int lane = c.lane, grp = rb >> 2, par = lane >> 4, i0 = 2 * (lane & 15);
  const uint32_t buf = c.sm + SM_BUF + (c.warp - 2) * 8192, bqk = c.bar + (B_LA + (c.warp - 2) * 2) * 8, bv = bqk + 8;
  const uint32_t mine = buf + 2304 + par * 160 + i0 * 4;
  const bool flags = c.phases & 16;
  auto fetch_qk = [&](int i) {
    if (flags && !(i & 1)) {
      const int q = i >> 1;
      const int tgt = q == 0 ? 24 : q == 3 ? 8 : 12;
      flag_wait<false>(F_QKVA + (grp - (grp > 0 && (rb & 3) == 0 ? par : 0)) * 4 + q, tgt);
    }
    mbar_expect(bqk, 5184);
    tma3d(buf, &p.map_t[0], rb * 32, 0, 9 * (4 * i + hs), bqk, POL(2));
    tma3d(buf + 2304, &p.map_t[1], rb * 32 - 8, 0, 288 + 9 * (4 * i + hs), bqk, POL(2));
  };
  auto fetch_v = [&](int i) { mbar_expect(bv, 2880); tma3d(buf + 5248, &p.map_t[1], rb * 32 - 8, 0, 576 + 9 * (4 * i + hs), bv, POL(2)); };
  fetch_qk(0);
  if (flags) flag_wait<true>(F_GATE, 256);
#pragma unroll 1
  for (int q = 0; q < 8; q++) {
    fetch_v(q);
    float a[8], b[8];
#pragma unroll
    for (int w = 0; w < 8; w++) a[w] = b[w] = 0.f;
    mbar_wait(bqk, q & 1);
#pragma unroll 1
    for (int j = 0; j < 9; j++) {
      uint32_t x, y, k[10];
      asm volatile("ld.shared.v2.u32 {%0, %1}, [%2];" : "=r"(x), "=r"(y) : "r"(buf + lane * 8 + j * 256));
      lds10(k, mine + j * 320);
      const float xl = bf_lo(x), xh = bf_hi(x), yl = bf_lo(y), yh = bf_hi(y);
#pragma unroll
      for (int m = 1; m < 10; m++) {
        const float kl = bf_lo(k[m]), kh = bf_hi(k[m]);
        if (m < 9) a[8 - m] = fmaf(xl, kl, fmaf(xh, kh, a[8 - m]));
        if (m > 1) b[9 - m] = fmaf(yl, kl, fmaf(yh, kh, b[9 - m]));
      }
    }
    __syncwarp();
    mbar_wait(bv, q & 1);
    if (q & 1) flag_add_rx(F_TS + (q >> 1));
    if (q < 7) fetch_qk(q + 1);
    constexpr float SC = 0.23570226039551584f * 1.4426950408889634f;
    const float* gp = g_gate + rb * 64 + 2 * i0 + par;
    const float ga = __ldcg(gp), gb = __ldcg(gp + 2);
    float ma = a[0], mb = b[0];
#pragma unroll
    for (int w = 1; w < 8; w++) {
      if (rb == 0) {
        if (i0 < w) a[w] = -INFINITY;
        if (i0 + 1 < w) b[w] = -INFINITY;
      }
      ma = fmaxf(ma, a[w]); mb = fmaxf(mb, b[w]);
    }
    float la = 0.f, lb = 0.f;
#pragma unroll
    for (int w = 0; w < 8; w++) {
      a[w] = ex2((a[w] - ma) * SC); b[w] = ex2((b[w] - mb) * SC);
      la += a[w]; lb += b[w];
    }
    la = __fdividef(ga, la); lb = __fdividef(gb, lb);
#pragma unroll
    for (int w = 0; w < 8; w++) { a[w] *= la; b[w] *= lb; }
    uint8_t* dst = g_oA + rb * 73728 + ((i0 & 2) + par) * 4;
#pragma unroll 1
    for (int j = 0; j < 9; j++) {
      uint32_t v[10];
      lds10(v, mine + 2944 + j * 320);
      float a0 = 0.f, a1 = 0.f, b0 = 0.f, b1 = 0.f;
#pragma unroll
      for (int m = 1; m < 10; m++) {
        const float vl = bf_lo(v[m]), vh = bf_hi(v[m]);
        if (m < 9) { a0 = fmaf(a[8 - m], vl, a0); a1 = fmaf(a[8 - m], vh, a1); }
        if (m > 1) { b0 = fmaf(b[9 - m], vl, b0); b1 = fmaf(b[9 - m], vh, b1); }
      }
      const uint32_t wa = pack_bf16(a0, a1), wb = pack_bf16(b0, b1);
      const uint32_t got = __shfl_xor_sync(0xffffffffu, par ? wa : wb, 16);
      const uint32_t r0 = par ? got : wa, r1 = par ? wb : got;
      const int col = 18 * (4 * q + hs) + 2 * j, o = col * 128 + ((((i0 >> 2) ^ col) & 7) << 4);
      *reinterpret_cast<uint32_t*>(dst + o) = __byte_perm(r0, r1, 0x5410);
      *reinterpret_cast<uint32_t*>(dst + ((o + 128) ^ 16)) = __byte_perm(r0, r1, 0x7632);
    }
    __syncwarp();
  }
  mbar_arrive_one(c.bar + B_LAD * 8);
  flag_add(F_CTX + grp * 64 + 32);
}

__global__ void __cluster_dims__(2, 1, 1) __launch_bounds__(384, 1) fused_kernel(const __grid_constant__ Params p) {
  extern __shared__ uint8_t smem_raw[];
  Ctx c;
  c.sm = ((uint32_t)__cvta_generic_to_shared(smem_raw) + 1023u) & ~1023u;
  c.bar = c.sm + SM_BAR;
  c.lane = threadIdx.x & 31;
  const int wid = __shfl_sync(0xffffffffu, threadIdx.x >> 5, 0);
  if (wid < 6) asm volatile("prefetch.tensormap [%0];" ::"l"(&p.map_a[0] + wid) : "memory");
  c.wg = wid >> 2;
  c.warp = wid & 3;
  c.cl = (blockIdx.x + (wid >> 4)) >> 1;
  c.rank = blockIdx.x & 1;
  c.rbar = mapa(c.bar, c.lane & 1);
  {
    const int w = wid, cnt = (((int)(B_CNT >> (4 * w)) - 1) & 15) + 1;
    if (w < 11) {
#pragma unroll
      for (int i = 0; i < 8; i++) asm volatile("mbarrier.init.shared::cta.b64 [%0], %1;" ::"r"(c.bar + w * 64 + i * 8), "r"(cnt));
    }
    asm volatile("fence.mbarrier_init.release.cluster;" ::: "memory");
  }
  asm volatile("barrier.cluster.arrive.relaxed;" ::: "memory");
  c.phases = p.s.r[c.cl].phases;
  const bool do1 = p.s.r[c.cl].n1 > 0, do2 = p.s.r[c.cl].n2 > 0, do3 = p.s.r[c.cl].p3 != 255;
  if (do1 && c.wg == 2 && c.warp == 0) {
    const int type = p.s.r[c.cl].slab >> 3;
    FENCE_ASYNC_SMEM();
    mbar_expect(c.bar + B_P1F * 8, type ? 32768 : 16384);
    tma2d(type ? c.sm + SM_BUF + 32768 : c.sm + SM_RING, &p.map_a[type], type ? 512 : 0, (p.s.r[c.cl].slab & 7) * 256 + c.rank * 128, c.bar + B_P1F * 8);
  }
  asm volatile("barrier.cluster.wait.acquire;" ::: "memory");
  if (do1 && c.wg == 2 && c.warp == 0) {
    const int type = p.s.r[c.cl].slab >> 3, tile = p.s.r[c.cl].tile[0] & 63;
    const CUtensorMap* m = &p.map_w[type * 2 + (tile >> 5)];
#pragma unroll 1
    for (int s = 1 - type; s < NPRO; s++) {
      const int kb = (s - type) >> 1;
      const uint32_t fb = c.bar + (B_P1F + s) * 8;
      if (s) mbar_expect(fb, 16384);
      if ((s ^ type) & 1) tma2d_mc(c.sm + SM_RING + s * 16384 + c.rank * 8192, m, (tile & 31) * 128 + c.rank * 64, kb < 0 ? 512 : kb * 64, fb);
      else tma2d(c.sm + SM_RING + s * 16384, &p.map_a[type], kb * 64, (p.s.r[c.cl].slab & 7) * 256 + c.rank * 128, fb);
    }
  }

  if (c.wg < 2) {
    asm volatile("setmaxnreg.inc.sync.aligned.u32 224;");
    if (c.wg == 1) {
      if (do1) bar_arrive(ORDER, 256);
      if (c.lane == 0) mbar_arrive(c.bar + B_P2F * 8);
    }
    if (do1) p1_consumer(p, c);
    if (do2) p2_consumer(p, c, p.s.r[c.cl].rot);
    if (do3) p3_consumer(p, c, p.s.r[c.cl].x3);
    if (c.lane == 0) mbar_arrive(c.bar + B_FIN * 8);
    __syncwarp();
    cluster_sync();
  } else {
    asm volatile("setmaxnreg.dec.sync.aligned.u32 56;");
    if (c.warp == 0) {
      if (do1) p1_producer(p, c);
      if (do2) p2_producer(p, c, p.s.r[c.cl].u1, p.s.r[c.cl].rot);
      if (do3) p3_producer(p, c, p.s.r[c.cl].u1, p.s.r[c.cl].u2, p.s.r[c.cl].rot, p.s.r[c.cl].x3);
    } else if (c.warp == 1) {
      const int f = do1 ? p1_storer(p, c) : -1;
      if (do2) {
        publish_and_load_q(p, c, f, 1, flag_peek(F_Q + p.s.r[c.cl].item[1]));
        p2_storer(p, c, (p.s.r[c.cl].n1 & 1) * 10);
      } else {
        const bool idle = mbar_test(c.bar + B_LAD * 8, 0);
        if (idle) release(c, B_DONE);
        if (f >= 0) flag_add(f, 2);
        if (!idle) { mbar_wait(c.bar + B_LAD * 8, 0); release(c, B_DONE); }
      }
      if (do3) {
        const int tile = p.s.r[c.cl].p3 % 24;
        if (p.s.task[c.cl][1] == 64) {
          mbar_wait(c.bar + B_ZF * 8, 0);
          const int j = tile / 3, nt = tile - 3 * j;
          uint4* o = reinterpret_cast<uint4*>(p.out + (size_t)(j * 256 + c.rank * 128 + (c.lane >> 3)) * DM + nt * 192) + (c.lane & 7);
#pragma unroll 4
          for (int r = 0; r < 32; r++) o[r * 288] = o[r * 288 + 8] = o[r * 288 + 16] = make_uint4(0u, 0u, 0u, 0u);
          __syncwarp();
          flag_add(F_OUT + tile * 2 + c.rank);
        } else if (c.phases & 16) {
          flag_wait<false, 256>(F_OUT + tile * 2 + c.rank, 1);
        }
        mbar_arrive_one(c.bar + B_OUT * 8);
      }
    } else {
      const int bw = blockIdx.x * 2 + (c.warp - 2);
      if ((c.phases & 1) && bw < 256) {
        gate_rows(p, bw * 8, c.lane);
        __syncwarp();
        flag_add(F_GATE);
      }
      if (p.s.r[c.cl].bg != 255) local_attn(p, c, p.s.r[c.cl].bg, bw & 3);
      else if (c.lane == 0) mbar_arrive(c.bar + B_LAD * 8);
    }
    __syncwarp();
    bar_sync(3, 128);
    if (c.warp == 0 && (c.phases & 32)) {
      int last = 0;
      if (c.lane == 0) { __threadfence(); last = atomicAdd(g_flags + F_DONE, 1) == 2 * NCL - 1; }
      if (__shfl_sync(0xffffffffu, last, 0)) for (int i = c.lane; i < F_NUM; i += 32) g_flags[i] = 0;
    }
    if (c.warp == 1) mbar_wait(c.bar + B_FIN * 8, 0);
    __syncwarp();
    cluster_sync();
  }
}

static const Sched k_sched = {
  {{8,19,4,39,0,{72,204,242,210,0,0,0,0,0,0,0},{0,0,0,0,0,0,0,0,0,0,0},{131,233,128,198,39,104,11,16,20,9,27,82,93,207,23,21,26,31,28,0,0,0,0,0,0,0,0,0,0,0}},
   {8,3,4,3,255,{15,108,65,158,0,0,0,0,0,0,0},{0,0,0,126,0,0,0,0,0,0,0},{129,225,71,0,0,0,0,0,0,0,0,0,0,0,0,0,0,0,0,0,0,0,0,0,0,0,0,0,0,0}},
   {8,3,5,22,255,{39,106,87,116,112,0,0,0,0,0,0},{0,0,0,0,1,0,0,0,0,0,0},{69,165,226,0,0,0,0,0,0,0,0,0,0,0,0,0,0,0,0,0,0,0,0,0,0,0,0,0,0,0}},
   {8,4,4,5,255,{40,7,167,220,0,0,0,0,0,0,0},{0,0,0,0,0,0,0,0,0,0,0},{96,106,166,77,0,0,0,0,0,0,0,0,0,0,0,0,0,0,0,0,0,0,0,0,0,0,0,0,0,0}},
   {0,30,3,32,1,{184,209,224,0,0,0,0,0,0,0,0},{0,0,0,0,0,0,0,0,0,0,0},{68,35,197,226,7,198,205,204,200,203,208,212,202,201,211,27,214,17,210,207,206,217,221,222,215,213,216,218,223,220}},
   {1,28,0,13,2,{0,0,0,0,0,0,0,0,0,0,0},{0,0,0,0,0,0,0,0,0,0,0},{68,35,194,229,6,231,12,8,11,16,20,10,9,19,27,22,17,18,15,14,25,29,30,23,21,24,26,31,0,0}},
   {2,30,1,41,3,{194,0,0,0,0,0,0,0,0,0,0},{0,0,0,0,0,0,0,0,0,0,0},{67,225,194,229,6,199,205,204,200,203,208,212,202,201,211,22,219,18,15,209,206,217,221,222,215,213,216,218,223,220}},
   {3,29,1,29,4,{252,0,0,0,0,0,0,0,0,0,0},{0,0,0,0,0,0,0,0,0,0,0},{66,225,195,228,6,231,8,204,11,16,20,9,202,19,22,27,17,18,15,14,25,29,23,222,21,24,31,218,28,0}},
   {4,28,0,16,5,{0,0,0,0,0,0,0,0,0,0,0},{0,0,0,0,0,0,0,0,0,0,0},{65,35,197,226,6,231,8,236,16,20,10,9,19,22,27,17,18,14,15,25,29,23,30,21,24,31,26,28,0,0}},
   {5,27,0,0,6,{0,0,0,0,0,0,0,0,0,0,0},{0,0,0,0,0,0,0,0,0,0,0},{67,34,197,228,6,231,12,40,16,52,9,19,22,27,17,18,14,15,25,29,23,30,21,24,31,26,28,0,0,0}},
   {6,26,0,11,7,{0,0,0,0,0,0,0,0,0,0,0},{0,0,0,0,0,0,0,0,0,0,0},{67,193,197,224,7,45,8,43,20,42,19,22,27,17,18,15,89,14,29,23,30,21,24,26,31,28,0,0,0,0}},
   {7,25,0,19,8,{0,0,0,0,0,0,0,0,0,0,0},{0,0,0,0,0,0,0,0,0,0,0},{65,2,197,70,77,72,80,116,73,83,86,91,81,82,79,78,89,93,87,94,85,88,90,95,92,0,0,0,0,0}},
   {0,30,1,20,9,{251,0,0,0,0,0,0,0,0,0,0},{0,0,0,0,0,0,0,0,0,0,0},{100,193,37,192,39,230,237,236,232,235,240,244,234,233,243,59,246,49,242,239,238,249,253,254,247,245,248,250,255,252}},
   {1,30,1,2,10,{211,0,0,0,0,0,0,0,0,0,0},{15,0,0,0,0,0,0,0,0,0,0},{100,193,34,192,38,13,44,40,43,48,52,42,41,51,59,54,49,50,47,46,57,61,62,55,53,56,58,63,28,252}},
   {2,30,1,26,11,{170,0,0,0,0,0,0,0,0,0,0},{0,0,0,0,0,0,0,0,0,0,0},{99,4,34,192,38,231,237,236,232,235,240,244,234,233,243,54,251,50,47,241,238,249,253,254,247,245,248,250,255,252}},
   {3,29,1,34,12,{212,0,0,0,0,0,0,0,0,0,0},{0,0,0,0,0,0,0,0,0,0,0},{98,69,227,192,38,13,40,236,43,48,52,41,234,51,54,59,49,50,47,46,57,61,55,254,53,56,63,250,60,0}},
   {4,28,0,14,13,{0,0,0,0,0,0,0,0,0,0,0},{0,0,0,0,0,0,0,0,0,0,0},{97,4,37,192,38,13,40,11,48,52,42,41,51,54,59,49,50,46,47,57,61,55,62,53,56,63,58,60,0,0}},
   {5,27,0,10,14,{0,0,0,0,0,0,0,0,0,0,0},{0,0,0,0,0,0,0,0,0,0,0},{99,193,37,192,38,13,44,11,48,10,41,51,54,59,49,50,46,47,57,61,55,62,53,56,63,58,60,0,0,0}},
   {6,26,0,7,15,{0,0,0,0,0,0,0,0,0,0,0},{0,0,0,0,0,0,0,0,0,0,0},{99,225,37,70,39,12,40,16,52,9,51,54,59,49,50,47,121,46,61,55,62,53,56,58,63,60,0,0,0,0}},
   {7,25,0,15,16,{0,0,0,0,0,0,0,0,0,0,0},{0,0,0,0,0,0,0,0,0,0,0},{97,34,37,102,109,104,112,74,105,115,118,123,113,114,111,110,121,125,119,126,117,120,122,127,124,0,0,0,0,0}},
   {0,4,8,10,255,{11,63,131,161,217,237,171,192,0,0,0},{0,0,0,0,0,0,0,0,0,0,0},{67,225,194,224,0,0,0,0,0,0,0,0,0,0,0,0,0,0,0,0,0,0,0,0,0,0,0,0,0,0}},
   {1,6,5,28,255,{6,69,143,236,249,0,0,0,0,0,0},{0,0,0,31,0,0,0,0,0,0,0},{67,225,197,224,7,45,0,0,0,0,0,0,0,0,0,0,0,0,0,0,0,0,0,0,0,0,0,0,0,0}},
   {2,4,6,16,255,{29,41,94,129,119,213,0,0,0,0,0},{0,0,0,0,2,0,0,0,0,0,0},{65,36,197,224,0,0,0,0,0,0,0,0,0,0,0,0,0,0,0,0,0,0,0,0,0,0,0,0,0,0}},
   {3,6,7,17,255,{16,20,95,157,145,188,226,0,0,0,0},{0,0,0,0,0,16,7,0,0,0,0},{65,101,196,224,7,45,0,0,0,0,0,0,0,0,0,0,0,0,0,0,0,0,0,0,0,0,0,0,0,0}},
   {4,8,5,12,255,{9,3,93,142,255,0,0,0,0,0,0},{0,0,0,0,128,0,0,0,0,0,0},{67,36,194,224,7,45,12,43,0,0,0,0,0,0,0,0,0,0,0,0,0,0,0,0,0,0,0,0,0,0}},
   {5,10,5,6,255,{104,60,132,156,152,0,0,0,0,0,0},{0,0,0,0,1,0,0,0,0,0,0},{66,225,196,224,7,45,8,43,20,42,0,0,0,0,0,0,0,0,0,0,0,0,0,0,0,0,0,0,0,0}},
   {6,10,7,14,255,{48,71,130,73,191,193,208,0,0,0,0},{0,0,0,0,128,0,0,0,0,0,0},{68,2,64,102,77,44,11,48,10,41,0,0,0,0,0,0,0,0,0,0,0,0,0,0,0,0,0,0,0,0}},
   {7,6,8,38,255,{0,35,2,97,79,138,189,240,0,0,0},{0,0,0,0,0,0,32,1,0,0,0},{68,3,64,71,76,75,0,0,0,0,0,0,0,0,0,0,0,0,0,0,0,0,0,0,0,0,0,0,0,0}},
   {8,17,3,12,17,{64,180,144,0,0,0,0,0,0,0,0},{0,0,0,0,0,0,0,0,0,0,0},{68,228,194,235,35,44,109,200,204,202,22,211,89,209,206,222,216,0,0,0,0,0,0,0,0,0,0,0,0,0}},
   {9,17,3,42,18,{96,126,173,0,0,0,0,0,0,0,0},{1,0,0,0,0,0,0,0,0,0,0},{68,165,166,198,44,12,109,11,20,83,201,17,78,25,94,88,26,0,0,0,0,0,0,0,0,0,0,0,0,0}},
   {10,20,3,40,19,{176,115,244,0,0,0,0,0,0,0,0},{0,0,0,0,0,0,0,0,0,0,0},{131,225,226,198,35,44,12,45,203,208,201,214,210,209,221,222,213,218,223,220,0,0,0,0,0,0,0,0,0,0}},
   {11,18,4,45,20,{160,177,123,198,0,0,0,0,0,0,0},{0,0,0,0,0,0,0,0,0,0,0},{66,228,196,198,199,12,40,11,73,202,22,17,15,25,23,21,26,28,0,0,0,0,0,0,0,0,0,0,0,0}},
   {12,17,2,6,21,{127,230,0,0,0,0,0,0,0,0,0},{2,0,0,0,0,0,0,0,0,0,0},{129,233,194,198,44,8,11,45,20,9,22,17,78,207,23,21,95,0,0,0,0,0,0,0,0,0,0,0,0,0}},
   {13,18,2,4,22,{150,254,0,0,0,0,0,0,0,0,0},{0,127,0,0,0,0,0,0,0,0,0},{131,233,196,198,44,12,11,45,20,9,22,17,78,25,23,88,95,28,0,0,0,0,0,0,0,0,0,0,0,0}},
   {14,18,4,0,23,{153,146,234,253,0,0,0,0,0,0,0},{0,0,0,0,0,0,0,0,0,0,0},{131,224,234,198,8,227,236,20,237,9,22,17,15,14,23,222,26,28,0,0,0,0,0,0,0,0,0,0,0,0}},
   {15,17,2,20,24,{128,206,0,0,0,0,0,0,0,0,0},{0,0,0,0,0,0,0,0,0,0,0},{129,224,234,230,75,231,80,74,237,83,27,82,78,29,94,88,95,0,0,0,0,0,0,0,0,0,0,0,0,0}},
   {9,18,4,30,25,{80,178,121,199,0,0,0,0,0,0,0},{0,0,0,255,0,0,0,0,0,0,0},{96,106,107,7,13,104,8,16,10,91,22,79,210,29,23,21,95,28,0,0,0,0,0,0,0,0,0,0,0,0}},
   {10,17,3,4,26,{88,141,120,0,0,0,0,0,0,0,0},{1,0,0,0,0,0,0,0,0,0,0},{129,165,166,7,39,205,40,200,10,212,19,219,15,14,217,215,216,0,0,0,0,0,0,0,0,0,0,0,0,0}},
   {11,17,4,36,27,{81,218,114,214,0,0,0,0,0,0,0},{0,0,0,0,0,0,0,0,0,0,0},{129,233,226,99,13,8,109,16,20,83,27,82,78,29,94,88,95,0,0,0,0,0,0,0,0,0,0,0,0,0}},
   {12,18,2,23,28,{155,216,0,0,0,0,0,0,0,0,0},{0,0,0,0,0,0,0,0,0,0,0},{131,225,226,7,13,12,40,16,10,83,27,82,89,29,94,88,26,28,0,0,0,0,0,0,0,0,0,0,0,0}},
   {13,17,2,2,29,{181,201,0,0,0,0,0,0,0,0,0},{0,0,0,0,0,0,0,0,0,0,0},{66,225,128,7,13,8,40,16,10,83,27,82,15,29,94,21,26,0,0,0,0,0,0,0,0,0,0,0,0,0}},
   {14,17,2,25,30,{221,174,0,0,0,0,0,0,0,0,0},{0,0,0,0,0,0,0,0,0,0,0},{68,228,128,7,75,231,80,232,10,83,27,82,89,29,85,88,95,0,0,0,0,0,0,0,0,0,0,0,0,0}},
   {15,17,4,21,31,{74,137,113,215,0,0,0,0,0,0,0},{0,0,0,240,0,0,0,0,0,0,0},{68,228,128,235,35,44,84,232,73,86,81,79,89,87,85,90,92,0,0,0,0,0,0,0,0,0,0,0,0,0}},
   {9,3,6,44,255,{12,62,165,125,235,169,0,0,0,0,0},{0,0,0,0,0,0,0,0,0,0,0},{100,2,195,0,0,0,0,0,0,0,0,0,0,0,0,0,0,0,0,0,0,0,0,0,0,0,0,0,0,0}},
   {10,3,6,24,255,{31,109,75,117,233,196,0,0,0,0,0},{0,0,0,0,0,0,0,0,0,0,0},{96,106,107,0,0,0,0,0,0,0,0,0,0,0,0,0,0,0,0,0,0,0,0,0,0,0,0,0,0,0}},
   {11,4,6,35,255,{43,4,100,163,140,245,0,0,0,0,0},{0,0,0,0,0,0,0,0,0,0,0},{69,225,166,103,0,0,0,0,0,0,0,0,0,0,0,0,0,0,0,0,0,0,0,0,0,0,0,0,0,0}},
   {12,4,6,33,255,{14,49,98,66,182,175,0,0,0,0,0},{0,0,0,0,0,255,0,0,0,0,0},{68,165,166,99,0,0,0,0,0,0,0,0,0,0,0,0,0,0,0,0,0,0,0,0,0,0,0,0,0,0}},
   {13,4,5,1,255,{38,102,89,154,124,0,0,0,0,0,0},{0,0,0,0,0,0,0,0,0,0,0},{129,165,226,99,0,0,0,0,0,0,0,0,0,0,0,0,0,0,0,0,0,0,0,0,0,0,0,0,0,0}},
   {14,4,5,22,255,{47,68,159,190,225,0,0,0,0,0,0},{0,0,0,64,0,0,0,0,0,0,0},{129,233,226,77,0,0,0,0,0,0,0,0,0,0,0,0,0,0,0,0,0,0,0,0,0,0,0,0,0,0}},
   {15,4,7,9,255,{10,17,53,67,83,139,136,0,0,0,0},{0,0,0,0,0,0,0,0,0,0,0},{66,233,70,77,0,0,0,0,0,0,0,0,0,0,0,0,0,0,0,0,0,0,0,0,0,0,0,0,0,0}},
   {9,4,6,8,255,{46,58,166,118,185,228,0,0,0,0,0},{0,0,0,0,0,0,0,0,0,0,0},{105,193,197,99,0,0,0,0,0,0,0,0,0,0,0,0,0,0,0,0,0,0,0,0,0,0,0,0,0,0}},
   {10,3,7,9,255,{28,54,86,122,202,172,248,0,0,0,0},{0,0,0,0,0,0,0,0,0,0,0},{100,4,194,0,0,0,0,0,0,0,0,0,0,0,0,0,0,0,0,0,0,0,0,0,0,0,0,0,0,0}},
   {11,3,4,8,255,{23,105,92,223,0,0,0,0,0,0,0},{0,0,0,255,0,0,0,0,0,0,0},{131,165,107,0,0,0,0,0,0,0,0,0,0,0,0,0,0,0,0,0,0,0,0,0,0,0,0,0,0,0}},
   {12,3,6,46,255,{26,5,101,76,238,186,0,0,0,0,0},{0,0,0,0,0,7,0,0,0,0,0},{96,106,107,0,0,0,0,0,0,0,0,0,0,0,0,0,0,0,0,0,0,0,0,0,0,0,0,0,0,0}},
   {13,4,4,17,255,{21,103,84,147,0,0,0,0,0,0,0},{0,0,0,0,0,0,0,0,0,0,0},{96,106,166,103,0,0,0,0,0,0,0,0,0,0,0,0,0,0,0,0,0,0,0,0,0,0,0,0,0,0}},
   {14,4,5,18,255,{36,111,164,148,231,0,0,0,0,0,0},{0,0,0,0,248,0,0,0,0,0,0},{66,225,166,76,0,0,0,0,0,0,0,0,0,0,0,0,0,0,0,0,0,0,0,0,0,0,0,0,0,0}},
   {15,4,6,21,255,{13,52,91,162,219,200,0,0,0,0,0},{0,0,0,0,0,0,0,0,0,0,0},{131,225,71,76,0,0,0,0,0,0,0,0,0,0,0,0,0,0,0,0,0,0,0,0,0,0,0,0,0,0}},
   {9,4,6,1,255,{22,57,107,85,239,227,0,0,0,0,0},{0,0,0,0,224,0,0,0,0,0,0},{97,98,128,103,0,0,0,0,0,0,0,0,0,0,0,0,0,0,0,0,0,0,0,0,0,0,0,0,0,0}},
   {10,3,5,27,255,{19,55,133,149,197,0,0,0,0,0,0},{0,0,0,0,0,0,0,0,0,0,0},{105,5,128,0,0,0,0,0,0,0,0,0,0,0,0,0,0,0,0,0,0,0,0,0,0,0,0,0,0,0}},
   {11,4,6,5,255,{24,45,50,134,207,229,0,0,0,0,0},{0,0,0,0,0,0,0,0,0,0,0},{96,106,128,108,0,0,0,0,0,0,0,0,0,0,0,0,0,0,0,0,0,0,0,0,0,0,0,0,0,0}},
   {12,4,6,31,255,{27,25,61,90,222,246,0,0,0,0,0},{0,0,0,0,0,112,0,0,0,0,0},{100,5,128,103,0,0,0,0,0,0,0,0,0,0,0,0,0,0,0,0,0,0,0,0,0,0,0,0,0,0}},
   {13,3,5,13,255,{30,110,77,247,250,0,0,0,0,0,0},{0,0,0,128,0,0,0,0,0,0,0},{100,5,107,0,0,0,0,0,0,0,0,0,0,0,0,0,0,0,0,0,0,0,0,0,0,0,0,0,0,0}},
   {14,3,9,43,255,{32,34,42,1,59,78,205,187,168,0,0},{0,0,0,0,0,0,0,8,0,0,0},{69,165,107,0,0,0,0,0,0,0,0,0,0,0,0,0,0,0,0,0,0,0,0,0,0,0,0,0,0,0}},
   {15,4,6,18,255,{8,44,51,99,183,232,0,0,0,0,0},{0,0,0,0,0,0,0,0,0,0,0},{69,165,226,72,0,0,0,0,0,0,0,0,0,0,0,0,0,0,0,0,0,0,0,0,0,0,0,0,0,0}},
   {6,2,7,37,255,{33,37,70,82,179,203,243,0,0,0,0},{0,0,0,0,0,3,14,0,0,0,0},{100,34,0,0,0,0,0,0,0,0,0,0,0,0,0,0,0,0,0,0,0,0,0,0,0,0,0,0,0,0}},
   {7,8,6,47,255,{56,18,135,151,241,195,0,0,0,0,0},{0,0,0,255,0,0,0,0,0,0,0},{100,35,96,103,108,107,84,106,0,0,0,0,0,0,0,0,0,0,0,0,0,0,0,0,0,0,0,0,0,0}}},
  {{0,6,0,0},{7,64,0,0},{22,64,0,0},{11,64,0,0},{0,3,0,0},{22,64,0,0},{0,7,0,0},{0,2,0,0},{22,64,0,0},{16,64,0,0},{10,64,0,0},
   {6,64,0,0},{8,19,0,0},{7,18,0,0},{0,7,0,0},{0,2,0,0},{22,64,0,0},{16,64,0,0},{10,64,0,0},{6,64,0,0},{2,16,0,0},{0,7,0,0},
   {10,22,0,0},{7,15,0,0},{2,13,0,0},{11,64,0,0},{9,22,0,0},{0,9,0,0},{13,64,0,0},{0,5,0,0},{0,10,0,0},{0,3,0,0},{2,11,0,0},
   {7,18,0,0},{3,16,0,0},{19,64,0,0},{0,2,0,0},{18,64,0,0},{0,2,0,0},{7,64,0,0},{18,64,0,0},{0,10,0,0},{3,14,0,0},{0,8,0,0},
   {0,3,0,0},{0,10,0,0},{0,5,0,0},{19,64,0,0},{8,22,0,0},{18,64,0,0},{3,12,0,0},{5,18,0,0},{12,64,0,0},{0,8,0,0},{15,64,0,0},
   {5,14,0,0},{14,64,0,0},{10,19,0,0},{0,7,0,0},{2,11,0,0},{0,10,0,0},{10,22,0,0},{0,6,0,0},{14,64,0,0},{0,10,0,0},{0,7,0,0}},
  {{48,62,56,38,36,50,58,34,30,28,46,60,42,52,63,57,8,9,6,7,2,3,10,11,4,5,0,1,14,15,12,13,26,27,22,23,24,25,32,33,16,17,40,41,20,21,18,19,44,45,54,55,39,37,51,59,35,31,29,47,61,43,49,53},
   {38,36,51,34,31,46,61,48,53,56,37,58,35,28,47,42,49,63,57,8,9,6,7,2,3,10,11,4,5,0,1,14,15,12,13,26,27,22,23,24,25,32,33,16,17,40,41,20,21,18,19,44,45,54,55,39,50,59,30,29,60,43,52,62},
   {34,31,46,61,48,53,56,38,36,50,58,35,28,47,42,49,62,57,8,9,6,7,2,3,10,11,4,5,0,1,14,15,12,13,26,27,22,23,24,25,32,33,16,17,40,41,20,21,18,19,44,45,54,55,39,37,51,59,30,29,60,43,52,63},
   {61,47,43,63,57,49,53,8,9,4,5,2,3,6,7,10,11,0,1,12,13,14,15,26,27,24,25,16,17,22,23,32,33,40,41,20,21,38,39,54,55,18,19,44,45,34,35,30,31,28,29,50,51,36,37,58,59,60,46,42,62,56,48,52},
   {50,37,60,47,62,57,52,44,34,30,28,51,58,61,42,63,48,53,8,9,4,5,2,3,6,7,10,11,0,1,12,13,14,15,26,27,24,25,16,17,22,23,32,33,40,41,20,21,38,39,54,55,18,19,45,35,31,29,36,59,46,43,56,49},
   {57,52,51,37,59,61,47,43,56,49,53,8,9,4,5,2,3,6,7,10,11,0,1,12,13,14,15,26,27,24,25,16,17,22,23,32,33,40,41,20,21,38,39,54,55,18,19,44,45,34,35,30,31,28,29,50,36,58,60,46,42,62,63,48},
   {52,56,29,59,51,61,47,43,49,62,57,6,7,2,3,8,9,10,11,4,5,0,1,12,13,14,15,26,27,24,25,16,17,22,23,20,21,32,33,40,41,18,19,38,39,44,45,54,55,36,37,30,31,34,35,28,58,50,60,46,42,48,53,63},
   {28,58,51,61,47,43,49,53,63,57,6,7,2,3,8,9,10,11,4,5,0,1,12,13,14,15,26,27,24,25,16,17,22,23,20,21,32,33,40,41,18,19,38,39,44,45,54,55,36,37,30,31,34,35,29,59,50,60,46,42,48,52,62,56},
   {48,53,56,28,58,50,60,46,42,49,62,57,6,7,2,3,8,9,10,11,4,5,0,1,12,13,14,15,26,27,24,25,16,17,22,23,20,21,32,33,40,41,18,19,38,39,44,45,54,55,36,37,30,31,34,35,29,59,51,61,47,43,52,63},
   {60,49,42,53,56,44,54,36,34,30,28,50,58,48,47,52,63,57,4,5,2,3,10,11,6,7,8,9,0,1,12,13,14,15,26,27,24,25,16,17,22,23,32,33,18,19,40,41,20,21,38,39,45,55,37,35,31,29,51,59,61,46,43,62},
   {53,56,45,55,37,35,31,50,58,60,48,46,42,52,63,57,4,5,2,3,10,11,6,7,8,9,0,1,12,13,14,15,26,27,24,25,16,17,22,23,32,33,18,19,40,41,20,21,38,39,44,54,36,34,30,28,29,51,59,61,49,47,43,62},
   {28,50,58,60,48,46,42,52,63,57,4,5,2,3,10,11,6,7,8,9,0,1,12,13,14,15,26,27,24,25,16,17,22,23,32,33,18,19,40,41,20,21,38,39,44,45,54,55,36,37,34,35,30,31,29,51,59,61,49,47,43,53,62,56},
   {53,56,37,31,29,51,59,61,47,43,49,62,57,6,7,2,3,8,9,10,11,4,5,0,1,12,13,14,15,26,27,16,17,24,25,22,23,32,33,40,41,20,21,18,19,38,39,54,55,44,45,34,35,36,30,28,50,58,60,46,42,48,52,63},
   {55,34,37,28,51,60,42,49,62,56,19,39,44,35,31,50,59,46,43,52,63,57,6,7,2,3,8,9,10,11,4,5,0,1,12,13,14,15,26,27,16,17,24,25,22,23,32,33,40,41,20,21,18,38,54,45,36,30,29,58,61,47,48,53},
   {34,37,28,51,60,47,48,53,56,18,38,54,44,35,30,29,58,61,42,49,62,57,6,7,2,3,8,9,10,11,4,5,0,1,12,13,14,15,26,27,16,17,24,25,22,23,32,33,40,41,20,21,19,39,55,45,36,31,50,59,46,43,52,63},
   {46,48,43,63,53,57,6,7,4,5,2,3,10,11,8,9,0,1,12,13,14,15,26,27,24,25,16,17,22,23,32,33,40,41,20,21,18,19,38,39,54,55,44,45,34,35,28,29,36,37,30,31,50,51,58,59,60,61,47,49,42,62,52,56},
   {55,34,29,30,51,60,47,42,63,56,19,39,44,35,36,31,58,61,49,62,53,57,6,7,4,5,2,3,10,11,8,9,0,1,12,13,14,15,26,27,24,25,16,17,22,23,32,33,40,41,20,21,18,38,54,45,28,37,50,59,46,48,43,52},
   {30,51,60,47,42,63,56,36,31,58,61,48,43,52,57,6,7,4,5,2,3,10,11,8,9,0,1,12,13,14,15,26,27,24,25,16,17,22,23,32,33,40,41,20,21,18,19,38,39,54,55,44,45,34,35,28,29,37,50,59,46,49,62,53},
   {59,61,48,53,56,36,30,28,58,43,46,49,62,57,6,7,8,9,2,3,4,5,10,11,0,1,12,13,14,15,26,27,24,25,16,17,22,23,32,33,40,41,20,21,18,19,38,39,44,45,54,55,34,35,50,51,37,31,29,42,60,47,52,63},
   {61,47,49,53,63,57,6,7,8,9,2,3,4,5,10,11,0,1,12,13,14,15,26,27,24,25,16,17,22,23,32,33,40,41,20,21,18,19,38,39,44,45,54,55,34,35,50,51,36,37,30,31,28,29,58,59,42,43,60,46,48,52,62,56},
   {51,30,29,42,61,48,53,56,45,55,35,36,31,58,43,46,49,62,57,6,7,8,9,2,3,4,5,10,11,0,1,12,13,14,15,26,27,24,25,16,17,22,23,32,33,40,41,20,21,18,19,38,39,44,54,34,50,37,28,59,60,47,52,63},
   {49,52,56,36,30,28,50,58,46,61,43,62,53,57,4,5,6,7,2,3,8,9,10,11,0,1,12,13,14,15,26,27,24,25,16,17,22,23,32,33,40,41,20,21,18,19,38,39,54,55,44,45,34,35,37,31,29,51,59,47,60,42,48,63},
   {37,28,51,46,61,48,63,56,21,19,39,55,45,35,30,29,58,47,42,49,52,57,4,5,6,7,2,3,8,9,10,11,0,1,12,13,14,15,26,27,24,25,16,17,22,23,32,33,40,41,20,18,38,54,44,34,36,31,50,59,60,43,62,53},
   {46,60,42,49,63,53,57,4,5,6,7,2,3,8,9,10,11,0,1,12,13,14,15,26,27,24,25,16,17,22,23,32,33,40,41,20,21,18,19,38,39,54,55,44,45,34,35,36,37,30,31,28,29,50,51,58,59,47,61,43,48,62,52,56}},
  {{5,5,5,5,5,5,5,5},{2,2,1,1,0,2,2,0},{4,3,3,0,4,1,3,2},{1,1,0,3,1,0,0,3},
   {0,0,2,4,2,4,1,1},{3,4,4,2,3,3,4,4},{7,6,6,6,6,6,6,6},{6,7,7,7,7,7,7,7},
   {10,10,10,9,9,10,10,10},{15,15,5,2,5,5,5,5},{14,14,4,5,3,3,1,4},{11,11,11,11,11,11,11,11},
   {9,9,9,10,10,9,9,9},{8,8,8,8,8,8,8,8},{2,8,9,10,11,11,4,11},{8,7,10,11,10,9,11,12},
   {12,12,12,12,12,12,12,12},{7,0,11,8,8,8,8,8},{6,6,8,9,9,10,10,10},{3,16,1,1,0,2,2,0},
   {13,13,0,13,13,13,4,13},{15,13,6,6,6,6,7,7},{0,5,6,6,6,6,7,7},{13,12,4,2,5,5,5,5},
   {14,15,11,8,8,8,8,8},{1,9,12,12,12,13,9,13},{0,14,10,12,12,13,11,12},{5,4,7,7,7,7,6,6},
   {8,0,9,10,11,11,4,11},{10,10,0,13,13,12,1,4},{12,11,5,5,3,3,12,9},{7,5,12,11,10,9,9,13}},
  {{255,255,255,255,255,255,255,255},{255,255,255,255,255,255,255,255},{255,255,255,255,255,255,255,255},{255,255,255,255,255,255,255,255},
   {255,255,255,255,255,255,255,255},{255,255,255,255,255,255,255,255},{255,255,255,255,255,255,255,255},{255,255,255,255,255,255,255,255},
   {255,255,255,255,255,255,255,255},{255,255,0,5,0,0,0,0},{255,255,5,0,5,5,4,5},{255,255,255,255,255,255,255,255},
   {255,255,255,255,255,255,255,255},{255,255,255,255,255,255,255,255},{1,13,12,12,11,11,20,11},{13,7,8,11,12,12,11,16},
   {255,255,255,255,255,255,255,255},{6,4,11,13,13,13,13,13},{7,6,13,8,8,8,8,8},{5,255,1,1,1,1,1,1},
   {255,255,3,255,255,255,5,255},{9,20,22,22,22,22,22,22},{4,0,6,6,6,6,7,7},{20,16,10,9,9,9,9,9},
   {10,9,17,17,17,17,17,17},{3,12,16,16,16,20,12,20},{22,10,15,25,25,25,15,15},{0,5,7,7,7,7,6,6},
   {15,17,14,14,14,14,14,14},{8,8,20,20,20,16,10,10},{16,11,9,10,10,10,16,12},{17,22,25,15,15,15,25,25}},
  {112,113,114,115,116,117,118,119,120,121,122,123,124,125,126,127,128,129,130,131,132,133,134,135,136,137,138,139,140,141,142,143,144,145,146,147,148,149,150,151,152,153,154,155,156,157,158,159,160,161,162,163,164,165,166,167,168,169,170,171,172,173,174,175,5,383,1,179,180,181,182,183,636,386,394,37,381,77,75,43,380,44,41,79,39,8,7,2,200,3,42,374,399,647,206,207,73,209,655,211,212,213,214,215,216,217,218,219,220,221,222,223,59,89,226,83,85,81,633,400,232,46,87,84,236,82,52,47,6,4,373,630,0,654,391,639,248,48,250,13,15,11,9,642,51,656,88,14,16,12,10,49,50,405,650,80,637,78,76,661,74,72,629,38,40,36,398,279,280,98,282,92,94,90,18,55,288,289,17,395,403,371,388,404,60,56,96,22,24,20,19,303,304,305,306,93,95,91,61,311,649,313,26,315,86,641,53,393,320,321,29,323,324,325,326,327,328,660,45,651,659,627,644,335,33,30,34,27,28,631,375,343,377,345,54,347,348,349,385,351,352,57,97,23,25,21,62,58,31,361,32,363,364,365,366,367},
  {511,511,511,511,511,511,511,511,511,511,511,511,511,511,511,511,511,511,511,511,511,511,511,511,511,511,511,511,511,511,511,511,511,511,511,511,511,511,511,511,511,511,511,511,511,511,511,511,511,511,511,511,511,511,511,511,511,511,511,511,511,511,511,511,256,39,256,511,511,511,511,511,28,34,18,256,21,256,256,256,28,256,256,256,256,256,256,256,511,256,256,30,31,23,511,511,256,511,31,511,511,511,511,511,511,511,511,511,511,511,511,511,258,257,511,257,257,257,25,16,511,257,257,257,511,257,257,257,256,256,29,30,256,22,23,39,511,257,511,257,257,257,257,34,257,16,257,257,257,257,257,257,257,37,18,256,21,256,256,37,256,256,29,256,256,256,22,511,511,258,511,258,258,258,258,258,511,511,257,27,35,19,36,20,258,258,258,258,258,258,258,511,511,511,511,258,258,258,258,511,17,511,258,511,257,9,257,17,511,511,259,511,511,511,511,511,511,20,257,27,35,19,36,511,259,259,259,259,259,159,159,511,25,511,258,511,511,511,9,511,511,258,258,258,258,258,258,258,259,511,259,511,511,511,511,511}};

typedef CUresult (*EncodeFn)(CUtensorMap*, CUtensorMapDataType, cuuint32_t, void*, const cuuint64_t*, const cuuint64_t*, const cuuint32_t*,
                             const cuuint32_t*, CUtensorMapInterleave, CUtensorMapSwizzle, CUtensorMapL2promotion, CUtensorMapFloatOOBfill);

void make_map2(EncodeFn enc, CUtensorMap* m, const void* ptr, int rows, int cols, int box_rows) {
  cuuint64_t dim[2] = {(cuuint64_t)cols, (cuuint64_t)rows}, str[1] = {(cuuint64_t)cols * 2};
  cuuint32_t box[2] = {64, (cuuint32_t)box_rows}, es[2] = {1, 1};
  enc(m, CU_TENSOR_MAP_DATA_TYPE_BFLOAT16, 2, const_cast<void*>(ptr), dim, str, box, es, CU_TENSOR_MAP_INTERLEAVE_NONE, CU_TENSOR_MAP_SWIZZLE_128B,
      CU_TENSOR_MAP_L2_PROMOTION_L2_128B, CU_TENSOR_MAP_FLOAT_OOB_FILL_NONE);
}
void make_map3(EncodeFn enc, CUtensorMap* m, const void* ptr, int rows) {
  cuuint64_t dim[3] = {64, (cuuint64_t)rows, 9}, str[2] = {DM * 2, 128};
  cuuint32_t box[3] = {64, 32, 3}, es[3] = {1, 1, 1};
  enc(m, CU_TENSOR_MAP_DATA_TYPE_BFLOAT16, 3, const_cast<void*>(ptr), dim, str, box, es, CU_TENSOR_MAP_INTERLEAVE_NONE, CU_TENSOR_MAP_SWIZZLE_128B,
      CU_TENSOR_MAP_L2_PROMOTION_L2_128B, CU_TENSOR_MAP_FLOAT_OOB_FILL_NONE);
}

void make_map_t(EncodeFn enc, CUtensorMap* m, void* ptr, int width, int cols) {
  cuuint64_t dim[3] = {SEQ / 2, 2, 864}, str[2] = {SEQ * 2, SEQ * 4};
  cuuint32_t box[3] = {(cuuint32_t)width, 2, (cuuint32_t)cols}, es[3] = {1, 1, 1};
  enc(m, CU_TENSOR_MAP_DATA_TYPE_UINT32, 3, ptr, dim, str, box, es, CU_TENSOR_MAP_INTERLEAVE_NONE, cols == 64 ? CU_TENSOR_MAP_SWIZZLE_128B : CU_TENSOR_MAP_SWIZZLE_NONE,
      CU_TENSOR_MAP_L2_PROMOTION_NONE, CU_TENSOR_MAP_FLOAT_OOB_FILL_NONE);
}

int g_mode = -1;

}

extern "C" void kernel_launch(void* const* d_in, const int* in_sizes, int n_in, void* d_out, int out_size) {
  static EncodeFn enc = nullptr;
  static void* t_ptr = nullptr;
  if (!enc) {
    void* fn = nullptr;
    cudaDriverEntryPointQueryResult st;
    cudaGetDriverEntryPoint("cuTensorMapEncodeTiled", &fn, cudaEnableDefault, &st);
    enc = (EncodeFn)fn;
    cudaGetSymbolAddress(&t_ptr, g_S);
    cudaFuncSetAttribute(fused_kernel, cudaFuncAttributeMaxDynamicSharedMemorySize, SMEM_BYTES);
    if (g_mode < 0) {
      cudaLaunchConfig_t cfg = {};
      cfg.gridDim = dim3(2 * NCL); cfg.blockDim = dim3(384); cfg.dynamicSmemBytes = SMEM_BYTES;
      cudaLaunchAttribute at; at.id = cudaLaunchAttributeClusterDimension;
      at.val.clusterDim.x = 2; at.val.clusterDim.y = 1; at.val.clusterDim.z = 1;
      cfg.attrs = &at; cfg.numAttrs = 1;
      int nc = 0;
      g_mode = (cudaOccupancyMaxActiveClusters(&nc, fused_kernel, &cfg) == cudaSuccess && nc >= NCL) ? 1 : 0;
      (void)cudaGetLastError();
    }
  }
  Params p;
  make_map2(enc, &p.map_a[0], d_in[4], SEQ, DC, 128);
  make_map2(enc, &p.map_a[1], d_in[0], SEQ, DM, 128);
  make_map2(enc, &p.map_w[0], d_in[6], DC, 4096, 64);
  make_map2(enc, &p.map_w[1], d_in[7], DC, 4096, 64);
  make_map2(enc, &p.map_w[2], d_in[5], DM, 4096, 64);
  make_map2(enc, &p.map_w[3], d_in[1], DM, 1728, 64);
  make_map3(enc, &p.map_o[0], d_in[8], 4096);
  make_map3(enc, &p.map_o[1], d_in[2], DM);
  make_map_t(enc, &p.map_t[0], t_ptr, 32, 9);
  make_map_t(enc, &p.map_t[1], t_ptr, 40, 9);
  make_map_t(enc, &p.map_t[2], t_ptr, 32, 64);
  p.x = (const __nv_bfloat16*)d_in[0];
  p.gate_w = (const __nv_bfloat16*)d_in[9];
  make_map2(enc, &p.map_out, d_out, SEQ, DM, 64);
  p.out = (__nv_bfloat16*)d_out;
  p.zero = 0;
  auto launch = [&](int phases) {
    p.s = k_sched;
    for (int i = 0; i < NCL; i++) {
      Rec& r = p.s.r[i];
      if (!(phases & 1)) r.n1 = 0;
      if (!(phases & 2)) r.n2 = 0;
      if (!(phases & (p.s.task[i][1] == 64 ? 4 : 32))) r.p3 = 255;
      if (!(phases & 8)) r.bg = 255;
      const int u1 = r.n1 ? 8 + r.n1 * (8 + (r.slab >> 3)) : 0;
      int u2 = 0;
      for (int k = 0; k < r.n2; k++) u2 += 4 * (r.item[k] & 7) + 4;
      r.u1 = (uint8_t)u1; r.u2 = (uint8_t)u2;
      r.rot = (uint8_t)(((u1 % 10 + 1) >> 1) % 5);
      r.x3 = (uint8_t)((r.rot + u2) % 5 & 3);
      r.phases = (uint8_t)phases;
    }
    if (!(phases & 16))
      for (int i = 0; i < 256; i++) { p.s.slot[i >> 3][i & 7] = (uint8_t)(i >> 3); p.s.prev[i >> 3][i & 7] = 255; p.s.qblk[i] = (uint16_t)(S_Q + i); p.s.qdep[i] = 511; }
    fused_kernel<<<2 * NCL, 384, SMEM_BYTES>>>(p);
  };
  if (g_mode == 1) launch(63);
  else { launch(1); launch(10); launch(4); launch(32); }
}
```

```cpp
#include <cuda_runtime.h>
#include <cuda_bf16.h>
#include <cuda.h>
#include <stdint.h>

namespace {

constexpr int SEQ = 2048, DM = 576, DC = 512, NH = 32;
constexpr int NCL = 66;
constexpr uint32_t DESC_HI = 0x40000040u;

constexpr int SM_RING = 0;
constexpr int SM_BUF = 163840;
constexpr int SM_BAR = 229376;
constexpr int B_P1E = 0, B_P2E = 10, B_P3E = 15, B_P2F = 24, B_SF = 32, B_ORD = 36, B_LAD = 40, B_DONE = 41, B_FIN = 48;
constexpr int B_P3F = 56, B_OUT = 61, B_ZF = 62, B_P1F = 64, B_SE = 74, B_QF = 80, B_LA = 84, B_NUM = 88;
constexpr uint64_t B_CNT = 0x11118245000ull;
constexpr int SMEM_BYTES = SM_BAR + B_NUM * 8 + 1024;

constexpr int F_QKVA = 32;
constexpr int F_GATE = 64;
constexpr int F_TS = 68;
constexpr int F_DONE = 65;
constexpr int F_CTX = 96;
constexpr int F_OUT = 96 + 8 * 64;
constexpr int F_KV = F_OUT + 64;
constexpr int F_Q = F_KV + 256;
constexpr int F_RD = F_Q + 256;
constexpr int F_NUM = F_RD + 256;

struct Rec {
  uint8_t slab;
  uint8_t n1, n2;
  uint8_t p3;
  uint8_t bg;
  uint8_t item[11];
  uint8_t last[11];
  uint8_t tile[32];
  uint8_t u1, u2;
  uint8_t rot, x3;
  uint8_t phases;
};
struct Sched {
  Rec r[NCL];
  uint8_t task[NCL][4];
  uint8_t p3_order[24][64];
  uint8_t slot[32][8];
  uint8_t prev[32][8];
  uint16_t qblk[256];
  uint16_t qdep[256];
};


struct Params {
  CUtensorMap map_a[2];
  CUtensorMap map_w[4];
  CUtensorMap map_o[2];
  CUtensorMap map_t[3];
  CUtensorMap map_out;
  const __nv_bfloat16* x;
  const __nv_bfloat16* gate_w;
  __nv_bfloat16* out;
  int zero;
  alignas(64) Sched s;
};

constexpr int S_Q = 112, S_K = S_Q + 256, S_V = S_K + 256, S_NUM = S_V + 256;
__device__ __align__(1024) uint8_t g_S[(size_t)S_NUM * 65536];
__device__ __align__(1024) uint8_t g_oA[32 * 576 * 128];
__device__ float g_gate[SEQ];
__device__ int g_flags[F_NUM];

__device__ __forceinline__ void mbar_arrive(uint32_t b) { asm volatile("mbarrier.arrive.shared::cta.b64 _, [%0];" ::"r"(b) : "memory"); }
__device__ __forceinline__ void mbar_arrive_cl(uint32_t b, int cnt) {
  asm volatile("mbarrier.arrive.shared::cluster.b64 _, [%0], %1;" ::"r"(b), "r"(cnt) : "memory");
}
__device__ __forceinline__ void mbar_wait(uint32_t b, int par) {
  asm volatile(
      "{\n.reg .pred p;\n.reg .u32 c;\n"
      "mbarrier.try_wait.parity.shared::cta.b64 p, [%0], %1;\n@p bra DN;\nmov.u32 c, 0;\n"
      "LP:\nmbarrier.try_wait.parity.shared::cta.b64 p, [%0], %1;\n@p bra DN;\n"
      "add.u32 c, c, 1;\nsetp.lt.u32 p, c, 4000000;\n@p bra LP;\ntrap;\nDN:\n}" ::"r"(b), "r"(par) : "memory");
}
__device__ __forceinline__ bool mbar_test(uint32_t b, int par) {
  uint32_t ok;
  asm volatile("{\n.reg .pred p;\nmbarrier.test_wait.parity.shared::cta.b64 p, [%1], %2;\nselp.u32 %0, 1, 0, p;\n}" : "=r"(ok) : "r"(b), "r"(par) : "memory");
  return __all_sync(0xffffffffu, ok);
}
__device__ __forceinline__ uint32_t mapa(uint32_t a, uint32_t cta) {
  uint32_t r; asm("mapa.shared::cluster.u32 %0, %1, %2;" : "=r"(r) : "r"(a), "r"(cta)); return r;
}
#define ELECT(ins) "{\n.reg .pred e;\nelect.sync _|e, 0xffffffff;\n@e " ins "\n}"
__device__ __forceinline__ void mbar_expect(uint32_t b, int bytes) {
  asm volatile(ELECT("mbarrier.arrive.expect_tx.shared::cta.b64 _, [%0], %1;") ::"r"(b), "r"(bytes) : "memory");
}
__device__ __forceinline__ void mbar_arrive_one(uint32_t b) { asm volatile(ELECT("mbarrier.arrive.shared::cta.b64 _, [%0];") ::"r"(b) : "memory"); }
constexpr uint64_t L2_NORMAL = 0x1000000000000000ull, L2_FIRST = 0x12F0000000000000ull;
__device__ __forceinline__ void bulk_load(uint32_t dst, const void* src, int bytes, uint32_t bar, uint64_t pol = L2_NORMAL) {
  asm volatile(ELECT("cp.async.bulk.shared::cluster.global.mbarrier::complete_tx::bytes.L2::cache_hint [%0], [%1], %2, [%3], %4;") ::"r"(dst), "l"(src), "r"(bytes), "r"(bar), "l"(pol) : "memory");
}
__device__ __forceinline__ void bulk_load_mc(uint32_t dst, const void* src, int bytes, uint32_t bar, uint64_t pol = L2_NORMAL) {
  asm volatile(ELECT("cp.async.bulk.shared::cluster.global.mbarrier::complete_tx::bytes.multicast::cluster.L2::cache_hint [%0], [%1], %2, [%3], %4, %5;") ::"r"(dst), "l"(src), "r"(bytes), "r"(bar), "h"((uint16_t)3), "l"(pol) : "memory");
}
__device__ __forceinline__ void bulk_store(void* dst, uint32_t src, int bytes, uint64_t pol = L2_NORMAL) {
  asm volatile(ELECT("cp.async.bulk.global.shared::cta.bulk_group.L2::cache_hint [%0], [%1], %2, %3;") ::"l"(dst), "r"(src), "r"(bytes), "l"(pol) : "memory");
}
__device__ __forceinline__ void tma2d(uint32_t dst, const CUtensorMap* m, int c0, int c1, uint32_t bar, uint64_t pol = L2_NORMAL) {
  asm volatile(ELECT("cp.async.bulk.tensor.2d.shared::cluster.global.mbarrier::complete_tx::bytes.L2::cache_hint [%0], [%1, {%3, %4}], [%2], %5;") ::"r"(dst), "l"(m), "r"(bar), "r"(c0), "r"(c1), "l"(pol) : "memory");
}
__device__ __forceinline__ void tma2d_mc(uint32_t dst, const CUtensorMap* m, int c0, int c1, uint32_t bar, uint64_t pol = L2_NORMAL) {
  asm volatile(ELECT("cp.async.bulk.tensor.2d.shared::cluster.global.mbarrier::complete_tx::bytes.multicast::cluster.L2::cache_hint [%0], [%1, {%3, %4}], [%2], %5, %6;") ::"r"(dst), "l"(m), "r"(bar), "r"(c0), "r"(c1), "h"((uint16_t)3), "l"(pol) : "memory");
}
__device__ __forceinline__ void tma3d(uint32_t dst, const CUtensorMap* m, int c0, int c1, int c2, uint32_t bar, uint64_t pol = L2_NORMAL) {
  asm volatile(ELECT("cp.async.bulk.tensor.3d.shared::cluster.global.mbarrier::complete_tx::bytes.L2::cache_hint [%0], [%1, {%3, %4, %5}], [%2], %6;") ::"r"(dst), "l"(m), "r"(bar), "r"(c0), "r"(c1), "r"(c2), "l"(pol) : "memory");
}
__device__ __forceinline__ void tma3d_mc(uint32_t dst, const CUtensorMap* m, int c0, int c1, int c2, uint32_t bar, uint64_t pol = L2_NORMAL) {
  asm volatile(ELECT("cp.async.bulk.tensor.3d.shared::cluster.global.mbarrier::complete_tx::bytes.multicast::cluster.L2::cache_hint [%0], [%1, {%3, %4, %5}], [%2], %6, %7;") ::"r"(dst), "l"(m), "r"(bar), "r"(c0), "r"(c1), "r"(c2), "h"((uint16_t)3), "l"(pol) : "memory");
}
__device__ __forceinline__ void tma2d_add(const CUtensorMap* m, uint32_t src, int c0, int c1) {
  asm volatile(ELECT("cp.reduce.async.bulk.tensor.2d.global.shared::cta.add.bulk_group [%0, {%2, %3}], [%1];") ::"l"(m), "r"(src), "r"(c0), "r"(c1) : "memory");
}
__device__ __forceinline__ void tma3d_store(const CUtensorMap* m, uint32_t src, int c0, int c1, int c2, uint64_t pol = L2_NORMAL) {
  asm volatile(ELECT("cp.async.bulk.tensor.3d.global.shared::cta.bulk_group.L2::cache_hint [%0, {%2, %3, %4}], [%1], %5;") ::"l"(m), "r"(src), "r"(c0), "r"(c1), "r"(c2), "l"(pol) : "memory");
}
__device__ __forceinline__ void tma2d_prefetch(const CUtensorMap* m, int c0, int c1, uint64_t pol = L2_NORMAL) {
  asm volatile(ELECT("cp.async.bulk.prefetch.tensor.2d.L2.global.L2::cache_hint [%0, {%1, %2}], %3;") ::"l"(m), "r"(c0), "r"(c1), "l"(pol) : "memory");
}
#define LAG 3
#define HINT 63
#define POL(bit) ((HINT >> (bit)) & 1 ? L2_FIRST : L2_NORMAL)
#define BULK_COMMIT() asm volatile("cp.async.bulk.commit_group;" ::: "memory")
#define BULK_WAIT(n) asm volatile("cp.async.bulk.wait_group %0;" ::"n"(n) : "memory")
#define BULK_WAIT_READ(n) asm volatile("cp.async.bulk.wait_group.read %0;" ::"n"(n) : "memory")
#define FENCE_ASYNC_SMEM() asm volatile("fence.proxy.async.shared::cta;" ::: "memory")
#define WG_FENCE() asm volatile("wgmma.fence.sync.aligned;" ::: "memory")
#define WG_COMMIT() asm volatile("wgmma.commit_group.sync.aligned;" ::: "memory")
#define WG_WAIT(n) asm volatile("wgmma.wait_group.sync.aligned %0;" ::"n"(n) : "memory")
__device__ __forceinline__ void bar_sync(int id, int n) { asm volatile("bar.sync %0, %1;" ::"r"(id), "r"(n) : "memory"); }
__device__ __forceinline__ void bar_arrive(int id, int n) { asm volatile("bar.arrive %0, %1;" ::"r"(id), "r"(n) : "memory"); }
__device__ __forceinline__ void cluster_sync() {
  asm volatile("barrier.cluster.arrive.relaxed;\nbarrier.cluster.wait.acquire;" ::: "memory");
}
template <int N> __device__ __forceinline__ void pin(float (&r)[N]) {
#pragma unroll
  for (int i = 0; i < N; i++) asm volatile("" : "+f"(r[i])::"memory");
}
template <int N> __device__ __forceinline__ void pin(uint32_t (&r)[N]) {
#pragma unroll
  for (int i = 0; i < N; i++) asm volatile("" : "+r"(r[i])::"memory");
}
__device__ __forceinline__ uint32_t pack_bf16(float lo, float hi) {
  uint32_t r; asm("cvt.rn.bf16x2.f32 %0, %1, %2;" : "=r"(r) : "f"(hi), "f"(lo)); return r;
}
__device__ __forceinline__ float ex2(float x) { float r; asm("ex2.approx.ftz.f32 %0, %1;" : "=f"(r) : "f"(x)); return r; }
__device__ __forceinline__ void ldsm4(uint32_t a, uint32_t& r0, uint32_t& r1, uint32_t& r2, uint32_t& r3) {
  asm volatile("ldmatrix.sync.aligned.m8n8.x4.shared.b16 {%0,%1,%2,%3}, [%4];" : "=r"(r0), "=r"(r1), "=r"(r2), "=r"(r3) : "r"(a) : "memory");
}
__device__ __forceinline__ void stsm4(uint32_t a, uint32_t r0, uint32_t r1, uint32_t r2, uint32_t r3) {
  asm volatile("stmatrix.sync.aligned.m8n8.x4.shared.b16 [%0], {%1,%2,%3,%4};" ::"r"(a), "r"(r0), "r"(r1), "r"(r2), "r"(r3) : "memory");
}
__device__ __forceinline__ void flag_add(int idx, int v = 1) {
  asm volatile(ELECT("red.release.gpu.global.add.s32 [%0], %1;") ::"l"(g_flags + idx), "r"(v) : "memory");
}
__device__ __forceinline__ void flag_add_rx(int idx, int v = 1) {
  asm volatile(ELECT("red.relaxed.gpu.global.add.s32 [%0], %1;") ::"l"(g_flags + idx), "r"(v) : "memory");
}
template <bool ACQ, int NS = 32> __device__ __forceinline__ void flag_wait(int idx, int target) {
  int n = 0;
  while (true) {
    int v;
    if (ACQ) asm volatile("ld.acquire.gpu.global.s32 %0, [%1];" : "=r"(v) : "l"(g_flags + idx) : "memory");
    else asm volatile("ld.relaxed.gpu.global.s32 %0, [%1];" : "=r"(v) : "l"(g_flags + idx) : "memory");
    if (__all_sync(0xffffffffu, v >= target)) break;
    if (++n > 20000000) __trap();
    __nanosleep(NS);
  }
}
__device__ __forceinline__ int flag_peek(int idx) {
  int v;
  asm volatile("ld.relaxed.gpu.global.s32 %0, [%1];" : "=r"(v) : "l"(g_flags + idx) : "memory");
  return v;
}
__device__ __forceinline__ void mask_wait(uint32_t& ready, int bit, int idx, int target) {
  for (int n = 0; !((ready >> bit) & 1); n++) {
    int v;
    if (n) { __nanosleep(32); if (n > 20000000) __trap(); }
    asm volatile("ld.relaxed.gpu.global.s32 %0, [%1];" : "=r"(v) : "l"(g_flags + idx) : "memory");
    ready = __ballot_sync(0xffffffffu, v >= target);
  }
}
__device__ __forceinline__ uint32_t desc_lo(uint32_t addr, uint32_t lbo) { return ((addr & 0x3FFFFu) >> 4) | ((lbo >> 4) << 16); }

template <int TB, int TA = 0> __device__ __forceinline__ void wgmma_ss64(float (&d)[32], uint32_t alo, uint32_t blo, int sd) {
  asm volatile("{\n.reg .pred p;\n.reg .b64 da, db;\n"
    "setp.ne.b32 p, %34, 0;\nmov.b64 da, {%32, %36};\nmov.b64 db, {%33, %36};\n"
    "wgmma.mma_async.sync.aligned.m64n64k16.f32.bf16.bf16 "
    "{%0,%1,%2,%3,%4,%5,%6,%7,%8,%9,%10,%11,%12,%13,%14,%15,%16,%17,%18,%19,%20,%21,%22,%23,"
    "%24,%25,%26,%27,%28,%29,%30,%31}, "
    "da, db, p, 1, 1, %37, %35;\n}\n"
    : "+f"(d[0]),"+f"(d[1]),"+f"(d[2]),"+f"(d[3]),"+f"(d[4]),"+f"(d[5]),"+f"(d[6]),"+f"(d[7]),"+f"(d[8]),"+f"(d[9]),"+f"(d[10]),"+f"(d[11]),
      "+f"(d[12]),"+f"(d[13]),"+f"(d[14]),"+f"(d[15]),"+f"(d[16]),"+f"(d[17]),"+f"(d[18]),"+f"(d[19]),"+f"(d[20]),"+f"(d[21]),"+f"(d[22]),"+f"(d[23]),
      "+f"(d[24]),"+f"(d[25]),"+f"(d[26]),"+f"(d[27]),"+f"(d[28]),"+f"(d[29]),"+f"(d[30]),"+f"(d[31])
    : "r"(alo), "r"(blo), "r"(sd), "n"(TB), "r"(DESC_HI), "n"(TA));
}
template <int TB, int TA = 0> __device__ __forceinline__ void wgmma_ss128(float (&d)[64], uint32_t alo, uint32_t blo, int sd) {
  asm volatile("{\n.reg .pred p;\n.reg .b64 da, db;\n"
    "setp.ne.b32 p, %66, 0;\nmov.b64 da, {%64, %68};\nmov.b64 db, {%65, %68};\n"
    "wgmma.mma_async.sync.aligned.m64n128k16.f32.bf16.bf16 "
    "{%0,%1,%2,%3,%4,%5,%6,%7,%8,%9,%10,%11,%12,%13,%14,%15,%16,%17,%18,%19,%20,%21,%22,%23,"
    "%24,%25,%26,%27,%28,%29,%30,%31,%32,%33,%34,%35,%36,%37,%38,%39,%40,%41,%42,%43,%44,%45,%46,%47,"
    "%48,%49,%50,%51,%52,%53,%54,%55,%56,%57,%58,%59,%60,%61,%62,%63}, "
    "da, db, p, 1, 1, %69, %67;\n}\n"
    : "+f"(d[0]),"+f"(d[1]),"+f"(d[2]),"+f"(d[3]),"+f"(d[4]),"+f"(d[5]),"+f"(d[6]),"+f"(d[7]),"+f"(d[8]),"+f"(d[9]),"+f"(d[10]),"+f"(d[11]),
      "+f"(d[12]),"+f"(d[13]),"+f"(d[14]),"+f"(d[15]),"+f"(d[16]),"+f"(d[17]),"+f"(d[18]),"+f"(d[19]),"+f"(d[20]),"+f"(d[21]),"+f"(d[22]),"+f"(d[23]),
      "+f"(d[24]),"+f"(d[25]),"+f"(d[26]),"+f"(d[27]),"+f"(d[28]),"+f"(d[29]),"+f"(d[30]),"+f"(d[31]),"+f"(d[32]),"+f"(d[33]),"+f"(d[34]),"+f"(d[35]),
      "+f"(d[36]),"+f"(d[37]),"+f"(d[38]),"+f"(d[39]),"+f"(d[40]),"+f"(d[41]),"+f"(d[42]),"+f"(d[43]),"+f"(d[44]),"+f"(d[45]),"+f"(d[46]),"+f"(d[47]),
      "+f"(d[48]),"+f"(d[49]),"+f"(d[50]),"+f"(d[51]),"+f"(d[52]),"+f"(d[53]),"+f"(d[54]),"+f"(d[55]),"+f"(d[56]),"+f"(d[57]),"+f"(d[58]),"+f"(d[59]),
      "+f"(d[60]),"+f"(d[61]),"+f"(d[62]),"+f"(d[63])
    : "r"(alo), "r"(blo), "r"(sd), "n"(TB), "r"(DESC_HI), "n"(TA));
}
template <int TB> __device__ __forceinline__ void wgmma_rs128(float (&d)[64], uint32_t a0, uint32_t a1, uint32_t a2, uint32_t a3, uint32_t blo, int sd) {
  asm volatile("{\n.reg .pred p;\n.reg .b64 db;\n"
    "setp.ne.b32 p, %69, 0;\nmov.b64 db, {%68, %71};\n"
    "wgmma.mma_async.sync.aligned.m64n128k16.f32.bf16.bf16 "
    "{%0,%1,%2,%3,%4,%5,%6,%7,%8,%9,%10,%11,%12,%13,%14,%15,%16,%17,%18,%19,%20,%21,%22,%23,"
    "%24,%25,%26,%27,%28,%29,%30,%31,%32,%33,%34,%35,%36,%37,%38,%39,%40,%41,%42,%43,%44,%45,%46,%47,"
    "%48,%49,%50,%51,%52,%53,%54,%55,%56,%57,%58,%59,%60,%61,%62,%63}, "
    "{%64,%65,%66,%67}, db, p, 1, 1, %70;\n}\n"
    : "+f"(d[0]),"+f"(d[1]),"+f"(d[2]),"+f"(d[3]),"+f"(d[4]),"+f"(d[5]),"+f"(d[6]),"+f"(d[7]),"+f"(d[8]),"+f"(d[9]),"+f"(d[10]),"+f"(d[11]),
      "+f"(d[12]),"+f"(d[13]),"+f"(d[14]),"+f"(d[15]),"+f"(d[16]),"+f"(d[17]),"+f"(d[18]),"+f"(d[19]),"+f"(d[20]),"+f"(d[21]),"+f"(d[22]),"+f"(d[23]),
      "+f"(d[24]),"+f"(d[25]),"+f"(d[26]),"+f"(d[27]),"+f"(d[28]),"+f"(d[29]),"+f"(d[30]),"+f"(d[31]),"+f"(d[32]),"+f"(d[33]),"+f"(d[34]),"+f"(d[35]),
      "+f"(d[36]),"+f"(d[37]),"+f"(d[38]),"+f"(d[39]),"+f"(d[40]),"+f"(d[41]),"+f"(d[42]),"+f"(d[43]),"+f"(d[44]),"+f"(d[45]),"+f"(d[46]),"+f"(d[47]),
      "+f"(d[48]),"+f"(d[49]),"+f"(d[50]),"+f"(d[51]),"+f"(d[52]),"+f"(d[53]),"+f"(d[54]),"+f"(d[55]),"+f"(d[56]),"+f"(d[57]),"+f"(d[58]),"+f"(d[59]),
      "+f"(d[60]),"+f"(d[61]),"+f"(d[62]),"+f"(d[63])
    : "r"(a0), "r"(a1), "r"(a2), "r"(a3), "r"(blo), "r"(sd), "n"(TB), "r"(DESC_HI));
}
template <int TB, int TA = 0> __device__ __forceinline__ void wgmma_ss192(float (&d)[96], uint32_t alo, uint32_t blo, int sd) {
  asm volatile("{\n.reg .pred p;\n.reg .b64 da, db;\n"
    "setp.ne.b32 p, %98, 0;\nmov.b64 da, {%96, %100};\nmov.b64 db, {%97, %100};\n"
    "wgmma.mma_async.sync.aligned.m64n192k16.f32.bf16.bf16 "
    "{%0,%1,%2,%3,%4,%5,%6,%7,%8,%9,%10,%11,%12,%13,%14,%15,%16,%17,%18,%19,%20,%21,%22,%23,"
    "%24,%25,%26,%27,%28,%29,%30,%31,%32,%33,%34,%35,%36,%37,%38,%39,%40,%41,%42,%43,%44,%45,%46,%47,"
    "%48,%49,%50,%51,%52,%53,%54,%55,%56,%57,%58,%59,%60,%61,%62,%63,%64,%65,%66,%67,%68,%69,%70,%71,"
    "%72,%73,%74,%75,%76,%77,%78,%79,%80,%81,%82,%83,%84,%85,%86,%87,%88,%89,%90,%91,%92,%93,%94,%95}, "
    "da, db, p, 1, 1, %101, %99;\n}\n"
    : "+f"(d[0]),"+f"(d[1]),"+f"(d[2]),"+f"(d[3]),"+f"(d[4]),"+f"(d[5]),"+f"(d[6]),"+f"(d[7]),"+f"(d[8]),"+f"(d[9]),"+f"(d[10]),"+f"(d[11]),
      "+f"(d[12]),"+f"(d[13]),"+f"(d[14]),"+f"(d[15]),"+f"(d[16]),"+f"(d[17]),"+f"(d[18]),"+f"(d[19]),"+f"(d[20]),"+f"(d[21]),"+f"(d[22]),"+f"(d[23]),
      "+f"(d[24]),"+f"(d[25]),"+f"(d[26]),"+f"(d[27]),"+f"(d[28]),"+f"(d[29]),"+f"(d[30]),"+f"(d[31]),"+f"(d[32]),"+f"(d[33]),"+f"(d[34]),"+f"(d[35]),
      "+f"(d[36]),"+f"(d[37]),"+f"(d[38]),"+f"(d[39]),"+f"(d[40]),"+f"(d[41]),"+f"(d[42]),"+f"(d[43]),"+f"(d[44]),"+f"(d[45]),"+f"(d[46]),"+f"(d[47]),
      "+f"(d[48]),"+f"(d[49]),"+f"(d[50]),"+f"(d[51]),"+f"(d[52]),"+f"(d[53]),"+f"(d[54]),"+f"(d[55]),"+f"(d[56]),"+f"(d[57]),"+f"(d[58]),"+f"(d[59]),
      "+f"(d[60]),"+f"(d[61]),"+f"(d[62]),"+f"(d[63]),"+f"(d[64]),"+f"(d[65]),"+f"(d[66]),"+f"(d[67]),"+f"(d[68]),"+f"(d[69]),"+f"(d[70]),"+f"(d[71]),
      "+f"(d[72]),"+f"(d[73]),"+f"(d[74]),"+f"(d[75]),"+f"(d[76]),"+f"(d[77]),"+f"(d[78]),"+f"(d[79]),"+f"(d[80]),"+f"(d[81]),"+f"(d[82]),"+f"(d[83]),
      "+f"(d[84]),"+f"(d[85]),"+f"(d[86]),"+f"(d[87]),"+f"(d[88]),"+f"(d[89]),"+f"(d[90]),"+f"(d[91]),"+f"(d[92]),"+f"(d[93]),"+f"(d[94]),"+f"(d[95])
    : "r"(alo), "r"(blo), "r"(sd), "n"(TB), "r"(DESC_HI), "n"(TA));
}

struct Ctx {
  uint32_t sm;
  uint32_t bar;
  uint32_t rbar;
  int cl, rank, wg, warp, lane, phases;
};
__device__ __forceinline__ void release(const Ctx& c, int b, int cnt = 1) {
  if (c.lane < 2) mbar_arrive_cl(c.rbar + b * 8, cnt);
}
#define HK 5
#define NPRO 6
#define ZLEAD 16
#define PFM 7
#define PF1 1
constexpr float SM_SCALE = 0.08838834764831845f * 1.4426950408889634f;
constexpr float SM_HI = 1.8446744e19f, SM_LO = 5.4210109e-20f;
constexpr int ORDER = 1;

__device__ __forceinline__ void stage_tile(const float (&a)[64], uint32_t buf, const Ctx& c, float s0, float s1) {
  const int row = (c.lane & 7) + ((c.lane >> 3) & 1) * 8;
  const uint32_t base = buf + (c.warp * 16 + row) * 128 + (((c.lane >> 4) ^ (row & 7)) << 4);
#pragma unroll
  for (int i = 0; i < 8; i++)
    stsm4((base ^ ((i & 3) << 5)) + (i >> 2) * 8192, pack_bf16(a[8 * i] * s0, a[8 * i + 1] * s0), pack_bf16(a[8 * i + 2] * s1, a[8 * i + 3] * s1),
          pack_bf16(a[8 * i + 4] * s0, a[8 * i + 5] * s0), pack_bf16(a[8 * i + 6] * s1, a[8 * i + 7] * s1));
}

__device__ __forceinline__ void p1_epilogue(const Params& p, const Ctx& c, const float (&acc)[64], int t, int type) {
  const int tile = p.s.r[c.cl].tile[t] & 63, b = c.wg * 2 + 1;
  mbar_wait(c.bar + (B_SE + b) * 8, (t & 1) ^ 1);
  if (type && tile >= 32) {
    const int r = 2 * (c.lane & 3) + ((c.lane >> 2) & 1);
    const uint32_t dst = c.sm + SM_BUF + b * 16384 + r * 128 + (((c.warp * 2) ^ r) << 4) + (c.lane >> 3) * 4;
#pragma unroll
    for (int i = 0; i < 16; i++) {
      asm volatile("st.shared.u32 [%0], %1;" ::"r"(dst + i * 1024), "r"(pack_bf16(acc[4 * i], acc[4 * i + 1])) : "memory");
      asm volatile("st.shared.u32 [%0], %1;" ::"r"((dst ^ 16) + i * 1024), "r"(pack_bf16(acc[4 * i + 2], acc[4 * i + 3])) : "memory");
    }
  } else {
    if (type) stage_tile(acc, c.sm + SM_BUF + b * 16384, c, SM_SCALE, SM_SCALE);
    else stage_tile(acc, c.sm + SM_BUF + b * 16384, c, 1.f, 1.f);
  }
  FENCE_ASYNC_SMEM();
  __syncwarp();
  if (c.lane == 0) mbar_arrive(c.bar + (B_SF + b) * 8);
}

__device__ __forceinline__ void p1_consumer(const Params& p, const Ctx& c) {
  const int n = p.s.r[c.cl].n1;
  const int type = p.s.r[c.cl].slab >> 3;
  const uint32_t bdesc = desc_lo(c.sm + SM_RING, 8192), adesc = desc_lo(c.sm + SM_BUF + 32768 + c.wg * 8192, 16);
  uint32_t A[128];
  float acc[64] = {};
  int slot = 0, par = 0;
  auto next = [&]() { if (++slot == 10) { slot = 0; par ^= 1; } };
  {
    const int row = (c.lane & 7) + ((c.lane >> 3) & 1) * 8;
    const uint32_t base = c.sm + SM_RING + (c.wg * 64 + c.warp * 16 + row) * 128 + (((c.lane >> 4) ^ (row & 7)) << 4);
    if (c.wg == 1) bar_sync(ORDER + 1, 256);
    int pa = -1, pb = -1;
    if (type) {
      mbar_wait(c.bar + B_P1F * 8, 0);
      WG_FENCE();
#pragma unroll
      for (int kk = 0; kk < 4; kk++) wgmma_ss128<1>(acc, adesc + kk * 2, bdesc + kk * 128, kk != 0);
      WG_COMMIT();
      pb = 0; slot = 1;
    }
#pragma unroll
    for (int kb = 0; kb < 8; kb++) {
      const int sa = slot;
      mbar_wait(c.bar + (B_P1F + slot) * 8, par);
      next();
      mbar_wait(c.bar + (B_P1F + slot) * 8, par);
      WG_FENCE();
#pragma unroll
      for (int kk = 0; kk < 4; kk++)
        wgmma_ss128<1>(acc, desc_lo(c.sm + SM_RING + c.wg * 8192, 16) + sa * 1024 + kk * 2, bdesc + slot * 1024 + kk * 128, (kb | kk) != 0 ? 1 : type);
      WG_COMMIT();
      if (kb == 1 && c.wg == 0) bar_arrive(ORDER + 1, 256);
#pragma unroll
      for (int kk = 0; kk < 4; kk++) ldsm4((base ^ (kk << 5)) + sa * 16384, A[kb * 16 + kk * 4], A[kb * 16 + kk * 4 + 1], A[kb * 16 + kk * 4 + 2], A[kb * 16 + kk * 4 + 3]);
      WG_WAIT(1);
      if (kb > 0) release(c, B_P1E + pa);
      if (kb > 0 || pb >= 0) release(c, B_P1E + pb);
      pa = sa; pb = slot;
      next();
    }
    WG_WAIT(0);
    __syncwarp();
    release(c, B_P1E + pa);
    release(c, B_P1E + pb);
    pin(acc);
    p1_epilogue(p, c, acc, 0, type);
  }
  for (int t = 1; t < n; t++) {
    bar_sync(ORDER + c.wg, 256);
    int prev1 = -1, prev2 = -1;
    if (type) {
      mbar_wait(c.bar + (B_P1F + slot) * 8, par);
      WG_FENCE();
#pragma unroll
      for (int kk = 0; kk < 4; kk++) wgmma_ss128<1>(acc, adesc + kk * 2, bdesc + slot * 1024 + kk * 128, kk != 0);
      WG_COMMIT();
      prev1 = slot;
      next();
    }
#pragma unroll
    for (int kb = 0; kb < 8; kb++) {
      mbar_wait(c.bar + (B_P1F + slot) * 8, par);
      WG_FENCE();
      const uint32_t d = bdesc + slot * 1024;
#pragma unroll
      for (int kk = 0; kk < 4; kk++)
        wgmma_rs128<1>(acc, A[kb * 16 + kk * 4], A[kb * 16 + kk * 4 + 1], A[kb * 16 + kk * 4 + 2], A[kb * 16 + kk * 4 + 3], d + kk * 128, (kb | kk) != 0 ? 1 : type);
      WG_COMMIT();
      if (kb == HK) {
        if (t + 1 < n || c.wg == 0) bar_arrive(ORDER + (c.wg ^ 1), 256);
      }
      if (kb > 0) { WG_WAIT(2); if (kb > 1 || prev2 >= 0) release(c, B_P1E + prev2); }
      prev2 = prev1; prev1 = slot;
      next();
    }
    WG_WAIT(1);
    release(c, B_P1E + prev2);
    WG_WAIT(0);
    pin(acc);
    release(c, B_P1E + prev1);
    p1_epilogue(p, c, acc, t, type);
  }
}

__device__ __forceinline__ void p1_producer(const Params& p, const Ctx& c) {
  const int n = p.s.r[c.cl].n1;
  const int type = p.s.r[c.cl].slab >> 3, grp = p.s.r[c.cl].slab & 7;
  int slot = NPRO % 10, par = NPRO < 10;
#pragma unroll 1
  for (int t = 0; t < n; t++) {
    const int tile = p.s.r[c.cl].tile[t] & 63;
    const CUtensorMap* m = &p.map_w[type * 2 + (tile >> 5)];
    const int n0 = (tile & 31) * 128 + c.rank * 64;
    const uint64_t pol = p.s.r[c.cl].tile[t] >= 192 ? POL(0) : L2_NORMAL;
    const int ptile = p.s.r[c.cl].tile[t + PF1 < n ? t + PF1 : t];
    const CUtensorMap* pm = &p.map_w[type * 2 + ((ptile >> 5) & 1)];
    if (t == 7 && (c.phases & 16)) flag_wait<true>(F_GATE, 256);
#pragma unroll 1
    for (int kb = t ? -type : (NPRO - type) >> 1; kb < 8; kb++) {
      if (t == 0 && 2 * kb + type >= NPRO) {
        mbar_wait(c.bar + (B_P1E + slot) * 8, par);
        mbar_expect(c.bar + (B_P1F + slot) * 8, 16384);
        tma2d(c.sm + SM_RING + slot * 16384, &p.map_a[type], kb * 64, grp * 256 + c.rank * 128, c.bar + (B_P1F + slot) * 8);
        if (++slot == 10) { slot = 0; par ^= 1; }
      }
      mbar_wait(c.bar + (B_P1E + slot) * 8, par);
      mbar_expect(c.bar + (B_P1F + slot) * 8, 16384);
      tma2d_mc(c.sm + SM_RING + slot * 16384 + c.rank * 8192, m, n0, kb < 0 ? 512 : kb * 64, c.bar + (B_P1F + slot) * 8, pol);
      if (t + PF1 < n && t > 0 && ((ptile >> 6) == 1 || ((ptile >> 6) == 2 && ((kb ^ grp) & PFM) == 0))) tma2d_prefetch(pm, (ptile & 31) * 128 + c.rank * 64, kb < 0 ? 512 : kb * 64);
      if (++slot == 10) { slot = 0; par ^= 1; }
    }
  }
}

__device__ __forceinline__ void wait_kv_dead(const Ctx& c, int h, int g) {
  if (g >= 2) flag_wait<false>(F_RD + h * 8 + g, 8 - g);
  else flag_wait<false>(F_CTX + max(c.lane & 7, g) * 64 + h, 4);
}
__device__ __forceinline__ int p1_storer(const Params& p, const Ctx& c) {
  const int n = p.s.r[c.cl].n1;
  const int type = p.s.r[c.cl].slab >> 3, grp = p.s.r[c.cl].slab & 7;
  for (int i = 0; i < 2 * n; i++) {
    const int t = i >> 1, w = i & 1, b = w * 2 + 1;
    const int tile = p.s.r[c.cl].tile[t] & 63;
    mbar_wait(c.bar + (B_SF + b) * 8, t & 1);
    const uint32_t src = c.sm + SM_BUF + b * 16384;
    int f = (type ? F_Q : F_KV) + (tile & 31) * 8 + grp;
    if (type == 0) {
      const int prev = p.s.prev[tile & 31][grp];
      if (prev != 255 && w == 0) wait_kv_dead(c, prev, grp);
      uint8_t* dst = g_S + (size_t)(S_K + ((tile & 32) + p.s.slot[tile & 31][grp]) * 8 + grp) * 65536 + c.rank * 32768 + w * 8192;
      bulk_store(dst, src, 8192);
      bulk_store(dst + 16384, src + 8192, 8192);
    } else if (tile < 32) {
      const int dep = p.s.qdep[tile * 8 + grp];
      if (dep != 511 && w == 0) {
        if (dep < 256) wait_kv_dead(c, dep >> 3, dep & 7);
        else flag_wait<false>(F_TS + dep - 256, 128);
      }
      bulk_store(g_S + (size_t)p.s.qblk[tile * 8 + grp] * 65536 + (c.rank * 2 + w) * 16384, src, 16384);
    } else {
      tma3d_store(&p.map_t[2], src, (grp * 4 + c.rank * 2 + w) * 32, 0, (tile - 32) * 64);
      f = F_QKVA + grp * 4 + ((0xE4390900u >> (2 * (tile - 30))) & 3);
    }
    BULK_COMMIT();
    BULK_WAIT(0);
    mbar_arrive_one(c.bar + (B_SE + b) * 8);
    if (i == 2 * n - 1) return f;
    if (w) flag_add(f, 2);
  }
  return -1;
}

__device__ __forceinline__ int p2_buf(int w, int i) { return w * 2 + (i & 1); }
__device__ __forceinline__ int p2_blk(int rank, int w, int i) { return ((i ^ w) & 1) == 0 ? 3 - rank : rank; }


template <int N>
__device__ __forceinline__ void row_max(const float (&s)[N], float& m0, float& m1) {
  float a0 = fmaxf(s[0], s[1]), a1 = fmaxf(s[2], s[3]);
#pragma unroll
  for (int i = 1; i < N / 4; i++) {
    m0 = fmaxf(m0, s[4 * i]); a0 = fmaxf(a0, s[4 * i + 1]);
    m1 = fmaxf(m1, s[4 * i + 2]); a1 = fmaxf(a1, s[4 * i + 3]);
  }
  m0 = fmaxf(m0, a0); m1 = fmaxf(m1, a1);
  m0 = fmaxf(m0, __shfl_xor_sync(0xffffffffu, m0, 1));
  m1 = fmaxf(m1, __shfl_xor_sync(0xffffffffu, m1, 1));
  m0 = fmaxf(m0, __shfl_xor_sync(0xffffffffu, m0, 2));
  m1 = fmaxf(m1, __shfl_xor_sync(0xffffffffu, m1, 2));
}
template <bool SUB, int N>
__device__ __forceinline__ void row_exp(const float (&s)[N], uint32_t (&P)[32], float m0, float m1, float& t0, float& t1) {
  float u0 = 0.f, u1 = 0.f;
  t0 = t1 = 0.f;
#pragma unroll
  for (int i = 0; i < N / 4; i++) {
    const float e0 = ex2(SUB ? s[4 * i] - m0 : s[4 * i]), e1 = ex2(SUB ? s[4 * i + 1] - m0 : s[4 * i + 1]);
    const float e2 = ex2(SUB ? s[4 * i + 2] - m1 : s[4 * i + 2]), e3 = ex2(SUB ? s[4 * i + 3] - m1 : s[4 * i + 3]);
    if (i == 0) { t0 = e0; u0 = e1; t1 = e2; u1 = e3; }
    else { t0 += e0; u0 += e1; t1 += e2; u1 += e3; }
    P[2 * i] = pack_bf16(e0, e1);
    P[2 * i + 1] = pack_bf16(e2, e3);
  }
#pragma unroll
  for (int i = N / 2; i < 32; i++) P[i] = 0;
  pin(P);
  t0 += u0; t1 += u1;
}
template <int N>
__device__ __forceinline__ void causal_mask(float (&s)[N], int thr) {
#pragma unroll
  for (int i = 0; i < 8; i++) {
    if (8 * i > thr) s[N - 32 + 4 * i] = -INFINITY;
    if (8 * i + 1 > thr) s[N - 32 + 4 * i + 1] = -INFINITY;
    if (8 * i - 8 > thr) s[N - 32 + 4 * i + 2] = -INFINITY;
    if (8 * i - 7 > thr) s[N - 32 + 4 * i + 3] = -INFINITY;
  }
}
__device__ __forceinline__ void issue_qk(float (&s)[32], uint32_t qd, uint32_t kd) {
  WG_FENCE();
#pragma unroll
  for (int kk = 0; kk < 8; kk++) wgmma_ss64<0>(s, qd + (kk >> 2) * 512 + (kk & 3) * 2, kd + (kk >> 2) * 1024 + (kk & 3) * 2, kk != 0);
  WG_COMMIT();
}
__device__ __forceinline__ void issue_qk(float (&s)[64], uint32_t qd, uint32_t kd) {
  WG_FENCE();
#pragma unroll
  for (int kk = 0; kk < 8; kk++) wgmma_ss128<0>(s, qd + (kk >> 2) * 512 + (kk & 3) * 2, kd + (kk >> 2) * 1024 + (kk & 3) * 2, kk != 0);
  WG_COMMIT();
}
template <int NK>
__device__ __forceinline__ void issue_pv(float (&o)[64], const uint32_t (&P)[32], uint32_t vd, int acc) {
  WG_FENCE();
#pragma unroll
  for (int kk = 0; kk < NK; kk++) wgmma_rs128<1>(o, P[4 * kk], P[4 * kk + 1], P[4 * kk + 2], P[4 * kk + 3], vd + kk * 128, kk != 0 ? 1 : acc);
  WG_COMMIT();
}
__device__ __forceinline__ void stage_done(const Ctx& c, int b) {
  FENCE_ASYNC_SMEM();
  __syncwarp();
  if (c.lane == 0) mbar_arrive(c.bar + (B_SF + b) * 8);
}
__device__ __forceinline__ void p2_epilogue(const float (&o)[64], float s0, float s1, const Ctx& c, int b) {
  stage_tile(o, c.sm + SM_BUF + b * 16384, c, s0, s1);
  stage_done(c, b);
}

struct P2State {
  float m0, m1, l0, l1;
  bool shift;
  float e0, e1;
  int ks;
  int wi, ai;
  uint32_t wb, ab;
  uint32_t qd;
};
__device__ __forceinline__ int wrap5(int q) { return q >= 5 ? q - 5 : q; }
__device__ __forceinline__ void turn_wait(uint32_t ring, int i) { mbar_wait(ring + (i & 3) * 8, (i >> 2) & 1); }
__device__ __forceinline__ void turn_pass(const Ctx& c, uint32_t ring, int i) { if (c.lane == 0) mbar_arrive(ring + (i & 3) * 8); }
__device__ __forceinline__ void p2_scales(P2State& z) {
  float l0 = z.l0, l1 = z.l1;
  l0 += __shfl_xor_sync(0xffffffffu, l0, 1);
  l1 += __shfl_xor_sync(0xffffffffu, l1, 1);
  l0 += __shfl_xor_sync(0xffffffffu, l0, 2);
  l1 += __shfl_xor_sync(0xffffffffu, l1, 2);
  asm("rcp.approx.ftz.f32 %0, %1;" : "=f"(z.e0) : "f"(l0));
  asm("rcp.approx.ftz.f32 %0, %1;" : "=f"(z.e1) : "f"(l1));
}
template <int N>
__device__ __forceinline__ void p2_first(const Ctx& c, P2State& z, float (&o)[64], uint32_t (&Pc)[32], uint32_t (&Pn)[32],
                                         int ks, int vs, int cnt, int acc) {
  float s[N] = {};
  issue_qk(s, z.qd, desc_lo(c.sm + SM_RING, 16) + ks * 2048);
  if (vs >= 0) {
    p2_scales(z);
    issue_pv<8>(o, Pc, desc_lo(c.sm + SM_RING, 16384) + vs * 2048, acc);
  } else {
    WG_COMMIT();
  }
  mbar_expect(z.ab + (z.ai++ & 3) * 8, cnt == 1 ? 8192 : 0);
  WG_WAIT(1);
  pin(s);
  release(c, B_P2E + ks, cnt);
  causal_mask(s, c.warp * 16 + (c.lane >> 2) - 2 * (c.lane & 3));
  z.m0 = z.m1 = 0.f;
  row_exp<false>(s, Pn, 0.f, 0.f, z.l0, z.l1);
  z.shift = __any_sync(0xffffffffu, !(z.l0 + z.l1 <= SM_HI) || ((c.lane & 3) == 0 && !(fminf(z.l0, z.l1) >= SM_LO)));
  if (__builtin_expect(z.shift, 0)) {
    z.m0 = z.m1 = -INFINITY;
    row_max(s, z.m0, z.m1);
    row_exp<true>(s, Pn, z.m0, z.m1, z.l0, z.l1);
  }
  WG_WAIT(0);
  pin(o);
  if (vs >= 0) release(c, B_P2E + vs, 1);
}

template <bool SECOND>
__device__ __forceinline__ void p2_turn(const Ctx& c, P2State& z, float (&o)[64], uint32_t (&Pc)[32], uint32_t (&Pn)[32],
                                        int eb = -1, bool half = false, int vcnt = 1) {
  float s[64] = {};
  const int ks = z.ks, vs = wrap5(ks + 1);
  turn_wait(z.wb, z.wi++);
  issue_qk(s, z.qd, desc_lo(c.sm + SM_RING, 16) + ks * 2048);
  const uint32_t vd = desc_lo(c.sm + SM_RING, 16384) + vs * 2048;
  if (SECOND) {
    if (eb >= 0) stage_tile(o, c.sm + SM_BUF + eb * 16384, c, z.e0, z.e1);
    if (half) issue_pv<4>(o, Pc, vd, 0); else issue_pv<8>(o, Pc, vd, 0);
  } else {
    issue_pv<8>(o, Pc, vd, 1);
  }
  turn_pass(c, z.ab, z.ai++);
  if (SECOND) { if (eb >= 0) stage_done(c, eb); }
  z.ks = wrap5(ks + 2);
  WG_WAIT(1);
  pin(s);
  release(c, B_P2E + ks, 1);
  float t0, t1, a0 = 1.f, a1 = 1.f;
  row_exp<false>(s, Pn, 0.f, 0.f, t0, t1);
  const bool redo = __any_sync(0xffffffffu, z.shift || !(t0 + t1 <= SM_HI));
  if (__builtin_expect(redo, 0)) {
    float n0 = z.m0, n1 = z.m1;
    if (!z.shift) { n0 = __log2f(z.l0); n1 = __log2f(z.l1); }
    z.shift = true;
    row_max(s, n0, n1);
    a0 = ex2(z.m0 - n0); a1 = ex2(z.m1 - n1);
    z.m0 = n0; z.m1 = n1;
    z.l0 *= a0; z.l1 *= a1;
    row_exp<true>(s, Pn, z.m0, z.m1, t0, t1);
  }
  WG_WAIT(0);
  pin(o);
  release(c, B_P2E + vs, vcnt);
  if (__builtin_expect(redo, 0)) {
#pragma unroll
    for (int i = 0; i < 16; i++) { o[4 * i] *= a0; o[4 * i + 1] *= a0; o[4 * i + 2] *= a1; o[4 * i + 3] *= a1; }
  }
  z.l0 += t0; z.l1 += t1;
}
__device__ __forceinline__ void copy_p(uint32_t (&d)[32], const uint32_t (&s)[32], int zero) {
#pragma unroll
  for (int i = 0; i < 32; i++) asm volatile("add.s32 %0, %1, %2;" : "=r"(d[i]) : "r"(s[i]), "r"(zero));
}

__device__ __forceinline__ void p2_consumer(const Params& p, const Ctx& c, int rot) {
  const int nit = p.s.r[c.cl].n2;
  const uint32_t fring = c.bar + B_P2F * 8, oring = c.bar + B_ORD * 8;
  float o[64] = {};
  uint32_t Pa[32] = {}, Pb[32] = {};
  P2State z;
  z.e0 = z.e1 = z.l0 = z.l1 = 0.f; z.ks = rot; z.shift = false;
  int acc = 0, n = 0;
  for (int it = 0; it < nit; it++) {
    const int j = p.s.r[c.cl].item[it] & 7, blk = p2_blk(c.rank, c.wg, it);
    const int lng = ((it ^ c.wg) & 1) ^ 1;
    z.qd = desc_lo(c.sm + SM_BUF, 16) + p2_buf(c.wg, it) * 1024;
    if (lng) { z.wb = oring; z.wi = n - it; z.ab = fring; z.ai = n + 1; }
    else { z.wb = fring; z.wi = n + 2; z.ab = oring; z.ai = n - it; }
    mbar_wait(c.bar + (B_QF + p2_buf(c.wg, it)) * 8, (it >> 1) & 1);
    turn_wait(fring, n + 1 - lng);
    const int vs = it ? wrap5(z.ks + 1) : -1, ks = lng ? z.ks : wrap5(z.ks + (it ? 2 : 1));
    if (blk & 1) p2_first<64>(c, z, o, Pa, Pb, ks, vs, 1 + lng, acc);
    else p2_first<32>(c, z, o, Pa, Pb, ks, vs, 1 + lng, acc);
    z.ks = wrap5(ks + (it == 0 && lng ? 1 : 2));
    n += 2 * j + 2;
    int left = 2 * j + lng;
    acc = left != 0;
    if (left == 0) { copy_p(Pa, Pb, p.zero); continue; }
    p2_turn<true>(c, z, o, Pb, Pa, it > 0 ? p2_buf(c.wg, it - 1) : -1, !(blk & 1), 1 + lng);
    while (--left > 0) {
      p2_turn<false>(c, z, o, Pa, Pb);
      if (--left == 0) { copy_p(Pa, Pb, p.zero); break; }
      p2_turn<false>(c, z, o, Pb, Pa);
    }
  }
  {
    if (!acc && nit > 1) p2_epilogue(o, z.e0, z.e1, c, p2_buf(c.wg, nit));
    turn_wait(z.wb, z.wi);
    issue_pv<8>(o, Pa, desc_lo(c.sm + SM_RING, 16384) + z.ks * 2048, acc);
    if (((nit - 1) ^ c.wg) & 1) turn_pass(c, z.ab, z.ai);
    p2_scales(z);
    WG_WAIT(0);
    pin(o);
    release(c, B_P2E + z.ks);
    p2_epilogue(o, z.e0, z.e1, c, p2_buf(c.wg, nit - 1));
  }
}

__device__ __forceinline__ void p2_load_q(const Params& p, const Ctx& c, int it, int w) {
  const int item = p.s.r[c.cl].item[it], b = p2_buf(w, it);
  mbar_expect(c.bar + (B_QF + b) * 8, 16384);
  bulk_load(c.sm + SM_BUF + b * 16384, g_S + (size_t)p.s.qblk[item] * 65536 + p2_blk(c.rank, w, it) * 16384, 16384, c.bar + (B_QF + b) * 8, POL(4));
}
__device__ __forceinline__ void wait_p1_free(const Ctx& c, int u1, int s) {
  mbar_wait(c.bar + (B_P1E + 2 * s) * 8, ((u1 - 1 - 2 * s) / 10) & 1);
  mbar_wait(c.bar + (B_P1E + 2 * s + 1) * 8, ((u1 - 2 - 2 * s) / 10) & 1);
}
__device__ __forceinline__ void p2_producer(const Params& p, const Ctx& c, int u1, int rot) {
  const int nit = p.s.r[c.cl].n2;
  int slot = rot, cnt = 0, par = 1, n = 0;
  const uint8_t* pv = nullptr;
  bool pl = false;
  auto load = [&](const uint8_t* src, int expect, uint32_t fb, bool last) {
    if (cnt < 5) {
      if (u1) {
        wait_p1_free(c, u1, slot);
        if (cnt == 0) p2_load_q(p, c, 0, 1);
      }
      cnt++;
    } else {
      if (slot == rot) par ^= 1;
      mbar_wait(c.bar + (B_P2E + slot) * 8, par);
    }
    if (expect) mbar_expect(fb, expect);
    bulk_load_mc(c.sm + SM_RING + slot * 32768 + c.rank * 16384, src, 16384, fb, last ? POL(5) : L2_NORMAL);
    slot = wrap5(slot + 1);
  };
  for (int it = 0; it < nit; it++) {
    const int item = p.s.r[c.cl].item[it], h = item >> 3, j = item & 7;
    if (it == 1 && (c.phases & 16) && p.s.r[c.cl].n1 < 8) flag_wait<true>(F_GATE, 256);
    uint32_t ready = (c.phases & 16) ? 0u : 255u;
    if (it == 0) { if (c.phases & 16) flag_wait<false>(F_Q + item, 4); mbar_wait(c.bar + B_LAD * 8, 0); p2_load_q(p, c, 0, 0); if (!u1) p2_load_q(p, c, 0, 1); }
    for (int t = 2 * j + 1; t >= 0; t--) {
      mask_wait(ready, t >> 1, F_KV + h * 8 + (c.lane & 7), 8);
      const uint8_t* k = g_S + (size_t)(2 * S_K + p.s.slot[h][t >> 1] * 16 + t) * 32768 + c.rank * 16384;
      const uint32_t fb = c.bar + (B_P2F + (n & 3)) * 8;
      const bool last = (p.s.r[c.cl].last[it] >> (t >> 1)) & 1;
      load(k, pv && t != 2 * j ? 65536 : 32768, fb, last);
      if (!(t & 1) && t + 4 <= 2 * j && c.rank == 0) flag_add_rx(F_RD + h * 8 + (t >> 1) + 2);
      if (pv) load(pv, 0, t != 2 * j ? fb : c.bar + (B_ORD + ((n - 1 - it) & 3)) * 8, pl);
      pl = last;
      pv = k + (size_t)NH * 16 * 32768;
      n++;
    }
  }
  load(pv, 32768, c.bar + (B_P2F + (n & 3)) * 8, pl);
}

__device__ __forceinline__ void publish_and_load_q(const Params& p, const Ctx& c, int f, int it, int seen) {
  const bool want = it < p.s.r[c.cl].n2, early = want && __all_sync(0xffffffffu, seen >= 4);
  if (early) { p2_load_q(p, c, it, it & 1); p2_load_q(p, c, it, (it & 1) ^ 1); }
  if (f >= 0) flag_add(f, 2);
  if (want && !early) {
    if (c.phases & 16) flag_wait<false>(F_Q + p.s.r[c.cl].item[it], 4);
    p2_load_q(p, c, it, it & 1); p2_load_q(p, c, it, (it & 1) ^ 1);
  }
}
__device__ __forceinline__ void p2_storer(const Params& p, const Ctx& c, int sfpar) {
  const int nit = p.s.r[c.cl].n2;
  int held = -1;
  for (int i = 0; i < 2 * nit; i++) {
    const int it = i >> 1, w = (it ^ i ^ 1) & 1, b = p2_buf(w, it);
    const int item = p.s.r[c.cl].item[it], h = item >> 3, j = item & 7;
    mbar_wait(c.bar + (B_SF + b) * 8, (sfpar >> b) & 1);
    sfpar ^= 1 << b;
    bulk_store(g_S + (size_t)p.s.qblk[item] * 65536 + p2_blk(c.rank, w, it) * 16384, c.sm + SM_BUF + b * 16384, 16384, POL(1));
    BULK_COMMIT();
    if (i & 1) {
      if (it + 2 == nit && (p.s.r[c.cl].item[it + 1] & 7) == 0) { held = F_CTX + j * 64 + h; continue; }
      const int seen = flag_peek(F_Q + p.s.r[c.cl].item[min(it + 2, nit - 1)]);
      BULK_WAIT(0);
      if (it + 1 == nit) release(c, B_DONE);
      publish_and_load_q(p, c, F_CTX + j * 64 + h, it + 2, seen);
    }
  }
  if (held >= 0) flag_add_rx(held, 2);
}

__device__ __forceinline__ int p3_pos(int i, int x) { return i < 4 ? (i + x) & 3 : 4; }
__device__ __forceinline__ void p3_consumer(const Params& p, const Ctx& c, int x) {
  const bool first = p.s.r[c.cl].p3 >= 24;
  const int tile = p.s.r[c.cl].p3 - (first ? 24 : 0), j = tile / 3, nt = tile - 3 * j;
  const int na = first ? 9 : 0, nb = p.s.task[c.cl][1] - p.s.task[c.cl][0];
  const uint32_t ad = desc_lo(c.sm + SM_RING + c.wg * 8192, 16), bd = desc_lo(c.sm + SM_RING + 16384, 4096);
  float acc[96] = {};
  int slot = 0, par = 0, prev = 0;
  float g0 = 0.f, g1 = 0.f;
  const int hold = c.wg && LAG ? na + nb - LAG : -1, pass = c.wg || !LAG ? -1 : na + nb - 1;
  const float* gp = g_gate + j * 256 + c.rank * 128 + c.wg * 64 + c.warp * 16 + (c.lane >> 2);
#pragma unroll 1
  for (int kb = 0; kb < na; kb++) {
    if (kb == hold) bar_sync(6, 256);
    mbar_wait(c.bar + (B_P3F + slot) * 8, par);
    WG_FENCE();
#pragma unroll
    for (int kk = 0; kk < 4; kk++) wgmma_ss192<1, 1>(acc, ad + p3_pos(slot, x) * 2560 + kk * 128, bd + p3_pos(slot, x) * 2560 + (kk >> 1) * 768 + (kk & 1) * 128, kk != 0 ? 1 : kb != 0);
    WG_COMMIT();
    if (kb == pass) bar_arrive(6, 256);
    WG_WAIT(1);
    if (kb > 0) release(c, B_P3E + prev);
    else { g0 = __ldcg(gp); g1 = __ldcg(gp + 8); }
    prev = slot;
    if (++slot == 5) { slot = 0; par ^= 1; }
  }
#pragma unroll 1
  for (int kb = na; kb < na + nb; kb++) {
    if (kb == hold) bar_sync(6, 256);
    mbar_wait(c.bar + (B_P3F + slot) * 8, par);
    WG_FENCE();
#pragma unroll
    for (int kk = 0; kk < 4; kk++) wgmma_ss192<1>(acc, ad + p3_pos(slot, x) * 2560 + kk * 2, bd + p3_pos(slot, x) * 2560 + (kk >> 1) * 768 + (kk & 1) * 128, kk != 0 ? 1 : kb != 0);
    WG_COMMIT();
    if (kb == pass) bar_arrive(6, 256);
    WG_WAIT(1);
    if (kb > 0) release(c, B_P3E + prev);
    else { g0 = __ldcg(gp); g1 = __ldcg(gp + 8); }
    prev = slot;
    if (++slot == 5) { slot = 0; par ^= 1; }
  }
  g0 = __fdividef(1.f, 1.f + g0); g1 = __fdividef(1.f, 1.f + g1);
  WG_WAIT(0);
  pin(acc);
  if (first) bar_sync(4 + c.wg, 128);
  mbar_wait(c.bar + B_OUT * 8, 0);
  const int row = (c.lane & 7) + ((c.lane >> 3) & 1) * 8;
  const uint32_t wbase = c.sm + SM_RING + c.wg * 8192 + c.warp * 2048;
  const uint32_t base = wbase + row * 128 + (((c.lane >> 4) ^ (row & 7)) << 4);
#pragma unroll
  for (int i = 0; i < 12; i++) {
    stsm4((base ^ ((i & 3) << 5)) + (i >> 2) * 40960, pack_bf16(acc[8 * i] * g0, acc[8 * i + 1] * g0), pack_bf16(acc[8 * i + 2] * g1, acc[8 * i + 3] * g1),
          pack_bf16(acc[8 * i + 4] * g0, acc[8 * i + 5] * g0), pack_bf16(acc[8 * i + 6] * g1, acc[8 * i + 7] * g1));
    if ((i & 3) == 3) {
      FENCE_ASYNC_SMEM();
      bar_sync(4 + c.wg, 128);
      if (c.warp == (i >> 2)) tma2d_add(&p.map_out, c.sm + SM_RING + c.wg * 8192 + c.warp * 40960, nt * 192 + c.warp * 64, j * 256 + c.rank * 128 + c.wg * 64);
    }
  }
  BULK_COMMIT();
  BULK_WAIT_READ(0);
}

__device__ __forceinline__ void p3_producer(const Params& p, const Ctx& c, int u1, int u2, int rot, int x) {
  const bool first = p.s.r[c.cl].p3 >= 24;
  const int tile = p.s.r[c.cl].p3 - (first ? 24 : 0), j = tile / 3, nt = tile - 3 * j;
  int slot = 0, par = 1, cnt = 0;
  auto wait_free = [&](int s) {
    const int f = wrap5(s + 5 - rot);
    if (f < u2) mbar_wait(c.bar + (B_P2E + s) * 8, ((u2 - 1 - f) / 5) & 1);
    else if (u1) wait_p1_free(c, u1, s);
  };
  asm volatile(ELECT("prefetch.tensormap [%0];") ::"l"(&p.map_o[0]) : "memory");
  asm volatile(ELECT("prefetch.tensormap [%0];") ::"l"(&p.map_out) : "memory");
  if ((c.phases & 16) && p.s.r[c.cl].n1 < 8 && p.s.r[c.cl].n2 < 2) flag_wait<true>(F_GATE, 256);
  uint32_t ready = (c.phases & 16) ? 0u : ~0u;
  const int q0 = p.s.task[c.cl][0], q1 = p.s.task[c.cl][1];
  for (int q = q0 - (first ? 9 : 0); q < q1; q++) {
    if (q == max(q0, 64 - ZLEAD)) mbar_arrive_one(c.bar + B_ZF * 8);
    const bool brA = q < q0;
    const int kb = brA ? q - q0 + 9 : p.s.p3_order[tile][q];
    if (!brA) mask_wait(ready, kb >> 1, F_CTX + j * 64 + c.lane, 4);
    else if (kb == 0 && (c.phases & 16)) flag_wait<false>(F_CTX + j * 64 + 32, 16);
    const uint8_t* a = brA ? g_oA + (j * 4 + c.rank * 2) * 73728 + kb * 8192 : g_S + (size_t)p.s.qblk[(kb >> 1) * 8 + j] * 65536 + c.rank * 32768 + (kb & 1) * 8192;
    const uint32_t st = c.sm + SM_RING + p3_pos(slot, x) * 40960, fb = c.bar + (B_P3F + slot) * 8;
    if (cnt < 4) { wait_free(p3_pos(cnt, x)); wait_free(p3_pos(cnt, x) + 1); }
    else if (cnt == 4) mbar_wait(c.bar + B_DONE * 8, 0);
    else mbar_wait(c.bar + (B_P3E + slot) * 8, par);
    cnt++;
    mbar_expect(fb, 40960);
    bulk_load(st, a, 8192, fb, POL(3));
    bulk_load(st + 8192, a + (brA ? 73728 : 16384), 8192, fb, POL(3));
    tma3d_mc(st + 16384 + c.rank * 12288, &p.map_o[brA], 0, kb * 64 + c.rank * 32, nt * 3, fb);
    if (++slot == 5) { slot = 0; par ^= 1; }
  }
}

__device__ __forceinline__ float bf_lo(uint32_t w) { return __uint_as_float(w << 16); }
__device__ __forceinline__ float bf_hi(uint32_t w) { return __uint_as_float(w & 0xffff0000u); }

__device__ __forceinline__ void gate_rows(const Params& p, int row0, int lane) {
  const uint4* x = reinterpret_cast<const uint4*>(p.x + (size_t)(row0 + (lane >> 2)) * DM) + (lane & 3);
  const uint4* w = reinterpret_cast<const uint4*>(p.gate_w) + (lane & 3);
  float a = 0.f;
#pragma unroll 1
  for (int b = 0; b < 3; b++) {
    uint4 u[6];
#pragma unroll
    for (int i = 0; i < 6; i++) u[i] = __ldg(x + (b * 6 + i) * 4);
#pragma unroll
    for (int i = 0; i < 6; i++) {
      const uint4 v = __ldg(w + (b * 6 + i) * 4);
      a = fmaf(bf_lo(u[i].x), bf_lo(v.x), a); a = fmaf(bf_hi(u[i].x), bf_hi(v.x), a);
      a = fmaf(bf_lo(u[i].y), bf_lo(v.y), a); a = fmaf(bf_hi(u[i].y), bf_hi(v.y), a);
      a = fmaf(bf_lo(u[i].z), bf_lo(v.z), a); a = fmaf(bf_hi(u[i].z), bf_hi(v.z), a);
      a = fmaf(bf_lo(u[i].w), bf_lo(v.w), a); a = fmaf(bf_hi(u[i].w), bf_hi(v.w), a);
    }
  }
  a += __shfl_xor_sync(0xffffffffu, a, 1);
  a += __shfl_xor_sync(0xffffffffu, a, 2);
  if ((lane & 3) == 0) g_gate[row0 + (lane >> 2)] = __expf(fminf(a, 60.f));
}

__device__ __forceinline__ void lds10(uint32_t (&k)[10], uint32_t a) {
  asm volatile("ld.shared.v2.u32 {%0, %1}, [%10];\nld.shared.v2.u32 {%2, %3}, [%10+8];\nld.shared.v2.u32 {%4, %5}, [%10+16];\n"
               "ld.shared.v2.u32 {%6, %7}, [%10+24];\nld.shared.v2.u32 {%8, %9}, [%10+32];"
               : "=r"(k[0]), "=r"(k[1]), "=r"(k[2]), "=r"(k[3]), "=r"(k[4]), "=r"(k[5]), "=r"(k[6]), "=r"(k[7]), "=r"(k[8]), "=r"(k[9]) : "r"(a));
}
__device__ __forceinline__ void local_attn(const Params& p, const Ctx& c, int rb, int hs) {
  const int lane = c.lane, grp = rb >> 2, par = lane >> 4, i0 = 2 * (lane & 15);
  const uint32_t buf = c.sm + SM_BUF + (c.warp - 2) * 8192, bqk = c.bar + (B_LA + (c.warp - 2) * 2) * 8, bv = bqk + 8;
  const uint32_t mine = buf + 2304 + par * 160 + i0 * 4;
  const bool flags = c.phases & 16;
  auto fetch_qk = [&](int i) {
    if (flags && !(i & 1)) {
      const int q = i >> 1;
      const int tgt = q == 0 ? 24 : q == 3 ? 8 : 12;
      flag_wait<false>(F_QKVA + (grp - (grp > 0 && (rb & 3) == 0 ? par : 0)) * 4 + q, tgt);
    }
    mbar_expect(bqk, 5184);
    tma3d(buf, &p.map_t[0], rb * 32, 0, 9 * (4 * i + hs), bqk, POL(2));
    tma3d(buf + 2304, &p.map_t[1], rb * 32 - 8, 0, 288 + 9 * (4 * i + hs), bqk, POL(2));
  };
  auto fetch_v = [&](int i) { mbar_expect(bv, 2880); tma3d(buf + 5248, &p.map_t[1], rb * 32 - 8, 0, 576 + 9 * (4 * i + hs), bv, POL(2)); };
  fetch_qk(0);
  if (flags) flag_wait<true>(F_GATE, 256);
#pragma unroll 1
  for (int q = 0; q < 8; q++) {
    fetch_v(q);
    float a[8], b[8];
#pragma unroll
    for (int w = 0; w < 8; w++) a[w] = b[w] = 0.f;
    mbar_wait(bqk, q & 1);
#pragma unroll 1
    for (int j = 0; j < 9; j++) {
      uint32_t x, y, k[10];
      asm volatile("ld.shared.v2.u32 {%0, %1}, [%2];" : "=r"(x), "=r"(y) : "r"(buf + lane * 8 + j * 256));
      lds10(k, mine + j * 320);
      const float xl = bf_lo(x), xh = bf_hi(x), yl = bf_lo(y), yh = bf_hi(y);
#pragma unroll
      for (int m = 1; m < 10; m++) {
        const float kl = bf_lo(k[m]), kh = bf_hi(k[m]);
        if (m < 9) a[8 - m] = fmaf(xl, kl, fmaf(xh, kh, a[8 - m]));
        if (m > 1) b[9 - m] = fmaf(yl, kl, fmaf(yh, kh, b[9 - m]));
      }
    }
    __syncwarp();
    mbar_wait(bv, q & 1);
    if (q & 1) flag_add_rx(F_TS + (q >> 1));
    if (q < 7) fetch_qk(q + 1);
    constexpr float SC = 0.23570226039551584f * 1.4426950408889634f;
    const float* gp = g_gate + rb * 64 + 2 * i0 + par;
    const float ga = __ldcg(gp), gb = __ldcg(gp + 2);
    float ma = a[0], mb = b[0];
#pragma unroll
    for (int w = 1; w < 8; w++) {
      if (rb == 0) {
        if (i0 < w) a[w] = -INFINITY;
        if (i0 + 1 < w) b[w] = -INFINITY;
      }
      ma = fmaxf(ma, a[w]); mb = fmaxf(mb, b[w]);
    }
    float la = 0.f, lb = 0.f;
#pragma unroll
    for (int w = 0; w < 8; w++) {
      a[w] = ex2((a[w] - ma) * SC); b[w] = ex2((b[w] - mb) * SC);
      la += a[w]; lb += b[w];
    }
    la = __fdividef(ga, la); lb = __fdividef(gb, lb);
#pragma unroll
    for (int w = 0; w < 8; w++) { a[w] *= la; b[w] *= lb; }
    uint8_t* dst = g_oA + rb * 73728 + ((i0 & 2) + par) * 4;
#pragma unroll 1
    for (int j = 0; j < 9; j++) {
      uint32_t v[10];
      lds10(v, mine + 2944 + j * 320);
      float a0 = 0.f, a1 = 0.f, b0 = 0.f, b1 = 0.f;
#pragma unroll
      for (int m = 1; m < 10; m++) {
        const float vl = bf_lo(v[m]), vh = bf_hi(v[m]);
        if (m < 9) { a0 = fmaf(a[8 - m], vl, a0); a1 = fmaf(a[8 - m], vh, a1); }
        if (m > 1) { b0 = fmaf(b[9 - m], vl, b0); b1 = fmaf(b[9 - m], vh, b1); }
      }
      const uint32_t wa = pack_bf16(a0, a1), wb = pack_bf16(b0, b1);
      const uint32_t got = __shfl_xor_sync(0xffffffffu, par ? wa : wb, 16);
      const uint32_t r0 = par ? got : wa, r1 = par ? wb : got;
      const int col = 18 * (4 * q + hs) + 2 * j, o = col * 128 + ((((i0 >> 2) ^ col) & 7) << 4);
      *reinterpret_cast<uint32_t*>(dst + o) = __byte_perm(r0, r1, 0x5410);
      *reinterpret_cast<uint32_t*>(dst + ((o + 128) ^ 16)) = __byte_perm(r0, r1, 0x7632);
    }
    __syncwarp();
  }
  mbar_arrive_one(c.bar + B_LAD * 8);
  flag_add(F_CTX + grp * 64 + 32);
}

__global__ void __cluster_dims__(2, 1, 1) __launch_bounds__(384, 1) fused_kernel(const __grid_constant__ Params p) {
  extern __shared__ uint8_t smem_raw[];
  Ctx c;
  c.sm = ((uint32_t)__cvta_generic_to_shared(smem_raw) + 1023u) & ~1023u;
  c.bar = c.sm + SM_BAR;
  c.lane = threadIdx.x & 31;
  const int wid = __shfl_sync(0xffffffffu, threadIdx.x >> 5, 0);
  if (wid < 6) asm volatile("prefetch.tensormap [%0];" ::"l"(&p.map_a[0] + wid) : "memory");
  c.wg = wid >> 2;
  c.warp = wid & 3;
  c.cl = (blockIdx.x + (wid >> 4)) >> 1;
  c.rank = blockIdx.x & 1;
  c.rbar = mapa(c.bar, c.lane & 1);
  {
    const int w = wid, cnt = (((int)(B_CNT >> (4 * w)) - 1) & 15) + 1;
    if (w < 11) {
#pragma unroll
      for (int i = 0; i < 8; i++) asm volatile("mbarrier.init.shared::cta.b64 [%0], %1;" ::"r"(c.bar + w * 64 + i * 8), "r"(cnt));
    }
    asm volatile("fence.mbarrier_init.release.cluster;" ::: "memory");
  }
  asm volatile("barrier.cluster.arrive.relaxed;" ::: "memory");
  c.phases = p.s.r[c.cl].phases;
  const bool do1 = p.s.r[c.cl].n1 > 0, do2 = p.s.r[c.cl].n2 > 0, do3 = p.s.r[c.cl].p3 != 255;
  if (do1 && c.wg == 2 && c.warp == 0) {
    const int type = p.s.r[c.cl].slab >> 3;
    FENCE_ASYNC_SMEM();
    mbar_expect(c.bar + B_P1F * 8, type ? 32768 : 16384);
    tma2d(type ? c.sm + SM_BUF + 32768 : c.sm + SM_RING, &p.map_a[type], type ? 512 : 0, (p.s.r[c.cl].slab & 7) * 256 + c.rank * 128, c.bar + B_P1F * 8);
  }
  asm volatile("barrier.cluster.wait.acquire;" ::: "memory");
  if (do1 && c.wg == 2 && c.warp == 0) {
    const int type = p.s.r[c.cl].slab >> 3, tile = p.s.r[c.cl].tile[0] & 63;
    const CUtensorMap* m = &p.map_w[type * 2 + (tile >> 5)];
#pragma unroll 1
    for (int s = 1 - type; s < NPRO; s++) {
      const int kb = (s - type) >> 1;
      const uint32_t fb = c.bar + (B_P1F + s) * 8;
      if (s) mbar_expect(fb, 16384);
      if ((s ^ type) & 1) tma2d_mc(c.sm + SM_RING + s * 16384 + c.rank * 8192, m, (tile & 31) * 128 + c.rank * 64, kb < 0 ? 512 : kb * 64, fb);
      else tma2d(c.sm + SM_RING + s * 16384, &p.map_a[type], kb * 64, (p.s.r[c.cl].slab & 7) * 256 + c.rank * 128, fb);
    }
  }

  if (c.wg < 2) {
    asm volatile("setmaxnreg.inc.sync.aligned.u32 224;");
    if (c.wg == 1) {
      if (do1) bar_arrive(ORDER, 256);
      if (c.lane == 0) mbar_arrive(c.bar + B_P2F * 8);
    }
    if (do1) p1_consumer(p, c);
    if (do2) p2_consumer(p, c, p.s.r[c.cl].rot);
    if (do3) p3_consumer(p, c, p.s.r[c.cl].x3);
    if (c.lane == 0) mbar_arrive(c.bar + B_FIN * 8);
    __syncwarp();
    cluster_sync();
  } else {
    asm volatile("setmaxnreg.dec.sync.aligned.u32 56;");
    if (c.warp == 0) {
      if (do1) p1_producer(p, c);
      if (do2) p2_producer(p, c, p.s.r[c.cl].u1, p.s.r[c.cl].rot);
      if (do3) p3_producer(p, c, p.s.r[c.cl].u1, p.s.r[c.cl].u2, p.s.r[c.cl].rot, p.s.r[c.cl].x3);
    } else if (c.warp == 1) {
      const int f = do1 ? p1_storer(p, c) : -1;
      if (do2) {
        publish_and_load_q(p, c, f, 1, flag_peek(F_Q + p.s.r[c.cl].item[1]));
        p2_storer(p, c, (p.s.r[c.cl].n1 & 1) * 10);
      } else {
        const bool idle = mbar_test(c.bar + B_LAD * 8, 0);
        if (idle) release(c, B_DONE);
        if (f >= 0) flag_add(f, 2);
        if (!idle) { mbar_wait(c.bar + B_LAD * 8, 0); release(c, B_DONE); }
      }
      if (do3) {
        const int tile = p.s.r[c.cl].p3 % 24;
        if (p.s.task[c.cl][1] == 64) {
          mbar_wait(c.bar + B_ZF * 8, 0);
          const int j = tile / 3, nt = tile - 3 * j;
          uint4* o = reinterpret_cast<uint4*>(p.out + (size_t)(j * 256 + c.rank * 128 + (c.lane >> 3)) * DM + nt * 192) + (c.lane & 7);
#pragma unroll 4
          for (int r = 0; r < 32; r++) o[r * 288] = o[r * 288 + 8] = o[r * 288 + 16] = make_uint4(0u, 0u, 0u, 0u);
          __syncwarp();
          flag_add(F_OUT + tile * 2 + c.rank);
        } else if (c.phases & 16) {
          flag_wait<false, 256>(F_OUT + tile * 2 + c.rank, 1);
        }
        mbar_arrive_one(c.bar + B_OUT * 8);
      }
    } else {
      const int bw = blockIdx.x * 2 + (c.warp - 2);
      if ((c.phases & 1) && bw < 256) {
        gate_rows(p, bw * 8, c.lane);
        __syncwarp();
        flag_add(F_GATE);
      }
      if (p.s.r[c.cl].bg != 255) local_attn(p, c, p.s.r[c.cl].bg, bw & 3);
      else if (c.lane == 0) mbar_arrive(c.bar + B_LAD * 8);
    }
    __syncwarp();
    bar_sync(3, 128);
    if (c.warp == 0 && (c.phases & 32)) {
      int last = 0;
      if (c.lane == 0) { __threadfence(); last = atomicAdd(g_flags + F_DONE, 1) == 2 * NCL - 1; }
      if (__shfl_sync(0xffffffffu, last, 0)) for (int i = c.lane; i < F_NUM; i += 32) g_flags[i] = 0;
    }
    if (c.warp == 1) mbar_wait(c.bar + B_FIN * 8, 0);
    __syncwarp();
    cluster_sync();
  }
}

static const Sched k_sched = {
  {{8,18,2,27,0,{109,181,0,0,0,0,0,0,0,0,0},{0,0,0,0,0,0,0,0,0,0,0},{73,229,65,194,104,198,206,74,149,152,26,13,148,221,91,156,146,217,0,0,0,0,0,0,0,0,0,0,0,0}},
   {8,3,4,11,255,{79,52,174,88,0,0,0,0,0,0,0},{0,0,95,0,0,0,0,0,0,0,0},{160,170,226,0,0,0,0,0,0,0,0,0,0,0,0,0,0,0,0,0,0,0,0,0,0,0,0,0,0,0}},
   {8,4,3,23,255,{30,255,197,0,0,0,0,0,0,0,0},{0,0,0,0,0,0,0,0,0,0,0},{164,72,166,163,0,0,0,0,0,0,0,0,0,0,0,0,0,0,0,0,0,0,0,0,0,0,0,0,0,0}},
   {8,4,6,10,255,{6,49,101,247,217,205,0,0,0,0,0},{0,0,0,0,0,63,0,0,0,0,0},{169,64,171,103,0,0,0,0,0,0,0,0,0,0,0,0,0,0,0,0,0,0,0,0,0,0,0,0,0,0}},
   {0,29,1,43,1,{179,0,0,0,0,0,0,0,0,0,0},{0,0,0,0,0,0,0,0,0,0,0},{135,163,136,224,193,226,206,204,223,197,202,213,196,216,16,218,203,205,222,212,221,19,207,214,219,23,220,210,217,0}},
   {1,29,2,35,2,{224,187,0,0,0,0,0,0,0,0,0},{0,0,0,0,0,0,0,0,0,0,0},{135,233,136,224,193,226,206,204,223,197,202,213,196,216,16,218,203,205,222,212,221,15,211,214,219,28,215,210,217,0}},
   {2,29,2,40,3,{216,147,0,0,0,0,0,0,0,0,0},{0,0,0,0,0,0,0,0,0,0,0},{137,231,192,232,194,225,206,204,223,197,202,213,196,216,16,218,203,205,222,212,221,15,211,214,219,28,215,210,217,0}},
   {3,29,1,47,4,{219,0,0,0,0,0,0,0,0,0,0},{0,0,0,0,0,0,0,0,0,0,0},{135,233,192,232,194,225,206,204,223,197,202,213,196,216,26,208,203,205,222,212,221,15,211,214,219,28,215,210,217,0}},
   {4,28,0,9,5,{0,0,0,0,0,0,0,0,0,0,0},{0,0,0,0,0,0,0,0,0,0,0},{135,233,192,232,194,225,206,236,5,10,21,4,24,26,16,11,13,30,20,29,15,19,22,27,28,23,18,25,0,0}},
   {5,27,0,6,6,{0,0,0,0,0,0,0,0,0,0,0},{0,0,0,0,0,0,0,0,0,0,0},{137,163,192,232,194,225,206,236,5,42,4,24,26,11,16,13,30,20,29,15,19,22,27,28,23,18,25,0,0,0}},
   {6,26,1,13,7,{153,0,0,0,0,0,0,0,0,0,0},{0,0,0,0,0,0,0,0,0,0,0},{137,64,136,241,193,230,12,63,10,53,24,26,11,16,13,30,20,29,15,19,22,27,28,87,18,25,0,0,0,0}},
   {7,25,0,19,8,{0,0,0,0,0,0,0,0,0,0,0},{0,0,0,0,0,0,0,0,0,0,0},{135,195,136,66,70,76,69,85,68,88,90,75,80,77,94,84,93,79,83,86,91,92,82,87,89,0,0,0,0,0}},
   {0,29,1,45,9,{148,0,0,0,0,0,0,0,0,0,0},{0,0,0,0,0,0,0,0,0,0,0},{103,201,104,209,33,198,238,236,255,229,234,245,228,248,48,250,235,237,254,244,253,51,239,246,251,55,252,242,249,0}},
   {1,29,2,37,10,{184,226,0,0,0,0,0,0,0,0,0},{0,0,0,0,0,0,0,0,0,0,0},{103,195,104,209,33,198,238,236,255,229,234,245,228,248,48,250,235,237,254,244,253,47,243,246,251,60,247,242,249,0}},
   {2,29,2,14,11,{185,202,0,0,0,0,0,0,0,0,0},{0,0,0,0,0,0,0,0,0,0,0},{105,195,32,209,34,198,238,236,255,229,234,245,228,248,48,250,235,237,254,244,253,47,243,246,251,60,247,242,249,0}},
   {3,29,1,5,12,{188,0,0,0,0,0,0,0,0,0,0},{0,0,0,0,0,0,0,0,0,0,0},{103,195,32,209,34,198,238,236,255,229,234,245,228,248,58,240,235,237,254,244,253,47,243,246,251,60,247,242,249,0}},
   {4,28,0,22,13,{0,0,0,0,0,0,0,0,0,0,0},{0,0,0,0,0,0,0,0,0,0,0},{103,195,32,209,34,198,238,31,37,42,53,36,56,58,48,43,45,62,52,61,47,51,54,59,60,55,50,57,0,0}},
   {5,27,0,10,14,{0,0,0,0,0,0,0,0,0,0,0},{0,0,0,0,0,0,0,0,0,0,0},{105,199,32,209,34,198,238,31,37,21,36,56,58,43,48,45,62,52,61,47,51,54,59,60,55,50,57,0,0,0}},
   {6,26,0,20,15,{0,0,0,0,0,0,0,0,0,0,0},{0,0,0,0,0,0,0,0,0,0,0},{105,96,104,66,33,14,44,5,42,4,56,58,43,48,45,62,52,61,47,51,54,59,60,119,50,57,0,0,0,0}},
   {7,25,0,15,16,{0,0,0,0,0,0,0,0,0,0,0},{0,0,0,0,0,0,0,0,0,0,0},{103,163,104,98,102,108,101,117,100,120,122,107,112,109,126,116,125,111,115,118,123,124,114,119,121,0,0,0,0,0}},
   {0,6,7,30,255,{136,137,2,118,35,165,180,0,0,0,0},{0,0,0,0,0,3,0,0,0,0,0},{67,233,192,241,194,230,0,0,0,0,0,0,0,0,0,0,0,0,0,0,0,0,0,0,0,0,0,0,0,0}},
   {1,6,4,21,255,{23,99,95,240,0,0,0,0,0,0,0},{0,0,192,0,0,0,0,0,0,0,0},{137,163,192,241,194,230,0,0,0,0,0,0,0,0,0,0,0,0,0,0,0,0,0,0,0,0,0,0,0,0}},
   {2,6,7,44,255,{0,66,14,172,130,242,190,0,0,0,0},{0,0,0,0,0,0,0,0,0,0,0},{135,163,136,241,193,230,0,0,0,0,0,0,0,0,0,0,0,0,0,0,0,0,0,0,0,0,0,0,0,0}},
   {3,6,6,38,255,{1,68,47,193,211,182,0,0,0,0,0},{0,0,0,0,0,0,0,0,0,0,0},{137,163,136,241,193,230,0,0,0,0,0,0,0,0,0,0,0,0,0,0,0,0,0,0,0,0,0,0,0,0}},
   {4,8,4,5,255,{141,46,245,152,0,0,0,0,0,0,0},{0,0,0,0,0,0,0,0,0,0,0},{137,163,136,241,193,230,12,63,0,0,0,0,0,0,0,0,0,0,0,0,0,0,0,0,0,0,0,0,0,0}},
   {5,10,6,9,255,{16,11,252,171,90,151,0,0,0,0,0},{0,0,0,0,0,128,0,0,0,0,0},{67,231,136,241,193,230,12,63,10,53,0,0,0,0,0,0,0,0,0,0,0,0,0,0,0,0,0,0,0,0}},
   {6,10,5,4,255,{56,53,250,110,191,0,0,0,0,0,0},{0,0,0,0,192,0,0,0,0,0,0},{135,195,81,98,70,46,31,37,21,36,0,0,0,0,0,0,0,0,0,0,0,0,0,0,0,0,0,0,0,0}},
   {7,7,5,24,255,{69,10,98,94,183,0,0,0,0,0,0},{0,0,0,0,255,0,0,0,0,0,0},{137,64,81,65,78,95,74,0,0,0,0,0,0,0,0,0,0,0,0,0,0,0,0,0,0,0,0,0,0,0}},
   {8,17,2,18,17,{168,246,0,0,0,0,0,0,0,0,0},{0,0,0,0,0,0,0,0,0,0,0},{67,225,145,199,44,109,204,223,197,196,16,203,30,83,150,87,207,0,0,0,0,0,0,0,0,0,0,0,0,0}},
   {9,17,2,1,18,{167,150,0,0,0,0,0,0,0,0,0},{0,64,0,0,0,0,0,0,0,0,0},{71,225,192,1,44,40,206,223,68,152,16,203,148,79,211,219,215,0,0,0,0,0,0,0,0,0,0,0,0,0}},
   {10,18,3,12,19,{128,238,189,0,0,0,0,0,0,0,0},{0,0,63,0,0,0,0,0,0,0,0},{160,170,226,163,193,14,45,223,10,196,216,218,30,221,211,219,215,217,0,0,0,0,0,0,0,0,0,0,0,0}},
   {11,18,2,39,20,{239,220,0,0,0,0,0,0,0,0,0},{0,0,0,0,0,0,0,0,0,0,0},{160,170,166,194,44,14,40,223,68,213,16,218,30,221,15,214,146,217,0,0,0,0,0,0,0,0,0,0,0,0}},
   {12,17,3,29,21,{248,93,222,0,0,0,0,0,0,0,0},{0,32,0,0,0,0,0,0,0,0,0},{160,170,226,194,44,14,40,223,149,196,16,203,30,221,211,219,215,0,0,0,0,0,0,0,0,0,0,0,0,0}},
   {13,18,4,16,22,{32,194,125,227,0,0,0,0,0,0,0},{0,0,0,0,0,0,0,0,0,0,0},{73,229,200,194,231,14,31,232,10,196,26,203,205,221,211,219,215,217,0,0,0,0,0,0,0,0,0,0,0,0}},
   {14,17,5,13,23,{96,82,164,123,201,0,0,0,0,0,0},{1,0,0,0,0,0,0,0,0,0,0},{73,229,200,194,44,76,69,45,149,152,75,13,148,79,150,87,146,0,0,0,0,0,0,0,0,0,0,0,0,0}},
   {15,18,1,2,24,{166,0,0,0,0,0,0,0,0,0,0},{0,0,0,0,0,0,0,0,0,0,0},{71,225,200,230,227,236,31,74,237,196,26,208,30,221,211,219,146,217,0,0,0,0,0,0,0,0,0,0,0,0}},
   {9,18,4,25,25,{208,131,233,221,0,0,0,0,0,0,0},{0,0,0,0,0,0,0,0,0,0,0},{73,229,145,194,6,109,204,5,149,202,26,13,93,222,150,156,146,217,0,0,0,0,0,0,0,0,0,0,0,0}},
   {10,17,4,17,26,{80,169,244,230,0,0,0,0,0,0,0},{0,0,0,64,0,0,0,0,0,0,0},{164,201,166,103,6,40,204,5,149,80,77,203,148,79,150,156,146,0,0,0,0,0,0,0,0,0,0,0,0,0}},
   {11,17,2,17,27,{112,133,0,0,0,0,0,0,0,0,0},{1,35,0,0,0,0,0,0,0,0,0},{164,7,171,1,6,76,45,5,10,152,75,13,148,83,91,156,215,0,0,0,0,0,0,0,0,0,0,0,0,0}},
   {12,18,3,1,28,{192,129,163,0,0,0,0,0,0,0,0},{0,0,0,0,0,0,0,0,0,0,0},{164,7,166,1,6,76,45,5,10,152,26,13,148,79,150,156,146,217,0,0,0,0,0,0,0,0,0,0,0,0}},
   {13,17,5,31,29,{41,81,243,155,186,0,0,0,0,0,0},{0,0,0,0,0,0,0,0,0,0,0},{160,170,226,1,44,76,69,45,149,152,16,94,148,79,150,156,146,0,0,0,0,0,0,0,0,0,0,0,0,0}},
   {14,17,5,2,30,{48,170,89,157,203,0,0,0,0,0,0},{1,0,0,0,0,0,0,0,0,0,0},{160,170,145,1,14,95,40,74,68,90,16,94,93,83,91,156,89,0,0,0,0,0,0,0,0,0,0,0,0,0}},
   {15,17,4,21,31,{40,132,235,228,0,0,0,0,0,0,0},{0,0,0,0,0,0,0,0,0,0,0},{73,229,145,235,231,76,69,232,149,152,75,13,148,79,150,156,215,0,0,0,0,0,0,0,0,0,0,0,0,0}},
   {9,3,7,36,255,{73,26,3,254,36,105,223,0,0,0,0},{0,0,0,0,0,0,255,0,0,0,0},{160,170,226,0,0,0,0,0,0,0,0,0,0,0,0,0,0,0,0,0,0,0,0,0,0,0,0,0,0,0}},
   {10,3,6,3,255,{72,75,9,13,249,135,0,0,0,0,0},{0,0,0,0,0,0,0,0,0,0,0},{169,7,171,0,0,0,0,0,0,0,0,0,0,0,0,0,0,0,0,0,0,0,0,0,0,0,0,0,0,0}},
   {11,3,8,42,255,{24,58,15,97,173,106,121,124,0,0,0},{0,0,0,0,0,0,0,30,0,0,0},{169,201,192,0,0,0,0,0,0,0,0,0,0,0,0,0,0,0,0,0,0,0,0,0,0,0,0,0,0,0}},
   {12,3,7,28,255,{78,19,45,213,178,218,144,0,0,0,0},{0,0,0,60,0,0,0,0,0,0,0},{169,201,171,0,0,0,0,0,0,0,0,0,0,0,0,0,0,0,0,0,0,0,0,0,0,0,0,0,0,0}},
   {13,3,6,0,255,{77,67,115,43,212,231,0,0,0,0,0},{0,0,0,0,0,128,0,0,0,0,0},{164,195,166,0,0,0,0,0,0,0,0,0,0,0,0,0,0,0,0,0,0,0,0,0,0,0,0,0,0,0}},
   {14,4,6,26,255,{62,103,83,209,158,120,0,0,0,0,0},{0,0,0,0,0,1,0,0,0,0,0},{164,7,226,70,0,0,0,0,0,0,0,0,0,0,0,0,0,0,0,0,0,0,0,0,0,0,0,0,0,0}},
   {15,3,5,8,255,{63,102,134,154,229,0,0,0,0,0,0},{0,0,0,0,63,0,0,0,0,0,0},{160,170,66,0,0,0,0,0,0,0,0,0,0,0,0,0,0,0,0,0,0,0,0,0,0,0,0,0,0,0}},
   {9,4,6,12,255,{5,12,44,33,91,160,0,0,0,0,0},{0,0,0,0,0,0,0,0,0,0,0},{164,195,166,163,0,0,0,0,0,0,0,0,0,0,0,0,0,0,0,0,0,0,0,0,0,0,0,0,0,0}},
   {10,4,7,33,255,{64,71,87,34,236,225,145,0,0,0,0},{0,0,0,0,0,0,0,0,0,0,0},{97,195,145,108,0,0,0,0,0,0,0,0,0,0,0,0,0,0,0,0,0,0,0,0,0,0,0,0,0,0}},
   {11,4,5,4,255,{59,22,251,111,176,0,0,0,0,0,0},{0,0,0,3,0,0,0,0,0,0,0},{97,195,200,163,0,0,0,0,0,0,0,0,0,0,0,0,0,0,0,0,0,0,0,0,0,0,0,0,0,0}},
   {12,4,6,0,255,{76,21,113,84,108,232,0,0,0,0,0},{0,0,0,0,0,0,0,0,0,0,0},{97,195,200,163,0,0,0,0,0,0,0,0,0,0,0,0,0,0,0,0,0,0,0,0,0,0,0,0,0,0}},
   {13,4,5,16,255,{61,139,100,42,92,0,0,0,0,0,0},{0,0,0,0,31,0,0,0,0,0,0},{169,7,171,70,0,0,0,0,0,0,0,0,0,0,0,0,0,0,0,0,0,0,0,0,0,0,0,0,0,0}},
   {14,4,4,32,255,{60,55,215,159,0,0,0,0,0,0,0},{0,0,0,224,0,0,0,0,0,0,0},{169,64,166,163,0,0,0,0,0,0,0,0,0,0,0,0,0,0,0,0,0,0,0,0,0,0,0,0,0,0}},
   {15,4,6,18,255,{4,140,114,38,237,204,0,0,0,0,0},{0,0,0,0,7,0,0,0,0,0,0},{164,195,65,70,0,0,0,0,0,0,0,0,0,0,0,0,0,0,0,0,0,0,0,0,0,0,0,0,0,0}},
   {9,4,7,41,255,{74,142,253,196,161,177,149,0,0,0,0},{0,0,0,0,0,0,63,0,0,0,0},{169,72,171,103,0,0,0,0,0,0,0,0,0,0,0,0,0,0,0,0,0,0,0,0,0,0,0,0,0,0}},
   {10,4,5,34,255,{28,119,198,127,200,0,0,0,0,0,0},{0,0,0,224,0,0,0,0,0,0,0},{101,72,192,194,0,0,0,0,0,0,0,0,0,0,0,0,0,0,0,0,0,0,0,0,0,0,0,0,0,0}},
   {11,4,6,22,255,{25,70,50,39,126,146,0,0,0,0,0},{0,0,0,0,0,0,0,0,0,0,0},{101,98,145,103,0,0,0,0,0,0,0,0,0,0,0,0,0,0,0,0,0,0,0,0,0,0,0,0,0,0}},
   {12,4,5,14,255,{7,18,85,195,162,0,0,0,0,0,0},{0,0,0,0,0,0,0,0,0,0,0},{101,64,145,103,0,0,0,0,0,0,0,0,0,0,0,0,0,0,0,0,0,0,0,0,0,0,0,0,0,0}},
   {13,4,5,6,255,{29,20,175,107,207,0,0,0,0,0,0},{0,0,0,0,192,0,0,0,0,0,0},{97,64,145,163,0,0,0,0,0,0,0,0,0,0,0,0,0,0,0,0,0,0,0,0,0,0,0,0,0,0}},
   {14,4,5,8,255,{31,51,86,210,241,0,0,0,0,0,0},{0,0,0,0,0,0,0,0,0,0,0},{97,195,171,103,0,0,0,0,0,0,0,0,0,0,0,0,0,0,0,0,0,0,0,0,0,0,0,0,0,0}},
   {15,4,6,20,255,{65,27,54,199,234,206,0,0,0,0,0},{0,0,0,128,0,0,0,0,0,0,0},{169,64,226,78,0,0,0,0,0,0,0,0,0,0,0,0,0,0,0,0,0,0,0,0,0,0,0,0,0,0}},
   {6,2,5,7,255,{57,143,116,37,104,0,0,0,0,0,0},{0,0,0,0,0,0,0,0,0,0,0},{103,163,0,0,0,0,0,0,0,0,0,0,0,0,0,0,0,0,0,0,0,0,0,0,0,0,0,0,0,0}},
   {7,7,7,46,255,{8,138,17,117,214,122,156,0,0,0,0},{0,0,0,0,64,0,31,0,0,0,0},{105,96,113,97,110,127,106,0,0,0,0,0,0,0,0,0,0,0,0,0,0,0,0,0,0,0,0,0,0,0}}},
  {{0,10,0,0},{3,64,0,0},{6,64,0,0},{8,16,0,0},{0,6,0,0},{0,3,0,0},{0,2,0,0},{0,6,0,0},{22,64,0,0},{16,64,0,0},{20,64,0,0},
   {6,64,0,0},{0,1,0,0},{0,7,0,0},{8,19,0,0},{7,18,0,0},{22,64,0,0},{16,64,0,0},{10,64,0,0},{6,64,0,0},{0,9,0,0},{12,64,0,0},
   {0,3,0,0},{0,8,0,0},{18,64,0,0},{10,22,0,0},{8,19,0,0},{0,7,0,0},{17,64,0,0},{7,18,0,0},{3,13,0,0},{0,6,0,0},{0,7,0,0},
   {2,13,0,0},{7,20,0,0},{19,64,0,0},{0,7,0,0},{2,13,0,0},{13,64,0,0},{18,64,0,0},{0,6,0,0},{10,19,0,0},{1,12,0,0},{0,3,0,0},
   {10,64,0,0},{0,10,0,0},{0,8,0,0},{7,19,0,0},{0,10,0,0},{8,18,0,0},{13,64,0,0},{0,10,0,0},{19,64,0,0},{19,64,0,0},{13,64,0,0},
   {0,8,0,0},{10,17,0,0},{0,2,0,0},{0,8,0,0},{8,22,0,0},{19,64,0,0},{9,16,0,0},{18,64,0,0},{3,10,0,0},{6,64,0,0},{0,8,0,0}},
  {{38,59,55,56,31,50,51,49,33,53,23,27,61,41,58,45,46,57,36,6,7,18,19,16,17,0,1,34,35,2,3,14,15,4,5,12,13,24,25,28,29,62,63,20,21,10,11,42,43,8,9,48,32,52,22,26,60,40,39,44,54,47,30,37},
   {40,39,44,55,56,31,37,22,26,60,41,58,45,46,57,36,50,51,6,7,18,19,16,17,0,1,34,35,2,3,14,15,4,5,12,13,24,25,28,29,62,63,20,21,10,11,42,43,8,9,48,49,32,33,52,53,23,27,61,38,59,54,47,30},
   {52,22,27,40,39,44,55,56,31,50,23,60,41,58,45,46,57,36,51,6,7,18,19,16,17,0,1,34,35,2,3,14,15,4,5,12,13,24,25,28,29,62,63,20,21,10,11,42,43,8,9,48,49,32,33,53,26,61,38,59,54,47,30,37},
   {60,38,59,31,45,55,57,47,37,51,14,15,18,19,6,7,16,17,0,1,34,35,2,3,4,5,12,13,28,29,24,25,62,63,10,11,8,9,42,43,48,49,20,21,32,33,52,53,22,23,26,27,40,41,61,39,58,30,44,54,56,46,36,50},
   {22,27,60,39,30,45,56,47,32,52,23,40,61,58,31,54,57,36,50,14,15,18,19,6,7,16,17,0,1,34,35,2,3,4,5,12,13,28,29,24,25,62,63,10,11,8,9,42,43,48,49,20,21,33,53,26,41,38,59,44,55,46,37,51},
   {60,39,30,45,56,47,50,52,22,26,40,61,58,31,54,57,36,51,14,15,18,19,6,7,16,17,0,1,34,35,2,3,4,5,12,13,28,29,24,25,62,63,10,11,8,9,42,43,48,49,20,21,32,33,53,23,27,41,38,59,44,55,46,37},
   {60,41,30,39,54,57,36,50,51,23,40,59,38,45,56,47,18,19,14,15,6,7,16,17,34,35,0,1,4,5,2,3,12,13,28,29,24,25,62,63,10,11,20,21,42,43,8,9,32,33,48,49,26,27,52,53,22,61,58,31,44,55,46,37},
   {55,57,47,37,50,51,18,19,14,15,6,7,16,17,34,35,0,1,4,5,2,3,12,13,28,29,24,25,62,63,10,11,20,21,42,43,8,9,32,33,48,49,26,27,52,53,22,23,60,61,40,41,58,59,30,31,38,39,44,45,54,56,46,36},
   {22,61,58,31,44,56,47,50,48,26,52,60,41,30,39,54,57,36,18,19,14,15,6,7,16,17,34,35,0,1,4,5,2,3,12,13,28,29,24,25,62,63,10,11,20,21,42,43,8,9,32,33,49,27,53,23,40,59,38,45,55,46,37,51},
   {33,52,41,60,59,30,55,56,37,50,43,49,22,53,26,61,38,31,44,57,46,51,14,15,18,19,6,7,0,1,16,17,34,35,4,5,2,3,12,13,28,29,24,25,62,63,10,11,8,9,20,21,42,48,32,23,40,27,58,39,54,45,36,47},
   {41,60,59,30,55,56,37,50,26,61,38,31,44,57,46,51,14,15,18,19,6,7,0,1,16,17,34,35,4,5,2,3,12,13,28,29,24,25,62,63,10,11,8,9,20,21,42,43,48,49,32,33,22,23,52,53,40,27,58,39,54,45,36,47},
   {47,50,51,14,15,18,19,6,7,0,1,16,17,34,35,4,5,2,3,12,13,28,29,24,25,62,63,10,11,8,9,20,21,42,43,48,49,32,33,22,23,52,53,40,41,26,27,60,61,58,59,38,39,30,31,54,55,44,45,56,57,36,37,46},
   {45,56,47,27,61,41,59,31,39,54,57,36,50,14,15,18,19,6,7,0,1,16,17,34,35,4,5,2,3,12,13,28,29,24,25,62,63,10,11,42,43,20,21,8,9,48,49,32,33,52,53,22,23,26,60,40,58,30,38,44,55,46,37,51},
   {40,59,38,45,56,47,50,8,48,32,52,22,26,60,41,30,39,54,57,36,14,15,18,19,6,7,0,1,16,17,34,35,4,5,2,3,12,13,28,29,24,25,62,63,10,11,42,43,20,21,9,49,33,53,23,27,61,58,31,44,55,46,37,51},
   {27,40,59,38,45,56,47,50,49,33,53,23,60,41,30,39,54,57,37,14,15,18,19,6,7,0,1,16,17,34,35,4,5,2,3,12,13,28,29,24,25,62,63,10,11,42,43,20,21,8,9,48,32,52,22,26,61,58,31,44,55,46,36,51},
   {45,55,57,47,37,51,18,19,6,7,14,15,0,1,16,17,34,35,4,5,2,3,12,13,28,29,24,25,62,63,10,11,20,21,42,43,8,9,48,49,32,33,52,53,22,23,60,61,26,27,40,41,58,59,30,31,38,39,44,54,56,46,36,50},
   {47,50,23,61,27,41,59,31,39,45,55,57,36,18,19,6,7,14,15,0,1,16,17,34,35,4,5,2,3,12,13,28,29,24,25,62,63,10,11,20,21,42,43,8,9,48,49,32,33,52,53,22,60,26,40,58,30,38,44,54,56,46,37,51},
   {50,51,61,27,41,59,31,39,45,55,57,47,37,18,19,6,7,14,15,0,1,16,17,34,35,4,5,2,3,12,13,28,29,24,25,62,63,10,11,20,21,42,43,8,9,48,49,32,33,52,53,22,23,60,26,40,58,30,38,44,54,56,46,36},
   {23,33,27,40,59,38,45,46,57,50,60,41,30,39,54,47,36,18,19,14,15,0,1,6,7,16,17,34,35,4,5,2,3,12,13,28,29,24,25,62,63,10,11,20,21,42,43,8,9,48,49,52,53,22,32,26,61,58,31,44,55,56,37,51},
   {44,54,46,56,36,50,18,19,14,15,0,1,6,7,16,17,34,35,4,5,2,3,12,13,28,29,24,25,62,63,10,11,20,21,42,43,8,9,48,49,52,53,22,23,32,33,26,27,60,61,40,41,58,59,30,31,38,39,45,55,47,57,37,51},
   {47,36,50,58,30,38,44,54,46,57,18,19,14,15,0,1,6,7,16,17,34,35,4,5,2,3,12,13,28,29,24,25,62,63,10,11,20,21,42,43,8,9,48,49,52,53,22,23,32,33,26,27,60,61,40,41,59,31,39,45,55,56,37,51},
   {50,26,60,40,58,30,38,44,54,56,36,46,14,15,18,19,6,7,0,1,16,17,34,35,4,5,2,3,12,13,28,29,24,25,62,63,10,11,20,21,42,43,8,9,48,49,52,53,32,33,22,23,27,61,41,59,31,39,45,55,57,37,47,51},
   {27,40,59,38,45,56,37,50,43,9,49,53,33,23,60,41,30,39,54,57,46,51,14,15,18,19,6,7,0,1,16,17,34,35,4,5,2,3,12,13,28,29,24,25,62,63,10,11,20,21,42,8,48,52,32,22,26,61,58,31,44,55,36,47},
   {39,45,55,57,37,50,14,15,18,19,6,7,0,1,16,17,34,35,4,5,2,3,12,13,28,29,24,25,62,63,10,11,20,21,42,43,8,9,48,49,52,53,32,33,22,23,26,27,60,61,40,41,58,59,30,31,38,44,54,56,36,46,47,51}},
  {{4,4,3,3,3,3,2,3},{6,6,7,7,7,7,7,7},{7,7,6,6,6,6,6,6},{1,2,2,2,2,1,3,2},
   {15,15,3,4,4,4,4,6},{12,12,12,12,12,0,0,1},{8,8,8,8,8,8,8,8},{0,0,1,0,0,2,1,0},
   {3,3,4,4,4,4,4,4},{2,1,0,1,1,0,0,1},{13,13,13,1,1,2,2,0},{5,5,7,8,8,7,7,4},
   {10,10,10,10,10,10,10,10},{7,7,8,9,9,9,9,8},{9,9,9,9,9,9,9,9},{11,10,12,1,1,2,2,3},
   {4,4,5,7,7,8,8,9},{5,5,5,5,5,5,5,5},{3,3,11,11,11,10,10,0},{16,11,13,4,4,4,4,6},
   {1,8,11,12,12,0,0,0},{14,14,0,3,3,3,3,3},{12,12,3,5,5,3,5,7},{15,1,9,12,12,0,0,1},
   {2,1,4,5,5,5,5,5},{6,6,8,10,10,11,11,8},{3,3,6,6,6,6,6,7},{13,13,4,7,7,5,8,9},
   {2,15,5,9,9,9,9,11},{0,9,10,10,10,11,10,1},{6,6,9,11,11,10,11,11},{11,11,11,11,11,11,11,11}},
  {{255,255,255,255,255,255,255,255},{255,255,255,255,255,255,255,255},{255,255,255,255,255,255,255,255},{255,255,255,255,255,255,255,255},
   {255,255,0,8,8,8,8,2},{255,255,255,255,255,9,9,9},{255,255,255,255,255,255,255,255},{255,255,255,255,255,255,255,255},
   {255,255,255,255,255,255,255,255},{255,255,255,255,255,255,255,255},{255,255,255,9,9,7,0,7},{17,17,1,6,6,1,1,8},
   {255,255,255,255,255,255,255,255},{2,2,6,14,14,14,14,6},{255,255,255,255,255,255,255,255},{31,12,5,10,10,10,10,21},
   {0,0,17,1,1,6,6,14},{255,255,255,255,255,255,255,255},{26,26,20,30,30,30,29,20},{255,31,10,4,4,4,4,4},
   {3,6,31,5,5,5,5,10},{255,255,9,0,0,0,3,0},{5,5,4,24,24,21,24,26},{4,24,30,20,20,20,20,29},
   {9,9,8,17,17,17,17,17},{30,30,13,29,29,29,30,13},{8,8,2,2,2,2,2,1},{10,10,24,16,16,24,16,16},
   {24,4,16,13,13,13,13,30},{7,14,12,12,12,31,12,5},{1,1,14,31,31,12,31,31},{255,255,255,255,255,255,255,255}},
  {112,113,114,115,116,117,118,119,120,121,122,123,124,125,126,127,128,129,130,131,132,133,134,135,136,137,138,139,140,141,142,143,46,637,13,78,11,371,74,15,152,42,40,36,38,647,391,2,160,161,162,163,164,165,166,167,168,169,170,171,172,173,174,175,176,177,178,179,180,181,182,183,184,185,186,187,188,189,190,191,73,16,638,79,80,76,8,43,200,201,202,52,204,634,48,85,6,3,1,211,212,213,214,215,216,217,83,642,220,455,643,223,7,4,226,227,228,229,230,231,68,55,26,92,24,20,18,56,89,86,14,53,81,50,49,247,248,249,250,251,252,253,254,255,69,64,35,31,33,29,27,65,59,98,96,22,94,90,19,271,272,273,274,385,276,711,369,279,280,372,381,9,382,77,75,628,288,289,97,291,95,91,61,295,296,66,63,32,34,30,302,67,47,17,84,10,12,627,388,45,103,101,100,71,99,70,28,102,387,87,322,323,82,51,644,88,328,329,330,93,332,333,62,335,336,337,338,339,340,341,342,343,60,345,54,23,25,21,625,57,352,58,354,641,356,386,378,359,72,44,41,37,39,0,366,5},
  {511,511,511,511,511,511,511,511,511,511,511,511,511,511,511,511,511,511,511,511,511,511,511,511,511,511,511,511,511,511,511,511,257,29,257,256,257,59,256,257,511,256,256,256,256,31,31,256,511,511,511,511,511,511,511,511,511,511,511,511,511,511,511,511,511,511,511,511,511,511,511,511,511,511,511,511,511,511,511,511,256,257,62,256,256,256,256,256,511,511,511,257,511,58,257,257,256,256,256,511,511,511,511,511,511,511,257,26,511,103,27,511,256,256,511,511,511,511,511,511,259,258,258,258,258,258,258,258,257,257,257,257,257,257,257,511,511,511,511,511,511,511,511,511,259,259,259,259,259,259,259,259,258,258,258,258,258,258,258,511,511,511,511,25,511,103,57,511,511,60,29,257,62,256,256,60,511,511,258,511,258,258,258,511,511,259,259,259,259,259,511,259,257,257,257,257,257,59,28,257,259,259,259,259,259,259,259,259,27,257,511,511,257,257,28,257,511,511,511,258,511,511,258,511,511,511,511,511,511,511,511,511,258,511,258,258,258,258,57,258,511,258,511,25,511,26,58,511,256,256,256,256,256,256,511,256}};

typedef CUresult (*EncodeFn)(CUtensorMap*, CUtensorMapDataType, cuuint32_t, void*, const cuuint64_t*, const cuuint64_t*, const cuuint32_t*,
                             const cuuint32_t*, CUtensorMapInterleave, CUtensorMapSwizzle, CUtensorMapL2promotion, CUtensorMapFloatOOBfill);

void make_map2(EncodeFn enc, CUtensorMap* m, const void* ptr, int rows, int cols, int box_rows) {
  cuuint64_t dim[2] = {(cuuint64_t)cols, (cuuint64_t)rows}, str[1] = {(cuuint64_t)cols * 2};
  cuuint32_t box[2] = {64, (cuuint32_t)box_rows}, es[2] = {1, 1};
  enc(m, CU_TENSOR_MAP_DATA_TYPE_BFLOAT16, 2, const_cast<void*>(ptr), dim, str, box, es, CU_TENSOR_MAP_INTERLEAVE_NONE, CU_TENSOR_MAP_SWIZZLE_128B,
      CU_TENSOR_MAP_L2_PROMOTION_L2_128B, CU_TENSOR_MAP_FLOAT_OOB_FILL_NONE);
}
void make_map3(EncodeFn enc, CUtensorMap* m, const void* ptr, int rows) {
  cuuint64_t dim[3] = {64, (cuuint64_t)rows, 9}, str[2] = {DM * 2, 128};
  cuuint32_t box[3] = {64, 32, 3}, es[3] = {1, 1, 1};
  enc(m, CU_TENSOR_MAP_DATA_TYPE_BFLOAT16, 3, const_cast<void*>(ptr), dim, str, box, es, CU_TENSOR_MAP_INTERLEAVE_NONE, CU_TENSOR_MAP_SWIZZLE_128B,
      CU_TENSOR_MAP_L2_PROMOTION_L2_128B, CU_TENSOR_MAP_FLOAT_OOB_FILL_NONE);
}

void make_map_t(EncodeFn enc, CUtensorMap* m, void* ptr, int width, int cols) {
  cuuint64_t dim[3] = {SEQ / 2, 2, 864}, str[2] = {SEQ * 2, SEQ * 4};
  cuuint32_t box[3] = {(cuuint32_t)width, 2, (cuuint32_t)cols}, es[3] = {1, 1, 1};
  enc(m, CU_TENSOR_MAP_DATA_TYPE_UINT32, 3, ptr, dim, str, box, es, CU_TENSOR_MAP_INTERLEAVE_NONE, cols == 64 ? CU_TENSOR_MAP_SWIZZLE_128B : CU_TENSOR_MAP_SWIZZLE_NONE,
      CU_TENSOR_MAP_L2_PROMOTION_NONE, CU_TENSOR_MAP_FLOAT_OOB_FILL_NONE);
}

int g_mode = -1;

}

extern "C" void kernel_launch(void* const* d_in, const int* in_sizes, int n_in, void* d_out, int out_size) {
  static EncodeFn enc = nullptr;
  static void* t_ptr = nullptr;
  if (!enc) {
    void* fn = nullptr;
    cudaDriverEntryPointQueryResult st;
    cudaGetDriverEntryPoint("cuTensorMapEncodeTiled", &fn, cudaEnableDefault, &st);
    enc = (EncodeFn)fn;
    cudaGetSymbolAddress(&t_ptr, g_S);
    cudaFuncSetAttribute(fused_kernel, cudaFuncAttributeMaxDynamicSharedMemorySize, SMEM_BYTES);
    if (g_mode < 0) {
      cudaLaunchConfig_t cfg = {};
      cfg.gridDim = dim3(2 * NCL); cfg.blockDim = dim3(384); cfg.dynamicSmemBytes = SMEM_BYTES;
      cudaLaunchAttribute at; at.id = cudaLaunchAttributeClusterDimension;
      at.val.clusterDim.x = 2; at.val.clusterDim.y = 1; at.val.clusterDim.z = 1;
      cfg.attrs = &at; cfg.numAttrs = 1;
      int nc = 0;
      g_mode = (cudaOccupancyMaxActiveClusters(&nc, fused_kernel, &cfg) == cudaSuccess && nc >= NCL) ? 1 : 0;
      (void)cudaGetLastError();
    }
  }
  Params p;
  make_map2(enc, &p.map_a[0], d_in[4], SEQ, DC, 128);
  make_map2(enc, &p.map_a[1], d_in[0], SEQ, DM, 128);
  make_map2(enc, &p.map_w[0], d_in[6], DC, 4096, 64);
  make_map2(enc, &p.map_w[1], d_in[7], DC, 4096, 64);
  make_map2(enc, &p.map_w[2], d_in[5], DM, 4096, 64);
  make_map2(enc, &p.map_w[3], d_in[1], DM, 1728, 64);
  make_map3(enc, &p.map_o[0], d_in[8], 4096);
  make_map3(enc, &p.map_o[1], d_in[2], DM);
  make_map_t(enc, &p.map_t[0], t_ptr, 32, 9);
  make_map_t(enc, &p.map_t[1], t_ptr, 40, 9);
  make_map_t(enc, &p.map_t[2], t_ptr, 32, 64);
  p.x = (const __nv_bfloat16*)d_in[0];
  p.gate_w = (const __nv_bfloat16*)d_in[9];
  make_map2(enc, &p.map_out, d_out, SEQ, DM, 64);
  p.out = (__nv_bfloat16*)d_out;
  p.zero = 0;
  auto launch = [&](int phases) {
    p.s = k_sched;
    for (int i = 0; i < NCL; i++) {
      Rec& r = p.s.r[i];
      if (!(phases & 1)) r.n1 = 0;
      if (!(phases & 2)) r.n2 = 0;
      if (!(phases & (p.s.task[i][1] == 64 ? 4 : 32))) r.p3 = 255;
      if (!(phases & 8)) r.bg = 255;
      const int u1 = r.n1 ? 8 + r.n1 * (8 + (r.slab >> 3)) : 0;
      int u2 = 0;
      for (int k = 0; k < r.n2; k++) u2 += 4 * (r.item[k] & 7) + 4;
      r.u1 = (uint8_t)u1; r.u2 = (uint8_t)u2;
      r.rot = (uint8_t)(((u1 % 10 + 1) >> 1) % 5);
      r.x3 = (uint8_t)((r.rot + u2) % 5 & 3);
      r.phases = (uint8_t)phases;
    }
    if (!(phases & 16))
      for (int i = 0; i < 256; i++) { p.s.slot[i >> 3][i & 7] = (uint8_t)(i >> 3); p.s.prev[i >> 3][i & 7] = 255; p.s.qblk[i] = (uint16_t)(S_Q + i); p.s.qdep[i] = 511; }
    fused_kernel<<<2 * NCL, 384, SMEM_BYTES>>>(p);
  };
  if (g_mode == 1) launch(63);
  else { launch(1); launch(10); launch(4); launch(32); }
}
```

```cpp
#include <cuda_runtime.h>
#include <cuda_bf16.h>
#include <cuda.h>
#include <stdint.h>

namespace {

constexpr int SEQ = 2048, DM = 576, DC = 512, NH = 32;
constexpr int NCL = 66;
constexpr uint32_t DESC_HI = 0x40000040u;

constexpr int SM_RING = 0;
constexpr int SM_BUF = 163840;
constexpr int SM_BAR = 229376;
constexpr int B_P1E = 0, B_P2E = 10, B_P3E = 15, B_P2F = 24, B_SF = 32, B_ORD = 36, B_LAD = 40, B_DONE = 41, B_FIN = 48, B_T0 = 49;
constexpr int B_P3F = 56, B_OUT = 61, B_ZF = 62, B_P1F = 64, B_SE = 74, B_QF = 80, B_LA = 84, B_NUM = 88;
constexpr uint64_t B_CNT = 0x11118245000ull;
constexpr int SMEM_BYTES = SM_BAR + B_NUM * 8 + 1024;

constexpr int F_QKVA = 32;
constexpr int F_GATE = 64;
constexpr int F_TS = 68;
constexpr int F_DONE = 65;
constexpr int F_CTX = 96;
constexpr int F_OUT = 96 + 8 * 64;
constexpr int F_KV = F_OUT + 64;
constexpr int F_Q = F_KV + 256;
constexpr int F_RD = F_Q + 256;
constexpr int F_NUM = F_RD + 256;

struct Rec {
  uint8_t slab;
  uint8_t n1, n2;
  uint8_t p3;
  uint8_t bg;
  uint8_t item[11];
  uint8_t last[11];
  uint8_t tile[32];
  uint8_t u1, u2;
  uint8_t rot, x3;
  uint8_t phases;
};
struct Sched {
  Rec r[NCL];
  uint8_t task[NCL][4];
  uint8_t p3_order[24][64];
  uint8_t slot[32][8];
  uint8_t prev[32][8];
  uint16_t qblk[256];
  uint16_t qdep[256];
};


struct Params {
  CUtensorMap map_a[2];
  CUtensorMap map_w[4];
  CUtensorMap map_o[2];
  CUtensorMap map_t[3];
  CUtensorMap map_out;
  const __nv_bfloat16* x;
  const __nv_bfloat16* gate_w;
  __nv_bfloat16* out;
  int zero;
  alignas(64) Sched s;
};

constexpr int S_Q = 112, S_K = S_Q + 256, S_V = S_K + 256, S_NUM = S_V + 256;
__device__ __align__(1024) uint8_t g_S[(size_t)S_NUM * 65536];
__device__ __align__(1024) uint8_t g_oA[32 * 576 * 128];
__device__ float g_gate[SEQ];
__device__ int g_flags[F_NUM];

__device__ __forceinline__ void mbar_arrive(uint32_t b) { asm volatile("mbarrier.arrive.shared::cta.b64 _, [%0];" ::"r"(b) : "memory"); }
__device__ __forceinline__ void mbar_arrive_cl(uint32_t b, int cnt) {
  asm volatile("mbarrier.arrive.shared::cluster.b64 _, [%0], %1;" ::"r"(b), "r"(cnt) : "memory");
}
__device__ __forceinline__ void mbar_wait(uint32_t b, int par) {
  asm volatile(
      "{\n.reg .pred p;\n.reg .u32 c;\n"
      "mbarrier.try_wait.parity.shared::cta.b64 p, [%0], %1;\n@p bra DN;\nmov.u32 c, 0;\n"
      "LP:\nmbarrier.try_wait.parity.shared::cta.b64 p, [%0], %1;\n@p bra DN;\n"
      "add.u32 c, c, 1;\nsetp.lt.u32 p, c, 4000000;\n@p bra LP;\ntrap;\nDN:\n}" ::"r"(b), "r"(par) : "memory");
}
__device__ __forceinline__ bool mbar_test(uint32_t b, int par) {
  uint32_t ok;
  asm volatile("{\n.reg .pred p;\nmbarrier.test_wait.parity.shared::cta.b64 p, [%1], %2;\nselp.u32 %0, 1, 0, p;\n}" : "=r"(ok) : "r"(b), "r"(par) : "memory");
  return __all_sync(0xffffffffu, ok);
}
__device__ __forceinline__ uint32_t mapa(uint32_t a, uint32_t cta) {
  uint32_t r; asm("mapa.shared::cluster.u32 %0, %1, %2;" : "=r"(r) : "r"(a), "r"(cta)); return r;
}
#define ELECT(ins) "{\n.reg .pred e;\nelect.sync _|e, 0xffffffff;\n@e " ins "\n}"
__device__ __forceinline__ void mbar_expect(uint32_t b, int bytes) {
  asm volatile(ELECT("mbarrier.arrive.expect_tx.shared::cta.b64 _, [%0], %1;") ::"r"(b), "r"(bytes) : "memory");
}
__device__ __forceinline__ void mbar_arrive_one(uint32_t b) { asm volatile(ELECT("mbarrier.arrive.shared::cta.b64 _, [%0];") ::"r"(b) : "memory"); }
constexpr uint64_t L2_NORMAL = 0x1000000000000000ull, L2_FIRST = 0x12F0000000000000ull;
__device__ __forceinline__ void bulk_load(uint32_t dst, const void* src, int bytes, uint32_t bar, uint64_t pol = L2_NORMAL) {
  asm volatile(ELECT("cp.async.bulk.shared::cluster.global.mbarrier::complete_tx::bytes.L2::cache_hint [%0], [%1], %2, [%3], %4;") ::"r"(dst), "l"(src), "r"(bytes), "r"(bar), "l"(pol) : "memory");
}
__device__ __forceinline__ void bulk_load_mc(uint32_t dst, const void* src, int bytes, uint32_t bar, uint64_t pol = L2_NORMAL) {
  asm volatile(ELECT("cp.async.bulk.shared::cluster.global.mbarrier::complete_tx::bytes.multicast::cluster.L2::cache_hint [%0], [%1], %2, [%3], %4, %5;") ::"r"(dst), "l"(src), "r"(bytes), "r"(bar), "h"((uint16_t)3), "l"(pol) : "memory");
}
__device__ __forceinline__ void bulk_store(void* dst, uint32_t src, int bytes, uint64_t pol = L2_NORMAL) {
  asm volatile(ELECT("cp.async.bulk.global.shared::cta.bulk_group.L2::cache_hint [%0], [%1], %2, %3;") ::"l"(dst), "r"(src), "r"(bytes), "l"(pol) : "memory");
}
__device__ __forceinline__ void tma2d(uint32_t dst, const CUtensorMap* m, int c0, int c1, uint32_t bar, uint64_t pol = L2_NORMAL) {
  asm volatile(ELECT("cp.async.bulk.tensor.2d.shared::cluster.global.mbarrier::complete_tx::bytes.L2::cache_hint [%0], [%1, {%3, %4}], [%2], %5;") ::"r"(dst), "l"(m), "r"(bar), "r"(c0), "r"(c1), "l"(pol) : "memory");
}
__device__ __forceinline__ void tma2d_mc(uint32_t dst, const CUtensorMap* m, int c0, int c1, uint32_t bar, uint64_t pol = L2_NORMAL) {
  asm volatile(ELECT("cp.async.bulk.tensor.2d.shared::cluster.global.mbarrier::complete_tx::bytes.multicast::cluster.L2::cache_hint [%0], [%1, {%3, %4}], [%2], %5, %6;") ::"r"(dst), "l"(m), "r"(bar), "r"(c0), "r"(c1), "h"((uint16_t)3), "l"(pol) : "memory");
}
__device__ __forceinline__ void tma3d(uint32_t dst, const CUtensorMap* m, int c0, int c1, int c2, uint32_t bar, uint64_t pol = L2_NORMAL) {
  asm volatile(ELECT("cp.async.bulk.tensor.3d.shared::cluster.global.mbarrier::complete_tx::bytes.L2::cache_hint [%0], [%1, {%3, %4, %5}], [%2], %6;") ::"r"(dst), "l"(m), "r"(bar), "r"(c0), "r"(c1), "r"(c2), "l"(pol) : "memory");
}
__device__ __forceinline__ void tma3d_mc(uint32_t dst, const CUtensorMap* m, int c0, int c1, int c2, uint32_t bar, uint64_t pol = L2_NORMAL) {
  asm volatile(ELECT("cp.async.bulk.tensor.3d.shared::cluster.global.mbarrier::complete_tx::bytes.multicast::cluster.L2::cache_hint [%0], [%1, {%3, %4, %5}], [%2], %6, %7;") ::"r"(dst), "l"(m), "r"(bar), "r"(c0), "r"(c1), "r"(c2), "h"((uint16_t)3), "l"(pol) : "memory");
}
__device__ __forceinline__ void tma2d_add(const CUtensorMap* m, uint32_t src, int c0, int c1) {
  asm volatile(ELECT("cp.reduce.async.bulk.tensor.2d.global.shared::cta.add.bulk_group [%0, {%2, %3}], [%1];") ::"l"(m), "r"(src), "r"(c0), "r"(c1) : "memory");
}
__device__ __forceinline__ void tma3d_store(const CUtensorMap* m, uint32_t src, int c0, int c1, int c2, uint64_t pol = L2_NORMAL) {
  asm volatile(ELECT("cp.async.bulk.tensor.3d.global.shared::cta.bulk_group.L2::cache_hint [%0, {%2, %3, %4}], [%1], %5;") ::"l"(m), "r"(src), "r"(c0), "r"(c1), "r"(c2), "l"(pol) : "memory");
}
__device__ __forceinline__ void tma2d_prefetch(const CUtensorMap* m, int c0, int c1, uint64_t pol = L2_NORMAL) {
  asm volatile(ELECT("cp.async.bulk.prefetch.tensor.2d.L2.global.L2::cache_hint [%0, {%1, %2}], %3;") ::"l"(m), "r"(c0), "r"(c1), "l"(pol) : "memory");
}
#define LAG 3
#define HINT 63
#define POL(bit) ((HINT >> (bit)) & 1 ? L2_FIRST : L2_NORMAL)
#define BULK_COMMIT() asm volatile("cp.async.bulk.commit_group;" ::: "memory")
#define BULK_WAIT(n) asm volatile("cp.async.bulk.wait_group %0;" ::"n"(n) : "memory")
#define BULK_WAIT_READ(n) asm volatile("cp.async.bulk.wait_group.read %0;" ::"n"(n) : "memory")
#define FENCE_ASYNC_SMEM() asm volatile("fence.proxy.async.shared::cta;" ::: "memory")
#define WG_FENCE() asm volatile("wgmma.fence.sync.aligned;" ::: "memory")
#define WG_COMMIT() asm volatile("wgmma.commit_group.sync.aligned;" ::: "memory")
#define WG_WAIT(n) asm volatile("wgmma.wait_group.sync.aligned %0;" ::"n"(n) : "memory")
__device__ __forceinline__ void bar_sync(int id, int n) { asm volatile("bar.sync %0, %1;" ::"r"(id), "r"(n) : "memory"); }
__device__ __forceinline__ void bar_arrive(int id, int n) { asm volatile("bar.arrive %0, %1;" ::"r"(id), "r"(n) : "memory"); }
__device__ __forceinline__ void cluster_sync() {
  asm volatile("barrier.cluster.arrive.relaxed;\nbarrier.cluster.wait.acquire;" ::: "memory");
}
template <int N> __device__ __forceinline__ void pin(float (&r)[N]) {
#pragma unroll
  for (int i = 0; i < N; i++) asm volatile("" : "+f"(r[i])::"memory");
}
template <int N> __device__ __forceinline__ void pin(uint32_t (&r)[N]) {
#pragma unroll
  for (int i = 0; i < N; i++) asm volatile("" : "+r"(r[i])::"memory");
}
__device__ __forceinline__ uint32_t pack_bf16(float lo, float hi) {
  uint32_t r; asm("cvt.rn.bf16x2.f32 %0, %1, %2;" : "=r"(r) : "f"(hi), "f"(lo)); return r;
}
__device__ __forceinline__ float ex2(float x) { float r; asm("ex2.approx.ftz.f32 %0, %1;" : "=f"(r) : "f"(x)); return r; }
__device__ __forceinline__ void ldsm4(uint32_t a, uint32_t& r0, uint32_t& r1, uint32_t& r2, uint32_t& r3) {
  asm volatile("ldmatrix.sync.aligned.m8n8.x4.shared.b16 {%0,%1,%2,%3}, [%4];" : "=r"(r0), "=r"(r1), "=r"(r2), "=r"(r3) : "r"(a) : "memory");
}
__device__ __forceinline__ void stsm4(uint32_t a, uint32_t r0, uint32_t r1, uint32_t r2, uint32_t r3) {
  asm volatile("stmatrix.sync.aligned.m8n8.x4.shared.b16 [%0], {%1,%2,%3,%4};" ::"r"(a), "r"(r0), "r"(r1), "r"(r2), "r"(r3) : "memory");
}
__device__ __forceinline__ void flag_add(int idx, int v = 1) {
  asm volatile(ELECT("red.release.gpu.global.add.s32 [%0], %1;") ::"l"(g_flags + idx), "r"(v) : "memory");
}
__device__ __forceinline__ void flag_add_rx(int idx, int v = 1) {
  asm volatile(ELECT("red.relaxed.gpu.global.add.s32 [%0], %1;") ::"l"(g_flags + idx), "r"(v) : "memory");
}
template <bool ACQ, int NS = 32> __device__ __forceinline__ void flag_wait(int idx, int target) {
  int n = 0;
  while (true) {
    int v;
    if (ACQ) asm volatile("ld.acquire.gpu.global.s32 %0, [%1];" : "=r"(v) : "l"(g_flags + idx) : "memory");
    else asm volatile("ld.relaxed.gpu.global.s32 %0, [%1];" : "=r"(v) : "l"(g_flags + idx) : "memory");
    if (__all_sync(0xffffffffu, v >= target)) break;
    if (++n > 20000000) __trap();
    __nanosleep(NS);
  }
}
__device__ __forceinline__ int flag_peek(int idx) {
  int v;
  asm volatile("ld.relaxed.gpu.global.s32 %0, [%1];" : "=r"(v) : "l"(g_flags + idx) : "memory");
  return v;
}
__device__ __forceinline__ void mask_wait(uint32_t& ready, int bit, int idx, int target) {
  for (int n = 0; !((ready >> bit) & 1); n++) {
    int v;
    if (n) { __nanosleep(32); if (n > 20000000) __trap(); }
    asm volatile("ld.relaxed.gpu.global.s32 %0, [%1];" : "=r"(v) : "l"(g_flags + idx) : "memory");
    ready = __ballot_sync(0xffffffffu, v >= target);
  }
}
__device__ __forceinline__ uint32_t desc_lo(uint32_t addr, uint32_t lbo) { return ((addr & 0x3FFFFu) >> 4) | ((lbo >> 4) << 16); }

template <int TB, int TA = 0> __device__ __forceinline__ void wgmma_ss64(float (&d)[32], uint32_t alo, uint32_t blo, int sd) {
  asm volatile("{\n.reg .pred p;\n.reg .b64 da, db;\n"
    "setp.ne.b32 p, %34, 0;\nmov.b64 da, {%32, %36};\nmov.b64 db, {%33, %36};\n"
    "wgmma.mma_async.sync.aligned.m64n64k16.f32.bf16.bf16 "
    "{%0,%1,%2,%3,%4,%5,%6,%7,%8,%9,%10,%11,%12,%13,%14,%15,%16,%17,%18,%19,%20,%21,%22,%23,"
    "%24,%25,%26,%27,%28,%29,%30,%31}, "
    "da, db, p, 1, 1, %37, %35;\n}\n"
    : "+f"(d[0]),"+f"(d[1]),"+f"(d[2]),"+f"(d[3]),"+f"(d[4]),"+f"(d[5]),"+f"(d[6]),"+f"(d[7]),"+f"(d[8]),"+f"(d[9]),"+f"(d[10]),"+f"(d[11]),
      "+f"(d[12]),"+f"(d[13]),"+f"(d[14]),"+f"(d[15]),"+f"(d[16]),"+f"(d[17]),"+f"(d[18]),"+f"(d[19]),"+f"(d[20]),"+f"(d[21]),"+f"(d[22]),"+f"(d[23]),
      "+f"(d[24]),"+f"(d[25]),"+f"(d[26]),"+f"(d[27]),"+f"(d[28]),"+f"(d[29]),"+f"(d[30]),"+f"(d[31])
    : "r"(alo), "r"(blo), "r"(sd), "n"(TB), "r"(DESC_HI), "n"(TA));
}
template <int TB, int TA = 0> __device__ __forceinline__ void wgmma_ss128(float (&d)[64], uint32_t alo, uint32_t blo, int sd) {
  asm volatile("{\n.reg .pred p;\n.reg .b64 da, db;\n"
    "setp.ne.b32 p, %66, 0;\nmov.b64 da, {%64, %68};\nmov.b64 db, {%65, %68};\n"
    "wgmma.mma_async.sync.aligned.m64n128k16.f32.bf16.bf16 "
    "{%0,%1,%2,%3,%4,%5,%6,%7,%8,%9,%10,%11,%12,%13,%14,%15,%16,%17,%18,%19,%20,%21,%22,%23,"
    "%24,%25,%26,%27,%28,%29,%30,%31,%32,%33,%34,%35,%36,%37,%38,%39,%40,%41,%42,%43,%44,%45,%46,%47,"
    "%48,%49,%50,%51,%52,%53,%54,%55,%56,%57,%58,%59,%60,%61,%62,%63}, "
    "da, db, p, 1, 1, %69, %67;\n}\n"
    : "+f"(d[0]),"+f"(d[1]),"+f"(d[2]),"+f"(d[3]),"+f"(d[4]),"+f"(d[5]),"+f"(d[6]),"+f"(d[7]),"+f"(d[8]),"+f"(d[9]),"+f"(d[10]),"+f"(d[11]),
      "+f"(d[12]),"+f"(d[13]),"+f"(d[14]),"+f"(d[15]),"+f"(d[16]),"+f"(d[17]),"+f"(d[18]),"+f"(d[19]),"+f"(d[20]),"+f"(d[21]),"+f"(d[22]),"+f"(d[23]),
      "+f"(d[24]),"+f"(d[25]),"+f"(d[26]),"+f"(d[27]),"+f"(d[28]),"+f"(d[29]),"+f"(d[30]),"+f"(d[31]),"+f"(d[32]),"+f"(d[33]),"+f"(d[34]),"+f"(d[35]),
      "+f"(d[36]),"+f"(d[37]),"+f"(d[38]),"+f"(d[39]),"+f"(d[40]),"+f"(d[41]),"+f"(d[42]),"+f"(d[43]),"+f"(d[44]),"+f"(d[45]),"+f"(d[46]),"+f"(d[47]),
      "+f"(d[48]),"+f"(d[49]),"+f"(d[50]),"+f"(d[51]),"+f"(d[52]),"+f"(d[53]),"+f"(d[54]),"+f"(d[55]),"+f"(d[56]),"+f"(d[57]),"+f"(d[58]),"+f"(d[59]),
      "+f"(d[60]),"+f"(d[61]),"+f"(d[62]),"+f"(d[63])
    : "r"(alo), "r"(blo), "r"(sd), "n"(TB), "r"(DESC_HI), "n"(TA));
}
template <int TB> __device__ __forceinline__ void wgmma_rs128(float (&d)[64], uint32_t a0, uint32_t a1, uint32_t a2, uint32_t a3, uint32_t blo, int sd) {
  asm volatile("{\n.reg .pred p;\n.reg .b64 db;\n"
    "setp.ne.b32 p, %69, 0;\nmov.b64 db, {%68, %71};\n"
    "wgmma.mma_async.sync.aligned.m64n128k16.f32.bf16.bf16 "
    "{%0,%1,%2,%3,%4,%5,%6,%7,%8,%9,%10,%11,%12,%13,%14,%15,%16,%17,%18,%19,%20,%21,%22,%23,"
    "%24,%25,%26,%27,%28,%29,%30,%31,%32,%33,%34,%35,%36,%37,%38,%39,%40,%41,%42,%43,%44,%45,%46,%47,"
    "%48,%49,%50,%51,%52,%53,%54,%55,%56,%57,%58,%59,%60,%61,%62,%63}, "
    "{%64,%65,%66,%67}, db, p, 1, 1, %70;\n}\n"
    : "+f"(d[0]),"+f"(d[1]),"+f"(d[2]),"+f"(d[3]),"+f"(d[4]),"+f"(d[5]),"+f"(d[6]),"+f"(d[7]),"+f"(d[8]),"+f"(d[9]),"+f"(d[10]),"+f"(d[11]),
      "+f"(d[12]),"+f"(d[13]),"+f"(d[14]),"+f"(d[15]),"+f"(d[16]),"+f"(d[17]),"+f"(d[18]),"+f"(d[19]),"+f"(d[20]),"+f"(d[21]),"+f"(d[22]),"+f"(d[23]),
      "+f"(d[24]),"+f"(d[25]),"+f"(d[26]),"+f"(d[27]),"+f"(d[28]),"+f"(d[29]),"+f"(d[30]),"+f"(d[31]),"+f"(d[32]),"+f"(d[33]),"+f"(d[34]),"+f"(d[35]),
      "+f"(d[36]),"+f"(d[37]),"+f"(d[38]),"+f"(d[39]),"+f"(d[40]),"+f"(d[41]),"+f"(d[42]),"+f"(d[43]),"+f"(d[44]),"+f"(d[45]),"+f"(d[46]),"+f"(d[47]),
      "+f"(d[48]),"+f"(d[49]),"+f"(d[50]),"+f"(d[51]),"+f"(d[52]),"+f"(d[53]),"+f"(d[54]),"+f"(d[55]),"+f"(d[56]),"+f"(d[57]),"+f"(d[58]),"+f"(d[59]),
      "+f"(d[60]),"+f"(d[61]),"+f"(d[62]),"+f"(d[63])
    : "r"(a0), "r"(a1), "r"(a2), "r"(a3), "r"(blo), "r"(sd), "n"(TB), "r"(DESC_HI));
}
template <int TB, int TA = 0> __device__ __forceinline__ void wgmma_ss192(float (&d)[96], uint32_t alo, uint32_t blo, int sd) {
  asm volatile("{\n.reg .pred p;\n.reg .b64 da, db;\n"
    "setp.ne.b32 p, %98, 0;\nmov.b64 da, {%96, %100};\nmov.b64 db, {%97, %100};\n"
    "wgmma.mma_async.sync.aligned.m64n192k16.f32.bf16.bf16 "
    "{%0,%1,%2,%3,%4,%5,%6,%7,%8,%9,%10,%11,%12,%13,%14,%15,%16,%17,%18,%19,%20,%21,%22,%23,"
    "%24,%25,%26,%27,%28,%29,%30,%31,%32,%33,%34,%35,%36,%37,%38,%39,%40,%41,%42,%43,%44,%45,%46,%47,"
    "%48,%49,%50,%51,%52,%53,%54,%55,%56,%57,%58,%59,%60,%61,%62,%63,%64,%65,%66,%67,%68,%69,%70,%71,"
    "%72,%73,%74,%75,%76,%77,%78,%79,%80,%81,%82,%83,%84,%85,%86,%87,%88,%89,%90,%91,%92,%93,%94,%95}, "
    "da, db, p, 1, 1, %101, %99;\n}\n"
    : "+f"(d[0]),"+f"(d[1]),"+f"(d[2]),"+f"(d[3]),"+f"(d[4]),"+f"(d[5]),"+f"(d[6]),"+f"(d[7]),"+f"(d[8]),"+f"(d[9]),"+f"(d[10]),"+f"(d[11]),
      "+f"(d[12]),"+f"(d[13]),"+f"(d[14]),"+f"(d[15]),"+f"(d[16]),"+f"(d[17]),"+f"(d[18]),"+f"(d[19]),"+f"(d[20]),"+f"(d[21]),"+f"(d[22]),"+f"(d[23]),
      "+f"(d[24]),"+f"(d[25]),"+f"(d[26]),"+f"(d[27]),"+f"(d[28]),"+f"(d[29]),"+f"(d[30]),"+f"(d[31]),"+f"(d[32]),"+f"(d[33]),"+f"(d[34]),"+f"(d[35]),
      "+f"(d[36]),"+f"(d[37]),"+f"(d[38]),"+f"(d[39]),"+f"(d[40]),"+f"(d[41]),"+f"(d[42]),"+f"(d[43]),"+f"(d[44]),"+f"(d[45]),"+f"(d[46]),"+f"(d[47]),
      "+f"(d[48]),"+f"(d[49]),"+f"(d[50]),"+f"(d[51]),"+f"(d[52]),"+f"(d[53]),"+f"(d[54]),"+f"(d[55]),"+f"(d[56]),"+f"(d[57]),"+f"(d[58]),"+f"(d[59]),
      "+f"(d[60]),"+f"(d[61]),"+f"(d[62]),"+f"(d[63]),"+f"(d[64]),"+f"(d[65]),"+f"(d[66]),"+f"(d[67]),"+f"(d[68]),"+f"(d[69]),"+f"(d[70]),"+f"(d[71]),
      "+f"(d[72]),"+f"(d[73]),"+f"(d[74]),"+f"(d[75]),"+f"(d[76]),"+f"(d[77]),"+f"(d[78]),"+f"(d[79]),"+f"(d[80]),"+f"(d[81]),"+f"(d[82]),"+f"(d[83]),
      "+f"(d[84]),"+f"(d[85]),"+f"(d[86]),"+f"(d[87]),"+f"(d[88]),"+f"(d[89]),"+f"(d[90]),"+f"(d[91]),"+f"(d[92]),"+f"(d[93]),"+f"(d[94]),"+f"(d[95])
    : "r"(alo), "r"(blo), "r"(sd), "n"(TB), "r"(DESC_HI), "n"(TA));
}

struct Ctx {
  uint32_t sm;
  uint32_t bar;
  uint32_t rbar;
  int cl, rank, wg, warp, lane, phases;
};
__device__ __forceinline__ void release(const Ctx& c, int b, int cnt = 1) {
  if (c.lane < 2) mbar_arrive_cl(c.rbar + b * 8, cnt);
}
#define HK 5
#define ZLEAD 16
#define PFM 7
#define PF1 1
constexpr float SM_SCALE = 0.08838834764831845f * 1.4426950408889634f;
constexpr float SM_HI = 1.8446744e19f, SM_LO = 5.4210109e-20f;
constexpr int ORDER = 1;

__device__ __forceinline__ void stage_tile(const float (&a)[64], uint32_t buf, const Ctx& c, float s0, float s1) {
  const int row = (c.lane & 7) + ((c.lane >> 3) & 1) * 8;
  const uint32_t base = buf + (c.warp * 16 + row) * 128 + (((c.lane >> 4) ^ (row & 7)) << 4);
#pragma unroll
  for (int i = 0; i < 8; i++)
    stsm4((base ^ ((i & 3) << 5)) + (i >> 2) * 8192, pack_bf16(a[8 * i] * s0, a[8 * i + 1] * s0), pack_bf16(a[8 * i + 2] * s1, a[8 * i + 3] * s1),
          pack_bf16(a[8 * i + 4] * s0, a[8 * i + 5] * s0), pack_bf16(a[8 * i + 6] * s1, a[8 * i + 7] * s1));
}

__device__ __forceinline__ int p1_abuf(int kb) { return kb < 2 ? kb : 5 - kb; }
__device__ __forceinline__ void p1_epilogue(const Params& p, const Ctx& c, const float (&acc)[64], int t, int type) {
  const int tile = p.s.r[c.cl].tile[t] & 63, b = c.wg * 2 + 1;
  mbar_wait(c.bar + (B_SE + b) * 8, (t & 1) ^ 1);
  if (type && tile >= 32) {
    const int r = 2 * (c.lane & 3) + ((c.lane >> 2) & 1);
    const uint32_t dst = c.sm + SM_BUF + b * 16384 + r * 128 + (((c.warp * 2) ^ r) << 4) + (c.lane >> 3) * 4;
#pragma unroll
    for (int i = 0; i < 16; i++) {
      asm volatile("st.shared.u32 [%0], %1;" ::"r"(dst + i * 1024), "r"(pack_bf16(acc[4 * i], acc[4 * i + 1])) : "memory");
      asm volatile("st.shared.u32 [%0], %1;" ::"r"((dst ^ 16) + i * 1024), "r"(pack_bf16(acc[4 * i + 2], acc[4 * i + 3])) : "memory");
    }
  } else {
    if (type) stage_tile(acc, c.sm + SM_BUF + b * 16384, c, SM_SCALE, SM_SCALE);
    else stage_tile(acc, c.sm + SM_BUF + b * 16384, c, 1.f, 1.f);
  }
  FENCE_ASYNC_SMEM();
  __syncwarp();
  if (c.lane == 0) mbar_arrive(c.bar + (B_SF + b) * 8);
}

__device__ __forceinline__ void p1_consumer(const Params& p, const Ctx& c) {
  const int n = p.s.r[c.cl].n1;
  const int type = (p.s.r[c.cl].slab >> 3) & 1;
  const uint32_t bdesc = desc_lo(c.sm + SM_RING, 8192), adesc = desc_lo(c.sm + SM_BUF + 32768 + c.wg * 8192, 16);
  uint32_t A[128];
  float acc[64] = {};
  int slot = 0, par = 0;
  auto next = [&]() { if (++slot == 10) { slot = 0; par ^= 1; } };
  {
    const int row = (c.lane & 7) + ((c.lane >> 3) & 1) * 8;
    const uint32_t base = c.sm + SM_RING + (c.wg * 64 + c.warp * 16 + row) * 128 + (((c.lane >> 4) ^ (row & 7)) << 4);
    if (c.wg == 1) bar_sync(ORDER + 1, 256);
    int pb = -1;
    if (type) {
      mbar_wait(c.bar + B_P1F * 8, 0);
      WG_FENCE();
#pragma unroll
      for (int kk = 0; kk < 4; kk++) wgmma_ss128<1>(acc, adesc + kk * 2, bdesc + kk * 128, kk != 0);
      WG_COMMIT();
      pb = 0; slot = 1;
    }
#pragma unroll
    for (int kb = 0; kb < 8; kb++) {
      const int sa = kb + type < 4 ? 10 + p1_abuf(kb) : slot;
      mbar_wait(c.bar + (B_P1F + slot) * 8, par);
#pragma unroll
      for (int kk = 0; kk < 4; kk++) ldsm4((base ^ (kk << 5)) + sa * 16384, A[kb * 16 + kk * 4], A[kb * 16 + kk * 4 + 1], A[kb * 16 + kk * 4 + 2], A[kb * 16 + kk * 4 + 3]);
      if (kb + type >= 4) { next(); mbar_wait(c.bar + (B_P1F + slot) * 8, par); }
      WG_WAIT(0);
      WG_FENCE();
#pragma unroll
      for (int kk = 0; kk < 4; kk++)
        wgmma_rs128<1>(acc, A[kb * 16 + kk * 4], A[kb * 16 + kk * 4 + 1], A[kb * 16 + kk * 4 + 2], A[kb * 16 + kk * 4 + 3], bdesc + slot * 1024 + kk * 128, (kb | kk) != 0 ? 1 : type);
      WG_COMMIT();
      if (kb == 1 && c.wg == 0) bar_arrive(ORDER + 1, 256);
      if (kb > 0 || pb >= 0) release(c, B_P1E + pb);
      if (kb + type >= 4) release(c, B_P1E + sa);
      pb = slot;
      next();
    }
    WG_WAIT(0);
    release(c, B_P1E + pb);
    if (c.lane == 0) mbar_arrive(c.bar + B_T0 * 8);
    pin(acc);
    p1_epilogue(p, c, acc, 0, type);
  }
  for (int t = 1; t < n; t++) {
    bar_sync(ORDER + c.wg, 256);
    int prev1 = -1, prev2 = -1;
    if (type) {
      mbar_wait(c.bar + (B_P1F + slot) * 8, par);
      WG_FENCE();
#pragma unroll
      for (int kk = 0; kk < 4; kk++) wgmma_ss128<1>(acc, adesc + kk * 2, bdesc + slot * 1024 + kk * 128, kk != 0);
      WG_COMMIT();
      prev1 = slot;
      next();
    }
#pragma unroll
    for (int kb = 0; kb < 8; kb++) {
      mbar_wait(c.bar + (B_P1F + slot) * 8, par);
      WG_FENCE();
      const uint32_t d = bdesc + slot * 1024;
#pragma unroll
      for (int kk = 0; kk < 4; kk++)
        wgmma_rs128<1>(acc, A[kb * 16 + kk * 4], A[kb * 16 + kk * 4 + 1], A[kb * 16 + kk * 4 + 2], A[kb * 16 + kk * 4 + 3], d + kk * 128, (kb | kk) != 0 ? 1 : type);
      WG_COMMIT();
      if (kb == HK) {
        if (t + 1 < n || c.wg == 0) bar_arrive(ORDER + (c.wg ^ 1), 256);
      }
      if (kb > 0) { WG_WAIT(2); if (kb > 1 || prev2 >= 0) release(c, B_P1E + prev2); }
      prev2 = prev1; prev1 = slot;
      next();
    }
    WG_WAIT(1);
    release(c, B_P1E + prev2);
    WG_WAIT(0);
    pin(acc);
    release(c, B_P1E + prev1);
    p1_epilogue(p, c, acc, t, type);
  }
}

__device__ __forceinline__ void p1_producer(const Params& p, const Ctx& c) {
  const int n = p.s.r[c.cl].n1;
  const int type = p.s.r[c.cl].slab >> 3, grp = p.s.r[c.cl].slab & 7;
  int slot = 4, par = 1;
#pragma unroll 1
  for (int t = 0; t < n; t++) {
    const int tile = p.s.r[c.cl].tile[t] & 63;
    const CUtensorMap* m = &p.map_w[type * 2 + (tile >> 5)];
    const int n0 = (tile & 31) * 128 + c.rank * 64;
    const uint64_t pol = p.s.r[c.cl].tile[t] >= 192 ? POL(0) : L2_NORMAL;
    const int ptile = p.s.r[c.cl].tile[t + PF1 < n ? t + PF1 : t];
    const CUtensorMap* pm = &p.map_w[type * 2 + ((ptile >> 5) & 1)];
    if (t == 7 && (c.phases & 16)) flag_wait<true>(F_GATE, 256);
#pragma unroll 1
    for (int kb = (t ? 0 : 4) - type; kb < 8; kb++) {
      if (t == 0) {
        mbar_wait(c.bar + (B_P1E + slot) * 8, par);
        mbar_expect(c.bar + (B_P1F + slot) * 8, 16384);
        tma2d(c.sm + SM_RING + slot * 16384, &p.map_a[type], kb * 64, grp * 256 + c.rank * 128, c.bar + (B_P1F + slot) * 8);
        if (++slot == 10) { slot = 0; par ^= 1; }
      }
      mbar_wait(c.bar + (B_P1E + slot) * 8, par);
      mbar_expect(c.bar + (B_P1F + slot) * 8, 16384);
      tma2d_mc(c.sm + SM_RING + slot * 16384 + c.rank * 8192, m, n0, kb < 0 ? 512 : kb * 64, c.bar + (B_P1F + slot) * 8, pol);
      if (t + PF1 < n && t > 0 && ((ptile >> 6) == 1 || ((ptile >> 6) == 2 && ((kb ^ grp) & PFM) == 0))) tma2d_prefetch(pm, (ptile & 31) * 128 + c.rank * 64, kb < 0 ? 512 : kb * 64);
      if (++slot == 10) { slot = 0; par ^= 1; }
    }
  }
}

__device__ __forceinline__ void wait_kv_dead(const Ctx& c, int h, int g) {
  if (g >= 2) flag_wait<false>(F_RD + h * 8 + g, 8 - g);
  else flag_wait<false>(F_CTX + max(c.lane & 7, g) * 64 + h, 4);
}
__device__ __forceinline__ int p1_storer(const Params& p, const Ctx& c) {
  const int n = p.s.r[c.cl].n1;
  const int type = p.s.r[c.cl].slab >> 3, grp = p.s.r[c.cl].slab & 7;
  for (int i = 0; i < 2 * n; i++) {
    const int t = i >> 1, w = i & 1, b = w * 2 + 1;
    const int tile = p.s.r[c.cl].tile[t] & 63;
    mbar_wait(c.bar + (B_SF + b) * 8, t & 1);
    const uint32_t src = c.sm + SM_BUF + b * 16384;
    int f = (type ? F_Q : F_KV) + (tile & 31) * 8 + grp;
    if (type == 0) {
      const int prev = p.s.prev[tile & 31][grp];
      if (prev != 255 && w == 0) wait_kv_dead(c, prev, grp);
      uint8_t* dst = g_S + (size_t)(S_K + ((tile & 32) + p.s.slot[tile & 31][grp]) * 8 + grp) * 65536 + c.rank * 32768 + w * 8192;
      bulk_store(dst, src, 8192);
      bulk_store(dst + 16384, src + 8192, 8192);
    } else if (tile < 32) {
      const int dep = p.s.qdep[tile * 8 + grp];
      if (dep != 511 && w == 0) {
        if (dep < 256) wait_kv_dead(c, dep >> 3, dep & 7);
        else flag_wait<false>(F_TS + dep - 256, 128);
      }
      bulk_store(g_S + (size_t)p.s.qblk[tile * 8 + grp] * 65536 + (c.rank * 2 + w) * 16384, src, 16384);
    } else {
      tma3d_store(&p.map_t[2], src, (grp * 4 + c.rank * 2 + w) * 32, 0, (tile - 32) * 64);
      f = F_QKVA + grp * 4 + ((0xE4390900u >> (2 * (tile - 30))) & 3);
    }
    BULK_COMMIT();
    BULK_WAIT(0);
    mbar_arrive_one(c.bar + (B_SE + b) * 8);
    if (i == 2 * n - 1) return f;
    if (w) flag_add(f, 2);
  }
  return -1;
}

__device__ __forceinline__ int p2_buf(int w, int i) { return w * 2 + (i & 1); }
__device__ __forceinline__ int p2_blk(int rank, int w, int i) { return ((i ^ w) & 1) == 0 ? 3 - rank : rank; }


template <int N>
__device__ __forceinline__ void row_max(const float (&s)[N], float& m0, float& m1) {
  float a0 = fmaxf(s[0], s[1]), a1 = fmaxf(s[2], s[3]);
#pragma unroll
  for (int i = 1; i < N / 4; i++) {
    m0 = fmaxf(m0, s[4 * i]); a0 = fmaxf(a0, s[4 * i + 1]);
    m1 = fmaxf(m1, s[4 * i + 2]); a1 = fmaxf(a1, s[4 * i + 3]);
  }
  m0 = fmaxf(m0, a0); m1 = fmaxf(m1, a1);
  m0 = fmaxf(m0, __shfl_xor_sync(0xffffffffu, m0, 1));
  m1 = fmaxf(m1, __shfl_xor_sync(0xffffffffu, m1, 1));
  m0 = fmaxf(m0, __shfl_xor_sync(0xffffffffu, m0, 2));
  m1 = fmaxf(m1, __shfl_xor_sync(0xffffffffu, m1, 2));
}
template <bool SUB, int N>
__device__ __forceinline__ void row_exp(const float (&s)[N], uint32_t (&P)[32], float m0, float m1, float& t0, float& t1) {
  float u0 = 0.f, u1 = 0.f;
  t0 = t1 = 0.f;
#pragma unroll
  for (int i = 0; i < N / 4; i++) {
    const float e0 = ex2(SUB ? s[4 * i] - m0 : s[4 * i]), e1 = ex2(SUB ? s[4 * i + 1] - m0 : s[4 * i + 1]);
    const float e2 = ex2(SUB ? s[4 * i + 2] - m1 : s[4 * i + 2]), e3 = ex2(SUB ? s[4 * i + 3] - m1 : s[4 * i + 3]);
    if (i == 0) { t0 = e0; u0 = e1; t1 = e2; u1 = e3; }
    else { t0 += e0; u0 += e1; t1 += e2; u1 += e3; }
    P[2 * i] = pack_bf16(e0, e1);
    P[2 * i + 1] = pack_bf16(e2, e3);
  }
#pragma unroll
  for (int i = N / 2; i < 32; i++) P[i] = 0;
  pin(P);
  t0 += u0; t1 += u1;
}
template <int N>
__device__ __forceinline__ void causal_mask(float (&s)[N], int thr) {
#pragma unroll
  for (int i = 0; i < 8; i++) {
    if (8 * i > thr) s[N - 32 + 4 * i] = -INFINITY;
    if (8 * i + 1 > thr) s[N - 32 + 4 * i + 1] = -INFINITY;
    if (8 * i - 8 > thr) s[N - 32 + 4 * i + 2] = -INFINITY;
    if (8 * i - 7 > thr) s[N - 32 + 4 * i + 3] = -INFINITY;
  }
}
__device__ __forceinline__ void issue_qk(float (&s)[32], uint32_t qd, uint32_t kd) {
  WG_FENCE();
#pragma unroll
  for (int kk = 0; kk < 8; kk++) wgmma_ss64<0>(s, qd + (kk >> 2) * 512 + (kk & 3) * 2, kd + (kk >> 2) * 1024 + (kk & 3) * 2, kk != 0);
  WG_COMMIT();
}
__device__ __forceinline__ void issue_qk(float (&s)[64], uint32_t qd, uint32_t kd) {
  WG_FENCE();
#pragma unroll
  for (int kk = 0; kk < 8; kk++) wgmma_ss128<0>(s, qd + (kk >> 2) * 512 + (kk & 3) * 2, kd + (kk >> 2) * 1024 + (kk & 3) * 2, kk != 0);
  WG_COMMIT();
}
template <int NK>
__device__ __forceinline__ void issue_pv(float (&o)[64], const uint32_t (&P)[32], uint32_t vd, int acc) {
  WG_FENCE();
#pragma unroll
  for (int kk = 0; kk < NK; kk++) wgmma_rs128<1>(o, P[4 * kk], P[4 * kk + 1], P[4 * kk + 2], P[4 * kk + 3], vd + kk * 128, kk != 0 ? 1 : acc);
  WG_COMMIT();
}
__device__ __forceinline__ void stage_done(const Ctx& c, int b) {
  FENCE_ASYNC_SMEM();
  __syncwarp();
  if (c.lane == 0) mbar_arrive(c.bar + (B_SF + b) * 8);
}
__device__ __forceinline__ void p2_epilogue(const float (&o)[64], float s0, float s1, const Ctx& c, int b) {
  stage_tile(o, c.sm + SM_BUF + b * 16384, c, s0, s1);
  stage_done(c, b);
}

struct P2State {
  float m0, m1, l0, l1;
  bool shift;
  float e0, e1;
  int ks;
  int wi, ai;
  uint32_t wb, ab;
  uint32_t qd;
};
__device__ __forceinline__ int wrap5(int q) { return q >= 5 ? q - 5 : q; }
__device__ __forceinline__ void turn_wait(uint32_t ring, int i) { mbar_wait(ring + (i & 3) * 8, (i >> 2) & 1); }
__device__ __forceinline__ void turn_pass(const Ctx& c, uint32_t ring, int i) { if (c.lane == 0) mbar_arrive(ring + (i & 3) * 8); }
__device__ __forceinline__ void p2_scales(P2State& z) {
  float l0 = z.l0, l1 = z.l1;
  l0 += __shfl_xor_sync(0xffffffffu, l0, 1);
  l1 += __shfl_xor_sync(0xffffffffu, l1, 1);
  l0 += __shfl_xor_sync(0xffffffffu, l0, 2);
  l1 += __shfl_xor_sync(0xffffffffu, l1, 2);
  asm("rcp.approx.ftz.f32 %0, %1;" : "=f"(z.e0) : "f"(l0));
  asm("rcp.approx.ftz.f32 %0, %1;" : "=f"(z.e1) : "f"(l1));
}
template <int N>
__device__ __forceinline__ void p2_first(const Ctx& c, P2State& z, float (&o)[64], uint32_t (&Pc)[32], uint32_t (&Pn)[32],
                                         int ks, int vs, int cnt, int acc) {
  float s[N] = {};
  issue_qk(s, z.qd, desc_lo(c.sm + SM_RING, 16) + ks * 2048);
  if (vs >= 0) {
    p2_scales(z);
    issue_pv<8>(o, Pc, desc_lo(c.sm + SM_RING, 16384) + vs * 2048, acc);
  } else {
    WG_COMMIT();
  }
  mbar_expect(z.ab + (z.ai++ & 3) * 8, cnt == 1 ? 8192 : 0);
  WG_WAIT(1);
  pin(s);
  release(c, B_P2E + ks, cnt);
  causal_mask(s, c.warp * 16 + (c.lane >> 2) - 2 * (c.lane & 3));
  z.m0 = z.m1 = 0.f;
  row_exp<false>(s, Pn, 0.f, 0.f, z.l0, z.l1);
  z.shift = __any_sync(0xffffffffu, !(z.l0 + z.l1 <= SM_HI) || ((c.lane & 3) == 0 && !(fminf(z.l0, z.l1) >= SM_LO)));
  if (__builtin_expect(z.shift, 0)) {
    z.m0 = z.m1 = -INFINITY;
    row_max(s, z.m0, z.m1);
    row_exp<true>(s, Pn, z.m0, z.m1, z.l0, z.l1);
  }
  WG_WAIT(0);
  pin(o);
  if (vs >= 0) release(c, B_P2E + vs, 1);
}

template <bool SECOND>
__device__ __forceinline__ void p2_turn(const Ctx& c, P2State& z, float (&o)[64], uint32_t (&Pc)[32], uint32_t (&Pn)[32],
                                        int eb = -1, bool half = false, int vcnt = 1) {
  float s[64] = {};
  const int ks = z.ks, vs = wrap5(ks + 1);
  turn_wait(z.wb, z.wi++);
  issue_qk(s, z.qd, desc_lo(c.sm + SM_RING, 16) + ks * 2048);
  const uint32_t vd = desc_lo(c.sm + SM_RING, 16384) + vs * 2048;
  if (SECOND) {
    if (eb >= 0) stage_tile(o, c.sm + SM_BUF + eb * 16384, c, z.e0, z.e1);
    if (half) issue_pv<4>(o, Pc, vd, 0); else issue_pv<8>(o, Pc, vd, 0);
  } else {
    issue_pv<8>(o, Pc, vd, 1);
  }
  turn_pass(c, z.ab, z.ai++);
  if (SECOND) { if (eb >= 0) stage_done(c, eb); }
  z.ks = wrap5(ks + 2);
  WG_WAIT(1);
  pin(s);
  release(c, B_P2E + ks, 1);
  float t0, t1, a0 = 1.f, a1 = 1.f;
  row_exp<false>(s, Pn, 0.f, 0.f, t0, t1);
  const bool redo = __any_sync(0xffffffffu, z.shift || !(t0 + t1 <= SM_HI));
  if (__builtin_expect(redo, 0)) {
    float n0 = z.m0, n1 = z.m1;
    if (!z.shift) { n0 = __log2f(z.l0); n1 = __log2f(z.l1); }
    z.shift = true;
    row_max(s, n0, n1);
    a0 = ex2(z.m0 - n0); a1 = ex2(z.m1 - n1);
    z.m0 = n0; z.m1 = n1;
    z.l0 *= a0; z.l1 *= a1;
    row_exp<true>(s, Pn, z.m0, z.m1, t0, t1);
  }
  WG_WAIT(0);
  pin(o);
  release(c, B_P2E + vs, vcnt);
  if (__builtin_expect(redo, 0)) {
#pragma unroll
    for (int i = 0; i < 16; i++) { o[4 * i] *= a0; o[4 * i + 1] *= a0; o[4 * i + 2] *= a1; o[4 * i + 3] *= a1; }
  }
  z.l0 += t0; z.l1 += t1;
}
__device__ __forceinline__ void copy_p(uint32_t (&d)[32], const uint32_t (&s)[32], int zero) {
#pragma unroll
  for (int i = 0; i < 32; i++) asm volatile("add.s32 %0, %1, %2;" : "=r"(d[i]) : "r"(s[i]), "r"(zero));
}

__device__ __forceinline__ void p2_consumer(const Params& p, const Ctx& c, int rot) {
  const int nit = p.s.r[c.cl].n2;
  const uint32_t fring = c.bar + B_P2F * 8, oring = c.bar + B_ORD * 8;
  float o[64] = {};
  uint32_t Pa[32] = {}, Pb[32] = {};
  P2State z;
  z.e0 = z.e1 = z.l0 = z.l1 = 0.f; z.ks = rot; z.shift = false;
  int acc = 0, n = 0;
  for (int it = 0; it < nit; it++) {
    const int j = p.s.r[c.cl].item[it] & 7, blk = p2_blk(c.rank, c.wg, it);
    const int lng = ((it ^ c.wg) & 1) ^ 1;
    z.qd = desc_lo(c.sm + SM_BUF, 16) + p2_buf(c.wg, it) * 1024;
    if (lng) { z.wb = oring; z.wi = n - it; z.ab = fring; z.ai = n + 1; }
    else { z.wb = fring; z.wi = n + 2; z.ab = oring; z.ai = n - it; }
    mbar_wait(c.bar + (B_QF + p2_buf(c.wg, it)) * 8, (it >> 1) & 1);
    turn_wait(fring, n + 1 - lng);
    const int vs = it ? wrap5(z.ks + 1) : -1, ks = lng ? z.ks : wrap5(z.ks + (it ? 2 : 1));
    if (blk & 1) p2_first<64>(c, z, o, Pa, Pb, ks, vs, 1 + lng, acc);
    else p2_first<32>(c, z, o, Pa, Pb, ks, vs, 1 + lng, acc);
    z.ks = wrap5(ks + (it == 0 && lng ? 1 : 2));
    n += 2 * j + 2;
    int left = 2 * j + lng;
    acc = left != 0;
    if (left == 0) { copy_p(Pa, Pb, p.zero); continue; }
    p2_turn<true>(c, z, o, Pb, Pa, it > 0 ? p2_buf(c.wg, it - 1) : -1, !(blk & 1), 1 + lng);
    while (--left > 0) {
      p2_turn<false>(c, z, o, Pa, Pb);
      if (--left == 0) { copy_p(Pa, Pb, p.zero); break; }
      p2_turn<false>(c, z, o, Pb, Pa);
    }
  }
  {
    if (!acc && nit > 1) p2_epilogue(o, z.e0, z.e1, c, p2_buf(c.wg, nit));
    turn_wait(z.wb, z.wi);
    issue_pv<8>(o, Pa, desc_lo(c.sm + SM_RING, 16384) + z.ks * 2048, acc);
    if (((nit - 1) ^ c.wg) & 1) turn_pass(c, z.ab, z.ai);
    p2_scales(z);
    WG_WAIT(0);
    pin(o);
    release(c, B_P2E + z.ks);
    p2_epilogue(o, z.e0, z.e1, c, p2_buf(c.wg, nit - 1));
  }
}

__device__ __forceinline__ void p2_load_q(const Params& p, const Ctx& c, int it, int w) {
  const int item = p.s.r[c.cl].item[it], b = p2_buf(w, it);
  mbar_expect(c.bar + (B_QF + b) * 8, 16384);
  bulk_load(c.sm + SM_BUF + b * 16384, g_S + (size_t)p.s.qblk[item] * 65536 + p2_blk(c.rank, w, it) * 16384, 16384, c.bar + (B_QF + b) * 8, POL(4));
}
__device__ __forceinline__ void wait_p1_free(const Ctx& c, int u1, int s) {
  mbar_wait(c.bar + (B_P1E + 2 * s) * 8, ((u1 - 1 - 2 * s) / 10) & 1);
  mbar_wait(c.bar + (B_P1E + 2 * s + 1) * 8, ((u1 - 2 - 2 * s) / 10) & 1);
}
__device__ __forceinline__ void p2_producer(const Params& p, const Ctx& c, int u1, int rot) {
  const int nit = p.s.r[c.cl].n2;
  int slot = rot, cnt = 0, par = 1, n = 0;
  const uint8_t* pv = nullptr;
  bool pl = false;
  auto load = [&](const uint8_t* src, int expect, uint32_t fb, bool last) {
    if (cnt < 5) {
      if (u1) {
        wait_p1_free(c, u1, slot);
        if (cnt == 0) p2_load_q(p, c, 0, 1);
      }
      cnt++;
    } else {
      if (slot == rot) par ^= 1;
      mbar_wait(c.bar + (B_P2E + slot) * 8, par);
    }
    if (expect) mbar_expect(fb, expect);
    bulk_load_mc(c.sm + SM_RING + slot * 32768 + c.rank * 16384, src, 16384, fb, last ? POL(5) : L2_NORMAL);
    slot = wrap5(slot + 1);
  };
  for (int it = 0; it < nit; it++) {
    const int item = p.s.r[c.cl].item[it], h = item >> 3, j = item & 7;
    if (it == 1 && (c.phases & 16) && p.s.r[c.cl].n1 < 8) flag_wait<true>(F_GATE, 256);
    uint32_t ready = (c.phases & 16) ? 0u : 255u;
    if (it == 0) { if (c.phases & 16) flag_wait<false>(F_Q + item, 4); mbar_wait(c.bar + B_LAD * 8, 0); p2_load_q(p, c, 0, 0); if (!u1) p2_load_q(p, c, 0, 1); }
    for (int t = 2 * j + 1; t >= 0; t--) {
      mask_wait(ready, t >> 1, F_KV + h * 8 + (c.lane & 7), 8);
      const uint8_t* k = g_S + (size_t)(2 * S_K + p.s.slot[h][t >> 1] * 16 + t) * 32768 + c.rank * 16384;
      const uint32_t fb = c.bar + (B_P2F + (n & 3)) * 8;
      const bool last = (p.s.r[c.cl].last[it] >> (t >> 1)) & 1;
      load(k, pv && t != 2 * j ? 65536 : 32768, fb, last);
      if (!(t & 1) && t + 4 <= 2 * j && c.rank == 0) flag_add_rx(F_RD + h * 8 + (t >> 1) + 2);
      if (pv) load(pv, 0, t != 2 * j ? fb : c.bar + (B_ORD + ((n - 1 - it) & 3)) * 8, pl);
      pl = last;
      pv = k + (size_t)NH * 16 * 32768;
      n++;
    }
  }
  load(pv, 32768, c.bar + (B_P2F + (n & 3)) * 8, pl);
}

__device__ __forceinline__ void publish_and_load_q(const Params& p, const Ctx& c, int f, int it, int seen) {
  const bool want = it < p.s.r[c.cl].n2, early = want && __all_sync(0xffffffffu, seen >= 4);
  if (early) { p2_load_q(p, c, it, it & 1); p2_load_q(p, c, it, (it & 1) ^ 1); }
  if (f >= 0) flag_add(f, 2);
  if (want && !early) {
    if (c.phases & 16) flag_wait<false>(F_Q + p.s.r[c.cl].item[it], 4);
    p2_load_q(p, c, it, it & 1); p2_load_q(p, c, it, (it & 1) ^ 1);
  }
}
__device__ __forceinline__ void p2_storer(const Params& p, const Ctx& c, int sfpar) {
  const int nit = p.s.r[c.cl].n2;
  int held = -1;
  for (int i = 0; i < 2 * nit; i++) {
    const int it = i >> 1, w = (it ^ i ^ 1) & 1, b = p2_buf(w, it);
    const int item = p.s.r[c.cl].item[it], h = item >> 3, j = item & 7;
    mbar_wait(c.bar + (B_SF + b) * 8, (sfpar >> b) & 1);
    sfpar ^= 1 << b;
    bulk_store(g_S + (size_t)p.s.qblk[item] * 65536 + p2_blk(c.rank, w, it) * 16384, c.sm + SM_BUF + b * 16384, 16384, POL(1));
    BULK_COMMIT();
    if (i & 1) {
      if (it + 2 == nit && (p.s.r[c.cl].item[it + 1] & 7) == 0) { held = F_CTX + j * 64 + h; continue; }
      const int seen = flag_peek(F_Q + p.s.r[c.cl].item[min(it + 2, nit - 1)]);
      BULK_WAIT(0);
      if (it + 1 == nit) release(c, B_DONE);
      publish_and_load_q(p, c, F_CTX + j * 64 + h, it + 2, seen);
    }
  }
  if (held >= 0) flag_add_rx(held, 2);
}

__device__ __forceinline__ int p3_pos(int i, int x) { return i < 4 ? (i + x) & 3 : 4; }
__device__ __forceinline__ void p3_consumer(const Params& p, const Ctx& c, int x) {
  const bool first = p.s.r[c.cl].p3 >= 24;
  const int tile = p.s.r[c.cl].p3 - (first ? 24 : 0), j = tile / 3, nt = tile - 3 * j;
  const int na = first ? 9 : 0, nb = p.s.task[c.cl][1] - p.s.task[c.cl][0];
  const uint32_t ad = desc_lo(c.sm + SM_RING + c.wg * 8192, 16), bd = desc_lo(c.sm + SM_RING + 16384, 4096);
  float acc[96] = {};
  int slot = 0, par = 0, prev = 0;
  float g0 = 0.f, g1 = 0.f;
  const int hold = c.wg && LAG ? na + nb - LAG : -1, pass = c.wg || !LAG ? -1 : na + nb - 1;
  const float* gp = g_gate + j * 256 + c.rank * 128 + c.wg * 64 + c.warp * 16 + (c.lane >> 2);
#pragma unroll 1
  for (int kb = 0; kb < na; kb++) {
    if (kb == hold) bar_sync(6, 256);
    mbar_wait(c.bar + (B_P3F + slot) * 8, par);
    WG_FENCE();
#pragma unroll
    for (int kk = 0; kk < 4; kk++) wgmma_ss192<1, 1>(acc, ad + p3_pos(slot, x) * 2560 + kk * 128, bd + p3_pos(slot, x) * 2560 + (kk >> 1) * 768 + (kk & 1) * 128, kk != 0 ? 1 : kb != 0);
    WG_COMMIT();
    if (kb == pass) bar_arrive(6, 256);
    WG_WAIT(1);
    if (kb > 0) release(c, B_P3E + prev);
    else { g0 = __ldcg(gp); g1 = __ldcg(gp + 8); }
    prev = slot;
    if (++slot == 5) { slot = 0; par ^= 1; }
  }
#pragma unroll 1
  for (int kb = na; kb < na + nb; kb++) {
    if (kb == hold) bar_sync(6, 256);
    mbar_wait(c.bar + (B_P3F + slot) * 8, par);
    WG_FENCE();
#pragma unroll
    for (int kk = 0; kk < 4; kk++) wgmma_ss192<1>(acc, ad + p3_pos(slot, x) * 2560 + kk * 2, bd + p3_pos(slot, x) * 2560 + (kk >> 1) * 768 + (kk & 1) * 128, kk != 0 ? 1 : kb != 0);
    WG_COMMIT();
    if (kb == pass) bar_arrive(6, 256);
    WG_WAIT(1);
    if (kb > 0) release(c, B_P3E + prev);
    else { g0 = __ldcg(gp); g1 = __ldcg(gp + 8); }
    prev = slot;
    if (++slot == 5) { slot = 0; par ^= 1; }
  }
  g0 = __fdividef(1.f, 1.f + g0); g1 = __fdividef(1.f, 1.f + g1);
  WG_WAIT(0);
  pin(acc);
  if (first) bar_sync(4 + c.wg, 128);
  mbar_wait(c.bar + B_OUT * 8, 0);
  const int row = (c.lane & 7) + ((c.lane >> 3) & 1) * 8;
  const uint32_t wbase = c.sm + SM_RING + c.wg * 8192 + c.warp * 2048;
  const uint32_t base = wbase + row * 128 + (((c.lane >> 4) ^ (row & 7)) << 4);
#pragma unroll
  for (int i = 0; i < 12; i++) {
    stsm4((base ^ ((i & 3) << 5)) + (i >> 2) * 40960, pack_bf16(acc[8 * i] * g0, acc[8 * i + 1] * g0), pack_bf16(acc[8 * i + 2] * g1, acc[8 * i + 3] * g1),
          pack_bf16(acc[8 * i + 4] * g0, acc[8 * i + 5] * g0), pack_bf16(acc[8 * i + 6] * g1, acc[8 * i + 7] * g1));
    if ((i & 3) == 3) {
      FENCE_ASYNC_SMEM();
      bar_sync(4 + c.wg, 128);
      if (c.warp == (i >> 2)) tma2d_add(&p.map_out, c.sm + SM_RING + c.wg * 8192 + c.warp * 40960, nt * 192 + c.warp * 64, j * 256 + c.rank * 128 + c.wg * 64);
    }
  }
  BULK_COMMIT();
  BULK_WAIT_READ(0);
}

__device__ __forceinline__ void p3_producer(const Params& p, const Ctx& c, int u1, int u2, int rot, int x) {
  const bool first = p.s.r[c.cl].p3 >= 24;
  const int tile = p.s.r[c.cl].p3 - (first ? 24 : 0), j = tile / 3, nt = tile - 3 * j;
  int slot = 0, par = 1, cnt = 0;
  auto wait_free = [&](int s) {
    const int f = wrap5(s + 5 - rot);
    if (f < u2) mbar_wait(c.bar + (B_P2E + s) * 8, ((u2 - 1 - f) / 5) & 1);
    else if (u1) wait_p1_free(c, u1, s);
  };
  asm volatile(ELECT("prefetch.tensormap [%0];") ::"l"(&p.map_o[0]) : "memory");
  asm volatile(ELECT("prefetch.tensormap [%0];") ::"l"(&p.map_out) : "memory");
  if ((c.phases & 16) && p.s.r[c.cl].n1 < 8 && p.s.r[c.cl].n2 < 2) flag_wait<true>(F_GATE, 256);
  uint32_t ready = (c.phases & 16) ? 0u : ~0u;
  const int q0 = p.s.task[c.cl][0], q1 = p.s.task[c.cl][1];
  for (int q = q0 - (first ? 9 : 0); q < q1; q++) {
    if (q == max(q0, 64 - ZLEAD)) mbar_arrive_one(c.bar + B_ZF * 8);
    const bool brA = q < q0;
    const int kb = brA ? q - q0 + 9 : p.s.p3_order[tile][q];
    if (!brA) mask_wait(ready, kb >> 1, F_CTX + j * 64 + c.lane, 4);
    else if (kb == 0 && (c.phases & 16)) flag_wait<false>(F_CTX + j * 64 + 32, 16);
    const uint8_t* a = brA ? g_oA + (j * 4 + c.rank * 2) * 73728 + kb * 8192 : g_S + (size_t)p.s.qblk[(kb >> 1) * 8 + j] * 65536 + c.rank * 32768 + (kb & 1) * 8192;
    const uint32_t st = c.sm + SM_RING + p3_pos(slot, x) * 40960, fb = c.bar + (B_P3F + slot) * 8;
    if (cnt < 4) { wait_free(p3_pos(cnt, x)); wait_free(p3_pos(cnt, x) + 1); }
    else if (cnt == 4) mbar_wait(c.bar + B_DONE * 8, 0);
    else mbar_wait(c.bar + (B_P3E + slot) * 8, par);
    cnt++;
    mbar_expect(fb, 40960);
    bulk_load(st, a, 8192, fb, POL(3));
    bulk_load(st + 8192, a + (brA ? 73728 : 16384), 8192, fb, POL(3));
    tma3d_mc(st + 16384 + c.rank * 12288, &p.map_o[brA], 0, kb * 64 + c.rank * 32, nt * 3, fb);
    if (++slot == 5) { slot = 0; par ^= 1; }
  }
}

__device__ __forceinline__ float bf_lo(uint32_t w) { return __uint_as_float(w << 16); }
__device__ __forceinline__ float bf_hi(uint32_t w) { return __uint_as_float(w & 0xffff0000u); }

__device__ __forceinline__ void gate_rows(const Params& p, int row0, int lane) {
  const uint4* x = reinterpret_cast<const uint4*>(p.x + (size_t)(row0 + (lane >> 2)) * DM) + (lane & 3);
  const uint4* w = reinterpret_cast<const uint4*>(p.gate_w) + (lane & 3);
  float a = 0.f;
#pragma unroll 1
  for (int b = 0; b < 3; b++) {
    uint4 u[6];
#pragma unroll
    for (int i = 0; i < 6; i++) u[i] = __ldg(x + (b * 6 + i) * 4);
#pragma unroll
    for (int i = 0; i < 6; i++) {
      const uint4 v = __ldg(w + (b * 6 + i) * 4);
      a = fmaf(bf_lo(u[i].x), bf_lo(v.x), a); a = fmaf(bf_hi(u[i].x), bf_hi(v.x), a);
      a = fmaf(bf_lo(u[i].y), bf_lo(v.y), a); a = fmaf(bf_hi(u[i].y), bf_hi(v.y), a);
      a = fmaf(bf_lo(u[i].z), bf_lo(v.z), a); a = fmaf(bf_hi(u[i].z), bf_hi(v.z), a);
      a = fmaf(bf_lo(u[i].w), bf_lo(v.w), a); a = fmaf(bf_hi(u[i].w), bf_hi(v.w), a);
    }
  }
  a += __shfl_xor_sync(0xffffffffu, a, 1);
  a += __shfl_xor_sync(0xffffffffu, a, 2);
  if ((lane & 3) == 0) g_gate[row0 + (lane >> 2)] = __expf(fminf(a, 60.f));
}

__device__ __forceinline__ void lds10(uint32_t (&k)[10], uint32_t a) {
  asm volatile("ld.shared.v2.u32 {%0, %1}, [%10];\nld.shared.v2.u32 {%2, %3}, [%10+8];\nld.shared.v2.u32 {%4, %5}, [%10+16];\n"
               "ld.shared.v2.u32 {%6, %7}, [%10+24];\nld.shared.v2.u32 {%8, %9}, [%10+32];"
               : "=r"(k[0]), "=r"(k[1]), "=r"(k[2]), "=r"(k[3]), "=r"(k[4]), "=r"(k[5]), "=r"(k[6]), "=r"(k[7]), "=r"(k[8]), "=r"(k[9]) : "r"(a));
}
__device__ __forceinline__ void local_attn(const Params& p, const Ctx& c, int rb, int hs) {
  const int lane = c.lane, grp = rb >> 2, par = lane >> 4, i0 = 2 * (lane & 15);
  const uint32_t buf = c.sm + SM_BUF + (c.warp - 2) * 8192, bqk = c.bar + (B_LA + (c.warp - 2) * 2) * 8, bv = bqk + 8;
  const uint32_t mine = buf + 2304 + par * 160 + i0 * 4;
  const bool flags = c.phases & 16;
  auto fetch_qk = [&](int i) {
    if (flags && !(i & 1)) {
      const int q = i >> 1;
      const int tgt = q == 0 ? 24 : q == 3 ? 8 : 12;
      flag_wait<false>(F_QKVA + (grp - (grp > 0 && (rb & 3) == 0 ? par : 0)) * 4 + q, tgt);
    }
    mbar_expect(bqk, 5184);
    tma3d(buf, &p.map_t[0], rb * 32, 0, 9 * (4 * i + hs), bqk, POL(2));
    tma3d(buf + 2304, &p.map_t[1], rb * 32 - 8, 0, 288 + 9 * (4 * i + hs), bqk, POL(2));
  };
  auto fetch_v = [&](int i) { mbar_expect(bv, 2880); tma3d(buf + 5248, &p.map_t[1], rb * 32 - 8, 0, 576 + 9 * (4 * i + hs), bv, POL(2)); };
  fetch_qk(0);
  if (flags) flag_wait<true>(F_GATE, 256);
#pragma unroll 1
  for (int q = 0; q < 8; q++) {
    fetch_v(q);
    float a[8], b[8];
#pragma unroll
    for (int w = 0; w < 8; w++) a[w] = b[w] = 0.f;
    mbar_wait(bqk, q & 1);
#pragma unroll 1
    for (int j = 0; j < 9; j++) {
      uint32_t x, y, k[10];
      asm volatile("ld.shared.v2.u32 {%0, %1}, [%2];" : "=r"(x), "=r"(y) : "r"(buf + lane * 8 + j * 256));
      lds10(k, mine + j * 320);
      const float xl = bf_lo(x), xh = bf_hi(x), yl = bf_lo(y), yh = bf_hi(y);
#pragma unroll
      for (int m = 1; m < 10; m++) {
        const float kl = bf_lo(k[m]), kh = bf_hi(k[m]);
        if (m < 9) a[8 - m] = fmaf(xl, kl, fmaf(xh, kh, a[8 - m]));
        if (m > 1) b[9 - m] = fmaf(yl, kl, fmaf(yh, kh, b[9 - m]));
      }
    }
    __syncwarp();
    mbar_wait(bv, q & 1);
    if (q & 1) flag_add_rx(F_TS + (q >> 1));
    if (q < 7) fetch_qk(q + 1);
    constexpr float SC = 0.23570226039551584f * 1.4426950408889634f;
    const float* gp = g_gate + rb * 64 + 2 * i0 + par;
    const float ga = __ldcg(gp), gb = __ldcg(gp + 2);
    float ma = a[0], mb = b[0];
#pragma unroll
    for (int w = 1; w < 8; w++) {
      if (rb == 0) {
        if (i0 < w) a[w] = -INFINITY;
        if (i0 + 1 < w) b[w] = -INFINITY;
      }
      ma = fmaxf(ma, a[w]); mb = fmaxf(mb, b[w]);
    }
    float la = 0.f, lb = 0.f;
#pragma unroll
    for (int w = 0; w < 8; w++) {
      a[w] = ex2((a[w] - ma) * SC); b[w] = ex2((b[w] - mb) * SC);
      la += a[w]; lb += b[w];
    }
    la = __fdividef(ga, la); lb = __fdividef(gb, lb);
#pragma unroll
    for (int w = 0; w < 8; w++) { a[w] *= la; b[w] *= lb; }
    uint8_t* dst = g_oA + rb * 73728 + ((i0 & 2) + par) * 4;
#pragma unroll 1
    for (int j = 0; j < 9; j++) {
      uint32_t v[10];
      lds10(v, mine + 2944 + j * 320);
      float a0 = 0.f, a1 = 0.f, b0 = 0.f, b1 = 0.f;
#pragma unroll
      for (int m = 1; m < 10; m++) {
        const float vl = bf_lo(v[m]), vh = bf_hi(v[m]);
        if (m < 9) { a0 = fmaf(a[8 - m], vl, a0); a1 = fmaf(a[8 - m], vh, a1); }
        if (m > 1) { b0 = fmaf(b[9 - m], vl, b0); b1 = fmaf(b[9 - m], vh, b1); }
      }
      const uint32_t wa = pack_bf16(a0, a1), wb = pack_bf16(b0, b1);
      const uint32_t got = __shfl_xor_sync(0xffffffffu, par ? wa : wb, 16);
      const uint32_t r0 = par ? got : wa, r1 = par ? wb : got;
      const int col = 18 * (4 * q + hs) + 2 * j, o = col * 128 + ((((i0 >> 2) ^ col) & 7) << 4);
      *reinterpret_cast<uint32_t*>(dst + o) = __byte_perm(r0, r1, 0x5410);
      *reinterpret_cast<uint32_t*>(dst + ((o + 128) ^ 16)) = __byte_perm(r0, r1, 0x7632);
    }
    __syncwarp();
  }
  mbar_arrive_one(c.bar + B_LAD * 8);
  flag_add(F_CTX + grp * 64 + 32);
}

__global__ void __cluster_dims__(2, 1, 1) __launch_bounds__(384, 1) fused_kernel(const __grid_constant__ Params p) {
  extern __shared__ uint8_t smem_raw[];
  Ctx c;
  c.sm = ((uint32_t)__cvta_generic_to_shared(smem_raw) + 1023u) & ~1023u;
  c.bar = c.sm + SM_BAR;
  c.lane = threadIdx.x & 31;
  const int wid = __shfl_sync(0xffffffffu, threadIdx.x >> 5, 0);
  if (wid < 6) asm volatile("prefetch.tensormap [%0];" ::"l"(&p.map_a[0] + wid) : "memory");
  c.wg = wid >> 2;
  c.warp = wid & 3;
  c.cl = (blockIdx.x + (wid >> 4)) >> 1;
  c.rank = blockIdx.x & 1;
  c.rbar = mapa(c.bar, c.lane & 1);
  {
    const int w = wid, cnt = (((int)(B_CNT >> (4 * w)) - 1) & 15) + 1;
    if (w < 11) {
#pragma unroll
      for (int i = 0; i < 8; i++) asm volatile("mbarrier.init.shared::cta.b64 [%0], %1;" ::"r"(c.bar + w * 64 + i * 8), "r"(cnt));
    }
    asm volatile("fence.mbarrier_init.release.cluster;" ::: "memory");
  }
  asm volatile("barrier.cluster.arrive.relaxed;" ::: "memory");
  c.phases = p.s.r[c.cl].phases;
  const bool do1 = p.s.r[c.cl].n1 > 0, do2 = p.s.r[c.cl].n2 > 0, do3 = p.s.r[c.cl].p3 != 255;
  if (do1 && c.wg == 2 && c.warp == 0) {
    const int type = p.s.r[c.cl].slab >> 3;
    FENCE_ASYNC_SMEM();
    mbar_expect(c.bar + B_P1F * 8, 32768);
    tma2d(c.sm + SM_BUF + type * 32768, &p.map_a[type], type ? 512 : 0, (p.s.r[c.cl].slab & 7) * 256 + c.rank * 128, c.bar + B_P1F * 8);
  }
  asm volatile("barrier.cluster.wait.acquire;" ::: "memory");
  if (do1 && c.wg == 2 && c.warp == 0) {
    const int type = p.s.r[c.cl].slab >> 3, tile = p.s.r[c.cl].tile[0] & 63;
    const CUtensorMap* m = &p.map_w[type * 2 + (tile >> 5)];
#pragma unroll 1
    for (int kb = -type; kb < 4 - type; kb++) {
      const uint32_t fb = c.bar + (B_P1F + kb + type) * 8;
      if (kb > -type) {
        mbar_expect(fb, 32768);
        tma2d(c.sm + SM_BUF + p1_abuf(kb) * 16384, &p.map_a[type], kb * 64, (p.s.r[c.cl].slab & 7) * 256 + c.rank * 128, fb);
      }
      tma2d_mc(c.sm + SM_RING + (kb + type) * 16384 + c.rank * 8192, m, (tile & 31) * 128 + c.rank * 64, kb < 0 ? 512 : kb * 64, fb);
    }
  }

  if (c.wg < 2) {
    asm volatile("setmaxnreg.inc.sync.aligned.u32 224;");
    if (c.wg == 1) {
      if (do1) bar_arrive(ORDER, 256);
      if (c.lane == 0) mbar_arrive(c.bar + B_P2F * 8);
    }
    if (do1) p1_consumer(p, c);
    if (do2) p2_consumer(p, c, p.s.r[c.cl].rot);
    if (do3) p3_consumer(p, c, p.s.r[c.cl].x3);
    if (c.lane == 0) mbar_arrive(c.bar + B_FIN * 8);
    __syncwarp();
    cluster_sync();
  } else {
    asm volatile("setmaxnreg.dec.sync.aligned.u32 56;");
    if (c.warp == 0) {
      if (do1) p1_producer(p, c);
      if (do2) p2_producer(p, c, p.s.r[c.cl].u1, p.s.r[c.cl].rot);
      if (do3) p3_producer(p, c, p.s.r[c.cl].u1, p.s.r[c.cl].u2, p.s.r[c.cl].rot, p.s.r[c.cl].x3);
    } else if (c.warp == 1) {
      const int f = do1 ? p1_storer(p, c) : -1;
      if (do2) {
        publish_and_load_q(p, c, f, 1, flag_peek(F_Q + p.s.r[c.cl].item[1]));
        p2_storer(p, c, (p.s.r[c.cl].n1 & 1) * 10);
      } else {
        const bool idle = mbar_test(c.bar + B_LAD * 8, 0);
        if (idle) release(c, B_DONE);
        if (f >= 0) flag_add(f, 2);
        if (!idle) { mbar_wait(c.bar + B_LAD * 8, 0); release(c, B_DONE); }
      }
      if (do3) {
        const int tile = p.s.r[c.cl].p3 % 24;
        if (p.s.task[c.cl][1] == 64) {
          mbar_wait(c.bar + B_ZF * 8, 0);
          const int j = tile / 3, nt = tile - 3 * j;
          uint4* o = reinterpret_cast<uint4*>(p.out + (size_t)(j * 256 + c.rank * 128 + (c.lane >> 3)) * DM + nt * 192) + (c.lane & 7);
#pragma unroll 4
          for (int r = 0; r < 32; r++) o[r * 288] = o[r * 288 + 8] = o[r * 288 + 16] = make_uint4(0u, 0u, 0u, 0u);
          __syncwarp();
          flag_add(F_OUT + tile * 2 + c.rank);
        } else if (c.phases & 16) {
          flag_wait<false, 256>(F_OUT + tile * 2 + c.rank, 1);
        }
        mbar_arrive_one(c.bar + B_OUT * 8);
      }
    } else {
      const int bw = blockIdx.x * 2 + (c.warp - 2);
      if ((c.phases & 1) && bw < 256) {
        gate_rows(p, bw * 8, c.lane);
        __syncwarp();
        flag_add(F_GATE);
      }
      if (do1) mbar_wait(c.bar + B_T0 * 8, 0);
      if (p.s.r[c.cl].bg != 255) local_attn(p, c, p.s.r[c.cl].bg, bw & 3);
      else if (c.lane == 0) mbar_arrive(c.bar + B_LAD * 8);
    }
    __syncwarp();
    bar_sync(3, 128);
    if (c.warp == 0 && (c.phases & 32)) {
      int last = 0;
      if (c.lane == 0) { __threadfence(); last = atomicAdd(g_flags + F_DONE, 1) == 2 * NCL - 1; }
      if (__shfl_sync(0xffffffffu, last, 0)) for (int i = c.lane; i < F_NUM; i += 32) g_flags[i] = 0;
    }
    if (c.warp == 1) mbar_wait(c.bar + B_FIN * 8, 0);
    __syncwarp();
    cluster_sync();
  }
}

static const Sched k_sched = {
  {{8,18,2,27,0,{109,181,0,0,0,0,0,0,0,0,0},{0,0,0,0,0,0,0,0,0,0,0},{73,229,65,194,104,198,206,74,149,152,26,13,148,221,91,156,146,217,0,0,0,0,0,0,0,0,0,0,0,0}},
   {8,3,4,11,255,{79,52,174,88,0,0,0,0,0,0,0},{0,0,95,0,0,0,0,0,0,0,0},{160,170,226,0,0,0,0,0,0,0,0,0,0,0,0,0,0,0,0,0,0,0,0,0,0,0,0,0,0,0}},
   {8,4,3,23,255,{30,255,197,0,0,0,0,0,0,0,0},{0,0,0,0,0,0,0,0,0,0,0},{164,72,166,163,0,0,0,0,0,0,0,0,0,0,0,0,0,0,0,0,0,0,0,0,0,0,0,0,0,0}},
   {8,4,6,10,255,{6,49,101,247,217,205,0,0,0,0,0},{0,0,0,0,0,63,0,0,0,0,0},{169,64,171,103,0,0,0,0,0,0,0,0,0,0,0,0,0,0,0,0,0,0,0,0,0,0,0,0,0,0}},
   {0,29,1,43,1,{179,0,0,0,0,0,0,0,0,0,0},{0,0,0,0,0,0,0,0,0,0,0},{135,163,136,224,193,226,206,204,223,197,202,213,196,216,16,218,203,205,222,212,221,19,207,214,219,23,220,210,217,0}},
   {1,29,2,35,2,{224,187,0,0,0,0,0,0,0,0,0},{0,0,0,0,0,0,0,0,0,0,0},{135,233,136,224,193,226,206,204,223,197,202,213,196,216,16,218,203,205,222,212,221,15,211,214,219,28,215,210,217,0}},
   {2,29,2,40,3,{216,147,0,0,0,0,0,0,0,0,0},{0,0,0,0,0,0,0,0,0,0,0},{137,231,192,232,194,225,206,204,223,197,202,213,196,216,16,218,203,205,222,212,221,15,211,214,219,28,215,210,217,0}},
   {3,29,1,47,4,{219,0,0,0,0,0,0,0,0,0,0},{0,0,0,0,0,0,0,0,0,0,0},{135,233,192,232,194,225,206,204,223,197,202,213,196,216,26,208,203,205,222,212,221,15,211,214,219,28,215,210,217,0}},
   {4,28,0,9,5,{0,0,0,0,0,0,0,0,0,0,0},{0,0,0,0,0,0,0,0,0,0,0},{135,233,192,232,194,225,206,236,5,10,21,4,24,26,16,11,13,30,20,29,15,19,22,27,28,23,18,25,0,0}},
   {5,27,0,6,6,{0,0,0,0,0,0,0,0,0,0,0},{0,0,0,0,0,0,0,0,0,0,0},{137,163,192,232,194,225,206,236,5,42,4,24,26,11,16,13,30,20,29,15,19,22,27,28,23,18,25,0,0,0}},
   {6,26,1,13,7,{153,0,0,0,0,0,0,0,0,0,0},{0,0,0,0,0,0,0,0,0,0,0},{137,64,136,241,193,230,12,63,10,53,24,26,11,16,13,30,20,29,15,19,22,27,28,87,18,25,0,0,0,0}},
   {7,25,0,19,8,{0,0,0,0,0,0,0,0,0,0,0},{0,0,0,0,0,0,0,0,0,0,0},{135,195,136,66,70,76,69,85,68,88,90,75,80,77,94,84,93,79,83,86,91,92,82,87,89,0,0,0,0,0}},
   {0,29,1,45,9,{148,0,0,0,0,0,0,0,0,0,0},{0,0,0,0,0,0,0,0,0,0,0},{103,201,104,209,33,198,238,236,255,229,234,245,228,248,48,250,235,237,254,244,253,51,239,246,251,55,252,242,249,0}},
   {1,29,2,37,10,{184,226,0,0,0,0,0,0,0,0,0},{0,0,0,0,0,0,0,0,0,0,0},{103,195,104,209,33,198,238,236,255,229,234,245,228,248,48,250,235,237,254,244,253,47,243,246,251,60,247,242,249,0}},
   {2,29,2,14,11,{185,202,0,0,0,0,0,0,0,0,0},{0,0,0,0,0,0,0,0,0,0,0},{105,195,32,209,34,198,238,236,255,229,234,245,228,248,48,250,235,237,254,244,253,47,243,246,251,60,247,242,249,0}},
   {3,29,1,5,12,{188,0,0,0,0,0,0,0,0,0,0},{0,0,0,0,0,0,0,0,0,0,0},{103,195,32,209,34,198,238,236,255,229,234,245,228,248,58,240,235,237,254,244,253,47,243,246,251,60,247,242,249,0}},
   {4,28,0,22,13,{0,0,0,0,0,0,0,0,0,0,0},{0,0,0,0,0,0,0,0,0,0,0},{103,195,32,209,34,198,238,31,37,42,53,36,56,58,48,43,45,62,52,61,47,51,54,59,60,55,50,57,0,0}},
   {5,27,0,10,14,{0,0,0,0,0,0,0,0,0,0,0},{0,0,0,0,0,0,0,0,0,0,0},{105,199,32,209,34,198,238,31,37,21,36,56,58,43,48,45,62,52,61,47,51,54,59,60,55,50,57,0,0,0}},
   {6,26,0,20,15,{0,0,0,0,0,0,0,0,0,0,0},{0,0,0,0,0,0,0,0,0,0,0},{105,96,104,66,33,14,44,5,42,4,56,58,43,48,45,62,52,61,47,51,54,59,60,119,50,57,0,0,0,0}},
   {7,25,0,15,16,{0,0,0,0,0,0,0,0,0,0,0},{0,0,0,0,0,0,0,0,0,0,0},{103,163,104,98,102,108,101,117,100,120,122,107,112,109,126,116,125,111,115,118,123,124,114,119,121,0,0,0,0,0}},
   {0,6,7,30,255,{136,137,2,118,35,165,180,0,0,0,0},{0,0,0,0,0,3,0,0,0,0,0},{67,233,192,241,194,230,0,0,0,0,0,0,0,0,0,0,0,0,0,0,0,0,0,0,0,0,0,0,0,0}},
   {1,6,4,21,255,{23,99,95,240,0,0,0,0,0,0,0},{0,0,192,0,0,0,0,0,0,0,0},{137,163,192,241,194,230,0,0,0,0,0,0,0,0,0,0,0,0,0,0,0,0,0,0,0,0,0,0,0,0}},
   {2,6,7,44,255,{0,66,14,172,130,242,190,0,0,0,0},{0,0,0,0,0,0,0,0,0,0,0},{135,163,136,241,193,230,0,0,0,0,0,0,0,0,0,0,0,0,0,0,0,0,0,0,0,0,0,0,0,0}},
   {3,6,6,38,255,{1,68,47,193,211,182,0,0,0,0,0},{0,0,0,0,0,0,0,0,0,0,0},{137,163,136,241,193,230,0,0,0,0,0,0,0,0,0,0,0,0,0,0,0,0,0,0,0,0,0,0,0,0}},
   {4,8,4,5,255,{141,46,245,152,0,0,0,0,0,0,0},{0,0,0,0,0,0,0,0,0,0,0},{137,163,136,241,193,230,12,63,0,0,0,0,0,0,0,0,0,0,0,0,0,0,0,0,0,0,0,0,0,0}},
   {5,10,6,9,255,{16,11,252,171,90,151,0,0,0,0,0},{0,0,0,0,0,128,0,0,0,0,0},{67,231,136,241,193,230,12,63,10,53,0,0,0,0,0,0,0,0,0,0,0,0,0,0,0,0,0,0,0,0}},
   {6,10,5,4,255,{56,53,250,110,191,0,0,0,0,0,0},{0,0,0,0,192,0,0,0,0,0,0},{135,195,81,98,70,46,31,37,21,36,0,0,0,0,0,0,0,0,0,0,0,0,0,0,0,0,0,0,0,0}},
   {7,7,5,24,255,{69,10,98,94,183,0,0,0,0,0,0},{0,0,0,0,255,0,0,0,0,0,0},{137,64,81,65,78,95,74,0,0,0,0,0,0,0,0,0,0,0,0,0,0,0,0,0,0,0,0,0,0,0}},
   {8,17,2,18,17,{168,246,0,0,0,0,0,0,0,0,0},{0,0,0,0,0,0,0,0,0,0,0},{67,225,145,199,44,109,204,223,197,196,16,203,30,83,150,87,207,0,0,0,0,0,0,0,0,0,0,0,0,0}},
   {9,17,2,1,18,{167,150,0,0,0,0,0,0,0,0,0},{0,64,0,0,0,0,0,0,0,0,0},{71,225,192,1,44,40,206,223,68,152,16,203,148,79,211,219,215,0,0,0,0,0,0,0,0,0,0,0,0,0}},
   {10,18,3,12,19,{128,238,189,0,0,0,0,0,0,0,0},{0,0,63,0,0,0,0,0,0,0,0},{160,170,226,163,193,14,45,223,10,196,216,218,30,221,211,219,215,217,0,0,0,0,0,0,0,0,0,0,0,0}},
   {11,18,2,39,20,{239,220,0,0,0,0,0,0,0,0,0},{0,0,0,0,0,0,0,0,0,0,0},{160,170,166,194,44,14,40,223,68,213,16,218,30,221,15,214,146,217,0,0,0,0,0,0,0,0,0,0,0,0}},
   {12,17,3,29,21,{248,93,222,0,0,0,0,0,0,0,0},{0,32,0,0,0,0,0,0,0,0,0},{160,170,226,194,44,14,40,223,149,196,16,203,30,221,211,219,215,0,0,0,0,0,0,0,0,0,0,0,0,0}},
   {13,18,4,16,22,{32,194,125,227,0,0,0,0,0,0,0},{0,0,0,0,0,0,0,0,0,0,0},{73,229,200,194,231,14,31,232,10,196,26,203,205,221,211,219,215,217,0,0,0,0,0,0,0,0,0,0,0,0}},
   {14,17,5,13,23,{96,82,164,123,201,0,0,0,0,0,0},{1,0,0,0,0,0,0,0,0,0,0},{73,229,200,194,44,76,69,45,149,152,75,13,148,79,150,87,146,0,0,0,0,0,0,0,0,0,0,0,0,0}},
   {15,18,1,2,24,{166,0,0,0,0,0,0,0,0,0,0},{0,0,0,0,0,0,0,0,0,0,0},{71,225,200,230,227,236,31,74,237,196,26,208,30,221,211,219,146,217,0,0,0,0,0,0,0,0,0,0,0,0}},
   {9,18,4,25,25,{208,131,233,221,0,0,0,0,0,0,0},{0,0,0,0,0,0,0,0,0,0,0},{73,229,145,194,6,109,204,5,149,202,26,13,93,222,150,156,146,217,0,0,0,0,0,0,0,0,0,0,0,0}},
   {10,17,4,17,26,{80,169,244,230,0,0,0,0,0,0,0},{0,0,0,64,0,0,0,0,0,0,0},{164,201,166,103,6,40,204,5,149,80,77,203,148,79,150,156,146,0,0,0,0,0,0,0,0,0,0,0,0,0}},
   {11,17,2,17,27,{112,133,0,0,0,0,0,0,0,0,0},{1,35,0,0,0,0,0,0,0,0,0},{164,7,171,1,6,76,45,5,10,152,75,13,148,83,91,156,215,0,0,0,0,0,0,0,0,0,0,0,0,0}},
   {12,18,3,1,28,{192,129,163,0,0,0,0,0,0,0,0},{0,0,0,0,0,0,0,0,0,0,0},{164,7,166,1,6,76,45,5,10,152,26,13,148,79,150,156,146,217,0,0,0,0,0,0,0,0,0,0,0,0}},
   {13,17,5,31,29,{41,81,243,155,186,0,0,0,0,0,0},{0,0,0,0,0,0,0,0,0,0,0},{160,170,226,1,44,76,69,45,149,152,16,94,148,79,150,156,146,0,0,0,0,0,0,0,0,0,0,0,0,0}},
   {14,17,5,2,30,{48,170,89,157,203,0,0,0,0,0,0},{1,0,0,0,0,0,0,0,0,0,0},{160,170,145,1,14,95,40,74,68,90,16,94,93,83,91,156,89,0,0,0,0,0,0,0,0,0,0,0,0,0}},
   {15,17,4,21,31,{40,132,235,228,0,0,0,0,0,0,0},{0,0,0,0,0,0,0,0,0,0,0},{73,229,145,235,231,76,69,232,149,152,75,13,148,79,150,156,215,0,0,0,0,0,0,0,0,0,0,0,0,0}},
   {9,3,7,36,255,{73,26,3,254,36,105,223,0,0,0,0},{0,0,0,0,0,0,255,0,0,0,0},{160,170,226,0,0,0,0,0,0,0,0,0,0,0,0,0,0,0,0,0,0,0,0,0,0,0,0,0,0,0}},
   {10,3,6,3,255,{72,75,9,13,249,135,0,0,0,0,0},{0,0,0,0,0,0,0,0,0,0,0},{169,7,171,0,0,0,0,0,0,0,0,0,0,0,0,0,0,0,0,0,0,0,0,0,0,0,0,0,0,0}},
   {11,3,8,42,255,{24,58,15,97,173,106,121,124,0,0,0},{0,0,0,0,0,0,0,30,0,0,0},{169,201,192,0,0,0,0,0,0,0,0,0,0,0,0,0,0,0,0,0,0,0,0,0,0,0,0,0,0,0}},
   {12,3,7,28,255,{78,19,45,213,178,218,144,0,0,0,0},{0,0,0,60,0,0,0,0,0,0,0},{169,201,171,0,0,0,0,0,0,0,0,0,0,0,0,0,0,0,0,0,0,0,0,0,0,0,0,0,0,0}},
   {13,3,6,0,255,{77,67,115,43,212,231,0,0,0,0,0},{0,0,0,0,0,128,0,0,0,0,0},{164,195,166,0,0,0,0,0,0,0,0,0,0,0,0,0,0,0,0,0,0,0,0,0,0,0,0,0,0,0}},
   {14,4,6,26,255,{62,103,83,209,158,120,0,0,0,0,0},{0,0,0,0,0,1,0,0,0,0,0},{164,7,226,70,0,0,0,0,0,0,0,0,0,0,0,0,0,0,0,0,0,0,0,0,0,0,0,0,0,0}},
   {15,3,5,8,255,{63,102,134,154,229,0,0,0,0,0,0},{0,0,0,0,63,0,0,0,0,0,0},{160,170,66,0,0,0,0,0,0,0,0,0,0,0,0,0,0,0,0,0,0,0,0,0,0,0,0,0,0,0}},
   {9,4,6,12,255,{5,12,44,33,91,160,0,0,0,0,0},{0,0,0,0,0,0,0,0,0,0,0},{164,195,166,163,0,0,0,0,0,0,0,0,0,0,0,0,0,0,0,0,0,0,0,0,0,0,0,0,0,0}},
   {10,4,7,33,255,{64,71,87,34,236,225,145,0,0,0,0},{0,0,0,0,0,0,0,0,0,0,0},{97,195,145,108,0,0,0,0,0,0,0,0,0,0,0,0,0,0,0,0,0,0,0,0,0,0,0,0,0,0}},
   {11,4,5,4,255,{59,22,251,111,176,0,0,0,0,0,0},{0,0,0,3,0,0,0,0,0,0,0},{97,195,200,163,0,0,0,0,0,0,0,0,0,0,0,0,0,0,0,0,0,0,0,0,0,0,0,0,0,0}},
   {12,4,6,0,255,{76,21,113,84,108,232,0,0,0,0,0},{0,0,0,0,0,0,0,0,0,0,0},{97,195,200,163,0,0,0,0,0,0,0,0,0,0,0,0,0,0,0,0,0,0,0,0,0,0,0,0,0,0}},
   {13,4,5,16,255,{61,139,100,42,92,0,0,0,0,0,0},{0,0,0,0,31,0,0,0,0,0,0},{169,7,171,70,0,0,0,0,0,0,0,0,0,0,0,0,0,0,0,0,0,0,0,0,0,0,0,0,0,0}},
   {14,4,4,32,255,{60,55,215,159,0,0,0,0,0,0,0},{0,0,0,224,0,0,0,0,0,0,0},{169,64,166,163,0,0,0,0,0,0,0,0,0,0,0,0,0,0,0,0,0,0,0,0,0,0,0,0,0,0}},
   {15,4,6,18,255,{4,140,114,38,237,204,0,0,0,0,0},{0,0,0,0,7,0,0,0,0,0,0},{164,195,65,70,0,0,0,0,0,0,0,0,0,0,0,0,0,0,0,0,0,0,0,0,0,0,0,0,0,0}},
   {9,4,7,41,255,{74,142,253,196,161,177,149,0,0,0,0},{0,0,0,0,0,0,63,0,0,0,0},{169,72,171,103,0,0,0,0,0,0,0,0,0,0,0,0,0,0,0,0,0,0,0,0,0,0,0,0,0,0}},
   {10,4,5,34,255,{28,119,198,127,200,0,0,0,0,0,0},{0,0,0,224,0,0,0,0,0,0,0},{101,72,192,194,0,0,0,0,0,0,0,0,0,0,0,0,0,0,0,0,0,0,0,0,0,0,0,0,0,0}},
   {11,4,6,22,255,{25,70,50,39,126,146,0,0,0,0,0},{0,0,0,0,0,0,0,0,0,0,0},{101,98,145,103,0,0,0,0,0,0,0,0,0,0,0,0,0,0,0,0,0,0,0,0,0,0,0,0,0,0}},
   {12,4,5,14,255,{7,18,85,195,162,0,0,0,0,0,0},{0,0,0,0,0,0,0,0,0,0,0},{101,64,145,103,0,0,0,0,0,0,0,0,0,0,0,0,0,0,0,0,0,0,0,0,0,0,0,0,0,0}},
   {13,4,5,6,255,{29,20,175,107,207,0,0,0,0,0,0},{0,0,0,0,192,0,0,0,0,0,0},{97,64,145,163,0,0,0,0,0,0,0,0,0,0,0,0,0,0,0,0,0,0,0,0,0,0,0,0,0,0}},
   {14,4,5,8,255,{31,51,86,210,241,0,0,0,0,0,0},{0,0,0,0,0,0,0,0,0,0,0},{97,195,171,103,0,0,0,0,0,0,0,0,0,0,0,0,0,0,0,0,0,0,0,0,0,0,0,0,0,0}},
   {15,4,6,20,255,{65,27,54,199,234,206,0,0,0,0,0},{0,0,0,128,0,0,0,0,0,0,0},{169,64,226,78,0,0,0,0,0,0,0,0,0,0,0,0,0,0,0,0,0,0,0,0,0,0,0,0,0,0}},
   {6,2,5,7,255,{57,143,116,37,104,0,0,0,0,0,0},{0,0,0,0,0,0,0,0,0,0,0},{103,163,0,0,0,0,0,0,0,0,0,0,0,0,0,0,0,0,0,0,0,0,0,0,0,0,0,0,0,0}},
   {7,7,7,46,255,{8,138,17,117,214,122,156,0,0,0,0},{0,0,0,0,64,0,31,0,0,0,0},{105,96,113,97,110,127,106,0,0,0,0,0,0,0,0,0,0,0,0,0,0,0,0,0,0,0,0,0,0,0}}},
  {{0,10,0,0},{3,64,0,0},{6,64,0,0},{8,16,0,0},{0,6,0,0},{0,3,0,0},{0,2,0,0},{0,6,0,0},{22,64,0,0},{16,64,0,0},{20,64,0,0},
   {6,64,0,0},{0,1,0,0},{0,7,0,0},{8,19,0,0},{7,18,0,0},{22,64,0,0},{16,64,0,0},{10,64,0,0},{6,64,0,0},{0,9,0,0},{12,64,0,0},
   {0,3,0,0},{0,8,0,0},{18,64,0,0},{10,22,0,0},{8,19,0,0},{0,7,0,0},{17,64,0,0},{7,18,0,0},{3,13,0,0},{0,6,0,0},{0,7,0,0},
   {2,13,0,0},{7,20,0,0},{19,64,0,0},{0,7,0,0},{2,13,0,0},{13,64,0,0},{18,64,0,0},{0,6,0,0},{10,19,0,0},{1,12,0,0},{0,3,0,0},
   {10,64,0,0},{0,10,0,0},{0,8,0,0},{7,19,0,0},{0,10,0,0},{8,18,0,0},{13,64,0,0},{0,10,0,0},{19,64,0,0},{19,64,0,0},{13,64,0,0},
   {0,8,0,0},{10,17,0,0},{0,2,0,0},{0,8,0,0},{8,22,0,0},{19,64,0,0},{9,16,0,0},{18,64,0,0},{3,10,0,0},{6,64,0,0},{0,8,0,0}},
  {{38,59,55,56,31,50,51,49,33,53,23,27,61,41,58,45,46,57,36,6,7,18,19,16,17,0,1,34,35,2,3,14,15,4,5,12,13,24,25,28,29,62,63,20,21,10,11,42,43,8,9,48,32,52,22,26,60,40,39,44,54,47,30,37},
   {40,39,44,55,56,31,37,22,26,60,41,58,45,46,57,36,50,51,6,7,18,19,16,17,0,1,34,35,2,3,14,15,4,5,12,13,24,25,28,29,62,63,20,21,10,11,42,43,8,9,48,49,32,33,52,53,23,27,61,38,59,54,47,30},
   {52,22,27,40,39,44,55,56,31,50,23,60,41,58,45,46,57,36,51,6,7,18,19,16,17,0,1,34,35,2,3,14,15,4,5,12,13,24,25,28,29,62,63,20,21,10,11,42,43,8,9,48,49,32,33,53,26,61,38,59,54,47,30,37},
   {60,38,59,31,45,55,57,47,37,51,14,15,18,19,6,7,16,17,0,1,34,35,2,3,4,5,12,13,28,29,24,25,62,63,10,11,8,9,42,43,48,49,20,21,32,33,52,53,22,23,26,27,40,41,61,39,58,30,44,54,56,46,36,50},
   {22,27,60,39,30,45,56,47,32,52,23,40,61,58,31,54,57,36,50,14,15,18,19,6,7,16,17,0,1,34,35,2,3,4,5,12,13,28,29,24,25,62,63,10,11,8,9,42,43,48,49,20,21,33,53,26,41,38,59,44,55,46,37,51},
   {60,39,30,45,56,47,50,52,22,26,40,61,58,31,54,57,36,51,14,15,18,19,6,7,16,17,0,1,34,35,2,3,4,5,12,13,28,29,24,25,62,63,10,11,8,9,42,43,48,49,20,21,32,33,53,23,27,41,38,59,44,55,46,37},
   {60,41,30,39,54,57,36,50,51,23,40,59,38,45,56,47,18,19,14,15,6,7,16,17,34,35,0,1,4,5,2,3,12,13,28,29,24,25,62,63,10,11,20,21,42,43,8,9,32,33,48,49,26,27,52,53,22,61,58,31,44,55,46,37},
   {55,57,47,37,50,51,18,19,14,15,6,7,16,17,34,35,0,1,4,5,2,3,12,13,28,29,24,25,62,63,10,11,20,21,42,43,8,9,32,33,48,49,26,27,52,53,22,23,60,61,40,41,58,59,30,31,38,39,44,45,54,56,46,36},
   {22,61,58,31,44,56,47,50,48,26,52,60,41,30,39,54,57,36,18,19,14,15,6,7,16,17,34,35,0,1,4,5,2,3,12,13,28,29,24,25,62,63,10,11,20,21,42,43,8,9,32,33,49,27,53,23,40,59,38,45,55,46,37,51},
   {33,52,41,60,59,30,55,56,37,50,43,49,22,53,26,61,38,31,44,57,46,51,14,15,18,19,6,7,0,1,16,17,34,35,4,5,2,3,12,13,28,29,24,25,62,63,10,11,8,9,20,21,42,48,32,23,40,27,58,39,54,45,36,47},
   {41,60,59,30,55,56,37,50,26,61,38,31,44,57,46,51,14,15,18,19,6,7,0,1,16,17,34,35,4,5,2,3,12,13,28,29,24,25,62,63,10,11,8,9,20,21,42,43,48,49,32,33,22,23,52,53,40,27,58,39,54,45,36,47},
   {47,50,51,14,15,18,19,6,7,0,1,16,17,34,35,4,5,2,3,12,13,28,29,24,25,62,63,10,11,8,9,20,21,42,43,48,49,32,33,22,23,52,53,40,41,26,27,60,61,58,59,38,39,30,31,54,55,44,45,56,57,36,37,46},
   {45,56,47,27,61,41,59,31,39,54,57,36,50,14,15,18,19,6,7,0,1,16,17,34,35,4,5,2,3,12,13,28,29,24,25,62,63,10,11,42,43,20,21,8,9,48,49,32,33,52,53,22,23,26,60,40,58,30,38,44,55,46,37,51},
   {40,59,38,45,56,47,50,8,48,32,52,22,26,60,41,30,39,54,57,36,14,15,18,19,6,7,0,1,16,17,34,35,4,5,2,3,12,13,28,29,24,25,62,63,10,11,42,43,20,21,9,49,33,53,23,27,61,58,31,44,55,46,37,51},
   {27,40,59,38,45,56,47,50,49,33,53,23,60,41,30,39,54,57,37,14,15,18,19,6,7,0,1,16,17,34,35,4,5,2,3,12,13,28,29,24,25,62,63,10,11,42,43,20,21,8,9,48,32,52,22,26,61,58,31,44,55,46,36,51},
   {45,55,57,47,37,51,18,19,6,7,14,15,0,1,16,17,34,35,4,5,2,3,12,13,28,29,24,25,62,63,10,11,20,21,42,43,8,9,48,49,32,33,52,53,22,23,60,61,26,27,40,41,58,59,30,31,38,39,44,54,56,46,36,50},
   {47,50,23,61,27,41,59,31,39,45,55,57,36,18,19,6,7,14,15,0,1,16,17,34,35,4,5,2,3,12,13,28,29,24,25,62,63,10,11,20,21,42,43,8,9,48,49,32,33,52,53,22,60,26,40,58,30,38,44,54,56,46,37,51},
   {50,51,61,27,41,59,31,39,45,55,57,47,37,18,19,6,7,14,15,0,1,16,17,34,35,4,5,2,3,12,13,28,29,24,25,62,63,10,11,20,21,42,43,8,9,48,49,32,33,52,53,22,23,60,26,40,58,30,38,44,54,56,46,36},
   {23,33,27,40,59,38,45,46,57,50,60,41,30,39,54,47,36,18,19,14,15,0,1,6,7,16,17,34,35,4,5,2,3,12,13,28,29,24,25,62,63,10,11,20,21,42,43,8,9,48,49,52,53,22,32,26,61,58,31,44,55,56,37,51},
   {44,54,46,56,36,50,18,19,14,15,0,1,6,7,16,17,34,35,4,5,2,3,12,13,28,29,24,25,62,63,10,11,20,21,42,43,8,9,48,49,52,53,22,23,32,33,26,27,60,61,40,41,58,59,30,31,38,39,45,55,47,57,37,51},
   {47,36,50,58,30,38,44,54,46,57,18,19,14,15,0,1,6,7,16,17,34,35,4,5,2,3,12,13,28,29,24,25,62,63,10,11,20,21,42,43,8,9,48,49,52,53,22,23,32,33,26,27,60,61,40,41,59,31,39,45,55,56,37,51},
   {50,26,60,40,58,30,38,44,54,56,36,46,14,15,18,19,6,7,0,1,16,17,34,35,4,5,2,3,12,13,28,29,24,25,62,63,10,11,20,21,42,43,8,9,48,49,52,53,32,33,22,23,27,61,41,59,31,39,45,55,57,37,47,51},
   {27,40,59,38,45,56,37,50,43,9,49,53,33,23,60,41,30,39,54,57,46,51,14,15,18,19,6,7,0,1,16,17,34,35,4,5,2,3,12,13,28,29,24,25,62,63,10,11,20,21,42,8,48,52,32,22,26,61,58,31,44,55,36,47},
   {39,45,55,57,37,50,14,15,18,19,6,7,0,1,16,17,34,35,4,5,2,3,12,13,28,29,24,25,62,63,10,11,20,21,42,43,8,9,48,49,52,53,32,33,22,23,26,27,60,61,40,41,58,59,30,31,38,44,54,56,36,46,47,51}},
  {{4,4,3,3,3,3,2,3},{6,6,7,7,7,7,7,7},{7,7,6,6,6,6,6,6},{1,2,2,2,2,1,3,2},
   {15,15,3,4,4,4,4,6},{12,12,12,12,12,0,0,1},{8,8,8,8,8,8,8,8},{0,0,1,0,0,2,1,0},
   {3,3,4,4,4,4,4,4},{2,1,0,1,1,0,0,1},{13,13,13,1,1,2,2,0},{5,5,7,8,8,7,7,4},
   {10,10,10,10,10,10,10,10},{7,7,8,9,9,9,9,8},{9,9,9,9,9,9,9,9},{11,10,12,1,1,2,2,3},
   {4,4,5,7,7,8,8,9},{5,5,5,5,5,5,5,5},{3,3,11,11,11,10,10,0},{16,11,13,4,4,4,4,6},
   {1,8,11,12,12,0,0,0},{14,14,0,3,3,3,3,3},{12,12,3,5,5,3,5,7},{15,1,9,12,12,0,0,1},
   {2,1,4,5,5,5,5,5},{6,6,8,10,10,11,11,8},{3,3,6,6,6,6,6,7},{13,13,4,7,7,5,8,9},
   {2,15,5,9,9,9,9,11},{0,9,10,10,10,11,10,1},{6,6,9,11,11,10,11,11},{11,11,11,11,11,11,11,11}},
  {{255,255,255,255,255,255,255,255},{255,255,255,255,255,255,255,255},{255,255,255,255,255,255,255,255},{255,255,255,255,255,255,255,255},
   {255,255,0,8,8,8,8,2},{255,255,255,255,255,9,9,9},{255,255,255,255,255,255,255,255},{255,255,255,255,255,255,255,255},
   {255,255,255,255,255,255,255,255},{255,255,255,255,255,255,255,255},{255,255,255,9,9,7,0,7},{17,17,1,6,6,1,1,8},
   {255,255,255,255,255,255,255,255},{2,2,6,14,14,14,14,6},{255,255,255,255,255,255,255,255},{31,12,5,10,10,10,10,21},
   {0,0,17,1,1,6,6,14},{255,255,255,255,255,255,255,255},{26,26,20,30,30,30,29,20},{255,31,10,4,4,4,4,4},
   {3,6,31,5,5,5,5,10},{255,255,9,0,0,0,3,0},{5,5,4,24,24,21,24,26},{4,24,30,20,20,20,20,29},
   {9,9,8,17,17,17,17,17},{30,30,13,29,29,29,30,13},{8,8,2,2,2,2,2,1},{10,10,24,16,16,24,16,16},
   {24,4,16,13,13,13,13,30},{7,14,12,12,12,31,12,5},{1,1,14,31,31,12,31,31},{255,255,255,255,255,255,255,255}},
  {112,113,114,115,116,117,118,119,120,121,122,123,124,125,126,127,128,129,130,131,132,133,134,135,136,137,138,139,140,141,142,143,46,637,13,78,11,371,74,15,152,42,40,36,38,647,391,2,160,161,162,163,164,165,166,167,168,169,170,171,172,173,174,175,176,177,178,179,180,181,182,183,184,185,186,187,188,189,190,191,73,16,638,79,80,76,8,43,200,201,202,52,204,634,48,85,6,3,1,211,212,213,214,215,216,217,83,642,220,455,643,223,7,4,226,227,228,229,230,231,68,55,26,92,24,20,18,56,89,86,14,53,81,50,49,247,248,249,250,251,252,253,254,255,69,64,35,31,33,29,27,65,59,98,96,22,94,90,19,271,272,273,274,385,276,711,369,279,280,372,381,9,382,77,75,628,288,289,97,291,95,91,61,295,296,66,63,32,34,30,302,67,47,17,84,10,12,627,388,45,103,101,100,71,99,70,28,102,387,87,322,323,82,51,644,88,328,329,330,93,332,333,62,335,336,337,338,339,340,341,342,343,60,345,54,23,25,21,625,57,352,58,354,641,356,386,378,359,72,44,41,37,39,0,366,5},
  {511,511,511,511,511,511,511,511,511,511,511,511,511,511,511,511,511,511,511,511,511,511,511,511,511,511,511,511,511,511,511,511,257,29,257,256,257,59,256,257,511,256,256,256,256,31,31,256,511,511,511,511,511,511,511,511,511,511,511,511,511,511,511,511,511,511,511,511,511,511,511,511,511,511,511,511,511,511,511,511,256,257,62,256,256,256,256,256,511,511,511,257,511,58,257,257,256,256,256,511,511,511,511,511,511,511,257,26,511,103,27,511,256,256,511,511,511,511,511,511,259,258,258,258,258,258,258,258,257,257,257,257,257,257,257,511,511,511,511,511,511,511,511,511,259,259,259,259,259,259,259,259,258,258,258,258,258,258,258,511,511,511,511,25,511,103,57,511,511,60,29,257,62,256,256,60,511,511,258,511,258,258,258,511,511,259,259,259,259,259,511,259,257,257,257,257,257,59,28,257,259,259,259,259,259,259,259,259,27,257,511,511,257,257,28,257,511,511,511,258,511,511,258,511,511,511,511,511,511,511,511,511,258,511,258,258,258,258,57,258,511,258,511,25,511,26,58,511,256,256,256,256,256,256,511,256}};

typedef CUresult (*EncodeFn)(CUtensorMap*, CUtensorMapDataType, cuuint32_t, void*, const cuuint64_t*, const cuuint64_t*, const cuuint32_t*,
                             const cuuint32_t*, CUtensorMapInterleave, CUtensorMapSwizzle, CUtensorMapL2promotion, CUtensorMapFloatOOBfill);

void make_map2(EncodeFn enc, CUtensorMap* m, const void* ptr, int rows, int cols, int box_rows) {
  cuuint64_t dim[2] = {(cuuint64_t)cols, (cuuint64_t)rows}, str[1] = {(cuuint64_t)cols * 2};
  cuuint32_t box[2] = {64, (cuuint32_t)box_rows}, es[2] = {1, 1};
  enc(m, CU_TENSOR_MAP_DATA_TYPE_BFLOAT16, 2, const_cast<void*>(ptr), dim, str, box, es, CU_TENSOR_MAP_INTERLEAVE_NONE, CU_TENSOR_MAP_SWIZZLE_128B,
      CU_TENSOR_MAP_L2_PROMOTION_L2_128B, CU_TENSOR_MAP_FLOAT_OOB_FILL_NONE);
}
void make_map3(EncodeFn enc, CUtensorMap* m, const void* ptr, int rows) {
  cuuint64_t dim[3] = {64, (cuuint64_t)rows, 9}, str[2] = {DM * 2, 128};
  cuuint32_t box[3] = {64, 32, 3}, es[3] = {1, 1, 1};
  enc(m, CU_TENSOR_MAP_DATA_TYPE_BFLOAT16, 3, const_cast<void*>(ptr), dim, str, box, es, CU_TENSOR_MAP_INTERLEAVE_NONE, CU_TENSOR_MAP_SWIZZLE_128B,
      CU_TENSOR_MAP_L2_PROMOTION_L2_128B, CU_TENSOR_MAP_FLOAT_OOB_FILL_NONE);
}

void make_map_t(EncodeFn enc, CUtensorMap* m, void* ptr, int width, int cols) {
  cuuint64_t dim[3] = {SEQ / 2, 2, 864}, str[2] = {SEQ * 2, SEQ * 4};
  cuuint32_t box[3] = {(cuuint32_t)width, 2, (cuuint32_t)cols}, es[3] = {1, 1, 1};
  enc(m, CU_TENSOR_MAP_DATA_TYPE_UINT32, 3, ptr, dim, str, box, es, CU_TENSOR_MAP_INTERLEAVE_NONE, cols == 64 ? CU_TENSOR_MAP_SWIZZLE_128B : CU_TENSOR_MAP_SWIZZLE_NONE,
      CU_TENSOR_MAP_L2_PROMOTION_NONE, CU_TENSOR_MAP_FLOAT_OOB_FILL_NONE);
}

int g_mode = -1;

}

extern "C" void kernel_launch(void* const* d_in, const int* in_sizes, int n_in, void* d_out, int out_size) {
  static EncodeFn enc = nullptr;
  static void* t_ptr = nullptr;
  if (!enc) {
    void* fn = nullptr;
    cudaDriverEntryPointQueryResult st;
    cudaGetDriverEntryPoint("cuTensorMapEncodeTiled", &fn, cudaEnableDefault, &st);
    enc = (EncodeFn)fn;
    cudaGetSymbolAddress(&t_ptr, g_S);
    cudaFuncSetAttribute(fused_kernel, cudaFuncAttributeMaxDynamicSharedMemorySize, SMEM_BYTES);
    if (g_mode < 0) {
      cudaLaunchConfig_t cfg = {};
      cfg.gridDim = dim3(2 * NCL); cfg.blockDim = dim3(384); cfg.dynamicSmemBytes = SMEM_BYTES;
      cudaLaunchAttribute at; at.id = cudaLaunchAttributeClusterDimension;
      at.val.clusterDim.x = 2; at.val.clusterDim.y = 1; at.val.clusterDim.z = 1;
      cfg.attrs = &at; cfg.numAttrs = 1;
      int nc = 0;
      g_mode = (cudaOccupancyMaxActiveClusters(&nc, fused_kernel, &cfg) == cudaSuccess && nc >= NCL) ? 1 : 0;
      (void)cudaGetLastError();
    }
  }
  Params p;
  make_map2(enc, &p.map_a[0], d_in[4], SEQ, DC, 128);
  make_map2(enc, &p.map_a[1], d_in[0], SEQ, DM, 128);
  make_map2(enc, &p.map_w[0], d_in[6], DC, 4096, 64);
  make_map2(enc, &p.map_w[1], d_in[7], DC, 4096, 64);
  make_map2(enc, &p.map_w[2], d_in[5], DM, 4096, 64);
  make_map2(enc, &p.map_w[3], d_in[1], DM, 1728, 64);
  make_map3(enc, &p.map_o[0], d_in[8], 4096);
  make_map3(enc, &p.map_o[1], d_in[2], DM);
  make_map_t(enc, &p.map_t[0], t_ptr, 32, 9);
  make_map_t(enc, &p.map_t[1], t_ptr, 40, 9);
  make_map_t(enc, &p.map_t[2], t_ptr, 32, 64);
  p.x = (const __nv_bfloat16*)d_in[0];
  p.gate_w = (const __nv_bfloat16*)d_in[9];
  make_map2(enc, &p.map_out, d_out, SEQ, DM, 64);
  p.out = (__nv_bfloat16*)d_out;
  p.zero = 0;
  auto launch = [&](int phases) {
    p.s = k_sched;
    for (int i = 0; i < NCL; i++) {
      Rec& r = p.s.r[i];
      if (!(phases & 1)) r.n1 = 0;
      if (!(phases & 2)) r.n2 = 0;
      if (!(phases & (p.s.task[i][1] == 64 ? 4 : 32))) r.p3 = 255;
      if (!(phases & 8)) r.bg = 255;
      const int u1 = r.n1 ? 4 + (r.slab >> 3) + r.n1 * (8 + (r.slab >> 3)) : 0;
      int u2 = 0;
      for (int k = 0; k < r.n2; k++) u2 += 4 * (r.item[k] & 7) + 4;
      r.u1 = (uint8_t)u1; r.u2 = (uint8_t)u2;
      r.rot = (uint8_t)(((u1 % 10 + 1) >> 1) % 5);
      r.x3 = (uint8_t)((r.rot + u2) % 5 & 3);
      r.phases = (uint8_t)phases;
    }
    if (!(phases & 16))
      for (int i = 0; i < 256; i++) { p.s.slot[i >> 3][i & 7] = (uint8_t)(i >> 3); p.s.prev[i >> 3][i & 7] = 255; p.s.qblk[i] = (uint16_t)(S_Q + i); p.s.qdep[i] = 511; }
    fused_kernel<<<2 * NCL, 384, SMEM_BYTES>>>(p);
  };
  if (g_mode == 1) launch(63);
  else { launch(1); launch(10); launch(4); launch(32); }
}
```
